```python
import torch

def _softmax(x, axis=-1):
    return torch.softmax(x, dim=axis)
def _gelu(x):
    return torch.nn.functional.gelu(x, approximate="tanh")
def _silu(x):
    return torch.nn.functional.silu(x)
def _sigmoid(x):
    return torch.sigmoid(x)
def _layernorm(x, axis=-1, eps=1e-5):
    m = x.mean(dim=axis, keepdim=True)
    v = x.var(dim=axis, keepdim=True, unbiased=False)
    return (x - m) / torch.sqrt(v + eps)
def _scatter_add(tgt, idx, src, axis=0):
    return tgt.clone().index_add_(axis, idx, src)
def _segment_sum(src, seg, n):
    out = torch.zeros((n,) + src.shape[1:], dtype=src.dtype)
    return out.index_add_(0, seg, src)
def _pad(x, pw):
    flat = tuple(v for pair in reversed(pw) for v in pair)
    return torch.nn.functional.pad(x, flat)

kernel_name = 'sequential_preLN__spectral_gfnet__swiglu_ffn__prompt'

def setup_inputs():

    _w = (lambda a: (lambda t: t.to(torch.bfloat16) if t.is_floating_point() else t)(torch.as_tensor(a)))
    def _A_setup():
        B, S, D = 1, 2048, 512
        Df = D // 2 + 1
        return {
            "x": _w((lambda *s: torch.randn(*s, dtype=torch.bfloat16) * 0.05)(B, S, D)),
            "w_r": _w((lambda *s: torch.randn(*s, dtype=torch.bfloat16) * 0.4)(S, Df) * 0.02),
            "w_i": _w((lambda *s: torch.randn(*s, dtype=torch.bfloat16) * 0.4)(S, Df) * 0.02),
        }
    _A_in = _A_setup()

    def _B_setup():
        B, S, D, F = 1, 2048, 512, 1792
        return {
            "x": _w((lambda *s: torch.randn(*s, dtype=torch.bfloat16) * 0.05)(B, S, D)),
            "w_gate": _w((lambda *s: torch.randn(*s, dtype=torch.bfloat16) * 0.05)(D, F)),
            "w_up": _w((lambda *s: torch.randn(*s, dtype=torch.bfloat16) * 0.05)(D, F)),
            "w_down": _w((lambda *s: torch.randn(*s, dtype=torch.bfloat16) * 0.05)(F, D)),
        }
    _B_in = _B_setup()

    return {
        "A_x": _A_in["x"],
        "A_w_r": _A_in["w_r"],
        "A_w_i": _A_in["w_i"],
        "B_x": _B_in["x"],
        "B_w_gate": _B_in["w_gate"],
        "B_w_up": _B_in["w_up"],
        "B_w_down": _B_in["w_down"],
    }

def reference(A_x, A_w_r, A_w_i, B_x, B_w_gate, B_w_up, B_w_down):
    def _A_ref(x, w_r, w_i):
        B, S, D = x.shape
        X = (lambda x, axes=(-2,-1): torch.fft.rfft2(x.float(), dim=axes))(x, axes=(-2, -1))
        W = w_r + 1j * w_i
        X = X * W
        y = (lambda x, s, axes=(-2,-1): torch.fft.irfft2(x, s=s, dim=axes).to(torch.bfloat16))(X, (S, D), axes=(-2, -1))
        return y

    def _B_ref(x, w_gate, w_up, w_down):
        g = _silu(x @ w_gate)
        u = x @ w_up
        return (g * u) @ w_down

    x = A_x
    h = x + _A_ref(_layernorm(x, axis=-1), A_w_r, A_w_i)
    h2 = h + _B_ref(_layernorm(h, axis=-1), B_w_gate, B_w_up, B_w_down)
    return h2
```

```cpp
#include <cuda_runtime.h>
#include <cuda_bf16.h>
#include <cuda.h>
#include <stdint.h>

namespace {

constexpr int NCTA = 128;
constexpr int NTHREADS = 384;
constexpr int SLOT = 16384;
constexpr int SMEM_BYTES = 14 * SLOT + 1024 + 1024;
constexpr int SPIN_LIMIT = 1 << 22;

__device__ uint4 g_Z1[128 * 1024];
__device__ uint4 g_Z2[128 * 1024];
__device__ uint4 g_LN[16 * 8 * 1024];
__device__ uint4 g_H[2048 * 64];
__device__ uint4 g_P[16 * 28 * 1024];
__device__ unsigned g_cnt[64 * 32];
#define PROF(i)

constexpr unsigned short kCos32[9] = {0x3f80, 0x3f7b, 0x3f6d, 0x3f55, 0x3f35, 0x3f0e, 0x3ec4, 0x3e48, 0x0000};
constexpr unsigned bcos(int i) {
  i &= 31;
  if (i > 16) i = 32 - i;
  return i <= 8 ? kCos32[i] : (kCos32[16 - i] | 0x8000u);
}
constexpr unsigned bsin(int i) { return bcos(i - 8); }
constexpr unsigned bneg(unsigned v, bool n) { return n ? (v ^ 0x8000u) : v; }
constexpr unsigned pk(unsigned lo, unsigned hi) { return lo | (hi << 16); }
constexpr unsigned fa_elem(int kp, int n1) {
  return kp <= 8 ? bcos(2 * kp * n1) : bneg(bsin(2 * (kp - 8) * n1), true);
}
struct Tables {
  unsigned fb[16][32][4];
  unsigned gb[16][32][4];
  unsigned fa[32][4];
  unsigned ga[32][4];
};
constexpr Tables make_tables() {
  Tables T = {};
  for (int l = 0; l < 32; l++) {
    const int g = l >> 2, t = l & 3;
    for (int i = 0; i < 4; i++)
      for (int u = 0; u < 8; u++) {
        const int ri = g & 1, m = 2 * (g >> 1) + ((u & 3) >> 1);
        const bool hi = u >= 4;
        const int k2 = hi ? 31 - 2 * m - (u & 1) : 2 * m + (u & 1);
        const int pa = (8 * t + i) * k2, pb = (8 * t + 4 + i) * k2;
        unsigned b0 = ri == 0 ? pk(bcos(pa), bcos(pb)) : pk(bneg(bsin(pa), !hi), bneg(bsin(pb), !hi));
        unsigned b1 = ri == 0 ? pk(bsin(pa), bsin(pb)) : pk(bneg(bcos(pa), hi), bneg(bcos(pb), hi));
        T.fb[i * 4 + (u >> 1)][l][(u & 1) * 2 + 0] = b0;
        T.fb[i * 4 + (u >> 1)][l][(u & 1) * 2 + 1] = b1;
      }
    for (int i = 0; i < 4; i++)
      for (int ks = 0; ks < 4; ks++) {
        const int n2 = 4 * g + i, m = 2 * t + (ks & 1);
        const bool hi = ks >= 2;
        const int pa = n2 * (hi ? 31 - 2 * m : 2 * m), pb = n2 * (hi ? 30 - 2 * m : 2 * m + 1);
        T.gb[i * 4 + ks][l][0] = pk(bcos(pa), bneg(bsin(pa), !hi));
        T.gb[i * 4 + ks][l][1] = pk(bsin(pa), bneg(bcos(pa), hi));
        T.gb[i * 4 + ks][l][2] = pk(bcos(pb), bneg(bsin(pb), !hi));
        T.gb[i * 4 + ks][l][3] = pk(bsin(pb), bneg(bcos(pb), hi));
      }
    T.fa[l][0] = pk(fa_elem(g, 2 * t), fa_elem(g, 2 * t + 1));
    T.fa[l][1] = pk(fa_elem(g + 8, 2 * t), fa_elem(g + 8, 2 * t + 1));
    T.fa[l][2] = pk(fa_elem(g, 2 * t + 8), fa_elem(g, 2 * t + 9));
    T.fa[l][3] = pk(fa_elem(g + 8, 2 * t + 8), fa_elem(g + 8, 2 * t + 9));
    T.ga[l][0] = pk(fa_elem(2 * t, g), fa_elem(2 * t + 1, g));
    T.ga[l][1] = pk(fa_elem(2 * t, g + 8), fa_elem(2 * t + 1, g + 8));
    T.ga[l][2] = pk(fa_elem(2 * t + 8, g), fa_elem(2 * t + 9, g));
    T.ga[l][3] = pk(fa_elem(2 * t + 8, g + 8), fa_elem(2 * t + 9, g + 8));
  }
  return T;
}
__device__ const __align__(128) Tables g_tab = make_tables();

__device__ __forceinline__ uint32_t s2u(const void* p) { return (uint32_t)__cvta_generic_to_shared(p); }
__device__ __forceinline__ void mbar_init(uint32_t b, int c) { asm volatile("mbarrier.init.shared::cta.b64 [%0], %1;" ::"r"(b), "r"(c)); }
__device__ __forceinline__ void mbar_expect(uint32_t b, int bytes) {
  asm volatile("mbarrier.arrive.expect_tx.shared::cta.b64 _, [%0], %1;" ::"r"(b), "r"(bytes) : "memory");
}
__device__ __forceinline__ void mbar_arrive(uint32_t b) { asm volatile("mbarrier.arrive.shared::cta.b64 _, [%0];" ::"r"(b) : "memory"); }
__device__ __forceinline__ void mbar_wait(uint32_t b, int parity) {
  uint32_t ok;
  int it = 0;
  do {
    asm volatile("{.reg .pred p; mbarrier.try_wait.parity.shared::cta.b64 p, [%1], %2; selp.u32 %0,1,0,p;}"
                 : "=r"(ok) : "r"(b), "r"(parity) : "memory");
    if (++it > SPIN_LIMIT) __trap();
  } while (!ok);
}
__device__ __forceinline__ void mbar_wait_cluster(uint32_t b, int parity) {
  uint32_t ok;
  int it = 0;
  do {
    asm volatile("{.reg .pred p; mbarrier.try_wait.parity.acquire.cluster.shared::cta.b64 p, [%1], %2; selp.u32 %0,1,0,p;}"
                 : "=r"(ok) : "r"(b), "r"(parity) : "memory");
    if (++it > SPIN_LIMIT) __trap();
  } while (!ok);
}
__device__ __forceinline__ void bar_sync(int id, int n) { asm volatile("bar.sync %0, %1;" ::"r"(id), "r"(n) : "memory"); }
__device__ __forceinline__ void bar_arrive(int id, int n) { asm volatile("bar.arrive %0, %1;" ::"r"(id), "r"(n) : "memory"); }
__device__ __forceinline__ void red_release(unsigned* p) { asm volatile("red.release.gpu.global.add.u32 [%0], 1;" ::"l"(p) : "memory"); }
__device__ __forceinline__ unsigned ld_acquire(const unsigned* p) {
  unsigned v;
  asm volatile("ld.acquire.gpu.global.u32 %0, [%1];" : "=r"(v) : "l"(p) : "memory");
  return v;
}
__device__ __forceinline__ unsigned ld_relaxed(const unsigned* p) {
  unsigned v;
  asm volatile("ld.relaxed.gpu.global.u32 %0, [%1];" : "=r"(v) : "l"(p) : "memory");
  return v;
}
__device__ __forceinline__ void wait_counter(const unsigned* p, unsigned target) {
  int it = 0;
  while ((int)(ld_acquire(p) - target) < 0)
    if (++it > SPIN_LIMIT) __trap();
}
__device__ __forceinline__ uint4 ldg_cg4(const uint4* p) {
  uint4 v;
  asm volatile("ld.global.cg.v4.u32 {%0,%1,%2,%3}, [%4];" : "=r"(v.x), "=r"(v.y), "=r"(v.z), "=r"(v.w) : "l"(p) : "memory");
  return v;
}
__device__ __forceinline__ uint4 ldg_nc4(const void* p) {
  uint4 v;
  asm volatile("ld.global.nc.v4.u32 {%0,%1,%2,%3}, [%4];" : "=r"(v.x), "=r"(v.y), "=r"(v.z), "=r"(v.w) : "l"(p));
  return v;
}
__device__ __forceinline__ uint2 ldg_nc2(const void* p) {
  uint2 v;
  asm volatile("ld.global.nc.v2.u32 {%0,%1}, [%2];" : "=r"(v.x), "=r"(v.y) : "l"(p));
  return v;
}
__device__ __forceinline__ uint32_t ldg_nc_u16(const void* p) {
  uint16_t v;
  asm volatile("ld.global.nc.u16 %0, [%1];" : "=h"(v) : "l"(p));
  return v;
}
__device__ __forceinline__ void sts4(uint32_t a, uint32_t x, uint32_t y, uint32_t z, uint32_t w) {
  asm volatile("st.shared.v4.u32 [%0], {%1,%2,%3,%4};" ::"r"(a), "r"(x), "r"(y), "r"(z), "r"(w) : "memory");
}
__device__ __forceinline__ uint4 lds4(uint32_t a) {
  uint4 v;
  asm volatile("ld.shared.v4.u32 {%0,%1,%2,%3}, [%4];" : "=r"(v.x), "=r"(v.y), "=r"(v.z), "=r"(v.w) : "r"(a) : "memory");
  return v;
}
__device__ __forceinline__ uint32_t pack2(float lo, float hi) {
  uint32_t r;
  asm("cvt.rn.bf16x2.f32 %0, %1, %2;" : "=r"(r) : "f"(hi), "f"(lo));
  return r;
}
__device__ __forceinline__ float bf_lo(uint32_t v) { return __uint_as_float(v << 16); }
__device__ __forceinline__ float bf_hi(uint32_t v) { return __uint_as_float(v & 0xffff0000u); }
__device__ __forceinline__ uint32_t hadd2_bf16(uint32_t a, uint32_t b) {
  uint32_t r;
  asm("add.rn.bf16x2 %0, %1, %2;" : "=r"(r) : "r"(a), "r"(b));
  return r;
}
__device__ __forceinline__ void mma16816(float (&d)[4], uint32_t a0, uint32_t a1, uint32_t a2, uint32_t a3, uint32_t b0, uint32_t b1) {
  asm("mma.sync.aligned.m16n8k16.row.col.f32.bf16.bf16.f32 {%0,%1,%2,%3}, {%4,%5,%6,%7}, {%8,%9}, {%0,%1,%2,%3};"
      : "+f"(d[0]), "+f"(d[1]), "+f"(d[2]), "+f"(d[3])
      : "r"(a0), "r"(a1), "r"(a2), "r"(a3), "r"(b0), "r"(b1));
}
template <int N>
__device__ __forceinline__ void cs_frac(int idx, float& c, float& s) {
  int i = ((idx + N / 2) & (N - 1)) - N / 2;
  float a = (float)i * (6.283185307179586f / N);
  c = __cosf(a);
  s = __sinf(a);
}
template <int N>
__device__ __forceinline__ uint32_t cfrag(int idx, int ri) {
  float c, s;
  cs_frac<N>(idx, c, s);
  return ri ? pack2(-s, c) : pack2(c, s);
}
__device__ __forceinline__ uint32_t word(const uint4& v, int e) { return e == 0 ? v.x : e == 1 ? v.y : e == 2 ? v.z : v.w; }
__device__ __forceinline__ void cdft16(const uint4 (&q)[4], const uint32_t (&F)[16], uint4 (&o)[4]) {
  float acc[2][4][4];
#pragma unroll
  for (int p = 0; p < 2; p++)
#pragma unroll
    for (int v = 0; v < 4; v++) {
      acc[p][v][0] = acc[p][v][1] = acc[p][v][2] = acc[p][v][3] = 0.f;
#pragma unroll
      for (int ks = 0; ks < 2; ks++)
        mma16816(acc[p][v], word(q[2 * ks], 2 * p), word(q[2 * ks], 2 * p + 1), word(q[2 * ks + 1], 2 * p),
                 word(q[2 * ks + 1], 2 * p + 1), F[(ks * 4 + v) * 2], F[(ks * 4 + v) * 2 + 1]);
    }
#pragma unroll
  for (int v = 0; v < 4; v++)
    o[v] = make_uint4(pack2(acc[0][v][0], acc[0][v][1]), pack2(acc[0][v][2], acc[0][v][3]),
                      pack2(acc[1][v][0], acc[1][v][1]), pack2(acc[1][v][2], acc[1][v][3]));
}
__device__ __forceinline__ float warp_sum(float v) {
#pragma unroll
  for (int o = 16; o > 0; o >>= 1) v += __shfl_xor_sync(0xffffffffu, v, o);
  return v;
}
__device__ __forceinline__ uint64_t mkdesc(uint32_t addr, uint32_t lbo, uint32_t sbo, uint32_t swz) {
  return (uint64_t)((addr & 0x3FFFF) >> 4) | ((uint64_t)(lbo >> 4) << 16) | ((uint64_t)(sbo >> 4) << 32) | ((uint64_t)swz << 62);
}
__device__ __forceinline__ void wg_fence() { asm volatile("wgmma.fence.sync.aligned;" ::: "memory"); }
__device__ __forceinline__ void wg_commit() { asm volatile("wgmma.commit_group.sync.aligned;" ::: "memory"); }
template <int N>
__device__ __forceinline__ void wg_wait() { asm volatile("wgmma.wait_group.sync.aligned %0;" ::"n"(N) : "memory"); }
__device__ __forceinline__ void bulk_load(uint32_t dst, const void* src, int bytes, uint32_t bar) {
  asm volatile("cp.async.bulk.shared::cluster.global.mbarrier::complete_tx::bytes [%0], [%1], %2, [%3];"
               ::"r"(dst), "l"(src), "r"(bytes), "r"(bar) : "memory");
}
__device__ __forceinline__ void tma3(uint32_t dst, const CUtensorMap* tm, uint32_t bar, int c0, int c1, int c2) {
  asm volatile("cp.async.bulk.tensor.3d.shared::cluster.global.mbarrier::complete_tx::bytes [%0], [%1, {%3,%4,%5}], [%2];"
               ::"r"(dst), "l"(tm), "r"(bar), "r"(c0), "r"(c1), "r"(c2) : "memory");
}
__device__ __forceinline__ void tma5(uint32_t dst, const CUtensorMap* tm, uint32_t bar, int c0, int c4) {
  asm volatile("cp.async.bulk.tensor.5d.shared::cluster.global.mbarrier::complete_tx::bytes [%0], [%1, {%3,%4,%4,%4,%5}], [%2];"
               ::"r"(dst), "l"(tm), "r"(bar), "r"(c0), "r"(0), "r"(c4) : "memory");
}
__device__ __forceinline__ void fence_proxy_async() { asm volatile("fence.proxy.async;" ::: "memory"); }
__device__ __forceinline__ float swiglu(float g, float u) {
  float hg = 0.5f * g, th;
  asm("tanh.approx.f32 %0, %1;" : "=f"(th) : "f"(hg));
  return fmaf(hg, th, hg) * u;
}

__device__ __forceinline__ void wgmma_n256(float (&d)[128], uint64_t da, uint64_t db, int sd) {
  asm volatile("{.reg .pred p; setp.ne.b32 p, %130, 0;\n"
      "wgmma.mma_async.sync.aligned.m64n256k16.f32.bf16.bf16 {"
      "%0,%1,%2,%3,%4,%5,%6,%7,%8,%9,%10,%11,%12,%13,%14,%15,"
      "%16,%17,%18,%19,%20,%21,%22,%23,%24,%25,%26,%27,%28,%29,%30,%31,"
      "%32,%33,%34,%35,%36,%37,%38,%39,%40,%41,%42,%43,%44,%45,%46,%47,"
      "%48,%49,%50,%51,%52,%53,%54,%55,%56,%57,%58,%59,%60,%61,%62,%63,"
      "%64,%65,%66,%67,%68,%69,%70,%71,%72,%73,%74,%75,%76,%77,%78,%79,"
      "%80,%81,%82,%83,%84,%85,%86,%87,%88,%89,%90,%91,%92,%93,%94,%95,"
      "%96,%97,%98,%99,%100,%101,%102,%103,%104,%105,%106,%107,%108,%109,%110,%111,"
      "%112,%113,%114,%115,%116,%117,%118,%119,%120,%121,%122,%123,%124,%125,%126,%127"
      "}, %128, %129, p, 1, 1, 0, 1;}\n"
      : "+f"(d[0]),"+f"(d[1]),"+f"(d[2]),"+f"(d[3]),"+f"(d[4]),"+f"(d[5]),"+f"(d[6]),"+f"(d[7]),
        "+f"(d[8]),"+f"(d[9]),"+f"(d[10]),"+f"(d[11]),"+f"(d[12]),"+f"(d[13]),"+f"(d[14]),"+f"(d[15]),
        "+f"(d[16]),"+f"(d[17]),"+f"(d[18]),"+f"(d[19]),"+f"(d[20]),"+f"(d[21]),"+f"(d[22]),"+f"(d[23]),
        "+f"(d[24]),"+f"(d[25]),"+f"(d[26]),"+f"(d[27]),"+f"(d[28]),"+f"(d[29]),"+f"(d[30]),"+f"(d[31]),
        "+f"(d[32]),"+f"(d[33]),"+f"(d[34]),"+f"(d[35]),"+f"(d[36]),"+f"(d[37]),"+f"(d[38]),"+f"(d[39]),
        "+f"(d[40]),"+f"(d[41]),"+f"(d[42]),"+f"(d[43]),"+f"(d[44]),"+f"(d[45]),"+f"(d[46]),"+f"(d[47]),
        "+f"(d[48]),"+f"(d[49]),"+f"(d[50]),"+f"(d[51]),"+f"(d[52]),"+f"(d[53]),"+f"(d[54]),"+f"(d[55]),
        "+f"(d[56]),"+f"(d[57]),"+f"(d[58]),"+f"(d[59]),"+f"(d[60]),"+f"(d[61]),"+f"(d[62]),"+f"(d[63]),
        "+f"(d[64]),"+f"(d[65]),"+f"(d[66]),"+f"(d[67]),"+f"(d[68]),"+f"(d[69]),"+f"(d[70]),"+f"(d[71]),
        "+f"(d[72]),"+f"(d[73]),"+f"(d[74]),"+f"(d[75]),"+f"(d[76]),"+f"(d[77]),"+f"(d[78]),"+f"(d[79]),
        "+f"(d[80]),"+f"(d[81]),"+f"(d[82]),"+f"(d[83]),"+f"(d[84]),"+f"(d[85]),"+f"(d[86]),"+f"(d[87]),
        "+f"(d[88]),"+f"(d[89]),"+f"(d[90]),"+f"(d[91]),"+f"(d[92]),"+f"(d[93]),"+f"(d[94]),"+f"(d[95]),
        "+f"(d[96]),"+f"(d[97]),"+f"(d[98]),"+f"(d[99]),"+f"(d[100]),"+f"(d[101]),"+f"(d[102]),"+f"(d[103]),
        "+f"(d[104]),"+f"(d[105]),"+f"(d[106]),"+f"(d[107]),"+f"(d[108]),"+f"(d[109]),"+f"(d[110]),"+f"(d[111]),
        "+f"(d[112]),"+f"(d[113]),"+f"(d[114]),"+f"(d[115]),"+f"(d[116]),"+f"(d[117]),"+f"(d[118]),"+f"(d[119]),
        "+f"(d[120]),"+f"(d[121]),"+f"(d[122]),"+f"(d[123]),"+f"(d[124]),"+f"(d[125]),"+f"(d[126]),"+f"(d[127])
      : "l"(da), "l"(db), "r"(sd));
}
__device__ __forceinline__ void wgmma_n192(float (&d)[96], uint64_t da, uint64_t db, int sd) {
  asm volatile("{.reg .pred p; setp.ne.b32 p, %98, 0;\n"
      "wgmma.mma_async.sync.aligned.m64n192k16.f32.bf16.bf16 {"
      "%0,%1,%2,%3,%4,%5,%6,%7,%8,%9,%10,%11,%12,%13,%14,%15,"
      "%16,%17,%18,%19,%20,%21,%22,%23,%24,%25,%26,%27,%28,%29,%30,%31,"
      "%32,%33,%34,%35,%36,%37,%38,%39,%40,%41,%42,%43,%44,%45,%46,%47,"
      "%48,%49,%50,%51,%52,%53,%54,%55,%56,%57,%58,%59,%60,%61,%62,%63,"
      "%64,%65,%66,%67,%68,%69,%70,%71,%72,%73,%74,%75,%76,%77,%78,%79,"
      "%80,%81,%82,%83,%84,%85,%86,%87,%88,%89,%90,%91,%92,%93,%94,%95"
      "}, %96, %97, p, 1, 1, 0, 1;}\n"
      : "+f"(d[0]),"+f"(d[1]),"+f"(d[2]),"+f"(d[3]),"+f"(d[4]),"+f"(d[5]),"+f"(d[6]),"+f"(d[7]),
        "+f"(d[8]),"+f"(d[9]),"+f"(d[10]),"+f"(d[11]),"+f"(d[12]),"+f"(d[13]),"+f"(d[14]),"+f"(d[15]),
        "+f"(d[16]),"+f"(d[17]),"+f"(d[18]),"+f"(d[19]),"+f"(d[20]),"+f"(d[21]),"+f"(d[22]),"+f"(d[23]),
        "+f"(d[24]),"+f"(d[25]),"+f"(d[26]),"+f"(d[27]),"+f"(d[28]),"+f"(d[29]),"+f"(d[30]),"+f"(d[31]),
        "+f"(d[32]),"+f"(d[33]),"+f"(d[34]),"+f"(d[35]),"+f"(d[36]),"+f"(d[37]),"+f"(d[38]),"+f"(d[39]),
        "+f"(d[40]),"+f"(d[41]),"+f"(d[42]),"+f"(d[43]),"+f"(d[44]),"+f"(d[45]),"+f"(d[46]),"+f"(d[47]),
        "+f"(d[48]),"+f"(d[49]),"+f"(d[50]),"+f"(d[51]),"+f"(d[52]),"+f"(d[53]),"+f"(d[54]),"+f"(d[55]),
        "+f"(d[56]),"+f"(d[57]),"+f"(d[58]),"+f"(d[59]),"+f"(d[60]),"+f"(d[61]),"+f"(d[62]),"+f"(d[63]),
        "+f"(d[64]),"+f"(d[65]),"+f"(d[66]),"+f"(d[67]),"+f"(d[68]),"+f"(d[69]),"+f"(d[70]),"+f"(d[71]),
        "+f"(d[72]),"+f"(d[73]),"+f"(d[74]),"+f"(d[75]),"+f"(d[76]),"+f"(d[77]),"+f"(d[78]),"+f"(d[79]),
        "+f"(d[80]),"+f"(d[81]),"+f"(d[82]),"+f"(d[83]),"+f"(d[84]),"+f"(d[85]),"+f"(d[86]),"+f"(d[87]),
        "+f"(d[88]),"+f"(d[89]),"+f"(d[90]),"+f"(d[91]),"+f"(d[92]),"+f"(d[93]),"+f"(d[94]),"+f"(d[95])
      : "l"(da), "l"(db), "r"(sd));
}
__device__ __forceinline__ void wgmma_n128(float (&d)[64], uint64_t da, uint64_t db, int sd) {
  asm volatile("{.reg .pred p; setp.ne.b32 p, %66, 0;\n"
      "wgmma.mma_async.sync.aligned.m64n128k16.f32.bf16.bf16 {"
      "%0,%1,%2,%3,%4,%5,%6,%7,%8,%9,%10,%11,%12,%13,%14,%15,"
      "%16,%17,%18,%19,%20,%21,%22,%23,%24,%25,%26,%27,%28,%29,%30,%31,"
      "%32,%33,%34,%35,%36,%37,%38,%39,%40,%41,%42,%43,%44,%45,%46,%47,"
      "%48,%49,%50,%51,%52,%53,%54,%55,%56,%57,%58,%59,%60,%61,%62,%63"
      "}, %64, %65, p, 1, 1, 0, 1;}\n"
      : "+f"(d[0]),"+f"(d[1]),"+f"(d[2]),"+f"(d[3]),"+f"(d[4]),"+f"(d[5]),"+f"(d[6]),"+f"(d[7]),
        "+f"(d[8]),"+f"(d[9]),"+f"(d[10]),"+f"(d[11]),"+f"(d[12]),"+f"(d[13]),"+f"(d[14]),"+f"(d[15]),
        "+f"(d[16]),"+f"(d[17]),"+f"(d[18]),"+f"(d[19]),"+f"(d[20]),"+f"(d[21]),"+f"(d[22]),"+f"(d[23]),
        "+f"(d[24]),"+f"(d[25]),"+f"(d[26]),"+f"(d[27]),"+f"(d[28]),"+f"(d[29]),"+f"(d[30]),"+f"(d[31]),
        "+f"(d[32]),"+f"(d[33]),"+f"(d[34]),"+f"(d[35]),"+f"(d[36]),"+f"(d[37]),"+f"(d[38]),"+f"(d[39]),
        "+f"(d[40]),"+f"(d[41]),"+f"(d[42]),"+f"(d[43]),"+f"(d[44]),"+f"(d[45]),"+f"(d[46]),"+f"(d[47]),
        "+f"(d[48]),"+f"(d[49]),"+f"(d[50]),"+f"(d[51]),"+f"(d[52]),"+f"(d[53]),"+f"(d[54]),"+f"(d[55]),
        "+f"(d[56]),"+f"(d[57]),"+f"(d[58]),"+f"(d[59]),"+f"(d[60]),"+f"(d[61]),"+f"(d[62]),"+f"(d[63])
      : "l"(da), "l"(db), "r"(sd));
}

constexpr int C_BAR1 = 0, C_BAR2 = 1, C_LN = 2, C_PX = 18, C_PY = 34;
constexpr int NB_CONS = 1, NB_LN = 2, NB_PUB0 = 3, NB_LAG = 5;
constexpr int LAG = 2;

struct Bars {
  uint64_t full1[6], empty1[6], fullA[8], full2[6], empty2[6], xbar;
};

template <int NT>
__device__ __forceinline__ void store_p(const float (&acc)[NT * 32], uint4* pbase, int G0, int lane_off) {
#pragma unroll
  for (int q = 0; q < NT; q++) {
    const int G = G0 + q;
    uint4* dst = pbase + (G >> 1) * 1024 + (G & 1) * 32 + lane_off;
#pragma unroll
    for (int h = 0; h < 2; h++) {
      uint32_t w[4];
#pragma unroll
      for (int i = 0; i < 4; i++) {
        const int a = (q * 4 + i) * 4 + 2 * h, b = a + NT * 16;
        w[i] = pack2(swiglu(acc[a], acc[b]), swiglu(acc[a + 1], acc[b + 1]));
      }
      dst[h * 64] = make_uint4(w[0], w[1], w[2], w[3]);
    }
  }
}

__global__ void __cluster_dims__(2, 1, 1) __launch_bounds__(NTHREADS, 1)
fused_kernel(const __grid_constant__ CUtensorMap tmGX, const __grid_constant__ CUtensorMap tmUX,
             const __grid_constant__ CUtensorMap tmGY, const __grid_constant__ CUtensorMap tmUY,
             const __grid_constant__ CUtensorMap tmD,
             const __nv_bfloat16* __restrict__ x, const __nv_bfloat16* __restrict__ wr, const __nv_bfloat16* __restrict__ wi,
             const char* __restrict__ wg_raw, const char* __restrict__ wu_raw, const char* __restrict__ wd_raw,
             __nv_bfloat16* __restrict__ out) {
  extern __shared__ __align__(1024) char smem_raw[];
  const uint32_t sbase = (s2u(smem_raw) + 1023) & ~1023u;
  const uint32_t sbar = sbase + 14 * SLOT;
  const int tid = threadIdx.x, warp = tid >> 5, lane = tid & 31;
  const int c = blockIdx.x, rb = c >> 3, f = c & 7;
#define BAR(field, i) (sbar + (uint32_t)offsetof(Bars, field) + 8u * (i))

  if (tid == 256) {
    for (int i = 0; i < 6; i++) {
      mbar_init(BAR(full1, i), 1); mbar_init(BAR(empty1, i), 8);
      mbar_init(BAR(full2, i), 1); mbar_init(BAR(empty2, i), 8);
    }
    for (int i = 0; i < 8; i++) mbar_init(BAR(fullA, i), 1);
    mbar_init(BAR(xbar, 0), 1);
    mbar_expect(BAR(xbar, 0), 32768);
    asm volatile("fence.mbarrier_init.release.cluster;" ::: "memory");
  }
  __syncthreads();
  asm volatile("barrier.cluster.arrive.relaxed.aligned;" ::: "memory");

  if (warp >= 8) {
    asm volatile("setmaxnreg.dec.sync.aligned.u32 40;");
    asm volatile("barrier.cluster.wait.aligned;" ::: "memory");
    if (warp <= 9) {
      if (lane == 0) {
        const int ax = (7 * f + 3 * (f & 1)) >> 1;
        const int ay = 7 * f + ((f & 1) ? 0 : 4);
        for (int n = warp - 8; n < 32; n += 2) {
          const int s = n % 6, r = n / 6;
          const uint32_t dst = sbase + (8 + s) * SLOT, fb = BAR(full1, s);
          if (r > 0) mbar_wait(BAR(empty1, s), (r - 1) & 1);
          if (n < 16) {
            mbar_expect(fb, 16384);
            tma3(dst, &tmGX, fb, 0, n * 32, ax);
            tma3(dst + 8192, &tmUX, fb, 0, n * 32, ax);
          } else {
            mbar_expect(fb, 12288);
            tma3(dst, &tmGY, fb, 0, (n - 16) * 32, ay);
            tma3(dst + 6144, &tmUY, fb, 0, (n - 16) * 32, ay);
          }
        }
      }
    } else if (warp == 10) {
      unsigned epoch = 0;
      if (lane == 0) epoch = ld_relaxed(&g_cnt[(C_LN + rb) * 32]) >> 3;
      bar_sync(NB_LN, 288);
      if (lane == 0) {
        red_release(&g_cnt[(C_LN + rb) * 32]);
        wait_counter(&g_cnt[(C_LN + rb) * 32], (epoch + 1) * 8);
        fence_proxy_async();
        for (int kb = 0; kb < 8; kb++) {
          mbar_expect(BAR(fullA, kb), 16384);
          bulk_load(sbase + kb * SLOT, &g_LN[(rb * 8 + kb) * 1024], 16384, BAR(fullA, kb));
        }
        const int nq = f >> 1, kh = f & 1;
        for (int s = 0; s < 14; s++) {
          const int d = s % 6, r = s / 6;
          const int dslot = (0x365210 >> (4 * d)) & 15;
          const int kblk = 14 * kh + (int)((0xBA9432DC876510ull >> (4 * s)) & 15);
          const uint32_t dst = sbase + dslot * 2 * SLOT, fb = BAR(full2, d);
          mbar_wait(BAR(empty2, d), r & 1);
          mbar_expect(fb, 32768);
          tma5(dst + SLOT, &tmD, fb, nq * 128, 2 * kblk);
          tma5(dst + SLOT + 8192, &tmD, fb, nq * 128 + 64, 2 * kblk);
          if (s == 0 || s == 8) {
            wait_counter(&g_cnt[((s == 0 ? C_PX : C_PY) + rb) * 32], (epoch + 1) * 16);
            fence_proxy_async();
          }
          bulk_load(dst, &g_P[(rb * 28 + kblk) * 1024], 16384, fb);
        }
      }
    } else {
      if (lane < 3) {
        const char* p = (lane == 0 ? wg_raw : lane == 1 ? wu_raw : wd_raw) + (size_t)c * 14336;
        asm volatile("cp.async.bulk.prefetch.L2.global [%0], %1;" ::"l"(p), "r"(14336) : "memory");
      }
      for (int e = 0; e < 4; e++) {
        bar_sync(NB_PUB0 + (e & 1), 160);
        if (lane == 0) red_release(&g_cnt[((e < 2 ? C_PX : C_PY) + rb) * 32]);
      }
    }
  } else {
    asm volatile("setmaxnreg.inc.sync.aligned.u32 232;");
    const int g = lane >> 2, t = lane & 3;
    PROF(0);
    unsigned epoch = 0;
    uint32_t wf[16];
    {
      const __nv_bfloat16* xa = x + (size_t)(c + 256 * warp) * 512 + 64 * t + 4 * g;
      uint2 v[2][4];
#pragma unroll
      for (int r = 0; r < 2; r++)
#pragma unroll
        for (int q = 0; q < 4; q++) v[r][q] = ldg_nc2(xa + r * 128 * 512 + (q & 1) * 32 + (q >> 1) * 256);
      uint4 fb[16];
#pragma unroll
      for (int i = 0; i < 16; i++) fb[i] = ldg_nc4(&g_tab.fb[i][lane][0]);
      const uint4 fa = ldg_nc4(&g_tab.fa[lane][0]);
      if (tid == 0) epoch = ld_relaxed(&g_cnt[C_BAR1 * 32]) >> 7;
      uint32_t wtr[16], wti[16];
      {
        const int j1 = c >> 3, m = c & 7, gg = g == 0 ? 8 : g;
#pragma unroll
        for (int i = 0; i < 16; i++) {
          const int ci = i >> 3, dd = (i >> 2) & 1, e = i & 3;
          const int row = j1 + 16 * (2 * warp + ci) + 256 * (t + 4 * dd);
          const int kk = 32 * m + (e == 0 ? gg : e == 1 ? 16 + gg : e == 2 ? 16 - g : 32 - g);
          wtr[i] = ldg_nc_u16(wr + row * 257 + kk);
          wti[i] = ldg_nc_u16(wi + row * 257 + kk);
        }
      }
      float twc[8], tws[8];
#pragma unroll
      for (int i = 0; i < 8; i++) cs_frac<512>((8 * t + i) * (g == 0 ? 8 : g), twc[i], tws[i]);
      uint32_t fc[16];
#pragma unroll
      for (int i = 0; i < 16; i++) {
        const int ks = i >> 3, vv = (i >> 1) & 3, hh = i & 1;
        fc[i] = cfrag<2048>((c + 128 * (t + 4 * hh + 8 * ks)) * (4 * vv + (g >> 1)), g & 1);
      }
      float mean[2], rstd[2];
#pragma unroll
      for (int r = 0; r < 2; r++) {
        float s = 0.f;
#pragma unroll
        for (int q = 0; q < 4; q++) s += (bf_lo(v[r][q].x) + bf_hi(v[r][q].x)) + (bf_lo(v[r][q].y) + bf_hi(v[r][q].y));
        mean[r] = warp_sum(s) * (1.f / 512.f);
      }
#pragma unroll
      for (int r = 0; r < 2; r++) {
        float s = 0.f;
#pragma unroll
        for (int q = 0; q < 4; q++) {
          float a0 = bf_lo(v[r][q].x) - mean[r], a1 = bf_hi(v[r][q].x) - mean[r];
          float a2 = bf_lo(v[r][q].y) - mean[r], a3 = bf_hi(v[r][q].y) - mean[r];
          s += (a0 * a0 + a1 * a1) + (a2 * a2 + a3 * a3);
        }
        rstd[r] = rsqrtf(warp_sum(s) * (1.f / 512.f) + 1e-5f);
      }
      uint32_t alo[4][4], ahi[4][4];
#pragma unroll
      for (int r = 0; r < 2; r++)
#pragma unroll
        for (int i = 0; i < 4; i++) {
          const uint32_t sel = (i & 1) ? 0x7632u : 0x5410u;
          const uint32_t b0 = __byte_perm((i & 2) ? v[r][0].y : v[r][0].x, (i & 2) ? v[r][1].y : v[r][1].x, sel);
          const uint32_t b1 = __byte_perm((i & 2) ? v[r][2].y : v[r][2].x, (i & 2) ? v[r][3].y : v[r][3].x, sel);
          float d[4] = {0.f, 0.f, 0.f, 0.f};
          mma16816(d, fa.x, fa.y, fa.z, fa.w, b0, b1);
          const float a0 = g == 0 ? d[2] : d[0], a1 = g == 0 ? d[3] : d[1];
          const float i0 = g == 0 ? 0.f : d[2], i1 = g == 0 ? 0.f : d[3];
          const uint32_t re = pack2(a0 * twc[i] + i0 * tws[i], a1 * twc[i + 4] + i1 * tws[i + 4]);
          const uint32_t im = pack2(i0 * twc[i] - a0 * tws[i], i1 * twc[i + 4] - a1 * tws[i + 4]);
          const uint32_t dc = pack2(d[0] - 16.f * mean[r], d[1] - 16.f * mean[r]);
          alo[i][r] = re; alo[i][2 + r] = im;
          ahi[i][r] = g == 0 ? dc : re; ahi[i][2 + r] = g == 0 ? 0u : im;
        }
      float acc[8][4];
#pragma unroll
      for (int u = 0; u < 8; u++) {
        acc[u][0] = acc[u][1] = acc[u][2] = acc[u][3] = 0.f;
#pragma unroll
        for (int i = 0; i < 4; i++) {
          const uint4& bq = fb[i * 4 + (u >> 1)];
          if (u < 4) mma16816(acc[u], alo[i][0], alo[i][1], alo[i][2], alo[i][3], (u & 1) ? bq.z : bq.x, (u & 1) ? bq.w : bq.y);
          else       mma16816(acc[u], ahi[i][0], ahi[i][1], ahi[i][2], ahi[i][3], (u & 1) ? bq.z : bq.x, (u & 1) ? bq.w : bq.y);
        }
      }
#pragma unroll
      for (int r = 0; r < 2; r++)
#pragma unroll
        for (int h = 0; h < 2; h++) {
          const int j = 2 * warp + r, m = 2 * t + h;
          const float rs = rstd[r];
          sts4(sbase + ((j * 8 + m) * 8 + (g ^ (2 * t) ^ (2 * (j & 3)))) * 16,
               pack2(acc[2 * h][2 * r] * rs, acc[2 * h][2 * r + 1] * rs), pack2(acc[2 * h + 1][2 * r] * rs, acc[2 * h + 1][2 * r + 1] * rs),
               pack2(acc[4 + 2 * h][2 * r] * rs, acc[4 + 2 * h][2 * r + 1] * rs), pack2(acc[5 + 2 * h][2 * r] * rs, acc[5 + 2 * h][2 * r + 1] * rs));
        }
      bar_sync(NB_CONS, 256);
      uint4 q[4], o[4];
#pragma unroll
      for (int i = 0; i < 4; i++) q[i] = lds4(sbase + (((t + 4 * i) * 8 + warp) * 8 + (g ^ (warp & 6) ^ (2 * t))) * 16);
      cdft16(q, fc, o);
#pragma unroll
      for (int vv = 0; vv < 4; vv++) g_Z1[(((4 * vv + t) * 8 + warp) * 128 + c) * 8 + g] = o[vv];
#pragma unroll
      for (int i = 0; i < 16; i++) wf[i] = wtr[i] | (wti[i] << 16);
    }
    PROF(1);
    bar_sync(NB_CONS, 256);
    if (tid == 0) red_release(&g_cnt[C_BAR1 * 32]);
    {
      uint32_t f2[16], g2[16], f8[4], g8[4];
#pragma unroll
      for (int i = 0; i < 16; i++) {
        const int ks = i >> 3, vv = (i >> 1) & 3, hh = i & 1;
        const int kidx = t + 4 * hh + 8 * ks, nidx = 4 * vv + (g >> 1);
        f2[i] = cfrag<128>((8 * kidx + warp) * nidx, g & 1);
        g2[i] = cfrag<128>(-(8 * nidx + warp) * kidx, g & 1);
      }
#pragma unroll
      for (int i = 0; i < 4; i++) {
        const int p = (t + 4 * (i & 1)) * (4 * (i >> 1) + (g >> 1));
        f8[i] = cfrag<8>(p, g & 1);
        g8[i] = cfrag<8>(-p, g & 1);
      }
      asm volatile("barrier.cluster.wait.aligned;" ::: "memory");
      if (tid == 0) wait_counter(&g_cnt[C_BAR1 * 32], (epoch + 1) * 128);
      bar_sync(NB_CONS, 256);
      PROF(2);
      uint4 q[4], o[4];
#pragma unroll
      for (int i = 0; i < 4; i++) q[i] = ldg_cg4(&g_Z1[(c * 128 + 8 * (t + 4 * i) + warp) * 8 + g]);
      cdft16(q, f2, o);
      const uint32_t e2 = sbase + SLOT;
#pragma unroll
      for (int vv = 0; vv < 4; vv++)
        sts4(e2 + ((warp * 16 + 4 * vv + t) * 8 + (g ^ (2 * t) ^ (2 * (warp & 3)))) * 16, o[vv].x, o[vv].y, o[vv].z, o[vv].w);
      bar_sync(NB_CONS, 256);
      const float fsc = 1.f / (1 << 19);
      const float fsc3 = ((c & 7) == 7 && g == 0) ? 0.5f * fsc : fsc;
#pragma unroll
      for (int ci = 0; ci < 2; ci++) {
        const int cc = 2 * warp + ci;
        uint32_t ad[2];
        uint4 u[2];
#pragma unroll
        for (int hh = 0; hh < 2; hh++) {
          ad[hh] = e2 + (((t + 4 * hh) * 16 + cc) * 8 + (g ^ (2 * (cc & 3)) ^ (2 * t))) * 16;
          u[hh] = lds4(ad[hh]);
        }
        uint32_t res[2][4];
#pragma unroll
        for (int p = 0; p < 2; p++) {
          uint32_t y[2][2];
#pragma unroll
          for (int vv = 0; vv < 2; vv++) {
            float d[4] = {0.f, 0.f, 0.f, 0.f};
            mma16816(d, word(u[0], 2 * p), word(u[0], 2 * p + 1), word(u[1], 2 * p), word(u[1], 2 * p + 1), f8[2 * vv], f8[2 * vv + 1]);
#pragma unroll
            for (int rr = 0; rr < 2; rr++) {
              const int e = 2 * p + rr;
              const uint32_t w = wf[ci * 8 + vv * 4 + e];
              const float sc = e == 3 ? fsc3 : fsc;
              const float fr = bf_lo(w) * sc, fi = bf_hi(w) * sc;
              y[vv][rr] = pack2(d[2 * rr] * fr - d[2 * rr + 1] * fi, d[2 * rr] * fi + d[2 * rr + 1] * fr);
            }
          }
#pragma unroll
          for (int vv = 0; vv < 2; vv++) {
            float d[4] = {0.f, 0.f, 0.f, 0.f};
            mma16816(d, y[0][0], y[0][1], y[1][0], y[1][1], g8[2 * vv], g8[2 * vv + 1]);
            res[vv][2 * p] = pack2(d[0], d[1]);
            res[vv][2 * p + 1] = pack2(d[2], d[3]);
          }
        }
#pragma unroll
        for (int vv = 0; vv < 2; vv++) sts4(ad[vv], res[vv][0], res[vv][1], res[vv][2], res[vv][3]);
      }
      bar_sync(NB_CONS, 256);
#pragma unroll
      for (int i = 0; i < 4; i++) q[i] = lds4(e2 + ((warp * 16 + 4 * i + t) * 8 + (g ^ (2 * t) ^ (2 * (warp & 3)))) * 16);
      cdft16(q, g2, o);
#pragma unroll
      for (int vv = 0; vv < 4; vv++) g_Z2[((8 * (4 * vv + t) + warp) * 128 + c) * 8 + g] = o[vv];
    }
    PROF(3);
    bar_sync(NB_CONS, 256);
    if (tid == 0) red_release(&g_cnt[C_BAR2 * 32]);
    {
      uint4 gb[16];
#pragma unroll
      for (int i = 0; i < 16; i++) gb[i] = ldg_nc4(&g_tab.gb[i][lane][0]);
      const uint4 ga = ldg_nc4(&g_tab.ga[lane][0]);
      uint4 xr[2][2];
#pragma unroll
      for (int r = 0; r < 2; r++)
#pragma unroll
        for (int h = 0; h < 2; h++) xr[r][h] = ldg_nc4(x + (size_t)(c + 128 * (2 * warp + r)) * 512 + 32 * (g + 8 * h) + 8 * t);
      uint32_t gc[16];
#pragma unroll
      for (int i = 0; i < 16; i++) {
        const int ks = i >> 3, vv = (i >> 1) & 3, hh = i & 1;
        gc[i] = cfrag<2048>(-(c + 128 * (4 * vv + (g >> 1))) * (t + 4 * hh + 8 * ks), g & 1);
      }
      float twc[8], tws[8];
#pragma unroll
      for (int i = 0; i < 8; i++) {
        const int k1 = 2 * t + (i & 1);
        cs_frac<512>((4 * g + (i >> 1)) * (k1 == 0 ? 8 : k1), twc[i], tws[i]);
      }
      if (tid == 0) wait_counter(&g_cnt[C_BAR2 * 32], (epoch + 1) * 128);
      bar_sync(NB_CONS, 256);
      PROF(4);
      uint4 q[4], o[4];
#pragma unroll
      for (int i = 0; i < 4; i++) q[i] = ldg_cg4(&g_Z2[((c * 16 + t + 4 * i) * 8 + warp) * 8 + g]);
      cdft16(q, gc, o);
#pragma unroll
      for (int vv = 0; vv < 4; vv++)
        sts4(sbase + (((4 * vv + t) * 8 + warp) * 8 + (g ^ (warp & 6) ^ (2 * t))) * 16, o[vv].x, o[vv].y, o[vv].z, o[vv].w);
      bar_sync(NB_CONS, 256);
      uint32_t hv[2][2][4];
#pragma unroll
      for (int r = 0; r < 2; r++) {
        const int j = 2 * warp + r;
        uint4 u[2];
#pragma unroll
        for (int h = 0; h < 2; h++) u[h] = lds4(sbase + ((j * 8 + 2 * t + h) * 8 + (g ^ (2 * t) ^ (2 * (j & 3)))) * 16);
        float yv[4][4];
#pragma unroll
        for (int i = 0; i < 4; i++) {
          float lo[4] = {0.f, 0.f, 0.f, 0.f}, hi[4] = {0.f, 0.f, 0.f, 0.f};
          mma16816(lo, gb[i * 4].x, gb[i * 4].y, gb[i * 4].z, gb[i * 4].w, u[0].x, u[0].y);
          mma16816(lo, gb[i * 4 + 1].x, gb[i * 4 + 1].y, gb[i * 4 + 1].z, gb[i * 4 + 1].w, u[1].x, u[1].y);
          mma16816(hi, gb[i * 4 + 2].x, gb[i * 4 + 2].y, gb[i * 4 + 2].z, gb[i * 4 + 2].w, u[0].z, u[0].w);
          mma16816(hi, gb[i * 4 + 3].x, gb[i * 4 + 3].y, gb[i * 4 + 3].z, gb[i * 4 + 3].w, u[1].z, u[1].w);
          const float tr0 = t == 0 ? lo[0] : lo[0] + hi[0], ti0 = t == 0 ? lo[2] : lo[2] + hi[2];
          const float tr1 = lo[1] + hi[1], ti1 = lo[3] + hi[3];
          const float vr0 = tr0 * twc[2 * i] - ti0 * tws[2 * i], vi0 = tr0 * tws[2 * i] + ti0 * twc[2 * i];
          const float vr1 = tr1 * twc[2 * i + 1] - ti1 * tws[2 * i + 1], vi1 = tr1 * tws[2 * i + 1] + ti1 * twc[2 * i + 1];
          const uint32_t b0 = pack2(t == 0 ? hi[0] : vr0, vr1), b1 = pack2(t == 0 ? vr0 : vi0, vi1);
          yv[i][0] = yv[i][1] = yv[i][2] = yv[i][3] = 0.f;
          mma16816(yv[i], ga.x, ga.y, ga.z, ga.w, b0, b1);
        }
#pragma unroll
        for (int h = 0; h < 2; h++) {
          hv[r][h][0] = hadd2_bf16(xr[r][h].x, pack2(yv[0][2 * h], yv[1][2 * h]));
          hv[r][h][1] = hadd2_bf16(xr[r][h].y, pack2(yv[2][2 * h], yv[3][2 * h]));
          hv[r][h][2] = hadd2_bf16(xr[r][h].z, pack2(yv[0][2 * h + 1], yv[1][2 * h + 1]));
          hv[r][h][3] = hadd2_bf16(xr[r][h].w, pack2(yv[2][2 * h + 1], yv[3][2 * h + 1]));
        }
      }
      float mean[2], rstd[2];
#pragma unroll
      for (int r = 0; r < 2; r++) {
        float s = 0.f;
#pragma unroll
        for (int i = 0; i < 8; i++) s += bf_lo(hv[r][i >> 2][i & 3]) + bf_hi(hv[r][i >> 2][i & 3]);
        mean[r] = warp_sum(s) * (1.f / 512.f);
      }
#pragma unroll
      for (int r = 0; r < 2; r++) {
        float s = 0.f;
#pragma unroll
        for (int i = 0; i < 8; i++) {
          const float a = bf_lo(hv[r][i >> 2][i & 3]) - mean[r], b = bf_hi(hv[r][i >> 2][i & 3]) - mean[r];
          s += a * a + b * b;
        }
        rstd[r] = rsqrtf(warp_sum(s) * (1.f / 512.f) + 1e-5f);
      }
#pragma unroll
      for (int r = 0; r < 2; r++) {
        const int row = 16 * f + 2 * warp + r;
        const float nm = -mean[r] * rstd[r];
#pragma unroll
        for (int h = 0; h < 2; h++) {
          uint32_t w[4];
#pragma unroll
          for (int i = 0; i < 4; i++) w[i] = pack2(fmaf(bf_lo(hv[r][h][i]), rstd[r], nm), fmaf(bf_hi(hv[r][h][i]), rstd[r], nm));
          const int n1 = g + 8 * h;
          g_LN[(rb * 8 + (n1 >> 1)) * 1024 + row * 8 + ((4 * (n1 & 1) + t) ^ (row & 7))] = make_uint4(w[0], w[1], w[2], w[3]);
        }
      }
#pragma unroll
      for (int r = 0; r < 2; r++)
#pragma unroll
        for (int h = 0; h < 2; h++)
          g_H[(c + 128 * (2 * warp + r)) * 64 + 4 * (g + 8 * h) + t] = make_uint4(hv[r][h][0], hv[r][h][1], hv[r][h][2], hv[r][h][3]);
      fence_proxy_async();
      bar_arrive(NB_LN, 288);
    }
    PROF(5);
    const int wgi = warp >> 2, wq = warp & 3;
    uint4* const pbase = &g_P[rb * 28 * 1024];
    const int p_lane = (8 * wgi + 2 * wq) * 64 + t * 8 + g;
    if (wgi == 1) bar_sync(NB_LAG, 256);
    {
      float acc[128];
#pragma unroll 1
      for (int n = 0; n < 16; n++) {
        const int s = n % 6;
        if ((n & 1) == 0) mbar_wait(BAR(fullA, n >> 1), 0);
        mbar_wait(BAR(full1, s), (n / 6) & 1);
        if (n == 0) PROF(6);
        const uint32_t aa = sbase + (n >> 1) * SLOT + wgi * 8192 + (n & 1) * 64, ba = sbase + (8 + s) * SLOT;
        wg_fence();
        wgmma_n256(acc, mkdesc(aa, 16, 1024, 1), mkdesc(ba, 4096, 1024, 1), n != 0);
        wgmma_n256(acc, mkdesc(aa + 32, 16, 1024, 1), mkdesc(ba + 2048, 4096, 1024, 1), 1);
        wg_commit();
        if (n == LAG && wgi == 0) bar_arrive(NB_LAG, 256);
        wg_wait<1>();
        if (n > 0 && lane == 0) mbar_arrive(BAR(empty1, (n - 1) % 6));
      }
      wg_wait<0>();
      if (lane == 0) mbar_arrive(BAR(empty1, 15 % 6));
      PROF(7);
      store_p<4>(acc, pbase, 7 * f + 3 * (f & 1), p_lane);
      bar_arrive(NB_PUB0 + wgi, 160);
    }
    PROF(8);
    {
      float acc[96];
#pragma unroll 1
      for (int n = 16; n < 32; n++) {
        const int s = n % 6, k = n - 16;
        mbar_wait(BAR(full1, s), (n / 6) & 1);
        const uint32_t aa = sbase + (k >> 1) * SLOT + wgi * 8192 + (k & 1) * 64, ba = sbase + (8 + s) * SLOT;
        wg_fence();
        wgmma_n192(acc, mkdesc(aa, 16, 1024, 1), mkdesc(ba, 2048, 512, 2), k != 0);
        wgmma_n192(acc, mkdesc(aa + 32, 16, 1024, 1), mkdesc(ba + 1024, 2048, 512, 2), 1);
        wg_commit();
        wg_wait<1>();
        if (lane == 0) {
          const int p = n - 1;
          if (p >= 16 && p < 26) mbar_arrive(BAR(empty1, p % 6));
          if (p == 19) mbar_arrive(BAR(empty2, 0));
          if (p == 23) mbar_arrive(BAR(empty2, 1));
          if (p == 27) { mbar_arrive(BAR(empty2, 2)); mbar_arrive(BAR(empty2, 3)); }
          if (p == 29) mbar_arrive(BAR(empty2, 4));
        }
      }
      wg_wait<0>();
      if (lane == 0) mbar_arrive(BAR(empty2, 5));
      PROF(9);
      store_p<3>(acc, pbase, 7 * f + ((f & 1) ? 0 : 4), p_lane);
      bar_arrive(NB_PUB0 + wgi, 160);
    }
    PROF(10);
    {
      const int kh = f & 1, nq = f >> 1;
      const int rh = wgi ^ kh ^ 1;
      uint4 hres[2][4];
      const int orow = 8 * rb + 4 * rh + wq;
      if (wgi == 1) {
#pragma unroll
        for (int h = 0; h < 2; h++)
#pragma unroll
          for (int q = 0; q < 4; q++) hres[h][q] = ldg_cg4(&g_H[(orow + 128 * (g + 8 * h)) * 64 + nq * 16 + 4 * q + t]);
      }
      float acc[64];
#pragma unroll 1
      for (int s = 0; s < 14; s++) {
        const int d = s % 6;
        const int dslot = (0x365210 >> (4 * d)) & 15;
        mbar_wait(BAR(full2, d), (s / 6) & 1);
        const uint32_t aa = sbase + dslot * 2 * SLOT + rh * 8192, ba = sbase + dslot * 2 * SLOT + SLOT;
        wg_fence();
#pragma unroll
        for (int kk = 0; kk < 4; kk++)
          wgmma_n128(acc, mkdesc(aa + kk * 256, 128, 1024, 0), mkdesc(ba + kk * 2048, 8192, 1024, 1), (s | kk) != 0);
        wg_commit();
        wg_wait<1>();
        if (s > 0 && s <= 8 && lane == 0) mbar_arrive(BAR(empty2, (s - 1) % 6));
      }
      wg_wait<0>();
      PROF(11);
      const uint32_t xbuf = sbase + 8 * SLOT + (tid & 127) * 16;
      if (wgi == 0) {
        uint32_t rbuf, rbar;
        asm volatile("mapa.shared::cluster.u32 %0, %1, %2;" : "=r"(rbuf) : "r"(xbuf), "r"(kh ^ 1));
        asm volatile("mapa.shared::cluster.u32 %0, %1, %2;" : "=r"(rbar) : "r"(BAR(xbar, 0)), "r"(kh ^ 1));
#pragma unroll
        for (int i = 0; i < 16; i++)
          asm volatile("st.async.weak.shared::cluster.mbarrier::complete_tx::bytes.v4.f32 [%0], {%1,%2,%3,%4}, [%5];"
                       ::"r"(rbuf + i * 2048), "f"(acc[4 * i]), "f"(acc[4 * i + 1]), "f"(acc[4 * i + 2]), "f"(acc[4 * i + 3]), "r"(rbar)
                       : "memory");
      } else {
        mbar_wait_cluster(BAR(xbar, 0), 0);
        uint32_t w[2][16];
#pragma unroll
        for (int i = 0; i < 16; i++) {
          const uint4 pv = lds4(xbuf + i * 2048);
          w[0][i] = pack2(acc[4 * i] + __uint_as_float(pv.x), acc[4 * i + 1] + __uint_as_float(pv.y));
          w[1][i] = pack2(acc[4 * i + 2] + __uint_as_float(pv.z), acc[4 * i + 3] + __uint_as_float(pv.w));
        }
        uint4* const o4 = reinterpret_cast<uint4*>(out);
#pragma unroll
        for (int h = 0; h < 2; h++)
#pragma unroll
          for (int q = 0; q < 4; q++) {
            uint32_t a0 = w[h][4 * q], a1 = w[h][4 * q + 1], a2 = w[h][4 * q + 2], a3 = w[h][4 * q + 3];
            {
              const bool od = t & 1;
              uint32_t s0 = od ? a0 : a1, s1 = od ? a2 : a3;
              s0 = __shfl_xor_sync(0xffffffffu, s0, 1); s1 = __shfl_xor_sync(0xffffffffu, s1, 1);
              if (od) { a0 = s0; a2 = s1; } else { a1 = s0; a3 = s1; }
            }
            {
              const bool up = t & 2;
              uint32_t s0 = up ? a0 : a2, s1 = up ? a1 : a3;
              s0 = __shfl_xor_sync(0xffffffffu, s0, 2); s1 = __shfl_xor_sync(0xffffffffu, s1, 2);
              if (up) { a0 = s0; a1 = s1; } else { a2 = s0; a3 = s1; }
            }
            o4[(orow + 128 * (g + 8 * h)) * 64 + nq * 16 + 4 * q + t] =
                make_uint4(hadd2_bf16(hres[h][q].x, a0), hadd2_bf16(hres[h][q].y, a1), hadd2_bf16(hres[h][q].z, a2), hadd2_bf16(hres[h][q].w, a3));
          }
      }
      PROF(12);
    }
  }
#undef BAR
}

typedef CUresult (*EncodeFn)(CUtensorMap*, CUtensorMapDataType, cuuint32_t, void*, const cuuint64_t*, const cuuint64_t*,
                             const cuuint32_t*, const cuuint32_t*, CUtensorMapInterleave, CUtensorMapSwizzle,
                             CUtensorMapL2promotion, CUtensorMapFloatOOBfill);

}

extern "C" void kernel_launch(void* const* d_in, const int* in_sizes, int n_in, void* d_out, int out_size) {
  (void)in_sizes; (void)n_in; (void)out_size;
  static EncodeFn encode = nullptr;
  if (!encode) {
    void* fn = nullptr;
    cudaDriverEntryPointQueryResult qr;
    cudaGetDriverEntryPoint("cuTensorMapEncodeTiled", &fn, cudaEnableDefault, &qr);
    encode = (EncodeFn)fn;
    cudaFuncSetAttribute(fused_kernel, cudaFuncAttributeMaxDynamicSharedMemorySize, SMEM_BYTES);
  }
  CUtensorMap tmGX, tmUX, tmGY, tmUY, tmD;
  const cuuint32_t es[5] = {1, 1, 1, 1, 1};
  {
    const cuuint64_t gd[3] = {64, 512, 28}, gs[2] = {3584, 128};
    const cuuint32_t bd[3] = {64, 32, 2};
    encode(&tmGX, CU_TENSOR_MAP_DATA_TYPE_BFLOAT16, 3, d_in[4], gd, gs, bd, es, CU_TENSOR_MAP_INTERLEAVE_NONE,
           CU_TENSOR_MAP_SWIZZLE_128B, CU_TENSOR_MAP_L2_PROMOTION_L2_256B, CU_TENSOR_MAP_FLOAT_OOB_FILL_NONE);
    encode(&tmUX, CU_TENSOR_MAP_DATA_TYPE_BFLOAT16, 3, d_in[5], gd, gs, bd, es, CU_TENSOR_MAP_INTERLEAVE_NONE,
           CU_TENSOR_MAP_SWIZZLE_128B, CU_TENSOR_MAP_L2_PROMOTION_L2_256B, CU_TENSOR_MAP_FLOAT_OOB_FILL_NONE);
  }
  {
    const cuuint64_t gd[3] = {32, 512, 56}, gs[2] = {3584, 64};
    const cuuint32_t bd[3] = {32, 32, 3};
    encode(&tmGY, CU_TENSOR_MAP_DATA_TYPE_BFLOAT16, 3, d_in[4], gd, gs, bd, es, CU_TENSOR_MAP_INTERLEAVE_NONE,
           CU_TENSOR_MAP_SWIZZLE_64B, CU_TENSOR_MAP_L2_PROMOTION_L2_128B, CU_TENSOR_MAP_FLOAT_OOB_FILL_NONE);
    encode(&tmUY, CU_TENSOR_MAP_DATA_TYPE_BFLOAT16, 3, d_in[5], gd, gs, bd, es, CU_TENSOR_MAP_INTERLEAVE_NONE,
           CU_TENSOR_MAP_SWIZZLE_64B, CU_TENSOR_MAP_L2_PROMOTION_L2_128B, CU_TENSOR_MAP_FLOAT_OOB_FILL_NONE);
  }
  {
    const cuuint64_t gd[5] = {512, 2, 4, 4, 56}, gs[4] = {1024, 8192, 2048, 32768};
    const cuuint32_t bd[5] = {64, 2, 4, 4, 2};
    encode(&tmD, CU_TENSOR_MAP_DATA_TYPE_BFLOAT16, 5, d_in[6], gd, gs, bd, es, CU_TENSOR_MAP_INTERLEAVE_NONE,
           CU_TENSOR_MAP_SWIZZLE_128B, CU_TENSOR_MAP_L2_PROMOTION_L2_256B, CU_TENSOR_MAP_FLOAT_OOB_FILL_NONE);
  }
  fused_kernel<<<NCTA, NTHREADS, SMEM_BYTES>>>(
      tmGX, tmUX, tmGY, tmUY, tmD, (const __nv_bfloat16*)d_in[0], (const __nv_bfloat16*)d_in[1], (const __nv_bfloat16*)d_in[2],
      (const char*)d_in[4], (const char*)d_in[5], (const char*)d_in[6], (__nv_bfloat16*)d_out);
}
```

```cpp
#include <cuda_runtime.h>
#include <cuda_bf16.h>
#include <cuda.h>
#include <stdint.h>

namespace {

constexpr int NCTA = 128;
constexpr int NTHREADS = 384;
constexpr int SLOT = 16384;
constexpr int SMEM_BYTES = 14 * SLOT + 1024 + 1024;
constexpr int SPIN_LIMIT = 1 << 22;

__device__ uint4 g_Z1[128 * 1024];
__device__ uint4 g_Z2[128 * 1024];
__device__ uint4 g_LN[16 * 8 * 1024];
__device__ uint4 g_H[2048 * 64];
__device__ uint4 g_P[16 * 28 * 1024];
__device__ unsigned g_cnt[64 * 32];
#define PROF(i)
#define PROFP(i)
#define PROFG(i)

constexpr double ccos(int i, int n) {
  i &= n - 1;
  if (i > n / 2) i = n - i;
  if (4 * i == n) return 0.0;
  const bool neg = 4 * i > n;
  if (neg) i = n / 2 - i;
  const double a = 6.283185307179586476925 * i / n, a2 = a * a;
  double term = 1.0, sum = 1.0;
  for (int k = 1; k < 14; k++) { term *= -a2 / ((2 * k - 1) * (2 * k)); sum += term; }
  return neg ? -sum : sum;
}
constexpr double csin(int i, int n) { return ccos(i - n / 4, n); }
constexpr unsigned fbits(double v, int mant) {
  if (v == 0.0) return 0;
  const unsigned sg = v < 0 ? 1u : 0u;
  if (v < 0) v = -v;
  int e = 127;
  while (v < 1.0) { v *= 2.0; e--; }
  const unsigned m = (unsigned)((v - 1.0) * (double)(1u << mant) + 0.5);
  return (sg << (8 + mant)) + ((unsigned)e << mant) + m;
}
constexpr unsigned pkb(double lo, double hi) { return fbits(lo, 7) | (fbits(hi, 7) << 16); }
constexpr double fa_elem(int kp, int n1) {
  return kp <= 8 ? ccos(kp * n1, 16) : -csin((kp - 8) * n1, 16);
}
constexpr unsigned cfrag_c(int idx, int n, int ri) {
  return ri ? pkb(-csin(idx, n), ccos(idx, n)) : pkb(ccos(idx, n), csin(idx, n));
}
struct Tables {
  unsigned fb[16][32][4];
  unsigned tw1[4][32][4];
  unsigned fa[32][4];
  unsigned pad[32][4];
  unsigned pad2[2][32][4];
  unsigned f2[8][4][32][4];
  unsigned g2[8][4][32][4];
  unsigned gb[16][32][4];
  unsigned tw3[4][32][4];
  unsigned ga[32][4];
  unsigned f8[32][4], g8[32][4];
  unsigned pad3[32][4];
};
constexpr int T1_BYTES = 12288, T2_BYTES = 45056;
static_assert(sizeof(Tables) == T1_BYTES + T2_BYTES, "table size");
constexpr Tables make_tables() {
  Tables T = {};
  for (int l = 0; l < 32; l++) {
    const int g = l >> 2, t = l & 3;
    for (int i = 0; i < 4; i++)
      for (int u = 0; u < 8; u++) {
        const int ri = g & 1, m = 2 * (g >> 1) + ((u & 3) >> 1);
        const double sg = u >= 4 ? -1.0 : 1.0;
        const int k2 = u >= 4 ? 31 - 2 * m - (u & 1) : 2 * m + (u & 1);
        const int pa = (8 * t + i) * k2, pb = (8 * t + 4 + i) * k2;
        T.fb[i * 4 + (u >> 1)][l][(u & 1) * 2 + 0] = ri == 0 ? pkb(ccos(pa, 32), ccos(pb, 32)) : pkb(-sg * csin(pa, 32), -sg * csin(pb, 32));
        T.fb[i * 4 + (u >> 1)][l][(u & 1) * 2 + 1] = ri == 0 ? pkb(csin(pa, 32), csin(pb, 32)) : pkb(sg * ccos(pa, 32), sg * ccos(pb, 32));
      }
    for (int i = 0; i < 4; i++)
      for (int ks = 0; ks < 4; ks++) {
        const int n2 = 4 * g + i, m = 2 * t + (ks & 1);
        const double sg = ks >= 2 ? -1.0 : 1.0;
        const int pa = n2 * (ks >= 2 ? 31 - 2 * m : 2 * m), pb = n2 * (ks >= 2 ? 30 - 2 * m : 2 * m + 1);
        T.gb[i * 4 + ks][l][0] = pkb(ccos(pa, 32), -sg * csin(pa, 32));
        T.gb[i * 4 + ks][l][1] = pkb(csin(pa, 32), sg * ccos(pa, 32));
        T.gb[i * 4 + ks][l][2] = pkb(ccos(pb, 32), -sg * csin(pb, 32));
        T.gb[i * 4 + ks][l][3] = pkb(csin(pb, 32), sg * ccos(pb, 32));
      }
    for (int i = 0; i < 4; i++) {
      const int k1 = g == 0 ? 8 : g;
      T.tw1[i][l][0] = fbits(ccos((8 * t + i) * k1, 512), 23);
      T.tw1[i][l][1] = fbits(csin((8 * t + i) * k1, 512), 23);
      T.tw1[i][l][2] = fbits(ccos((8 * t + 4 + i) * k1, 512), 23);
      T.tw1[i][l][3] = fbits(csin((8 * t + 4 + i) * k1, 512), 23);
      const int ka = t == 0 ? 8 : 2 * t, kb = 2 * t + 1;
      T.tw3[i][l][0] = fbits(ccos((4 * g + i) * ka, 512), 23);
      T.tw3[i][l][1] = fbits(csin((4 * g + i) * ka, 512), 23);
      T.tw3[i][l][2] = fbits(ccos((4 * g + i) * kb, 512), 23);
      T.tw3[i][l][3] = fbits(csin((4 * g + i) * kb, 512), 23);
      const int p8 = (t + 4 * (i & 1)) * (4 * (i >> 1) + (g >> 1));
      T.f8[l][i] = cfrag_c(p8, 8, g & 1);
      T.g8[l][i] = cfrag_c(-p8, 8, g & 1);
    }
    for (int w = 0; w < 8; w++)
      for (int i = 0; i < 16; i++) {
        const int kidx = t + 4 * (i & 1) + 8 * (i >> 3), nidx = 4 * ((i >> 1) & 3) + (g >> 1);
        T.f2[w][i >> 2][l][i & 3] = cfrag_c((8 * kidx + w) * nidx, 128, g & 1);
        T.g2[w][i >> 2][l][i & 3] = cfrag_c(-(8 * nidx + w) * kidx, 128, g & 1);
      }
    T.fa[l][0] = pkb(fa_elem(g, 2 * t), fa_elem(g, 2 * t + 1));
    T.fa[l][1] = pkb(fa_elem(g + 8, 2 * t), fa_elem(g + 8, 2 * t + 1));
    T.fa[l][2] = pkb(fa_elem(g, 2 * t + 8), fa_elem(g, 2 * t + 9));
    T.fa[l][3] = pkb(fa_elem(g + 8, 2 * t + 8), fa_elem(g + 8, 2 * t + 9));
    T.ga[l][0] = pkb(fa_elem(2 * t, g), fa_elem(2 * t + 1, g));
    T.ga[l][1] = pkb(fa_elem(2 * t, g + 8), fa_elem(2 * t + 1, g + 8));
    T.ga[l][2] = pkb(fa_elem(2 * t + 8, g), fa_elem(2 * t + 9, g));
    T.ga[l][3] = pkb(fa_elem(2 * t + 8, g + 8), fa_elem(2 * t + 9, g + 8));
  }
  return T;
}
__device__ const __align__(128) Tables g_tab = make_tables();

__device__ __forceinline__ uint32_t s2u(const void* p) { return (uint32_t)__cvta_generic_to_shared(p); }
__device__ __forceinline__ void mbar_init(uint32_t b, int c) { asm volatile("mbarrier.init.shared::cta.b64 [%0], %1;" ::"r"(b), "r"(c)); }
__device__ __forceinline__ void mbar_expect(uint32_t b, int bytes) {
  asm volatile("mbarrier.arrive.expect_tx.shared::cta.b64 _, [%0], %1;" ::"r"(b), "r"(bytes) : "memory");
}
__device__ __forceinline__ void mbar_arrive(uint32_t b) { asm volatile("mbarrier.arrive.shared::cta.b64 _, [%0];" ::"r"(b) : "memory"); }
__device__ __forceinline__ uint32_t mbar_try(uint32_t b, uint32_t parity) {
  uint32_t ok;
  asm volatile("{.reg .pred p; mbarrier.try_wait.parity.shared::cta.b64 p, [%1], %2; selp.u32 %0,1,0,p;}"
               : "=r"(ok) : "r"(b), "r"(parity) : "memory");
  return ok;
}
__device__ __forceinline__ void mbar_wait(uint32_t b, uint32_t parity) {
  int it = 0;
  while (!mbar_try(b, parity))
    if (++it > SPIN_LIMIT) __trap();
}
__device__ __forceinline__ void mbar_wait_cluster(uint32_t b, int parity) {
  uint32_t ok;
  int it = 0;
  do {
    asm volatile("{.reg .pred p; mbarrier.try_wait.parity.acquire.cluster.shared::cta.b64 p, [%1], %2; selp.u32 %0,1,0,p;}"
                 : "=r"(ok) : "r"(b), "r"(parity) : "memory");
    if (++it > SPIN_LIMIT) __trap();
  } while (!ok);
}
__device__ __forceinline__ void bar_sync(int id, int n) { asm volatile("bar.sync %0, %1;" ::"r"(id), "r"(n) : "memory"); }
__device__ __forceinline__ void bar_arrive(int id, int n) { asm volatile("bar.arrive %0, %1;" ::"r"(id), "r"(n) : "memory"); }
__device__ __forceinline__ void red_release(unsigned* p) { asm volatile("red.release.gpu.global.add.u32 [%0], 1;" ::"l"(p) : "memory"); }
__device__ __forceinline__ unsigned ld_acquire(const unsigned* p) {
  unsigned v;
  asm volatile("ld.acquire.gpu.global.u32 %0, [%1];" : "=r"(v) : "l"(p) : "memory");
  return v;
}
__device__ __forceinline__ unsigned ld_relaxed(const unsigned* p) {
  unsigned v;
  asm volatile("ld.relaxed.gpu.global.u32 %0, [%1];" : "=r"(v) : "l"(p) : "memory");
  return v;
}
__device__ __forceinline__ void wait_counter(const unsigned* p, unsigned target) {
  int it = 0;
  while ((int)(ld_acquire(p) - target) < 0)
    if (++it > SPIN_LIMIT) __trap();
}
__device__ __forceinline__ uint4 ldg_cg4(const uint4* p) {
  uint4 v;
  asm volatile("ld.global.cg.v4.u32 {%0,%1,%2,%3}, [%4];" : "=r"(v.x), "=r"(v.y), "=r"(v.z), "=r"(v.w) : "l"(p) : "memory");
  return v;
}
__device__ __forceinline__ void sts4(uint32_t a, uint32_t x, uint32_t y, uint32_t z, uint32_t w) {
  asm volatile("st.shared.v4.u32 [%0], {%1,%2,%3,%4};" ::"r"(a), "r"(x), "r"(y), "r"(z), "r"(w) : "memory");
}
__device__ __forceinline__ uint4 lds4(uint32_t a) {
  uint4 v;
  asm volatile("ld.shared.v4.u32 {%0,%1,%2,%3}, [%4];" : "=r"(v.x), "=r"(v.y), "=r"(v.z), "=r"(v.w) : "r"(a) : "memory");
  return v;
}
__device__ __forceinline__ uint32_t pack2(float lo, float hi) {
  uint32_t r;
  asm("cvt.rn.bf16x2.f32 %0, %1, %2;" : "=r"(r) : "f"(hi), "f"(lo));
  return r;
}
__device__ __forceinline__ float bf_lo(uint32_t v) { return __uint_as_float(v << 16); }
__device__ __forceinline__ float bf_hi(uint32_t v) { return __uint_as_float(v & 0xffff0000u); }
__device__ __forceinline__ uint32_t hadd2_bf16(uint32_t a, uint32_t b) {
  uint32_t r;
  asm("add.rn.bf16x2 %0, %1, %2;" : "=r"(r) : "r"(a), "r"(b));
  return r;
}
__device__ __forceinline__ void mma16816(float (&d)[4], uint32_t a0, uint32_t a1, uint32_t a2, uint32_t a3, uint32_t b0, uint32_t b1) {
  asm("mma.sync.aligned.m16n8k16.row.col.f32.bf16.bf16.f32 {%0,%1,%2,%3}, {%4,%5,%6,%7}, {%8,%9}, {%0,%1,%2,%3};"
      : "+f"(d[0]), "+f"(d[1]), "+f"(d[2]), "+f"(d[3])
      : "r"(a0), "r"(a1), "r"(a2), "r"(a3), "r"(b0), "r"(b1));
}
template <int N>
__device__ __forceinline__ void cs_frac(int idx, float& c, float& s) {
  int i = ((idx + N / 2) & (N - 1)) - N / 2;
  float a = (float)i * (6.283185307179586f / N);
  c = __cosf(a);
  s = __sinf(a);
}
template <int N>
__device__ __forceinline__ uint32_t cfrag(int idx, int ri) {
  float c, s;
  cs_frac<N>(idx, c, s);
  return ri ? pack2(-s, c) : pack2(c, s);
}
__device__ __forceinline__ uint32_t word(const uint4& v, int e) { return e == 0 ? v.x : e == 1 ? v.y : e == 2 ? v.z : v.w; }
__device__ __forceinline__ void cdft16(const uint4 (&q)[4], const uint4 (&F)[4], uint4 (&o)[4]) {
  float acc[2][4][4];
#pragma unroll
  for (int p = 0; p < 2; p++)
#pragma unroll
    for (int v = 0; v < 4; v++) {
      acc[p][v][0] = acc[p][v][1] = acc[p][v][2] = acc[p][v][3] = 0.f;
#pragma unroll
      for (int ks = 0; ks < 2; ks++)
        mma16816(acc[p][v], word(q[2 * ks], 2 * p), word(q[2 * ks], 2 * p + 1), word(q[2 * ks + 1], 2 * p),
                 word(q[2 * ks + 1], 2 * p + 1), word(F[ks * 2 + (v >> 1)], (v & 1) * 2), word(F[ks * 2 + (v >> 1)], (v & 1) * 2 + 1));
    }
#pragma unroll
  for (int v = 0; v < 4; v++)
    o[v] = make_uint4(pack2(acc[0][v][0], acc[0][v][1]), pack2(acc[0][v][2], acc[0][v][3]),
                      pack2(acc[1][v][0], acc[1][v][1]), pack2(acc[1][v][2], acc[1][v][3]));
}
__device__ __forceinline__ float warp_sum(float v) {
#pragma unroll
  for (int o = 16; o > 0; o >>= 1) v += __shfl_xor_sync(0xffffffffu, v, o);
  return v;
}
__device__ __forceinline__ uint64_t desc64(uint32_t lo, uint32_t hi) {
  uint64_t d;
  asm("mov.b64 %0, {%1, %2};" : "=l"(d) : "r"(lo), "r"(hi));
  return d;
}
constexpr uint32_t desc_hi(uint32_t sbo, uint32_t swz) { return (sbo >> 4) | (swz << 30); }
__device__ __forceinline__ uint32_t desc_lo(uint32_t addr, uint32_t lbo) { return ((addr & 0x3FFFF) >> 4) | ((lbo >> 4) << 16); }
__device__ __forceinline__ void cp_async16(uint32_t dst, const void* src) {
  asm volatile("cp.async.cg.shared.global [%0], [%1], 16;" ::"r"(dst), "l"(src) : "memory");
}
__device__ __forceinline__ uint2 lds2(uint32_t a) {
  uint2 v;
  asm volatile("ld.shared.v2.u32 {%0,%1}, [%2];" : "=r"(v.x), "=r"(v.y) : "r"(a) : "memory");
  return v;
}
__device__ __forceinline__ uint32_t lds_u16(uint32_t a) {
  uint16_t v;
  asm volatile("ld.shared.u16 %0, [%1];" : "=h"(v) : "r"(a) : "memory");
  return v;
}
__device__ __forceinline__ void wg_fence() { asm volatile("wgmma.fence.sync.aligned;" ::: "memory"); }
__device__ __forceinline__ void wg_commit() { asm volatile("wgmma.commit_group.sync.aligned;" ::: "memory"); }
template <int N>
__device__ __forceinline__ void wg_wait() { asm volatile("wgmma.wait_group.sync.aligned %0;" ::"n"(N) : "memory"); }
__device__ __forceinline__ void bulk_load(uint32_t dst, const void* src, int bytes, uint32_t bar) {
  asm volatile("cp.async.bulk.shared::cluster.global.mbarrier::complete_tx::bytes [%0], [%1], %2, [%3];"
               ::"r"(dst), "l"(src), "r"(bytes), "r"(bar) : "memory");
}
__device__ __forceinline__ void tma3(uint32_t dst, const CUtensorMap* tm, uint32_t bar, int c0, int c1, int c2) {
  asm volatile("cp.async.bulk.tensor.3d.shared::cluster.global.mbarrier::complete_tx::bytes [%0], [%1, {%3,%4,%5}], [%2];"
               ::"r"(dst), "l"(tm), "r"(bar), "r"(c0), "r"(c1), "r"(c2) : "memory");
}
__device__ __forceinline__ void tma5(uint32_t dst, const CUtensorMap* tm, uint32_t bar, int c0, int c4) {
  asm volatile("cp.async.bulk.tensor.5d.shared::cluster.global.mbarrier::complete_tx::bytes [%0], [%1, {%3,%4,%4,%4,%5}], [%2];"
               ::"r"(dst), "l"(tm), "r"(bar), "r"(c0), "r"(0), "r"(c4) : "memory");
}
__device__ __forceinline__ float swiglu(float g, float u) {
  float hg = 0.5f * g, th;
  asm("tanh.approx.f32 %0, %1;" : "=f"(th) : "f"(hg));
  return fmaf(hg, th, hg) * u;
}

__device__ __forceinline__ void wgmma_n256(float (&d)[128], uint64_t da, uint64_t db) {
  asm volatile("wgmma.mma_async.sync.aligned.m64n256k16.f32.bf16.bf16 {"
      "%0,%1,%2,%3,%4,%5,%6,%7,%8,%9,%10,%11,%12,%13,%14,%15,"
      "%16,%17,%18,%19,%20,%21,%22,%23,%24,%25,%26,%27,%28,%29,%30,%31,"
      "%32,%33,%34,%35,%36,%37,%38,%39,%40,%41,%42,%43,%44,%45,%46,%47,"
      "%48,%49,%50,%51,%52,%53,%54,%55,%56,%57,%58,%59,%60,%61,%62,%63,"
      "%64,%65,%66,%67,%68,%69,%70,%71,%72,%73,%74,%75,%76,%77,%78,%79,"
      "%80,%81,%82,%83,%84,%85,%86,%87,%88,%89,%90,%91,%92,%93,%94,%95,"
      "%96,%97,%98,%99,%100,%101,%102,%103,%104,%105,%106,%107,%108,%109,%110,%111,"
      "%112,%113,%114,%115,%116,%117,%118,%119,%120,%121,%122,%123,%124,%125,%126,%127"
      "}, %128, %129, 1, 1, 1, 0, 1;\n"
      : "+f"(d[0]),"+f"(d[1]),"+f"(d[2]),"+f"(d[3]),"+f"(d[4]),"+f"(d[5]),"+f"(d[6]),"+f"(d[7]),
        "+f"(d[8]),"+f"(d[9]),"+f"(d[10]),"+f"(d[11]),"+f"(d[12]),"+f"(d[13]),"+f"(d[14]),"+f"(d[15]),
        "+f"(d[16]),"+f"(d[17]),"+f"(d[18]),"+f"(d[19]),"+f"(d[20]),"+f"(d[21]),"+f"(d[22]),"+f"(d[23]),
        "+f"(d[24]),"+f"(d[25]),"+f"(d[26]),"+f"(d[27]),"+f"(d[28]),"+f"(d[29]),"+f"(d[30]),"+f"(d[31]),
        "+f"(d[32]),"+f"(d[33]),"+f"(d[34]),"+f"(d[35]),"+f"(d[36]),"+f"(d[37]),"+f"(d[38]),"+f"(d[39]),
        "+f"(d[40]),"+f"(d[41]),"+f"(d[42]),"+f"(d[43]),"+f"(d[44]),"+f"(d[45]),"+f"(d[46]),"+f"(d[47]),
        "+f"(d[48]),"+f"(d[49]),"+f"(d[50]),"+f"(d[51]),"+f"(d[52]),"+f"(d[53]),"+f"(d[54]),"+f"(d[55]),
        "+f"(d[56]),"+f"(d[57]),"+f"(d[58]),"+f"(d[59]),"+f"(d[60]),"+f"(d[61]),"+f"(d[62]),"+f"(d[63]),
        "+f"(d[64]),"+f"(d[65]),"+f"(d[66]),"+f"(d[67]),"+f"(d[68]),"+f"(d[69]),"+f"(d[70]),"+f"(d[71]),
        "+f"(d[72]),"+f"(d[73]),"+f"(d[74]),"+f"(d[75]),"+f"(d[76]),"+f"(d[77]),"+f"(d[78]),"+f"(d[79]),
        "+f"(d[80]),"+f"(d[81]),"+f"(d[82]),"+f"(d[83]),"+f"(d[84]),"+f"(d[85]),"+f"(d[86]),"+f"(d[87]),
        "+f"(d[88]),"+f"(d[89]),"+f"(d[90]),"+f"(d[91]),"+f"(d[92]),"+f"(d[93]),"+f"(d[94]),"+f"(d[95]),
        "+f"(d[96]),"+f"(d[97]),"+f"(d[98]),"+f"(d[99]),"+f"(d[100]),"+f"(d[101]),"+f"(d[102]),"+f"(d[103]),
        "+f"(d[104]),"+f"(d[105]),"+f"(d[106]),"+f"(d[107]),"+f"(d[108]),"+f"(d[109]),"+f"(d[110]),"+f"(d[111]),
        "+f"(d[112]),"+f"(d[113]),"+f"(d[114]),"+f"(d[115]),"+f"(d[116]),"+f"(d[117]),"+f"(d[118]),"+f"(d[119]),
        "+f"(d[120]),"+f"(d[121]),"+f"(d[122]),"+f"(d[123]),"+f"(d[124]),"+f"(d[125]),"+f"(d[126]),"+f"(d[127])
      : "l"(da), "l"(db));
}
__device__ __forceinline__ void wgmma_n192(float (&d)[96], uint64_t da, uint64_t db) {
  asm volatile("wgmma.mma_async.sync.aligned.m64n192k16.f32.bf16.bf16 {"
      "%0,%1,%2,%3,%4,%5,%6,%7,%8,%9,%10,%11,%12,%13,%14,%15,"
      "%16,%17,%18,%19,%20,%21,%22,%23,%24,%25,%26,%27,%28,%29,%30,%31,"
      "%32,%33,%34,%35,%36,%37,%38,%39,%40,%41,%42,%43,%44,%45,%46,%47,"
      "%48,%49,%50,%51,%52,%53,%54,%55,%56,%57,%58,%59,%60,%61,%62,%63,"
      "%64,%65,%66,%67,%68,%69,%70,%71,%72,%73,%74,%75,%76,%77,%78,%79,"
      "%80,%81,%82,%83,%84,%85,%86,%87,%88,%89,%90,%91,%92,%93,%94,%95"
      "}, %96, %97, 1, 1, 1, 0, 1;\n"
      : "+f"(d[0]),"+f"(d[1]),"+f"(d[2]),"+f"(d[3]),"+f"(d[4]),"+f"(d[5]),"+f"(d[6]),"+f"(d[7]),
        "+f"(d[8]),"+f"(d[9]),"+f"(d[10]),"+f"(d[11]),"+f"(d[12]),"+f"(d[13]),"+f"(d[14]),"+f"(d[15]),
        "+f"(d[16]),"+f"(d[17]),"+f"(d[18]),"+f"(d[19]),"+f"(d[20]),"+f"(d[21]),"+f"(d[22]),"+f"(d[23]),
        "+f"(d[24]),"+f"(d[25]),"+f"(d[26]),"+f"(d[27]),"+f"(d[28]),"+f"(d[29]),"+f"(d[30]),"+f"(d[31]),
        "+f"(d[32]),"+f"(d[33]),"+f"(d[34]),"+f"(d[35]),"+f"(d[36]),"+f"(d[37]),"+f"(d[38]),"+f"(d[39]),
        "+f"(d[40]),"+f"(d[41]),"+f"(d[42]),"+f"(d[43]),"+f"(d[44]),"+f"(d[45]),"+f"(d[46]),"+f"(d[47]),
        "+f"(d[48]),"+f"(d[49]),"+f"(d[50]),"+f"(d[51]),"+f"(d[52]),"+f"(d[53]),"+f"(d[54]),"+f"(d[55]),
        "+f"(d[56]),"+f"(d[57]),"+f"(d[58]),"+f"(d[59]),"+f"(d[60]),"+f"(d[61]),"+f"(d[62]),"+f"(d[63]),
        "+f"(d[64]),"+f"(d[65]),"+f"(d[66]),"+f"(d[67]),"+f"(d[68]),"+f"(d[69]),"+f"(d[70]),"+f"(d[71]),
        "+f"(d[72]),"+f"(d[73]),"+f"(d[74]),"+f"(d[75]),"+f"(d[76]),"+f"(d[77]),"+f"(d[78]),"+f"(d[79]),
        "+f"(d[80]),"+f"(d[81]),"+f"(d[82]),"+f"(d[83]),"+f"(d[84]),"+f"(d[85]),"+f"(d[86]),"+f"(d[87]),
        "+f"(d[88]),"+f"(d[89]),"+f"(d[90]),"+f"(d[91]),"+f"(d[92]),"+f"(d[93]),"+f"(d[94]),"+f"(d[95])
      : "l"(da), "l"(db));
}
__device__ __forceinline__ void wgmma_n128(float (&d)[64], uint64_t da, uint64_t db) {
  asm volatile("wgmma.mma_async.sync.aligned.m64n128k16.f32.bf16.bf16 {"
      "%0,%1,%2,%3,%4,%5,%6,%7,%8,%9,%10,%11,%12,%13,%14,%15,"
      "%16,%17,%18,%19,%20,%21,%22,%23,%24,%25,%26,%27,%28,%29,%30,%31,"
      "%32,%33,%34,%35,%36,%37,%38,%39,%40,%41,%42,%43,%44,%45,%46,%47,"
      "%48,%49,%50,%51,%52,%53,%54,%55,%56,%57,%58,%59,%60,%61,%62,%63"
      "}, %64, %65, 1, 1, 1, 0, 1;\n"
      : "+f"(d[0]),"+f"(d[1]),"+f"(d[2]),"+f"(d[3]),"+f"(d[4]),"+f"(d[5]),"+f"(d[6]),"+f"(d[7]),
        "+f"(d[8]),"+f"(d[9]),"+f"(d[10]),"+f"(d[11]),"+f"(d[12]),"+f"(d[13]),"+f"(d[14]),"+f"(d[15]),
        "+f"(d[16]),"+f"(d[17]),"+f"(d[18]),"+f"(d[19]),"+f"(d[20]),"+f"(d[21]),"+f"(d[22]),"+f"(d[23]),
        "+f"(d[24]),"+f"(d[25]),"+f"(d[26]),"+f"(d[27]),"+f"(d[28]),"+f"(d[29]),"+f"(d[30]),"+f"(d[31]),
        "+f"(d[32]),"+f"(d[33]),"+f"(d[34]),"+f"(d[35]),"+f"(d[36]),"+f"(d[37]),"+f"(d[38]),"+f"(d[39]),
        "+f"(d[40]),"+f"(d[41]),"+f"(d[42]),"+f"(d[43]),"+f"(d[44]),"+f"(d[45]),"+f"(d[46]),"+f"(d[47]),
        "+f"(d[48]),"+f"(d[49]),"+f"(d[50]),"+f"(d[51]),"+f"(d[52]),"+f"(d[53]),"+f"(d[54]),"+f"(d[55]),
        "+f"(d[56]),"+f"(d[57]),"+f"(d[58]),"+f"(d[59]),"+f"(d[60]),"+f"(d[61]),"+f"(d[62]),"+f"(d[63])
      : "l"(da), "l"(db));
}

constexpr int C_BAR1 = 0, C_BAR2 = 1, C_LN = 2, C_PX = 18, C_PY = 34;
constexpr int NB_CONS = 1, NB_LN = 2, NB_PUB0 = 3, NB_LAG = 5, NB_INIT = 6, NB_PROD = 7;
#define LAG 2
constexpr int SM_E = 0, SM_E2 = 16384, SM_X = 32768, SM_W = 49152, SM_FC = 69632, SM_T = 73728;

constexpr uint32_t HI128 = desc_hi(1024, 1), HI64 = desc_hi(512, 2), HI0 = desc_hi(1024, 0);

struct Bars {
  uint64_t full1[6], empty1[6], fullA[8], full2[6], empty2[6], xbar, tbar;
};

template <int NT>
__device__ __forceinline__ void store_p(const float (&acc)[NT * 32], uint4* pbase, int G0, int lane_off) {
#pragma unroll
  for (int q = 0; q < NT; q++) {
    const int G = G0 + q;
    uint4* dst = pbase + (G >> 1) * 1024 + (G & 1) * 32 + lane_off;
#pragma unroll
    for (int h = 0; h < 2; h++) {
      uint32_t w[4];
#pragma unroll
      for (int i = 0; i < 4; i++) {
        const int a = (q * 4 + i) * 4 + 2 * h, b = a + NT * 16;
        w[i] = pack2(swiglu(acc[a], acc[b]), swiglu(acc[a + 1], acc[b + 1]));
      }
      dst[h * 64] = make_uint4(w[0], w[1], w[2], w[3]);
    }
  }
}

__global__ void __cluster_dims__(2, 1, 1) __launch_bounds__(NTHREADS, 1)
fused_kernel(const __grid_constant__ CUtensorMap tmGX, const __grid_constant__ CUtensorMap tmUX,
             const __grid_constant__ CUtensorMap tmGY, const __grid_constant__ CUtensorMap tmUY,
             const __grid_constant__ CUtensorMap tmD,
             const __nv_bfloat16* __restrict__ x, const __nv_bfloat16* __restrict__ wr, const __nv_bfloat16* __restrict__ wi,
             const char* __restrict__ wg_raw, const char* __restrict__ wu_raw, const char* __restrict__ wd_raw,
             __nv_bfloat16* __restrict__ out) {
  extern __shared__ __align__(1024) char smem_raw[];
  const uint32_t sbase = (s2u(smem_raw) + 1023) & ~1023u;
  const uint32_t sbar = sbase + 14 * SLOT;
  const int tid = threadIdx.x, lane = tid & 31;
  const int warp = __shfl_sync(0xffffffffu, tid >> 5, 0);
  const int c = blockIdx.x, rb = c >> 3, f = c & 7;
#define BAR(field, i) (sbar + (uint32_t)offsetof(Bars, field) + 8u * (i))
#define TOFF(field) (sbase + SM_T + (uint32_t)offsetof(Tables, field) + lane * 16)

  if (warp >= 8) {
    asm volatile("setmaxnreg.dec.sync.aligned.u32 40;");
    if (tid == 256) {
      for (int i = 0; i < 6; i++) {
        mbar_init(BAR(full1, i), 1); mbar_init(BAR(empty1, i), 8);
        mbar_init(BAR(full2, i), 1); mbar_init(BAR(empty2, i), 8);
      }
      for (int i = 0; i < 8; i++) mbar_init(BAR(fullA, i), 1);
      mbar_init(BAR(xbar, 0), 1);
      mbar_init(BAR(tbar, 0), 1);
      mbar_expect(BAR(xbar, 0), 32768);
      asm volatile("fence.mbarrier_init.release.cluster;" ::: "memory");
    }
    __syncwarp();
    bar_sync(NB_PROD, 128);
    bar_arrive(NB_INIT, 384);
    asm volatile("barrier.cluster.arrive.relaxed.aligned;" ::: "memory");
    if (warp <= 9) {
      if (lane == 0) {
        const int ax = (7 * f + 3 * (f & 1)) >> 1;
        const int ay = 7 * f + ((f & 1) ? 0 : 4);
        uint32_t s = warp - 8, ph = 1;
#pragma unroll 1
        for (int n = warp - 8; n < 32; n += 2) {
          const uint32_t dst = sbase + (8 + s) * SLOT, fb = BAR(full1, s);
          mbar_wait(BAR(empty1, s), ph);
          if (n < 16) {
            mbar_expect(fb, 16384);
            tma3(dst, &tmGX, fb, 0, n * 32, ax);
            tma3(dst + 8192, &tmUX, fb, 0, n * 32, ax);
          } else {
            mbar_expect(fb, 12288);
            tma3(dst, &tmGY, fb, 0, (n - 16) * 32, ay);
            tma3(dst + 6144, &tmUY, fb, 0, (n - 16) * 32, ay);
          }
          s += 2;
          if (s >= 6) { s -= 6; ph ^= 1; }
        }
      }
    } else if (warp == 10) {
      unsigned epoch = 0;
      if (lane == 0) {
        mbar_expect(BAR(tbar, 0), T2_BYTES);
        bulk_load(sbase + SM_T + T1_BYTES, reinterpret_cast<const char*>(&g_tab) + T1_BYTES, T2_BYTES, BAR(tbar, 0));
        epoch = ld_relaxed(&g_cnt[(C_LN + rb) * 32]) >> 3;
      }
      bar_sync(NB_LN, 288);
      if (lane == 0) {
        PROFP(0);
        red_release(&g_cnt[(C_LN + rb) * 32]);
        PROFP(1);
        wait_counter(&g_cnt[(C_LN + rb) * 32], (epoch + 1) * 8);
        asm volatile("fence.proxy.async.global;" ::: "memory");
        PROFP(2);
#pragma unroll 1
        for (int kb = 0; kb < 8; kb++) {
          mbar_expect(BAR(fullA, kb), 16384);
          bulk_load(sbase + kb * SLOT, &g_LN[(rb * 8 + kb) * 1024], 16384, BAR(fullA, kb));
        }
        const int nq = f >> 1, kh = f & 1;
        uint32_t d = 0, ph = 0;
#pragma unroll 1
        for (int s = 0; s < 14; s++) {
          const int dslot = (0x365210 >> (4 * d)) & 15;
          const int kblk = 14 * kh + (int)((0xBA9432DC876510ull >> (4 * s)) & 15);
          const uint32_t dst = sbase + dslot * 2 * SLOT, fb = BAR(full2, d);
          mbar_wait(BAR(empty2, d), ph);
          mbar_expect(fb, 32768);
          tma5(dst + SLOT, &tmD, fb, nq * 128, 2 * kblk);
          tma5(dst + SLOT + 8192, &tmD, fb, nq * 128 + 64, 2 * kblk);
          if (s == 0 || s == 8) {
            PROFP(3 + (s >> 2));
            wait_counter(&g_cnt[((s == 0 ? C_PX : C_PY) + rb) * 32], (epoch + 1) * 16);
            asm volatile("fence.proxy.async.global;" ::: "memory");
            PROFP(4 + (s >> 2));
          }
          bulk_load(dst, &g_P[(rb * 28 + kblk) * 1024], 16384, fb);
          if (++d == 6) { d = 0; ph ^= 1; }
        }
        PROFP(7);
      }
    } else {
      if (lane < 3) {
        const char* p = (lane == 0 ? wg_raw : lane == 1 ? wu_raw : wd_raw) + (size_t)c * 14336;
        asm volatile("cp.async.bulk.prefetch.L2.global [%0], %1;" ::"l"(p), "r"(14336) : "memory");
      }
#pragma unroll 1
      for (int e = 0; e < 4; e++) {
        bar_sync(NB_PUB0 + (e & 1), 160);
        if (lane == 0) red_release(&g_cnt[((e < 2 ? C_PX : C_PY) + rb) * 32]);
      }
    }
    __syncwarp();
    asm volatile("barrier.cluster.wait.aligned;" ::: "memory");
  } else {
    const int g = lane >> 2, t = lane & 3;
    PROF(0);
    PROFG(14);
#pragma unroll
    for (int i = 0; i < 4; i++) {
      const int r = i >> 1, ch = (i & 1) * 32 + lane;
      cp_async16(sbase + SM_X + (2 * warp + r) * 1024 + ((ch ^ ((ch >> 2) & 6)) * 16),
                 x + (size_t)(c + 128 * (2 * warp + r)) * 512 + ch * 8);
    }
#pragma unroll
    for (int i = 0; i < 3; i++)
      cp_async16(sbase + SM_T + (tid + 256 * i) * 16, reinterpret_cast<const char*>(&g_tab) + (tid + 256 * i) * 16);
    asm volatile("cp.async.commit_group;" ::: "memory");
    const int wsh = (2 * (c >> 3) + 2) & 15;
#pragma unroll
    for (int i = 0; i < 5; i++) {
      const int idx = tid + 256 * i, ra = idx / 5, ch = idx - 5 * ra, j2 = ra & 127;
      const char* src = reinterpret_cast<const char*>(ra >= 128 ? wi : wr) + ((c >> 3) + 16 * j2) * 514 + 64 * (c & 7) + 2 - wsh + 16 * ch;
      if (ch < 4 || wsh != 0) cp_async16(sbase + SM_W + ((ra & 128) + (j2 & 15) * 8 + (j2 >> 4)) * 80 + ch * 16, src);
    }
    asm volatile("cp.async.commit_group;" ::: "memory");
    asm volatile("barrier.cluster.arrive.relaxed.aligned;" ::: "memory");
    asm volatile("setmaxnreg.inc.sync.aligned.u32 232;");
    unsigned epoch = 0;
    if (tid == 0) epoch = ld_relaxed(&g_cnt[C_BAR1 * 32]) >> 7;
    {
      const int ln = (tid >> 1) & 31, lg = ln >> 2, lt = ln & 3, i = 4 * (tid >> 6) + 2 * (tid & 1);
      const int kidx = lt + 8 * (i >> 3), nidx = 4 * ((i >> 1) & 3) + (lg >> 1);
      const uint32_t a0 = cfrag<2048>((c + 128 * kidx) * nidx, lg & 1), a1 = cfrag<2048>((c + 128 * (kidx + 4)) * nidx, lg & 1);
      const uint32_t b0 = cfrag<2048>(-(c + 128 * nidx) * kidx, lg & 1), b1 = cfrag<2048>(-(c + 128 * nidx) * (kidx + 4), lg & 1);
      asm volatile("st.shared.v2.u32 [%0], {%1,%2};" ::"r"(sbase + SM_FC + tid * 8), "r"(a0), "r"(a1) : "memory");
      asm volatile("st.shared.v2.u32 [%0], {%1,%2};" ::"r"(sbase + SM_FC + 2048 + tid * 8), "r"(b0), "r"(b1) : "memory");
    }
    asm volatile("cp.async.wait_group 1;" ::: "memory");
    bar_sync(NB_INIT, 384);
    PROF(13);
    {
      uint2 v[2][4];
#pragma unroll
      for (int r = 0; r < 2; r++)
#pragma unroll
        for (int q = 0; q < 4; q++)
          v[r][q] = lds2(sbase + SM_X + (2 * warp + r) * 1024 + (t + 4 * (q >> 1)) * 128 + (((4 * (q & 1) + (g >> 1)) ^ (2 * t)) * 16) + (g & 1) * 8);
      const uint4 fa = lds4(TOFF(fa));
      uint4 tw[4], fb[16];
#pragma unroll
      for (int i = 0; i < 4; i++) tw[i] = lds4(TOFF(tw1) + i * 512);
#pragma unroll
      for (int i = 0; i < 16; i++) fb[i] = lds4(TOFF(fb) + i * 512);
      float mean[2], rstd[2];
#pragma unroll
      for (int r = 0; r < 2; r++) {
        float s = 0.f;
#pragma unroll
        for (int q = 0; q < 4; q++) s += (bf_lo(v[r][q].x) + bf_hi(v[r][q].x)) + (bf_lo(v[r][q].y) + bf_hi(v[r][q].y));
        mean[r] = warp_sum(s) * (1.f / 512.f);
      }
#pragma unroll
      for (int r = 0; r < 2; r++) {
        float s = 0.f;
#pragma unroll
        for (int q = 0; q < 4; q++) {
          float a0 = bf_lo(v[r][q].x) - mean[r], a1 = bf_hi(v[r][q].x) - mean[r];
          float a2 = bf_lo(v[r][q].y) - mean[r], a3 = bf_hi(v[r][q].y) - mean[r];
          s += (a0 * a0 + a1 * a1) + (a2 * a2 + a3 * a3);
        }
        rstd[r] = rsqrtf(warp_sum(s) * (1.f / 512.f) + 1e-5f);
      }
      uint32_t alo[4][4], ahi[4][4];
#pragma unroll
      for (int r = 0; r < 2; r++)
#pragma unroll
        for (int i = 0; i < 4; i++) {
          const uint32_t sel = (i & 1) ? 0x7632u : 0x5410u;
          const uint32_t b0 = __byte_perm((i & 2) ? v[r][0].y : v[r][0].x, (i & 2) ? v[r][1].y : v[r][1].x, sel);
          const uint32_t b1 = __byte_perm((i & 2) ? v[r][2].y : v[r][2].x, (i & 2) ? v[r][3].y : v[r][3].x, sel);
          float d[4] = {0.f, 0.f, 0.f, 0.f};
          mma16816(d, fa.x, fa.y, fa.z, fa.w, b0, b1);
          const float ca = __uint_as_float(tw[i].x), sa = __uint_as_float(tw[i].y), cb = __uint_as_float(tw[i].z), sb = __uint_as_float(tw[i].w);
          const float a0 = g == 0 ? d[2] : d[0], a1 = g == 0 ? d[3] : d[1];
          const float i0 = g == 0 ? 0.f : d[2], i1 = g == 0 ? 0.f : d[3];
          const uint32_t re = pack2(a0 * ca + i0 * sa, a1 * cb + i1 * sb);
          const uint32_t im = pack2(i0 * ca - a0 * sa, i1 * cb - a1 * sb);
          const uint32_t dc = pack2(d[0] - 16.f * mean[r], d[1] - 16.f * mean[r]);
          alo[i][r] = re; alo[i][2 + r] = im;
          ahi[i][r] = g == 0 ? dc : re; ahi[i][2 + r] = g == 0 ? 0u : im;
        }
      float acc[8][4];
#pragma unroll
      for (int u = 0; u < 8; u++) {
        acc[u][0] = acc[u][1] = acc[u][2] = acc[u][3] = 0.f;
#pragma unroll
        for (int i = 0; i < 4; i++) {
          const uint4& bq = fb[i * 4 + (u >> 1)];
          if (u < 4) mma16816(acc[u], alo[i][0], alo[i][1], alo[i][2], alo[i][3], (u & 1) ? bq.z : bq.x, (u & 1) ? bq.w : bq.y);
          else       mma16816(acc[u], ahi[i][0], ahi[i][1], ahi[i][2], ahi[i][3], (u & 1) ? bq.z : bq.x, (u & 1) ? bq.w : bq.y);
        }
      }
      uint4 fc[4];
#pragma unroll
      for (int i = 0; i < 4; i++) fc[i] = lds4(sbase + SM_FC + i * 512 + lane * 16);
#pragma unroll
      for (int r = 0; r < 2; r++)
#pragma unroll
        for (int h = 0; h < 2; h++) {
          const int j = 2 * warp + r, m = 2 * t + h;
          const float rs = rstd[r];
          sts4(sbase + SM_E + ((j * 8 + m) * 8 + (g ^ (2 * t) ^ (2 * (j & 3)))) * 16,
               pack2(acc[2 * h][2 * r] * rs, acc[2 * h][2 * r + 1] * rs), pack2(acc[2 * h + 1][2 * r] * rs, acc[2 * h + 1][2 * r + 1] * rs),
               pack2(acc[4 + 2 * h][2 * r] * rs, acc[4 + 2 * h][2 * r + 1] * rs), pack2(acc[5 + 2 * h][2 * r] * rs, acc[5 + 2 * h][2 * r + 1] * rs));
        }
      bar_sync(NB_CONS, 256);
      uint4 q[4], o[4];
#pragma unroll
      for (int i = 0; i < 4; i++) q[i] = lds4(sbase + SM_E + (((t + 4 * i) * 8 + warp) * 8 + (g ^ (warp & 6) ^ (2 * t))) * 16);
      cdft16(q, fc, o);
#pragma unroll
      for (int vv = 0; vv < 4; vv++) g_Z1[(((4 * vv + t) * 8 + warp) * 128 + c) * 8 + g] = o[vv];
    }
    PROF(1);
    asm volatile("cp.async.wait_group 0;" ::: "memory");
    bar_sync(NB_CONS, 256);
    if (tid == 0) red_release(&g_cnt[C_BAR1 * 32]);
    {
      mbar_wait(BAR(tbar, 0), 0);
      uint4 f2[4], g2[4];
#pragma unroll
      for (int i = 0; i < 4; i++) {
        f2[i] = lds4(TOFF(f2) + warp * 2048 + i * 512);
        g2[i] = lds4(TOFF(g2) + warp * 2048 + i * 512);
      }
      const uint4 f8 = lds4(TOFF(f8)), g8 = lds4(TOFF(g8));
      float wfr[16], wfi[16];
      {
        const float fsc = 1.f / (1 << 19);
        const float fsc3 = ((c & 7) == 7 && g == 0) ? 0.5f * fsc : fsc;
        const int gg = g == 0 ? 8 : g;
#pragma unroll
        for (int i = 0; i < 16; i++) {
          const int ci = i >> 3, dd = (i >> 2) & 1, e = i & 3;
          const int kk = (e == 0 ? gg : e == 1 ? 16 + gg : e == 2 ? 16 - g : 32 - g) - 1;
          const uint32_t a = sbase + SM_W + ((2 * warp + ci) * 8 + t + 4 * dd) * 80 + wsh + 2 * kk;
          wfr[i] = bf_lo(lds_u16(a)) * (e == 3 ? fsc3 : fsc);
          wfi[i] = bf_lo(lds_u16(a + 128 * 80)) * (e == 3 ? fsc3 : fsc);
        }
      }
      asm volatile("barrier.cluster.wait.aligned;" ::: "memory");
      if (tid == 0) wait_counter(&g_cnt[C_BAR1 * 32], (epoch + 1) * 128);
      bar_sync(NB_CONS, 256);
      PROF(2);
      uint4 q[4], o[4];
#pragma unroll
      for (int i = 0; i < 4; i++) q[i] = ldg_cg4(&g_Z1[(c * 128 + 8 * (t + 4 * i) + warp) * 8 + g]);
      cdft16(q, f2, o);
      const uint32_t e2 = sbase + SM_E2;
#pragma unroll
      for (int vv = 0; vv < 4; vv++)
        sts4(e2 + ((warp * 16 + 4 * vv + t) * 8 + (g ^ (2 * t) ^ (2 * (warp & 3)))) * 16, o[vv].x, o[vv].y, o[vv].z, o[vv].w);
      bar_sync(NB_CONS, 256);
#pragma unroll
      for (int ci = 0; ci < 2; ci++) {
        const int cc = 2 * warp + ci;
        uint32_t ad[2];
        uint4 u[2];
#pragma unroll
        for (int hh = 0; hh < 2; hh++) {
          ad[hh] = e2 + (((t + 4 * hh) * 16 + cc) * 8 + (g ^ (2 * (cc & 3)) ^ (2 * t))) * 16;
          u[hh] = lds4(ad[hh]);
        }
        uint32_t res[2][4];
#pragma unroll
        for (int p = 0; p < 2; p++) {
          uint32_t y[2][2];
#pragma unroll
          for (int vv = 0; vv < 2; vv++) {
            float d[4] = {0.f, 0.f, 0.f, 0.f};
            mma16816(d, word(u[0], 2 * p), word(u[0], 2 * p + 1), word(u[1], 2 * p), word(u[1], 2 * p + 1), word(f8, 2 * vv), word(f8, 2 * vv + 1));
#pragma unroll
            for (int rr = 0; rr < 2; rr++) {
              const float fr = wfr[ci * 8 + vv * 4 + 2 * p + rr], fi = wfi[ci * 8 + vv * 4 + 2 * p + rr];
              y[vv][rr] = pack2(d[2 * rr] * fr - d[2 * rr + 1] * fi, d[2 * rr] * fi + d[2 * rr + 1] * fr);
            }
          }
#pragma unroll
          for (int vv = 0; vv < 2; vv++) {
            float d[4] = {0.f, 0.f, 0.f, 0.f};
            mma16816(d, y[0][0], y[0][1], y[1][0], y[1][1], word(g8, 2 * vv), word(g8, 2 * vv + 1));
            res[vv][2 * p] = pack2(d[0], d[1]);
            res[vv][2 * p + 1] = pack2(d[2], d[3]);
          }
        }
#pragma unroll
        for (int vv = 0; vv < 2; vv++) sts4(ad[vv], res[vv][0], res[vv][1], res[vv][2], res[vv][3]);
      }
      bar_sync(NB_CONS, 256);
#pragma unroll
      for (int i = 0; i < 4; i++) q[i] = lds4(e2 + ((warp * 16 + 4 * i + t) * 8 + (g ^ (2 * t) ^ (2 * (warp & 3)))) * 16);
      cdft16(q, g2, o);
#pragma unroll
      for (int vv = 0; vv < 4; vv++) g_Z2[((8 * (4 * vv + t) + warp) * 128 + c) * 8 + g] = o[vv];
    }
    PROF(3);
    bar_sync(NB_CONS, 256);
    if (tid == 0) red_release(&g_cnt[C_BAR2 * 32]);
    {
      uint4 gb[16], gc[4], tw[4], xr[2][2];
#pragma unroll
      for (int i = 0; i < 16; i++) gb[i] = lds4(TOFF(gb) + i * 512);
      const uint4 ga = lds4(TOFF(ga));
#pragma unroll
      for (int i = 0; i < 4; i++) {
        gc[i] = lds4(sbase + SM_FC + 2048 + i * 512 + lane * 16);
        tw[i] = lds4(TOFF(tw3) + i * 512);
        const int ch = 4 * (g + 8 * (i & 1)) + t;
        xr[i >> 1][i & 1] = lds4(sbase + SM_X + (2 * warp + (i >> 1)) * 1024 + ((ch ^ ((ch >> 2) & 6)) * 16));
      }
      if (tid == 0) wait_counter(&g_cnt[C_BAR2 * 32], (epoch + 1) * 128);
      bar_sync(NB_CONS, 256);
      PROF(4);
      uint4 q[4], o[4];
#pragma unroll
      for (int i = 0; i < 4; i++) q[i] = ldg_cg4(&g_Z2[((c * 16 + t + 4 * i) * 8 + warp) * 8 + g]);
      cdft16(q, gc, o);
#pragma unroll
      for (int vv = 0; vv < 4; vv++)
        sts4(sbase + SM_E + (((4 * vv + t) * 8 + warp) * 8 + (g ^ (warp & 6) ^ (2 * t))) * 16, o[vv].x, o[vv].y, o[vv].z, o[vv].w);
      bar_sync(NB_CONS, 256);
      uint32_t hv[2][2][4];
#pragma unroll
      for (int r = 0; r < 2; r++) {
        const int j = 2 * warp + r;
        uint4 u[2];
#pragma unroll
        for (int h = 0; h < 2; h++) u[h] = lds4(sbase + SM_E + ((j * 8 + 2 * t + h) * 8 + (g ^ (2 * t) ^ (2 * (j & 3)))) * 16);
        float yv[4][4];
#pragma unroll
        for (int i = 0; i < 4; i++) {
          float lo[4] = {0.f, 0.f, 0.f, 0.f}, hi[4] = {0.f, 0.f, 0.f, 0.f};
          mma16816(lo, gb[i * 4].x, gb[i * 4].y, gb[i * 4].z, gb[i * 4].w, u[0].x, u[0].y);
          mma16816(lo, gb[i * 4 + 1].x, gb[i * 4 + 1].y, gb[i * 4 + 1].z, gb[i * 4 + 1].w, u[1].x, u[1].y);
          mma16816(hi, gb[i * 4 + 2].x, gb[i * 4 + 2].y, gb[i * 4 + 2].z, gb[i * 4 + 2].w, u[0].z, u[0].w);
          mma16816(hi, gb[i * 4 + 3].x, gb[i * 4 + 3].y, gb[i * 4 + 3].z, gb[i * 4 + 3].w, u[1].z, u[1].w);
          const float ca = __uint_as_float(tw[i].x), sa = __uint_as_float(tw[i].y), cb = __uint_as_float(tw[i].z), sb = __uint_as_float(tw[i].w);
          const float tr0 = t == 0 ? lo[0] : lo[0] + hi[0], ti0 = t == 0 ? lo[2] : lo[2] + hi[2];
          const float tr1 = lo[1] + hi[1], ti1 = lo[3] + hi[3];
          const float vr0 = tr0 * ca - ti0 * sa, vi0 = tr0 * sa + ti0 * ca;
          const float vr1 = tr1 * cb - ti1 * sb, vi1 = tr1 * sb + ti1 * cb;
          const uint32_t b0 = pack2(t == 0 ? hi[0] : vr0, vr1), b1 = pack2(t == 0 ? vr0 : vi0, vi1);
          yv[i][0] = yv[i][1] = yv[i][2] = yv[i][3] = 0.f;
          mma16816(yv[i], ga.x, ga.y, ga.z, ga.w, b0, b1);
        }
#pragma unroll
        for (int h = 0; h < 2; h++) {
          hv[r][h][0] = hadd2_bf16(xr[r][h].x, pack2(yv[0][2 * h], yv[1][2 * h]));
          hv[r][h][1] = hadd2_bf16(xr[r][h].y, pack2(yv[2][2 * h], yv[3][2 * h]));
          hv[r][h][2] = hadd2_bf16(xr[r][h].z, pack2(yv[0][2 * h + 1], yv[1][2 * h + 1]));
          hv[r][h][3] = hadd2_bf16(xr[r][h].w, pack2(yv[2][2 * h + 1], yv[3][2 * h + 1]));
        }
      }
      float mean[2], rstd[2];
#pragma unroll
      for (int r = 0; r < 2; r++) {
        float s = 0.f;
#pragma unroll
        for (int i = 0; i < 8; i++) s += bf_lo(hv[r][i >> 2][i & 3]) + bf_hi(hv[r][i >> 2][i & 3]);
        mean[r] = warp_sum(s) * (1.f / 512.f);
      }
#pragma unroll
      for (int r = 0; r < 2; r++) {
        float s = 0.f;
#pragma unroll
        for (int i = 0; i < 8; i++) {
          const float a = bf_lo(hv[r][i >> 2][i & 3]) - mean[r], b = bf_hi(hv[r][i >> 2][i & 3]) - mean[r];
          s += a * a + b * b;
        }
        rstd[r] = rsqrtf(warp_sum(s) * (1.f / 512.f) + 1e-5f);
      }
#pragma unroll
      for (int r = 0; r < 2; r++) {
        const int row = 16 * f + 2 * warp + r;
        const float nm = -mean[r] * rstd[r];
#pragma unroll
        for (int h = 0; h < 2; h++) {
          uint32_t w[4];
#pragma unroll
          for (int i = 0; i < 4; i++) w[i] = pack2(fmaf(bf_lo(hv[r][h][i]), rstd[r], nm), fmaf(bf_hi(hv[r][h][i]), rstd[r], nm));
          const int n1 = g + 8 * h;
          g_LN[(rb * 8 + (n1 >> 1)) * 1024 + row * 8 + ((4 * (n1 & 1) + t) ^ (row & 7))] = make_uint4(w[0], w[1], w[2], w[3]);
        }
      }
      asm volatile("fence.proxy.async.shared::cta;" ::: "memory");
      bar_arrive(NB_LN, 288);
#pragma unroll
      for (int r = 0; r < 2; r++)
#pragma unroll
        for (int h = 0; h < 2; h++)
          g_H[(c + 128 * (2 * warp + r)) * 64 + 4 * (g + 8 * h) + t] = make_uint4(hv[r][h][0], hv[r][h][1], hv[r][h][2], hv[r][h][3]);
    }
    PROF(5);
    const int wgi = warp >> 2, wq = warp & 3;
    uint4* const pbase = &g_P[rb * 28 * 1024];
    const int p_lane = (8 * wgi + 2 * wq) * 64 + t * 8 + g;
    const uint32_t a_lo0 = desc_lo(sbase + wgi * 8192, 16);
    uint32_t slot = 0, ph = 0, prev = 0;
    {
      float acc[128];
#pragma unroll
      for (int i = 0; i < 128; i++) acc[i] = 0.f;
      if (wgi == 1) bar_sync(NB_LAG, 256);
      const uint32_t b_lo0 = desc_lo(sbase + 8 * SLOT, 4096);
#pragma unroll 1
      for (int kb = 0; kb < 8; kb++) {
        mbar_wait(BAR(fullA, kb), 0);
        if (kb == 0) PROF(6);
#pragma unroll
        for (int hh = 0; hh < 2; hh++) {
          mbar_wait(BAR(full1, slot), ph);
          const uint32_t al = a_lo0 + kb * 1024 + hh * 4, bl = b_lo0 + slot * 1024;
          wg_fence();
          wgmma_n256(acc, desc64(al, HI128), desc64(bl, HI128));
          wgmma_n256(acc, desc64(al + 2, HI128), desc64(bl + 128, HI128));
          wg_commit();
          if (hh == (LAG & 1) && kb == (LAG >> 1) && wgi == 0) bar_arrive(NB_LAG, 256);
          wg_wait<1>();
          if ((kb | hh) != 0 && lane == 0) mbar_arrive(BAR(empty1, prev));
          prev = slot;
          if (++slot == 6) { slot = 0; ph ^= 1; }
        }
      }
      wg_wait<0>();
      if (lane == 0) mbar_arrive(BAR(empty1, prev));
      PROF(7);
      store_p<4>(acc, pbase, 7 * f + 3 * (f & 1), p_lane);
      bar_arrive(NB_PUB0 + wgi, 160);
    }
    PROF(8);
    {
      float acc[96];
#pragma unroll
      for (int i = 0; i < 96; i++) acc[i] = 0.f;
      const uint32_t b_lo0 = desc_lo(sbase + 8 * SLOT, 2048);
#pragma unroll 1
      for (int kb = 0; kb < 8; kb++) {
#pragma unroll
        for (int hh = 0; hh < 2; hh++) {
          mbar_wait(BAR(full1, slot), ph);
          const uint32_t al = a_lo0 + kb * 1024 + hh * 4, bl = b_lo0 + slot * 1024;
          wg_fence();
          wgmma_n192(acc, desc64(al, HI128), desc64(bl, HI64));
          wgmma_n192(acc, desc64(al + 2, HI128), desc64(bl + 64, HI64));
          wg_commit();
          wg_wait<1>();
          if (lane == 0) {
            if ((kb | hh) != 0 && 2 * kb + hh <= 10) mbar_arrive(BAR(empty1, prev));
            if (hh == 0) {
              if (kb == 2 || kb == 4 || kb == 6) mbar_arrive(BAR(empty2, (kb >> 1) - 1));
              if (kb >= 6) mbar_arrive(BAR(empty2, kb - 3));
            }
          }
          prev = slot;
          if (++slot == 6) { slot = 0; ph ^= 1; }
        }
      }
      wg_wait<0>();
      if (lane == 0) mbar_arrive(BAR(empty2, 5));
      PROF(9);
      store_p<3>(acc, pbase, 7 * f + ((f & 1) ? 0 : 4), p_lane);
      bar_arrive(NB_PUB0 + wgi, 160);
    }
    PROF(10);
    {
      const int kh = f & 1, nq = f >> 1;
      const int rh = wgi ^ kh ^ 1;
      const int orow = 8 * rb + 4 * rh + wq;
      float acc[64];
#pragma unroll
      for (int i = 0; i < 64; i++) acc[i] = 0.f;
      const uint32_t a2_lo0 = desc_lo(sbase + rh * 8192, 128), b2_lo0 = desc_lo(sbase + SLOT, 8192);
      uint4 hres[2][4];
      slot = 0; ph = 0;
#pragma unroll 1
      for (int s = 0; s < 14; s++) {
        const uint32_t doff = ((0x365210 >> (4 * slot)) & 15) * 2048;
        mbar_wait(BAR(full2, slot), ph);
        wg_fence();
#pragma unroll
        for (int kk = 0; kk < 4; kk++) wgmma_n128(acc, desc64(a2_lo0 + doff + kk * 16, HI0), desc64(b2_lo0 + doff + kk * 128, HI128));
        wg_commit();
        if (s == 0) {
#pragma unroll
          for (int h = 0; h < 2; h++)
#pragma unroll
            for (int q = 0; q < 4; q++) hres[h][q] = ldg_cg4(&g_H[(orow + 128 * (g + 8 * h)) * 64 + nq * 16 + 4 * q + t]);
        }
        wg_wait<1>();
        if (s > 0 && s <= 8 && lane == 0) mbar_arrive(BAR(empty2, prev));
        prev = slot;
        if (++slot == 6) { slot = 0; ph ^= 1; }
      }
      wg_wait<0>();
      PROF(11);
      const uint32_t xbuf = sbase + 8 * SLOT + (tid & 127) * 16;
      if (wgi == 0) {
        uint32_t rbuf, rbar;
        asm volatile("mapa.shared::cluster.u32 %0, %1, %2;" : "=r"(rbuf) : "r"(xbuf), "r"(kh ^ 1));
        asm volatile("mapa.shared::cluster.u32 %0, %1, %2;" : "=r"(rbar) : "r"(BAR(xbar, 0)), "r"(kh ^ 1));
#pragma unroll
        for (int i = 0; i < 16; i++)
          asm volatile("st.async.weak.shared::cluster.mbarrier::complete_tx::bytes.v4.f32 [%0], {%1,%2,%3,%4}, [%5];"
                       ::"r"(rbuf + i * 2048), "f"(acc[4 * i]), "f"(acc[4 * i + 1]), "f"(acc[4 * i + 2]), "f"(acc[4 * i + 3]), "r"(rbar)
                       : "memory");
      } else {
        mbar_wait_cluster(BAR(xbar, 0), 0);
      }
      uint32_t w[2][16];
#pragma unroll
      for (int i = 0; i < 16; i++) {
        const uint4 pv = lds4(xbuf + i * 2048);
        w[0][i] = pack2(acc[4 * i] + __uint_as_float(pv.x), acc[4 * i + 1] + __uint_as_float(pv.y));
        w[1][i] = pack2(acc[4 * i + 2] + __uint_as_float(pv.z), acc[4 * i + 3] + __uint_as_float(pv.w));
      }
      uint4* const o4 = reinterpret_cast<uint4*>(out);
#pragma unroll
      for (int h = 0; h < 2; h++)
#pragma unroll
        for (int q = 0; q < 4; q++) {
          uint32_t a0 = w[h][4 * q], a1 = w[h][4 * q + 1], a2 = w[h][4 * q + 2], a3 = w[h][4 * q + 3];
          {
            const bool od = t & 1;
            uint32_t s0 = od ? a0 : a1, s1 = od ? a2 : a3;
            s0 = __shfl_xor_sync(0xffffffffu, s0, 1); s1 = __shfl_xor_sync(0xffffffffu, s1, 1);
            if (od) { a0 = s0; a2 = s1; } else { a1 = s0; a3 = s1; }
          }
          {
            const bool up = t & 2;
            uint32_t s0 = up ? a0 : a2, s1 = up ? a1 : a3;
            s0 = __shfl_xor_sync(0xffffffffu, s0, 2); s1 = __shfl_xor_sync(0xffffffffu, s1, 2);
            if (up) { a0 = s0; a1 = s1; } else { a2 = s0; a3 = s1; }
          }
          if (wgi == 1)
            o4[(orow + 128 * (g + 8 * h)) * 64 + nq * 16 + 4 * q + t] =
                make_uint4(hadd2_bf16(hres[h][q].x, a0), hadd2_bf16(hres[h][q].y, a1), hadd2_bf16(hres[h][q].z, a2), hadd2_bf16(hres[h][q].w, a3));
        }
      PROF(12);
      PROFG(15);
    }
  }
#undef BAR
#undef TOFF
}

typedef CUresult (*EncodeFn)(CUtensorMap*, CUtensorMapDataType, cuuint32_t, void*, const cuuint64_t*, const cuuint64_t*,
                             const cuuint32_t*, const cuuint32_t*, CUtensorMapInterleave, CUtensorMapSwizzle,
                             CUtensorMapL2promotion, CUtensorMapFloatOOBfill);

}

extern "C" void kernel_launch(void* const* d_in, const int* in_sizes, int n_in, void* d_out, int out_size) {
  (void)in_sizes; (void)n_in; (void)out_size;
  static EncodeFn encode = nullptr;
  if (!encode) {
    void* fn = nullptr;
    cudaDriverEntryPointQueryResult qr;
    cudaGetDriverEntryPoint("cuTensorMapEncodeTiled", &fn, cudaEnableDefault, &qr);
    encode = (EncodeFn)fn;
    cudaFuncSetAttribute(fused_kernel, cudaFuncAttributeMaxDynamicSharedMemorySize, SMEM_BYTES);
  }
  CUtensorMap tmGX, tmUX, tmGY, tmUY, tmD;
  const cuuint32_t es[5] = {1, 1, 1, 1, 1};
  {
    const cuuint64_t gd[3] = {64, 512, 28}, gs[2] = {3584, 128};
    const cuuint32_t bd[3] = {64, 32, 2};
    encode(&tmGX, CU_TENSOR_MAP_DATA_TYPE_BFLOAT16, 3, d_in[4], gd, gs, bd, es, CU_TENSOR_MAP_INTERLEAVE_NONE,
           CU_TENSOR_MAP_SWIZZLE_128B, CU_TENSOR_MAP_L2_PROMOTION_L2_256B, CU_TENSOR_MAP_FLOAT_OOB_FILL_NONE);
    encode(&tmUX, CU_TENSOR_MAP_DATA_TYPE_BFLOAT16, 3, d_in[5], gd, gs, bd, es, CU_TENSOR_MAP_INTERLEAVE_NONE,
           CU_TENSOR_MAP_SWIZZLE_128B, CU_TENSOR_MAP_L2_PROMOTION_L2_256B, CU_TENSOR_MAP_FLOAT_OOB_FILL_NONE);
  }
  {
    const cuuint64_t gd[3] = {32, 512, 56}, gs[2] = {3584, 64};
    const cuuint32_t bd[3] = {32, 32, 3};
    encode(&tmGY, CU_TENSOR_MAP_DATA_TYPE_BFLOAT16, 3, d_in[4], gd, gs, bd, es, CU_TENSOR_MAP_INTERLEAVE_NONE,
           CU_TENSOR_MAP_SWIZZLE_64B, CU_TENSOR_MAP_L2_PROMOTION_L2_128B, CU_TENSOR_MAP_FLOAT_OOB_FILL_NONE);
    encode(&tmUY, CU_TENSOR_MAP_DATA_TYPE_BFLOAT16, 3, d_in[5], gd, gs, bd, es, CU_TENSOR_MAP_INTERLEAVE_NONE,
           CU_TENSOR_MAP_SWIZZLE_64B, CU_TENSOR_MAP_L2_PROMOTION_L2_128B, CU_TENSOR_MAP_FLOAT_OOB_FILL_NONE);
  }
  {
    const cuuint64_t gd[5] = {512, 2, 4, 4, 56}, gs[4] = {1024, 8192, 2048, 32768};
    const cuuint32_t bd[5] = {64, 2, 4, 4, 2};
    encode(&tmD, CU_TENSOR_MAP_DATA_TYPE_BFLOAT16, 5, d_in[6], gd, gs, bd, es, CU_TENSOR_MAP_INTERLEAVE_NONE,
           CU_TENSOR_MAP_SWIZZLE_128B, CU_TENSOR_MAP_L2_PROMOTION_L2_256B, CU_TENSOR_MAP_FLOAT_OOB_FILL_NONE);
  }
  fused_kernel<<<NCTA, NTHREADS, SMEM_BYTES>>>(
      tmGX, tmUX, tmGY, tmUY, tmD, (const __nv_bfloat16*)d_in[0], (const __nv_bfloat16*)d_in[1], (const __nv_bfloat16*)d_in[2],
      (const char*)d_in[4], (const char*)d_in[5], (const char*)d_in[6], (__nv_bfloat16*)d_out);
}
```

```cpp
#include <cuda_runtime.h>
#include <cuda_bf16.h>
#include <cuda.h>
#include <stdint.h>

namespace {

constexpr int NCTA = 128;
constexpr int NTHREADS = 384;
constexpr int SLOT = 16384;
constexpr int SMEM_BYTES = 14 * SLOT + 1024 + 1024;
constexpr int SPIN_LIMIT = 1 << 22;

__device__ uint4 g_Z1[128 * 1024];
__device__ uint4 g_Z2[128 * 1024];
__device__ uint4 g_LN[16 * 8 * 1024];
__device__ uint4 g_H[2048 * 64];
__device__ uint4 g_P[16 * 28 * 1024];
__device__ unsigned g_cnt[64 * 32];
#define PROF(i)
#define PROFP(i)
#define PROFG(i)

constexpr double ccos(int i, int n) {
  i &= n - 1;
  if (i > n / 2) i = n - i;
  if (4 * i == n) return 0.0;
  const bool neg = 4 * i > n;
  if (neg) i = n / 2 - i;
  const double a = 6.283185307179586476925 * i / n, a2 = a * a;
  double term = 1.0, sum = 1.0;
  for (int k = 1; k < 14; k++) { term *= -a2 / ((2 * k - 1) * (2 * k)); sum += term; }
  return neg ? -sum : sum;
}
constexpr double csin(int i, int n) { return ccos(i - n / 4, n); }
constexpr unsigned fbits(double v, int mant) {
  if (v == 0.0) return 0;
  const unsigned sg = v < 0 ? 1u : 0u;
  if (v < 0) v = -v;
  int e = 127;
  while (v < 1.0) { v *= 2.0; e--; }
  const unsigned m = (unsigned)((v - 1.0) * (double)(1u << mant) + 0.5);
  return (sg << (8 + mant)) + ((unsigned)e << mant) + m;
}
constexpr unsigned pkb(double lo, double hi) { return fbits(lo, 7) | (fbits(hi, 7) << 16); }
constexpr double fa_elem(int kp, int n1) {
  return kp <= 8 ? ccos(kp * n1, 16) : -csin((kp - 8) * n1, 16);
}
constexpr unsigned cfrag_c(int idx, int n, int ri) {
  return ri ? pkb(-csin(idx, n), ccos(idx, n)) : pkb(ccos(idx, n), csin(idx, n));
}
struct Tables {
  unsigned fb[16][32][4];
  unsigned tw1[4][32][4];
  unsigned fa[32][4];
  unsigned pad[32][4];
  unsigned pad2[2][32][4];
  unsigned f2[8][4][32][4];
  unsigned g2[8][4][32][4];
  unsigned gb[16][32][4];
  unsigned tw3[4][32][4];
  unsigned ga[32][4];
  unsigned f8[32][4], g8[32][4];
  unsigned pad3[32][4];
};
constexpr int T1_BYTES = 12288, T2_BYTES = 45056;
static_assert(sizeof(Tables) == T1_BYTES + T2_BYTES, "table size");
constexpr Tables make_tables() {
  Tables T = {};
  for (int l = 0; l < 32; l++) {
    const int g = l >> 2, t = l & 3;
    for (int i = 0; i < 4; i++)
      for (int u = 0; u < 8; u++) {
        const int ri = g & 1, m = 2 * (g >> 1) + ((u & 3) >> 1);
        const double sg = u >= 4 ? -1.0 : 1.0;
        const int k2 = u >= 4 ? 31 - 2 * m - (u & 1) : 2 * m + (u & 1);
        const int pa = (8 * t + i) * k2, pb = (8 * t + 4 + i) * k2;
        T.fb[i * 4 + (u >> 1)][l][(u & 1) * 2 + 0] = ri == 0 ? pkb(ccos(pa, 32), ccos(pb, 32)) : pkb(-sg * csin(pa, 32), -sg * csin(pb, 32));
        T.fb[i * 4 + (u >> 1)][l][(u & 1) * 2 + 1] = ri == 0 ? pkb(csin(pa, 32), csin(pb, 32)) : pkb(sg * ccos(pa, 32), sg * ccos(pb, 32));
      }
    for (int i = 0; i < 4; i++)
      for (int ks = 0; ks < 4; ks++) {
        const int n2 = 4 * g + i, m = 2 * t + (ks & 1);
        const double sg = ks >= 2 ? -1.0 : 1.0;
        const int pa = n2 * (ks >= 2 ? 31 - 2 * m : 2 * m), pb = n2 * (ks >= 2 ? 30 - 2 * m : 2 * m + 1);
        T.gb[i * 4 + ks][l][0] = pkb(ccos(pa, 32), -sg * csin(pa, 32));
        T.gb[i * 4 + ks][l][1] = pkb(csin(pa, 32), sg * ccos(pa, 32));
        T.gb[i * 4 + ks][l][2] = pkb(ccos(pb, 32), -sg * csin(pb, 32));
        T.gb[i * 4 + ks][l][3] = pkb(csin(pb, 32), sg * ccos(pb, 32));
      }
    for (int i = 0; i < 4; i++) {
      const int k1 = g == 0 ? 8 : g;
      T.tw1[i][l][0] = fbits(ccos((8 * t + i) * k1, 512), 23);
      T.tw1[i][l][1] = fbits(csin((8 * t + i) * k1, 512), 23);
      T.tw1[i][l][2] = fbits(ccos((8 * t + 4 + i) * k1, 512), 23);
      T.tw1[i][l][3] = fbits(csin((8 * t + 4 + i) * k1, 512), 23);
      const int ka = t == 0 ? 8 : 2 * t, kb = 2 * t + 1;
      T.tw3[i][l][0] = fbits(ccos((4 * g + i) * ka, 512), 23);
      T.tw3[i][l][1] = fbits(csin((4 * g + i) * ka, 512), 23);
      T.tw3[i][l][2] = fbits(ccos((4 * g + i) * kb, 512), 23);
      T.tw3[i][l][3] = fbits(csin((4 * g + i) * kb, 512), 23);
      const int p8 = (t + 4 * (i & 1)) * (4 * (i >> 1) + (g >> 1));
      T.f8[l][i] = cfrag_c(p8, 8, g & 1);
      T.g8[l][i] = cfrag_c(-p8, 8, g & 1);
    }
    for (int w = 0; w < 8; w++)
      for (int i = 0; i < 16; i++) {
        const int kidx = t + 4 * (i & 1) + 8 * (i >> 3), nidx = 4 * ((i >> 1) & 3) + (g >> 1);
        T.f2[w][i >> 2][l][i & 3] = cfrag_c((8 * kidx + w) * nidx, 128, g & 1);
        T.g2[w][i >> 2][l][i & 3] = cfrag_c(-(8 * nidx + w) * kidx, 128, g & 1);
      }
    T.fa[l][0] = pkb(fa_elem(g, 2 * t), fa_elem(g, 2 * t + 1));
    T.fa[l][1] = pkb(fa_elem(g + 8, 2 * t), fa_elem(g + 8, 2 * t + 1));
    T.fa[l][2] = pkb(fa_elem(g, 2 * t + 8), fa_elem(g, 2 * t + 9));
    T.fa[l][3] = pkb(fa_elem(g + 8, 2 * t + 8), fa_elem(g + 8, 2 * t + 9));
    T.ga[l][0] = pkb(fa_elem(2 * t, g), fa_elem(2 * t + 1, g));
    T.ga[l][1] = pkb(fa_elem(2 * t, g + 8), fa_elem(2 * t + 1, g + 8));
    T.ga[l][2] = pkb(fa_elem(2 * t + 8, g), fa_elem(2 * t + 9, g));
    T.ga[l][3] = pkb(fa_elem(2 * t + 8, g + 8), fa_elem(2 * t + 9, g + 8));
  }
  return T;
}
__device__ const __align__(128) Tables g_tab = make_tables();

__device__ __forceinline__ uint32_t s2u(const void* p) { return (uint32_t)__cvta_generic_to_shared(p); }
__device__ __forceinline__ void mbar_init(uint32_t b, int c) { asm volatile("mbarrier.init.shared::cta.b64 [%0], %1;" ::"r"(b), "r"(c)); }
__device__ __forceinline__ void mbar_expect(uint32_t b, int bytes) {
  asm volatile("mbarrier.arrive.expect_tx.shared::cta.b64 _, [%0], %1;" ::"r"(b), "r"(bytes) : "memory");
}
__device__ __forceinline__ void mbar_arrive(uint32_t b) { asm volatile("mbarrier.arrive.shared::cta.b64 _, [%0];" ::"r"(b) : "memory"); }
__device__ __forceinline__ uint32_t mbar_try(uint32_t b, uint32_t parity) {
  uint32_t ok;
  asm volatile("{.reg .pred p; mbarrier.try_wait.parity.shared::cta.b64 p, [%1], %2; selp.u32 %0,1,0,p;}"
               : "=r"(ok) : "r"(b), "r"(parity) : "memory");
  return ok;
}
__device__ __forceinline__ void mbar_wait(uint32_t b, uint32_t parity) {
  int it = 0;
  while (!mbar_try(b, parity))
    if (++it > SPIN_LIMIT) __trap();
}
__device__ __forceinline__ void mbar_wait_cluster(uint32_t b, int parity) {
  uint32_t ok;
  int it = 0;
  do {
    asm volatile("{.reg .pred p; mbarrier.try_wait.parity.acquire.cluster.shared::cta.b64 p, [%1], %2; selp.u32 %0,1,0,p;}"
                 : "=r"(ok) : "r"(b), "r"(parity) : "memory");
    if (++it > SPIN_LIMIT) __trap();
  } while (!ok);
}
__device__ __forceinline__ void bar_sync(int id, int n) { asm volatile("bar.sync %0, %1;" ::"r"(id), "r"(n) : "memory"); }
__device__ __forceinline__ void bar_arrive(int id, int n) { asm volatile("bar.arrive %0, %1;" ::"r"(id), "r"(n) : "memory"); }
__device__ __forceinline__ void red_release(unsigned* p) { asm volatile("red.release.gpu.global.add.u32 [%0], 1;" ::"l"(p) : "memory"); }
__device__ __forceinline__ unsigned ld_acquire(const unsigned* p) {
  unsigned v;
  asm volatile("ld.acquire.gpu.global.u32 %0, [%1];" : "=r"(v) : "l"(p) : "memory");
  return v;
}
__device__ __forceinline__ unsigned ld_relaxed(const unsigned* p) {
  unsigned v;
  asm volatile("ld.relaxed.gpu.global.u32 %0, [%1];" : "=r"(v) : "l"(p) : "memory");
  return v;
}
__device__ __forceinline__ void wait_counter(const unsigned* p, unsigned target) {
  int it = 0;
  while ((int)(ld_acquire(p) - target) < 0)
    if (++it > SPIN_LIMIT) __trap();
}
__device__ __forceinline__ uint4 ldg_cg4(const uint4* p) {
  uint4 v;
  asm volatile("ld.global.cg.v4.u32 {%0,%1,%2,%3}, [%4];" : "=r"(v.x), "=r"(v.y), "=r"(v.z), "=r"(v.w) : "l"(p) : "memory");
  return v;
}
__device__ __forceinline__ void sts4(uint32_t a, uint32_t x, uint32_t y, uint32_t z, uint32_t w) {
  asm volatile("st.shared.v4.u32 [%0], {%1,%2,%3,%4};" ::"r"(a), "r"(x), "r"(y), "r"(z), "r"(w) : "memory");
}
__device__ __forceinline__ uint4 lds4(uint32_t a) {
  uint4 v;
  asm volatile("ld.shared.v4.u32 {%0,%1,%2,%3}, [%4];" : "=r"(v.x), "=r"(v.y), "=r"(v.z), "=r"(v.w) : "r"(a) : "memory");
  return v;
}
__device__ __forceinline__ uint32_t pack2(float lo, float hi) {
  uint32_t r;
  asm("cvt.rn.bf16x2.f32 %0, %1, %2;" : "=r"(r) : "f"(hi), "f"(lo));
  return r;
}
__device__ __forceinline__ float bf_lo(uint32_t v) { return __uint_as_float(v << 16); }
__device__ __forceinline__ float bf_hi(uint32_t v) { return __uint_as_float(v & 0xffff0000u); }
__device__ __forceinline__ uint32_t hadd2_bf16(uint32_t a, uint32_t b) {
  uint32_t r;
  asm("add.rn.bf16x2 %0, %1, %2;" : "=r"(r) : "r"(a), "r"(b));
  return r;
}
__device__ __forceinline__ void mma16816(float (&d)[4], uint32_t a0, uint32_t a1, uint32_t a2, uint32_t a3, uint32_t b0, uint32_t b1) {
  asm("mma.sync.aligned.m16n8k16.row.col.f32.bf16.bf16.f32 {%0,%1,%2,%3}, {%4,%5,%6,%7}, {%8,%9}, {%0,%1,%2,%3};"
      : "+f"(d[0]), "+f"(d[1]), "+f"(d[2]), "+f"(d[3])
      : "r"(a0), "r"(a1), "r"(a2), "r"(a3), "r"(b0), "r"(b1));
}
template <int N>
__device__ __forceinline__ void cs_frac(int idx, float& c, float& s) {
  int i = ((idx + N / 2) & (N - 1)) - N / 2;
  float a = (float)i * (6.283185307179586f / N);
  c = __cosf(a);
  s = __sinf(a);
}
template <int N>
__device__ __forceinline__ uint32_t cfrag(int idx, int ri) {
  float c, s;
  cs_frac<N>(idx, c, s);
  return ri ? pack2(-s, c) : pack2(c, s);
}
__device__ __forceinline__ uint32_t word(const uint4& v, int e) { return e == 0 ? v.x : e == 1 ? v.y : e == 2 ? v.z : v.w; }
__device__ __forceinline__ void cdft16(const uint4 (&q)[4], const uint4 (&F)[4], uint4 (&o)[4]) {
  float acc[2][4][4];
#pragma unroll
  for (int p = 0; p < 2; p++)
#pragma unroll
    for (int v = 0; v < 4; v++) {
      acc[p][v][0] = acc[p][v][1] = acc[p][v][2] = acc[p][v][3] = 0.f;
#pragma unroll
      for (int ks = 0; ks < 2; ks++)
        mma16816(acc[p][v], word(q[2 * ks], 2 * p), word(q[2 * ks], 2 * p + 1), word(q[2 * ks + 1], 2 * p),
                 word(q[2 * ks + 1], 2 * p + 1), word(F[ks * 2 + (v >> 1)], (v & 1) * 2), word(F[ks * 2 + (v >> 1)], (v & 1) * 2 + 1));
    }
#pragma unroll
  for (int v = 0; v < 4; v++)
    o[v] = make_uint4(pack2(acc[0][v][0], acc[0][v][1]), pack2(acc[0][v][2], acc[0][v][3]),
                      pack2(acc[1][v][0], acc[1][v][1]), pack2(acc[1][v][2], acc[1][v][3]));
}
__device__ __forceinline__ float warp_sum(float v) {
#pragma unroll
  for (int o = 16; o > 0; o >>= 1) v += __shfl_xor_sync(0xffffffffu, v, o);
  return v;
}
__device__ __forceinline__ uint64_t desc64(uint32_t lo, uint32_t hi) {
  uint64_t d;
  asm("mov.b64 %0, {%1, %2};" : "=l"(d) : "r"(lo), "r"(hi));
  return d;
}
constexpr uint32_t desc_hi(uint32_t sbo, uint32_t swz) { return (sbo >> 4) | (swz << 30); }
__device__ __forceinline__ uint32_t desc_lo(uint32_t addr, uint32_t lbo) { return ((addr & 0x3FFFF) >> 4) | ((lbo >> 4) << 16); }
__device__ __forceinline__ void cp_async16(uint32_t dst, const void* src) {
  asm volatile("cp.async.cg.shared.global [%0], [%1], 16;" ::"r"(dst), "l"(src) : "memory");
}
__device__ __forceinline__ uint2 lds2(uint32_t a) {
  uint2 v;
  asm volatile("ld.shared.v2.u32 {%0,%1}, [%2];" : "=r"(v.x), "=r"(v.y) : "r"(a) : "memory");
  return v;
}
__device__ __forceinline__ uint32_t lds_u16(uint32_t a) {
  uint16_t v;
  asm volatile("ld.shared.u16 %0, [%1];" : "=h"(v) : "r"(a) : "memory");
  return v;
}
__device__ __forceinline__ void wg_fence() { asm volatile("wgmma.fence.sync.aligned;" ::: "memory"); }
__device__ __forceinline__ void wg_commit() { asm volatile("wgmma.commit_group.sync.aligned;" ::: "memory"); }
template <int N>
__device__ __forceinline__ void wg_wait() { asm volatile("wgmma.wait_group.sync.aligned %0;" ::"n"(N) : "memory"); }
__device__ __forceinline__ void bulk_load(uint32_t dst, const void* src, int bytes, uint32_t bar) {
  asm volatile("cp.async.bulk.shared::cluster.global.mbarrier::complete_tx::bytes [%0], [%1], %2, [%3];"
               ::"r"(dst), "l"(src), "r"(bytes), "r"(bar) : "memory");
}
__device__ __forceinline__ void tma3(uint32_t dst, const CUtensorMap* tm, uint32_t bar, int c0, int c1, int c2) {
  asm volatile("cp.async.bulk.tensor.3d.shared::cluster.global.mbarrier::complete_tx::bytes [%0], [%1, {%3,%4,%5}], [%2];"
               ::"r"(dst), "l"(tm), "r"(bar), "r"(c0), "r"(c1), "r"(c2) : "memory");
}
__device__ __forceinline__ void tma5(uint32_t dst, const CUtensorMap* tm, uint32_t bar, int c0, int c4) {
  asm volatile("cp.async.bulk.tensor.5d.shared::cluster.global.mbarrier::complete_tx::bytes [%0], [%1, {%3,%4,%4,%4,%5}], [%2];"
               ::"r"(dst), "l"(tm), "r"(bar), "r"(c0), "r"(0), "r"(c4) : "memory");
}
__device__ __forceinline__ float swiglu(float g, float u) {
  float hg = 0.5f * g, th;
  asm("tanh.approx.f32 %0, %1;" : "=f"(th) : "f"(hg));
  return fmaf(hg, th, hg) * u;
}

__device__ __forceinline__ void wgmma_n256(float (&d)[128], uint64_t da, uint64_t db) {
  asm volatile("wgmma.mma_async.sync.aligned.m64n256k16.f32.bf16.bf16 {"
      "%0,%1,%2,%3,%4,%5,%6,%7,%8,%9,%10,%11,%12,%13,%14,%15,"
      "%16,%17,%18,%19,%20,%21,%22,%23,%24,%25,%26,%27,%28,%29,%30,%31,"
      "%32,%33,%34,%35,%36,%37,%38,%39,%40,%41,%42,%43,%44,%45,%46,%47,"
      "%48,%49,%50,%51,%52,%53,%54,%55,%56,%57,%58,%59,%60,%61,%62,%63,"
      "%64,%65,%66,%67,%68,%69,%70,%71,%72,%73,%74,%75,%76,%77,%78,%79,"
      "%80,%81,%82,%83,%84,%85,%86,%87,%88,%89,%90,%91,%92,%93,%94,%95,"
      "%96,%97,%98,%99,%100,%101,%102,%103,%104,%105,%106,%107,%108,%109,%110,%111,"
      "%112,%113,%114,%115,%116,%117,%118,%119,%120,%121,%122,%123,%124,%125,%126,%127"
      "}, %128, %129, 1, 1, 1, 0, 1;\n"
      : "+f"(d[0]),"+f"(d[1]),"+f"(d[2]),"+f"(d[3]),"+f"(d[4]),"+f"(d[5]),"+f"(d[6]),"+f"(d[7]),
        "+f"(d[8]),"+f"(d[9]),"+f"(d[10]),"+f"(d[11]),"+f"(d[12]),"+f"(d[13]),"+f"(d[14]),"+f"(d[15]),
        "+f"(d[16]),"+f"(d[17]),"+f"(d[18]),"+f"(d[19]),"+f"(d[20]),"+f"(d[21]),"+f"(d[22]),"+f"(d[23]),
        "+f"(d[24]),"+f"(d[25]),"+f"(d[26]),"+f"(d[27]),"+f"(d[28]),"+f"(d[29]),"+f"(d[30]),"+f"(d[31]),
        "+f"(d[32]),"+f"(d[33]),"+f"(d[34]),"+f"(d[35]),"+f"(d[36]),"+f"(d[37]),"+f"(d[38]),"+f"(d[39]),
        "+f"(d[40]),"+f"(d[41]),"+f"(d[42]),"+f"(d[43]),"+f"(d[44]),"+f"(d[45]),"+f"(d[46]),"+f"(d[47]),
        "+f"(d[48]),"+f"(d[49]),"+f"(d[50]),"+f"(d[51]),"+f"(d[52]),"+f"(d[53]),"+f"(d[54]),"+f"(d[55]),
        "+f"(d[56]),"+f"(d[57]),"+f"(d[58]),"+f"(d[59]),"+f"(d[60]),"+f"(d[61]),"+f"(d[62]),"+f"(d[63]),
        "+f"(d[64]),"+f"(d[65]),"+f"(d[66]),"+f"(d[67]),"+f"(d[68]),"+f"(d[69]),"+f"(d[70]),"+f"(d[71]),
        "+f"(d[72]),"+f"(d[73]),"+f"(d[74]),"+f"(d[75]),"+f"(d[76]),"+f"(d[77]),"+f"(d[78]),"+f"(d[79]),
        "+f"(d[80]),"+f"(d[81]),"+f"(d[82]),"+f"(d[83]),"+f"(d[84]),"+f"(d[85]),"+f"(d[86]),"+f"(d[87]),
        "+f"(d[88]),"+f"(d[89]),"+f"(d[90]),"+f"(d[91]),"+f"(d[92]),"+f"(d[93]),"+f"(d[94]),"+f"(d[95]),
        "+f"(d[96]),"+f"(d[97]),"+f"(d[98]),"+f"(d[99]),"+f"(d[100]),"+f"(d[101]),"+f"(d[102]),"+f"(d[103]),
        "+f"(d[104]),"+f"(d[105]),"+f"(d[106]),"+f"(d[107]),"+f"(d[108]),"+f"(d[109]),"+f"(d[110]),"+f"(d[111]),
        "+f"(d[112]),"+f"(d[113]),"+f"(d[114]),"+f"(d[115]),"+f"(d[116]),"+f"(d[117]),"+f"(d[118]),"+f"(d[119]),
        "+f"(d[120]),"+f"(d[121]),"+f"(d[122]),"+f"(d[123]),"+f"(d[124]),"+f"(d[125]),"+f"(d[126]),"+f"(d[127])
      : "l"(da), "l"(db));
}
__device__ __forceinline__ void wgmma_n192(float (&d)[96], uint64_t da, uint64_t db) {
  asm volatile("wgmma.mma_async.sync.aligned.m64n192k16.f32.bf16.bf16 {"
      "%0,%1,%2,%3,%4,%5,%6,%7,%8,%9,%10,%11,%12,%13,%14,%15,"
      "%16,%17,%18,%19,%20,%21,%22,%23,%24,%25,%26,%27,%28,%29,%30,%31,"
      "%32,%33,%34,%35,%36,%37,%38,%39,%40,%41,%42,%43,%44,%45,%46,%47,"
      "%48,%49,%50,%51,%52,%53,%54,%55,%56,%57,%58,%59,%60,%61,%62,%63,"
      "%64,%65,%66,%67,%68,%69,%70,%71,%72,%73,%74,%75,%76,%77,%78,%79,"
      "%80,%81,%82,%83,%84,%85,%86,%87,%88,%89,%90,%91,%92,%93,%94,%95"
      "}, %96, %97, 1, 1, 1, 0, 1;\n"
      : "+f"(d[0]),"+f"(d[1]),"+f"(d[2]),"+f"(d[3]),"+f"(d[4]),"+f"(d[5]),"+f"(d[6]),"+f"(d[7]),
        "+f"(d[8]),"+f"(d[9]),"+f"(d[10]),"+f"(d[11]),"+f"(d[12]),"+f"(d[13]),"+f"(d[14]),"+f"(d[15]),
        "+f"(d[16]),"+f"(d[17]),"+f"(d[18]),"+f"(d[19]),"+f"(d[20]),"+f"(d[21]),"+f"(d[22]),"+f"(d[23]),
        "+f"(d[24]),"+f"(d[25]),"+f"(d[26]),"+f"(d[27]),"+f"(d[28]),"+f"(d[29]),"+f"(d[30]),"+f"(d[31]),
        "+f"(d[32]),"+f"(d[33]),"+f"(d[34]),"+f"(d[35]),"+f"(d[36]),"+f"(d[37]),"+f"(d[38]),"+f"(d[39]),
        "+f"(d[40]),"+f"(d[41]),"+f"(d[42]),"+f"(d[43]),"+f"(d[44]),"+f"(d[45]),"+f"(d[46]),"+f"(d[47]),
        "+f"(d[48]),"+f"(d[49]),"+f"(d[50]),"+f"(d[51]),"+f"(d[52]),"+f"(d[53]),"+f"(d[54]),"+f"(d[55]),
        "+f"(d[56]),"+f"(d[57]),"+f"(d[58]),"+f"(d[59]),"+f"(d[60]),"+f"(d[61]),"+f"(d[62]),"+f"(d[63]),
        "+f"(d[64]),"+f"(d[65]),"+f"(d[66]),"+f"(d[67]),"+f"(d[68]),"+f"(d[69]),"+f"(d[70]),"+f"(d[71]),
        "+f"(d[72]),"+f"(d[73]),"+f"(d[74]),"+f"(d[75]),"+f"(d[76]),"+f"(d[77]),"+f"(d[78]),"+f"(d[79]),
        "+f"(d[80]),"+f"(d[81]),"+f"(d[82]),"+f"(d[83]),"+f"(d[84]),"+f"(d[85]),"+f"(d[86]),"+f"(d[87]),
        "+f"(d[88]),"+f"(d[89]),"+f"(d[90]),"+f"(d[91]),"+f"(d[92]),"+f"(d[93]),"+f"(d[94]),"+f"(d[95])
      : "l"(da), "l"(db));
}
__device__ __forceinline__ void wgmma_n128(float (&d)[64], uint64_t da, uint64_t db) {
  asm volatile("wgmma.mma_async.sync.aligned.m64n128k16.f32.bf16.bf16 {"
      "%0,%1,%2,%3,%4,%5,%6,%7,%8,%9,%10,%11,%12,%13,%14,%15,"
      "%16,%17,%18,%19,%20,%21,%22,%23,%24,%25,%26,%27,%28,%29,%30,%31,"
      "%32,%33,%34,%35,%36,%37,%38,%39,%40,%41,%42,%43,%44,%45,%46,%47,"
      "%48,%49,%50,%51,%52,%53,%54,%55,%56,%57,%58,%59,%60,%61,%62,%63"
      "}, %64, %65, 1, 1, 1, 0, 1;\n"
      : "+f"(d[0]),"+f"(d[1]),"+f"(d[2]),"+f"(d[3]),"+f"(d[4]),"+f"(d[5]),"+f"(d[6]),"+f"(d[7]),
        "+f"(d[8]),"+f"(d[9]),"+f"(d[10]),"+f"(d[11]),"+f"(d[12]),"+f"(d[13]),"+f"(d[14]),"+f"(d[15]),
        "+f"(d[16]),"+f"(d[17]),"+f"(d[18]),"+f"(d[19]),"+f"(d[20]),"+f"(d[21]),"+f"(d[22]),"+f"(d[23]),
        "+f"(d[24]),"+f"(d[25]),"+f"(d[26]),"+f"(d[27]),"+f"(d[28]),"+f"(d[29]),"+f"(d[30]),"+f"(d[31]),
        "+f"(d[32]),"+f"(d[33]),"+f"(d[34]),"+f"(d[35]),"+f"(d[36]),"+f"(d[37]),"+f"(d[38]),"+f"(d[39]),
        "+f"(d[40]),"+f"(d[41]),"+f"(d[42]),"+f"(d[43]),"+f"(d[44]),"+f"(d[45]),"+f"(d[46]),"+f"(d[47]),
        "+f"(d[48]),"+f"(d[49]),"+f"(d[50]),"+f"(d[51]),"+f"(d[52]),"+f"(d[53]),"+f"(d[54]),"+f"(d[55]),
        "+f"(d[56]),"+f"(d[57]),"+f"(d[58]),"+f"(d[59]),"+f"(d[60]),"+f"(d[61]),"+f"(d[62]),"+f"(d[63])
      : "l"(da), "l"(db));
}

constexpr int C_BAR1 = 0, C_BAR2 = 1, C_LN = 2, C_PX = 18, C_PY = 34;
constexpr int NB_CONS = 1, NB_LN = 2, NB_PUB0 = 3, NB_LAG = 5, NB_INIT = 6;
#define LAG 2
constexpr int SM_E = 0, SM_E2 = 16384, SM_X = 32768, SM_W = 49152, SM_FC = 69632, SM_T = 73728;

constexpr unsigned long long KORDER = 0xBA9432DC876510ull;
constexpr uint32_t HI128 = desc_hi(1024, 1), HI64 = desc_hi(512, 2), HI0 = desc_hi(1024, 0);

struct Bars {
  uint64_t full1[6], empty1[6], fullA[8], full2[14], empty2[8], xbar, xfree, tbar;
};

template <int NT>
__device__ __forceinline__ void store_p(const float (&acc)[NT * 32], uint4* pbase, int G0, int lane_off) {
#pragma unroll
  for (int q = 0; q < NT; q++) {
    const int G = G0 + q;
    uint4* dst = pbase + (G >> 1) * 1024 + (G & 1) * 32 + lane_off;
#pragma unroll
    for (int h = 0; h < 2; h++) {
      uint32_t w[4];
#pragma unroll
      for (int i = 0; i < 4; i++) {
        const int a = (q * 4 + i) * 4 + 2 * h, b = a + NT * 16;
        w[i] = pack2(swiglu(acc[a], acc[b]), swiglu(acc[a + 1], acc[b + 1]));
      }
      dst[h * 64] = make_uint4(w[0], w[1], w[2], w[3]);
    }
  }
}

__global__ void __cluster_dims__(2, 1, 1) __launch_bounds__(NTHREADS, 1)
fused_kernel(const __grid_constant__ CUtensorMap tmGX, const __grid_constant__ CUtensorMap tmUX,
             const __grid_constant__ CUtensorMap tmGY, const __grid_constant__ CUtensorMap tmUY,
             const __grid_constant__ CUtensorMap tmD,
             const __nv_bfloat16* __restrict__ x, const __nv_bfloat16* __restrict__ wr, const __nv_bfloat16* __restrict__ wi,
             const char* __restrict__ wg_raw, const char* __restrict__ wu_raw, const char* __restrict__ wd_raw,
             __nv_bfloat16* __restrict__ out) {
  extern __shared__ __align__(1024) char smem_raw[];
  const uint32_t sbase = (s2u(smem_raw) + 1023) & ~1023u;
  const uint32_t sbar = sbase + 14 * SLOT;
  const int tid = threadIdx.x, lane = tid & 31;
  const int c = blockIdx.x, rb = c >> 3, f = c & 7;
#define BAR(field, i) (sbar + (uint32_t)offsetof(Bars, field) + 8u * (i))
#define TOFF(field) (sbase + SM_T + (uint32_t)offsetof(Tables, field) + lane * 16)

  if (tid >= 256) {
    asm volatile("setmaxnreg.dec.sync.aligned.u32 56;");
    const int warp = __shfl_sync(0xffffffffu, tid >> 5, 0);
    if (tid == 256) {
      for (int i = 0; i < 6; i++) { mbar_init(BAR(full1, i), 1); mbar_init(BAR(empty1, i), 8); }
      for (int i = 0; i < 8; i++) { mbar_init(BAR(fullA, i), 1); mbar_init(BAR(empty2, i), 8); }
      for (int i = 0; i < 14; i++) mbar_init(BAR(full2, i), 2);
      mbar_init(BAR(xbar, 0), 1);
      mbar_init(BAR(xfree, 0), 8);
      mbar_init(BAR(tbar, 0), 129);
      mbar_expect(BAR(xbar, 0), 32768);
      asm volatile("fence.mbarrier_init.release.cluster;" ::: "memory");
    }
    __syncwarp();
    asm volatile("barrier.cluster.arrive.relaxed.aligned;" ::: "memory");
    unsigned epoch = 0;
    if (tid == 320) epoch = ld_relaxed(&g_cnt[(C_LN + rb) * 32]) >> 3;
    bar_sync(NB_INIT, 384);
    {
      const int wsh = (2 * (c >> 3) + 2) & 15;
#pragma unroll
      for (int i = 0; i < 10; i++) {
        const int idx = tid - 256 + 128 * i, ra = idx / 5, ch = idx - 5 * ra, j2 = ra & 127;
        const char* src = reinterpret_cast<const char*>(ra >= 128 ? wi : wr) + ((c >> 3) + 16 * j2) * 514 + 64 * (c & 7) + 2 - wsh + 16 * ch;
        if (ch < 4 || wsh != 0) cp_async16(sbase + SM_W + ((ra & 128) + (j2 & 15) * 8 + (j2 >> 4)) * 80 + ch * 16, src);
      }
      asm volatile("cp.async.mbarrier.arrive.noinc.shared::cta.b64 [%0];" ::"r"(BAR(tbar, 0)) : "memory");
    }
    const int nq = f >> 1, kh = f & 1;
    if (warp <= 9) {
      if (lane == 0) {
        const int ax = (7 * f + 3 * (f & 1)) >> 1;
        const int ay = 7 * f + ((f & 1) ? 0 : 4);
        uint32_t s = warp - 8, ph = 1;
#pragma unroll 1
        for (int n = warp - 8; n < (warp == 8 ? 32 : 38); n += 2) {
          const uint32_t dst = sbase + (8 + s) * SLOT, fb = BAR(full1, s);
          mbar_wait(BAR(empty1, s), ph);
          if (n < 16) {
            mbar_expect(fb, 16384);
            tma3(dst, &tmGX, fb, 0, n * 32, ax);
            tma3(dst + 8192, &tmUX, fb, 0, n * 32, ax);
          } else if (n < 32) {
            mbar_expect(fb, 12288);
            tma3(dst, &tmGY, fb, 0, (n - 16) * 32, ay);
            tma3(dst + 6144, &tmUY, fb, 0, (n - 16) * 32, ay);
          }
          if (n >= 23 && warp == 9) {
            const int i = (n - 23) >> 1, kblk = 14 * kh + (int)((KORDER >> (4 * i)) & 15);
            mbar_expect(BAR(full2, i), 16384);
            tma5(sbase + i * SLOT, &tmD, BAR(full2, i), nq * 128, 2 * kblk);
            tma5(sbase + i * SLOT + 8192, &tmD, BAR(full2, i), nq * 128 + 64, 2 * kblk);
          }
          s += 2;
          if (s >= 6) { s -= 6; ph ^= 1; }
        }
        if (warp == 9) {
#pragma unroll 1
          for (int i = 8; i < 14; i++) {
            const int kblk = 14 * kh + (int)((KORDER >> (4 * i)) & 15);
            mbar_wait(BAR(empty2, i - 8), 0);
            mbar_expect(BAR(full2, i), 16384);
            tma5(sbase + (i - 8) * SLOT, &tmD, BAR(full2, i), nq * 128, 2 * kblk);
            tma5(sbase + (i - 8) * SLOT + 8192, &tmD, BAR(full2, i), nq * 128 + 64, 2 * kblk);
          }
        }
      }
    } else if (warp == 10) {
      if (lane == 0) {
        mbar_expect(BAR(tbar, 0), T2_BYTES);
        bulk_load(sbase + SM_T + T1_BYTES, reinterpret_cast<const char*>(&g_tab) + T1_BYTES, T2_BYTES, BAR(tbar, 0));
      }
      bar_sync(NB_LN, 288);
      if (lane == 0) {
        PROFP(0);
        red_release(&g_cnt[(C_LN + rb) * 32]);
        PROFP(1);
        wait_counter(&g_cnt[(C_LN + rb) * 32], (epoch + 1) * 8);
        asm volatile("fence.proxy.async.global;" ::: "memory");
        PROFP(2);
#pragma unroll 1
        for (int kb = 0; kb < 8; kb++) {
          mbar_expect(BAR(fullA, kb), 16384);
          bulk_load(sbase + kb * SLOT, &g_LN[(rb * 8 + kb) * 1024], 16384, BAR(fullA, kb));
        }
#pragma unroll 1
        for (int i = 0; i < 4; i++) mbar_wait(BAR(empty1, 2), i & 1);
        uint32_t d = 2;
#pragma unroll 1
        for (int s = 0; s < 14; s++) {
          const int kblk = 14 * kh + (int)((KORDER >> (4 * s)) & 15);
          if (s == 0 || s == 8) {
            PROFP(3 + (s >> 2));
            wait_counter(&g_cnt[((s == 0 ? C_PX : C_PY) + rb) * 32], (epoch + 1) * 16);
            asm volatile("fence.proxy.async.global;" ::: "memory");
            PROFP(4 + (s >> 2));
          }
          if (s < 6) mbar_wait(BAR(empty1, d), s < 4 ? 0 : 1);
          else mbar_wait(BAR(empty2, s - 6), 0);
          mbar_expect(BAR(full2, s), 16384);
          bulk_load(sbase + (8 + d) * SLOT, &g_P[(rb * 28 + kblk) * 1024], 16384, BAR(full2, s));
          if (++d == 6) d = 0;
        }
        PROFP(7);
      }
    } else {
      if (lane == 0) {
        asm volatile("cp.async.bulk.prefetch.L2.global [%0], %1;" ::"l"(wg_raw + (size_t)c * 14336), "r"(14336) : "memory");
        asm volatile("cp.async.bulk.prefetch.L2.global [%0], %1;" ::"l"(wu_raw + (size_t)c * 14336), "r"(14336) : "memory");
        asm volatile("cp.async.bulk.prefetch.L2.global [%0], %1;" ::"l"(wd_raw + (size_t)c * 14336), "r"(14336) : "memory");
      }
#pragma unroll 1
      for (int e = 0; e < 4; e++) {
        bar_sync(NB_PUB0 + (e & 1), 160);
        if (lane == 0) red_release(&g_cnt[((e < 2 ? C_PX : C_PY) + rb) * 32]);
      }
    }
    __syncwarp();
    asm volatile("barrier.cluster.wait.aligned;" ::: "memory");
  } else {
    const int warp = __shfl_sync(0xffffffffu, tid >> 5, 0);
    const int g = lane >> 2, t = lane & 3;
    PROF(0);
    PROFG(14);
#pragma unroll
    for (int i = 0; i < 4; i++) {
      const int r = i >> 1, ch = (i & 1) * 32 + lane;
      cp_async16(sbase + SM_X + (2 * warp + r) * 1024 + ((ch ^ ((ch >> 2) & 6)) * 16),
                 x + (size_t)(c + 128 * (2 * warp + r)) * 512 + ch * 8);
    }
#pragma unroll
    for (int i = 0; i < 3; i++)
      cp_async16(sbase + SM_T + (tid + 256 * i) * 16, reinterpret_cast<const char*>(&g_tab) + (tid + 256 * i) * 16);
    asm volatile("cp.async.commit_group;" ::: "memory");
    const int wsh = (2 * (c >> 3) + 2) & 15;
    asm volatile("barrier.cluster.arrive.relaxed.aligned;" ::: "memory");
    asm volatile("setmaxnreg.inc.sync.aligned.u32 224;");
    unsigned epoch = 0;
    if (tid == 0) epoch = ld_relaxed(&g_cnt[C_BAR1 * 32]) >> 7;
    {
      const int ln = (tid >> 1) & 31, lg = ln >> 2, lt = ln & 3, i = 4 * (tid >> 6) + 2 * (tid & 1);
      const int kidx = lt + 8 * (i >> 3), nidx = 4 * ((i >> 1) & 3) + (lg >> 1);
      const uint32_t a0 = cfrag<2048>((c + 128 * kidx) * nidx, lg & 1), a1 = cfrag<2048>((c + 128 * (kidx + 4)) * nidx, lg & 1);
      const uint32_t b0 = cfrag<2048>(-(c + 128 * nidx) * kidx, lg & 1), b1 = cfrag<2048>(-(c + 128 * nidx) * (kidx + 4), lg & 1);
      asm volatile("st.shared.v2.u32 [%0], {%1,%2};" ::"r"(sbase + SM_FC + tid * 8), "r"(a0), "r"(a1) : "memory");
      asm volatile("st.shared.v2.u32 [%0], {%1,%2};" ::"r"(sbase + SM_FC + 2048 + tid * 8), "r"(b0), "r"(b1) : "memory");
    }
    asm volatile("cp.async.wait_group 0;" ::: "memory");
    bar_sync(NB_INIT, 384);
    PROF(13);
    {
      uint2 v[2][4];
#pragma unroll
      for (int r = 0; r < 2; r++)
#pragma unroll
        for (int q = 0; q < 4; q++)
          v[r][q] = lds2(sbase + SM_X + (2 * warp + r) * 1024 + (t + 4 * (q >> 1)) * 128 + (((4 * (q & 1) + (g >> 1)) ^ (2 * t)) * 16) + (g & 1) * 8);
      const uint4 fa = lds4(TOFF(fa));
      uint4 tw[4], fb[16];
#pragma unroll
      for (int i = 0; i < 4; i++) tw[i] = lds4(TOFF(tw1) + i * 512);
#pragma unroll
      for (int i = 0; i < 16; i++) fb[i] = lds4(TOFF(fb) + i * 512);
      float mean[2], rstd[2];
#pragma unroll
      for (int r = 0; r < 2; r++) {
        float s = 0.f;
#pragma unroll
        for (int q = 0; q < 4; q++) s += (bf_lo(v[r][q].x) + bf_hi(v[r][q].x)) + (bf_lo(v[r][q].y) + bf_hi(v[r][q].y));
        mean[r] = warp_sum(s) * (1.f / 512.f);
      }
#pragma unroll
      for (int r = 0; r < 2; r++) {
        float s = 0.f;
#pragma unroll
        for (int q = 0; q < 4; q++) {
          float a0 = bf_lo(v[r][q].x) - mean[r], a1 = bf_hi(v[r][q].x) - mean[r];
          float a2 = bf_lo(v[r][q].y) - mean[r], a3 = bf_hi(v[r][q].y) - mean[r];
          s += (a0 * a0 + a1 * a1) + (a2 * a2 + a3 * a3);
        }
        rstd[r] = rsqrtf(warp_sum(s) * (1.f / 512.f) + 1e-5f);
      }
      uint32_t alo[4][4], ahi[4][4];
#pragma unroll
      for (int r = 0; r < 2; r++)
#pragma unroll
        for (int i = 0; i < 4; i++) {
          const uint32_t sel = (i & 1) ? 0x7632u : 0x5410u;
          const uint32_t b0 = __byte_perm((i & 2) ? v[r][0].y : v[r][0].x, (i & 2) ? v[r][1].y : v[r][1].x, sel);
          const uint32_t b1 = __byte_perm((i & 2) ? v[r][2].y : v[r][2].x, (i & 2) ? v[r][3].y : v[r][3].x, sel);
          float d[4] = {0.f, 0.f, 0.f, 0.f};
          mma16816(d, fa.x, fa.y, fa.z, fa.w, b0, b1);
          const float ca = __uint_as_float(tw[i].x), sa = __uint_as_float(tw[i].y), cb = __uint_as_float(tw[i].z), sb = __uint_as_float(tw[i].w);
          const float a0 = g == 0 ? d[2] : d[0], a1 = g == 0 ? d[3] : d[1];
          const float i0 = g == 0 ? 0.f : d[2], i1 = g == 0 ? 0.f : d[3];
          const uint32_t re = pack2(a0 * ca + i0 * sa, a1 * cb + i1 * sb);
          const uint32_t im = pack2(i0 * ca - a0 * sa, i1 * cb - a1 * sb);
          const uint32_t dc = pack2(d[0] - 16.f * mean[r], d[1] - 16.f * mean[r]);
          alo[i][r] = re; alo[i][2 + r] = im;
          ahi[i][r] = g == 0 ? dc : re; ahi[i][2 + r] = g == 0 ? 0u : im;
        }
      float acc[8][4];
#pragma unroll
      for (int u = 0; u < 8; u++) {
        acc[u][0] = acc[u][1] = acc[u][2] = acc[u][3] = 0.f;
#pragma unroll
        for (int i = 0; i < 4; i++) {
          const uint4& bq = fb[i * 4 + (u >> 1)];
          if (u < 4) mma16816(acc[u], alo[i][0], alo[i][1], alo[i][2], alo[i][3], (u & 1) ? bq.z : bq.x, (u & 1) ? bq.w : bq.y);
          else       mma16816(acc[u], ahi[i][0], ahi[i][1], ahi[i][2], ahi[i][3], (u & 1) ? bq.z : bq.x, (u & 1) ? bq.w : bq.y);
        }
      }
      uint4 fc[4];
#pragma unroll
      for (int i = 0; i < 4; i++) fc[i] = lds4(sbase + SM_FC + i * 512 + lane * 16);
#pragma unroll
      for (int r = 0; r < 2; r++)
#pragma unroll
        for (int h = 0; h < 2; h++) {
          const int j = 2 * warp + r, m = 2 * t + h;
          const float rs = rstd[r];
          sts4(sbase + SM_E + ((j * 8 + m) * 8 + (g ^ (2 * t) ^ (2 * (j & 3)))) * 16,
               pack2(acc[2 * h][2 * r] * rs, acc[2 * h][2 * r + 1] * rs), pack2(acc[2 * h + 1][2 * r] * rs, acc[2 * h + 1][2 * r + 1] * rs),
               pack2(acc[4 + 2 * h][2 * r] * rs, acc[4 + 2 * h][2 * r + 1] * rs), pack2(acc[5 + 2 * h][2 * r] * rs, acc[5 + 2 * h][2 * r + 1] * rs));
        }
      bar_sync(NB_CONS, 256);
      uint4 q[4], o[4];
#pragma unroll
      for (int i = 0; i < 4; i++) q[i] = lds4(sbase + SM_E + (((t + 4 * i) * 8 + warp) * 8 + (g ^ (warp & 6) ^ (2 * t))) * 16);
      cdft16(q, fc, o);
#pragma unroll
      for (int vv = 0; vv < 4; vv++) g_Z1[(((4 * vv + t) * 8 + warp) * 128 + c) * 8 + g] = o[vv];
    }
    PROF(1);
    bar_sync(NB_CONS, 256);
    if (tid == 0) red_release(&g_cnt[C_BAR1 * 32]);
    {
      mbar_wait(BAR(tbar, 0), 0);
      uint4 f2[4], g2[4];
#pragma unroll
      for (int i = 0; i < 4; i++) {
        f2[i] = lds4(TOFF(f2) + warp * 2048 + i * 512);
        g2[i] = lds4(TOFF(g2) + warp * 2048 + i * 512);
      }
      const uint4 f8 = lds4(TOFF(f8)), g8 = lds4(TOFF(g8));
      float wfr[16], wfi[16];
      {
        const float fsc = 1.f / (1 << 19);
        const float fsc3 = ((c & 7) == 7 && g == 0) ? 0.5f * fsc : fsc;
        const int gg = g == 0 ? 8 : g;
#pragma unroll
        for (int i = 0; i < 16; i++) {
          const int ci = i >> 3, dd = (i >> 2) & 1, e = i & 3;
          const int kk = (e == 0 ? gg : e == 1 ? 16 + gg : e == 2 ? 16 - g : 32 - g) - 1;
          const uint32_t a = sbase + SM_W + ((2 * warp + ci) * 8 + t + 4 * dd) * 80 + wsh + 2 * kk;
          wfr[i] = bf_lo(lds_u16(a)) * (e == 3 ? fsc3 : fsc);
          wfi[i] = bf_lo(lds_u16(a + 128 * 80)) * (e == 3 ? fsc3 : fsc);
        }
      }
      asm volatile("barrier.cluster.wait.aligned;" ::: "memory");
      if (tid == 0) wait_counter(&g_cnt[C_BAR1 * 32], (epoch + 1) * 128);
      bar_sync(NB_CONS, 256);
      PROF(2);
      uint4 q[4], o[4];
#pragma unroll
      for (int i = 0; i < 4; i++) q[i] = ldg_cg4(&g_Z1[(c * 128 + 8 * (t + 4 * i) + warp) * 8 + g]);
      cdft16(q, f2, o);
      const uint32_t e2 = sbase + SM_E2;
#pragma unroll
      for (int vv = 0; vv < 4; vv++)
        sts4(e2 + ((warp * 16 + 4 * vv + t) * 8 + (g ^ (2 * t) ^ (2 * (warp & 3)))) * 16, o[vv].x, o[vv].y, o[vv].z, o[vv].w);
      bar_sync(NB_CONS, 256);
#pragma unroll
      for (int ci = 0; ci < 2; ci++) {
        const int cc = 2 * warp + ci;
        uint32_t ad[2];
        uint4 u[2];
#pragma unroll
        for (int hh = 0; hh < 2; hh++) {
          ad[hh] = e2 + (((t + 4 * hh) * 16 + cc) * 8 + (g ^ (2 * (cc & 3)) ^ (2 * t))) * 16;
          u[hh] = lds4(ad[hh]);
        }
        uint32_t res[2][4];
#pragma unroll
        for (int p = 0; p < 2; p++) {
          uint32_t y[2][2];
#pragma unroll
          for (int vv = 0; vv < 2; vv++) {
            float d[4] = {0.f, 0.f, 0.f, 0.f};
            mma16816(d, word(u[0], 2 * p), word(u[0], 2 * p + 1), word(u[1], 2 * p), word(u[1], 2 * p + 1), word(f8, 2 * vv), word(f8, 2 * vv + 1));
#pragma unroll
            for (int rr = 0; rr < 2; rr++) {
              const float fr = wfr[ci * 8 + vv * 4 + 2 * p + rr], fi = wfi[ci * 8 + vv * 4 + 2 * p + rr];
              y[vv][rr] = pack2(d[2 * rr] * fr - d[2 * rr + 1] * fi, d[2 * rr] * fi + d[2 * rr + 1] * fr);
            }
          }
#pragma unroll
          for (int vv = 0; vv < 2; vv++) {
            float d[4] = {0.f, 0.f, 0.f, 0.f};
            mma16816(d, y[0][0], y[0][1], y[1][0], y[1][1], word(g8, 2 * vv), word(g8, 2 * vv + 1));
            res[vv][2 * p] = pack2(d[0], d[1]);
            res[vv][2 * p + 1] = pack2(d[2], d[3]);
          }
        }
#pragma unroll
        for (int vv = 0; vv < 2; vv++) sts4(ad[vv], res[vv][0], res[vv][1], res[vv][2], res[vv][3]);
      }
      bar_sync(NB_CONS, 256);
#pragma unroll
      for (int i = 0; i < 4; i++) q[i] = lds4(e2 + ((warp * 16 + 4 * i + t) * 8 + (g ^ (2 * t) ^ (2 * (warp & 3)))) * 16);
      cdft16(q, g2, o);
#pragma unroll
      for (int vv = 0; vv < 4; vv++) g_Z2[((8 * (4 * vv + t) + warp) * 128 + c) * 8 + g] = o[vv];
    }
    PROF(3);
    bar_sync(NB_CONS, 256);
    if (tid == 0) red_release(&g_cnt[C_BAR2 * 32]);
    uint32_t hv[2][2][4];
    {
      uint4 gb[16], gc[4], tw[4], xr[2][2];
#pragma unroll
      for (int i = 0; i < 16; i++) gb[i] = lds4(TOFF(gb) + i * 512);
      const uint4 ga = lds4(TOFF(ga));
#pragma unroll
      for (int i = 0; i < 4; i++) {
        gc[i] = lds4(sbase + SM_FC + 2048 + i * 512 + lane * 16);
        tw[i] = lds4(TOFF(tw3) + i * 512);
        const int ch = 4 * (g + 8 * (i & 1)) + t;
        xr[i >> 1][i & 1] = lds4(sbase + SM_X + (2 * warp + (i >> 1)) * 1024 + ((ch ^ ((ch >> 2) & 6)) * 16));
      }
      if (tid == 0) wait_counter(&g_cnt[C_BAR2 * 32], (epoch + 1) * 128);
      bar_sync(NB_CONS, 256);
      PROF(4);
      uint4 q[4], o[4];
#pragma unroll
      for (int i = 0; i < 4; i++) q[i] = ldg_cg4(&g_Z2[((c * 16 + t + 4 * i) * 8 + warp) * 8 + g]);
      cdft16(q, gc, o);
#pragma unroll
      for (int vv = 0; vv < 4; vv++)
        sts4(sbase + SM_E + (((4 * vv + t) * 8 + warp) * 8 + (g ^ (warp & 6) ^ (2 * t))) * 16, o[vv].x, o[vv].y, o[vv].z, o[vv].w);
      bar_sync(NB_CONS, 256);
#pragma unroll
      for (int r = 0; r < 2; r++) {
        const int j = 2 * warp + r;
        uint4 u[2];
#pragma unroll
        for (int h = 0; h < 2; h++) u[h] = lds4(sbase + SM_E + ((j * 8 + 2 * t + h) * 8 + (g ^ (2 * t) ^ (2 * (j & 3)))) * 16);
        float yv[4][4];
#pragma unroll
        for (int i = 0; i < 4; i++) {
          float lo[4] = {0.f, 0.f, 0.f, 0.f}, hi[4] = {0.f, 0.f, 0.f, 0.f};
          mma16816(lo, gb[i * 4].x, gb[i * 4].y, gb[i * 4].z, gb[i * 4].w, u[0].x, u[0].y);
          mma16816(lo, gb[i * 4 + 1].x, gb[i * 4 + 1].y, gb[i * 4 + 1].z, gb[i * 4 + 1].w, u[1].x, u[1].y);
          mma16816(hi, gb[i * 4 + 2].x, gb[i * 4 + 2].y, gb[i * 4 + 2].z, gb[i * 4 + 2].w, u[0].z, u[0].w);
          mma16816(hi, gb[i * 4 + 3].x, gb[i * 4 + 3].y, gb[i * 4 + 3].z, gb[i * 4 + 3].w, u[1].z, u[1].w);
          const float ca = __uint_as_float(tw[i].x), sa = __uint_as_float(tw[i].y), cb = __uint_as_float(tw[i].z), sb = __uint_as_float(tw[i].w);
          const float tr0 = t == 0 ? lo[0] : lo[0] + hi[0], ti0 = t == 0 ? lo[2] : lo[2] + hi[2];
          const float tr1 = lo[1] + hi[1], ti1 = lo[3] + hi[3];
          const float vr0 = tr0 * ca - ti0 * sa, vi0 = tr0 * sa + ti0 * ca;
          const float vr1 = tr1 * cb - ti1 * sb, vi1 = tr1 * sb + ti1 * cb;
          const uint32_t b0 = pack2(t == 0 ? hi[0] : vr0, vr1), b1 = pack2(t == 0 ? vr0 : vi0, vi1);
          yv[i][0] = yv[i][1] = yv[i][2] = yv[i][3] = 0.f;
          mma16816(yv[i], ga.x, ga.y, ga.z, ga.w, b0, b1);
        }
#pragma unroll
        for (int h = 0; h < 2; h++) {
          hv[r][h][0] = hadd2_bf16(xr[r][h].x, pack2(yv[0][2 * h], yv[1][2 * h]));
          hv[r][h][1] = hadd2_bf16(xr[r][h].y, pack2(yv[2][2 * h], yv[3][2 * h]));
          hv[r][h][2] = hadd2_bf16(xr[r][h].z, pack2(yv[0][2 * h + 1], yv[1][2 * h + 1]));
          hv[r][h][3] = hadd2_bf16(xr[r][h].w, pack2(yv[2][2 * h + 1], yv[3][2 * h + 1]));
        }
      }
      float mean[2], rstd[2];
#pragma unroll
      for (int r = 0; r < 2; r++) {
        float s = 0.f;
#pragma unroll
        for (int i = 0; i < 8; i++) s += bf_lo(hv[r][i >> 2][i & 3]) + bf_hi(hv[r][i >> 2][i & 3]);
        mean[r] = warp_sum(s) * (1.f / 512.f);
      }
#pragma unroll
      for (int r = 0; r < 2; r++) {
        float s = 0.f;
#pragma unroll
        for (int i = 0; i < 8; i++) {
          const float a = bf_lo(hv[r][i >> 2][i & 3]) - mean[r], b = bf_hi(hv[r][i >> 2][i & 3]) - mean[r];
          s += a * a + b * b;
        }
        rstd[r] = rsqrtf(warp_sum(s) * (1.f / 512.f) + 1e-5f);
      }
#pragma unroll
      for (int r = 0; r < 2; r++) {
        const int row = 16 * f + 2 * warp + r;
        const float nm = -mean[r] * rstd[r];
#pragma unroll
        for (int h = 0; h < 2; h++) {
          uint32_t w[4];
#pragma unroll
          for (int i = 0; i < 4; i++) w[i] = pack2(fmaf(bf_lo(hv[r][h][i]), rstd[r], nm), fmaf(bf_hi(hv[r][h][i]), rstd[r], nm));
          const int n1 = g + 8 * h;
          g_LN[(rb * 8 + (n1 >> 1)) * 1024 + row * 8 + ((4 * (n1 & 1) + t) ^ (row & 7))] = make_uint4(w[0], w[1], w[2], w[3]);
        }
      }
      asm volatile("fence.proxy.async.shared::cta;" ::: "memory");
      bar_arrive(NB_LN, 288);
    }
    PROF(5);
    const int wgi = warp >> 2, wq = warp & 3;
    uint4* const pbase = &g_P[rb * 28 * 1024];
    const int p_lane = (8 * wgi + 2 * wq) * 64 + t * 8 + g;
    const uint32_t a_lo0 = desc_lo(sbase + wgi * 8192, 16);
    uint32_t slot = 0, ph = 0, prev = 0;
    {
      float acc[128];
#pragma unroll
      for (int i = 0; i < 128; i++) acc[i] = 0.f;
      if (wgi == 1) bar_sync(NB_LAG, 256);
      const uint32_t b_lo0 = desc_lo(sbase + 8 * SLOT, 4096);
#pragma unroll 1
      for (int kb = 0; kb < 8; kb++) {
        mbar_wait(BAR(fullA, kb), 0);
        if (kb == 0) PROF(6);
#pragma unroll
        for (int hh = 0; hh < 2; hh++) {
          mbar_wait(BAR(full1, slot), ph);
          const uint32_t al = a_lo0 + kb * 1024 + hh * 4, bl = b_lo0 + slot * 1024;
          wg_fence();
          wgmma_n256(acc, desc64(al, HI128), desc64(bl, HI128));
          wgmma_n256(acc, desc64(al + 2, HI128), desc64(bl + 128, HI128));
          wg_commit();
          if (hh == (LAG & 1) && kb == (LAG >> 1) && wgi == 0) bar_arrive(NB_LAG, 256);
          if (hh == 0 && kb == 0) {
#pragma unroll
            for (int i = 0; i < 4; i++)
              g_H[(c + 128 * (2 * warp + (i >> 1))) * 64 + 4 * (g + 8 * (i & 1)) + t] =
                  make_uint4(hv[i >> 1][i & 1][0], hv[i >> 1][i & 1][1], hv[i >> 1][i & 1][2], hv[i >> 1][i & 1][3]);
          }
          wg_wait<1>();
          if ((kb | hh) != 0 && lane == 0) mbar_arrive(BAR(empty1, prev));
          prev = slot;
          if (++slot == 6) { slot = 0; ph ^= 1; }
        }
      }
      wg_wait<0>();
      if (lane == 0) mbar_arrive(BAR(empty1, prev));
      PROF(7);
      store_p<4>(acc, pbase, 7 * f + 3 * (f & 1), p_lane);
      bar_arrive(NB_PUB0 + wgi, 160);
    }
    PROF(8);
    {
      float acc[96];
#pragma unroll
      for (int i = 0; i < 96; i++) acc[i] = 0.f;
      const uint32_t b_lo0 = desc_lo(sbase + 8 * SLOT, 2048);
#pragma unroll 1
      for (int kb = 0; kb < 8; kb++) {
#pragma unroll
        for (int hh = 0; hh < 2; hh++) {
          mbar_wait(BAR(full1, slot), ph);
          const uint32_t al = a_lo0 + kb * 1024 + hh * 4, bl = b_lo0 + slot * 1024;
          wg_fence();
          wgmma_n192(acc, desc64(al, HI128), desc64(bl, HI64));
          wgmma_n192(acc, desc64(al + 2, HI128), desc64(bl + 64, HI64));
          wg_commit();
          wg_wait<1>();
          if ((kb | hh) != 0 && lane == 0) mbar_arrive(BAR(empty1, prev));
          prev = slot;
          if (++slot == 6) { slot = 0; ph ^= 1; }
        }
      }
      wg_wait<0>();
      if (lane == 0) mbar_arrive(BAR(empty1, prev));
      PROF(9);
      store_p<3>(acc, pbase, 7 * f + ((f & 1) ? 0 : 4), p_lane);
      bar_arrive(NB_PUB0 + wgi, 160);
    }
    PROF(10);
    {
      const int kh = f & 1, nq = f >> 1;
      const int rh = wgi ^ kh ^ 1;
      const int orow = 8 * rb + 4 * rh + wq;
      float acc[64];
#pragma unroll
      for (int i = 0; i < 64; i++) acc[i] = 0.f;
      const uint32_t a2_lo0 = desc_lo(sbase + 8 * SLOT + rh * 8192, 128), b2_lo0 = desc_lo(sbase, 8192);
      uint4 hres[2][4];
      slot = 2;
#pragma unroll 1
      for (int s = 0; s < 14; s++) {
        const uint32_t al = a2_lo0 + slot * 1024, bl = b2_lo0 + (s & 7) * 1024;
        mbar_wait(BAR(full2, s), 0);
        wg_fence();
#pragma unroll
        for (int kk = 0; kk < 4; kk++) wgmma_n128(acc, desc64(al + kk * 16, HI0), desc64(bl + kk * 128, HI128));
        wg_commit();
        if (s == 0) {
#pragma unroll
          for (int h = 0; h < 2; h++)
#pragma unroll
            for (int q = 0; q < 4; q++) hres[h][q] = ldg_cg4(&g_H[(orow + 128 * (g + 8 * h)) * 64 + nq * 16 + 4 * q + t]);
        }
        wg_wait<1>();
        if (s > 0 && s <= 8 && lane == 0) {
          mbar_arrive(BAR(empty2, s - 1));
          if (s == 8)
            asm volatile("{.reg .b32 r; mapa.shared::cluster.u32 r, %0, %1; mbarrier.arrive.shared::cluster.b64 _, [r];}"
                         ::"r"(BAR(xfree, 0)), "r"(kh ^ 1) : "memory");
        }
        if (++slot == 6) slot = 0;
      }
      wg_wait<0>();
      PROF(11);
      const uint32_t xbuf = sbase + 6 * SLOT + (tid & 127) * 16;
      if (wgi == 0) {
        uint32_t rbuf, rbar;
        mbar_wait(BAR(xfree, 0), 0);
        asm volatile("mapa.shared::cluster.u32 %0, %1, %2;" : "=r"(rbuf) : "r"(xbuf), "r"(kh ^ 1));
        asm volatile("mapa.shared::cluster.u32 %0, %1, %2;" : "=r"(rbar) : "r"(BAR(xbar, 0)), "r"(kh ^ 1));
#pragma unroll
        for (int i = 0; i < 16; i++)
          asm volatile("st.async.weak.shared::cluster.mbarrier::complete_tx::bytes.v4.f32 [%0], {%1,%2,%3,%4}, [%5];"
                       ::"r"(rbuf + i * 2048), "f"(acc[4 * i]), "f"(acc[4 * i + 1]), "f"(acc[4 * i + 2]), "f"(acc[4 * i + 3]), "r"(rbar)
                       : "memory");
      } else {
        mbar_wait_cluster(BAR(xbar, 0), 0);
      }
      uint32_t w[2][16];
#pragma unroll
      for (int i = 0; i < 16; i++) {
        const uint4 pv = lds4(xbuf + i * 2048);
        w[0][i] = pack2(acc[4 * i] + __uint_as_float(pv.x), acc[4 * i + 1] + __uint_as_float(pv.y));
        w[1][i] = pack2(acc[4 * i + 2] + __uint_as_float(pv.z), acc[4 * i + 3] + __uint_as_float(pv.w));
      }
      uint4* const o4 = reinterpret_cast<uint4*>(out);
#pragma unroll
      for (int h = 0; h < 2; h++)
#pragma unroll
        for (int q = 0; q < 4; q++) {
          uint32_t a0 = w[h][4 * q], a1 = w[h][4 * q + 1], a2 = w[h][4 * q + 2], a3 = w[h][4 * q + 3];
          {
            const bool od = t & 1;
            uint32_t s0 = od ? a0 : a1, s1 = od ? a2 : a3;
            s0 = __shfl_xor_sync(0xffffffffu, s0, 1); s1 = __shfl_xor_sync(0xffffffffu, s1, 1);
            if (od) { a0 = s0; a2 = s1; } else { a1 = s0; a3 = s1; }
          }
          {
            const bool up = t & 2;
            uint32_t s0 = up ? a0 : a2, s1 = up ? a1 : a3;
            s0 = __shfl_xor_sync(0xffffffffu, s0, 2); s1 = __shfl_xor_sync(0xffffffffu, s1, 2);
            if (up) { a0 = s0; a1 = s1; } else { a2 = s0; a3 = s1; }
          }
          if (wgi == 1)
            o4[(orow + 128 * (g + 8 * h)) * 64 + nq * 16 + 4 * q + t] =
                make_uint4(hadd2_bf16(hres[h][q].x, a0), hadd2_bf16(hres[h][q].y, a1), hadd2_bf16(hres[h][q].z, a2), hadd2_bf16(hres[h][q].w, a3));
        }
      PROF(12);
      PROFG(15);
    }
  }
#undef BAR
#undef TOFF
}

typedef CUresult (*EncodeFn)(CUtensorMap*, CUtensorMapDataType, cuuint32_t, void*, const cuuint64_t*, const cuuint64_t*,
                             const cuuint32_t*, const cuuint32_t*, CUtensorMapInterleave, CUtensorMapSwizzle,
                             CUtensorMapL2promotion, CUtensorMapFloatOOBfill);

}

extern "C" void kernel_launch(void* const* d_in, const int* in_sizes, int n_in, void* d_out, int out_size) {
  (void)in_sizes; (void)n_in; (void)out_size;
  static EncodeFn encode = nullptr;
  if (!encode) {
    void* fn = nullptr;
    cudaDriverEntryPointQueryResult qr;
    cudaGetDriverEntryPoint("cuTensorMapEncodeTiled", &fn, cudaEnableDefault, &qr);
    encode = (EncodeFn)fn;
    cudaFuncSetAttribute(fused_kernel, cudaFuncAttributeMaxDynamicSharedMemorySize, SMEM_BYTES);
  }
  CUtensorMap tmGX, tmUX, tmGY, tmUY, tmD;
  const cuuint32_t es[5] = {1, 1, 1, 1, 1};
  {
    const cuuint64_t gd[3] = {64, 512, 28}, gs[2] = {3584, 128};
    const cuuint32_t bd[3] = {64, 32, 2};
    encode(&tmGX, CU_TENSOR_MAP_DATA_TYPE_BFLOAT16, 3, d_in[4], gd, gs, bd, es, CU_TENSOR_MAP_INTERLEAVE_NONE,
           CU_TENSOR_MAP_SWIZZLE_128B, CU_TENSOR_MAP_L2_PROMOTION_L2_256B, CU_TENSOR_MAP_FLOAT_OOB_FILL_NONE);
    encode(&tmUX, CU_TENSOR_MAP_DATA_TYPE_BFLOAT16, 3, d_in[5], gd, gs, bd, es, CU_TENSOR_MAP_INTERLEAVE_NONE,
           CU_TENSOR_MAP_SWIZZLE_128B, CU_TENSOR_MAP_L2_PROMOTION_L2_256B, CU_TENSOR_MAP_FLOAT_OOB_FILL_NONE);
  }
  {
    const cuuint64_t gd[3] = {32, 512, 56}, gs[2] = {3584, 64};
    const cuuint32_t bd[3] = {32, 32, 3};
    encode(&tmGY, CU_TENSOR_MAP_DATA_TYPE_BFLOAT16, 3, d_in[4], gd, gs, bd, es, CU_TENSOR_MAP_INTERLEAVE_NONE,
           CU_TENSOR_MAP_SWIZZLE_64B, CU_TENSOR_MAP_L2_PROMOTION_L2_128B, CU_TENSOR_MAP_FLOAT_OOB_FILL_NONE);
    encode(&tmUY, CU_TENSOR_MAP_DATA_TYPE_BFLOAT16, 3, d_in[5], gd, gs, bd, es, CU_TENSOR_MAP_INTERLEAVE_NONE,
           CU_TENSOR_MAP_SWIZZLE_64B, CU_TENSOR_MAP_L2_PROMOTION_L2_128B, CU_TENSOR_MAP_FLOAT_OOB_FILL_NONE);
  }
  {
    const cuuint64_t gd[5] = {512, 2, 4, 4, 56}, gs[4] = {1024, 8192, 2048, 32768};
    const cuuint32_t bd[5] = {64, 2, 4, 4, 2};
    encode(&tmD, CU_TENSOR_MAP_DATA_TYPE_BFLOAT16, 5, d_in[6], gd, gs, bd, es, CU_TENSOR_MAP_INTERLEAVE_NONE,
           CU_TENSOR_MAP_SWIZZLE_128B, CU_TENSOR_MAP_L2_PROMOTION_L2_256B, CU_TENSOR_MAP_FLOAT_OOB_FILL_NONE);
  }
  fused_kernel<<<NCTA, NTHREADS, SMEM_BYTES>>>(
      tmGX, tmUX, tmGY, tmUY, tmD, (const __nv_bfloat16*)d_in[0], (const __nv_bfloat16*)d_in[1], (const __nv_bfloat16*)d_in[2],
      (const char*)d_in[4], (const char*)d_in[5], (const char*)d_in[6], (__nv_bfloat16*)d_out);
}
```

```cpp
#include <cuda_runtime.h>
#include <cuda_bf16.h>
#include <cuda.h>
#include <stdint.h>

namespace {

constexpr int NCTA = 128;
constexpr int NTHREADS = 384;
constexpr int SLOT = 16384;
constexpr int SMEM_BYTES = 14 * SLOT + 1024 + 1024;
constexpr int SPIN_LIMIT = 1 << 22;

__device__ uint4 g_Z1[128 * 1024];
__device__ uint4 g_Z2[128 * 1024];
__device__ uint4 g_LN[16 * 8 * 1024];
__device__ uint4 g_H[2048 * 64];
__device__ uint4 g_P[16 * 28 * 1024];
__device__ unsigned g_cnt[64 * 32];
#define PROF(i)
#define PROFP(i)
#define PROFG(i)

constexpr double ccos(int i, int n) {
  i &= n - 1;
  if (i > n / 2) i = n - i;
  if (4 * i == n) return 0.0;
  const bool neg = 4 * i > n;
  if (neg) i = n / 2 - i;
  const double a = 6.283185307179586476925 * i / n, a2 = a * a;
  double term = 1.0, sum = 1.0;
  for (int k = 1; k < 14; k++) { term *= -a2 / ((2 * k - 1) * (2 * k)); sum += term; }
  return neg ? -sum : sum;
}
constexpr double csin(int i, int n) { return ccos(i - n / 4, n); }
constexpr unsigned fbits(double v, int mant) {
  if (v == 0.0) return 0;
  const unsigned sg = v < 0 ? 1u : 0u;
  if (v < 0) v = -v;
  int e = 127;
  while (v < 1.0) { v *= 2.0; e--; }
  const unsigned m = (unsigned)((v - 1.0) * (double)(1u << mant) + 0.5);
  return (sg << (8 + mant)) + ((unsigned)e << mant) + m;
}
constexpr unsigned pkb(double lo, double hi) { return fbits(lo, 7) | (fbits(hi, 7) << 16); }
constexpr double fa_elem(int kp, int n1) {
  return kp <= 8 ? ccos(kp * n1, 16) : -csin((kp - 8) * n1, 16);
}
constexpr unsigned cfrag_c(int idx, int n, int ri) {
  return ri ? pkb(-csin(idx, n), ccos(idx, n)) : pkb(ccos(idx, n), csin(idx, n));
}
struct Tables {
  unsigned fb[16][32][4];
  unsigned tw1[4][32][4];
  unsigned fa[32][4];
  unsigned pad[32][4];
  unsigned pad2[2][32][4];
  unsigned f2[8][4][32][4];
  unsigned g2[8][4][32][4];
  unsigned gb[16][32][4];
  unsigned tw3[4][32][4];
  unsigned ga[32][4];
  unsigned f8[32][4], g8[32][4];
  unsigned pad3[32][4];
};
constexpr int T1_BYTES = 12288, T2_BYTES = 45056;
static_assert(sizeof(Tables) == T1_BYTES + T2_BYTES, "table size");
constexpr Tables make_tables() {
  Tables T = {};
  for (int l = 0; l < 32; l++) {
    const int g = l >> 2, t = l & 3;
    for (int i = 0; i < 4; i++)
      for (int u = 0; u < 8; u++) {
        const int ri = g & 1, m = 2 * (g >> 1) + ((u & 3) >> 1);
        const double sg = u >= 4 ? -1.0 : 1.0;
        const int k2 = u >= 4 ? 31 - 2 * m - (u & 1) : 2 * m + (u & 1);
        const int pa = (8 * t + i) * k2, pb = (8 * t + 4 + i) * k2;
        T.fb[i * 4 + (u >> 1)][l][(u & 1) * 2 + 0] = ri == 0 ? pkb(ccos(pa, 32), ccos(pb, 32)) : pkb(-sg * csin(pa, 32), -sg * csin(pb, 32));
        T.fb[i * 4 + (u >> 1)][l][(u & 1) * 2 + 1] = ri == 0 ? pkb(csin(pa, 32), csin(pb, 32)) : pkb(sg * ccos(pa, 32), sg * ccos(pb, 32));
      }
    for (int i = 0; i < 4; i++)
      for (int ks = 0; ks < 4; ks++) {
        const int n2 = 4 * g + i, m = 2 * t + (ks & 1);
        const double sg = ks >= 2 ? -1.0 : 1.0;
        const int pa = n2 * (ks >= 2 ? 31 - 2 * m : 2 * m), pb = n2 * (ks >= 2 ? 30 - 2 * m : 2 * m + 1);
        T.gb[i * 4 + ks][l][0] = pkb(ccos(pa, 32), -sg * csin(pa, 32));
        T.gb[i * 4 + ks][l][1] = pkb(csin(pa, 32), sg * ccos(pa, 32));
        T.gb[i * 4 + ks][l][2] = pkb(ccos(pb, 32), -sg * csin(pb, 32));
        T.gb[i * 4 + ks][l][3] = pkb(csin(pb, 32), sg * ccos(pb, 32));
      }
    for (int i = 0; i < 4; i++) {
      const int k1 = g == 0 ? 8 : g;
      T.tw1[i][l][0] = fbits(ccos((8 * t + i) * k1, 512), 23);
      T.tw1[i][l][1] = fbits(csin((8 * t + i) * k1, 512), 23);
      T.tw1[i][l][2] = fbits(ccos((8 * t + 4 + i) * k1, 512), 23);
      T.tw1[i][l][3] = fbits(csin((8 * t + 4 + i) * k1, 512), 23);
      const int ka = t == 0 ? 8 : 2 * t, kb = 2 * t + 1;
      T.tw3[i][l][0] = fbits(ccos((4 * g + i) * ka, 512), 23);
      T.tw3[i][l][1] = fbits(csin((4 * g + i) * ka, 512), 23);
      T.tw3[i][l][2] = fbits(ccos((4 * g + i) * kb, 512), 23);
      T.tw3[i][l][3] = fbits(csin((4 * g + i) * kb, 512), 23);
      const int p8 = (t + 4 * (i & 1)) * (4 * (i >> 1) + (g >> 1));
      T.f8[l][i] = cfrag_c(p8, 8, g & 1);
      T.g8[l][i] = cfrag_c(-p8, 8, g & 1);
    }
    for (int w = 0; w < 8; w++)
      for (int i = 0; i < 16; i++) {
        const int kidx = t + 4 * (i & 1) + 8 * (i >> 3), nidx = 4 * ((i >> 1) & 3) + (g >> 1);
        T.f2[w][i >> 2][l][i & 3] = cfrag_c((8 * kidx + w) * nidx, 128, g & 1);
        T.g2[w][i >> 2][l][i & 3] = cfrag_c(-(8 * nidx + w) * kidx, 128, g & 1);
      }
    T.fa[l][0] = pkb(fa_elem(g, 2 * t), fa_elem(g, 2 * t + 1));
    T.fa[l][1] = pkb(fa_elem(g + 8, 2 * t), fa_elem(g + 8, 2 * t + 1));
    T.fa[l][2] = pkb(fa_elem(g, 2 * t + 8), fa_elem(g, 2 * t + 9));
    T.fa[l][3] = pkb(fa_elem(g + 8, 2 * t + 8), fa_elem(g + 8, 2 * t + 9));
    T.ga[l][0] = pkb(fa_elem(2 * t, g), fa_elem(2 * t + 1, g));
    T.ga[l][1] = pkb(fa_elem(2 * t, g + 8), fa_elem(2 * t + 1, g + 8));
    T.ga[l][2] = pkb(fa_elem(2 * t + 8, g), fa_elem(2 * t + 9, g));
    T.ga[l][3] = pkb(fa_elem(2 * t + 8, g + 8), fa_elem(2 * t + 9, g + 8));
  }
  return T;
}
__device__ const __align__(128) Tables g_tab = make_tables();

__device__ __forceinline__ uint32_t s2u(const void* p) { return (uint32_t)__cvta_generic_to_shared(p); }
__device__ __forceinline__ void mbar_init(uint32_t b, int c) { asm volatile("mbarrier.init.shared::cta.b64 [%0], %1;" ::"r"(b), "r"(c)); }
__device__ __forceinline__ void mbar_expect(uint32_t b, int bytes) {
  asm volatile("mbarrier.arrive.expect_tx.shared::cta.b64 _, [%0], %1;" ::"r"(b), "r"(bytes) : "memory");
}
__device__ __forceinline__ void mbar_arrive(uint32_t b) { asm volatile("mbarrier.arrive.shared::cta.b64 _, [%0];" ::"r"(b) : "memory"); }
__device__ __forceinline__ uint32_t mbar_try(uint32_t b, uint32_t parity) {
  uint32_t ok;
  asm volatile("{.reg .pred p; mbarrier.try_wait.parity.shared::cta.b64 p, [%1], %2; selp.u32 %0,1,0,p;}"
               : "=r"(ok) : "r"(b), "r"(parity) : "memory");
  return ok;
}
__device__ __forceinline__ void mbar_wait(uint32_t b, uint32_t parity) {
  int it = 0;
  while (!mbar_try(b, parity))
    if (++it > SPIN_LIMIT) __trap();
}
__device__ __forceinline__ void mbar_wait_cluster(uint32_t b, int parity) {
  uint32_t ok;
  int it = 0;
  do {
    asm volatile("{.reg .pred p; mbarrier.try_wait.parity.acquire.cluster.shared::cta.b64 p, [%1], %2; selp.u32 %0,1,0,p;}"
                 : "=r"(ok) : "r"(b), "r"(parity) : "memory");
    if (++it > SPIN_LIMIT) __trap();
  } while (!ok);
}
__device__ __forceinline__ void bar_sync(int id, int n) { asm volatile("bar.sync %0, %1;" ::"r"(id), "r"(n) : "memory"); }
__device__ __forceinline__ void bar_arrive(int id, int n) { asm volatile("bar.arrive %0, %1;" ::"r"(id), "r"(n) : "memory"); }
__device__ __forceinline__ void red_release(unsigned* p) { asm volatile("red.release.gpu.global.add.u32 [%0], 1;" ::"l"(p) : "memory"); }
__device__ __forceinline__ unsigned ld_acquire(const unsigned* p) {
  unsigned v;
  asm volatile("ld.acquire.gpu.global.u32 %0, [%1];" : "=r"(v) : "l"(p) : "memory");
  return v;
}
__device__ __forceinline__ unsigned ld_relaxed(const unsigned* p) {
  unsigned v;
  asm volatile("ld.relaxed.gpu.global.u32 %0, [%1];" : "=r"(v) : "l"(p) : "memory");
  return v;
}
__device__ __forceinline__ void wait_counter(const unsigned* p, unsigned target) {
  int it = 0;
  while ((int)(ld_acquire(p) - target) < 0)
    if (++it > SPIN_LIMIT) __trap();
}
__device__ __forceinline__ uint4 ldg_cg4(const uint4* p) {
  uint4 v;
  asm volatile("ld.global.cg.v4.u32 {%0,%1,%2,%3}, [%4];" : "=r"(v.x), "=r"(v.y), "=r"(v.z), "=r"(v.w) : "l"(p) : "memory");
  return v;
}
__device__ __forceinline__ void sts4(uint32_t a, uint32_t x, uint32_t y, uint32_t z, uint32_t w) {
  asm volatile("st.shared.v4.u32 [%0], {%1,%2,%3,%4};" ::"r"(a), "r"(x), "r"(y), "r"(z), "r"(w) : "memory");
}
__device__ __forceinline__ uint4 lds4(uint32_t a) {
  uint4 v;
  asm volatile("ld.shared.v4.u32 {%0,%1,%2,%3}, [%4];" : "=r"(v.x), "=r"(v.y), "=r"(v.z), "=r"(v.w) : "r"(a) : "memory");
  return v;
}
__device__ __forceinline__ uint32_t pack2(float lo, float hi) {
  uint32_t r;
  asm("cvt.rn.bf16x2.f32 %0, %1, %2;" : "=r"(r) : "f"(hi), "f"(lo));
  return r;
}
__device__ __forceinline__ float bf_lo(uint32_t v) { return __uint_as_float(v << 16); }
__device__ __forceinline__ float bf_hi(uint32_t v) { return __uint_as_float(v & 0xffff0000u); }
__device__ __forceinline__ uint32_t hadd2_bf16(uint32_t a, uint32_t b) {
  uint32_t r;
  asm("add.rn.bf16x2 %0, %1, %2;" : "=r"(r) : "r"(a), "r"(b));
  return r;
}
__device__ __forceinline__ void mma16816(float (&d)[4], uint32_t a0, uint32_t a1, uint32_t a2, uint32_t a3, uint32_t b0, uint32_t b1) {
  asm("mma.sync.aligned.m16n8k16.row.col.f32.bf16.bf16.f32 {%0,%1,%2,%3}, {%4,%5,%6,%7}, {%8,%9}, {%0,%1,%2,%3};"
      : "+f"(d[0]), "+f"(d[1]), "+f"(d[2]), "+f"(d[3])
      : "r"(a0), "r"(a1), "r"(a2), "r"(a3), "r"(b0), "r"(b1));
}
template <int N>
__device__ __forceinline__ void cs_frac(int idx, float& c, float& s) {
  int i = ((idx + N / 2) & (N - 1)) - N / 2;
  float a = (float)i * (6.283185307179586f / N);
  c = __cosf(a);
  s = __sinf(a);
}
template <int N>
__device__ __forceinline__ uint32_t cfrag(int idx, int ri) {
  float c, s;
  cs_frac<N>(idx, c, s);
  return ri ? pack2(-s, c) : pack2(c, s);
}
__device__ __forceinline__ uint32_t word(const uint4& v, int e) { return e == 0 ? v.x : e == 1 ? v.y : e == 2 ? v.z : v.w; }
__device__ __forceinline__ void cdft16(const uint4 (&q)[4], const uint4 (&F)[4], uint4 (&o)[4]) {
  float acc[2][4][4];
#pragma unroll
  for (int p = 0; p < 2; p++)
#pragma unroll
    for (int v = 0; v < 4; v++) {
      acc[p][v][0] = acc[p][v][1] = acc[p][v][2] = acc[p][v][3] = 0.f;
#pragma unroll
      for (int ks = 0; ks < 2; ks++)
        mma16816(acc[p][v], word(q[2 * ks], 2 * p), word(q[2 * ks], 2 * p + 1), word(q[2 * ks + 1], 2 * p),
                 word(q[2 * ks + 1], 2 * p + 1), word(F[ks * 2 + (v >> 1)], (v & 1) * 2), word(F[ks * 2 + (v >> 1)], (v & 1) * 2 + 1));
    }
#pragma unroll
  for (int v = 0; v < 4; v++)
    o[v] = make_uint4(pack2(acc[0][v][0], acc[0][v][1]), pack2(acc[0][v][2], acc[0][v][3]),
                      pack2(acc[1][v][0], acc[1][v][1]), pack2(acc[1][v][2], acc[1][v][3]));
}
__device__ __forceinline__ float warp_sum(float v) {
#pragma unroll
  for (int o = 16; o > 0; o >>= 1) v += __shfl_xor_sync(0xffffffffu, v, o);
  return v;
}
__device__ __forceinline__ uint64_t desc64(uint32_t lo, uint32_t hi) {
  uint64_t d;
  asm("mov.b64 %0, {%1, %2};" : "=l"(d) : "r"(lo), "r"(hi));
  return d;
}
constexpr uint32_t desc_hi(uint32_t sbo, uint32_t swz) { return (sbo >> 4) | (swz << 30); }
__device__ __forceinline__ uint32_t desc_lo(uint32_t addr, uint32_t lbo) { return ((addr & 0x3FFFF) >> 4) | ((lbo >> 4) << 16); }
__device__ __forceinline__ void cp_async16(uint32_t dst, const void* src) {
  asm volatile("cp.async.cg.shared.global [%0], [%1], 16;" ::"r"(dst), "l"(src) : "memory");
}
__device__ __forceinline__ uint2 lds2(uint32_t a) {
  uint2 v;
  asm volatile("ld.shared.v2.u32 {%0,%1}, [%2];" : "=r"(v.x), "=r"(v.y) : "r"(a) : "memory");
  return v;
}
__device__ __forceinline__ uint32_t lds_u16(uint32_t a) {
  uint16_t v;
  asm volatile("ld.shared.u16 %0, [%1];" : "=h"(v) : "r"(a) : "memory");
  return v;
}
__device__ __forceinline__ void wg_fence() { asm volatile("wgmma.fence.sync.aligned;" ::: "memory"); }
__device__ __forceinline__ void wg_commit() { asm volatile("wgmma.commit_group.sync.aligned;" ::: "memory"); }
template <int N>
__device__ __forceinline__ void wg_wait() { asm volatile("wgmma.wait_group.sync.aligned %0;" ::"n"(N) : "memory"); }
__device__ __forceinline__ void bulk_load(uint32_t dst, const void* src, int bytes, uint32_t bar) {
  asm volatile("cp.async.bulk.shared::cluster.global.mbarrier::complete_tx::bytes [%0], [%1], %2, [%3];"
               ::"r"(dst), "l"(src), "r"(bytes), "r"(bar) : "memory");
}
__device__ __forceinline__ void tma3(uint32_t dst, const CUtensorMap* tm, uint32_t bar, int c0, int c1, int c2) {
  asm volatile("cp.async.bulk.tensor.3d.shared::cluster.global.mbarrier::complete_tx::bytes [%0], [%1, {%3,%4,%5}], [%2];"
               ::"r"(dst), "l"(tm), "r"(bar), "r"(c0), "r"(c1), "r"(c2) : "memory");
}
__device__ __forceinline__ void tma5(uint32_t dst, const CUtensorMap* tm, uint32_t bar, int c0, int c4) {
  asm volatile("cp.async.bulk.tensor.5d.shared::cluster.global.mbarrier::complete_tx::bytes [%0], [%1, {%3,%4,%4,%4,%5}], [%2];"
               ::"r"(dst), "l"(tm), "r"(bar), "r"(c0), "r"(0), "r"(c4) : "memory");
}
__device__ __forceinline__ float swiglu(float g, float u) {
  float hg = 0.5f * g, th;
  asm("tanh.approx.f32 %0, %1;" : "=f"(th) : "f"(hg));
  return fmaf(hg, th, hg) * u;
}

__device__ __forceinline__ void wgmma_n256(float (&d)[128], uint64_t da, uint64_t db) {
  asm volatile("wgmma.mma_async.sync.aligned.m64n256k16.f32.bf16.bf16 {"
      "%0,%1,%2,%3,%4,%5,%6,%7,%8,%9,%10,%11,%12,%13,%14,%15,"
      "%16,%17,%18,%19,%20,%21,%22,%23,%24,%25,%26,%27,%28,%29,%30,%31,"
      "%32,%33,%34,%35,%36,%37,%38,%39,%40,%41,%42,%43,%44,%45,%46,%47,"
      "%48,%49,%50,%51,%52,%53,%54,%55,%56,%57,%58,%59,%60,%61,%62,%63,"
      "%64,%65,%66,%67,%68,%69,%70,%71,%72,%73,%74,%75,%76,%77,%78,%79,"
      "%80,%81,%82,%83,%84,%85,%86,%87,%88,%89,%90,%91,%92,%93,%94,%95,"
      "%96,%97,%98,%99,%100,%101,%102,%103,%104,%105,%106,%107,%108,%109,%110,%111,"
      "%112,%113,%114,%115,%116,%117,%118,%119,%120,%121,%122,%123,%124,%125,%126,%127"
      "}, %128, %129, 1, 1, 1, 0, 1;\n"
      : "+f"(d[0]),"+f"(d[1]),"+f"(d[2]),"+f"(d[3]),"+f"(d[4]),"+f"(d[5]),"+f"(d[6]),"+f"(d[7]),
        "+f"(d[8]),"+f"(d[9]),"+f"(d[10]),"+f"(d[11]),"+f"(d[12]),"+f"(d[13]),"+f"(d[14]),"+f"(d[15]),
        "+f"(d[16]),"+f"(d[17]),"+f"(d[18]),"+f"(d[19]),"+f"(d[20]),"+f"(d[21]),"+f"(d[22]),"+f"(d[23]),
        "+f"(d[24]),"+f"(d[25]),"+f"(d[26]),"+f"(d[27]),"+f"(d[28]),"+f"(d[29]),"+f"(d[30]),"+f"(d[31]),
        "+f"(d[32]),"+f"(d[33]),"+f"(d[34]),"+f"(d[35]),"+f"(d[36]),"+f"(d[37]),"+f"(d[38]),"+f"(d[39]),
        "+f"(d[40]),"+f"(d[41]),"+f"(d[42]),"+f"(d[43]),"+f"(d[44]),"+f"(d[45]),"+f"(d[46]),"+f"(d[47]),
        "+f"(d[48]),"+f"(d[49]),"+f"(d[50]),"+f"(d[51]),"+f"(d[52]),"+f"(d[53]),"+f"(d[54]),"+f"(d[55]),
        "+f"(d[56]),"+f"(d[57]),"+f"(d[58]),"+f"(d[59]),"+f"(d[60]),"+f"(d[61]),"+f"(d[62]),"+f"(d[63]),
        "+f"(d[64]),"+f"(d[65]),"+f"(d[66]),"+f"(d[67]),"+f"(d[68]),"+f"(d[69]),"+f"(d[70]),"+f"(d[71]),
        "+f"(d[72]),"+f"(d[73]),"+f"(d[74]),"+f"(d[75]),"+f"(d[76]),"+f"(d[77]),"+f"(d[78]),"+f"(d[79]),
        "+f"(d[80]),"+f"(d[81]),"+f"(d[82]),"+f"(d[83]),"+f"(d[84]),"+f"(d[85]),"+f"(d[86]),"+f"(d[87]),
        "+f"(d[88]),"+f"(d[89]),"+f"(d[90]),"+f"(d[91]),"+f"(d[92]),"+f"(d[93]),"+f"(d[94]),"+f"(d[95]),
        "+f"(d[96]),"+f"(d[97]),"+f"(d[98]),"+f"(d[99]),"+f"(d[100]),"+f"(d[101]),"+f"(d[102]),"+f"(d[103]),
        "+f"(d[104]),"+f"(d[105]),"+f"(d[106]),"+f"(d[107]),"+f"(d[108]),"+f"(d[109]),"+f"(d[110]),"+f"(d[111]),
        "+f"(d[112]),"+f"(d[113]),"+f"(d[114]),"+f"(d[115]),"+f"(d[116]),"+f"(d[117]),"+f"(d[118]),"+f"(d[119]),
        "+f"(d[120]),"+f"(d[121]),"+f"(d[122]),"+f"(d[123]),"+f"(d[124]),"+f"(d[125]),"+f"(d[126]),"+f"(d[127])
      : "l"(da), "l"(db));
}
__device__ __forceinline__ void wgmma_n192(float (&d)[96], uint64_t da, uint64_t db) {
  asm volatile("wgmma.mma_async.sync.aligned.m64n192k16.f32.bf16.bf16 {"
      "%0,%1,%2,%3,%4,%5,%6,%7,%8,%9,%10,%11,%12,%13,%14,%15,"
      "%16,%17,%18,%19,%20,%21,%22,%23,%24,%25,%26,%27,%28,%29,%30,%31,"
      "%32,%33,%34,%35,%36,%37,%38,%39,%40,%41,%42,%43,%44,%45,%46,%47,"
      "%48,%49,%50,%51,%52,%53,%54,%55,%56,%57,%58,%59,%60,%61,%62,%63,"
      "%64,%65,%66,%67,%68,%69,%70,%71,%72,%73,%74,%75,%76,%77,%78,%79,"
      "%80,%81,%82,%83,%84,%85,%86,%87,%88,%89,%90,%91,%92,%93,%94,%95"
      "}, %96, %97, 1, 1, 1, 0, 1;\n"
      : "+f"(d[0]),"+f"(d[1]),"+f"(d[2]),"+f"(d[3]),"+f"(d[4]),"+f"(d[5]),"+f"(d[6]),"+f"(d[7]),
        "+f"(d[8]),"+f"(d[9]),"+f"(d[10]),"+f"(d[11]),"+f"(d[12]),"+f"(d[13]),"+f"(d[14]),"+f"(d[15]),
        "+f"(d[16]),"+f"(d[17]),"+f"(d[18]),"+f"(d[19]),"+f"(d[20]),"+f"(d[21]),"+f"(d[22]),"+f"(d[23]),
        "+f"(d[24]),"+f"(d[25]),"+f"(d[26]),"+f"(d[27]),"+f"(d[28]),"+f"(d[29]),"+f"(d[30]),"+f"(d[31]),
        "+f"(d[32]),"+f"(d[33]),"+f"(d[34]),"+f"(d[35]),"+f"(d[36]),"+f"(d[37]),"+f"(d[38]),"+f"(d[39]),
        "+f"(d[40]),"+f"(d[41]),"+f"(d[42]),"+f"(d[43]),"+f"(d[44]),"+f"(d[45]),"+f"(d[46]),"+f"(d[47]),
        "+f"(d[48]),"+f"(d[49]),"+f"(d[50]),"+f"(d[51]),"+f"(d[52]),"+f"(d[53]),"+f"(d[54]),"+f"(d[55]),
        "+f"(d[56]),"+f"(d[57]),"+f"(d[58]),"+f"(d[59]),"+f"(d[60]),"+f"(d[61]),"+f"(d[62]),"+f"(d[63]),
        "+f"(d[64]),"+f"(d[65]),"+f"(d[66]),"+f"(d[67]),"+f"(d[68]),"+f"(d[69]),"+f"(d[70]),"+f"(d[71]),
        "+f"(d[72]),"+f"(d[73]),"+f"(d[74]),"+f"(d[75]),"+f"(d[76]),"+f"(d[77]),"+f"(d[78]),"+f"(d[79]),
        "+f"(d[80]),"+f"(d[81]),"+f"(d[82]),"+f"(d[83]),"+f"(d[84]),"+f"(d[85]),"+f"(d[86]),"+f"(d[87]),
        "+f"(d[88]),"+f"(d[89]),"+f"(d[90]),"+f"(d[91]),"+f"(d[92]),"+f"(d[93]),"+f"(d[94]),"+f"(d[95])
      : "l"(da), "l"(db));
}
__device__ __forceinline__ void wgmma_n128(float (&d)[64], uint64_t da, uint64_t db) {
  asm volatile("wgmma.mma_async.sync.aligned.m64n128k16.f32.bf16.bf16 {"
      "%0,%1,%2,%3,%4,%5,%6,%7,%8,%9,%10,%11,%12,%13,%14,%15,"
      "%16,%17,%18,%19,%20,%21,%22,%23,%24,%25,%26,%27,%28,%29,%30,%31,"
      "%32,%33,%34,%35,%36,%37,%38,%39,%40,%41,%42,%43,%44,%45,%46,%47,"
      "%48,%49,%50,%51,%52,%53,%54,%55,%56,%57,%58,%59,%60,%61,%62,%63"
      "}, %64, %65, 1, 1, 1, 0, 1;\n"
      : "+f"(d[0]),"+f"(d[1]),"+f"(d[2]),"+f"(d[3]),"+f"(d[4]),"+f"(d[5]),"+f"(d[6]),"+f"(d[7]),
        "+f"(d[8]),"+f"(d[9]),"+f"(d[10]),"+f"(d[11]),"+f"(d[12]),"+f"(d[13]),"+f"(d[14]),"+f"(d[15]),
        "+f"(d[16]),"+f"(d[17]),"+f"(d[18]),"+f"(d[19]),"+f"(d[20]),"+f"(d[21]),"+f"(d[22]),"+f"(d[23]),
        "+f"(d[24]),"+f"(d[25]),"+f"(d[26]),"+f"(d[27]),"+f"(d[28]),"+f"(d[29]),"+f"(d[30]),"+f"(d[31]),
        "+f"(d[32]),"+f"(d[33]),"+f"(d[34]),"+f"(d[35]),"+f"(d[36]),"+f"(d[37]),"+f"(d[38]),"+f"(d[39]),
        "+f"(d[40]),"+f"(d[41]),"+f"(d[42]),"+f"(d[43]),"+f"(d[44]),"+f"(d[45]),"+f"(d[46]),"+f"(d[47]),
        "+f"(d[48]),"+f"(d[49]),"+f"(d[50]),"+f"(d[51]),"+f"(d[52]),"+f"(d[53]),"+f"(d[54]),"+f"(d[55]),
        "+f"(d[56]),"+f"(d[57]),"+f"(d[58]),"+f"(d[59]),"+f"(d[60]),"+f"(d[61]),"+f"(d[62]),"+f"(d[63])
      : "l"(da), "l"(db));
}

constexpr int C_BAR1 = 0, C_BAR2 = 1, C_LN = 2, C_PX = 18, C_PY = 34;
constexpr int NB_CONS = 1, NB_LN = 2, NB_PUB0 = 3, NB_LAG = 5, NB_INIT = 6;
#define LAG 2
constexpr int SM_E = 0, SM_E2 = 16384, SM_X = 32768, SM_W = 49152, SM_FC = 69632, SM_T = 73728;

constexpr unsigned long long KORDER = 0xBA9432DC876510ull;
constexpr uint32_t HI128 = desc_hi(1024, 1), HI64 = desc_hi(512, 2), HI0 = desc_hi(1024, 0);

struct Bars {
  uint64_t full1[6], empty1[6], fullA[8], full2[14], empty2[8], xbar, xfree, tbar;
};

template <int NT>
__device__ __forceinline__ void store_p(const float (&acc)[NT * 32], uint4* pbase, int G0, int lane_off) {
#pragma unroll
  for (int q = 0; q < NT; q++) {
    const int G = G0 + q;
    uint4* dst = pbase + (G >> 1) * 1024 + (G & 1) * 32 + lane_off;
#pragma unroll
    for (int h = 0; h < 2; h++) {
      uint32_t w[4];
#pragma unroll
      for (int i = 0; i < 4; i++) {
        const int a = (q * 4 + i) * 4 + 2 * h, b = a + NT * 16;
        w[i] = pack2(swiglu(acc[a], acc[b]), swiglu(acc[a + 1], acc[b + 1]));
      }
      dst[h * 64] = make_uint4(w[0], w[1], w[2], w[3]);
    }
  }
}

__global__ void __cluster_dims__(2, 1, 1) __launch_bounds__(NTHREADS, 1)
fused_kernel(const __grid_constant__ CUtensorMap tmGX, const __grid_constant__ CUtensorMap tmUX,
             const __grid_constant__ CUtensorMap tmGY, const __grid_constant__ CUtensorMap tmUY,
             const __grid_constant__ CUtensorMap tmD,
             const __nv_bfloat16* __restrict__ x, const __nv_bfloat16* __restrict__ wr, const __nv_bfloat16* __restrict__ wi,
             const char* __restrict__ wg_raw, const char* __restrict__ wu_raw, const char* __restrict__ wd_raw,
             __nv_bfloat16* __restrict__ out) {
  extern __shared__ __align__(1024) char smem_raw[];
  const uint32_t sbase = (s2u(smem_raw) + 1023) & ~1023u;
  const uint32_t sbar = sbase + 14 * SLOT;
  const int tid = threadIdx.x, lane = tid & 31;
  const int c = blockIdx.x, rb = c >> 3, f = c & 7;
#define BAR(field, i) (sbar + (uint32_t)offsetof(Bars, field) + 8u * (i))
#define TOFF(field) (sbase + SM_T + (uint32_t)offsetof(Tables, field) + lane * 16)

  if (tid >= 256) {
    asm volatile("setmaxnreg.dec.sync.aligned.u32 56;");
    const int warp = __shfl_sync(0xffffffffu, tid >> 5, 0);
    if (tid == 256) {
      for (int i = 0; i < 6; i++) { mbar_init(BAR(full1, i), 1); mbar_init(BAR(empty1, i), 8); }
      for (int i = 0; i < 8; i++) { mbar_init(BAR(fullA, i), 1); mbar_init(BAR(empty2, i), 8); }
      for (int i = 0; i < 14; i++) mbar_init(BAR(full2, i), 2);
      mbar_init(BAR(xbar, 0), 1);
      mbar_init(BAR(xfree, 0), 8);
      mbar_init(BAR(tbar, 0), 129);
      mbar_expect(BAR(xbar, 0), 32768);
      asm volatile("fence.mbarrier_init.release.cluster;" ::: "memory");
    }
    __syncwarp();
    asm volatile("barrier.cluster.arrive.relaxed.aligned;" ::: "memory");
    unsigned epoch = 0;
    if (tid == 320) epoch = ld_relaxed(&g_cnt[(C_LN + rb) * 32]) >> 3;
    {
      const int wsh = (2 * (c >> 3) + 2) & 15;
      const int j2 = tid - 256, off = ((c >> 3) + 16 * j2) * 514 + 64 * (c & 7) + 2 - wsh;
      const char* s0 = reinterpret_cast<const char*>(wr) + off;
      const char* s1 = reinterpret_cast<const char*>(wi) + off;
      const uint32_t d0 = sbase + SM_W + ((j2 & 15) * 8 + (j2 >> 4)) * 80;
      bar_sync(NB_INIT, 384);
      if (tid == 320) {
        mbar_expect(BAR(tbar, 0), T2_BYTES);
        bulk_load(sbase + SM_T + T1_BYTES, reinterpret_cast<const char*>(&g_tab) + T1_BYTES, T2_BYTES, BAR(tbar, 0));
      }
#pragma unroll
      for (int ch = 0; ch < 5; ch++)
        if (ch < 4 || wsh != 0) {
          cp_async16(d0 + ch * 16, s0 + ch * 16);
          cp_async16(d0 + 128 * 80 + ch * 16, s1 + ch * 16);
        }
      asm volatile("cp.async.mbarrier.arrive.noinc.shared::cta.b64 [%0];" ::"r"(BAR(tbar, 0)) : "memory");
    }
    const int nq = f >> 1, kh = f & 1;
    if (warp != 10) mbar_wait(BAR(tbar, 0), 0);
    if (warp <= 9) {
      if (lane == 0) {
        const int ax = (7 * f + 3 * (f & 1)) >> 1;
        const int ay = 7 * f + ((f & 1) ? 0 : 4);
        uint32_t s = warp - 8, ph = 1;
#pragma unroll 1
        for (int n = warp - 8; n < (warp == 8 ? 32 : 38); n += 2) {
          const uint32_t dst = sbase + (8 + s) * SLOT, fb = BAR(full1, s);
          mbar_wait(BAR(empty1, s), ph);
          if (n < 16) {
            mbar_expect(fb, 16384);
            tma3(dst, &tmGX, fb, 0, n * 32, ax);
            tma3(dst + 8192, &tmUX, fb, 0, n * 32, ax);
          } else if (n < 32) {
            mbar_expect(fb, 12288);
            tma3(dst, &tmGY, fb, 0, (n - 16) * 32, ay);
            tma3(dst + 6144, &tmUY, fb, 0, (n - 16) * 32, ay);
          }
          if (n >= 23 && warp == 9) {
            const int i = (n - 23) >> 1, kblk = 14 * kh + (int)((KORDER >> (4 * i)) & 15);
            mbar_expect(BAR(full2, i), 16384);
            tma5(sbase + i * SLOT, &tmD, BAR(full2, i), nq * 128, 2 * kblk);
            tma5(sbase + i * SLOT + 8192, &tmD, BAR(full2, i), nq * 128 + 64, 2 * kblk);
          }
          s += 2;
          if (s >= 6) { s -= 6; ph ^= 1; }
        }
        if (warp == 9) {
#pragma unroll 1
          for (int i = 8; i < 14; i++) {
            const int kblk = 14 * kh + (int)((KORDER >> (4 * i)) & 15);
            mbar_wait(BAR(empty2, i - 8), 0);
            mbar_expect(BAR(full2, i), 16384);
            tma5(sbase + (i - 8) * SLOT, &tmD, BAR(full2, i), nq * 128, 2 * kblk);
            tma5(sbase + (i - 8) * SLOT + 8192, &tmD, BAR(full2, i), nq * 128 + 64, 2 * kblk);
          }
        }
      }
    } else if (warp == 10) {
      bar_sync(NB_LN, 288);
      if (lane == 0) {
        PROFP(0);
        red_release(&g_cnt[(C_LN + rb) * 32]);
        PROFP(1);
        wait_counter(&g_cnt[(C_LN + rb) * 32], (epoch + 1) * 8);
        asm volatile("fence.proxy.async.global;" ::: "memory");
        PROFP(2);
#pragma unroll 1
        for (int kb = 0; kb < 8; kb++) {
          mbar_expect(BAR(fullA, kb), 16384);
          bulk_load(sbase + kb * SLOT, &g_LN[(rb * 8 + kb) * 1024], 16384, BAR(fullA, kb));
        }
#pragma unroll 1
        for (int i = 0; i < 4; i++) mbar_wait(BAR(empty1, 2), i & 1);
        uint32_t d = 2;
#pragma unroll 1
        for (int s = 0; s < 14; s++) {
          const int kblk = 14 * kh + (int)((KORDER >> (4 * s)) & 15);
          if (s == 0 || s == 8) {
            PROFP(3 + (s >> 2));
            wait_counter(&g_cnt[((s == 0 ? C_PX : C_PY) + rb) * 32], (epoch + 1) * 16);
            asm volatile("fence.proxy.async.global;" ::: "memory");
            PROFP(4 + (s >> 2));
          }
          if (s < 6) mbar_wait(BAR(empty1, d), s < 4 ? 0 : 1);
          else mbar_wait(BAR(empty2, s - 6), 0);
          mbar_expect(BAR(full2, s), 16384);
          bulk_load(sbase + (8 + d) * SLOT, &g_P[(rb * 28 + kblk) * 1024], 16384, BAR(full2, s));
          if (++d == 6) d = 0;
        }
        PROFP(7);
      }
    } else {
      if (lane == 0) {
        asm volatile("cp.async.bulk.prefetch.L2.global [%0], %1;" ::"l"(wg_raw + (size_t)c * 14336), "r"(14336) : "memory");
        asm volatile("cp.async.bulk.prefetch.L2.global [%0], %1;" ::"l"(wu_raw + (size_t)c * 14336), "r"(14336) : "memory");
        asm volatile("cp.async.bulk.prefetch.L2.global [%0], %1;" ::"l"(wd_raw + (size_t)c * 14336), "r"(14336) : "memory");
      }
#pragma unroll 1
      for (int e = 0; e < 4; e++) {
        bar_sync(NB_PUB0 + (e & 1), 160);
        if (lane == 0) red_release(&g_cnt[((e < 2 ? C_PX : C_PY) + rb) * 32]);
      }
    }
    __syncwarp();
    asm volatile("barrier.cluster.wait.aligned;" ::: "memory");
  } else {
    const int warp = __shfl_sync(0xffffffffu, tid >> 5, 0);
    const int g = lane >> 2, t = lane & 3;
    PROF(0);
    PROFG(14);
#pragma unroll
    for (int i = 0; i < 4; i++) {
      const int r = i >> 1, ch = (i & 1) * 32 + lane;
      cp_async16(sbase + SM_X + (2 * warp + r) * 1024 + ((ch ^ ((ch >> 2) & 6)) * 16),
                 x + (size_t)(c + 128 * (2 * warp + r)) * 512 + ch * 8);
    }
#pragma unroll
    for (int i = 0; i < 3; i++)
      cp_async16(sbase + SM_T + (tid + 256 * i) * 16, reinterpret_cast<const char*>(&g_tab) + (tid + 256 * i) * 16);
    asm volatile("cp.async.commit_group;" ::: "memory");
    const int wsh = (2 * (c >> 3) + 2) & 15;
    asm volatile("barrier.cluster.arrive.relaxed.aligned;" ::: "memory");
    asm volatile("setmaxnreg.inc.sync.aligned.u32 224;");
    unsigned epoch = 0;
    if (tid == 0) epoch = ld_relaxed(&g_cnt[C_BAR1 * 32]) >> 7;
    {
      const int ln = (tid >> 1) & 31, lg = ln >> 2, lt = ln & 3, i = 4 * (tid >> 6) + 2 * (tid & 1);
      const int kidx = lt + 8 * (i >> 3), nidx = 4 * ((i >> 1) & 3) + (lg >> 1);
      const uint32_t a0 = cfrag<2048>((c + 128 * kidx) * nidx, lg & 1), a1 = cfrag<2048>((c + 128 * (kidx + 4)) * nidx, lg & 1);
      const uint32_t b0 = cfrag<2048>(-(c + 128 * nidx) * kidx, lg & 1), b1 = cfrag<2048>(-(c + 128 * nidx) * (kidx + 4), lg & 1);
      asm volatile("st.shared.v2.u32 [%0], {%1,%2};" ::"r"(sbase + SM_FC + tid * 8), "r"(a0), "r"(a1) : "memory");
      asm volatile("st.shared.v2.u32 [%0], {%1,%2};" ::"r"(sbase + SM_FC + 2048 + tid * 8), "r"(b0), "r"(b1) : "memory");
    }
    asm volatile("cp.async.wait_group 0;" ::: "memory");
    bar_sync(NB_INIT, 384);
    PROF(13);
    {
      uint2 v[2][4];
#pragma unroll
      for (int r = 0; r < 2; r++)
#pragma unroll
        for (int q = 0; q < 4; q++)
          v[r][q] = lds2(sbase + SM_X + (2 * warp + r) * 1024 + (t + 4 * (q >> 1)) * 128 + (((4 * (q & 1) + (g >> 1)) ^ (2 * t)) * 16) + (g & 1) * 8);
      const uint4 fa = lds4(TOFF(fa));
      uint4 tw[4], fb[16];
#pragma unroll
      for (int i = 0; i < 4; i++) tw[i] = lds4(TOFF(tw1) + i * 512);
#pragma unroll
      for (int i = 0; i < 16; i++) fb[i] = lds4(TOFF(fb) + i * 512);
      float mean[2], rstd[2];
#pragma unroll
      for (int r = 0; r < 2; r++) {
        float s = 0.f;
#pragma unroll
        for (int q = 0; q < 4; q++) s += (bf_lo(v[r][q].x) + bf_hi(v[r][q].x)) + (bf_lo(v[r][q].y) + bf_hi(v[r][q].y));
        mean[r] = warp_sum(s) * (1.f / 512.f);
      }
#pragma unroll
      for (int r = 0; r < 2; r++) {
        float s = 0.f;
#pragma unroll
        for (int q = 0; q < 4; q++) {
          float a0 = bf_lo(v[r][q].x) - mean[r], a1 = bf_hi(v[r][q].x) - mean[r];
          float a2 = bf_lo(v[r][q].y) - mean[r], a3 = bf_hi(v[r][q].y) - mean[r];
          s += (a0 * a0 + a1 * a1) + (a2 * a2 + a3 * a3);
        }
        rstd[r] = rsqrtf(warp_sum(s) * (1.f / 512.f) + 1e-5f);
      }
      uint32_t alo[4][4], ahi[4][4];
#pragma unroll
      for (int r = 0; r < 2; r++)
#pragma unroll
        for (int i = 0; i < 4; i++) {
          const uint32_t sel = (i & 1) ? 0x7632u : 0x5410u;
          const uint32_t b0 = __byte_perm((i & 2) ? v[r][0].y : v[r][0].x, (i & 2) ? v[r][1].y : v[r][1].x, sel);
          const uint32_t b1 = __byte_perm((i & 2) ? v[r][2].y : v[r][2].x, (i & 2) ? v[r][3].y : v[r][3].x, sel);
          float d[4] = {0.f, 0.f, 0.f, 0.f};
          mma16816(d, fa.x, fa.y, fa.z, fa.w, b0, b1);
          const float ca = __uint_as_float(tw[i].x), sa = __uint_as_float(tw[i].y), cb = __uint_as_float(tw[i].z), sb = __uint_as_float(tw[i].w);
          const float a0 = g == 0 ? d[2] : d[0], a1 = g == 0 ? d[3] : d[1];
          const float i0 = g == 0 ? 0.f : d[2], i1 = g == 0 ? 0.f : d[3];
          const uint32_t re = pack2(a0 * ca + i0 * sa, a1 * cb + i1 * sb);
          const uint32_t im = pack2(i0 * ca - a0 * sa, i1 * cb - a1 * sb);
          const uint32_t dc = pack2(d[0] - 16.f * mean[r], d[1] - 16.f * mean[r]);
          alo[i][r] = re; alo[i][2 + r] = im;
          ahi[i][r] = g == 0 ? dc : re; ahi[i][2 + r] = g == 0 ? 0u : im;
        }
      float acc[8][4];
#pragma unroll
      for (int u = 0; u < 8; u++) {
        acc[u][0] = acc[u][1] = acc[u][2] = acc[u][3] = 0.f;
#pragma unroll
        for (int i = 0; i < 4; i++) {
          const uint4& bq = fb[i * 4 + (u >> 1)];
          if (u < 4) mma16816(acc[u], alo[i][0], alo[i][1], alo[i][2], alo[i][3], (u & 1) ? bq.z : bq.x, (u & 1) ? bq.w : bq.y);
          else       mma16816(acc[u], ahi[i][0], ahi[i][1], ahi[i][2], ahi[i][3], (u & 1) ? bq.z : bq.x, (u & 1) ? bq.w : bq.y);
        }
      }
      uint4 fc[4];
#pragma unroll
      for (int i = 0; i < 4; i++) fc[i] = lds4(sbase + SM_FC + i * 512 + lane * 16);
#pragma unroll
      for (int r = 0; r < 2; r++)
#pragma unroll
        for (int h = 0; h < 2; h++) {
          const int j = 2 * warp + r, m = 2 * t + h;
          const float rs = rstd[r];
          sts4(sbase + SM_E + ((j * 8 + m) * 8 + (g ^ (2 * t) ^ (2 * (j & 3)))) * 16,
               pack2(acc[2 * h][2 * r] * rs, acc[2 * h][2 * r + 1] * rs), pack2(acc[2 * h + 1][2 * r] * rs, acc[2 * h + 1][2 * r + 1] * rs),
               pack2(acc[4 + 2 * h][2 * r] * rs, acc[4 + 2 * h][2 * r + 1] * rs), pack2(acc[5 + 2 * h][2 * r] * rs, acc[5 + 2 * h][2 * r + 1] * rs));
        }
      bar_sync(NB_CONS, 256);
      uint4 q[4], o[4];
#pragma unroll
      for (int i = 0; i < 4; i++) q[i] = lds4(sbase + SM_E + (((t + 4 * i) * 8 + warp) * 8 + (g ^ (warp & 6) ^ (2 * t))) * 16);
      cdft16(q, fc, o);
#pragma unroll
      for (int vv = 0; vv < 4; vv++) g_Z1[(((4 * vv + t) * 8 + warp) * 128 + c) * 8 + g] = o[vv];
    }
    PROF(1);
    bar_sync(NB_CONS, 256);
    if (tid == 0) red_release(&g_cnt[C_BAR1 * 32]);
    {
      mbar_wait(BAR(tbar, 0), 0);
      uint4 f2[4], g2[4];
#pragma unroll
      for (int i = 0; i < 4; i++) {
        f2[i] = lds4(TOFF(f2) + warp * 2048 + i * 512);
        g2[i] = lds4(TOFF(g2) + warp * 2048 + i * 512);
      }
      const uint4 f8 = lds4(TOFF(f8)), g8 = lds4(TOFF(g8));
      float wfr[16], wfi[16];
      {
        const float fsc = 1.f / (1 << 19);
        const float fsc3 = ((c & 7) == 7 && g == 0) ? 0.5f * fsc : fsc;
        const int gg = g == 0 ? 8 : g;
#pragma unroll
        for (int i = 0; i < 16; i++) {
          const int ci = i >> 3, dd = (i >> 2) & 1, e = i & 3;
          const int kk = (e == 0 ? gg : e == 1 ? 16 + gg : e == 2 ? 16 - g : 32 - g) - 1;
          const uint32_t a = sbase + SM_W + ((2 * warp + ci) * 8 + t + 4 * dd) * 80 + wsh + 2 * kk;
          wfr[i] = bf_lo(lds_u16(a)) * (e == 3 ? fsc3 : fsc);
          wfi[i] = bf_lo(lds_u16(a + 128 * 80)) * (e == 3 ? fsc3 : fsc);
        }
      }
      asm volatile("barrier.cluster.wait.aligned;" ::: "memory");
      if (tid == 0) wait_counter(&g_cnt[C_BAR1 * 32], (epoch + 1) * 128);
      bar_sync(NB_CONS, 256);
      PROF(2);
      uint4 q[4], o[4];
#pragma unroll
      for (int i = 0; i < 4; i++) q[i] = ldg_cg4(&g_Z1[(c * 128 + 8 * (t + 4 * i) + warp) * 8 + g]);
      cdft16(q, f2, o);
      const uint32_t e2 = sbase + SM_E2;
#pragma unroll
      for (int vv = 0; vv < 4; vv++)
        sts4(e2 + ((warp * 16 + 4 * vv + t) * 8 + (g ^ (2 * t) ^ (2 * (warp & 3)))) * 16, o[vv].x, o[vv].y, o[vv].z, o[vv].w);
      bar_sync(NB_CONS, 256);
#pragma unroll
      for (int ci = 0; ci < 2; ci++) {
        const int cc = 2 * warp + ci;
        uint32_t ad[2];
        uint4 u[2];
#pragma unroll
        for (int hh = 0; hh < 2; hh++) {
          ad[hh] = e2 + (((t + 4 * hh) * 16 + cc) * 8 + (g ^ (2 * (cc & 3)) ^ (2 * t))) * 16;
          u[hh] = lds4(ad[hh]);
        }
        uint32_t res[2][4];
#pragma unroll
        for (int p = 0; p < 2; p++) {
          uint32_t y[2][2];
#pragma unroll
          for (int vv = 0; vv < 2; vv++) {
            float d[4] = {0.f, 0.f, 0.f, 0.f};
            mma16816(d, word(u[0], 2 * p), word(u[0], 2 * p + 1), word(u[1], 2 * p), word(u[1], 2 * p + 1), word(f8, 2 * vv), word(f8, 2 * vv + 1));
#pragma unroll
            for (int rr = 0; rr < 2; rr++) {
              const float fr = wfr[ci * 8 + vv * 4 + 2 * p + rr], fi = wfi[ci * 8 + vv * 4 + 2 * p + rr];
              y[vv][rr] = pack2(d[2 * rr] * fr - d[2 * rr + 1] * fi, d[2 * rr] * fi + d[2 * rr + 1] * fr);
            }
          }
#pragma unroll
          for (int vv = 0; vv < 2; vv++) {
            float d[4] = {0.f, 0.f, 0.f, 0.f};
            mma16816(d, y[0][0], y[0][1], y[1][0], y[1][1], word(g8, 2 * vv), word(g8, 2 * vv + 1));
            res[vv][2 * p] = pack2(d[0], d[1]);
            res[vv][2 * p + 1] = pack2(d[2], d[3]);
          }
        }
#pragma unroll
        for (int vv = 0; vv < 2; vv++) sts4(ad[vv], res[vv][0], res[vv][1], res[vv][2], res[vv][3]);
      }
      bar_sync(NB_CONS, 256);
#pragma unroll
      for (int i = 0; i < 4; i++) q[i] = lds4(e2 + ((warp * 16 + 4 * i + t) * 8 + (g ^ (2 * t) ^ (2 * (warp & 3)))) * 16);
      cdft16(q, g2, o);
#pragma unroll
      for (int vv = 0; vv < 4; vv++) g_Z2[((8 * (4 * vv + t) + warp) * 128 + c) * 8 + g] = o[vv];
    }
    PROF(3);
    bar_sync(NB_CONS, 256);
    if (tid == 0) red_release(&g_cnt[C_BAR2 * 32]);
    uint32_t hv[2][2][4];
    {
      uint4 gb[16], gc[4], tw[4], xr[2][2];
#pragma unroll
      for (int i = 0; i < 16; i++) gb[i] = lds4(TOFF(gb) + i * 512);
      const uint4 ga = lds4(TOFF(ga));
#pragma unroll
      for (int i = 0; i < 4; i++) {
        gc[i] = lds4(sbase + SM_FC + 2048 + i * 512 + lane * 16);
        tw[i] = lds4(TOFF(tw3) + i * 512);
        const int ch = 4 * (g + 8 * (i & 1)) + t;
        xr[i >> 1][i & 1] = lds4(sbase + SM_X + (2 * warp + (i >> 1)) * 1024 + ((ch ^ ((ch >> 2) & 6)) * 16));
      }
      if (tid == 0) wait_counter(&g_cnt[C_BAR2 * 32], (epoch + 1) * 128);
      bar_sync(NB_CONS, 256);
      PROF(4);
      uint4 q[4], o[4];
#pragma unroll
      for (int i = 0; i < 4; i++) q[i] = ldg_cg4(&g_Z2[((c * 16 + t + 4 * i) * 8 + warp) * 8 + g]);
      cdft16(q, gc, o);
#pragma unroll
      for (int vv = 0; vv < 4; vv++)
        sts4(sbase + SM_E + (((4 * vv + t) * 8 + warp) * 8 + (g ^ (warp & 6) ^ (2 * t))) * 16, o[vv].x, o[vv].y, o[vv].z, o[vv].w);
      bar_sync(NB_CONS, 256);
#pragma unroll
      for (int r = 0; r < 2; r++) {
        const int j = 2 * warp + r;
        uint4 u[2];
#pragma unroll
        for (int h = 0; h < 2; h++) u[h] = lds4(sbase + SM_E + ((j * 8 + 2 * t + h) * 8 + (g ^ (2 * t) ^ (2 * (j & 3)))) * 16);
        float yv[4][4];
#pragma unroll
        for (int i = 0; i < 4; i++) {
          float lo[4] = {0.f, 0.f, 0.f, 0.f}, hi[4] = {0.f, 0.f, 0.f, 0.f};
          mma16816(lo, gb[i * 4].x, gb[i * 4].y, gb[i * 4].z, gb[i * 4].w, u[0].x, u[0].y);
          mma16816(lo, gb[i * 4 + 1].x, gb[i * 4 + 1].y, gb[i * 4 + 1].z, gb[i * 4 + 1].w, u[1].x, u[1].y);
          mma16816(hi, gb[i * 4 + 2].x, gb[i * 4 + 2].y, gb[i * 4 + 2].z, gb[i * 4 + 2].w, u[0].z, u[0].w);
          mma16816(hi, gb[i * 4 + 3].x, gb[i * 4 + 3].y, gb[i * 4 + 3].z, gb[i * 4 + 3].w, u[1].z, u[1].w);
          const float ca = __uint_as_float(tw[i].x), sa = __uint_as_float(tw[i].y), cb = __uint_as_float(tw[i].z), sb = __uint_as_float(tw[i].w);
          const float tr0 = t == 0 ? lo[0] : lo[0] + hi[0], ti0 = t == 0 ? lo[2] : lo[2] + hi[2];
          const float tr1 = lo[1] + hi[1], ti1 = lo[3] + hi[3];
          const float vr0 = tr0 * ca - ti0 * sa, vi0 = tr0 * sa + ti0 * ca;
          const float vr1 = tr1 * cb - ti1 * sb, vi1 = tr1 * sb + ti1 * cb;
          const uint32_t b0 = pack2(t == 0 ? hi[0] : vr0, vr1), b1 = pack2(t == 0 ? vr0 : vi0, vi1);
          yv[i][0] = yv[i][1] = yv[i][2] = yv[i][3] = 0.f;
          mma16816(yv[i], ga.x, ga.y, ga.z, ga.w, b0, b1);
        }
#pragma unroll
        for (int h = 0; h < 2; h++) {
          hv[r][h][0] = hadd2_bf16(xr[r][h].x, pack2(yv[0][2 * h], yv[1][2 * h]));
          hv[r][h][1] = hadd2_bf16(xr[r][h].y, pack2(yv[2][2 * h], yv[3][2 * h]));
          hv[r][h][2] = hadd2_bf16(xr[r][h].z, pack2(yv[0][2 * h + 1], yv[1][2 * h + 1]));
          hv[r][h][3] = hadd2_bf16(xr[r][h].w, pack2(yv[2][2 * h + 1], yv[3][2 * h + 1]));
        }
      }
      float mean[2], rstd[2];
#pragma unroll
      for (int r = 0; r < 2; r++) {
        float s = 0.f;
#pragma unroll
        for (int i = 0; i < 8; i++) s += bf_lo(hv[r][i >> 2][i & 3]) + bf_hi(hv[r][i >> 2][i & 3]);
        mean[r] = warp_sum(s) * (1.f / 512.f);
      }
#pragma unroll
      for (int r = 0; r < 2; r++) {
        float s = 0.f;
#pragma unroll
        for (int i = 0; i < 8; i++) {
          const float a = bf_lo(hv[r][i >> 2][i & 3]) - mean[r], b = bf_hi(hv[r][i >> 2][i & 3]) - mean[r];
          s += a * a + b * b;
        }
        rstd[r] = rsqrtf(warp_sum(s) * (1.f / 512.f) + 1e-5f);
      }
#pragma unroll
      for (int r = 0; r < 2; r++) {
        const int row = 16 * f + 2 * warp + r;
        const float nm = -mean[r] * rstd[r];
#pragma unroll
        for (int h = 0; h < 2; h++) {
          uint32_t w[4];
#pragma unroll
          for (int i = 0; i < 4; i++) w[i] = pack2(fmaf(bf_lo(hv[r][h][i]), rstd[r], nm), fmaf(bf_hi(hv[r][h][i]), rstd[r], nm));
          const int n1 = g + 8 * h;
          g_LN[(rb * 8 + (n1 >> 1)) * 1024 + row * 8 + ((4 * (n1 & 1) + t) ^ (row & 7))] = make_uint4(w[0], w[1], w[2], w[3]);
        }
      }
      asm volatile("fence.proxy.async.shared::cta;" ::: "memory");
      bar_arrive(NB_LN, 288);
    }
    PROF(5);
    const int wgi = warp >> 2, wq = warp & 3;
    uint4* const pbase = &g_P[rb * 28 * 1024];
    const int p_lane = (8 * wgi + 2 * wq) * 64 + t * 8 + g;
    const uint32_t a_lo0 = desc_lo(sbase + wgi * 8192, 16);
    uint32_t slot = 0, ph = 0, prev = 0;
    {
      float acc[128];
#pragma unroll
      for (int i = 0; i < 128; i++) acc[i] = 0.f;
      if (wgi == 1) bar_sync(NB_LAG, 256);
      const uint32_t b_lo0 = desc_lo(sbase + 8 * SLOT, 4096);
#pragma unroll 1
      for (int kb = 0; kb < 8; kb++) {
        mbar_wait(BAR(fullA, kb), 0);
        if (kb == 0) PROF(6);
#pragma unroll
        for (int hh = 0; hh < 2; hh++) {
          mbar_wait(BAR(full1, slot), ph);
          const uint32_t al = a_lo0 + kb * 1024 + hh * 4, bl = b_lo0 + slot * 1024;
          wg_fence();
          wgmma_n256(acc, desc64(al, HI128), desc64(bl, HI128));
          wgmma_n256(acc, desc64(al + 2, HI128), desc64(bl + 128, HI128));
          wg_commit();
          if (hh == (LAG & 1) && kb == (LAG >> 1) && wgi == 0) bar_arrive(NB_LAG, 256);
          if (hh == 0 && kb == 0) {
#pragma unroll
            for (int i = 0; i < 4; i++)
              g_H[(c + 128 * (2 * warp + (i >> 1))) * 64 + 4 * (g + 8 * (i & 1)) + t] =
                  make_uint4(hv[i >> 1][i & 1][0], hv[i >> 1][i & 1][1], hv[i >> 1][i & 1][2], hv[i >> 1][i & 1][3]);
          }
          wg_wait<1>();
          if ((kb | hh) != 0 && lane == 0) mbar_arrive(BAR(empty1, prev));
          prev = slot;
          if (++slot == 6) { slot = 0; ph ^= 1; }
        }
      }
      wg_wait<0>();
      if (lane == 0) mbar_arrive(BAR(empty1, prev));
      PROF(7);
      store_p<4>(acc, pbase, 7 * f + 3 * (f & 1), p_lane);
      bar_arrive(NB_PUB0 + wgi, 160);
    }
    PROF(8);
    {
      float acc[96];
#pragma unroll
      for (int i = 0; i < 96; i++) acc[i] = 0.f;
      const uint32_t b_lo0 = desc_lo(sbase + 8 * SLOT, 2048);
#pragma unroll 1
      for (int kb = 0; kb < 8; kb++) {
#pragma unroll
        for (int hh = 0; hh < 2; hh++) {
          mbar_wait(BAR(full1, slot), ph);
          const uint32_t al = a_lo0 + kb * 1024 + hh * 4, bl = b_lo0 + slot * 1024;
          wg_fence();
          wgmma_n192(acc, desc64(al, HI128), desc64(bl, HI64));
          wgmma_n192(acc, desc64(al + 2, HI128), desc64(bl + 64, HI64));
          wg_commit();
          wg_wait<1>();
          if ((kb | hh) != 0 && lane == 0) mbar_arrive(BAR(empty1, prev));
          prev = slot;
          if (++slot == 6) { slot = 0; ph ^= 1; }
        }
      }
      wg_wait<0>();
      if (lane == 0) mbar_arrive(BAR(empty1, prev));
      PROF(9);
      store_p<3>(acc, pbase, 7 * f + ((f & 1) ? 0 : 4), p_lane);
      bar_arrive(NB_PUB0 + wgi, 160);
    }
    PROF(10);
    {
      const int kh = f & 1, nq = f >> 1;
      const int rh = wgi ^ kh ^ 1;
      const int orow = 8 * rb + 4 * rh + wq;
      float acc[64];
#pragma unroll
      for (int i = 0; i < 64; i++) acc[i] = 0.f;
      const uint32_t a2_lo0 = desc_lo(sbase + 8 * SLOT + rh * 8192, 128), b2_lo0 = desc_lo(sbase, 8192);
      uint4 hres[2][4];
#pragma unroll
      for (int s = 0; s < 14; s++) {
        const uint32_t al = a2_lo0 + ((s + 2) % 6) * 1024, bl = b2_lo0 + (s & 7) * 1024;
        mbar_wait(BAR(full2, s), 0);
        if (tid == 0) PROFP(16 + s);
        wg_fence();
#pragma unroll
        for (int kk = 0; kk < 4; kk++) wgmma_n128(acc, desc64(al + kk * 16, HI0), desc64(bl + kk * 128, HI128));
        wg_commit();
        if (s == 8) {
#pragma unroll
          for (int h = 0; h < 2; h++)
#pragma unroll
            for (int q = 0; q < 4; q++) hres[h][q] = ldg_cg4(&g_H[(orow + 128 * (g + 8 * h)) * 64 + nq * 16 + 4 * q + t]);
        }
        wg_wait<1>();
        if (s > 0 && s <= 8 && lane == 0) {
          mbar_arrive(BAR(empty2, s - 1));
          if (s == 8)
            asm volatile("{.reg .b32 r; mapa.shared::cluster.u32 r, %0, %1; mbarrier.arrive.shared::cluster.b64 _, [r];}"
                         ::"r"(BAR(xfree, 0)), "r"(kh ^ 1) : "memory");
        }
      }
      wg_wait<0>();
      PROF(11);
      const uint32_t xbuf = sbase + 6 * SLOT + (tid & 127) * 16;
      if (wgi == 0) {
        uint32_t rbuf, rbar;
        mbar_wait(BAR(xfree, 0), 0);
        asm volatile("mapa.shared::cluster.u32 %0, %1, %2;" : "=r"(rbuf) : "r"(xbuf), "r"(kh ^ 1));
        asm volatile("mapa.shared::cluster.u32 %0, %1, %2;" : "=r"(rbar) : "r"(BAR(xbar, 0)), "r"(kh ^ 1));
#pragma unroll
        for (int i = 0; i < 16; i++)
          asm volatile("st.async.weak.shared::cluster.mbarrier::complete_tx::bytes.v4.f32 [%0], {%1,%2,%3,%4}, [%5];"
                       ::"r"(rbuf + i * 2048), "f"(acc[4 * i]), "f"(acc[4 * i + 1]), "f"(acc[4 * i + 2]), "f"(acc[4 * i + 3]), "r"(rbar)
                       : "memory");
      } else {
        mbar_wait_cluster(BAR(xbar, 0), 0);
      }
      uint32_t w[2][16];
#pragma unroll
      for (int i = 0; i < 16; i++) {
        const uint4 pv = lds4(xbuf + i * 2048);
        w[0][i] = pack2(acc[4 * i] + __uint_as_float(pv.x), acc[4 * i + 1] + __uint_as_float(pv.y));
        w[1][i] = pack2(acc[4 * i + 2] + __uint_as_float(pv.z), acc[4 * i + 3] + __uint_as_float(pv.w));
      }
      uint4* const o4 = reinterpret_cast<uint4*>(out);
#pragma unroll
      for (int h = 0; h < 2; h++)
#pragma unroll
        for (int q = 0; q < 4; q++) {
          uint32_t a0 = w[h][4 * q], a1 = w[h][4 * q + 1], a2 = w[h][4 * q + 2], a3 = w[h][4 * q + 3];
          {
            const bool od = t & 1;
            uint32_t s0 = od ? a0 : a1, s1 = od ? a2 : a3;
            s0 = __shfl_xor_sync(0xffffffffu, s0, 1); s1 = __shfl_xor_sync(0xffffffffu, s1, 1);
            if (od) { a0 = s0; a2 = s1; } else { a1 = s0; a3 = s1; }
          }
          {
            const bool up = t & 2;
            uint32_t s0 = up ? a0 : a2, s1 = up ? a1 : a3;
            s0 = __shfl_xor_sync(0xffffffffu, s0, 2); s1 = __shfl_xor_sync(0xffffffffu, s1, 2);
            if (up) { a0 = s0; a1 = s1; } else { a2 = s0; a3 = s1; }
          }
          if (wgi == 1)
            o4[(orow + 128 * (g + 8 * h)) * 64 + nq * 16 + 4 * q + t] =
                make_uint4(hadd2_bf16(hres[h][q].x, a0), hadd2_bf16(hres[h][q].y, a1), hadd2_bf16(hres[h][q].z, a2), hadd2_bf16(hres[h][q].w, a3));
        }
      PROF(12);
      PROFG(15);
    }
  }
#undef BAR
#undef TOFF
}

typedef CUresult (*EncodeFn)(CUtensorMap*, CUtensorMapDataType, cuuint32_t, void*, const cuuint64_t*, const cuuint64_t*,
                             const cuuint32_t*, const cuuint32_t*, CUtensorMapInterleave, CUtensorMapSwizzle,
                             CUtensorMapL2promotion, CUtensorMapFloatOOBfill);

}

extern "C" void kernel_launch(void* const* d_in, const int* in_sizes, int n_in, void* d_out, int out_size) {
  (void)in_sizes; (void)n_in; (void)out_size;
  static EncodeFn encode = nullptr;
  if (!encode) {
    void* fn = nullptr;
    cudaDriverEntryPointQueryResult qr;
    cudaGetDriverEntryPoint("cuTensorMapEncodeTiled", &fn, cudaEnableDefault, &qr);
    encode = (EncodeFn)fn;
    cudaFuncSetAttribute(fused_kernel, cudaFuncAttributeMaxDynamicSharedMemorySize, SMEM_BYTES);
  }
  CUtensorMap tmGX, tmUX, tmGY, tmUY, tmD;
  const cuuint32_t es[5] = {1, 1, 1, 1, 1};
  {
    const cuuint64_t gd[3] = {64, 512, 28}, gs[2] = {3584, 128};
    const cuuint32_t bd[3] = {64, 32, 2};
    encode(&tmGX, CU_TENSOR_MAP_DATA_TYPE_BFLOAT16, 3, d_in[4], gd, gs, bd, es, CU_TENSOR_MAP_INTERLEAVE_NONE,
           CU_TENSOR_MAP_SWIZZLE_128B, CU_TENSOR_MAP_L2_PROMOTION_L2_256B, CU_TENSOR_MAP_FLOAT_OOB_FILL_NONE);
    encode(&tmUX, CU_TENSOR_MAP_DATA_TYPE_BFLOAT16, 3, d_in[5], gd, gs, bd, es, CU_TENSOR_MAP_INTERLEAVE_NONE,
           CU_TENSOR_MAP_SWIZZLE_128B, CU_TENSOR_MAP_L2_PROMOTION_L2_256B, CU_TENSOR_MAP_FLOAT_OOB_FILL_NONE);
  }
  {
    const cuuint64_t gd[3] = {32, 512, 56}, gs[2] = {3584, 64};
    const cuuint32_t bd[3] = {32, 32, 3};
    encode(&tmGY, CU_TENSOR_MAP_DATA_TYPE_BFLOAT16, 3, d_in[4], gd, gs, bd, es, CU_TENSOR_MAP_INTERLEAVE_NONE,
           CU_TENSOR_MAP_SWIZZLE_64B, CU_TENSOR_MAP_L2_PROMOTION_L2_128B, CU_TENSOR_MAP_FLOAT_OOB_FILL_NONE);
    encode(&tmUY, CU_TENSOR_MAP_DATA_TYPE_BFLOAT16, 3, d_in[5], gd, gs, bd, es, CU_TENSOR_MAP_INTERLEAVE_NONE,
           CU_TENSOR_MAP_SWIZZLE_64B, CU_TENSOR_MAP_L2_PROMOTION_L2_128B, CU_TENSOR_MAP_FLOAT_OOB_FILL_NONE);
  }
  {
    const cuuint64_t gd[5] = {512, 2, 4, 4, 56}, gs[4] = {1024, 8192, 2048, 32768};
    const cuuint32_t bd[5] = {64, 2, 4, 4, 2};
    encode(&tmD, CU_TENSOR_MAP_DATA_TYPE_BFLOAT16, 5, d_in[6], gd, gs, bd, es, CU_TENSOR_MAP_INTERLEAVE_NONE,
           CU_TENSOR_MAP_SWIZZLE_128B, CU_TENSOR_MAP_L2_PROMOTION_L2_256B, CU_TENSOR_MAP_FLOAT_OOB_FILL_NONE);
  }
  fused_kernel<<<NCTA, NTHREADS, SMEM_BYTES>>>(
      tmGX, tmUX, tmGY, tmUY, tmD, (const __nv_bfloat16*)d_in[0], (const __nv_bfloat16*)d_in[1], (const __nv_bfloat16*)d_in[2],
      (const char*)d_in[4], (const char*)d_in[5], (const char*)d_in[6], (__nv_bfloat16*)d_out);
}
```

```cpp
#include <cuda_runtime.h>
#include <cuda_bf16.h>
#include <cuda.h>
#include <stdint.h>

namespace {

constexpr int NCTA = 128;
constexpr int NTHREADS = 384;
constexpr int SLOT = 16384;
constexpr int SMEM_BYTES = 14 * SLOT + 2048 + 1024;
constexpr int SPIN_LIMIT = 1 << 22;

__device__ uint4 g_Z1[128 * 1024];
__device__ uint4 g_Z2[128 * 1024];
__device__ uint4 g_LN[16 * 8 * 1024];
__device__ uint4 g_ST[1024];
__device__ uint4 g_P[16 * 28 * 1024];
__device__ unsigned g_cnt[64 * 32];
#define PROF(i)
#define PROFP(i)
#define PROFG(i)

constexpr double ccos(int i, int n) {
  i &= n - 1;
  if (i > n / 2) i = n - i;
  if (4 * i == n) return 0.0;
  const bool neg = 4 * i > n;
  if (neg) i = n / 2 - i;
  const double a = 6.283185307179586476925 * i / n, a2 = a * a;
  double term = 1.0, sum = 1.0;
  for (int k = 1; k < 14; k++) { term *= -a2 / ((2 * k - 1) * (2 * k)); sum += term; }
  return neg ? -sum : sum;
}
constexpr double csin(int i, int n) { return ccos(i - n / 4, n); }
constexpr unsigned fbits(double v, int mant) {
  if (v == 0.0) return 0;
  const unsigned sg = v < 0 ? 1u : 0u;
  if (v < 0) v = -v;
  int e = 127;
  while (v < 1.0) { v *= 2.0; e--; }
  const unsigned m = (unsigned)((v - 1.0) * (double)(1u << mant) + 0.5);
  return (sg << (8 + mant)) + ((unsigned)e << mant) + m;
}
constexpr unsigned pkb(double lo, double hi) { return fbits(lo, 7) | (fbits(hi, 7) << 16); }
constexpr double fa_elem(int kp, int n1) {
  return kp <= 8 ? ccos(kp * n1, 16) : -csin((kp - 8) * n1, 16);
}
constexpr unsigned cfrag_c(int idx, int n, int ri) {
  return ri ? pkb(-csin(idx, n), ccos(idx, n)) : pkb(ccos(idx, n), csin(idx, n));
}
struct Tables {
  unsigned fb[16][32][4];
  unsigned tw1[8][32][4];
  unsigned fa[32][4];
  unsigned f2[8][4][32][4];
  unsigned g2[8][4][32][4];
  unsigned gb[16][32][4];
  unsigned tw3[4][32][4];
  unsigned ga[32][4];
  unsigned f8[32][4], g8[32][4];
};
constexpr int T1_BYTES = 12800, T2_BYTES = 44544;
static_assert(sizeof(Tables) == T1_BYTES + T2_BYTES, "table size");
constexpr Tables make_tables() {
  Tables T = {};
  for (int l = 0; l < 32; l++) {
    const int g = l >> 2, t = l & 3;
    for (int i = 0; i < 4; i++)
      for (int u = 0; u < 8; u++) {
        const int ri = g & 1, m = 2 * (g >> 1) + ((u & 3) >> 1);
        const double sg = u >= 4 ? -1.0 : 1.0;
        const int k2 = u >= 4 ? 31 - 2 * m - (u & 1) : 2 * m + (u & 1);
        const int pa = (8 * t + i) * k2, pb = (8 * t + 4 + i) * k2;
        T.fb[i * 4 + (u >> 1)][l][(u & 1) * 2 + 0] = ri == 0 ? pkb(ccos(pa, 32), ccos(pb, 32)) : pkb(-sg * csin(pa, 32), -sg * csin(pb, 32));
        T.fb[i * 4 + (u >> 1)][l][(u & 1) * 2 + 1] = ri == 0 ? pkb(csin(pa, 32), csin(pb, 32)) : pkb(sg * ccos(pa, 32), sg * ccos(pb, 32));
      }
    for (int i = 0; i < 4; i++)
      for (int ks = 0; ks < 4; ks++) {
        const int n2 = 4 * g + i, m = 2 * t + (ks & 1);
        const double sg = ks >= 2 ? -1.0 : 1.0;
        const int pa = n2 * (ks >= 2 ? 31 - 2 * m : 2 * m), pb = n2 * (ks >= 2 ? 30 - 2 * m : 2 * m + 1);
        T.gb[i * 4 + ks][l][0] = pkb(ccos(pa, 32), -sg * csin(pa, 32));
        T.gb[i * 4 + ks][l][1] = pkb(csin(pa, 32), sg * ccos(pa, 32));
        T.gb[i * 4 + ks][l][2] = pkb(ccos(pb, 32), -sg * csin(pb, 32));
        T.gb[i * 4 + ks][l][3] = pkb(csin(pb, 32), sg * ccos(pb, 32));
      }
    for (int i = 0; i < 4; i++) {
      for (int e = 0; e < 2; e++) {
        const int p = (8 * t + 4 * e + i) * (g == 0 ? 8 : g);
        T.tw1[2 * i + e][l][0] = fbits(g == 0 ? 0.0 : ccos(p, 512), 23);
        T.tw1[2 * i + e][l][1] = fbits(g == 0 ? ccos(p, 512) : csin(p, 512), 23);
        T.tw1[2 * i + e][l][2] = fbits(g == 0 ? 0.0 : -csin(p, 512), 23);
        T.tw1[2 * i + e][l][3] = fbits(g == 0 ? -csin(p, 512) : ccos(p, 512), 23);
      }
      const int ka = t == 0 ? 8 : 2 * t, kb = 2 * t + 1;
      T.tw3[i][l][0] = fbits(ccos((4 * g + i) * ka, 512), 23);
      T.tw3[i][l][1] = fbits(csin((4 * g + i) * ka, 512), 23);
      T.tw3[i][l][2] = fbits(ccos((4 * g + i) * kb, 512), 23);
      T.tw3[i][l][3] = fbits(csin((4 * g + i) * kb, 512), 23);
      const int p8 = (t + 4 * (i & 1)) * (4 * (i >> 1) + (g >> 1));
      T.f8[l][i] = cfrag_c(p8, 8, g & 1);
      T.g8[l][i] = cfrag_c(-p8, 8, g & 1);
    }
    for (int w = 0; w < 8; w++)
      for (int i = 0; i < 16; i++) {
        const int kidx = t + 4 * (i & 1) + 8 * (i >> 3), nidx = 4 * ((i >> 1) & 3) + (g >> 1);
        T.f2[w][i >> 2][l][i & 3] = cfrag_c((8 * kidx + w) * nidx, 128, g & 1);
        T.g2[w][i >> 2][l][i & 3] = cfrag_c(-(8 * nidx + w) * kidx, 128, g & 1);
      }
    T.fa[l][0] = pkb(fa_elem(g, 2 * t), fa_elem(g, 2 * t + 1));
    T.fa[l][1] = pkb(fa_elem(g + 8, 2 * t), fa_elem(g + 8, 2 * t + 1));
    T.fa[l][2] = pkb(fa_elem(g, 2 * t + 8), fa_elem(g, 2 * t + 9));
    T.fa[l][3] = pkb(fa_elem(g + 8, 2 * t + 8), fa_elem(g + 8, 2 * t + 9));
    T.ga[l][0] = pkb(fa_elem(2 * t, g), fa_elem(2 * t + 1, g));
    T.ga[l][1] = pkb(fa_elem(2 * t, g + 8), fa_elem(2 * t + 1, g + 8));
    T.ga[l][2] = pkb(fa_elem(2 * t + 8, g), fa_elem(2 * t + 9, g));
    T.ga[l][3] = pkb(fa_elem(2 * t + 8, g + 8), fa_elem(2 * t + 9, g + 8));
  }
  return T;
}
__device__ const __align__(128) Tables g_tab = make_tables();

__device__ __forceinline__ uint32_t s2u(const void* p) { return (uint32_t)__cvta_generic_to_shared(p); }
__device__ __forceinline__ void mbar_init(uint32_t b, int c) { asm volatile("mbarrier.init.shared::cta.b64 [%0], %1;" ::"r"(b), "r"(c)); }
__device__ __forceinline__ void mbar_expect(uint32_t b, int bytes) {
  asm volatile("mbarrier.arrive.expect_tx.shared::cta.b64 _, [%0], %1;" ::"r"(b), "r"(bytes) : "memory");
}
__device__ __forceinline__ void mbar_arrive(uint32_t b) { asm volatile("mbarrier.arrive.shared::cta.b64 _, [%0];" ::"r"(b) : "memory"); }
__device__ __forceinline__ uint32_t mbar_try(uint32_t b, uint32_t parity) {
  uint32_t ok;
  asm volatile("{.reg .pred p; mbarrier.try_wait.parity.shared::cta.b64 p, [%1], %2; selp.u32 %0,1,0,p;}"
               : "=r"(ok) : "r"(b), "r"(parity) : "memory");
  return ok;
}
__device__ __forceinline__ void mbar_wait(uint32_t b, uint32_t parity) {
  int it = 0;
  while (!mbar_try(b, parity))
    if (++it > SPIN_LIMIT) __trap();
}
__device__ __forceinline__ void mbar_wait_cluster(uint32_t b, int parity) {
  uint32_t ok;
  int it = 0;
  do {
    asm volatile("{.reg .pred p; mbarrier.try_wait.parity.acquire.cluster.shared::cta.b64 p, [%1], %2; selp.u32 %0,1,0,p;}"
                 : "=r"(ok) : "r"(b), "r"(parity) : "memory");
    if (++it > SPIN_LIMIT) __trap();
  } while (!ok);
}
__device__ __forceinline__ void bar_sync(int id, int n) { asm volatile("bar.sync %0, %1;" ::"r"(id), "r"(n) : "memory"); }
__device__ __forceinline__ void bar_arrive(int id, int n) { asm volatile("bar.arrive %0, %1;" ::"r"(id), "r"(n) : "memory"); }
__device__ __forceinline__ void red_release(unsigned* p) { asm volatile("red.release.gpu.global.add.u32 [%0], 1;" ::"l"(p) : "memory"); }
__device__ __forceinline__ unsigned ld_acquire(const unsigned* p) {
  unsigned v;
  asm volatile("ld.acquire.gpu.global.u32 %0, [%1];" : "=r"(v) : "l"(p) : "memory");
  return v;
}
__device__ __forceinline__ unsigned ld_relaxed(const unsigned* p) {
  unsigned v;
  asm volatile("ld.relaxed.gpu.global.u32 %0, [%1];" : "=r"(v) : "l"(p) : "memory");
  return v;
}
__device__ __forceinline__ void wait_counter(const unsigned* p, unsigned target) {
  int it = 0;
  while ((int)(ld_acquire(p) - target) < 0)
    if (++it > SPIN_LIMIT) __trap();
}
__device__ __forceinline__ uint4 ldg_cg4(const uint4* p) {
  uint4 v;
  asm volatile("ld.global.cg.v4.u32 {%0,%1,%2,%3}, [%4];" : "=r"(v.x), "=r"(v.y), "=r"(v.z), "=r"(v.w) : "l"(p) : "memory");
  return v;
}
__device__ __forceinline__ void sts4(uint32_t a, uint32_t x, uint32_t y, uint32_t z, uint32_t w) {
  asm volatile("st.shared.v4.u32 [%0], {%1,%2,%3,%4};" ::"r"(a), "r"(x), "r"(y), "r"(z), "r"(w) : "memory");
}
__device__ __forceinline__ uint4 lds4(uint32_t a) {
  uint4 v;
  asm volatile("ld.shared.v4.u32 {%0,%1,%2,%3}, [%4];" : "=r"(v.x), "=r"(v.y), "=r"(v.z), "=r"(v.w) : "r"(a) : "memory");
  return v;
}
__device__ __forceinline__ uint32_t pack2(float lo, float hi) {
  uint32_t r;
  asm("cvt.rn.bf16x2.f32 %0, %1, %2;" : "=r"(r) : "f"(hi), "f"(lo));
  return r;
}
__device__ __forceinline__ float bf_lo(uint32_t v) { return __uint_as_float(v << 16); }
__device__ __forceinline__ float bf_hi(uint32_t v) { return __uint_as_float(v & 0xffff0000u); }
__device__ __forceinline__ uint32_t hadd2_bf16(uint32_t a, uint32_t b) {
  uint32_t r;
  asm("add.rn.bf16x2 %0, %1, %2;" : "=r"(r) : "r"(a), "r"(b));
  return r;
}
__device__ __forceinline__ void mma16816(float (&d)[4], uint32_t a0, uint32_t a1, uint32_t a2, uint32_t a3, uint32_t b0, uint32_t b1) {
  asm("mma.sync.aligned.m16n8k16.row.col.f32.bf16.bf16.f32 {%0,%1,%2,%3}, {%4,%5,%6,%7}, {%8,%9}, {%0,%1,%2,%3};"
      : "+f"(d[0]), "+f"(d[1]), "+f"(d[2]), "+f"(d[3])
      : "r"(a0), "r"(a1), "r"(a2), "r"(a3), "r"(b0), "r"(b1));
}
template <int N>
__device__ __forceinline__ void cs_frac(int idx, float& c, float& s) {
  int i = ((idx + N / 2) & (N - 1)) - N / 2;
  float a = (float)i * (6.283185307179586f / N);
  c = __cosf(a);
  s = __sinf(a);
}
template <int N>
__device__ __forceinline__ uint32_t cfrag(int idx, int ri) {
  float c, s;
  cs_frac<N>(idx, c, s);
  return ri ? pack2(-s, c) : pack2(c, s);
}
__device__ __forceinline__ uint32_t word(const uint4& v, int e) { return e == 0 ? v.x : e == 1 ? v.y : e == 2 ? v.z : v.w; }
__device__ __forceinline__ void cdft16(const uint4 (&q)[4], const uint4 (&F)[4], uint4 (&o)[4]) {
  float acc[2][4][4];
#pragma unroll
  for (int p = 0; p < 2; p++)
#pragma unroll
    for (int v = 0; v < 4; v++) {
      acc[p][v][0] = acc[p][v][1] = acc[p][v][2] = acc[p][v][3] = 0.f;
#pragma unroll
      for (int ks = 0; ks < 2; ks++)
        mma16816(acc[p][v], word(q[2 * ks], 2 * p), word(q[2 * ks], 2 * p + 1), word(q[2 * ks + 1], 2 * p),
                 word(q[2 * ks + 1], 2 * p + 1), word(F[ks * 2 + (v >> 1)], (v & 1) * 2), word(F[ks * 2 + (v >> 1)], (v & 1) * 2 + 1));
    }
#pragma unroll
  for (int v = 0; v < 4; v++)
    o[v] = make_uint4(pack2(acc[0][v][0], acc[0][v][1]), pack2(acc[0][v][2], acc[0][v][3]),
                      pack2(acc[1][v][0], acc[1][v][1]), pack2(acc[1][v][2], acc[1][v][3]));
}
__device__ __forceinline__ void st_tag(uint4* p, const uint4& v, uint32_t tag) {
  asm volatile("{.reg .b128 r; .reg .b64 a, b; mov.b64 a, {%1,%2}; mov.b64 b, {%3,%4}; mov.b128 r, {a,b}; st.relaxed.gpu.global.b128 [%0], r;}"
               ::"l"(p), "r"((v.x & ~1u) | tag), "r"(v.y), "r"(v.z), "r"(v.w) : "memory");
}
__device__ __forceinline__ uint4 ld_b128(const uint4* p) {
  uint4 v;
  asm volatile("{.reg .b128 r; .reg .b64 a, b; ld.relaxed.gpu.global.b128 r, [%4]; mov.b128 {a,b}, r; mov.b64 {%0,%1}, a; mov.b64 {%2,%3}, b;}"
               : "=r"(v.x), "=r"(v.y), "=r"(v.z), "=r"(v.w) : "l"(p) : "memory");
  return v;
}
__device__ __forceinline__ void ld_tag4(uint4 (&q)[4], const uint4* p, int stride, uint32_t tag) {
  int it = 0;
  while (true) {
#pragma unroll
    for (int i = 0; i < 4; i++) q[i] = ld_b128(p + i * stride);
    const uint32_t bad = ((q[0].x ^ tag) | (q[1].x ^ tag) | (q[2].x ^ tag) | (q[3].x ^ tag)) & 1u;
    if (!__any_sync(0xffffffffu, bad)) break;
    if (++it > SPIN_LIMIT) __trap();
  }
#pragma unroll
  for (int i = 0; i < 4; i++) q[i].x &= ~1u;
}
__device__ __forceinline__ void row_stats(const uint32_t (&a)[8], const uint32_t (&b)[8], int lane, float (&sum)[2], float (&sq)[2]) {
  float da[4] = {0.f, 0.f, 0.f, 0.f}, db[4] = {0.f, 0.f, 0.f, 0.f}, ds[4] = {0.f, 0.f, 0.f, 0.f};
#pragma unroll
  for (int q = 0; q < 4; q++) {
    mma16816(ds, a[2 * q], b[2 * q], a[2 * q + 1], b[2 * q + 1], 0x3f803f80u, 0x3f803f80u);
    mma16816(da, a[2 * q], b[2 * q], a[2 * q + 1], b[2 * q + 1], a[2 * q], a[2 * q + 1]);
    mma16816(db, a[2 * q], b[2 * q], a[2 * q + 1], b[2 * q + 1], b[2 * q], b[2 * q + 1]);
  }
  const int src = (lane & 28) | (lane >> 3);
  const float qa = __shfl_sync(0xffffffffu, (lane & 4) ? da[1] : da[0], src);
  const float qb = __shfl_sync(0xffffffffu, (lane & 4) ? db[3] : db[2], src);
  float v = (lane & 2) ? ((lane & 1) ? ds[2] : ds[0]) : ((lane & 1) ? qb : qa);
  v += __shfl_xor_sync(0xffffffffu, v, 4);
  v += __shfl_xor_sync(0xffffffffu, v, 8);
  v += __shfl_xor_sync(0xffffffffu, v, 16);
  sq[0] = __shfl_sync(0xffffffffu, v, 0);
  sq[1] = __shfl_sync(0xffffffffu, v, 1);
  sum[0] = __shfl_sync(0xffffffffu, v, 2);
  sum[1] = __shfl_sync(0xffffffffu, v, 3);
}
__device__ __forceinline__ uint64_t desc64(uint32_t lo, uint32_t hi) {
  uint64_t d;
  asm("mov.b64 %0, {%1, %2};" : "=l"(d) : "r"(lo), "r"(hi));
  return d;
}
constexpr uint32_t desc_hi(uint32_t sbo, uint32_t swz) { return (sbo >> 4) | (swz << 30); }
__device__ __forceinline__ uint32_t desc_lo(uint32_t addr, uint32_t lbo) { return ((addr & 0x3FFFF) >> 4) | ((lbo >> 4) << 16); }
__device__ __forceinline__ void cp_async16(uint32_t dst, const void* src) {
  asm volatile("cp.async.cg.shared.global [%0], [%1], 16;" ::"r"(dst), "l"(src) : "memory");
}
__device__ __forceinline__ uint2 lds2(uint32_t a) {
  uint2 v;
  asm volatile("ld.shared.v2.u32 {%0,%1}, [%2];" : "=r"(v.x), "=r"(v.y) : "r"(a) : "memory");
  return v;
}
__device__ __forceinline__ uint32_t lds_u16(uint32_t a) {
  uint16_t v;
  asm volatile("ld.shared.u16 %0, [%1];" : "=h"(v) : "r"(a) : "memory");
  return v;
}
__device__ __forceinline__ void wg_fence() { asm volatile("wgmma.fence.sync.aligned;" ::: "memory"); }
__device__ __forceinline__ void wg_commit() { asm volatile("wgmma.commit_group.sync.aligned;" ::: "memory"); }
template <int N>
__device__ __forceinline__ void wg_wait() { asm volatile("wgmma.wait_group.sync.aligned %0;" ::"n"(N) : "memory"); }
__device__ __forceinline__ void bulk_load(uint32_t dst, const void* src, int bytes, uint32_t bar) {
  asm volatile("cp.async.bulk.shared::cluster.global.mbarrier::complete_tx::bytes [%0], [%1], %2, [%3];"
               ::"r"(dst), "l"(src), "r"(bytes), "r"(bar) : "memory");
}
__device__ __forceinline__ void tma3(uint32_t dst, const CUtensorMap* tm, uint32_t bar, int c0, int c1, int c2) {
  asm volatile("cp.async.bulk.tensor.3d.shared::cluster.global.mbarrier::complete_tx::bytes [%0], [%1, {%3,%4,%5}], [%2];"
               ::"r"(dst), "l"(tm), "r"(bar), "r"(c0), "r"(c1), "r"(c2) : "memory");
}
__device__ __forceinline__ void tma5(uint32_t dst, const CUtensorMap* tm, uint32_t bar, int c0, int c4) {
  asm volatile("cp.async.bulk.tensor.5d.shared::cluster.global.mbarrier::complete_tx::bytes [%0], [%1, {%3,%4,%4,%4,%5}], [%2];"
               ::"r"(dst), "l"(tm), "r"(bar), "r"(c0), "r"(0), "r"(c4) : "memory");
}
__device__ __forceinline__ float swiglu(float g, float u, float r) {
  float hg = (0.5f * r) * g, th;
  asm("tanh.approx.f32 %0, %1;" : "=f"(th) : "f"(hg));
  return fmaf(hg, th, hg) * (r * u);
}
__device__ __forceinline__ uint32_t hsub2_bf16(uint32_t a, uint32_t b) {
  uint32_t r;
  asm("sub.rn.bf16x2 %0, %1, %2;" : "=r"(r) : "r"(a), "r"(b));
  return r;
}
__device__ __forceinline__ void l2_prefetch(const void* p, int bytes) {
  asm volatile("cp.async.bulk.prefetch.L2.global [%0], %1;" ::"l"(p), "r"(bytes) : "memory");
}

__device__ __forceinline__ void wgmma_n256(float (&d)[128], uint64_t da, uint64_t db) {
  asm volatile("wgmma.mma_async.sync.aligned.m64n256k16.f32.bf16.bf16 {"
      "%0,%1,%2,%3,%4,%5,%6,%7,%8,%9,%10,%11,%12,%13,%14,%15,"
      "%16,%17,%18,%19,%20,%21,%22,%23,%24,%25,%26,%27,%28,%29,%30,%31,"
      "%32,%33,%34,%35,%36,%37,%38,%39,%40,%41,%42,%43,%44,%45,%46,%47,"
      "%48,%49,%50,%51,%52,%53,%54,%55,%56,%57,%58,%59,%60,%61,%62,%63,"
      "%64,%65,%66,%67,%68,%69,%70,%71,%72,%73,%74,%75,%76,%77,%78,%79,"
      "%80,%81,%82,%83,%84,%85,%86,%87,%88,%89,%90,%91,%92,%93,%94,%95,"
      "%96,%97,%98,%99,%100,%101,%102,%103,%104,%105,%106,%107,%108,%109,%110,%111,"
      "%112,%113,%114,%115,%116,%117,%118,%119,%120,%121,%122,%123,%124,%125,%126,%127"
      "}, %128, %129, 1, 1, 1, 0, 1;\n"
      : "+f"(d[0]),"+f"(d[1]),"+f"(d[2]),"+f"(d[3]),"+f"(d[4]),"+f"(d[5]),"+f"(d[6]),"+f"(d[7]),
        "+f"(d[8]),"+f"(d[9]),"+f"(d[10]),"+f"(d[11]),"+f"(d[12]),"+f"(d[13]),"+f"(d[14]),"+f"(d[15]),
        "+f"(d[16]),"+f"(d[17]),"+f"(d[18]),"+f"(d[19]),"+f"(d[20]),"+f"(d[21]),"+f"(d[22]),"+f"(d[23]),
        "+f"(d[24]),"+f"(d[25]),"+f"(d[26]),"+f"(d[27]),"+f"(d[28]),"+f"(d[29]),"+f"(d[30]),"+f"(d[31]),
        "+f"(d[32]),"+f"(d[33]),"+f"(d[34]),"+f"(d[35]),"+f"(d[36]),"+f"(d[37]),"+f"(d[38]),"+f"(d[39]),
        "+f"(d[40]),"+f"(d[41]),"+f"(d[42]),"+f"(d[43]),"+f"(d[44]),"+f"(d[45]),"+f"(d[46]),"+f"(d[47]),
        "+f"(d[48]),"+f"(d[49]),"+f"(d[50]),"+f"(d[51]),"+f"(d[52]),"+f"(d[53]),"+f"(d[54]),"+f"(d[55]),
        "+f"(d[56]),"+f"(d[57]),"+f"(d[58]),"+f"(d[59]),"+f"(d[60]),"+f"(d[61]),"+f"(d[62]),"+f"(d[63]),
        "+f"(d[64]),"+f"(d[65]),"+f"(d[66]),"+f"(d[67]),"+f"(d[68]),"+f"(d[69]),"+f"(d[70]),"+f"(d[71]),
        "+f"(d[72]),"+f"(d[73]),"+f"(d[74]),"+f"(d[75]),"+f"(d[76]),"+f"(d[77]),"+f"(d[78]),"+f"(d[79]),
        "+f"(d[80]),"+f"(d[81]),"+f"(d[82]),"+f"(d[83]),"+f"(d[84]),"+f"(d[85]),"+f"(d[86]),"+f"(d[87]),
        "+f"(d[88]),"+f"(d[89]),"+f"(d[90]),"+f"(d[91]),"+f"(d[92]),"+f"(d[93]),"+f"(d[94]),"+f"(d[95]),
        "+f"(d[96]),"+f"(d[97]),"+f"(d[98]),"+f"(d[99]),"+f"(d[100]),"+f"(d[101]),"+f"(d[102]),"+f"(d[103]),
        "+f"(d[104]),"+f"(d[105]),"+f"(d[106]),"+f"(d[107]),"+f"(d[108]),"+f"(d[109]),"+f"(d[110]),"+f"(d[111]),
        "+f"(d[112]),"+f"(d[113]),"+f"(d[114]),"+f"(d[115]),"+f"(d[116]),"+f"(d[117]),"+f"(d[118]),"+f"(d[119]),
        "+f"(d[120]),"+f"(d[121]),"+f"(d[122]),"+f"(d[123]),"+f"(d[124]),"+f"(d[125]),"+f"(d[126]),"+f"(d[127])
      : "l"(da), "l"(db));
}
__device__ __forceinline__ void wgmma_n192(float (&d)[96], uint64_t da, uint64_t db) {
  asm volatile("wgmma.mma_async.sync.aligned.m64n192k16.f32.bf16.bf16 {"
      "%0,%1,%2,%3,%4,%5,%6,%7,%8,%9,%10,%11,%12,%13,%14,%15,"
      "%16,%17,%18,%19,%20,%21,%22,%23,%24,%25,%26,%27,%28,%29,%30,%31,"
      "%32,%33,%34,%35,%36,%37,%38,%39,%40,%41,%42,%43,%44,%45,%46,%47,"
      "%48,%49,%50,%51,%52,%53,%54,%55,%56,%57,%58,%59,%60,%61,%62,%63,"
      "%64,%65,%66,%67,%68,%69,%70,%71,%72,%73,%74,%75,%76,%77,%78,%79,"
      "%80,%81,%82,%83,%84,%85,%86,%87,%88,%89,%90,%91,%92,%93,%94,%95"
      "}, %96, %97, 1, 1, 1, 0, 1;\n"
      : "+f"(d[0]),"+f"(d[1]),"+f"(d[2]),"+f"(d[3]),"+f"(d[4]),"+f"(d[5]),"+f"(d[6]),"+f"(d[7]),
        "+f"(d[8]),"+f"(d[9]),"+f"(d[10]),"+f"(d[11]),"+f"(d[12]),"+f"(d[13]),"+f"(d[14]),"+f"(d[15]),
        "+f"(d[16]),"+f"(d[17]),"+f"(d[18]),"+f"(d[19]),"+f"(d[20]),"+f"(d[21]),"+f"(d[22]),"+f"(d[23]),
        "+f"(d[24]),"+f"(d[25]),"+f"(d[26]),"+f"(d[27]),"+f"(d[28]),"+f"(d[29]),"+f"(d[30]),"+f"(d[31]),
        "+f"(d[32]),"+f"(d[33]),"+f"(d[34]),"+f"(d[35]),"+f"(d[36]),"+f"(d[37]),"+f"(d[38]),"+f"(d[39]),
        "+f"(d[40]),"+f"(d[41]),"+f"(d[42]),"+f"(d[43]),"+f"(d[44]),"+f"(d[45]),"+f"(d[46]),"+f"(d[47]),
        "+f"(d[48]),"+f"(d[49]),"+f"(d[50]),"+f"(d[51]),"+f"(d[52]),"+f"(d[53]),"+f"(d[54]),"+f"(d[55]),
        "+f"(d[56]),"+f"(d[57]),"+f"(d[58]),"+f"(d[59]),"+f"(d[60]),"+f"(d[61]),"+f"(d[62]),"+f"(d[63]),
        "+f"(d[64]),"+f"(d[65]),"+f"(d[66]),"+f"(d[67]),"+f"(d[68]),"+f"(d[69]),"+f"(d[70]),"+f"(d[71]),
        "+f"(d[72]),"+f"(d[73]),"+f"(d[74]),"+f"(d[75]),"+f"(d[76]),"+f"(d[77]),"+f"(d[78]),"+f"(d[79]),
        "+f"(d[80]),"+f"(d[81]),"+f"(d[82]),"+f"(d[83]),"+f"(d[84]),"+f"(d[85]),"+f"(d[86]),"+f"(d[87]),
        "+f"(d[88]),"+f"(d[89]),"+f"(d[90]),"+f"(d[91]),"+f"(d[92]),"+f"(d[93]),"+f"(d[94]),"+f"(d[95])
      : "l"(da), "l"(db));
}
__device__ __forceinline__ void wgmma_n128(float (&d)[64], uint64_t da, uint64_t db) {
  asm volatile("wgmma.mma_async.sync.aligned.m64n128k16.f32.bf16.bf16 {"
      "%0,%1,%2,%3,%4,%5,%6,%7,%8,%9,%10,%11,%12,%13,%14,%15,"
      "%16,%17,%18,%19,%20,%21,%22,%23,%24,%25,%26,%27,%28,%29,%30,%31,"
      "%32,%33,%34,%35,%36,%37,%38,%39,%40,%41,%42,%43,%44,%45,%46,%47,"
      "%48,%49,%50,%51,%52,%53,%54,%55,%56,%57,%58,%59,%60,%61,%62,%63"
      "}, %64, %65, 1, 1, 1, 0, 1;\n"
      : "+f"(d[0]),"+f"(d[1]),"+f"(d[2]),"+f"(d[3]),"+f"(d[4]),"+f"(d[5]),"+f"(d[6]),"+f"(d[7]),
        "+f"(d[8]),"+f"(d[9]),"+f"(d[10]),"+f"(d[11]),"+f"(d[12]),"+f"(d[13]),"+f"(d[14]),"+f"(d[15]),
        "+f"(d[16]),"+f"(d[17]),"+f"(d[18]),"+f"(d[19]),"+f"(d[20]),"+f"(d[21]),"+f"(d[22]),"+f"(d[23]),
        "+f"(d[24]),"+f"(d[25]),"+f"(d[26]),"+f"(d[27]),"+f"(d[28]),"+f"(d[29]),"+f"(d[30]),"+f"(d[31]),
        "+f"(d[32]),"+f"(d[33]),"+f"(d[34]),"+f"(d[35]),"+f"(d[36]),"+f"(d[37]),"+f"(d[38]),"+f"(d[39]),
        "+f"(d[40]),"+f"(d[41]),"+f"(d[42]),"+f"(d[43]),"+f"(d[44]),"+f"(d[45]),"+f"(d[46]),"+f"(d[47]),
        "+f"(d[48]),"+f"(d[49]),"+f"(d[50]),"+f"(d[51]),"+f"(d[52]),"+f"(d[53]),"+f"(d[54]),"+f"(d[55]),
        "+f"(d[56]),"+f"(d[57]),"+f"(d[58]),"+f"(d[59]),"+f"(d[60]),"+f"(d[61]),"+f"(d[62]),"+f"(d[63])
      : "l"(da), "l"(db));
}

constexpr int C_BAR1 = 0, C_BAR2 = 1, C_LN = 2, C_PX = 18, C_PY = 34;
constexpr int NB_CONS = 1, NB_LN = 2, NB_PUB = 3, NB_LAG = 4, NB_LAG2 = 5, NB_INIT = 6;
#define LAG 2
#define LAG2 3
#define PF2_SIG 1
#define USE_LL 1
constexpr int SM_E = 0, SM_X = 16384, SM_FC = 32768, SM_T = 36864, SM_E2 = 131072, SM_W = 147456;
constexpr unsigned long long KORDER = 0xBA9432DC876510ull;
constexpr uint32_t HI128 = desc_hi(1024, 1), HI64 = desc_hi(512, 2), HI0 = desc_hi(1024, 0);

struct Bars {
  uint64_t full1[6], empty1[6], fullA[8], full2[14], empty2[8], xbar, xfree, tbar, sbar, sig[2];
  uint32_t epoch;
};

template <int NT>
__device__ __forceinline__ void make_p(const float (&acc)[NT * 32], float r0, float r1, uint4 (&p)[NT * 2]) {
#pragma unroll
  for (int q = 0; q < NT; q++)
#pragma unroll
    for (int h = 0; h < 2; h++) {
      uint32_t w[4];
#pragma unroll
      for (int i = 0; i < 4; i++) {
        const int a = (q * 4 + i) * 4 + 2 * h, b = a + NT * 16;
        w[i] = pack2(swiglu(acc[a], acc[b], h ? r1 : r0), swiglu(acc[a + 1], acc[b + 1], h ? r1 : r0));
      }
      p[2 * q + h] = make_uint4(w[0], w[1], w[2], w[3]);
    }
}
__device__ __forceinline__ void stg4(uint4* p, const uint4& v) {
  asm volatile("st.global.v4.u32 [%0], {%1,%2,%3,%4};" ::"l"(p), "r"(v.x), "r"(v.y), "r"(v.z), "r"(v.w) : "memory");
}

__global__ void __cluster_dims__(2, 1, 1) __launch_bounds__(NTHREADS, 1)
fused_kernel(const __grid_constant__ CUtensorMap tmGX, const __grid_constant__ CUtensorMap tmUX,
             const __grid_constant__ CUtensorMap tmGY, const __grid_constant__ CUtensorMap tmUY,
             const __grid_constant__ CUtensorMap tmD, const __grid_constant__ CUtensorMap tmWR,
             const __grid_constant__ CUtensorMap tmWI, const __nv_bfloat16* __restrict__ x,
             const char* __restrict__ wg_raw, const char* __restrict__ wu_raw, const char* __restrict__ wd_raw,
             __nv_bfloat16* __restrict__ out) {
  extern __shared__ __align__(1024) char smem_raw[];
  const uint32_t sbase = (s2u(smem_raw) + 1023) & ~1023u;
  const uint32_t sbar = sbase + 14 * SLOT, sstat = sbar + 1024;
  const int tid = threadIdx.x, lane = tid & 31;
  const int c = blockIdx.x, rb = c >> 3, f = c & 7;
#define BAR(field, i) (sbar + (uint32_t)offsetof(Bars, field) + 8u * (i))
#define TOFF(field) (sbase + SM_T + (uint32_t)offsetof(Tables, field) + lane * 16)

  if (tid >= 256) {
    asm volatile("setmaxnreg.dec.sync.aligned.u32 56;");
    const int warp = __shfl_sync(0xffffffffu, tid >> 5, 0);
    if (tid == 256) {
      for (int i = 0; i < 6; i++) { mbar_init(BAR(full1, i), 1); mbar_init(BAR(empty1, i), 8); }
      for (int i = 0; i < 8; i++) { mbar_init(BAR(fullA, i), 1); mbar_init(BAR(empty2, i), 8); }
      for (int i = 0; i < 14; i++) mbar_init(BAR(full2, i), 2);
      mbar_init(BAR(xbar, 0), 1);
      mbar_init(BAR(xfree, 0), 8);
      mbar_init(BAR(tbar, 0), 1);
      mbar_init(BAR(sbar, 0), 32);
      mbar_init(BAR(sig, 0), 8);
      mbar_init(BAR(sig, 1), 8);
      mbar_expect(BAR(xbar, 0), 16384);
      asm volatile("fence.mbarrier_init.release.cluster;" ::: "memory");
    }
    if (tid == 320) {
      const unsigned e = ld_relaxed(&g_cnt[(C_LN + rb) * 32]) >> 3;
      asm volatile("st.shared.u32 [%0], %1;" ::"r"(BAR(epoch, 0)), "r"(e) : "memory");
    }
    __syncwarp();
    asm volatile("barrier.cluster.arrive.relaxed.aligned;" ::: "memory");
    bar_sync(NB_INIT, 384);
    unsigned epoch;
    asm volatile("ld.shared.u32 %0, [%1];" : "=r"(epoch) : "r"(BAR(epoch, 0)) : "memory");
    const int nq = f >> 1, kh = f & 1;
    if (warp <= 9) {
      if (lane == 0) {
        const int ax = (7 * f + 3 * (f & 1)) >> 1;
        const int ay = 7 * f + ((f & 1) ? 0 : 4);
        uint32_t s = warp - 8, ph = 1;
        mbar_wait(BAR(sig, 1), 0);
#pragma unroll 1
        for (int n = warp - 8; n < (warp == 8 ? 32 : 38); n += 2) {
          const uint32_t dst = sbase + (8 + s) * SLOT, fb = BAR(full1, s);
          mbar_wait(BAR(empty1, s), ph);
          if (n < 16) {
            mbar_expect(fb, 16384);
            tma3(dst, &tmGX, fb, 0, n * 32, ax);
            tma3(dst + 8192, &tmUX, fb, 0, n * 32, ax);
          } else if (n < 32) {
            mbar_expect(fb, 12288);
            tma3(dst, &tmGY, fb, 0, (n - 16) * 32, ay);
            tma3(dst + 6144, &tmUY, fb, 0, (n - 16) * 32, ay);
          }
          if (n >= 23 && warp == 9) {
            const int i = (n - 23) >> 1, kblk = 14 * kh + (int)((KORDER >> (4 * i)) & 15);
            mbar_expect(BAR(full2, i), 16384);
            tma5(sbase + i * SLOT, &tmD, BAR(full2, i), nq * 128, 2 * kblk);
            tma5(sbase + i * SLOT + 8192, &tmD, BAR(full2, i), nq * 128 + 64, 2 * kblk);
          }
          s += 2;
          if (s >= 6) { s -= 6; ph ^= 1; }
        }
        if (warp == 9) {
#pragma unroll 1
          for (int i = 8; i < 14; i++) {
            const int kblk = 14 * kh + (int)((KORDER >> (4 * i)) & 15);
            mbar_wait(BAR(empty2, i - 8), 0);
            mbar_expect(BAR(full2, i), 16384);
            tma5(sbase + (i - 8) * SLOT, &tmD, BAR(full2, i), nq * 128, 2 * kblk);
            tma5(sbase + (i - 8) * SLOT + 8192, &tmD, BAR(full2, i), nq * 128 + 64, 2 * kblk);
          }
        }
      }
    } else if (warp == 10) {
      if (lane == 0) {
        const int w0 = ((c >> 3) * 257 + 32 * (c & 7) + 1) & ~7;
        mbar_expect(BAR(tbar, 0), T2_BYTES + 2 * 10240);
        tma3(sbase + SM_W, &tmWR, BAR(tbar, 0), w0, 0, 0);
        tma3(sbase + SM_W + 10240, &tmWI, BAR(tbar, 0), w0, 0, 0);
        bulk_load(sbase + SM_T + T1_BYTES, reinterpret_cast<const char*>(&g_tab) + T1_BYTES, T2_BYTES, BAR(tbar, 0));
      }
      bar_sync(NB_LN, 288);
      if (lane == 0) {
        PROFP(0);
        red_release(&g_cnt[(C_LN + rb) * 32]);
        PROFP(1);
        wait_counter(&g_cnt[(C_LN + rb) * 32], (epoch + 1) * 8);
        asm volatile("fence.proxy.async.global;" ::: "memory");
        PROFP(2);
#pragma unroll 1
        for (int kb = 0; kb < 8; kb++) {
          mbar_expect(BAR(fullA, kb), 16384);
          bulk_load(sbase + kb * SLOT, &g_LN[(rb * 8 + kb) * 1024], 16384, BAR(fullA, kb));
        }
#pragma unroll 1
        for (int i = 0; i < 4; i++) mbar_wait(BAR(empty1, 2), i & 1);
        uint32_t d = 2;
#pragma unroll 1
        for (int s = 0; s < 14; s++) {
          const int kblk = 14 * kh + (int)((KORDER >> (4 * s)) & 15);
          if (s == 0 || s == 8) {
            PROFP(3 + (s >> 2));
            wait_counter(&g_cnt[((s == 0 ? C_PX : C_PY) + rb) * 32], (epoch + 1) * 8);
            asm volatile("fence.proxy.async.global;" ::: "memory");
            PROFP(4 + (s >> 2));
          }
          if (s < 6) mbar_wait(BAR(empty1, d), s < 4 ? 0 : 1);
          else mbar_wait(BAR(empty2, s - 6), 0);
          mbar_expect(BAR(full2, s), 16384);
          bulk_load(sbase + (8 + d) * SLOT, &g_P[(rb * 28 + kblk) * 1024], 16384, BAR(full2, s));
          if (++d == 6) d = 0;
        }
        PROFP(7);
      }
    } else {
      if (lane == 0) {
        l2_prefetch(wg_raw + (size_t)c * 5376, 5376);
        l2_prefetch(wu_raw + (size_t)c * 5376, 5376);
        mbar_wait(BAR(sig, PF2_SIG), 0);
        l2_prefetch(wg_raw + 688128 + (size_t)c * 8960, 8960);
        l2_prefetch(wu_raw + 688128 + (size_t)c * 8960, 8960);
      }
      mbar_wait(BAR(fullA, 7), 0);
      if (lane == 0) l2_prefetch(wd_raw + (size_t)c * 14336, 14336);
      {
        const uint32_t tag = (epoch + 1) & 1;
        uint4 v0, v1;
        int it = 0;
        while (true) {
          v0 = ld_b128(&g_ST[rb * 64 + lane]);
          v1 = ld_b128(&g_ST[rb * 64 + 32 + lane]);
          if (!__any_sync(0xffffffffu, ((v0.x ^ tag) | (v1.x ^ tag)) & 1u)) break;
          if (++it > SPIN_LIMIT) __trap();
        }
        sts4(sstat + lane * 16, v0.x & ~1u, v0.y, v0.z, v0.w);
        sts4(sstat + 512 + lane * 16, v1.x & ~1u, v1.y, v1.z, v1.w);
        mbar_arrive(BAR(sbar, 0));
      }
#pragma unroll 1
      for (int e = 0; e < 2; e++) {
        bar_sync(NB_PUB, 288);
        if (lane == 0) {
          PROFP(8 + 2 * e);
          red_release(&g_cnt[((e == 0 ? C_PX : C_PY) + rb) * 32]);
          PROFP(9 + 2 * e);
        }
      }
    }
    __syncwarp();
    asm volatile("barrier.cluster.wait.aligned;" ::: "memory");
  } else {
    const int warp = __shfl_sync(0xffffffffu, tid >> 5, 0);
    const int g = lane >> 2, t = lane & 3;
    PROF(0);
    PROFG(14);
#pragma unroll
    for (int i = 0; i < 4; i++) {
      const int r = i >> 1, ch = (i & 1) * 32 + lane;
      cp_async16(sbase + SM_X + (2 * warp + r) * 1024 + ((ch ^ ((ch >> 2) & 6)) * 16),
                 x + (size_t)(c + 128 * (2 * warp + r)) * 512 + ch * 8);
    }
#pragma unroll
    for (int i = 0; i < 4; i++)
      if (i < 3 || tid < (T1_BYTES - 12288) / 16)
        cp_async16(sbase + SM_T + (tid + 256 * i) * 16, reinterpret_cast<const char*>(&g_tab) + (tid + 256 * i) * 16);
    asm volatile("cp.async.commit_group;" ::: "memory");
    asm volatile("barrier.cluster.arrive.relaxed.aligned;" ::: "memory");
    asm volatile("setmaxnreg.inc.sync.aligned.u32 224;");
    {
      const int ln = (tid >> 1) & 31, lg = ln >> 2, lt = ln & 3, i = 4 * (tid >> 6) + 2 * (tid & 1);
      const int kidx = lt + 8 * (i >> 3), nidx = 4 * ((i >> 1) & 3) + (lg >> 1);
      const uint32_t a0 = cfrag<2048>((c + 128 * kidx) * nidx, lg & 1), a1 = cfrag<2048>((c + 128 * (kidx + 4)) * nidx, lg & 1);
      const uint32_t b0 = cfrag<2048>(-(c + 128 * nidx) * kidx, lg & 1), b1 = cfrag<2048>(-(c + 128 * nidx) * (kidx + 4), lg & 1);
      asm volatile("st.shared.v2.u32 [%0], {%1,%2};" ::"r"(sbase + SM_FC + tid * 8), "r"(a0), "r"(a1) : "memory");
      asm volatile("st.shared.v2.u32 [%0], {%1,%2};" ::"r"(sbase + SM_FC + 2048 + tid * 8), "r"(b0), "r"(b1) : "memory");
    }
    asm volatile("cp.async.wait_group 0;" ::: "memory");
    bar_sync(NB_INIT, 384);
    PROF(13);
    unsigned epoch;
    asm volatile("ld.shared.u32 %0, [%1];" : "=r"(epoch) : "r"(BAR(epoch, 0)) : "memory");
    const uint32_t tag = (epoch + 1) & 1;
    {
      uint32_t v[2][8];
#pragma unroll
      for (int r = 0; r < 2; r++)
#pragma unroll
        for (int q = 0; q < 4; q++) {
          const uint2 u = lds2(sbase + SM_X + (2 * warp + r) * 1024 + (t + 4 * (q >> 1)) * 128 + (((4 * (q & 1) + (g >> 1)) ^ (2 * t)) * 16) + (g & 1) * 8);
          v[r][2 * q] = u.x; v[r][2 * q + 1] = u.y;
        }
      const uint4 fa = lds4(TOFF(fa));
      uint4 tw[8], fb[16];
#pragma unroll
      for (int i = 0; i < 8; i++) tw[i] = lds4(TOFF(tw1) + i * 512);
#pragma unroll
      for (int i = 0; i < 16; i++) fb[i] = lds4(TOFF(fb) + i * 512);
      float sum[2], sq[2], rstd[2];
      row_stats(v[0], v[1], lane, sum, sq);
#pragma unroll
      for (int r = 0; r < 2; r++) {
        const float m = sum[r] * (1.f / 512.f);
        rstd[r] = rsqrtf(fmaxf(fmaf(-m, m, sq[r] * (1.f / 512.f)), 0.f) + 1e-5f);
      }
      uint32_t alo[4][4], ahi[4][4];
#pragma unroll
      for (int r = 0; r < 2; r++)
#pragma unroll
        for (int i = 0; i < 4; i++) {
          const uint32_t sel = (i & 1) ? 0x7632u : 0x5410u;
          const uint32_t b0 = __byte_perm(v[r][i >> 1], v[r][2 + (i >> 1)], sel);
          const uint32_t b1 = __byte_perm(v[r][4 + (i >> 1)], v[r][6 + (i >> 1)], sel);
          float d[4] = {0.f, 0.f, 0.f, 0.f};
          mma16816(d, fa.x, fa.y, fa.z, fa.w, b0, b1);
          const uint4 &ka = tw[2 * i], &kb = tw[2 * i + 1];
          const uint32_t re = pack2(d[0] * __uint_as_float(ka.x) + d[2] * __uint_as_float(ka.y), d[1] * __uint_as_float(kb.x) + d[3] * __uint_as_float(kb.y));
          const uint32_t im = pack2(d[0] * __uint_as_float(ka.z) + d[2] * __uint_as_float(ka.w), d[1] * __uint_as_float(kb.z) + d[3] * __uint_as_float(kb.w));
          const uint32_t dc = pack2(fmaf(sum[r], -1.f / 32.f, d[0]), fmaf(sum[r], -1.f / 32.f, d[1]));
          alo[i][r] = re; alo[i][2 + r] = im;
          ahi[i][r] = g == 0 ? dc : re; ahi[i][2 + r] = g == 0 ? 0u : im;
        }
      float acc[8][4];
#pragma unroll
      for (int u = 0; u < 8; u++) {
        acc[u][0] = acc[u][1] = acc[u][2] = acc[u][3] = 0.f;
#pragma unroll
        for (int i = 0; i < 4; i++) {
          const uint4& bq = fb[i * 4 + (u >> 1)];
          if (u < 4) mma16816(acc[u], alo[i][0], alo[i][1], alo[i][2], alo[i][3], (u & 1) ? bq.z : bq.x, (u & 1) ? bq.w : bq.y);
          else       mma16816(acc[u], ahi[i][0], ahi[i][1], ahi[i][2], ahi[i][3], (u & 1) ? bq.z : bq.x, (u & 1) ? bq.w : bq.y);
        }
      }
      uint4 fc[4];
#pragma unroll
      for (int i = 0; i < 4; i++) fc[i] = lds4(sbase + SM_FC + i * 512 + lane * 16);
#pragma unroll
      for (int r = 0; r < 2; r++)
#pragma unroll
        for (int h = 0; h < 2; h++) {
          const int j = 2 * warp + r, m = 2 * t + h;
          const float rs = rstd[r];
          sts4(sbase + SM_E + ((j * 8 + m) * 8 + (g ^ (2 * t) ^ (2 * (j & 3)))) * 16,
               pack2(acc[2 * h][2 * r] * rs, acc[2 * h][2 * r + 1] * rs), pack2(acc[2 * h + 1][2 * r] * rs, acc[2 * h + 1][2 * r + 1] * rs),
               pack2(acc[4 + 2 * h][2 * r] * rs, acc[4 + 2 * h][2 * r + 1] * rs), pack2(acc[5 + 2 * h][2 * r] * rs, acc[5 + 2 * h][2 * r + 1] * rs));
        }
      bar_sync(NB_CONS, 256);
      uint4 q[4], o[4];
#pragma unroll
      for (int i = 0; i < 4; i++) q[i] = lds4(sbase + SM_E + (((t + 4 * i) * 8 + warp) * 8 + (g ^ (warp & 6) ^ (2 * t))) * 16);
      cdft16(q, fc, o);
#pragma unroll
      for (int vv = 0; vv < 4; vv++) st_tag(&g_Z1[(((4 * vv + t) * 8 + warp) * 128 + c) * 8 + g], o[vv], tag);
    }
    PROF(1);
    {
      mbar_wait(BAR(tbar, 0), 0);
      uint4 f2[4], g2[4];
#pragma unroll
      for (int i = 0; i < 4; i++) {
        f2[i] = lds4(TOFF(f2) + warp * 2048 + i * 512);
        g2[i] = lds4(TOFF(g2) + warp * 2048 + i * 512);
      }
      const uint4 f8 = lds4(TOFF(f8)), g8 = lds4(TOFF(g8));
      float wfr[16], wfi[16];
      {
        const float fsc = 1.f / (1 << 19);
        const float fsc3 = ((c & 7) == 7 && g == 0) ? 0.5f * fsc : fsc;
        const int gg = g == 0 ? 8 : g, wsh = (2 * (c >> 3) + 2) & 15;
#pragma unroll
        for (int i = 0; i < 16; i++) {
          const int ci = i >> 3, dd = (i >> 2) & 1, e = i & 3;
          const int kk = (e == 0 ? gg : e == 1 ? 16 + gg : e == 2 ? 16 - g : 32 - g) - 1;
          const uint32_t a = sbase + SM_W + ((2 * warp + ci) * 8 + t + 4 * dd) * 80 + wsh + 2 * kk;
          wfr[i] = bf_lo(lds_u16(a)) * (e == 3 ? fsc3 : fsc);
          wfi[i] = bf_lo(lds_u16(a + 10240)) * (e == 3 ? fsc3 : fsc);
        }
      }
      asm volatile("barrier.cluster.wait.aligned;" ::: "memory");
      PROF(2);
      uint4 q[4], o[4];
      ld_tag4(q, &g_Z1[(c * 128 + 8 * t + warp) * 8 + g], 256, tag);
      if (lane == 0) mbar_arrive(BAR(sig, 0));
      cdft16(q, f2, o);
      const uint32_t e2 = sbase + SM_E2;
#pragma unroll
      for (int vv = 0; vv < 4; vv++)
        sts4(e2 + ((warp * 16 + 4 * vv + t) * 8 + (g ^ (2 * t) ^ (2 * (warp & 3)))) * 16, o[vv].x, o[vv].y, o[vv].z, o[vv].w);
      bar_sync(NB_CONS, 256);
#pragma unroll
      for (int ci = 0; ci < 2; ci++) {
        const int cc = 2 * warp + ci;
        uint32_t ad[2];
        uint4 u[2];
#pragma unroll
        for (int hh = 0; hh < 2; hh++) {
          ad[hh] = e2 + (((t + 4 * hh) * 16 + cc) * 8 + (g ^ (2 * (cc & 3)) ^ (2 * t))) * 16;
          u[hh] = lds4(ad[hh]);
        }
        uint32_t res[2][4];
#pragma unroll
        for (int p = 0; p < 2; p++) {
          uint32_t y[2][2];
#pragma unroll
          for (int vv = 0; vv < 2; vv++) {
            float d[4] = {0.f, 0.f, 0.f, 0.f};
            mma16816(d, word(u[0], 2 * p), word(u[0], 2 * p + 1), word(u[1], 2 * p), word(u[1], 2 * p + 1), word(f8, 2 * vv), word(f8, 2 * vv + 1));
#pragma unroll
            for (int rr = 0; rr < 2; rr++) {
              const float fr = wfr[ci * 8 + vv * 4 + 2 * p + rr], fi = wfi[ci * 8 + vv * 4 + 2 * p + rr];
              y[vv][rr] = pack2(d[2 * rr] * fr - d[2 * rr + 1] * fi, d[2 * rr] * fi + d[2 * rr + 1] * fr);
            }
          }
#pragma unroll
          for (int vv = 0; vv < 2; vv++) {
            float d[4] = {0.f, 0.f, 0.f, 0.f};
            mma16816(d, y[0][0], y[0][1], y[1][0], y[1][1], word(g8, 2 * vv), word(g8, 2 * vv + 1));
            res[vv][2 * p] = pack2(d[0], d[1]);
            res[vv][2 * p + 1] = pack2(d[2], d[3]);
          }
        }
#pragma unroll
        for (int vv = 0; vv < 2; vv++) sts4(ad[vv], res[vv][0], res[vv][1], res[vv][2], res[vv][3]);
      }
      bar_sync(NB_CONS, 256);
#pragma unroll
      for (int i = 0; i < 4; i++) q[i] = lds4(e2 + ((warp * 16 + 4 * i + t) * 8 + (g ^ (2 * t) ^ (2 * (warp & 3)))) * 16);
      cdft16(q, g2, o);
#pragma unroll
      for (int vv = 0; vv < 4; vv++) st_tag(&g_Z2[((8 * (4 * vv + t) + warp) * 128 + c) * 8 + g], o[vv], tag);
    }
    PROF(3);
    {
      uint4 gb[16], gc[4], tw[4], xr[2][2];
#pragma unroll
      for (int i = 0; i < 16; i++) gb[i] = lds4(TOFF(gb) + i * 512);
      const uint4 ga = lds4(TOFF(ga));
#pragma unroll
      for (int i = 0; i < 4; i++) {
        gc[i] = lds4(sbase + SM_FC + 2048 + i * 512 + lane * 16);
        tw[i] = lds4(TOFF(tw3) + i * 512);
        const int ch = 4 * (g + 8 * (i & 1)) + t;
        xr[i >> 1][i & 1] = lds4(sbase + SM_X + (2 * warp + (i >> 1)) * 1024 + ((ch ^ ((ch >> 2) & 6)) * 16));
      }
      asm volatile("fence.proxy.async.shared::cta;" ::: "memory");
      PROF(4);
      uint4 q[4], o[4];
      ld_tag4(q, &g_Z2[((c * 16 + t) * 8 + warp) * 8 + g], 256, tag);
      if (lane == 0) mbar_arrive(BAR(sig, 1));
      cdft16(q, gc, o);
#pragma unroll
      for (int vv = 0; vv < 4; vv++)
        sts4(sbase + SM_E + (((4 * vv + t) * 8 + warp) * 8 + (g ^ (warp & 6) ^ (2 * t))) * 16, o[vv].x, o[vv].y, o[vv].z, o[vv].w);
      bar_sync(NB_CONS, 256);
      uint32_t hv[2][8];
      const float mk = t == 0 ? 0.f : 1.f;
#pragma unroll
      for (int r = 0; r < 2; r++) {
        const int j = 2 * warp + r;
        uint4 u[2];
#pragma unroll
        for (int h = 0; h < 2; h++) u[h] = lds4(sbase + SM_E + ((j * 8 + 2 * t + h) * 8 + (g ^ (2 * t) ^ (2 * (j & 3)))) * 16);
        float yv[4][4];
#pragma unroll
        for (int i = 0; i < 4; i++) {
          float lo[4] = {0.f, 0.f, 0.f, 0.f}, hi[4] = {0.f, 0.f, 0.f, 0.f};
          mma16816(lo, gb[i * 4].x, gb[i * 4].y, gb[i * 4].z, gb[i * 4].w, u[0].x, u[0].y);
          mma16816(lo, gb[i * 4 + 1].x, gb[i * 4 + 1].y, gb[i * 4 + 1].z, gb[i * 4 + 1].w, u[1].x, u[1].y);
          mma16816(hi, gb[i * 4 + 2].x, gb[i * 4 + 2].y, gb[i * 4 + 2].z, gb[i * 4 + 2].w, u[0].z, u[0].w);
          mma16816(hi, gb[i * 4 + 3].x, gb[i * 4 + 3].y, gb[i * 4 + 3].z, gb[i * 4 + 3].w, u[1].z, u[1].w);
          const float ca = __uint_as_float(tw[i].x), sa = __uint_as_float(tw[i].y), cb = __uint_as_float(tw[i].z), sb = __uint_as_float(tw[i].w);
          const float tr0 = fmaf(hi[0], mk, lo[0]), ti0 = fmaf(hi[2], mk, lo[2]);
          const float tr1 = lo[1] + hi[1], ti1 = lo[3] + hi[3];
          const float vr0 = tr0 * ca - ti0 * sa, vi0 = tr0 * sa + ti0 * ca;
          const float vr1 = tr1 * cb - ti1 * sb, vi1 = tr1 * sb + ti1 * cb;
          const uint32_t b0 = pack2(t == 0 ? hi[0] : vr0, vr1), b1 = pack2(t == 0 ? vr0 : vi0, vi1);
          yv[i][0] = yv[i][1] = yv[i][2] = yv[i][3] = 0.f;
          mma16816(yv[i], ga.x, ga.y, ga.z, ga.w, b0, b1);
        }
#pragma unroll
        for (int h = 0; h < 2; h++) {
          hv[r][4 * h + 0] = hadd2_bf16(xr[r][h].x, pack2(yv[0][2 * h], yv[1][2 * h]));
          hv[r][4 * h + 1] = hadd2_bf16(xr[r][h].y, pack2(yv[2][2 * h], yv[3][2 * h]));
          hv[r][4 * h + 2] = hadd2_bf16(xr[r][h].z, pack2(yv[0][2 * h + 1], yv[1][2 * h + 1]));
          hv[r][4 * h + 3] = hadd2_bf16(xr[r][h].w, pack2(yv[2][2 * h + 1], yv[3][2 * h + 1]));
        }
      }
      float ds[4] = {0.f, 0.f, 0.f, 0.f};
#pragma unroll
      for (int q4 = 0; q4 < 4; q4++) mma16816(ds, hv[0][2 * q4], hv[1][2 * q4], hv[0][2 * q4 + 1], hv[1][2 * q4 + 1], 0x3f803f80u, 0x3f803f80u);
#pragma unroll
      for (int o2 = 4; o2 <= 16; o2 <<= 1) {
        ds[0] += __shfl_xor_sync(0xffffffffu, ds[0], o2);
        ds[2] += __shfl_xor_sync(0xffffffffu, ds[2], o2);
      }
      uint32_t mb[2];
#pragma unroll
      for (int r = 0; r < 2; r++) {
        const int row = 16 * f + 2 * warp + r;
        mb[r] = pack2(ds[2 * r] * (1.f / 512.f), ds[2 * r] * (1.f / 512.f));
#pragma unroll
        for (int i = 0; i < 8; i++) hv[r][i] = hsub2_bf16(hv[r][i], mb[r]);
#pragma unroll
        for (int h = 0; h < 2; h++) {
          const int n1 = g + 8 * h;
          stg4(&g_LN[(rb * 8 + (n1 >> 1)) * 1024 + row * 8 + ((4 * (n1 & 1) + t) ^ (row & 7))],
               make_uint4(hv[r][4 * h], hv[r][4 * h + 1], hv[r][4 * h + 2], hv[r][4 * h + 3]));
        }
      }
      asm volatile("fence.proxy.async.shared::cta;" ::: "memory");
      bar_arrive(NB_LN, 288);
      float sum[2], sq[2], rstd[2];
      row_stats(hv[0], hv[1], lane, sum, sq);
#pragma unroll
      for (int r = 0; r < 2; r++) {
        const float m = sum[r] * (1.f / 512.f);
        rstd[r] = rsqrtf(fmaxf(fmaf(-m, m, sq[r] * (1.f / 512.f)), 0.f) + 1e-5f);
      }
      if (lane == 0)
        st_tag(&g_ST[rb * 64 + 8 * f + warp], make_uint4(mb[0] << 16, __float_as_uint(rstd[0]), mb[1] << 16, __float_as_uint(rstd[1])), tag);
    }
    PROF(5);
    const int wgi = warp >> 2, wq = warp & 3;
    uint4* const pbase = &g_P[rb * 28 * 1024 + (8 * wgi + 2 * wq) * 64 + t * 8 + g];
    const uint32_t a_lo0 = desc_lo(sbase + wgi * 8192, 16);
    float r0, r1;
    uint4 px[8], py[6];
    {
      float acc[128];
#pragma unroll
      for (int i = 0; i < 128; i++) acc[i] = 0.f;
      if (wgi == 1) bar_sync(NB_LAG, 256);
      const uint32_t b_lo0 = desc_lo(sbase + 8 * SLOT, 4096);
      uint32_t slot = 0, ph = 0, prev = 0;
#pragma unroll 1
      for (int kb = 0; kb < 8; kb++) {
        mbar_wait(BAR(fullA, kb), 0);
        if (kb == 0) PROF(6);
#pragma unroll
        for (int hh = 0; hh < 2; hh++) {
          mbar_wait(BAR(full1, slot), ph);
          const uint32_t al = a_lo0 + kb * 1024 + hh * 4, bl = b_lo0 + slot * 1024;
          wg_fence();
          wgmma_n256(acc, desc64(al, HI128), desc64(bl, HI128));
          wgmma_n256(acc, desc64(al + 2, HI128), desc64(bl + 128, HI128));
          wg_commit();
          if (hh == (LAG & 1) && kb == (LAG >> 1) && wgi == 0) bar_arrive(NB_LAG, 256);
          wg_wait<1>();
          if ((kb | hh) != 0 && lane == 0) mbar_arrive(BAR(empty1, prev));
          prev = slot;
          if (++slot == 6) { slot = 0; ph ^= 1; }
        }
      }
      mbar_wait(BAR(sbar, 0), 0);
      r0 = __uint_as_float(lds2(sstat + (16 * warp + g) * 8).y);
      r1 = __uint_as_float(lds2(sstat + (16 * warp + g + 8) * 8).y);
      wg_wait<0>();
      if (lane == 0) mbar_arrive(BAR(empty1, prev));
      PROF(7);
      make_p<4>(acc, r0, r1, px);
    }
    PROF(8);
    {
      float acc[96];
#pragma unroll
      for (int i = 0; i < 96; i++) acc[i] = 0.f;
      const uint32_t b_lo0 = desc_lo(sbase + 8 * SLOT, 2048);
      uint4* const pdst = pbase + ((7 * f + 3 * (f & 1)) >> 1) * 1024;
#pragma unroll
      for (int k = 0; k < 16; k++) {
        mbar_wait(BAR(full1, (16 + k) % 6), ((16 + k) / 6) & 1);
        const uint32_t al = a_lo0 + (k >> 1) * 1024 + (k & 1) * 4, bl = b_lo0 + ((16 + k) % 6) * 1024;
        wg_fence();
        wgmma_n192(acc, desc64(al, HI128), desc64(bl, HI64));
        wgmma_n192(acc, desc64(al + 2, HI128), desc64(bl + 64, HI64));
        wg_commit();
        if (k < 8) stg4(pdst + (k >> 2) * 1024 + ((k >> 1) & 1) * 32 + (k & 1) * 64, px[k]);
        if (k == 7) bar_arrive(NB_PUB, 288);
        wg_wait<1>();
        if (k != 0 && lane == 0) mbar_arrive(BAR(empty1, (15 + k) % 6));
      }
      wg_wait<0>();
      if (lane == 0) mbar_arrive(BAR(empty1, 31 % 6));
      PROF(9);
      make_p<3>(acc, r0, r1, py);
    }
    PROF(10);
    {
      const int kh = f & 1, nq = f >> 1;
      const int rh = wgi ^ kh ^ 1;
      const int trow = 64 * rh + 16 * wq + g;
      const int G0 = 7 * f + (kh ? 0 : 4);
      float acc[64];
      {
        const float m0 = wgi ? __uint_as_float(lds2(sstat + trow * 8).x) : 0.f;
        const float m1 = wgi ? __uint_as_float(lds2(sstat + (trow + 8) * 8).x) : 0.f;
#pragma unroll
        for (int i = 0; i < 64; i++) acc[i] = (i & 2) ? m1 : m0;
      }
      if (wgi == 1) {
#pragma unroll
        for (int k = 0; k < 6; k++) stg4(pbase + ((G0 + (k >> 1)) >> 1) * 1024 + ((G0 + (k >> 1)) & 1) * 32 + (k & 1) * 64, py[k]);
        bar_arrive(NB_PUB, 288);
        bar_sync(NB_LAG2, 256);
      }
      const uint32_t a2_lo0 = desc_lo(sbase + 8 * SLOT + rh * 8192, 128), b2_lo0 = desc_lo(sbase, 8192);
      uint4 hres[2][4];
#pragma unroll
      for (int s = 0; s < 14; s++) {
        const uint32_t al = a2_lo0 + ((s + 2) % 6) * 1024, bl = b2_lo0 + (s & 7) * 1024;
        mbar_wait(BAR(full2, s), 0);
        if (tid == 0) PROFP(16 + s);
        wg_fence();
#pragma unroll
        for (int kk = 0; kk < 4; kk++) wgmma_n128(acc, desc64(al + kk * 16, HI0), desc64(bl + kk * 128, HI128));
        wg_commit();
        if (s < 3 && wgi == 0) {
          stg4(pbase + ((G0 + s) >> 1) * 1024 + ((G0 + s) & 1) * 32, py[2 * s]);
          stg4(pbase + ((G0 + s) >> 1) * 1024 + ((G0 + s) & 1) * 32 + 64, py[2 * s + 1]);
          if (s == 2) bar_arrive(NB_PUB, 288);
        }
        if (s == LAG2 && wgi == 0) bar_arrive(NB_LAG2, 256);
        if (s == 8) {
#pragma unroll
          for (int h = 0; h < 2; h++)
#pragma unroll
            for (int q = 0; q < 4; q++)
              hres[h][q] = ldg_cg4(&g_LN[(rb * 8 + 2 * nq + (q >> 1)) * 1024 + (trow + 8 * h) * 8 + ((4 * (q & 1) + t) ^ g)]);
        }
        wg_wait<1>();
        if (s > 0 && s <= 8 && lane == 0) {
          mbar_arrive(BAR(empty2, s - 1));
          if (s == 8)
            asm volatile("{.reg .b32 r; mapa.shared::cluster.u32 r, %0, %1; mbarrier.arrive.shared::cluster.b64 _, [r];}"
                         ::"r"(BAR(xfree, 0)), "r"(kh ^ 1) : "memory");
        }
      }
      wg_wait<0>();
      PROF(11);
      const uint32_t xbuf = sbase + 6 * SLOT + (tid & 127) * 16;
      if (wgi == 0) {
        uint32_t rbuf, rbar;
        mbar_wait(BAR(xfree, 0), 0);
        asm volatile("mapa.shared::cluster.u32 %0, %1, %2;" : "=r"(rbuf) : "r"(xbuf), "r"(kh ^ 1));
        asm volatile("mapa.shared::cluster.u32 %0, %1, %2;" : "=r"(rbar) : "r"(BAR(xbar, 0)), "r"(kh ^ 1));
#pragma unroll
        for (int i = 0; i < 8; i++)
          asm volatile("st.async.weak.shared::cluster.mbarrier::complete_tx::bytes.v4.b32 [%0], {%1,%2,%3,%4}, [%5];"
                       ::"r"(rbuf + i * 2048), "r"(pack2(acc[8 * i], acc[8 * i + 1])), "r"(pack2(acc[8 * i + 2], acc[8 * i + 3])),
                         "r"(pack2(acc[8 * i + 4], acc[8 * i + 5])), "r"(pack2(acc[8 * i + 6], acc[8 * i + 7])), "r"(rbar)
                       : "memory");
      } else {
        mbar_wait_cluster(BAR(xbar, 0), 0);
      }
      uint32_t w[2][16];
#pragma unroll
      for (int i = 0; i < 8; i++) {
        const uint4 pv = lds4(xbuf + i * 2048);
        w[0][2 * i] = pack2(acc[8 * i] + bf_lo(pv.x), acc[8 * i + 1] + bf_hi(pv.x));
        w[1][2 * i] = pack2(acc[8 * i + 2] + bf_lo(pv.y), acc[8 * i + 3] + bf_hi(pv.y));
        w[0][2 * i + 1] = pack2(acc[8 * i + 4] + bf_lo(pv.z), acc[8 * i + 5] + bf_hi(pv.z));
        w[1][2 * i + 1] = pack2(acc[8 * i + 6] + bf_lo(pv.w), acc[8 * i + 7] + bf_hi(pv.w));
      }
      uint4* const o4 = reinterpret_cast<uint4*>(out) + (8 * rb + 4 * rh + wq + 128 * g) * 64 + nq * 16 + t;
#pragma unroll
      for (int h = 0; h < 2; h++)
#pragma unroll
        for (int q = 0; q < 4; q++) {
          uint32_t a0 = w[h][4 * q], a1 = w[h][4 * q + 1], a2 = w[h][4 * q + 2], a3 = w[h][4 * q + 3];
          {
            const bool od = t & 1;
            uint32_t s0 = od ? a0 : a1, s1 = od ? a2 : a3;
            s0 = __shfl_xor_sync(0xffffffffu, s0, 1); s1 = __shfl_xor_sync(0xffffffffu, s1, 1);
            if (od) { a0 = s0; a2 = s1; } else { a1 = s0; a3 = s1; }
          }
          {
            const bool up = t & 2;
            uint32_t s0 = up ? a0 : a2, s1 = up ? a1 : a3;
            s0 = __shfl_xor_sync(0xffffffffu, s0, 2); s1 = __shfl_xor_sync(0xffffffffu, s1, 2);
            if (up) { a0 = s0; a1 = s1; } else { a2 = s0; a3 = s1; }
          }
          if (wgi == 1)
            o4[h * 1024 * 64 + 4 * q] =
                make_uint4(hadd2_bf16(hres[h][q].x, a0), hadd2_bf16(hres[h][q].y, a1), hadd2_bf16(hres[h][q].z, a2), hadd2_bf16(hres[h][q].w, a3));
        }
      PROF(12);
      PROFG(15);
    }
  }
#undef BAR
#undef TOFF
}

typedef CUresult (*EncodeFn)(CUtensorMap*, CUtensorMapDataType, cuuint32_t, void*, const cuuint64_t*, const cuuint64_t*,
                             const cuuint32_t*, const cuuint32_t*, CUtensorMapInterleave, CUtensorMapSwizzle,
                             CUtensorMapL2promotion, CUtensorMapFloatOOBfill);

}

extern "C" void kernel_launch(void* const* d_in, const int* in_sizes, int n_in, void* d_out, int out_size) {
  (void)in_sizes; (void)n_in; (void)out_size;
  static EncodeFn encode = nullptr;
  if (!encode) {
    void* fn = nullptr;
    cudaDriverEntryPointQueryResult qr;
    cudaGetDriverEntryPoint("cuTensorMapEncodeTiled", &fn, cudaEnableDefault, &qr);
    encode = (EncodeFn)fn;
    cudaFuncSetAttribute(fused_kernel, cudaFuncAttributeMaxDynamicSharedMemorySize, SMEM_BYTES);
  }
  CUtensorMap tmGX, tmUX, tmGY, tmUY, tmD, tmWR, tmWI;
  const cuuint32_t es[5] = {1, 1, 1, 1, 1};
  auto enc = [&](CUtensorMap* m, void* p, int rank, const cuuint64_t* gd, const cuuint64_t* gs, const cuuint32_t* bd,
                 CUtensorMapSwizzle sw, CUtensorMapL2promotion pr) {
    encode(m, CU_TENSOR_MAP_DATA_TYPE_BFLOAT16, rank, p, gd, gs, bd, es, CU_TENSOR_MAP_INTERLEAVE_NONE, sw, pr,
           CU_TENSOR_MAP_FLOAT_OOB_FILL_NONE);
  };
  {
    const cuuint64_t gd[3] = {64, 512, 28}, gs[2] = {3584, 128};
    const cuuint32_t bd[3] = {64, 32, 2};
    enc(&tmGX, d_in[4], 3, gd, gs, bd, CU_TENSOR_MAP_SWIZZLE_128B, CU_TENSOR_MAP_L2_PROMOTION_L2_256B);
    enc(&tmUX, d_in[5], 3, gd, gs, bd, CU_TENSOR_MAP_SWIZZLE_128B, CU_TENSOR_MAP_L2_PROMOTION_L2_256B);
  }
  {
    const cuuint64_t gd[3] = {32, 512, 56}, gs[2] = {3584, 64};
    const cuuint32_t bd[3] = {32, 32, 3};
    enc(&tmGY, d_in[4], 3, gd, gs, bd, CU_TENSOR_MAP_SWIZZLE_64B, CU_TENSOR_MAP_L2_PROMOTION_L2_128B);
    enc(&tmUY, d_in[5], 3, gd, gs, bd, CU_TENSOR_MAP_SWIZZLE_64B, CU_TENSOR_MAP_L2_PROMOTION_L2_128B);
  }
  {
    const cuuint64_t gd[5] = {512, 2, 4, 4, 56}, gs[4] = {1024, 8192, 2048, 32768};
    const cuuint32_t bd[5] = {64, 2, 4, 4, 2};
    enc(&tmD, d_in[6], 5, gd, gs, bd, CU_TENSOR_MAP_SWIZZLE_128B, CU_TENSOR_MAP_L2_PROMOTION_L2_256B);
  }
  {
    const cuuint64_t gd[3] = {4112, 8, 16}, gs[2] = {16 * 8224, 8224};
    const cuuint32_t bd[3] = {40, 8, 16};
    enc(&tmWR, d_in[1], 3, gd, gs, bd, CU_TENSOR_MAP_SWIZZLE_NONE, CU_TENSOR_MAP_L2_PROMOTION_NONE);
    enc(&tmWI, d_in[2], 3, gd, gs, bd, CU_TENSOR_MAP_SWIZZLE_NONE, CU_TENSOR_MAP_L2_PROMOTION_NONE);
  }
  fused_kernel<<<NCTA, NTHREADS, SMEM_BYTES>>>(tmGX, tmUX, tmGY, tmUY, tmD, tmWR, tmWI, (const __nv_bfloat16*)d_in[0],
                                               (const char*)d_in[4], (const char*)d_in[5], (const char*)d_in[6],
                                               (__nv_bfloat16*)d_out);
}
```

```cpp
#include <cuda_runtime.h>
#include <cuda_bf16.h>
#include <cuda.h>
#include <stdint.h>

namespace {

constexpr int NCTA = 128;
constexpr int NTHREADS = 384;
constexpr int SLOT = 16384;
constexpr int SMEM_BYTES = 14 * SLOT + 2048 + 1024;
constexpr int SPIN_LIMIT = 1 << 22;

__device__ uint4 g_Z1[128 * 1024];
__device__ uint4 g_Z2[128 * 1024];
__device__ uint4 g_LN[16 * 8 * 1024];
__device__ uint4 g_ST[1024];
__device__ uint4 g_P[16 * 28 * 1024];
__device__ unsigned g_cnt[64 * 32];
#define PROF(i)
#define PROFP(i)
#define PROFG(i)

constexpr double ccos(int i, int n) {
  i &= n - 1;
  if (i > n / 2) i = n - i;
  if (4 * i == n) return 0.0;
  const bool neg = 4 * i > n;
  if (neg) i = n / 2 - i;
  const double a = 6.283185307179586476925 * i / n, a2 = a * a;
  double term = 1.0, sum = 1.0;
  for (int k = 1; k < 14; k++) { term *= -a2 / ((2 * k - 1) * (2 * k)); sum += term; }
  return neg ? -sum : sum;
}
constexpr double csin(int i, int n) { return ccos(i - n / 4, n); }
constexpr unsigned fbits(double v, int mant) {
  if (v == 0.0) return 0;
  const unsigned sg = v < 0 ? 1u : 0u;
  if (v < 0) v = -v;
  int e = 127;
  while (v < 1.0) { v *= 2.0; e--; }
  const unsigned m = (unsigned)((v - 1.0) * (double)(1u << mant) + 0.5);
  return (sg << (8 + mant)) + ((unsigned)e << mant) + m;
}
constexpr unsigned pkb(double lo, double hi) { return fbits(lo, 7) | (fbits(hi, 7) << 16); }
constexpr double fa_elem(int kp, int n1) {
  return kp <= 8 ? ccos(kp * n1, 16) : -csin((kp - 8) * n1, 16);
}
constexpr unsigned cfrag_c(int idx, int n, int ri) {
  return ri ? pkb(-csin(idx, n), ccos(idx, n)) : pkb(ccos(idx, n), csin(idx, n));
}
struct Tables {
  unsigned fb[16][32][4];
  unsigned tw1[8][32][4];
  unsigned fa[32][4];
  unsigned f2[8][4][32][4];
  unsigned g2[8][4][32][4];
  unsigned gb[16][32][4];
  unsigned tw3[4][32][4];
  unsigned ga[32][4];
  unsigned f8[32][4], g8[32][4];
};
constexpr int T1_BYTES = 12800, T2_BYTES = 44544;
static_assert(sizeof(Tables) == T1_BYTES + T2_BYTES, "table size");
constexpr Tables make_tables() {
  Tables T = {};
  for (int l = 0; l < 32; l++) {
    const int g = l >> 2, t = l & 3;
    for (int i = 0; i < 4; i++)
      for (int u = 0; u < 8; u++) {
        const int ri = g & 1, m = 2 * (g >> 1) + ((u & 3) >> 1);
        const double sg = u >= 4 ? -1.0 : 1.0;
        const int k2 = u >= 4 ? 31 - 2 * m - (u & 1) : 2 * m + (u & 1);
        const int pa = (8 * t + i) * k2, pb = (8 * t + 4 + i) * k2;
        T.fb[i * 4 + (u >> 1)][l][(u & 1) * 2 + 0] = ri == 0 ? pkb(ccos(pa, 32), ccos(pb, 32)) : pkb(-sg * csin(pa, 32), -sg * csin(pb, 32));
        T.fb[i * 4 + (u >> 1)][l][(u & 1) * 2 + 1] = ri == 0 ? pkb(csin(pa, 32), csin(pb, 32)) : pkb(sg * ccos(pa, 32), sg * ccos(pb, 32));
      }
    for (int i = 0; i < 4; i++)
      for (int ks = 0; ks < 4; ks++) {
        const int n2 = 4 * g + i, m = 2 * t + (ks & 1);
        const double sg = ks >= 2 ? -1.0 : 1.0;
        const int pa = n2 * (ks >= 2 ? 31 - 2 * m : 2 * m), pb = n2 * (ks >= 2 ? 30 - 2 * m : 2 * m + 1);
        T.gb[i * 4 + ks][l][0] = pkb(ccos(pa, 32), -sg * csin(pa, 32));
        T.gb[i * 4 + ks][l][1] = pkb(csin(pa, 32), sg * ccos(pa, 32));
        T.gb[i * 4 + ks][l][2] = pkb(ccos(pb, 32), -sg * csin(pb, 32));
        T.gb[i * 4 + ks][l][3] = pkb(csin(pb, 32), sg * ccos(pb, 32));
      }
    for (int i = 0; i < 4; i++) {
      for (int e = 0; e < 2; e++) {
        const int p = (8 * t + 4 * e + i) * (g == 0 ? 8 : g);
        T.tw1[2 * i + e][l][0] = fbits(g == 0 ? 0.0 : ccos(p, 512), 23);
        T.tw1[2 * i + e][l][1] = fbits(g == 0 ? ccos(p, 512) : csin(p, 512), 23);
        T.tw1[2 * i + e][l][2] = fbits(g == 0 ? 0.0 : -csin(p, 512), 23);
        T.tw1[2 * i + e][l][3] = fbits(g == 0 ? -csin(p, 512) : ccos(p, 512), 23);
      }
      const int ka = t == 0 ? 8 : 2 * t, kb = 2 * t + 1;
      T.tw3[i][l][0] = fbits(ccos((4 * g + i) * ka, 512), 23);
      T.tw3[i][l][1] = fbits(csin((4 * g + i) * ka, 512), 23);
      T.tw3[i][l][2] = fbits(ccos((4 * g + i) * kb, 512), 23);
      T.tw3[i][l][3] = fbits(csin((4 * g + i) * kb, 512), 23);
      const int p8 = (t + 4 * (i & 1)) * (4 * (i >> 1) + (g >> 1));
      T.f8[l][i] = cfrag_c(p8, 8, g & 1);
      T.g8[l][i] = cfrag_c(-p8, 8, g & 1);
    }
    for (int w = 0; w < 8; w++)
      for (int i = 0; i < 16; i++) {
        const int kidx = t + 4 * (i & 1) + 8 * (i >> 3), nidx = 4 * ((i >> 1) & 3) + (g >> 1);
        T.f2[w][i >> 2][l][i & 3] = cfrag_c((8 * kidx + w) * nidx, 128, g & 1);
        T.g2[w][i >> 2][l][i & 3] = cfrag_c(-(8 * nidx + w) * kidx, 128, g & 1);
      }
    T.fa[l][0] = pkb(fa_elem(g, 2 * t), fa_elem(g, 2 * t + 1));
    T.fa[l][1] = pkb(fa_elem(g + 8, 2 * t), fa_elem(g + 8, 2 * t + 1));
    T.fa[l][2] = pkb(fa_elem(g, 2 * t + 8), fa_elem(g, 2 * t + 9));
    T.fa[l][3] = pkb(fa_elem(g + 8, 2 * t + 8), fa_elem(g + 8, 2 * t + 9));
    T.ga[l][0] = pkb(fa_elem(2 * t, g), fa_elem(2 * t + 1, g));
    T.ga[l][1] = pkb(fa_elem(2 * t, g + 8), fa_elem(2 * t + 1, g + 8));
    T.ga[l][2] = pkb(fa_elem(2 * t + 8, g), fa_elem(2 * t + 9, g));
    T.ga[l][3] = pkb(fa_elem(2 * t + 8, g + 8), fa_elem(2 * t + 9, g + 8));
  }
  return T;
}
__device__ const __align__(128) Tables g_tab = make_tables();

__device__ __forceinline__ uint32_t s2u(const void* p) { return (uint32_t)__cvta_generic_to_shared(p); }
__device__ __forceinline__ void mbar_init(uint32_t b, int c) { asm volatile("mbarrier.init.shared::cta.b64 [%0], %1;" ::"r"(b), "r"(c)); }
__device__ __forceinline__ void mbar_expect(uint32_t b, int bytes) {
  asm volatile("mbarrier.arrive.expect_tx.shared::cta.b64 _, [%0], %1;" ::"r"(b), "r"(bytes) : "memory");
}
__device__ __forceinline__ void mbar_arrive(uint32_t b) { asm volatile("mbarrier.arrive.shared::cta.b64 _, [%0];" ::"r"(b) : "memory"); }
__device__ __forceinline__ uint32_t mbar_try(uint32_t b, uint32_t parity) {
  uint32_t ok;
  asm volatile("{.reg .pred p; mbarrier.try_wait.parity.shared::cta.b64 p, [%1], %2; selp.u32 %0,1,0,p;}"
               : "=r"(ok) : "r"(b), "r"(parity) : "memory");
  return ok;
}
__device__ __forceinline__ void mbar_wait(uint32_t b, uint32_t parity) {
  int it = 0;
  while (!mbar_try(b, parity))
    if (++it > SPIN_LIMIT) __trap();
}
__device__ __forceinline__ void mbar_wait_cluster(uint32_t b, int parity) {
  uint32_t ok;
  int it = 0;
  do {
    asm volatile("{.reg .pred p; mbarrier.try_wait.parity.acquire.cluster.shared::cta.b64 p, [%1], %2; selp.u32 %0,1,0,p;}"
                 : "=r"(ok) : "r"(b), "r"(parity) : "memory");
    if (++it > SPIN_LIMIT) __trap();
  } while (!ok);
}
__device__ __forceinline__ void bar_sync(int id, int n) { asm volatile("bar.sync %0, %1;" ::"r"(id), "r"(n) : "memory"); }
__device__ __forceinline__ void bar_arrive(int id, int n) { asm volatile("bar.arrive %0, %1;" ::"r"(id), "r"(n) : "memory"); }
__device__ __forceinline__ void red_release(unsigned* p) { asm volatile("red.release.gpu.global.add.u32 [%0], 1;" ::"l"(p) : "memory"); }
__device__ __forceinline__ unsigned ld_acquire(const unsigned* p) {
  unsigned v;
  asm volatile("ld.acquire.gpu.global.u32 %0, [%1];" : "=r"(v) : "l"(p) : "memory");
  return v;
}
__device__ __forceinline__ unsigned ld_relaxed(const unsigned* p) {
  unsigned v;
  asm volatile("ld.relaxed.gpu.global.u32 %0, [%1];" : "=r"(v) : "l"(p) : "memory");
  return v;
}
__device__ __forceinline__ void wait_counter(const unsigned* p, unsigned target) {
  int it = 0;
  while ((int)(ld_acquire(p) - target) < 0)
    if (++it > SPIN_LIMIT) __trap();
}
__device__ __forceinline__ uint4 ldg_cg4(const uint4* p) {
  uint4 v;
  asm volatile("ld.global.cg.v4.u32 {%0,%1,%2,%3}, [%4];" : "=r"(v.x), "=r"(v.y), "=r"(v.z), "=r"(v.w) : "l"(p) : "memory");
  return v;
}
__device__ __forceinline__ void sts4(uint32_t a, uint32_t x, uint32_t y, uint32_t z, uint32_t w) {
  asm volatile("st.shared.v4.u32 [%0], {%1,%2,%3,%4};" ::"r"(a), "r"(x), "r"(y), "r"(z), "r"(w) : "memory");
}
__device__ __forceinline__ uint4 lds4(uint32_t a) {
  uint4 v;
  asm volatile("ld.shared.v4.u32 {%0,%1,%2,%3}, [%4];" : "=r"(v.x), "=r"(v.y), "=r"(v.z), "=r"(v.w) : "r"(a) : "memory");
  return v;
}
__device__ __forceinline__ uint32_t pack2(float lo, float hi) {
  uint32_t r;
  asm("cvt.rn.bf16x2.f32 %0, %1, %2;" : "=r"(r) : "f"(hi), "f"(lo));
  return r;
}
__device__ __forceinline__ float bf_lo(uint32_t v) { return __uint_as_float(v << 16); }
__device__ __forceinline__ float bf_hi(uint32_t v) { return __uint_as_float(v & 0xffff0000u); }
__device__ __forceinline__ uint32_t hadd2_bf16(uint32_t a, uint32_t b) {
  uint32_t r;
  asm("add.rn.bf16x2 %0, %1, %2;" : "=r"(r) : "r"(a), "r"(b));
  return r;
}
__device__ __forceinline__ void mma16816(float (&d)[4], uint32_t a0, uint32_t a1, uint32_t a2, uint32_t a3, uint32_t b0, uint32_t b1) {
  asm("mma.sync.aligned.m16n8k16.row.col.f32.bf16.bf16.f32 {%0,%1,%2,%3}, {%4,%5,%6,%7}, {%8,%9}, {%0,%1,%2,%3};"
      : "+f"(d[0]), "+f"(d[1]), "+f"(d[2]), "+f"(d[3])
      : "r"(a0), "r"(a1), "r"(a2), "r"(a3), "r"(b0), "r"(b1));
}
template <int N>
__device__ __forceinline__ void cs_frac(int idx, float& c, float& s) {
  int i = ((idx + N / 2) & (N - 1)) - N / 2;
  float a = (float)i * (6.283185307179586f / N);
  c = __cosf(a);
  s = __sinf(a);
}
template <int N>
__device__ __forceinline__ uint32_t cfrag(int idx, int ri) {
  float c, s;
  cs_frac<N>(idx, c, s);
  return ri ? pack2(-s, c) : pack2(c, s);
}
__device__ __forceinline__ uint32_t word(const uint4& v, int e) { return e == 0 ? v.x : e == 1 ? v.y : e == 2 ? v.z : v.w; }
__device__ __forceinline__ void cdft16(const uint4 (&q)[4], const uint4 (&F)[4], uint4 (&o)[4]) {
  float acc[2][4][4];
#pragma unroll
  for (int p = 0; p < 2; p++)
#pragma unroll
    for (int v = 0; v < 4; v++) {
      acc[p][v][0] = acc[p][v][1] = acc[p][v][2] = acc[p][v][3] = 0.f;
#pragma unroll
      for (int ks = 0; ks < 2; ks++)
        mma16816(acc[p][v], word(q[2 * ks], 2 * p), word(q[2 * ks], 2 * p + 1), word(q[2 * ks + 1], 2 * p),
                 word(q[2 * ks + 1], 2 * p + 1), word(F[ks * 2 + (v >> 1)], (v & 1) * 2), word(F[ks * 2 + (v >> 1)], (v & 1) * 2 + 1));
    }
#pragma unroll
  for (int v = 0; v < 4; v++)
    o[v] = make_uint4(pack2(acc[0][v][0], acc[0][v][1]), pack2(acc[0][v][2], acc[0][v][3]),
                      pack2(acc[1][v][0], acc[1][v][1]), pack2(acc[1][v][2], acc[1][v][3]));
}
__device__ __forceinline__ void st_tag(uint4* p, const uint4& v, uint32_t tag) {
  asm volatile("{.reg .b128 r; .reg .b64 a, b; mov.b64 a, {%1,%2}; mov.b64 b, {%3,%4}; mov.b128 r, {a,b}; st.relaxed.gpu.global.b128 [%0], r;}"
               ::"l"(p), "r"((v.x & ~1u) | tag), "r"(v.y), "r"(v.z), "r"(v.w) : "memory");
}
__device__ __forceinline__ uint4 ld_b128(const uint4* p) {
  uint4 v;
  asm volatile("{.reg .b128 r; .reg .b64 a, b; ld.relaxed.gpu.global.b128 r, [%4]; mov.b128 {a,b}, r; mov.b64 {%0,%1}, a; mov.b64 {%2,%3}, b;}"
               : "=r"(v.x), "=r"(v.y), "=r"(v.z), "=r"(v.w) : "l"(p) : "memory");
  return v;
}
__device__ __forceinline__ void ld_tag4_issue(uint4 (&q)[4], const uint4* p) {
#pragma unroll
  for (int i = 0; i < 4; i++) q[i] = ld_b128(p + i * 256);
}
__device__ __forceinline__ void ld_tag4_finish(uint4 (&q)[4], const uint4* p, uint32_t tag) {
  int it = 0;
  while (__any_sync(0xffffffffu, ((q[0].x ^ tag) | (q[1].x ^ tag) | (q[2].x ^ tag) | (q[3].x ^ tag)) & 1u)) {
#pragma unroll
    for (int i = 0; i < 4; i++)
      if ((q[i].x ^ tag) & 1u) q[i] = ld_b128(p + i * 256);
    if (++it > SPIN_LIMIT) __trap();
  }
#pragma unroll
  for (int i = 0; i < 4; i++) q[i].x &= ~1u;
}
__device__ __forceinline__ void row_stats(const uint32_t (&a)[8], const uint32_t (&b)[8], int lane, float (&sum)[2], float (&sq)[2]) {
  float da[4] = {0.f, 0.f, 0.f, 0.f}, db[4] = {0.f, 0.f, 0.f, 0.f}, ds[4] = {0.f, 0.f, 0.f, 0.f};
#pragma unroll
  for (int q = 0; q < 4; q++) {
    mma16816(ds, a[2 * q], b[2 * q], a[2 * q + 1], b[2 * q + 1], 0x3f803f80u, 0x3f803f80u);
    mma16816(da, a[2 * q], b[2 * q], a[2 * q + 1], b[2 * q + 1], a[2 * q], a[2 * q + 1]);
    mma16816(db, a[2 * q], b[2 * q], a[2 * q + 1], b[2 * q + 1], b[2 * q], b[2 * q + 1]);
  }
  const int src = (lane & 28) | (lane >> 3);
  const float qa = __shfl_sync(0xffffffffu, (lane & 4) ? da[1] : da[0], src);
  const float qb = __shfl_sync(0xffffffffu, (lane & 4) ? db[3] : db[2], src);
  float v = (lane & 2) ? ((lane & 1) ? ds[2] : ds[0]) : ((lane & 1) ? qb : qa);
  v += __shfl_xor_sync(0xffffffffu, v, 4);
  v += __shfl_xor_sync(0xffffffffu, v, 8);
  v += __shfl_xor_sync(0xffffffffu, v, 16);
  sq[0] = __shfl_sync(0xffffffffu, v, 0);
  sq[1] = __shfl_sync(0xffffffffu, v, 1);
  sum[0] = __shfl_sync(0xffffffffu, v, 2);
  sum[1] = __shfl_sync(0xffffffffu, v, 3);
}
__device__ __forceinline__ uint64_t desc64(uint32_t lo, uint32_t hi) {
  uint64_t d;
  asm("mov.b64 %0, {%1, %2};" : "=l"(d) : "r"(lo), "r"(hi));
  return d;
}
constexpr uint32_t desc_hi(uint32_t sbo, uint32_t swz) { return (sbo >> 4) | (swz << 30); }
__device__ __forceinline__ uint32_t desc_lo(uint32_t addr, uint32_t lbo) { return ((addr & 0x3FFFF) >> 4) | ((lbo >> 4) << 16); }
__device__ __forceinline__ void cp_async16(uint32_t dst, const void* src) {
  asm volatile("cp.async.cg.shared.global [%0], [%1], 16;" ::"r"(dst), "l"(src) : "memory");
}
__device__ __forceinline__ uint2 lds2(uint32_t a) {
  uint2 v;
  asm volatile("ld.shared.v2.u32 {%0,%1}, [%2];" : "=r"(v.x), "=r"(v.y) : "r"(a) : "memory");
  return v;
}
__device__ __forceinline__ uint32_t lds_u16(uint32_t a) {
  uint16_t v;
  asm volatile("ld.shared.u16 %0, [%1];" : "=h"(v) : "r"(a) : "memory");
  return v;
}
__device__ __forceinline__ void wg_fence() { asm volatile("wgmma.fence.sync.aligned;" ::: "memory"); }
__device__ __forceinline__ void wg_commit() { asm volatile("wgmma.commit_group.sync.aligned;" ::: "memory"); }
template <int N>
__device__ __forceinline__ void wg_wait() { asm volatile("wgmma.wait_group.sync.aligned %0;" ::"n"(N) : "memory"); }
__device__ __forceinline__ void bulk_load(uint32_t dst, const void* src, int bytes, uint32_t bar) {
  asm volatile("cp.async.bulk.shared::cluster.global.mbarrier::complete_tx::bytes [%0], [%1], %2, [%3];"
               ::"r"(dst), "l"(src), "r"(bytes), "r"(bar) : "memory");
}
__device__ __forceinline__ void tma3(uint32_t dst, const CUtensorMap* tm, uint32_t bar, int c0, int c1, int c2) {
  asm volatile("cp.async.bulk.tensor.3d.shared::cluster.global.mbarrier::complete_tx::bytes [%0], [%1, {%3,%4,%5}], [%2];"
               ::"r"(dst), "l"(tm), "r"(bar), "r"(c0), "r"(c1), "r"(c2) : "memory");
}
__device__ __forceinline__ void tma3_mc(uint32_t dst, const CUtensorMap* tm, uint32_t bar, int c1, int c2) {
  asm volatile("cp.async.bulk.tensor.3d.shared::cluster.global.mbarrier::complete_tx::bytes.multicast::cluster [%0], [%1, {%3,%4,%5}], [%2], %6;"
               ::"r"(dst), "l"(tm), "r"(bar), "r"(0), "r"(c1), "r"(c2), "h"((uint16_t)3) : "memory");
}
__device__ __forceinline__ void mbar_arrive_remote(uint32_t rb) {
  asm volatile("mbarrier.arrive.shared::cluster.b64 _, [%0];" ::"r"(rb) : "memory");
}
__device__ __forceinline__ uint4 ldg_ca4(const void* p) {
  uint4 v;
  asm volatile("ld.global.ca.v4.u32 {%0,%1,%2,%3}, [%4];" : "=r"(v.x), "=r"(v.y), "=r"(v.z), "=r"(v.w) : "l"(p) : "memory");
  return v;
}
__device__ __forceinline__ void tma5(uint32_t dst, const CUtensorMap* tm, uint32_t bar, int c0, int c4) {
  asm volatile("cp.async.bulk.tensor.5d.shared::cluster.global.mbarrier::complete_tx::bytes [%0], [%1, {%3,%4,%4,%4,%5}], [%2];"
               ::"r"(dst), "l"(tm), "r"(bar), "r"(c0), "r"(0), "r"(c4) : "memory");
}
__device__ __forceinline__ float swiglu(float g, float u, float r) {
  float hg = (0.5f * r) * g, th;
  asm("tanh.approx.f32 %0, %1;" : "=f"(th) : "f"(hg));
  return fmaf(hg, th, hg) * (r * u);
}
__device__ __forceinline__ uint32_t hsub2_bf16(uint32_t a, uint32_t b) {
  uint32_t r;
  asm("sub.rn.bf16x2 %0, %1, %2;" : "=r"(r) : "r"(a), "r"(b));
  return r;
}
__device__ __forceinline__ void l2_prefetch(const void* p, int bytes) {
  asm volatile("cp.async.bulk.prefetch.L2.global [%0], %1;" ::"l"(p), "r"(bytes) : "memory");
}

__device__ __forceinline__ void wgmma_n256(float (&d)[128], uint64_t da, uint64_t db) {
  asm volatile("wgmma.mma_async.sync.aligned.m64n256k16.f32.bf16.bf16 {"
      "%0,%1,%2,%3,%4,%5,%6,%7,%8,%9,%10,%11,%12,%13,%14,%15,"
      "%16,%17,%18,%19,%20,%21,%22,%23,%24,%25,%26,%27,%28,%29,%30,%31,"
      "%32,%33,%34,%35,%36,%37,%38,%39,%40,%41,%42,%43,%44,%45,%46,%47,"
      "%48,%49,%50,%51,%52,%53,%54,%55,%56,%57,%58,%59,%60,%61,%62,%63,"
      "%64,%65,%66,%67,%68,%69,%70,%71,%72,%73,%74,%75,%76,%77,%78,%79,"
      "%80,%81,%82,%83,%84,%85,%86,%87,%88,%89,%90,%91,%92,%93,%94,%95,"
      "%96,%97,%98,%99,%100,%101,%102,%103,%104,%105,%106,%107,%108,%109,%110,%111,"
      "%112,%113,%114,%115,%116,%117,%118,%119,%120,%121,%122,%123,%124,%125,%126,%127"
      "}, %128, %129, 1, 1, 1, 0, 1;\n"
      : "+f"(d[0]),"+f"(d[1]),"+f"(d[2]),"+f"(d[3]),"+f"(d[4]),"+f"(d[5]),"+f"(d[6]),"+f"(d[7]),
        "+f"(d[8]),"+f"(d[9]),"+f"(d[10]),"+f"(d[11]),"+f"(d[12]),"+f"(d[13]),"+f"(d[14]),"+f"(d[15]),
        "+f"(d[16]),"+f"(d[17]),"+f"(d[18]),"+f"(d[19]),"+f"(d[20]),"+f"(d[21]),"+f"(d[22]),"+f"(d[23]),
        "+f"(d[24]),"+f"(d[25]),"+f"(d[26]),"+f"(d[27]),"+f"(d[28]),"+f"(d[29]),"+f"(d[30]),"+f"(d[31]),
        "+f"(d[32]),"+f"(d[33]),"+f"(d[34]),"+f"(d[35]),"+f"(d[36]),"+f"(d[37]),"+f"(d[38]),"+f"(d[39]),
        "+f"(d[40]),"+f"(d[41]),"+f"(d[42]),"+f"(d[43]),"+f"(d[44]),"+f"(d[45]),"+f"(d[46]),"+f"(d[47]),
        "+f"(d[48]),"+f"(d[49]),"+f"(d[50]),"+f"(d[51]),"+f"(d[52]),"+f"(d[53]),"+f"(d[54]),"+f"(d[55]),
        "+f"(d[56]),"+f"(d[57]),"+f"(d[58]),"+f"(d[59]),"+f"(d[60]),"+f"(d[61]),"+f"(d[62]),"+f"(d[63]),
        "+f"(d[64]),"+f"(d[65]),"+f"(d[66]),"+f"(d[67]),"+f"(d[68]),"+f"(d[69]),"+f"(d[70]),"+f"(d[71]),
        "+f"(d[72]),"+f"(d[73]),"+f"(d[74]),"+f"(d[75]),"+f"(d[76]),"+f"(d[77]),"+f"(d[78]),"+f"(d[79]),
        "+f"(d[80]),"+f"(d[81]),"+f"(d[82]),"+f"(d[83]),"+f"(d[84]),"+f"(d[85]),"+f"(d[86]),"+f"(d[87]),
        "+f"(d[88]),"+f"(d[89]),"+f"(d[90]),"+f"(d[91]),"+f"(d[92]),"+f"(d[93]),"+f"(d[94]),"+f"(d[95]),
        "+f"(d[96]),"+f"(d[97]),"+f"(d[98]),"+f"(d[99]),"+f"(d[100]),"+f"(d[101]),"+f"(d[102]),"+f"(d[103]),
        "+f"(d[104]),"+f"(d[105]),"+f"(d[106]),"+f"(d[107]),"+f"(d[108]),"+f"(d[109]),"+f"(d[110]),"+f"(d[111]),
        "+f"(d[112]),"+f"(d[113]),"+f"(d[114]),"+f"(d[115]),"+f"(d[116]),"+f"(d[117]),"+f"(d[118]),"+f"(d[119]),
        "+f"(d[120]),"+f"(d[121]),"+f"(d[122]),"+f"(d[123]),"+f"(d[124]),"+f"(d[125]),"+f"(d[126]),"+f"(d[127])
      : "l"(da), "l"(db));
}
__device__ __forceinline__ void wgmma_n192(float (&d)[96], uint64_t da, uint64_t db) {
  asm volatile("wgmma.mma_async.sync.aligned.m64n192k16.f32.bf16.bf16 {"
      "%0,%1,%2,%3,%4,%5,%6,%7,%8,%9,%10,%11,%12,%13,%14,%15,"
      "%16,%17,%18,%19,%20,%21,%22,%23,%24,%25,%26,%27,%28,%29,%30,%31,"
      "%32,%33,%34,%35,%36,%37,%38,%39,%40,%41,%42,%43,%44,%45,%46,%47,"
      "%48,%49,%50,%51,%52,%53,%54,%55,%56,%57,%58,%59,%60,%61,%62,%63,"
      "%64,%65,%66,%67,%68,%69,%70,%71,%72,%73,%74,%75,%76,%77,%78,%79,"
      "%80,%81,%82,%83,%84,%85,%86,%87,%88,%89,%90,%91,%92,%93,%94,%95"
      "}, %96, %97, 1, 1, 1, 0, 1;\n"
      : "+f"(d[0]),"+f"(d[1]),"+f"(d[2]),"+f"(d[3]),"+f"(d[4]),"+f"(d[5]),"+f"(d[6]),"+f"(d[7]),
        "+f"(d[8]),"+f"(d[9]),"+f"(d[10]),"+f"(d[11]),"+f"(d[12]),"+f"(d[13]),"+f"(d[14]),"+f"(d[15]),
        "+f"(d[16]),"+f"(d[17]),"+f"(d[18]),"+f"(d[19]),"+f"(d[20]),"+f"(d[21]),"+f"(d[22]),"+f"(d[23]),
        "+f"(d[24]),"+f"(d[25]),"+f"(d[26]),"+f"(d[27]),"+f"(d[28]),"+f"(d[29]),"+f"(d[30]),"+f"(d[31]),
        "+f"(d[32]),"+f"(d[33]),"+f"(d[34]),"+f"(d[35]),"+f"(d[36]),"+f"(d[37]),"+f"(d[38]),"+f"(d[39]),
        "+f"(d[40]),"+f"(d[41]),"+f"(d[42]),"+f"(d[43]),"+f"(d[44]),"+f"(d[45]),"+f"(d[46]),"+f"(d[47]),
        "+f"(d[48]),"+f"(d[49]),"+f"(d[50]),"+f"(d[51]),"+f"(d[52]),"+f"(d[53]),"+f"(d[54]),"+f"(d[55]),
        "+f"(d[56]),"+f"(d[57]),"+f"(d[58]),"+f"(d[59]),"+f"(d[60]),"+f"(d[61]),"+f"(d[62]),"+f"(d[63]),
        "+f"(d[64]),"+f"(d[65]),"+f"(d[66]),"+f"(d[67]),"+f"(d[68]),"+f"(d[69]),"+f"(d[70]),"+f"(d[71]),
        "+f"(d[72]),"+f"(d[73]),"+f"(d[74]),"+f"(d[75]),"+f"(d[76]),"+f"(d[77]),"+f"(d[78]),"+f"(d[79]),
        "+f"(d[80]),"+f"(d[81]),"+f"(d[82]),"+f"(d[83]),"+f"(d[84]),"+f"(d[85]),"+f"(d[86]),"+f"(d[87]),
        "+f"(d[88]),"+f"(d[89]),"+f"(d[90]),"+f"(d[91]),"+f"(d[92]),"+f"(d[93]),"+f"(d[94]),"+f"(d[95])
      : "l"(da), "l"(db));
}
__device__ __forceinline__ void wgmma_n128(float (&d)[64], uint64_t da, uint64_t db) {
  asm volatile("wgmma.mma_async.sync.aligned.m64n128k16.f32.bf16.bf16 {"
      "%0,%1,%2,%3,%4,%5,%6,%7,%8,%9,%10,%11,%12,%13,%14,%15,"
      "%16,%17,%18,%19,%20,%21,%22,%23,%24,%25,%26,%27,%28,%29,%30,%31,"
      "%32,%33,%34,%35,%36,%37,%38,%39,%40,%41,%42,%43,%44,%45,%46,%47,"
      "%48,%49,%50,%51,%52,%53,%54,%55,%56,%57,%58,%59,%60,%61,%62,%63"
      "}, %64, %65, 1, 1, 1, 0, 1;\n"
      : "+f"(d[0]),"+f"(d[1]),"+f"(d[2]),"+f"(d[3]),"+f"(d[4]),"+f"(d[5]),"+f"(d[6]),"+f"(d[7]),
        "+f"(d[8]),"+f"(d[9]),"+f"(d[10]),"+f"(d[11]),"+f"(d[12]),"+f"(d[13]),"+f"(d[14]),"+f"(d[15]),
        "+f"(d[16]),"+f"(d[17]),"+f"(d[18]),"+f"(d[19]),"+f"(d[20]),"+f"(d[21]),"+f"(d[22]),"+f"(d[23]),
        "+f"(d[24]),"+f"(d[25]),"+f"(d[26]),"+f"(d[27]),"+f"(d[28]),"+f"(d[29]),"+f"(d[30]),"+f"(d[31]),
        "+f"(d[32]),"+f"(d[33]),"+f"(d[34]),"+f"(d[35]),"+f"(d[36]),"+f"(d[37]),"+f"(d[38]),"+f"(d[39]),
        "+f"(d[40]),"+f"(d[41]),"+f"(d[42]),"+f"(d[43]),"+f"(d[44]),"+f"(d[45]),"+f"(d[46]),"+f"(d[47]),
        "+f"(d[48]),"+f"(d[49]),"+f"(d[50]),"+f"(d[51]),"+f"(d[52]),"+f"(d[53]),"+f"(d[54]),"+f"(d[55]),
        "+f"(d[56]),"+f"(d[57]),"+f"(d[58]),"+f"(d[59]),"+f"(d[60]),"+f"(d[61]),"+f"(d[62]),"+f"(d[63])
      : "l"(da), "l"(db));
}

constexpr int C_LN = 0, C_PX = 16, C_PY = 32;
constexpr int NB_CONS = 1, NB_LN = 2, NB_PUB = 3, NB_LAG = 4, NB_LAG2 = 5, NB_INIT = 6, NB_RDY = 7;
#define LAG 2
#define LAG2 3
#define EARLY_POLL 1
#define PF2_SIG 1
constexpr int SM_E = 0, SM_X = 16384, SM_FC = 32768, SM_T = 36864, SM_E2 = 131072, SM_W = 147456;
constexpr unsigned long long KORDER = 0xBA9432DC876510ull;
constexpr uint32_t HI128 = desc_hi(1024, 1), HI64 = desc_hi(512, 2), HI0 = desc_hi(1024, 0);

struct Bars {
  uint64_t full1[6], empty1[6], fullA[8], full2[14], empty2[8], xbar, xfree, tbar, sbar, sig[2];
  uint32_t epoch;
};

template <int NT>
__device__ __forceinline__ void make_p(const float (&acc)[NT * 32], float r0, float r1, uint4 (&p)[NT * 2]) {
#pragma unroll
  for (int q = 0; q < NT; q++)
#pragma unroll
    for (int h = 0; h < 2; h++) {
      uint32_t w[4];
#pragma unroll
      for (int i = 0; i < 4; i++) {
        const int a = (q * 4 + i) * 4 + 2 * h, b = a + NT * 16;
        w[i] = pack2(swiglu(acc[a], acc[b], h ? r1 : r0), swiglu(acc[a + 1], acc[b + 1], h ? r1 : r0));
      }
      p[2 * q + h] = make_uint4(w[0], w[1], w[2], w[3]);
    }
}
__device__ __forceinline__ void stg4(uint4* p, const uint4& v) {
  asm volatile("st.global.v4.u32 [%0], {%1,%2,%3,%4};" ::"l"(p), "r"(v.x), "r"(v.y), "r"(v.z), "r"(v.w) : "memory");
}

__global__ void __cluster_dims__(2, 1, 1) __launch_bounds__(NTHREADS, 1)
fused_kernel(const __grid_constant__ CUtensorMap tmGX, const __grid_constant__ CUtensorMap tmUX,
             const __grid_constant__ CUtensorMap tmGY, const __grid_constant__ CUtensorMap tmUY,
             const __grid_constant__ CUtensorMap tmD, const __grid_constant__ CUtensorMap tmWR,
             const __grid_constant__ CUtensorMap tmWI, const __nv_bfloat16* __restrict__ x,
             const char* __restrict__ wg_raw, const char* __restrict__ wu_raw, const char* __restrict__ wd_raw,
             __nv_bfloat16* __restrict__ out) {
  extern __shared__ __align__(1024) char smem_raw[];
  const uint32_t sbase = (s2u(smem_raw) + 1023) & ~1023u;
  const uint32_t sbar = sbase + 14 * SLOT, sstat = sbar + 512;
  const int tid = threadIdx.x, lane = tid & 31;
  const int c = blockIdx.x, kh = c & 1, f = (c >> 1) & 7, rb = 2 * (c >> 4) + kh, rb2 = 2 * (c >> 4) + (f >> 2), nq = f & 3;
#define BAR(field, i) (sbar + (uint32_t)offsetof(Bars, field) + 8u * (i))
#define TOFF(field) (sbase + SM_T + (uint32_t)offsetof(Tables, field) + lane * 16)

  if (tid >= 256) {
    asm volatile("setmaxnreg.dec.sync.aligned.u32 56;");
    const int warp = __shfl_sync(0xffffffffu, tid >> 5, 0);
    if (tid == 256) {
      for (int i = 0; i < 6; i++) { mbar_init(BAR(full1, i), 1); mbar_init(BAR(empty1, i), 16); }
      for (int i = 0; i < 8; i++) { mbar_init(BAR(fullA, i), 1); mbar_init(BAR(empty2, i), 8); }
      for (int i = 0; i < 14; i++) mbar_init(BAR(full2, i), 2);
      mbar_init(BAR(xbar, 0), 1);
      mbar_init(BAR(xfree, 0), 8);
      mbar_init(BAR(tbar, 0), 1);
      mbar_init(BAR(sbar, 0), 32);
      mbar_init(BAR(sig, 0), 8);
      mbar_init(BAR(sig, 1), 16);
      mbar_expect(BAR(xbar, 0), 16384);
      asm volatile("fence.mbarrier_init.release.cluster;" ::: "memory");
    }
    if (tid == 320) {
      const unsigned e = ld_relaxed(&g_cnt[(C_LN + rb) * 32]) >> 3;
      asm volatile("st.shared.u32 [%0], %1;" ::"r"(BAR(epoch, 0)), "r"(e) : "memory");
    }
    __syncwarp();
    asm volatile("barrier.cluster.arrive.relaxed.aligned;" ::: "memory");
    bar_arrive(NB_RDY, 384);
    bar_sync(NB_INIT, 384);
    unsigned epoch;
    asm volatile("ld.shared.u32 %0, [%1];" : "=r"(epoch) : "r"(BAR(epoch, 0)) : "memory");
    if (warp == 8) {
      if (lane == 0) {
        const int ax = (7 * f + 3 * (f & 1)) >> 1;
        const int ay = 7 * f + ((f & 1) ? 0 : 4);
        const CUtensorMap* tx = kh ? &tmUX : &tmGX;
        const CUtensorMap* ty = kh ? &tmUY : &tmGY;
        uint32_t s = 0, ph = 1;
        mbar_wait(BAR(sig, 1), 0);
#pragma unroll 1
        for (int n = 0; n < 32; n++) {
          const uint32_t dst = sbase + (8 + s) * SLOT, fb = BAR(full1, s);
          mbar_wait(BAR(empty1, s), ph);
          if (n < 16) {
            mbar_expect(fb, 16384);
            tma3_mc(dst + kh * 8192, tx, fb, n * 32, ax);
          } else {
            mbar_expect(fb, 12288);
            tma3_mc(dst + kh * 6144, ty, fb, (n - 16) * 32, ay);
          }
          if (++s == 6) { s = 0; ph ^= 1; }
        }
      }
    } else if (warp == 9) {
      if (lane == 0) {
        mbar_wait(BAR(empty1, 5), 0);
        mbar_wait(BAR(empty1, 5), 1);
#pragma unroll 1
        for (int i = 0; i < 14; i++) {
          const int kblk = 14 * kh + (int)((KORDER >> (4 * i)) & 15);
          if (i < 8) mbar_wait(BAR(empty1, (17 + 2 * i) % 6), ((17 + 2 * i) / 6) & 1);
          else mbar_wait(BAR(empty2, i - 8), 0);
          mbar_expect(BAR(full2, i), 16384);
          tma5(sbase + (i & 7) * SLOT, &tmD, BAR(full2, i), nq * 128, 2 * kblk);
          tma5(sbase + (i & 7) * SLOT + 8192, &tmD, BAR(full2, i), nq * 128 + 64, 2 * kblk);
        }
      }
    } else if (warp == 10) {
      if (lane == 0) {
        const int w0 = ((c >> 3) * 257 + 32 * (c & 7) + 1) & ~7;
        mbar_expect(BAR(tbar, 0), T2_BYTES + 2 * 10240);
        tma3(sbase + SM_W, &tmWR, BAR(tbar, 0), w0, 0, 0);
        tma3(sbase + SM_W + 10240, &tmWI, BAR(tbar, 0), w0, 0, 0);
        bulk_load(sbase + SM_T + T1_BYTES, reinterpret_cast<const char*>(&g_tab) + T1_BYTES, T2_BYTES, BAR(tbar, 0));
      }
      bar_sync(NB_LN, 288);
      if (lane == 0) {
        PROFP(0);
        red_release(&g_cnt[(C_LN + rb) * 32]);
        PROFP(1);
        wait_counter(&g_cnt[(C_LN + rb) * 32], (epoch + 1) * 8);
        asm volatile("fence.proxy.async.global;" ::: "memory");
        PROFP(2);
#pragma unroll 1
        for (int kb = 0; kb < 8; kb++) {
          mbar_expect(BAR(fullA, kb), 16384);
          bulk_load(sbase + kb * SLOT, &g_LN[(rb * 8 + kb) * 1024], 16384, BAR(fullA, kb));
        }
#pragma unroll 1
        for (int i = 0; i < 4; i++) mbar_wait(BAR(empty1, 2), i & 1);
        uint32_t d = 2;
#pragma unroll 1
        for (int s = 0; s < 14; s++) {
          const int kblk = 14 * kh + (int)((KORDER >> (4 * s)) & 15);
          if (s == 0 || s == 8) {
            PROFP(3 + (s >> 2));
            wait_counter(&g_cnt[((s == 0 ? C_PX : C_PY) + rb2) * 32], (epoch + 1) * 8);
            asm volatile("fence.proxy.async.global;" ::: "memory");
            PROFP(4 + (s >> 2));
          }
          if (s < 6) mbar_wait(BAR(empty1, d), s < 4 ? 0 : 1);
          else mbar_wait(BAR(empty2, s - 6), 0);
          mbar_expect(BAR(full2, s), 16384);
          bulk_load(sbase + (8 + d) * SLOT, &g_P[(rb2 * 28 + kblk) * 1024], 16384, BAR(full2, s));
          if (++d == 6) d = 0;
        }
        PROFP(7);
      }
    } else {
      if (lane == 0) {
        l2_prefetch(wg_raw + (size_t)c * 5376, 5376);
        l2_prefetch(wu_raw + (size_t)c * 5376, 5376);
        mbar_wait(BAR(sig, PF2_SIG), 0);
        l2_prefetch(wg_raw + 688128 + (size_t)c * 8960, 8960);
        l2_prefetch(wu_raw + 688128 + (size_t)c * 8960, 8960);
      }
      mbar_wait(BAR(fullA, 7), 0);
      if (lane == 0) l2_prefetch(wd_raw + (size_t)c * 14336, 14336);
      {
        const uint32_t tag = (epoch + 1) & 1;
        uint4 v0, v1, v2;
        int it = 0;
        while (true) {
          v0 = ld_b128(&g_ST[rb * 64 + lane]);
          v1 = ld_b128(&g_ST[rb * 64 + 32 + lane]);
          v2 = ld_b128(&g_ST[rb2 * 64 + 32 * kh + lane]);
          if (!__any_sync(0xffffffffu, ((v0.x ^ tag) | (v1.x ^ tag) | (v2.x ^ tag)) & 1u)) break;
          if (++it > SPIN_LIMIT) __trap();
        }
        sts4(sstat + lane * 16, v0.x & ~1u, v0.y, v0.z, v0.w);
        sts4(sstat + 512 + lane * 16, v1.x & ~1u, v1.y, v1.z, v1.w);
        sts4(sstat + 1024 + lane * 16, v2.x & ~1u, v2.y, v2.z, v2.w);
        mbar_arrive(BAR(sbar, 0));
      }
#pragma unroll 1
      for (int e = 0; e < 2; e++) {
        bar_sync(NB_PUB, 288);
        if (lane == 0) {
          PROFP(8 + 2 * e);
          red_release(&g_cnt[((e == 0 ? C_PX : C_PY) + rb) * 32]);
          PROFP(9 + 2 * e);
        }
      }
    }
    __syncwarp();
    asm volatile("barrier.cluster.wait.aligned;" ::: "memory");
  } else {
    const int warp = __shfl_sync(0xffffffffu, tid >> 5, 0);
    const int g = lane >> 2, t = lane & 3;
    PROF(0);
    PROFG(14);
#pragma unroll
    for (int i = 0; i < 4; i++) {
      const int r = i >> 1, ch = (i & 1) * 32 + lane;
      cp_async16(sbase + SM_X + (2 * warp + r) * 1024 + ((ch ^ ((ch >> 2) & 6)) * 16),
                 x + (size_t)(c + 128 * (2 * warp + r)) * 512 + ch * 8);
    }
    asm volatile("cp.async.commit_group;" ::: "memory");
    asm volatile("barrier.cluster.arrive.relaxed.aligned;" ::: "memory");
    uint4 tw[8], fb[16];
    const uint4 fa = ldg_ca4(&g_tab.fa[lane][0]);
#pragma unroll
    for (int i = 0; i < 8; i++) tw[i] = ldg_ca4(&g_tab.tw1[i][lane][0]);
#pragma unroll
    for (int i = 0; i < 16; i++) fb[i] = ldg_ca4(&g_tab.fb[i][lane][0]);
    asm volatile("setmaxnreg.inc.sync.aligned.u32 224;");
    uint32_t rbar;
    asm volatile("mapa.shared::cluster.u32 %0, %1, %2;" : "=r"(rbar) : "r"(sbar), "r"(kh ^ 1));
#define RBAR(field, i) (rbar + (uint32_t)offsetof(Bars, field) + 8u * (i))
    {
      const int ln = (tid >> 1) & 31, lg = ln >> 2, lt = ln & 3, i = 4 * (tid >> 6) + 2 * (tid & 1);
      const int kidx = lt + 8 * (i >> 3), nidx = 4 * ((i >> 1) & 3) + (lg >> 1);
      const uint32_t a0 = cfrag<2048>((c + 128 * kidx) * nidx, lg & 1), a1 = cfrag<2048>((c + 128 * (kidx + 4)) * nidx, lg & 1);
      const uint32_t b0 = cfrag<2048>(-(c + 128 * nidx) * kidx, lg & 1), b1 = cfrag<2048>(-(c + 128 * nidx) * (kidx + 4), lg & 1);
      asm volatile("st.shared.v2.u32 [%0], {%1,%2};" ::"r"(sbase + SM_FC + tid * 8), "r"(a0), "r"(a1) : "memory");
      asm volatile("st.shared.v2.u32 [%0], {%1,%2};" ::"r"(sbase + SM_FC + 2048 + tid * 8), "r"(b0), "r"(b1) : "memory");
    }
    asm volatile("cp.async.wait_group 0;" ::: "memory");
    __syncwarp();
    bar_arrive(NB_INIT, 384);
    PROF(13);
    uint32_t tag;
    uint4 q[4], o[4];
    {
      uint32_t v[2][8];
#pragma unroll
      for (int r = 0; r < 2; r++)
#pragma unroll
        for (int q = 0; q < 4; q++) {
          const uint2 u = lds2(sbase + SM_X + (2 * warp + r) * 1024 + (t + 4 * (q >> 1)) * 128 + (((4 * (q & 1) + (g >> 1)) ^ (2 * t)) * 16) + (g & 1) * 8);
          v[r][2 * q] = u.x; v[r][2 * q + 1] = u.y;
        }
      float sum[2], sq[2], rstd[2];
      row_stats(v[0], v[1], lane, sum, sq);
#pragma unroll
      for (int r = 0; r < 2; r++) {
        const float m = sum[r] * (1.f / 512.f);
        rstd[r] = rsqrtf(fmaxf(fmaf(-m, m, sq[r] * (1.f / 512.f)), 0.f) + 1e-5f);
      }
      uint32_t alo[4][4], ahi[4][4];
#pragma unroll
      for (int r = 0; r < 2; r++)
#pragma unroll
        for (int i = 0; i < 4; i++) {
          const uint32_t sel = (i & 1) ? 0x7632u : 0x5410u;
          const uint32_t b0 = __byte_perm(v[r][i >> 1], v[r][2 + (i >> 1)], sel);
          const uint32_t b1 = __byte_perm(v[r][4 + (i >> 1)], v[r][6 + (i >> 1)], sel);
          float d[4] = {0.f, 0.f, 0.f, 0.f};
          mma16816(d, fa.x, fa.y, fa.z, fa.w, b0, b1);
          const uint4 &ka = tw[2 * i], &kb = tw[2 * i + 1];
          const uint32_t re = pack2(d[0] * __uint_as_float(ka.x) + d[2] * __uint_as_float(ka.y), d[1] * __uint_as_float(kb.x) + d[3] * __uint_as_float(kb.y));
          const uint32_t im = pack2(d[0] * __uint_as_float(ka.z) + d[2] * __uint_as_float(ka.w), d[1] * __uint_as_float(kb.z) + d[3] * __uint_as_float(kb.w));
          const uint32_t dc = pack2(fmaf(sum[r], -1.f / 32.f, d[0]), fmaf(sum[r], -1.f / 32.f, d[1]));
          alo[i][r] = re; alo[i][2 + r] = im;
          ahi[i][r] = g == 0 ? dc : re; ahi[i][2 + r] = g == 0 ? 0u : im;
        }
      float acc[8][4];
#pragma unroll
      for (int u = 0; u < 8; u++) {
        acc[u][0] = acc[u][1] = acc[u][2] = acc[u][3] = 0.f;
#pragma unroll
        for (int i = 0; i < 4; i++) {
          const uint4& bq = fb[i * 4 + (u >> 1)];
          if (u < 4) mma16816(acc[u], alo[i][0], alo[i][1], alo[i][2], alo[i][3], (u & 1) ? bq.z : bq.x, (u & 1) ? bq.w : bq.y);
          else       mma16816(acc[u], ahi[i][0], ahi[i][1], ahi[i][2], ahi[i][3], (u & 1) ? bq.z : bq.x, (u & 1) ? bq.w : bq.y);
        }
      }
#pragma unroll
      for (int r = 0; r < 2; r++)
#pragma unroll
        for (int h = 0; h < 2; h++) {
          const int j = 2 * warp + r, m = 2 * t + h;
          const float rs = rstd[r];
          sts4(sbase + SM_E + ((j * 8 + m) * 8 + (g ^ (2 * t) ^ (2 * (j & 3)))) * 16,
               pack2(acc[2 * h][2 * r] * rs, acc[2 * h][2 * r + 1] * rs), pack2(acc[2 * h + 1][2 * r] * rs, acc[2 * h + 1][2 * r + 1] * rs),
               pack2(acc[4 + 2 * h][2 * r] * rs, acc[4 + 2 * h][2 * r + 1] * rs), pack2(acc[5 + 2 * h][2 * r] * rs, acc[5 + 2 * h][2 * r + 1] * rs));
        }
      bar_sync(NB_RDY, 384);
      uint4 fc[4];
#pragma unroll
      for (int i = 0; i < 4; i++) fc[i] = lds4(sbase + SM_FC + i * 512 + lane * 16);
      asm volatile("ld.shared.u32 %0, [%1];" : "=r"(tag) : "r"(BAR(epoch, 0)) : "memory");
      tag = (tag + 1) & 1;
#pragma unroll
      for (int i = 0; i < 4; i++) q[i] = lds4(sbase + SM_E + (((t + 4 * i) * 8 + warp) * 8 + (g ^ (warp & 6) ^ (2 * t))) * 16);
      cdft16(q, fc, o);
#pragma unroll
      for (int vv = 0; vv < 4; vv++) st_tag(&g_Z1[(((4 * vv + t) * 8 + warp) * 128 + c) * 8 + g], o[vv], tag);
    }
    PROF(1);
    {
      const uint4* const zp = &g_Z1[(c * 128 + 8 * t + warp) * 8 + g];
      if (EARLY_POLL) ld_tag4_issue(q, zp);
      mbar_wait(BAR(tbar, 0), 0);
      uint4 f2[4], g2[4];
#pragma unroll
      for (int i = 0; i < 4; i++) {
        f2[i] = lds4(TOFF(f2) + warp * 2048 + i * 512);
        g2[i] = lds4(TOFF(g2) + warp * 2048 + i * 512);
      }
      const uint4 f8 = lds4(TOFF(f8)), g8 = lds4(TOFF(g8));
      float wfr[16], wfi[16];
      {
        const float fsc = 1.f / (1 << 19);
        const float fsc3 = ((c & 7) == 7 && g == 0) ? 0.5f * fsc : fsc;
        const int gg = g == 0 ? 8 : g, wsh = (2 * (c >> 3) + 2) & 15;
#pragma unroll
        for (int i = 0; i < 16; i++) {
          const int ci = i >> 3, dd = (i >> 2) & 1, e = i & 3;
          const int kk = (e == 0 ? gg : e == 1 ? 16 + gg : e == 2 ? 16 - g : 32 - g) - 1;
          const uint32_t a = sbase + SM_W + ((2 * warp + ci) * 8 + t + 4 * dd) * 80 + wsh + 2 * kk;
          wfr[i] = bf_lo(lds_u16(a)) * (e == 3 ? fsc3 : fsc);
          wfi[i] = bf_lo(lds_u16(a + 10240)) * (e == 3 ? fsc3 : fsc);
        }
      }
      asm volatile("barrier.cluster.wait.aligned;" ::: "memory");
      PROF(2);
      if (!EARLY_POLL) ld_tag4_issue(q, zp);
      ld_tag4_finish(q, zp, tag);
      if (lane == 0) mbar_arrive(BAR(sig, 0));
      cdft16(q, f2, o);
      const uint32_t e2 = sbase + SM_E2;
#pragma unroll
      for (int vv = 0; vv < 4; vv++)
        sts4(e2 + ((warp * 16 + 4 * vv + t) * 8 + (g ^ (2 * t) ^ (2 * (warp & 3)))) * 16, o[vv].x, o[vv].y, o[vv].z, o[vv].w);
      bar_sync(NB_CONS, 256);
#pragma unroll
      for (int ci = 0; ci < 2; ci++) {
        const int cc = 2 * warp + ci;
        uint32_t ad[2];
        uint4 u[2];
#pragma unroll
        for (int hh = 0; hh < 2; hh++) {
          ad[hh] = e2 + (((t + 4 * hh) * 16 + cc) * 8 + (g ^ (2 * (cc & 3)) ^ (2 * t))) * 16;
          u[hh] = lds4(ad[hh]);
        }
        uint32_t res[2][4];
#pragma unroll
        for (int p = 0; p < 2; p++) {
          uint32_t y[2][2];
#pragma unroll
          for (int vv = 0; vv < 2; vv++) {
            float d[4] = {0.f, 0.f, 0.f, 0.f};
            mma16816(d, word(u[0], 2 * p), word(u[0], 2 * p + 1), word(u[1], 2 * p), word(u[1], 2 * p + 1), word(f8, 2 * vv), word(f8, 2 * vv + 1));
#pragma unroll
            for (int rr = 0; rr < 2; rr++) {
              const float fr = wfr[ci * 8 + vv * 4 + 2 * p + rr], fi = wfi[ci * 8 + vv * 4 + 2 * p + rr];
              y[vv][rr] = pack2(d[2 * rr] * fr - d[2 * rr + 1] * fi, d[2 * rr] * fi + d[2 * rr + 1] * fr);
            }
          }
#pragma unroll
          for (int vv = 0; vv < 2; vv++) {
            float d[4] = {0.f, 0.f, 0.f, 0.f};
            mma16816(d, y[0][0], y[0][1], y[1][0], y[1][1], word(g8, 2 * vv), word(g8, 2 * vv + 1));
            res[vv][2 * p] = pack2(d[0], d[1]);
            res[vv][2 * p + 1] = pack2(d[2], d[3]);
          }
        }
#pragma unroll
        for (int vv = 0; vv < 2; vv++) sts4(ad[vv], res[vv][0], res[vv][1], res[vv][2], res[vv][3]);
      }
      bar_sync(NB_CONS, 256);
#pragma unroll
      for (int i = 0; i < 4; i++) q[i] = lds4(e2 + ((warp * 16 + 4 * i + t) * 8 + (g ^ (2 * t) ^ (2 * (warp & 3)))) * 16);
      cdft16(q, g2, o);
#pragma unroll
      for (int vv = 0; vv < 4; vv++) st_tag(&g_Z2[((8 * (4 * vv + t) + warp) * 128 + c) * 8 + g], o[vv], tag);
    }
    PROF(3);
    {
      const uint4* const zp = &g_Z2[((c * 16 + t) * 8 + warp) * 8 + g];
      if (EARLY_POLL) ld_tag4_issue(q, zp);
      uint4 gb[16], gc[4], tw[4], xr[2][2];
#pragma unroll
      for (int i = 0; i < 16; i++) gb[i] = lds4(TOFF(gb) + i * 512);
      const uint4 ga = lds4(TOFF(ga));
#pragma unroll
      for (int i = 0; i < 4; i++) {
        gc[i] = lds4(sbase + SM_FC + 2048 + i * 512 + lane * 16);
        tw[i] = lds4(TOFF(tw3) + i * 512);
        const int ch = 4 * (g + 8 * (i & 1)) + t;
        xr[i >> 1][i & 1] = lds4(sbase + SM_X + (2 * warp + (i >> 1)) * 1024 + ((ch ^ ((ch >> 2) & 6)) * 16));
      }
      asm volatile("fence.proxy.async.shared::cta;" ::: "memory");
      PROF(4);
      if (!EARLY_POLL) ld_tag4_issue(q, zp);
      ld_tag4_finish(q, zp, tag);
      if (lane == 0) { mbar_arrive(BAR(sig, 1)); mbar_arrive_remote(RBAR(sig, 1)); }
      cdft16(q, gc, o);
#pragma unroll
      for (int vv = 0; vv < 4; vv++)
        sts4(sbase + SM_E + (((4 * vv + t) * 8 + warp) * 8 + (g ^ (warp & 6) ^ (2 * t))) * 16, o[vv].x, o[vv].y, o[vv].z, o[vv].w);
      bar_sync(NB_CONS, 256);
      uint32_t hv[2][8];
      const float mk = t == 0 ? 0.f : 1.f;
#pragma unroll
      for (int r = 0; r < 2; r++) {
        const int j = 2 * warp + r;
        uint4 u[2];
#pragma unroll
        for (int h = 0; h < 2; h++) u[h] = lds4(sbase + SM_E + ((j * 8 + 2 * t + h) * 8 + (g ^ (2 * t) ^ (2 * (j & 3)))) * 16);
        float yv[4][4];
#pragma unroll
        for (int i = 0; i < 4; i++) {
          float lo[4] = {0.f, 0.f, 0.f, 0.f}, hi[4] = {0.f, 0.f, 0.f, 0.f};
          mma16816(lo, gb[i * 4].x, gb[i * 4].y, gb[i * 4].z, gb[i * 4].w, u[0].x, u[0].y);
          mma16816(lo, gb[i * 4 + 1].x, gb[i * 4 + 1].y, gb[i * 4 + 1].z, gb[i * 4 + 1].w, u[1].x, u[1].y);
          mma16816(hi, gb[i * 4 + 2].x, gb[i * 4 + 2].y, gb[i * 4 + 2].z, gb[i * 4 + 2].w, u[0].z, u[0].w);
          mma16816(hi, gb[i * 4 + 3].x, gb[i * 4 + 3].y, gb[i * 4 + 3].z, gb[i * 4 + 3].w, u[1].z, u[1].w);
          const float ca = __uint_as_float(tw[i].x), sa = __uint_as_float(tw[i].y), cb = __uint_as_float(tw[i].z), sb = __uint_as_float(tw[i].w);
          const float tr0 = fmaf(hi[0], mk, lo[0]), ti0 = fmaf(hi[2], mk, lo[2]);
          const float tr1 = lo[1] + hi[1], ti1 = lo[3] + hi[3];
          const float vr0 = tr0 * ca - ti0 * sa, vi0 = tr0 * sa + ti0 * ca;
          const float vr1 = tr1 * cb - ti1 * sb, vi1 = tr1 * sb + ti1 * cb;
          const uint32_t b0 = pack2(t == 0 ? hi[0] : vr0, vr1), b1 = pack2(t == 0 ? vr0 : vi0, vi1);
          yv[i][0] = yv[i][1] = yv[i][2] = yv[i][3] = 0.f;
          mma16816(yv[i], ga.x, ga.y, ga.z, ga.w, b0, b1);
        }
#pragma unroll
        for (int h = 0; h < 2; h++) {
          hv[r][4 * h + 0] = hadd2_bf16(xr[r][h].x, pack2(yv[0][2 * h], yv[1][2 * h]));
          hv[r][4 * h + 1] = hadd2_bf16(xr[r][h].y, pack2(yv[2][2 * h], yv[3][2 * h]));
          hv[r][4 * h + 2] = hadd2_bf16(xr[r][h].z, pack2(yv[0][2 * h + 1], yv[1][2 * h + 1]));
          hv[r][4 * h + 3] = hadd2_bf16(xr[r][h].w, pack2(yv[2][2 * h + 1], yv[3][2 * h + 1]));
        }
      }
      float ds[4] = {0.f, 0.f, 0.f, 0.f};
#pragma unroll
      for (int q4 = 0; q4 < 4; q4++) mma16816(ds, hv[0][2 * q4], hv[1][2 * q4], hv[0][2 * q4 + 1], hv[1][2 * q4 + 1], 0x3f803f80u, 0x3f803f80u);
#pragma unroll
      for (int o2 = 4; o2 <= 16; o2 <<= 1) {
        ds[0] += __shfl_xor_sync(0xffffffffu, ds[0], o2);
        ds[2] += __shfl_xor_sync(0xffffffffu, ds[2], o2);
      }
      uint32_t mb[2];
#pragma unroll
      for (int r = 0; r < 2; r++) {
        const int row = 16 * f + 2 * warp + r;
        mb[r] = pack2(ds[2 * r] * (1.f / 512.f), ds[2 * r] * (1.f / 512.f));
#pragma unroll
        for (int i = 0; i < 8; i++) hv[r][i] = hsub2_bf16(hv[r][i], mb[r]);
#pragma unroll
        for (int h = 0; h < 2; h++) {
          const int n1 = g + 8 * h;
          stg4(&g_LN[(rb * 8 + (n1 >> 1)) * 1024 + row * 8 + ((4 * (n1 & 1) + t) ^ (row & 7))],
               make_uint4(hv[r][4 * h], hv[r][4 * h + 1], hv[r][4 * h + 2], hv[r][4 * h + 3]));
        }
      }
      asm volatile("fence.proxy.async.shared::cta;" ::: "memory");
      bar_arrive(NB_LN, 288);
      float sum[2], sq[2], rstd[2];
      row_stats(hv[0], hv[1], lane, sum, sq);
#pragma unroll
      for (int r = 0; r < 2; r++) {
        const float m = sum[r] * (1.f / 512.f);
        rstd[r] = rsqrtf(fmaxf(fmaf(-m, m, sq[r] * (1.f / 512.f)), 0.f) + 1e-5f);
      }
      if (lane == 0)
        st_tag(&g_ST[rb * 64 + 8 * f + warp], make_uint4(mb[0] << 16, __float_as_uint(rstd[0]), mb[1] << 16, __float_as_uint(rstd[1])), tag);
    }
    PROF(5);
    const int wgi = warp >> 2, wq = warp & 3;
    uint4* const pbase = &g_P[rb * 28 * 1024 + (8 * wgi + 2 * wq) * 64 + t * 8 + g];
    const uint32_t a_lo0 = desc_lo(sbase + wgi * 8192, 16);
    const uint32_t ebar = lane == 0 ? BAR(empty1, 0) : RBAR(empty1, 0);
    float r0, r1;
    uint4 px[8], py[6];
    {
      float acc[128];
#pragma unroll
      for (int i = 0; i < 128; i++) acc[i] = 0.f;
      if (wgi == 1) bar_sync(NB_LAG, 256);
      const uint32_t b_lo0 = desc_lo(sbase + 8 * SLOT, 4096);
      uint32_t slot = 0, ph = 0, prev = 0;
#pragma unroll 1
      for (int kb = 0; kb < 8; kb++) {
        mbar_wait(BAR(fullA, kb), 0);
        if (kb == 0) PROF(6);
#pragma unroll
        for (int hh = 0; hh < 2; hh++) {
          mbar_wait(BAR(full1, slot), ph);
          const uint32_t al = a_lo0 + kb * 1024 + hh * 4, bl = b_lo0 + slot * 1024;
          wg_fence();
          wgmma_n256(acc, desc64(al, HI128), desc64(bl, HI128));
          wgmma_n256(acc, desc64(al + 2, HI128), desc64(bl + 128, HI128));
          wg_commit();
          if (hh == (LAG & 1) && kb == (LAG >> 1) && wgi == 0) bar_arrive(NB_LAG, 256);
          wg_wait<1>();
          if ((kb | hh) != 0 && lane < 2) mbar_arrive_remote(ebar + 8 * prev);
          prev = slot;
          if (++slot == 6) { slot = 0; ph ^= 1; }
        }
      }
      mbar_wait(BAR(sbar, 0), 0);
      r0 = __uint_as_float(lds2(sstat + (16 * warp + g) * 8).y);
      r1 = __uint_as_float(lds2(sstat + (16 * warp + g + 8) * 8).y);
      wg_wait<0>();
      if (lane < 2) mbar_arrive_remote(ebar + 8 * prev);
      PROF(7);
      make_p<4>(acc, r0, r1, px);
    }
    PROF(8);
    {
      float acc[96];
#pragma unroll
      for (int i = 0; i < 96; i++) acc[i] = 0.f;
      const uint32_t b_lo0 = desc_lo(sbase + 8 * SLOT, 2048);
      uint4* const pdst = pbase + ((7 * f + 3 * (f & 1)) >> 1) * 1024;
#pragma unroll
      for (int k = 0; k < 16; k++) {
        mbar_wait(BAR(full1, (16 + k) % 6), ((16 + k) / 6) & 1);
        const uint32_t al = a_lo0 + (k >> 1) * 1024 + (k & 1) * 4, bl = b_lo0 + ((16 + k) % 6) * 1024;
        wg_fence();
        wgmma_n192(acc, desc64(al, HI128), desc64(bl, HI64));
        wgmma_n192(acc, desc64(al + 2, HI128), desc64(bl + 64, HI64));
        wg_commit();
        if (k < 8) stg4(pdst + (k >> 2) * 1024 + ((k >> 1) & 1) * 32 + (k & 1) * 64, px[k]);
        if (k == 7) bar_arrive(NB_PUB, 288);
        wg_wait<1>();
        if (k != 0 && lane < 2) mbar_arrive_remote(ebar + 8 * ((15 + k) % 6));
      }
      wg_wait<0>();
      if (lane < 2) mbar_arrive_remote(ebar + 8 * (31 % 6));
      PROF(9);
      make_p<3>(acc, r0, r1, py);
    }
    PROF(10);
    {
      const int rh = wgi ^ kh ^ 1;
      const int trow = 64 * rh + 16 * wq + g;
      const int G0 = 7 * f + ((f & 1) ? 0 : 4);
      float acc[64];
      {
        const float m0 = wgi ? __uint_as_float(lds2(sstat + 1024 + (16 * wq + g) * 8).x) : 0.f;
        const float m1 = wgi ? __uint_as_float(lds2(sstat + 1024 + (16 * wq + g + 8) * 8).x) : 0.f;
#pragma unroll
        for (int i = 0; i < 64; i++) acc[i] = (i & 2) ? m1 : m0;
      }
      if (wgi == 1) {
#pragma unroll
        for (int k = 0; k < 6; k++) stg4(pbase + ((G0 + (k >> 1)) >> 1) * 1024 + ((G0 + (k >> 1)) & 1) * 32 + (k & 1) * 64, py[k]);
        bar_arrive(NB_PUB, 288);
        bar_sync(NB_LAG2, 256);
      }
      const uint32_t a2_lo0 = desc_lo(sbase + 8 * SLOT + rh * 8192, 128), b2_lo0 = desc_lo(sbase, 8192);
      uint4 hres[2][4];
#pragma unroll
      for (int s = 0; s < 14; s++) {
        const uint32_t al = a2_lo0 + ((s + 2) % 6) * 1024, bl = b2_lo0 + (s & 7) * 1024;
        mbar_wait(BAR(full2, s), 0);
        if (tid == 0) PROFP(16 + s);
        wg_fence();
#pragma unroll
        for (int kk = 0; kk < 4; kk++) wgmma_n128(acc, desc64(al + kk * 16, HI0), desc64(bl + kk * 128, HI128));
        wg_commit();
        if (s < 3 && wgi == 0) {
          stg4(pbase + ((G0 + s) >> 1) * 1024 + ((G0 + s) & 1) * 32, py[2 * s]);
          stg4(pbase + ((G0 + s) >> 1) * 1024 + ((G0 + s) & 1) * 32 + 64, py[2 * s + 1]);
          if (s == 2) bar_arrive(NB_PUB, 288);
        }
        if (s == LAG2 && wgi == 0) bar_arrive(NB_LAG2, 256);
        if (s == 8) {
#pragma unroll
          for (int h = 0; h < 2; h++)
#pragma unroll
            for (int q = 0; q < 4; q++)
              hres[h][q] = ldg_cg4(&g_LN[(rb2 * 8 + 2 * nq + (q >> 1)) * 1024 + (trow + 8 * h) * 8 + ((4 * (q & 1) + t) ^ g)]);
        }
        wg_wait<1>();
        if (s > 0 && s <= 8 && lane == 0) {
          mbar_arrive(BAR(empty2, s - 1));
          if (s == 8) mbar_arrive_remote(RBAR(xfree, 0));
        }
      }
      wg_wait<0>();
      PROF(11);
      const uint32_t xbuf = sbase + 6 * SLOT + (tid & 127) * 16;
      if (wgi == 0) {
        uint32_t rbuf;
        mbar_wait(BAR(xfree, 0), 0);
        asm volatile("mapa.shared::cluster.u32 %0, %1, %2;" : "=r"(rbuf) : "r"(xbuf), "r"(kh ^ 1));
#pragma unroll
        for (int i = 0; i < 8; i++)
          asm volatile("st.async.weak.shared::cluster.mbarrier::complete_tx::bytes.v4.b32 [%0], {%1,%2,%3,%4}, [%5];"
                       ::"r"(rbuf + i * 2048), "r"(pack2(acc[8 * i], acc[8 * i + 1])), "r"(pack2(acc[8 * i + 2], acc[8 * i + 3])),
                         "r"(pack2(acc[8 * i + 4], acc[8 * i + 5])), "r"(pack2(acc[8 * i + 6], acc[8 * i + 7])), "r"(RBAR(xbar, 0))
                       : "memory");
      } else {
        mbar_wait_cluster(BAR(xbar, 0), 0);
      }
      uint32_t w[2][16];
#pragma unroll
      for (int i = 0; i < 8; i++) {
        const uint4 pv = lds4(xbuf + i * 2048);
        w[0][2 * i] = pack2(acc[8 * i] + bf_lo(pv.x), acc[8 * i + 1] + bf_hi(pv.x));
        w[1][2 * i] = pack2(acc[8 * i + 2] + bf_lo(pv.y), acc[8 * i + 3] + bf_hi(pv.y));
        w[0][2 * i + 1] = pack2(acc[8 * i + 4] + bf_lo(pv.z), acc[8 * i + 5] + bf_hi(pv.z));
        w[1][2 * i + 1] = pack2(acc[8 * i + 6] + bf_lo(pv.w), acc[8 * i + 7] + bf_hi(pv.w));
      }
      uint4* const o4 = reinterpret_cast<uint4*>(out) + (16 * (c >> 4) + 2 * (4 * rh + wq) + (rb2 & 1) + 128 * g) * 64 + nq * 16 + t;
#pragma unroll
      for (int h = 0; h < 2; h++)
#pragma unroll
        for (int q = 0; q < 4; q++) {
          uint32_t a0 = w[h][4 * q], a1 = w[h][4 * q + 1], a2 = w[h][4 * q + 2], a3 = w[h][4 * q + 3];
          {
            const bool od = t & 1;
            uint32_t s0 = od ? a0 : a1, s1 = od ? a2 : a3;
            s0 = __shfl_xor_sync(0xffffffffu, s0, 1); s1 = __shfl_xor_sync(0xffffffffu, s1, 1);
            if (od) { a0 = s0; a2 = s1; } else { a1 = s0; a3 = s1; }
          }
          {
            const bool up = t & 2;
            uint32_t s0 = up ? a0 : a2, s1 = up ? a1 : a3;
            s0 = __shfl_xor_sync(0xffffffffu, s0, 2); s1 = __shfl_xor_sync(0xffffffffu, s1, 2);
            if (up) { a0 = s0; a1 = s1; } else { a2 = s0; a3 = s1; }
          }
          if (wgi == 1)
            o4[h * 1024 * 64 + 4 * q] =
                make_uint4(hadd2_bf16(hres[h][q].x, a0), hadd2_bf16(hres[h][q].y, a1), hadd2_bf16(hres[h][q].z, a2), hadd2_bf16(hres[h][q].w, a3));
        }
      PROF(12);
      PROFG(15);
    }
  }
#undef BAR
#undef TOFF
#undef RBAR
}

typedef CUresult (*EncodeFn)(CUtensorMap*, CUtensorMapDataType, cuuint32_t, void*, const cuuint64_t*, const cuuint64_t*,
                             const cuuint32_t*, const cuuint32_t*, CUtensorMapInterleave, CUtensorMapSwizzle,
                             CUtensorMapL2promotion, CUtensorMapFloatOOBfill);

}

extern "C" void kernel_launch(void* const* d_in, const int* in_sizes, int n_in, void* d_out, int out_size) {
  (void)in_sizes; (void)n_in; (void)out_size;
  static EncodeFn encode = nullptr;
  if (!encode) {
    void* fn = nullptr;
    cudaDriverEntryPointQueryResult qr;
    cudaGetDriverEntryPoint("cuTensorMapEncodeTiled", &fn, cudaEnableDefault, &qr);
    encode = (EncodeFn)fn;
    cudaFuncSetAttribute(fused_kernel, cudaFuncAttributeMaxDynamicSharedMemorySize, SMEM_BYTES);
  }
  CUtensorMap tmGX, tmUX, tmGY, tmUY, tmD, tmWR, tmWI;
  const cuuint32_t es[5] = {1, 1, 1, 1, 1};
  auto enc = [&](CUtensorMap* m, void* p, int rank, const cuuint64_t* gd, const cuuint64_t* gs, const cuuint32_t* bd,
                 CUtensorMapSwizzle sw, CUtensorMapL2promotion pr) {
    encode(m, CU_TENSOR_MAP_DATA_TYPE_BFLOAT16, rank, p, gd, gs, bd, es, CU_TENSOR_MAP_INTERLEAVE_NONE, sw, pr,
           CU_TENSOR_MAP_FLOAT_OOB_FILL_NONE);
  };
  {
    const cuuint64_t gd[3] = {64, 512, 28}, gs[2] = {3584, 128};
    const cuuint32_t bd[3] = {64, 32, 2};
    enc(&tmGX, d_in[4], 3, gd, gs, bd, CU_TENSOR_MAP_SWIZZLE_128B, CU_TENSOR_MAP_L2_PROMOTION_L2_256B);
    enc(&tmUX, d_in[5], 3, gd, gs, bd, CU_TENSOR_MAP_SWIZZLE_128B, CU_TENSOR_MAP_L2_PROMOTION_L2_256B);
  }
  {
    const cuuint64_t gd[3] = {32, 512, 56}, gs[2] = {3584, 64};
    const cuuint32_t bd[3] = {32, 32, 3};
    enc(&tmGY, d_in[4], 3, gd, gs, bd, CU_TENSOR_MAP_SWIZZLE_64B, CU_TENSOR_MAP_L2_PROMOTION_L2_128B);
    enc(&tmUY, d_in[5], 3, gd, gs, bd, CU_TENSOR_MAP_SWIZZLE_64B, CU_TENSOR_MAP_L2_PROMOTION_L2_128B);
  }
  {
    const cuuint64_t gd[5] = {512, 2, 4, 4, 56}, gs[4] = {1024, 8192, 2048, 32768};
    const cuuint32_t bd[5] = {64, 2, 4, 4, 2};
    enc(&tmD, d_in[6], 5, gd, gs, bd, CU_TENSOR_MAP_SWIZZLE_128B, CU_TENSOR_MAP_L2_PROMOTION_L2_256B);
  }
  {
    const cuuint64_t gd[3] = {4112, 8, 16}, gs[2] = {16 * 8224, 8224};
    const cuuint32_t bd[3] = {40, 8, 16};
    enc(&tmWR, d_in[1], 3, gd, gs, bd, CU_TENSOR_MAP_SWIZZLE_NONE, CU_TENSOR_MAP_L2_PROMOTION_NONE);
    enc(&tmWI, d_in[2], 3, gd, gs, bd, CU_TENSOR_MAP_SWIZZLE_NONE, CU_TENSOR_MAP_L2_PROMOTION_NONE);
  }
  fused_kernel<<<NCTA, NTHREADS, SMEM_BYTES>>>(tmGX, tmUX, tmGY, tmUY, tmD, tmWR, tmWI, (const __nv_bfloat16*)d_in[0],
                                               (const char*)d_in[4], (const char*)d_in[5], (const char*)d_in[6],
                                               (__nv_bfloat16*)d_out);
}
```

```cpp
#include <cuda_runtime.h>
#include <cuda_bf16.h>
#include <cuda.h>
#include <stdint.h>

namespace {

constexpr int NCTA = 128;
constexpr int NTHREADS = 384;
constexpr int SLOT = 16384;
constexpr int SMEM_BYTES = 14 * SLOT + 2048 + 1024;
constexpr int SPIN_LIMIT = 1 << 22;

__device__ uint4 g_Z1[128 * 1024];
__device__ uint4 g_Z2[128 * 1024];
__device__ uint4 g_LN[16 * 8 * 1024];
__device__ uint4 g_ST[1024];
__device__ uint4 g_P[16 * 28 * 1024];
__device__ unsigned g_cnt[64 * 32];
#define PROF(i)
#define PROFP(i)
#define PROFG(i)

constexpr double ccos(int i, int n) {
  i &= n - 1;
  if (i > n / 2) i = n - i;
  if (4 * i == n) return 0.0;
  const bool neg = 4 * i > n;
  if (neg) i = n / 2 - i;
  const double a = 6.283185307179586476925 * i / n, a2 = a * a;
  double term = 1.0, sum = 1.0;
  for (int k = 1; k < 14; k++) { term *= -a2 / ((2 * k - 1) * (2 * k)); sum += term; }
  return neg ? -sum : sum;
}
constexpr double csin(int i, int n) { return ccos(i - n / 4, n); }
constexpr unsigned fbits(double v, int mant) {
  if (v == 0.0) return 0;
  const unsigned sg = v < 0 ? 1u : 0u;
  if (v < 0) v = -v;
  int e = 127;
  while (v < 1.0) { v *= 2.0; e--; }
  const unsigned m = (unsigned)((v - 1.0) * (double)(1u << mant) + 0.5);
  return (sg << (8 + mant)) + ((unsigned)e << mant) + m;
}
constexpr unsigned pkb(double lo, double hi) { return fbits(lo, 7) | (fbits(hi, 7) << 16); }
constexpr double fa_elem(int kp, int n1) {
  return kp <= 8 ? ccos(kp * n1, 16) : -csin((kp - 8) * n1, 16);
}
constexpr unsigned cfrag_c(int idx, int n, int ri) {
  return ri ? pkb(-csin(idx, n), ccos(idx, n)) : pkb(ccos(idx, n), csin(idx, n));
}
struct Tables {
  unsigned fb[16][32][4];
  unsigned tw1[8][32][4];
  unsigned fa[32][4];
  unsigned f2[8][4][32][4];
  unsigned g2[8][4][32][4];
  unsigned gb[16][32][4];
  unsigned tw3[4][32][4];
  unsigned ga[32][4];
  unsigned f8[32][4], g8[32][4];
};
constexpr int T1_BYTES = 12800, T2_BYTES = 44544;
static_assert(sizeof(Tables) == T1_BYTES + T2_BYTES, "table size");
constexpr Tables make_tables() {
  Tables T = {};
  for (int l = 0; l < 32; l++) {
    const int g = l >> 2, t = l & 3;
    for (int i = 0; i < 4; i++)
      for (int u = 0; u < 8; u++) {
        const int ri = g & 1, m = 2 * (g >> 1) + ((u & 3) >> 1);
        const double sg = u >= 4 ? -1.0 : 1.0;
        const int k2 = u >= 4 ? 31 - 2 * m - (u & 1) : 2 * m + (u & 1);
        const int pa = (8 * t + i) * k2, pb = (8 * t + 4 + i) * k2;
        T.fb[i * 4 + (u >> 1)][l][(u & 1) * 2 + 0] = ri == 0 ? pkb(ccos(pa, 32), ccos(pb, 32)) : pkb(-sg * csin(pa, 32), -sg * csin(pb, 32));
        T.fb[i * 4 + (u >> 1)][l][(u & 1) * 2 + 1] = ri == 0 ? pkb(csin(pa, 32), csin(pb, 32)) : pkb(sg * ccos(pa, 32), sg * ccos(pb, 32));
      }
    for (int i = 0; i < 4; i++)
      for (int ks = 0; ks < 4; ks++) {
        const int n2 = 4 * g + i, m = 2 * t + (ks & 1);
        const double sg = ks >= 2 ? -1.0 : 1.0;
        const int pa = n2 * (ks >= 2 ? 31 - 2 * m : 2 * m), pb = n2 * (ks >= 2 ? 30 - 2 * m : 2 * m + 1);
        T.gb[i * 4 + ks][l][0] = pkb(ccos(pa, 32), -sg * csin(pa, 32));
        T.gb[i * 4 + ks][l][1] = pkb(csin(pa, 32), sg * ccos(pa, 32));
        T.gb[i * 4 + ks][l][2] = pkb(ccos(pb, 32), -sg * csin(pb, 32));
        T.gb[i * 4 + ks][l][3] = pkb(csin(pb, 32), sg * ccos(pb, 32));
      }
    for (int i = 0; i < 4; i++) {
      for (int e = 0; e < 2; e++) {
        const int p = (8 * t + 4 * e + i) * (g == 0 ? 8 : g);
        T.tw1[2 * i + e][l][0] = fbits(g == 0 ? 0.0 : ccos(p, 512), 23);
        T.tw1[2 * i + e][l][1] = fbits(g == 0 ? ccos(p, 512) : csin(p, 512), 23);
        T.tw1[2 * i + e][l][2] = fbits(g == 0 ? 0.0 : -csin(p, 512), 23);
        T.tw1[2 * i + e][l][3] = fbits(g == 0 ? -csin(p, 512) : ccos(p, 512), 23);
      }
      const int ka = t == 0 ? 8 : 2 * t, kb = 2 * t + 1;
      T.tw3[i][l][0] = fbits(ccos((4 * g + i) * ka, 512), 23);
      T.tw3[i][l][1] = fbits(csin((4 * g + i) * ka, 512), 23);
      T.tw3[i][l][2] = fbits(ccos((4 * g + i) * kb, 512), 23);
      T.tw3[i][l][3] = fbits(csin((4 * g + i) * kb, 512), 23);
      const int p8 = (t + 4 * (i & 1)) * (4 * (i >> 1) + (g >> 1));
      T.f8[l][i] = cfrag_c(p8, 8, g & 1);
      T.g8[l][i] = cfrag_c(-p8, 8, g & 1);
    }
    for (int w = 0; w < 8; w++)
      for (int i = 0; i < 16; i++) {
        const int kidx = t + 4 * (i & 1) + 8 * (i >> 3), nidx = 4 * ((i >> 1) & 3) + (g >> 1);
        T.f2[w][i >> 2][l][i & 3] = cfrag_c((8 * kidx + w) * nidx, 128, g & 1);
        T.g2[w][i >> 2][l][i & 3] = cfrag_c(-(8 * nidx + w) * kidx, 128, g & 1);
      }
    T.fa[l][0] = pkb(fa_elem(g, 2 * t), fa_elem(g, 2 * t + 1));
    T.fa[l][1] = pkb(fa_elem(g + 8, 2 * t), fa_elem(g + 8, 2 * t + 1));
    T.fa[l][2] = pkb(fa_elem(g, 2 * t + 8), fa_elem(g, 2 * t + 9));
    T.fa[l][3] = pkb(fa_elem(g + 8, 2 * t + 8), fa_elem(g + 8, 2 * t + 9));
    T.ga[l][0] = pkb(fa_elem(2 * t, g), fa_elem(2 * t + 1, g));
    T.ga[l][1] = pkb(fa_elem(2 * t, g + 8), fa_elem(2 * t + 1, g + 8));
    T.ga[l][2] = pkb(fa_elem(2 * t + 8, g), fa_elem(2 * t + 9, g));
    T.ga[l][3] = pkb(fa_elem(2 * t + 8, g + 8), fa_elem(2 * t + 9, g + 8));
  }
  return T;
}
__device__ const __align__(128) Tables g_tab = make_tables();

__device__ __forceinline__ uint32_t s2u(const void* p) { return (uint32_t)__cvta_generic_to_shared(p); }
__device__ __forceinline__ void mbar_init(uint32_t b, int c) { asm volatile("mbarrier.init.shared::cta.b64 [%0], %1;" ::"r"(b), "r"(c)); }
__device__ __forceinline__ void mbar_expect(uint32_t b, int bytes) {
  asm volatile("mbarrier.arrive.expect_tx.shared::cta.b64 _, [%0], %1;" ::"r"(b), "r"(bytes) : "memory");
}
__device__ __forceinline__ void mbar_arrive(uint32_t b) { asm volatile("mbarrier.arrive.shared::cta.b64 _, [%0];" ::"r"(b) : "memory"); }
__device__ __forceinline__ uint32_t mbar_try(uint32_t b, uint32_t parity) {
  uint32_t ok;
  asm volatile("{.reg .pred p; mbarrier.try_wait.parity.shared::cta.b64 p, [%1], %2; selp.u32 %0,1,0,p;}"
               : "=r"(ok) : "r"(b), "r"(parity) : "memory");
  return ok;
}
__device__ __forceinline__ void mbar_wait(uint32_t b, uint32_t parity) {
  int it = 0;
  while (!mbar_try(b, parity))
    if (++it > SPIN_LIMIT) __trap();
}
__device__ __forceinline__ void mbar_wait_cluster(uint32_t b, int parity) {
  uint32_t ok;
  int it = 0;
  do {
    asm volatile("{.reg .pred p; mbarrier.try_wait.parity.acquire.cluster.shared::cta.b64 p, [%1], %2; selp.u32 %0,1,0,p;}"
                 : "=r"(ok) : "r"(b), "r"(parity) : "memory");
    if (++it > SPIN_LIMIT) __trap();
  } while (!ok);
}
__device__ __forceinline__ void bar_sync(int id, int n) { asm volatile("bar.sync %0, %1;" ::"r"(id), "r"(n) : "memory"); }
__device__ __forceinline__ void bar_arrive(int id, int n) { asm volatile("bar.arrive %0, %1;" ::"r"(id), "r"(n) : "memory"); }
__device__ __forceinline__ void red_release(unsigned* p) { asm volatile("red.release.gpu.global.add.u32 [%0], 1;" ::"l"(p) : "memory"); }
__device__ __forceinline__ unsigned ld_acquire(const unsigned* p) {
  unsigned v;
  asm volatile("ld.acquire.gpu.global.u32 %0, [%1];" : "=r"(v) : "l"(p) : "memory");
  return v;
}
__device__ __forceinline__ unsigned ld_relaxed(const unsigned* p) {
  unsigned v;
  asm volatile("ld.relaxed.gpu.global.u32 %0, [%1];" : "=r"(v) : "l"(p) : "memory");
  return v;
}
__device__ __forceinline__ void wait_counter(const unsigned* p, unsigned target) {
  int it = 0;
  while ((int)(ld_acquire(p) - target) < 0)
    if (++it > SPIN_LIMIT) __trap();
}
__device__ __forceinline__ uint4 ldg_cg4(const uint4* p) {
  uint4 v;
  asm volatile("ld.global.cg.v4.u32 {%0,%1,%2,%3}, [%4];" : "=r"(v.x), "=r"(v.y), "=r"(v.z), "=r"(v.w) : "l"(p) : "memory");
  return v;
}
__device__ __forceinline__ void sts4(uint32_t a, uint32_t x, uint32_t y, uint32_t z, uint32_t w) {
  asm volatile("st.shared.v4.u32 [%0], {%1,%2,%3,%4};" ::"r"(a), "r"(x), "r"(y), "r"(z), "r"(w) : "memory");
}
__device__ __forceinline__ uint4 lds4(uint32_t a) {
  uint4 v;
  asm volatile("ld.shared.v4.u32 {%0,%1,%2,%3}, [%4];" : "=r"(v.x), "=r"(v.y), "=r"(v.z), "=r"(v.w) : "r"(a) : "memory");
  return v;
}
__device__ __forceinline__ uint32_t pack2(float lo, float hi) {
  uint32_t r;
  asm("cvt.rn.bf16x2.f32 %0, %1, %2;" : "=r"(r) : "f"(hi), "f"(lo));
  return r;
}
__device__ __forceinline__ float bf_lo(uint32_t v) { return __uint_as_float(v << 16); }
__device__ __forceinline__ float bf_hi(uint32_t v) { return __uint_as_float(v & 0xffff0000u); }
__device__ __forceinline__ uint32_t hadd2_bf16(uint32_t a, uint32_t b) {
  uint32_t r;
  asm("add.rn.bf16x2 %0, %1, %2;" : "=r"(r) : "r"(a), "r"(b));
  return r;
}
__device__ __forceinline__ void mma16816(float (&d)[4], uint32_t a0, uint32_t a1, uint32_t a2, uint32_t a3, uint32_t b0, uint32_t b1) {
  asm("mma.sync.aligned.m16n8k16.row.col.f32.bf16.bf16.f32 {%0,%1,%2,%3}, {%4,%5,%6,%7}, {%8,%9}, {%0,%1,%2,%3};"
      : "+f"(d[0]), "+f"(d[1]), "+f"(d[2]), "+f"(d[3])
      : "r"(a0), "r"(a1), "r"(a2), "r"(a3), "r"(b0), "r"(b1));
}
template <int N>
__device__ __forceinline__ void cs_frac(int idx, float& c, float& s) {
  int i = ((idx + N / 2) & (N - 1)) - N / 2;
  float a = (float)i * (6.283185307179586f / N);
  c = __cosf(a);
  s = __sinf(a);
}
template <int N>
__device__ __forceinline__ uint32_t cfrag(int idx, int ri) {
  float c, s;
  cs_frac<N>(idx, c, s);
  return ri ? pack2(-s, c) : pack2(c, s);
}
__device__ __forceinline__ uint32_t word(const uint4& v, int e) { return e == 0 ? v.x : e == 1 ? v.y : e == 2 ? v.z : v.w; }
__device__ __forceinline__ void cdft16(const uint4 (&q)[4], const uint4 (&F)[4], uint4 (&o)[4]) {
  float acc[2][4][4];
#pragma unroll
  for (int p = 0; p < 2; p++)
#pragma unroll
    for (int v = 0; v < 4; v++) {
      acc[p][v][0] = acc[p][v][1] = acc[p][v][2] = acc[p][v][3] = 0.f;
#pragma unroll
      for (int ks = 0; ks < 2; ks++)
        mma16816(acc[p][v], word(q[2 * ks], 2 * p), word(q[2 * ks], 2 * p + 1), word(q[2 * ks + 1], 2 * p),
                 word(q[2 * ks + 1], 2 * p + 1), word(F[ks * 2 + (v >> 1)], (v & 1) * 2), word(F[ks * 2 + (v >> 1)], (v & 1) * 2 + 1));
    }
#pragma unroll
  for (int v = 0; v < 4; v++)
    o[v] = make_uint4(pack2(acc[0][v][0], acc[0][v][1]), pack2(acc[0][v][2], acc[0][v][3]),
                      pack2(acc[1][v][0], acc[1][v][1]), pack2(acc[1][v][2], acc[1][v][3]));
}
__device__ __forceinline__ void st_tag(uint4* p, const uint4& v, uint32_t tag) {
  asm volatile("{.reg .b128 r; .reg .b64 a, b; mov.b64 a, {%1,%2}; mov.b64 b, {%3,%4}; mov.b128 r, {a,b}; st.relaxed.gpu.global.b128 [%0], r;}"
               ::"l"(p), "r"((v.x & ~1u) | tag), "r"(v.y), "r"(v.z), "r"(v.w) : "memory");
}
__device__ __forceinline__ uint4 ld_b128(const uint4* p) {
  uint4 v;
  asm volatile("{.reg .b128 r; .reg .b64 a, b; ld.relaxed.gpu.global.b128 r, [%4]; mov.b128 {a,b}, r; mov.b64 {%0,%1}, a; mov.b64 {%2,%3}, b;}"
               : "=r"(v.x), "=r"(v.y), "=r"(v.z), "=r"(v.w) : "l"(p) : "memory");
  return v;
}
__device__ __forceinline__ void ld_tag4_issue(uint4 (&q)[4], const uint4* p) {
#pragma unroll
  for (int i = 0; i < 4; i++) q[i] = ld_b128(p + i * 256);
}
__device__ __forceinline__ void ld_tag4_finish(uint4 (&q)[4], const uint4* p, uint32_t tag) {
  int it = 0;
  while (__any_sync(0xffffffffu, ((q[0].x ^ tag) | (q[1].x ^ tag) | (q[2].x ^ tag) | (q[3].x ^ tag)) & 1u)) {
#pragma unroll
    for (int i = 0; i < 4; i++)
      if ((q[i].x ^ tag) & 1u) q[i] = ld_b128(p + i * 256);
    if (++it > SPIN_LIMIT) __trap();
  }
#pragma unroll
  for (int i = 0; i < 4; i++) q[i].x &= ~1u;
}
__device__ __forceinline__ void row_stats(const uint32_t (&a)[8], const uint32_t (&b)[8], int lane, float (&sum)[2], float (&sq)[2]) {
  float da[4] = {0.f, 0.f, 0.f, 0.f}, db[4] = {0.f, 0.f, 0.f, 0.f}, ds[4] = {0.f, 0.f, 0.f, 0.f};
#pragma unroll
  for (int q = 0; q < 4; q++) {
    mma16816(ds, a[2 * q], b[2 * q], a[2 * q + 1], b[2 * q + 1], 0x3f803f80u, 0x3f803f80u);
    mma16816(da, a[2 * q], b[2 * q], a[2 * q + 1], b[2 * q + 1], a[2 * q], a[2 * q + 1]);
    mma16816(db, a[2 * q], b[2 * q], a[2 * q + 1], b[2 * q + 1], b[2 * q], b[2 * q + 1]);
  }
  const int src = (lane & 28) | (lane >> 3);
  const float qa = __shfl_sync(0xffffffffu, (lane & 4) ? da[1] : da[0], src);
  const float qb = __shfl_sync(0xffffffffu, (lane & 4) ? db[3] : db[2], src);
  float v = (lane & 2) ? ((lane & 1) ? ds[2] : ds[0]) : ((lane & 1) ? qb : qa);
  v += __shfl_xor_sync(0xffffffffu, v, 4);
  v += __shfl_xor_sync(0xffffffffu, v, 8);
  v += __shfl_xor_sync(0xffffffffu, v, 16);
  sq[0] = __shfl_sync(0xffffffffu, v, 0);
  sq[1] = __shfl_sync(0xffffffffu, v, 1);
  sum[0] = __shfl_sync(0xffffffffu, v, 2);
  sum[1] = __shfl_sync(0xffffffffu, v, 3);
}
__device__ __forceinline__ uint64_t desc64(uint32_t lo, uint32_t hi) {
  uint64_t d;
  asm("mov.b64 %0, {%1, %2};" : "=l"(d) : "r"(lo), "r"(hi));
  return d;
}
constexpr uint32_t desc_hi(uint32_t sbo, uint32_t swz) { return (sbo >> 4) | (swz << 30); }
__device__ __forceinline__ uint32_t desc_lo(uint32_t addr, uint32_t lbo) { return ((addr & 0x3FFFF) >> 4) | ((lbo >> 4) << 16); }
__device__ __forceinline__ void cp_async16(uint32_t dst, const void* src) {
  asm volatile("cp.async.cg.shared.global [%0], [%1], 16;" ::"r"(dst), "l"(src) : "memory");
}
__device__ __forceinline__ uint2 lds2(uint32_t a) {
  uint2 v;
  asm volatile("ld.shared.v2.u32 {%0,%1}, [%2];" : "=r"(v.x), "=r"(v.y) : "r"(a) : "memory");
  return v;
}
__device__ __forceinline__ uint32_t lds_u16(uint32_t a) {
  uint16_t v;
  asm volatile("ld.shared.u16 %0, [%1];" : "=h"(v) : "r"(a) : "memory");
  return v;
}
__device__ __forceinline__ void wg_fence() { asm volatile("wgmma.fence.sync.aligned;" ::: "memory"); }
__device__ __forceinline__ void wg_commit() { asm volatile("wgmma.commit_group.sync.aligned;" ::: "memory"); }
template <int N>
__device__ __forceinline__ void wg_wait() { asm volatile("wgmma.wait_group.sync.aligned %0;" ::"n"(N) : "memory"); }
__device__ __forceinline__ void bulk_load(uint32_t dst, const void* src, int bytes, uint32_t bar) {
  asm volatile("cp.async.bulk.shared::cluster.global.mbarrier::complete_tx::bytes [%0], [%1], %2, [%3];"
               ::"r"(dst), "l"(src), "r"(bytes), "r"(bar) : "memory");
}
__device__ __forceinline__ void tma3(uint32_t dst, const CUtensorMap* tm, uint32_t bar, int c0, int c1, int c2) {
  asm volatile("cp.async.bulk.tensor.3d.shared::cluster.global.mbarrier::complete_tx::bytes [%0], [%1, {%3,%4,%5}], [%2];"
               ::"r"(dst), "l"(tm), "r"(bar), "r"(c0), "r"(c1), "r"(c2) : "memory");
}
__device__ __forceinline__ void tma3_mc(uint32_t dst, const CUtensorMap* tm, uint32_t bar, int c1, int c2) {
  asm volatile("cp.async.bulk.tensor.3d.shared::cluster.global.mbarrier::complete_tx::bytes.multicast::cluster [%0], [%1, {%3,%4,%5}], [%2], %6;"
               ::"r"(dst), "l"(tm), "r"(bar), "r"(0), "r"(c1), "r"(c2), "h"((uint16_t)3) : "memory");
}
__device__ __forceinline__ void mbar_arrive_remote(uint32_t rb) {
  asm volatile("mbarrier.arrive.shared::cluster.b64 _, [%0];" ::"r"(rb) : "memory");
}
__device__ __forceinline__ uint4 ldg_ca4(const void* p) {
  uint4 v;
  asm volatile("ld.global.ca.v4.u32 {%0,%1,%2,%3}, [%4];" : "=r"(v.x), "=r"(v.y), "=r"(v.z), "=r"(v.w) : "l"(p) : "memory");
  return v;
}
__device__ __forceinline__ void tma5(uint32_t dst, const CUtensorMap* tm, uint32_t bar, int c0, int c4) {
  asm volatile("cp.async.bulk.tensor.5d.shared::cluster.global.mbarrier::complete_tx::bytes [%0], [%1, {%3,%4,%4,%4,%5}], [%2];"
               ::"r"(dst), "l"(tm), "r"(bar), "r"(c0), "r"(0), "r"(c4) : "memory");
}
__device__ __forceinline__ float swiglu(float g, float u, float r) {
  float hg = (0.5f * r) * g, th;
  asm("tanh.approx.f32 %0, %1;" : "=f"(th) : "f"(hg));
  return fmaf(hg, th, hg) * (r * u);
}
__device__ __forceinline__ uint32_t hsub2_bf16(uint32_t a, uint32_t b) {
  uint32_t r;
  asm("sub.rn.bf16x2 %0, %1, %2;" : "=r"(r) : "r"(a), "r"(b));
  return r;
}
__device__ __forceinline__ void l2_prefetch(const void* p, int bytes) {
  asm volatile("cp.async.bulk.prefetch.L2.global [%0], %1;" ::"l"(p), "r"(bytes) : "memory");
}

__device__ __forceinline__ void wgmma_n256(float (&d)[128], uint64_t da, uint64_t db) {
  asm volatile("wgmma.mma_async.sync.aligned.m64n256k16.f32.bf16.bf16 {"
      "%0,%1,%2,%3,%4,%5,%6,%7,%8,%9,%10,%11,%12,%13,%14,%15,"
      "%16,%17,%18,%19,%20,%21,%22,%23,%24,%25,%26,%27,%28,%29,%30,%31,"
      "%32,%33,%34,%35,%36,%37,%38,%39,%40,%41,%42,%43,%44,%45,%46,%47,"
      "%48,%49,%50,%51,%52,%53,%54,%55,%56,%57,%58,%59,%60,%61,%62,%63,"
      "%64,%65,%66,%67,%68,%69,%70,%71,%72,%73,%74,%75,%76,%77,%78,%79,"
      "%80,%81,%82,%83,%84,%85,%86,%87,%88,%89,%90,%91,%92,%93,%94,%95,"
      "%96,%97,%98,%99,%100,%101,%102,%103,%104,%105,%106,%107,%108,%109,%110,%111,"
      "%112,%113,%114,%115,%116,%117,%118,%119,%120,%121,%122,%123,%124,%125,%126,%127"
      "}, %128, %129, 1, 1, 1, 0, 1;\n"
      : "+f"(d[0]),"+f"(d[1]),"+f"(d[2]),"+f"(d[3]),"+f"(d[4]),"+f"(d[5]),"+f"(d[6]),"+f"(d[7]),
        "+f"(d[8]),"+f"(d[9]),"+f"(d[10]),"+f"(d[11]),"+f"(d[12]),"+f"(d[13]),"+f"(d[14]),"+f"(d[15]),
        "+f"(d[16]),"+f"(d[17]),"+f"(d[18]),"+f"(d[19]),"+f"(d[20]),"+f"(d[21]),"+f"(d[22]),"+f"(d[23]),
        "+f"(d[24]),"+f"(d[25]),"+f"(d[26]),"+f"(d[27]),"+f"(d[28]),"+f"(d[29]),"+f"(d[30]),"+f"(d[31]),
        "+f"(d[32]),"+f"(d[33]),"+f"(d[34]),"+f"(d[35]),"+f"(d[36]),"+f"(d[37]),"+f"(d[38]),"+f"(d[39]),
        "+f"(d[40]),"+f"(d[41]),"+f"(d[42]),"+f"(d[43]),"+f"(d[44]),"+f"(d[45]),"+f"(d[46]),"+f"(d[47]),
        "+f"(d[48]),"+f"(d[49]),"+f"(d[50]),"+f"(d[51]),"+f"(d[52]),"+f"(d[53]),"+f"(d[54]),"+f"(d[55]),
        "+f"(d[56]),"+f"(d[57]),"+f"(d[58]),"+f"(d[59]),"+f"(d[60]),"+f"(d[61]),"+f"(d[62]),"+f"(d[63]),
        "+f"(d[64]),"+f"(d[65]),"+f"(d[66]),"+f"(d[67]),"+f"(d[68]),"+f"(d[69]),"+f"(d[70]),"+f"(d[71]),
        "+f"(d[72]),"+f"(d[73]),"+f"(d[74]),"+f"(d[75]),"+f"(d[76]),"+f"(d[77]),"+f"(d[78]),"+f"(d[79]),
        "+f"(d[80]),"+f"(d[81]),"+f"(d[82]),"+f"(d[83]),"+f"(d[84]),"+f"(d[85]),"+f"(d[86]),"+f"(d[87]),
        "+f"(d[88]),"+f"(d[89]),"+f"(d[90]),"+f"(d[91]),"+f"(d[92]),"+f"(d[93]),"+f"(d[94]),"+f"(d[95]),
        "+f"(d[96]),"+f"(d[97]),"+f"(d[98]),"+f"(d[99]),"+f"(d[100]),"+f"(d[101]),"+f"(d[102]),"+f"(d[103]),
        "+f"(d[104]),"+f"(d[105]),"+f"(d[106]),"+f"(d[107]),"+f"(d[108]),"+f"(d[109]),"+f"(d[110]),"+f"(d[111]),
        "+f"(d[112]),"+f"(d[113]),"+f"(d[114]),"+f"(d[115]),"+f"(d[116]),"+f"(d[117]),"+f"(d[118]),"+f"(d[119]),
        "+f"(d[120]),"+f"(d[121]),"+f"(d[122]),"+f"(d[123]),"+f"(d[124]),"+f"(d[125]),"+f"(d[126]),"+f"(d[127])
      : "l"(da), "l"(db));
}
__device__ __forceinline__ void wgmma_n192(float (&d)[96], uint64_t da, uint64_t db) {
  asm volatile("wgmma.mma_async.sync.aligned.m64n192k16.f32.bf16.bf16 {"
      "%0,%1,%2,%3,%4,%5,%6,%7,%8,%9,%10,%11,%12,%13,%14,%15,"
      "%16,%17,%18,%19,%20,%21,%22,%23,%24,%25,%26,%27,%28,%29,%30,%31,"
      "%32,%33,%34,%35,%36,%37,%38,%39,%40,%41,%42,%43,%44,%45,%46,%47,"
      "%48,%49,%50,%51,%52,%53,%54,%55,%56,%57,%58,%59,%60,%61,%62,%63,"
      "%64,%65,%66,%67,%68,%69,%70,%71,%72,%73,%74,%75,%76,%77,%78,%79,"
      "%80,%81,%82,%83,%84,%85,%86,%87,%88,%89,%90,%91,%92,%93,%94,%95"
      "}, %96, %97, 1, 1, 1, 0, 1;\n"
      : "+f"(d[0]),"+f"(d[1]),"+f"(d[2]),"+f"(d[3]),"+f"(d[4]),"+f"(d[5]),"+f"(d[6]),"+f"(d[7]),
        "+f"(d[8]),"+f"(d[9]),"+f"(d[10]),"+f"(d[11]),"+f"(d[12]),"+f"(d[13]),"+f"(d[14]),"+f"(d[15]),
        "+f"(d[16]),"+f"(d[17]),"+f"(d[18]),"+f"(d[19]),"+f"(d[20]),"+f"(d[21]),"+f"(d[22]),"+f"(d[23]),
        "+f"(d[24]),"+f"(d[25]),"+f"(d[26]),"+f"(d[27]),"+f"(d[28]),"+f"(d[29]),"+f"(d[30]),"+f"(d[31]),
        "+f"(d[32]),"+f"(d[33]),"+f"(d[34]),"+f"(d[35]),"+f"(d[36]),"+f"(d[37]),"+f"(d[38]),"+f"(d[39]),
        "+f"(d[40]),"+f"(d[41]),"+f"(d[42]),"+f"(d[43]),"+f"(d[44]),"+f"(d[45]),"+f"(d[46]),"+f"(d[47]),
        "+f"(d[48]),"+f"(d[49]),"+f"(d[50]),"+f"(d[51]),"+f"(d[52]),"+f"(d[53]),"+f"(d[54]),"+f"(d[55]),
        "+f"(d[56]),"+f"(d[57]),"+f"(d[58]),"+f"(d[59]),"+f"(d[60]),"+f"(d[61]),"+f"(d[62]),"+f"(d[63]),
        "+f"(d[64]),"+f"(d[65]),"+f"(d[66]),"+f"(d[67]),"+f"(d[68]),"+f"(d[69]),"+f"(d[70]),"+f"(d[71]),
        "+f"(d[72]),"+f"(d[73]),"+f"(d[74]),"+f"(d[75]),"+f"(d[76]),"+f"(d[77]),"+f"(d[78]),"+f"(d[79]),
        "+f"(d[80]),"+f"(d[81]),"+f"(d[82]),"+f"(d[83]),"+f"(d[84]),"+f"(d[85]),"+f"(d[86]),"+f"(d[87]),
        "+f"(d[88]),"+f"(d[89]),"+f"(d[90]),"+f"(d[91]),"+f"(d[92]),"+f"(d[93]),"+f"(d[94]),"+f"(d[95])
      : "l"(da), "l"(db));
}
__device__ __forceinline__ void wgmma_n128(float (&d)[64], uint64_t da, uint64_t db) {
  asm volatile("wgmma.mma_async.sync.aligned.m64n128k16.f32.bf16.bf16 {"
      "%0,%1,%2,%3,%4,%5,%6,%7,%8,%9,%10,%11,%12,%13,%14,%15,"
      "%16,%17,%18,%19,%20,%21,%22,%23,%24,%25,%26,%27,%28,%29,%30,%31,"
      "%32,%33,%34,%35,%36,%37,%38,%39,%40,%41,%42,%43,%44,%45,%46,%47,"
      "%48,%49,%50,%51,%52,%53,%54,%55,%56,%57,%58,%59,%60,%61,%62,%63"
      "}, %64, %65, 1, 1, 1, 0, 1;\n"
      : "+f"(d[0]),"+f"(d[1]),"+f"(d[2]),"+f"(d[3]),"+f"(d[4]),"+f"(d[5]),"+f"(d[6]),"+f"(d[7]),
        "+f"(d[8]),"+f"(d[9]),"+f"(d[10]),"+f"(d[11]),"+f"(d[12]),"+f"(d[13]),"+f"(d[14]),"+f"(d[15]),
        "+f"(d[16]),"+f"(d[17]),"+f"(d[18]),"+f"(d[19]),"+f"(d[20]),"+f"(d[21]),"+f"(d[22]),"+f"(d[23]),
        "+f"(d[24]),"+f"(d[25]),"+f"(d[26]),"+f"(d[27]),"+f"(d[28]),"+f"(d[29]),"+f"(d[30]),"+f"(d[31]),
        "+f"(d[32]),"+f"(d[33]),"+f"(d[34]),"+f"(d[35]),"+f"(d[36]),"+f"(d[37]),"+f"(d[38]),"+f"(d[39]),
        "+f"(d[40]),"+f"(d[41]),"+f"(d[42]),"+f"(d[43]),"+f"(d[44]),"+f"(d[45]),"+f"(d[46]),"+f"(d[47]),
        "+f"(d[48]),"+f"(d[49]),"+f"(d[50]),"+f"(d[51]),"+f"(d[52]),"+f"(d[53]),"+f"(d[54]),"+f"(d[55]),
        "+f"(d[56]),"+f"(d[57]),"+f"(d[58]),"+f"(d[59]),"+f"(d[60]),"+f"(d[61]),"+f"(d[62]),"+f"(d[63])
      : "l"(da), "l"(db));
}

constexpr int C_LN = 0, C_PX = 16, C_PY = 32;
constexpr int NB_CONS = 1, NB_LN = 2, NB_PUB = 3, NB_LAG = 4, NB_LAG2 = 5, NB_INIT = 6, NB_RDY = 7;
#define LAG 2
#define LAG2 3
#define EARLY_POLL 0
#define PF2_SIG 1
constexpr int SM_E = 0, SM_X = 16384, SM_FC = 32768, SM_T = 36864, SM_E2 = 131072, SM_W = 147456;
constexpr unsigned long long KORDER = 0xBA9432DC876510ull;
constexpr uint32_t HI128 = desc_hi(1024, 1), HI64 = desc_hi(512, 2), HI0 = desc_hi(1024, 0);

struct Bars {
  uint64_t full1[6], empty1[6], fullA[8], full2[14], empty2[8], xbar, xfree, tbar, sbar, sig[2];
  uint32_t epoch;
};

template <int NT>
__device__ __forceinline__ void make_p(const float (&acc)[NT * 32], float r0, float r1, uint4 (&p)[NT * 2]) {
#pragma unroll
  for (int q = 0; q < NT; q++)
#pragma unroll
    for (int h = 0; h < 2; h++) {
      uint32_t w[4];
#pragma unroll
      for (int i = 0; i < 4; i++) {
        const int a = (q * 4 + i) * 4 + 2 * h, b = a + NT * 16;
        w[i] = pack2(swiglu(acc[a], acc[b], h ? r1 : r0), swiglu(acc[a + 1], acc[b + 1], h ? r1 : r0));
      }
      p[2 * q + h] = make_uint4(w[0], w[1], w[2], w[3]);
    }
}
__device__ __forceinline__ void stg4(uint4* p, const uint4& v) {
  asm volatile("st.global.v4.u32 [%0], {%1,%2,%3,%4};" ::"l"(p), "r"(v.x), "r"(v.y), "r"(v.z), "r"(v.w) : "memory");
}

__global__ void __cluster_dims__(2, 1, 1) __launch_bounds__(NTHREADS, 1)
fused_kernel(const __grid_constant__ CUtensorMap tmGX, const __grid_constant__ CUtensorMap tmUX,
             const __grid_constant__ CUtensorMap tmGY, const __grid_constant__ CUtensorMap tmUY,
             const __grid_constant__ CUtensorMap tmD, const __grid_constant__ CUtensorMap tmWR,
             const __grid_constant__ CUtensorMap tmWI, const __nv_bfloat16* __restrict__ x,
             const char* __restrict__ wg_raw, const char* __restrict__ wu_raw, const char* __restrict__ wd_raw,
             __nv_bfloat16* __restrict__ out) {
  extern __shared__ __align__(1024) char smem_raw[];
  const uint32_t sbase = (s2u(smem_raw) + 1023) & ~1023u;
  const uint32_t sbar = sbase + 14 * SLOT, sstat = sbar + 512;
  const int tid = threadIdx.x, lane = tid & 31;
  const int c = blockIdx.x, kh = c & 1, f = (c >> 1) & 7, rb = 2 * (c >> 4) + kh, rb2 = 2 * (c >> 4) + (f >> 2), nq = f & 3;
#define BAR(field, i) (sbar + (uint32_t)offsetof(Bars, field) + 8u * (i))
#define TOFF(field) (sbase + SM_T + (uint32_t)offsetof(Tables, field) + lane * 16)

  if (tid >= 256) {
    asm volatile("setmaxnreg.dec.sync.aligned.u32 56;");
    const int warp = __shfl_sync(0xffffffffu, tid >> 5, 0);
    if (tid == 256) {
      for (int i = 0; i < 6; i++) { mbar_init(BAR(full1, i), 1); mbar_init(BAR(empty1, i), 16); }
      for (int i = 0; i < 8; i++) { mbar_init(BAR(fullA, i), 1); mbar_init(BAR(empty2, i), 8); }
      for (int i = 0; i < 14; i++) mbar_init(BAR(full2, i), 2);
      mbar_init(BAR(xbar, 0), 1);
      mbar_init(BAR(xfree, 0), 8);
      mbar_init(BAR(tbar, 0), 1);
      mbar_init(BAR(sbar, 0), 32);
      mbar_init(BAR(sig, 0), 8);
      mbar_init(BAR(sig, 1), 16);
      mbar_expect(BAR(xbar, 0), 16384);
      asm volatile("fence.mbarrier_init.release.cluster;" ::: "memory");
    }
    if (tid == 320) {
      const unsigned e = ld_relaxed(&g_cnt[(C_LN + rb) * 32]) >> 3;
      asm volatile("st.shared.u32 [%0], %1;" ::"r"(BAR(epoch, 0)), "r"(e) : "memory");
    }
    __syncwarp();
    asm volatile("barrier.cluster.arrive.relaxed.aligned;" ::: "memory");
    bar_arrive(NB_RDY, 384);
    bar_sync(NB_INIT, 384);
    unsigned epoch;
    asm volatile("ld.shared.u32 %0, [%1];" : "=r"(epoch) : "r"(BAR(epoch, 0)) : "memory");
    if (warp == 8) {
      if (lane == 0) {
        const int ax = (7 * f + 3 * (f & 1)) >> 1;
        const int ay = 7 * f + ((f & 1) ? 0 : 4);
        const CUtensorMap* tx = kh ? &tmUX : &tmGX;
        const CUtensorMap* ty = kh ? &tmUY : &tmGY;
        uint32_t s = 0, ph = 1;
        mbar_wait(BAR(sig, 1), 0);
#pragma unroll 1
        for (int n = 0; n < 32; n++) {
          const uint32_t dst = sbase + (8 + s) * SLOT, fb = BAR(full1, s);
          mbar_wait(BAR(empty1, s), ph);
          if (n < 16) {
            mbar_expect(fb, 16384);
            tma3_mc(dst + kh * 8192, tx, fb, n * 32, ax);
          } else {
            mbar_expect(fb, 12288);
            tma3_mc(dst + kh * 6144, ty, fb, (n - 16) * 32, ay);
          }
          if (++s == 6) { s = 0; ph ^= 1; }
        }
      }
    } else if (warp == 9) {
      if (lane == 0) {
        mbar_wait(BAR(empty1, 5), 0);
        mbar_wait(BAR(empty1, 5), 1);
#pragma unroll 1
        for (int i = 0; i < 14; i++) {
          const int kblk = 14 * kh + (int)((KORDER >> (4 * i)) & 15);
          if (i < 8) mbar_wait(BAR(empty1, (17 + 2 * i) % 6), ((17 + 2 * i) / 6) & 1);
          else mbar_wait(BAR(empty2, i - 8), 0);
          mbar_expect(BAR(full2, i), 16384);
          tma5(sbase + (i & 7) * SLOT, &tmD, BAR(full2, i), nq * 128, 2 * kblk);
          tma5(sbase + (i & 7) * SLOT + 8192, &tmD, BAR(full2, i), nq * 128 + 64, 2 * kblk);
        }
      }
    } else if (warp == 10) {
      if (lane == 0) {
        const int w0 = ((c >> 3) * 257 + 32 * (c & 7) + 1) & ~7;
        mbar_expect(BAR(tbar, 0), T2_BYTES + 2 * 10240);
        tma3(sbase + SM_W, &tmWR, BAR(tbar, 0), w0, 0, 0);
        tma3(sbase + SM_W + 10240, &tmWI, BAR(tbar, 0), w0, 0, 0);
        bulk_load(sbase + SM_T + T1_BYTES, reinterpret_cast<const char*>(&g_tab) + T1_BYTES, T2_BYTES, BAR(tbar, 0));
      }
      bar_sync(NB_LN, 288);
      if (lane == 0) {
        PROFP(0);
        red_release(&g_cnt[(C_LN + rb) * 32]);
        PROFP(1);
        wait_counter(&g_cnt[(C_LN + rb) * 32], (epoch + 1) * 8);
        asm volatile("fence.proxy.async.global;" ::: "memory");
        PROFP(2);
#pragma unroll 1
        for (int kb = 0; kb < 8; kb++) {
          mbar_expect(BAR(fullA, kb), 16384);
          bulk_load(sbase + kb * SLOT, &g_LN[(rb * 8 + kb) * 1024], 16384, BAR(fullA, kb));
        }
#pragma unroll 1
        for (int i = 0; i < 4; i++) mbar_wait(BAR(empty1, 2), i & 1);
        uint32_t d = 2;
#pragma unroll 1
        for (int s = 0; s < 14; s++) {
          const int kblk = 14 * kh + (int)((KORDER >> (4 * s)) & 15);
          if (s == 0 || s == 8) {
            PROFP(3 + (s >> 2));
            wait_counter(&g_cnt[((s == 0 ? C_PX : C_PY) + rb2) * 32], (epoch + 1) * 8);
            asm volatile("fence.proxy.async.global;" ::: "memory");
            PROFP(4 + (s >> 2));
          }
          if (s < 6) mbar_wait(BAR(empty1, d), s < 4 ? 0 : 1);
          else mbar_wait(BAR(empty2, s - 6), 0);
          mbar_expect(BAR(full2, s), 16384);
          bulk_load(sbase + (8 + d) * SLOT, &g_P[(rb2 * 28 + kblk) * 1024], 16384, BAR(full2, s));
          if (++d == 6) d = 0;
        }
        PROFP(7);
      }
    } else {
      if (lane == 0) {
        l2_prefetch(wg_raw + (size_t)c * 5376, 5376);
        l2_prefetch(wu_raw + (size_t)c * 5376, 5376);
        mbar_wait(BAR(sig, PF2_SIG), 0);
        l2_prefetch(wg_raw + 688128 + (size_t)c * 8960, 8960);
        l2_prefetch(wu_raw + 688128 + (size_t)c * 8960, 8960);
      }
      mbar_wait(BAR(fullA, 7), 0);
      if (lane == 0) l2_prefetch(wd_raw + (size_t)c * 14336, 14336);
      {
        const uint32_t tag = (epoch + 1) & 1;
        uint4 v0, v1, v2;
        int it = 0;
        while (true) {
          v0 = ld_b128(&g_ST[rb * 64 + lane]);
          v1 = ld_b128(&g_ST[rb * 64 + 32 + lane]);
          v2 = ld_b128(&g_ST[rb2 * 64 + 32 * kh + lane]);
          if (!__any_sync(0xffffffffu, ((v0.x ^ tag) | (v1.x ^ tag) | (v2.x ^ tag)) & 1u)) break;
          if (++it > SPIN_LIMIT) __trap();
        }
        sts4(sstat + lane * 16, v0.x & ~1u, v0.y, v0.z, v0.w);
        sts4(sstat + 512 + lane * 16, v1.x & ~1u, v1.y, v1.z, v1.w);
        sts4(sstat + 1024 + lane * 16, v2.x & ~1u, v2.y, v2.z, v2.w);
        mbar_arrive(BAR(sbar, 0));
      }
#pragma unroll 1
      for (int e = 0; e < 2; e++) {
        bar_sync(NB_PUB, 288);
        if (lane == 0) {
          PROFP(8 + 2 * e);
          red_release(&g_cnt[((e == 0 ? C_PX : C_PY) + rb) * 32]);
          PROFP(9 + 2 * e);
        }
      }
    }
    __syncwarp();
    asm volatile("barrier.cluster.wait.aligned;" ::: "memory");
  } else {
    const int warp = __shfl_sync(0xffffffffu, tid >> 5, 0);
    const int g = lane >> 2, t = lane & 3;
    PROF(0);
    PROFG(14);
#pragma unroll
    for (int i = 0; i < 4; i++) {
      const int r = i >> 1, ch = (i & 1) * 32 + lane;
      cp_async16(sbase + SM_X + (2 * warp + r) * 1024 + ((ch ^ ((ch >> 2) & 6)) * 16),
                 x + (size_t)(c + 128 * (2 * warp + r)) * 512 + ch * 8);
    }
    asm volatile("cp.async.commit_group;" ::: "memory");
    asm volatile("barrier.cluster.arrive.relaxed.aligned;" ::: "memory");
    uint4 tw[8], fb[16];
    const uint4 fa = ldg_ca4(&g_tab.fa[lane][0]);
#pragma unroll
    for (int i = 0; i < 8; i++) tw[i] = ldg_ca4(&g_tab.tw1[i][lane][0]);
#pragma unroll
    for (int i = 0; i < 16; i++) fb[i] = ldg_ca4(&g_tab.fb[i][lane][0]);
    asm volatile("setmaxnreg.inc.sync.aligned.u32 224;");
    uint32_t rbar;
    asm volatile("mapa.shared::cluster.u32 %0, %1, %2;" : "=r"(rbar) : "r"(sbar), "r"(kh ^ 1));
#define RBAR(field, i) (rbar + (uint32_t)offsetof(Bars, field) + 8u * (i))
    {
      const int ln = (tid >> 1) & 31, lg = ln >> 2, lt = ln & 3, i = 4 * (tid >> 6) + 2 * (tid & 1);
      const int kidx = lt + 8 * (i >> 3), nidx = 4 * ((i >> 1) & 3) + (lg >> 1);
      const uint32_t a0 = cfrag<2048>((c + 128 * kidx) * nidx, lg & 1), a1 = cfrag<2048>((c + 128 * (kidx + 4)) * nidx, lg & 1);
      const uint32_t b0 = cfrag<2048>(-(c + 128 * nidx) * kidx, lg & 1), b1 = cfrag<2048>(-(c + 128 * nidx) * (kidx + 4), lg & 1);
      asm volatile("st.shared.v2.u32 [%0], {%1,%2};" ::"r"(sbase + SM_FC + tid * 8), "r"(a0), "r"(a1) : "memory");
      asm volatile("st.shared.v2.u32 [%0], {%1,%2};" ::"r"(sbase + SM_FC + 2048 + tid * 8), "r"(b0), "r"(b1) : "memory");
    }
    asm volatile("cp.async.wait_group 0;" ::: "memory");
    __syncwarp();
    bar_arrive(NB_INIT, 384);
    PROF(13);
    uint32_t tag;
    uint4 q[4], o[4];
    {
      uint32_t v[2][8];
#pragma unroll
      for (int r = 0; r < 2; r++)
#pragma unroll
        for (int q = 0; q < 4; q++) {
          const uint2 u = lds2(sbase + SM_X + (2 * warp + r) * 1024 + (t + 4 * (q >> 1)) * 128 + (((4 * (q & 1) + (g >> 1)) ^ (2 * t)) * 16) + (g & 1) * 8);
          v[r][2 * q] = u.x; v[r][2 * q + 1] = u.y;
        }
      float sum[2], sq[2], rstd[2];
      row_stats(v[0], v[1], lane, sum, sq);
#pragma unroll
      for (int r = 0; r < 2; r++) {
        const float m = sum[r] * (1.f / 512.f);
        rstd[r] = rsqrtf(fmaxf(fmaf(-m, m, sq[r] * (1.f / 512.f)), 0.f) + 1e-5f);
      }
      uint32_t alo[4][4], ahi[4][4];
#pragma unroll
      for (int r = 0; r < 2; r++)
#pragma unroll
        for (int i = 0; i < 4; i++) {
          const uint32_t sel = (i & 1) ? 0x7632u : 0x5410u;
          const uint32_t b0 = __byte_perm(v[r][i >> 1], v[r][2 + (i >> 1)], sel);
          const uint32_t b1 = __byte_perm(v[r][4 + (i >> 1)], v[r][6 + (i >> 1)], sel);
          float d[4] = {0.f, 0.f, 0.f, 0.f};
          mma16816(d, fa.x, fa.y, fa.z, fa.w, b0, b1);
          const uint4 &ka = tw[2 * i], &kb = tw[2 * i + 1];
          const uint32_t re = pack2(d[0] * __uint_as_float(ka.x) + d[2] * __uint_as_float(ka.y), d[1] * __uint_as_float(kb.x) + d[3] * __uint_as_float(kb.y));
          const uint32_t im = pack2(d[0] * __uint_as_float(ka.z) + d[2] * __uint_as_float(ka.w), d[1] * __uint_as_float(kb.z) + d[3] * __uint_as_float(kb.w));
          const uint32_t dc = pack2(fmaf(sum[r], -1.f / 32.f, d[0]), fmaf(sum[r], -1.f / 32.f, d[1]));
          alo[i][r] = re; alo[i][2 + r] = im;
          ahi[i][r] = g == 0 ? dc : re; ahi[i][2 + r] = g == 0 ? 0u : im;
        }
      float acc[8][4];
#pragma unroll
      for (int u = 0; u < 8; u++) {
        acc[u][0] = acc[u][1] = acc[u][2] = acc[u][3] = 0.f;
#pragma unroll
        for (int i = 0; i < 4; i++) {
          const uint4& bq = fb[i * 4 + (u >> 1)];
          if (u < 4) mma16816(acc[u], alo[i][0], alo[i][1], alo[i][2], alo[i][3], (u & 1) ? bq.z : bq.x, (u & 1) ? bq.w : bq.y);
          else       mma16816(acc[u], ahi[i][0], ahi[i][1], ahi[i][2], ahi[i][3], (u & 1) ? bq.z : bq.x, (u & 1) ? bq.w : bq.y);
        }
      }
#pragma unroll
      for (int r = 0; r < 2; r++)
#pragma unroll
        for (int h = 0; h < 2; h++) {
          const int j = 2 * warp + r, m = 2 * t + h;
          const float rs = rstd[r];
          sts4(sbase + SM_E + ((j * 8 + m) * 8 + (g ^ (2 * t) ^ (2 * (j & 3)))) * 16,
               pack2(acc[2 * h][2 * r] * rs, acc[2 * h][2 * r + 1] * rs), pack2(acc[2 * h + 1][2 * r] * rs, acc[2 * h + 1][2 * r + 1] * rs),
               pack2(acc[4 + 2 * h][2 * r] * rs, acc[4 + 2 * h][2 * r + 1] * rs), pack2(acc[5 + 2 * h][2 * r] * rs, acc[5 + 2 * h][2 * r + 1] * rs));
        }
      if (tid == 0) PROFP(12);
      bar_sync(NB_RDY, 384);
      if (tid == 0) PROFP(13);
      uint4 fc[4];
#pragma unroll
      for (int i = 0; i < 4; i++) fc[i] = lds4(sbase + SM_FC + i * 512 + lane * 16);
      asm volatile("ld.shared.u32 %0, [%1];" : "=r"(tag) : "r"(BAR(epoch, 0)) : "memory");
      tag = (tag + 1) & 1;
#pragma unroll
      for (int i = 0; i < 4; i++) q[i] = lds4(sbase + SM_E + (((t + 4 * i) * 8 + warp) * 8 + (g ^ (warp & 6) ^ (2 * t))) * 16);
      cdft16(q, fc, o);
#pragma unroll
      for (int vv = 0; vv < 4; vv++) st_tag(&g_Z1[(((4 * vv + t) * 8 + warp) * 128 + c) * 8 + g], o[vv], tag);
    }
    PROF(1);
    {
      const uint4* const zp = &g_Z1[(c * 128 + 8 * t + warp) * 8 + g];
      if (EARLY_POLL) ld_tag4_issue(q, zp);
      mbar_wait(BAR(tbar, 0), 0);
      uint4 f2[4], g2[4];
#pragma unroll
      for (int i = 0; i < 4; i++) {
        f2[i] = lds4(TOFF(f2) + warp * 2048 + i * 512);
        g2[i] = lds4(TOFF(g2) + warp * 2048 + i * 512);
      }
      const uint4 f8 = lds4(TOFF(f8)), g8 = lds4(TOFF(g8));
      float wfr[16], wfi[16];
      {
        const float fsc = 1.f / (1 << 19);
        const float fsc3 = ((c & 7) == 7 && g == 0) ? 0.5f * fsc : fsc;
        const int gg = g == 0 ? 8 : g, wsh = (2 * (c >> 3) + 2) & 15;
#pragma unroll
        for (int i = 0; i < 16; i++) {
          const int ci = i >> 3, dd = (i >> 2) & 1, e = i & 3;
          const int kk = (e == 0 ? gg : e == 1 ? 16 + gg : e == 2 ? 16 - g : 32 - g) - 1;
          const uint32_t a = sbase + SM_W + ((2 * warp + ci) * 8 + t + 4 * dd) * 80 + wsh + 2 * kk;
          wfr[i] = bf_lo(lds_u16(a)) * (e == 3 ? fsc3 : fsc);
          wfi[i] = bf_lo(lds_u16(a + 10240)) * (e == 3 ? fsc3 : fsc);
        }
      }
      asm volatile("barrier.cluster.wait.aligned;" ::: "memory");
      PROF(2);
      if (!EARLY_POLL) ld_tag4_issue(q, zp);
      ld_tag4_finish(q, zp, tag);
      if (tid == 0) PROFP(30);
      if (lane == 0) mbar_arrive(BAR(sig, 0));
      cdft16(q, f2, o);
      const uint32_t e2 = sbase + SM_E2;
#pragma unroll
      for (int vv = 0; vv < 4; vv++)
        sts4(e2 + ((warp * 16 + 4 * vv + t) * 8 + (g ^ (2 * t) ^ (2 * (warp & 3)))) * 16, o[vv].x, o[vv].y, o[vv].z, o[vv].w);
      bar_sync(NB_CONS, 256);
#pragma unroll
      for (int ci = 0; ci < 2; ci++) {
        const int cc = 2 * warp + ci;
        uint32_t ad[2];
        uint4 u[2];
#pragma unroll
        for (int hh = 0; hh < 2; hh++) {
          ad[hh] = e2 + (((t + 4 * hh) * 16 + cc) * 8 + (g ^ (2 * (cc & 3)) ^ (2 * t))) * 16;
          u[hh] = lds4(ad[hh]);
        }
        uint32_t res[2][4];
#pragma unroll
        for (int p = 0; p < 2; p++) {
          uint32_t y[2][2];
#pragma unroll
          for (int vv = 0; vv < 2; vv++) {
            float d[4] = {0.f, 0.f, 0.f, 0.f};
            mma16816(d, word(u[0], 2 * p), word(u[0], 2 * p + 1), word(u[1], 2 * p), word(u[1], 2 * p + 1), word(f8, 2 * vv), word(f8, 2 * vv + 1));
#pragma unroll
            for (int rr = 0; rr < 2; rr++) {
              const float fr = wfr[ci * 8 + vv * 4 + 2 * p + rr], fi = wfi[ci * 8 + vv * 4 + 2 * p + rr];
              y[vv][rr] = pack2(d[2 * rr] * fr - d[2 * rr + 1] * fi, d[2 * rr] * fi + d[2 * rr + 1] * fr);
            }
          }
#pragma unroll
          for (int vv = 0; vv < 2; vv++) {
            float d[4] = {0.f, 0.f, 0.f, 0.f};
            mma16816(d, y[0][0], y[0][1], y[1][0], y[1][1], word(g8, 2 * vv), word(g8, 2 * vv + 1));
            res[vv][2 * p] = pack2(d[0], d[1]);
            res[vv][2 * p + 1] = pack2(d[2], d[3]);
          }
        }
#pragma unroll
        for (int vv = 0; vv < 2; vv++) sts4(ad[vv], res[vv][0], res[vv][1], res[vv][2], res[vv][3]);
      }
      bar_sync(NB_CONS, 256);
#pragma unroll
      for (int i = 0; i < 4; i++) q[i] = lds4(e2 + ((warp * 16 + 4 * i + t) * 8 + (g ^ (2 * t) ^ (2 * (warp & 3)))) * 16);
      cdft16(q, g2, o);
#pragma unroll
      for (int vv = 0; vv < 4; vv++) st_tag(&g_Z2[((8 * (4 * vv + t) + warp) * 128 + c) * 8 + g], o[vv], tag);
    }
    PROF(3);
    {
      const uint4* const zp = &g_Z2[((c * 16 + t) * 8 + warp) * 8 + g];
      if (EARLY_POLL) ld_tag4_issue(q, zp);
      uint4 gb[16], gc[4], tw[4], xr[2][2];
#pragma unroll
      for (int i = 0; i < 16; i++) gb[i] = lds4(TOFF(gb) + i * 512);
      const uint4 ga = lds4(TOFF(ga));
#pragma unroll
      for (int i = 0; i < 4; i++) {
        gc[i] = lds4(sbase + SM_FC + 2048 + i * 512 + lane * 16);
        tw[i] = lds4(TOFF(tw3) + i * 512);
        const int ch = 4 * (g + 8 * (i & 1)) + t;
        xr[i >> 1][i & 1] = lds4(sbase + SM_X + (2 * warp + (i >> 1)) * 1024 + ((ch ^ ((ch >> 2) & 6)) * 16));
      }
      asm volatile("fence.proxy.async.shared::cta;" ::: "memory");
      PROF(4);
      if (!EARLY_POLL) ld_tag4_issue(q, zp);
      ld_tag4_finish(q, zp, tag);
      if (tid == 0) PROFP(31);
      if (lane == 0) { mbar_arrive(BAR(sig, 1)); mbar_arrive_remote(RBAR(sig, 1)); }
      cdft16(q, gc, o);
#pragma unroll
      for (int vv = 0; vv < 4; vv++)
        sts4(sbase + SM_E + (((4 * vv + t) * 8 + warp) * 8 + (g ^ (warp & 6) ^ (2 * t))) * 16, o[vv].x, o[vv].y, o[vv].z, o[vv].w);
      bar_sync(NB_CONS, 256);
      uint32_t hv[2][8];
      const float mk = t == 0 ? 0.f : 1.f;
#pragma unroll
      for (int r = 0; r < 2; r++) {
        const int j = 2 * warp + r;
        uint4 u[2];
#pragma unroll
        for (int h = 0; h < 2; h++) u[h] = lds4(sbase + SM_E + ((j * 8 + 2 * t + h) * 8 + (g ^ (2 * t) ^ (2 * (j & 3)))) * 16);
        float yv[4][4];
#pragma unroll
        for (int i = 0; i < 4; i++) {
          float lo[4] = {0.f, 0.f, 0.f, 0.f}, hi[4] = {0.f, 0.f, 0.f, 0.f};
          mma16816(lo, gb[i * 4].x, gb[i * 4].y, gb[i * 4].z, gb[i * 4].w, u[0].x, u[0].y);
          mma16816(lo, gb[i * 4 + 1].x, gb[i * 4 + 1].y, gb[i * 4 + 1].z, gb[i * 4 + 1].w, u[1].x, u[1].y);
          mma16816(hi, gb[i * 4 + 2].x, gb[i * 4 + 2].y, gb[i * 4 + 2].z, gb[i * 4 + 2].w, u[0].z, u[0].w);
          mma16816(hi, gb[i * 4 + 3].x, gb[i * 4 + 3].y, gb[i * 4 + 3].z, gb[i * 4 + 3].w, u[1].z, u[1].w);
          const float ca = __uint_as_float(tw[i].x), sa = __uint_as_float(tw[i].y), cb = __uint_as_float(tw[i].z), sb = __uint_as_float(tw[i].w);
          const float tr0 = fmaf(hi[0], mk, lo[0]), ti0 = fmaf(hi[2], mk, lo[2]);
          const float tr1 = lo[1] + hi[1], ti1 = lo[3] + hi[3];
          const float vr0 = tr0 * ca - ti0 * sa, vi0 = tr0 * sa + ti0 * ca;
          const float vr1 = tr1 * cb - ti1 * sb, vi1 = tr1 * sb + ti1 * cb;
          const uint32_t b0 = pack2(t == 0 ? hi[0] : vr0, vr1), b1 = pack2(t == 0 ? vr0 : vi0, vi1);
          yv[i][0] = yv[i][1] = yv[i][2] = yv[i][3] = 0.f;
          mma16816(yv[i], ga.x, ga.y, ga.z, ga.w, b0, b1);
        }
#pragma unroll
        for (int h = 0; h < 2; h++) {
          hv[r][4 * h + 0] = hadd2_bf16(xr[r][h].x, pack2(yv[0][2 * h], yv[1][2 * h]));
          hv[r][4 * h + 1] = hadd2_bf16(xr[r][h].y, pack2(yv[2][2 * h], yv[3][2 * h]));
          hv[r][4 * h + 2] = hadd2_bf16(xr[r][h].z, pack2(yv[0][2 * h + 1], yv[1][2 * h + 1]));
          hv[r][4 * h + 3] = hadd2_bf16(xr[r][h].w, pack2(yv[2][2 * h + 1], yv[3][2 * h + 1]));
        }
      }
      float ds[4] = {0.f, 0.f, 0.f, 0.f};
#pragma unroll
      for (int q4 = 0; q4 < 4; q4++) mma16816(ds, hv[0][2 * q4], hv[1][2 * q4], hv[0][2 * q4 + 1], hv[1][2 * q4 + 1], 0x3f803f80u, 0x3f803f80u);
#pragma unroll
      for (int o2 = 4; o2 <= 16; o2 <<= 1) {
        ds[0] += __shfl_xor_sync(0xffffffffu, ds[0], o2);
        ds[2] += __shfl_xor_sync(0xffffffffu, ds[2], o2);
      }
      uint32_t mb[2];
#pragma unroll
      for (int r = 0; r < 2; r++) {
        const int row = 16 * f + 2 * warp + r;
        mb[r] = pack2(ds[2 * r] * (1.f / 512.f), ds[2 * r] * (1.f / 512.f));
#pragma unroll
        for (int i = 0; i < 8; i++) hv[r][i] = hsub2_bf16(hv[r][i], mb[r]);
#pragma unroll
        for (int h = 0; h < 2; h++) {
          const int n1 = g + 8 * h;
          stg4(&g_LN[(rb * 8 + (n1 >> 1)) * 1024 + row * 8 + ((4 * (n1 & 1) + t) ^ (row & 7))],
               make_uint4(hv[r][4 * h], hv[r][4 * h + 1], hv[r][4 * h + 2], hv[r][4 * h + 3]));
        }
      }
      asm volatile("fence.proxy.async.shared::cta;" ::: "memory");
      bar_arrive(NB_LN, 288);
      float sum[2], sq[2], rstd[2];
      row_stats(hv[0], hv[1], lane, sum, sq);
#pragma unroll
      for (int r = 0; r < 2; r++) {
        const float m = sum[r] * (1.f / 512.f);
        rstd[r] = rsqrtf(fmaxf(fmaf(-m, m, sq[r] * (1.f / 512.f)), 0.f) + 1e-5f);
      }
      if (lane == 0)
        st_tag(&g_ST[rb * 64 + 8 * f + warp], make_uint4(mb[0] << 16, __float_as_uint(rstd[0]), mb[1] << 16, __float_as_uint(rstd[1])), tag);
    }
    PROF(5);
    const int wgi = warp >> 2, wq = warp & 3;
    uint4* const pbase = &g_P[rb * 28 * 1024 + (8 * wgi + 2 * wq) * 64 + t * 8 + g];
    const uint32_t a_lo0 = desc_lo(sbase + wgi * 8192, 16);
    const uint32_t ebar = lane == 0 ? BAR(empty1, 0) : RBAR(empty1, 0);
    float r0, r1;
    uint4 px[8], py[6];
    {
      float acc[128];
#pragma unroll
      for (int i = 0; i < 128; i++) acc[i] = 0.f;
      if (wgi == 1) bar_sync(NB_LAG, 256);
      const uint32_t b_lo0 = desc_lo(sbase + 8 * SLOT, 4096);
      uint32_t slot = 0, ph = 0, prev = 0;
#pragma unroll 1
      for (int kb = 0; kb < 8; kb++) {
        mbar_wait(BAR(fullA, kb), 0);
        if (kb == 0) PROF(6);
#pragma unroll
        for (int hh = 0; hh < 2; hh++) {
          mbar_wait(BAR(full1, slot), ph);
          const uint32_t al = a_lo0 + kb * 1024 + hh * 4, bl = b_lo0 + slot * 1024;
          wg_fence();
          wgmma_n256(acc, desc64(al, HI128), desc64(bl, HI128));
          wgmma_n256(acc, desc64(al + 2, HI128), desc64(bl + 128, HI128));
          wg_commit();
          if (hh == (LAG & 1) && kb == (LAG >> 1) && wgi == 0) bar_arrive(NB_LAG, 256);
          wg_wait<1>();
          if ((kb | hh) != 0 && lane < 2) mbar_arrive_remote(ebar + 8 * prev);
          prev = slot;
          if (++slot == 6) { slot = 0; ph ^= 1; }
        }
      }
      mbar_wait(BAR(sbar, 0), 0);
      r0 = __uint_as_float(lds2(sstat + (16 * warp + g) * 8).y);
      r1 = __uint_as_float(lds2(sstat + (16 * warp + g + 8) * 8).y);
      wg_wait<0>();
      if (lane < 2) mbar_arrive_remote(ebar + 8 * prev);
      PROF(7);
      make_p<4>(acc, r0, r1, px);
    }
    PROF(8);
    {
      float acc[96];
#pragma unroll
      for (int i = 0; i < 96; i++) acc[i] = 0.f;
      const uint32_t b_lo0 = desc_lo(sbase + 8 * SLOT, 2048);
      uint4* const pdst = pbase + ((7 * f + 3 * (f & 1)) >> 1) * 1024;
#pragma unroll
      for (int k = 0; k < 16; k++) {
        mbar_wait(BAR(full1, (16 + k) % 6), ((16 + k) / 6) & 1);
        const uint32_t al = a_lo0 + (k >> 1) * 1024 + (k & 1) * 4, bl = b_lo0 + ((16 + k) % 6) * 1024;
        wg_fence();
        wgmma_n192(acc, desc64(al, HI128), desc64(bl, HI64));
        wgmma_n192(acc, desc64(al + 2, HI128), desc64(bl + 64, HI64));
        wg_commit();
        if (k < 4) {
          stg4(pdst + (k >> 1) * 1024 + (k & 1) * 32, px[2 * k]);
          stg4(pdst + (k >> 1) * 1024 + (k & 1) * 32 + 64, px[2 * k + 1]);
        }
        if (k == 3) bar_arrive(NB_PUB, 288);
        wg_wait<1>();
        if (k != 0 && lane < 2) mbar_arrive_remote(ebar + 8 * ((15 + k) % 6));
      }
      wg_wait<0>();
      if (lane < 2) mbar_arrive_remote(ebar + 8 * (31 % 6));
      PROF(9);
      make_p<3>(acc, r0, r1, py);
    }
    PROF(10);
    {
      const int rh = wgi ^ kh ^ 1;
      const int trow = 64 * rh + 16 * wq + g;
      const int G0 = 7 * f + ((f & 1) ? 0 : 4);
      float acc[64];
      {
        const float m0 = wgi ? __uint_as_float(lds2(sstat + 1024 + (16 * wq + g) * 8).x) : 0.f;
        const float m1 = wgi ? __uint_as_float(lds2(sstat + 1024 + (16 * wq + g + 8) * 8).x) : 0.f;
#pragma unroll
        for (int i = 0; i < 64; i++) acc[i] = (i & 2) ? m1 : m0;
      }
#pragma unroll
      for (int k = 0; k < 6; k++) stg4(pbase + ((G0 + (k >> 1)) >> 1) * 1024 + ((G0 + (k >> 1)) & 1) * 32 + (k & 1) * 64, py[k]);
      bar_arrive(NB_PUB, 288);
      if (wgi == 1) bar_sync(NB_LAG2, 256);
      const uint32_t a2_lo0 = desc_lo(sbase + 8 * SLOT + rh * 8192, 128), b2_lo0 = desc_lo(sbase, 8192);
      uint4 hres[2][4];
#pragma unroll
      for (int s = 0; s < 14; s++) {
        const uint32_t al = a2_lo0 + ((s + 2) % 6) * 1024, bl = b2_lo0 + (s & 7) * 1024;
        mbar_wait(BAR(full2, s), 0);
        if (tid == 0) PROFP(16 + s);
        wg_fence();
#pragma unroll
        for (int kk = 0; kk < 4; kk++) wgmma_n128(acc, desc64(al + kk * 16, HI0), desc64(bl + kk * 128, HI128));
        wg_commit();
        if (s == LAG2 && wgi == 0) bar_arrive(NB_LAG2, 256);
        if (s == 8) {
#pragma unroll
          for (int h = 0; h < 2; h++)
#pragma unroll
            for (int q = 0; q < 4; q++)
              hres[h][q] = ldg_cg4(&g_LN[(rb2 * 8 + 2 * nq + (q >> 1)) * 1024 + (trow + 8 * h) * 8 + ((4 * (q & 1) + t) ^ g)]);
        }
        wg_wait<1>();
        if (s > 0 && s <= 8 && lane == 0) {
          mbar_arrive(BAR(empty2, s - 1));
          if (s == 8) mbar_arrive_remote(RBAR(xfree, 0));
        }
      }
      wg_wait<0>();
      PROF(11);
      const uint32_t xbuf = sbase + 6 * SLOT + (tid & 127) * 16;
      if (wgi == 0) {
        uint32_t rbuf;
        mbar_wait(BAR(xfree, 0), 0);
        asm volatile("mapa.shared::cluster.u32 %0, %1, %2;" : "=r"(rbuf) : "r"(xbuf), "r"(kh ^ 1));
#pragma unroll
        for (int i = 0; i < 8; i++)
          asm volatile("st.async.weak.shared::cluster.mbarrier::complete_tx::bytes.v4.b32 [%0], {%1,%2,%3,%4}, [%5];"
                       ::"r"(rbuf + i * 2048), "r"(pack2(acc[8 * i], acc[8 * i + 1])), "r"(pack2(acc[8 * i + 2], acc[8 * i + 3])),
                         "r"(pack2(acc[8 * i + 4], acc[8 * i + 5])), "r"(pack2(acc[8 * i + 6], acc[8 * i + 7])), "r"(RBAR(xbar, 0))
                       : "memory");
      } else {
        mbar_wait_cluster(BAR(xbar, 0), 0);
      }
      uint32_t w[2][16];
#pragma unroll
      for (int i = 0; i < 8; i++) {
        const uint4 pv = lds4(xbuf + i * 2048);
        w[0][2 * i] = pack2(acc[8 * i] + bf_lo(pv.x), acc[8 * i + 1] + bf_hi(pv.x));
        w[1][2 * i] = pack2(acc[8 * i + 2] + bf_lo(pv.y), acc[8 * i + 3] + bf_hi(pv.y));
        w[0][2 * i + 1] = pack2(acc[8 * i + 4] + bf_lo(pv.z), acc[8 * i + 5] + bf_hi(pv.z));
        w[1][2 * i + 1] = pack2(acc[8 * i + 6] + bf_lo(pv.w), acc[8 * i + 7] + bf_hi(pv.w));
      }
      uint4* const o4 = reinterpret_cast<uint4*>(out) + (16 * (c >> 4) + 2 * (4 * rh + wq) + (rb2 & 1) + 128 * g) * 64 + nq * 16 + t;
#pragma unroll
      for (int h = 0; h < 2; h++)
#pragma unroll
        for (int q = 0; q < 4; q++) {
          uint32_t a0 = w[h][4 * q], a1 = w[h][4 * q + 1], a2 = w[h][4 * q + 2], a3 = w[h][4 * q + 3];
          {
            const bool od = t & 1;
            uint32_t s0 = od ? a0 : a1, s1 = od ? a2 : a3;
            s0 = __shfl_xor_sync(0xffffffffu, s0, 1); s1 = __shfl_xor_sync(0xffffffffu, s1, 1);
            if (od) { a0 = s0; a2 = s1; } else { a1 = s0; a3 = s1; }
          }
          {
            const bool up = t & 2;
            uint32_t s0 = up ? a0 : a2, s1 = up ? a1 : a3;
            s0 = __shfl_xor_sync(0xffffffffu, s0, 2); s1 = __shfl_xor_sync(0xffffffffu, s1, 2);
            if (up) { a0 = s0; a1 = s1; } else { a2 = s0; a3 = s1; }
          }
          if (wgi == 1)
            o4[h * 1024 * 64 + 4 * q] =
                make_uint4(hadd2_bf16(hres[h][q].x, a0), hadd2_bf16(hres[h][q].y, a1), hadd2_bf16(hres[h][q].z, a2), hadd2_bf16(hres[h][q].w, a3));
        }
      PROF(12);
      PROFG(15);
    }
  }
#undef BAR
#undef TOFF
#undef RBAR
}

typedef CUresult (*EncodeFn)(CUtensorMap*, CUtensorMapDataType, cuuint32_t, void*, const cuuint64_t*, const cuuint64_t*,
                             const cuuint32_t*, const cuuint32_t*, CUtensorMapInterleave, CUtensorMapSwizzle,
                             CUtensorMapL2promotion, CUtensorMapFloatOOBfill);

}

extern "C" void kernel_launch(void* const* d_in, const int* in_sizes, int n_in, void* d_out, int out_size) {
  (void)in_sizes; (void)n_in; (void)out_size;
  static EncodeFn encode = nullptr;
  if (!encode) {
    void* fn = nullptr;
    cudaDriverEntryPointQueryResult qr;
    cudaGetDriverEntryPoint("cuTensorMapEncodeTiled", &fn, cudaEnableDefault, &qr);
    encode = (EncodeFn)fn;
    cudaFuncSetAttribute(fused_kernel, cudaFuncAttributeMaxDynamicSharedMemorySize, SMEM_BYTES);
  }
  CUtensorMap tmGX, tmUX, tmGY, tmUY, tmD, tmWR, tmWI;
  const cuuint32_t es[5] = {1, 1, 1, 1, 1};
  auto enc = [&](CUtensorMap* m, void* p, int rank, const cuuint64_t* gd, const cuuint64_t* gs, const cuuint32_t* bd,
                 CUtensorMapSwizzle sw, CUtensorMapL2promotion pr) {
    encode(m, CU_TENSOR_MAP_DATA_TYPE_BFLOAT16, rank, p, gd, gs, bd, es, CU_TENSOR_MAP_INTERLEAVE_NONE, sw, pr,
           CU_TENSOR_MAP_FLOAT_OOB_FILL_NONE);
  };
  {
    const cuuint64_t gd[3] = {64, 512, 28}, gs[2] = {3584, 128};
    const cuuint32_t bd[3] = {64, 32, 2};
    enc(&tmGX, d_in[4], 3, gd, gs, bd, CU_TENSOR_MAP_SWIZZLE_128B, CU_TENSOR_MAP_L2_PROMOTION_L2_256B);
    enc(&tmUX, d_in[5], 3, gd, gs, bd, CU_TENSOR_MAP_SWIZZLE_128B, CU_TENSOR_MAP_L2_PROMOTION_L2_256B);
  }
  {
    const cuuint64_t gd[3] = {32, 512, 56}, gs[2] = {3584, 64};
    const cuuint32_t bd[3] = {32, 32, 3};
    enc(&tmGY, d_in[4], 3, gd, gs, bd, CU_TENSOR_MAP_SWIZZLE_64B, CU_TENSOR_MAP_L2_PROMOTION_L2_128B);
    enc(&tmUY, d_in[5], 3, gd, gs, bd, CU_TENSOR_MAP_SWIZZLE_64B, CU_TENSOR_MAP_L2_PROMOTION_L2_128B);
  }
  {
    const cuuint64_t gd[5] = {512, 2, 4, 4, 56}, gs[4] = {1024, 8192, 2048, 32768};
    const cuuint32_t bd[5] = {64, 2, 4, 4, 2};
    enc(&tmD, d_in[6], 5, gd, gs, bd, CU_TENSOR_MAP_SWIZZLE_128B, CU_TENSOR_MAP_L2_PROMOTION_L2_256B);
  }
  {
    const cuuint64_t gd[3] = {4112, 8, 16}, gs[2] = {16 * 8224, 8224};
    const cuuint32_t bd[3] = {40, 8, 16};
    enc(&tmWR, d_in[1], 3, gd, gs, bd, CU_TENSOR_MAP_SWIZZLE_NONE, CU_TENSOR_MAP_L2_PROMOTION_NONE);
    enc(&tmWI, d_in[2], 3, gd, gs, bd, CU_TENSOR_MAP_SWIZZLE_NONE, CU_TENSOR_MAP_L2_PROMOTION_NONE);
  }
  fused_kernel<<<NCTA, NTHREADS, SMEM_BYTES>>>(tmGX, tmUX, tmGY, tmUY, tmD, tmWR, tmWI, (const __nv_bfloat16*)d_in[0],
                                               (const char*)d_in[4], (const char*)d_in[5], (const char*)d_in[6],
                                               (__nv_bfloat16*)d_out);
}
```

```cpp
#include <cuda_runtime.h>
#include <cuda_bf16.h>
#include <cuda.h>
#include <stdint.h>

namespace {

constexpr int NCTA = 128;
constexpr int NTHREADS = 384;
constexpr int SLOT = 16384;
constexpr int SMEM_BYTES = 14 * SLOT + 2048 + 1024;
constexpr int SPIN_LIMIT = 1 << 22;

__device__ uint4 g_Z1[128 * 1024];
__device__ uint4 g_Z2[128 * 1024];
__device__ uint4 g_LN[16 * 8 * 1024];
__device__ uint4 g_ST[1024];
__device__ uint4 g_P[16 * 28 * 1024];
__device__ unsigned g_cnt[64 * 32];
#define PROF(i)
#define PROFP(i)
#define PROFG(i)

constexpr double ccos(int i, int n) {
  i &= n - 1;
  if (i > n / 2) i = n - i;
  if (4 * i == n) return 0.0;
  const bool neg = 4 * i > n;
  if (neg) i = n / 2 - i;
  const double a = 6.283185307179586476925 * i / n, a2 = a * a;
  double term = 1.0, sum = 1.0;
  for (int k = 1; k < 14; k++) { term *= -a2 / ((2 * k - 1) * (2 * k)); sum += term; }
  return neg ? -sum : sum;
}
constexpr double csin(int i, int n) { return ccos(i - n / 4, n); }
constexpr unsigned fbits(double v, int mant) {
  if (v == 0.0) return 0;
  const unsigned sg = v < 0 ? 1u : 0u;
  if (v < 0) v = -v;
  int e = 127;
  while (v < 1.0) { v *= 2.0; e--; }
  const unsigned m = (unsigned)((v - 1.0) * (double)(1u << mant) + 0.5);
  return (sg << (8 + mant)) + ((unsigned)e << mant) + m;
}
constexpr unsigned pkb(double lo, double hi) { return fbits(lo, 7) | (fbits(hi, 7) << 16); }
constexpr double fa_elem(int kp, int n1) {
  return kp <= 8 ? ccos(kp * n1, 16) : -csin((kp - 8) * n1, 16);
}
constexpr unsigned cfrag_c(int idx, int n, int ri) {
  return ri ? pkb(-csin(idx, n), ccos(idx, n)) : pkb(ccos(idx, n), csin(idx, n));
}
struct Tables {
  unsigned fb[16][32][4];
  unsigned tw1[8][32][4];
  unsigned fa[32][4];
  unsigned f2[8][4][32][4];
  unsigned g2[8][4][32][4];
  unsigned gb[16][32][4];
  unsigned tw3[4][32][4];
  unsigned ga[32][4];
  unsigned f8[32][4], g8[32][4];
};
constexpr int T1_BYTES = 12800, T2_BYTES = 44544;
static_assert(sizeof(Tables) == T1_BYTES + T2_BYTES, "table size");
constexpr Tables make_tables() {
  Tables T = {};
  for (int l = 0; l < 32; l++) {
    const int g = l >> 2, t = l & 3;
    for (int i = 0; i < 4; i++)
      for (int u = 0; u < 8; u++) {
        const int ri = g & 1, m = 2 * (g >> 1) + ((u & 3) >> 1);
        const double sg = u >= 4 ? -1.0 : 1.0;
        const int k2 = u >= 4 ? 31 - 2 * m - (u & 1) : 2 * m + (u & 1);
        const int pa = (8 * t + i) * k2, pb = (8 * t + 4 + i) * k2;
        T.fb[i * 4 + (u >> 1)][l][(u & 1) * 2 + 0] = ri == 0 ? pkb(ccos(pa, 32), ccos(pb, 32)) : pkb(-sg * csin(pa, 32), -sg * csin(pb, 32));
        T.fb[i * 4 + (u >> 1)][l][(u & 1) * 2 + 1] = ri == 0 ? pkb(csin(pa, 32), csin(pb, 32)) : pkb(sg * ccos(pa, 32), sg * ccos(pb, 32));
      }
    for (int i = 0; i < 4; i++)
      for (int ks = 0; ks < 4; ks++) {
        const int n2 = 4 * g + i, m = 2 * t + (ks & 1);
        const double sg = ks >= 2 ? -1.0 : 1.0;
        const int pa = n2 * (ks >= 2 ? 31 - 2 * m : 2 * m), pb = n2 * (ks >= 2 ? 30 - 2 * m : 2 * m + 1);
        T.gb[i * 4 + ks][l][0] = pkb(ccos(pa, 32), -sg * csin(pa, 32));
        T.gb[i * 4 + ks][l][1] = pkb(csin(pa, 32), sg * ccos(pa, 32));
        T.gb[i * 4 + ks][l][2] = pkb(ccos(pb, 32), -sg * csin(pb, 32));
        T.gb[i * 4 + ks][l][3] = pkb(csin(pb, 32), sg * ccos(pb, 32));
      }
    for (int i = 0; i < 4; i++) {
      for (int e = 0; e < 2; e++) {
        const int p = (8 * t + 4 * e + i) * (g == 0 ? 8 : g);
        T.tw1[2 * i + e][l][0] = fbits(g == 0 ? 0.0 : ccos(p, 512), 23);
        T.tw1[2 * i + e][l][1] = fbits(g == 0 ? ccos(p, 512) : csin(p, 512), 23);
        T.tw1[2 * i + e][l][2] = fbits(g == 0 ? 0.0 : -csin(p, 512), 23);
        T.tw1[2 * i + e][l][3] = fbits(g == 0 ? -csin(p, 512) : ccos(p, 512), 23);
      }
      const int ka = t == 0 ? 8 : 2 * t, kb = 2 * t + 1;
      T.tw3[i][l][0] = fbits(ccos((4 * g + i) * ka, 512), 23);
      T.tw3[i][l][1] = fbits(csin((4 * g + i) * ka, 512), 23);
      T.tw3[i][l][2] = fbits(ccos((4 * g + i) * kb, 512), 23);
      T.tw3[i][l][3] = fbits(csin((4 * g + i) * kb, 512), 23);
      const int p8 = (t + 4 * (i & 1)) * (4 * (i >> 1) + (g >> 1));
      T.f8[l][i] = cfrag_c(p8, 8, g & 1);
      T.g8[l][i] = cfrag_c(-p8, 8, g & 1);
    }
    for (int w = 0; w < 8; w++)
      for (int i = 0; i < 16; i++) {
        const int kidx = t + 4 * (i & 1) + 8 * (i >> 3), nidx = 4 * ((i >> 1) & 3) + (g >> 1);
        T.f2[w][i >> 2][l][i & 3] = cfrag_c((8 * kidx + w) * nidx, 128, g & 1);
        T.g2[w][i >> 2][l][i & 3] = cfrag_c(-(8 * nidx + w) * kidx, 128, g & 1);
      }
    T.fa[l][0] = pkb(fa_elem(g, 2 * t), fa_elem(g, 2 * t + 1));
    T.fa[l][1] = pkb(fa_elem(g + 8, 2 * t), fa_elem(g + 8, 2 * t + 1));
    T.fa[l][2] = pkb(fa_elem(g, 2 * t + 8), fa_elem(g, 2 * t + 9));
    T.fa[l][3] = pkb(fa_elem(g + 8, 2 * t + 8), fa_elem(g + 8, 2 * t + 9));
    T.ga[l][0] = pkb(fa_elem(2 * t, g), fa_elem(2 * t + 1, g));
    T.ga[l][1] = pkb(fa_elem(2 * t, g + 8), fa_elem(2 * t + 1, g + 8));
    T.ga[l][2] = pkb(fa_elem(2 * t + 8, g), fa_elem(2 * t + 9, g));
    T.ga[l][3] = pkb(fa_elem(2 * t + 8, g + 8), fa_elem(2 * t + 9, g + 8));
  }
  return T;
}
__device__ const __align__(128) Tables g_tab = make_tables();

__device__ __forceinline__ uint32_t s2u(const void* p) { return (uint32_t)__cvta_generic_to_shared(p); }
__device__ __forceinline__ void mbar_init(uint32_t b, int c) { asm volatile("mbarrier.init.shared::cta.b64 [%0], %1;" ::"r"(b), "r"(c)); }
__device__ __forceinline__ void mbar_expect(uint32_t b, int bytes) {
  asm volatile("mbarrier.arrive.expect_tx.shared::cta.b64 _, [%0], %1;" ::"r"(b), "r"(bytes) : "memory");
}
__device__ __forceinline__ void mbar_arrive(uint32_t b) { asm volatile("mbarrier.arrive.shared::cta.b64 _, [%0];" ::"r"(b) : "memory"); }
__device__ __forceinline__ uint32_t mbar_try(uint32_t b, uint32_t parity) {
  uint32_t ok;
  asm volatile("{.reg .pred p; mbarrier.try_wait.parity.shared::cta.b64 p, [%1], %2; selp.u32 %0,1,0,p;}"
               : "=r"(ok) : "r"(b), "r"(parity) : "memory");
  return ok;
}
__device__ __forceinline__ void mbar_wait(uint32_t b, uint32_t parity) {
  int it = 0;
  while (!mbar_try(b, parity))
    if (++it > SPIN_LIMIT) __trap();
}
__device__ __forceinline__ void mbar_wait_cluster(uint32_t b, int parity) {
  uint32_t ok;
  int it = 0;
  do {
    asm volatile("{.reg .pred p; mbarrier.try_wait.parity.acquire.cluster.shared::cta.b64 p, [%1], %2; selp.u32 %0,1,0,p;}"
                 : "=r"(ok) : "r"(b), "r"(parity) : "memory");
    if (++it > SPIN_LIMIT) __trap();
  } while (!ok);
}
__device__ __forceinline__ void bar_sync(int id, int n) { asm volatile("bar.sync %0, %1;" ::"r"(id), "r"(n) : "memory"); }
__device__ __forceinline__ void bar_arrive(int id, int n) { asm volatile("bar.arrive %0, %1;" ::"r"(id), "r"(n) : "memory"); }
__device__ __forceinline__ void red_release(unsigned* p) { asm volatile("red.release.gpu.global.add.u32 [%0], 1;" ::"l"(p) : "memory"); }
__device__ __forceinline__ unsigned ld_acquire(const unsigned* p) {
  unsigned v;
  asm volatile("ld.acquire.gpu.global.u32 %0, [%1];" : "=r"(v) : "l"(p) : "memory");
  return v;
}
__device__ __forceinline__ unsigned ld_relaxed(const unsigned* p) {
  unsigned v;
  asm volatile("ld.relaxed.gpu.global.u32 %0, [%1];" : "=r"(v) : "l"(p) : "memory");
  return v;
}
__device__ __forceinline__ void wait_counter(const unsigned* p, unsigned target) {
  int it = 0;
  while ((int)(ld_acquire(p) - target) < 0)
    if (++it > SPIN_LIMIT) __trap();
}
__device__ __forceinline__ uint4 ldg_cg4(const uint4* p) {
  uint4 v;
  asm volatile("ld.global.cg.v4.u32 {%0,%1,%2,%3}, [%4];" : "=r"(v.x), "=r"(v.y), "=r"(v.z), "=r"(v.w) : "l"(p) : "memory");
  return v;
}
__device__ __forceinline__ void sts4(uint32_t a, uint32_t x, uint32_t y, uint32_t z, uint32_t w) {
  asm volatile("st.shared.v4.u32 [%0], {%1,%2,%3,%4};" ::"r"(a), "r"(x), "r"(y), "r"(z), "r"(w) : "memory");
}
__device__ __forceinline__ uint4 lds4(uint32_t a) {
  uint4 v;
  asm volatile("ld.shared.v4.u32 {%0,%1,%2,%3}, [%4];" : "=r"(v.x), "=r"(v.y), "=r"(v.z), "=r"(v.w) : "r"(a) : "memory");
  return v;
}
__device__ __forceinline__ uint32_t pack2(float lo, float hi) {
  uint32_t r;
  asm("cvt.rn.bf16x2.f32 %0, %1, %2;" : "=r"(r) : "f"(hi), "f"(lo));
  return r;
}
__device__ __forceinline__ float bf_lo(uint32_t v) { return __uint_as_float(v << 16); }
__device__ __forceinline__ float bf_hi(uint32_t v) { return __uint_as_float(v & 0xffff0000u); }
__device__ __forceinline__ uint32_t hadd2_bf16(uint32_t a, uint32_t b) {
  uint32_t r;
  asm("add.rn.bf16x2 %0, %1, %2;" : "=r"(r) : "r"(a), "r"(b));
  return r;
}
__device__ __forceinline__ void mma16816(float (&d)[4], uint32_t a0, uint32_t a1, uint32_t a2, uint32_t a3, uint32_t b0, uint32_t b1) {
  asm("mma.sync.aligned.m16n8k16.row.col.f32.bf16.bf16.f32 {%0,%1,%2,%3}, {%4,%5,%6,%7}, {%8,%9}, {%0,%1,%2,%3};"
      : "+f"(d[0]), "+f"(d[1]), "+f"(d[2]), "+f"(d[3])
      : "r"(a0), "r"(a1), "r"(a2), "r"(a3), "r"(b0), "r"(b1));
}
template <int N>
__device__ __forceinline__ void cs_frac(int idx, float& c, float& s) {
  int i = ((idx + N / 2) & (N - 1)) - N / 2;
  float a = (float)i * (6.283185307179586f / N);
  c = __cosf(a);
  s = __sinf(a);
}
template <int N>
__device__ __forceinline__ uint32_t cfrag(int idx, int ri) {
  float c, s;
  cs_frac<N>(idx, c, s);
  return ri ? pack2(-s, c) : pack2(c, s);
}
__device__ __forceinline__ uint32_t word(const uint4& v, int e) { return e == 0 ? v.x : e == 1 ? v.y : e == 2 ? v.z : v.w; }
__device__ __forceinline__ void cdft16(const uint4 (&q)[4], const uint4 (&F)[4], uint4 (&o)[4]) {
  float acc[2][4][4];
#pragma unroll
  for (int p = 0; p < 2; p++)
#pragma unroll
    for (int v = 0; v < 4; v++) {
      acc[p][v][0] = acc[p][v][1] = acc[p][v][2] = acc[p][v][3] = 0.f;
#pragma unroll
      for (int ks = 0; ks < 2; ks++)
        mma16816(acc[p][v], word(q[2 * ks], 2 * p), word(q[2 * ks], 2 * p + 1), word(q[2 * ks + 1], 2 * p),
                 word(q[2 * ks + 1], 2 * p + 1), word(F[ks * 2 + (v >> 1)], (v & 1) * 2), word(F[ks * 2 + (v >> 1)], (v & 1) * 2 + 1));
    }
#pragma unroll
  for (int v = 0; v < 4; v++)
    o[v] = make_uint4(pack2(acc[0][v][0], acc[0][v][1]), pack2(acc[0][v][2], acc[0][v][3]),
                      pack2(acc[1][v][0], acc[1][v][1]), pack2(acc[1][v][2], acc[1][v][3]));
}
__device__ __forceinline__ void st_tag(uint4* p, const uint4& v, uint32_t tag) {
  asm volatile("{.reg .b128 r; .reg .b64 a, b; mov.b64 a, {%1,%2}; mov.b64 b, {%3,%4}; mov.b128 r, {a,b}; st.relaxed.gpu.global.b128 [%0], r;}"
               ::"l"(p), "r"((v.x & ~1u) | tag), "r"(v.y), "r"(v.z), "r"(v.w) : "memory");
}
__device__ __forceinline__ uint4 ld_b128(const uint4* p) {
  uint4 v;
  asm volatile("{.reg .b128 r; .reg .b64 a, b; ld.relaxed.gpu.global.b128 r, [%4]; mov.b128 {a,b}, r; mov.b64 {%0,%1}, a; mov.b64 {%2,%3}, b;}"
               : "=r"(v.x), "=r"(v.y), "=r"(v.z), "=r"(v.w) : "l"(p) : "memory");
  return v;
}
template <int STRIDE>
__device__ __forceinline__ void ld_tag4_issue(uint4 (&q)[4], const uint4* p) {
#pragma unroll
  for (int i = 0; i < 4; i++) q[i] = ld_b128(p + i * STRIDE);
}
template <int STRIDE>
__device__ __forceinline__ void ld_tag4_finish(uint4 (&q)[4], const uint4* p, uint32_t tag) {
  int it = 0;
  while (__any_sync(0xffffffffu, ((q[0].x ^ tag) | (q[1].x ^ tag) | (q[2].x ^ tag) | (q[3].x ^ tag)) & 1u)) {
    ld_tag4_issue<STRIDE>(q, p);
    if (++it > SPIN_LIMIT) __trap();
  }
#pragma unroll
  for (int i = 0; i < 4; i++) q[i].x &= ~1u;
}
__device__ __forceinline__ void row_stats(const uint32_t (&a)[8], const uint32_t (&b)[8], int lane, float (&sum)[2], float (&sq)[2]) {
  float da[4] = {0.f, 0.f, 0.f, 0.f}, db[4] = {0.f, 0.f, 0.f, 0.f}, ds[4] = {0.f, 0.f, 0.f, 0.f};
#pragma unroll
  for (int q = 0; q < 4; q++) {
    mma16816(ds, a[2 * q], b[2 * q], a[2 * q + 1], b[2 * q + 1], 0x3f803f80u, 0x3f803f80u);
    mma16816(da, a[2 * q], b[2 * q], a[2 * q + 1], b[2 * q + 1], a[2 * q], a[2 * q + 1]);
    mma16816(db, a[2 * q], b[2 * q], a[2 * q + 1], b[2 * q + 1], b[2 * q], b[2 * q + 1]);
  }
  const int src = (lane & 28) | (lane >> 3);
  const float qa = __shfl_sync(0xffffffffu, (lane & 4) ? da[1] : da[0], src);
  const float qb = __shfl_sync(0xffffffffu, (lane & 4) ? db[3] : db[2], src);
  float v = (lane & 2) ? ((lane & 1) ? ds[2] : ds[0]) : ((lane & 1) ? qb : qa);
  v += __shfl_xor_sync(0xffffffffu, v, 4);
  v += __shfl_xor_sync(0xffffffffu, v, 8);
  v += __shfl_xor_sync(0xffffffffu, v, 16);
  sq[0] = __shfl_sync(0xffffffffu, v, 0);
  sq[1] = __shfl_sync(0xffffffffu, v, 1);
  sum[0] = __shfl_sync(0xffffffffu, v, 2);
  sum[1] = __shfl_sync(0xffffffffu, v, 3);
}
__device__ __forceinline__ uint64_t desc64(uint32_t lo, uint32_t hi) {
  uint64_t d;
  asm("mov.b64 %0, {%1, %2};" : "=l"(d) : "r"(lo), "r"(hi));
  return d;
}
constexpr uint32_t desc_hi(uint32_t sbo, uint32_t swz) { return (sbo >> 4) | (swz << 30); }
__device__ __forceinline__ uint32_t desc_lo(uint32_t addr, uint32_t lbo) { return ((addr & 0x3FFFF) >> 4) | ((lbo >> 4) << 16); }
__device__ __forceinline__ void cp_async16(uint32_t dst, const void* src) {
  asm volatile("cp.async.cg.shared.global [%0], [%1], 16;" ::"r"(dst), "l"(src) : "memory");
}
__device__ __forceinline__ uint2 lds2(uint32_t a) {
  uint2 v;
  asm volatile("ld.shared.v2.u32 {%0,%1}, [%2];" : "=r"(v.x), "=r"(v.y) : "r"(a) : "memory");
  return v;
}
__device__ __forceinline__ uint32_t lds_u16(uint32_t a) {
  uint16_t v;
  asm volatile("ld.shared.u16 %0, [%1];" : "=h"(v) : "r"(a) : "memory");
  return v;
}
__device__ __forceinline__ void wg_fence() { asm volatile("wgmma.fence.sync.aligned;" ::: "memory"); }
__device__ __forceinline__ void wg_commit() { asm volatile("wgmma.commit_group.sync.aligned;" ::: "memory"); }
template <int N>
__device__ __forceinline__ void wg_wait() { asm volatile("wgmma.wait_group.sync.aligned %0;" ::"n"(N) : "memory"); }
__device__ __forceinline__ void bulk_load(uint32_t dst, const void* src, int bytes, uint32_t bar) {
  asm volatile("cp.async.bulk.shared::cluster.global.mbarrier::complete_tx::bytes [%0], [%1], %2, [%3];"
               ::"r"(dst), "l"(src), "r"(bytes), "r"(bar) : "memory");
}
__device__ __forceinline__ void tma3(uint32_t dst, const CUtensorMap* tm, uint32_t bar, int c0, int c1, int c2) {
  asm volatile("cp.async.bulk.tensor.3d.shared::cluster.global.mbarrier::complete_tx::bytes [%0], [%1, {%3,%4,%5}], [%2];"
               ::"r"(dst), "l"(tm), "r"(bar), "r"(c0), "r"(c1), "r"(c2) : "memory");
}
__device__ __forceinline__ void tma3_mc(uint32_t dst, const CUtensorMap* tm, uint32_t bar, int c1, int c2) {
  asm volatile("cp.async.bulk.tensor.3d.shared::cluster.global.mbarrier::complete_tx::bytes.multicast::cluster [%0], [%1, {%3,%4,%5}], [%2], %6;"
               ::"r"(dst), "l"(tm), "r"(bar), "r"(0), "r"(c1), "r"(c2), "h"((uint16_t)3) : "memory");
}
__device__ __forceinline__ void mbar_arrive_remote(uint32_t rb) {
  asm volatile("mbarrier.arrive.shared::cluster.b64 _, [%0];" ::"r"(rb) : "memory");
}
__device__ __forceinline__ uint4 ldg_ca4(const void* p) {
  uint4 v;
  asm volatile("ld.global.ca.v4.u32 {%0,%1,%2,%3}, [%4];" : "=r"(v.x), "=r"(v.y), "=r"(v.z), "=r"(v.w) : "l"(p) : "memory");
  return v;
}
__device__ __forceinline__ uint32_t clock32() {
  uint32_t v;
  asm volatile("mov.u32 %0, %%clock;" : "=r"(v) :: "memory");
  return v;
}
__device__ __forceinline__ float swiglu(float g, float u, float r) {
  float hg = (0.5f * r) * g, th;
  asm("tanh.approx.f32 %0, %1;" : "=f"(th) : "f"(hg));
  return fmaf(hg, th, hg) * (r * u);
}
__device__ __forceinline__ uint32_t hsub2_bf16(uint32_t a, uint32_t b) {
  uint32_t r;
  asm("sub.rn.bf16x2 %0, %1, %2;" : "=r"(r) : "r"(a), "r"(b));
  return r;
}
__device__ __forceinline__ void l2_prefetch(const void* p, int bytes) {
  asm volatile("cp.async.bulk.prefetch.L2.global [%0], %1;" ::"l"(p), "r"(bytes) : "memory");
}

__device__ __forceinline__ void wgmma_n256(float (&d)[128], uint64_t da, uint64_t db) {
  asm volatile("wgmma.mma_async.sync.aligned.m64n256k16.f32.bf16.bf16 {"
      "%0,%1,%2,%3,%4,%5,%6,%7,%8,%9,%10,%11,%12,%13,%14,%15,"
      "%16,%17,%18,%19,%20,%21,%22,%23,%24,%25,%26,%27,%28,%29,%30,%31,"
      "%32,%33,%34,%35,%36,%37,%38,%39,%40,%41,%42,%43,%44,%45,%46,%47,"
      "%48,%49,%50,%51,%52,%53,%54,%55,%56,%57,%58,%59,%60,%61,%62,%63,"
      "%64,%65,%66,%67,%68,%69,%70,%71,%72,%73,%74,%75,%76,%77,%78,%79,"
      "%80,%81,%82,%83,%84,%85,%86,%87,%88,%89,%90,%91,%92,%93,%94,%95,"
      "%96,%97,%98,%99,%100,%101,%102,%103,%104,%105,%106,%107,%108,%109,%110,%111,"
      "%112,%113,%114,%115,%116,%117,%118,%119,%120,%121,%122,%123,%124,%125,%126,%127"
      "}, %128, %129, 1, 1, 1, 0, 1;\n"
      : "+f"(d[0]),"+f"(d[1]),"+f"(d[2]),"+f"(d[3]),"+f"(d[4]),"+f"(d[5]),"+f"(d[6]),"+f"(d[7]),
        "+f"(d[8]),"+f"(d[9]),"+f"(d[10]),"+f"(d[11]),"+f"(d[12]),"+f"(d[13]),"+f"(d[14]),"+f"(d[15]),
        "+f"(d[16]),"+f"(d[17]),"+f"(d[18]),"+f"(d[19]),"+f"(d[20]),"+f"(d[21]),"+f"(d[22]),"+f"(d[23]),
        "+f"(d[24]),"+f"(d[25]),"+f"(d[26]),"+f"(d[27]),"+f"(d[28]),"+f"(d[29]),"+f"(d[30]),"+f"(d[31]),
        "+f"(d[32]),"+f"(d[33]),"+f"(d[34]),"+f"(d[35]),"+f"(d[36]),"+f"(d[37]),"+f"(d[38]),"+f"(d[39]),
        "+f"(d[40]),"+f"(d[41]),"+f"(d[42]),"+f"(d[43]),"+f"(d[44]),"+f"(d[45]),"+f"(d[46]),"+f"(d[47]),
        "+f"(d[48]),"+f"(d[49]),"+f"(d[50]),"+f"(d[51]),"+f"(d[52]),"+f"(d[53]),"+f"(d[54]),"+f"(d[55]),
        "+f"(d[56]),"+f"(d[57]),"+f"(d[58]),"+f"(d[59]),"+f"(d[60]),"+f"(d[61]),"+f"(d[62]),"+f"(d[63]),
        "+f"(d[64]),"+f"(d[65]),"+f"(d[66]),"+f"(d[67]),"+f"(d[68]),"+f"(d[69]),"+f"(d[70]),"+f"(d[71]),
        "+f"(d[72]),"+f"(d[73]),"+f"(d[74]),"+f"(d[75]),"+f"(d[76]),"+f"(d[77]),"+f"(d[78]),"+f"(d[79]),
        "+f"(d[80]),"+f"(d[81]),"+f"(d[82]),"+f"(d[83]),"+f"(d[84]),"+f"(d[85]),"+f"(d[86]),"+f"(d[87]),
        "+f"(d[88]),"+f"(d[89]),"+f"(d[90]),"+f"(d[91]),"+f"(d[92]),"+f"(d[93]),"+f"(d[94]),"+f"(d[95]),
        "+f"(d[96]),"+f"(d[97]),"+f"(d[98]),"+f"(d[99]),"+f"(d[100]),"+f"(d[101]),"+f"(d[102]),"+f"(d[103]),
        "+f"(d[104]),"+f"(d[105]),"+f"(d[106]),"+f"(d[107]),"+f"(d[108]),"+f"(d[109]),"+f"(d[110]),"+f"(d[111]),
        "+f"(d[112]),"+f"(d[113]),"+f"(d[114]),"+f"(d[115]),"+f"(d[116]),"+f"(d[117]),"+f"(d[118]),"+f"(d[119]),
        "+f"(d[120]),"+f"(d[121]),"+f"(d[122]),"+f"(d[123]),"+f"(d[124]),"+f"(d[125]),"+f"(d[126]),"+f"(d[127])
      : "l"(da), "l"(db));
}
__device__ __forceinline__ void wgmma_n192(float (&d)[96], uint64_t da, uint64_t db) {
  asm volatile("wgmma.mma_async.sync.aligned.m64n192k16.f32.bf16.bf16 {"
      "%0,%1,%2,%3,%4,%5,%6,%7,%8,%9,%10,%11,%12,%13,%14,%15,"
      "%16,%17,%18,%19,%20,%21,%22,%23,%24,%25,%26,%27,%28,%29,%30,%31,"
      "%32,%33,%34,%35,%36,%37,%38,%39,%40,%41,%42,%43,%44,%45,%46,%47,"
      "%48,%49,%50,%51,%52,%53,%54,%55,%56,%57,%58,%59,%60,%61,%62,%63,"
      "%64,%65,%66,%67,%68,%69,%70,%71,%72,%73,%74,%75,%76,%77,%78,%79,"
      "%80,%81,%82,%83,%84,%85,%86,%87,%88,%89,%90,%91,%92,%93,%94,%95"
      "}, %96, %97, 1, 1, 1, 0, 1;\n"
      : "+f"(d[0]),"+f"(d[1]),"+f"(d[2]),"+f"(d[3]),"+f"(d[4]),"+f"(d[5]),"+f"(d[6]),"+f"(d[7]),
        "+f"(d[8]),"+f"(d[9]),"+f"(d[10]),"+f"(d[11]),"+f"(d[12]),"+f"(d[13]),"+f"(d[14]),"+f"(d[15]),
        "+f"(d[16]),"+f"(d[17]),"+f"(d[18]),"+f"(d[19]),"+f"(d[20]),"+f"(d[21]),"+f"(d[22]),"+f"(d[23]),
        "+f"(d[24]),"+f"(d[25]),"+f"(d[26]),"+f"(d[27]),"+f"(d[28]),"+f"(d[29]),"+f"(d[30]),"+f"(d[31]),
        "+f"(d[32]),"+f"(d[33]),"+f"(d[34]),"+f"(d[35]),"+f"(d[36]),"+f"(d[37]),"+f"(d[38]),"+f"(d[39]),
        "+f"(d[40]),"+f"(d[41]),"+f"(d[42]),"+f"(d[43]),"+f"(d[44]),"+f"(d[45]),"+f"(d[46]),"+f"(d[47]),
        "+f"(d[48]),"+f"(d[49]),"+f"(d[50]),"+f"(d[51]),"+f"(d[52]),"+f"(d[53]),"+f"(d[54]),"+f"(d[55]),
        "+f"(d[56]),"+f"(d[57]),"+f"(d[58]),"+f"(d[59]),"+f"(d[60]),"+f"(d[61]),"+f"(d[62]),"+f"(d[63]),
        "+f"(d[64]),"+f"(d[65]),"+f"(d[66]),"+f"(d[67]),"+f"(d[68]),"+f"(d[69]),"+f"(d[70]),"+f"(d[71]),
        "+f"(d[72]),"+f"(d[73]),"+f"(d[74]),"+f"(d[75]),"+f"(d[76]),"+f"(d[77]),"+f"(d[78]),"+f"(d[79]),
        "+f"(d[80]),"+f"(d[81]),"+f"(d[82]),"+f"(d[83]),"+f"(d[84]),"+f"(d[85]),"+f"(d[86]),"+f"(d[87]),
        "+f"(d[88]),"+f"(d[89]),"+f"(d[90]),"+f"(d[91]),"+f"(d[92]),"+f"(d[93]),"+f"(d[94]),"+f"(d[95])
      : "l"(da), "l"(db));
}
__device__ __forceinline__ void wgmma_rs_n128(float (&d)[64], uint32_t a0, uint32_t a1, uint32_t a2, uint32_t a3, uint64_t db) {
  asm volatile("wgmma.mma_async.sync.aligned.m64n128k16.f32.bf16.bf16 {"
      "%0,%1,%2,%3,%4,%5,%6,%7,%8,%9,%10,%11,%12,%13,%14,%15,"
      "%16,%17,%18,%19,%20,%21,%22,%23,%24,%25,%26,%27,%28,%29,%30,%31,"
      "%32,%33,%34,%35,%36,%37,%38,%39,%40,%41,%42,%43,%44,%45,%46,%47,"
      "%48,%49,%50,%51,%52,%53,%54,%55,%56,%57,%58,%59,%60,%61,%62,%63"
      "}, {%64,%65,%66,%67}, %68, 1, 1, 1, 1;\n"
      : "+f"(d[0]),"+f"(d[1]),"+f"(d[2]),"+f"(d[3]),"+f"(d[4]),"+f"(d[5]),"+f"(d[6]),"+f"(d[7]),
        "+f"(d[8]),"+f"(d[9]),"+f"(d[10]),"+f"(d[11]),"+f"(d[12]),"+f"(d[13]),"+f"(d[14]),"+f"(d[15]),
        "+f"(d[16]),"+f"(d[17]),"+f"(d[18]),"+f"(d[19]),"+f"(d[20]),"+f"(d[21]),"+f"(d[22]),"+f"(d[23]),
        "+f"(d[24]),"+f"(d[25]),"+f"(d[26]),"+f"(d[27]),"+f"(d[28]),"+f"(d[29]),"+f"(d[30]),"+f"(d[31]),
        "+f"(d[32]),"+f"(d[33]),"+f"(d[34]),"+f"(d[35]),"+f"(d[36]),"+f"(d[37]),"+f"(d[38]),"+f"(d[39]),
        "+f"(d[40]),"+f"(d[41]),"+f"(d[42]),"+f"(d[43]),"+f"(d[44]),"+f"(d[45]),"+f"(d[46]),"+f"(d[47]),
        "+f"(d[48]),"+f"(d[49]),"+f"(d[50]),"+f"(d[51]),"+f"(d[52]),"+f"(d[53]),"+f"(d[54]),"+f"(d[55]),
        "+f"(d[56]),"+f"(d[57]),"+f"(d[58]),"+f"(d[59]),"+f"(d[60]),"+f"(d[61]),"+f"(d[62]),"+f"(d[63])
      : "r"(a0), "r"(a1), "r"(a2), "r"(a3), "l"(db));
}

constexpr int C_LN = 0;
constexpr int NB_CONS = 1, NB_LN = 2, NB_LAG = 4, NB_INIT = 6, NB_RDY = 7;
#define LAGX 3
#define LAGY 3
#define LAG2 4
#define NLL 2
#define POLL_DELAY3 500
#define POLL_DELAY 700
#define PF2_SIG 1
constexpr int SM_E = 0, SM_X = 16384, SM_FC = 32768, SM_T = 36864, SM_E2 = 131072, SM_W = 147456;
constexpr unsigned long long KORDER = 0xBA9432DC876510ull;
constexpr uint32_t HI128 = desc_hi(1024, 1), HI64 = desc_hi(512, 2);

struct Bars {
  uint64_t full1[6], empty1[6], fullA[8], full2[14], prog2[6], xbar, xfree, tbar, sbar, sig[2];
  uint32_t epoch;
};

template <int NK>
__device__ __forceinline__ void make_p(const float (&acc)[NK * 16], float r0, float r1, uint4 (&p)[NK]) {
#pragma unroll
  for (int j = 0; j < NK; j++) {
    uint32_t w[4];
#pragma unroll
    for (int i = 0; i < 4; i++) {
      const int a = 8 * j + 2 * i, b = a + NK * 8;
      w[i] = pack2(swiglu(acc[a], acc[b], (i & 1) ? r1 : r0), swiglu(acc[a + 1], acc[b + 1], (i & 1) ? r1 : r0));
    }
    p[j] = make_uint4(w[0], w[1], w[2], w[3]);
  }
}
__device__ __forceinline__ void spin_cycles(uint32_t n) {
  const uint32_t t0 = clock32();
  while (clock32() - t0 < n) {}
}

__global__ void __cluster_dims__(2, 1, 1) __launch_bounds__(NTHREADS, 1)
fused_kernel(const __grid_constant__ CUtensorMap tmGX, const __grid_constant__ CUtensorMap tmUX,
             const __grid_constant__ CUtensorMap tmGY, const __grid_constant__ CUtensorMap tmUY,
             const __grid_constant__ CUtensorMap tmD, const __grid_constant__ CUtensorMap tmWR,
             const __grid_constant__ CUtensorMap tmWI, const __nv_bfloat16* __restrict__ x,
             const char* __restrict__ wg_raw, const char* __restrict__ wu_raw, const char* __restrict__ wd_raw,
             __nv_bfloat16* __restrict__ out) {
  extern __shared__ __align__(1024) char smem_raw[];
  const uint32_t sbase = (s2u(smem_raw) + 1023) & ~1023u;
  const uint32_t sbar = sbase + 14 * SLOT, sstat = sbar + 512;
  const int tid = threadIdx.x, lane = tid & 31;
  const int c = blockIdx.x, kh = c & 1, f = (c >> 1) & 7, rb = 2 * (c >> 4) + kh, rb2 = 2 * (c >> 4) + (f >> 2), nq = f & 3;
#define BAR(field, i) (sbar + (uint32_t)offsetof(Bars, field) + 8u * (i))
#define TOFF(field) (sbase + SM_T + (uint32_t)offsetof(Tables, field) + lane * 16)

  if (tid >= 256) {
    asm volatile("setmaxnreg.dec.sync.aligned.u32 56;");
    const int warp = __shfl_sync(0xffffffffu, tid >> 5, 0);
    if (tid == 256) {
      for (int i = 0; i < 6; i++) { mbar_init(BAR(full1, i), 1); mbar_init(BAR(empty1, i), 16); mbar_init(BAR(prog2, i), 8); }
      for (int i = 0; i < 8; i++) mbar_init(BAR(fullA, i), 1);
      for (int i = 0; i < 14; i++) mbar_init(BAR(full2, i), 1);
      mbar_init(BAR(xbar, 0), 1);
      mbar_init(BAR(xfree, 0), 8);
      mbar_init(BAR(tbar, 0), 1);
      mbar_init(BAR(sbar, 0), 32);
      mbar_init(BAR(sig, 0), 8);
      mbar_init(BAR(sig, 1), 16);
      mbar_expect(BAR(xbar, 0), 16384);
      asm volatile("fence.mbarrier_init.release.cluster;" ::: "memory");
    }
    if (tid == 320) {
      const unsigned e = ld_relaxed(&g_cnt[(C_LN + rb) * 32]) >> 3;
      asm volatile("st.shared.u32 [%0], %1;" ::"r"(BAR(epoch, 0)), "r"(e) : "memory");
    }
    __syncwarp();
    asm volatile("barrier.cluster.arrive.relaxed.aligned;" ::: "memory");
    bar_arrive(NB_RDY, 384);
    bar_sync(NB_INIT, 384);
    unsigned epoch;
    asm volatile("ld.shared.u32 %0, [%1];" : "=r"(epoch) : "r"(BAR(epoch, 0)) : "memory");
    if (warp == 8) {
      if (lane == 0) {
        const int ax = (7 * f + 3 * (f & 1)) >> 1;
        const int ay = 7 * f + ((f & 1) ? 0 : 4);
        const CUtensorMap* tx = kh ? &tmUX : &tmGX;
        const CUtensorMap* ty = kh ? &tmUY : &tmGY;
        uint32_t s = 0, ph = 1;
        mbar_wait(BAR(sig, 1), 0);
#pragma unroll 1
        for (int n = 0; n < 32; n++) {
          const uint32_t dst = sbase + (8 + s) * SLOT, fb = BAR(full1, s);
          mbar_wait(BAR(empty1, s), ph);
          if (n < 16) {
            mbar_expect(fb, 16384);
            tma3_mc(dst + kh * 8192, tx, fb, n * 32, ax);
          } else {
            mbar_expect(fb, 12288);
            tma3_mc(dst + kh * 6144, ty, fb, (n - 16) * 32, ay);
          }
          if (++s == 6) { s = 0; ph ^= 1; }
        }
      }
    } else if (warp == 9) {
      if (lane == 0) {
        mbar_wait(BAR(empty1, 5), 0);
        mbar_wait(BAR(empty1, 5), 1);
#pragma unroll 1
        for (int i = 0; i < 14; i++) {
          const int kblk = 14 * kh + (int)((KORDER >> (4 * i)) & 15);
          if (i < 8) mbar_wait(BAR(empty1, (17 + 2 * i) % 6), ((17 + 2 * i) / 6) & 1);
          else mbar_wait(BAR(prog2, i - 8), 0);
          mbar_expect(BAR(full2, i), 16384);
          tma3(sbase + i * SLOT, &tmD, BAR(full2, i), 0, 64 * kblk, 2 * nq);
        }
      }
    } else if (warp == 10) {
      if (lane == 0) {
        const int w0 = ((c >> 3) * 257 + 32 * (c & 7) + 1) & ~7;
        mbar_expect(BAR(tbar, 0), T2_BYTES + 2 * 10240);
        tma3(sbase + SM_W, &tmWR, BAR(tbar, 0), w0, 0, 0);
        tma3(sbase + SM_W + 10240, &tmWI, BAR(tbar, 0), w0, 0, 0);
        bulk_load(sbase + SM_T + T1_BYTES, reinterpret_cast<const char*>(&g_tab) + T1_BYTES, T2_BYTES, BAR(tbar, 0));
      }
      bar_sync(NB_LN, 288);
      if (lane == 0) {
        PROFP(0);
        red_release(&g_cnt[(C_LN + rb) * 32]);
        PROFP(1);
        wait_counter(&g_cnt[(C_LN + rb) * 32], (epoch + 1) * 8);
        asm volatile("fence.proxy.async.global;" ::: "memory");
        PROFP(2);
#pragma unroll 1
        for (int kb = NLL; kb < 8; kb++) {
          mbar_expect(BAR(fullA, kb), 16384);
          bulk_load(sbase + kb * SLOT, &g_LN[(rb * 8 + kb) * 1024], 16384, BAR(fullA, kb));
        }
      }
    } else {
      if (lane == 0) {
        l2_prefetch(wg_raw + (size_t)c * 5376, 5376);
        l2_prefetch(wu_raw + (size_t)c * 5376, 5376);
        mbar_wait(BAR(sig, PF2_SIG), 0);
        l2_prefetch(wg_raw + 688128 + (size_t)c * 8960, 8960);
        l2_prefetch(wu_raw + 688128 + (size_t)c * 8960, 8960);
      }
      mbar_wait(BAR(fullA, 7), 0);
      if (lane == 0) l2_prefetch(wd_raw + (size_t)c * 14336, 14336);
      {
        const uint32_t tag = (epoch + 1) & 1;
        uint4 v0, v1, v2;
        int it = 0;
        while (true) {
          v0 = ld_b128(&g_ST[rb * 64 + lane]);
          v1 = ld_b128(&g_ST[rb * 64 + 32 + lane]);
          v2 = ld_b128(&g_ST[rb2 * 64 + 32 * kh + lane]);
          if (!__any_sync(0xffffffffu, ((v0.x ^ tag) | (v1.x ^ tag) | (v2.x ^ tag)) & 1u)) break;
          if (++it > SPIN_LIMIT) __trap();
        }
        sts4(sstat + lane * 16, v0.x & ~1u, v0.y, v0.z, v0.w);
        sts4(sstat + 512 + lane * 16, v1.x & ~1u, v1.y, v1.z, v1.w);
        sts4(sstat + 1024 + lane * 16, v2.x & ~1u, v2.y, v2.z, v2.w);
        mbar_arrive(BAR(sbar, 0));
      }
    }
    __syncwarp();
    asm volatile("barrier.cluster.wait.aligned;" ::: "memory");
  } else {
    const int warp = __shfl_sync(0xffffffffu, tid >> 5, 0);
    const int g = lane >> 2, t = lane & 3;
    PROF(0);
    PROFG(14);
#pragma unroll
    for (int i = 0; i < 4; i++) {
      const int r = i >> 1, ch = (i & 1) * 32 + lane;
      cp_async16(sbase + SM_X + (2 * warp + r) * 1024 + ((ch ^ ((ch >> 2) & 6)) * 16),
                 x + (size_t)(c + 128 * (2 * warp + r)) * 512 + ch * 8);
    }
    asm volatile("cp.async.commit_group;" ::: "memory");
    asm volatile("barrier.cluster.arrive.relaxed.aligned;" ::: "memory");
    uint4 tw[8], fb[16];
    const uint4 fa = ldg_ca4(&g_tab.fa[lane][0]);
#pragma unroll
    for (int i = 0; i < 8; i++) tw[i] = ldg_ca4(&g_tab.tw1[i][lane][0]);
#pragma unroll
    for (int i = 0; i < 16; i++) fb[i] = ldg_ca4(&g_tab.fb[i][lane][0]);
    asm volatile("setmaxnreg.inc.sync.aligned.u32 224;");
    uint32_t rbar;
    asm volatile("mapa.shared::cluster.u32 %0, %1, %2;" : "=r"(rbar) : "r"(sbar), "r"(kh ^ 1));
#define RBAR(field, i) (rbar + (uint32_t)offsetof(Bars, field) + 8u * (i))
    {
      const int ln = (tid >> 1) & 31, lg = ln >> 2, lt = ln & 3, i = 4 * (tid >> 6) + 2 * (tid & 1);
      const int kidx = lt + 8 * (i >> 3), nidx = 4 * ((i >> 1) & 3) + (lg >> 1);
      const uint32_t a0 = cfrag<2048>((c + 128 * kidx) * nidx, lg & 1), a1 = cfrag<2048>((c + 128 * (kidx + 4)) * nidx, lg & 1);
      const uint32_t b0 = cfrag<2048>(-(c + 128 * nidx) * kidx, lg & 1), b1 = cfrag<2048>(-(c + 128 * nidx) * (kidx + 4), lg & 1);
      asm volatile("st.shared.v2.u32 [%0], {%1,%2};" ::"r"(sbase + SM_FC + tid * 8), "r"(a0), "r"(a1) : "memory");
      asm volatile("st.shared.v2.u32 [%0], {%1,%2};" ::"r"(sbase + SM_FC + 2048 + tid * 8), "r"(b0), "r"(b1) : "memory");
    }
    asm volatile("cp.async.wait_group 0;" ::: "memory");
    __syncwarp();
    bar_arrive(NB_INIT, 384);
    PROF(13);
    uint32_t tag;
    uint4 q[4], o[4];
    {
      uint32_t v[2][8];
#pragma unroll
      for (int r = 0; r < 2; r++)
#pragma unroll
        for (int q = 0; q < 4; q++) {
          const uint2 u = lds2(sbase + SM_X + (2 * warp + r) * 1024 + (t + 4 * (q >> 1)) * 128 + (((4 * (q & 1) + (g >> 1)) ^ (2 * t)) * 16) + (g & 1) * 8);
          v[r][2 * q] = u.x; v[r][2 * q + 1] = u.y;
        }
      float sum[2], sq[2], rstd[2];
      row_stats(v[0], v[1], lane, sum, sq);
#pragma unroll
      for (int r = 0; r < 2; r++) {
        const float m = sum[r] * (1.f / 512.f);
        rstd[r] = rsqrtf(fmaxf(fmaf(-m, m, sq[r] * (1.f / 512.f)), 0.f) + 1e-5f);
      }
      uint32_t alo[4][4], ahi[4][4];
#pragma unroll
      for (int r = 0; r < 2; r++)
#pragma unroll
        for (int i = 0; i < 4; i++) {
          const uint32_t sel = (i & 1) ? 0x7632u : 0x5410u;
          const uint32_t b0 = __byte_perm(v[r][i >> 1], v[r][2 + (i >> 1)], sel);
          const uint32_t b1 = __byte_perm(v[r][4 + (i >> 1)], v[r][6 + (i >> 1)], sel);
          float d[4] = {0.f, 0.f, 0.f, 0.f};
          mma16816(d, fa.x, fa.y, fa.z, fa.w, b0, b1);
          const uint4 &ka = tw[2 * i], &kb = tw[2 * i + 1];
          const uint32_t re = pack2(d[0] * __uint_as_float(ka.x) + d[2] * __uint_as_float(ka.y), d[1] * __uint_as_float(kb.x) + d[3] * __uint_as_float(kb.y));
          const uint32_t im = pack2(d[0] * __uint_as_float(ka.z) + d[2] * __uint_as_float(ka.w), d[1] * __uint_as_float(kb.z) + d[3] * __uint_as_float(kb.w));
          const uint32_t dc = pack2(fmaf(sum[r], -1.f / 32.f, d[0]), fmaf(sum[r], -1.f / 32.f, d[1]));
          alo[i][r] = re; alo[i][2 + r] = im;
          ahi[i][r] = g == 0 ? dc : re; ahi[i][2 + r] = g == 0 ? 0u : im;
        }
      float acc[8][4];
#pragma unroll
      for (int u = 0; u < 8; u++) {
        acc[u][0] = acc[u][1] = acc[u][2] = acc[u][3] = 0.f;
#pragma unroll
        for (int i = 0; i < 4; i++) {
          const uint4& bq = fb[i * 4 + (u >> 1)];
          if (u < 4) mma16816(acc[u], alo[i][0], alo[i][1], alo[i][2], alo[i][3], (u & 1) ? bq.z : bq.x, (u & 1) ? bq.w : bq.y);
          else       mma16816(acc[u], ahi[i][0], ahi[i][1], ahi[i][2], ahi[i][3], (u & 1) ? bq.z : bq.x, (u & 1) ? bq.w : bq.y);
        }
      }
#pragma unroll
      for (int r = 0; r < 2; r++)
#pragma unroll
        for (int h = 0; h < 2; h++) {
          const int j = 2 * warp + r, m = 2 * t + h;
          const float rs = rstd[r];
          sts4(sbase + SM_E + ((j * 8 + m) * 8 + (g ^ (2 * t) ^ (2 * (j & 3)))) * 16,
               pack2(acc[2 * h][2 * r] * rs, acc[2 * h][2 * r + 1] * rs), pack2(acc[2 * h + 1][2 * r] * rs, acc[2 * h + 1][2 * r + 1] * rs),
               pack2(acc[4 + 2 * h][2 * r] * rs, acc[4 + 2 * h][2 * r + 1] * rs), pack2(acc[5 + 2 * h][2 * r] * rs, acc[5 + 2 * h][2 * r + 1] * rs));
        }
      if (tid == 0) PROFP(12);
      bar_sync(NB_RDY, 384);
      if (tid == 0) PROFP(13);
      uint4 fc[4];
#pragma unroll
      for (int i = 0; i < 4; i++) fc[i] = lds4(sbase + SM_FC + i * 512 + lane * 16);
      asm volatile("ld.shared.u32 %0, [%1];" : "=r"(tag) : "r"(BAR(epoch, 0)) : "memory");
      tag = (tag + 1) & 1;
#pragma unroll
      for (int i = 0; i < 4; i++) q[i] = lds4(sbase + SM_E + (((t + 4 * i) * 8 + warp) * 8 + (g ^ (warp & 6) ^ (2 * t))) * 16);
      cdft16(q, fc, o);
#pragma unroll
      for (int vv = 0; vv < 4; vv++) st_tag(&g_Z1[(((4 * vv + t) * 8 + warp) * 128 + c) * 8 + g], o[vv], tag);
    }
    PROF(1);
    {
      const uint4* const zp = &g_Z1[(c * 128 + 8 * t + warp) * 8 + g];
      spin_cycles(POLL_DELAY);
      ld_tag4_issue<256>(q, zp);
      mbar_wait(BAR(tbar, 0), 0);
      if (tid == 0) PROFP(14);
      uint4 f2[4], g2[4];
#pragma unroll
      for (int i = 0; i < 4; i++) {
        f2[i] = lds4(TOFF(f2) + warp * 2048 + i * 512);
        g2[i] = lds4(TOFF(g2) + warp * 2048 + i * 512);
      }
      const uint4 f8 = lds4(TOFF(f8)), g8 = lds4(TOFF(g8));
      float wfr[16], wfi[16];
      {
        const float fsc = 1.f / (1 << 19);
        const float fsc3 = ((c & 7) == 7 && g == 0) ? 0.5f * fsc : fsc;
        const int gg = g == 0 ? 8 : g, wsh = (2 * (c >> 3) + 2) & 15;
#pragma unroll
        for (int i = 0; i < 16; i++) {
          const int ci = i >> 3, dd = (i >> 2) & 1, e = i & 3;
          const int kk = (e == 0 ? gg : e == 1 ? 16 + gg : e == 2 ? 16 - g : 32 - g) - 1;
          const uint32_t a = sbase + SM_W + ((2 * warp + ci) * 8 + t + 4 * dd) * 80 + wsh + 2 * kk;
          wfr[i] = bf_lo(lds_u16(a)) * (e == 3 ? fsc3 : fsc);
          wfi[i] = bf_lo(lds_u16(a + 10240)) * (e == 3 ? fsc3 : fsc);
        }
      }
      asm volatile("barrier.cluster.wait.aligned;" ::: "memory");
      PROF(2);
      ld_tag4_finish<256>(q, zp, tag);
      if (tid == 0) PROFP(30);
      if (lane == 0) mbar_arrive(BAR(sig, 0));
      cdft16(q, f2, o);
      const uint32_t e2 = sbase + SM_E2;
#pragma unroll
      for (int vv = 0; vv < 4; vv++)
        sts4(e2 + ((warp * 16 + 4 * vv + t) * 8 + (g ^ (2 * t) ^ (2 * (warp & 3)))) * 16, o[vv].x, o[vv].y, o[vv].z, o[vv].w);
      bar_sync(NB_CONS, 256);
#pragma unroll
      for (int ci = 0; ci < 2; ci++) {
        const int cc = 2 * warp + ci;
        uint32_t ad[2];
        uint4 u[2];
#pragma unroll
        for (int hh = 0; hh < 2; hh++) {
          ad[hh] = e2 + (((t + 4 * hh) * 16 + cc) * 8 + (g ^ (2 * (cc & 3)) ^ (2 * t))) * 16;
          u[hh] = lds4(ad[hh]);
        }
        uint32_t res[2][4];
#pragma unroll
        for (int p = 0; p < 2; p++) {
          uint32_t y[2][2];
#pragma unroll
          for (int vv = 0; vv < 2; vv++) {
            float d[4] = {0.f, 0.f, 0.f, 0.f};
            mma16816(d, word(u[0], 2 * p), word(u[0], 2 * p + 1), word(u[1], 2 * p), word(u[1], 2 * p + 1), word(f8, 2 * vv), word(f8, 2 * vv + 1));
#pragma unroll
            for (int rr = 0; rr < 2; rr++) {
              const float fr = wfr[ci * 8 + vv * 4 + 2 * p + rr], fi = wfi[ci * 8 + vv * 4 + 2 * p + rr];
              y[vv][rr] = pack2(d[2 * rr] * fr - d[2 * rr + 1] * fi, d[2 * rr] * fi + d[2 * rr + 1] * fr);
            }
          }
#pragma unroll
          for (int vv = 0; vv < 2; vv++) {
            float d[4] = {0.f, 0.f, 0.f, 0.f};
            mma16816(d, y[0][0], y[0][1], y[1][0], y[1][1], word(g8, 2 * vv), word(g8, 2 * vv + 1));
            res[vv][2 * p] = pack2(d[0], d[1]);
            res[vv][2 * p + 1] = pack2(d[2], d[3]);
          }
        }
#pragma unroll
        for (int vv = 0; vv < 2; vv++) sts4(ad[vv], res[vv][0], res[vv][1], res[vv][2], res[vv][3]);
      }
      bar_sync(NB_CONS, 256);
#pragma unroll
      for (int i = 0; i < 4; i++) q[i] = lds4(e2 + ((warp * 16 + 4 * i + t) * 8 + (g ^ (2 * t) ^ (2 * (warp & 3)))) * 16);
      cdft16(q, g2, o);
#pragma unroll
      for (int vv = 0; vv < 4; vv++) st_tag(&g_Z2[((8 * (4 * vv + t) + warp) * 128 + c) * 8 + g], o[vv], tag);
    }
    PROF(3);
    {
      const uint4* const zp = &g_Z2[((c * 16 + t) * 8 + warp) * 8 + g];
      spin_cycles(POLL_DELAY);
      ld_tag4_issue<256>(q, zp);
      uint4 gb[16], gc[4], tw[4], xr[2][2];
#pragma unroll
      for (int i = 0; i < 16; i++) gb[i] = lds4(TOFF(gb) + i * 512);
      const uint4 ga = lds4(TOFF(ga));
#pragma unroll
      for (int i = 0; i < 4; i++) {
        gc[i] = lds4(sbase + SM_FC + 2048 + i * 512 + lane * 16);
        tw[i] = lds4(TOFF(tw3) + i * 512);
        const int ch = 4 * (g + 8 * (i & 1)) + t;
        xr[i >> 1][i & 1] = lds4(sbase + SM_X + (2 * warp + (i >> 1)) * 1024 + ((ch ^ ((ch >> 2) & 6)) * 16));
      }
      asm volatile("fence.proxy.async.shared::cta;" ::: "memory");
      PROF(4);
      ld_tag4_finish<256>(q, zp, tag);
      if (tid == 0) PROFP(31);
      if (lane == 0) { mbar_arrive(BAR(sig, 1)); mbar_arrive_remote(RBAR(sig, 1)); }
      cdft16(q, gc, o);
#pragma unroll
      for (int vv = 0; vv < 4; vv++)
        sts4(sbase + SM_E + (((4 * vv + t) * 8 + warp) * 8 + (g ^ (warp & 6) ^ (2 * t))) * 16, o[vv].x, o[vv].y, o[vv].z, o[vv].w);
      bar_sync(NB_CONS, 256);
      uint32_t hv[2][8];
      const float mk = t == 0 ? 0.f : 1.f;
#pragma unroll
      for (int r = 0; r < 2; r++) {
        const int j = 2 * warp + r;
        uint4 u[2];
#pragma unroll
        for (int h = 0; h < 2; h++) u[h] = lds4(sbase + SM_E + ((j * 8 + 2 * t + h) * 8 + (g ^ (2 * t) ^ (2 * (j & 3)))) * 16);
        float yv[4][4];
#pragma unroll
        for (int i = 0; i < 4; i++) {
          float lo[4] = {0.f, 0.f, 0.f, 0.f}, hi[4] = {0.f, 0.f, 0.f, 0.f};
          mma16816(lo, gb[i * 4].x, gb[i * 4].y, gb[i * 4].z, gb[i * 4].w, u[0].x, u[0].y);
          mma16816(lo, gb[i * 4 + 1].x, gb[i * 4 + 1].y, gb[i * 4 + 1].z, gb[i * 4 + 1].w, u[1].x, u[1].y);
          mma16816(hi, gb[i * 4 + 2].x, gb[i * 4 + 2].y, gb[i * 4 + 2].z, gb[i * 4 + 2].w, u[0].z, u[0].w);
          mma16816(hi, gb[i * 4 + 3].x, gb[i * 4 + 3].y, gb[i * 4 + 3].z, gb[i * 4 + 3].w, u[1].z, u[1].w);
          const float ca = __uint_as_float(tw[i].x), sa = __uint_as_float(tw[i].y), cb = __uint_as_float(tw[i].z), sb = __uint_as_float(tw[i].w);
          const float tr0 = fmaf(hi[0], mk, lo[0]), ti0 = fmaf(hi[2], mk, lo[2]);
          const float tr1 = lo[1] + hi[1], ti1 = lo[3] + hi[3];
          const float vr0 = tr0 * ca - ti0 * sa, vi0 = tr0 * sa + ti0 * ca;
          const float vr1 = tr1 * cb - ti1 * sb, vi1 = tr1 * sb + ti1 * cb;
          const uint32_t b0 = pack2(t == 0 ? hi[0] : vr0, vr1), b1 = pack2(t == 0 ? vr0 : vi0, vi1);
          yv[i][0] = yv[i][1] = yv[i][2] = yv[i][3] = 0.f;
          mma16816(yv[i], ga.x, ga.y, ga.z, ga.w, b0, b1);
        }
#pragma unroll
        for (int h = 0; h < 2; h++) {
          hv[r][4 * h + 0] = hadd2_bf16(xr[r][h].x, pack2(yv[0][2 * h], yv[1][2 * h]));
          hv[r][4 * h + 1] = hadd2_bf16(xr[r][h].y, pack2(yv[2][2 * h], yv[3][2 * h]));
          hv[r][4 * h + 2] = hadd2_bf16(xr[r][h].z, pack2(yv[0][2 * h + 1], yv[1][2 * h + 1]));
          hv[r][4 * h + 3] = hadd2_bf16(xr[r][h].w, pack2(yv[2][2 * h + 1], yv[3][2 * h + 1]));
        }
      }
      float ds[4] = {0.f, 0.f, 0.f, 0.f};
#pragma unroll
      for (int q4 = 0; q4 < 4; q4++) mma16816(ds, hv[0][2 * q4], hv[1][2 * q4], hv[0][2 * q4 + 1], hv[1][2 * q4 + 1], 0x3f803f80u, 0x3f803f80u);
#pragma unroll
      for (int o2 = 4; o2 <= 16; o2 <<= 1) {
        ds[0] += __shfl_xor_sync(0xffffffffu, ds[0], o2);
        ds[2] += __shfl_xor_sync(0xffffffffu, ds[2], o2);
      }
      uint32_t mb[2];
#pragma unroll
      for (int r = 0; r < 2; r++) {
        const int row = 16 * f + 2 * warp + r;
        mb[r] = pack2(ds[2 * r] * (1.f / 512.f), ds[2 * r] * (1.f / 512.f));
#pragma unroll
        for (int i = 0; i < 8; i++) hv[r][i] = hsub2_bf16(hv[r][i], mb[r]);
#pragma unroll
        for (int h = 0; h < 2; h++) {
          const int n1 = g + 8 * h;
          st_tag(&g_LN[(rb * 8 + (n1 >> 1)) * 1024 + row * 8 + ((4 * (n1 & 1) + t) ^ (row & 7))],
                 make_uint4(hv[r][4 * h], hv[r][4 * h + 1], hv[r][4 * h + 2], hv[r][4 * h + 3]), n1 < 2 * NLL ? tag : (hv[r][4 * h] & 1u));
        }
      }
      asm volatile("fence.proxy.async.shared::cta;" ::: "memory");
      bar_arrive(NB_LN, 288);
      float sum[2], sq[2], rstd[2];
      row_stats(hv[0], hv[1], lane, sum, sq);
#pragma unroll
      for (int r = 0; r < 2; r++) {
        const float m = sum[r] * (1.f / 512.f);
        rstd[r] = rsqrtf(fmaxf(fmaf(-m, m, sq[r] * (1.f / 512.f)), 0.f) + 1e-5f);
      }
      if (lane == 0)
        st_tag(&g_ST[rb * 64 + 8 * f + warp], make_uint4(mb[0] << 16, __float_as_uint(rstd[0]), mb[1] << 16, __float_as_uint(rstd[1])), tag);
    }
    PROF(5);
    if (NLL) {
      const uint4* const ap = &g_LN[rb * 8 * 1024 + tid];
      uint4 av[NLL ? NLL : 1][4];
      spin_cycles(POLL_DELAY3);
#pragma unroll
      for (int kb = 0; kb < NLL; kb++) ld_tag4_issue<256>(av[kb], ap + kb * 1024);
      bar_sync(NB_CONS, 256);
#pragma unroll
      for (int kb = 0; kb < NLL; kb++) {
        ld_tag4_finish<256>(av[kb], ap + kb * 1024, tag);
#pragma unroll
        for (int i = 0; i < 4; i++) sts4(sbase + kb * SLOT + (tid + 256 * i) * 16, av[kb][i].x, av[kb][i].y, av[kb][i].z, av[kb][i].w);
      }
      asm volatile("fence.proxy.async.shared::cta;" ::: "memory");
      bar_sync(NB_CONS, 256);
    }
    const int wgi = warp >> 2, wq = warp & 3;
    uint4* const pbase = &g_P[rb * 28 * 1024 + warp * 128 + lane];
    const uint32_t a_lo0 = desc_lo(sbase + wgi * 8192, 16);
    const uint32_t ebar = lane == 0 ? BAR(empty1, 0) : RBAR(empty1, 0);
    float r0, r1;
    uint4 px[8], py[6], pa[3][4];
    const int rh = wgi ^ kh ^ 1;
    const uint4* const psrc = &g_P[(rb2 * 28 + 14 * kh) * 1024 + (4 * rh + wq) * 128 + lane];
    {
      float acc[128];
#pragma unroll
      for (int i = 0; i < 128; i++) acc[i] = 0.f;
      const uint32_t b_lo0 = desc_lo(sbase + 8 * SLOT, 4096);
      uint32_t slot = 0, ph = 0, prev = 0;
#pragma unroll 1
      for (int kb = 0; kb < 8; kb++) {
        if (kb >= NLL) mbar_wait(BAR(fullA, kb), 0);
        if (kb == 0) PROF(6);
#pragma unroll
        for (int hh = 0; hh < 2; hh++) {
          if (LAGX && hh == ((16 - LAGX) & 1) && kb == ((16 - LAGX) >> 1) && wgi == 1) bar_sync(NB_LAG, 256);
          mbar_wait(BAR(full1, slot), ph);
          const uint32_t al = a_lo0 + kb * 1024 + hh * 4, bl = b_lo0 + slot * 1024;
          wg_fence();
          wgmma_n256(acc, desc64(al, HI128), desc64(bl, HI128));
          wgmma_n256(acc, desc64(al + 2, HI128), desc64(bl + 128, HI128));
          wg_commit();
          if (LAGX && hh == 1 && kb == 7 && wgi == 0) bar_arrive(NB_LAG, 256);
          wg_wait<1>();
          if ((kb | hh) != 0 && lane < 2) mbar_arrive_remote(ebar + 8 * prev);
          prev = slot;
          if (++slot == 6) { slot = 0; ph ^= 1; }
        }
      }
      mbar_wait(BAR(sbar, 0), 0);
      r0 = __uint_as_float(lds2(sstat + (16 * warp + g) * 8).y);
      r1 = __uint_as_float(lds2(sstat + (16 * warp + g + 8) * 8).y);
      wg_wait<0>();
      if (lane < 2) mbar_arrive_remote(ebar + 8 * prev);
      PROF(7);
      make_p<8>(acc, r0, r1, px);
    }
    PROF(8);
    {
      float acc[96];
#pragma unroll
      for (int i = 0; i < 96; i++) acc[i] = 0.f;
      const uint32_t b_lo0 = desc_lo(sbase + 8 * SLOT, 2048);
      uint4* const pdst = pbase + ((7 * f + 3 * (f & 1)) >> 1) * 1024;
#pragma unroll
      for (int k = 0; k < 16; k++) {
        if (LAGY && k == 16 - LAGY && wgi == 1) bar_sync(NB_LAG, 256);
        mbar_wait(BAR(full1, (16 + k) % 6), ((16 + k) / 6) & 1);
        const uint32_t al = a_lo0 + (k >> 1) * 1024 + (k & 1) * 4, bl = b_lo0 + ((16 + k) % 6) * 1024;
        wg_fence();
        wgmma_n192(acc, desc64(al, HI128), desc64(bl, HI64));
        wgmma_n192(acc, desc64(al + 2, HI128), desc64(bl + 64, HI64));
        wg_commit();
        if (k < 4) {
          st_tag(pdst + (k >> 1) * 1024 + (k & 1) * 64, px[2 * k], tag);
          st_tag(pdst + (k >> 1) * 1024 + (k & 1) * 64 + 32, px[2 * k + 1], tag);
        }
        if (k >= 14) ld_tag4_issue<32>(pa[k - 14], psrc + (int)((KORDER >> (4 * (k - 14))) & 15) * 1024);
        if (LAGY && k == 15 && wgi == 0) bar_arrive(NB_LAG, 256);
        wg_wait<1>();
        if (k != 0 && lane < 2) mbar_arrive_remote(ebar + 8 * ((15 + k) % 6));
      }
      wg_wait<0>();
      if (lane < 2) mbar_arrive_remote(ebar + 8 * (31 % 6));
      PROF(9);
      make_p<6>(acc, r0, r1, py);
    }
    PROF(10);
    {
      const int trow = 64 * rh + 16 * wq + g;
      const int G0 = 7 * f + ((f & 1) ? 0 : 4);
      float acc[64];
      {
        const float m0 = wgi ? __uint_as_float(lds2(sstat + 1024 + (16 * wq + g) * 8).x) : 0.f;
        const float m1 = wgi ? __uint_as_float(lds2(sstat + 1024 + (16 * wq + g + 8) * 8).x) : 0.f;
#pragma unroll
        for (int i = 0; i < 64; i++) acc[i] = (i & 2) ? m1 : m0;
      }
      const uint32_t b2_lo0 = desc_lo(sbase, 8192);
      uint4 hres[2][4];
#pragma unroll
      for (int s = 0; s < 14; s++) {
        uint4 (&a)[4] = pa[s % 3];
        if (LAG2 && s == 14 - LAG2 && wgi == 1) bar_sync(NB_LAG, 256);
        ld_tag4_finish<32>(a, psrc + (int)((KORDER >> (4 * s)) & 15) * 1024, tag);
        mbar_wait(BAR(full2, s), 0);
        if (tid == 0) PROFP(16 + s);
        const uint32_t bl = b2_lo0 + s * 1024;
        wg_fence();
#pragma unroll
        for (int kk = 0; kk < 4; kk++) wgmma_rs_n128(acc, a[kk].x, a[kk].y, a[kk].z, a[kk].w, desc64(bl + kk * 128, HI128));
        wg_commit();
        if (s == 0) {
#pragma unroll
          for (int k = 0; k < 6; k++) st_tag(pbase + ((G0 + (k >> 1)) >> 1) * 1024 + ((G0 + (k >> 1)) & 1) * 64 + (k & 1) * 32, py[k], tag);
        }
        if (LAG2 && s == 13 && wgi == 0) bar_arrive(NB_LAG, 256);
        if (s == 11) {
#pragma unroll
          for (int h = 0; h < 2; h++)
#pragma unroll
            for (int q = 0; q < 4; q++) {
              hres[h][q] = ldg_cg4(&g_LN[(rb2 * 8 + 2 * nq + (q >> 1)) * 1024 + (trow + 8 * h) * 8 + ((4 * (q & 1) + t) ^ g)]);
              if (2 * nq + (q >> 1) < NLL) hres[h][q].x &= ~1u;
            }
        }
        wg_wait<1>();
        if (s + 2 < 14) ld_tag4_issue<32>(pa[(s + 2) % 3], psrc + (int)((KORDER >> (4 * (s + 2))) & 15) * 1024);
        if (lane == 0) {
          if (s < 6) mbar_arrive(BAR(prog2, s));
          if (s == 1) mbar_arrive_remote(RBAR(xfree, 0));
        }
      }
      wg_wait<0>();
      PROF(11);
      const uint32_t xbuf = sbase + (tid & 127) * 16;
      if (wgi == 0) {
        uint32_t rbuf;
        mbar_wait(BAR(xfree, 0), 0);
        asm volatile("mapa.shared::cluster.u32 %0, %1, %2;" : "=r"(rbuf) : "r"(xbuf), "r"(kh ^ 1));
#pragma unroll
        for (int i = 0; i < 8; i++)
          asm volatile("st.async.weak.shared::cluster.mbarrier::complete_tx::bytes.v4.b32 [%0], {%1,%2,%3,%4}, [%5];"
                       ::"r"(rbuf + i * 2048), "r"(pack2(acc[8 * i], acc[8 * i + 1])), "r"(pack2(acc[8 * i + 2], acc[8 * i + 3])),
                         "r"(pack2(acc[8 * i + 4], acc[8 * i + 5])), "r"(pack2(acc[8 * i + 6], acc[8 * i + 7])), "r"(RBAR(xbar, 0))
                       : "memory");
      } else {
        mbar_wait_cluster(BAR(xbar, 0), 0);
      }
      uint32_t w[2][16];
#pragma unroll
      for (int i = 0; i < 8; i++) {
        const uint4 pv = lds4(xbuf + i * 2048);
        w[0][2 * i] = pack2(acc[8 * i] + bf_lo(pv.x), acc[8 * i + 1] + bf_hi(pv.x));
        w[1][2 * i] = pack2(acc[8 * i + 2] + bf_lo(pv.y), acc[8 * i + 3] + bf_hi(pv.y));
        w[0][2 * i + 1] = pack2(acc[8 * i + 4] + bf_lo(pv.z), acc[8 * i + 5] + bf_hi(pv.z));
        w[1][2 * i + 1] = pack2(acc[8 * i + 6] + bf_lo(pv.w), acc[8 * i + 7] + bf_hi(pv.w));
      }
      uint4* const o4 = reinterpret_cast<uint4*>(out) + (16 * (c >> 4) + 2 * (4 * rh + wq) + (rb2 & 1) + 128 * g) * 64 + nq * 16 + t;
#pragma unroll
      for (int h = 0; h < 2; h++)
#pragma unroll
        for (int q = 0; q < 4; q++) {
          uint32_t a0 = w[h][4 * q], a1 = w[h][4 * q + 1], a2 = w[h][4 * q + 2], a3 = w[h][4 * q + 3];
          {
            const bool od = t & 1;
            uint32_t s0 = od ? a0 : a1, s1 = od ? a2 : a3;
            s0 = __shfl_xor_sync(0xffffffffu, s0, 1); s1 = __shfl_xor_sync(0xffffffffu, s1, 1);
            if (od) { a0 = s0; a2 = s1; } else { a1 = s0; a3 = s1; }
          }
          {
            const bool up = t & 2;
            uint32_t s0 = up ? a0 : a2, s1 = up ? a1 : a3;
            s0 = __shfl_xor_sync(0xffffffffu, s0, 2); s1 = __shfl_xor_sync(0xffffffffu, s1, 2);
            if (up) { a0 = s0; a1 = s1; } else { a2 = s0; a3 = s1; }
          }
          if (wgi == 1)
            o4[h * 1024 * 64 + 4 * q] =
                make_uint4(hadd2_bf16(hres[h][q].x, a0), hadd2_bf16(hres[h][q].y, a1), hadd2_bf16(hres[h][q].z, a2), hadd2_bf16(hres[h][q].w, a3));
        }
      PROF(12);
      PROFG(15);
    }
  }
#undef BAR
#undef TOFF
#undef RBAR
}

typedef CUresult (*EncodeFn)(CUtensorMap*, CUtensorMapDataType, cuuint32_t, void*, const cuuint64_t*, const cuuint64_t*,
                             const cuuint32_t*, const cuuint32_t*, CUtensorMapInterleave, CUtensorMapSwizzle,
                             CUtensorMapL2promotion, CUtensorMapFloatOOBfill);

}

extern "C" void kernel_launch(void* const* d_in, const int* in_sizes, int n_in, void* d_out, int out_size) {
  (void)in_sizes; (void)n_in; (void)out_size;
  static EncodeFn encode = nullptr;
  if (!encode) {
    void* fn = nullptr;
    cudaDriverEntryPointQueryResult qr;
    cudaGetDriverEntryPoint("cuTensorMapEncodeTiled", &fn, cudaEnableDefault, &qr);
    encode = (EncodeFn)fn;
    cudaFuncSetAttribute(fused_kernel, cudaFuncAttributeMaxDynamicSharedMemorySize, SMEM_BYTES);
  }
  CUtensorMap tmGX, tmUX, tmGY, tmUY, tmD, tmWR, tmWI;
  const cuuint32_t es[5] = {1, 1, 1, 1, 1};
  auto enc = [&](CUtensorMap* m, void* p, int rank, const cuuint64_t* gd, const cuuint64_t* gs, const cuuint32_t* bd,
                 CUtensorMapSwizzle sw, CUtensorMapL2promotion pr) {
    encode(m, CU_TENSOR_MAP_DATA_TYPE_BFLOAT16, rank, p, gd, gs, bd, es, CU_TENSOR_MAP_INTERLEAVE_NONE, sw, pr,
           CU_TENSOR_MAP_FLOAT_OOB_FILL_NONE);
  };
  {
    const cuuint64_t gd[3] = {64, 512, 28}, gs[2] = {3584, 128};
    const cuuint32_t bd[3] = {64, 32, 2};
    enc(&tmGX, d_in[4], 3, gd, gs, bd, CU_TENSOR_MAP_SWIZZLE_128B, CU_TENSOR_MAP_L2_PROMOTION_L2_256B);
    enc(&tmUX, d_in[5], 3, gd, gs, bd, CU_TENSOR_MAP_SWIZZLE_128B, CU_TENSOR_MAP_L2_PROMOTION_L2_256B);
  }
  {
    const cuuint64_t gd[3] = {32, 512, 56}, gs[2] = {3584, 64};
    const cuuint32_t bd[3] = {32, 32, 3};
    enc(&tmGY, d_in[4], 3, gd, gs, bd, CU_TENSOR_MAP_SWIZZLE_64B, CU_TENSOR_MAP_L2_PROMOTION_L2_128B);
    enc(&tmUY, d_in[5], 3, gd, gs, bd, CU_TENSOR_MAP_SWIZZLE_64B, CU_TENSOR_MAP_L2_PROMOTION_L2_128B);
  }
  {
    const cuuint64_t gd[3] = {64, 1792, 8}, gs[2] = {1024, 128};
    const cuuint32_t bd[3] = {64, 64, 2};
    enc(&tmD, d_in[6], 3, gd, gs, bd, CU_TENSOR_MAP_SWIZZLE_128B, CU_TENSOR_MAP_L2_PROMOTION_L2_256B);
  }
  {
    const cuuint64_t gd[3] = {4112, 8, 16}, gs[2] = {16 * 8224, 8224};
    const cuuint32_t bd[3] = {40, 8, 16};
    enc(&tmWR, d_in[1], 3, gd, gs, bd, CU_TENSOR_MAP_SWIZZLE_NONE, CU_TENSOR_MAP_L2_PROMOTION_NONE);
    enc(&tmWI, d_in[2], 3, gd, gs, bd, CU_TENSOR_MAP_SWIZZLE_NONE, CU_TENSOR_MAP_L2_PROMOTION_NONE);
  }
  fused_kernel<<<NCTA, NTHREADS, SMEM_BYTES>>>(tmGX, tmUX, tmGY, tmUY, tmD, tmWR, tmWI, (const __nv_bfloat16*)d_in[0],
                                               (const char*)d_in[4], (const char*)d_in[5], (const char*)d_in[6],
                                               (__nv_bfloat16*)d_out);
}
```

```cpp
#include <cuda_runtime.h>
#include <cuda_bf16.h>
#include <cuda.h>
#include <stdint.h>

namespace {

constexpr int NCTA = 128;
constexpr int NTHREADS = 384;
constexpr int SLOT = 16384;
constexpr int SMEM_BYTES = 14 * SLOT + 2048 + 1024;
constexpr int SPIN_LIMIT = 1 << 22;

__device__ uint4 g_Z1[128 * 1024];
__device__ uint4 g_Z2[128 * 1024];
__device__ uint4 g_LN[16 * 8 * 1024];
__device__ uint4 g_ST[1024];
__device__ uint4 g_P[16 * 28 * 1024];
__device__ unsigned g_cnt[64 * 32];
#define PROF(i)
#define PROFP(i)
#define PROFG(i)

constexpr double ccos(int i, int n) {
  i &= n - 1;
  if (i > n / 2) i = n - i;
  if (4 * i == n) return 0.0;
  const bool neg = 4 * i > n;
  if (neg) i = n / 2 - i;
  const double a = 6.283185307179586476925 * i / n, a2 = a * a;
  double term = 1.0, sum = 1.0;
  for (int k = 1; k < 14; k++) { term *= -a2 / ((2 * k - 1) * (2 * k)); sum += term; }
  return neg ? -sum : sum;
}
constexpr double csin(int i, int n) { return ccos(i - n / 4, n); }
constexpr unsigned fbits(double v, int mant) {
  if (v == 0.0) return 0;
  const unsigned sg = v < 0 ? 1u : 0u;
  if (v < 0) v = -v;
  int e = 127;
  while (v < 1.0) { v *= 2.0; e--; }
  const unsigned m = (unsigned)((v - 1.0) * (double)(1u << mant) + 0.5);
  return (sg << (8 + mant)) + ((unsigned)e << mant) + m;
}
constexpr unsigned pkb(double lo, double hi) { return fbits(lo, 7) | (fbits(hi, 7) << 16); }
constexpr double fa_elem(int kp, int n1) {
  return kp <= 8 ? ccos(kp * n1, 16) : -csin((kp - 8) * n1, 16);
}
constexpr unsigned cfrag_c(int idx, int n, int ri) {
  return ri ? pkb(-csin(idx, n), ccos(idx, n)) : pkb(ccos(idx, n), csin(idx, n));
}
struct Tables {
  unsigned fb[16][32][4];
  unsigned tw1[8][32][4];
  unsigned fa[32][4];
  unsigned f2[8][4][32][4];
  unsigned g2[8][4][32][4];
  unsigned gb[16][32][4];
  unsigned tw3[4][32][4];
  unsigned ga[32][4];
  unsigned f8[32][4], g8[32][4];
};
constexpr int T1_BYTES = 12800, T2_BYTES = 44544;
static_assert(sizeof(Tables) == T1_BYTES + T2_BYTES, "table size");
constexpr Tables make_tables() {
  Tables T = {};
  for (int l = 0; l < 32; l++) {
    const int g = l >> 2, t = l & 3;
    for (int i = 0; i < 4; i++)
      for (int u = 0; u < 8; u++) {
        const int ri = g & 1, m = 2 * (g >> 1) + ((u & 3) >> 1);
        const double sg = u >= 4 ? -1.0 : 1.0;
        const int k2 = u >= 4 ? 31 - 2 * m - (u & 1) : 2 * m + (u & 1);
        const int pa = (8 * t + i) * k2, pb = (8 * t + 4 + i) * k2;
        T.fb[i * 4 + (u >> 1)][l][(u & 1) * 2 + 0] = ri == 0 ? pkb(ccos(pa, 32), ccos(pb, 32)) : pkb(-sg * csin(pa, 32), -sg * csin(pb, 32));
        T.fb[i * 4 + (u >> 1)][l][(u & 1) * 2 + 1] = ri == 0 ? pkb(csin(pa, 32), csin(pb, 32)) : pkb(sg * ccos(pa, 32), sg * ccos(pb, 32));
      }
    for (int i = 0; i < 4; i++)
      for (int ks = 0; ks < 4; ks++) {
        const int n2 = 4 * g + i, m = 2 * t + (ks & 1);
        const double sg = ks >= 2 ? -1.0 : 1.0;
        const int pa = n2 * (ks >= 2 ? 31 - 2 * m : 2 * m), pb = n2 * (ks >= 2 ? 30 - 2 * m : 2 * m + 1);
        T.gb[i * 4 + ks][l][0] = pkb(ccos(pa, 32), -sg * csin(pa, 32));
        T.gb[i * 4 + ks][l][1] = pkb(csin(pa, 32), sg * ccos(pa, 32));
        T.gb[i * 4 + ks][l][2] = pkb(ccos(pb, 32), -sg * csin(pb, 32));
        T.gb[i * 4 + ks][l][3] = pkb(csin(pb, 32), sg * ccos(pb, 32));
      }
    for (int i = 0; i < 4; i++) {
      for (int e = 0; e < 2; e++) {
        const int p = (8 * t + 4 * e + i) * (g == 0 ? 8 : g);
        T.tw1[2 * i + e][l][0] = fbits(g == 0 ? 0.0 : ccos(p, 512), 23);
        T.tw1[2 * i + e][l][1] = fbits(g == 0 ? ccos(p, 512) : csin(p, 512), 23);
        T.tw1[2 * i + e][l][2] = fbits(g == 0 ? 0.0 : -csin(p, 512), 23);
        T.tw1[2 * i + e][l][3] = fbits(g == 0 ? -csin(p, 512) : ccos(p, 512), 23);
      }
      const int ka = t == 0 ? 8 : 2 * t, kb = 2 * t + 1;
      T.tw3[i][l][0] = fbits(ccos((4 * g + i) * ka, 512), 23);
      T.tw3[i][l][1] = fbits(csin((4 * g + i) * ka, 512), 23);
      T.tw3[i][l][2] = fbits(ccos((4 * g + i) * kb, 512), 23);
      T.tw3[i][l][3] = fbits(csin((4 * g + i) * kb, 512), 23);
      const int p8 = (t + 4 * (i & 1)) * (4 * (i >> 1) + (g >> 1));
      T.f8[l][i] = cfrag_c(p8, 8, g & 1);
      T.g8[l][i] = cfrag_c(-p8, 8, g & 1);
    }
    for (int w = 0; w < 8; w++)
      for (int i = 0; i < 16; i++) {
        const int kidx = t + 4 * (i & 1) + 8 * (i >> 3), nidx = 4 * ((i >> 1) & 3) + (g >> 1);
        T.f2[w][i >> 2][l][i & 3] = cfrag_c((8 * kidx + w) * nidx, 128, g & 1);
        T.g2[w][i >> 2][l][i & 3] = cfrag_c(-(8 * nidx + w) * kidx, 128, g & 1);
      }
    T.fa[l][0] = pkb(fa_elem(g, 2 * t), fa_elem(g, 2 * t + 1));
    T.fa[l][1] = pkb(fa_elem(g + 8, 2 * t), fa_elem(g + 8, 2 * t + 1));
    T.fa[l][2] = pkb(fa_elem(g, 2 * t + 8), fa_elem(g, 2 * t + 9));
    T.fa[l][3] = pkb(fa_elem(g + 8, 2 * t + 8), fa_elem(g + 8, 2 * t + 9));
    T.ga[l][0] = pkb(fa_elem(2 * t, g), fa_elem(2 * t + 1, g));
    T.ga[l][1] = pkb(fa_elem(2 * t, g + 8), fa_elem(2 * t + 1, g + 8));
    T.ga[l][2] = pkb(fa_elem(2 * t + 8, g), fa_elem(2 * t + 9, g));
    T.ga[l][3] = pkb(fa_elem(2 * t + 8, g + 8), fa_elem(2 * t + 9, g + 8));
  }
  return T;
}
__device__ const __align__(128) Tables g_tab = make_tables();

__device__ __forceinline__ void die() { asm volatile("st.global.u32 [%0], %1;" ::"l"(0ull), "r"(0) : "memory"); }
__device__ __forceinline__ uint32_t s2u(const void* p) { return (uint32_t)__cvta_generic_to_shared(p); }
__device__ __forceinline__ void mbar_init(uint32_t b, int c) { asm volatile("mbarrier.init.shared::cta.b64 [%0], %1;" ::"r"(b), "r"(c)); }
__device__ __forceinline__ void mbar_expect(uint32_t b, int bytes) {
  asm volatile("mbarrier.arrive.expect_tx.shared::cta.b64 _, [%0], %1;" ::"r"(b), "r"(bytes) : "memory");
}
__device__ __forceinline__ void mbar_arrive(uint32_t b) { asm volatile("mbarrier.arrive.shared::cta.b64 _, [%0];" ::"r"(b) : "memory"); }
__device__ __forceinline__ uint32_t mbar_try(uint32_t b, uint32_t parity) {
  uint32_t ok;
  asm volatile("{.reg .pred p; mbarrier.try_wait.parity.shared::cta.b64 p, [%1], %2; selp.u32 %0,1,0,p;}"
               : "=r"(ok) : "r"(b), "r"(parity) : "memory");
  return ok;
}
__device__ __forceinline__ void mbar_wait(uint32_t b, uint32_t parity) {
  int it = 0;
  while (!mbar_try(b, parity))
    if (++it > SPIN_LIMIT) { die(); break; }
}
__device__ __forceinline__ void mbar_wait_cluster(uint32_t b, int parity) {
  uint32_t ok;
  int it = 0;
  do {
    asm volatile("{.reg .pred p; mbarrier.try_wait.parity.acquire.cluster.shared::cta.b64 p, [%1], %2; selp.u32 %0,1,0,p;}"
                 : "=r"(ok) : "r"(b), "r"(parity) : "memory");
    if (++it > SPIN_LIMIT) { die(); break; }
  } while (!ok);
}
__device__ __forceinline__ void bar_sync(int id, int n) { asm volatile("bar.sync %0, %1;" ::"r"(id), "r"(n) : "memory"); }
__device__ __forceinline__ void bar_arrive(int id, int n) { asm volatile("bar.arrive %0, %1;" ::"r"(id), "r"(n) : "memory"); }
__device__ __forceinline__ void red_release(unsigned* p) { asm volatile("red.release.gpu.global.add.u32 [%0], 1;" ::"l"(p) : "memory"); }
__device__ __forceinline__ unsigned ld_acquire(const unsigned* p) {
  unsigned v;
  asm volatile("ld.acquire.gpu.global.u32 %0, [%1];" : "=r"(v) : "l"(p) : "memory");
  return v;
}
__device__ __forceinline__ unsigned ld_relaxed(const unsigned* p) {
  unsigned v;
  asm volatile("ld.relaxed.gpu.global.u32 %0, [%1];" : "=r"(v) : "l"(p) : "memory");
  return v;
}
__device__ __forceinline__ void wait_counter(const unsigned* p, unsigned target) {
  int it = 0;
  while ((int)(ld_acquire(p) - target) < 0)
    if (++it > SPIN_LIMIT) { die(); break; }
}
__device__ __forceinline__ uint4 ldg_cg4(const uint4* p) {
  uint4 v;
  asm volatile("ld.global.cg.v4.u32 {%0,%1,%2,%3}, [%4];" : "=r"(v.x), "=r"(v.y), "=r"(v.z), "=r"(v.w) : "l"(p) : "memory");
  return v;
}
__device__ __forceinline__ void sts4(uint32_t a, uint32_t x, uint32_t y, uint32_t z, uint32_t w) {
  asm volatile("st.shared.v4.u32 [%0], {%1,%2,%3,%4};" ::"r"(a), "r"(x), "r"(y), "r"(z), "r"(w) : "memory");
}
__device__ __forceinline__ uint4 lds4(uint32_t a) {
  uint4 v;
  asm volatile("ld.shared.v4.u32 {%0,%1,%2,%3}, [%4];" : "=r"(v.x), "=r"(v.y), "=r"(v.z), "=r"(v.w) : "r"(a) : "memory");
  return v;
}
__device__ __forceinline__ uint32_t pack2(float lo, float hi) {
  uint32_t r;
  asm("cvt.rn.bf16x2.f32 %0, %1, %2;" : "=r"(r) : "f"(hi), "f"(lo));
  return r;
}
__device__ __forceinline__ float bf_lo(uint32_t v) { return __uint_as_float(v << 16); }
__device__ __forceinline__ float bf_hi(uint32_t v) { return __uint_as_float(v & 0xffff0000u); }
__device__ __forceinline__ uint32_t hadd2_bf16(uint32_t a, uint32_t b) {
  uint32_t r;
  asm("add.rn.bf16x2 %0, %1, %2;" : "=r"(r) : "r"(a), "r"(b));
  return r;
}
__device__ __forceinline__ void mma16816(float (&d)[4], uint32_t a0, uint32_t a1, uint32_t a2, uint32_t a3, uint32_t b0, uint32_t b1) {
  asm("mma.sync.aligned.m16n8k16.row.col.f32.bf16.bf16.f32 {%0,%1,%2,%3}, {%4,%5,%6,%7}, {%8,%9}, {%0,%1,%2,%3};"
      : "+f"(d[0]), "+f"(d[1]), "+f"(d[2]), "+f"(d[3])
      : "r"(a0), "r"(a1), "r"(a2), "r"(a3), "r"(b0), "r"(b1));
}
template <int N>
__device__ __forceinline__ void cs_frac(int idx, float& c, float& s) {
  int i = ((idx + N / 2) & (N - 1)) - N / 2;
  float a = (float)i * (6.283185307179586f / N);
  c = __cosf(a);
  s = __sinf(a);
}
template <int N>
__device__ __forceinline__ uint32_t cfrag(int idx, int ri) {
  float c, s;
  cs_frac<N>(idx, c, s);
  return ri ? pack2(-s, c) : pack2(c, s);
}
__device__ __forceinline__ uint32_t word(const uint4& v, int e) { return e == 0 ? v.x : e == 1 ? v.y : e == 2 ? v.z : v.w; }
__device__ __forceinline__ void cdft16(const uint4 (&q)[4], const uint4 (&F)[4], uint4 (&o)[4]) {
  float acc[2][4][4];
#pragma unroll
  for (int p = 0; p < 2; p++)
#pragma unroll
    for (int v = 0; v < 4; v++) {
      acc[p][v][0] = acc[p][v][1] = acc[p][v][2] = acc[p][v][3] = 0.f;
#pragma unroll
      for (int ks = 0; ks < 2; ks++)
        mma16816(acc[p][v], word(q[2 * ks], 2 * p), word(q[2 * ks], 2 * p + 1), word(q[2 * ks + 1], 2 * p),
                 word(q[2 * ks + 1], 2 * p + 1), word(F[ks * 2 + (v >> 1)], (v & 1) * 2), word(F[ks * 2 + (v >> 1)], (v & 1) * 2 + 1));
    }
#pragma unroll
  for (int v = 0; v < 4; v++)
    o[v] = make_uint4(pack2(acc[0][v][0], acc[0][v][1]), pack2(acc[0][v][2], acc[0][v][3]),
                      pack2(acc[1][v][0], acc[1][v][1]), pack2(acc[1][v][2], acc[1][v][3]));
}
__device__ __forceinline__ void st_tag(uint4* p, const uint4& v, uint32_t tag) {
  asm volatile("{.reg .b128 r; .reg .b64 a, b; mov.b64 a, {%1,%2}; mov.b64 b, {%3,%4}; mov.b128 r, {a,b}; st.relaxed.gpu.global.b128 [%0], r;}"
               ::"l"(p), "r"((v.x & ~1u) | tag), "r"(v.y), "r"(v.z), "r"(v.w) : "memory");
}
__device__ __forceinline__ uint4 ld_b128(const uint4* p) {
  uint4 v;
  asm volatile("{.reg .b128 r; .reg .b64 a, b; ld.relaxed.gpu.global.b128 r, [%4]; mov.b128 {a,b}, r; mov.b64 {%0,%1}, a; mov.b64 {%2,%3}, b;}"
               : "=r"(v.x), "=r"(v.y), "=r"(v.z), "=r"(v.w) : "l"(p) : "memory");
  return v;
}
template <int STRIDE>
__device__ __forceinline__ void ld_tag4_issue(uint4 (&q)[4], const uint4* p) {
#pragma unroll
  for (int i = 0; i < 4; i++) q[i] = ld_b128(p + i * STRIDE);
}
template <int STRIDE>
__device__ __forceinline__ void ld_tag4_finish(uint4 (&q)[4], const uint4* p, uint32_t tag) {
  int it = 0;
  while (__any_sync(0xffffffffu, ((q[0].x ^ tag) | (q[1].x ^ tag) | (q[2].x ^ tag) | (q[3].x ^ tag)) & 1u)) {
    ld_tag4_issue<STRIDE>(q, p);
    if (++it > SPIN_LIMIT) { die(); break; }
  }
#pragma unroll
  for (int i = 0; i < 4; i++) asm volatile("and.b32 %0, %0, 0xfffffffe;" : "+r"(q[i].x));
}
__device__ __forceinline__ void row_stats(const uint32_t (&a)[8], const uint32_t (&b)[8], int lane, float (&sum)[2], float (&sq)[2]) {
  float da[4] = {0.f, 0.f, 0.f, 0.f}, db[4] = {0.f, 0.f, 0.f, 0.f}, ds[4] = {0.f, 0.f, 0.f, 0.f};
#pragma unroll
  for (int q = 0; q < 4; q++) {
    mma16816(ds, a[2 * q], b[2 * q], a[2 * q + 1], b[2 * q + 1], 0x3f803f80u, 0x3f803f80u);
    mma16816(da, a[2 * q], b[2 * q], a[2 * q + 1], b[2 * q + 1], a[2 * q], a[2 * q + 1]);
    mma16816(db, a[2 * q], b[2 * q], a[2 * q + 1], b[2 * q + 1], b[2 * q], b[2 * q + 1]);
  }
  const int src = (lane & 28) | (lane >> 3);
  const float qa = __shfl_sync(0xffffffffu, (lane & 4) ? da[1] : da[0], src);
  const float qb = __shfl_sync(0xffffffffu, (lane & 4) ? db[3] : db[2], src);
  float v = (lane & 2) ? ((lane & 1) ? ds[2] : ds[0]) : ((lane & 1) ? qb : qa);
  v += __shfl_xor_sync(0xffffffffu, v, 4);
  v += __shfl_xor_sync(0xffffffffu, v, 8);
  v += __shfl_xor_sync(0xffffffffu, v, 16);
  sq[0] = __shfl_sync(0xffffffffu, v, 0);
  sq[1] = __shfl_sync(0xffffffffu, v, 1);
  sum[0] = __shfl_sync(0xffffffffu, v, 2);
  sum[1] = __shfl_sync(0xffffffffu, v, 3);
}
__device__ __forceinline__ uint64_t desc64(uint32_t lo, uint32_t hi) {
  uint64_t d;
  asm("mov.b64 %0, {%1, %2};" : "=l"(d) : "r"(lo), "r"(hi));
  return d;
}
constexpr uint32_t desc_hi(uint32_t sbo, uint32_t swz) { return (sbo >> 4) | (swz << 30); }
__device__ __forceinline__ uint32_t desc_lo(uint32_t addr, uint32_t lbo) { return ((addr & 0x3FFFF) >> 4) | ((lbo >> 4) << 16); }
__device__ __forceinline__ void cp_async16(uint32_t dst, const void* src) {
  asm volatile("cp.async.cg.shared.global [%0], [%1], 16;" ::"r"(dst), "l"(src) : "memory");
}
__device__ __forceinline__ uint2 lds2(uint32_t a) {
  uint2 v;
  asm volatile("ld.shared.v2.u32 {%0,%1}, [%2];" : "=r"(v.x), "=r"(v.y) : "r"(a) : "memory");
  return v;
}
__device__ __forceinline__ uint32_t lds_u16(uint32_t a) {
  uint16_t v;
  asm volatile("ld.shared.u16 %0, [%1];" : "=h"(v) : "r"(a) : "memory");
  return v;
}
__device__ __forceinline__ void wg_fence() { asm volatile("wgmma.fence.sync.aligned;" ::: "memory"); }
__device__ __forceinline__ void wg_commit() { asm volatile("wgmma.commit_group.sync.aligned;" ::: "memory"); }
template <int N>
__device__ __forceinline__ void wg_wait() { asm volatile("wgmma.wait_group.sync.aligned %0;" ::"n"(N) : "memory"); }
__device__ __forceinline__ void bulk_load(uint32_t dst, const void* src, int bytes, uint32_t bar) {
  asm volatile("cp.async.bulk.shared::cluster.global.mbarrier::complete_tx::bytes [%0], [%1], %2, [%3];"
               ::"r"(dst), "l"(src), "r"(bytes), "r"(bar) : "memory");
}
__device__ __forceinline__ void tma3(uint32_t dst, const CUtensorMap* tm, uint32_t bar, int c0, int c1, int c2) {
  asm volatile("cp.async.bulk.tensor.3d.shared::cluster.global.mbarrier::complete_tx::bytes [%0], [%1, {%3,%4,%5}], [%2];"
               ::"r"(dst), "l"(tm), "r"(bar), "r"(c0), "r"(c1), "r"(c2) : "memory");
}
__device__ __forceinline__ void tma3_mc(uint32_t dst, const CUtensorMap* tm, uint32_t bar, int c1, int c2) {
  asm volatile("cp.async.bulk.tensor.3d.shared::cluster.global.mbarrier::complete_tx::bytes.multicast::cluster [%0], [%1, {%3,%4,%5}], [%2], %6;"
               ::"r"(dst), "l"(tm), "r"(bar), "r"(0), "r"(c1), "r"(c2), "h"((uint16_t)3) : "memory");
}
__device__ __forceinline__ void mbar_arrive_remote(uint32_t rb) {
  asm volatile("mbarrier.arrive.shared::cluster.b64 _, [%0];" ::"r"(rb) : "memory");
}
__device__ __forceinline__ uint4 ldg_ca4(const void* p) {
  uint4 v;
  asm volatile("ld.global.ca.v4.u32 {%0,%1,%2,%3}, [%4];" : "=r"(v.x), "=r"(v.y), "=r"(v.z), "=r"(v.w) : "l"(p) : "memory");
  return v;
}
__device__ __forceinline__ uint32_t clock32() {
  uint32_t v;
  asm volatile("mov.u32 %0, %%clock;" : "=r"(v) :: "memory");
  return v;
}
__device__ __forceinline__ float swiglu(float g, float u, float r) {
  float hg = (0.5f * r) * g, th;
  asm("tanh.approx.f32 %0, %1;" : "=f"(th) : "f"(hg));
  return fmaf(hg, th, hg) * (r * u);
}
__device__ __forceinline__ uint32_t hsub2_bf16(uint32_t a, uint32_t b) {
  uint32_t r;
  asm("sub.rn.bf16x2 %0, %1, %2;" : "=r"(r) : "r"(a), "r"(b));
  return r;
}
__device__ __forceinline__ void l2_prefetch(const void* p, int bytes) {
  asm volatile("cp.async.bulk.prefetch.L2.global [%0], %1;" ::"l"(p), "r"(bytes) : "memory");
}

__device__ __forceinline__ void wgmma_n256(float (&d)[128], uint64_t da, uint64_t db) {
  asm volatile("wgmma.mma_async.sync.aligned.m64n256k16.f32.bf16.bf16 {"
      "%0,%1,%2,%3,%4,%5,%6,%7,%8,%9,%10,%11,%12,%13,%14,%15,"
      "%16,%17,%18,%19,%20,%21,%22,%23,%24,%25,%26,%27,%28,%29,%30,%31,"
      "%32,%33,%34,%35,%36,%37,%38,%39,%40,%41,%42,%43,%44,%45,%46,%47,"
      "%48,%49,%50,%51,%52,%53,%54,%55,%56,%57,%58,%59,%60,%61,%62,%63,"
      "%64,%65,%66,%67,%68,%69,%70,%71,%72,%73,%74,%75,%76,%77,%78,%79,"
      "%80,%81,%82,%83,%84,%85,%86,%87,%88,%89,%90,%91,%92,%93,%94,%95,"
      "%96,%97,%98,%99,%100,%101,%102,%103,%104,%105,%106,%107,%108,%109,%110,%111,"
      "%112,%113,%114,%115,%116,%117,%118,%119,%120,%121,%122,%123,%124,%125,%126,%127"
      "}, %128, %129, 1, 1, 1, 0, 1;\n"
      : "+f"(d[0]),"+f"(d[1]),"+f"(d[2]),"+f"(d[3]),"+f"(d[4]),"+f"(d[5]),"+f"(d[6]),"+f"(d[7]),
        "+f"(d[8]),"+f"(d[9]),"+f"(d[10]),"+f"(d[11]),"+f"(d[12]),"+f"(d[13]),"+f"(d[14]),"+f"(d[15]),
        "+f"(d[16]),"+f"(d[17]),"+f"(d[18]),"+f"(d[19]),"+f"(d[20]),"+f"(d[21]),"+f"(d[22]),"+f"(d[23]),
        "+f"(d[24]),"+f"(d[25]),"+f"(d[26]),"+f"(d[27]),"+f"(d[28]),"+f"(d[29]),"+f"(d[30]),"+f"(d[31]),
        "+f"(d[32]),"+f"(d[33]),"+f"(d[34]),"+f"(d[35]),"+f"(d[36]),"+f"(d[37]),"+f"(d[38]),"+f"(d[39]),
        "+f"(d[40]),"+f"(d[41]),"+f"(d[42]),"+f"(d[43]),"+f"(d[44]),"+f"(d[45]),"+f"(d[46]),"+f"(d[47]),
        "+f"(d[48]),"+f"(d[49]),"+f"(d[50]),"+f"(d[51]),"+f"(d[52]),"+f"(d[53]),"+f"(d[54]),"+f"(d[55]),
        "+f"(d[56]),"+f"(d[57]),"+f"(d[58]),"+f"(d[59]),"+f"(d[60]),"+f"(d[61]),"+f"(d[62]),"+f"(d[63]),
        "+f"(d[64]),"+f"(d[65]),"+f"(d[66]),"+f"(d[67]),"+f"(d[68]),"+f"(d[69]),"+f"(d[70]),"+f"(d[71]),
        "+f"(d[72]),"+f"(d[73]),"+f"(d[74]),"+f"(d[75]),"+f"(d[76]),"+f"(d[77]),"+f"(d[78]),"+f"(d[79]),
        "+f"(d[80]),"+f"(d[81]),"+f"(d[82]),"+f"(d[83]),"+f"(d[84]),"+f"(d[85]),"+f"(d[86]),"+f"(d[87]),
        "+f"(d[88]),"+f"(d[89]),"+f"(d[90]),"+f"(d[91]),"+f"(d[92]),"+f"(d[93]),"+f"(d[94]),"+f"(d[95]),
        "+f"(d[96]),"+f"(d[97]),"+f"(d[98]),"+f"(d[99]),"+f"(d[100]),"+f"(d[101]),"+f"(d[102]),"+f"(d[103]),
        "+f"(d[104]),"+f"(d[105]),"+f"(d[106]),"+f"(d[107]),"+f"(d[108]),"+f"(d[109]),"+f"(d[110]),"+f"(d[111]),
        "+f"(d[112]),"+f"(d[113]),"+f"(d[114]),"+f"(d[115]),"+f"(d[116]),"+f"(d[117]),"+f"(d[118]),"+f"(d[119]),
        "+f"(d[120]),"+f"(d[121]),"+f"(d[122]),"+f"(d[123]),"+f"(d[124]),"+f"(d[125]),"+f"(d[126]),"+f"(d[127])
      : "l"(da), "l"(db));
}
__device__ __forceinline__ void wgmma_n192(float (&d)[96], uint64_t da, uint64_t db) {
  asm volatile("wgmma.mma_async.sync.aligned.m64n192k16.f32.bf16.bf16 {"
      "%0,%1,%2,%3,%4,%5,%6,%7,%8,%9,%10,%11,%12,%13,%14,%15,"
      "%16,%17,%18,%19,%20,%21,%22,%23,%24,%25,%26,%27,%28,%29,%30,%31,"
      "%32,%33,%34,%35,%36,%37,%38,%39,%40,%41,%42,%43,%44,%45,%46,%47,"
      "%48,%49,%50,%51,%52,%53,%54,%55,%56,%57,%58,%59,%60,%61,%62,%63,"
      "%64,%65,%66,%67,%68,%69,%70,%71,%72,%73,%74,%75,%76,%77,%78,%79,"
      "%80,%81,%82,%83,%84,%85,%86,%87,%88,%89,%90,%91,%92,%93,%94,%95"
      "}, %96, %97, 1, 1, 1, 0, 1;\n"
      : "+f"(d[0]),"+f"(d[1]),"+f"(d[2]),"+f"(d[3]),"+f"(d[4]),"+f"(d[5]),"+f"(d[6]),"+f"(d[7]),
        "+f"(d[8]),"+f"(d[9]),"+f"(d[10]),"+f"(d[11]),"+f"(d[12]),"+f"(d[13]),"+f"(d[14]),"+f"(d[15]),
        "+f"(d[16]),"+f"(d[17]),"+f"(d[18]),"+f"(d[19]),"+f"(d[20]),"+f"(d[21]),"+f"(d[22]),"+f"(d[23]),
        "+f"(d[24]),"+f"(d[25]),"+f"(d[26]),"+f"(d[27]),"+f"(d[28]),"+f"(d[29]),"+f"(d[30]),"+f"(d[31]),
        "+f"(d[32]),"+f"(d[33]),"+f"(d[34]),"+f"(d[35]),"+f"(d[36]),"+f"(d[37]),"+f"(d[38]),"+f"(d[39]),
        "+f"(d[40]),"+f"(d[41]),"+f"(d[42]),"+f"(d[43]),"+f"(d[44]),"+f"(d[45]),"+f"(d[46]),"+f"(d[47]),
        "+f"(d[48]),"+f"(d[49]),"+f"(d[50]),"+f"(d[51]),"+f"(d[52]),"+f"(d[53]),"+f"(d[54]),"+f"(d[55]),
        "+f"(d[56]),"+f"(d[57]),"+f"(d[58]),"+f"(d[59]),"+f"(d[60]),"+f"(d[61]),"+f"(d[62]),"+f"(d[63]),
        "+f"(d[64]),"+f"(d[65]),"+f"(d[66]),"+f"(d[67]),"+f"(d[68]),"+f"(d[69]),"+f"(d[70]),"+f"(d[71]),
        "+f"(d[72]),"+f"(d[73]),"+f"(d[74]),"+f"(d[75]),"+f"(d[76]),"+f"(d[77]),"+f"(d[78]),"+f"(d[79]),
        "+f"(d[80]),"+f"(d[81]),"+f"(d[82]),"+f"(d[83]),"+f"(d[84]),"+f"(d[85]),"+f"(d[86]),"+f"(d[87]),
        "+f"(d[88]),"+f"(d[89]),"+f"(d[90]),"+f"(d[91]),"+f"(d[92]),"+f"(d[93]),"+f"(d[94]),"+f"(d[95])
      : "l"(da), "l"(db));
}
__device__ __forceinline__ void wgmma_rs_n128(float (&d)[64], uint32_t a0, uint32_t a1, uint32_t a2, uint32_t a3, uint64_t db) {
  asm volatile("wgmma.mma_async.sync.aligned.m64n128k16.f32.bf16.bf16 {"
      "%0,%1,%2,%3,%4,%5,%6,%7,%8,%9,%10,%11,%12,%13,%14,%15,"
      "%16,%17,%18,%19,%20,%21,%22,%23,%24,%25,%26,%27,%28,%29,%30,%31,"
      "%32,%33,%34,%35,%36,%37,%38,%39,%40,%41,%42,%43,%44,%45,%46,%47,"
      "%48,%49,%50,%51,%52,%53,%54,%55,%56,%57,%58,%59,%60,%61,%62,%63"
      "}, {%64,%65,%66,%67}, %68, 1, 1, 1, 1;\n"
      : "+f"(d[0]),"+f"(d[1]),"+f"(d[2]),"+f"(d[3]),"+f"(d[4]),"+f"(d[5]),"+f"(d[6]),"+f"(d[7]),
        "+f"(d[8]),"+f"(d[9]),"+f"(d[10]),"+f"(d[11]),"+f"(d[12]),"+f"(d[13]),"+f"(d[14]),"+f"(d[15]),
        "+f"(d[16]),"+f"(d[17]),"+f"(d[18]),"+f"(d[19]),"+f"(d[20]),"+f"(d[21]),"+f"(d[22]),"+f"(d[23]),
        "+f"(d[24]),"+f"(d[25]),"+f"(d[26]),"+f"(d[27]),"+f"(d[28]),"+f"(d[29]),"+f"(d[30]),"+f"(d[31]),
        "+f"(d[32]),"+f"(d[33]),"+f"(d[34]),"+f"(d[35]),"+f"(d[36]),"+f"(d[37]),"+f"(d[38]),"+f"(d[39]),
        "+f"(d[40]),"+f"(d[41]),"+f"(d[42]),"+f"(d[43]),"+f"(d[44]),"+f"(d[45]),"+f"(d[46]),"+f"(d[47]),
        "+f"(d[48]),"+f"(d[49]),"+f"(d[50]),"+f"(d[51]),"+f"(d[52]),"+f"(d[53]),"+f"(d[54]),"+f"(d[55]),
        "+f"(d[56]),"+f"(d[57]),"+f"(d[58]),"+f"(d[59]),"+f"(d[60]),"+f"(d[61]),"+f"(d[62]),"+f"(d[63])
      : "r"(a0), "r"(a1), "r"(a2), "r"(a3), "l"(db));
}

constexpr int C_LN = 0;
constexpr int NB_CONS = 1, NB_LN = 2, NB_LAG = 4, NB_INIT = 6, NB_RDY = 7;
#define LAGX 3
#define LAGY 3
#define LAG2 4
#define PDIST 4
#define NLL 2
#define POLL_DELAY3 900
#define POLL_DELAY 900
#define PF2_SIG 1
constexpr int SM_E = 0, SM_X = 16384, SM_FC = 32768, SM_T = 36864, SM_E2 = 131072, SM_W = 147456;
constexpr unsigned long long KORDER = 0xBA9432DC876510ull;
constexpr uint32_t HI128 = desc_hi(1024, 1), HI64 = desc_hi(512, 2);

struct Bars {
  uint64_t full1[6], empty1[6], fullA[8], full2[14], prog2[6], xbar, xfree, tbar, sbar, sig[2];
  uint32_t epoch;
};

template <int NK>
__device__ __forceinline__ void make_p(const float (&acc)[NK * 16], float r0, float r1, uint4 (&p)[NK]) {
#pragma unroll
  for (int j = 0; j < NK; j++) {
    uint32_t w[4];
#pragma unroll
    for (int i = 0; i < 4; i++) {
      const int a = 8 * j + 2 * i, b = a + NK * 8;
      w[i] = pack2(swiglu(acc[a], acc[b], (i & 1) ? r1 : r0), swiglu(acc[a + 1], acc[b + 1], (i & 1) ? r1 : r0));
    }
    asm volatile("" : "+r"(w[0]), "+r"(w[1]), "+r"(w[2]), "+r"(w[3]));
    p[j] = make_uint4(w[0], w[1], w[2], w[3]);
  }
}
__device__ __forceinline__ void spin_cycles(uint32_t n) {
  const uint32_t t0 = clock32();
  while (clock32() - t0 < n) {}
}

__global__ void __cluster_dims__(2, 1, 1) __launch_bounds__(NTHREADS, 1)
fused_kernel(const __grid_constant__ CUtensorMap tmGX, const __grid_constant__ CUtensorMap tmUX,
             const __grid_constant__ CUtensorMap tmGY, const __grid_constant__ CUtensorMap tmUY,
             const __grid_constant__ CUtensorMap tmD, const __grid_constant__ CUtensorMap tmWR,
             const __grid_constant__ CUtensorMap tmWI, const __nv_bfloat16* __restrict__ x,
             const char* __restrict__ wg_raw, const char* __restrict__ wu_raw, const char* __restrict__ wd_raw,
             __nv_bfloat16* __restrict__ out) {
  extern __shared__ __align__(1024) char smem_raw[];
  const uint32_t sbase = (s2u(smem_raw) + 1023) & ~1023u;
  const uint32_t sbar = sbase + 14 * SLOT, sstat = sbar + 512;
  const int tid = threadIdx.x, lane = tid & 31;
  const int c = blockIdx.x, kh = c & 1, f = (c >> 1) & 7, rb = 2 * (c >> 4) + kh, rb2 = 2 * (c >> 4) + (f >> 2), nq = f & 3;
#define BAR(field, i) (sbar + (uint32_t)offsetof(Bars, field) + 8u * (i))
#define TOFF(field) (sbase + SM_T + (uint32_t)offsetof(Tables, field) + lane * 16)

  if (tid >= 256) {
    asm volatile("setmaxnreg.dec.sync.aligned.u32 56;");
    const int warp = __shfl_sync(0xffffffffu, tid >> 5, 0);
    if (tid == 256) {
      for (int i = 0; i < 6; i++) { mbar_init(BAR(full1, i), 1); mbar_init(BAR(empty1, i), 16); mbar_init(BAR(prog2, i), 8); }
      for (int i = 0; i < 8; i++) mbar_init(BAR(fullA, i), 1);
      for (int i = 0; i < 14; i++) mbar_init(BAR(full2, i), 1);
      mbar_init(BAR(xbar, 0), 1);
      mbar_init(BAR(xfree, 0), 8);
      mbar_init(BAR(tbar, 0), 1);
      mbar_init(BAR(sbar, 0), 32);
      mbar_init(BAR(sig, 0), 8);
      mbar_init(BAR(sig, 1), 16);
      mbar_expect(BAR(xbar, 0), 16384);
      asm volatile("fence.mbarrier_init.release.cluster;" ::: "memory");
    }
    if (tid == 320) {
      const unsigned e = ld_relaxed(&g_cnt[(C_LN + rb) * 32]) >> 3;
      asm volatile("st.shared.u32 [%0], %1;" ::"r"(BAR(epoch, 0)), "r"(e) : "memory");
    }
    __syncwarp();
    asm volatile("barrier.cluster.arrive.relaxed.aligned;" ::: "memory");
    bar_arrive(NB_RDY, 384);
    bar_sync(NB_INIT, 384);
    unsigned epoch;
    asm volatile("ld.shared.u32 %0, [%1];" : "=r"(epoch) : "r"(BAR(epoch, 0)) : "memory");
    if (warp == 8) {
      if (lane == 0) {
        const int ax = (7 * f + 3 * (f & 1)) >> 1;
        const int ay = 7 * f + ((f & 1) ? 0 : 4);
        const CUtensorMap* tx = kh ? &tmUX : &tmGX;
        const CUtensorMap* ty = kh ? &tmUY : &tmGY;
        uint32_t s = 0, ph = 1;
        mbar_wait(BAR(sig, 1), 0);
#pragma unroll 1
        for (int n = 0; n < 32; n++) {
          const uint32_t dst = sbase + (8 + s) * SLOT, fb = BAR(full1, s);
          mbar_wait(BAR(empty1, s), ph);
          if (n < 16) {
            mbar_expect(fb, 16384);
            tma3_mc(dst + kh * 8192, tx, fb, n * 32, ax);
          } else {
            mbar_expect(fb, 12288);
            tma3_mc(dst + kh * 6144, ty, fb, (n - 16) * 32, ay);
          }
          if (++s == 6) { s = 0; ph ^= 1; }
        }
      }
    } else if (warp == 9) {
      if (lane == 0) {
        mbar_wait(BAR(empty1, 5), 0);
        mbar_wait(BAR(empty1, 5), 1);
#pragma unroll 1
        for (int i = 0; i < 14; i++) {
          const int kblk = 14 * kh + (int)((KORDER >> (4 * i)) & 15);
          if (i < 8) mbar_wait(BAR(empty1, (17 + 2 * i) % 6), ((17 + 2 * i) / 6) & 1);
          else mbar_wait(BAR(prog2, i - 8), 0);
          mbar_expect(BAR(full2, i), 16384);
          tma3(sbase + i * SLOT, &tmD, BAR(full2, i), 0, 64 * kblk, 2 * nq);
        }
      }
    } else if (warp == 10) {
      if (lane == 0) {
        const int w0 = ((c >> 3) * 257 + 32 * (c & 7) + 1) & ~7;
        mbar_expect(BAR(tbar, 0), T2_BYTES + 2 * 10240);
        tma3(sbase + SM_W, &tmWR, BAR(tbar, 0), w0, 0, 0);
        tma3(sbase + SM_W + 10240, &tmWI, BAR(tbar, 0), w0, 0, 0);
        bulk_load(sbase + SM_T + T1_BYTES, reinterpret_cast<const char*>(&g_tab) + T1_BYTES, T2_BYTES, BAR(tbar, 0));
      }
      bar_sync(NB_LN, 288);
      if (lane == 0) {
        PROFP(0);
        red_release(&g_cnt[(C_LN + rb) * 32]);
        PROFP(1);
        wait_counter(&g_cnt[(C_LN + rb) * 32], (epoch + 1) * 8);
        asm volatile("fence.proxy.async.global;" ::: "memory");
        PROFP(2);
#pragma unroll 1
        for (int kb = NLL; kb < 8; kb++) {
          mbar_expect(BAR(fullA, kb), 16384);
          bulk_load(sbase + kb * SLOT, &g_LN[(rb * 8 + kb) * 1024], 16384, BAR(fullA, kb));
        }
      }
    } else {
      if (lane == 0) {
        l2_prefetch(wg_raw + (size_t)c * 5376, 5376);
        l2_prefetch(wu_raw + (size_t)c * 5376, 5376);
        mbar_wait(BAR(sig, PF2_SIG), 0);
        l2_prefetch(wg_raw + 688128 + (size_t)c * 8960, 8960);
        l2_prefetch(wu_raw + 688128 + (size_t)c * 8960, 8960);
      }
      mbar_wait(BAR(fullA, 7), 0);
      if (lane == 0) l2_prefetch(wd_raw + (size_t)c * 14336, 14336);
      {
        const uint32_t tag = (epoch + 1) & 1;
        uint4 v0, v1, v2;
        int it = 0;
        while (true) {
          v0 = ld_b128(&g_ST[rb * 64 + lane]);
          v1 = ld_b128(&g_ST[rb * 64 + 32 + lane]);
          v2 = ld_b128(&g_ST[rb2 * 64 + 32 * kh + lane]);
          if (!__any_sync(0xffffffffu, ((v0.x ^ tag) | (v1.x ^ tag) | (v2.x ^ tag)) & 1u)) break;
          if (++it > SPIN_LIMIT) { die(); break; }
        }
        sts4(sstat + lane * 16, v0.x & ~1u, v0.y, v0.z, v0.w);
        sts4(sstat + 512 + lane * 16, v1.x & ~1u, v1.y, v1.z, v1.w);
        sts4(sstat + 1024 + lane * 16, v2.x & ~1u, v2.y, v2.z, v2.w);
        mbar_arrive(BAR(sbar, 0));
      }
    }
    __syncwarp();
    asm volatile("barrier.cluster.wait.aligned;" ::: "memory");
  } else {
    const int warp = __shfl_sync(0xffffffffu, tid >> 5, 0);
    const int g = lane >> 2, t = lane & 3;
    PROF(0);
    PROFG(14);
#pragma unroll
    for (int i = 0; i < 4; i++) {
      const int r = i >> 1, ch = (i & 1) * 32 + lane;
      cp_async16(sbase + SM_X + (2 * warp + r) * 1024 + ((ch ^ ((ch >> 2) & 6)) * 16),
                 x + (size_t)(c + 128 * (2 * warp + r)) * 512 + ch * 8);
    }
    asm volatile("cp.async.commit_group;" ::: "memory");
    asm volatile("barrier.cluster.arrive.relaxed.aligned;" ::: "memory");
    asm volatile("setmaxnreg.inc.sync.aligned.u32 224;");
    uint4 tw[8], fb[16];
    const uint4 fa = ldg_ca4(&g_tab.fa[lane][0]);
#pragma unroll
    for (int i = 0; i < 8; i++) tw[i] = ldg_ca4(&g_tab.tw1[i][lane][0]);
#pragma unroll
    for (int i = 0; i < 16; i++) fb[i] = ldg_ca4(&g_tab.fb[i][lane][0]);
    uint32_t rbar;
    asm volatile("mapa.shared::cluster.u32 %0, %1, %2;" : "=r"(rbar) : "r"(sbar), "r"(kh ^ 1));
#define RBAR(field, i) (rbar + (uint32_t)offsetof(Bars, field) + 8u * (i))
    {
      const int ln = (tid >> 1) & 31, lg = ln >> 2, lt = ln & 3, i = 4 * (tid >> 6) + 2 * (tid & 1);
      const int kidx = lt + 8 * (i >> 3), nidx = 4 * ((i >> 1) & 3) + (lg >> 1);
      const uint32_t a0 = cfrag<2048>((c + 128 * kidx) * nidx, lg & 1), a1 = cfrag<2048>((c + 128 * (kidx + 4)) * nidx, lg & 1);
      const uint32_t b0 = cfrag<2048>(-(c + 128 * nidx) * kidx, lg & 1), b1 = cfrag<2048>(-(c + 128 * nidx) * (kidx + 4), lg & 1);
      asm volatile("st.shared.v2.u32 [%0], {%1,%2};" ::"r"(sbase + SM_FC + tid * 8), "r"(a0), "r"(a1) : "memory");
      asm volatile("st.shared.v2.u32 [%0], {%1,%2};" ::"r"(sbase + SM_FC + 2048 + tid * 8), "r"(b0), "r"(b1) : "memory");
    }
    asm volatile("cp.async.wait_group 0;" ::: "memory");
    __syncwarp();
    bar_arrive(NB_INIT, 384);
    PROF(13);
    uint32_t tag;
    uint4 q[4], o[4];
    {
      uint32_t v[2][8];
#pragma unroll
      for (int r = 0; r < 2; r++)
#pragma unroll
        for (int q = 0; q < 4; q++) {
          const uint2 u = lds2(sbase + SM_X + (2 * warp + r) * 1024 + (t + 4 * (q >> 1)) * 128 + (((4 * (q & 1) + (g >> 1)) ^ (2 * t)) * 16) + (g & 1) * 8);
          v[r][2 * q] = u.x; v[r][2 * q + 1] = u.y;
        }
      float sum[2], sq[2], rstd[2];
      row_stats(v[0], v[1], lane, sum, sq);
#pragma unroll
      for (int r = 0; r < 2; r++) {
        const float m = sum[r] * (1.f / 512.f);
        rstd[r] = rsqrtf(fmaxf(fmaf(-m, m, sq[r] * (1.f / 512.f)), 0.f) + 1e-5f);
      }
      uint32_t alo[4][4], ahi[4][4];
#pragma unroll
      for (int r = 0; r < 2; r++)
#pragma unroll
        for (int i = 0; i < 4; i++) {
          const uint32_t sel = (i & 1) ? 0x7632u : 0x5410u;
          const uint32_t b0 = __byte_perm(v[r][i >> 1], v[r][2 + (i >> 1)], sel);
          const uint32_t b1 = __byte_perm(v[r][4 + (i >> 1)], v[r][6 + (i >> 1)], sel);
          float d[4] = {0.f, 0.f, 0.f, 0.f};
          mma16816(d, fa.x, fa.y, fa.z, fa.w, b0, b1);
          const uint4 &ka = tw[2 * i], &kb = tw[2 * i + 1];
          const uint32_t re = pack2(d[0] * __uint_as_float(ka.x) + d[2] * __uint_as_float(ka.y), d[1] * __uint_as_float(kb.x) + d[3] * __uint_as_float(kb.y));
          const uint32_t im = pack2(d[0] * __uint_as_float(ka.z) + d[2] * __uint_as_float(ka.w), d[1] * __uint_as_float(kb.z) + d[3] * __uint_as_float(kb.w));
          const uint32_t dc = pack2(fmaf(sum[r], -1.f / 32.f, d[0]), fmaf(sum[r], -1.f / 32.f, d[1]));
          alo[i][r] = re; alo[i][2 + r] = im;
          ahi[i][r] = g == 0 ? dc : re; ahi[i][2 + r] = g == 0 ? 0u : im;
        }
      float acc[8][4];
#pragma unroll
      for (int u = 0; u < 8; u++) {
        acc[u][0] = acc[u][1] = acc[u][2] = acc[u][3] = 0.f;
#pragma unroll
        for (int i = 0; i < 4; i++) {
          const uint4& bq = fb[i * 4 + (u >> 1)];
          if (u < 4) mma16816(acc[u], alo[i][0], alo[i][1], alo[i][2], alo[i][3], (u & 1) ? bq.z : bq.x, (u & 1) ? bq.w : bq.y);
          else       mma16816(acc[u], ahi[i][0], ahi[i][1], ahi[i][2], ahi[i][3], (u & 1) ? bq.z : bq.x, (u & 1) ? bq.w : bq.y);
        }
      }
#pragma unroll
      for (int r = 0; r < 2; r++)
#pragma unroll
        for (int h = 0; h < 2; h++) {
          const int j = 2 * warp + r, m = 2 * t + h;
          const float rs = rstd[r];
          sts4(sbase + SM_E + ((j * 8 + m) * 8 + (g ^ (2 * t) ^ (2 * (j & 3)))) * 16,
               pack2(acc[2 * h][2 * r] * rs, acc[2 * h][2 * r + 1] * rs), pack2(acc[2 * h + 1][2 * r] * rs, acc[2 * h + 1][2 * r + 1] * rs),
               pack2(acc[4 + 2 * h][2 * r] * rs, acc[4 + 2 * h][2 * r + 1] * rs), pack2(acc[5 + 2 * h][2 * r] * rs, acc[5 + 2 * h][2 * r + 1] * rs));
        }
      if (tid == 0) PROFP(12);
      bar_sync(NB_RDY, 384);
      if (tid == 0) PROFP(13);
      uint4 fc[4];
#pragma unroll
      for (int i = 0; i < 4; i++) fc[i] = lds4(sbase + SM_FC + i * 512 + lane * 16);
      asm volatile("ld.shared.u32 %0, [%1];" : "=r"(tag) : "r"(BAR(epoch, 0)) : "memory");
      tag = (tag + 1) & 1;
#pragma unroll
      for (int i = 0; i < 4; i++) q[i] = lds4(sbase + SM_E + (((t + 4 * i) * 8 + warp) * 8 + (g ^ (warp & 6) ^ (2 * t))) * 16);
      cdft16(q, fc, o);
#pragma unroll
      for (int vv = 0; vv < 4; vv++) st_tag(&g_Z1[(((4 * vv + t) * 8 + warp) * 128 + c) * 8 + g], o[vv], tag);
    }
    PROF(1);
    {
      const uint4* const zp = &g_Z1[(c * 128 + 8 * t + warp) * 8 + g];
      const uint32_t tst = clock32();
      mbar_wait(BAR(tbar, 0), 0);
      if (tid == 0) PROFP(14);
      uint4 f2[4], g2[4];
#pragma unroll
      for (int i = 0; i < 4; i++) {
        f2[i] = lds4(TOFF(f2) + warp * 2048 + i * 512);
        g2[i] = lds4(TOFF(g2) + warp * 2048 + i * 512);
      }
      const uint4 f8 = lds4(TOFF(f8)), g8 = lds4(TOFF(g8));
      float wfr[16], wfi[16];
      {
        const float fsc = 1.f / (1 << 19);
        const float fsc3 = ((c & 7) == 7 && g == 0) ? 0.5f * fsc : fsc;
        const int gg = g == 0 ? 8 : g, wsh = (2 * (c >> 3) + 2) & 15;
#pragma unroll
        for (int i = 0; i < 16; i++) {
          const int ci = i >> 3, dd = (i >> 2) & 1, e = i & 3;
          const int kk = (e == 0 ? gg : e == 1 ? 16 + gg : e == 2 ? 16 - g : 32 - g) - 1;
          const uint32_t a = sbase + SM_W + ((2 * warp + ci) * 8 + t + 4 * dd) * 80 + wsh + 2 * kk;
          wfr[i] = bf_lo(lds_u16(a)) * (e == 3 ? fsc3 : fsc);
          wfi[i] = bf_lo(lds_u16(a + 10240)) * (e == 3 ? fsc3 : fsc);
        }
      }
      asm volatile("barrier.cluster.wait.aligned;" ::: "memory");
      PROF(2);
      while (clock32() - tst < POLL_DELAY) {}
      ld_tag4_issue<256>(q, zp);
      ld_tag4_finish<256>(q, zp, tag);
      if (tid == 0) PROFP(30);
      if (lane == 0) mbar_arrive(BAR(sig, 0));
      cdft16(q, f2, o);
      const uint32_t e2 = sbase + SM_E2;
#pragma unroll
      for (int vv = 0; vv < 4; vv++)
        sts4(e2 + ((warp * 16 + 4 * vv + t) * 8 + (g ^ (2 * t) ^ (2 * (warp & 3)))) * 16, o[vv].x, o[vv].y, o[vv].z, o[vv].w);
      bar_sync(NB_CONS, 256);
#pragma unroll
      for (int ci = 0; ci < 2; ci++) {
        const int cc = 2 * warp + ci;
        uint32_t ad[2];
        uint4 u[2];
#pragma unroll
        for (int hh = 0; hh < 2; hh++) {
          ad[hh] = e2 + (((t + 4 * hh) * 16 + cc) * 8 + (g ^ (2 * (cc & 3)) ^ (2 * t))) * 16;
          u[hh] = lds4(ad[hh]);
        }
        uint32_t res[2][4];
#pragma unroll
        for (int p = 0; p < 2; p++) {
          uint32_t y[2][2];
#pragma unroll
          for (int vv = 0; vv < 2; vv++) {
            float d[4] = {0.f, 0.f, 0.f, 0.f};
            mma16816(d, word(u[0], 2 * p), word(u[0], 2 * p + 1), word(u[1], 2 * p), word(u[1], 2 * p + 1), word(f8, 2 * vv), word(f8, 2 * vv + 1));
#pragma unroll
            for (int rr = 0; rr < 2; rr++) {
              const float fr = wfr[ci * 8 + vv * 4 + 2 * p + rr], fi = wfi[ci * 8 + vv * 4 + 2 * p + rr];
              y[vv][rr] = pack2(d[2 * rr] * fr - d[2 * rr + 1] * fi, d[2 * rr] * fi + d[2 * rr + 1] * fr);
            }
          }
#pragma unroll
          for (int vv = 0; vv < 2; vv++) {
            float d[4] = {0.f, 0.f, 0.f, 0.f};
            mma16816(d, y[0][0], y[0][1], y[1][0], y[1][1], word(g8, 2 * vv), word(g8, 2 * vv + 1));
            res[vv][2 * p] = pack2(d[0], d[1]);
            res[vv][2 * p + 1] = pack2(d[2], d[3]);
          }
        }
#pragma unroll
        for (int vv = 0; vv < 2; vv++) sts4(ad[vv], res[vv][0], res[vv][1], res[vv][2], res[vv][3]);
      }
      bar_sync(NB_CONS, 256);
#pragma unroll
      for (int i = 0; i < 4; i++) q[i] = lds4(e2 + ((warp * 16 + 4 * i + t) * 8 + (g ^ (2 * t) ^ (2 * (warp & 3)))) * 16);
      cdft16(q, g2, o);
#pragma unroll
      for (int vv = 0; vv < 4; vv++) st_tag(&g_Z2[((8 * (4 * vv + t) + warp) * 128 + c) * 8 + g], o[vv], tag);
    }
    PROF(3);
    {
      const uint4* const zp = &g_Z2[((c * 16 + t) * 8 + warp) * 8 + g];
      const uint32_t tst = clock32();
      uint4 gb[16], gc[4], tw[4], xr[2][2];
#pragma unroll
      for (int i = 0; i < 16; i++) gb[i] = lds4(TOFF(gb) + i * 512);
      const uint4 ga = lds4(TOFF(ga));
#pragma unroll
      for (int i = 0; i < 4; i++) {
        gc[i] = lds4(sbase + SM_FC + 2048 + i * 512 + lane * 16);
        tw[i] = lds4(TOFF(tw3) + i * 512);
        const int ch = 4 * (g + 8 * (i & 1)) + t;
        xr[i >> 1][i & 1] = lds4(sbase + SM_X + (2 * warp + (i >> 1)) * 1024 + ((ch ^ ((ch >> 2) & 6)) * 16));
      }
      asm volatile("fence.proxy.async.shared::cta;" ::: "memory");
      PROF(4);
      while (clock32() - tst < POLL_DELAY) {}
      ld_tag4_issue<256>(q, zp);
      ld_tag4_finish<256>(q, zp, tag);
      if (tid == 0) PROFP(31);
      if (lane == 0) { mbar_arrive(BAR(sig, 1)); mbar_arrive_remote(RBAR(sig, 1)); }
      cdft16(q, gc, o);
#pragma unroll
      for (int vv = 0; vv < 4; vv++)
        sts4(sbase + SM_E + (((4 * vv + t) * 8 + warp) * 8 + (g ^ (warp & 6) ^ (2 * t))) * 16, o[vv].x, o[vv].y, o[vv].z, o[vv].w);
      bar_sync(NB_CONS, 256);
      uint32_t hv[2][8];
      const float mk = t == 0 ? 0.f : 1.f;
#pragma unroll
      for (int r = 0; r < 2; r++) {
        const int j = 2 * warp + r;
        uint4 u[2];
#pragma unroll
        for (int h = 0; h < 2; h++) u[h] = lds4(sbase + SM_E + ((j * 8 + 2 * t + h) * 8 + (g ^ (2 * t) ^ (2 * (j & 3)))) * 16);
        float yv[4][4];
#pragma unroll
        for (int i = 0; i < 4; i++) {
          float lo[4] = {0.f, 0.f, 0.f, 0.f}, hi[4] = {0.f, 0.f, 0.f, 0.f};
          mma16816(lo, gb[i * 4].x, gb[i * 4].y, gb[i * 4].z, gb[i * 4].w, u[0].x, u[0].y);
          mma16816(lo, gb[i * 4 + 1].x, gb[i * 4 + 1].y, gb[i * 4 + 1].z, gb[i * 4 + 1].w, u[1].x, u[1].y);
          mma16816(hi, gb[i * 4 + 2].x, gb[i * 4 + 2].y, gb[i * 4 + 2].z, gb[i * 4 + 2].w, u[0].z, u[0].w);
          mma16816(hi, gb[i * 4 + 3].x, gb[i * 4 + 3].y, gb[i * 4 + 3].z, gb[i * 4 + 3].w, u[1].z, u[1].w);
          const float ca = __uint_as_float(tw[i].x), sa = __uint_as_float(tw[i].y), cb = __uint_as_float(tw[i].z), sb = __uint_as_float(tw[i].w);
          const float tr0 = fmaf(hi[0], mk, lo[0]), ti0 = fmaf(hi[2], mk, lo[2]);
          const float tr1 = lo[1] + hi[1], ti1 = lo[3] + hi[3];
          const float vr0 = tr0 * ca - ti0 * sa, vi0 = tr0 * sa + ti0 * ca;
          const float vr1 = tr1 * cb - ti1 * sb, vi1 = tr1 * sb + ti1 * cb;
          const uint32_t b0 = pack2(t == 0 ? hi[0] : vr0, vr1), b1 = pack2(t == 0 ? vr0 : vi0, vi1);
          yv[i][0] = yv[i][1] = yv[i][2] = yv[i][3] = 0.f;
          mma16816(yv[i], ga.x, ga.y, ga.z, ga.w, b0, b1);
        }
#pragma unroll
        for (int h = 0; h < 2; h++) {
          hv[r][4 * h + 0] = hadd2_bf16(xr[r][h].x, pack2(yv[0][2 * h], yv[1][2 * h]));
          hv[r][4 * h + 1] = hadd2_bf16(xr[r][h].y, pack2(yv[2][2 * h], yv[3][2 * h]));
          hv[r][4 * h + 2] = hadd2_bf16(xr[r][h].z, pack2(yv[0][2 * h + 1], yv[1][2 * h + 1]));
          hv[r][4 * h + 3] = hadd2_bf16(xr[r][h].w, pack2(yv[2][2 * h + 1], yv[3][2 * h + 1]));
        }
      }
      float ds[4] = {0.f, 0.f, 0.f, 0.f};
#pragma unroll
      for (int q4 = 0; q4 < 4; q4++) mma16816(ds, hv[0][2 * q4], hv[1][2 * q4], hv[0][2 * q4 + 1], hv[1][2 * q4 + 1], 0x3f803f80u, 0x3f803f80u);
#pragma unroll
      for (int o2 = 4; o2 <= 16; o2 <<= 1) {
        ds[0] += __shfl_xor_sync(0xffffffffu, ds[0], o2);
        ds[2] += __shfl_xor_sync(0xffffffffu, ds[2], o2);
      }
      uint32_t mb[2];
#pragma unroll
      for (int r = 0; r < 2; r++) {
        const int row = 16 * f + 2 * warp + r;
        mb[r] = pack2(ds[2 * r] * (1.f / 512.f), ds[2 * r] * (1.f / 512.f));
#pragma unroll
        for (int i = 0; i < 8; i++) hv[r][i] = hsub2_bf16(hv[r][i], mb[r]);
#pragma unroll
        for (int h = 0; h < 2; h++) {
          const int n1 = g + 8 * h;
          st_tag(&g_LN[(rb * 8 + (n1 >> 1)) * 1024 + row * 8 + ((4 * (n1 & 1) + t) ^ (row & 7))],
                 make_uint4(hv[r][4 * h], hv[r][4 * h + 1], hv[r][4 * h + 2], hv[r][4 * h + 3]), n1 < 2 * NLL ? tag : (hv[r][4 * h] & 1u));
        }
      }
      asm volatile("fence.proxy.async.shared::cta;" ::: "memory");
      bar_arrive(NB_LN, 288);
      float sum[2], sq[2], rstd[2];
      row_stats(hv[0], hv[1], lane, sum, sq);
#pragma unroll
      for (int r = 0; r < 2; r++) {
        const float m = sum[r] * (1.f / 512.f);
        rstd[r] = rsqrtf(fmaxf(fmaf(-m, m, sq[r] * (1.f / 512.f)), 0.f) + 1e-5f);
      }
      if (lane == 0)
        st_tag(&g_ST[rb * 64 + 8 * f + warp], make_uint4(mb[0] << 16, __float_as_uint(rstd[0]), mb[1] << 16, __float_as_uint(rstd[1])), tag);
    }
    PROF(5);
    if (NLL) {
      const uint4* const ap = &g_LN[rb * 8 * 1024 + tid];
      uint4 av[NLL ? NLL : 1][4];
      spin_cycles(POLL_DELAY3);
#pragma unroll
      for (int kb = 0; kb < NLL; kb++) ld_tag4_issue<256>(av[kb], ap + kb * 1024);
      bar_sync(NB_CONS, 256);
#pragma unroll
      for (int kb = 0; kb < NLL; kb++) {
        ld_tag4_finish<256>(av[kb], ap + kb * 1024, tag);
#pragma unroll
        for (int i = 0; i < 4; i++) sts4(sbase + kb * SLOT + (tid + 256 * i) * 16, av[kb][i].x, av[kb][i].y, av[kb][i].z, av[kb][i].w);
      }
      asm volatile("fence.proxy.async.shared::cta;" ::: "memory");
      bar_sync(NB_CONS, 256);
    }
    const int wgi = warp >> 2, wq = warp & 3;
    uint4* const pbase = &g_P[rb * 28 * 1024 + warp * 128 + lane];
    const uint32_t a_lo0 = desc_lo(sbase + wgi * 8192, 16);
    const uint32_t ebar = lane == 0 ? BAR(empty1, 0) : RBAR(empty1, 0);
    float r0, r1;
    uint4 px[8], py[6], pa[PDIST + 1][4];
    const int rh = wgi ^ kh ^ 1;
    const uint4* const psrc = &g_P[(rb2 * 28 + 14 * kh) * 1024 + (4 * rh + wq) * 128 + lane];
    {
      float acc[128];
#pragma unroll
      for (int i = 0; i < 128; i++) acc[i] = 0.f;
      const uint32_t b_lo0 = desc_lo(sbase + 8 * SLOT, 4096);
      uint32_t slot = 0, ph = 0, prev = 0;
#pragma unroll 1
      for (int kb = 0; kb < 8; kb++) {
        if (kb >= NLL) mbar_wait(BAR(fullA, kb), 0);
        if (kb == 0) PROF(6);
#pragma unroll
        for (int hh = 0; hh < 2; hh++) {
          if (LAGX && hh == ((16 - LAGX) & 1) && kb == ((16 - LAGX) >> 1) && wgi == 1) bar_sync(NB_LAG, 256);
          mbar_wait(BAR(full1, slot), ph);
          const uint32_t al = a_lo0 + kb * 1024 + hh * 4, bl = b_lo0 + slot * 1024;
          wg_fence();
          wgmma_n256(acc, desc64(al, HI128), desc64(bl, HI128));
          wgmma_n256(acc, desc64(al + 2, HI128), desc64(bl + 128, HI128));
          wg_commit();
          if (LAGX && hh == 1 && kb == 7 && wgi == 0) bar_arrive(NB_LAG, 256);
          wg_wait<1>();
          if ((kb | hh) != 0 && lane < 2) mbar_arrive_remote(ebar + 8 * prev);
          prev = slot;
          if (++slot == 6) { slot = 0; ph ^= 1; }
        }
      }
      mbar_wait(BAR(sbar, 0), 0);
      r0 = __uint_as_float(lds2(sstat + (16 * warp + g) * 8).y);
      r1 = __uint_as_float(lds2(sstat + (16 * warp + g + 8) * 8).y);
      wg_wait<0>();
      if (lane < 2) mbar_arrive_remote(ebar + 8 * prev);
      PROF(7);
      make_p<8>(acc, r0, r1, px);
    }
    PROF(8);
    {
      float acc[96];
#pragma unroll
      for (int i = 0; i < 96; i++) acc[i] = 0.f;
      const uint32_t b_lo0 = desc_lo(sbase + 8 * SLOT, 2048);
      uint4* const pdst = pbase + ((7 * f + 3 * (f & 1)) >> 1) * 1024;
#pragma unroll
      for (int k = 0; k < 16; k++) {
        if (LAGY && k == 16 - LAGY && wgi == 1) bar_sync(NB_LAG, 256);
        mbar_wait(BAR(full1, (16 + k) % 6), ((16 + k) / 6) & 1);
        const uint32_t al = a_lo0 + (k >> 1) * 1024 + (k & 1) * 4, bl = b_lo0 + ((16 + k) % 6) * 1024;
        wg_fence();
        wgmma_n192(acc, desc64(al, HI128), desc64(bl, HI64));
        wgmma_n192(acc, desc64(al + 2, HI128), desc64(bl + 64, HI64));
        wg_commit();
        if (k < 4) {
          st_tag(pdst + (k >> 1) * 1024 + (k & 1) * 64, px[2 * k], tag);
          st_tag(pdst + (k >> 1) * 1024 + (k & 1) * 64 + 32, px[2 * k + 1], tag);
        }
        if (k >= 14) ld_tag4_issue<32>(pa[k - 14], psrc + (int)((KORDER >> (4 * (k - 14))) & 15) * 1024);
        if (LAGY && k == 15 && wgi == 0) bar_arrive(NB_LAG, 256);
        wg_wait<1>();
        if (k != 0 && lane < 2) mbar_arrive_remote(ebar + 8 * ((15 + k) % 6));
      }
      wg_wait<0>();
      if (lane < 2) mbar_arrive_remote(ebar + 8 * (31 % 6));
      PROF(9);
      make_p<6>(acc, r0, r1, py);
    }
    PROF(10);
    {
      const int trow = 64 * rh + 16 * wq + g;
      const int G0 = 7 * f + ((f & 1) ? 0 : 4);
      float acc[64];
      {
        const float m0 = wgi ? __uint_as_float(lds2(sstat + 1024 + (16 * wq + g) * 8).x) : 0.f;
        const float m1 = wgi ? __uint_as_float(lds2(sstat + 1024 + (16 * wq + g + 8) * 8).x) : 0.f;
#pragma unroll
        for (int i = 0; i < 64; i++) acc[i] = (i & 2) ? m1 : m0;
      }
#pragma unroll
      for (int s = 2; s < PDIST; s++) ld_tag4_issue<32>(pa[s], psrc + (int)((KORDER >> (4 * s)) & 15) * 1024);
      const uint32_t b2_lo0 = desc_lo(sbase, 8192);
      uint4 hres[2][4];
#pragma unroll
      for (int s = 0; s < 14; s++) {
        uint4 (&a)[4] = pa[s % (PDIST + 1)];
        if (LAG2 && s == 14 - LAG2 && wgi == 1) bar_sync(NB_LAG, 256);
        ld_tag4_finish<32>(a, psrc + (int)((KORDER >> (4 * s)) & 15) * 1024, tag);
        mbar_wait(BAR(full2, s), 0);
        if (tid == 0) PROFP(16 + s);
        const uint32_t bl = b2_lo0 + s * 1024;
        wg_fence();
#pragma unroll
        for (int kk = 0; kk < 4; kk++) wgmma_rs_n128(acc, a[kk].x, a[kk].y, a[kk].z, a[kk].w, desc64(bl + kk * 128, HI128));
        wg_commit();
        if (s == 0) {
#pragma unroll
          for (int k = 0; k < 6; k++) st_tag(pbase + ((G0 + (k >> 1)) >> 1) * 1024 + ((G0 + (k >> 1)) & 1) * 64 + (k & 1) * 32, py[k], tag);
        }
        if (LAG2 && s == 13 && wgi == 0) bar_arrive(NB_LAG, 256);
        if (s == 11) {
#pragma unroll
          for (int h = 0; h < 2; h++)
#pragma unroll
            for (int q = 0; q < 4; q++) {
              hres[h][q] = ldg_cg4(&g_LN[(rb2 * 8 + 2 * nq + (q >> 1)) * 1024 + (trow + 8 * h) * 8 + ((4 * (q & 1) + t) ^ g)]);
              if (2 * nq + (q >> 1) < NLL) hres[h][q].x &= ~1u;
            }
        }
        wg_wait<1>();
        if (s + PDIST < 14) ld_tag4_issue<32>(pa[(s + PDIST) % (PDIST + 1)], psrc + (int)((KORDER >> (4 * (s + PDIST))) & 15) * 1024);
        if (lane == 0) {
          if (s < 6) mbar_arrive(BAR(prog2, s));
          if (s == 1) mbar_arrive_remote(RBAR(xfree, 0));
        }
      }
      wg_wait<0>();
      PROF(11);
      const uint32_t xbuf = sbase + (tid & 127) * 16;
      if (wgi == 0) {
        uint32_t rbuf;
        mbar_wait(BAR(xfree, 0), 0);
        asm volatile("mapa.shared::cluster.u32 %0, %1, %2;" : "=r"(rbuf) : "r"(xbuf), "r"(kh ^ 1));
#pragma unroll
        for (int i = 0; i < 8; i++)
          asm volatile("st.async.weak.shared::cluster.mbarrier::complete_tx::bytes.v4.b32 [%0], {%1,%2,%3,%4}, [%5];"
                       ::"r"(rbuf + i * 2048), "r"(pack2(acc[8 * i], acc[8 * i + 1])), "r"(pack2(acc[8 * i + 2], acc[8 * i + 3])),
                         "r"(pack2(acc[8 * i + 4], acc[8 * i + 5])), "r"(pack2(acc[8 * i + 6], acc[8 * i + 7])), "r"(RBAR(xbar, 0))
                       : "memory");
      } else {
        mbar_wait_cluster(BAR(xbar, 0), 0);
      }
      uint32_t w[2][16];
#pragma unroll
      for (int i = 0; i < 8; i++) {
        const uint4 pv = lds4(xbuf + i * 2048);
        w[0][2 * i] = pack2(acc[8 * i] + bf_lo(pv.x), acc[8 * i + 1] + bf_hi(pv.x));
        w[1][2 * i] = pack2(acc[8 * i + 2] + bf_lo(pv.y), acc[8 * i + 3] + bf_hi(pv.y));
        w[0][2 * i + 1] = pack2(acc[8 * i + 4] + bf_lo(pv.z), acc[8 * i + 5] + bf_hi(pv.z));
        w[1][2 * i + 1] = pack2(acc[8 * i + 6] + bf_lo(pv.w), acc[8 * i + 7] + bf_hi(pv.w));
      }
      uint4* const o4 = reinterpret_cast<uint4*>(out) + (16 * (c >> 4) + 2 * (4 * rh + wq) + (rb2 & 1) + 128 * g) * 64 + nq * 16 + t;
#pragma unroll
      for (int h = 0; h < 2; h++)
#pragma unroll
        for (int q = 0; q < 4; q++) {
          uint32_t a0 = w[h][4 * q], a1 = w[h][4 * q + 1], a2 = w[h][4 * q + 2], a3 = w[h][4 * q + 3];
          {
            const bool od = t & 1;
            uint32_t s0 = od ? a0 : a1, s1 = od ? a2 : a3;
            s0 = __shfl_xor_sync(0xffffffffu, s0, 1); s1 = __shfl_xor_sync(0xffffffffu, s1, 1);
            if (od) { a0 = s0; a2 = s1; } else { a1 = s0; a3 = s1; }
          }
          {
            const bool up = t & 2;
            uint32_t s0 = up ? a0 : a2, s1 = up ? a1 : a3;
            s0 = __shfl_xor_sync(0xffffffffu, s0, 2); s1 = __shfl_xor_sync(0xffffffffu, s1, 2);
            if (up) { a0 = s0; a1 = s1; } else { a2 = s0; a3 = s1; }
          }
          if (wgi == 1)
            o4[h * 1024 * 64 + 4 * q] =
                make_uint4(hadd2_bf16(hres[h][q].x, a0), hadd2_bf16(hres[h][q].y, a1), hadd2_bf16(hres[h][q].z, a2), hadd2_bf16(hres[h][q].w, a3));
        }
      PROF(12);
      PROFG(15);
    }
  }
#undef BAR
#undef TOFF
#undef RBAR
}

typedef CUresult (*EncodeFn)(CUtensorMap*, CUtensorMapDataType, cuuint32_t, void*, const cuuint64_t*, const cuuint64_t*,
                             const cuuint32_t*, const cuuint32_t*, CUtensorMapInterleave, CUtensorMapSwizzle,
                             CUtensorMapL2promotion, CUtensorMapFloatOOBfill);

}

extern "C" void kernel_launch(void* const* d_in, const int* in_sizes, int n_in, void* d_out, int out_size) {
  (void)in_sizes; (void)n_in; (void)out_size;
  static EncodeFn encode = nullptr;
  if (!encode) {
    void* fn = nullptr;
    cudaDriverEntryPointQueryResult qr;
    cudaGetDriverEntryPoint("cuTensorMapEncodeTiled", &fn, cudaEnableDefault, &qr);
    encode = (EncodeFn)fn;
    cudaFuncSetAttribute(fused_kernel, cudaFuncAttributeMaxDynamicSharedMemorySize, SMEM_BYTES);
  }
  CUtensorMap tmGX, tmUX, tmGY, tmUY, tmD, tmWR, tmWI;
  const cuuint32_t es[5] = {1, 1, 1, 1, 1};
  auto enc = [&](CUtensorMap* m, void* p, int rank, const cuuint64_t* gd, const cuuint64_t* gs, const cuuint32_t* bd,
                 CUtensorMapSwizzle sw, CUtensorMapL2promotion pr) {
    encode(m, CU_TENSOR_MAP_DATA_TYPE_BFLOAT16, rank, p, gd, gs, bd, es, CU_TENSOR_MAP_INTERLEAVE_NONE, sw, pr,
           CU_TENSOR_MAP_FLOAT_OOB_FILL_NONE);
  };
  {
    const cuuint64_t gd[3] = {64, 512, 28}, gs[2] = {3584, 128};
    const cuuint32_t bd[3] = {64, 32, 2};
    enc(&tmGX, d_in[4], 3, gd, gs, bd, CU_TENSOR_MAP_SWIZZLE_128B, CU_TENSOR_MAP_L2_PROMOTION_L2_256B);
    enc(&tmUX, d_in[5], 3, gd, gs, bd, CU_TENSOR_MAP_SWIZZLE_128B, CU_TENSOR_MAP_L2_PROMOTION_L2_256B);
  }
  {
    const cuuint64_t gd[3] = {32, 512, 56}, gs[2] = {3584, 64};
    const cuuint32_t bd[3] = {32, 32, 3};
    enc(&tmGY, d_in[4], 3, gd, gs, bd, CU_TENSOR_MAP_SWIZZLE_64B, CU_TENSOR_MAP_L2_PROMOTION_L2_128B);
    enc(&tmUY, d_in[5], 3, gd, gs, bd, CU_TENSOR_MAP_SWIZZLE_64B, CU_TENSOR_MAP_L2_PROMOTION_L2_128B);
  }
  {
    const cuuint64_t gd[3] = {64, 1792, 8}, gs[2] = {1024, 128};
    const cuuint32_t bd[3] = {64, 64, 2};
    enc(&tmD, d_in[6], 3, gd, gs, bd, CU_TENSOR_MAP_SWIZZLE_128B, CU_TENSOR_MAP_L2_PROMOTION_L2_256B);
  }
  {
    const cuuint64_t gd[3] = {4112, 8, 16}, gs[2] = {16 * 8224, 8224};
    const cuuint32_t bd[3] = {40, 8, 16};
    enc(&tmWR, d_in[1], 3, gd, gs, bd, CU_TENSOR_MAP_SWIZZLE_NONE, CU_TENSOR_MAP_L2_PROMOTION_NONE);
    enc(&tmWI, d_in[2], 3, gd, gs, bd, CU_TENSOR_MAP_SWIZZLE_NONE, CU_TENSOR_MAP_L2_PROMOTION_NONE);
  }
  fused_kernel<<<NCTA, NTHREADS, SMEM_BYTES>>>(tmGX, tmUX, tmGY, tmUY, tmD, tmWR, tmWI, (const __nv_bfloat16*)d_in[0],
                                               (const char*)d_in[4], (const char*)d_in[5], (const char*)d_in[6],
                                               (__nv_bfloat16*)d_out);
}
```

```cpp
#include <cuda_runtime.h>
#include <cuda_bf16.h>
#include <cuda.h>
#include <stdint.h>

namespace {

constexpr int NCTA = 128;
constexpr int NTHREADS = 384;
constexpr int SLOT = 16384;
constexpr int SMEM_BYTES = 14 * SLOT + 2048 + 1024;
constexpr int SPIN_LIMIT = 1 << 22;

__device__ uint4 g_Z1[128 * 1024];
__device__ uint4 g_Z2[128 * 1024];
__device__ uint4 g_LN[16 * 8 * 1024];
__device__ uint4 g_ST[1024];
__device__ uint4 g_P[16 * 28 * 1024];
__device__ unsigned g_cnt[64 * 32];
#define PROF(i)
#define PROFP(i)
#define PROFG(i)

constexpr double ccos(int i, int n) {
  i &= n - 1;
  if (i > n / 2) i = n - i;
  if (4 * i == n) return 0.0;
  const bool neg = 4 * i > n;
  if (neg) i = n / 2 - i;
  const double a = 6.283185307179586476925 * i / n, a2 = a * a;
  double term = 1.0, sum = 1.0;
  for (int k = 1; k < 14; k++) { term *= -a2 / ((2 * k - 1) * (2 * k)); sum += term; }
  return neg ? -sum : sum;
}
constexpr double csin(int i, int n) { return ccos(i - n / 4, n); }
constexpr unsigned fbits(double v, int mant) {
  if (v == 0.0) return 0;
  const unsigned sg = v < 0 ? 1u : 0u;
  if (v < 0) v = -v;
  int e = 127;
  while (v < 1.0) { v *= 2.0; e--; }
  const unsigned m = (unsigned)((v - 1.0) * (double)(1u << mant) + 0.5);
  return (sg << (8 + mant)) + ((unsigned)e << mant) + m;
}
constexpr unsigned pkb(double lo, double hi) { return fbits(lo, 7) | (fbits(hi, 7) << 16); }
constexpr double fa_elem(int kp, int n1) {
  return kp <= 8 ? ccos(kp * n1, 16) : -csin((kp - 8) * n1, 16);
}
constexpr unsigned cfrag_c(int idx, int n, int ri) {
  return ri ? pkb(-csin(idx, n), ccos(idx, n)) : pkb(ccos(idx, n), csin(idx, n));
}
struct Tables {
  unsigned fb[16][32][4];
  unsigned tw1[8][32][4];
  unsigned fa[32][4];
  unsigned f2[8][4][32][4];
  unsigned g2[8][4][32][4];
  unsigned gb[16][32][4];
  unsigned tw3[4][32][4];
  unsigned ga[32][4];
  unsigned f8[32][4], g8[32][4];
};
constexpr int T1_BYTES = 12800, T2_BYTES = 44544;
static_assert(sizeof(Tables) == T1_BYTES + T2_BYTES, "table size");
constexpr Tables make_tables() {
  Tables T = {};
  for (int l = 0; l < 32; l++) {
    const int g = l >> 2, t = l & 3;
    for (int i = 0; i < 4; i++)
      for (int u = 0; u < 8; u++) {
        const int ri = g & 1, m = 2 * (g >> 1) + ((u & 3) >> 1);
        const double sg = u >= 4 ? -1.0 : 1.0;
        const int k2 = u >= 4 ? 31 - 2 * m - (u & 1) : 2 * m + (u & 1);
        const int pa = (8 * t + i) * k2, pb = (8 * t + 4 + i) * k2;
        T.fb[i * 4 + (u >> 1)][l][(u & 1) * 2 + 0] = ri == 0 ? pkb(ccos(pa, 32), ccos(pb, 32)) : pkb(-sg * csin(pa, 32), -sg * csin(pb, 32));
        T.fb[i * 4 + (u >> 1)][l][(u & 1) * 2 + 1] = ri == 0 ? pkb(csin(pa, 32), csin(pb, 32)) : pkb(sg * ccos(pa, 32), sg * ccos(pb, 32));
      }
    for (int i = 0; i < 4; i++)
      for (int ks = 0; ks < 4; ks++) {
        const int n2 = 4 * g + i, m = 2 * t + (ks & 1);
        const double sg = ks >= 2 ? -1.0 : 1.0;
        const int pa = n2 * (ks >= 2 ? 31 - 2 * m : 2 * m), pb = n2 * (ks >= 2 ? 30 - 2 * m : 2 * m + 1);
        T.gb[i * 4 + ks][l][0] = pkb(ccos(pa, 32), -sg * csin(pa, 32));
        T.gb[i * 4 + ks][l][1] = pkb(csin(pa, 32), sg * ccos(pa, 32));
        T.gb[i * 4 + ks][l][2] = pkb(ccos(pb, 32), -sg * csin(pb, 32));
        T.gb[i * 4 + ks][l][3] = pkb(csin(pb, 32), sg * ccos(pb, 32));
      }
    for (int i = 0; i < 4; i++) {
      for (int e = 0; e < 2; e++) {
        const int p = (8 * t + 4 * e + i) * (g == 0 ? 8 : g);
        T.tw1[2 * i + e][l][0] = fbits(g == 0 ? 0.0 : ccos(p, 512), 23);
        T.tw1[2 * i + e][l][1] = fbits(g == 0 ? ccos(p, 512) : csin(p, 512), 23);
        T.tw1[2 * i + e][l][2] = fbits(g == 0 ? 0.0 : -csin(p, 512), 23);
        T.tw1[2 * i + e][l][3] = fbits(g == 0 ? -csin(p, 512) : ccos(p, 512), 23);
      }
      const int ka = t == 0 ? 8 : 2 * t, kb = 2 * t + 1;
      T.tw3[i][l][0] = fbits(ccos((4 * g + i) * ka, 512), 23);
      T.tw3[i][l][1] = fbits(csin((4 * g + i) * ka, 512), 23);
      T.tw3[i][l][2] = fbits(ccos((4 * g + i) * kb, 512), 23);
      T.tw3[i][l][3] = fbits(csin((4 * g + i) * kb, 512), 23);
      const int p8 = (t + 4 * (i & 1)) * (4 * (i >> 1) + (g >> 1));
      T.f8[l][i] = cfrag_c(p8, 8, g & 1);
      T.g8[l][i] = cfrag_c(-p8, 8, g & 1);
    }
    for (int w = 0; w < 8; w++)
      for (int i = 0; i < 16; i++) {
        const int kidx = t + 4 * (i & 1) + 8 * (i >> 3), nidx = 4 * ((i >> 1) & 3) + (g >> 1);
        T.f2[w][i >> 2][l][i & 3] = cfrag_c((8 * kidx + w) * nidx, 128, g & 1);
        T.g2[w][i >> 2][l][i & 3] = cfrag_c(-(8 * nidx + w) * kidx, 128, g & 1);
      }
    T.fa[l][0] = pkb(fa_elem(g, 2 * t), fa_elem(g, 2 * t + 1));
    T.fa[l][1] = pkb(fa_elem(g + 8, 2 * t), fa_elem(g + 8, 2 * t + 1));
    T.fa[l][2] = pkb(fa_elem(g, 2 * t + 8), fa_elem(g, 2 * t + 9));
    T.fa[l][3] = pkb(fa_elem(g + 8, 2 * t + 8), fa_elem(g + 8, 2 * t + 9));
    T.ga[l][0] = pkb(fa_elem(2 * t, g), fa_elem(2 * t + 1, g));
    T.ga[l][1] = pkb(fa_elem(2 * t, g + 8), fa_elem(2 * t + 1, g + 8));
    T.ga[l][2] = pkb(fa_elem(2 * t + 8, g), fa_elem(2 * t + 9, g));
    T.ga[l][3] = pkb(fa_elem(2 * t + 8, g + 8), fa_elem(2 * t + 9, g + 8));
  }
  return T;
}
__device__ const __align__(128) Tables g_tab = make_tables();

__device__ __forceinline__ void die() { asm volatile("st.global.u32 [%0], %1;" ::"l"(0ull), "r"(0) : "memory"); }
__device__ __forceinline__ uint32_t s2u(const void* p) { return (uint32_t)__cvta_generic_to_shared(p); }
__device__ __forceinline__ void mbar_init(uint32_t b, int c) { asm volatile("mbarrier.init.shared::cta.b64 [%0], %1;" ::"r"(b), "r"(c)); }
__device__ __forceinline__ void mbar_expect(uint32_t b, int bytes) {
  asm volatile("mbarrier.arrive.expect_tx.shared::cta.b64 _, [%0], %1;" ::"r"(b), "r"(bytes) : "memory");
}
__device__ __forceinline__ void mbar_arrive(uint32_t b) { asm volatile("mbarrier.arrive.shared::cta.b64 _, [%0];" ::"r"(b) : "memory"); }
__device__ __forceinline__ uint32_t mbar_try(uint32_t b, uint32_t parity) {
  uint32_t ok;
  asm volatile("{.reg .pred p; mbarrier.try_wait.parity.shared::cta.b64 p, [%1], %2; selp.u32 %0,1,0,p;}"
               : "=r"(ok) : "r"(b), "r"(parity) : "memory");
  return ok;
}
__device__ __forceinline__ void mbar_wait(uint32_t b, uint32_t parity) {
  int it = 0;
#pragma unroll 1
  while (!mbar_try(b, parity))
    if (++it > SPIN_LIMIT) { die(); break; }
}
__device__ __forceinline__ void mbar_wait_cluster(uint32_t b, int parity) {
  uint32_t ok;
  int it = 0;
  do {
    asm volatile("{.reg .pred p; mbarrier.try_wait.parity.acquire.cluster.shared::cta.b64 p, [%1], %2; selp.u32 %0,1,0,p;}"
                 : "=r"(ok) : "r"(b), "r"(parity) : "memory");
    if (++it > SPIN_LIMIT) { die(); break; }
  } while (!ok);
}
__device__ __forceinline__ void bar_sync(int id, int n) { asm volatile("bar.sync %0, %1;" ::"r"(id), "r"(n) : "memory"); }
__device__ __forceinline__ void bar_arrive(int id, int n) { asm volatile("bar.arrive %0, %1;" ::"r"(id), "r"(n) : "memory"); }
__device__ __forceinline__ void red_release(unsigned* p) { asm volatile("red.release.gpu.global.add.u32 [%0], 1;" ::"l"(p) : "memory"); }
__device__ __forceinline__ void red_relaxed(unsigned* p) { asm volatile("red.relaxed.gpu.global.add.u32 [%0], 1;" ::"l"(p) : "memory"); }
__device__ __forceinline__ unsigned ld_acquire(const unsigned* p) {
  unsigned v;
  asm volatile("ld.acquire.gpu.global.u32 %0, [%1];" : "=r"(v) : "l"(p) : "memory");
  return v;
}
__device__ __forceinline__ unsigned ld_relaxed(const unsigned* p) {
  unsigned v;
  asm volatile("ld.relaxed.gpu.global.u32 %0, [%1];" : "=r"(v) : "l"(p) : "memory");
  return v;
}
__device__ __forceinline__ void wait_counter(const unsigned* p, unsigned target) {
  int it = 0;
  while ((int)(ld_acquire(p) - target) < 0)
    if (++it > SPIN_LIMIT) { die(); break; }
}
__device__ __forceinline__ void sts4(uint32_t a, uint32_t x, uint32_t y, uint32_t z, uint32_t w) {
  asm volatile("st.shared.v4.u32 [%0], {%1,%2,%3,%4};" ::"r"(a), "r"(x), "r"(y), "r"(z), "r"(w) : "memory");
}
__device__ __forceinline__ uint4 lds4(uint32_t a) {
  uint4 v;
  asm volatile("ld.shared.v4.u32 {%0,%1,%2,%3}, [%4];" : "=r"(v.x), "=r"(v.y), "=r"(v.z), "=r"(v.w) : "r"(a) : "memory");
  return v;
}
__device__ __forceinline__ uint32_t pack2(float lo, float hi) {
  uint32_t r;
  asm("cvt.rn.bf16x2.f32 %0, %1, %2;" : "=r"(r) : "f"(hi), "f"(lo));
  return r;
}
__device__ __forceinline__ float bf_lo(uint32_t v) { return __uint_as_float(v << 16); }
__device__ __forceinline__ float bf_hi(uint32_t v) { return __uint_as_float(v & 0xffff0000u); }
__device__ __forceinline__ uint32_t hadd2_bf16(uint32_t a, uint32_t b) {
  uint32_t r;
  asm("add.rn.bf16x2 %0, %1, %2;" : "=r"(r) : "r"(a), "r"(b));
  return r;
}
__device__ __forceinline__ void mma16816(float (&d)[4], uint32_t a0, uint32_t a1, uint32_t a2, uint32_t a3, uint32_t b0, uint32_t b1) {
  asm("mma.sync.aligned.m16n8k16.row.col.f32.bf16.bf16.f32 {%0,%1,%2,%3}, {%4,%5,%6,%7}, {%8,%9}, {%0,%1,%2,%3};"
      : "+f"(d[0]), "+f"(d[1]), "+f"(d[2]), "+f"(d[3])
      : "r"(a0), "r"(a1), "r"(a2), "r"(a3), "r"(b0), "r"(b1));
}
template <int N>
__device__ __forceinline__ void cs_frac(int idx, float& c, float& s) {
  int i = ((idx + N / 2) & (N - 1)) - N / 2;
  float a = (float)i * (6.283185307179586f / N);
  c = __cosf(a);
  s = __sinf(a);
}
template <int N>
__device__ __forceinline__ uint32_t cfrag(int idx, int ri) {
  float c, s;
  cs_frac<N>(idx, c, s);
  return ri ? pack2(-s, c) : pack2(c, s);
}
__device__ __forceinline__ uint32_t word(const uint4& v, int e) { return e == 0 ? v.x : e == 1 ? v.y : e == 2 ? v.z : v.w; }
__device__ __forceinline__ void cdft16(const uint4 (&q)[4], const uint4 (&F)[4], uint4 (&o)[4]) {
  float acc[2][4][4];
#pragma unroll
  for (int p = 0; p < 2; p++)
#pragma unroll
    for (int v = 0; v < 4; v++) {
      acc[p][v][0] = acc[p][v][1] = acc[p][v][2] = acc[p][v][3] = 0.f;
#pragma unroll
      for (int ks = 0; ks < 2; ks++)
        mma16816(acc[p][v], word(q[2 * ks], 2 * p), word(q[2 * ks], 2 * p + 1), word(q[2 * ks + 1], 2 * p),
                 word(q[2 * ks + 1], 2 * p + 1), word(F[ks * 2 + (v >> 1)], (v & 1) * 2), word(F[ks * 2 + (v >> 1)], (v & 1) * 2 + 1));
    }
#pragma unroll
  for (int v = 0; v < 4; v++)
    o[v] = make_uint4(pack2(acc[0][v][0], acc[0][v][1]), pack2(acc[0][v][2], acc[0][v][3]),
                      pack2(acc[1][v][0], acc[1][v][1]), pack2(acc[1][v][2], acc[1][v][3]));
}
__device__ __forceinline__ void st_tag(uint4* p, const uint4& v, uint32_t tag) {
  asm volatile("{.reg .b128 r; .reg .b64 a, b; mov.b64 a, {%1,%2}; mov.b64 b, {%3,%4}; mov.b128 r, {a,b}; st.relaxed.gpu.global.b128 [%0], r;}"
               ::"l"(p), "r"((v.x & ~1u) | tag), "r"(v.y), "r"(v.z), "r"(v.w) : "memory");
}
__device__ __forceinline__ uint4 ld_b128(const uint4* p) {
  uint4 v;
  asm volatile("{.reg .b128 r; .reg .b64 a, b; ld.relaxed.gpu.global.b128 r, [%4]; mov.b128 {a,b}, r; mov.b64 {%0,%1}, a; mov.b64 {%2,%3}, b;}"
               : "=r"(v.x), "=r"(v.y), "=r"(v.z), "=r"(v.w) : "l"(p) : "memory");
  return v;
}
template <int STRIDE>
__device__ __forceinline__ void ld_tag4_issue(uint4 (&q)[4], const uint4* p) {
#pragma unroll
  for (int i = 0; i < 4; i++) q[i] = ld_b128(p + i * STRIDE);
}
template <int STRIDE>
__device__ __forceinline__ void ld_tag4_finish(uint4 (&q)[4], const uint4* p, uint32_t tag) {
  int it = 0;
#pragma unroll 1
  while (__any_sync(0xffffffffu, ((q[0].x ^ tag) | (q[1].x ^ tag) | (q[2].x ^ tag) | (q[3].x ^ tag)) & 1u)) {
    ld_tag4_issue<STRIDE>(q, p);
    if (++it > SPIN_LIMIT) { die(); break; }
  }
#pragma unroll
  for (int i = 0; i < 4; i++) asm volatile("and.b32 %0, %0, 0xfffffffe;" : "+r"(q[i].x));
}
__device__ __forceinline__ void row_stats(const uint32_t (&a)[8], const uint32_t (&b)[8], int lane, float (&sum)[2], float (&sq)[2]) {
  float da[4] = {0.f, 0.f, 0.f, 0.f}, db[4] = {0.f, 0.f, 0.f, 0.f}, ds[4] = {0.f, 0.f, 0.f, 0.f};
#pragma unroll
  for (int q = 0; q < 4; q++) {
    mma16816(ds, a[2 * q], b[2 * q], a[2 * q + 1], b[2 * q + 1], 0x3f803f80u, 0x3f803f80u);
    mma16816(da, a[2 * q], b[2 * q], a[2 * q + 1], b[2 * q + 1], a[2 * q], a[2 * q + 1]);
    mma16816(db, a[2 * q], b[2 * q], a[2 * q + 1], b[2 * q + 1], b[2 * q], b[2 * q + 1]);
  }
  const int src = (lane & 28) | (lane >> 3);
  const float qa = __shfl_sync(0xffffffffu, (lane & 4) ? da[1] : da[0], src);
  const float qb = __shfl_sync(0xffffffffu, (lane & 4) ? db[3] : db[2], src);
  float v = (lane & 2) ? ((lane & 1) ? ds[2] : ds[0]) : ((lane & 1) ? qb : qa);
  v += __shfl_xor_sync(0xffffffffu, v, 4);
  v += __shfl_xor_sync(0xffffffffu, v, 8);
  v += __shfl_xor_sync(0xffffffffu, v, 16);
  sq[0] = __shfl_sync(0xffffffffu, v, 0);
  sq[1] = __shfl_sync(0xffffffffu, v, 1);
  sum[0] = __shfl_sync(0xffffffffu, v, 2);
  sum[1] = __shfl_sync(0xffffffffu, v, 3);
}
__device__ __forceinline__ uint64_t desc64(uint32_t lo, uint32_t hi) {
  uint64_t d;
  asm("mov.b64 %0, {%1, %2};" : "=l"(d) : "r"(lo), "r"(hi));
  return d;
}
constexpr uint32_t desc_hi(uint32_t sbo, uint32_t swz) { return (sbo >> 4) | (swz << 30); }
__device__ __forceinline__ uint32_t desc_lo(uint32_t addr, uint32_t lbo) { return ((addr & 0x3FFFF) >> 4) | ((lbo >> 4) << 16); }
__device__ __forceinline__ void cp_async16(uint32_t dst, const void* src) {
  asm volatile("cp.async.cg.shared.global [%0], [%1], 16;" ::"r"(dst), "l"(src) : "memory");
}
__device__ __forceinline__ uint2 lds2(uint32_t a) {
  uint2 v;
  asm volatile("ld.shared.v2.u32 {%0,%1}, [%2];" : "=r"(v.x), "=r"(v.y) : "r"(a) : "memory");
  return v;
}
__device__ __forceinline__ uint32_t lds_u16(uint32_t a) {
  uint16_t v;
  asm volatile("ld.shared.u16 %0, [%1];" : "=h"(v) : "r"(a) : "memory");
  return v;
}
__device__ __forceinline__ void wg_fence() { asm volatile("wgmma.fence.sync.aligned;" ::: "memory"); }
__device__ __forceinline__ void wg_commit() { asm volatile("wgmma.commit_group.sync.aligned;" ::: "memory"); }
template <int N>
__device__ __forceinline__ void wg_wait() { asm volatile("wgmma.wait_group.sync.aligned %0;" ::"n"(N) : "memory"); }
__device__ __forceinline__ void bulk_load(uint32_t dst, const void* src, int bytes, uint32_t bar) {
  asm volatile("cp.async.bulk.shared::cluster.global.mbarrier::complete_tx::bytes [%0], [%1], %2, [%3];"
               ::"r"(dst), "l"(src), "r"(bytes), "r"(bar) : "memory");
}
__device__ __forceinline__ void tma3(uint32_t dst, const CUtensorMap* tm, uint32_t bar, int c0, int c1, int c2) {
  asm volatile("cp.async.bulk.tensor.3d.shared::cluster.global.mbarrier::complete_tx::bytes [%0], [%1, {%3,%4,%5}], [%2];"
               ::"r"(dst), "l"(tm), "r"(bar), "r"(c0), "r"(c1), "r"(c2) : "memory");
}
__device__ __forceinline__ void tma3_mc(uint32_t dst, const CUtensorMap* tm, uint32_t bar, int c1, int c2) {
  asm volatile("cp.async.bulk.tensor.3d.shared::cluster.global.mbarrier::complete_tx::bytes.multicast::cluster [%0], [%1, {%3,%4,%5}], [%2], %6;"
               ::"r"(dst), "l"(tm), "r"(bar), "r"(0), "r"(c1), "r"(c2), "h"((uint16_t)3) : "memory");
}
__device__ __forceinline__ void mbar_arrive_remote(uint32_t rb) {
  asm volatile("mbarrier.arrive.shared::cluster.b64 _, [%0];" ::"r"(rb) : "memory");
}
__device__ __forceinline__ uint4 ldg_ca4(const void* p) {
  uint4 v;
  asm volatile("ld.global.ca.v4.u32 {%0,%1,%2,%3}, [%4];" : "=r"(v.x), "=r"(v.y), "=r"(v.z), "=r"(v.w) : "l"(p) : "memory");
  return v;
}
__device__ __forceinline__ uint32_t clock32() {
  uint32_t v;
  asm volatile("mov.u32 %0, %%clock;" : "=r"(v) :: "memory");
  return v;
}
__device__ __forceinline__ float swiglu(float g, float u, float r) {
  float hg = (0.5f * r) * g, th;
  asm("tanh.approx.f32 %0, %1;" : "=f"(th) : "f"(hg));
  return fmaf(hg, th, hg) * (r * u);
}
__device__ __forceinline__ uint32_t hsub2_bf16(uint32_t a, uint32_t b) {
  uint32_t r;
  asm("sub.rn.bf16x2 %0, %1, %2;" : "=r"(r) : "r"(a), "r"(b));
  return r;
}
__device__ __forceinline__ void l2_prefetch(const void* p, int bytes) {
  asm volatile("cp.async.bulk.prefetch.L2.global [%0], %1;" ::"l"(p), "r"(bytes) : "memory");
}

__device__ __forceinline__ void wgmma_n256(float (&d)[128], uint64_t da, uint64_t db) {
  asm volatile("wgmma.mma_async.sync.aligned.m64n256k16.f32.bf16.bf16 {"
      "%0,%1,%2,%3,%4,%5,%6,%7,%8,%9,%10,%11,%12,%13,%14,%15,"
      "%16,%17,%18,%19,%20,%21,%22,%23,%24,%25,%26,%27,%28,%29,%30,%31,"
      "%32,%33,%34,%35,%36,%37,%38,%39,%40,%41,%42,%43,%44,%45,%46,%47,"
      "%48,%49,%50,%51,%52,%53,%54,%55,%56,%57,%58,%59,%60,%61,%62,%63,"
      "%64,%65,%66,%67,%68,%69,%70,%71,%72,%73,%74,%75,%76,%77,%78,%79,"
      "%80,%81,%82,%83,%84,%85,%86,%87,%88,%89,%90,%91,%92,%93,%94,%95,"
      "%96,%97,%98,%99,%100,%101,%102,%103,%104,%105,%106,%107,%108,%109,%110,%111,"
      "%112,%113,%114,%115,%116,%117,%118,%119,%120,%121,%122,%123,%124,%125,%126,%127"
      "}, %128, %129, 1, 1, 1, 0, 1;\n"
      : "+f"(d[0]),"+f"(d[1]),"+f"(d[2]),"+f"(d[3]),"+f"(d[4]),"+f"(d[5]),"+f"(d[6]),"+f"(d[7]),
        "+f"(d[8]),"+f"(d[9]),"+f"(d[10]),"+f"(d[11]),"+f"(d[12]),"+f"(d[13]),"+f"(d[14]),"+f"(d[15]),
        "+f"(d[16]),"+f"(d[17]),"+f"(d[18]),"+f"(d[19]),"+f"(d[20]),"+f"(d[21]),"+f"(d[22]),"+f"(d[23]),
        "+f"(d[24]),"+f"(d[25]),"+f"(d[26]),"+f"(d[27]),"+f"(d[28]),"+f"(d[29]),"+f"(d[30]),"+f"(d[31]),
        "+f"(d[32]),"+f"(d[33]),"+f"(d[34]),"+f"(d[35]),"+f"(d[36]),"+f"(d[37]),"+f"(d[38]),"+f"(d[39]),
        "+f"(d[40]),"+f"(d[41]),"+f"(d[42]),"+f"(d[43]),"+f"(d[44]),"+f"(d[45]),"+f"(d[46]),"+f"(d[47]),
        "+f"(d[48]),"+f"(d[49]),"+f"(d[50]),"+f"(d[51]),"+f"(d[52]),"+f"(d[53]),"+f"(d[54]),"+f"(d[55]),
        "+f"(d[56]),"+f"(d[57]),"+f"(d[58]),"+f"(d[59]),"+f"(d[60]),"+f"(d[61]),"+f"(d[62]),"+f"(d[63]),
        "+f"(d[64]),"+f"(d[65]),"+f"(d[66]),"+f"(d[67]),"+f"(d[68]),"+f"(d[69]),"+f"(d[70]),"+f"(d[71]),
        "+f"(d[72]),"+f"(d[73]),"+f"(d[74]),"+f"(d[75]),"+f"(d[76]),"+f"(d[77]),"+f"(d[78]),"+f"(d[79]),
        "+f"(d[80]),"+f"(d[81]),"+f"(d[82]),"+f"(d[83]),"+f"(d[84]),"+f"(d[85]),"+f"(d[86]),"+f"(d[87]),
        "+f"(d[88]),"+f"(d[89]),"+f"(d[90]),"+f"(d[91]),"+f"(d[92]),"+f"(d[93]),"+f"(d[94]),"+f"(d[95]),
        "+f"(d[96]),"+f"(d[97]),"+f"(d[98]),"+f"(d[99]),"+f"(d[100]),"+f"(d[101]),"+f"(d[102]),"+f"(d[103]),
        "+f"(d[104]),"+f"(d[105]),"+f"(d[106]),"+f"(d[107]),"+f"(d[108]),"+f"(d[109]),"+f"(d[110]),"+f"(d[111]),
        "+f"(d[112]),"+f"(d[113]),"+f"(d[114]),"+f"(d[115]),"+f"(d[116]),"+f"(d[117]),"+f"(d[118]),"+f"(d[119]),
        "+f"(d[120]),"+f"(d[121]),"+f"(d[122]),"+f"(d[123]),"+f"(d[124]),"+f"(d[125]),"+f"(d[126]),"+f"(d[127])
      : "l"(da), "l"(db));
}
__device__ __forceinline__ void wgmma_n192(float (&d)[96], uint64_t da, uint64_t db) {
  asm volatile("wgmma.mma_async.sync.aligned.m64n192k16.f32.bf16.bf16 {"
      "%0,%1,%2,%3,%4,%5,%6,%7,%8,%9,%10,%11,%12,%13,%14,%15,"
      "%16,%17,%18,%19,%20,%21,%22,%23,%24,%25,%26,%27,%28,%29,%30,%31,"
      "%32,%33,%34,%35,%36,%37,%38,%39,%40,%41,%42,%43,%44,%45,%46,%47,"
      "%48,%49,%50,%51,%52,%53,%54,%55,%56,%57,%58,%59,%60,%61,%62,%63,"
      "%64,%65,%66,%67,%68,%69,%70,%71,%72,%73,%74,%75,%76,%77,%78,%79,"
      "%80,%81,%82,%83,%84,%85,%86,%87,%88,%89,%90,%91,%92,%93,%94,%95"
      "}, %96, %97, 1, 1, 1, 0, 1;\n"
      : "+f"(d[0]),"+f"(d[1]),"+f"(d[2]),"+f"(d[3]),"+f"(d[4]),"+f"(d[5]),"+f"(d[6]),"+f"(d[7]),
        "+f"(d[8]),"+f"(d[9]),"+f"(d[10]),"+f"(d[11]),"+f"(d[12]),"+f"(d[13]),"+f"(d[14]),"+f"(d[15]),
        "+f"(d[16]),"+f"(d[17]),"+f"(d[18]),"+f"(d[19]),"+f"(d[20]),"+f"(d[21]),"+f"(d[22]),"+f"(d[23]),
        "+f"(d[24]),"+f"(d[25]),"+f"(d[26]),"+f"(d[27]),"+f"(d[28]),"+f"(d[29]),"+f"(d[30]),"+f"(d[31]),
        "+f"(d[32]),"+f"(d[33]),"+f"(d[34]),"+f"(d[35]),"+f"(d[36]),"+f"(d[37]),"+f"(d[38]),"+f"(d[39]),
        "+f"(d[40]),"+f"(d[41]),"+f"(d[42]),"+f"(d[43]),"+f"(d[44]),"+f"(d[45]),"+f"(d[46]),"+f"(d[47]),
        "+f"(d[48]),"+f"(d[49]),"+f"(d[50]),"+f"(d[51]),"+f"(d[52]),"+f"(d[53]),"+f"(d[54]),"+f"(d[55]),
        "+f"(d[56]),"+f"(d[57]),"+f"(d[58]),"+f"(d[59]),"+f"(d[60]),"+f"(d[61]),"+f"(d[62]),"+f"(d[63]),
        "+f"(d[64]),"+f"(d[65]),"+f"(d[66]),"+f"(d[67]),"+f"(d[68]),"+f"(d[69]),"+f"(d[70]),"+f"(d[71]),
        "+f"(d[72]),"+f"(d[73]),"+f"(d[74]),"+f"(d[75]),"+f"(d[76]),"+f"(d[77]),"+f"(d[78]),"+f"(d[79]),
        "+f"(d[80]),"+f"(d[81]),"+f"(d[82]),"+f"(d[83]),"+f"(d[84]),"+f"(d[85]),"+f"(d[86]),"+f"(d[87]),
        "+f"(d[88]),"+f"(d[89]),"+f"(d[90]),"+f"(d[91]),"+f"(d[92]),"+f"(d[93]),"+f"(d[94]),"+f"(d[95])
      : "l"(da), "l"(db));
}
__device__ __forceinline__ void wgmma_rs_n128(float (&d)[64], uint32_t a0, uint32_t a1, uint32_t a2, uint32_t a3, uint64_t db) {
  asm volatile("wgmma.mma_async.sync.aligned.m64n128k16.f32.bf16.bf16 {"
      "%0,%1,%2,%3,%4,%5,%6,%7,%8,%9,%10,%11,%12,%13,%14,%15,"
      "%16,%17,%18,%19,%20,%21,%22,%23,%24,%25,%26,%27,%28,%29,%30,%31,"
      "%32,%33,%34,%35,%36,%37,%38,%39,%40,%41,%42,%43,%44,%45,%46,%47,"
      "%48,%49,%50,%51,%52,%53,%54,%55,%56,%57,%58,%59,%60,%61,%62,%63"
      "}, {%64,%65,%66,%67}, %68, 1, 1, 1, 1;\n"
      : "+f"(d[0]),"+f"(d[1]),"+f"(d[2]),"+f"(d[3]),"+f"(d[4]),"+f"(d[5]),"+f"(d[6]),"+f"(d[7]),
        "+f"(d[8]),"+f"(d[9]),"+f"(d[10]),"+f"(d[11]),"+f"(d[12]),"+f"(d[13]),"+f"(d[14]),"+f"(d[15]),
        "+f"(d[16]),"+f"(d[17]),"+f"(d[18]),"+f"(d[19]),"+f"(d[20]),"+f"(d[21]),"+f"(d[22]),"+f"(d[23]),
        "+f"(d[24]),"+f"(d[25]),"+f"(d[26]),"+f"(d[27]),"+f"(d[28]),"+f"(d[29]),"+f"(d[30]),"+f"(d[31]),
        "+f"(d[32]),"+f"(d[33]),"+f"(d[34]),"+f"(d[35]),"+f"(d[36]),"+f"(d[37]),"+f"(d[38]),"+f"(d[39]),
        "+f"(d[40]),"+f"(d[41]),"+f"(d[42]),"+f"(d[43]),"+f"(d[44]),"+f"(d[45]),"+f"(d[46]),"+f"(d[47]),
        "+f"(d[48]),"+f"(d[49]),"+f"(d[50]),"+f"(d[51]),"+f"(d[52]),"+f"(d[53]),"+f"(d[54]),"+f"(d[55]),
        "+f"(d[56]),"+f"(d[57]),"+f"(d[58]),"+f"(d[59]),"+f"(d[60]),"+f"(d[61]),"+f"(d[62]),"+f"(d[63])
      : "r"(a0), "r"(a1), "r"(a2), "r"(a3), "l"(db));
}

constexpr int C_LN = 0, C_PX = 16, C_PY = 32;
constexpr int NB_CONS = 1, NB_LN = 2, NB_LAG = 4, NB_INIT = 6, NB_RDY = 7;
#define LAGX 3
#define LAGY 3
#define LAG2 4
#define NLL 2
#define POLL_DELAY3 900
#define POLL_DELAY 900
#define PF2_SIG 1
constexpr int SM_E = 0, SM_X = 16384, SM_FC = 32768, SM_T = 36864, SM_E2 = 131072, SM_W = 147456;
constexpr unsigned long long KORDER = 0xBA9432DC876510ull;
constexpr uint32_t HI128 = desc_hi(1024, 1), HI64 = desc_hi(512, 2);

struct Bars {
  uint64_t full1[6], empty1[6], fullA[8], full2[14], empty2[8], xbar, xfree, hbar, tbar, sbar, sig[2];
  uint32_t epoch;
};

template <int NK>
__device__ __forceinline__ void make_p(const float (&acc)[NK * 16], float r0, float r1, uint4 (&p)[NK]) {
#pragma unroll
  for (int j = 0; j < NK; j++) {
    uint32_t w[4];
#pragma unroll
    for (int i = 0; i < 4; i++) {
      const int a = 8 * j + 2 * i, b = a + NK * 8;
      w[i] = pack2(swiglu(acc[a], acc[b], (i & 1) ? r1 : r0), swiglu(acc[a + 1], acc[b + 1], (i & 1) ? r1 : r0));
    }
    asm volatile("" : "+r"(w[0]), "+r"(w[1]), "+r"(w[2]), "+r"(w[3]));
    p[j] = make_uint4(w[0], w[1], w[2], w[3]);
  }
}
__device__ __forceinline__ void spin_cycles(uint32_t n) {
  const uint32_t t0 = clock32();
  while (clock32() - t0 < n) {}
}

__global__ void __cluster_dims__(2, 1, 1) __launch_bounds__(NTHREADS, 1)
fused_kernel(const __grid_constant__ CUtensorMap tmGX, const __grid_constant__ CUtensorMap tmUX,
             const __grid_constant__ CUtensorMap tmGY, const __grid_constant__ CUtensorMap tmUY,
             const __grid_constant__ CUtensorMap tmD, const __grid_constant__ CUtensorMap tmWR,
             const __grid_constant__ CUtensorMap tmWI, const __nv_bfloat16* __restrict__ x,
             const char* __restrict__ wg_raw, const char* __restrict__ wu_raw, const char* __restrict__ wd_raw,
             __nv_bfloat16* __restrict__ out) {
  extern __shared__ __align__(1024) char smem_raw[];
  const uint32_t sbase = (s2u(smem_raw) + 1023) & ~1023u;
  const uint32_t sbar = sbase + 14 * SLOT, sstat = sbar + 512;
  const int tid = threadIdx.x, lane = tid & 31;
  const int c = blockIdx.x, kh = c & 1, f = (c >> 1) & 7, rb = 2 * (c >> 4) + kh, rb2 = 2 * (c >> 4) + (f >> 2), nq = f & 3;
#define BAR(field, i) (sbar + (uint32_t)offsetof(Bars, field) + 8u * (i))
#define TOFF(field) (sbase + SM_T + (uint32_t)offsetof(Tables, field) + lane * 16)

  if (tid >= 256) {
    asm volatile("setmaxnreg.dec.sync.aligned.u32 56;");
    const int warp = __shfl_sync(0xffffffffu, tid >> 5, 0);
    if (tid == 256) {
      for (int i = 0; i < 6; i++) { mbar_init(BAR(full1, i), 1); mbar_init(BAR(empty1, i), 16); }
      for (int i = 0; i < 8; i++) { mbar_init(BAR(fullA, i), 1); mbar_init(BAR(empty2, i), 8); }
      for (int i = 0; i < 14; i++) mbar_init(BAR(full2, i), 2);
      mbar_init(BAR(xbar, 0), 1);
      mbar_init(BAR(xfree, 0), 8);
      mbar_init(BAR(tbar, 0), 1);
      mbar_init(BAR(hbar, 0), 1);
      mbar_init(BAR(sbar, 0), 32);
      mbar_init(BAR(sig, 0), 8);
      mbar_init(BAR(sig, 1), 16);
      mbar_expect(BAR(xbar, 0), 16384);
      asm volatile("fence.mbarrier_init.release.cluster;" ::: "memory");
    }
    if (tid == 320) {
      const unsigned e = ld_relaxed(&g_cnt[(C_LN + rb) * 32]) >> 3;
      asm volatile("st.shared.u32 [%0], %1;" ::"r"(BAR(epoch, 0)), "r"(e) : "memory");
    }
    __syncwarp();
    asm volatile("barrier.cluster.arrive.relaxed.aligned;" ::: "memory");
    bar_arrive(NB_RDY, 384);
    bar_sync(NB_INIT, 384);
    unsigned epoch;
    asm volatile("ld.shared.u32 %0, [%1];" : "=r"(epoch) : "r"(BAR(epoch, 0)) : "memory");
    if (warp == 8) {
      if (lane == 0) {
        const int ax = (7 * f + 3 * (f & 1)) >> 1;
        const int ay = 7 * f + ((f & 1) ? 0 : 4);
        const CUtensorMap* tx = kh ? &tmUX : &tmGX;
        const CUtensorMap* ty = kh ? &tmUY : &tmGY;
        uint32_t s = 0, ph = 1;
        mbar_wait(BAR(sig, 1), 0);
#pragma unroll 1
        for (int n = 0; n < 32; n++) {
          const uint32_t dst = sbase + (8 + s) * SLOT, fb = BAR(full1, s);
          mbar_wait(BAR(empty1, s), ph);
          if (n < 16) {
            mbar_expect(fb, 16384);
            tma3_mc(dst + kh * 8192, tx, fb, n * 32, ax);
          } else {
            mbar_expect(fb, 12288);
            tma3_mc(dst + kh * 6144, ty, fb, (n - 16) * 32, ay);
          }
          if (++s == 6) { s = 0; ph ^= 1; }
        }
      }
    } else if (warp == 9) {
      if (lane == 0) {
        mbar_wait(BAR(empty1, 5), 0);
        mbar_wait(BAR(empty1, 5), 1);
#pragma unroll 1
        for (int i = 0; i < 14; i++) {
          const int kblk = 14 * kh + (int)((KORDER >> (4 * i)) & 15);
          if (i < 8) mbar_wait(BAR(empty1, (17 + 2 * i) % 6), ((17 + 2 * i) / 6) & 1);
          else mbar_wait(BAR(empty2, i - 8), 0);
          mbar_expect(BAR(full2, i), 16384);
          tma3(sbase + (i & 7) * SLOT, &tmD, BAR(full2, i), 0, 64 * kblk, 2 * nq);
        }
        wait_counter(&g_cnt[(C_LN + rb2) * 32], (epoch + 1) * 8);
        asm volatile("fence.proxy.async.global;" ::: "memory");
        mbar_wait(BAR(empty2, 7), 0);
        mbar_expect(BAR(hbar, 0), 16384);
        bulk_load(sbase + 7 * SLOT, &g_LN[(rb2 * 8 + 2 * nq) * 1024 + kh * 512], 8192, BAR(hbar, 0));
        bulk_load(sbase + 7 * SLOT + 8192, &g_LN[(rb2 * 8 + 2 * nq + 1) * 1024 + kh * 512], 8192, BAR(hbar, 0));
      }
    } else if (warp == 10) {
      if (lane == 0) {
        const int w0 = ((c >> 3) * 257 + 32 * (c & 7) + 1) & ~7;
        mbar_expect(BAR(tbar, 0), T2_BYTES + 2 * 10240);
        tma3(sbase + SM_W, &tmWR, BAR(tbar, 0), w0, 0, 0);
        tma3(sbase + SM_W + 10240, &tmWI, BAR(tbar, 0), w0, 0, 0);
        bulk_load(sbase + SM_T + T1_BYTES, reinterpret_cast<const char*>(&g_tab) + T1_BYTES, T2_BYTES, BAR(tbar, 0));
      }
      bar_sync(NB_LN, 288);
      if (lane == 0) {
        PROFP(0);
        red_release(&g_cnt[(C_LN + rb) * 32]);
        PROFP(1);
        wait_counter(&g_cnt[(C_LN + rb) * 32], (epoch + 1) * 8);
        asm volatile("fence.proxy.async.global;" ::: "memory");
        PROFP(2);
#pragma unroll 1
        for (int kb = NLL; kb < 8; kb++) {
          mbar_expect(BAR(fullA, kb), 16384);
          bulk_load(sbase + kb * SLOT, &g_LN[(rb * 8 + kb) * 1024], 16384, BAR(fullA, kb));
        }
#pragma unroll 1
        for (int i = 0; i < 4; i++) mbar_wait(BAR(empty1, 2), i & 1);
        uint32_t d = 2;
#pragma unroll 1
        for (int s = 0; s < 14; s++) {
          const int kblk = 14 * kh + (int)((KORDER >> (4 * s)) & 15);
          if (s == 0 || s == 8) {
            PROFP(3 + (s >> 2));
            const unsigned* cp = &g_cnt[((s == 0 ? C_PX : C_PY) + rb2) * 32];
            int it = 0;
            while ((int)(ld_relaxed(cp) - (epoch + 1) * 64) < 0)
              if (++it > SPIN_LIMIT) { die(); break; }
            PROFP(4 + (s >> 2));
          }
          if (s < 6) mbar_wait(BAR(empty1, d), s < 4 ? 0 : 1);
          else mbar_wait(BAR(empty2, s - 6), 0);
          mbar_expect(BAR(full2, s), 16384);
          bulk_load(sbase + (8 + d) * SLOT, &g_P[(rb2 * 28 + kblk) * 1024], 16384, BAR(full2, s));
          if (++d == 6) d = 0;
        }
        PROFP(7);
      }
    } else {
      if (lane == 0) {
        l2_prefetch(wg_raw + (size_t)c * 5376, 5376);
        l2_prefetch(wu_raw + (size_t)c * 5376, 5376);
        mbar_wait(BAR(sig, PF2_SIG), 0);
        l2_prefetch(wg_raw + 688128 + (size_t)c * 8960, 8960);
        l2_prefetch(wu_raw + 688128 + (size_t)c * 8960, 8960);
      }
      mbar_wait(BAR(fullA, 7), 0);
      if (lane == 0) l2_prefetch(wd_raw + (size_t)c * 14336, 14336);
      {
        const uint32_t tag = (epoch + 1) & 1;
        uint4 v0, v1, v2;
        int it = 0;
        while (true) {
          v0 = ld_b128(&g_ST[rb * 64 + lane]);
          v1 = ld_b128(&g_ST[rb * 64 + 32 + lane]);
          v2 = ld_b128(&g_ST[rb2 * 64 + 32 * kh + lane]);
          if (!__any_sync(0xffffffffu, ((v0.x ^ tag) | (v1.x ^ tag) | (v2.x ^ tag)) & 1u)) break;
          if (++it > SPIN_LIMIT) { die(); break; }
        }
        sts4(sstat + lane * 16, v0.x & ~1u, v0.y, v0.z, v0.w);
        sts4(sstat + 512 + lane * 16, v1.x & ~1u, v1.y, v1.z, v1.w);
        sts4(sstat + 1024 + lane * 16, v2.x & ~1u, v2.y, v2.z, v2.w);
        mbar_arrive(BAR(sbar, 0));
      }
    }
    __syncwarp();
    asm volatile("barrier.cluster.wait.aligned;" ::: "memory");
  } else {
    const int warp = __shfl_sync(0xffffffffu, tid >> 5, 0);
    const int g = lane >> 2, t = lane & 3;
    PROF(0);
    PROFG(14);
#pragma unroll
    for (int i = 0; i < 4; i++) {
      const int r = i >> 1, ch = (i & 1) * 32 + lane;
      cp_async16(sbase + SM_X + (2 * warp + r) * 1024 + ((ch ^ ((ch >> 2) & 6)) * 16),
                 x + (size_t)(c + 128 * (2 * warp + r)) * 512 + ch * 8);
    }
    asm volatile("cp.async.commit_group;" ::: "memory");
    asm volatile("barrier.cluster.arrive.relaxed.aligned;" ::: "memory");
    asm volatile("setmaxnreg.inc.sync.aligned.u32 224;");
    uint4 tw[8], fb[16];
    const uint4 fa = ldg_ca4(&g_tab.fa[lane][0]);
#pragma unroll
    for (int i = 0; i < 8; i++) tw[i] = ldg_ca4(&g_tab.tw1[i][lane][0]);
#pragma unroll
    for (int i = 0; i < 16; i++) fb[i] = ldg_ca4(&g_tab.fb[i][lane][0]);
    uint32_t rbar;
    asm volatile("mapa.shared::cluster.u32 %0, %1, %2;" : "=r"(rbar) : "r"(sbar), "r"(kh ^ 1));
#define RBAR(field, i) (rbar + (uint32_t)offsetof(Bars, field) + 8u * (i))
    {
      const int ln = (tid >> 1) & 31, lg = ln >> 2, lt = ln & 3, i = 4 * (tid >> 6) + 2 * (tid & 1);
      const int kidx = lt + 8 * (i >> 3), nidx = 4 * ((i >> 1) & 3) + (lg >> 1);
      const uint32_t a0 = cfrag<2048>((c + 128 * kidx) * nidx, lg & 1), a1 = cfrag<2048>((c + 128 * (kidx + 4)) * nidx, lg & 1);
      const uint32_t b0 = cfrag<2048>(-(c + 128 * nidx) * kidx, lg & 1), b1 = cfrag<2048>(-(c + 128 * nidx) * (kidx + 4), lg & 1);
      asm volatile("st.shared.v2.u32 [%0], {%1,%2};" ::"r"(sbase + SM_FC + tid * 8), "r"(a0), "r"(a1) : "memory");
      asm volatile("st.shared.v2.u32 [%0], {%1,%2};" ::"r"(sbase + SM_FC + 2048 + tid * 8), "r"(b0), "r"(b1) : "memory");
    }
    asm volatile("cp.async.wait_group 0;" ::: "memory");
    __syncwarp();
    bar_arrive(NB_INIT, 384);
    PROF(13);
    uint32_t tag;
    uint4 q[4], o[4];
    {
      uint32_t v[2][8];
#pragma unroll
      for (int r = 0; r < 2; r++)
#pragma unroll
        for (int q = 0; q < 4; q++) {
          const uint2 u = lds2(sbase + SM_X + (2 * warp + r) * 1024 + (t + 4 * (q >> 1)) * 128 + (((4 * (q & 1) + (g >> 1)) ^ (2 * t)) * 16) + (g & 1) * 8);
          v[r][2 * q] = u.x; v[r][2 * q + 1] = u.y;
        }
      float sum[2], sq[2], rstd[2];
      row_stats(v[0], v[1], lane, sum, sq);
#pragma unroll
      for (int r = 0; r < 2; r++) {
        const float m = sum[r] * (1.f / 512.f);
        rstd[r] = rsqrtf(fmaxf(fmaf(-m, m, sq[r] * (1.f / 512.f)), 0.f) + 1e-5f);
      }
      uint32_t alo[4][4], ahi[4][4];
#pragma unroll
      for (int r = 0; r < 2; r++)
#pragma unroll
        for (int i = 0; i < 4; i++) {
          const uint32_t sel = (i & 1) ? 0x7632u : 0x5410u;
          const uint32_t b0 = __byte_perm(v[r][i >> 1], v[r][2 + (i >> 1)], sel);
          const uint32_t b1 = __byte_perm(v[r][4 + (i >> 1)], v[r][6 + (i >> 1)], sel);
          float d[4] = {0.f, 0.f, 0.f, 0.f};
          mma16816(d, fa.x, fa.y, fa.z, fa.w, b0, b1);
          const uint4 &ka = tw[2 * i], &kb = tw[2 * i + 1];
          const uint32_t re = pack2(d[0] * __uint_as_float(ka.x) + d[2] * __uint_as_float(ka.y), d[1] * __uint_as_float(kb.x) + d[3] * __uint_as_float(kb.y));
          const uint32_t im = pack2(d[0] * __uint_as_float(ka.z) + d[2] * __uint_as_float(ka.w), d[1] * __uint_as_float(kb.z) + d[3] * __uint_as_float(kb.w));
          const uint32_t dc = pack2(fmaf(sum[r], -1.f / 32.f, d[0]), fmaf(sum[r], -1.f / 32.f, d[1]));
          alo[i][r] = re; alo[i][2 + r] = im;
          ahi[i][r] = g == 0 ? dc : re; ahi[i][2 + r] = g == 0 ? 0u : im;
        }
      float acc[8][4];
#pragma unroll
      for (int u = 0; u < 8; u++) {
        acc[u][0] = acc[u][1] = acc[u][2] = acc[u][3] = 0.f;
#pragma unroll
        for (int i = 0; i < 4; i++) {
          const uint4& bq = fb[i * 4 + (u >> 1)];
          if (u < 4) mma16816(acc[u], alo[i][0], alo[i][1], alo[i][2], alo[i][3], (u & 1) ? bq.z : bq.x, (u & 1) ? bq.w : bq.y);
          else       mma16816(acc[u], ahi[i][0], ahi[i][1], ahi[i][2], ahi[i][3], (u & 1) ? bq.z : bq.x, (u & 1) ? bq.w : bq.y);
        }
      }
#pragma unroll
      for (int r = 0; r < 2; r++)
#pragma unroll
        for (int h = 0; h < 2; h++) {
          const int j = 2 * warp + r, m = 2 * t + h;
          const float rs = rstd[r];
          sts4(sbase + SM_E + ((j * 8 + m) * 8 + (g ^ (2 * t) ^ (2 * (j & 3)))) * 16,
               pack2(acc[2 * h][2 * r] * rs, acc[2 * h][2 * r + 1] * rs), pack2(acc[2 * h + 1][2 * r] * rs, acc[2 * h + 1][2 * r + 1] * rs),
               pack2(acc[4 + 2 * h][2 * r] * rs, acc[4 + 2 * h][2 * r + 1] * rs), pack2(acc[5 + 2 * h][2 * r] * rs, acc[5 + 2 * h][2 * r + 1] * rs));
        }
      if (tid == 0) PROFP(12);
      bar_sync(NB_RDY, 384);
      if (tid == 0) PROFP(13);
      uint4 fc[4];
#pragma unroll
      for (int i = 0; i < 4; i++) fc[i] = lds4(sbase + SM_FC + i * 512 + lane * 16);
      asm volatile("ld.shared.u32 %0, [%1];" : "=r"(tag) : "r"(BAR(epoch, 0)) : "memory");
      tag = (tag + 1) & 1;
#pragma unroll
      for (int i = 0; i < 4; i++) q[i] = lds4(sbase + SM_E + (((t + 4 * i) * 8 + warp) * 8 + (g ^ (warp & 6) ^ (2 * t))) * 16);
      cdft16(q, fc, o);
#pragma unroll
      for (int vv = 0; vv < 4; vv++) st_tag(&g_Z1[(((4 * vv + t) * 8 + warp) * 128 + c) * 8 + g], o[vv], tag);
    }
    PROF(1);
    {
      const uint4* const zp = &g_Z1[(c * 128 + 8 * t + warp) * 8 + g];
      const uint32_t tst = clock32();
      mbar_wait(BAR(tbar, 0), 0);
      if (tid == 0) PROFP(14);
      uint4 f2[4], g2[4];
#pragma unroll
      for (int i = 0; i < 4; i++) {
        f2[i] = lds4(TOFF(f2) + warp * 2048 + i * 512);
        g2[i] = lds4(TOFF(g2) + warp * 2048 + i * 512);
      }
      const uint4 f8 = lds4(TOFF(f8)), g8 = lds4(TOFF(g8));
      float wfr[16], wfi[16];
      {
        const float fsc = 1.f / (1 << 19);
        const float fsc3 = ((c & 7) == 7 && g == 0) ? 0.5f * fsc : fsc;
        const int gg = g == 0 ? 8 : g, wsh = (2 * (c >> 3) + 2) & 15;
#pragma unroll
        for (int i = 0; i < 16; i++) {
          const int ci = i >> 3, dd = (i >> 2) & 1, e = i & 3;
          const int kk = (e == 0 ? gg : e == 1 ? 16 + gg : e == 2 ? 16 - g : 32 - g) - 1;
          const uint32_t a = sbase + SM_W + ((2 * warp + ci) * 8 + t + 4 * dd) * 80 + wsh + 2 * kk;
          wfr[i] = bf_lo(lds_u16(a)) * (e == 3 ? fsc3 : fsc);
          wfi[i] = bf_lo(lds_u16(a + 10240)) * (e == 3 ? fsc3 : fsc);
        }
      }
      asm volatile("barrier.cluster.wait.aligned;" ::: "memory");
      PROF(2);
      while (clock32() - tst < POLL_DELAY) {}
      ld_tag4_issue<256>(q, zp);
      ld_tag4_finish<256>(q, zp, tag);
      if (tid == 0) PROFP(30);
      if (lane == 0) mbar_arrive(BAR(sig, 0));
      cdft16(q, f2, o);
      const uint32_t e2 = sbase + SM_E2;
#pragma unroll
      for (int vv = 0; vv < 4; vv++)
        sts4(e2 + ((warp * 16 + 4 * vv + t) * 8 + (g ^ (2 * t) ^ (2 * (warp & 3)))) * 16, o[vv].x, o[vv].y, o[vv].z, o[vv].w);
      bar_sync(NB_CONS, 256);
#pragma unroll
      for (int ci = 0; ci < 2; ci++) {
        const int cc = 2 * warp + ci;
        uint32_t ad[2];
        uint4 u[2];
#pragma unroll
        for (int hh = 0; hh < 2; hh++) {
          ad[hh] = e2 + (((t + 4 * hh) * 16 + cc) * 8 + (g ^ (2 * (cc & 3)) ^ (2 * t))) * 16;
          u[hh] = lds4(ad[hh]);
        }
        uint32_t res[2][4];
#pragma unroll
        for (int p = 0; p < 2; p++) {
          uint32_t y[2][2];
#pragma unroll
          for (int vv = 0; vv < 2; vv++) {
            float d[4] = {0.f, 0.f, 0.f, 0.f};
            mma16816(d, word(u[0], 2 * p), word(u[0], 2 * p + 1), word(u[1], 2 * p), word(u[1], 2 * p + 1), word(f8, 2 * vv), word(f8, 2 * vv + 1));
#pragma unroll
            for (int rr = 0; rr < 2; rr++) {
              const float fr = wfr[ci * 8 + vv * 4 + 2 * p + rr], fi = wfi[ci * 8 + vv * 4 + 2 * p + rr];
              y[vv][rr] = pack2(d[2 * rr] * fr - d[2 * rr + 1] * fi, d[2 * rr] * fi + d[2 * rr + 1] * fr);
            }
          }
#pragma unroll
          for (int vv = 0; vv < 2; vv++) {
            float d[4] = {0.f, 0.f, 0.f, 0.f};
            mma16816(d, y[0][0], y[0][1], y[1][0], y[1][1], word(g8, 2 * vv), word(g8, 2 * vv + 1));
            res[vv][2 * p] = pack2(d[0], d[1]);
            res[vv][2 * p + 1] = pack2(d[2], d[3]);
          }
        }
#pragma unroll
        for (int vv = 0; vv < 2; vv++) sts4(ad[vv], res[vv][0], res[vv][1], res[vv][2], res[vv][3]);
      }
      bar_sync(NB_CONS, 256);
#pragma unroll
      for (int i = 0; i < 4; i++) q[i] = lds4(e2 + ((warp * 16 + 4 * i + t) * 8 + (g ^ (2 * t) ^ (2 * (warp & 3)))) * 16);
      cdft16(q, g2, o);
#pragma unroll
      for (int vv = 0; vv < 4; vv++) st_tag(&g_Z2[((8 * (4 * vv + t) + warp) * 128 + c) * 8 + g], o[vv], tag);
    }
    PROF(3);
    {
      const uint4* const zp = &g_Z2[((c * 16 + t) * 8 + warp) * 8 + g];
      const uint32_t tst = clock32();
      uint4 gb[16], gc[4], tw[4], xr[2][2];
#pragma unroll
      for (int i = 0; i < 16; i++) gb[i] = lds4(TOFF(gb) + i * 512);
      const uint4 ga = lds4(TOFF(ga));
#pragma unroll
      for (int i = 0; i < 4; i++) {
        gc[i] = lds4(sbase + SM_FC + 2048 + i * 512 + lane * 16);
        tw[i] = lds4(TOFF(tw3) + i * 512);
        const int ch = 4 * (g + 8 * (i & 1)) + t;
        xr[i >> 1][i & 1] = lds4(sbase + SM_X + (2 * warp + (i >> 1)) * 1024 + ((ch ^ ((ch >> 2) & 6)) * 16));
      }
      asm volatile("fence.proxy.async.shared::cta;" ::: "memory");
      PROF(4);
      while (clock32() - tst < POLL_DELAY) {}
      ld_tag4_issue<256>(q, zp);
      ld_tag4_finish<256>(q, zp, tag);
      if (tid == 0) PROFP(31);
      if (lane == 0) { mbar_arrive(BAR(sig, 1)); mbar_arrive_remote(RBAR(sig, 1)); }
      cdft16(q, gc, o);
#pragma unroll
      for (int vv = 0; vv < 4; vv++)
        sts4(sbase + SM_E + (((4 * vv + t) * 8 + warp) * 8 + (g ^ (warp & 6) ^ (2 * t))) * 16, o[vv].x, o[vv].y, o[vv].z, o[vv].w);
      bar_sync(NB_CONS, 256);
      uint32_t hv[2][8];
      const float mk = t == 0 ? 0.f : 1.f;
#pragma unroll
      for (int r = 0; r < 2; r++) {
        const int j = 2 * warp + r;
        uint4 u[2];
#pragma unroll
        for (int h = 0; h < 2; h++) u[h] = lds4(sbase + SM_E + ((j * 8 + 2 * t + h) * 8 + (g ^ (2 * t) ^ (2 * (j & 3)))) * 16);
        float yv[4][4];
#pragma unroll
        for (int i = 0; i < 4; i++) {
          float lo[4] = {0.f, 0.f, 0.f, 0.f}, hi[4] = {0.f, 0.f, 0.f, 0.f};
          mma16816(lo, gb[i * 4].x, gb[i * 4].y, gb[i * 4].z, gb[i * 4].w, u[0].x, u[0].y);
          mma16816(lo, gb[i * 4 + 1].x, gb[i * 4 + 1].y, gb[i * 4 + 1].z, gb[i * 4 + 1].w, u[1].x, u[1].y);
          mma16816(hi, gb[i * 4 + 2].x, gb[i * 4 + 2].y, gb[i * 4 + 2].z, gb[i * 4 + 2].w, u[0].z, u[0].w);
          mma16816(hi, gb[i * 4 + 3].x, gb[i * 4 + 3].y, gb[i * 4 + 3].z, gb[i * 4 + 3].w, u[1].z, u[1].w);
          const float ca = __uint_as_float(tw[i].x), sa = __uint_as_float(tw[i].y), cb = __uint_as_float(tw[i].z), sb = __uint_as_float(tw[i].w);
          const float tr0 = fmaf(hi[0], mk, lo[0]), ti0 = fmaf(hi[2], mk, lo[2]);
          const float tr1 = lo[1] + hi[1], ti1 = lo[3] + hi[3];
          const float vr0 = tr0 * ca - ti0 * sa, vi0 = tr0 * sa + ti0 * ca;
          const float vr1 = tr1 * cb - ti1 * sb, vi1 = tr1 * sb + ti1 * cb;
          const uint32_t b0 = pack2(t == 0 ? hi[0] : vr0, vr1), b1 = pack2(t == 0 ? vr0 : vi0, vi1);
          yv[i][0] = yv[i][1] = yv[i][2] = yv[i][3] = 0.f;
          mma16816(yv[i], ga.x, ga.y, ga.z, ga.w, b0, b1);
        }
#pragma unroll
        for (int h = 0; h < 2; h++) {
          hv[r][4 * h + 0] = hadd2_bf16(xr[r][h].x, pack2(yv[0][2 * h], yv[1][2 * h]));
          hv[r][4 * h + 1] = hadd2_bf16(xr[r][h].y, pack2(yv[2][2 * h], yv[3][2 * h]));
          hv[r][4 * h + 2] = hadd2_bf16(xr[r][h].z, pack2(yv[0][2 * h + 1], yv[1][2 * h + 1]));
          hv[r][4 * h + 3] = hadd2_bf16(xr[r][h].w, pack2(yv[2][2 * h + 1], yv[3][2 * h + 1]));
        }
      }
      float ds[4] = {0.f, 0.f, 0.f, 0.f};
#pragma unroll
      for (int q4 = 0; q4 < 4; q4++) mma16816(ds, hv[0][2 * q4], hv[1][2 * q4], hv[0][2 * q4 + 1], hv[1][2 * q4 + 1], 0x3f803f80u, 0x3f803f80u);
#pragma unroll
      for (int o2 = 4; o2 <= 16; o2 <<= 1) {
        ds[0] += __shfl_xor_sync(0xffffffffu, ds[0], o2);
        ds[2] += __shfl_xor_sync(0xffffffffu, ds[2], o2);
      }
      uint32_t mb[2];
#pragma unroll
      for (int r = 0; r < 2; r++) {
        const int row = 16 * f + 2 * warp + r;
        mb[r] = pack2(ds[2 * r] * (1.f / 512.f), ds[2 * r] * (1.f / 512.f));
#pragma unroll
        for (int i = 0; i < 8; i++) hv[r][i] = hsub2_bf16(hv[r][i], mb[r]);
#pragma unroll
        for (int h = 0; h < 2; h++) {
          const int n1 = g + 8 * h;
          st_tag(&g_LN[(rb * 8 + (n1 >> 1)) * 1024 + row * 8 + ((4 * (n1 & 1) + t) ^ (row & 7))],
                 make_uint4(hv[r][4 * h], hv[r][4 * h + 1], hv[r][4 * h + 2], hv[r][4 * h + 3]), n1 < 2 * NLL ? tag : (hv[r][4 * h] & 1u));
        }
      }
      asm volatile("fence.proxy.async.shared::cta;" ::: "memory");
      bar_arrive(NB_LN, 288);
      float sum[2], sq[2], rstd[2];
      row_stats(hv[0], hv[1], lane, sum, sq);
#pragma unroll
      for (int r = 0; r < 2; r++) {
        const float m = sum[r] * (1.f / 512.f);
        rstd[r] = rsqrtf(fmaxf(fmaf(-m, m, sq[r] * (1.f / 512.f)), 0.f) + 1e-5f);
      }
      if (lane == 0)
        st_tag(&g_ST[rb * 64 + 8 * f + warp], make_uint4(mb[0] << 16, __float_as_uint(rstd[0]), mb[1] << 16, __float_as_uint(rstd[1])), tag);
    }
    PROF(5);
    if (NLL) {
      const uint4* const ap = &g_LN[rb * 8 * 1024 + tid];
      uint4 av[NLL ? NLL : 1][4];
      spin_cycles(POLL_DELAY3);
#pragma unroll
      for (int kb = 0; kb < NLL; kb++) ld_tag4_issue<256>(av[kb], ap + kb * 1024);
      bar_sync(NB_CONS, 256);
#pragma unroll
      for (int kb = 0; kb < NLL; kb++) {
        ld_tag4_finish<256>(av[kb], ap + kb * 1024, tag);
#pragma unroll
        for (int i = 0; i < 4; i++) sts4(sbase + kb * SLOT + (tid + 256 * i) * 16, av[kb][i].x, av[kb][i].y, av[kb][i].z, av[kb][i].w);
      }
      asm volatile("fence.proxy.async.shared::cta;" ::: "memory");
      bar_sync(NB_CONS, 256);
    }
    const int wgi = warp >> 2, wq = warp & 3;
    uint4* const pbase = &g_P[rb * 28 * 1024 + warp * 128 + lane];
    const uint32_t a_lo0 = desc_lo(sbase + wgi * 8192, 16);
    const uint32_t ebar = lane == 0 ? BAR(empty1, 0) : RBAR(empty1, 0);
    float r0, r1;
    uint4 px[8], py[6];
    const int rh = wgi ^ kh ^ 1;
    const uint4* const psrc = &g_P[(rb2 * 28 + 14 * kh) * 1024 + (4 * rh + wq) * 128 + lane];
    {
      float acc[128];
#pragma unroll
      for (int i = 0; i < 128; i++) acc[i] = 0.f;
      const uint32_t b_lo0 = desc_lo(sbase + 8 * SLOT, 4096);
      uint32_t slot = 0, ph = 0, prev = 0;
#pragma unroll 1
      for (int kb = 0; kb < 8; kb++) {
        if (kb >= NLL) mbar_wait(BAR(fullA, kb), 0);
        if (kb == 0) PROF(6);
#pragma unroll
        for (int hh = 0; hh < 2; hh++) {
          if (LAGX && hh == ((16 - LAGX) & 1) && kb == ((16 - LAGX) >> 1) && wgi == 1) bar_sync(NB_LAG, 256);
          mbar_wait(BAR(full1, slot), ph);
          const uint32_t al = a_lo0 + kb * 1024 + hh * 4, bl = b_lo0 + slot * 1024;
          wg_fence();
          wgmma_n256(acc, desc64(al, HI128), desc64(bl, HI128));
          wgmma_n256(acc, desc64(al + 2, HI128), desc64(bl + 128, HI128));
          wg_commit();
          if (LAGX && hh == 1 && kb == 7 && wgi == 0) bar_arrive(NB_LAG, 256);
          wg_wait<1>();
          if ((kb | hh) != 0 && lane < 2) mbar_arrive_remote(ebar + 8 * prev);
          prev = slot;
          if (++slot == 6) { slot = 0; ph ^= 1; }
        }
      }
      mbar_wait(BAR(sbar, 0), 0);
      r0 = __uint_as_float(lds2(sstat + (16 * warp + g) * 8).y);
      r1 = __uint_as_float(lds2(sstat + (16 * warp + g + 8) * 8).y);
      wg_wait<0>();
      if (lane < 2) mbar_arrive_remote(ebar + 8 * prev);
      PROF(7);
      make_p<8>(acc, r0, r1, px);
    }
    PROF(8);
    {
      float acc[96];
#pragma unroll
      for (int i = 0; i < 96; i++) acc[i] = 0.f;
      const uint32_t b_lo0 = desc_lo(sbase + 8 * SLOT, 2048);
      uint4* const pdst = pbase + ((7 * f + 3 * (f & 1)) >> 1) * 1024;
#pragma unroll
      for (int k = 0; k < 16; k++) {
        if (LAGY && k == 16 - LAGY && wgi == 1) bar_sync(NB_LAG, 256);
        mbar_wait(BAR(full1, (16 + k) % 6), ((16 + k) / 6) & 1);
        const uint32_t al = a_lo0 + (k >> 1) * 1024 + (k & 1) * 4, bl = b_lo0 + ((16 + k) % 6) * 1024;
        wg_fence();
        wgmma_n192(acc, desc64(al, HI128), desc64(bl, HI64));
        wgmma_n192(acc, desc64(al + 2, HI128), desc64(bl + 64, HI64));
        wg_commit();
        if (k < 4) {
          st_tag(pdst + (k >> 1) * 1024 + (k & 1) * 64, px[2 * k], tag);
          st_tag(pdst + (k >> 1) * 1024 + (k & 1) * 64 + 32, px[2 * k + 1], tag);
        }
        if (k == 3 && lane == 0) red_relaxed(&g_cnt[(C_PX + rb) * 32]);
        if (LAGY && k == 15 && wgi == 0) bar_arrive(NB_LAG, 256);
        wg_wait<1>();
        if (k != 0 && lane < 2) mbar_arrive_remote(ebar + 8 * ((15 + k) % 6));
      }
      wg_wait<0>();
      if (lane < 2) mbar_arrive_remote(ebar + 8 * (31 % 6));
      PROF(9);
      make_p<6>(acc, r0, r1, py);
    }
    PROF(10);
    {
      const int G0 = 7 * f + ((f & 1) ? 0 : 4);
      float acc[64];
      {
        const float m0 = wgi ? __uint_as_float(lds2(sstat + 1024 + (16 * wq + g) * 8).x) : 0.f;
        const float m1 = wgi ? __uint_as_float(lds2(sstat + 1024 + (16 * wq + g + 8) * 8).x) : 0.f;
#pragma unroll
        for (int i = 0; i < 64; i++) acc[i] = (i & 2) ? m1 : m0;
      }
      const uint32_t b2_lo0 = desc_lo(sbase, 8192);
#pragma unroll
      for (int s = 0; s < 14; s++) {
        uint4 a[4];
        if (LAG2 && s == 14 - LAG2 && wgi == 1) bar_sync(NB_LAG, 256);
        mbar_wait(BAR(full2, s), 0);
        if (tid == 0) PROFP(16 + s);
#pragma unroll
        for (int kk = 0; kk < 4; kk++) a[kk] = lds4(sbase + (8 + (s + 2) % 6) * SLOT + (4 * rh + wq) * 2048 + kk * 512 + lane * 16);
        ld_tag4_finish<32>(a, psrc + (int)((KORDER >> (4 * s)) & 15) * 1024, tag);
        const uint32_t bl = b2_lo0 + (s & 7) * 1024;
        wg_fence();
#pragma unroll
        for (int kk = 0; kk < 4; kk++) wgmma_rs_n128(acc, a[kk].x, a[kk].y, a[kk].z, a[kk].w, desc64(bl + kk * 128, HI128));
        wg_commit();
        if (s == 0) {
#pragma unroll
          for (int k = 0; k < 6; k++) st_tag(pbase + ((G0 + (k >> 1)) >> 1) * 1024 + ((G0 + (k >> 1)) & 1) * 64 + (k & 1) * 32, py[k], tag);
          if (lane == 0) red_relaxed(&g_cnt[(C_PY + rb) * 32]);
        }
        if (LAG2 && s == 13 && wgi == 0) bar_arrive(NB_LAG, 256);
        wg_wait<1>();
        if (s > 0 && s <= 8 && lane == 0) {
          mbar_arrive(BAR(empty2, s - 1));
          if (s == 8) mbar_arrive_remote(RBAR(xfree, 0));
        }
      }
      uint4 hres[2][4];
      mbar_wait(BAR(hbar, 0), 0);
#pragma unroll
      for (int h = 0; h < 2; h++)
#pragma unroll
        for (int q = 0; q < 4; q++) {
          hres[h][q] = lds4(sbase + 7 * SLOT + (q >> 1) * 8192 + (16 * wq + g + 8 * h) * 128 + (((4 * (q & 1) + t) ^ g) * 16));
          if (2 * nq + (q >> 1) < NLL) hres[h][q].x &= ~1u;
        }
      wg_wait<0>();
      PROF(11);
      const uint32_t xbuf = sbase + 6 * SLOT + (tid & 127) * 16;
      if (wgi == 0) {
        uint32_t rbuf;
        mbar_wait(BAR(xfree, 0), 0);
        asm volatile("mapa.shared::cluster.u32 %0, %1, %2;" : "=r"(rbuf) : "r"(xbuf), "r"(kh ^ 1));
#pragma unroll
        for (int i = 0; i < 8; i++)
          asm volatile("st.async.weak.shared::cluster.mbarrier::complete_tx::bytes.v4.b32 [%0], {%1,%2,%3,%4}, [%5];"
                       ::"r"(rbuf + i * 2048), "r"(pack2(acc[8 * i], acc[8 * i + 1])), "r"(pack2(acc[8 * i + 2], acc[8 * i + 3])),
                         "r"(pack2(acc[8 * i + 4], acc[8 * i + 5])), "r"(pack2(acc[8 * i + 6], acc[8 * i + 7])), "r"(RBAR(xbar, 0))
                       : "memory");
      } else {
        mbar_wait_cluster(BAR(xbar, 0), 0);
      }
      uint32_t w[2][16];
#pragma unroll
      for (int i = 0; i < 8; i++) {
        const uint4 pv = lds4(xbuf + i * 2048);
        w[0][2 * i] = pack2(acc[8 * i] + bf_lo(pv.x), acc[8 * i + 1] + bf_hi(pv.x));
        w[1][2 * i] = pack2(acc[8 * i + 2] + bf_lo(pv.y), acc[8 * i + 3] + bf_hi(pv.y));
        w[0][2 * i + 1] = pack2(acc[8 * i + 4] + bf_lo(pv.z), acc[8 * i + 5] + bf_hi(pv.z));
        w[1][2 * i + 1] = pack2(acc[8 * i + 6] + bf_lo(pv.w), acc[8 * i + 7] + bf_hi(pv.w));
      }
      uint4* const o4 = reinterpret_cast<uint4*>(out) + (16 * (c >> 4) + 2 * (4 * rh + wq) + (rb2 & 1) + 128 * g) * 64 + nq * 16 + t;
#pragma unroll
      for (int h = 0; h < 2; h++)
#pragma unroll
        for (int q = 0; q < 4; q++) {
          uint32_t a0 = w[h][4 * q], a1 = w[h][4 * q + 1], a2 = w[h][4 * q + 2], a3 = w[h][4 * q + 3];
          {
            const bool od = t & 1;
            uint32_t s0 = od ? a0 : a1, s1 = od ? a2 : a3;
            s0 = __shfl_xor_sync(0xffffffffu, s0, 1); s1 = __shfl_xor_sync(0xffffffffu, s1, 1);
            if (od) { a0 = s0; a2 = s1; } else { a1 = s0; a3 = s1; }
          }
          {
            const bool up = t & 2;
            uint32_t s0 = up ? a0 : a2, s1 = up ? a1 : a3;
            s0 = __shfl_xor_sync(0xffffffffu, s0, 2); s1 = __shfl_xor_sync(0xffffffffu, s1, 2);
            if (up) { a0 = s0; a1 = s1; } else { a2 = s0; a3 = s1; }
          }
          if (wgi == 1)
            o4[h * 1024 * 64 + 4 * q] =
                make_uint4(hadd2_bf16(hres[h][q].x, a0), hadd2_bf16(hres[h][q].y, a1), hadd2_bf16(hres[h][q].z, a2), hadd2_bf16(hres[h][q].w, a3));
        }
      PROF(12);
      PROFG(15);
    }
  }
#undef BAR
#undef TOFF
#undef RBAR
}

typedef CUresult (*EncodeFn)(CUtensorMap*, CUtensorMapDataType, cuuint32_t, void*, const cuuint64_t*, const cuuint64_t*,
                             const cuuint32_t*, const cuuint32_t*, CUtensorMapInterleave, CUtensorMapSwizzle,
                             CUtensorMapL2promotion, CUtensorMapFloatOOBfill);

}

extern "C" void kernel_launch(void* const* d_in, const int* in_sizes, int n_in, void* d_out, int out_size) {
  (void)in_sizes; (void)n_in; (void)out_size;
  static EncodeFn encode = nullptr;
  if (!encode) {
    void* fn = nullptr;
    cudaDriverEntryPointQueryResult qr;
    cudaGetDriverEntryPoint("cuTensorMapEncodeTiled", &fn, cudaEnableDefault, &qr);
    encode = (EncodeFn)fn;
    cudaFuncSetAttribute(fused_kernel, cudaFuncAttributeMaxDynamicSharedMemorySize, SMEM_BYTES);
  }
  CUtensorMap tmGX, tmUX, tmGY, tmUY, tmD, tmWR, tmWI;
  const cuuint32_t es[5] = {1, 1, 1, 1, 1};
  auto enc = [&](CUtensorMap* m, void* p, int rank, const cuuint64_t* gd, const cuuint64_t* gs, const cuuint32_t* bd,
                 CUtensorMapSwizzle sw, CUtensorMapL2promotion pr) {
    encode(m, CU_TENSOR_MAP_DATA_TYPE_BFLOAT16, rank, p, gd, gs, bd, es, CU_TENSOR_MAP_INTERLEAVE_NONE, sw, pr,
           CU_TENSOR_MAP_FLOAT_OOB_FILL_NONE);
  };
  {
    const cuuint64_t gd[3] = {64, 512, 28}, gs[2] = {3584, 128};
    const cuuint32_t bd[3] = {64, 32, 2};
    enc(&tmGX, d_in[4], 3, gd, gs, bd, CU_TENSOR_MAP_SWIZZLE_128B, CU_TENSOR_MAP_L2_PROMOTION_L2_256B);
    enc(&tmUX, d_in[5], 3, gd, gs, bd, CU_TENSOR_MAP_SWIZZLE_128B, CU_TENSOR_MAP_L2_PROMOTION_L2_256B);
  }
  {
    const cuuint64_t gd[3] = {32, 512, 56}, gs[2] = {3584, 64};
    const cuuint32_t bd[3] = {32, 32, 3};
    enc(&tmGY, d_in[4], 3, gd, gs, bd, CU_TENSOR_MAP_SWIZZLE_64B, CU_TENSOR_MAP_L2_PROMOTION_L2_128B);
    enc(&tmUY, d_in[5], 3, gd, gs, bd, CU_TENSOR_MAP_SWIZZLE_64B, CU_TENSOR_MAP_L2_PROMOTION_L2_128B);
  }
  {
    const cuuint64_t gd[3] = {64, 1792, 8}, gs[2] = {1024, 128};
    const cuuint32_t bd[3] = {64, 64, 2};
    enc(&tmD, d_in[6], 3, gd, gs, bd, CU_TENSOR_MAP_SWIZZLE_128B, CU_TENSOR_MAP_L2_PROMOTION_L2_256B);
  }
  {
    const cuuint64_t gd[3] = {4112, 8, 16}, gs[2] = {16 * 8224, 8224};
    const cuuint32_t bd[3] = {40, 8, 16};
    enc(&tmWR, d_in[1], 3, gd, gs, bd, CU_TENSOR_MAP_SWIZZLE_NONE, CU_TENSOR_MAP_L2_PROMOTION_NONE);
    enc(&tmWI, d_in[2], 3, gd, gs, bd, CU_TENSOR_MAP_SWIZZLE_NONE, CU_TENSOR_MAP_L2_PROMOTION_NONE);
  }
  fused_kernel<<<NCTA, NTHREADS, SMEM_BYTES>>>(tmGX, tmUX, tmGY, tmUY, tmD, tmWR, tmWI, (const __nv_bfloat16*)d_in[0],
                                               (const char*)d_in[4], (const char*)d_in[5], (const char*)d_in[6],
                                               (__nv_bfloat16*)d_out);
}
```

```cpp
#include <cuda_runtime.h>
#include <cuda_bf16.h>
#include <cuda.h>
#include <stdint.h>

namespace {

constexpr int NCTA = 128;
constexpr int NTHREADS = 384;
constexpr int SLOT = 16384;
constexpr int SMEM_BYTES = 14 * SLOT + 2048 + 1024;
constexpr int SPIN_LIMIT = 1 << 22;

struct Scratch {
  uint4 Z1[128 * 1024];
  uint4 Z2[128 * 1024];
  uint4 LN[16 * 8 * 1024];
  uint4 P[16 * 28 * 1024];
  uint4 ST[1024];
  unsigned cnt[64 * 32];
};
__device__ __align__(1024) Scratch g_scr;
#define PROF(i)
#define PROFP(i)
#define PROFG(i)

constexpr double ccos(int i, int n) {
  i &= n - 1;
  if (i > n / 2) i = n - i;
  if (4 * i == n) return 0.0;
  const bool neg = 4 * i > n;
  if (neg) i = n / 2 - i;
  const double a = 6.283185307179586476925 * i / n, a2 = a * a;
  double term = 1.0, sum = 1.0;
  for (int k = 1; k < 14; k++) { term *= -a2 / ((2 * k - 1) * (2 * k)); sum += term; }
  return neg ? -sum : sum;
}
constexpr double csin(int i, int n) { return ccos(i - n / 4, n); }
constexpr unsigned fbits(double v, int mant) {
  if (v == 0.0) return 0;
  const unsigned sg = v < 0 ? 1u : 0u;
  if (v < 0) v = -v;
  int e = 127;
  while (v < 1.0) { v *= 2.0; e--; }
  const unsigned m = (unsigned)((v - 1.0) * (double)(1u << mant) + 0.5);
  return (sg << (8 + mant)) + ((unsigned)e << mant) + m;
}
constexpr unsigned pkb(double lo, double hi) { return fbits(lo, 7) | (fbits(hi, 7) << 16); }
constexpr double fa_elem(int kp, int n1) {
  return kp <= 8 ? ccos(kp * n1, 16) : -csin((kp - 8) * n1, 16);
}
constexpr unsigned cfrag_c(int idx, int n, int ri) {
  return ri ? pkb(-csin(idx, n), ccos(idx, n)) : pkb(ccos(idx, n), csin(idx, n));
}
struct Tables {
  unsigned fb[16][32][4];
  unsigned tw1[8][32][4];
  unsigned fa[32][4];
  unsigned f2[8][4][32][4];
  unsigned g2[8][4][32][4];
  unsigned gb[16][32][4];
  unsigned tw3[4][32][4];
  unsigned ga[32][4];
  unsigned f8[32][4], g8[32][4];
};
constexpr int T1_BYTES = 12800, T2_BYTES = 44544;
static_assert(sizeof(Tables) == T1_BYTES + T2_BYTES, "table size");
constexpr Tables make_tables() {
  Tables T = {};
  for (int l = 0; l < 32; l++) {
    const int g = l >> 2, t = l & 3;
    for (int i = 0; i < 4; i++)
      for (int u = 0; u < 8; u++) {
        const int ri = g & 1, m = 2 * (g >> 1) + ((u & 3) >> 1);
        const double sg = u >= 4 ? -1.0 : 1.0;
        const int k2 = u >= 4 ? 31 - 2 * m - (u & 1) : 2 * m + (u & 1);
        const int pa = (8 * t + i) * k2, pb = (8 * t + 4 + i) * k2;
        T.fb[i * 4 + (u >> 1)][l][(u & 1) * 2 + 0] = ri == 0 ? pkb(ccos(pa, 32), ccos(pb, 32)) : pkb(-sg * csin(pa, 32), -sg * csin(pb, 32));
        T.fb[i * 4 + (u >> 1)][l][(u & 1) * 2 + 1] = ri == 0 ? pkb(csin(pa, 32), csin(pb, 32)) : pkb(sg * ccos(pa, 32), sg * ccos(pb, 32));
      }
    for (int i = 0; i < 4; i++)
      for (int ks = 0; ks < 4; ks++) {
        const int n2 = 4 * g + i, m = 2 * t + (ks & 1);
        const double sg = ks >= 2 ? -1.0 : 1.0;
        const int pa = n2 * (ks >= 2 ? 31 - 2 * m : 2 * m), pb = n2 * (ks >= 2 ? 30 - 2 * m : 2 * m + 1);
        T.gb[i * 4 + ks][l][0] = pkb(ccos(pa, 32), -sg * csin(pa, 32));
        T.gb[i * 4 + ks][l][1] = pkb(csin(pa, 32), sg * ccos(pa, 32));
        T.gb[i * 4 + ks][l][2] = pkb(ccos(pb, 32), -sg * csin(pb, 32));
        T.gb[i * 4 + ks][l][3] = pkb(csin(pb, 32), sg * ccos(pb, 32));
      }
    for (int i = 0; i < 4; i++) {
      for (int e = 0; e < 2; e++) {
        const int p = (8 * t + 4 * e + i) * (g == 0 ? 8 : g);
        T.tw1[2 * i + e][l][0] = fbits(g == 0 ? 0.0 : ccos(p, 512), 23);
        T.tw1[2 * i + e][l][1] = fbits(g == 0 ? ccos(p, 512) : csin(p, 512), 23);
        T.tw1[2 * i + e][l][2] = fbits(g == 0 ? 0.0 : -csin(p, 512), 23);
        T.tw1[2 * i + e][l][3] = fbits(g == 0 ? -csin(p, 512) : ccos(p, 512), 23);
      }
      const int ka = t == 0 ? 8 : 2 * t, kb = 2 * t + 1;
      T.tw3[i][l][0] = fbits(ccos((4 * g + i) * ka, 512), 23);
      T.tw3[i][l][1] = fbits(csin((4 * g + i) * ka, 512), 23);
      T.tw3[i][l][2] = fbits(ccos((4 * g + i) * kb, 512), 23);
      T.tw3[i][l][3] = fbits(csin((4 * g + i) * kb, 512), 23);
      const int p8 = (t + 4 * (i & 1)) * (4 * (i >> 1) + (g >> 1));
      T.f8[l][i] = cfrag_c(p8, 8, g & 1);
      T.g8[l][i] = cfrag_c(-p8, 8, g & 1);
    }
    for (int w = 0; w < 8; w++)
      for (int i = 0; i < 16; i++) {
        const int kidx = t + 4 * (i & 1) + 8 * (i >> 3), nidx = 4 * ((i >> 1) & 3) + (g >> 1);
        T.f2[w][i >> 2][l][i & 3] = cfrag_c((8 * kidx + w) * nidx, 128, g & 1);
        T.g2[w][i >> 2][l][i & 3] = cfrag_c(-(8 * nidx + w) * kidx, 128, g & 1);
      }
    T.fa[l][0] = pkb(fa_elem(g, 2 * t), fa_elem(g, 2 * t + 1));
    T.fa[l][1] = pkb(fa_elem(g + 8, 2 * t), fa_elem(g + 8, 2 * t + 1));
    T.fa[l][2] = pkb(fa_elem(g, 2 * t + 8), fa_elem(g, 2 * t + 9));
    T.fa[l][3] = pkb(fa_elem(g + 8, 2 * t + 8), fa_elem(g + 8, 2 * t + 9));
    T.ga[l][0] = pkb(fa_elem(2 * t, g), fa_elem(2 * t + 1, g));
    T.ga[l][1] = pkb(fa_elem(2 * t, g + 8), fa_elem(2 * t + 1, g + 8));
    T.ga[l][2] = pkb(fa_elem(2 * t + 8, g), fa_elem(2 * t + 9, g));
    T.ga[l][3] = pkb(fa_elem(2 * t + 8, g + 8), fa_elem(2 * t + 9, g + 8));
  }
  return T;
}
__device__ const __align__(128) Tables g_tab = make_tables();

__device__ __forceinline__ void die() { asm volatile("st.global.u32 [%0], %1;" ::"l"(0ull), "r"(0) : "memory"); }
__device__ __forceinline__ uint32_t s2u(const void* p) { return (uint32_t)__cvta_generic_to_shared(p); }
__device__ __forceinline__ void mbar_init(uint32_t b, int c) { asm volatile("mbarrier.init.shared::cta.b64 [%0], %1;" ::"r"(b), "r"(c)); }
__device__ __forceinline__ void mbar_expect(uint32_t b, int bytes) {
  asm volatile("mbarrier.arrive.expect_tx.shared::cta.b64 _, [%0], %1;" ::"r"(b), "r"(bytes) : "memory");
}
__device__ __forceinline__ void mbar_arrive(uint32_t b) { asm volatile("mbarrier.arrive.shared::cta.b64 _, [%0];" ::"r"(b) : "memory"); }
__device__ __forceinline__ uint32_t mbar_try(uint32_t b, uint32_t parity) {
  uint32_t ok;
  asm volatile("{.reg .pred p; mbarrier.try_wait.parity.shared::cta.b64 p, [%1], %2; selp.u32 %0,1,0,p;}"
               : "=r"(ok) : "r"(b), "r"(parity) : "memory");
  return ok;
}
__device__ __forceinline__ void mbar_wait(uint32_t b, uint32_t parity) {
  int it = 0;
#pragma unroll 1
  while (!mbar_try(b, parity))
    if (++it > SPIN_LIMIT) { die(); break; }
}
__device__ __forceinline__ void mbar_wait_cluster(uint32_t b, int parity) {
  uint32_t ok;
  int it = 0;
  do {
    asm volatile("{.reg .pred p; mbarrier.try_wait.parity.acquire.cluster.shared::cta.b64 p, [%1], %2; selp.u32 %0,1,0,p;}"
                 : "=r"(ok) : "r"(b), "r"(parity) : "memory");
    if (++it > SPIN_LIMIT) { die(); break; }
  } while (!ok);
}
__device__ __forceinline__ void bar_sync(int id, int n) { asm volatile("bar.sync %0, %1;" ::"r"(id), "r"(n) : "memory"); }
__device__ __forceinline__ void bar_arrive(int id, int n) { asm volatile("bar.arrive %0, %1;" ::"r"(id), "r"(n) : "memory"); }
__device__ __forceinline__ void red_release(unsigned* p) { asm volatile("red.release.gpu.global.add.u32 [%0], 1;" ::"l"(p) : "memory"); }
__device__ __forceinline__ void red_relaxed(unsigned* p) { asm volatile("red.relaxed.gpu.global.add.u32 [%0], 1;" ::"l"(p) : "memory"); }
__device__ __forceinline__ unsigned ld_acquire(const unsigned* p) {
  unsigned v;
  asm volatile("ld.acquire.gpu.global.u32 %0, [%1];" : "=r"(v) : "l"(p) : "memory");
  return v;
}
__device__ __forceinline__ unsigned ld_relaxed(const unsigned* p) {
  unsigned v;
  asm volatile("ld.relaxed.gpu.global.u32 %0, [%1];" : "=r"(v) : "l"(p) : "memory");
  return v;
}
__device__ __forceinline__ void wait_counter(const unsigned* p, unsigned target) {
  int it = 0;
  while ((int)(ld_acquire(p) - target) < 0)
    if (++it > SPIN_LIMIT) { die(); break; }
}
__device__ __forceinline__ void sts4(uint32_t a, uint32_t x, uint32_t y, uint32_t z, uint32_t w) {
  asm volatile("st.shared.v4.u32 [%0], {%1,%2,%3,%4};" ::"r"(a), "r"(x), "r"(y), "r"(z), "r"(w) : "memory");
}
__device__ __forceinline__ uint4 lds4(uint32_t a) {
  uint4 v;
  asm volatile("ld.shared.v4.u32 {%0,%1,%2,%3}, [%4];" : "=r"(v.x), "=r"(v.y), "=r"(v.z), "=r"(v.w) : "r"(a) : "memory");
  return v;
}
__device__ __forceinline__ uint32_t pack2(float lo, float hi) {
  uint32_t r;
  asm("cvt.rn.bf16x2.f32 %0, %1, %2;" : "=r"(r) : "f"(hi), "f"(lo));
  return r;
}
__device__ __forceinline__ float bf_lo(uint32_t v) { return __uint_as_float(v << 16); }
__device__ __forceinline__ float bf_hi(uint32_t v) { return __uint_as_float(v & 0xffff0000u); }
__device__ __forceinline__ uint32_t hadd2_bf16(uint32_t a, uint32_t b) {
  uint32_t r;
  asm("add.rn.bf16x2 %0, %1, %2;" : "=r"(r) : "r"(a), "r"(b));
  return r;
}
__device__ __forceinline__ void mma16816(float (&d)[4], uint32_t a0, uint32_t a1, uint32_t a2, uint32_t a3, uint32_t b0, uint32_t b1) {
  asm("mma.sync.aligned.m16n8k16.row.col.f32.bf16.bf16.f32 {%0,%1,%2,%3}, {%4,%5,%6,%7}, {%8,%9}, {%0,%1,%2,%3};"
      : "+f"(d[0]), "+f"(d[1]), "+f"(d[2]), "+f"(d[3])
      : "r"(a0), "r"(a1), "r"(a2), "r"(a3), "r"(b0), "r"(b1));
}
template <int N>
__device__ __forceinline__ void cs_frac(int idx, float& c, float& s) {
  int i = ((idx + N / 2) & (N - 1)) - N / 2;
  float a = (float)i * (6.283185307179586f / N);
  c = __cosf(a);
  s = __sinf(a);
}
template <int N>
__device__ __forceinline__ uint32_t cfrag(int idx, int ri) {
  float c, s;
  cs_frac<N>(idx, c, s);
  return ri ? pack2(-s, c) : pack2(c, s);
}
__device__ __forceinline__ uint32_t word(const uint4& v, int e) { return e == 0 ? v.x : e == 1 ? v.y : e == 2 ? v.z : v.w; }
__device__ __forceinline__ void cdft16(const uint4 (&q)[4], const uint4 (&F)[4], uint4 (&o)[4]) {
  float acc[2][4][4];
#pragma unroll
  for (int p = 0; p < 2; p++)
#pragma unroll
    for (int v = 0; v < 4; v++) {
      acc[p][v][0] = acc[p][v][1] = acc[p][v][2] = acc[p][v][3] = 0.f;
#pragma unroll
      for (int ks = 0; ks < 2; ks++)
        mma16816(acc[p][v], word(q[2 * ks], 2 * p), word(q[2 * ks], 2 * p + 1), word(q[2 * ks + 1], 2 * p),
                 word(q[2 * ks + 1], 2 * p + 1), word(F[ks * 2 + (v >> 1)], (v & 1) * 2), word(F[ks * 2 + (v >> 1)], (v & 1) * 2 + 1));
    }
#pragma unroll
  for (int v = 0; v < 4; v++)
    o[v] = make_uint4(pack2(acc[0][v][0], acc[0][v][1]), pack2(acc[0][v][2], acc[0][v][3]),
                      pack2(acc[1][v][0], acc[1][v][1]), pack2(acc[1][v][2], acc[1][v][3]));
}
__device__ __forceinline__ void st_tag(uint4* p, const uint4& v, uint32_t tag) {
  asm volatile("{.reg .b128 r; .reg .b64 a, b; mov.b64 a, {%1,%2}; mov.b64 b, {%3,%4}; mov.b128 r, {a,b}; st.relaxed.gpu.global.b128 [%0], r;}"
               ::"l"(p), "r"((v.x & ~1u) | tag), "r"(v.y), "r"(v.z), "r"(v.w) : "memory");
}
__device__ __forceinline__ uint4 ld_b128(const uint4* p) {
  uint4 v;
  asm volatile("{.reg .b128 r; .reg .b64 a, b; ld.relaxed.gpu.global.b128 r, [%4]; mov.b128 {a,b}, r; mov.b64 {%0,%1}, a; mov.b64 {%2,%3}, b;}"
               : "=r"(v.x), "=r"(v.y), "=r"(v.z), "=r"(v.w) : "l"(p) : "memory");
  return v;
}
template <int STRIDE>
__device__ __forceinline__ void ld_tag4_issue(uint4 (&q)[4], const uint4* p) {
#pragma unroll
  for (int i = 0; i < 4; i++) q[i] = ld_b128(p + i * STRIDE);
}
template <int STRIDE>
__device__ __forceinline__ void ld_tag4_finish(uint4 (&q)[4], const uint4* p, uint32_t tag) {
  int it = 0;
#pragma unroll 1
  while (__any_sync(0xffffffffu, ((q[0].x ^ tag) | (q[1].x ^ tag) | (q[2].x ^ tag) | (q[3].x ^ tag)) & 1u)) {
    ld_tag4_issue<STRIDE>(q, p);
    if (++it > SPIN_LIMIT) { die(); break; }
  }
#pragma unroll
  for (int i = 0; i < 4; i++) asm volatile("and.b32 %0, %0, 0xfffffffe;" : "+r"(q[i].x));
}
__device__ __forceinline__ void row_stats(const uint32_t (&a)[8], const uint32_t (&b)[8], int lane, float (&sum)[2], float (&sq)[2]) {
  float da[4] = {0.f, 0.f, 0.f, 0.f}, db[4] = {0.f, 0.f, 0.f, 0.f}, ds[4] = {0.f, 0.f, 0.f, 0.f};
#pragma unroll
  for (int q = 0; q < 4; q++) {
    mma16816(ds, a[2 * q], b[2 * q], a[2 * q + 1], b[2 * q + 1], 0x3f803f80u, 0x3f803f80u);
    mma16816(da, a[2 * q], b[2 * q], a[2 * q + 1], b[2 * q + 1], a[2 * q], a[2 * q + 1]);
    mma16816(db, a[2 * q], b[2 * q], a[2 * q + 1], b[2 * q + 1], b[2 * q], b[2 * q + 1]);
  }
  const int src = (lane & 28) | (lane >> 3);
  const float qa = __shfl_sync(0xffffffffu, (lane & 4) ? da[1] : da[0], src);
  const float qb = __shfl_sync(0xffffffffu, (lane & 4) ? db[3] : db[2], src);
  float v = (lane & 2) ? ((lane & 1) ? ds[2] : ds[0]) : ((lane & 1) ? qb : qa);
  v += __shfl_xor_sync(0xffffffffu, v, 4);
  v += __shfl_xor_sync(0xffffffffu, v, 8);
  v += __shfl_xor_sync(0xffffffffu, v, 16);
  sq[0] = __shfl_sync(0xffffffffu, v, 0);
  sq[1] = __shfl_sync(0xffffffffu, v, 1);
  sum[0] = __shfl_sync(0xffffffffu, v, 2);
  sum[1] = __shfl_sync(0xffffffffu, v, 3);
}
__device__ __forceinline__ uint64_t desc64(uint32_t lo, uint32_t hi) {
  uint64_t d;
  asm("mov.b64 %0, {%1, %2};" : "=l"(d) : "r"(lo), "r"(hi));
  return d;
}
constexpr uint32_t desc_hi(uint32_t sbo, uint32_t swz) { return (sbo >> 4) | (swz << 30); }
__device__ __forceinline__ uint32_t desc_lo(uint32_t addr, uint32_t lbo) { return ((addr & 0x3FFFF) >> 4) | ((lbo >> 4) << 16); }
__device__ __forceinline__ void cp_async16(uint32_t dst, const void* src) {
  asm volatile("cp.async.cg.shared.global [%0], [%1], 16;" ::"r"(dst), "l"(src) : "memory");
}
__device__ __forceinline__ uint2 lds2(uint32_t a) {
  uint2 v;
  asm volatile("ld.shared.v2.u32 {%0,%1}, [%2];" : "=r"(v.x), "=r"(v.y) : "r"(a) : "memory");
  return v;
}
__device__ __forceinline__ uint32_t lds_u16(uint32_t a) {
  uint16_t v;
  asm volatile("ld.shared.u16 %0, [%1];" : "=h"(v) : "r"(a) : "memory");
  return v;
}
__device__ __forceinline__ void wg_fence() { asm volatile("wgmma.fence.sync.aligned;" ::: "memory"); }
__device__ __forceinline__ void wg_commit() { asm volatile("wgmma.commit_group.sync.aligned;" ::: "memory"); }
template <int N>
__device__ __forceinline__ void wg_wait() { asm volatile("wgmma.wait_group.sync.aligned %0;" ::"n"(N) : "memory"); }
__device__ __forceinline__ void bulk_load(uint32_t dst, const void* src, int bytes, uint32_t bar) {
  asm volatile("cp.async.bulk.shared::cluster.global.mbarrier::complete_tx::bytes [%0], [%1], %2, [%3];"
               ::"r"(dst), "l"(src), "r"(bytes), "r"(bar) : "memory");
}
__device__ __forceinline__ void tma3(uint32_t dst, const CUtensorMap* tm, uint32_t bar, int c0, int c1, int c2) {
  asm volatile("cp.async.bulk.tensor.3d.shared::cluster.global.mbarrier::complete_tx::bytes [%0], [%1, {%3,%4,%5}], [%2];"
               ::"r"(dst), "l"(tm), "r"(bar), "r"(c0), "r"(c1), "r"(c2) : "memory");
}
__device__ __forceinline__ void tma3_mc(uint32_t dst, const CUtensorMap* tm, uint32_t bar, int c1, int c2) {
  asm volatile("cp.async.bulk.tensor.3d.shared::cluster.global.mbarrier::complete_tx::bytes.multicast::cluster [%0], [%1, {%3,%4,%5}], [%2], %6;"
               ::"r"(dst), "l"(tm), "r"(bar), "r"(0), "r"(c1), "r"(c2), "h"((uint16_t)3) : "memory");
}
__device__ __forceinline__ void mbar_arrive_remote(uint32_t rb) {
  asm volatile("mbarrier.arrive.shared::cluster.b64 _, [%0];" ::"r"(rb) : "memory");
}
__device__ __forceinline__ uint4 ldg_ca4(const void* p) {
  uint4 v;
  asm volatile("ld.global.ca.v4.u32 {%0,%1,%2,%3}, [%4];" : "=r"(v.x), "=r"(v.y), "=r"(v.z), "=r"(v.w) : "l"(p) : "memory");
  return v;
}
__device__ __forceinline__ uint32_t clock32() {
  uint32_t v;
  asm volatile("mov.u32 %0, %%clock;" : "=r"(v) :: "memory");
  return v;
}
__device__ __forceinline__ float swiglu(float g, float u, float r) {
  float hg = (0.5f * r) * g, th;
  asm("tanh.approx.f32 %0, %1;" : "=f"(th) : "f"(hg));
  return fmaf(hg, th, hg) * (r * u);
}
__device__ __forceinline__ uint32_t hsub2_bf16(uint32_t a, uint32_t b) {
  uint32_t r;
  asm("sub.rn.bf16x2 %0, %1, %2;" : "=r"(r) : "r"(a), "r"(b));
  return r;
}
__device__ __forceinline__ void l2_prefetch(const void* p, int bytes) {
  asm volatile("cp.async.bulk.prefetch.L2.global [%0], %1;" ::"l"(p), "r"(bytes) : "memory");
}

__device__ __forceinline__ void wgmma_n256(float (&d)[128], uint64_t da, uint64_t db) {
  asm volatile("wgmma.mma_async.sync.aligned.m64n256k16.f32.bf16.bf16 {"
      "%0,%1,%2,%3,%4,%5,%6,%7,%8,%9,%10,%11,%12,%13,%14,%15,"
      "%16,%17,%18,%19,%20,%21,%22,%23,%24,%25,%26,%27,%28,%29,%30,%31,"
      "%32,%33,%34,%35,%36,%37,%38,%39,%40,%41,%42,%43,%44,%45,%46,%47,"
      "%48,%49,%50,%51,%52,%53,%54,%55,%56,%57,%58,%59,%60,%61,%62,%63,"
      "%64,%65,%66,%67,%68,%69,%70,%71,%72,%73,%74,%75,%76,%77,%78,%79,"
      "%80,%81,%82,%83,%84,%85,%86,%87,%88,%89,%90,%91,%92,%93,%94,%95,"
      "%96,%97,%98,%99,%100,%101,%102,%103,%104,%105,%106,%107,%108,%109,%110,%111,"
      "%112,%113,%114,%115,%116,%117,%118,%119,%120,%121,%122,%123,%124,%125,%126,%127"
      "}, %128, %129, 1, 1, 1, 0, 1;\n"
      : "+f"(d[0]),"+f"(d[1]),"+f"(d[2]),"+f"(d[3]),"+f"(d[4]),"+f"(d[5]),"+f"(d[6]),"+f"(d[7]),
        "+f"(d[8]),"+f"(d[9]),"+f"(d[10]),"+f"(d[11]),"+f"(d[12]),"+f"(d[13]),"+f"(d[14]),"+f"(d[15]),
        "+f"(d[16]),"+f"(d[17]),"+f"(d[18]),"+f"(d[19]),"+f"(d[20]),"+f"(d[21]),"+f"(d[22]),"+f"(d[23]),
        "+f"(d[24]),"+f"(d[25]),"+f"(d[26]),"+f"(d[27]),"+f"(d[28]),"+f"(d[29]),"+f"(d[30]),"+f"(d[31]),
        "+f"(d[32]),"+f"(d[33]),"+f"(d[34]),"+f"(d[35]),"+f"(d[36]),"+f"(d[37]),"+f"(d[38]),"+f"(d[39]),
        "+f"(d[40]),"+f"(d[41]),"+f"(d[42]),"+f"(d[43]),"+f"(d[44]),"+f"(d[45]),"+f"(d[46]),"+f"(d[47]),
        "+f"(d[48]),"+f"(d[49]),"+f"(d[50]),"+f"(d[51]),"+f"(d[52]),"+f"(d[53]),"+f"(d[54]),"+f"(d[55]),
        "+f"(d[56]),"+f"(d[57]),"+f"(d[58]),"+f"(d[59]),"+f"(d[60]),"+f"(d[61]),"+f"(d[62]),"+f"(d[63]),
        "+f"(d[64]),"+f"(d[65]),"+f"(d[66]),"+f"(d[67]),"+f"(d[68]),"+f"(d[69]),"+f"(d[70]),"+f"(d[71]),
        "+f"(d[72]),"+f"(d[73]),"+f"(d[74]),"+f"(d[75]),"+f"(d[76]),"+f"(d[77]),"+f"(d[78]),"+f"(d[79]),
        "+f"(d[80]),"+f"(d[81]),"+f"(d[82]),"+f"(d[83]),"+f"(d[84]),"+f"(d[85]),"+f"(d[86]),"+f"(d[87]),
        "+f"(d[88]),"+f"(d[89]),"+f"(d[90]),"+f"(d[91]),"+f"(d[92]),"+f"(d[93]),"+f"(d[94]),"+f"(d[95]),
        "+f"(d[96]),"+f"(d[97]),"+f"(d[98]),"+f"(d[99]),"+f"(d[100]),"+f"(d[101]),"+f"(d[102]),"+f"(d[103]),
        "+f"(d[104]),"+f"(d[105]),"+f"(d[106]),"+f"(d[107]),"+f"(d[108]),"+f"(d[109]),"+f"(d[110]),"+f"(d[111]),
        "+f"(d[112]),"+f"(d[113]),"+f"(d[114]),"+f"(d[115]),"+f"(d[116]),"+f"(d[117]),"+f"(d[118]),"+f"(d[119]),
        "+f"(d[120]),"+f"(d[121]),"+f"(d[122]),"+f"(d[123]),"+f"(d[124]),"+f"(d[125]),"+f"(d[126]),"+f"(d[127])
      : "l"(da), "l"(db));
}
__device__ __forceinline__ void wgmma_n192(float (&d)[96], uint64_t da, uint64_t db) {
  asm volatile("wgmma.mma_async.sync.aligned.m64n192k16.f32.bf16.bf16 {"
      "%0,%1,%2,%3,%4,%5,%6,%7,%8,%9,%10,%11,%12,%13,%14,%15,"
      "%16,%17,%18,%19,%20,%21,%22,%23,%24,%25,%26,%27,%28,%29,%30,%31,"
      "%32,%33,%34,%35,%36,%37,%38,%39,%40,%41,%42,%43,%44,%45,%46,%47,"
      "%48,%49,%50,%51,%52,%53,%54,%55,%56,%57,%58,%59,%60,%61,%62,%63,"
      "%64,%65,%66,%67,%68,%69,%70,%71,%72,%73,%74,%75,%76,%77,%78,%79,"
      "%80,%81,%82,%83,%84,%85,%86,%87,%88,%89,%90,%91,%92,%93,%94,%95"
      "}, %96, %97, 1, 1, 1, 0, 1;\n"
      : "+f"(d[0]),"+f"(d[1]),"+f"(d[2]),"+f"(d[3]),"+f"(d[4]),"+f"(d[5]),"+f"(d[6]),"+f"(d[7]),
        "+f"(d[8]),"+f"(d[9]),"+f"(d[10]),"+f"(d[11]),"+f"(d[12]),"+f"(d[13]),"+f"(d[14]),"+f"(d[15]),
        "+f"(d[16]),"+f"(d[17]),"+f"(d[18]),"+f"(d[19]),"+f"(d[20]),"+f"(d[21]),"+f"(d[22]),"+f"(d[23]),
        "+f"(d[24]),"+f"(d[25]),"+f"(d[26]),"+f"(d[27]),"+f"(d[28]),"+f"(d[29]),"+f"(d[30]),"+f"(d[31]),
        "+f"(d[32]),"+f"(d[33]),"+f"(d[34]),"+f"(d[35]),"+f"(d[36]),"+f"(d[37]),"+f"(d[38]),"+f"(d[39]),
        "+f"(d[40]),"+f"(d[41]),"+f"(d[42]),"+f"(d[43]),"+f"(d[44]),"+f"(d[45]),"+f"(d[46]),"+f"(d[47]),
        "+f"(d[48]),"+f"(d[49]),"+f"(d[50]),"+f"(d[51]),"+f"(d[52]),"+f"(d[53]),"+f"(d[54]),"+f"(d[55]),
        "+f"(d[56]),"+f"(d[57]),"+f"(d[58]),"+f"(d[59]),"+f"(d[60]),"+f"(d[61]),"+f"(d[62]),"+f"(d[63]),
        "+f"(d[64]),"+f"(d[65]),"+f"(d[66]),"+f"(d[67]),"+f"(d[68]),"+f"(d[69]),"+f"(d[70]),"+f"(d[71]),
        "+f"(d[72]),"+f"(d[73]),"+f"(d[74]),"+f"(d[75]),"+f"(d[76]),"+f"(d[77]),"+f"(d[78]),"+f"(d[79]),
        "+f"(d[80]),"+f"(d[81]),"+f"(d[82]),"+f"(d[83]),"+f"(d[84]),"+f"(d[85]),"+f"(d[86]),"+f"(d[87]),
        "+f"(d[88]),"+f"(d[89]),"+f"(d[90]),"+f"(d[91]),"+f"(d[92]),"+f"(d[93]),"+f"(d[94]),"+f"(d[95])
      : "l"(da), "l"(db));
}
__device__ __forceinline__ void wgmma_rs_n128(float (&d)[64], uint32_t a0, uint32_t a1, uint32_t a2, uint32_t a3, uint64_t db) {
  asm volatile("wgmma.mma_async.sync.aligned.m64n128k16.f32.bf16.bf16 {"
      "%0,%1,%2,%3,%4,%5,%6,%7,%8,%9,%10,%11,%12,%13,%14,%15,"
      "%16,%17,%18,%19,%20,%21,%22,%23,%24,%25,%26,%27,%28,%29,%30,%31,"
      "%32,%33,%34,%35,%36,%37,%38,%39,%40,%41,%42,%43,%44,%45,%46,%47,"
      "%48,%49,%50,%51,%52,%53,%54,%55,%56,%57,%58,%59,%60,%61,%62,%63"
      "}, {%64,%65,%66,%67}, %68, 1, 1, 1, 1;\n"
      : "+f"(d[0]),"+f"(d[1]),"+f"(d[2]),"+f"(d[3]),"+f"(d[4]),"+f"(d[5]),"+f"(d[6]),"+f"(d[7]),
        "+f"(d[8]),"+f"(d[9]),"+f"(d[10]),"+f"(d[11]),"+f"(d[12]),"+f"(d[13]),"+f"(d[14]),"+f"(d[15]),
        "+f"(d[16]),"+f"(d[17]),"+f"(d[18]),"+f"(d[19]),"+f"(d[20]),"+f"(d[21]),"+f"(d[22]),"+f"(d[23]),
        "+f"(d[24]),"+f"(d[25]),"+f"(d[26]),"+f"(d[27]),"+f"(d[28]),"+f"(d[29]),"+f"(d[30]),"+f"(d[31]),
        "+f"(d[32]),"+f"(d[33]),"+f"(d[34]),"+f"(d[35]),"+f"(d[36]),"+f"(d[37]),"+f"(d[38]),"+f"(d[39]),
        "+f"(d[40]),"+f"(d[41]),"+f"(d[42]),"+f"(d[43]),"+f"(d[44]),"+f"(d[45]),"+f"(d[46]),"+f"(d[47]),
        "+f"(d[48]),"+f"(d[49]),"+f"(d[50]),"+f"(d[51]),"+f"(d[52]),"+f"(d[53]),"+f"(d[54]),"+f"(d[55]),
        "+f"(d[56]),"+f"(d[57]),"+f"(d[58]),"+f"(d[59]),"+f"(d[60]),"+f"(d[61]),"+f"(d[62]),"+f"(d[63])
      : "r"(a0), "r"(a1), "r"(a2), "r"(a3), "l"(db));
}

constexpr int C_LN = 0, C_PX = 16, C_PY = 32;
constexpr int NB_CONS = 1, NB_LN = 2, NB_LAG = 4, NB_INIT = 6, NB_RDY = 7;
#define LAGX 3
#define LAGY 3
#define LAG2 2
#define NLL 2
#define POLL_DELAY3 900
#define POLL_DELAY 900
#define RING_SIG 0
#define PF2_SIG 1
constexpr int SM_E = 0, SM_X = 16384, SM_E2 = 32768, SM_W = 49152, SM_FC = 69632, SM_T = 73728 - T1_BYTES;
constexpr unsigned long long KORDER = 0xBA9432DC876510ull;
constexpr uint32_t HI128 = desc_hi(1024, 1), HI64 = desc_hi(512, 2);

struct Bars {
  uint64_t full1[6], empty1[6], fullA[8], full2[14], empty2[8], xbar, xfree, hbar, tbar, sbar, sig[2];
  uint32_t epoch;
};

template <int NK>
__device__ __forceinline__ void make_p(const float (&acc)[NK * 16], float r0, float r1, uint4 (&p)[NK]) {
#pragma unroll
  for (int j = 0; j < NK; j++) {
    uint32_t w[4];
#pragma unroll
    for (int i = 0; i < 4; i++) {
      const int a = 8 * j + 2 * i, b = a + NK * 8;
      w[i] = pack2(swiglu(acc[a], acc[b], (i & 1) ? r1 : r0), swiglu(acc[a + 1], acc[b + 1], (i & 1) ? r1 : r0));
    }
    asm volatile("" : "+r"(w[0]), "+r"(w[1]), "+r"(w[2]), "+r"(w[3]));
    p[j] = make_uint4(w[0], w[1], w[2], w[3]);
  }
}
__device__ __forceinline__ void spin_cycles(uint32_t n) {
  const uint32_t t0 = clock32();
  while (clock32() - t0 < n) {}
}

__global__ void __cluster_dims__(2, 1, 1) __launch_bounds__(NTHREADS, 1)
fused_kernel(const __nv_bfloat16* __restrict__ x, const Tables* __restrict__ tab, Scratch* __restrict__ scr,
             __nv_bfloat16* __restrict__ out, const char* __restrict__ wg_raw, const char* __restrict__ wu_raw,
             const char* __restrict__ wd_raw,
             const __grid_constant__ CUtensorMap tmWR, const __grid_constant__ CUtensorMap tmWI,
             const __grid_constant__ CUtensorMap tmGX, const __grid_constant__ CUtensorMap tmUX,
             const __grid_constant__ CUtensorMap tmGY, const __grid_constant__ CUtensorMap tmUY,
             const __grid_constant__ CUtensorMap tmD) {
  extern __shared__ __align__(1024) char smem_raw[];
  const uint32_t sbase = (s2u(smem_raw) + 1023) & ~1023u;
  const uint32_t sbar = sbase + 14 * SLOT, sstat = sbar + 512;
  const int tid = threadIdx.x, lane = tid & 31;
  const int c = blockIdx.x, kh = c & 1, f = (c >> 1) & 7, rb = 2 * (c >> 4) + kh, rb2 = 2 * (c >> 4) + (f >> 2), nq = f & 3;
#define BAR(field, i) (sbar + (uint32_t)offsetof(Bars, field) + 8u * (i))
#define TOFF(field) (sbase + SM_T + (uint32_t)offsetof(Tables, field) + lane * 16)

  if (tid >= 256) {
    asm volatile("setmaxnreg.dec.sync.aligned.u32 56;");
    const int warp = __shfl_sync(0xffffffffu, tid >> 5, 0);
    if (tid == 256) {
      for (int i = 0; i < 6; i++) { mbar_init(BAR(full1, i), 1); mbar_init(BAR(empty1, i), 16); }
      for (int i = 0; i < 8; i++) { mbar_init(BAR(fullA, i), 1); mbar_init(BAR(empty2, i), 8); }
      for (int i = 0; i < 14; i++) mbar_init(BAR(full2, i), 2);
      mbar_init(BAR(xbar, 0), 1);
      mbar_init(BAR(xfree, 0), 8);
      mbar_init(BAR(tbar, 0), 1);
      mbar_init(BAR(hbar, 0), 1);
      mbar_init(BAR(sbar, 0), 32);
      mbar_init(BAR(sig, 0), 8);
      mbar_init(BAR(sig, 1), 8);
      mbar_expect(BAR(xbar, 0), 16384);
      asm volatile("fence.mbarrier_init.release.cluster;" ::: "memory");
      const int w0 = ((c >> 3) * 257 + 32 * (c & 7) + 1) & ~7;
      mbar_expect(BAR(tbar, 0), T2_BYTES + 2 * 10240);
      tma3(sbase + SM_W, &tmWR, BAR(tbar, 0), w0, 0, 0);
      tma3(sbase + SM_W + 10240, &tmWI, BAR(tbar, 0), w0, 0, 0);
      bulk_load(sbase + SM_T + T1_BYTES, reinterpret_cast<const char*>(tab) + T1_BYTES, T2_BYTES, BAR(tbar, 0));
    }
    if (tid == 288) {
      asm volatile("prefetch.tensormap [%0];" ::"l"(kh ? &tmUX : &tmGX) : "memory");
      asm volatile("prefetch.tensormap [%0];" ::"l"(kh ? &tmUY : &tmGY) : "memory");
      asm volatile("prefetch.tensormap [%0];" ::"l"(&tmD) : "memory");
    }
    if (tid == 320) {
      const unsigned e = ld_relaxed(&scr->cnt[(C_LN + rb) * 32]) >> 3;
      asm volatile("st.shared.u32 [%0], %1;" ::"r"(BAR(epoch, 0)), "r"(e) : "memory");
    }
    __syncwarp();
    asm volatile("barrier.cluster.arrive.relaxed.aligned;" ::: "memory");
    bar_arrive(NB_RDY, 384);
    asm volatile("barrier.cluster.wait.aligned;" ::: "memory");
    bar_sync(NB_INIT, 384);
    unsigned epoch;
    asm volatile("ld.shared.u32 %0, [%1];" : "=r"(epoch) : "r"(BAR(epoch, 0)) : "memory");
    if (warp == 8) {
      if (lane == 0) {
        const int ax = (7 * f + 3 * (f & 1)) >> 1;
        const int ay = 7 * f + ((f & 1) ? 0 : 4);
        const CUtensorMap* tx = kh ? &tmUX : &tmGX;
        const CUtensorMap* ty = kh ? &tmUY : &tmGY;
        uint32_t s = 0, ph = 1;
        if (RING_SIG >= 0) mbar_wait(BAR(sig, RING_SIG), 0);
#pragma unroll 1
        for (int n = 0; n < 32; n++) {
          const uint32_t dst = sbase + (8 + s) * SLOT, fb = BAR(full1, s);
          mbar_wait(BAR(empty1, s), ph);
          if (n < 16) {
            mbar_expect(fb, 16384);
            tma3_mc(dst + kh * 8192, tx, fb, n * 32, ax);
          } else {
            mbar_expect(fb, 12288);
            tma3_mc(dst + kh * 6144, ty, fb, (n - 16) * 32, ay);
          }
          if (++s == 6) { s = 0; ph ^= 1; }
        }
      }
    } else if (warp == 9) {
      if (lane == 0) {
        mbar_wait(BAR(empty1, 5), 0);
        mbar_wait(BAR(empty1, 5), 1);
#pragma unroll 1
        for (int i = 0; i < 14; i++) {
          const int kblk = 14 * kh + (int)((KORDER >> (4 * i)) & 15);
          if (i < 8) mbar_wait(BAR(empty1, (17 + 2 * i) % 6), ((17 + 2 * i) / 6) & 1);
          else mbar_wait(BAR(empty2, i - 8), 0);
          mbar_expect(BAR(full2, i), 16384);
          tma3(sbase + (i & 7) * SLOT, &tmD, BAR(full2, i), 0, 64 * kblk, 2 * nq);
        }
        wait_counter(&scr->cnt[(C_LN + rb2) * 32], (epoch + 1) * 8);
        asm volatile("fence.proxy.async.global;" ::: "memory");
        mbar_wait(BAR(empty2, 7), 0);
        mbar_expect(BAR(hbar, 0), 16384);
        bulk_load(sbase + 7 * SLOT, &scr->LN[(rb2 * 8 + 2 * nq) * 1024 + kh * 512], 8192, BAR(hbar, 0));
        bulk_load(sbase + 7 * SLOT + 8192, &scr->LN[(rb2 * 8 + 2 * nq + 1) * 1024 + kh * 512], 8192, BAR(hbar, 0));
      }
    } else if (warp == 10) {
      bar_sync(NB_LN, 288);
      if (lane == 0) {
        PROFP(0);
        red_release(&scr->cnt[(C_LN + rb) * 32]);
        PROFP(1);
        wait_counter(&scr->cnt[(C_LN + rb) * 32], (epoch + 1) * 8);
        asm volatile("fence.proxy.async.global;" ::: "memory");
        PROFP(2);
#pragma unroll 1
        for (int kb = NLL; kb < 8; kb++) {
          mbar_expect(BAR(fullA, kb), 16384);
          bulk_load(sbase + kb * SLOT, &scr->LN[(rb * 8 + kb) * 1024], 16384, BAR(fullA, kb));
        }
#pragma unroll 1
        for (int i = 0; i < 4; i++) mbar_wait(BAR(empty1, 2), i & 1);
        uint32_t d = 2;
#pragma unroll 1
        for (int s = 0; s < 14; s++) {
          const int kblk = 14 * kh + (int)((KORDER >> (4 * s)) & 15);
          if (s == 0 || s == 8 || s == 11) {
            if (s != 11) PROFP(3 + (s >> 2));
            const unsigned* cp = s == 0 ? &scr->cnt[(C_PX + rb2) * 32] : &scr->cnt[(C_PY + rb2) * 32 + 2 * kh + (s == 11)];
            int it = 0;
            while ((int)(ld_relaxed(cp) - (epoch + 1) * (s == 0 ? 64 : 16)) < 0)
              if (++it > SPIN_LIMIT) { die(); break; }
            if (s != 11) PROFP(4 + (s >> 2));
          }
          if (s < 6) mbar_wait(BAR(empty1, d), s < 4 ? 0 : 1);
          else mbar_wait(BAR(empty2, s - 6), 0);
          mbar_expect(BAR(full2, s), 16384);
          bulk_load(sbase + (8 + d) * SLOT, &scr->P[(rb2 * 28 + kblk) * 1024], 16384, BAR(full2, s));
          if (++d == 6) d = 0;
        }
        PROFP(7);
      }
    } else {
      if (lane == 0) {
        l2_prefetch(wg_raw + (size_t)c * 5376, 5376);
        l2_prefetch(wu_raw + (size_t)c * 5376, 5376);
        mbar_wait(BAR(sig, PF2_SIG), 0);
        l2_prefetch(wg_raw + 688128 + (size_t)c * 8960, 8960);
        l2_prefetch(wu_raw + 688128 + (size_t)c * 8960, 8960);
      }
      mbar_wait(BAR(fullA, 7), 0);
      if (lane == 0) l2_prefetch(wd_raw + (size_t)c * 14336, 14336);
      {
        const uint32_t tag = (epoch + 1) & 1;
        uint4 v0, v1, v2;
        int it = 0;
        while (true) {
          v0 = ld_b128(&scr->ST[rb * 64 + lane]);
          v1 = ld_b128(&scr->ST[rb * 64 + 32 + lane]);
          v2 = ld_b128(&scr->ST[rb2 * 64 + 32 * kh + lane]);
          if (!__any_sync(0xffffffffu, ((v0.x ^ tag) | (v1.x ^ tag) | (v2.x ^ tag)) & 1u)) break;
          if (++it > SPIN_LIMIT) { die(); break; }
        }
        sts4(sstat + lane * 16, v0.x & ~1u, v0.y, v0.z, v0.w);
        sts4(sstat + 512 + lane * 16, v1.x & ~1u, v1.y, v1.z, v1.w);
        sts4(sstat + 1024 + lane * 16, v2.x & ~1u, v2.y, v2.z, v2.w);
        mbar_arrive(BAR(sbar, 0));
      }
    }
  } else {
    const int warp = __shfl_sync(0xffffffffu, tid >> 5, 0);
    const int g = lane >> 2, t = lane & 3;
    PROF(0);
    PROFG(14);
#pragma unroll
    for (int i = 0; i < 4; i++) {
      const int r = i >> 1, ch = (i & 1) * 32 + lane;
      cp_async16(sbase + SM_X + (2 * warp + r) * 1024 + ((ch ^ ((ch >> 2) & 6)) * 16),
                 x + (size_t)(c + 128 * (2 * warp + r)) * 512 + ch * 8);
    }
    asm volatile("cp.async.commit_group;" ::: "memory");
    asm volatile("barrier.cluster.arrive.relaxed.aligned;" ::: "memory");
    asm volatile("setmaxnreg.inc.sync.aligned.u32 224;");
    uint4 tw[8], fb[16];
    const uint4 fa = ldg_ca4(&tab->fa[lane][0]);
#pragma unroll
    for (int i = 0; i < 8; i++) tw[i] = ldg_ca4(&tab->tw1[i][lane][0]);
#pragma unroll
    for (int i = 0; i < 16; i++) fb[i] = ldg_ca4(&tab->fb[i][lane][0]);
    uint32_t rbar;
    asm volatile("mapa.shared::cluster.u32 %0, %1, %2;" : "=r"(rbar) : "r"(sbar), "r"(kh ^ 1));
#define RBAR(field, i) (rbar + (uint32_t)offsetof(Bars, field) + 8u * (i))
    {
      const int ln = (tid >> 1) & 31, lg = ln >> 2, lt = ln & 3, i = 4 * (tid >> 6) + 2 * (tid & 1);
      const int kidx = lt + 8 * (i >> 3), nidx = 4 * ((i >> 1) & 3) + (lg >> 1);
      const uint32_t a0 = cfrag<2048>((c + 128 * kidx) * nidx, lg & 1), a1 = cfrag<2048>((c + 128 * (kidx + 4)) * nidx, lg & 1);
      const uint32_t b0 = cfrag<2048>(-(c + 128 * nidx) * kidx, lg & 1), b1 = cfrag<2048>(-(c + 128 * nidx) * (kidx + 4), lg & 1);
      asm volatile("st.shared.v2.u32 [%0], {%1,%2};" ::"r"(sbase + SM_FC + tid * 8), "r"(a0), "r"(a1) : "memory");
      asm volatile("st.shared.v2.u32 [%0], {%1,%2};" ::"r"(sbase + SM_FC + 2048 + tid * 8), "r"(b0), "r"(b1) : "memory");
    }
    asm volatile("cp.async.wait_group 0;" ::: "memory");
    __syncwarp();
    bar_arrive(NB_INIT, 384);
    PROF(13);
    uint32_t tag;
    uint4 q[4], o[4];
    {
      uint32_t v[2][8];
#pragma unroll
      for (int r = 0; r < 2; r++)
#pragma unroll
        for (int q = 0; q < 4; q++) {
          const uint2 u = lds2(sbase + SM_X + (2 * warp + r) * 1024 + (t + 4 * (q >> 1)) * 128 + (((4 * (q & 1) + (g >> 1)) ^ (2 * t)) * 16) + (g & 1) * 8);
          v[r][2 * q] = u.x; v[r][2 * q + 1] = u.y;
        }
      float sum[2], sq[2], rstd[2];
      row_stats(v[0], v[1], lane, sum, sq);
#pragma unroll
      for (int r = 0; r < 2; r++) {
        const float m = sum[r] * (1.f / 512.f);
        rstd[r] = rsqrtf(fmaxf(fmaf(-m, m, sq[r] * (1.f / 512.f)), 0.f) + 1e-5f);
      }
      uint32_t alo[4][4], ahi[4][4];
#pragma unroll
      for (int r = 0; r < 2; r++)
#pragma unroll
        for (int i = 0; i < 4; i++) {
          const uint32_t sel = (i & 1) ? 0x7632u : 0x5410u;
          const uint32_t b0 = __byte_perm(v[r][i >> 1], v[r][2 + (i >> 1)], sel);
          const uint32_t b1 = __byte_perm(v[r][4 + (i >> 1)], v[r][6 + (i >> 1)], sel);
          float d[4] = {0.f, 0.f, 0.f, 0.f};
          mma16816(d, fa.x, fa.y, fa.z, fa.w, b0, b1);
          const uint4 &ka = tw[2 * i], &kb = tw[2 * i + 1];
          const uint32_t re = pack2(d[0] * __uint_as_float(ka.x) + d[2] * __uint_as_float(ka.y), d[1] * __uint_as_float(kb.x) + d[3] * __uint_as_float(kb.y));
          const uint32_t im = pack2(d[0] * __uint_as_float(ka.z) + d[2] * __uint_as_float(ka.w), d[1] * __uint_as_float(kb.z) + d[3] * __uint_as_float(kb.w));
          const uint32_t dc = pack2(fmaf(sum[r], -1.f / 32.f, d[0]), fmaf(sum[r], -1.f / 32.f, d[1]));
          alo[i][r] = re; alo[i][2 + r] = im;
          ahi[i][r] = g == 0 ? dc : re; ahi[i][2 + r] = g == 0 ? 0u : im;
        }
      float acc[8][4];
#pragma unroll
      for (int u = 0; u < 8; u++) {
        acc[u][0] = acc[u][1] = acc[u][2] = acc[u][3] = 0.f;
#pragma unroll
        for (int i = 0; i < 4; i++) {
          const uint4& bq = fb[i * 4 + (u >> 1)];
          if (u < 4) mma16816(acc[u], alo[i][0], alo[i][1], alo[i][2], alo[i][3], (u & 1) ? bq.z : bq.x, (u & 1) ? bq.w : bq.y);
          else       mma16816(acc[u], ahi[i][0], ahi[i][1], ahi[i][2], ahi[i][3], (u & 1) ? bq.z : bq.x, (u & 1) ? bq.w : bq.y);
        }
      }
#pragma unroll
      for (int r = 0; r < 2; r++)
#pragma unroll
        for (int h = 0; h < 2; h++) {
          const int j = 2 * warp + r, m = 2 * t + h;
          const float rs = rstd[r];
          sts4(sbase + SM_E + ((j * 8 + m) * 8 + (g ^ (2 * t) ^ (2 * (j & 3)))) * 16,
               pack2(acc[2 * h][2 * r] * rs, acc[2 * h][2 * r + 1] * rs), pack2(acc[2 * h + 1][2 * r] * rs, acc[2 * h + 1][2 * r + 1] * rs),
               pack2(acc[4 + 2 * h][2 * r] * rs, acc[4 + 2 * h][2 * r + 1] * rs), pack2(acc[5 + 2 * h][2 * r] * rs, acc[5 + 2 * h][2 * r + 1] * rs));
        }
      if (tid == 0) PROFP(12);
      bar_sync(NB_RDY, 384);
      if (tid == 0) PROFP(13);
      uint4 fc[4];
#pragma unroll
      for (int i = 0; i < 4; i++) fc[i] = lds4(sbase + SM_FC + i * 512 + lane * 16);
      asm volatile("ld.shared.u32 %0, [%1];" : "=r"(tag) : "r"(BAR(epoch, 0)) : "memory");
      tag = (tag + 1) & 1;
#pragma unroll
      for (int i = 0; i < 4; i++) q[i] = lds4(sbase + SM_E + (((t + 4 * i) * 8 + warp) * 8 + (g ^ (warp & 6) ^ (2 * t))) * 16);
      cdft16(q, fc, o);
#pragma unroll
      for (int vv = 0; vv < 4; vv++) st_tag(&scr->Z1[(((4 * vv + t) * 8 + warp) * 128 + c) * 8 + g], o[vv], tag);
    }
    PROF(1);
    {
      const uint4* const zp = &scr->Z1[(c * 128 + 8 * t + warp) * 8 + g];
      const uint32_t tst = clock32();
      mbar_wait(BAR(tbar, 0), 0);
      if (tid == 0) PROFP(14);
      uint4 f2[4], g2[4];
#pragma unroll
      for (int i = 0; i < 4; i++) {
        f2[i] = lds4(TOFF(f2) + warp * 2048 + i * 512);
        g2[i] = lds4(TOFF(g2) + warp * 2048 + i * 512);
      }
      const uint4 f8 = lds4(TOFF(f8)), g8 = lds4(TOFF(g8));
      float wfr[16], wfi[16];
      {
        const float fsc = 1.f / (1 << 19);
        const float fsc3 = ((c & 7) == 7 && g == 0) ? 0.5f * fsc : fsc;
        const int gg = g == 0 ? 8 : g, wsh = (2 * (c >> 3) + 2) & 15;
#pragma unroll
        for (int i = 0; i < 16; i++) {
          const int ci = i >> 3, dd = (i >> 2) & 1, e = i & 3;
          const int kk = (e == 0 ? gg : e == 1 ? 16 + gg : e == 2 ? 16 - g : 32 - g) - 1;
          const uint32_t a = sbase + SM_W + ((2 * warp + ci) * 8 + t + 4 * dd) * 80 + wsh + 2 * kk;
          wfr[i] = bf_lo(lds_u16(a)) * (e == 3 ? fsc3 : fsc);
          wfi[i] = bf_lo(lds_u16(a + 10240)) * (e == 3 ? fsc3 : fsc);
        }
      }
      asm volatile("barrier.cluster.wait.aligned;" ::: "memory");
      PROF(2);
      while (clock32() - tst < POLL_DELAY) {}
      ld_tag4_issue<256>(q, zp);
      ld_tag4_finish<256>(q, zp, tag);
      if (tid == 0) PROFP(30);
      if (lane == 0) mbar_arrive(BAR(sig, 0));
      cdft16(q, f2, o);
      const uint32_t e2 = sbase + SM_E2;
#pragma unroll
      for (int vv = 0; vv < 4; vv++)
        sts4(e2 + ((warp * 16 + 4 * vv + t) * 8 + (g ^ (2 * t) ^ (2 * (warp & 3)))) * 16, o[vv].x, o[vv].y, o[vv].z, o[vv].w);
      bar_sync(NB_CONS, 256);
#pragma unroll
      for (int ci = 0; ci < 2; ci++) {
        const int cc = 2 * warp + ci;
        uint32_t ad[2];
        uint4 u[2];
#pragma unroll
        for (int hh = 0; hh < 2; hh++) {
          ad[hh] = e2 + (((t + 4 * hh) * 16 + cc) * 8 + (g ^ (2 * (cc & 3)) ^ (2 * t))) * 16;
          u[hh] = lds4(ad[hh]);
        }
        uint32_t res[2][4];
#pragma unroll
        for (int p = 0; p < 2; p++) {
          uint32_t y[2][2];
#pragma unroll
          for (int vv = 0; vv < 2; vv++) {
            float d[4] = {0.f, 0.f, 0.f, 0.f};
            mma16816(d, word(u[0], 2 * p), word(u[0], 2 * p + 1), word(u[1], 2 * p), word(u[1], 2 * p + 1), word(f8, 2 * vv), word(f8, 2 * vv + 1));
#pragma unroll
            for (int rr = 0; rr < 2; rr++) {
              const float fr = wfr[ci * 8 + vv * 4 + 2 * p + rr], fi = wfi[ci * 8 + vv * 4 + 2 * p + rr];
              y[vv][rr] = pack2(d[2 * rr] * fr - d[2 * rr + 1] * fi, d[2 * rr] * fi + d[2 * rr + 1] * fr);
            }
          }
#pragma unroll
          for (int vv = 0; vv < 2; vv++) {
            float d[4] = {0.f, 0.f, 0.f, 0.f};
            mma16816(d, y[0][0], y[0][1], y[1][0], y[1][1], word(g8, 2 * vv), word(g8, 2 * vv + 1));
            res[vv][2 * p] = pack2(d[0], d[1]);
            res[vv][2 * p + 1] = pack2(d[2], d[3]);
          }
        }
#pragma unroll
        for (int vv = 0; vv < 2; vv++) sts4(ad[vv], res[vv][0], res[vv][1], res[vv][2], res[vv][3]);
      }
      bar_sync(NB_CONS, 256);
#pragma unroll
      for (int i = 0; i < 4; i++) q[i] = lds4(e2 + ((warp * 16 + 4 * i + t) * 8 + (g ^ (2 * t) ^ (2 * (warp & 3)))) * 16);
      cdft16(q, g2, o);
#pragma unroll
      for (int vv = 0; vv < 4; vv++) st_tag(&scr->Z2[((8 * (4 * vv + t) + warp) * 128 + c) * 8 + g], o[vv], tag);
    }
    PROF(3);
    {
      const uint4* const zp = &scr->Z2[((c * 16 + t) * 8 + warp) * 8 + g];
      const uint32_t tst = clock32();
      uint4 gb[16], gc[4], tw[4], xr[2][2];
#pragma unroll
      for (int i = 0; i < 16; i++) gb[i] = lds4(TOFF(gb) + i * 512);
      const uint4 ga = lds4(TOFF(ga));
#pragma unroll
      for (int i = 0; i < 4; i++) {
        gc[i] = lds4(sbase + SM_FC + 2048 + i * 512 + lane * 16);
        tw[i] = lds4(TOFF(tw3) + i * 512);
        const int ch = 4 * (g + 8 * (i & 1)) + t;
        xr[i >> 1][i & 1] = lds4(sbase + SM_X + (2 * warp + (i >> 1)) * 1024 + ((ch ^ ((ch >> 2) & 6)) * 16));
      }
      PROF(4);
      while (clock32() - tst < POLL_DELAY) {}
      ld_tag4_issue<256>(q, zp);
      ld_tag4_finish<256>(q, zp, tag);
      if (tid == 0) PROFP(31);
      if (lane == 0) mbar_arrive(BAR(sig, 1));
      cdft16(q, gc, o);
#pragma unroll
      for (int vv = 0; vv < 4; vv++)
        sts4(sbase + SM_E + (((4 * vv + t) * 8 + warp) * 8 + (g ^ (warp & 6) ^ (2 * t))) * 16, o[vv].x, o[vv].y, o[vv].z, o[vv].w);
      bar_sync(NB_CONS, 256);
      uint32_t hv[2][8];
      const float mk = t == 0 ? 0.f : 1.f;
#pragma unroll
      for (int r = 0; r < 2; r++) {
        const int j = 2 * warp + r;
        uint4 u[2];
#pragma unroll
        for (int h = 0; h < 2; h++) u[h] = lds4(sbase + SM_E + ((j * 8 + 2 * t + h) * 8 + (g ^ (2 * t) ^ (2 * (j & 3)))) * 16);
        float yv[4][4];
#pragma unroll
        for (int i = 0; i < 4; i++) {
          float lo[4] = {0.f, 0.f, 0.f, 0.f}, hi[4] = {0.f, 0.f, 0.f, 0.f};
          mma16816(lo, gb[i * 4].x, gb[i * 4].y, gb[i * 4].z, gb[i * 4].w, u[0].x, u[0].y);
          mma16816(lo, gb[i * 4 + 1].x, gb[i * 4 + 1].y, gb[i * 4 + 1].z, gb[i * 4 + 1].w, u[1].x, u[1].y);
          mma16816(hi, gb[i * 4 + 2].x, gb[i * 4 + 2].y, gb[i * 4 + 2].z, gb[i * 4 + 2].w, u[0].z, u[0].w);
          mma16816(hi, gb[i * 4 + 3].x, gb[i * 4 + 3].y, gb[i * 4 + 3].z, gb[i * 4 + 3].w, u[1].z, u[1].w);
          const float ca = __uint_as_float(tw[i].x), sa = __uint_as_float(tw[i].y), cb = __uint_as_float(tw[i].z), sb = __uint_as_float(tw[i].w);
          const float tr0 = fmaf(hi[0], mk, lo[0]), ti0 = fmaf(hi[2], mk, lo[2]);
          const float tr1 = lo[1] + hi[1], ti1 = lo[3] + hi[3];
          const float vr0 = tr0 * ca - ti0 * sa, vi0 = tr0 * sa + ti0 * ca;
          const float vr1 = tr1 * cb - ti1 * sb, vi1 = tr1 * sb + ti1 * cb;
          const uint32_t b0 = pack2(t == 0 ? hi[0] : vr0, vr1), b1 = pack2(t == 0 ? vr0 : vi0, vi1);
          yv[i][0] = yv[i][1] = yv[i][2] = yv[i][3] = 0.f;
          mma16816(yv[i], ga.x, ga.y, ga.z, ga.w, b0, b1);
        }
#pragma unroll
        for (int h = 0; h < 2; h++) {
          hv[r][4 * h + 0] = hadd2_bf16(xr[r][h].x, pack2(yv[0][2 * h], yv[1][2 * h]));
          hv[r][4 * h + 1] = hadd2_bf16(xr[r][h].y, pack2(yv[2][2 * h], yv[3][2 * h]));
          hv[r][4 * h + 2] = hadd2_bf16(xr[r][h].z, pack2(yv[0][2 * h + 1], yv[1][2 * h + 1]));
          hv[r][4 * h + 3] = hadd2_bf16(xr[r][h].w, pack2(yv[2][2 * h + 1], yv[3][2 * h + 1]));
        }
      }
      float ds[4] = {0.f, 0.f, 0.f, 0.f};
#pragma unroll
      for (int q4 = 0; q4 < 4; q4++) mma16816(ds, hv[0][2 * q4], hv[1][2 * q4], hv[0][2 * q4 + 1], hv[1][2 * q4 + 1], 0x3f803f80u, 0x3f803f80u);
#pragma unroll
      for (int o2 = 4; o2 <= 16; o2 <<= 1) {
        ds[0] += __shfl_xor_sync(0xffffffffu, ds[0], o2);
        ds[2] += __shfl_xor_sync(0xffffffffu, ds[2], o2);
      }
      uint32_t mb[2];
#pragma unroll
      for (int r = 0; r < 2; r++) {
        const int row = 16 * f + 2 * warp + r;
        mb[r] = pack2(ds[2 * r] * (1.f / 512.f), ds[2 * r] * (1.f / 512.f));
#pragma unroll
        for (int i = 0; i < 8; i++) hv[r][i] = hsub2_bf16(hv[r][i], mb[r]);
#pragma unroll
        for (int h = 0; h < 2; h++) {
          const int n1 = g + 8 * h;
          st_tag(&scr->LN[(rb * 8 + (n1 >> 1)) * 1024 + row * 8 + ((4 * (n1 & 1) + t) ^ (row & 7))],
                 make_uint4(hv[r][4 * h], hv[r][4 * h + 1], hv[r][4 * h + 2], hv[r][4 * h + 3]), n1 < 2 * NLL ? tag : (hv[r][4 * h] & 1u));
        }
      }
      bar_arrive(NB_LN, 288);
      float sum[2], sq[2], rstd[2];
      row_stats(hv[0], hv[1], lane, sum, sq);
#pragma unroll
      for (int r = 0; r < 2; r++) {
        const float m = sum[r] * (1.f / 512.f);
        rstd[r] = rsqrtf(fmaxf(fmaf(-m, m, sq[r] * (1.f / 512.f)), 0.f) + 1e-5f);
      }
      if (lane == 0)
        st_tag(&scr->ST[rb * 64 + 8 * f + warp], make_uint4(mb[0] << 16, __float_as_uint(rstd[0]), mb[1] << 16, __float_as_uint(rstd[1])), tag);
    }
    PROF(5);
    if (NLL) {
      const uint4* const ap = &scr->LN[rb * 8 * 1024 + tid];
      uint4 av[NLL ? NLL : 1][4];
      spin_cycles(POLL_DELAY3);
#pragma unroll
      for (int kb = 0; kb < NLL; kb++) ld_tag4_issue<256>(av[kb], ap + kb * 1024);
      bar_sync(NB_CONS, 256);
#pragma unroll
      for (int kb = 0; kb < NLL; kb++) {
        ld_tag4_finish<256>(av[kb], ap + kb * 1024, tag);
#pragma unroll
        for (int i = 0; i < 4; i++) sts4(sbase + kb * SLOT + (tid + 256 * i) * 16, av[kb][i].x, av[kb][i].y, av[kb][i].z, av[kb][i].w);
      }
      asm volatile("fence.proxy.async.shared::cta;" ::: "memory");
      bar_sync(NB_CONS, 256);
    }
    const int wgi = warp >> 2, wq = warp & 3;
    uint4* const pbase = &scr->P[rb * 28 * 1024 + warp * 128 + lane];
    const uint32_t a_lo0 = desc_lo(sbase + wgi * 8192, 16);
    const uint32_t ebar = lane == 0 ? BAR(empty1, 0) : RBAR(empty1, 0);
    float r0, r1;
    uint4 px[8], py[6];
    const int rh = wgi ^ kh ^ 1;
    const uint4* const psrc = &scr->P[(rb2 * 28 + 14 * kh) * 1024 + (4 * rh + wq) * 128 + lane];
    {
      float acc[128];
#pragma unroll
      for (int i = 0; i < 128; i++) acc[i] = 0.f;
      const uint32_t b_lo0 = desc_lo(sbase + 8 * SLOT, 4096);
      uint32_t slot = 0, ph = 0, prev = 0;
#pragma unroll 1
      for (int kb = 0; kb < 8; kb++) {
        if (kb >= NLL) mbar_wait(BAR(fullA, kb), 0);
        if (kb == 0) PROF(6);
#pragma unroll
        for (int hh = 0; hh < 2; hh++) {
          if (LAGX && hh == ((16 - LAGX) & 1) && kb == ((16 - LAGX) >> 1) && wgi == 1) bar_sync(NB_LAG, 256);
          mbar_wait(BAR(full1, slot), ph);
          const uint32_t al = a_lo0 + kb * 1024 + hh * 4, bl = b_lo0 + slot * 1024;
          wg_fence();
          wgmma_n256(acc, desc64(al, HI128), desc64(bl, HI128));
          wgmma_n256(acc, desc64(al + 2, HI128), desc64(bl + 128, HI128));
          wg_commit();
          if (LAGX && hh == 1 && kb == 7 && wgi == 0) bar_arrive(NB_LAG, 256);
          wg_wait<1>();
          if ((kb | hh) != 0 && lane < 2) mbar_arrive_remote(ebar + 8 * prev);
          prev = slot;
          if (++slot == 6) { slot = 0; ph ^= 1; }
        }
      }
      mbar_wait(BAR(sbar, 0), 0);
      r0 = __uint_as_float(lds2(sstat + (16 * warp + g) * 8).y);
      r1 = __uint_as_float(lds2(sstat + (16 * warp + g + 8) * 8).y);
      wg_wait<0>();
      if (lane < 2) mbar_arrive_remote(ebar + 8 * prev);
      PROF(7);
      make_p<8>(acc, r0, r1, px);
    }
    PROF(8);
    {
      float acc[96];
#pragma unroll
      for (int i = 0; i < 96; i++) acc[i] = 0.f;
      const uint32_t b_lo0 = desc_lo(sbase + 8 * SLOT, 2048);
      uint4* const pdst = pbase + ((7 * f + 3 * (f & 1)) >> 1) * 1024;
      auto stage_y = [&](int k, uint32_t slot, uint32_t ph) {
        if (LAGY && k == 16 - LAGY && wgi == 1) bar_sync(NB_LAG, 256);
        mbar_wait(BAR(full1, slot), ph);
        const uint32_t al = a_lo0 + (k >> 1) * 1024 + (k & 1) * 4, bl = b_lo0 + slot * 1024;
        wg_fence();
        wgmma_n192(acc, desc64(al, HI128), desc64(bl, HI64));
        wgmma_n192(acc, desc64(al + 2, HI128), desc64(bl + 64, HI64));
        wg_commit();
      };
#pragma unroll
      for (int k = 0; k < 4; k++) {
        stage_y(k, (16 + k) % 6, ((16 + k) / 6) & 1);
        st_tag(pdst + (k >> 1) * 1024 + (k & 1) * 64, px[2 * k], tag);
        st_tag(pdst + (k >> 1) * 1024 + (k & 1) * 64 + 32, px[2 * k + 1], tag);
        if (k == 3 && lane == 0) red_relaxed(&scr->cnt[(C_PX + rb) * 32]);
        wg_wait<1>();
        if (k != 0 && lane < 2) mbar_arrive_remote(ebar + 8 * ((15 + k) % 6));
      }
      uint32_t slot = 2, ph = 1, prev = 1;
#pragma unroll 1
      for (int k = 4; k < 16; k++) {
        stage_y(k, slot, ph);
        if (LAGY && k == 15 && wgi == 0) bar_arrive(NB_LAG, 256);
        wg_wait<1>();
        if (lane < 2) mbar_arrive_remote(ebar + 8 * prev);
        prev = slot;
        if (++slot == 6) { slot = 0; ph ^= 1; }
      }
      wg_wait<0>();
      if (lane < 2) mbar_arrive_remote(ebar + 8 * (31 % 6));
      PROF(9);
      make_p<6>(acc, r0, r1, py);
    }
    PROF(10);
    {
      const int G0 = 7 * f + ((f & 1) ? 0 : 4);
      float acc[64];
      {
        const float m0 = wgi ? __uint_as_float(lds2(sstat + 1024 + (16 * wq + g) * 8).x) : 0.f;
        const float m1 = wgi ? __uint_as_float(lds2(sstat + 1024 + (16 * wq + g + 8) * 8).x) : 0.f;
#pragma unroll
        for (int i = 0; i < 64; i++) acc[i] = (i & 2) ? m1 : m0;
      }
      const uint32_t b2_lo0 = desc_lo(sbase, 8192);
      const uint32_t pa0 = sbase + 8 * SLOT + (4 * rh + wq) * 2048 + lane * 16;
      uint32_t slot = 2;
      auto stage2 = [&](int s) {
        uint4 a[4];
        if (LAG2 && s == 14 - LAG2 && wgi == 1) bar_sync(NB_LAG, 256);
        mbar_wait(BAR(full2, s), 0);
        if (tid == 0) PROFP(16 + s);
#pragma unroll
        for (int kk = 0; kk < 4; kk++) a[kk] = lds4(pa0 + slot * SLOT + kk * 512);
        ld_tag4_finish<32>(a, psrc + (int)((KORDER >> (4 * s)) & 15) * 1024, tag);
        const uint32_t bl = b2_lo0 + (s & 7) * 1024;
        wg_fence();
#pragma unroll
        for (int kk = 0; kk < 4; kk++) wgmma_rs_n128(acc, a[kk].x, a[kk].y, a[kk].z, a[kk].w, desc64(bl + kk * 128, HI128));
        wg_commit();
        if (++slot == 6) slot = 0;
      };
      auto release2 = [&](int s) {
        wg_wait<1>();
        if (s <= 8 && lane == 0) {
          mbar_arrive(BAR(empty2, s - 1));
          if (s == 8) mbar_arrive_remote(RBAR(xfree, 0));
        }
      };
      stage2(0);
#pragma unroll
      for (int k = 0; k < 6; k++) st_tag(pbase + ((G0 + (k >> 1)) >> 1) * 1024 + ((G0 + (k >> 1)) & 1) * 64 + (k & 1) * 32, py[k], tag);
      if (lane == 0) red_relaxed(&scr->cnt[(C_PY + rb) * 32 + (f >> 1)]);
      stage2(1);
      release2(1);
#pragma unroll 1
      for (int s = 2; s < 14; s += 2) {
        stage2(s);
        release2(s);
        stage2(s + 1);
        if (LAG2 && s == 12 && wgi == 0) bar_arrive(NB_LAG, 256);
        release2(s + 1);
      }
      uint4 hres[2][4];
      mbar_wait(BAR(hbar, 0), 0);
#pragma unroll
      for (int h = 0; h < 2; h++)
#pragma unroll
        for (int q = 0; q < 4; q++) {
          hres[h][q] = lds4(sbase + 7 * SLOT + (q >> 1) * 8192 + (16 * wq + g + 8 * h) * 128 + (((4 * (q & 1) + t) ^ g) * 16));
          if (2 * nq + (q >> 1) < NLL) hres[h][q].x &= ~1u;
        }
      wg_wait<0>();
      PROF(11);
      const uint32_t xbuf = sbase + 6 * SLOT + (tid & 127) * 16;
      if (wgi == 0) {
        uint32_t rbuf;
        mbar_wait(BAR(xfree, 0), 0);
        asm volatile("mapa.shared::cluster.u32 %0, %1, %2;" : "=r"(rbuf) : "r"(xbuf), "r"(kh ^ 1));
#pragma unroll
        for (int i = 0; i < 8; i++)
          asm volatile("st.async.weak.shared::cluster.mbarrier::complete_tx::bytes.v4.b32 [%0], {%1,%2,%3,%4}, [%5];"
                       ::"r"(rbuf + i * 2048), "r"(pack2(acc[8 * i], acc[8 * i + 1])), "r"(pack2(acc[8 * i + 2], acc[8 * i + 3])),
                         "r"(pack2(acc[8 * i + 4], acc[8 * i + 5])), "r"(pack2(acc[8 * i + 6], acc[8 * i + 7])), "r"(RBAR(xbar, 0))
                       : "memory");
      } else {
        mbar_wait_cluster(BAR(xbar, 0), 0);
      }
      uint32_t w[2][16];
#pragma unroll
      for (int i = 0; i < 8; i++) {
        const uint4 pv = lds4(xbuf + i * 2048);
        w[0][2 * i] = pack2(acc[8 * i] + bf_lo(pv.x), acc[8 * i + 1] + bf_hi(pv.x));
        w[1][2 * i] = pack2(acc[8 * i + 2] + bf_lo(pv.y), acc[8 * i + 3] + bf_hi(pv.y));
        w[0][2 * i + 1] = pack2(acc[8 * i + 4] + bf_lo(pv.z), acc[8 * i + 5] + bf_hi(pv.z));
        w[1][2 * i + 1] = pack2(acc[8 * i + 6] + bf_lo(pv.w), acc[8 * i + 7] + bf_hi(pv.w));
      }
      uint4* const o4 = reinterpret_cast<uint4*>(out) + (16 * (c >> 4) + 2 * (4 * rh + wq) + (rb2 & 1) + 128 * g) * 64 + nq * 16 + t;
#pragma unroll
      for (int h = 0; h < 2; h++)
#pragma unroll
        for (int q = 0; q < 4; q++) {
          uint32_t a0 = w[h][4 * q], a1 = w[h][4 * q + 1], a2 = w[h][4 * q + 2], a3 = w[h][4 * q + 3];
          {
            const bool od = t & 1;
            uint32_t s0 = od ? a0 : a1, s1 = od ? a2 : a3;
            s0 = __shfl_xor_sync(0xffffffffu, s0, 1); s1 = __shfl_xor_sync(0xffffffffu, s1, 1);
            if (od) { a0 = s0; a2 = s1; } else { a1 = s0; a3 = s1; }
          }
          {
            const bool up = t & 2;
            uint32_t s0 = up ? a0 : a2, s1 = up ? a1 : a3;
            s0 = __shfl_xor_sync(0xffffffffu, s0, 2); s1 = __shfl_xor_sync(0xffffffffu, s1, 2);
            if (up) { a0 = s0; a1 = s1; } else { a2 = s0; a3 = s1; }
          }
          if (wgi == 1)
            o4[h * 1024 * 64 + 4 * q] =
                make_uint4(hadd2_bf16(hres[h][q].x, a0), hadd2_bf16(hres[h][q].y, a1), hadd2_bf16(hres[h][q].z, a2), hadd2_bf16(hres[h][q].w, a3));
        }
      PROF(12);
      PROFG(15);
    }
  }
#undef BAR
#undef TOFF
#undef RBAR
}

typedef CUresult (*EncodeFn)(CUtensorMap*, CUtensorMapDataType, cuuint32_t, void*, const cuuint64_t*, const cuuint64_t*,
                             const cuuint32_t*, const cuuint32_t*, CUtensorMapInterleave, CUtensorMapSwizzle,
                             CUtensorMapL2promotion, CUtensorMapFloatOOBfill);

}

extern "C" void kernel_launch(void* const* d_in, const int* in_sizes, int n_in, void* d_out, int out_size) {
  (void)in_sizes; (void)n_in; (void)out_size;
  static EncodeFn encode = nullptr;
  static void *tab = nullptr, *scr = nullptr;
  if (!encode) {
    void* fn = nullptr;
    cudaDriverEntryPointQueryResult qr;
    cudaGetDriverEntryPoint("cuTensorMapEncodeTiled", &fn, cudaEnableDefault, &qr);
    encode = (EncodeFn)fn;
    cudaGetSymbolAddress(&tab, g_tab);
    cudaGetSymbolAddress(&scr, g_scr);
    cudaFuncSetAttribute(fused_kernel, cudaFuncAttributeMaxDynamicSharedMemorySize, SMEM_BYTES);
  }
  CUtensorMap tmGX, tmUX, tmGY, tmUY, tmD, tmWR, tmWI;
  const cuuint32_t es[5] = {1, 1, 1, 1, 1};
  auto enc = [&](CUtensorMap* m, void* p, int rank, const cuuint64_t* gd, const cuuint64_t* gs, const cuuint32_t* bd,
                 CUtensorMapSwizzle sw, CUtensorMapL2promotion pr) {
    encode(m, CU_TENSOR_MAP_DATA_TYPE_BFLOAT16, rank, p, gd, gs, bd, es, CU_TENSOR_MAP_INTERLEAVE_NONE, sw, pr,
           CU_TENSOR_MAP_FLOAT_OOB_FILL_NONE);
  };
  {
    const cuuint64_t gd[3] = {64, 512, 28}, gs[2] = {3584, 128};
    const cuuint32_t bd[3] = {64, 32, 2};
    enc(&tmGX, d_in[4], 3, gd, gs, bd, CU_TENSOR_MAP_SWIZZLE_128B, CU_TENSOR_MAP_L2_PROMOTION_L2_256B);
    enc(&tmUX, d_in[5], 3, gd, gs, bd, CU_TENSOR_MAP_SWIZZLE_128B, CU_TENSOR_MAP_L2_PROMOTION_L2_256B);
  }
  {
    const cuuint64_t gd[3] = {32, 512, 56}, gs[2] = {3584, 64};
    const cuuint32_t bd[3] = {32, 32, 3};
    enc(&tmGY, d_in[4], 3, gd, gs, bd, CU_TENSOR_MAP_SWIZZLE_64B, CU_TENSOR_MAP_L2_PROMOTION_L2_128B);
    enc(&tmUY, d_in[5], 3, gd, gs, bd, CU_TENSOR_MAP_SWIZZLE_64B, CU_TENSOR_MAP_L2_PROMOTION_L2_128B);
  }
  {
    const cuuint64_t gd[3] = {64, 1792, 8}, gs[2] = {1024, 128};
    const cuuint32_t bd[3] = {64, 64, 2};
    enc(&tmD, d_in[6], 3, gd, gs, bd, CU_TENSOR_MAP_SWIZZLE_128B, CU_TENSOR_MAP_L2_PROMOTION_L2_256B);
  }
  {
    const cuuint64_t gd[3] = {4112, 8, 16}, gs[2] = {16 * 8224, 8224};
    const cuuint32_t bd[3] = {40, 8, 16};
    enc(&tmWR, d_in[1], 3, gd, gs, bd, CU_TENSOR_MAP_SWIZZLE_NONE, CU_TENSOR_MAP_L2_PROMOTION_NONE);
    enc(&tmWI, d_in[2], 3, gd, gs, bd, CU_TENSOR_MAP_SWIZZLE_NONE, CU_TENSOR_MAP_L2_PROMOTION_NONE);
  }
  fused_kernel<<<NCTA, NTHREADS, SMEM_BYTES>>>((const __nv_bfloat16*)d_in[0], (const Tables*)tab, (Scratch*)scr,
                                               (__nv_bfloat16*)d_out, (const char*)d_in[4], (const char*)d_in[5],
                                               (const char*)d_in[6], tmWR, tmWI, tmGX, tmUX, tmGY, tmUY, tmD);
}
```

```cpp
#include <cuda_runtime.h>
#include <cuda_bf16.h>
#include <cuda.h>
#include <stdint.h>

namespace {

constexpr int NCTA = 128;
constexpr int NTHREADS = 384;
constexpr int SLOT = 16384;
constexpr int SMEM_BYTES = 14 * SLOT + 2048 + 1024;
constexpr int SPIN_LIMIT = 1 << 22;

struct Scratch {
  uint4 Z1[128 * 1024];
  uint4 Z2[128 * 1024];
  uint4 LN[16 * 8 * 1024];
  uint4 P[16 * 28 * 1024];
  uint4 ST[1024];
  unsigned cnt[64 * 32];
};
__device__ __align__(1024) Scratch g_scr;
#define PROF(i)
#define PROFP(i)
#define PROFG(i)

constexpr double ccos(int i, int n) {
  i &= n - 1;
  if (i > n / 2) i = n - i;
  if (4 * i == n) return 0.0;
  const bool neg = 4 * i > n;
  if (neg) i = n / 2 - i;
  const double a = 6.283185307179586476925 * i / n, a2 = a * a;
  double term = 1.0, sum = 1.0;
  for (int k = 1; k < 14; k++) { term *= -a2 / ((2 * k - 1) * (2 * k)); sum += term; }
  return neg ? -sum : sum;
}
constexpr double csin(int i, int n) { return ccos(i - n / 4, n); }
constexpr unsigned fbits(double v, int mant) {
  if (v == 0.0) return 0;
  const unsigned sg = v < 0 ? 1u : 0u;
  if (v < 0) v = -v;
  int e = 127;
  while (v < 1.0) { v *= 2.0; e--; }
  const unsigned m = (unsigned)((v - 1.0) * (double)(1u << mant) + 0.5);
  return (sg << (8 + mant)) + ((unsigned)e << mant) + m;
}
constexpr unsigned pkb(double lo, double hi) { return fbits(lo, 7) | (fbits(hi, 7) << 16); }
constexpr double fa_elem(int kp, int n1) {
  return kp <= 8 ? ccos(kp * n1, 16) : -csin((kp - 8) * n1, 16);
}
constexpr unsigned cfrag_c(int idx, int n, int ri) {
  return ri ? pkb(-csin(idx, n), ccos(idx, n)) : pkb(ccos(idx, n), csin(idx, n));
}
struct Tables {
  unsigned fb[16][32][4];
  unsigned tw1[8][32][4];
  unsigned fa[32][4];
  unsigned f2[8][4][32][4];
  unsigned g2[8][4][32][4];
  unsigned gb[16][32][4];
  unsigned tw3[4][32][4];
  unsigned ga[32][4];
  unsigned f8[32][4], g8[32][4];
};
constexpr int T1_BYTES = 12800, T2_BYTES = 44544;
static_assert(sizeof(Tables) == T1_BYTES + T2_BYTES, "table size");
constexpr Tables make_tables() {
  Tables T = {};
  for (int l = 0; l < 32; l++) {
    const int g = l >> 2, t = l & 3;
    for (int i = 0; i < 4; i++)
      for (int u = 0; u < 8; u++) {
        const int ri = g & 1, m = 2 * (g >> 1) + ((u & 3) >> 1);
        const double sg = u >= 4 ? -1.0 : 1.0;
        const int k2 = u >= 4 ? 31 - 2 * m - (u & 1) : 2 * m + (u & 1);
        const int pa = (8 * t + i) * k2, pb = (8 * t + 4 + i) * k2;
        T.fb[i * 4 + (u >> 1)][l][(u & 1) * 2 + 0] = ri == 0 ? pkb(ccos(pa, 32), ccos(pb, 32)) : pkb(-sg * csin(pa, 32), -sg * csin(pb, 32));
        T.fb[i * 4 + (u >> 1)][l][(u & 1) * 2 + 1] = ri == 0 ? pkb(csin(pa, 32), csin(pb, 32)) : pkb(sg * ccos(pa, 32), sg * ccos(pb, 32));
      }
    for (int i = 0; i < 4; i++)
      for (int ks = 0; ks < 4; ks++) {
        const int n2 = 4 * g + i, m = 2 * t + (ks & 1);
        const double sg = ks >= 2 ? -1.0 : 1.0;
        const int pa = n2 * (ks >= 2 ? 31 - 2 * m : 2 * m), pb = n2 * (ks >= 2 ? 30 - 2 * m : 2 * m + 1);
        T.gb[i * 4 + ks][l][0] = pkb(ccos(pa, 32), -sg * csin(pa, 32));
        T.gb[i * 4 + ks][l][1] = pkb(csin(pa, 32), sg * ccos(pa, 32));
        T.gb[i * 4 + ks][l][2] = pkb(ccos(pb, 32), -sg * csin(pb, 32));
        T.gb[i * 4 + ks][l][3] = pkb(csin(pb, 32), sg * ccos(pb, 32));
      }
    for (int i = 0; i < 4; i++) {
      for (int e = 0; e < 2; e++) {
        const int p = (8 * t + 4 * e + i) * (g == 0 ? 8 : g);
        T.tw1[2 * i + e][l][0] = fbits(g == 0 ? 0.0 : ccos(p, 512), 23);
        T.tw1[2 * i + e][l][1] = fbits(g == 0 ? ccos(p, 512) : csin(p, 512), 23);
        T.tw1[2 * i + e][l][2] = fbits(g == 0 ? 0.0 : -csin(p, 512), 23);
        T.tw1[2 * i + e][l][3] = fbits(g == 0 ? -csin(p, 512) : ccos(p, 512), 23);
      }
      const int ka = t == 0 ? 8 : 2 * t, kb = 2 * t + 1;
      T.tw3[i][l][0] = fbits(ccos((4 * g + i) * ka, 512), 23);
      T.tw3[i][l][1] = fbits(csin((4 * g + i) * ka, 512), 23);
      T.tw3[i][l][2] = fbits(ccos((4 * g + i) * kb, 512), 23);
      T.tw3[i][l][3] = fbits(csin((4 * g + i) * kb, 512), 23);
      const int p8 = (t + 4 * (i & 1)) * (4 * (i >> 1) + (g >> 1));
      T.f8[l][i] = cfrag_c(p8, 8, g & 1);
      T.g8[l][i] = cfrag_c(-p8, 8, g & 1);
    }
    for (int w = 0; w < 8; w++)
      for (int i = 0; i < 16; i++) {
        const int kidx = t + 4 * (i & 1) + 8 * (i >> 3), nidx = 4 * ((i >> 1) & 3) + (g >> 1);
        T.f2[w][i >> 2][l][i & 3] = cfrag_c((8 * kidx + w) * nidx, 128, g & 1);
        T.g2[w][i >> 2][l][i & 3] = cfrag_c(-(8 * nidx + w) * kidx, 128, g & 1);
      }
    T.fa[l][0] = pkb(fa_elem(g, 2 * t), fa_elem(g, 2 * t + 1));
    T.fa[l][1] = pkb(fa_elem(g + 8, 2 * t), fa_elem(g + 8, 2 * t + 1));
    T.fa[l][2] = pkb(fa_elem(g, 2 * t + 8), fa_elem(g, 2 * t + 9));
    T.fa[l][3] = pkb(fa_elem(g + 8, 2 * t + 8), fa_elem(g + 8, 2 * t + 9));
    T.ga[l][0] = pkb(fa_elem(2 * t, g), fa_elem(2 * t + 1, g));
    T.ga[l][1] = pkb(fa_elem(2 * t, g + 8), fa_elem(2 * t + 1, g + 8));
    T.ga[l][2] = pkb(fa_elem(2 * t + 8, g), fa_elem(2 * t + 9, g));
    T.ga[l][3] = pkb(fa_elem(2 * t + 8, g + 8), fa_elem(2 * t + 9, g + 8));
  }
  return T;
}
__device__ const __align__(128) Tables g_tab = make_tables();

__device__ __forceinline__ void die() { asm volatile("st.global.u32 [%0], %1;" ::"l"(0ull), "r"(0) : "memory"); }
__device__ __forceinline__ uint32_t s2u(const void* p) { return (uint32_t)__cvta_generic_to_shared(p); }
__device__ __forceinline__ void mbar_init(uint32_t b, int c) { asm volatile("mbarrier.init.shared::cta.b64 [%0], %1;" ::"r"(b), "r"(c)); }
__device__ __forceinline__ void mbar_expect(uint32_t b, int bytes) {
  asm volatile("mbarrier.arrive.expect_tx.shared::cta.b64 _, [%0], %1;" ::"r"(b), "r"(bytes) : "memory");
}
__device__ __forceinline__ void mbar_arrive(uint32_t b) { asm volatile("mbarrier.arrive.shared::cta.b64 _, [%0];" ::"r"(b) : "memory"); }
__device__ __forceinline__ uint32_t mbar_try(uint32_t b, uint32_t parity) {
  uint32_t ok;
  asm volatile("{.reg .pred p; mbarrier.try_wait.parity.shared::cta.b64 p, [%1], %2; selp.u32 %0,1,0,p;}"
               : "=r"(ok) : "r"(b), "r"(parity) : "memory");
  return ok;
}
__device__ __forceinline__ void mbar_wait(uint32_t b, uint32_t parity) {
  int it = 0;
#pragma unroll 1
  while (!mbar_try(b, parity))
    if (++it > SPIN_LIMIT) { die(); break; }
}
__device__ __forceinline__ void mbar_wait_cluster(uint32_t b, int parity) {
  uint32_t ok;
  int it = 0;
  do {
    asm volatile("{.reg .pred p; mbarrier.try_wait.parity.acquire.cluster.shared::cta.b64 p, [%1], %2; selp.u32 %0,1,0,p;}"
                 : "=r"(ok) : "r"(b), "r"(parity) : "memory");
    if (++it > SPIN_LIMIT) { die(); break; }
  } while (!ok);
}
__device__ __forceinline__ void bar_sync(int id, int n) { asm volatile("bar.sync %0, %1;" ::"r"(id), "r"(n) : "memory"); }
__device__ __forceinline__ void bar_arrive(int id, int n) { asm volatile("bar.arrive %0, %1;" ::"r"(id), "r"(n) : "memory"); }
__device__ __forceinline__ void red_release(unsigned* p) { asm volatile("red.release.gpu.global.add.u32 [%0], 1;" ::"l"(p) : "memory"); }
__device__ __forceinline__ void red_relaxed(unsigned* p) { asm volatile("red.relaxed.gpu.global.add.u32 [%0], 1;" ::"l"(p) : "memory"); }
__device__ __forceinline__ unsigned ld_acquire(const unsigned* p) {
  unsigned v;
  asm volatile("ld.acquire.gpu.global.u32 %0, [%1];" : "=r"(v) : "l"(p) : "memory");
  return v;
}
__device__ __forceinline__ unsigned ld_relaxed(const unsigned* p) {
  unsigned v;
  asm volatile("ld.relaxed.gpu.global.u32 %0, [%1];" : "=r"(v) : "l"(p) : "memory");
  return v;
}
__device__ __forceinline__ void wait_counter(const unsigned* p, unsigned target) {
  int it = 0;
  while ((int)(ld_acquire(p) - target) < 0)
    if (++it > SPIN_LIMIT) { die(); break; }
}
__device__ __forceinline__ void sts4(uint32_t a, uint32_t x, uint32_t y, uint32_t z, uint32_t w) {
  asm volatile("st.shared.v4.u32 [%0], {%1,%2,%3,%4};" ::"r"(a), "r"(x), "r"(y), "r"(z), "r"(w) : "memory");
}
__device__ __forceinline__ uint4 lds4(uint32_t a) {
  uint4 v;
  asm volatile("ld.shared.v4.u32 {%0,%1,%2,%3}, [%4];" : "=r"(v.x), "=r"(v.y), "=r"(v.z), "=r"(v.w) : "r"(a) : "memory");
  return v;
}
__device__ __forceinline__ uint32_t pack2(float lo, float hi) {
  uint32_t r;
  asm("cvt.rn.bf16x2.f32 %0, %1, %2;" : "=r"(r) : "f"(hi), "f"(lo));
  return r;
}
__device__ __forceinline__ float bf_lo(uint32_t v) { return __uint_as_float(v << 16); }
__device__ __forceinline__ float bf_hi(uint32_t v) { return __uint_as_float(v & 0xffff0000u); }
__device__ __forceinline__ uint32_t hadd2_bf16(uint32_t a, uint32_t b) {
  uint32_t r;
  asm("add.rn.bf16x2 %0, %1, %2;" : "=r"(r) : "r"(a), "r"(b));
  return r;
}
__device__ __forceinline__ void mma16816(float (&d)[4], uint32_t a0, uint32_t a1, uint32_t a2, uint32_t a3, uint32_t b0, uint32_t b1) {
  asm("mma.sync.aligned.m16n8k16.row.col.f32.bf16.bf16.f32 {%0,%1,%2,%3}, {%4,%5,%6,%7}, {%8,%9}, {%0,%1,%2,%3};"
      : "+f"(d[0]), "+f"(d[1]), "+f"(d[2]), "+f"(d[3])
      : "r"(a0), "r"(a1), "r"(a2), "r"(a3), "r"(b0), "r"(b1));
}
template <int N>
__device__ __forceinline__ void cs_frac(int idx, float& c, float& s) {
  int i = ((idx + N / 2) & (N - 1)) - N / 2;
  float a = (float)i * (6.283185307179586f / N);
  c = __cosf(a);
  s = __sinf(a);
}
template <int N>
__device__ __forceinline__ uint32_t cfrag(int idx, int ri) {
  float c, s;
  cs_frac<N>(idx, c, s);
  return ri ? pack2(-s, c) : pack2(c, s);
}
__device__ __forceinline__ uint32_t word(const uint4& v, int e) { return e == 0 ? v.x : e == 1 ? v.y : e == 2 ? v.z : v.w; }
__device__ __forceinline__ void cdft16(const uint4 (&q)[4], const uint4 (&F)[4], uint4 (&o)[4]) {
  float acc[2][4][4];
#pragma unroll
  for (int p = 0; p < 2; p++)
#pragma unroll
    for (int v = 0; v < 4; v++) {
      acc[p][v][0] = acc[p][v][1] = acc[p][v][2] = acc[p][v][3] = 0.f;
#pragma unroll
      for (int ks = 0; ks < 2; ks++)
        mma16816(acc[p][v], word(q[2 * ks], 2 * p), word(q[2 * ks], 2 * p + 1), word(q[2 * ks + 1], 2 * p),
                 word(q[2 * ks + 1], 2 * p + 1), word(F[ks * 2 + (v >> 1)], (v & 1) * 2), word(F[ks * 2 + (v >> 1)], (v & 1) * 2 + 1));
    }
#pragma unroll
  for (int v = 0; v < 4; v++)
    o[v] = make_uint4(pack2(acc[0][v][0], acc[0][v][1]), pack2(acc[0][v][2], acc[0][v][3]),
                      pack2(acc[1][v][0], acc[1][v][1]), pack2(acc[1][v][2], acc[1][v][3]));
}
__device__ __forceinline__ void st_tag(uint4* p, const uint4& v, uint32_t tag) {
  asm volatile("{.reg .b128 r; .reg .b64 a, b; mov.b64 a, {%1,%2}; mov.b64 b, {%3,%4}; mov.b128 r, {a,b}; st.relaxed.gpu.global.b128 [%0], r;}"
               ::"l"(p), "r"((v.x & ~1u) | tag), "r"(v.y), "r"(v.z), "r"(v.w) : "memory");
}
__device__ __forceinline__ uint4 ld_b128(const uint4* p) {
  uint4 v;
  asm volatile("{.reg .b128 r; .reg .b64 a, b; ld.relaxed.gpu.global.b128 r, [%4]; mov.b128 {a,b}, r; mov.b64 {%0,%1}, a; mov.b64 {%2,%3}, b;}"
               : "=r"(v.x), "=r"(v.y), "=r"(v.z), "=r"(v.w) : "l"(p) : "memory");
  return v;
}
template <int STRIDE>
__device__ __forceinline__ void ld_tag4_issue(uint4 (&q)[4], const uint4* p) {
#pragma unroll
  for (int i = 0; i < 4; i++) q[i] = ld_b128(p + i * STRIDE);
}
template <int STRIDE>
__device__ __forceinline__ void ld_tag4_finish(uint4 (&q)[4], const uint4* p, uint32_t tag) {
  int it = 0;
#pragma unroll 1
  while (__any_sync(0xffffffffu, ((q[0].x ^ tag) | (q[1].x ^ tag) | (q[2].x ^ tag) | (q[3].x ^ tag)) & 1u)) {
    ld_tag4_issue<STRIDE>(q, p);
    if (++it > SPIN_LIMIT) { die(); break; }
  }
#pragma unroll
  for (int i = 0; i < 4; i++) asm volatile("and.b32 %0, %0, 0xfffffffe;" : "+r"(q[i].x));
}
__device__ __forceinline__ void row_stats(const uint32_t (&a)[8], const uint32_t (&b)[8], int lane, float (&sum)[2], float (&sq)[2]) {
  float da[4] = {0.f, 0.f, 0.f, 0.f}, db[4] = {0.f, 0.f, 0.f, 0.f}, ds[4] = {0.f, 0.f, 0.f, 0.f};
#pragma unroll
  for (int q = 0; q < 4; q++) {
    mma16816(ds, a[2 * q], b[2 * q], a[2 * q + 1], b[2 * q + 1], 0x3f803f80u, 0x3f803f80u);
    mma16816(da, a[2 * q], b[2 * q], a[2 * q + 1], b[2 * q + 1], a[2 * q], a[2 * q + 1]);
    mma16816(db, a[2 * q], b[2 * q], a[2 * q + 1], b[2 * q + 1], b[2 * q], b[2 * q + 1]);
  }
  const int src = (lane & 28) | (lane >> 3);
  const float qa = __shfl_sync(0xffffffffu, (lane & 4) ? da[1] : da[0], src);
  const float qb = __shfl_sync(0xffffffffu, (lane & 4) ? db[3] : db[2], src);
  float v = (lane & 2) ? ((lane & 1) ? ds[2] : ds[0]) : ((lane & 1) ? qb : qa);
  v += __shfl_xor_sync(0xffffffffu, v, 4);
  v += __shfl_xor_sync(0xffffffffu, v, 8);
  v += __shfl_xor_sync(0xffffffffu, v, 16);
  sq[0] = __shfl_sync(0xffffffffu, v, 0);
  sq[1] = __shfl_sync(0xffffffffu, v, 1);
  sum[0] = __shfl_sync(0xffffffffu, v, 2);
  sum[1] = __shfl_sync(0xffffffffu, v, 3);
}
__device__ __forceinline__ uint64_t desc64(uint32_t lo, uint32_t hi) {
  uint64_t d;
  asm("mov.b64 %0, {%1, %2};" : "=l"(d) : "r"(lo), "r"(hi));
  return d;
}
constexpr uint32_t desc_hi(uint32_t sbo, uint32_t swz) { return (sbo >> 4) | (swz << 30); }
__device__ __forceinline__ uint32_t desc_lo(uint32_t addr, uint32_t lbo) { return ((addr & 0x3FFFF) >> 4) | ((lbo >> 4) << 16); }
__device__ __forceinline__ void cp_async16(uint32_t dst, const void* src) {
  asm volatile("cp.async.cg.shared.global [%0], [%1], 16;" ::"r"(dst), "l"(src) : "memory");
}
__device__ __forceinline__ uint2 lds2(uint32_t a) {
  uint2 v;
  asm volatile("ld.shared.v2.u32 {%0,%1}, [%2];" : "=r"(v.x), "=r"(v.y) : "r"(a) : "memory");
  return v;
}
__device__ __forceinline__ uint32_t lds_u16(uint32_t a) {
  uint16_t v;
  asm volatile("ld.shared.u16 %0, [%1];" : "=h"(v) : "r"(a) : "memory");
  return v;
}
__device__ __forceinline__ void wg_fence() { asm volatile("wgmma.fence.sync.aligned;" ::: "memory"); }
__device__ __forceinline__ void wg_commit() { asm volatile("wgmma.commit_group.sync.aligned;" ::: "memory"); }
template <int N>
__device__ __forceinline__ void wg_wait() { asm volatile("wgmma.wait_group.sync.aligned %0;" ::"n"(N) : "memory"); }
__device__ __forceinline__ void bulk_load(uint32_t dst, const void* src, int bytes, uint32_t bar) {
  asm volatile("cp.async.bulk.shared::cluster.global.mbarrier::complete_tx::bytes [%0], [%1], %2, [%3];"
               ::"r"(dst), "l"(src), "r"(bytes), "r"(bar) : "memory");
}
__device__ __forceinline__ void tma3(uint32_t dst, const CUtensorMap* tm, uint32_t bar, int c0, int c1, int c2) {
  asm volatile("cp.async.bulk.tensor.3d.shared::cluster.global.mbarrier::complete_tx::bytes [%0], [%1, {%3,%4,%5}], [%2];"
               ::"r"(dst), "l"(tm), "r"(bar), "r"(c0), "r"(c1), "r"(c2) : "memory");
}
__device__ __forceinline__ void tma3_mc(uint32_t dst, const CUtensorMap* tm, uint32_t bar, int c1, int c2) {
  asm volatile("cp.async.bulk.tensor.3d.shared::cluster.global.mbarrier::complete_tx::bytes.multicast::cluster [%0], [%1, {%3,%4,%5}], [%2], %6;"
               ::"r"(dst), "l"(tm), "r"(bar), "r"(0), "r"(c1), "r"(c2), "h"((uint16_t)3) : "memory");
}
__device__ __forceinline__ void mbar_arrive_remote(uint32_t rb) {
  asm volatile("mbarrier.arrive.shared::cluster.b64 _, [%0];" ::"r"(rb) : "memory");
}
__device__ __forceinline__ uint4 ldg_ca4(const void* p) {
  uint4 v;
  asm volatile("ld.global.ca.v4.u32 {%0,%1,%2,%3}, [%4];" : "=r"(v.x), "=r"(v.y), "=r"(v.z), "=r"(v.w) : "l"(p) : "memory");
  return v;
}
__device__ __forceinline__ uint32_t clock32() {
  uint32_t v;
  asm volatile("mov.u32 %0, %%clock;" : "=r"(v) :: "memory");
  return v;
}
__device__ __forceinline__ float swiglu(float g, float u, float r) {
  float hg = (0.5f * r) * g, th;
  asm("tanh.approx.f32 %0, %1;" : "=f"(th) : "f"(hg));
  return fmaf(hg, th, hg) * (r * u);
}
__device__ __forceinline__ uint32_t hsub2_bf16(uint32_t a, uint32_t b) {
  uint32_t r;
  asm("sub.rn.bf16x2 %0, %1, %2;" : "=r"(r) : "r"(a), "r"(b));
  return r;
}
__device__ __forceinline__ void l2_prefetch(const void* p, int bytes) {
  asm volatile("cp.async.bulk.prefetch.L2.global [%0], %1;" ::"l"(p), "r"(bytes) : "memory");
}

__device__ __forceinline__ void wgmma_n256(float (&d)[128], uint64_t da, uint64_t db) {
  asm volatile("wgmma.mma_async.sync.aligned.m64n256k16.f32.bf16.bf16 {"
      "%0,%1,%2,%3,%4,%5,%6,%7,%8,%9,%10,%11,%12,%13,%14,%15,"
      "%16,%17,%18,%19,%20,%21,%22,%23,%24,%25,%26,%27,%28,%29,%30,%31,"
      "%32,%33,%34,%35,%36,%37,%38,%39,%40,%41,%42,%43,%44,%45,%46,%47,"
      "%48,%49,%50,%51,%52,%53,%54,%55,%56,%57,%58,%59,%60,%61,%62,%63,"
      "%64,%65,%66,%67,%68,%69,%70,%71,%72,%73,%74,%75,%76,%77,%78,%79,"
      "%80,%81,%82,%83,%84,%85,%86,%87,%88,%89,%90,%91,%92,%93,%94,%95,"
      "%96,%97,%98,%99,%100,%101,%102,%103,%104,%105,%106,%107,%108,%109,%110,%111,"
      "%112,%113,%114,%115,%116,%117,%118,%119,%120,%121,%122,%123,%124,%125,%126,%127"
      "}, %128, %129, 1, 1, 1, 0, 1;\n"
      : "+f"(d[0]),"+f"(d[1]),"+f"(d[2]),"+f"(d[3]),"+f"(d[4]),"+f"(d[5]),"+f"(d[6]),"+f"(d[7]),
        "+f"(d[8]),"+f"(d[9]),"+f"(d[10]),"+f"(d[11]),"+f"(d[12]),"+f"(d[13]),"+f"(d[14]),"+f"(d[15]),
        "+f"(d[16]),"+f"(d[17]),"+f"(d[18]),"+f"(d[19]),"+f"(d[20]),"+f"(d[21]),"+f"(d[22]),"+f"(d[23]),
        "+f"(d[24]),"+f"(d[25]),"+f"(d[26]),"+f"(d[27]),"+f"(d[28]),"+f"(d[29]),"+f"(d[30]),"+f"(d[31]),
        "+f"(d[32]),"+f"(d[33]),"+f"(d[34]),"+f"(d[35]),"+f"(d[36]),"+f"(d[37]),"+f"(d[38]),"+f"(d[39]),
        "+f"(d[40]),"+f"(d[41]),"+f"(d[42]),"+f"(d[43]),"+f"(d[44]),"+f"(d[45]),"+f"(d[46]),"+f"(d[47]),
        "+f"(d[48]),"+f"(d[49]),"+f"(d[50]),"+f"(d[51]),"+f"(d[52]),"+f"(d[53]),"+f"(d[54]),"+f"(d[55]),
        "+f"(d[56]),"+f"(d[57]),"+f"(d[58]),"+f"(d[59]),"+f"(d[60]),"+f"(d[61]),"+f"(d[62]),"+f"(d[63]),
        "+f"(d[64]),"+f"(d[65]),"+f"(d[66]),"+f"(d[67]),"+f"(d[68]),"+f"(d[69]),"+f"(d[70]),"+f"(d[71]),
        "+f"(d[72]),"+f"(d[73]),"+f"(d[74]),"+f"(d[75]),"+f"(d[76]),"+f"(d[77]),"+f"(d[78]),"+f"(d[79]),
        "+f"(d[80]),"+f"(d[81]),"+f"(d[82]),"+f"(d[83]),"+f"(d[84]),"+f"(d[85]),"+f"(d[86]),"+f"(d[87]),
        "+f"(d[88]),"+f"(d[89]),"+f"(d[90]),"+f"(d[91]),"+f"(d[92]),"+f"(d[93]),"+f"(d[94]),"+f"(d[95]),
        "+f"(d[96]),"+f"(d[97]),"+f"(d[98]),"+f"(d[99]),"+f"(d[100]),"+f"(d[101]),"+f"(d[102]),"+f"(d[103]),
        "+f"(d[104]),"+f"(d[105]),"+f"(d[106]),"+f"(d[107]),"+f"(d[108]),"+f"(d[109]),"+f"(d[110]),"+f"(d[111]),
        "+f"(d[112]),"+f"(d[113]),"+f"(d[114]),"+f"(d[115]),"+f"(d[116]),"+f"(d[117]),"+f"(d[118]),"+f"(d[119]),
        "+f"(d[120]),"+f"(d[121]),"+f"(d[122]),"+f"(d[123]),"+f"(d[124]),"+f"(d[125]),"+f"(d[126]),"+f"(d[127])
      : "l"(da), "l"(db));
}
__device__ __forceinline__ void wgmma_n192(float (&d)[96], uint64_t da, uint64_t db) {
  asm volatile("wgmma.mma_async.sync.aligned.m64n192k16.f32.bf16.bf16 {"
      "%0,%1,%2,%3,%4,%5,%6,%7,%8,%9,%10,%11,%12,%13,%14,%15,"
      "%16,%17,%18,%19,%20,%21,%22,%23,%24,%25,%26,%27,%28,%29,%30,%31,"
      "%32,%33,%34,%35,%36,%37,%38,%39,%40,%41,%42,%43,%44,%45,%46,%47,"
      "%48,%49,%50,%51,%52,%53,%54,%55,%56,%57,%58,%59,%60,%61,%62,%63,"
      "%64,%65,%66,%67,%68,%69,%70,%71,%72,%73,%74,%75,%76,%77,%78,%79,"
      "%80,%81,%82,%83,%84,%85,%86,%87,%88,%89,%90,%91,%92,%93,%94,%95"
      "}, %96, %97, 1, 1, 1, 0, 1;\n"
      : "+f"(d[0]),"+f"(d[1]),"+f"(d[2]),"+f"(d[3]),"+f"(d[4]),"+f"(d[5]),"+f"(d[6]),"+f"(d[7]),
        "+f"(d[8]),"+f"(d[9]),"+f"(d[10]),"+f"(d[11]),"+f"(d[12]),"+f"(d[13]),"+f"(d[14]),"+f"(d[15]),
        "+f"(d[16]),"+f"(d[17]),"+f"(d[18]),"+f"(d[19]),"+f"(d[20]),"+f"(d[21]),"+f"(d[22]),"+f"(d[23]),
        "+f"(d[24]),"+f"(d[25]),"+f"(d[26]),"+f"(d[27]),"+f"(d[28]),"+f"(d[29]),"+f"(d[30]),"+f"(d[31]),
        "+f"(d[32]),"+f"(d[33]),"+f"(d[34]),"+f"(d[35]),"+f"(d[36]),"+f"(d[37]),"+f"(d[38]),"+f"(d[39]),
        "+f"(d[40]),"+f"(d[41]),"+f"(d[42]),"+f"(d[43]),"+f"(d[44]),"+f"(d[45]),"+f"(d[46]),"+f"(d[47]),
        "+f"(d[48]),"+f"(d[49]),"+f"(d[50]),"+f"(d[51]),"+f"(d[52]),"+f"(d[53]),"+f"(d[54]),"+f"(d[55]),
        "+f"(d[56]),"+f"(d[57]),"+f"(d[58]),"+f"(d[59]),"+f"(d[60]),"+f"(d[61]),"+f"(d[62]),"+f"(d[63]),
        "+f"(d[64]),"+f"(d[65]),"+f"(d[66]),"+f"(d[67]),"+f"(d[68]),"+f"(d[69]),"+f"(d[70]),"+f"(d[71]),
        "+f"(d[72]),"+f"(d[73]),"+f"(d[74]),"+f"(d[75]),"+f"(d[76]),"+f"(d[77]),"+f"(d[78]),"+f"(d[79]),
        "+f"(d[80]),"+f"(d[81]),"+f"(d[82]),"+f"(d[83]),"+f"(d[84]),"+f"(d[85]),"+f"(d[86]),"+f"(d[87]),
        "+f"(d[88]),"+f"(d[89]),"+f"(d[90]),"+f"(d[91]),"+f"(d[92]),"+f"(d[93]),"+f"(d[94]),"+f"(d[95])
      : "l"(da), "l"(db));
}
__device__ __forceinline__ void wgmma_rs_n128(float (&d)[64], uint32_t a0, uint32_t a1, uint32_t a2, uint32_t a3, uint64_t db) {
  asm volatile("wgmma.mma_async.sync.aligned.m64n128k16.f32.bf16.bf16 {"
      "%0,%1,%2,%3,%4,%5,%6,%7,%8,%9,%10,%11,%12,%13,%14,%15,"
      "%16,%17,%18,%19,%20,%21,%22,%23,%24,%25,%26,%27,%28,%29,%30,%31,"
      "%32,%33,%34,%35,%36,%37,%38,%39,%40,%41,%42,%43,%44,%45,%46,%47,"
      "%48,%49,%50,%51,%52,%53,%54,%55,%56,%57,%58,%59,%60,%61,%62,%63"
      "}, {%64,%65,%66,%67}, %68, 1, 1, 1, 1;\n"
      : "+f"(d[0]),"+f"(d[1]),"+f"(d[2]),"+f"(d[3]),"+f"(d[4]),"+f"(d[5]),"+f"(d[6]),"+f"(d[7]),
        "+f"(d[8]),"+f"(d[9]),"+f"(d[10]),"+f"(d[11]),"+f"(d[12]),"+f"(d[13]),"+f"(d[14]),"+f"(d[15]),
        "+f"(d[16]),"+f"(d[17]),"+f"(d[18]),"+f"(d[19]),"+f"(d[20]),"+f"(d[21]),"+f"(d[22]),"+f"(d[23]),
        "+f"(d[24]),"+f"(d[25]),"+f"(d[26]),"+f"(d[27]),"+f"(d[28]),"+f"(d[29]),"+f"(d[30]),"+f"(d[31]),
        "+f"(d[32]),"+f"(d[33]),"+f"(d[34]),"+f"(d[35]),"+f"(d[36]),"+f"(d[37]),"+f"(d[38]),"+f"(d[39]),
        "+f"(d[40]),"+f"(d[41]),"+f"(d[42]),"+f"(d[43]),"+f"(d[44]),"+f"(d[45]),"+f"(d[46]),"+f"(d[47]),
        "+f"(d[48]),"+f"(d[49]),"+f"(d[50]),"+f"(d[51]),"+f"(d[52]),"+f"(d[53]),"+f"(d[54]),"+f"(d[55]),
        "+f"(d[56]),"+f"(d[57]),"+f"(d[58]),"+f"(d[59]),"+f"(d[60]),"+f"(d[61]),"+f"(d[62]),"+f"(d[63])
      : "r"(a0), "r"(a1), "r"(a2), "r"(a3), "l"(db));
}

constexpr int C_LN = 0, C_PX = 16, C_PY = 32;
constexpr int NB_CONS = 1, NB_LN = 2, NB_LAG = 4, NB_INIT = 6, NB_RDY = 7;
#define LAGX 3
#define LAGY 3
#define LAG2 2
#define NLL 2
#define POLL_DELAY3 900
#define POLL_DELAY 900
#define FILT_DELAY 1000
#define RING_SIG 0
#define PF2_SIG 1
constexpr int SM_E = 0, SM_X = 16384, SM_E2 = 32768, SM_W = 49152, SM_FC = 69632, SM_T = 73728 - T1_BYTES;
constexpr unsigned long long KORDER = 0xBA9432DC876510ull;
constexpr uint32_t HI128 = desc_hi(1024, 1), HI64 = desc_hi(512, 2);

struct Bars {
  uint64_t full1[6], empty1[6], fullA[8], full2[14], empty2[8], xbar, xfree, hbar, tbar, sbar, sig[2], hint[3];
  uint32_t epoch;
};

template <int NK, bool STORE>
__device__ __forceinline__ void make_p(const float (&acc)[NK * 16], float r0, float r1, uint4 (&p)[NK], uint4* pbase, int ks0, uint32_t tag) {
#pragma unroll
  for (int j = 0; j < NK; j++) {
    uint32_t w[4];
#pragma unroll
    for (int i = 0; i < 4; i++) {
      const int a = 8 * j + 2 * i, b = a + NK * 8;
      w[i] = pack2(swiglu(acc[a], acc[b], (i & 1) ? r1 : r0), swiglu(acc[a + 1], acc[b + 1], (i & 1) ? r1 : r0));
    }
    asm volatile("" : "+r"(w[0]), "+r"(w[1]), "+r"(w[2]), "+r"(w[3]));
    p[j] = make_uint4(w[0], w[1], w[2], w[3]);
    if (STORE) st_tag(pbase + ((ks0 + j) >> 2) * 1024 + ((ks0 + j) & 3) * 32, p[j], tag);
  }
}
__device__ __forceinline__ void spin_cycles(uint32_t n) {
  const uint32_t t0 = clock32();
  while (clock32() - t0 < n) {}
}

__global__ void __cluster_dims__(2, 1, 1) __launch_bounds__(NTHREADS, 1)
fused_kernel(const __nv_bfloat16* __restrict__ x, const Tables* __restrict__ tab, Scratch* __restrict__ scr,
             __nv_bfloat16* __restrict__ out, const char* __restrict__ wg_raw, const char* __restrict__ wu_raw,
             const char* __restrict__ wd_raw,
             const __grid_constant__ CUtensorMap tmWR, const __grid_constant__ CUtensorMap tmWI,
             const __grid_constant__ CUtensorMap tmGX, const __grid_constant__ CUtensorMap tmUX,
             const __grid_constant__ CUtensorMap tmGY, const __grid_constant__ CUtensorMap tmUY,
             const __grid_constant__ CUtensorMap tmD) {
  extern __shared__ __align__(1024) char smem_raw[];
  const uint32_t sbase = (s2u(smem_raw) + 1023) & ~1023u;
  const uint32_t sbar = sbase + 14 * SLOT, sstat = sbar + 512;
  const int tid = threadIdx.x, lane = tid & 31;
  const int c = blockIdx.x, kh = c & 1, f = (c >> 1) & 7, rb = 2 * (c >> 4) + kh, rb2 = 2 * (c >> 4) + (f >> 2), nq = f & 3;
#define BAR(field, i) (sbar + (uint32_t)offsetof(Bars, field) + 8u * (i))
#define TOFF(field) (sbase + SM_T + (uint32_t)offsetof(Tables, field) + lane * 16)

  if (tid >= 256) {
    asm volatile("setmaxnreg.dec.sync.aligned.u32 56;");
    const int warp = __shfl_sync(0xffffffffu, tid >> 5, 0);
    if (tid == 256) {
      for (int i = 0; i < 6; i++) { mbar_init(BAR(full1, i), 1); mbar_init(BAR(empty1, i), 16); }
      for (int i = 0; i < 8; i++) { mbar_init(BAR(fullA, i), 1); mbar_init(BAR(empty2, i), 8); }
      for (int i = 0; i < 14; i++) mbar_init(BAR(full2, i), 2);
      mbar_init(BAR(xbar, 0), 1);
      mbar_init(BAR(xfree, 0), 8);
      mbar_init(BAR(tbar, 0), 1);
      mbar_init(BAR(hbar, 0), 1);
      mbar_init(BAR(sbar, 0), 32);
      for (int i = 0; i < 3; i++) mbar_init(BAR(hint, i), 1);
      mbar_init(BAR(sig, 0), 8);
      mbar_init(BAR(sig, 1), 8);
      mbar_expect(BAR(xbar, 0), 16384);
      asm volatile("fence.mbarrier_init.release.cluster;" ::: "memory");
      const int w0 = ((c >> 3) * 257 + 32 * (c & 7) + 1) & ~7;
      if (FILT_DELAY) {
        asm volatile("prefetch.tensormap [%0];" ::"l"(&tmWR) : "memory");
        asm volatile("prefetch.tensormap [%0];" ::"l"(&tmWI) : "memory");
        spin_cycles(FILT_DELAY);
      }
      mbar_expect(BAR(tbar, 0), T2_BYTES + 2 * 10240);
      tma3(sbase + SM_W, &tmWR, BAR(tbar, 0), w0, 0, 0);
      tma3(sbase + SM_W + 10240, &tmWI, BAR(tbar, 0), w0, 0, 0);
      bulk_load(sbase + SM_T + T1_BYTES, reinterpret_cast<const char*>(tab) + T1_BYTES, T2_BYTES, BAR(tbar, 0));
    }
    if (tid == 288) {
      asm volatile("prefetch.tensormap [%0];" ::"l"(kh ? &tmUX : &tmGX) : "memory");
      asm volatile("prefetch.tensormap [%0];" ::"l"(kh ? &tmUY : &tmGY) : "memory");
      asm volatile("prefetch.tensormap [%0];" ::"l"(&tmD) : "memory");
    }
    if (tid == 320) {
      const unsigned e = ld_relaxed(&scr->cnt[(C_LN + rb) * 32]) >> 3;
      asm volatile("st.shared.u32 [%0], %1;" ::"r"(BAR(epoch, 0)), "r"(e) : "memory");
    }
    __syncwarp();
    asm volatile("barrier.cluster.arrive.relaxed.aligned;" ::: "memory");
    bar_arrive(NB_RDY, 384);
    asm volatile("barrier.cluster.wait.aligned;" ::: "memory");
    bar_sync(NB_INIT, 384);
    unsigned epoch;
    asm volatile("ld.shared.u32 %0, [%1];" : "=r"(epoch) : "r"(BAR(epoch, 0)) : "memory");
    if (warp == 8) {
      if (lane == 0) {
        const int ax = (7 * f + 3 * (f & 1)) >> 1;
        const int ay = 7 * f + ((f & 1) ? 0 : 4);
        const CUtensorMap* tx = kh ? &tmUX : &tmGX;
        const CUtensorMap* ty = kh ? &tmUY : &tmGY;
        uint32_t s = 0, ph = 1;
        if (RING_SIG >= 0) mbar_wait(BAR(sig, RING_SIG), 0);
#pragma unroll 1
        for (int n = 0; n < 32; n++) {
          const uint32_t dst = sbase + (8 + s) * SLOT, fb = BAR(full1, s);
          mbar_wait(BAR(empty1, s), ph);
          if (n < 16) {
            mbar_expect(fb, 16384);
            tma3_mc(dst + kh * 8192, tx, fb, n * 32, ax);
          } else {
            mbar_expect(fb, 12288);
            tma3_mc(dst + kh * 6144, ty, fb, (n - 16) * 32, ay);
          }
          if (++s == 6) { s = 0; ph ^= 1; }
        }
      }
    } else if (warp == 9) {
      if (lane == 0) {
        mbar_wait(BAR(empty1, 5), 0);
        mbar_wait(BAR(empty1, 5), 1);
#pragma unroll 1
        for (int i = 0; i < 14; i++) {
          const int kblk = 14 * kh + (int)((KORDER >> (4 * i)) & 15);
          if (i < 8) mbar_wait(BAR(empty1, (17 + 2 * i) % 6), ((17 + 2 * i) / 6) & 1);
          else mbar_wait(BAR(empty2, i - 8), 0);
          mbar_expect(BAR(full2, i), 16384);
          tma3(sbase + (i & 7) * SLOT, &tmD, BAR(full2, i), 0, 64 * kblk, 2 * nq);
        }
        wait_counter(&scr->cnt[(C_LN + rb2) * 32], (epoch + 1) * 8);
        asm volatile("fence.proxy.async.global;" ::: "memory");
        mbar_wait(BAR(empty2, 7), 0);
        mbar_expect(BAR(hbar, 0), 16384);
        bulk_load(sbase + 7 * SLOT, &scr->LN[(rb2 * 8 + 2 * nq) * 1024 + kh * 512], 8192, BAR(hbar, 0));
        bulk_load(sbase + 7 * SLOT + 8192, &scr->LN[(rb2 * 8 + 2 * nq + 1) * 1024 + kh * 512], 8192, BAR(hbar, 0));
      }
    } else if (warp == 10) {
      bar_sync(NB_LN, 288);
      if (lane == 0) {
        PROFP(0);
        red_release(&scr->cnt[(C_LN + rb) * 32]);
        PROFP(1);
        wait_counter(&scr->cnt[(C_LN + rb) * 32], (epoch + 1) * 8);
        asm volatile("fence.proxy.async.global;" ::: "memory");
        PROFP(2);
#pragma unroll 1
        for (int kb = NLL; kb < 8; kb++) {
          mbar_expect(BAR(fullA, kb), 16384);
          bulk_load(sbase + kb * SLOT, &scr->LN[(rb * 8 + kb) * 1024], 16384, BAR(fullA, kb));
        }
#pragma unroll 1
        for (int i = 0; i < 4; i++) mbar_wait(BAR(empty1, 2), i & 1);
        uint32_t d = 2;
#pragma unroll 1
        for (int s = 0; s < 14; s++) {
          const int kblk = 14 * kh + (int)((KORDER >> (4 * s)) & 15);
          if (s == 0 || s == 8 || s == 11) {
            if (s != 11) PROFP(3 + (s >> 2));
            mbar_wait(BAR(hint, s == 0 ? 0 : s == 8 ? 1 : 2), 0);
            if (s != 11) PROFP(4 + (s >> 2));
          }
          if (s < 6) mbar_wait(BAR(empty1, d), s < 4 ? 0 : 1);
          else mbar_wait(BAR(empty2, s - 6), 0);
          mbar_expect(BAR(full2, s), 16384);
          bulk_load(sbase + (8 + d) * SLOT, &scr->P[(rb2 * 28 + kblk) * 1024], 16384, BAR(full2, s));
          if (++d == 6) d = 0;
        }
        PROFP(7);
      }
    } else {
      if (lane == 0) {
        l2_prefetch(wg_raw + (size_t)c * 5376, 5376);
        l2_prefetch(wu_raw + (size_t)c * 5376, 5376);
        mbar_wait(BAR(sig, PF2_SIG), 0);
        l2_prefetch(wg_raw + 688128 + (size_t)c * 8960, 8960);
        l2_prefetch(wu_raw + 688128 + (size_t)c * 8960, 8960);
      }
      mbar_wait(BAR(fullA, 7), 0);
      if (lane == 0) l2_prefetch(wd_raw + (size_t)c * 14336, 14336);
      {
        const uint32_t tag = (epoch + 1) & 1;
        uint4 v0, v1, v2;
        int it = 0;
        while (true) {
          v0 = ld_b128(&scr->ST[rb * 64 + lane]);
          v1 = ld_b128(&scr->ST[rb * 64 + 32 + lane]);
          v2 = ld_b128(&scr->ST[rb2 * 64 + 32 * kh + lane]);
          if (!__any_sync(0xffffffffu, ((v0.x ^ tag) | (v1.x ^ tag) | (v2.x ^ tag)) & 1u)) break;
          if (++it > SPIN_LIMIT) { die(); break; }
        }
        sts4(sstat + lane * 16, v0.x & ~1u, v0.y, v0.z, v0.w);
        sts4(sstat + 512 + lane * 16, v1.x & ~1u, v1.y, v1.z, v1.w);
        sts4(sstat + 1024 + lane * 16, v2.x & ~1u, v2.y, v2.z, v2.w);
        mbar_arrive(BAR(sbar, 0));
      }
      if (lane == 0) {
        mbar_wait(BAR(empty1, 5), 0);
        mbar_wait(BAR(empty1, 5), 1);
        mbar_wait(BAR(empty1, 5), 0);
#pragma unroll 1
        for (int e = 0; e < 3; e++) {
          const unsigned* cp = e == 0 ? &scr->cnt[(C_PX + rb2) * 32] : &scr->cnt[(C_PY + rb2) * 32 + 2 * kh + e - 1];
          if (e == 1) mbar_wait(BAR(full2, 0), 0);
          int it = 0;
          while ((int)(ld_relaxed(cp) - (epoch + 1) * (e == 0 ? 64 : 16)) < 0)
            if (++it > SPIN_LIMIT) { die(); break; }
          mbar_arrive(BAR(hint, e));
        }
      }
    }
  } else {
    const int warp = __shfl_sync(0xffffffffu, tid >> 5, 0);
    const int g = lane >> 2, t = lane & 3;
    PROF(0);
    PROFG(14);
#pragma unroll
    for (int i = 0; i < 4; i++) {
      const int r = i >> 1, ch = (i & 1) * 32 + lane;
      cp_async16(sbase + SM_X + (2 * warp + r) * 1024 + ((ch ^ ((ch >> 2) & 6)) * 16),
                 x + (size_t)(c + 128 * (2 * warp + r)) * 512 + ch * 8);
    }
    asm volatile("cp.async.commit_group;" ::: "memory");
    asm volatile("barrier.cluster.arrive.relaxed.aligned;" ::: "memory");
    uint4 tw[8], fb[16];
    const uint4 fa = ldg_ca4(&tab->fa[lane][0]);
#pragma unroll
    for (int i = 0; i < 8; i++) tw[i] = ldg_ca4(&tab->tw1[i][lane][0]);
#pragma unroll
    for (int i = 0; i < 16; i++) fb[i] = ldg_ca4(&tab->fb[i][lane][0]);
    uint32_t rbar;
    asm volatile("mapa.shared::cluster.u32 %0, %1, %2;" : "=r"(rbar) : "r"(sbar), "r"(kh ^ 1));
#define RBAR(field, i) (rbar + (uint32_t)offsetof(Bars, field) + 8u * (i))
    {
      const int ln = (tid >> 1) & 31, lg = ln >> 2, lt = ln & 3, i = 4 * (tid >> 6) + 2 * (tid & 1);
      const int kidx = lt + 8 * (i >> 3), nidx = 4 * ((i >> 1) & 3) + (lg >> 1);
      const uint32_t a0 = cfrag<2048>((c + 128 * kidx) * nidx, lg & 1), a1 = cfrag<2048>((c + 128 * (kidx + 4)) * nidx, lg & 1);
      const uint32_t b0 = cfrag<2048>(-(c + 128 * nidx) * kidx, lg & 1), b1 = cfrag<2048>(-(c + 128 * nidx) * (kidx + 4), lg & 1);
      asm volatile("st.shared.v2.u32 [%0], {%1,%2};" ::"r"(sbase + SM_FC + tid * 8), "r"(a0), "r"(a1) : "memory");
      asm volatile("st.shared.v2.u32 [%0], {%1,%2};" ::"r"(sbase + SM_FC + 2048 + tid * 8), "r"(b0), "r"(b1) : "memory");
    }
    asm volatile("cp.async.wait_group 0;" ::: "memory");
    __syncwarp();
    bar_arrive(NB_INIT, 384);
    PROF(13);
    uint32_t tag;
    uint4 q[4], o[4];
    {
      uint32_t v[2][8];
#pragma unroll
      for (int r = 0; r < 2; r++)
#pragma unroll
        for (int q = 0; q < 4; q++) {
          const uint2 u = lds2(sbase + SM_X + (2 * warp + r) * 1024 + (t + 4 * (q >> 1)) * 128 + (((4 * (q & 1) + (g >> 1)) ^ (2 * t)) * 16) + (g & 1) * 8);
          v[r][2 * q] = u.x; v[r][2 * q + 1] = u.y;
        }
      float sum[2], sq[2], rstd[2];
      row_stats(v[0], v[1], lane, sum, sq);
#pragma unroll
      for (int r = 0; r < 2; r++) {
        const float m = sum[r] * (1.f / 512.f);
        rstd[r] = rsqrtf(fmaxf(fmaf(-m, m, sq[r] * (1.f / 512.f)), 0.f) + 1e-5f);
      }
      uint32_t alo[4][4], ahi[4][4];
#pragma unroll
      for (int r = 0; r < 2; r++)
#pragma unroll
        for (int i = 0; i < 4; i++) {
          const uint32_t sel = (i & 1) ? 0x7632u : 0x5410u;
          const uint32_t b0 = __byte_perm(v[r][i >> 1], v[r][2 + (i >> 1)], sel);
          const uint32_t b1 = __byte_perm(v[r][4 + (i >> 1)], v[r][6 + (i >> 1)], sel);
          float d[4] = {0.f, 0.f, 0.f, 0.f};
          mma16816(d, fa.x, fa.y, fa.z, fa.w, b0, b1);
          const uint4 &ka = tw[2 * i], &kb = tw[2 * i + 1];
          const uint32_t re = pack2(d[0] * __uint_as_float(ka.x) + d[2] * __uint_as_float(ka.y), d[1] * __uint_as_float(kb.x) + d[3] * __uint_as_float(kb.y));
          const uint32_t im = pack2(d[0] * __uint_as_float(ka.z) + d[2] * __uint_as_float(ka.w), d[1] * __uint_as_float(kb.z) + d[3] * __uint_as_float(kb.w));
          const uint32_t dc = pack2(fmaf(sum[r], -1.f / 32.f, d[0]), fmaf(sum[r], -1.f / 32.f, d[1]));
          alo[i][r] = re; alo[i][2 + r] = im;
          ahi[i][r] = g == 0 ? dc : re; ahi[i][2 + r] = g == 0 ? 0u : im;
        }
      float acc[8][4];
#pragma unroll
      for (int u = 0; u < 8; u++) {
        acc[u][0] = acc[u][1] = acc[u][2] = acc[u][3] = 0.f;
#pragma unroll
        for (int i = 0; i < 4; i++) {
          const uint4& bq = fb[i * 4 + (u >> 1)];
          if (u < 4) mma16816(acc[u], alo[i][0], alo[i][1], alo[i][2], alo[i][3], (u & 1) ? bq.z : bq.x, (u & 1) ? bq.w : bq.y);
          else       mma16816(acc[u], ahi[i][0], ahi[i][1], ahi[i][2], ahi[i][3], (u & 1) ? bq.z : bq.x, (u & 1) ? bq.w : bq.y);
        }
      }
#pragma unroll
      for (int r = 0; r < 2; r++)
#pragma unroll
        for (int h = 0; h < 2; h++) {
          const int j = 2 * warp + r, m = 2 * t + h;
          const float rs = rstd[r];
          sts4(sbase + SM_E + ((j * 8 + m) * 8 + (g ^ (2 * t) ^ (2 * (j & 3)))) * 16,
               pack2(acc[2 * h][2 * r] * rs, acc[2 * h][2 * r + 1] * rs), pack2(acc[2 * h + 1][2 * r] * rs, acc[2 * h + 1][2 * r + 1] * rs),
               pack2(acc[4 + 2 * h][2 * r] * rs, acc[4 + 2 * h][2 * r + 1] * rs), pack2(acc[5 + 2 * h][2 * r] * rs, acc[5 + 2 * h][2 * r + 1] * rs));
        }
      if (tid == 0) PROFP(12);
      bar_sync(NB_RDY, 384);
      if (tid == 0) PROFP(13);
      uint4 fc[4];
#pragma unroll
      for (int i = 0; i < 4; i++) fc[i] = lds4(sbase + SM_FC + i * 512 + lane * 16);
      asm volatile("ld.shared.u32 %0, [%1];" : "=r"(tag) : "r"(BAR(epoch, 0)) : "memory");
      tag = (tag + 1) & 1;
#pragma unroll
      for (int i = 0; i < 4; i++) q[i] = lds4(sbase + SM_E + (((t + 4 * i) * 8 + warp) * 8 + (g ^ (warp & 6) ^ (2 * t))) * 16);
      cdft16(q, fc, o);
#pragma unroll
      for (int vv = 0; vv < 4; vv++) st_tag(&scr->Z1[(((4 * vv + t) * 8 + warp) * 128 + c) * 8 + g], o[vv], tag);
    }
    PROF(1);
    {
      const uint4* const zp = &scr->Z1[(c * 128 + 8 * t + warp) * 8 + g];
      const uint32_t tst = clock32();
      mbar_wait(BAR(tbar, 0), 0);
      if (tid == 0) PROFP(14);
      uint4 f2[4], g2[4];
#pragma unroll
      for (int i = 0; i < 4; i++) {
        f2[i] = lds4(TOFF(f2) + warp * 2048 + i * 512);
        g2[i] = lds4(TOFF(g2) + warp * 2048 + i * 512);
      }
      const uint4 f8 = lds4(TOFF(f8)), g8 = lds4(TOFF(g8));
      float wfr[16], wfi[16];
      {
        const float fsc = 1.f / (1 << 19);
        const float fsc3 = ((c & 7) == 7 && g == 0) ? 0.5f * fsc : fsc;
        const int gg = g == 0 ? 8 : g, wsh = (2 * (c >> 3) + 2) & 15;
#pragma unroll
        for (int i = 0; i < 16; i++) {
          const int ci = i >> 3, dd = (i >> 2) & 1, e = i & 3;
          const int kk = (e == 0 ? gg : e == 1 ? 16 + gg : e == 2 ? 16 - g : 32 - g) - 1;
          const uint32_t a = sbase + SM_W + ((2 * warp + ci) * 8 + t + 4 * dd) * 80 + wsh + 2 * kk;
          wfr[i] = bf_lo(lds_u16(a)) * (e == 3 ? fsc3 : fsc);
          wfi[i] = bf_lo(lds_u16(a + 10240)) * (e == 3 ? fsc3 : fsc);
        }
      }
      asm volatile("barrier.cluster.wait.aligned;" ::: "memory");
      PROF(2);
      while (clock32() - tst < POLL_DELAY) {}
      ld_tag4_issue<256>(q, zp);
      ld_tag4_finish<256>(q, zp, tag);
      if (tid == 0) PROFP(30);
      if (lane == 0) mbar_arrive(BAR(sig, 0));
      cdft16(q, f2, o);
      const uint32_t e2 = sbase + SM_E2;
#pragma unroll
      for (int vv = 0; vv < 4; vv++)
        sts4(e2 + ((warp * 16 + 4 * vv + t) * 8 + (g ^ (2 * t) ^ (2 * (warp & 3)))) * 16, o[vv].x, o[vv].y, o[vv].z, o[vv].w);
      bar_sync(NB_CONS, 256);
#pragma unroll
      for (int ci = 0; ci < 2; ci++) {
        const int cc = 2 * warp + ci;
        uint32_t ad[2];
        uint4 u[2];
#pragma unroll
        for (int hh = 0; hh < 2; hh++) {
          ad[hh] = e2 + (((t + 4 * hh) * 16 + cc) * 8 + (g ^ (2 * (cc & 3)) ^ (2 * t))) * 16;
          u[hh] = lds4(ad[hh]);
        }
        uint32_t res[2][4];
#pragma unroll
        for (int p = 0; p < 2; p++) {
          uint32_t y[2][2];
#pragma unroll
          for (int vv = 0; vv < 2; vv++) {
            float d[4] = {0.f, 0.f, 0.f, 0.f};
            mma16816(d, word(u[0], 2 * p), word(u[0], 2 * p + 1), word(u[1], 2 * p), word(u[1], 2 * p + 1), word(f8, 2 * vv), word(f8, 2 * vv + 1));
#pragma unroll
            for (int rr = 0; rr < 2; rr++) {
              const float fr = wfr[ci * 8 + vv * 4 + 2 * p + rr], fi = wfi[ci * 8 + vv * 4 + 2 * p + rr];
              y[vv][rr] = pack2(d[2 * rr] * fr - d[2 * rr + 1] * fi, d[2 * rr] * fi + d[2 * rr + 1] * fr);
            }
          }
#pragma unroll
          for (int vv = 0; vv < 2; vv++) {
            float d[4] = {0.f, 0.f, 0.f, 0.f};
            mma16816(d, y[0][0], y[0][1], y[1][0], y[1][1], word(g8, 2 * vv), word(g8, 2 * vv + 1));
            res[vv][2 * p] = pack2(d[0], d[1]);
            res[vv][2 * p + 1] = pack2(d[2], d[3]);
          }
        }
#pragma unroll
        for (int vv = 0; vv < 2; vv++) sts4(ad[vv], res[vv][0], res[vv][1], res[vv][2], res[vv][3]);
      }
      bar_sync(NB_CONS, 256);
#pragma unroll
      for (int i = 0; i < 4; i++) q[i] = lds4(e2 + ((warp * 16 + 4 * i + t) * 8 + (g ^ (2 * t) ^ (2 * (warp & 3)))) * 16);
      cdft16(q, g2, o);
#pragma unroll
      for (int vv = 0; vv < 4; vv++) st_tag(&scr->Z2[((8 * (4 * vv + t) + warp) * 128 + c) * 8 + g], o[vv], tag);
    }
    PROF(3);
    {
      const uint4* const zp = &scr->Z2[((c * 16 + t) * 8 + warp) * 8 + g];
      const uint32_t tst = clock32();
      uint4 gb[16], gc[4], tw[4], xr[2][2];
#pragma unroll
      for (int i = 0; i < 16; i++) gb[i] = lds4(TOFF(gb) + i * 512);
      const uint4 ga = lds4(TOFF(ga));
#pragma unroll
      for (int i = 0; i < 4; i++) {
        gc[i] = lds4(sbase + SM_FC + 2048 + i * 512 + lane * 16);
        tw[i] = lds4(TOFF(tw3) + i * 512);
        const int ch = 4 * (g + 8 * (i & 1)) + t;
        xr[i >> 1][i & 1] = lds4(sbase + SM_X + (2 * warp + (i >> 1)) * 1024 + ((ch ^ ((ch >> 2) & 6)) * 16));
      }
      PROF(4);
      while (clock32() - tst < POLL_DELAY) {}
      ld_tag4_issue<256>(q, zp);
      ld_tag4_finish<256>(q, zp, tag);
      if (tid == 0) PROFP(31);
      if (lane == 0) mbar_arrive(BAR(sig, 1));
      cdft16(q, gc, o);
#pragma unroll
      for (int vv = 0; vv < 4; vv++)
        sts4(sbase + SM_E + (((4 * vv + t) * 8 + warp) * 8 + (g ^ (warp & 6) ^ (2 * t))) * 16, o[vv].x, o[vv].y, o[vv].z, o[vv].w);
      bar_sync(NB_CONS, 256);
      uint32_t hv[2][8];
      const float mk = t == 0 ? 0.f : 1.f;
#pragma unroll
      for (int r = 0; r < 2; r++) {
        const int j = 2 * warp + r;
        uint4 u[2];
#pragma unroll
        for (int h = 0; h < 2; h++) u[h] = lds4(sbase + SM_E + ((j * 8 + 2 * t + h) * 8 + (g ^ (2 * t) ^ (2 * (j & 3)))) * 16);
        float yv[4][4];
#pragma unroll
        for (int i = 0; i < 4; i++) {
          float lo[4] = {0.f, 0.f, 0.f, 0.f}, hi[4] = {0.f, 0.f, 0.f, 0.f};
          mma16816(lo, gb[i * 4].x, gb[i * 4].y, gb[i * 4].z, gb[i * 4].w, u[0].x, u[0].y);
          mma16816(lo, gb[i * 4 + 1].x, gb[i * 4 + 1].y, gb[i * 4 + 1].z, gb[i * 4 + 1].w, u[1].x, u[1].y);
          mma16816(hi, gb[i * 4 + 2].x, gb[i * 4 + 2].y, gb[i * 4 + 2].z, gb[i * 4 + 2].w, u[0].z, u[0].w);
          mma16816(hi, gb[i * 4 + 3].x, gb[i * 4 + 3].y, gb[i * 4 + 3].z, gb[i * 4 + 3].w, u[1].z, u[1].w);
          const float ca = __uint_as_float(tw[i].x), sa = __uint_as_float(tw[i].y), cb = __uint_as_float(tw[i].z), sb = __uint_as_float(tw[i].w);
          const float tr0 = fmaf(hi[0], mk, lo[0]), ti0 = fmaf(hi[2], mk, lo[2]);
          const float tr1 = lo[1] + hi[1], ti1 = lo[3] + hi[3];
          const float vr0 = tr0 * ca - ti0 * sa, vi0 = tr0 * sa + ti0 * ca;
          const float vr1 = tr1 * cb - ti1 * sb, vi1 = tr1 * sb + ti1 * cb;
          const uint32_t b0 = pack2(t == 0 ? hi[0] : vr0, vr1), b1 = pack2(t == 0 ? vr0 : vi0, vi1);
          yv[i][0] = yv[i][1] = yv[i][2] = yv[i][3] = 0.f;
          mma16816(yv[i], ga.x, ga.y, ga.z, ga.w, b0, b1);
        }
#pragma unroll
        for (int h = 0; h < 2; h++) {
          hv[r][4 * h + 0] = hadd2_bf16(xr[r][h].x, pack2(yv[0][2 * h], yv[1][2 * h]));
          hv[r][4 * h + 1] = hadd2_bf16(xr[r][h].y, pack2(yv[2][2 * h], yv[3][2 * h]));
          hv[r][4 * h + 2] = hadd2_bf16(xr[r][h].z, pack2(yv[0][2 * h + 1], yv[1][2 * h + 1]));
          hv[r][4 * h + 3] = hadd2_bf16(xr[r][h].w, pack2(yv[2][2 * h + 1], yv[3][2 * h + 1]));
        }
      }
      float ds[4] = {0.f, 0.f, 0.f, 0.f};
#pragma unroll
      for (int q4 = 0; q4 < 4; q4++) mma16816(ds, hv[0][2 * q4], hv[1][2 * q4], hv[0][2 * q4 + 1], hv[1][2 * q4 + 1], 0x3f803f80u, 0x3f803f80u);
#pragma unroll
      for (int o2 = 4; o2 <= 16; o2 <<= 1) {
        ds[0] += __shfl_xor_sync(0xffffffffu, ds[0], o2);
        ds[2] += __shfl_xor_sync(0xffffffffu, ds[2], o2);
      }
      uint32_t mb[2];
#pragma unroll
      for (int r = 0; r < 2; r++) {
        const int row = 16 * f + 2 * warp + r;
        mb[r] = pack2(ds[2 * r] * (1.f / 512.f), ds[2 * r] * (1.f / 512.f));
#pragma unroll
        for (int i = 0; i < 8; i++) hv[r][i] = hsub2_bf16(hv[r][i], mb[r]);
#pragma unroll
        for (int h = 0; h < 2; h++) {
          const int n1 = g + 8 * h;
          st_tag(&scr->LN[(rb * 8 + (n1 >> 1)) * 1024 + row * 8 + ((4 * (n1 & 1) + t) ^ (row & 7))],
                 make_uint4(hv[r][4 * h], hv[r][4 * h + 1], hv[r][4 * h + 2], hv[r][4 * h + 3]), n1 < 2 * NLL ? tag : (hv[r][4 * h] & 1u));
        }
      }
      bar_arrive(NB_LN, 288);
      float sum[2], sq[2], rstd[2];
      row_stats(hv[0], hv[1], lane, sum, sq);
#pragma unroll
      for (int r = 0; r < 2; r++) {
        const float m = sum[r] * (1.f / 512.f);
        rstd[r] = rsqrtf(fmaxf(fmaf(-m, m, sq[r] * (1.f / 512.f)), 0.f) + 1e-5f);
      }
      if (lane == 0)
        st_tag(&scr->ST[rb * 64 + 8 * f + warp], make_uint4(mb[0] << 16, __float_as_uint(rstd[0]), mb[1] << 16, __float_as_uint(rstd[1])), tag);
    }
    PROF(5);
    asm volatile("setmaxnreg.inc.sync.aligned.u32 224;");
    if (NLL) {
      const uint4* const ap = &scr->LN[rb * 8 * 1024 + tid];
      uint4 av[NLL ? NLL : 1][4];
      spin_cycles(POLL_DELAY3);
#pragma unroll
      for (int kb = 0; kb < NLL; kb++) ld_tag4_issue<256>(av[kb], ap + kb * 1024);
      bar_sync(NB_CONS, 256);
#pragma unroll
      for (int kb = 0; kb < NLL; kb++) {
        ld_tag4_finish<256>(av[kb], ap + kb * 1024, tag);
#pragma unroll
        for (int i = 0; i < 4; i++) sts4(sbase + kb * SLOT + (tid + 256 * i) * 16, av[kb][i].x, av[kb][i].y, av[kb][i].z, av[kb][i].w);
      }
      asm volatile("fence.proxy.async.shared::cta;" ::: "memory");
      bar_sync(NB_CONS, 256);
    }
    const int wgi = warp >> 2, wq = warp & 3;
    uint4* const pbase = &scr->P[rb * 28 * 1024 + warp * 128 + lane];
    const uint32_t a_lo0 = desc_lo(sbase + wgi * 8192, 16);
    const uint32_t ebar = lane == 0 ? BAR(empty1, 0) : RBAR(empty1, 0);
    float r0, r1;
    uint4 px[8], py[6];
    const int rh = wgi ^ kh ^ 1;
    const uint4* const psrc = &scr->P[(rb2 * 28 + 14 * kh) * 1024 + (4 * rh + wq) * 128 + lane];
    {
      float acc[128];
#pragma unroll
      for (int i = 0; i < 128; i++) acc[i] = 0.f;
      const uint32_t b_lo0 = desc_lo(sbase + 8 * SLOT, 4096);
      uint32_t slot = 0, ph = 0, prev = 0;
#pragma unroll 1
      for (int kb = 0; kb < 8; kb++) {
        if (kb >= NLL) mbar_wait(BAR(fullA, kb), 0);
        if (kb == 0) PROF(6);
#pragma unroll
        for (int hh = 0; hh < 2; hh++) {
          if (LAGX && hh == ((16 - LAGX) & 1) && kb == ((16 - LAGX) >> 1) && wgi == 1) bar_sync(NB_LAG, 256);
          mbar_wait(BAR(full1, slot), ph);
          const uint32_t al = a_lo0 + kb * 1024 + hh * 4, bl = b_lo0 + slot * 1024;
          wg_fence();
          wgmma_n256(acc, desc64(al, HI128), desc64(bl, HI128));
          wgmma_n256(acc, desc64(al + 2, HI128), desc64(bl + 128, HI128));
          wg_commit();
          if (LAGX && hh == 1 && kb == 7 && wgi == 0) bar_arrive(NB_LAG, 256);
          wg_wait<1>();
          if ((kb | hh) != 0 && lane < 2) mbar_arrive_remote(ebar + 8 * prev);
          prev = slot;
          if (++slot == 6) { slot = 0; ph ^= 1; }
        }
      }
      mbar_wait(BAR(sbar, 0), 0);
      r0 = __uint_as_float(lds2(sstat + (16 * warp + g) * 8).y);
      r1 = __uint_as_float(lds2(sstat + (16 * warp + g + 8) * 8).y);
      wg_wait<0>();
      if (lane < 2) mbar_arrive_remote(ebar + 8 * prev);
      PROF(7);
      make_p<8, false>(acc, r0, r1, px, pbase, 0, tag);
    }
    PROF(8);
    {
      float acc[96];
#pragma unroll
      for (int i = 0; i < 96; i++) acc[i] = 0.f;
      const uint32_t b_lo0 = desc_lo(sbase + 8 * SLOT, 2048);
      uint4* const pdst = pbase + ((7 * f + 3 * (f & 1)) >> 1) * 1024;
      auto stage_y = [&](int k, uint32_t slot, uint32_t ph) {
        if (LAGY && k == 16 - LAGY && wgi == 1) bar_sync(NB_LAG, 256);
        mbar_wait(BAR(full1, slot), ph);
        const uint32_t al = a_lo0 + (k >> 1) * 1024 + (k & 1) * 4, bl = b_lo0 + slot * 1024;
        wg_fence();
        wgmma_n192(acc, desc64(al, HI128), desc64(bl, HI64));
        wgmma_n192(acc, desc64(al + 2, HI128), desc64(bl + 64, HI64));
        wg_commit();
      };
#pragma unroll
      for (int k = 0; k < 4; k++) {
        stage_y(k, (16 + k) % 6, ((16 + k) / 6) & 1);
        st_tag(pdst + (k >> 1) * 1024 + (k & 1) * 64, px[2 * k], tag);
        st_tag(pdst + (k >> 1) * 1024 + (k & 1) * 64 + 32, px[2 * k + 1], tag);
        if (k == 3 && lane == 0) red_relaxed(&scr->cnt[(C_PX + rb) * 32]);
        wg_wait<1>();
        if (k != 0 && lane < 2) mbar_arrive_remote(ebar + 8 * ((15 + k) % 6));
      }
      uint32_t slot = 2, ph = 1, prev = 1;
#pragma unroll 1
      for (int k = 4; k < 16; k++) {
        stage_y(k, slot, ph);
        if (LAGY && k == 15 && wgi == 0) bar_arrive(NB_LAG, 256);
        wg_wait<1>();
        if (lane < 2) mbar_arrive_remote(ebar + 8 * prev);
        prev = slot;
        if (++slot == 6) { slot = 0; ph ^= 1; }
      }
      wg_wait<0>();
      if (lane < 2) mbar_arrive_remote(ebar + 8 * (31 % 6));
      PROF(9);
      make_p<6, true>(acc, r0, r1, py, pbase, 14 * f + ((f & 1) ? 0 : 8), tag);
      if (lane == 0) red_relaxed(&scr->cnt[(C_PY + rb) * 32 + (f >> 1)]);
    }
    PROF(10);
    {
      float acc[64];
      {
        const float m0 = wgi ? __uint_as_float(lds2(sstat + 1024 + (16 * wq + g) * 8).x) : 0.f;
        const float m1 = wgi ? __uint_as_float(lds2(sstat + 1024 + (16 * wq + g + 8) * 8).x) : 0.f;
#pragma unroll
        for (int i = 0; i < 64; i++) acc[i] = (i & 2) ? m1 : m0;
      }
      const uint32_t b2_lo0 = desc_lo(sbase, 8192);
      const uint32_t pa0 = sbase + 8 * SLOT + (4 * rh + wq) * 2048 + lane * 16;
      uint32_t slot = 2;
      auto stage2 = [&](int s) {
        uint4 a[4];
        if (LAG2 && s == 14 - LAG2 && wgi == 1) bar_sync(NB_LAG, 256);
        mbar_wait(BAR(full2, s), 0);
        if (tid == 0) PROFP(16 + s);
#pragma unroll
        for (int kk = 0; kk < 4; kk++) a[kk] = lds4(pa0 + slot * SLOT + kk * 512);
        ld_tag4_finish<32>(a, psrc + (int)((KORDER >> (4 * s)) & 15) * 1024, tag);
        const uint32_t bl = b2_lo0 + (s & 7) * 1024;
        wg_fence();
#pragma unroll
        for (int kk = 0; kk < 4; kk++) wgmma_rs_n128(acc, a[kk].x, a[kk].y, a[kk].z, a[kk].w, desc64(bl + kk * 128, HI128));
        wg_commit();
        if (++slot == 6) slot = 0;
      };
      auto release2 = [&](int s) {
        wg_wait<1>();
        if (s >= 1 && s <= 8 && lane == 0) {
          mbar_arrive(BAR(empty2, s - 1));
          if (s == 8) mbar_arrive_remote(RBAR(xfree, 0));
        }
      };
#pragma unroll 1
      for (int s = 0; s < 14; s += 2) {
        stage2(s);
        release2(s);
        stage2(s + 1);
        if (LAG2 && s == 12 && wgi == 0) bar_arrive(NB_LAG, 256);
        release2(s + 1);
      }
      uint4 hres[2][4];
      mbar_wait(BAR(hbar, 0), 0);
#pragma unroll
      for (int h = 0; h < 2; h++)
#pragma unroll
        for (int q = 0; q < 4; q++) {
          hres[h][q] = lds4(sbase + 7 * SLOT + (q >> 1) * 8192 + (16 * wq + g + 8 * h) * 128 + (((4 * (q & 1) + t) ^ g) * 16));
          if (2 * nq + (q >> 1) < NLL) hres[h][q].x &= ~1u;
        }
      wg_wait<0>();
      PROF(11);
      const uint32_t xbuf = sbase + 6 * SLOT + (tid & 127) * 16;
      if (wgi == 0) {
        uint32_t rbuf;
        mbar_wait(BAR(xfree, 0), 0);
        asm volatile("mapa.shared::cluster.u32 %0, %1, %2;" : "=r"(rbuf) : "r"(xbuf), "r"(kh ^ 1));
#pragma unroll
        for (int i = 0; i < 8; i++)
          asm volatile("st.async.weak.shared::cluster.mbarrier::complete_tx::bytes.v4.b32 [%0], {%1,%2,%3,%4}, [%5];"
                       ::"r"(rbuf + i * 2048), "r"(pack2(acc[8 * i], acc[8 * i + 1])), "r"(pack2(acc[8 * i + 2], acc[8 * i + 3])),
                         "r"(pack2(acc[8 * i + 4], acc[8 * i + 5])), "r"(pack2(acc[8 * i + 6], acc[8 * i + 7])), "r"(RBAR(xbar, 0))
                       : "memory");
      } else {
        mbar_wait_cluster(BAR(xbar, 0), 0);
      }
      uint32_t w[2][16];
#pragma unroll
      for (int i = 0; i < 8; i++) {
        const uint4 pv = lds4(xbuf + i * 2048);
        w[0][2 * i] = pack2(acc[8 * i] + bf_lo(pv.x), acc[8 * i + 1] + bf_hi(pv.x));
        w[1][2 * i] = pack2(acc[8 * i + 2] + bf_lo(pv.y), acc[8 * i + 3] + bf_hi(pv.y));
        w[0][2 * i + 1] = pack2(acc[8 * i + 4] + bf_lo(pv.z), acc[8 * i + 5] + bf_hi(pv.z));
        w[1][2 * i + 1] = pack2(acc[8 * i + 6] + bf_lo(pv.w), acc[8 * i + 7] + bf_hi(pv.w));
      }
      uint4* const o4 = reinterpret_cast<uint4*>(out) + (16 * (c >> 4) + 2 * (4 * rh + wq) + (rb2 & 1) + 128 * g) * 64 + nq * 16 + t;
#pragma unroll
      for (int h = 0; h < 2; h++)
#pragma unroll
        for (int q = 0; q < 4; q++) {
          uint32_t a0 = w[h][4 * q], a1 = w[h][4 * q + 1], a2 = w[h][4 * q + 2], a3 = w[h][4 * q + 3];
          {
            const bool od = t & 1;
            uint32_t s0 = od ? a0 : a1, s1 = od ? a2 : a3;
            s0 = __shfl_xor_sync(0xffffffffu, s0, 1); s1 = __shfl_xor_sync(0xffffffffu, s1, 1);
            if (od) { a0 = s0; a2 = s1; } else { a1 = s0; a3 = s1; }
          }
          {
            const bool up = t & 2;
            uint32_t s0 = up ? a0 : a2, s1 = up ? a1 : a3;
            s0 = __shfl_xor_sync(0xffffffffu, s0, 2); s1 = __shfl_xor_sync(0xffffffffu, s1, 2);
            if (up) { a0 = s0; a1 = s1; } else { a2 = s0; a3 = s1; }
          }
          if (wgi == 1)
            o4[h * 1024 * 64 + 4 * q] =
                make_uint4(hadd2_bf16(hres[h][q].x, a0), hadd2_bf16(hres[h][q].y, a1), hadd2_bf16(hres[h][q].z, a2), hadd2_bf16(hres[h][q].w, a3));
        }
      PROF(12);
      PROFG(15);
    }
  }
#undef BAR
#undef TOFF
#undef RBAR
}

typedef CUresult (*EncodeFn)(CUtensorMap*, CUtensorMapDataType, cuuint32_t, void*, const cuuint64_t*, const cuuint64_t*,
                             const cuuint32_t*, const cuuint32_t*, CUtensorMapInterleave, CUtensorMapSwizzle,
                             CUtensorMapL2promotion, CUtensorMapFloatOOBfill);

}

extern "C" void kernel_launch(void* const* d_in, const int* in_sizes, int n_in, void* d_out, int out_size) {
  (void)in_sizes; (void)n_in; (void)out_size;
  static EncodeFn encode = nullptr;
  static void *tab = nullptr, *scr = nullptr;
  if (!encode) {
    void* fn = nullptr;
    cudaDriverEntryPointQueryResult qr;
    cudaGetDriverEntryPoint("cuTensorMapEncodeTiled", &fn, cudaEnableDefault, &qr);
    encode = (EncodeFn)fn;
    cudaGetSymbolAddress(&tab, g_tab);
    cudaGetSymbolAddress(&scr, g_scr);
    cudaFuncSetAttribute(fused_kernel, cudaFuncAttributeMaxDynamicSharedMemorySize, SMEM_BYTES);
  }
  CUtensorMap tmGX, tmUX, tmGY, tmUY, tmD, tmWR, tmWI;
  const cuuint32_t es[5] = {1, 1, 1, 1, 1};
  auto enc = [&](CUtensorMap* m, void* p, int rank, const cuuint64_t* gd, const cuuint64_t* gs, const cuuint32_t* bd,
                 CUtensorMapSwizzle sw, CUtensorMapL2promotion pr) {
    encode(m, CU_TENSOR_MAP_DATA_TYPE_BFLOAT16, rank, p, gd, gs, bd, es, CU_TENSOR_MAP_INTERLEAVE_NONE, sw, pr,
           CU_TENSOR_MAP_FLOAT_OOB_FILL_NONE);
  };
  {
    const cuuint64_t gd[3] = {64, 512, 28}, gs[2] = {3584, 128};
    const cuuint32_t bd[3] = {64, 32, 2};
    enc(&tmGX, d_in[4], 3, gd, gs, bd, CU_TENSOR_MAP_SWIZZLE_128B, CU_TENSOR_MAP_L2_PROMOTION_L2_256B);
    enc(&tmUX, d_in[5], 3, gd, gs, bd, CU_TENSOR_MAP_SWIZZLE_128B, CU_TENSOR_MAP_L2_PROMOTION_L2_256B);
  }
  {
    const cuuint64_t gd[3] = {32, 512, 56}, gs[2] = {3584, 64};
    const cuuint32_t bd[3] = {32, 32, 3};
    enc(&tmGY, d_in[4], 3, gd, gs, bd, CU_TENSOR_MAP_SWIZZLE_64B, CU_TENSOR_MAP_L2_PROMOTION_L2_128B);
    enc(&tmUY, d_in[5], 3, gd, gs, bd, CU_TENSOR_MAP_SWIZZLE_64B, CU_TENSOR_MAP_L2_PROMOTION_L2_128B);
  }
  {
    const cuuint64_t gd[3] = {64, 1792, 8}, gs[2] = {1024, 128};
    const cuuint32_t bd[3] = {64, 64, 2};
    enc(&tmD, d_in[6], 3, gd, gs, bd, CU_TENSOR_MAP_SWIZZLE_128B, CU_TENSOR_MAP_L2_PROMOTION_L2_256B);
  }
  {
    const cuuint64_t gd[3] = {4112, 8, 16}, gs[2] = {16 * 8224, 8224};
    const cuuint32_t bd[3] = {40, 8, 16};
    enc(&tmWR, d_in[1], 3, gd, gs, bd, CU_TENSOR_MAP_SWIZZLE_NONE, CU_TENSOR_MAP_L2_PROMOTION_NONE);
    enc(&tmWI, d_in[2], 3, gd, gs, bd, CU_TENSOR_MAP_SWIZZLE_NONE, CU_TENSOR_MAP_L2_PROMOTION_NONE);
  }
  fused_kernel<<<NCTA, NTHREADS, SMEM_BYTES>>>((const __nv_bfloat16*)d_in[0], (const Tables*)tab, (Scratch*)scr,
                                               (__nv_bfloat16*)d_out, (const char*)d_in[4], (const char*)d_in[5],
                                               (const char*)d_in[6], tmWR, tmWI, tmGX, tmUX, tmGY, tmUY, tmD);
}
```

```cpp
#include <cuda_runtime.h>
#include <cuda_bf16.h>
#include <cuda.h>
#include <stdint.h>

namespace {

constexpr int NCTA = 128;
constexpr int NTHREADS = 384;
constexpr int SLOT = 16384;
constexpr int SMEM_BYTES = 14 * SLOT + 2048 + 1024;
constexpr int SPIN_LIMIT = 1 << 22;

struct Scratch {
  uint4 Z1[128 * 1024];
  uint4 Z2[128 * 1024];
  uint4 LN[16 * 8 * 1024];
  uint4 P[16 * 28 * 1024];
  uint4 ST[1024];
  unsigned cnt[64 * 32];
};
__device__ __align__(1024) Scratch g_scr;
#define PROF(i)
#define PROFP(i)
#define PROFG(i)

constexpr double ccos(int i, int n) {
  i &= n - 1;
  if (i > n / 2) i = n - i;
  if (4 * i == n) return 0.0;
  const bool neg = 4 * i > n;
  if (neg) i = n / 2 - i;
  const double a = 6.283185307179586476925 * i / n, a2 = a * a;
  double term = 1.0, sum = 1.0;
  for (int k = 1; k < 14; k++) { term *= -a2 / ((2 * k - 1) * (2 * k)); sum += term; }
  return neg ? -sum : sum;
}
constexpr double csin(int i, int n) { return ccos(i - n / 4, n); }
constexpr unsigned fbits(double v, int mant) {
  if (v == 0.0) return 0;
  const unsigned sg = v < 0 ? 1u : 0u;
  if (v < 0) v = -v;
  int e = 127;
  while (v < 1.0) { v *= 2.0; e--; }
  const unsigned m = (unsigned)((v - 1.0) * (double)(1u << mant) + 0.5);
  return (sg << (8 + mant)) + ((unsigned)e << mant) + m;
}
constexpr unsigned pkb(double lo, double hi) { return fbits(lo, 7) | (fbits(hi, 7) << 16); }
constexpr double fa_elem(int kp, int n1) {
  return kp <= 8 ? ccos(kp * n1, 16) : -csin((kp - 8) * n1, 16);
}
constexpr unsigned cfrag_c(int idx, int n, int ri) {
  return ri ? pkb(-csin(idx, n), ccos(idx, n)) : pkb(ccos(idx, n), csin(idx, n));
}
struct Tables {
  unsigned fb[16][32][4];
  unsigned tw1[8][32][4];
  unsigned fa[32][4];
  unsigned f2[8][4][32][4];
  unsigned g2[8][4][32][4];
  unsigned gb[16][32][4];
  unsigned tw3[4][32][4];
  unsigned ga[32][4];
  unsigned f8[32][4], g8[32][4];
};
constexpr int T1_BYTES = 12800, T2_BYTES = 44544;
static_assert(sizeof(Tables) == T1_BYTES + T2_BYTES, "table size");
constexpr Tables make_tables() {
  Tables T = {};
  for (int l = 0; l < 32; l++) {
    const int g = l >> 2, t = l & 3;
    for (int i = 0; i < 4; i++)
      for (int u = 0; u < 8; u++) {
        const int ri = g & 1, m = 2 * (g >> 1) + ((u & 3) >> 1);
        const double sg = u >= 4 ? -1.0 : 1.0;
        const int k2 = u >= 4 ? 31 - 2 * m - (u & 1) : 2 * m + (u & 1);
        const int pa = (8 * t + i) * k2, pb = (8 * t + 4 + i) * k2;
        T.fb[i * 4 + (u >> 1)][l][(u & 1) * 2 + 0] = ri == 0 ? pkb(ccos(pa, 32), ccos(pb, 32)) : pkb(-sg * csin(pa, 32), -sg * csin(pb, 32));
        T.fb[i * 4 + (u >> 1)][l][(u & 1) * 2 + 1] = ri == 0 ? pkb(csin(pa, 32), csin(pb, 32)) : pkb(sg * ccos(pa, 32), sg * ccos(pb, 32));
      }
    for (int i = 0; i < 4; i++)
      for (int ks = 0; ks < 4; ks++) {
        const int n2 = 4 * g + i, m = 2 * t + (ks & 1);
        const double sg = ks >= 2 ? -1.0 : 1.0;
        const int pa = n2 * (ks >= 2 ? 31 - 2 * m : 2 * m), pb = n2 * (ks >= 2 ? 30 - 2 * m : 2 * m + 1);
        T.gb[i * 4 + ks][l][0] = pkb(ccos(pa, 32), -sg * csin(pa, 32));
        T.gb[i * 4 + ks][l][1] = pkb(csin(pa, 32), sg * ccos(pa, 32));
        T.gb[i * 4 + ks][l][2] = pkb(ccos(pb, 32), -sg * csin(pb, 32));
        T.gb[i * 4 + ks][l][3] = pkb(csin(pb, 32), sg * ccos(pb, 32));
      }
    for (int i = 0; i < 4; i++) {
      for (int e = 0; e < 2; e++) {
        const int p = (8 * t + 4 * e + i) * (g == 0 ? 8 : g);
        T.tw1[2 * i + e][l][0] = fbits(g == 0 ? 0.0 : ccos(p, 512), 23);
        T.tw1[2 * i + e][l][1] = fbits(g == 0 ? ccos(p, 512) : csin(p, 512), 23);
        T.tw1[2 * i + e][l][2] = fbits(g == 0 ? 0.0 : -csin(p, 512), 23);
        T.tw1[2 * i + e][l][3] = fbits(g == 0 ? -csin(p, 512) : ccos(p, 512), 23);
      }
      const int ka = t == 0 ? 8 : 2 * t, kb = 2 * t + 1;
      T.tw3[i][l][0] = fbits(ccos((4 * g + i) * ka, 512), 23);
      T.tw3[i][l][1] = fbits(csin((4 * g + i) * ka, 512), 23);
      T.tw3[i][l][2] = fbits(ccos((4 * g + i) * kb, 512), 23);
      T.tw3[i][l][3] = fbits(csin((4 * g + i) * kb, 512), 23);
      const int p8 = (t + 4 * (i & 1)) * (4 * (i >> 1) + (g >> 1));
      T.f8[l][i] = cfrag_c(p8, 8, g & 1);
      T.g8[l][i] = cfrag_c(-p8, 8, g & 1);
    }
    for (int w = 0; w < 8; w++)
      for (int i = 0; i < 16; i++) {
        const int kidx = t + 4 * (i & 1) + 8 * (i >> 3), nidx = 4 * ((i >> 1) & 3) + (g >> 1);
        T.f2[w][i >> 2][l][i & 3] = cfrag_c((8 * kidx + w) * nidx, 128, g & 1);
        T.g2[w][i >> 2][l][i & 3] = cfrag_c(-(8 * nidx + w) * kidx, 128, g & 1);
      }
    T.fa[l][0] = pkb(fa_elem(g, 2 * t), fa_elem(g, 2 * t + 1));
    T.fa[l][1] = pkb(fa_elem(g + 8, 2 * t), fa_elem(g + 8, 2 * t + 1));
    T.fa[l][2] = pkb(fa_elem(g, 2 * t + 8), fa_elem(g, 2 * t + 9));
    T.fa[l][3] = pkb(fa_elem(g + 8, 2 * t + 8), fa_elem(g + 8, 2 * t + 9));
    T.ga[l][0] = pkb(fa_elem(2 * t, g), fa_elem(2 * t + 1, g));
    T.ga[l][1] = pkb(fa_elem(2 * t, g + 8), fa_elem(2 * t + 1, g + 8));
    T.ga[l][2] = pkb(fa_elem(2 * t + 8, g), fa_elem(2 * t + 9, g));
    T.ga[l][3] = pkb(fa_elem(2 * t + 8, g + 8), fa_elem(2 * t + 9, g + 8));
  }
  return T;
}
__device__ const __align__(128) Tables g_tab = make_tables();

__device__ __forceinline__ void die() { asm volatile("st.global.u32 [%0], %1;" ::"l"(0ull), "r"(0) : "memory"); }
__device__ __forceinline__ uint32_t s2u(const void* p) { return (uint32_t)__cvta_generic_to_shared(p); }
__device__ __forceinline__ void mbar_init(uint32_t b, int c) { asm volatile("mbarrier.init.shared::cta.b64 [%0], %1;" ::"r"(b), "r"(c)); }
__device__ __forceinline__ void mbar_expect(uint32_t b, int bytes) {
  asm volatile("mbarrier.arrive.expect_tx.shared::cta.b64 _, [%0], %1;" ::"r"(b), "r"(bytes) : "memory");
}
__device__ __forceinline__ void mbar_arrive(uint32_t b) { asm volatile("mbarrier.arrive.shared::cta.b64 _, [%0];" ::"r"(b) : "memory"); }
__device__ __forceinline__ uint32_t mbar_try(uint32_t b, uint32_t parity) {
  uint32_t ok;
  asm volatile("{.reg .pred p; mbarrier.try_wait.parity.shared::cta.b64 p, [%1], %2; selp.u32 %0,1,0,p;}"
               : "=r"(ok) : "r"(b), "r"(parity) : "memory");
  return ok;
}
__device__ __forceinline__ void mbar_wait(uint32_t b, uint32_t parity) {
  int it = 0;
#pragma unroll 1
  while (!mbar_try(b, parity))
    if (++it > SPIN_LIMIT) { die(); break; }
}
__device__ __forceinline__ void mbar_wait_cluster(uint32_t b, int parity) {
  uint32_t ok;
  int it = 0;
  do {
    asm volatile("{.reg .pred p; mbarrier.try_wait.parity.acquire.cluster.shared::cta.b64 p, [%1], %2; selp.u32 %0,1,0,p;}"
                 : "=r"(ok) : "r"(b), "r"(parity) : "memory");
    if (++it > SPIN_LIMIT) { die(); break; }
  } while (!ok);
}
__device__ __forceinline__ void bar_sync(int id, int n) { asm volatile("bar.sync %0, %1;" ::"r"(id), "r"(n) : "memory"); }
__device__ __forceinline__ void bar_arrive(int id, int n) { asm volatile("bar.arrive %0, %1;" ::"r"(id), "r"(n) : "memory"); }
__device__ __forceinline__ void red_release(unsigned* p) { asm volatile("red.release.gpu.global.add.u32 [%0], 1;" ::"l"(p) : "memory"); }
__device__ __forceinline__ void red_relaxed(unsigned* p) { asm volatile("red.relaxed.gpu.global.add.u32 [%0], 1;" ::"l"(p) : "memory"); }
__device__ __forceinline__ unsigned ld_acquire(const unsigned* p) {
  unsigned v;
  asm volatile("ld.acquire.gpu.global.u32 %0, [%1];" : "=r"(v) : "l"(p) : "memory");
  return v;
}
__device__ __forceinline__ unsigned ld_relaxed(const unsigned* p) {
  unsigned v;
  asm volatile("ld.relaxed.gpu.global.u32 %0, [%1];" : "=r"(v) : "l"(p) : "memory");
  return v;
}
__device__ __forceinline__ void wait_counter(const unsigned* p, unsigned target) {
  int it = 0;
  while ((int)(ld_acquire(p) - target) < 0)
    if (++it > SPIN_LIMIT) { die(); break; }
}
__device__ __forceinline__ void sts4(uint32_t a, uint32_t x, uint32_t y, uint32_t z, uint32_t w) {
  asm volatile("st.shared.v4.u32 [%0], {%1,%2,%3,%4};" ::"r"(a), "r"(x), "r"(y), "r"(z), "r"(w) : "memory");
}
__device__ __forceinline__ uint4 lds4(uint32_t a) {
  uint4 v;
  asm volatile("ld.shared.v4.u32 {%0,%1,%2,%3}, [%4];" : "=r"(v.x), "=r"(v.y), "=r"(v.z), "=r"(v.w) : "r"(a) : "memory");
  return v;
}
__device__ __forceinline__ uint32_t pack2(float lo, float hi) {
  uint32_t r;
  asm("cvt.rn.bf16x2.f32 %0, %1, %2;" : "=r"(r) : "f"(hi), "f"(lo));
  return r;
}
__device__ __forceinline__ float bf_lo(uint32_t v) { return __uint_as_float(v << 16); }
__device__ __forceinline__ float bf_hi(uint32_t v) { return __uint_as_float(v & 0xffff0000u); }
__device__ __forceinline__ uint32_t hadd2_bf16(uint32_t a, uint32_t b) {
  uint32_t r;
  asm("add.rn.bf16x2 %0, %1, %2;" : "=r"(r) : "r"(a), "r"(b));
  return r;
}
__device__ __forceinline__ void mma16816(float (&d)[4], uint32_t a0, uint32_t a1, uint32_t a2, uint32_t a3, uint32_t b0, uint32_t b1) {
  asm("mma.sync.aligned.m16n8k16.row.col.f32.bf16.bf16.f32 {%0,%1,%2,%3}, {%4,%5,%6,%7}, {%8,%9}, {%0,%1,%2,%3};"
      : "+f"(d[0]), "+f"(d[1]), "+f"(d[2]), "+f"(d[3])
      : "r"(a0), "r"(a1), "r"(a2), "r"(a3), "r"(b0), "r"(b1));
}
template <int N>
__device__ __forceinline__ void cs_frac(int idx, float& c, float& s) {
  int i = ((idx + N / 2) & (N - 1)) - N / 2;
  float a = (float)i * (6.283185307179586f / N);
  c = __cosf(a);
  s = __sinf(a);
}
template <int N>
__device__ __forceinline__ uint32_t cfrag(int idx, int ri) {
  float c, s;
  cs_frac<N>(idx, c, s);
  return ri ? pack2(-s, c) : pack2(c, s);
}
__device__ __forceinline__ uint32_t word(const uint4& v, int e) { return e == 0 ? v.x : e == 1 ? v.y : e == 2 ? v.z : v.w; }
__device__ __forceinline__ void cdft16(const uint4 (&q)[4], const uint4 (&F)[4], uint4 (&o)[4]) {
  float acc[2][4][4];
#pragma unroll
  for (int p = 0; p < 2; p++)
#pragma unroll
    for (int v = 0; v < 4; v++) {
      acc[p][v][0] = acc[p][v][1] = acc[p][v][2] = acc[p][v][3] = 0.f;
#pragma unroll
      for (int ks = 0; ks < 2; ks++)
        mma16816(acc[p][v], word(q[2 * ks], 2 * p), word(q[2 * ks], 2 * p + 1), word(q[2 * ks + 1], 2 * p),
                 word(q[2 * ks + 1], 2 * p + 1), word(F[ks * 2 + (v >> 1)], (v & 1) * 2), word(F[ks * 2 + (v >> 1)], (v & 1) * 2 + 1));
    }
#pragma unroll
  for (int v = 0; v < 4; v++)
    o[v] = make_uint4(pack2(acc[0][v][0], acc[0][v][1]), pack2(acc[0][v][2], acc[0][v][3]),
                      pack2(acc[1][v][0], acc[1][v][1]), pack2(acc[1][v][2], acc[1][v][3]));
}
__device__ __forceinline__ void st_tag(uint4* p, const uint4& v, uint32_t tag) {
  asm volatile("{.reg .b128 r; .reg .b64 a, b; mov.b64 a, {%1,%2}; mov.b64 b, {%3,%4}; mov.b128 r, {a,b}; st.relaxed.gpu.global.b128 [%0], r;}"
               ::"l"(p), "r"((v.x & ~1u) | tag), "r"(v.y), "r"(v.z), "r"(v.w) : "memory");
}
__device__ __forceinline__ uint4 ld_b128(const uint4* p) {
  uint4 v;
  asm volatile("{.reg .b128 r; .reg .b64 a, b; ld.relaxed.gpu.global.b128 r, [%4]; mov.b128 {a,b}, r; mov.b64 {%0,%1}, a; mov.b64 {%2,%3}, b;}"
               : "=r"(v.x), "=r"(v.y), "=r"(v.z), "=r"(v.w) : "l"(p) : "memory");
  return v;
}
template <int STRIDE>
__device__ __forceinline__ void ld_tag4_issue(uint4 (&q)[4], const uint4* p) {
#pragma unroll
  for (int i = 0; i < 4; i++) q[i] = ld_b128(p + i * STRIDE);
}
template <int STRIDE>
__device__ __forceinline__ void ld_tag4_finish(uint4 (&q)[4], const uint4* p, uint32_t tag) {
  int it = 0;
#pragma unroll 1
  while (__any_sync(0xffffffffu, ((q[0].x ^ tag) | (q[1].x ^ tag) | (q[2].x ^ tag) | (q[3].x ^ tag)) & 1u)) {
    ld_tag4_issue<STRIDE>(q, p);
    if (++it > SPIN_LIMIT) { die(); break; }
  }
#pragma unroll
  for (int i = 0; i < 4; i++) asm volatile("and.b32 %0, %0, 0xfffffffe;" : "+r"(q[i].x));
}
__device__ __forceinline__ void row_stats(const uint32_t (&a)[8], const uint32_t (&b)[8], int lane, float (&sum)[2], float (&sq)[2]) {
  float da[4] = {0.f, 0.f, 0.f, 0.f}, db[4] = {0.f, 0.f, 0.f, 0.f}, ds[4] = {0.f, 0.f, 0.f, 0.f};
#pragma unroll
  for (int q = 0; q < 4; q++) {
    mma16816(ds, a[2 * q], b[2 * q], a[2 * q + 1], b[2 * q + 1], 0x3f803f80u, 0x3f803f80u);
    mma16816(da, a[2 * q], b[2 * q], a[2 * q + 1], b[2 * q + 1], a[2 * q], a[2 * q + 1]);
    mma16816(db, a[2 * q], b[2 * q], a[2 * q + 1], b[2 * q + 1], b[2 * q], b[2 * q + 1]);
  }
  const int src = (lane & 28) | (lane >> 3);
  const float qa = __shfl_sync(0xffffffffu, (lane & 4) ? da[1] : da[0], src);
  const float qb = __shfl_sync(0xffffffffu, (lane & 4) ? db[3] : db[2], src);
  float v = (lane & 2) ? ((lane & 1) ? ds[2] : ds[0]) : ((lane & 1) ? qb : qa);
  v += __shfl_xor_sync(0xffffffffu, v, 4);
  v += __shfl_xor_sync(0xffffffffu, v, 8);
  v += __shfl_xor_sync(0xffffffffu, v, 16);
  sq[0] = __shfl_sync(0xffffffffu, v, 0);
  sq[1] = __shfl_sync(0xffffffffu, v, 1);
  sum[0] = __shfl_sync(0xffffffffu, v, 2);
  sum[1] = __shfl_sync(0xffffffffu, v, 3);
}
__device__ __forceinline__ uint64_t desc64(uint32_t lo, uint32_t hi) {
  uint64_t d;
  asm("mov.b64 %0, {%1, %2};" : "=l"(d) : "r"(lo), "r"(hi));
  return d;
}
constexpr uint32_t desc_hi(uint32_t sbo, uint32_t swz) { return (sbo >> 4) | (swz << 30); }
__device__ __forceinline__ uint32_t desc_lo(uint32_t addr, uint32_t lbo) { return ((addr & 0x3FFFF) >> 4) | ((lbo >> 4) << 16); }
__device__ __forceinline__ void cp_async16(uint32_t dst, const void* src) {
  asm volatile("cp.async.cg.shared.global [%0], [%1], 16;" ::"r"(dst), "l"(src) : "memory");
}
__device__ __forceinline__ uint2 lds2(uint32_t a) {
  uint2 v;
  asm volatile("ld.shared.v2.u32 {%0,%1}, [%2];" : "=r"(v.x), "=r"(v.y) : "r"(a) : "memory");
  return v;
}
__device__ __forceinline__ uint32_t lds_u16(uint32_t a) {
  uint16_t v;
  asm volatile("ld.shared.u16 %0, [%1];" : "=h"(v) : "r"(a) : "memory");
  return v;
}
__device__ __forceinline__ void wg_fence() { asm volatile("wgmma.fence.sync.aligned;" ::: "memory"); }
__device__ __forceinline__ void wg_commit() { asm volatile("wgmma.commit_group.sync.aligned;" ::: "memory"); }
template <int N>
__device__ __forceinline__ void wg_wait() { asm volatile("wgmma.wait_group.sync.aligned %0;" ::"n"(N) : "memory"); }
__device__ __forceinline__ void bulk_load(uint32_t dst, const void* src, int bytes, uint32_t bar) {
  asm volatile("cp.async.bulk.shared::cluster.global.mbarrier::complete_tx::bytes [%0], [%1], %2, [%3];"
               ::"r"(dst), "l"(src), "r"(bytes), "r"(bar) : "memory");
}
__device__ __forceinline__ void tma3(uint32_t dst, const CUtensorMap* tm, uint32_t bar, int c0, int c1, int c2) {
  asm volatile("cp.async.bulk.tensor.3d.shared::cluster.global.mbarrier::complete_tx::bytes [%0], [%1, {%3,%4,%5}], [%2];"
               ::"r"(dst), "l"(tm), "r"(bar), "r"(c0), "r"(c1), "r"(c2) : "memory");
}
__device__ __forceinline__ void tma3_mc(uint32_t dst, const CUtensorMap* tm, uint32_t bar, int c1, int c2) {
  asm volatile("cp.async.bulk.tensor.3d.shared::cluster.global.mbarrier::complete_tx::bytes.multicast::cluster [%0], [%1, {%3,%4,%5}], [%2], %6;"
               ::"r"(dst), "l"(tm), "r"(bar), "r"(0), "r"(c1), "r"(c2), "h"((uint16_t)3) : "memory");
}
__device__ __forceinline__ void mbar_arrive_remote(uint32_t rb) {
  asm volatile("mbarrier.arrive.shared::cluster.b64 _, [%0];" ::"r"(rb) : "memory");
}
__device__ __forceinline__ uint4 ldg_ca4(const void* p) {
  uint4 v;
  asm volatile("ld.global.ca.v4.u32 {%0,%1,%2,%3}, [%4];" : "=r"(v.x), "=r"(v.y), "=r"(v.z), "=r"(v.w) : "l"(p) : "memory");
  return v;
}
__device__ __forceinline__ uint32_t clock32() {
  uint32_t v;
  asm volatile("mov.u32 %0, %%clock;" : "=r"(v) :: "memory");
  return v;
}
__device__ __forceinline__ float swiglu(float g, float u, float r) {
  float hg = (0.5f * r) * g, th;
  asm("tanh.approx.f32 %0, %1;" : "=f"(th) : "f"(hg));
  return fmaf(hg, th, hg) * (r * u);
}
__device__ __forceinline__ uint32_t hsub2_bf16(uint32_t a, uint32_t b) {
  uint32_t r;
  asm("sub.rn.bf16x2 %0, %1, %2;" : "=r"(r) : "r"(a), "r"(b));
  return r;
}
__device__ __forceinline__ void l2_prefetch(const void* p, int bytes) {
  asm volatile("cp.async.bulk.prefetch.L2.global [%0], %1;" ::"l"(p), "r"(bytes) : "memory");
}

__device__ __forceinline__ void wgmma_n256(float (&d)[128], uint64_t da, uint64_t db) {
  asm volatile("wgmma.mma_async.sync.aligned.m64n256k16.f32.bf16.bf16 {"
      "%0,%1,%2,%3,%4,%5,%6,%7,%8,%9,%10,%11,%12,%13,%14,%15,"
      "%16,%17,%18,%19,%20,%21,%22,%23,%24,%25,%26,%27,%28,%29,%30,%31,"
      "%32,%33,%34,%35,%36,%37,%38,%39,%40,%41,%42,%43,%44,%45,%46,%47,"
      "%48,%49,%50,%51,%52,%53,%54,%55,%56,%57,%58,%59,%60,%61,%62,%63,"
      "%64,%65,%66,%67,%68,%69,%70,%71,%72,%73,%74,%75,%76,%77,%78,%79,"
      "%80,%81,%82,%83,%84,%85,%86,%87,%88,%89,%90,%91,%92,%93,%94,%95,"
      "%96,%97,%98,%99,%100,%101,%102,%103,%104,%105,%106,%107,%108,%109,%110,%111,"
      "%112,%113,%114,%115,%116,%117,%118,%119,%120,%121,%122,%123,%124,%125,%126,%127"
      "}, %128, %129, 1, 1, 1, 0, 1;\n"
      : "+f"(d[0]),"+f"(d[1]),"+f"(d[2]),"+f"(d[3]),"+f"(d[4]),"+f"(d[5]),"+f"(d[6]),"+f"(d[7]),
        "+f"(d[8]),"+f"(d[9]),"+f"(d[10]),"+f"(d[11]),"+f"(d[12]),"+f"(d[13]),"+f"(d[14]),"+f"(d[15]),
        "+f"(d[16]),"+f"(d[17]),"+f"(d[18]),"+f"(d[19]),"+f"(d[20]),"+f"(d[21]),"+f"(d[22]),"+f"(d[23]),
        "+f"(d[24]),"+f"(d[25]),"+f"(d[26]),"+f"(d[27]),"+f"(d[28]),"+f"(d[29]),"+f"(d[30]),"+f"(d[31]),
        "+f"(d[32]),"+f"(d[33]),"+f"(d[34]),"+f"(d[35]),"+f"(d[36]),"+f"(d[37]),"+f"(d[38]),"+f"(d[39]),
        "+f"(d[40]),"+f"(d[41]),"+f"(d[42]),"+f"(d[43]),"+f"(d[44]),"+f"(d[45]),"+f"(d[46]),"+f"(d[47]),
        "+f"(d[48]),"+f"(d[49]),"+f"(d[50]),"+f"(d[51]),"+f"(d[52]),"+f"(d[53]),"+f"(d[54]),"+f"(d[55]),
        "+f"(d[56]),"+f"(d[57]),"+f"(d[58]),"+f"(d[59]),"+f"(d[60]),"+f"(d[61]),"+f"(d[62]),"+f"(d[63]),
        "+f"(d[64]),"+f"(d[65]),"+f"(d[66]),"+f"(d[67]),"+f"(d[68]),"+f"(d[69]),"+f"(d[70]),"+f"(d[71]),
        "+f"(d[72]),"+f"(d[73]),"+f"(d[74]),"+f"(d[75]),"+f"(d[76]),"+f"(d[77]),"+f"(d[78]),"+f"(d[79]),
        "+f"(d[80]),"+f"(d[81]),"+f"(d[82]),"+f"(d[83]),"+f"(d[84]),"+f"(d[85]),"+f"(d[86]),"+f"(d[87]),
        "+f"(d[88]),"+f"(d[89]),"+f"(d[90]),"+f"(d[91]),"+f"(d[92]),"+f"(d[93]),"+f"(d[94]),"+f"(d[95]),
        "+f"(d[96]),"+f"(d[97]),"+f"(d[98]),"+f"(d[99]),"+f"(d[100]),"+f"(d[101]),"+f"(d[102]),"+f"(d[103]),
        "+f"(d[104]),"+f"(d[105]),"+f"(d[106]),"+f"(d[107]),"+f"(d[108]),"+f"(d[109]),"+f"(d[110]),"+f"(d[111]),
        "+f"(d[112]),"+f"(d[113]),"+f"(d[114]),"+f"(d[115]),"+f"(d[116]),"+f"(d[117]),"+f"(d[118]),"+f"(d[119]),
        "+f"(d[120]),"+f"(d[121]),"+f"(d[122]),"+f"(d[123]),"+f"(d[124]),"+f"(d[125]),"+f"(d[126]),"+f"(d[127])
      : "l"(da), "l"(db));
}
__device__ __forceinline__ void wgmma_n192(float (&d)[96], uint64_t da, uint64_t db) {
  asm volatile("wgmma.mma_async.sync.aligned.m64n192k16.f32.bf16.bf16 {"
      "%0,%1,%2,%3,%4,%5,%6,%7,%8,%9,%10,%11,%12,%13,%14,%15,"
      "%16,%17,%18,%19,%20,%21,%22,%23,%24,%25,%26,%27,%28,%29,%30,%31,"
      "%32,%33,%34,%35,%36,%37,%38,%39,%40,%41,%42,%43,%44,%45,%46,%47,"
      "%48,%49,%50,%51,%52,%53,%54,%55,%56,%57,%58,%59,%60,%61,%62,%63,"
      "%64,%65,%66,%67,%68,%69,%70,%71,%72,%73,%74,%75,%76,%77,%78,%79,"
      "%80,%81,%82,%83,%84,%85,%86,%87,%88,%89,%90,%91,%92,%93,%94,%95"
      "}, %96, %97, 1, 1, 1, 0, 1;\n"
      : "+f"(d[0]),"+f"(d[1]),"+f"(d[2]),"+f"(d[3]),"+f"(d[4]),"+f"(d[5]),"+f"(d[6]),"+f"(d[7]),
        "+f"(d[8]),"+f"(d[9]),"+f"(d[10]),"+f"(d[11]),"+f"(d[12]),"+f"(d[13]),"+f"(d[14]),"+f"(d[15]),
        "+f"(d[16]),"+f"(d[17]),"+f"(d[18]),"+f"(d[19]),"+f"(d[20]),"+f"(d[21]),"+f"(d[22]),"+f"(d[23]),
        "+f"(d[24]),"+f"(d[25]),"+f"(d[26]),"+f"(d[27]),"+f"(d[28]),"+f"(d[29]),"+f"(d[30]),"+f"(d[31]),
        "+f"(d[32]),"+f"(d[33]),"+f"(d[34]),"+f"(d[35]),"+f"(d[36]),"+f"(d[37]),"+f"(d[38]),"+f"(d[39]),
        "+f"(d[40]),"+f"(d[41]),"+f"(d[42]),"+f"(d[43]),"+f"(d[44]),"+f"(d[45]),"+f"(d[46]),"+f"(d[47]),
        "+f"(d[48]),"+f"(d[49]),"+f"(d[50]),"+f"(d[51]),"+f"(d[52]),"+f"(d[53]),"+f"(d[54]),"+f"(d[55]),
        "+f"(d[56]),"+f"(d[57]),"+f"(d[58]),"+f"(d[59]),"+f"(d[60]),"+f"(d[61]),"+f"(d[62]),"+f"(d[63]),
        "+f"(d[64]),"+f"(d[65]),"+f"(d[66]),"+f"(d[67]),"+f"(d[68]),"+f"(d[69]),"+f"(d[70]),"+f"(d[71]),
        "+f"(d[72]),"+f"(d[73]),"+f"(d[74]),"+f"(d[75]),"+f"(d[76]),"+f"(d[77]),"+f"(d[78]),"+f"(d[79]),
        "+f"(d[80]),"+f"(d[81]),"+f"(d[82]),"+f"(d[83]),"+f"(d[84]),"+f"(d[85]),"+f"(d[86]),"+f"(d[87]),
        "+f"(d[88]),"+f"(d[89]),"+f"(d[90]),"+f"(d[91]),"+f"(d[92]),"+f"(d[93]),"+f"(d[94]),"+f"(d[95])
      : "l"(da), "l"(db));
}
__device__ __forceinline__ void wgmma_rs_n128(float (&d)[64], uint32_t a0, uint32_t a1, uint32_t a2, uint32_t a3, uint64_t db) {
  asm volatile("wgmma.mma_async.sync.aligned.m64n128k16.f32.bf16.bf16 {"
      "%0,%1,%2,%3,%4,%5,%6,%7,%8,%9,%10,%11,%12,%13,%14,%15,"
      "%16,%17,%18,%19,%20,%21,%22,%23,%24,%25,%26,%27,%28,%29,%30,%31,"
      "%32,%33,%34,%35,%36,%37,%38,%39,%40,%41,%42,%43,%44,%45,%46,%47,"
      "%48,%49,%50,%51,%52,%53,%54,%55,%56,%57,%58,%59,%60,%61,%62,%63"
      "}, {%64,%65,%66,%67}, %68, 1, 1, 1, 1;\n"
      : "+f"(d[0]),"+f"(d[1]),"+f"(d[2]),"+f"(d[3]),"+f"(d[4]),"+f"(d[5]),"+f"(d[6]),"+f"(d[7]),
        "+f"(d[8]),"+f"(d[9]),"+f"(d[10]),"+f"(d[11]),"+f"(d[12]),"+f"(d[13]),"+f"(d[14]),"+f"(d[15]),
        "+f"(d[16]),"+f"(d[17]),"+f"(d[18]),"+f"(d[19]),"+f"(d[20]),"+f"(d[21]),"+f"(d[22]),"+f"(d[23]),
        "+f"(d[24]),"+f"(d[25]),"+f"(d[26]),"+f"(d[27]),"+f"(d[28]),"+f"(d[29]),"+f"(d[30]),"+f"(d[31]),
        "+f"(d[32]),"+f"(d[33]),"+f"(d[34]),"+f"(d[35]),"+f"(d[36]),"+f"(d[37]),"+f"(d[38]),"+f"(d[39]),
        "+f"(d[40]),"+f"(d[41]),"+f"(d[42]),"+f"(d[43]),"+f"(d[44]),"+f"(d[45]),"+f"(d[46]),"+f"(d[47]),
        "+f"(d[48]),"+f"(d[49]),"+f"(d[50]),"+f"(d[51]),"+f"(d[52]),"+f"(d[53]),"+f"(d[54]),"+f"(d[55]),
        "+f"(d[56]),"+f"(d[57]),"+f"(d[58]),"+f"(d[59]),"+f"(d[60]),"+f"(d[61]),"+f"(d[62]),"+f"(d[63])
      : "r"(a0), "r"(a1), "r"(a2), "r"(a3), "l"(db));
}

constexpr int C_LN = 0, C_PX = 16, C_PY = 32;
constexpr int NB_CONS = 1, NB_LN = 2, NB_LAG = 4, NB_INIT = 6, NB_RDY = 7;
#define LAGX 3
#define LAGY 3
#define LAG2 2
#define NLL 2
#define POLL_DELAY3 900
#define POLL_DELAY 900
#define FILT_DELAY 1000
#define RING_SIG 0
#define PF2_SIG 1
constexpr int SM_E = 0, SM_X = 16384, SM_E2 = 32768, SM_W = 49152, SM_FC = 69632, SM_T = 73728 - T1_BYTES;
constexpr unsigned long long KORDER = 0xBA9432DC876510ull;
constexpr uint32_t HI128 = desc_hi(1024, 1), HI64 = desc_hi(512, 2);

struct Bars {
  uint64_t full1[6], empty1[6], fullA[8], full2[14], empty2[8], xbar, xfree, hbar, tbar, sbar, sig[2], hint[3];
  uint32_t epoch;
};

template <int NK, bool STORE>
__device__ __forceinline__ void make_p(const float (&acc)[NK * 16], float r0, float r1, uint4 (&p)[NK], uint4* pbase, int ks0, uint32_t tag) {
#pragma unroll
  for (int j = 0; j < NK; j++) {
    uint32_t w[4];
#pragma unroll
    for (int i = 0; i < 4; i++) {
      const int a = 8 * j + 2 * i, b = a + NK * 8;
      w[i] = pack2(swiglu(acc[a], acc[b], (i & 1) ? r1 : r0), swiglu(acc[a + 1], acc[b + 1], (i & 1) ? r1 : r0));
    }
    asm volatile("" : "+r"(w[0]), "+r"(w[1]), "+r"(w[2]), "+r"(w[3]));
    p[j] = make_uint4(w[0], w[1], w[2], w[3]);
    if (STORE) st_tag(pbase + ((ks0 + j) >> 2) * 1024 + ((ks0 + j) & 3) * 32, p[j], tag);
  }
}
__device__ __forceinline__ void spin_cycles(uint32_t n) {
  const uint32_t t0 = clock32();
  while (clock32() - t0 < n) {}
}

__global__ void __cluster_dims__(2, 1, 1) __launch_bounds__(NTHREADS, 1)
fused_kernel(const __nv_bfloat16* __restrict__ x, const Tables* __restrict__ tab, Scratch* __restrict__ scr,
             __nv_bfloat16* __restrict__ out, const char* __restrict__ wg_raw, const char* __restrict__ wu_raw,
             const char* __restrict__ wd_raw,
             const __grid_constant__ CUtensorMap tmWR, const __grid_constant__ CUtensorMap tmWI,
             const __grid_constant__ CUtensorMap tmGX, const __grid_constant__ CUtensorMap tmUX,
             const __grid_constant__ CUtensorMap tmGY, const __grid_constant__ CUtensorMap tmUY,
             const __grid_constant__ CUtensorMap tmD) {
  extern __shared__ __align__(1024) char smem_raw[];
  const uint32_t sbase = (s2u(smem_raw) + 1023) & ~1023u;
  const uint32_t sbar = sbase + 14 * SLOT, sstat = sbar + 512;
  const int tid = threadIdx.x, lane = tid & 31;
  const int c = blockIdx.x, kh = c & 1, f = (c >> 1) & 7, rb = 2 * (c >> 4) + kh, rb2 = 2 * (c >> 4) + (f >> 2), nq = f & 3;
#define BAR(field, i) (sbar + (uint32_t)offsetof(Bars, field) + 8u * (i))
#define TOFF(field) (sbase + SM_T + (uint32_t)offsetof(Tables, field) + lane * 16)

  if (tid >= 256) {
    asm volatile("setmaxnreg.dec.sync.aligned.u32 56;");
    const int warp = __shfl_sync(0xffffffffu, tid >> 5, 0);
    if (tid == 256) {
      for (int i = 0; i < 6; i++) { mbar_init(BAR(full1, i), 1); mbar_init(BAR(empty1, i), 16); }
      for (int i = 0; i < 8; i++) { mbar_init(BAR(fullA, i), 1); mbar_init(BAR(empty2, i), 8); }
      for (int i = 0; i < 14; i++) mbar_init(BAR(full2, i), 2);
      mbar_init(BAR(xbar, 0), 1);
      mbar_init(BAR(xfree, 0), 8);
      mbar_init(BAR(tbar, 0), 1);
      mbar_init(BAR(hbar, 0), 1);
      mbar_init(BAR(sbar, 0), 32);
      for (int i = 0; i < 3; i++) mbar_init(BAR(hint, i), 1);
      mbar_init(BAR(sig, 0), 8);
      mbar_init(BAR(sig, 1), 8);
      mbar_expect(BAR(xbar, 0), 16384);
      asm volatile("fence.mbarrier_init.release.cluster;" ::: "memory");
      const int w0 = ((c >> 3) * 257 + 32 * (c & 7) + 1) & ~7;
      if (FILT_DELAY) {
        asm volatile("prefetch.tensormap [%0];" ::"l"(&tmWR) : "memory");
        asm volatile("prefetch.tensormap [%0];" ::"l"(&tmWI) : "memory");
        spin_cycles(FILT_DELAY);
      }
      mbar_expect(BAR(tbar, 0), T2_BYTES + 2 * 10240);
      tma3(sbase + SM_W, &tmWR, BAR(tbar, 0), w0, 0, 0);
      tma3(sbase + SM_W + 10240, &tmWI, BAR(tbar, 0), w0, 0, 0);
      bulk_load(sbase + SM_T + T1_BYTES, reinterpret_cast<const char*>(tab) + T1_BYTES, T2_BYTES, BAR(tbar, 0));
    }
    if (tid == 288) {
      asm volatile("prefetch.tensormap [%0];" ::"l"(kh ? &tmUX : &tmGX) : "memory");
      asm volatile("prefetch.tensormap [%0];" ::"l"(kh ? &tmUY : &tmGY) : "memory");
      asm volatile("prefetch.tensormap [%0];" ::"l"(&tmD) : "memory");
    }
    if (tid == 320) {
      const unsigned e = ld_relaxed(&scr->cnt[(C_LN + rb) * 32]) >> 3;
      asm volatile("st.shared.u32 [%0], %1;" ::"r"(BAR(epoch, 0)), "r"(e) : "memory");
    }
    __syncwarp();
    asm volatile("barrier.cluster.arrive.relaxed.aligned;" ::: "memory");
    bar_arrive(NB_RDY, 384);
    asm volatile("barrier.cluster.wait.aligned;" ::: "memory");
    bar_sync(NB_INIT, 384);
    unsigned epoch;
    asm volatile("ld.shared.u32 %0, [%1];" : "=r"(epoch) : "r"(BAR(epoch, 0)) : "memory");
    if (warp == 8) {
      if (lane == 0) {
        const int ax = (7 * f + 3 * (f & 1)) >> 1;
        const int ay = 7 * f + ((f & 1) ? 0 : 4);
        const CUtensorMap* tx = kh ? &tmUX : &tmGX;
        const CUtensorMap* ty = kh ? &tmUY : &tmGY;
        uint32_t s = 0, ph = 1;
        if (RING_SIG >= 0) mbar_wait(BAR(sig, RING_SIG), 0);
#pragma unroll 1
        for (int n = 0; n < 32; n++) {
          const uint32_t dst = sbase + (8 + s) * SLOT, fb = BAR(full1, s);
          mbar_wait(BAR(empty1, s), ph);
          if (n < 16) {
            mbar_expect(fb, 16384);
            tma3_mc(dst + kh * 8192, tx, fb, n * 32, ax);
          } else {
            mbar_expect(fb, 12288);
            tma3_mc(dst + kh * 6144, ty, fb, (n - 16) * 32, ay);
          }
          if (++s == 6) { s = 0; ph ^= 1; }
        }
      }
    } else if (warp == 9) {
      if (lane == 0) {
        mbar_wait(BAR(empty1, 5), 0);
        mbar_wait(BAR(empty1, 5), 1);
#pragma unroll 1
        for (int i = 0; i < 14; i++) {
          const int kblk = 14 * kh + (int)((KORDER >> (4 * i)) & 15);
          if (i < 8) mbar_wait(BAR(empty1, (17 + 2 * i) % 6), ((17 + 2 * i) / 6) & 1);
          else mbar_wait(BAR(empty2, i - 8), 0);
          mbar_expect(BAR(full2, i), 16384);
          tma3(sbase + (i & 7) * SLOT, &tmD, BAR(full2, i), 0, 64 * kblk, 2 * nq);
        }
        wait_counter(&scr->cnt[(C_LN + rb2) * 32], (epoch + 1) * 8);
        asm volatile("fence.proxy.async.global;" ::: "memory");
        mbar_wait(BAR(empty2, 7), 0);
        mbar_expect(BAR(hbar, 0), 16384);
        bulk_load(sbase + 7 * SLOT, &scr->LN[(rb2 * 8 + 2 * nq) * 1024 + kh * 512], 8192, BAR(hbar, 0));
        bulk_load(sbase + 7 * SLOT + 8192, &scr->LN[(rb2 * 8 + 2 * nq + 1) * 1024 + kh * 512], 8192, BAR(hbar, 0));
      }
    } else if (warp == 10) {
      bar_sync(NB_LN, 288);
      if (lane == 0) {
        PROFP(0);
        red_release(&scr->cnt[(C_LN + rb) * 32]);
        PROFP(1);
        wait_counter(&scr->cnt[(C_LN + rb) * 32], (epoch + 1) * 8);
        asm volatile("fence.proxy.async.global;" ::: "memory");
        PROFP(2);
#pragma unroll 1
        for (int kb = NLL; kb < 8; kb++) {
          mbar_expect(BAR(fullA, kb), 16384);
          bulk_load(sbase + kb * SLOT, &scr->LN[(rb * 8 + kb) * 1024], 16384, BAR(fullA, kb));
        }
#pragma unroll 1
        for (int i = 0; i < 4; i++) mbar_wait(BAR(empty1, 2), i & 1);
        uint32_t d = 2;
#pragma unroll 1
        for (int s = 0; s < 14; s++) {
          const int kblk = 14 * kh + (int)((KORDER >> (4 * s)) & 15);
          if (s == 0 || s == 8 || s == 11) {
            if (s != 11) PROFP(3 + (s >> 2));
            mbar_wait(BAR(hint, s == 0 ? 0 : s == 8 ? 1 : 2), 0);
            if (s != 11) PROFP(4 + (s >> 2));
          }
          if (s < 6) mbar_wait(BAR(empty1, d), s < 4 ? 0 : 1);
          else mbar_wait(BAR(empty2, s - 6), 0);
          mbar_expect(BAR(full2, s), 16384);
          bulk_load(sbase + (8 + d) * SLOT, &scr->P[(rb2 * 28 + kblk) * 1024], 16384, BAR(full2, s));
          if (++d == 6) d = 0;
        }
        PROFP(7);
      }
    } else {
      if (lane == 0) {
        l2_prefetch(wg_raw + (size_t)c * 5376, 5376);
        l2_prefetch(wu_raw + (size_t)c * 5376, 5376);
        mbar_wait(BAR(sig, PF2_SIG), 0);
        l2_prefetch(wg_raw + 688128 + (size_t)c * 8960, 8960);
        l2_prefetch(wu_raw + 688128 + (size_t)c * 8960, 8960);
      }
      mbar_wait(BAR(fullA, 7), 0);
      if (lane == 0) l2_prefetch(wd_raw + (size_t)c * 14336, 14336);
      {
        const uint32_t tag = (epoch + 1) & 1;
        uint4 v0, v1, v2;
        int it = 0;
        while (true) {
          v0 = ld_b128(&scr->ST[rb * 64 + lane]);
          v1 = ld_b128(&scr->ST[rb * 64 + 32 + lane]);
          v2 = ld_b128(&scr->ST[rb2 * 64 + 32 * kh + lane]);
          if (!__any_sync(0xffffffffu, ((v0.x ^ tag) | (v1.x ^ tag) | (v2.x ^ tag)) & 1u)) break;
          if (++it > SPIN_LIMIT) { die(); break; }
        }
        sts4(sstat + lane * 16, v0.x & ~1u, v0.y, v0.z, v0.w);
        sts4(sstat + 512 + lane * 16, v1.x & ~1u, v1.y, v1.z, v1.w);
        sts4(sstat + 1024 + lane * 16, v2.x & ~1u, v2.y, v2.z, v2.w);
        mbar_arrive(BAR(sbar, 0));
      }
      if (lane == 0) {
        mbar_wait(BAR(empty1, 5), 0);
        mbar_wait(BAR(empty1, 5), 1);
        mbar_wait(BAR(empty1, 5), 0);
#pragma unroll 1
        for (int e = 0; e < 3; e++) {
          const unsigned* cp = e == 0 ? &scr->cnt[(C_PX + rb2) * 32] : &scr->cnt[(C_PY + rb2) * 32 + 2 * kh + e - 1];
          if (e == 1) mbar_wait(BAR(full2, 0), 0);
          int it = 0;
          while ((int)(ld_relaxed(cp) - (epoch + 1) * (e == 0 ? 64 : 16)) < 0)
            if (++it > SPIN_LIMIT) { die(); break; }
          mbar_arrive(BAR(hint, e));
        }
      }
    }
  } else {
    const int warp = __shfl_sync(0xffffffffu, tid >> 5, 0);
    const int g = lane >> 2, t = lane & 3;
    PROF(0);
    PROFG(14);
#pragma unroll
    for (int i = 0; i < 4; i++) {
      const int r = i >> 1, ch = (i & 1) * 32 + lane;
      cp_async16(sbase + SM_X + (2 * warp + r) * 1024 + ((ch ^ ((ch >> 2) & 6)) * 16),
                 x + (size_t)(c + 128 * (2 * warp + r)) * 512 + ch * 8);
    }
    asm volatile("cp.async.commit_group;" ::: "memory");
    asm volatile("barrier.cluster.arrive.relaxed.aligned;" ::: "memory");
    uint4 tw[8], fb[16];
    const uint4 fa = ldg_ca4(&tab->fa[lane][0]);
#pragma unroll
    for (int i = 0; i < 8; i++) tw[i] = ldg_ca4(&tab->tw1[i][lane][0]);
#pragma unroll
    for (int i = 0; i < 16; i++) fb[i] = ldg_ca4(&tab->fb[i][lane][0]);
    uint32_t rbar;
    asm volatile("mapa.shared::cluster.u32 %0, %1, %2;" : "=r"(rbar) : "r"(sbar), "r"(kh ^ 1));
#define RBAR(field, i) (rbar + (uint32_t)offsetof(Bars, field) + 8u * (i))
    {
      const int ln = (tid >> 1) & 31, lg = ln >> 2, lt = ln & 3, i = 4 * (tid >> 6) + 2 * (tid & 1);
      const int kidx = lt + 8 * (i >> 3), nidx = 4 * ((i >> 1) & 3) + (lg >> 1);
      const uint32_t a0 = cfrag<2048>((c + 128 * kidx) * nidx, lg & 1), a1 = cfrag<2048>((c + 128 * (kidx + 4)) * nidx, lg & 1);
      const uint32_t b0 = cfrag<2048>(-(c + 128 * nidx) * kidx, lg & 1), b1 = cfrag<2048>(-(c + 128 * nidx) * (kidx + 4), lg & 1);
      asm volatile("st.shared.v2.u32 [%0], {%1,%2};" ::"r"(sbase + SM_FC + tid * 8), "r"(a0), "r"(a1) : "memory");
      asm volatile("st.shared.v2.u32 [%0], {%1,%2};" ::"r"(sbase + SM_FC + 2048 + tid * 8), "r"(b0), "r"(b1) : "memory");
    }
    asm volatile("cp.async.wait_group 0;" ::: "memory");
    __syncwarp();
    bar_arrive(NB_INIT, 384);
    PROF(13);
    uint32_t tag;
    uint4 q[4], o[4];
    {
      uint32_t v[2][8];
#pragma unroll
      for (int r = 0; r < 2; r++)
#pragma unroll
        for (int q = 0; q < 4; q++) {
          const uint2 u = lds2(sbase + SM_X + (2 * warp + r) * 1024 + (t + 4 * (q >> 1)) * 128 + (((4 * (q & 1) + (g >> 1)) ^ (2 * t)) * 16) + (g & 1) * 8);
          v[r][2 * q] = u.x; v[r][2 * q + 1] = u.y;
        }
      float sum[2], sq[2], rstd[2];
      row_stats(v[0], v[1], lane, sum, sq);
#pragma unroll
      for (int r = 0; r < 2; r++) {
        const float m = sum[r] * (1.f / 512.f);
        rstd[r] = rsqrtf(fmaxf(fmaf(-m, m, sq[r] * (1.f / 512.f)), 0.f) + 1e-5f);
      }
      uint32_t alo[4][4], ahi[4][4];
#pragma unroll
      for (int r = 0; r < 2; r++)
#pragma unroll
        for (int i = 0; i < 4; i++) {
          const uint32_t sel = (i & 1) ? 0x7632u : 0x5410u;
          const uint32_t b0 = __byte_perm(v[r][i >> 1], v[r][2 + (i >> 1)], sel);
          const uint32_t b1 = __byte_perm(v[r][4 + (i >> 1)], v[r][6 + (i >> 1)], sel);
          float d[4] = {0.f, 0.f, 0.f, 0.f};
          mma16816(d, fa.x, fa.y, fa.z, fa.w, b0, b1);
          const uint4 &ka = tw[2 * i], &kb = tw[2 * i + 1];
          const uint32_t re = pack2(d[0] * __uint_as_float(ka.x) + d[2] * __uint_as_float(ka.y), d[1] * __uint_as_float(kb.x) + d[3] * __uint_as_float(kb.y));
          const uint32_t im = pack2(d[0] * __uint_as_float(ka.z) + d[2] * __uint_as_float(ka.w), d[1] * __uint_as_float(kb.z) + d[3] * __uint_as_float(kb.w));
          const uint32_t dc = pack2(fmaf(sum[r], -1.f / 32.f, d[0]), fmaf(sum[r], -1.f / 32.f, d[1]));
          alo[i][r] = re; alo[i][2 + r] = im;
          ahi[i][r] = g == 0 ? dc : re; ahi[i][2 + r] = g == 0 ? 0u : im;
        }
      float acc[8][4];
#pragma unroll
      for (int u = 0; u < 8; u++) {
        acc[u][0] = acc[u][1] = acc[u][2] = acc[u][3] = 0.f;
#pragma unroll
        for (int i = 0; i < 4; i++) {
          const uint4& bq = fb[i * 4 + (u >> 1)];
          if (u < 4) mma16816(acc[u], alo[i][0], alo[i][1], alo[i][2], alo[i][3], (u & 1) ? bq.z : bq.x, (u & 1) ? bq.w : bq.y);
          else       mma16816(acc[u], ahi[i][0], ahi[i][1], ahi[i][2], ahi[i][3], (u & 1) ? bq.z : bq.x, (u & 1) ? bq.w : bq.y);
        }
      }
#pragma unroll
      for (int r = 0; r < 2; r++)
#pragma unroll
        for (int h = 0; h < 2; h++) {
          const int j = 2 * warp + r, m = 2 * t + h;
          const float rs = rstd[r];
          sts4(sbase + SM_E + ((j * 8 + m) * 8 + (g ^ (2 * t) ^ (2 * (j & 3)))) * 16,
               pack2(acc[2 * h][2 * r] * rs, acc[2 * h][2 * r + 1] * rs), pack2(acc[2 * h + 1][2 * r] * rs, acc[2 * h + 1][2 * r + 1] * rs),
               pack2(acc[4 + 2 * h][2 * r] * rs, acc[4 + 2 * h][2 * r + 1] * rs), pack2(acc[5 + 2 * h][2 * r] * rs, acc[5 + 2 * h][2 * r + 1] * rs));
        }
      if (tid == 0) PROFP(12);
      bar_sync(NB_RDY, 384);
      if (tid == 0) PROFP(13);
      uint4 fc[4];
#pragma unroll
      for (int i = 0; i < 4; i++) fc[i] = lds4(sbase + SM_FC + i * 512 + lane * 16);
      asm volatile("ld.shared.u32 %0, [%1];" : "=r"(tag) : "r"(BAR(epoch, 0)) : "memory");
      tag = (tag + 1) & 1;
#pragma unroll
      for (int i = 0; i < 4; i++) q[i] = lds4(sbase + SM_E + (((t + 4 * i) * 8 + warp) * 8 + (g ^ (warp & 6) ^ (2 * t))) * 16);
      cdft16(q, fc, o);
#pragma unroll
      for (int vv = 0; vv < 4; vv++) st_tag(&scr->Z1[(((4 * vv + t) * 8 + warp) * 128 + c) * 8 + g], o[vv], tag);
    }
    PROF(1);
    {
      const uint4* const zp = &scr->Z1[(c * 128 + 8 * t + warp) * 8 + g];
      const uint32_t tst = clock32();
      mbar_wait(BAR(tbar, 0), 0);
      if (tid == 0) PROFP(14);
      uint4 f2[4], g2[4];
#pragma unroll
      for (int i = 0; i < 4; i++) {
        f2[i] = lds4(TOFF(f2) + warp * 2048 + i * 512);
        g2[i] = lds4(TOFF(g2) + warp * 2048 + i * 512);
      }
      const uint4 f8 = lds4(TOFF(f8)), g8 = lds4(TOFF(g8));
      float wfr[16], wfi[16];
      {
        const float fsc = 1.f / (1 << 19);
        const float fsc3 = ((c & 7) == 7 && g == 0) ? 0.5f * fsc : fsc;
        const int gg = g == 0 ? 8 : g, wsh = (2 * (c >> 3) + 2) & 15;
#pragma unroll
        for (int i = 0; i < 16; i++) {
          const int ci = i >> 3, dd = (i >> 2) & 1, e = i & 3;
          const int kk = (e == 0 ? gg : e == 1 ? 16 + gg : e == 2 ? 16 - g : 32 - g) - 1;
          const uint32_t a = sbase + SM_W + ((2 * warp + ci) * 8 + t + 4 * dd) * 80 + wsh + 2 * kk;
          wfr[i] = bf_lo(lds_u16(a)) * (e == 3 ? fsc3 : fsc);
          wfi[i] = bf_lo(lds_u16(a + 10240)) * (e == 3 ? fsc3 : fsc);
        }
      }
      asm volatile("barrier.cluster.wait.aligned;" ::: "memory");
      PROF(2);
      while (clock32() - tst < POLL_DELAY) {}
      ld_tag4_issue<256>(q, zp);
      ld_tag4_finish<256>(q, zp, tag);
      if (tid == 0) PROFP(30);
      if (lane == 0) mbar_arrive(BAR(sig, 0));
      cdft16(q, f2, o);
      const uint32_t e2 = sbase + SM_E2;
#pragma unroll
      for (int vv = 0; vv < 4; vv++)
        sts4(e2 + ((warp * 16 + 4 * vv + t) * 8 + (g ^ (2 * t) ^ (2 * (warp & 3)))) * 16, o[vv].x, o[vv].y, o[vv].z, o[vv].w);
      bar_sync(NB_CONS, 256);
#pragma unroll
      for (int ci = 0; ci < 2; ci++) {
        const int cc = 2 * warp + ci;
        uint32_t ad[2];
        uint4 u[2];
#pragma unroll
        for (int hh = 0; hh < 2; hh++) {
          ad[hh] = e2 + (((t + 4 * hh) * 16 + cc) * 8 + (g ^ (2 * (cc & 3)) ^ (2 * t))) * 16;
          u[hh] = lds4(ad[hh]);
        }
        uint32_t res[2][4];
#pragma unroll
        for (int p = 0; p < 2; p++) {
          uint32_t y[2][2];
#pragma unroll
          for (int vv = 0; vv < 2; vv++) {
            float d[4] = {0.f, 0.f, 0.f, 0.f};
            mma16816(d, word(u[0], 2 * p), word(u[0], 2 * p + 1), word(u[1], 2 * p), word(u[1], 2 * p + 1), word(f8, 2 * vv), word(f8, 2 * vv + 1));
#pragma unroll
            for (int rr = 0; rr < 2; rr++) {
              const float fr = wfr[ci * 8 + vv * 4 + 2 * p + rr], fi = wfi[ci * 8 + vv * 4 + 2 * p + rr];
              y[vv][rr] = pack2(d[2 * rr] * fr - d[2 * rr + 1] * fi, d[2 * rr] * fi + d[2 * rr + 1] * fr);
            }
          }
#pragma unroll
          for (int vv = 0; vv < 2; vv++) {
            float d[4] = {0.f, 0.f, 0.f, 0.f};
            mma16816(d, y[0][0], y[0][1], y[1][0], y[1][1], word(g8, 2 * vv), word(g8, 2 * vv + 1));
            res[vv][2 * p] = pack2(d[0], d[1]);
            res[vv][2 * p + 1] = pack2(d[2], d[3]);
          }
        }
#pragma unroll
        for (int vv = 0; vv < 2; vv++) sts4(ad[vv], res[vv][0], res[vv][1], res[vv][2], res[vv][3]);
      }
      bar_sync(NB_CONS, 256);
#pragma unroll
      for (int i = 0; i < 4; i++) q[i] = lds4(e2 + ((warp * 16 + 4 * i + t) * 8 + (g ^ (2 * t) ^ (2 * (warp & 3)))) * 16);
      cdft16(q, g2, o);
#pragma unroll
      for (int vv = 0; vv < 4; vv++) st_tag(&scr->Z2[((8 * (4 * vv + t) + warp) * 128 + c) * 8 + g], o[vv], tag);
    }
    PROF(3);
    {
      const uint4* const zp = &scr->Z2[((c * 16 + t) * 8 + warp) * 8 + g];
      const uint32_t tst = clock32();
      uint4 gb[16], gc[4], tw[4], xr[2][2];
#pragma unroll
      for (int i = 0; i < 16; i++) gb[i] = lds4(TOFF(gb) + i * 512);
      const uint4 ga = lds4(TOFF(ga));
#pragma unroll
      for (int i = 0; i < 4; i++) {
        gc[i] = lds4(sbase + SM_FC + 2048 + i * 512 + lane * 16);
        tw[i] = lds4(TOFF(tw3) + i * 512);
        const int ch = 4 * (g + 8 * (i & 1)) + t;
        xr[i >> 1][i & 1] = lds4(sbase + SM_X + (2 * warp + (i >> 1)) * 1024 + ((ch ^ ((ch >> 2) & 6)) * 16));
      }
      PROF(4);
      while (clock32() - tst < POLL_DELAY) {}
      ld_tag4_issue<256>(q, zp);
      ld_tag4_finish<256>(q, zp, tag);
      if (tid == 0) PROFP(31);
      if (lane == 0) mbar_arrive(BAR(sig, 1));
      cdft16(q, gc, o);
#pragma unroll
      for (int vv = 0; vv < 4; vv++)
        sts4(sbase + SM_E + (((4 * vv + t) * 8 + warp) * 8 + (g ^ (warp & 6) ^ (2 * t))) * 16, o[vv].x, o[vv].y, o[vv].z, o[vv].w);
      bar_sync(NB_CONS, 256);
      uint32_t hv[2][8];
      const float mk = t == 0 ? 0.f : 1.f;
#pragma unroll
      for (int r = 0; r < 2; r++) {
        const int j = 2 * warp + r;
        uint4 u[2];
#pragma unroll
        for (int h = 0; h < 2; h++) u[h] = lds4(sbase + SM_E + ((j * 8 + 2 * t + h) * 8 + (g ^ (2 * t) ^ (2 * (j & 3)))) * 16);
        float yv[4][4];
#pragma unroll
        for (int i = 0; i < 4; i++) {
          float lo[4] = {0.f, 0.f, 0.f, 0.f}, hi[4] = {0.f, 0.f, 0.f, 0.f};
          mma16816(lo, gb[i * 4].x, gb[i * 4].y, gb[i * 4].z, gb[i * 4].w, u[0].x, u[0].y);
          mma16816(lo, gb[i * 4 + 1].x, gb[i * 4 + 1].y, gb[i * 4 + 1].z, gb[i * 4 + 1].w, u[1].x, u[1].y);
          mma16816(hi, gb[i * 4 + 2].x, gb[i * 4 + 2].y, gb[i * 4 + 2].z, gb[i * 4 + 2].w, u[0].z, u[0].w);
          mma16816(hi, gb[i * 4 + 3].x, gb[i * 4 + 3].y, gb[i * 4 + 3].z, gb[i * 4 + 3].w, u[1].z, u[1].w);
          const float ca = __uint_as_float(tw[i].x), sa = __uint_as_float(tw[i].y), cb = __uint_as_float(tw[i].z), sb = __uint_as_float(tw[i].w);
          const float tr0 = fmaf(hi[0], mk, lo[0]), ti0 = fmaf(hi[2], mk, lo[2]);
          const float tr1 = lo[1] + hi[1], ti1 = lo[3] + hi[3];
          const float vr0 = tr0 * ca - ti0 * sa, vi0 = tr0 * sa + ti0 * ca;
          const float vr1 = tr1 * cb - ti1 * sb, vi1 = tr1 * sb + ti1 * cb;
          const uint32_t b0 = pack2(t == 0 ? hi[0] : vr0, vr1), b1 = pack2(t == 0 ? vr0 : vi0, vi1);
          yv[i][0] = yv[i][1] = yv[i][2] = yv[i][3] = 0.f;
          mma16816(yv[i], ga.x, ga.y, ga.z, ga.w, b0, b1);
        }
#pragma unroll
        for (int h = 0; h < 2; h++) {
          hv[r][4 * h + 0] = hadd2_bf16(xr[r][h].x, pack2(yv[0][2 * h], yv[1][2 * h]));
          hv[r][4 * h + 1] = hadd2_bf16(xr[r][h].y, pack2(yv[2][2 * h], yv[3][2 * h]));
          hv[r][4 * h + 2] = hadd2_bf16(xr[r][h].z, pack2(yv[0][2 * h + 1], yv[1][2 * h + 1]));
          hv[r][4 * h + 3] = hadd2_bf16(xr[r][h].w, pack2(yv[2][2 * h + 1], yv[3][2 * h + 1]));
        }
      }
      float ds[4] = {0.f, 0.f, 0.f, 0.f};
#pragma unroll
      for (int q4 = 0; q4 < 4; q4++) mma16816(ds, hv[0][2 * q4], hv[1][2 * q4], hv[0][2 * q4 + 1], hv[1][2 * q4 + 1], 0x3f803f80u, 0x3f803f80u);
#pragma unroll
      for (int o2 = 4; o2 <= 16; o2 <<= 1) {
        ds[0] += __shfl_xor_sync(0xffffffffu, ds[0], o2);
        ds[2] += __shfl_xor_sync(0xffffffffu, ds[2], o2);
      }
      uint32_t mb[2];
#pragma unroll
      for (int r = 0; r < 2; r++) {
        const int row = 16 * f + 2 * warp + r;
        mb[r] = pack2(ds[2 * r] * (1.f / 512.f), ds[2 * r] * (1.f / 512.f));
#pragma unroll
        for (int i = 0; i < 8; i++) hv[r][i] = hsub2_bf16(hv[r][i], mb[r]);
#pragma unroll
        for (int h = 0; h < 2; h++) {
          const int n1 = g + 8 * h;
          st_tag(&scr->LN[(rb * 8 + (n1 >> 1)) * 1024 + row * 8 + ((4 * (n1 & 1) + t) ^ (row & 7))],
                 make_uint4(hv[r][4 * h], hv[r][4 * h + 1], hv[r][4 * h + 2], hv[r][4 * h + 3]), n1 < 2 * NLL ? tag : (hv[r][4 * h] & 1u));
        }
      }
      bar_arrive(NB_LN, 288);
      float sum[2], sq[2], rstd[2];
      row_stats(hv[0], hv[1], lane, sum, sq);
#pragma unroll
      for (int r = 0; r < 2; r++) {
        const float m = sum[r] * (1.f / 512.f);
        rstd[r] = rsqrtf(fmaxf(fmaf(-m, m, sq[r] * (1.f / 512.f)), 0.f) + 1e-5f);
      }
      if (lane == 0)
        st_tag(&scr->ST[rb * 64 + 8 * f + warp], make_uint4(mb[0] << 16, __float_as_uint(rstd[0]), mb[1] << 16, __float_as_uint(rstd[1])), tag);
    }
    PROF(5);
    asm volatile("setmaxnreg.inc.sync.aligned.u32 224;");
    if (NLL) {
      const uint4* const ap = &scr->LN[rb * 8 * 1024 + tid];
      uint4 av[NLL ? NLL : 1][4];
      spin_cycles(POLL_DELAY3);
#pragma unroll
      for (int kb = 0; kb < NLL; kb++) ld_tag4_issue<256>(av[kb], ap + kb * 1024);
      bar_sync(NB_CONS, 256);
#pragma unroll
      for (int kb = 0; kb < NLL; kb++) {
        ld_tag4_finish<256>(av[kb], ap + kb * 1024, tag);
#pragma unroll
        for (int i = 0; i < 4; i++) sts4(sbase + kb * SLOT + (tid + 256 * i) * 16, av[kb][i].x, av[kb][i].y, av[kb][i].z, av[kb][i].w);
      }
      asm volatile("fence.proxy.async.shared::cta;" ::: "memory");
      bar_sync(NB_CONS, 256);
    }
    const int wgi = warp >> 2, wq = warp & 3;
    uint4* const pbase = &scr->P[rb * 28 * 1024 + warp * 128 + lane];
    const uint32_t a_lo0 = desc_lo(sbase + wgi * 8192, 16);
    const uint32_t ebar = lane == 0 ? BAR(empty1, 0) : RBAR(empty1, 0);
    float r0, r1;
    uint4 px[8], py[6];
    const int rh = wgi ^ kh ^ 1;
    const uint4* const psrc = &scr->P[(rb2 * 28 + 14 * kh) * 1024 + (4 * rh + wq) * 128 + lane];
    {
      float acc[128];
#pragma unroll
      for (int i = 0; i < 128; i++) acc[i] = 0.f;
      const uint32_t b_lo0 = desc_lo(sbase + 8 * SLOT, 4096);
      uint32_t slot = 0, ph = 0, prev = 0;
#pragma unroll 1
      for (int kb = 0; kb < 8; kb++) {
        if (kb >= NLL) mbar_wait(BAR(fullA, kb), 0);
        if (kb == 0) PROF(6);
#pragma unroll
        for (int hh = 0; hh < 2; hh++) {
          if (LAGX && hh == ((16 - LAGX) & 1) && kb == ((16 - LAGX) >> 1) && wgi == 1) bar_sync(NB_LAG, 256);
          mbar_wait(BAR(full1, slot), ph);
          const uint32_t al = a_lo0 + kb * 1024 + hh * 4, bl = b_lo0 + slot * 1024;
          wg_fence();
          wgmma_n256(acc, desc64(al, HI128), desc64(bl, HI128));
          wgmma_n256(acc, desc64(al + 2, HI128), desc64(bl + 128, HI128));
          wg_commit();
          if (LAGX && hh == 1 && kb == 7 && wgi == 0) bar_arrive(NB_LAG, 256);
          wg_wait<1>();
          if ((kb | hh) != 0 && lane < 2) mbar_arrive_remote(ebar + 8 * prev);
          prev = slot;
          if (++slot == 6) { slot = 0; ph ^= 1; }
        }
      }
      mbar_wait(BAR(sbar, 0), 0);
      r0 = __uint_as_float(lds2(sstat + (16 * warp + g) * 8).y);
      r1 = __uint_as_float(lds2(sstat + (16 * warp + g + 8) * 8).y);
      wg_wait<0>();
      if (lane < 2) mbar_arrive_remote(ebar + 8 * prev);
      PROF(7);
      make_p<8, false>(acc, r0, r1, px, pbase, 0, tag);
    }
    PROF(8);
    {
      float acc[96];
#pragma unroll
      for (int i = 0; i < 96; i++) acc[i] = 0.f;
      const uint32_t b_lo0 = desc_lo(sbase + 8 * SLOT, 2048);
      uint4* const pdst = pbase + ((7 * f + 3 * (f & 1)) >> 1) * 1024;
      auto stage_y = [&](int k, uint32_t slot, uint32_t ph) {
        if (LAGY && k == 16 - LAGY && wgi == 1) bar_sync(NB_LAG, 256);
        mbar_wait(BAR(full1, slot), ph);
        const uint32_t al = a_lo0 + (k >> 1) * 1024 + (k & 1) * 4, bl = b_lo0 + slot * 1024;
        wg_fence();
        wgmma_n192(acc, desc64(al, HI128), desc64(bl, HI64));
        wgmma_n192(acc, desc64(al + 2, HI128), desc64(bl + 64, HI64));
        wg_commit();
      };
#pragma unroll
      for (int k = 0; k < 4; k++) {
        stage_y(k, (16 + k) % 6, ((16 + k) / 6) & 1);
        st_tag(pdst + (k >> 1) * 1024 + (k & 1) * 64, px[2 * k], tag);
        st_tag(pdst + (k >> 1) * 1024 + (k & 1) * 64 + 32, px[2 * k + 1], tag);
        if (k == 3 && lane == 0) red_relaxed(&scr->cnt[(C_PX + rb) * 32]);
        wg_wait<1>();
        if (k != 0 && lane < 2) mbar_arrive_remote(ebar + 8 * ((15 + k) % 6));
      }
      uint32_t slot = 2, ph = 1, prev = 1;
#pragma unroll 1
      for (int k = 4; k < 16; k++) {
        stage_y(k, slot, ph);
        if (LAGY && k == 15 && wgi == 0) bar_arrive(NB_LAG, 256);
        wg_wait<1>();
        if (lane < 2) mbar_arrive_remote(ebar + 8 * prev);
        prev = slot;
        if (++slot == 6) { slot = 0; ph ^= 1; }
      }
      wg_wait<0>();
      if (lane < 2) mbar_arrive_remote(ebar + 8 * (31 % 6));
      PROF(9);
      make_p<6, true>(acc, r0, r1, py, pbase, 14 * f + ((f & 1) ? 0 : 8), tag);
      if (lane == 0) red_relaxed(&scr->cnt[(C_PY + rb) * 32 + (f >> 1)]);
    }
    PROF(10);
    {
      float acc[64];
      {
        const float m0 = wgi ? __uint_as_float(lds2(sstat + 1024 + (16 * wq + g) * 8).x) : 0.f;
        const float m1 = wgi ? __uint_as_float(lds2(sstat + 1024 + (16 * wq + g + 8) * 8).x) : 0.f;
#pragma unroll
        for (int i = 0; i < 64; i++) acc[i] = (i & 2) ? m1 : m0;
      }
      const uint32_t b2_lo0 = desc_lo(sbase, 8192);
      const uint32_t pa0 = sbase + 8 * SLOT + (4 * rh + wq) * 2048 + lane * 16;
      uint32_t slot = 2;
      auto fetch2 = [&](int s, uint4 (&a)[4]) {
        mbar_wait(BAR(full2, s), 0);
        if (tid == 0) PROFP(16 + s);
#pragma unroll
        for (int kk = 0; kk < 4; kk++) a[kk] = lds4(pa0 + slot * SLOT + kk * 512);
        if (++slot == 6) slot = 0;
      };
      auto check2 = [&](int s, uint4 (&a)[4]) { ld_tag4_finish<32>(a, psrc + (int)((KORDER >> (4 * s)) & 15) * 1024, tag); };
      auto stage2 = [&](int s, uint4 (&a)[4], uint4 (&nx)[4]) {
        const uint32_t bl = b2_lo0 + (s & 7) * 1024;
        if (LAG2 && s == 14 - LAG2 && wgi == 1) bar_sync(NB_LAG, 256);
        wg_fence();
        wgmma_rs_n128(acc, a[0].x, a[0].y, a[0].z, a[0].w, desc64(bl, HI128));
        wgmma_rs_n128(acc, a[1].x, a[1].y, a[1].z, a[1].w, desc64(bl + 128, HI128));
        wg_commit();
        wg_wait<1>();
        if (s >= 1 && s <= 8 && lane == 0) {
          mbar_arrive(BAR(empty2, s - 1));
          if (s == 8) mbar_arrive_remote(RBAR(xfree, 0));
        }
        if (s < 13) fetch2(s + 1, nx);
        wgmma_rs_n128(acc, a[2].x, a[2].y, a[2].z, a[2].w, desc64(bl + 256, HI128));
        wgmma_rs_n128(acc, a[3].x, a[3].y, a[3].z, a[3].w, desc64(bl + 384, HI128));
        wg_commit();
        if (s < 13) check2(s + 1, nx);
      };
      uint4 fa0[4], fa1[4];
      fetch2(0, fa0);
      check2(0, fa0);
#pragma unroll 1
      for (int s = 0; s < 14; s += 2) {
        stage2(s, fa0, fa1);
        stage2(s + 1, fa1, fa0);
      }
      if (LAG2 && wgi == 0) bar_arrive(NB_LAG, 256);
      uint4 hres[2][4];
      mbar_wait(BAR(hbar, 0), 0);
#pragma unroll
      for (int h = 0; h < 2; h++)
#pragma unroll
        for (int q = 0; q < 4; q++) {
          hres[h][q] = lds4(sbase + 7 * SLOT + (q >> 1) * 8192 + (16 * wq + g + 8 * h) * 128 + (((4 * (q & 1) + t) ^ g) * 16));
          if (2 * nq + (q >> 1) < NLL) hres[h][q].x &= ~1u;
        }
      wg_wait<0>();
      PROF(11);
      const uint32_t xbuf = sbase + 6 * SLOT + (tid & 127) * 16;
      if (wgi == 0) {
        uint32_t rbuf;
        mbar_wait(BAR(xfree, 0), 0);
        asm volatile("mapa.shared::cluster.u32 %0, %1, %2;" : "=r"(rbuf) : "r"(xbuf), "r"(kh ^ 1));
#pragma unroll
        for (int i = 0; i < 8; i++)
          asm volatile("st.async.weak.shared::cluster.mbarrier::complete_tx::bytes.v4.b32 [%0], {%1,%2,%3,%4}, [%5];"
                       ::"r"(rbuf + i * 2048), "r"(pack2(acc[8 * i], acc[8 * i + 1])), "r"(pack2(acc[8 * i + 2], acc[8 * i + 3])),
                         "r"(pack2(acc[8 * i + 4], acc[8 * i + 5])), "r"(pack2(acc[8 * i + 6], acc[8 * i + 7])), "r"(RBAR(xbar, 0))
                       : "memory");
      } else {
        mbar_wait_cluster(BAR(xbar, 0), 0);
      }
      uint32_t w[2][16];
#pragma unroll
      for (int i = 0; i < 8; i++) {
        const uint4 pv = lds4(xbuf + i * 2048);
        w[0][2 * i] = pack2(acc[8 * i] + bf_lo(pv.x), acc[8 * i + 1] + bf_hi(pv.x));
        w[1][2 * i] = pack2(acc[8 * i + 2] + bf_lo(pv.y), acc[8 * i + 3] + bf_hi(pv.y));
        w[0][2 * i + 1] = pack2(acc[8 * i + 4] + bf_lo(pv.z), acc[8 * i + 5] + bf_hi(pv.z));
        w[1][2 * i + 1] = pack2(acc[8 * i + 6] + bf_lo(pv.w), acc[8 * i + 7] + bf_hi(pv.w));
      }
      uint4* const o4 = reinterpret_cast<uint4*>(out) + (16 * (c >> 4) + 2 * (4 * rh + wq) + (rb2 & 1) + 128 * g) * 64 + nq * 16 + t;
#pragma unroll
      for (int h = 0; h < 2; h++)
#pragma unroll
        for (int q = 0; q < 4; q++) {
          uint32_t a0 = w[h][4 * q], a1 = w[h][4 * q + 1], a2 = w[h][4 * q + 2], a3 = w[h][4 * q + 3];
          {
            const bool od = t & 1;
            uint32_t s0 = od ? a0 : a1, s1 = od ? a2 : a3;
            s0 = __shfl_xor_sync(0xffffffffu, s0, 1); s1 = __shfl_xor_sync(0xffffffffu, s1, 1);
            if (od) { a0 = s0; a2 = s1; } else { a1 = s0; a3 = s1; }
          }
          {
            const bool up = t & 2;
            uint32_t s0 = up ? a0 : a2, s1 = up ? a1 : a3;
            s0 = __shfl_xor_sync(0xffffffffu, s0, 2); s1 = __shfl_xor_sync(0xffffffffu, s1, 2);
            if (up) { a0 = s0; a1 = s1; } else { a2 = s0; a3 = s1; }
          }
          if (wgi == 1)
            o4[h * 1024 * 64 + 4 * q] =
                make_uint4(hadd2_bf16(hres[h][q].x, a0), hadd2_bf16(hres[h][q].y, a1), hadd2_bf16(hres[h][q].z, a2), hadd2_bf16(hres[h][q].w, a3));
        }
      PROF(12);
      PROFG(15);
    }
  }
#undef BAR
#undef TOFF
#undef RBAR
}

typedef CUresult (*EncodeFn)(CUtensorMap*, CUtensorMapDataType, cuuint32_t, void*, const cuuint64_t*, const cuuint64_t*,
                             const cuuint32_t*, const cuuint32_t*, CUtensorMapInterleave, CUtensorMapSwizzle,
                             CUtensorMapL2promotion, CUtensorMapFloatOOBfill);

}

extern "C" void kernel_launch(void* const* d_in, const int* in_sizes, int n_in, void* d_out, int out_size) {
  (void)in_sizes; (void)n_in; (void)out_size;
  static EncodeFn encode = nullptr;
  static void *tab = nullptr, *scr = nullptr;
  if (!encode) {
    void* fn = nullptr;
    cudaDriverEntryPointQueryResult qr;
    cudaGetDriverEntryPoint("cuTensorMapEncodeTiled", &fn, cudaEnableDefault, &qr);
    encode = (EncodeFn)fn;
    cudaGetSymbolAddress(&tab, g_tab);
    cudaGetSymbolAddress(&scr, g_scr);
    cudaFuncSetAttribute(fused_kernel, cudaFuncAttributeMaxDynamicSharedMemorySize, SMEM_BYTES);
  }
  CUtensorMap tmGX, tmUX, tmGY, tmUY, tmD, tmWR, tmWI;
  const cuuint32_t es[5] = {1, 1, 1, 1, 1};
  auto enc = [&](CUtensorMap* m, void* p, int rank, const cuuint64_t* gd, const cuuint64_t* gs, const cuuint32_t* bd,
                 CUtensorMapSwizzle sw, CUtensorMapL2promotion pr) {
    encode(m, CU_TENSOR_MAP_DATA_TYPE_BFLOAT16, rank, p, gd, gs, bd, es, CU_TENSOR_MAP_INTERLEAVE_NONE, sw, pr,
           CU_TENSOR_MAP_FLOAT_OOB_FILL_NONE);
  };
  {
    const cuuint64_t gd[3] = {64, 512, 28}, gs[2] = {3584, 128};
    const cuuint32_t bd[3] = {64, 32, 2};
    enc(&tmGX, d_in[4], 3, gd, gs, bd, CU_TENSOR_MAP_SWIZZLE_128B, CU_TENSOR_MAP_L2_PROMOTION_L2_256B);
    enc(&tmUX, d_in[5], 3, gd, gs, bd, CU_TENSOR_MAP_SWIZZLE_128B, CU_TENSOR_MAP_L2_PROMOTION_L2_256B);
  }
  {
    const cuuint64_t gd[3] = {32, 512, 56}, gs[2] = {3584, 64};
    const cuuint32_t bd[3] = {32, 32, 3};
    enc(&tmGY, d_in[4], 3, gd, gs, bd, CU_TENSOR_MAP_SWIZZLE_64B, CU_TENSOR_MAP_L2_PROMOTION_L2_128B);
    enc(&tmUY, d_in[5], 3, gd, gs, bd, CU_TENSOR_MAP_SWIZZLE_64B, CU_TENSOR_MAP_L2_PROMOTION_L2_128B);
  }
  {
    const cuuint64_t gd[3] = {64, 1792, 8}, gs[2] = {1024, 128};
    const cuuint32_t bd[3] = {64, 64, 2};
    enc(&tmD, d_in[6], 3, gd, gs, bd, CU_TENSOR_MAP_SWIZZLE_128B, CU_TENSOR_MAP_L2_PROMOTION_L2_256B);
  }
  {
    const cuuint64_t gd[3] = {4112, 8, 16}, gs[2] = {16 * 8224, 8224};
    const cuuint32_t bd[3] = {40, 8, 16};
    enc(&tmWR, d_in[1], 3, gd, gs, bd, CU_TENSOR_MAP_SWIZZLE_NONE, CU_TENSOR_MAP_L2_PROMOTION_NONE);
    enc(&tmWI, d_in[2], 3, gd, gs, bd, CU_TENSOR_MAP_SWIZZLE_NONE, CU_TENSOR_MAP_L2_PROMOTION_NONE);
  }
  fused_kernel<<<NCTA, NTHREADS, SMEM_BYTES>>>((const __nv_bfloat16*)d_in[0], (const Tables*)tab, (Scratch*)scr,
                                               (__nv_bfloat16*)d_out, (const char*)d_in[4], (const char*)d_in[5],
                                               (const char*)d_in[6], tmWR, tmWI, tmGX, tmUX, tmGY, tmUY, tmD);
}
```

```cpp
#include <cuda_runtime.h>
#include <cuda_bf16.h>
#include <cuda.h>
#include <stdint.h>

namespace {

constexpr int NCTA = 128;
constexpr int NTHREADS = 384;
constexpr int SLOT = 16384;
constexpr int SMEM_BYTES = 14 * SLOT + 2048 + 1024;
constexpr int SPIN_LIMIT = 1 << 22;

struct Scratch {
  uint4 Z1[128 * 1024];
  uint4 Z2[128 * 1024];
  uint4 LN[16 * 8 * 1024];
  uint4 P[16 * 28 * 1024];
  uint4 ST[1024];
  unsigned cnt[64 * 32];
};
__device__ __align__(1024) Scratch g_scr;
#define PROF(i)
#define PROFP(i)
#define PROFG(i)

constexpr double ccos(int i, int n) {
  i &= n - 1;
  if (i > n / 2) i = n - i;
  if (4 * i == n) return 0.0;
  const bool neg = 4 * i > n;
  if (neg) i = n / 2 - i;
  const double a = 6.283185307179586476925 * i / n, a2 = a * a;
  double term = 1.0, sum = 1.0;
  for (int k = 1; k < 14; k++) { term *= -a2 / ((2 * k - 1) * (2 * k)); sum += term; }
  return neg ? -sum : sum;
}
constexpr double csin(int i, int n) { return ccos(i - n / 4, n); }
constexpr unsigned fbits(double v, int mant) {
  if (v == 0.0) return 0;
  const unsigned sg = v < 0 ? 1u : 0u;
  if (v < 0) v = -v;
  int e = 127;
  while (v < 1.0) { v *= 2.0; e--; }
  const unsigned m = (unsigned)((v - 1.0) * (double)(1u << mant) + 0.5);
  return (sg << (8 + mant)) + ((unsigned)e << mant) + m;
}
constexpr unsigned pkb(double lo, double hi) { return fbits(lo, 7) | (fbits(hi, 7) << 16); }
constexpr double fa_elem(int kp, int n1) {
  return kp <= 8 ? ccos(kp * n1, 16) : -csin((kp - 8) * n1, 16);
}
constexpr unsigned cfrag_c(int idx, int n, int ri) {
  return ri ? pkb(-csin(idx, n), ccos(idx, n)) : pkb(ccos(idx, n), csin(idx, n));
}
struct Tables {
  unsigned fb[16][32][4];
  unsigned tw1[8][32][4];
  unsigned fa[32][4];
  unsigned f2[8][4][32][4];
  unsigned g2[8][4][32][4];
  unsigned gb[16][32][4];
  unsigned tw3[4][32][4];
  unsigned ga[32][4];
  unsigned f8[32][4], g8[32][4];
};
constexpr int T1_BYTES = 12800, T2_BYTES = 44544;
static_assert(sizeof(Tables) == T1_BYTES + T2_BYTES, "table size");
constexpr Tables make_tables() {
  Tables T = {};
  for (int l = 0; l < 32; l++) {
    const int g = l >> 2, t = l & 3;
    for (int i = 0; i < 4; i++)
      for (int u = 0; u < 8; u++) {
        const int ri = g & 1, m = 2 * (g >> 1) + ((u & 3) >> 1);
        const double sg = u >= 4 ? -1.0 : 1.0;
        const int k2 = u >= 4 ? 31 - 2 * m - (u & 1) : 2 * m + (u & 1);
        const int pa = (8 * t + i) * k2, pb = (8 * t + 4 + i) * k2;
        T.fb[i * 4 + (u >> 1)][l][(u & 1) * 2 + 0] = ri == 0 ? pkb(ccos(pa, 32), ccos(pb, 32)) : pkb(-sg * csin(pa, 32), -sg * csin(pb, 32));
        T.fb[i * 4 + (u >> 1)][l][(u & 1) * 2 + 1] = ri == 0 ? pkb(csin(pa, 32), csin(pb, 32)) : pkb(sg * ccos(pa, 32), sg * ccos(pb, 32));
      }
    for (int i = 0; i < 4; i++)
      for (int ks = 0; ks < 4; ks++) {
        const int n2 = 4 * g + i, m = 2 * t + (ks & 1);
        const double sg = ks >= 2 ? -1.0 : 1.0;
        const int pa = n2 * (ks >= 2 ? 31 - 2 * m : 2 * m), pb = n2 * (ks >= 2 ? 30 - 2 * m : 2 * m + 1);
        T.gb[i * 4 + ks][l][0] = pkb(ccos(pa, 32), -sg * csin(pa, 32));
        T.gb[i * 4 + ks][l][1] = pkb(csin(pa, 32), sg * ccos(pa, 32));
        T.gb[i * 4 + ks][l][2] = pkb(ccos(pb, 32), -sg * csin(pb, 32));
        T.gb[i * 4 + ks][l][3] = pkb(csin(pb, 32), sg * ccos(pb, 32));
      }
    for (int i = 0; i < 4; i++) {
      for (int e = 0; e < 2; e++) {
        const int p = (8 * t + 4 * e + i) * (g == 0 ? 8 : g);
        T.tw1[2 * i + e][l][0] = fbits(g == 0 ? 0.0 : ccos(p, 512), 23);
        T.tw1[2 * i + e][l][1] = fbits(g == 0 ? ccos(p, 512) : csin(p, 512), 23);
        T.tw1[2 * i + e][l][2] = fbits(g == 0 ? 0.0 : -csin(p, 512), 23);
        T.tw1[2 * i + e][l][3] = fbits(g == 0 ? -csin(p, 512) : ccos(p, 512), 23);
      }
      const int ka = t == 0 ? 8 : 2 * t, kb = 2 * t + 1;
      T.tw3[i][l][0] = fbits(ccos((4 * g + i) * ka, 512), 23);
      T.tw3[i][l][1] = fbits(csin((4 * g + i) * ka, 512), 23);
      T.tw3[i][l][2] = fbits(ccos((4 * g + i) * kb, 512), 23);
      T.tw3[i][l][3] = fbits(csin((4 * g + i) * kb, 512), 23);
      const int p8 = (t + 4 * (i & 1)) * (4 * (i >> 1) + (g >> 1));
      T.f8[l][i] = cfrag_c(p8, 8, g & 1);
      T.g8[l][i] = cfrag_c(-p8, 8, g & 1);
    }
    for (int w = 0; w < 8; w++)
      for (int i = 0; i < 16; i++) {
        const int kidx = t + 4 * (i & 1) + 8 * (i >> 3), nidx = 4 * ((i >> 1) & 3) + (g >> 1);
        T.f2[w][i >> 2][l][i & 3] = cfrag_c((8 * kidx + w) * nidx, 128, g & 1);
        T.g2[w][i >> 2][l][i & 3] = cfrag_c(-(8 * nidx + w) * kidx, 128, g & 1);
      }
    T.fa[l][0] = pkb(fa_elem(g, 2 * t), fa_elem(g, 2 * t + 1));
    T.fa[l][1] = pkb(fa_elem(g + 8, 2 * t), fa_elem(g + 8, 2 * t + 1));
    T.fa[l][2] = pkb(fa_elem(g, 2 * t + 8), fa_elem(g, 2 * t + 9));
    T.fa[l][3] = pkb(fa_elem(g + 8, 2 * t + 8), fa_elem(g + 8, 2 * t + 9));
    T.ga[l][0] = pkb(fa_elem(2 * t, g), fa_elem(2 * t + 1, g));
    T.ga[l][1] = pkb(fa_elem(2 * t, g + 8), fa_elem(2 * t + 1, g + 8));
    T.ga[l][2] = pkb(fa_elem(2 * t + 8, g), fa_elem(2 * t + 9, g));
    T.ga[l][3] = pkb(fa_elem(2 * t + 8, g + 8), fa_elem(2 * t + 9, g + 8));
  }
  return T;
}
__device__ const __align__(128) Tables g_tab = make_tables();

__device__ __forceinline__ void die() { asm volatile("st.global.u32 [%0], %1;" ::"l"(0ull), "r"(0) : "memory"); }
__device__ __forceinline__ uint32_t s2u(const void* p) { return (uint32_t)__cvta_generic_to_shared(p); }
__device__ __forceinline__ void mbar_init(uint32_t b, int c) { asm volatile("mbarrier.init.shared::cta.b64 [%0], %1;" ::"r"(b), "r"(c)); }
__device__ __forceinline__ void mbar_expect(uint32_t b, int bytes) {
  asm volatile("mbarrier.arrive.expect_tx.shared::cta.b64 _, [%0], %1;" ::"r"(b), "r"(bytes) : "memory");
}
__device__ __forceinline__ void mbar_arrive(uint32_t b) { asm volatile("mbarrier.arrive.shared::cta.b64 _, [%0];" ::"r"(b) : "memory"); }
__device__ __forceinline__ uint32_t mbar_try(uint32_t b, uint32_t parity) {
  uint32_t ok;
  asm volatile("{.reg .pred p; mbarrier.try_wait.parity.shared::cta.b64 p, [%1], %2; selp.u32 %0,1,0,p;}"
               : "=r"(ok) : "r"(b), "r"(parity) : "memory");
  return ok;
}
__device__ __forceinline__ void mbar_wait(uint32_t b, uint32_t parity) {
  int it = 0;
#pragma unroll 1
  while (!mbar_try(b, parity))
    if (++it > SPIN_LIMIT) { die(); break; }
}
__device__ __forceinline__ void mbar_wait_cluster(uint32_t b, int parity) {
  uint32_t ok;
  int it = 0;
  do {
    asm volatile("{.reg .pred p; mbarrier.try_wait.parity.acquire.cluster.shared::cta.b64 p, [%1], %2; selp.u32 %0,1,0,p;}"
                 : "=r"(ok) : "r"(b), "r"(parity) : "memory");
    if (++it > SPIN_LIMIT) { die(); break; }
  } while (!ok);
}
__device__ __forceinline__ void bar_sync(int id, int n) { asm volatile("bar.sync %0, %1;" ::"r"(id), "r"(n) : "memory"); }
__device__ __forceinline__ void bar_arrive(int id, int n) { asm volatile("bar.arrive %0, %1;" ::"r"(id), "r"(n) : "memory"); }
__device__ __forceinline__ void red_release(unsigned* p) { asm volatile("red.release.gpu.global.add.u32 [%0], 1;" ::"l"(p) : "memory"); }
__device__ __forceinline__ void red_relaxed(unsigned* p) { asm volatile("red.relaxed.gpu.global.add.u32 [%0], 1;" ::"l"(p) : "memory"); }
__device__ __forceinline__ unsigned ld_acquire(const unsigned* p) {
  unsigned v;
  asm volatile("ld.acquire.gpu.global.u32 %0, [%1];" : "=r"(v) : "l"(p) : "memory");
  return v;
}
__device__ __forceinline__ unsigned ld_relaxed(const unsigned* p) {
  unsigned v;
  asm volatile("ld.relaxed.gpu.global.u32 %0, [%1];" : "=r"(v) : "l"(p) : "memory");
  return v;
}
__device__ __forceinline__ void wait_counter(const unsigned* p, unsigned target) {
  int it = 0;
  while ((int)(ld_acquire(p) - target) < 0)
    if (++it > SPIN_LIMIT) { die(); break; }
}
__device__ __forceinline__ void sts4(uint32_t a, uint32_t x, uint32_t y, uint32_t z, uint32_t w) {
  asm volatile("st.shared.v4.u32 [%0], {%1,%2,%3,%4};" ::"r"(a), "r"(x), "r"(y), "r"(z), "r"(w) : "memory");
}
__device__ __forceinline__ uint4 lds4(uint32_t a) {
  uint4 v;
  asm volatile("ld.shared.v4.u32 {%0,%1,%2,%3}, [%4];" : "=r"(v.x), "=r"(v.y), "=r"(v.z), "=r"(v.w) : "r"(a) : "memory");
  return v;
}
__device__ __forceinline__ uint32_t pack2(float lo, float hi) {
  uint32_t r;
  asm("cvt.rn.bf16x2.f32 %0, %1, %2;" : "=r"(r) : "f"(hi), "f"(lo));
  return r;
}
__device__ __forceinline__ float bf_lo(uint32_t v) { return __uint_as_float(v << 16); }
__device__ __forceinline__ float bf_hi(uint32_t v) { return __uint_as_float(v & 0xffff0000u); }
__device__ __forceinline__ uint32_t hadd2_bf16(uint32_t a, uint32_t b) {
  uint32_t r;
  asm("add.rn.bf16x2 %0, %1, %2;" : "=r"(r) : "r"(a), "r"(b));
  return r;
}
__device__ __forceinline__ void mma16816(float (&d)[4], uint32_t a0, uint32_t a1, uint32_t a2, uint32_t a3, uint32_t b0, uint32_t b1) {
  asm("mma.sync.aligned.m16n8k16.row.col.f32.bf16.bf16.f32 {%0,%1,%2,%3}, {%4,%5,%6,%7}, {%8,%9}, {%0,%1,%2,%3};"
      : "+f"(d[0]), "+f"(d[1]), "+f"(d[2]), "+f"(d[3])
      : "r"(a0), "r"(a1), "r"(a2), "r"(a3), "r"(b0), "r"(b1));
}
template <int N>
__device__ __forceinline__ void cs_frac(int idx, float& c, float& s) {
  int i = ((idx + N / 2) & (N - 1)) - N / 2;
  float a = (float)i * (6.283185307179586f / N);
  c = __cosf(a);
  s = __sinf(a);
}
template <int N>
__device__ __forceinline__ uint32_t cfrag(int idx, int ri) {
  float c, s;
  cs_frac<N>(idx, c, s);
  return ri ? pack2(-s, c) : pack2(c, s);
}
__device__ __forceinline__ uint32_t word(const uint4& v, int e) { return e == 0 ? v.x : e == 1 ? v.y : e == 2 ? v.z : v.w; }
__device__ __forceinline__ void cdft16(const uint4 (&q)[4], const uint4 (&F)[4], uint4 (&o)[4]) {
  float acc[2][4][4];
#pragma unroll
  for (int p = 0; p < 2; p++)
#pragma unroll
    for (int v = 0; v < 4; v++) {
      acc[p][v][0] = acc[p][v][1] = acc[p][v][2] = acc[p][v][3] = 0.f;
#pragma unroll
      for (int ks = 0; ks < 2; ks++)
        mma16816(acc[p][v], word(q[2 * ks], 2 * p), word(q[2 * ks], 2 * p + 1), word(q[2 * ks + 1], 2 * p),
                 word(q[2 * ks + 1], 2 * p + 1), word(F[ks * 2 + (v >> 1)], (v & 1) * 2), word(F[ks * 2 + (v >> 1)], (v & 1) * 2 + 1));
    }
#pragma unroll
  for (int v = 0; v < 4; v++)
    o[v] = make_uint4(pack2(acc[0][v][0], acc[0][v][1]), pack2(acc[0][v][2], acc[0][v][3]),
                      pack2(acc[1][v][0], acc[1][v][1]), pack2(acc[1][v][2], acc[1][v][3]));
}
__device__ __forceinline__ void st_tag(uint4* p, const uint4& v, uint32_t tag) {
  asm volatile("{.reg .b128 r; .reg .b64 a, b; mov.b64 a, {%1,%2}; mov.b64 b, {%3,%4}; mov.b128 r, {a,b}; st.relaxed.gpu.global.b128 [%0], r;}"
               ::"l"(p), "r"((v.x & ~1u) | tag), "r"(v.y), "r"(v.z), "r"(v.w) : "memory");
}
__device__ __forceinline__ uint4 ld_b128(const uint4* p) {
  uint4 v;
  asm volatile("{.reg .b128 r; .reg .b64 a, b; ld.relaxed.gpu.global.b128 r, [%4]; mov.b128 {a,b}, r; mov.b64 {%0,%1}, a; mov.b64 {%2,%3}, b;}"
               : "=r"(v.x), "=r"(v.y), "=r"(v.z), "=r"(v.w) : "l"(p) : "memory");
  return v;
}
template <int STRIDE>
__device__ __forceinline__ void ld_tag4_issue(uint4 (&q)[4], const uint4* p) {
#pragma unroll
  for (int i = 0; i < 4; i++) q[i] = ld_b128(p + i * STRIDE);
}
template <int STRIDE>
__device__ __forceinline__ void ld_tag4_finish(uint4 (&q)[4], const uint4* p, uint32_t tag) {
  int it = 0;
#pragma unroll 1
  while (__any_sync(0xffffffffu, ((q[0].x ^ tag) | (q[1].x ^ tag) | (q[2].x ^ tag) | (q[3].x ^ tag)) & 1u)) {
    ld_tag4_issue<STRIDE>(q, p);
    if (++it > SPIN_LIMIT) { die(); break; }
  }
#pragma unroll
  for (int i = 0; i < 4; i++) asm volatile("and.b32 %0, %0, 0xfffffffe;" : "+r"(q[i].x));
}
__device__ __forceinline__ void row_stats(const uint32_t (&a)[8], const uint32_t (&b)[8], int lane, float (&sum)[2], float (&sq)[2]) {
  float da[4] = {0.f, 0.f, 0.f, 0.f}, db[4] = {0.f, 0.f, 0.f, 0.f}, ds[4] = {0.f, 0.f, 0.f, 0.f};
#pragma unroll
  for (int q = 0; q < 4; q++) {
    mma16816(ds, a[2 * q], b[2 * q], a[2 * q + 1], b[2 * q + 1], 0x3f803f80u, 0x3f803f80u);
    mma16816(da, a[2 * q], b[2 * q], a[2 * q + 1], b[2 * q + 1], a[2 * q], a[2 * q + 1]);
    mma16816(db, a[2 * q], b[2 * q], a[2 * q + 1], b[2 * q + 1], b[2 * q], b[2 * q + 1]);
  }
  const int src = (lane & 28) | (lane >> 3);
  const float qa = __shfl_sync(0xffffffffu, (lane & 4) ? da[1] : da[0], src);
  const float qb = __shfl_sync(0xffffffffu, (lane & 4) ? db[3] : db[2], src);
  float v = (lane & 2) ? ((lane & 1) ? ds[2] : ds[0]) : ((lane & 1) ? qb : qa);
  v += __shfl_xor_sync(0xffffffffu, v, 4);
  v += __shfl_xor_sync(0xffffffffu, v, 8);
  v += __shfl_xor_sync(0xffffffffu, v, 16);
  sq[0] = __shfl_sync(0xffffffffu, v, 0);
  sq[1] = __shfl_sync(0xffffffffu, v, 1);
  sum[0] = __shfl_sync(0xffffffffu, v, 2);
  sum[1] = __shfl_sync(0xffffffffu, v, 3);
}
__device__ __forceinline__ uint64_t desc64(uint32_t lo, uint32_t hi) {
  uint64_t d;
  asm("mov.b64 %0, {%1, %2};" : "=l"(d) : "r"(lo), "r"(hi));
  return d;
}
constexpr uint32_t desc_hi(uint32_t sbo, uint32_t swz) { return (sbo >> 4) | (swz << 30); }
__device__ __forceinline__ uint32_t desc_lo(uint32_t addr, uint32_t lbo) { return ((addr & 0x3FFFF) >> 4) | ((lbo >> 4) << 16); }
__device__ __forceinline__ void cp_async16(uint32_t dst, const void* src) {
  asm volatile("cp.async.cg.shared.global [%0], [%1], 16;" ::"r"(dst), "l"(src) : "memory");
}
__device__ __forceinline__ uint2 lds2(uint32_t a) {
  uint2 v;
  asm volatile("ld.shared.v2.u32 {%0,%1}, [%2];" : "=r"(v.x), "=r"(v.y) : "r"(a) : "memory");
  return v;
}
__device__ __forceinline__ uint32_t lds_u16(uint32_t a) {
  uint16_t v;
  asm volatile("ld.shared.u16 %0, [%1];" : "=h"(v) : "r"(a) : "memory");
  return v;
}
__device__ __forceinline__ void wg_fence() { asm volatile("wgmma.fence.sync.aligned;" ::: "memory"); }
__device__ __forceinline__ void wg_commit() { asm volatile("wgmma.commit_group.sync.aligned;" ::: "memory"); }
template <int N>
__device__ __forceinline__ void wg_wait() { asm volatile("wgmma.wait_group.sync.aligned %0;" ::"n"(N) : "memory"); }
__device__ __forceinline__ void bulk_load(uint32_t dst, const void* src, int bytes, uint32_t bar) {
  asm volatile("cp.async.bulk.shared::cluster.global.mbarrier::complete_tx::bytes [%0], [%1], %2, [%3];"
               ::"r"(dst), "l"(src), "r"(bytes), "r"(bar) : "memory");
}
__device__ __forceinline__ void tma3(uint32_t dst, const CUtensorMap* tm, uint32_t bar, int c0, int c1, int c2) {
  asm volatile("cp.async.bulk.tensor.3d.shared::cluster.global.mbarrier::complete_tx::bytes [%0], [%1, {%3,%4,%5}], [%2];"
               ::"r"(dst), "l"(tm), "r"(bar), "r"(c0), "r"(c1), "r"(c2) : "memory");
}
__device__ __forceinline__ void tma3_mc(uint32_t dst, const CUtensorMap* tm, uint32_t bar, int c1, int c2) {
  asm volatile("cp.async.bulk.tensor.3d.shared::cluster.global.mbarrier::complete_tx::bytes.multicast::cluster [%0], [%1, {%3,%4,%5}], [%2], %6;"
               ::"r"(dst), "l"(tm), "r"(bar), "r"(0), "r"(c1), "r"(c2), "h"((uint16_t)3) : "memory");
}
__device__ __forceinline__ void mbar_arrive_remote(uint32_t rb) {
  asm volatile("mbarrier.arrive.shared::cluster.b64 _, [%0];" ::"r"(rb) : "memory");
}
__device__ __forceinline__ uint4 ldg_ca4(const void* p) {
  uint4 v;
  asm volatile("ld.global.ca.v4.u32 {%0,%1,%2,%3}, [%4];" : "=r"(v.x), "=r"(v.y), "=r"(v.z), "=r"(v.w) : "l"(p) : "memory");
  return v;
}
__device__ __forceinline__ uint32_t clock32() {
  uint32_t v;
  asm volatile("mov.u32 %0, %%clock;" : "=r"(v) :: "memory");
  return v;
}
__device__ __forceinline__ float swiglu(float g, float u, float r) {
  float hg = (0.5f * r) * g, th;
  asm("tanh.approx.f32 %0, %1;" : "=f"(th) : "f"(hg));
  return fmaf(hg, th, hg) * (r * u);
}
__device__ __forceinline__ uint32_t hsub2_bf16(uint32_t a, uint32_t b) {
  uint32_t r;
  asm("sub.rn.bf16x2 %0, %1, %2;" : "=r"(r) : "r"(a), "r"(b));
  return r;
}
__device__ __forceinline__ void l2_prefetch(const void* p, int bytes) {
  asm volatile("cp.async.bulk.prefetch.L2.global [%0], %1;" ::"l"(p), "r"(bytes) : "memory");
}

__device__ __forceinline__ void wgmma_n256(float (&d)[128], uint64_t da, uint64_t db) {
  asm volatile("wgmma.mma_async.sync.aligned.m64n256k16.f32.bf16.bf16 {"
      "%0,%1,%2,%3,%4,%5,%6,%7,%8,%9,%10,%11,%12,%13,%14,%15,"
      "%16,%17,%18,%19,%20,%21,%22,%23,%24,%25,%26,%27,%28,%29,%30,%31,"
      "%32,%33,%34,%35,%36,%37,%38,%39,%40,%41,%42,%43,%44,%45,%46,%47,"
      "%48,%49,%50,%51,%52,%53,%54,%55,%56,%57,%58,%59,%60,%61,%62,%63,"
      "%64,%65,%66,%67,%68,%69,%70,%71,%72,%73,%74,%75,%76,%77,%78,%79,"
      "%80,%81,%82,%83,%84,%85,%86,%87,%88,%89,%90,%91,%92,%93,%94,%95,"
      "%96,%97,%98,%99,%100,%101,%102,%103,%104,%105,%106,%107,%108,%109,%110,%111,"
      "%112,%113,%114,%115,%116,%117,%118,%119,%120,%121,%122,%123,%124,%125,%126,%127"
      "}, %128, %129, 1, 1, 1, 0, 1;\n"
      : "+f"(d[0]),"+f"(d[1]),"+f"(d[2]),"+f"(d[3]),"+f"(d[4]),"+f"(d[5]),"+f"(d[6]),"+f"(d[7]),
        "+f"(d[8]),"+f"(d[9]),"+f"(d[10]),"+f"(d[11]),"+f"(d[12]),"+f"(d[13]),"+f"(d[14]),"+f"(d[15]),
        "+f"(d[16]),"+f"(d[17]),"+f"(d[18]),"+f"(d[19]),"+f"(d[20]),"+f"(d[21]),"+f"(d[22]),"+f"(d[23]),
        "+f"(d[24]),"+f"(d[25]),"+f"(d[26]),"+f"(d[27]),"+f"(d[28]),"+f"(d[29]),"+f"(d[30]),"+f"(d[31]),
        "+f"(d[32]),"+f"(d[33]),"+f"(d[34]),"+f"(d[35]),"+f"(d[36]),"+f"(d[37]),"+f"(d[38]),"+f"(d[39]),
        "+f"(d[40]),"+f"(d[41]),"+f"(d[42]),"+f"(d[43]),"+f"(d[44]),"+f"(d[45]),"+f"(d[46]),"+f"(d[47]),
        "+f"(d[48]),"+f"(d[49]),"+f"(d[50]),"+f"(d[51]),"+f"(d[52]),"+f"(d[53]),"+f"(d[54]),"+f"(d[55]),
        "+f"(d[56]),"+f"(d[57]),"+f"(d[58]),"+f"(d[59]),"+f"(d[60]),"+f"(d[61]),"+f"(d[62]),"+f"(d[63]),
        "+f"(d[64]),"+f"(d[65]),"+f"(d[66]),"+f"(d[67]),"+f"(d[68]),"+f"(d[69]),"+f"(d[70]),"+f"(d[71]),
        "+f"(d[72]),"+f"(d[73]),"+f"(d[74]),"+f"(d[75]),"+f"(d[76]),"+f"(d[77]),"+f"(d[78]),"+f"(d[79]),
        "+f"(d[80]),"+f"(d[81]),"+f"(d[82]),"+f"(d[83]),"+f"(d[84]),"+f"(d[85]),"+f"(d[86]),"+f"(d[87]),
        "+f"(d[88]),"+f"(d[89]),"+f"(d[90]),"+f"(d[91]),"+f"(d[92]),"+f"(d[93]),"+f"(d[94]),"+f"(d[95]),
        "+f"(d[96]),"+f"(d[97]),"+f"(d[98]),"+f"(d[99]),"+f"(d[100]),"+f"(d[101]),"+f"(d[102]),"+f"(d[103]),
        "+f"(d[104]),"+f"(d[105]),"+f"(d[106]),"+f"(d[107]),"+f"(d[108]),"+f"(d[109]),"+f"(d[110]),"+f"(d[111]),
        "+f"(d[112]),"+f"(d[113]),"+f"(d[114]),"+f"(d[115]),"+f"(d[116]),"+f"(d[117]),"+f"(d[118]),"+f"(d[119]),
        "+f"(d[120]),"+f"(d[121]),"+f"(d[122]),"+f"(d[123]),"+f"(d[124]),"+f"(d[125]),"+f"(d[126]),"+f"(d[127])
      : "l"(da), "l"(db));
}
__device__ __forceinline__ void wgmma_n192(float (&d)[96], uint64_t da, uint64_t db) {
  asm volatile("wgmma.mma_async.sync.aligned.m64n192k16.f32.bf16.bf16 {"
      "%0,%1,%2,%3,%4,%5,%6,%7,%8,%9,%10,%11,%12,%13,%14,%15,"
      "%16,%17,%18,%19,%20,%21,%22,%23,%24,%25,%26,%27,%28,%29,%30,%31,"
      "%32,%33,%34,%35,%36,%37,%38,%39,%40,%41,%42,%43,%44,%45,%46,%47,"
      "%48,%49,%50,%51,%52,%53,%54,%55,%56,%57,%58,%59,%60,%61,%62,%63,"
      "%64,%65,%66,%67,%68,%69,%70,%71,%72,%73,%74,%75,%76,%77,%78,%79,"
      "%80,%81,%82,%83,%84,%85,%86,%87,%88,%89,%90,%91,%92,%93,%94,%95"
      "}, %96, %97, 1, 1, 1, 0, 1;\n"
      : "+f"(d[0]),"+f"(d[1]),"+f"(d[2]),"+f"(d[3]),"+f"(d[4]),"+f"(d[5]),"+f"(d[6]),"+f"(d[7]),
        "+f"(d[8]),"+f"(d[9]),"+f"(d[10]),"+f"(d[11]),"+f"(d[12]),"+f"(d[13]),"+f"(d[14]),"+f"(d[15]),
        "+f"(d[16]),"+f"(d[17]),"+f"(d[18]),"+f"(d[19]),"+f"(d[20]),"+f"(d[21]),"+f"(d[22]),"+f"(d[23]),
        "+f"(d[24]),"+f"(d[25]),"+f"(d[26]),"+f"(d[27]),"+f"(d[28]),"+f"(d[29]),"+f"(d[30]),"+f"(d[31]),
        "+f"(d[32]),"+f"(d[33]),"+f"(d[34]),"+f"(d[35]),"+f"(d[36]),"+f"(d[37]),"+f"(d[38]),"+f"(d[39]),
        "+f"(d[40]),"+f"(d[41]),"+f"(d[42]),"+f"(d[43]),"+f"(d[44]),"+f"(d[45]),"+f"(d[46]),"+f"(d[47]),
        "+f"(d[48]),"+f"(d[49]),"+f"(d[50]),"+f"(d[51]),"+f"(d[52]),"+f"(d[53]),"+f"(d[54]),"+f"(d[55]),
        "+f"(d[56]),"+f"(d[57]),"+f"(d[58]),"+f"(d[59]),"+f"(d[60]),"+f"(d[61]),"+f"(d[62]),"+f"(d[63]),
        "+f"(d[64]),"+f"(d[65]),"+f"(d[66]),"+f"(d[67]),"+f"(d[68]),"+f"(d[69]),"+f"(d[70]),"+f"(d[71]),
        "+f"(d[72]),"+f"(d[73]),"+f"(d[74]),"+f"(d[75]),"+f"(d[76]),"+f"(d[77]),"+f"(d[78]),"+f"(d[79]),
        "+f"(d[80]),"+f"(d[81]),"+f"(d[82]),"+f"(d[83]),"+f"(d[84]),"+f"(d[85]),"+f"(d[86]),"+f"(d[87]),
        "+f"(d[88]),"+f"(d[89]),"+f"(d[90]),"+f"(d[91]),"+f"(d[92]),"+f"(d[93]),"+f"(d[94]),"+f"(d[95])
      : "l"(da), "l"(db));
}
__device__ __forceinline__ void wgmma_rs_n128(float (&d)[64], uint32_t a0, uint32_t a1, uint32_t a2, uint32_t a3, uint64_t db) {
  asm volatile("wgmma.mma_async.sync.aligned.m64n128k16.f32.bf16.bf16 {"
      "%0,%1,%2,%3,%4,%5,%6,%7,%8,%9,%10,%11,%12,%13,%14,%15,"
      "%16,%17,%18,%19,%20,%21,%22,%23,%24,%25,%26,%27,%28,%29,%30,%31,"
      "%32,%33,%34,%35,%36,%37,%38,%39,%40,%41,%42,%43,%44,%45,%46,%47,"
      "%48,%49,%50,%51,%52,%53,%54,%55,%56,%57,%58,%59,%60,%61,%62,%63"
      "}, {%64,%65,%66,%67}, %68, 1, 1, 1, 1;\n"
      : "+f"(d[0]),"+f"(d[1]),"+f"(d[2]),"+f"(d[3]),"+f"(d[4]),"+f"(d[5]),"+f"(d[6]),"+f"(d[7]),
        "+f"(d[8]),"+f"(d[9]),"+f"(d[10]),"+f"(d[11]),"+f"(d[12]),"+f"(d[13]),"+f"(d[14]),"+f"(d[15]),
        "+f"(d[16]),"+f"(d[17]),"+f"(d[18]),"+f"(d[19]),"+f"(d[20]),"+f"(d[21]),"+f"(d[22]),"+f"(d[23]),
        "+f"(d[24]),"+f"(d[25]),"+f"(d[26]),"+f"(d[27]),"+f"(d[28]),"+f"(d[29]),"+f"(d[30]),"+f"(d[31]),
        "+f"(d[32]),"+f"(d[33]),"+f"(d[34]),"+f"(d[35]),"+f"(d[36]),"+f"(d[37]),"+f"(d[38]),"+f"(d[39]),
        "+f"(d[40]),"+f"(d[41]),"+f"(d[42]),"+f"(d[43]),"+f"(d[44]),"+f"(d[45]),"+f"(d[46]),"+f"(d[47]),
        "+f"(d[48]),"+f"(d[49]),"+f"(d[50]),"+f"(d[51]),"+f"(d[52]),"+f"(d[53]),"+f"(d[54]),"+f"(d[55]),
        "+f"(d[56]),"+f"(d[57]),"+f"(d[58]),"+f"(d[59]),"+f"(d[60]),"+f"(d[61]),"+f"(d[62]),"+f"(d[63])
      : "r"(a0), "r"(a1), "r"(a2), "r"(a3), "l"(db));
}

constexpr int C_LN = 0, C_PX = 16, C_PY = 32;
constexpr int NB_CONS = 1, NB_LN = 2, NB_LAG = 4, NB_INIT = 6, NB_RDY = 7, NB_PP = 8;
#define LAGX 3
#define LAGY 3
#define LAG2 2
#define NLL 2
#define POLL_DELAY3 900
#define POLL_DELAY 900
#define FILT_DELAY 1000
#define RING_SIG 0
#define PF2_SIG 1
constexpr int SM_E = 0, SM_X = 16384, SM_E2 = 32768, SM_W = 49152, SM_FC = 69632, SM_T = 73728 - T1_BYTES;
constexpr unsigned long long KORDER = 0xBA9432DC876510ull;
constexpr uint32_t HI128 = desc_hi(1024, 1), HI64 = desc_hi(512, 2);

struct Bars {
  uint64_t full1[6], empty1[6], fullA[8], full2[14], empty2[8], xbar, xfree, hbar, tbar, sbar, sig[2], hint[3];
  uint32_t epoch;
};

template <int NK, bool STORE>
__device__ __forceinline__ void make_p(const float (&acc)[NK * 16], float r0, float r1, uint4 (&p)[NK], uint4* pbase, int ks0, uint32_t tag) {
#pragma unroll
  for (int j = 0; j < NK; j++) {
    uint32_t w[4];
#pragma unroll
    for (int i = 0; i < 4; i++) {
      const int a = 8 * j + 2 * i, b = a + NK * 8;
      w[i] = pack2(swiglu(acc[a], acc[b], (i & 1) ? r1 : r0), swiglu(acc[a + 1], acc[b + 1], (i & 1) ? r1 : r0));
    }
    asm volatile("" : "+r"(w[0]), "+r"(w[1]), "+r"(w[2]), "+r"(w[3]));
    p[j] = make_uint4(w[0], w[1], w[2], w[3]);
    if (STORE) st_tag(pbase + ((ks0 + j) >> 2) * 1024 + ((ks0 + j) & 3) * 32, p[j], tag);
  }
}
__device__ __forceinline__ void spin_cycles(uint32_t n) {
  const uint32_t t0 = clock32();
  while (clock32() - t0 < n) {}
}

__global__ void __cluster_dims__(2, 1, 1) __launch_bounds__(NTHREADS, 1)
fused_kernel(const __nv_bfloat16* __restrict__ x, const Tables* __restrict__ tab, Scratch* __restrict__ scr,
             __nv_bfloat16* __restrict__ out, const char* __restrict__ wg_raw, const char* __restrict__ wu_raw,
             const char* __restrict__ wd_raw,
             const __grid_constant__ CUtensorMap tmWR, const __grid_constant__ CUtensorMap tmWI,
             const __grid_constant__ CUtensorMap tmGX, const __grid_constant__ CUtensorMap tmUX,
             const __grid_constant__ CUtensorMap tmGY, const __grid_constant__ CUtensorMap tmUY,
             const __grid_constant__ CUtensorMap tmD) {
  extern __shared__ __align__(1024) char smem_raw[];
  const uint32_t sbase = (s2u(smem_raw) + 1023) & ~1023u;
  const uint32_t sbar = sbase + 14 * SLOT, sstat = sbar + 512;
  const int tid = threadIdx.x, lane = tid & 31;
  const int c = blockIdx.x, kh = c & 1, f = (c >> 1) & 7, rb = 2 * (c >> 4) + kh, rb2 = 2 * (c >> 4) + (f >> 2), nq = f & 3;
#define BAR(field, i) (sbar + (uint32_t)offsetof(Bars, field) + 8u * (i))
#define TOFF(field) (sbase + SM_T + (uint32_t)offsetof(Tables, field) + lane * 16)

  if (tid >= 256) {
    asm volatile("setmaxnreg.dec.sync.aligned.u32 56;");
    const int warp = __shfl_sync(0xffffffffu, tid >> 5, 0);
    if (tid == 256) {
      for (int i = 0; i < 6; i++) { mbar_init(BAR(full1, i), 1); mbar_init(BAR(empty1, i), 16); }
      for (int i = 0; i < 8; i++) { mbar_init(BAR(fullA, i), 1); mbar_init(BAR(empty2, i), 8); }
      for (int i = 0; i < 14; i++) mbar_init(BAR(full2, i), 2);
      mbar_init(BAR(xbar, 0), 1);
      mbar_init(BAR(xfree, 0), 8);
      mbar_init(BAR(tbar, 0), 1);
      mbar_init(BAR(hbar, 0), 1);
      mbar_init(BAR(sbar, 0), 32);
      for (int i = 0; i < 3; i++) mbar_init(BAR(hint, i), 1);
      mbar_init(BAR(sig, 0), 8);
      mbar_init(BAR(sig, 1), 8);
      mbar_expect(BAR(xbar, 0), 16384);
      asm volatile("fence.mbarrier_init.release.cluster;" ::: "memory");
      const int w0 = ((c >> 3) * 257 + 32 * (c & 7) + 1) & ~7;
      if (FILT_DELAY) {
        asm volatile("prefetch.tensormap [%0];" ::"l"(&tmWR) : "memory");
        asm volatile("prefetch.tensormap [%0];" ::"l"(&tmWI) : "memory");
        spin_cycles(FILT_DELAY);
      }
      mbar_expect(BAR(tbar, 0), T2_BYTES + 2 * 10240);
      tma3(sbase + SM_W, &tmWR, BAR(tbar, 0), w0, 0, 0);
      tma3(sbase + SM_W + 10240, &tmWI, BAR(tbar, 0), w0, 0, 0);
      bulk_load(sbase + SM_T + T1_BYTES, reinterpret_cast<const char*>(tab) + T1_BYTES, T2_BYTES, BAR(tbar, 0));
    }
    if (tid == 288) {
      asm volatile("prefetch.tensormap [%0];" ::"l"(kh ? &tmUX : &tmGX) : "memory");
      asm volatile("prefetch.tensormap [%0];" ::"l"(kh ? &tmUY : &tmGY) : "memory");
      asm volatile("prefetch.tensormap [%0];" ::"l"(&tmD) : "memory");
    }
    if (tid == 320) {
      const unsigned e = ld_relaxed(&scr->cnt[(C_LN + rb) * 32]) >> 3;
      asm volatile("st.shared.u32 [%0], %1;" ::"r"(BAR(epoch, 0)), "r"(e) : "memory");
    }
    __syncwarp();
    asm volatile("barrier.cluster.arrive.relaxed.aligned;" ::: "memory");
    bar_arrive(NB_RDY, 384);
    asm volatile("barrier.cluster.wait.aligned;" ::: "memory");
    bar_sync(NB_INIT, 384);
    unsigned epoch;
    asm volatile("ld.shared.u32 %0, [%1];" : "=r"(epoch) : "r"(BAR(epoch, 0)) : "memory");
    if (warp == 8) {
      if (lane == 0) {
        const int ax = (7 * f + 3 * (f & 1)) >> 1;
        const int ay = 7 * f + ((f & 1) ? 0 : 4);
        const CUtensorMap* tx = kh ? &tmUX : &tmGX;
        const CUtensorMap* ty = kh ? &tmUY : &tmGY;
        uint32_t s = 0, ph = 1;
        if (RING_SIG >= 0) mbar_wait(BAR(sig, RING_SIG), 0);
#pragma unroll 1
        for (int n = 0; n < 32; n++) {
          const uint32_t dst = sbase + (8 + s) * SLOT, fb = BAR(full1, s);
          mbar_wait(BAR(empty1, s), ph);
          if (n < 16) {
            mbar_expect(fb, 16384);
            tma3_mc(dst + kh * 8192, tx, fb, n * 32, ax);
          } else {
            mbar_expect(fb, 12288);
            tma3_mc(dst + kh * 6144, ty, fb, (n - 16) * 32, ay);
          }
          if (++s == 6) { s = 0; ph ^= 1; }
        }
      }
    } else if (warp == 9) {
      if (lane == 0) {
        mbar_wait(BAR(empty1, 5), 0);
        mbar_wait(BAR(empty1, 5), 1);
#pragma unroll 1
        for (int i = 0; i < 14; i++) {
          const int kblk = 14 * kh + (int)((KORDER >> (4 * i)) & 15);
          if (i < 8) mbar_wait(BAR(empty1, (17 + 2 * i) % 6), ((17 + 2 * i) / 6) & 1);
          else mbar_wait(BAR(empty2, i - 8), 0);
          mbar_expect(BAR(full2, i), 16384);
          tma3(sbase + (i & 7) * SLOT, &tmD, BAR(full2, i), 0, 64 * kblk, 2 * nq);
        }
        wait_counter(&scr->cnt[(C_LN + rb2) * 32], (epoch + 1) * 8);
        asm volatile("fence.proxy.async.global;" ::: "memory");
        mbar_wait(BAR(empty2, 7), 0);
        mbar_expect(BAR(hbar, 0), 16384);
        bulk_load(sbase + 7 * SLOT, &scr->LN[(rb2 * 8 + 2 * nq) * 1024 + kh * 512], 8192, BAR(hbar, 0));
        bulk_load(sbase + 7 * SLOT + 8192, &scr->LN[(rb2 * 8 + 2 * nq + 1) * 1024 + kh * 512], 8192, BAR(hbar, 0));
      }
    } else if (warp == 10) {
      bar_sync(NB_LN, 288);
      if (lane == 0) {
        PROFP(0);
        red_release(&scr->cnt[(C_LN + rb) * 32]);
        PROFP(1);
        wait_counter(&scr->cnt[(C_LN + rb) * 32], (epoch + 1) * 8);
        asm volatile("fence.proxy.async.global;" ::: "memory");
        PROFP(2);
#pragma unroll 1
        for (int kb = NLL; kb < 8; kb++) {
          mbar_expect(BAR(fullA, kb), 16384);
          bulk_load(sbase + kb * SLOT, &scr->LN[(rb * 8 + kb) * 1024], 16384, BAR(fullA, kb));
        }
#pragma unroll 1
        for (int i = 0; i < 4; i++) mbar_wait(BAR(empty1, 2), i & 1);
        uint32_t d = 2;
#pragma unroll 1
        for (int s = 0; s < 14; s++) {
          const int kblk = 14 * kh + (int)((KORDER >> (4 * s)) & 15);
          if (s == 0 || s == 8 || s == 11) {
            if (s != 11) PROFP(3 + (s >> 2));
            mbar_wait(BAR(hint, s == 0 ? 0 : s == 8 ? 1 : 2), 0);
            if (s != 11) PROFP(4 + (s >> 2));
          }
          if (s < 6) mbar_wait(BAR(empty1, d), s < 4 ? 0 : 1);
          else mbar_wait(BAR(empty2, s - 6), 0);
          mbar_expect(BAR(full2, s), 16384);
          bulk_load(sbase + (8 + d) * SLOT, &scr->P[(rb2 * 28 + kblk) * 1024], 16384, BAR(full2, s));
          if (++d == 6) d = 0;
        }
        PROFP(7);
      }
    } else {
      if (lane == 0) {
        l2_prefetch(wg_raw + (size_t)c * 5376, 5376);
        l2_prefetch(wu_raw + (size_t)c * 5376, 5376);
        mbar_wait(BAR(sig, PF2_SIG), 0);
        l2_prefetch(wg_raw + 688128 + (size_t)c * 8960, 8960);
        l2_prefetch(wu_raw + 688128 + (size_t)c * 8960, 8960);
      }
      mbar_wait(BAR(fullA, 7), 0);
      if (lane == 0) l2_prefetch(wd_raw + (size_t)c * 14336, 14336);
      {
        const uint32_t tag = (epoch + 1) & 1;
        uint4 v0, v1, v2;
        int it = 0;
        while (true) {
          v0 = ld_b128(&scr->ST[rb * 64 + lane]);
          v1 = ld_b128(&scr->ST[rb * 64 + 32 + lane]);
          v2 = ld_b128(&scr->ST[rb2 * 64 + 32 * kh + lane]);
          if (!__any_sync(0xffffffffu, ((v0.x ^ tag) | (v1.x ^ tag) | (v2.x ^ tag)) & 1u)) break;
          if (++it > SPIN_LIMIT) { die(); break; }
        }
        sts4(sstat + lane * 16, v0.x & ~1u, v0.y, v0.z, v0.w);
        sts4(sstat + 512 + lane * 16, v1.x & ~1u, v1.y, v1.z, v1.w);
        sts4(sstat + 1024 + lane * 16, v2.x & ~1u, v2.y, v2.z, v2.w);
        mbar_arrive(BAR(sbar, 0));
      }
      if (lane == 0) {
        mbar_wait(BAR(empty1, 5), 0);
        mbar_wait(BAR(empty1, 5), 1);
        mbar_wait(BAR(empty1, 5), 0);
#pragma unroll 1
        for (int e = 0; e < 3; e++) {
          const unsigned* cp = e == 0 ? &scr->cnt[(C_PX + rb2) * 32] : &scr->cnt[(C_PY + rb2) * 32 + 2 * kh + e - 1];
          if (e == 1) mbar_wait(BAR(full2, 0), 0);
          int it = 0;
          while ((int)(ld_relaxed(cp) - (epoch + 1) * (e == 0 ? 64 : 16)) < 0)
            if (++it > SPIN_LIMIT) { die(); break; }
          mbar_arrive(BAR(hint, e));
        }
      }
    }
  } else {
    const int warp = __shfl_sync(0xffffffffu, tid >> 5, 0);
    const int g = lane >> 2, t = lane & 3;
    PROF(0);
    PROFG(14);
#pragma unroll
    for (int i = 0; i < 4; i++) {
      const int r = i >> 1, ch = (i & 1) * 32 + lane;
      cp_async16(sbase + SM_X + (2 * warp + r) * 1024 + ((ch ^ ((ch >> 2) & 6)) * 16),
                 x + (size_t)(c + 128 * (2 * warp + r)) * 512 + ch * 8);
    }
    asm volatile("cp.async.commit_group;" ::: "memory");
    asm volatile("barrier.cluster.arrive.relaxed.aligned;" ::: "memory");
    uint4 tw[8], fb[16];
    const uint4 fa = ldg_ca4(&tab->fa[lane][0]);
#pragma unroll
    for (int i = 0; i < 8; i++) tw[i] = ldg_ca4(&tab->tw1[i][lane][0]);
#pragma unroll
    for (int i = 0; i < 16; i++) fb[i] = ldg_ca4(&tab->fb[i][lane][0]);
    uint32_t rbar;
    asm volatile("mapa.shared::cluster.u32 %0, %1, %2;" : "=r"(rbar) : "r"(sbar), "r"(kh ^ 1));
#define RBAR(field, i) (rbar + (uint32_t)offsetof(Bars, field) + 8u * (i))
    {
      const int ln = (tid >> 1) & 31, lg = ln >> 2, lt = ln & 3, i = 4 * (tid >> 6) + 2 * (tid & 1);
      const int kidx = lt + 8 * (i >> 3), nidx = 4 * ((i >> 1) & 3) + (lg >> 1);
      const uint32_t a0 = cfrag<2048>((c + 128 * kidx) * nidx, lg & 1), a1 = cfrag<2048>((c + 128 * (kidx + 4)) * nidx, lg & 1);
      const uint32_t b0 = cfrag<2048>(-(c + 128 * nidx) * kidx, lg & 1), b1 = cfrag<2048>(-(c + 128 * nidx) * (kidx + 4), lg & 1);
      asm volatile("st.shared.v2.u32 [%0], {%1,%2};" ::"r"(sbase + SM_FC + tid * 8), "r"(a0), "r"(a1) : "memory");
      asm volatile("st.shared.v2.u32 [%0], {%1,%2};" ::"r"(sbase + SM_FC + 2048 + tid * 8), "r"(b0), "r"(b1) : "memory");
    }
    asm volatile("cp.async.wait_group 0;" ::: "memory");
    __syncwarp();
    bar_arrive(NB_INIT, 384);
    PROF(13);
    uint32_t tag;
    uint4 q[4], o[4];
    {
      uint32_t v[2][8];
#pragma unroll
      for (int r = 0; r < 2; r++)
#pragma unroll
        for (int q = 0; q < 4; q++) {
          const uint2 u = lds2(sbase + SM_X + (2 * warp + r) * 1024 + (t + 4 * (q >> 1)) * 128 + (((4 * (q & 1) + (g >> 1)) ^ (2 * t)) * 16) + (g & 1) * 8);
          v[r][2 * q] = u.x; v[r][2 * q + 1] = u.y;
        }
      float sum[2], sq[2], rstd[2];
      row_stats(v[0], v[1], lane, sum, sq);
#pragma unroll
      for (int r = 0; r < 2; r++) {
        const float m = sum[r] * (1.f / 512.f);
        rstd[r] = rsqrtf(fmaxf(fmaf(-m, m, sq[r] * (1.f / 512.f)), 0.f) + 1e-5f);
      }
      uint32_t alo[4][4], ahi[4][4];
#pragma unroll
      for (int r = 0; r < 2; r++)
#pragma unroll
        for (int i = 0; i < 4; i++) {
          const uint32_t sel = (i & 1) ? 0x7632u : 0x5410u;
          const uint32_t b0 = __byte_perm(v[r][i >> 1], v[r][2 + (i >> 1)], sel);
          const uint32_t b1 = __byte_perm(v[r][4 + (i >> 1)], v[r][6 + (i >> 1)], sel);
          float d[4] = {0.f, 0.f, 0.f, 0.f};
          mma16816(d, fa.x, fa.y, fa.z, fa.w, b0, b1);
          const uint4 &ka = tw[2 * i], &kb = tw[2 * i + 1];
          const uint32_t re = pack2(d[0] * __uint_as_float(ka.x) + d[2] * __uint_as_float(ka.y), d[1] * __uint_as_float(kb.x) + d[3] * __uint_as_float(kb.y));
          const uint32_t im = pack2(d[0] * __uint_as_float(ka.z) + d[2] * __uint_as_float(ka.w), d[1] * __uint_as_float(kb.z) + d[3] * __uint_as_float(kb.w));
          const uint32_t dc = pack2(fmaf(sum[r], -1.f / 32.f, d[0]), fmaf(sum[r], -1.f / 32.f, d[1]));
          alo[i][r] = re; alo[i][2 + r] = im;
          ahi[i][r] = g == 0 ? dc : re; ahi[i][2 + r] = g == 0 ? 0u : im;
        }
      float acc[8][4];
#pragma unroll
      for (int u = 0; u < 8; u++) {
        acc[u][0] = acc[u][1] = acc[u][2] = acc[u][3] = 0.f;
#pragma unroll
        for (int i = 0; i < 4; i++) {
          const uint4& bq = fb[i * 4 + (u >> 1)];
          if (u < 4) mma16816(acc[u], alo[i][0], alo[i][1], alo[i][2], alo[i][3], (u & 1) ? bq.z : bq.x, (u & 1) ? bq.w : bq.y);
          else       mma16816(acc[u], ahi[i][0], ahi[i][1], ahi[i][2], ahi[i][3], (u & 1) ? bq.z : bq.x, (u & 1) ? bq.w : bq.y);
        }
      }
#pragma unroll
      for (int r = 0; r < 2; r++)
#pragma unroll
        for (int h = 0; h < 2; h++) {
          const int j = 2 * warp + r, m = 2 * t + h;
          const float rs = rstd[r];
          sts4(sbase + SM_E + ((j * 8 + m) * 8 + (g ^ (2 * t) ^ (2 * (j & 3)))) * 16,
               pack2(acc[2 * h][2 * r] * rs, acc[2 * h][2 * r + 1] * rs), pack2(acc[2 * h + 1][2 * r] * rs, acc[2 * h + 1][2 * r + 1] * rs),
               pack2(acc[4 + 2 * h][2 * r] * rs, acc[4 + 2 * h][2 * r + 1] * rs), pack2(acc[5 + 2 * h][2 * r] * rs, acc[5 + 2 * h][2 * r + 1] * rs));
        }
      if (tid == 0) PROFP(12);
      bar_sync(NB_RDY, 384);
      if (tid == 0) PROFP(13);
      uint4 fc[4];
#pragma unroll
      for (int i = 0; i < 4; i++) fc[i] = lds4(sbase + SM_FC + i * 512 + lane * 16);
      asm volatile("ld.shared.u32 %0, [%1];" : "=r"(tag) : "r"(BAR(epoch, 0)) : "memory");
      tag = (tag + 1) & 1;
#pragma unroll
      for (int i = 0; i < 4; i++) q[i] = lds4(sbase + SM_E + (((t + 4 * i) * 8 + warp) * 8 + (g ^ (warp & 6) ^ (2 * t))) * 16);
      cdft16(q, fc, o);
#pragma unroll
      for (int vv = 0; vv < 4; vv++) st_tag(&scr->Z1[(((4 * vv + t) * 8 + warp) * 128 + c) * 8 + g], o[vv], tag);
    }
    PROF(1);
    {
      const uint4* const zp = &scr->Z1[(c * 128 + 8 * t + warp) * 8 + g];
      const uint32_t tst = clock32();
      mbar_wait(BAR(tbar, 0), 0);
      if (tid == 0) PROFP(14);
      uint4 f2[4], g2[4];
#pragma unroll
      for (int i = 0; i < 4; i++) {
        f2[i] = lds4(TOFF(f2) + warp * 2048 + i * 512);
        g2[i] = lds4(TOFF(g2) + warp * 2048 + i * 512);
      }
      const uint4 f8 = lds4(TOFF(f8)), g8 = lds4(TOFF(g8));
      float wfr[16], wfi[16];
      {
        const float fsc = 1.f / (1 << 19);
        const float fsc3 = ((c & 7) == 7 && g == 0) ? 0.5f * fsc : fsc;
        const int gg = g == 0 ? 8 : g, wsh = (2 * (c >> 3) + 2) & 15;
#pragma unroll
        for (int i = 0; i < 16; i++) {
          const int ci = i >> 3, dd = (i >> 2) & 1, e = i & 3;
          const int kk = (e == 0 ? gg : e == 1 ? 16 + gg : e == 2 ? 16 - g : 32 - g) - 1;
          const uint32_t a = sbase + SM_W + ((2 * warp + ci) * 8 + t + 4 * dd) * 80 + wsh + 2 * kk;
          wfr[i] = bf_lo(lds_u16(a)) * (e == 3 ? fsc3 : fsc);
          wfi[i] = bf_lo(lds_u16(a + 10240)) * (e == 3 ? fsc3 : fsc);
        }
      }
      asm volatile("barrier.cluster.wait.aligned;" ::: "memory");
      PROF(2);
      while (clock32() - tst < POLL_DELAY) {}
      ld_tag4_issue<256>(q, zp);
      ld_tag4_finish<256>(q, zp, tag);
      if (tid == 0) PROFP(30);
      if (lane == 0) mbar_arrive(BAR(sig, 0));
      cdft16(q, f2, o);
      const uint32_t e2 = sbase + SM_E2;
#pragma unroll
      for (int vv = 0; vv < 4; vv++)
        sts4(e2 + ((warp * 16 + 4 * vv + t) * 8 + (g ^ (2 * t) ^ (2 * (warp & 3)))) * 16, o[vv].x, o[vv].y, o[vv].z, o[vv].w);
      bar_sync(NB_CONS, 256);
#pragma unroll
      for (int ci = 0; ci < 2; ci++) {
        const int cc = 2 * warp + ci;
        uint32_t ad[2];
        uint4 u[2];
#pragma unroll
        for (int hh = 0; hh < 2; hh++) {
          ad[hh] = e2 + (((t + 4 * hh) * 16 + cc) * 8 + (g ^ (2 * (cc & 3)) ^ (2 * t))) * 16;
          u[hh] = lds4(ad[hh]);
        }
        uint32_t res[2][4];
#pragma unroll
        for (int p = 0; p < 2; p++) {
          uint32_t y[2][2];
#pragma unroll
          for (int vv = 0; vv < 2; vv++) {
            float d[4] = {0.f, 0.f, 0.f, 0.f};
            mma16816(d, word(u[0], 2 * p), word(u[0], 2 * p + 1), word(u[1], 2 * p), word(u[1], 2 * p + 1), word(f8, 2 * vv), word(f8, 2 * vv + 1));
#pragma unroll
            for (int rr = 0; rr < 2; rr++) {
              const float fr = wfr[ci * 8 + vv * 4 + 2 * p + rr], fi = wfi[ci * 8 + vv * 4 + 2 * p + rr];
              y[vv][rr] = pack2(d[2 * rr] * fr - d[2 * rr + 1] * fi, d[2 * rr] * fi + d[2 * rr + 1] * fr);
            }
          }
#pragma unroll
          for (int vv = 0; vv < 2; vv++) {
            float d[4] = {0.f, 0.f, 0.f, 0.f};
            mma16816(d, y[0][0], y[0][1], y[1][0], y[1][1], word(g8, 2 * vv), word(g8, 2 * vv + 1));
            res[vv][2 * p] = pack2(d[0], d[1]);
            res[vv][2 * p + 1] = pack2(d[2], d[3]);
          }
        }
#pragma unroll
        for (int vv = 0; vv < 2; vv++) sts4(ad[vv], res[vv][0], res[vv][1], res[vv][2], res[vv][3]);
      }
      bar_sync(NB_CONS, 256);
#pragma unroll
      for (int i = 0; i < 4; i++) q[i] = lds4(e2 + ((warp * 16 + 4 * i + t) * 8 + (g ^ (2 * t) ^ (2 * (warp & 3)))) * 16);
      cdft16(q, g2, o);
#pragma unroll
      for (int vv = 0; vv < 4; vv++) st_tag(&scr->Z2[((8 * (4 * vv + t) + warp) * 128 + c) * 8 + g], o[vv], tag);
    }
    PROF(3);
    {
      const uint4* const zp = &scr->Z2[((c * 16 + t) * 8 + warp) * 8 + g];
      const uint32_t tst = clock32();
      uint4 gb[16], gc[4], tw[4], xr[2][2];
#pragma unroll
      for (int i = 0; i < 16; i++) gb[i] = lds4(TOFF(gb) + i * 512);
      const uint4 ga = lds4(TOFF(ga));
#pragma unroll
      for (int i = 0; i < 4; i++) {
        gc[i] = lds4(sbase + SM_FC + 2048 + i * 512 + lane * 16);
        tw[i] = lds4(TOFF(tw3) + i * 512);
        const int ch = 4 * (g + 8 * (i & 1)) + t;
        xr[i >> 1][i & 1] = lds4(sbase + SM_X + (2 * warp + (i >> 1)) * 1024 + ((ch ^ ((ch >> 2) & 6)) * 16));
      }
      PROF(4);
      while (clock32() - tst < POLL_DELAY) {}
      ld_tag4_issue<256>(q, zp);
      ld_tag4_finish<256>(q, zp, tag);
      if (tid == 0) PROFP(31);
      if (lane == 0) mbar_arrive(BAR(sig, 1));
      cdft16(q, gc, o);
#pragma unroll
      for (int vv = 0; vv < 4; vv++)
        sts4(sbase + SM_E + (((4 * vv + t) * 8 + warp) * 8 + (g ^ (warp & 6) ^ (2 * t))) * 16, o[vv].x, o[vv].y, o[vv].z, o[vv].w);
      bar_sync(NB_CONS, 256);
      uint32_t hv[2][8];
      const float mk = t == 0 ? 0.f : 1.f;
#pragma unroll
      for (int r = 0; r < 2; r++) {
        const int j = 2 * warp + r;
        uint4 u[2];
#pragma unroll
        for (int h = 0; h < 2; h++) u[h] = lds4(sbase + SM_E + ((j * 8 + 2 * t + h) * 8 + (g ^ (2 * t) ^ (2 * (j & 3)))) * 16);
        float yv[4][4];
#pragma unroll
        for (int i = 0; i < 4; i++) {
          float lo[4] = {0.f, 0.f, 0.f, 0.f}, hi[4] = {0.f, 0.f, 0.f, 0.f};
          mma16816(lo, gb[i * 4].x, gb[i * 4].y, gb[i * 4].z, gb[i * 4].w, u[0].x, u[0].y);
          mma16816(lo, gb[i * 4 + 1].x, gb[i * 4 + 1].y, gb[i * 4 + 1].z, gb[i * 4 + 1].w, u[1].x, u[1].y);
          mma16816(hi, gb[i * 4 + 2].x, gb[i * 4 + 2].y, gb[i * 4 + 2].z, gb[i * 4 + 2].w, u[0].z, u[0].w);
          mma16816(hi, gb[i * 4 + 3].x, gb[i * 4 + 3].y, gb[i * 4 + 3].z, gb[i * 4 + 3].w, u[1].z, u[1].w);
          const float ca = __uint_as_float(tw[i].x), sa = __uint_as_float(tw[i].y), cb = __uint_as_float(tw[i].z), sb = __uint_as_float(tw[i].w);
          const float tr0 = fmaf(hi[0], mk, lo[0]), ti0 = fmaf(hi[2], mk, lo[2]);
          const float tr1 = lo[1] + hi[1], ti1 = lo[3] + hi[3];
          const float vr0 = tr0 * ca - ti0 * sa, vi0 = tr0 * sa + ti0 * ca;
          const float vr1 = tr1 * cb - ti1 * sb, vi1 = tr1 * sb + ti1 * cb;
          const uint32_t b0 = pack2(t == 0 ? hi[0] : vr0, vr1), b1 = pack2(t == 0 ? vr0 : vi0, vi1);
          yv[i][0] = yv[i][1] = yv[i][2] = yv[i][3] = 0.f;
          mma16816(yv[i], ga.x, ga.y, ga.z, ga.w, b0, b1);
        }
#pragma unroll
        for (int h = 0; h < 2; h++) {
          hv[r][4 * h + 0] = hadd2_bf16(xr[r][h].x, pack2(yv[0][2 * h], yv[1][2 * h]));
          hv[r][4 * h + 1] = hadd2_bf16(xr[r][h].y, pack2(yv[2][2 * h], yv[3][2 * h]));
          hv[r][4 * h + 2] = hadd2_bf16(xr[r][h].z, pack2(yv[0][2 * h + 1], yv[1][2 * h + 1]));
          hv[r][4 * h + 3] = hadd2_bf16(xr[r][h].w, pack2(yv[2][2 * h + 1], yv[3][2 * h + 1]));
        }
      }
      float ds[4] = {0.f, 0.f, 0.f, 0.f};
#pragma unroll
      for (int q4 = 0; q4 < 4; q4++) mma16816(ds, hv[0][2 * q4], hv[1][2 * q4], hv[0][2 * q4 + 1], hv[1][2 * q4 + 1], 0x3f803f80u, 0x3f803f80u);
#pragma unroll
      for (int o2 = 4; o2 <= 16; o2 <<= 1) {
        ds[0] += __shfl_xor_sync(0xffffffffu, ds[0], o2);
        ds[2] += __shfl_xor_sync(0xffffffffu, ds[2], o2);
      }
      uint32_t mb[2];
#pragma unroll
      for (int r = 0; r < 2; r++) {
        const int row = 16 * f + 2 * warp + r;
        mb[r] = pack2(ds[2 * r] * (1.f / 512.f), ds[2 * r] * (1.f / 512.f));
#pragma unroll
        for (int i = 0; i < 8; i++) hv[r][i] = hsub2_bf16(hv[r][i], mb[r]);
#pragma unroll
        for (int h = 0; h < 2; h++) {
          const int n1 = g + 8 * h;
          st_tag(&scr->LN[(rb * 8 + (n1 >> 1)) * 1024 + row * 8 + ((4 * (n1 & 1) + t) ^ (row & 7))],
                 make_uint4(hv[r][4 * h], hv[r][4 * h + 1], hv[r][4 * h + 2], hv[r][4 * h + 3]), n1 < 2 * NLL ? tag : (hv[r][4 * h] & 1u));
        }
      }
      bar_arrive(NB_LN, 288);
      float sum[2], sq[2], rstd[2];
      row_stats(hv[0], hv[1], lane, sum, sq);
#pragma unroll
      for (int r = 0; r < 2; r++) {
        const float m = sum[r] * (1.f / 512.f);
        rstd[r] = rsqrtf(fmaxf(fmaf(-m, m, sq[r] * (1.f / 512.f)), 0.f) + 1e-5f);
      }
      if (lane == 0)
        st_tag(&scr->ST[rb * 64 + 8 * f + warp], make_uint4(mb[0] << 16, __float_as_uint(rstd[0]), mb[1] << 16, __float_as_uint(rstd[1])), tag);
    }
    PROF(5);
    asm volatile("setmaxnreg.inc.sync.aligned.u32 224;");
    if (NLL) {
      const uint4* const ap = &scr->LN[rb * 8 * 1024 + tid];
      uint4 av[NLL ? NLL : 1][4];
      spin_cycles(POLL_DELAY3);
#pragma unroll
      for (int kb = 0; kb < NLL; kb++) ld_tag4_issue<256>(av[kb], ap + kb * 1024);
      bar_sync(NB_CONS, 256);
#pragma unroll
      for (int kb = 0; kb < NLL; kb++) {
        ld_tag4_finish<256>(av[kb], ap + kb * 1024, tag);
#pragma unroll
        for (int i = 0; i < 4; i++) sts4(sbase + kb * SLOT + (tid + 256 * i) * 16, av[kb][i].x, av[kb][i].y, av[kb][i].z, av[kb][i].w);
      }
      asm volatile("fence.proxy.async.shared::cta;" ::: "memory");
      bar_sync(NB_CONS, 256);
    }
    const int wgi = warp >> 2, wq = warp & 3;
    uint4* const pbase = &scr->P[rb * 28 * 1024 + warp * 128 + lane];
    const uint32_t a_lo0 = desc_lo(sbase + wgi * 8192, 16);
    const uint32_t ebar = lane == 0 ? BAR(empty1, 0) : RBAR(empty1, 0);
    float r0, r1;
    uint4 px[8], py[6];
    const int rh = wgi ^ kh ^ 1;
    const uint4* const psrc = &scr->P[(rb2 * 28 + 14 * kh) * 1024 + (4 * rh + wq) * 128 + lane];
    {
      float acc[128];
#pragma unroll
      for (int i = 0; i < 128; i++) acc[i] = 0.f;
      const uint32_t b_lo0 = desc_lo(sbase + 8 * SLOT, 4096);
      uint32_t slot = 0, ph = 0, prev = 0;
#pragma unroll 1
      for (int kb = 0; kb < 8; kb++) {
        if (kb >= NLL) mbar_wait(BAR(fullA, kb), 0);
        if (kb == 0) PROF(6);
#pragma unroll
        for (int hh = 0; hh < 2; hh++) {
          if (LAGX && hh == ((16 - LAGX) & 1) && kb == ((16 - LAGX) >> 1) && wgi == 1) bar_sync(NB_LAG, 256);
          mbar_wait(BAR(full1, slot), ph);
          const uint32_t al = a_lo0 + kb * 1024 + hh * 4, bl = b_lo0 + slot * 1024;
          wg_fence();
          wgmma_n256(acc, desc64(al, HI128), desc64(bl, HI128));
          wgmma_n256(acc, desc64(al + 2, HI128), desc64(bl + 128, HI128));
          wg_commit();
          if (LAGX && hh == 1 && kb == 7 && wgi == 0) bar_arrive(NB_LAG, 256);
          wg_wait<1>();
          if ((kb | hh) != 0 && lane < 2) mbar_arrive_remote(ebar + 8 * prev);
          prev = slot;
          if (++slot == 6) { slot = 0; ph ^= 1; }
        }
      }
      mbar_wait(BAR(sbar, 0), 0);
      r0 = __uint_as_float(lds2(sstat + (16 * warp + g) * 8).y);
      r1 = __uint_as_float(lds2(sstat + (16 * warp + g + 8) * 8).y);
      wg_wait<0>();
      if (lane < 2) mbar_arrive_remote(ebar + 8 * prev);
      PROF(7);
      make_p<8, false>(acc, r0, r1, px, pbase, 0, tag);
    }
    PROF(8);
    {
      float acc[96];
#pragma unroll
      for (int i = 0; i < 96; i++) acc[i] = 0.f;
      const uint32_t b_lo0 = desc_lo(sbase + 8 * SLOT, 2048);
      uint4* const pdst = pbase + ((7 * f + 3 * (f & 1)) >> 1) * 1024;
      auto stage_y = [&](int k, uint32_t slot, uint32_t ph) {
        if (LAGY && k == 16 - LAGY && wgi == 1) bar_sync(NB_LAG, 256);
        mbar_wait(BAR(full1, slot), ph);
        const uint32_t al = a_lo0 + (k >> 1) * 1024 + (k & 1) * 4, bl = b_lo0 + slot * 1024;
        wg_fence();
        wgmma_n192(acc, desc64(al, HI128), desc64(bl, HI64));
        wgmma_n192(acc, desc64(al + 2, HI128), desc64(bl + 64, HI64));
        wg_commit();
      };
#pragma unroll
      for (int k = 0; k < 4; k++) {
        stage_y(k, (16 + k) % 6, ((16 + k) / 6) & 1);
        st_tag(pdst + (k >> 1) * 1024 + (k & 1) * 64, px[2 * k], tag);
        st_tag(pdst + (k >> 1) * 1024 + (k & 1) * 64 + 32, px[2 * k + 1], tag);
        if (k == 3 && lane == 0) red_relaxed(&scr->cnt[(C_PX + rb) * 32]);
        wg_wait<1>();
        if (k != 0 && lane < 2) mbar_arrive_remote(ebar + 8 * ((15 + k) % 6));
      }
      uint32_t slot = 2, ph = 1, prev = 1;
#pragma unroll 1
      for (int k = 4; k < 16; k++) {
        stage_y(k, slot, ph);
        if (LAGY && k == 15 && wgi == 0) bar_arrive(NB_LAG, 256);
        wg_wait<1>();
        if (lane < 2) mbar_arrive_remote(ebar + 8 * prev);
        prev = slot;
        if (++slot == 6) { slot = 0; ph ^= 1; }
      }
      wg_wait<0>();
      if (lane < 2) mbar_arrive_remote(ebar + 8 * (31 % 6));
      PROF(9);
      make_p<6, true>(acc, r0, r1, py, pbase, 14 * f + ((f & 1) ? 0 : 8), tag);
      if (lane == 0) red_relaxed(&scr->cnt[(C_PY + rb) * 32 + (f >> 1)]);
    }
    PROF(10);
    {
      float acc[64];
      {
        const float m0 = wgi ? __uint_as_float(lds2(sstat + 1024 + (16 * wq + g) * 8).x) : 0.f;
        const float m1 = wgi ? __uint_as_float(lds2(sstat + 1024 + (16 * wq + g + 8) * 8).x) : 0.f;
#pragma unroll
        for (int i = 0; i < 64; i++) acc[i] = (i & 2) ? m1 : m0;
      }
      const uint32_t b2_lo0 = desc_lo(sbase, 8192);
      const uint32_t pa0 = sbase + 8 * SLOT + (4 * rh + wq) * 2048 + lane * 16;
      uint32_t slot = 2;
      auto stage2 = [&](int s) {
        uint4 a[4];
        mbar_wait(BAR(full2, s), 0);
        if (tid == 0) PROFP(16 + s);
#pragma unroll
        for (int kk = 0; kk < 4; kk++) a[kk] = lds4(pa0 + slot * SLOT + kk * 512);
        ld_tag4_finish<32>(a, psrc + (int)((KORDER >> (4 * s)) & 15) * 1024, tag);
        const uint32_t bl = b2_lo0 + (s & 7) * 1024;
        if (wgi ? s <= 14 - LAG2 : s >= LAG2) bar_sync(NB_PP + wgi, 256);
        wg_fence();
#pragma unroll
        for (int kk = 0; kk < 4; kk++) wgmma_rs_n128(acc, a[kk].x, a[kk].y, a[kk].z, a[kk].w, desc64(bl + kk * 128, HI128));
        wg_commit();
        if (wgi ? s <= 13 - LAG2 : s >= LAG2 - 1) bar_arrive(NB_PP + (wgi ^ 1), 256);
        if (++slot == 6) slot = 0;
        wg_wait<1>();
        if (s >= 1 && s <= 8 && lane == 0) {
          mbar_arrive(BAR(empty2, s - 1));
          if (s == 8) mbar_arrive_remote(RBAR(xfree, 0));
        }
      };
#pragma unroll 1
      for (int s = 0; s < 14; s += 2) {
        stage2(s);
        stage2(s + 1);
      }
      uint4 hres[2][4];
      mbar_wait(BAR(hbar, 0), 0);
#pragma unroll
      for (int h = 0; h < 2; h++)
#pragma unroll
        for (int q = 0; q < 4; q++) {
          hres[h][q] = lds4(sbase + 7 * SLOT + (q >> 1) * 8192 + (16 * wq + g + 8 * h) * 128 + (((4 * (q & 1) + t) ^ g) * 16));
          if (2 * nq + (q >> 1) < NLL) hres[h][q].x &= ~1u;
        }
      wg_wait<0>();
      PROF(11);
      const uint32_t xbuf = sbase + 6 * SLOT + (tid & 127) * 16;
      if (wgi == 0) {
        uint32_t rbuf;
        mbar_wait(BAR(xfree, 0), 0);
        asm volatile("mapa.shared::cluster.u32 %0, %1, %2;" : "=r"(rbuf) : "r"(xbuf), "r"(kh ^ 1));
#pragma unroll
        for (int i = 0; i < 8; i++)
          asm volatile("st.async.weak.shared::cluster.mbarrier::complete_tx::bytes.v4.b32 [%0], {%1,%2,%3,%4}, [%5];"
                       ::"r"(rbuf + i * 2048), "r"(pack2(acc[8 * i], acc[8 * i + 1])), "r"(pack2(acc[8 * i + 2], acc[8 * i + 3])),
                         "r"(pack2(acc[8 * i + 4], acc[8 * i + 5])), "r"(pack2(acc[8 * i + 6], acc[8 * i + 7])), "r"(RBAR(xbar, 0))
                       : "memory");
      } else {
        mbar_wait_cluster(BAR(xbar, 0), 0);
      }
      uint32_t w[2][16];
#pragma unroll
      for (int i = 0; i < 8; i++) {
        const uint4 pv = lds4(xbuf + i * 2048);
        w[0][2 * i] = pack2(acc[8 * i] + bf_lo(pv.x), acc[8 * i + 1] + bf_hi(pv.x));
        w[1][2 * i] = pack2(acc[8 * i + 2] + bf_lo(pv.y), acc[8 * i + 3] + bf_hi(pv.y));
        w[0][2 * i + 1] = pack2(acc[8 * i + 4] + bf_lo(pv.z), acc[8 * i + 5] + bf_hi(pv.z));
        w[1][2 * i + 1] = pack2(acc[8 * i + 6] + bf_lo(pv.w), acc[8 * i + 7] + bf_hi(pv.w));
      }
      uint4* const o4 = reinterpret_cast<uint4*>(out) + (16 * (c >> 4) + 2 * (4 * rh + wq) + (rb2 & 1) + 128 * g) * 64 + nq * 16 + t;
#pragma unroll
      for (int h = 0; h < 2; h++)
#pragma unroll
        for (int q = 0; q < 4; q++) {
          uint32_t a0 = w[h][4 * q], a1 = w[h][4 * q + 1], a2 = w[h][4 * q + 2], a3 = w[h][4 * q + 3];
          {
            const bool od = t & 1;
            uint32_t s0 = od ? a0 : a1, s1 = od ? a2 : a3;
            s0 = __shfl_xor_sync(0xffffffffu, s0, 1); s1 = __shfl_xor_sync(0xffffffffu, s1, 1);
            if (od) { a0 = s0; a2 = s1; } else { a1 = s0; a3 = s1; }
          }
          {
            const bool up = t & 2;
            uint32_t s0 = up ? a0 : a2, s1 = up ? a1 : a3;
            s0 = __shfl_xor_sync(0xffffffffu, s0, 2); s1 = __shfl_xor_sync(0xffffffffu, s1, 2);
            if (up) { a0 = s0; a1 = s1; } else { a2 = s0; a3 = s1; }
          }
          if (wgi == 1)
            o4[h * 1024 * 64 + 4 * q] =
                make_uint4(hadd2_bf16(hres[h][q].x, a0), hadd2_bf16(hres[h][q].y, a1), hadd2_bf16(hres[h][q].z, a2), hadd2_bf16(hres[h][q].w, a3));
        }
      PROF(12);
      PROFG(15);
    }
  }
#undef BAR
#undef TOFF
#undef RBAR
}

typedef CUresult (*EncodeFn)(CUtensorMap*, CUtensorMapDataType, cuuint32_t, void*, const cuuint64_t*, const cuuint64_t*,
                             const cuuint32_t*, const cuuint32_t*, CUtensorMapInterleave, CUtensorMapSwizzle,
                             CUtensorMapL2promotion, CUtensorMapFloatOOBfill);

}

extern "C" void kernel_launch(void* const* d_in, const int* in_sizes, int n_in, void* d_out, int out_size) {
  (void)in_sizes; (void)n_in; (void)out_size;
  static EncodeFn encode = nullptr;
  static void *tab = nullptr, *scr = nullptr;
  if (!encode) {
    void* fn = nullptr;
    cudaDriverEntryPointQueryResult qr;
    cudaGetDriverEntryPoint("cuTensorMapEncodeTiled", &fn, cudaEnableDefault, &qr);
    encode = (EncodeFn)fn;
    cudaGetSymbolAddress(&tab, g_tab);
    cudaGetSymbolAddress(&scr, g_scr);
    cudaFuncSetAttribute(fused_kernel, cudaFuncAttributeMaxDynamicSharedMemorySize, SMEM_BYTES);
  }
  CUtensorMap tmGX, tmUX, tmGY, tmUY, tmD, tmWR, tmWI;
  const cuuint32_t es[5] = {1, 1, 1, 1, 1};
  auto enc = [&](CUtensorMap* m, void* p, int rank, const cuuint64_t* gd, const cuuint64_t* gs, const cuuint32_t* bd,
                 CUtensorMapSwizzle sw, CUtensorMapL2promotion pr) {
    encode(m, CU_TENSOR_MAP_DATA_TYPE_BFLOAT16, rank, p, gd, gs, bd, es, CU_TENSOR_MAP_INTERLEAVE_NONE, sw, pr,
           CU_TENSOR_MAP_FLOAT_OOB_FILL_NONE);
  };
  {
    const cuuint64_t gd[3] = {64, 512, 28}, gs[2] = {3584, 128};
    const cuuint32_t bd[3] = {64, 32, 2};
    enc(&tmGX, d_in[4], 3, gd, gs, bd, CU_TENSOR_MAP_SWIZZLE_128B, CU_TENSOR_MAP_L2_PROMOTION_L2_256B);
    enc(&tmUX, d_in[5], 3, gd, gs, bd, CU_TENSOR_MAP_SWIZZLE_128B, CU_TENSOR_MAP_L2_PROMOTION_L2_256B);
  }
  {
    const cuuint64_t gd[3] = {32, 512, 56}, gs[2] = {3584, 64};
    const cuuint32_t bd[3] = {32, 32, 3};
    enc(&tmGY, d_in[4], 3, gd, gs, bd, CU_TENSOR_MAP_SWIZZLE_64B, CU_TENSOR_MAP_L2_PROMOTION_L2_128B);
    enc(&tmUY, d_in[5], 3, gd, gs, bd, CU_TENSOR_MAP_SWIZZLE_64B, CU_TENSOR_MAP_L2_PROMOTION_L2_128B);
  }
  {
    const cuuint64_t gd[3] = {64, 1792, 8}, gs[2] = {1024, 128};
    const cuuint32_t bd[3] = {64, 64, 2};
    enc(&tmD, d_in[6], 3, gd, gs, bd, CU_TENSOR_MAP_SWIZZLE_128B, CU_TENSOR_MAP_L2_PROMOTION_L2_256B);
  }
  {
    const cuuint64_t gd[3] = {4112, 8, 16}, gs[2] = {16 * 8224, 8224};
    const cuuint32_t bd[3] = {40, 8, 16};
    enc(&tmWR, d_in[1], 3, gd, gs, bd, CU_TENSOR_MAP_SWIZZLE_NONE, CU_TENSOR_MAP_L2_PROMOTION_NONE);
    enc(&tmWI, d_in[2], 3, gd, gs, bd, CU_TENSOR_MAP_SWIZZLE_NONE, CU_TENSOR_MAP_L2_PROMOTION_NONE);
  }
  fused_kernel<<<NCTA, NTHREADS, SMEM_BYTES>>>((const __nv_bfloat16*)d_in[0], (const Tables*)tab, (Scratch*)scr,
                                               (__nv_bfloat16*)d_out, (const char*)d_in[4], (const char*)d_in[5],
                                               (const char*)d_in[6], tmWR, tmWI, tmGX, tmUX, tmGY, tmUY, tmD);
}
```

```cpp
#include <cuda_runtime.h>
#include <cuda_bf16.h>
#include <cuda.h>
#include <stdint.h>

namespace {

constexpr int NCTA = 128;
constexpr int NTHREADS = 384;
constexpr int SLOT = 16384;
constexpr int SMEM_BYTES = 14 * SLOT + 2048 + 1024;
constexpr int SPIN_LIMIT = 1 << 22;

struct Scratch {
  uint4 Z1[128 * 1024];
  uint4 Z2[128 * 1024];
  uint4 LN[16 * 8 * 1024];
  uint4 P[16 * 28 * 1024];
  uint4 ST[1024];
  unsigned cnt[64 * 32];
};
__device__ __align__(1024) Scratch g_scr;
#define PROF(i)
#define PROFP(i)
#define PROFG(i)

constexpr double ccos(int i, int n) {
  i &= n - 1;
  if (i > n / 2) i = n - i;
  if (4 * i == n) return 0.0;
  const bool neg = 4 * i > n;
  if (neg) i = n / 2 - i;
  const double a = 6.283185307179586476925 * i / n, a2 = a * a;
  double term = 1.0, sum = 1.0;
  for (int k = 1; k < 14; k++) { term *= -a2 / ((2 * k - 1) * (2 * k)); sum += term; }
  return neg ? -sum : sum;
}
constexpr double csin(int i, int n) { return ccos(i - n / 4, n); }
constexpr unsigned fbits(double v, int mant) {
  if (v == 0.0) return 0;
  const unsigned sg = v < 0 ? 1u : 0u;
  if (v < 0) v = -v;
  int e = 127;
  while (v < 1.0) { v *= 2.0; e--; }
  const unsigned m = (unsigned)((v - 1.0) * (double)(1u << mant) + 0.5);
  return (sg << (8 + mant)) + ((unsigned)e << mant) + m;
}
constexpr unsigned pkb(double lo, double hi) { return fbits(lo, 7) | (fbits(hi, 7) << 16); }
constexpr double fa_elem(int kp, int n1) {
  return kp <= 8 ? ccos(kp * n1, 16) : -csin((kp - 8) * n1, 16);
}
constexpr unsigned cfrag_c(int idx, int n, int ri) {
  return ri ? pkb(-csin(idx, n), ccos(idx, n)) : pkb(ccos(idx, n), csin(idx, n));
}
struct Tables {
  unsigned fb[16][32][4];
  unsigned tw1[8][32][4];
  unsigned fa[32][4];
  unsigned f2[8][4][32][4];
  unsigned g2[8][4][32][4];
  unsigned gb[16][32][4];
  unsigned tw3[4][32][4];
  unsigned ga[32][4];
  unsigned f8[32][4], g8[32][4];
};
constexpr int T1_BYTES = 12800, T2_BYTES = 44544;
static_assert(sizeof(Tables) == T1_BYTES + T2_BYTES, "table size");
constexpr Tables make_tables() {
  Tables T = {};
  for (int l = 0; l < 32; l++) {
    const int g = l >> 2, t = l & 3;
    for (int i = 0; i < 4; i++)
      for (int u = 0; u < 8; u++) {
        const int ri = g & 1, m = 2 * (g >> 1) + ((u & 3) >> 1);
        const double sg = u >= 4 ? -1.0 : 1.0;
        const int k2 = u >= 4 ? 31 - 2 * m - (u & 1) : 2 * m + (u & 1);
        const int pa = (8 * t + i) * k2, pb = (8 * t + 4 + i) * k2;
        T.fb[i * 4 + (u >> 1)][l][(u & 1) * 2 + 0] = ri == 0 ? pkb(ccos(pa, 32), ccos(pb, 32)) : pkb(-sg * csin(pa, 32), -sg * csin(pb, 32));
        T.fb[i * 4 + (u >> 1)][l][(u & 1) * 2 + 1] = ri == 0 ? pkb(csin(pa, 32), csin(pb, 32)) : pkb(sg * ccos(pa, 32), sg * ccos(pb, 32));
      }
    for (int i = 0; i < 4; i++)
      for (int ks = 0; ks < 4; ks++) {
        const int n2 = 4 * g + i, m = 2 * t + (ks & 1);
        const double sg = ks >= 2 ? -1.0 : 1.0;
        const int pa = n2 * (ks >= 2 ? 31 - 2 * m : 2 * m), pb = n2 * (ks >= 2 ? 30 - 2 * m : 2 * m + 1);
        T.gb[i * 4 + ks][l][0] = pkb(ccos(pa, 32), -sg * csin(pa, 32));
        T.gb[i * 4 + ks][l][1] = pkb(csin(pa, 32), sg * ccos(pa, 32));
        T.gb[i * 4 + ks][l][2] = pkb(ccos(pb, 32), -sg * csin(pb, 32));
        T.gb[i * 4 + ks][l][3] = pkb(csin(pb, 32), sg * ccos(pb, 32));
      }
    for (int i = 0; i < 4; i++) {
      for (int e = 0; e < 2; e++) {
        const int p = (8 * t + 4 * e + i) * (g == 0 ? 8 : g);
        T.tw1[2 * i + e][l][0] = fbits(g == 0 ? 0.0 : ccos(p, 512), 23);
        T.tw1[2 * i + e][l][1] = fbits(g == 0 ? ccos(p, 512) : csin(p, 512), 23);
        T.tw1[2 * i + e][l][2] = fbits(g == 0 ? 0.0 : -csin(p, 512), 23);
        T.tw1[2 * i + e][l][3] = fbits(g == 0 ? -csin(p, 512) : ccos(p, 512), 23);
      }
      const int ka = t == 0 ? 8 : 2 * t, kb = 2 * t + 1;
      T.tw3[i][l][0] = fbits(ccos((4 * g + i) * ka, 512), 23);
      T.tw3[i][l][1] = fbits(csin((4 * g + i) * ka, 512), 23);
      T.tw3[i][l][2] = fbits(ccos((4 * g + i) * kb, 512), 23);
      T.tw3[i][l][3] = fbits(csin((4 * g + i) * kb, 512), 23);
      const int p8 = (t + 4 * (i & 1)) * (4 * (i >> 1) + (g >> 1));
      T.f8[l][i] = cfrag_c(p8, 8, g & 1);
      T.g8[l][i] = cfrag_c(-p8, 8, g & 1);
    }
    for (int w = 0; w < 8; w++)
      for (int i = 0; i < 16; i++) {
        const int kidx = t + 4 * (i & 1) + 8 * (i >> 3), nidx = 4 * ((i >> 1) & 3) + (g >> 1);
        T.f2[w][i >> 2][l][i & 3] = cfrag_c((8 * kidx + w) * nidx, 128, g & 1);
        T.g2[w][i >> 2][l][i & 3] = cfrag_c(-(8 * nidx + w) * kidx, 128, g & 1);
      }
    T.fa[l][0] = pkb(fa_elem(g, 2 * t), fa_elem(g, 2 * t + 1));
    T.fa[l][1] = pkb(fa_elem(g + 8, 2 * t), fa_elem(g + 8, 2 * t + 1));
    T.fa[l][2] = pkb(fa_elem(g, 2 * t + 8), fa_elem(g, 2 * t + 9));
    T.fa[l][3] = pkb(fa_elem(g + 8, 2 * t + 8), fa_elem(g + 8, 2 * t + 9));
    T.ga[l][0] = pkb(fa_elem(2 * t, g), fa_elem(2 * t + 1, g));
    T.ga[l][1] = pkb(fa_elem(2 * t, g + 8), fa_elem(2 * t + 1, g + 8));
    T.ga[l][2] = pkb(fa_elem(2 * t + 8, g), fa_elem(2 * t + 9, g));
    T.ga[l][3] = pkb(fa_elem(2 * t + 8, g + 8), fa_elem(2 * t + 9, g + 8));
  }
  return T;
}
__device__ const __align__(128) Tables g_tab = make_tables();

__device__ __forceinline__ void die() { asm volatile("st.global.u32 [%0], %1;" ::"l"(0ull), "r"(0) : "memory"); }
__device__ __forceinline__ uint32_t s2u(const void* p) { return (uint32_t)__cvta_generic_to_shared(p); }
__device__ __forceinline__ void mbar_init(uint32_t b, int c) { asm volatile("mbarrier.init.shared::cta.b64 [%0], %1;" ::"r"(b), "r"(c)); }
__device__ __forceinline__ void mbar_expect(uint32_t b, int bytes) {
  asm volatile("mbarrier.arrive.expect_tx.shared::cta.b64 _, [%0], %1;" ::"r"(b), "r"(bytes) : "memory");
}
__device__ __forceinline__ void mbar_arrive(uint32_t b) { asm volatile("mbarrier.arrive.shared::cta.b64 _, [%0];" ::"r"(b) : "memory"); }
__device__ __forceinline__ uint32_t mbar_try(uint32_t b, uint32_t parity) {
  uint32_t ok;
  asm volatile("{.reg .pred p; mbarrier.try_wait.parity.shared::cta.b64 p, [%1], %2; selp.u32 %0,1,0,p;}"
               : "=r"(ok) : "r"(b), "r"(parity) : "memory");
  return ok;
}
__device__ __forceinline__ void mbar_wait(uint32_t b, uint32_t parity) {
  int it = 0;
#pragma unroll 1
  while (!mbar_try(b, parity))
    if (++it > SPIN_LIMIT) { die(); break; }
}
__device__ __forceinline__ void mbar_wait_cluster(uint32_t b, int parity) {
  uint32_t ok;
  int it = 0;
  do {
    asm volatile("{.reg .pred p; mbarrier.try_wait.parity.acquire.cluster.shared::cta.b64 p, [%1], %2; selp.u32 %0,1,0,p;}"
                 : "=r"(ok) : "r"(b), "r"(parity) : "memory");
    if (++it > SPIN_LIMIT) { die(); break; }
  } while (!ok);
}
__device__ __forceinline__ void bar_sync(int id, int n) { asm volatile("bar.sync %0, %1;" ::"r"(id), "r"(n) : "memory"); }
__device__ __forceinline__ void bar_arrive(int id, int n) { asm volatile("bar.arrive %0, %1;" ::"r"(id), "r"(n) : "memory"); }
__device__ __forceinline__ void red_release(unsigned* p) { asm volatile("red.release.gpu.global.add.u32 [%0], 1;" ::"l"(p) : "memory"); }
__device__ __forceinline__ void red_relaxed(unsigned* p) { asm volatile("red.relaxed.gpu.global.add.u32 [%0], 1;" ::"l"(p) : "memory"); }
__device__ __forceinline__ unsigned ld_acquire(const unsigned* p) {
  unsigned v;
  asm volatile("ld.acquire.gpu.global.u32 %0, [%1];" : "=r"(v) : "l"(p) : "memory");
  return v;
}
__device__ __forceinline__ unsigned ld_relaxed(const unsigned* p) {
  unsigned v;
  asm volatile("ld.relaxed.gpu.global.u32 %0, [%1];" : "=r"(v) : "l"(p) : "memory");
  return v;
}
__device__ __forceinline__ void wait_counter(const unsigned* p, unsigned target) {
  int it = 0;
  while ((int)(ld_acquire(p) - target) < 0)
    if (++it > SPIN_LIMIT) { die(); break; }
}
__device__ __forceinline__ void sts4(uint32_t a, uint32_t x, uint32_t y, uint32_t z, uint32_t w) {
  asm volatile("st.shared.v4.u32 [%0], {%1,%2,%3,%4};" ::"r"(a), "r"(x), "r"(y), "r"(z), "r"(w) : "memory");
}
__device__ __forceinline__ uint4 lds4(uint32_t a) {
  uint4 v;
  asm volatile("ld.shared.v4.u32 {%0,%1,%2,%3}, [%4];" : "=r"(v.x), "=r"(v.y), "=r"(v.z), "=r"(v.w) : "r"(a) : "memory");
  return v;
}
__device__ __forceinline__ uint32_t pack2(float lo, float hi) {
  uint32_t r;
  asm("cvt.rn.bf16x2.f32 %0, %1, %2;" : "=r"(r) : "f"(hi), "f"(lo));
  return r;
}
__device__ __forceinline__ float bf_lo(uint32_t v) { return __uint_as_float(v << 16); }
__device__ __forceinline__ float bf_hi(uint32_t v) { return __uint_as_float(v & 0xffff0000u); }
__device__ __forceinline__ uint32_t hadd2_bf16(uint32_t a, uint32_t b) {
  uint32_t r;
  asm("add.rn.bf16x2 %0, %1, %2;" : "=r"(r) : "r"(a), "r"(b));
  return r;
}
__device__ __forceinline__ void mma16816(float (&d)[4], uint32_t a0, uint32_t a1, uint32_t a2, uint32_t a3, uint32_t b0, uint32_t b1) {
  asm("mma.sync.aligned.m16n8k16.row.col.f32.bf16.bf16.f32 {%0,%1,%2,%3}, {%4,%5,%6,%7}, {%8,%9}, {%0,%1,%2,%3};"
      : "+f"(d[0]), "+f"(d[1]), "+f"(d[2]), "+f"(d[3])
      : "r"(a0), "r"(a1), "r"(a2), "r"(a3), "r"(b0), "r"(b1));
}
template <int N>
__device__ __forceinline__ void cs_frac(int idx, float& c, float& s) {
  int i = ((idx + N / 2) & (N - 1)) - N / 2;
  float a = (float)i * (6.283185307179586f / N);
  c = __cosf(a);
  s = __sinf(a);
}
template <int N>
__device__ __forceinline__ uint32_t cfrag(int idx, int ri) {
  float c, s;
  cs_frac<N>(idx, c, s);
  return ri ? pack2(-s, c) : pack2(c, s);
}
__device__ __forceinline__ uint32_t word(const uint4& v, int e) { return e == 0 ? v.x : e == 1 ? v.y : e == 2 ? v.z : v.w; }
__device__ __forceinline__ void cdft16(const uint4 (&q)[4], const uint4 (&F)[4], uint4 (&o)[4]) {
  float acc[2][4][4];
#pragma unroll
  for (int p = 0; p < 2; p++)
#pragma unroll
    for (int v = 0; v < 4; v++) {
      acc[p][v][0] = acc[p][v][1] = acc[p][v][2] = acc[p][v][3] = 0.f;
#pragma unroll
      for (int ks = 0; ks < 2; ks++)
        mma16816(acc[p][v], word(q[2 * ks], 2 * p), word(q[2 * ks], 2 * p + 1), word(q[2 * ks + 1], 2 * p),
                 word(q[2 * ks + 1], 2 * p + 1), word(F[ks * 2 + (v >> 1)], (v & 1) * 2), word(F[ks * 2 + (v >> 1)], (v & 1) * 2 + 1));
    }
#pragma unroll
  for (int v = 0; v < 4; v++)
    o[v] = make_uint4(pack2(acc[0][v][0], acc[0][v][1]), pack2(acc[0][v][2], acc[0][v][3]),
                      pack2(acc[1][v][0], acc[1][v][1]), pack2(acc[1][v][2], acc[1][v][3]));
}
__device__ __forceinline__ void st_tag(uint4* p, const uint4& v, uint32_t tag) {
  asm volatile("{.reg .b128 r; .reg .b64 a, b; mov.b64 a, {%1,%2}; mov.b64 b, {%3,%4}; mov.b128 r, {a,b}; st.relaxed.gpu.global.b128 [%0], r;}"
               ::"l"(p), "r"((v.x & ~1u) | tag), "r"(v.y), "r"(v.z), "r"(v.w) : "memory");
}
__device__ __forceinline__ uint4 ld_b128(const uint4* p) {
  uint4 v;
  asm volatile("{.reg .b128 r; .reg .b64 a, b; ld.relaxed.gpu.global.b128 r, [%4]; mov.b128 {a,b}, r; mov.b64 {%0,%1}, a; mov.b64 {%2,%3}, b;}"
               : "=r"(v.x), "=r"(v.y), "=r"(v.z), "=r"(v.w) : "l"(p) : "memory");
  return v;
}
template <int STRIDE>
__device__ __forceinline__ void ld_tag4_issue(uint4 (&q)[4], const uint4* p) {
#pragma unroll
  for (int i = 0; i < 4; i++) q[i] = ld_b128(p + i * STRIDE);
}
template <int STRIDE>
__device__ __forceinline__ void ld_tag4_finish(uint4 (&q)[4], const uint4* p, uint32_t tag) {
  int it = 0;
#pragma unroll 1
  while (__any_sync(0xffffffffu, ((q[0].x ^ tag) | (q[1].x ^ tag) | (q[2].x ^ tag) | (q[3].x ^ tag)) & 1u)) {
    ld_tag4_issue<STRIDE>(q, p);
    if (++it > SPIN_LIMIT) { die(); break; }
  }
#pragma unroll
  for (int i = 0; i < 4; i++) asm volatile("and.b32 %0, %0, 0xfffffffe;" : "+r"(q[i].x));
}
__device__ __forceinline__ void row_stats(const uint32_t (&a)[8], const uint32_t (&b)[8], int lane, float (&sum)[2], float (&sq)[2]) {
  float da[4] = {0.f, 0.f, 0.f, 0.f}, db[4] = {0.f, 0.f, 0.f, 0.f}, ds[4] = {0.f, 0.f, 0.f, 0.f};
#pragma unroll
  for (int q = 0; q < 4; q++) {
    mma16816(ds, a[2 * q], b[2 * q], a[2 * q + 1], b[2 * q + 1], 0x3f803f80u, 0x3f803f80u);
    mma16816(da, a[2 * q], b[2 * q], a[2 * q + 1], b[2 * q + 1], a[2 * q], a[2 * q + 1]);
    mma16816(db, a[2 * q], b[2 * q], a[2 * q + 1], b[2 * q + 1], b[2 * q], b[2 * q + 1]);
  }
  const int src = (lane & 28) | (lane >> 3);
  const float qa = __shfl_sync(0xffffffffu, (lane & 4) ? da[1] : da[0], src);
  const float qb = __shfl_sync(0xffffffffu, (lane & 4) ? db[3] : db[2], src);
  float v = (lane & 2) ? ((lane & 1) ? ds[2] : ds[0]) : ((lane & 1) ? qb : qa);
  v += __shfl_xor_sync(0xffffffffu, v, 4);
  v += __shfl_xor_sync(0xffffffffu, v, 8);
  v += __shfl_xor_sync(0xffffffffu, v, 16);
  sq[0] = __shfl_sync(0xffffffffu, v, 0);
  sq[1] = __shfl_sync(0xffffffffu, v, 1);
  sum[0] = __shfl_sync(0xffffffffu, v, 2);
  sum[1] = __shfl_sync(0xffffffffu, v, 3);
}
__device__ __forceinline__ uint64_t desc64(uint32_t lo, uint32_t hi) {
  uint64_t d;
  asm("mov.b64 %0, {%1, %2};" : "=l"(d) : "r"(lo), "r"(hi));
  return d;
}
constexpr uint32_t desc_hi(uint32_t sbo, uint32_t swz) { return (sbo >> 4) | (swz << 30); }
__device__ __forceinline__ uint32_t desc_lo(uint32_t addr, uint32_t lbo) { return ((addr & 0x3FFFF) >> 4) | ((lbo >> 4) << 16); }
__device__ __forceinline__ void cp_async16(uint32_t dst, const void* src) {
  asm volatile("cp.async.cg.shared.global [%0], [%1], 16;" ::"r"(dst), "l"(src) : "memory");
}
__device__ __forceinline__ uint2 lds2(uint32_t a) {
  uint2 v;
  asm volatile("ld.shared.v2.u32 {%0,%1}, [%2];" : "=r"(v.x), "=r"(v.y) : "r"(a) : "memory");
  return v;
}
__device__ __forceinline__ uint32_t lds_u16(uint32_t a) {
  uint16_t v;
  asm volatile("ld.shared.u16 %0, [%1];" : "=h"(v) : "r"(a) : "memory");
  return v;
}
__device__ __forceinline__ void wg_fence() { asm volatile("wgmma.fence.sync.aligned;" ::: "memory"); }
__device__ __forceinline__ void wg_commit() { asm volatile("wgmma.commit_group.sync.aligned;" ::: "memory"); }
template <int N>
__device__ __forceinline__ void wg_wait() { asm volatile("wgmma.wait_group.sync.aligned %0;" ::"n"(N) : "memory"); }
__device__ __forceinline__ void bulk_load(uint32_t dst, const void* src, int bytes, uint32_t bar) {
  asm volatile("cp.async.bulk.shared::cluster.global.mbarrier::complete_tx::bytes [%0], [%1], %2, [%3];"
               ::"r"(dst), "l"(src), "r"(bytes), "r"(bar) : "memory");
}
__device__ __forceinline__ void tma3(uint32_t dst, const CUtensorMap* tm, uint32_t bar, int c0, int c1, int c2) {
  asm volatile("cp.async.bulk.tensor.3d.shared::cluster.global.mbarrier::complete_tx::bytes [%0], [%1, {%3,%4,%5}], [%2];"
               ::"r"(dst), "l"(tm), "r"(bar), "r"(c0), "r"(c1), "r"(c2) : "memory");
}
__device__ __forceinline__ void tma3_mc(uint32_t dst, const CUtensorMap* tm, uint32_t bar, int c1, int c2) {
  asm volatile("cp.async.bulk.tensor.3d.shared::cluster.global.mbarrier::complete_tx::bytes.multicast::cluster [%0], [%1, {%3,%4,%5}], [%2], %6;"
               ::"r"(dst), "l"(tm), "r"(bar), "r"(0), "r"(c1), "r"(c2), "h"((uint16_t)3) : "memory");
}
__device__ __forceinline__ void mbar_arrive_remote(uint32_t rb) {
  asm volatile("mbarrier.arrive.shared::cluster.b64 _, [%0];" ::"r"(rb) : "memory");
}
__device__ __forceinline__ uint4 ldg_ca4(const void* p) {
  uint4 v;
  asm volatile("ld.global.ca.v4.u32 {%0,%1,%2,%3}, [%4];" : "=r"(v.x), "=r"(v.y), "=r"(v.z), "=r"(v.w) : "l"(p) : "memory");
  return v;
}
__device__ __forceinline__ uint32_t clock32() {
  uint32_t v;
  asm volatile("mov.u32 %0, %%clock;" : "=r"(v) :: "memory");
  return v;
}
__device__ __forceinline__ float swiglu(float g, float u, float r) {
  float hg = (0.5f * r) * g, th;
  asm("tanh.approx.f32 %0, %1;" : "=f"(th) : "f"(hg));
  return fmaf(hg, th, hg) * (r * u);
}
__device__ __forceinline__ uint32_t hsub2_bf16(uint32_t a, uint32_t b) {
  uint32_t r;
  asm("sub.rn.bf16x2 %0, %1, %2;" : "=r"(r) : "r"(a), "r"(b));
  return r;
}
__device__ __forceinline__ void l2_prefetch(const void* p, int bytes) {
  asm volatile("cp.async.bulk.prefetch.L2.global [%0], %1;" ::"l"(p), "r"(bytes) : "memory");
}

__device__ __forceinline__ void wgmma_n256(float (&d)[128], uint64_t da, uint64_t db) {
  asm volatile("wgmma.mma_async.sync.aligned.m64n256k16.f32.bf16.bf16 {"
      "%0,%1,%2,%3,%4,%5,%6,%7,%8,%9,%10,%11,%12,%13,%14,%15,"
      "%16,%17,%18,%19,%20,%21,%22,%23,%24,%25,%26,%27,%28,%29,%30,%31,"
      "%32,%33,%34,%35,%36,%37,%38,%39,%40,%41,%42,%43,%44,%45,%46,%47,"
      "%48,%49,%50,%51,%52,%53,%54,%55,%56,%57,%58,%59,%60,%61,%62,%63,"
      "%64,%65,%66,%67,%68,%69,%70,%71,%72,%73,%74,%75,%76,%77,%78,%79,"
      "%80,%81,%82,%83,%84,%85,%86,%87,%88,%89,%90,%91,%92,%93,%94,%95,"
      "%96,%97,%98,%99,%100,%101,%102,%103,%104,%105,%106,%107,%108,%109,%110,%111,"
      "%112,%113,%114,%115,%116,%117,%118,%119,%120,%121,%122,%123,%124,%125,%126,%127"
      "}, %128, %129, 1, 1, 1, 0, 1;\n"
      : "+f"(d[0]),"+f"(d[1]),"+f"(d[2]),"+f"(d[3]),"+f"(d[4]),"+f"(d[5]),"+f"(d[6]),"+f"(d[7]),
        "+f"(d[8]),"+f"(d[9]),"+f"(d[10]),"+f"(d[11]),"+f"(d[12]),"+f"(d[13]),"+f"(d[14]),"+f"(d[15]),
        "+f"(d[16]),"+f"(d[17]),"+f"(d[18]),"+f"(d[19]),"+f"(d[20]),"+f"(d[21]),"+f"(d[22]),"+f"(d[23]),
        "+f"(d[24]),"+f"(d[25]),"+f"(d[26]),"+f"(d[27]),"+f"(d[28]),"+f"(d[29]),"+f"(d[30]),"+f"(d[31]),
        "+f"(d[32]),"+f"(d[33]),"+f"(d[34]),"+f"(d[35]),"+f"(d[36]),"+f"(d[37]),"+f"(d[38]),"+f"(d[39]),
        "+f"(d[40]),"+f"(d[41]),"+f"(d[42]),"+f"(d[43]),"+f"(d[44]),"+f"(d[45]),"+f"(d[46]),"+f"(d[47]),
        "+f"(d[48]),"+f"(d[49]),"+f"(d[50]),"+f"(d[51]),"+f"(d[52]),"+f"(d[53]),"+f"(d[54]),"+f"(d[55]),
        "+f"(d[56]),"+f"(d[57]),"+f"(d[58]),"+f"(d[59]),"+f"(d[60]),"+f"(d[61]),"+f"(d[62]),"+f"(d[63]),
        "+f"(d[64]),"+f"(d[65]),"+f"(d[66]),"+f"(d[67]),"+f"(d[68]),"+f"(d[69]),"+f"(d[70]),"+f"(d[71]),
        "+f"(d[72]),"+f"(d[73]),"+f"(d[74]),"+f"(d[75]),"+f"(d[76]),"+f"(d[77]),"+f"(d[78]),"+f"(d[79]),
        "+f"(d[80]),"+f"(d[81]),"+f"(d[82]),"+f"(d[83]),"+f"(d[84]),"+f"(d[85]),"+f"(d[86]),"+f"(d[87]),
        "+f"(d[88]),"+f"(d[89]),"+f"(d[90]),"+f"(d[91]),"+f"(d[92]),"+f"(d[93]),"+f"(d[94]),"+f"(d[95]),
        "+f"(d[96]),"+f"(d[97]),"+f"(d[98]),"+f"(d[99]),"+f"(d[100]),"+f"(d[101]),"+f"(d[102]),"+f"(d[103]),
        "+f"(d[104]),"+f"(d[105]),"+f"(d[106]),"+f"(d[107]),"+f"(d[108]),"+f"(d[109]),"+f"(d[110]),"+f"(d[111]),
        "+f"(d[112]),"+f"(d[113]),"+f"(d[114]),"+f"(d[115]),"+f"(d[116]),"+f"(d[117]),"+f"(d[118]),"+f"(d[119]),
        "+f"(d[120]),"+f"(d[121]),"+f"(d[122]),"+f"(d[123]),"+f"(d[124]),"+f"(d[125]),"+f"(d[126]),"+f"(d[127])
      : "l"(da), "l"(db));
}
__device__ __forceinline__ void wgmma_n192(float (&d)[96], uint64_t da, uint64_t db) {
  asm volatile("wgmma.mma_async.sync.aligned.m64n192k16.f32.bf16.bf16 {"
      "%0,%1,%2,%3,%4,%5,%6,%7,%8,%9,%10,%11,%12,%13,%14,%15,"
      "%16,%17,%18,%19,%20,%21,%22,%23,%24,%25,%26,%27,%28,%29,%30,%31,"
      "%32,%33,%34,%35,%36,%37,%38,%39,%40,%41,%42,%43,%44,%45,%46,%47,"
      "%48,%49,%50,%51,%52,%53,%54,%55,%56,%57,%58,%59,%60,%61,%62,%63,"
      "%64,%65,%66,%67,%68,%69,%70,%71,%72,%73,%74,%75,%76,%77,%78,%79,"
      "%80,%81,%82,%83,%84,%85,%86,%87,%88,%89,%90,%91,%92,%93,%94,%95"
      "}, %96, %97, 1, 1, 1, 0, 1;\n"
      : "+f"(d[0]),"+f"(d[1]),"+f"(d[2]),"+f"(d[3]),"+f"(d[4]),"+f"(d[5]),"+f"(d[6]),"+f"(d[7]),
        "+f"(d[8]),"+f"(d[9]),"+f"(d[10]),"+f"(d[11]),"+f"(d[12]),"+f"(d[13]),"+f"(d[14]),"+f"(d[15]),
        "+f"(d[16]),"+f"(d[17]),"+f"(d[18]),"+f"(d[19]),"+f"(d[20]),"+f"(d[21]),"+f"(d[22]),"+f"(d[23]),
        "+f"(d[24]),"+f"(d[25]),"+f"(d[26]),"+f"(d[27]),"+f"(d[28]),"+f"(d[29]),"+f"(d[30]),"+f"(d[31]),
        "+f"(d[32]),"+f"(d[33]),"+f"(d[34]),"+f"(d[35]),"+f"(d[36]),"+f"(d[37]),"+f"(d[38]),"+f"(d[39]),
        "+f"(d[40]),"+f"(d[41]),"+f"(d[42]),"+f"(d[43]),"+f"(d[44]),"+f"(d[45]),"+f"(d[46]),"+f"(d[47]),
        "+f"(d[48]),"+f"(d[49]),"+f"(d[50]),"+f"(d[51]),"+f"(d[52]),"+f"(d[53]),"+f"(d[54]),"+f"(d[55]),
        "+f"(d[56]),"+f"(d[57]),"+f"(d[58]),"+f"(d[59]),"+f"(d[60]),"+f"(d[61]),"+f"(d[62]),"+f"(d[63]),
        "+f"(d[64]),"+f"(d[65]),"+f"(d[66]),"+f"(d[67]),"+f"(d[68]),"+f"(d[69]),"+f"(d[70]),"+f"(d[71]),
        "+f"(d[72]),"+f"(d[73]),"+f"(d[74]),"+f"(d[75]),"+f"(d[76]),"+f"(d[77]),"+f"(d[78]),"+f"(d[79]),
        "+f"(d[80]),"+f"(d[81]),"+f"(d[82]),"+f"(d[83]),"+f"(d[84]),"+f"(d[85]),"+f"(d[86]),"+f"(d[87]),
        "+f"(d[88]),"+f"(d[89]),"+f"(d[90]),"+f"(d[91]),"+f"(d[92]),"+f"(d[93]),"+f"(d[94]),"+f"(d[95])
      : "l"(da), "l"(db));
}
__device__ __forceinline__ void wgmma_rs_n128(float (&d)[64], uint32_t a0, uint32_t a1, uint32_t a2, uint32_t a3, uint64_t db) {
  asm volatile("wgmma.mma_async.sync.aligned.m64n128k16.f32.bf16.bf16 {"
      "%0,%1,%2,%3,%4,%5,%6,%7,%8,%9,%10,%11,%12,%13,%14,%15,"
      "%16,%17,%18,%19,%20,%21,%22,%23,%24,%25,%26,%27,%28,%29,%30,%31,"
      "%32,%33,%34,%35,%36,%37,%38,%39,%40,%41,%42,%43,%44,%45,%46,%47,"
      "%48,%49,%50,%51,%52,%53,%54,%55,%56,%57,%58,%59,%60,%61,%62,%63"
      "}, {%64,%65,%66,%67}, %68, 1, 1, 1, 1;\n"
      : "+f"(d[0]),"+f"(d[1]),"+f"(d[2]),"+f"(d[3]),"+f"(d[4]),"+f"(d[5]),"+f"(d[6]),"+f"(d[7]),
        "+f"(d[8]),"+f"(d[9]),"+f"(d[10]),"+f"(d[11]),"+f"(d[12]),"+f"(d[13]),"+f"(d[14]),"+f"(d[15]),
        "+f"(d[16]),"+f"(d[17]),"+f"(d[18]),"+f"(d[19]),"+f"(d[20]),"+f"(d[21]),"+f"(d[22]),"+f"(d[23]),
        "+f"(d[24]),"+f"(d[25]),"+f"(d[26]),"+f"(d[27]),"+f"(d[28]),"+f"(d[29]),"+f"(d[30]),"+f"(d[31]),
        "+f"(d[32]),"+f"(d[33]),"+f"(d[34]),"+f"(d[35]),"+f"(d[36]),"+f"(d[37]),"+f"(d[38]),"+f"(d[39]),
        "+f"(d[40]),"+f"(d[41]),"+f"(d[42]),"+f"(d[43]),"+f"(d[44]),"+f"(d[45]),"+f"(d[46]),"+f"(d[47]),
        "+f"(d[48]),"+f"(d[49]),"+f"(d[50]),"+f"(d[51]),"+f"(d[52]),"+f"(d[53]),"+f"(d[54]),"+f"(d[55]),
        "+f"(d[56]),"+f"(d[57]),"+f"(d[58]),"+f"(d[59]),"+f"(d[60]),"+f"(d[61]),"+f"(d[62]),"+f"(d[63])
      : "r"(a0), "r"(a1), "r"(a2), "r"(a3), "l"(db));
}

constexpr int C_LN = 0, C_PX = 16, C_PY = 32;
constexpr int NB_CONS = 1, NB_LN = 2, NB_LAG = 4, NB_INIT = 6, NB_RDY = 7;
#define LAGX 3
#define LAGY 3
#define LAG2 2
#define NLL 2
#define POLL_DELAY3 900
#define POLL_DELAY 900
#define FILT_DELAY 1000
#define RING_SIG 0
#define PF2_SIG 1
constexpr int SM_E = 0, SM_X = 16384, SM_E2 = 32768, SM_W = 49152, SM_FC = 69632, SM_T = 73728 - T1_BYTES;
constexpr unsigned long long KORDER = 0xBA9432DC876510ull;
constexpr uint32_t HI128 = desc_hi(1024, 1), HI64 = desc_hi(512, 2);

struct Bars {
  uint64_t full1[6], empty1[6], fullA[8], full2[14], empty2[8], xbar, xfree, hbar, tbar, sbar, sig[2], hint[3];
  uint32_t epoch;
};

template <int NK, bool STORE>
__device__ __forceinline__ void make_p(const float (&acc)[NK * 16], float r0, float r1, uint4 (&p)[NK], uint4* pbase, int ks0, uint32_t tag) {
#pragma unroll
  for (int j = 0; j < NK; j++) {
    uint32_t w[4];
#pragma unroll
    for (int i = 0; i < 4; i++) {
      const int a = 8 * j + 2 * i, b = a + NK * 8;
      w[i] = pack2(swiglu(acc[a], acc[b], (i & 1) ? r1 : r0), swiglu(acc[a + 1], acc[b + 1], (i & 1) ? r1 : r0));
    }
    asm volatile("" : "+r"(w[0]), "+r"(w[1]), "+r"(w[2]), "+r"(w[3]));
    p[j] = make_uint4(w[0], w[1], w[2], w[3]);
    if (STORE) st_tag(pbase + ((ks0 + j) >> 2) * 1024 + ((ks0 + j) & 3) * 32, p[j], tag);
  }
}
__device__ __forceinline__ void spin_cycles(uint32_t n) {
  const uint32_t t0 = clock32();
  while (clock32() - t0 < n) {}
}

__global__ void __cluster_dims__(2, 1, 1) __launch_bounds__(NTHREADS, 1)
fused_kernel(const __nv_bfloat16* __restrict__ x, const Tables* __restrict__ tab, Scratch* __restrict__ scr,
             __nv_bfloat16* __restrict__ out, const char* __restrict__ wg_raw, const char* __restrict__ wu_raw,
             const char* __restrict__ wd_raw,
             const __grid_constant__ CUtensorMap tmWR, const __grid_constant__ CUtensorMap tmWI,
             const __grid_constant__ CUtensorMap tmGX, const __grid_constant__ CUtensorMap tmUX,
             const __grid_constant__ CUtensorMap tmGY, const __grid_constant__ CUtensorMap tmUY,
             const __grid_constant__ CUtensorMap tmD) {
  extern __shared__ __align__(1024) char smem_raw[];
  const uint32_t sbase = (s2u(smem_raw) + 1023) & ~1023u;
  const uint32_t sbar = sbase + 14 * SLOT, sstat = sbar + 512;
  const int tid = threadIdx.x, lane = tid & 31;
  const int c = blockIdx.x, kh = c & 1, f = (c >> 1) & 7, rb = 2 * (c >> 4) + kh, rb2 = 2 * (c >> 4) + (f >> 2), nq = f & 3;
#define BAR(field, i) (sbar + (uint32_t)offsetof(Bars, field) + 8u * (i))
#define TOFF(field) (sbase + SM_T + (uint32_t)offsetof(Tables, field) + lane * 16)

  if (tid >= 256) {
    asm volatile("setmaxnreg.dec.sync.aligned.u32 56;");
    const int warp = __shfl_sync(0xffffffffu, tid >> 5, 0);
    if (tid == 256) {
      for (int i = 0; i < 6; i++) { mbar_init(BAR(full1, i), 1); mbar_init(BAR(empty1, i), 16); }
      for (int i = 0; i < 8; i++) { mbar_init(BAR(fullA, i), 1); mbar_init(BAR(empty2, i), 8); }
      for (int i = 0; i < 14; i++) mbar_init(BAR(full2, i), 2);
      mbar_init(BAR(xbar, 0), 1);
      mbar_init(BAR(xfree, 0), 8);
      mbar_init(BAR(tbar, 0), 1);
      mbar_init(BAR(hbar, 0), 1);
      mbar_init(BAR(sbar, 0), 32);
      for (int i = 0; i < 3; i++) mbar_init(BAR(hint, i), 1);
      mbar_init(BAR(sig, 0), 8);
      mbar_init(BAR(sig, 1), 8);
      mbar_expect(BAR(xbar, 0), 16384);
      asm volatile("fence.mbarrier_init.release.cluster;" ::: "memory");
      const int w0 = ((c >> 3) * 257 + 32 * (c & 7) + 1) & ~7;
      if (FILT_DELAY) {
        asm volatile("prefetch.tensormap [%0];" ::"l"(&tmWR) : "memory");
        asm volatile("prefetch.tensormap [%0];" ::"l"(&tmWI) : "memory");
        spin_cycles(FILT_DELAY);
      }
      mbar_expect(BAR(tbar, 0), T2_BYTES + 2 * 10240);
      tma3(sbase + SM_W, &tmWR, BAR(tbar, 0), w0, 0, 0);
      tma3(sbase + SM_W + 10240, &tmWI, BAR(tbar, 0), w0, 0, 0);
      bulk_load(sbase + SM_T + T1_BYTES, reinterpret_cast<const char*>(tab) + T1_BYTES, T2_BYTES, BAR(tbar, 0));
    }
    if (tid == 288) {
      asm volatile("prefetch.tensormap [%0];" ::"l"(kh ? &tmUX : &tmGX) : "memory");
      asm volatile("prefetch.tensormap [%0];" ::"l"(kh ? &tmUY : &tmGY) : "memory");
      asm volatile("prefetch.tensormap [%0];" ::"l"(&tmD) : "memory");
    }
    if (tid == 320) {
      const unsigned e = ld_relaxed(&scr->cnt[(C_LN + rb) * 32]) >> 3;
      asm volatile("st.shared.u32 [%0], %1;" ::"r"(BAR(epoch, 0)), "r"(e) : "memory");
    }
    __syncwarp();
    asm volatile("barrier.cluster.arrive.relaxed.aligned;" ::: "memory");
    bar_arrive(NB_RDY, 384);
    asm volatile("barrier.cluster.wait.aligned;" ::: "memory");
    bar_sync(NB_INIT, 384);
    unsigned epoch;
    asm volatile("ld.shared.u32 %0, [%1];" : "=r"(epoch) : "r"(BAR(epoch, 0)) : "memory");
    if (warp == 8) {
      if (lane == 0) {
        const int ax = (7 * f + 3 * (f & 1)) >> 1;
        const int ay = 7 * f + ((f & 1) ? 0 : 4);
        const CUtensorMap* tx = kh ? &tmUX : &tmGX;
        const CUtensorMap* ty = kh ? &tmUY : &tmGY;
        uint32_t s = 0, ph = 1;
        if (RING_SIG >= 0) mbar_wait(BAR(sig, RING_SIG), 0);
#pragma unroll 1
        for (int n = 0; n < 32; n++) {
          const uint32_t dst = sbase + (8 + s) * SLOT, fb = BAR(full1, s);
          mbar_wait(BAR(empty1, s), ph);
          if (n < 16) {
            mbar_expect(fb, 16384);
            tma3_mc(dst + kh * 8192, tx, fb, n * 32, ax);
          } else {
            mbar_expect(fb, 12288);
            tma3_mc(dst + kh * 6144, ty, fb, (n - 16) * 32, ay);
          }
          if (++s == 6) { s = 0; ph ^= 1; }
        }
      }
    } else if (warp == 9) {
      if (lane == 0) {
        mbar_wait(BAR(empty1, 5), 0);
        mbar_wait(BAR(empty1, 5), 1);
#pragma unroll 1
        for (int i = 0; i < 14; i++) {
          const int kblk = 14 * kh + (int)((KORDER >> (4 * i)) & 15);
          if (i < 8) mbar_wait(BAR(empty1, (17 + 2 * i) % 6), ((17 + 2 * i) / 6) & 1);
          else mbar_wait(BAR(empty2, i - 8), 0);
          mbar_expect(BAR(full2, i), 16384);
          tma3(sbase + (i & 7) * SLOT, &tmD, BAR(full2, i), 0, 64 * kblk, 2 * nq);
        }
        wait_counter(&scr->cnt[(C_LN + rb2) * 32], (epoch + 1) * 8);
        asm volatile("fence.proxy.async.global;" ::: "memory");
        mbar_wait(BAR(empty2, 7), 0);
        mbar_expect(BAR(hbar, 0), 16384);
        bulk_load(sbase + 7 * SLOT, &scr->LN[(rb2 * 8 + 2 * nq) * 1024 + kh * 512], 8192, BAR(hbar, 0));
        bulk_load(sbase + 7 * SLOT + 8192, &scr->LN[(rb2 * 8 + 2 * nq + 1) * 1024 + kh * 512], 8192, BAR(hbar, 0));
      }
    } else if (warp == 10) {
      bar_sync(NB_LN, 288);
      if (lane == 0) {
        PROFP(0);
        red_release(&scr->cnt[(C_LN + rb) * 32]);
        PROFP(1);
        wait_counter(&scr->cnt[(C_LN + rb) * 32], (epoch + 1) * 8);
        asm volatile("fence.proxy.async.global;" ::: "memory");
        PROFP(2);
#pragma unroll 1
        for (int kb = NLL; kb < 8; kb++) {
          mbar_expect(BAR(fullA, kb), 16384);
          bulk_load(sbase + kb * SLOT, &scr->LN[(rb * 8 + kb) * 1024], 16384, BAR(fullA, kb));
        }
#pragma unroll 1
        for (int i = 0; i < 4; i++) mbar_wait(BAR(empty1, 2), i & 1);
        uint32_t d = 2;
#pragma unroll 1
        for (int s = 0; s < 14; s++) {
          const int kblk = 14 * kh + (int)((KORDER >> (4 * s)) & 15);
          if (s == 0 || s == 8 || s == 11) {
            if (s != 11) PROFP(3 + (s >> 2));
            mbar_wait(BAR(hint, s == 0 ? 0 : s == 8 ? 1 : 2), 0);
            if (s != 11) PROFP(4 + (s >> 2));
          }
          if (s < 6) mbar_wait(BAR(empty1, d), s < 4 ? 0 : 1);
          else mbar_wait(BAR(empty2, s - 6), 0);
          mbar_expect(BAR(full2, s), 16384);
          bulk_load(sbase + (8 + d) * SLOT, &scr->P[(rb2 * 28 + kblk) * 1024], 16384, BAR(full2, s));
          if (++d == 6) d = 0;
        }
        PROFP(7);
      }
    } else {
      if (lane == 0) {
        l2_prefetch(wg_raw + (size_t)c * 5376, 5376);
        l2_prefetch(wu_raw + (size_t)c * 5376, 5376);
        mbar_wait(BAR(sig, PF2_SIG), 0);
        l2_prefetch(wg_raw + 688128 + (size_t)c * 8960, 8960);
        l2_prefetch(wu_raw + 688128 + (size_t)c * 8960, 8960);
      }
      mbar_wait(BAR(fullA, 7), 0);
      if (lane == 0) l2_prefetch(wd_raw + (size_t)c * 14336, 14336);
      {
        const uint32_t tag = (epoch + 1) & 1;
        uint4 v0, v1, v2;
        int it = 0;
        while (true) {
          v0 = ld_b128(&scr->ST[rb * 64 + lane]);
          v1 = ld_b128(&scr->ST[rb * 64 + 32 + lane]);
          v2 = ld_b128(&scr->ST[rb2 * 64 + 32 * kh + lane]);
          if (!__any_sync(0xffffffffu, ((v0.x ^ tag) | (v1.x ^ tag) | (v2.x ^ tag)) & 1u)) break;
          if (++it > SPIN_LIMIT) { die(); break; }
        }
        sts4(sstat + lane * 16, v0.x & ~1u, v0.y, v0.z, v0.w);
        sts4(sstat + 512 + lane * 16, v1.x & ~1u, v1.y, v1.z, v1.w);
        sts4(sstat + 1024 + lane * 16, v2.x & ~1u, v2.y, v2.z, v2.w);
        mbar_arrive(BAR(sbar, 0));
      }
      if (lane == 0) {
        mbar_wait(BAR(empty1, 5), 0);
        mbar_wait(BAR(empty1, 5), 1);
        mbar_wait(BAR(empty1, 5), 0);
#pragma unroll 1
        for (int e = 0; e < 3; e++) {
          const unsigned* cp = e == 0 ? &scr->cnt[(C_PX + rb2) * 32] : &scr->cnt[(C_PY + rb2) * 32 + 2 * kh + e - 1];
          if (e == 1) mbar_wait(BAR(full2, 0), 0);
          int it = 0;
          while ((int)(ld_relaxed(cp) - (epoch + 1) * (e == 0 ? 64 : 16)) < 0)
            if (++it > SPIN_LIMIT) { die(); break; }
          mbar_arrive(BAR(hint, e));
        }
      }
    }
  } else {
    const int warp = __shfl_sync(0xffffffffu, tid >> 5, 0);
    const int g = lane >> 2, t = lane & 3;
    PROF(0);
    PROFG(14);
#pragma unroll
    for (int i = 0; i < 4; i++) {
      const int r = i >> 1, ch = (i & 1) * 32 + lane;
      cp_async16(sbase + SM_X + (2 * warp + r) * 1024 + ((ch ^ ((ch >> 2) & 6)) * 16),
                 x + (size_t)(c + 128 * (2 * warp + r)) * 512 + ch * 8);
    }
    asm volatile("cp.async.commit_group;" ::: "memory");
    asm volatile("barrier.cluster.arrive.relaxed.aligned;" ::: "memory");
    uint4 tw[8], fb[16];
    const uint4 fa = ldg_ca4(&tab->fa[lane][0]);
#pragma unroll
    for (int i = 0; i < 8; i++) tw[i] = ldg_ca4(&tab->tw1[i][lane][0]);
#pragma unroll
    for (int i = 0; i < 16; i++) fb[i] = ldg_ca4(&tab->fb[i][lane][0]);
    uint32_t rbar;
    asm volatile("mapa.shared::cluster.u32 %0, %1, %2;" : "=r"(rbar) : "r"(sbar), "r"(kh ^ 1));
#define RBAR(field, i) (rbar + (uint32_t)offsetof(Bars, field) + 8u * (i))
    {
      const int ln = (tid >> 1) & 31, lg = ln >> 2, lt = ln & 3, i = 4 * (tid >> 6) + 2 * (tid & 1);
      const int kidx = lt + 8 * (i >> 3), nidx = 4 * ((i >> 1) & 3) + (lg >> 1);
      const uint32_t a0 = cfrag<2048>((c + 128 * kidx) * nidx, lg & 1), a1 = cfrag<2048>((c + 128 * (kidx + 4)) * nidx, lg & 1);
      const uint32_t b0 = cfrag<2048>(-(c + 128 * nidx) * kidx, lg & 1), b1 = cfrag<2048>(-(c + 128 * nidx) * (kidx + 4), lg & 1);
      asm volatile("st.shared.v2.u32 [%0], {%1,%2};" ::"r"(sbase + SM_FC + tid * 8), "r"(a0), "r"(a1) : "memory");
      asm volatile("st.shared.v2.u32 [%0], {%1,%2};" ::"r"(sbase + SM_FC + 2048 + tid * 8), "r"(b0), "r"(b1) : "memory");
    }
    asm volatile("cp.async.wait_group 0;" ::: "memory");
    __syncwarp();
    bar_arrive(NB_INIT, 384);
    PROF(13);
    uint32_t tag;
    uint4 q[4], o[4];
    {
      uint32_t v[2][8];
#pragma unroll
      for (int r = 0; r < 2; r++)
#pragma unroll
        for (int q = 0; q < 4; q++) {
          const uint2 u = lds2(sbase + SM_X + (2 * warp + r) * 1024 + (t + 4 * (q >> 1)) * 128 + (((4 * (q & 1) + (g >> 1)) ^ (2 * t)) * 16) + (g & 1) * 8);
          v[r][2 * q] = u.x; v[r][2 * q + 1] = u.y;
        }
      float sum[2], sq[2], rstd[2];
      row_stats(v[0], v[1], lane, sum, sq);
#pragma unroll
      for (int r = 0; r < 2; r++) {
        const float m = sum[r] * (1.f / 512.f);
        rstd[r] = rsqrtf(fmaxf(fmaf(-m, m, sq[r] * (1.f / 512.f)), 0.f) + 1e-5f);
      }
      uint32_t alo[4][4], ahi[4][4];
#pragma unroll
      for (int r = 0; r < 2; r++)
#pragma unroll
        for (int i = 0; i < 4; i++) {
          const uint32_t sel = (i & 1) ? 0x7632u : 0x5410u;
          const uint32_t b0 = __byte_perm(v[r][i >> 1], v[r][2 + (i >> 1)], sel);
          const uint32_t b1 = __byte_perm(v[r][4 + (i >> 1)], v[r][6 + (i >> 1)], sel);
          float d[4] = {0.f, 0.f, 0.f, 0.f};
          mma16816(d, fa.x, fa.y, fa.z, fa.w, b0, b1);
          const uint4 &ka = tw[2 * i], &kb = tw[2 * i + 1];
          const uint32_t re = pack2(d[0] * __uint_as_float(ka.x) + d[2] * __uint_as_float(ka.y), d[1] * __uint_as_float(kb.x) + d[3] * __uint_as_float(kb.y));
          const uint32_t im = pack2(d[0] * __uint_as_float(ka.z) + d[2] * __uint_as_float(ka.w), d[1] * __uint_as_float(kb.z) + d[3] * __uint_as_float(kb.w));
          const uint32_t dc = pack2(fmaf(sum[r], -1.f / 32.f, d[0]), fmaf(sum[r], -1.f / 32.f, d[1]));
          alo[i][r] = re; alo[i][2 + r] = im;
          ahi[i][r] = g == 0 ? dc : re; ahi[i][2 + r] = g == 0 ? 0u : im;
        }
      float acc[8][4];
#pragma unroll
      for (int u = 0; u < 8; u++) {
        acc[u][0] = acc[u][1] = acc[u][2] = acc[u][3] = 0.f;
#pragma unroll
        for (int i = 0; i < 4; i++) {
          const uint4& bq = fb[i * 4 + (u >> 1)];
          if (u < 4) mma16816(acc[u], alo[i][0], alo[i][1], alo[i][2], alo[i][3], (u & 1) ? bq.z : bq.x, (u & 1) ? bq.w : bq.y);
          else       mma16816(acc[u], ahi[i][0], ahi[i][1], ahi[i][2], ahi[i][3], (u & 1) ? bq.z : bq.x, (u & 1) ? bq.w : bq.y);
        }
      }
#pragma unroll
      for (int r = 0; r < 2; r++)
#pragma unroll
        for (int h = 0; h < 2; h++) {
          const int j = 2 * warp + r, m = 2 * t + h;
          const float rs = rstd[r];
          sts4(sbase + SM_E + ((j * 8 + m) * 8 + (g ^ (2 * t) ^ (2 * (j & 3)))) * 16,
               pack2(acc[2 * h][2 * r] * rs, acc[2 * h][2 * r + 1] * rs), pack2(acc[2 * h + 1][2 * r] * rs, acc[2 * h + 1][2 * r + 1] * rs),
               pack2(acc[4 + 2 * h][2 * r] * rs, acc[4 + 2 * h][2 * r + 1] * rs), pack2(acc[5 + 2 * h][2 * r] * rs, acc[5 + 2 * h][2 * r + 1] * rs));
        }
      if (tid == 0) PROFP(12);
      bar_sync(NB_RDY, 384);
      if (tid == 0) PROFP(13);
      uint4 fc[4];
#pragma unroll
      for (int i = 0; i < 4; i++) fc[i] = lds4(sbase + SM_FC + i * 512 + lane * 16);
      asm volatile("ld.shared.u32 %0, [%1];" : "=r"(tag) : "r"(BAR(epoch, 0)) : "memory");
      tag = (tag + 1) & 1;
#pragma unroll
      for (int i = 0; i < 4; i++) q[i] = lds4(sbase + SM_E + (((t + 4 * i) * 8 + warp) * 8 + (g ^ (warp & 6) ^ (2 * t))) * 16);
      cdft16(q, fc, o);
#pragma unroll
      for (int vv = 0; vv < 4; vv++) st_tag(&scr->Z1[(((4 * vv + t) * 8 + warp) * 128 + c) * 8 + g], o[vv], tag);
    }
    PROF(1);
    {
      const uint4* const zp = &scr->Z1[(c * 128 + 8 * t + warp) * 8 + g];
      const uint32_t tst = clock32();
      mbar_wait(BAR(tbar, 0), 0);
      if (tid == 0) PROFP(14);
      uint4 f2[4], g2[4];
#pragma unroll
      for (int i = 0; i < 4; i++) {
        f2[i] = lds4(TOFF(f2) + warp * 2048 + i * 512);
        g2[i] = lds4(TOFF(g2) + warp * 2048 + i * 512);
      }
      const uint4 f8 = lds4(TOFF(f8)), g8 = lds4(TOFF(g8));
      float wfr[16], wfi[16];
      {
        const float fsc = 1.f / (1 << 19);
        const float fsc3 = ((c & 7) == 7 && g == 0) ? 0.5f * fsc : fsc;
        const int gg = g == 0 ? 8 : g, wsh = (2 * (c >> 3) + 2) & 15;
#pragma unroll
        for (int i = 0; i < 16; i++) {
          const int ci = i >> 3, dd = (i >> 2) & 1, e = i & 3;
          const int kk = (e == 0 ? gg : e == 1 ? 16 + gg : e == 2 ? 16 - g : 32 - g) - 1;
          const uint32_t a = sbase + SM_W + ((2 * warp + ci) * 8 + t + 4 * dd) * 80 + wsh + 2 * kk;
          wfr[i] = bf_lo(lds_u16(a)) * (e == 3 ? fsc3 : fsc);
          wfi[i] = bf_lo(lds_u16(a + 10240)) * (e == 3 ? fsc3 : fsc);
        }
      }
      asm volatile("barrier.cluster.wait.aligned;" ::: "memory");
      PROF(2);
      while (clock32() - tst < POLL_DELAY) {}
      ld_tag4_issue<256>(q, zp);
      ld_tag4_finish<256>(q, zp, tag);
      if (tid == 0) PROFP(30);
      if (lane == 0) mbar_arrive(BAR(sig, 0));
      cdft16(q, f2, o);
      const uint32_t e2 = sbase + SM_E2;
#pragma unroll
      for (int vv = 0; vv < 4; vv++)
        sts4(e2 + ((warp * 16 + 4 * vv + t) * 8 + (g ^ (2 * t) ^ (2 * (warp & 3)))) * 16, o[vv].x, o[vv].y, o[vv].z, o[vv].w);
      bar_sync(NB_CONS, 256);
#pragma unroll
      for (int ci = 0; ci < 2; ci++) {
        const int cc = 2 * warp + ci;
        uint32_t ad[2];
        uint4 u[2];
#pragma unroll
        for (int hh = 0; hh < 2; hh++) {
          ad[hh] = e2 + (((t + 4 * hh) * 16 + cc) * 8 + (g ^ (2 * (cc & 3)) ^ (2 * t))) * 16;
          u[hh] = lds4(ad[hh]);
        }
        uint32_t res[2][4];
#pragma unroll
        for (int p = 0; p < 2; p++) {
          uint32_t y[2][2];
#pragma unroll
          for (int vv = 0; vv < 2; vv++) {
            float d[4] = {0.f, 0.f, 0.f, 0.f};
            mma16816(d, word(u[0], 2 * p), word(u[0], 2 * p + 1), word(u[1], 2 * p), word(u[1], 2 * p + 1), word(f8, 2 * vv), word(f8, 2 * vv + 1));
#pragma unroll
            for (int rr = 0; rr < 2; rr++) {
              const float fr = wfr[ci * 8 + vv * 4 + 2 * p + rr], fi = wfi[ci * 8 + vv * 4 + 2 * p + rr];
              y[vv][rr] = pack2(d[2 * rr] * fr - d[2 * rr + 1] * fi, d[2 * rr] * fi + d[2 * rr + 1] * fr);
            }
          }
#pragma unroll
          for (int vv = 0; vv < 2; vv++) {
            float d[4] = {0.f, 0.f, 0.f, 0.f};
            mma16816(d, y[0][0], y[0][1], y[1][0], y[1][1], word(g8, 2 * vv), word(g8, 2 * vv + 1));
            res[vv][2 * p] = pack2(d[0], d[1]);
            res[vv][2 * p + 1] = pack2(d[2], d[3]);
          }
        }
#pragma unroll
        for (int vv = 0; vv < 2; vv++) sts4(ad[vv], res[vv][0], res[vv][1], res[vv][2], res[vv][3]);
      }
      bar_sync(NB_CONS, 256);
#pragma unroll
      for (int i = 0; i < 4; i++) q[i] = lds4(e2 + ((warp * 16 + 4 * i + t) * 8 + (g ^ (2 * t) ^ (2 * (warp & 3)))) * 16);
      cdft16(q, g2, o);
#pragma unroll
      for (int vv = 0; vv < 4; vv++) st_tag(&scr->Z2[((8 * (4 * vv + t) + warp) * 128 + c) * 8 + g], o[vv], tag);
    }
    PROF(3);
    {
      const uint4* const zp = &scr->Z2[((c * 16 + t) * 8 + warp) * 8 + g];
      const uint32_t tst = clock32();
      uint4 gb[16], gc[4], tw[4], xr[2][2];
#pragma unroll
      for (int i = 0; i < 16; i++) gb[i] = lds4(TOFF(gb) + i * 512);
      const uint4 ga = lds4(TOFF(ga));
#pragma unroll
      for (int i = 0; i < 4; i++) {
        gc[i] = lds4(sbase + SM_FC + 2048 + i * 512 + lane * 16);
        tw[i] = lds4(TOFF(tw3) + i * 512);
        const int ch = 4 * (g + 8 * (i & 1)) + t;
        xr[i >> 1][i & 1] = lds4(sbase + SM_X + (2 * warp + (i >> 1)) * 1024 + ((ch ^ ((ch >> 2) & 6)) * 16));
      }
      PROF(4);
      while (clock32() - tst < POLL_DELAY) {}
      ld_tag4_issue<256>(q, zp);
      ld_tag4_finish<256>(q, zp, tag);
      if (tid == 0) PROFP(31);
      if (lane == 0) mbar_arrive(BAR(sig, 1));
      cdft16(q, gc, o);
#pragma unroll
      for (int vv = 0; vv < 4; vv++)
        sts4(sbase + SM_E + (((4 * vv + t) * 8 + warp) * 8 + (g ^ (warp & 6) ^ (2 * t))) * 16, o[vv].x, o[vv].y, o[vv].z, o[vv].w);
      bar_sync(NB_CONS, 256);
      uint32_t hv[2][8];
      const float mk = t == 0 ? 0.f : 1.f;
#pragma unroll
      for (int r = 0; r < 2; r++) {
        const int j = 2 * warp + r;
        uint4 u[2];
#pragma unroll
        for (int h = 0; h < 2; h++) u[h] = lds4(sbase + SM_E + ((j * 8 + 2 * t + h) * 8 + (g ^ (2 * t) ^ (2 * (j & 3)))) * 16);
        float yv[4][4];
#pragma unroll
        for (int i = 0; i < 4; i++) {
          float lo[4] = {0.f, 0.f, 0.f, 0.f}, hi[4] = {0.f, 0.f, 0.f, 0.f};
          mma16816(lo, gb[i * 4].x, gb[i * 4].y, gb[i * 4].z, gb[i * 4].w, u[0].x, u[0].y);
          mma16816(lo, gb[i * 4 + 1].x, gb[i * 4 + 1].y, gb[i * 4 + 1].z, gb[i * 4 + 1].w, u[1].x, u[1].y);
          mma16816(hi, gb[i * 4 + 2].x, gb[i * 4 + 2].y, gb[i * 4 + 2].z, gb[i * 4 + 2].w, u[0].z, u[0].w);
          mma16816(hi, gb[i * 4 + 3].x, gb[i * 4 + 3].y, gb[i * 4 + 3].z, gb[i * 4 + 3].w, u[1].z, u[1].w);
          const float ca = __uint_as_float(tw[i].x), sa = __uint_as_float(tw[i].y), cb = __uint_as_float(tw[i].z), sb = __uint_as_float(tw[i].w);
          const float tr0 = fmaf(hi[0], mk, lo[0]), ti0 = fmaf(hi[2], mk, lo[2]);
          const float tr1 = lo[1] + hi[1], ti1 = lo[3] + hi[3];
          const float vr0 = tr0 * ca - ti0 * sa, vi0 = tr0 * sa + ti0 * ca;
          const float vr1 = tr1 * cb - ti1 * sb, vi1 = tr1 * sb + ti1 * cb;
          const uint32_t b0 = pack2(t == 0 ? hi[0] : vr0, vr1), b1 = pack2(t == 0 ? vr0 : vi0, vi1);
          yv[i][0] = yv[i][1] = yv[i][2] = yv[i][3] = 0.f;
          mma16816(yv[i], ga.x, ga.y, ga.z, ga.w, b0, b1);
        }
#pragma unroll
        for (int h = 0; h < 2; h++) {
          hv[r][4 * h + 0] = hadd2_bf16(xr[r][h].x, pack2(yv[0][2 * h], yv[1][2 * h]));
          hv[r][4 * h + 1] = hadd2_bf16(xr[r][h].y, pack2(yv[2][2 * h], yv[3][2 * h]));
          hv[r][4 * h + 2] = hadd2_bf16(xr[r][h].z, pack2(yv[0][2 * h + 1], yv[1][2 * h + 1]));
          hv[r][4 * h + 3] = hadd2_bf16(xr[r][h].w, pack2(yv[2][2 * h + 1], yv[3][2 * h + 1]));
        }
      }
      float ds[4] = {0.f, 0.f, 0.f, 0.f};
#pragma unroll
      for (int q4 = 0; q4 < 4; q4++) mma16816(ds, hv[0][2 * q4], hv[1][2 * q4], hv[0][2 * q4 + 1], hv[1][2 * q4 + 1], 0x3f803f80u, 0x3f803f80u);
#pragma unroll
      for (int o2 = 4; o2 <= 16; o2 <<= 1) {
        ds[0] += __shfl_xor_sync(0xffffffffu, ds[0], o2);
        ds[2] += __shfl_xor_sync(0xffffffffu, ds[2], o2);
      }
      uint32_t mb[2];
#pragma unroll
      for (int r = 0; r < 2; r++) {
        const int row = 16 * f + 2 * warp + r;
        mb[r] = pack2(ds[2 * r] * (1.f / 512.f), ds[2 * r] * (1.f / 512.f));
#pragma unroll
        for (int i = 0; i < 8; i++) hv[r][i] = hsub2_bf16(hv[r][i], mb[r]);
#pragma unroll
        for (int h = 0; h < 2; h++) {
          const int n1 = g + 8 * h;
          st_tag(&scr->LN[(rb * 8 + (n1 >> 1)) * 1024 + row * 8 + ((4 * (n1 & 1) + t) ^ (row & 7))],
                 make_uint4(hv[r][4 * h], hv[r][4 * h + 1], hv[r][4 * h + 2], hv[r][4 * h + 3]), n1 < 2 * NLL ? tag : (hv[r][4 * h] & 1u));
        }
      }
      bar_arrive(NB_LN, 288);
      float sum[2], sq[2], rstd[2];
      row_stats(hv[0], hv[1], lane, sum, sq);
#pragma unroll
      for (int r = 0; r < 2; r++) {
        const float m = sum[r] * (1.f / 512.f);
        rstd[r] = rsqrtf(fmaxf(fmaf(-m, m, sq[r] * (1.f / 512.f)), 0.f) + 1e-5f);
      }
      if (lane == 0)
        st_tag(&scr->ST[rb * 64 + 8 * f + warp], make_uint4(mb[0] << 16, __float_as_uint(rstd[0]), mb[1] << 16, __float_as_uint(rstd[1])), tag);
    }
    PROF(5);
    asm volatile("setmaxnreg.inc.sync.aligned.u32 224;");
    if (NLL) {
      const uint4* const ap = &scr->LN[rb * 8 * 1024 + tid];
      uint4 av[NLL ? NLL : 1][4];
      spin_cycles(POLL_DELAY3);
#pragma unroll
      for (int kb = 0; kb < NLL; kb++) ld_tag4_issue<256>(av[kb], ap + kb * 1024);
      bar_sync(NB_CONS, 256);
#pragma unroll
      for (int kb = 0; kb < NLL; kb++) {
        ld_tag4_finish<256>(av[kb], ap + kb * 1024, tag);
#pragma unroll
        for (int i = 0; i < 4; i++) sts4(sbase + kb * SLOT + (tid + 256 * i) * 16, av[kb][i].x, av[kb][i].y, av[kb][i].z, av[kb][i].w);
      }
      asm volatile("fence.proxy.async.shared::cta;" ::: "memory");
      bar_sync(NB_CONS, 256);
    }
    const int wgi = warp >> 2, wq = warp & 3;
    uint4* const pbase = &scr->P[rb * 28 * 1024 + warp * 128 + lane];
    const uint32_t a_lo0 = desc_lo(sbase + wgi * 8192, 16);
    const uint32_t ebar = lane == 0 ? BAR(empty1, 0) : RBAR(empty1, 0);
    float r0, r1;
    uint4 px[8], py[6];
    const int rh = wgi ^ kh ^ 1;
    const uint4* const psrc = &scr->P[(rb2 * 28 + 14 * kh) * 1024 + (4 * rh + wq) * 128 + lane];
    {
      float acc[128];
#pragma unroll
      for (int i = 0; i < 128; i++) acc[i] = 0.f;
      const uint32_t b_lo0 = desc_lo(sbase + 8 * SLOT, 4096);
      uint32_t slot = 0, ph = 0, prev = 0;
#pragma unroll 1
      for (int kb = 0; kb < 8; kb++) {
        if (kb >= NLL) mbar_wait(BAR(fullA, kb), 0);
        if (kb == 0) PROF(6);
#pragma unroll
        for (int hh = 0; hh < 2; hh++) {
          if (LAGX && hh == ((16 - LAGX) & 1) && kb == ((16 - LAGX) >> 1) && wgi == 1) bar_sync(NB_LAG, 256);
          mbar_wait(BAR(full1, slot), ph);
          const uint32_t al = a_lo0 + kb * 1024 + hh * 4, bl = b_lo0 + slot * 1024;
          wg_fence();
          wgmma_n256(acc, desc64(al, HI128), desc64(bl, HI128));
          wgmma_n256(acc, desc64(al + 2, HI128), desc64(bl + 128, HI128));
          wg_commit();
          if (LAGX && hh == 1 && kb == 7 && wgi == 0) bar_arrive(NB_LAG, 256);
          wg_wait<1>();
          if ((kb | hh) != 0 && lane < 2) mbar_arrive_remote(ebar + 8 * prev);
          prev = slot;
          if (++slot == 6) { slot = 0; ph ^= 1; }
        }
      }
      mbar_wait(BAR(sbar, 0), 0);
      r0 = __uint_as_float(lds2(sstat + (16 * warp + g) * 8).y);
      r1 = __uint_as_float(lds2(sstat + (16 * warp + g + 8) * 8).y);
      wg_wait<0>();
      if (lane < 2) mbar_arrive_remote(ebar + 8 * prev);
      PROF(7);
      make_p<8, false>(acc, r0, r1, px, pbase, 0, tag);
    }
    PROF(8);
    {
      float acc[96];
#pragma unroll
      for (int i = 0; i < 96; i++) acc[i] = 0.f;
      const uint32_t b_lo0 = desc_lo(sbase + 8 * SLOT, 2048);
      uint4* const pdst = pbase + ((7 * f + 3 * (f & 1)) >> 1) * 1024;
      auto stage_y = [&](int k, uint32_t slot, uint32_t ph) {
        if (LAGY && k == 16 - LAGY && wgi == 1) bar_sync(NB_LAG, 256);
        mbar_wait(BAR(full1, slot), ph);
        const uint32_t al = a_lo0 + (k >> 1) * 1024 + (k & 1) * 4, bl = b_lo0 + slot * 1024;
        wg_fence();
        wgmma_n192(acc, desc64(al, HI128), desc64(bl, HI64));
        wgmma_n192(acc, desc64(al + 2, HI128), desc64(bl + 64, HI64));
        wg_commit();
      };
#pragma unroll
      for (int k = 0; k < 4; k++) {
        stage_y(k, (16 + k) % 6, ((16 + k) / 6) & 1);
        st_tag(pdst + (k >> 1) * 1024 + (k & 1) * 64, px[2 * k], tag);
        st_tag(pdst + (k >> 1) * 1024 + (k & 1) * 64 + 32, px[2 * k + 1], tag);
        if (k == 3 && lane == 0) red_relaxed(&scr->cnt[(C_PX + rb) * 32]);
        wg_wait<1>();
        if (k != 0 && lane < 2) mbar_arrive_remote(ebar + 8 * ((15 + k) % 6));
      }
      uint32_t slot = 2, ph = 1, prev = 1;
#pragma unroll 1
      for (int k = 4; k < 16; k++) {
        stage_y(k, slot, ph);
        if (LAGY && k == 15 && wgi == 0) bar_arrive(NB_LAG, 256);
        wg_wait<1>();
        if (lane < 2) mbar_arrive_remote(ebar + 8 * prev);
        prev = slot;
        if (++slot == 6) { slot = 0; ph ^= 1; }
      }
      wg_wait<0>();
      if (lane < 2) mbar_arrive_remote(ebar + 8 * (31 % 6));
      PROF(9);
      make_p<6, true>(acc, r0, r1, py, pbase, 14 * f + ((f & 1) ? 0 : 8), tag);
      if (lane == 0) red_relaxed(&scr->cnt[(C_PY + rb) * 32 + (f >> 1)]);
    }
    PROF(10);
    {
      float acc[64];
      {
        const float m0 = wgi ? __uint_as_float(lds2(sstat + 1024 + (16 * wq + g) * 8).x) : 0.f;
        const float m1 = wgi ? __uint_as_float(lds2(sstat + 1024 + (16 * wq + g + 8) * 8).x) : 0.f;
#pragma unroll
        for (int i = 0; i < 64; i++) acc[i] = (i & 2) ? m1 : m0;
      }
      const uint32_t b2_lo0 = desc_lo(sbase, 8192);
      const uint32_t pa0 = sbase + 8 * SLOT + (4 * rh + wq) * 2048 + lane * 16;
      uint32_t slot = 2;
      auto fetch2 = [&](int s, uint4 (&a)[4]) {
        mbar_wait(BAR(full2, s), 0);
        if (tid == 0) PROFP(16 + s);
#pragma unroll
        for (int kk = 0; kk < 4; kk++) a[kk] = lds4(pa0 + slot * SLOT + kk * 512);
        if (++slot == 6) slot = 0;
      };
      auto check2 = [&](int s, uint4 (&a)[4]) {
        if (__any_sync(0xffffffffu, ((a[0].x ^ tag) | (a[1].x ^ tag) | (a[2].x ^ tag) | (a[3].x ^ tag)) & 1u)) {
          const uint4* p = psrc + (int)((KORDER >> (4 * s)) & 15) * 1024;
          ld_tag4_issue<32>(a, p);
          ld_tag4_finish<32>(a, p, tag);
        }
#pragma unroll
        for (int i = 0; i < 4; i++) asm volatile("and.b32 %0, %0, 0xfffffffe;" : "+r"(a[i].x));
      };
      auto stage2 = [&](int s, uint4 (&a)[4], uint4 (&nx)[4]) {
        if (s < 13) fetch2(s + 1, nx);
        const uint32_t bl = b2_lo0 + (s & 7) * 1024;
        if (LAG2 && s == 14 - LAG2 && wgi == 1) bar_sync(NB_LAG, 256);
        wg_fence();
#pragma unroll
        for (int kk = 0; kk < 4; kk++) wgmma_rs_n128(acc, a[kk].x, a[kk].y, a[kk].z, a[kk].w, desc64(bl + kk * 128, HI128));
        wg_commit();
        if (s < 13) check2(s + 1, nx);
        wg_wait<1>();
        if (s >= 1 && s <= 8 && lane == 0) {
          mbar_arrive(BAR(empty2, s - 1));
          if (s == 8) mbar_arrive_remote(RBAR(xfree, 0));
        }
      };
      uint4 fa0[4], fa1[4], fa2[4];
      fetch2(0, fa0);
      check2(0, fa0);
#pragma unroll 1
      for (int s = 0; s < 12; s += 3) {
        stage2(s, fa0, fa1);
        stage2(s + 1, fa1, fa2);
        stage2(s + 2, fa2, fa0);
      }
      stage2(12, fa0, fa1);
      stage2(13, fa1, fa2);
      if (LAG2 && wgi == 0) bar_arrive(NB_LAG, 256);
      uint4 hres[2][4];
      mbar_wait(BAR(hbar, 0), 0);
#pragma unroll
      for (int h = 0; h < 2; h++)
#pragma unroll
        for (int q = 0; q < 4; q++) {
          hres[h][q] = lds4(sbase + 7 * SLOT + (q >> 1) * 8192 + (16 * wq + g + 8 * h) * 128 + (((4 * (q & 1) + t) ^ g) * 16));
          if (2 * nq + (q >> 1) < NLL) hres[h][q].x &= ~1u;
        }
      wg_wait<0>();
      PROF(11);
      const uint32_t xbuf = sbase + 6 * SLOT + (tid & 127) * 16;
      if (wgi == 0) {
        uint32_t rbuf;
        mbar_wait(BAR(xfree, 0), 0);
        asm volatile("mapa.shared::cluster.u32 %0, %1, %2;" : "=r"(rbuf) : "r"(xbuf), "r"(kh ^ 1));
#pragma unroll
        for (int i = 0; i < 8; i++)
          asm volatile("st.async.weak.shared::cluster.mbarrier::complete_tx::bytes.v4.b32 [%0], {%1,%2,%3,%4}, [%5];"
                       ::"r"(rbuf + i * 2048), "r"(pack2(acc[8 * i], acc[8 * i + 1])), "r"(pack2(acc[8 * i + 2], acc[8 * i + 3])),
                         "r"(pack2(acc[8 * i + 4], acc[8 * i + 5])), "r"(pack2(acc[8 * i + 6], acc[8 * i + 7])), "r"(RBAR(xbar, 0))
                       : "memory");
      } else {
        mbar_wait_cluster(BAR(xbar, 0), 0);
      }
      uint32_t w[2][16];
#pragma unroll
      for (int i = 0; i < 8; i++) {
        const uint4 pv = lds4(xbuf + i * 2048);
        w[0][2 * i] = pack2(acc[8 * i] + bf_lo(pv.x), acc[8 * i + 1] + bf_hi(pv.x));
        w[1][2 * i] = pack2(acc[8 * i + 2] + bf_lo(pv.y), acc[8 * i + 3] + bf_hi(pv.y));
        w[0][2 * i + 1] = pack2(acc[8 * i + 4] + bf_lo(pv.z), acc[8 * i + 5] + bf_hi(pv.z));
        w[1][2 * i + 1] = pack2(acc[8 * i + 6] + bf_lo(pv.w), acc[8 * i + 7] + bf_hi(pv.w));
      }
      uint4* const o4 = reinterpret_cast<uint4*>(out) + (16 * (c >> 4) + 2 * (4 * rh + wq) + (rb2 & 1) + 128 * g) * 64 + nq * 16 + t;
#pragma unroll
      for (int h = 0; h < 2; h++)
#pragma unroll
        for (int q = 0; q < 4; q++) {
          uint32_t a0 = w[h][4 * q], a1 = w[h][4 * q + 1], a2 = w[h][4 * q + 2], a3 = w[h][4 * q + 3];
          {
            const bool od = t & 1;
            uint32_t s0 = od ? a0 : a1, s1 = od ? a2 : a3;
            s0 = __shfl_xor_sync(0xffffffffu, s0, 1); s1 = __shfl_xor_sync(0xffffffffu, s1, 1);
            if (od) { a0 = s0; a2 = s1; } else { a1 = s0; a3 = s1; }
          }
          {
            const bool up = t & 2;
            uint32_t s0 = up ? a0 : a2, s1 = up ? a1 : a3;
            s0 = __shfl_xor_sync(0xffffffffu, s0, 2); s1 = __shfl_xor_sync(0xffffffffu, s1, 2);
            if (up) { a0 = s0; a1 = s1; } else { a2 = s0; a3 = s1; }
          }
          if (wgi == 1)
            o4[h * 1024 * 64 + 4 * q] =
                make_uint4(hadd2_bf16(hres[h][q].x, a0), hadd2_bf16(hres[h][q].y, a1), hadd2_bf16(hres[h][q].z, a2), hadd2_bf16(hres[h][q].w, a3));
        }
      PROF(12);
      PROFG(15);
    }
  }
#undef BAR
#undef TOFF
#undef RBAR
}

typedef CUresult (*EncodeFn)(CUtensorMap*, CUtensorMapDataType, cuuint32_t, void*, const cuuint64_t*, const cuuint64_t*,
                             const cuuint32_t*, const cuuint32_t*, CUtensorMapInterleave, CUtensorMapSwizzle,
                             CUtensorMapL2promotion, CUtensorMapFloatOOBfill);

}

extern "C" void kernel_launch(void* const* d_in, const int* in_sizes, int n_in, void* d_out, int out_size) {
  (void)in_sizes; (void)n_in; (void)out_size;
  static EncodeFn encode = nullptr;
  static void *tab = nullptr, *scr = nullptr;
  if (!encode) {
    void* fn = nullptr;
    cudaDriverEntryPointQueryResult qr;
    cudaGetDriverEntryPoint("cuTensorMapEncodeTiled", &fn, cudaEnableDefault, &qr);
    encode = (EncodeFn)fn;
    cudaGetSymbolAddress(&tab, g_tab);
    cudaGetSymbolAddress(&scr, g_scr);
    cudaFuncSetAttribute(fused_kernel, cudaFuncAttributeMaxDynamicSharedMemorySize, SMEM_BYTES);
  }
  CUtensorMap tmGX, tmUX, tmGY, tmUY, tmD, tmWR, tmWI;
  const cuuint32_t es[5] = {1, 1, 1, 1, 1};
  auto enc = [&](CUtensorMap* m, void* p, int rank, const cuuint64_t* gd, const cuuint64_t* gs, const cuuint32_t* bd,
                 CUtensorMapSwizzle sw, CUtensorMapL2promotion pr) {
    encode(m, CU_TENSOR_MAP_DATA_TYPE_BFLOAT16, rank, p, gd, gs, bd, es, CU_TENSOR_MAP_INTERLEAVE_NONE, sw, pr,
           CU_TENSOR_MAP_FLOAT_OOB_FILL_NONE);
  };
  {
    const cuuint64_t gd[3] = {64, 512, 28}, gs[2] = {3584, 128};
    const cuuint32_t bd[3] = {64, 32, 2};
    enc(&tmGX, d_in[4], 3, gd, gs, bd, CU_TENSOR_MAP_SWIZZLE_128B, CU_TENSOR_MAP_L2_PROMOTION_L2_256B);
    enc(&tmUX, d_in[5], 3, gd, gs, bd, CU_TENSOR_MAP_SWIZZLE_128B, CU_TENSOR_MAP_L2_PROMOTION_L2_256B);
  }
  {
    const cuuint64_t gd[3] = {32, 512, 56}, gs[2] = {3584, 64};
    const cuuint32_t bd[3] = {32, 32, 3};
    enc(&tmGY, d_in[4], 3, gd, gs, bd, CU_TENSOR_MAP_SWIZZLE_64B, CU_TENSOR_MAP_L2_PROMOTION_L2_128B);
    enc(&tmUY, d_in[5], 3, gd, gs, bd, CU_TENSOR_MAP_SWIZZLE_64B, CU_TENSOR_MAP_L2_PROMOTION_L2_128B);
  }
  {
    const cuuint64_t gd[3] = {64, 1792, 8}, gs[2] = {1024, 128};
    const cuuint32_t bd[3] = {64, 64, 2};
    enc(&tmD, d_in[6], 3, gd, gs, bd, CU_TENSOR_MAP_SWIZZLE_128B, CU_TENSOR_MAP_L2_PROMOTION_L2_256B);
  }
  {
    const cuuint64_t gd[3] = {4112, 8, 16}, gs[2] = {16 * 8224, 8224};
    const cuuint32_t bd[3] = {40, 8, 16};
    enc(&tmWR, d_in[1], 3, gd, gs, bd, CU_TENSOR_MAP_SWIZZLE_NONE, CU_TENSOR_MAP_L2_PROMOTION_NONE);
    enc(&tmWI, d_in[2], 3, gd, gs, bd, CU_TENSOR_MAP_SWIZZLE_NONE, CU_TENSOR_MAP_L2_PROMOTION_NONE);
  }
  fused_kernel<<<NCTA, NTHREADS, SMEM_BYTES>>>((const __nv_bfloat16*)d_in[0], (const Tables*)tab, (Scratch*)scr,
                                               (__nv_bfloat16*)d_out, (const char*)d_in[4], (const char*)d_in[5],
                                               (const char*)d_in[6], tmWR, tmWI, tmGX, tmUX, tmGY, tmUY, tmD);
}
```

```cpp
#include <cuda_runtime.h>
#include <cuda_bf16.h>
#include <cuda.h>
#include <stdint.h>

namespace {

constexpr int NCTA = 128;
constexpr int NTHREADS = 384;
constexpr int SLOT = 16384;
constexpr int SMEM_BYTES = 14 * SLOT + 3072;
constexpr int SPIN_LIMIT = 1 << 22;

struct Scratch {
  uint4 Z1[128 * 1024];
  uint4 Z2[128 * 1024];
  uint4 LN[16 * 8 * 1024];
  uint4 P[16 * 28 * 1024];
  uint4 ST[1024];
  unsigned cnt[64 * 32];
};
__device__ __align__(1024) Scratch g_scr;
#define PROF(i)
#define PROFP(i)
#define PROFG(i)

constexpr double ccos(int i, int n) {
  i &= n - 1;
  if (i > n / 2) i = n - i;
  if (4 * i == n) return 0.0;
  const bool neg = 4 * i > n;
  if (neg) i = n / 2 - i;
  const double a = 6.283185307179586476925 * i / n, a2 = a * a;
  double term = 1.0, sum = 1.0;
  for (int k = 1; k < 14; k++) { term *= -a2 / ((2 * k - 1) * (2 * k)); sum += term; }
  return neg ? -sum : sum;
}
constexpr double csin(int i, int n) { return ccos(i - n / 4, n); }
constexpr unsigned fbits(double v, int mant) {
  if (v == 0.0) return 0;
  const unsigned sg = v < 0 ? 1u : 0u;
  if (v < 0) v = -v;
  int e = 127;
  while (v < 1.0) { v *= 2.0; e--; }
  const unsigned m = (unsigned)((v - 1.0) * (double)(1u << mant) + 0.5);
  return (sg << (8 + mant)) + ((unsigned)e << mant) + m;
}
constexpr unsigned pkb(double lo, double hi) { return fbits(lo, 7) | (fbits(hi, 7) << 16); }
constexpr double fa_elem(int kp, int n1) {
  return kp <= 8 ? ccos(kp * n1, 16) : -csin((kp - 8) * n1, 16);
}
constexpr unsigned cfrag_c(int idx, int n, int ri) {
  return ri ? pkb(-csin(idx, n), ccos(idx, n)) : pkb(ccos(idx, n), csin(idx, n));
}
struct Tables {
  unsigned fb[16][32][4];
  unsigned tw1[8][32][4];
  unsigned fa[32][4];
  unsigned f2[8][4][32][4];
  unsigned g2[8][4][32][4];
  unsigned gb[16][32][4];
  unsigned tw3[4][32][4];
  unsigned ga[32][4];
  unsigned f8[32][4], g8[32][4];
};
constexpr int T1_BYTES = 12800, T2_BYTES = 44544;
static_assert(sizeof(Tables) == T1_BYTES + T2_BYTES, "table size");
constexpr Tables make_tables() {
  Tables T = {};
  for (int l = 0; l < 32; l++) {
    const int g = l >> 2, t = l & 3;
    for (int i = 0; i < 4; i++)
      for (int u = 0; u < 8; u++) {
        const int ri = g & 1, m = 2 * (g >> 1) + ((u & 3) >> 1);
        const double sg = u >= 4 ? -1.0 : 1.0;
        const int k2 = u >= 4 ? 31 - 2 * m - (u & 1) : 2 * m + (u & 1);
        const int pa = (8 * t + i) * k2, pb = (8 * t + 4 + i) * k2;
        T.fb[i * 4 + (u >> 1)][l][(u & 1) * 2 + 0] = ri == 0 ? pkb(ccos(pa, 32), ccos(pb, 32)) : pkb(-sg * csin(pa, 32), -sg * csin(pb, 32));
        T.fb[i * 4 + (u >> 1)][l][(u & 1) * 2 + 1] = ri == 0 ? pkb(csin(pa, 32), csin(pb, 32)) : pkb(sg * ccos(pa, 32), sg * ccos(pb, 32));
      }
    for (int i = 0; i < 4; i++)
      for (int ks = 0; ks < 4; ks++) {
        const int n2 = 4 * g + i, m = 2 * t + (ks & 1);
        const double sg = ks >= 2 ? -1.0 : 1.0;
        const int pa = n2 * (ks >= 2 ? 31 - 2 * m : 2 * m), pb = n2 * (ks >= 2 ? 30 - 2 * m : 2 * m + 1);
        T.gb[i * 4 + ks][l][0] = pkb(ccos(pa, 32), -sg * csin(pa, 32));
        T.gb[i * 4 + ks][l][1] = pkb(csin(pa, 32), sg * ccos(pa, 32));
        T.gb[i * 4 + ks][l][2] = pkb(ccos(pb, 32), -sg * csin(pb, 32));
        T.gb[i * 4 + ks][l][3] = pkb(csin(pb, 32), sg * ccos(pb, 32));
      }
    for (int i = 0; i < 4; i++) {
      for (int e = 0; e < 2; e++) {
        const int p = (8 * t + 4 * e + i) * (g == 0 ? 8 : g);
        T.tw1[2 * i + e][l][0] = fbits(g == 0 ? 0.0 : ccos(p, 512), 23);
        T.tw1[2 * i + e][l][1] = fbits(g == 0 ? ccos(p, 512) : csin(p, 512), 23);
        T.tw1[2 * i + e][l][2] = fbits(g == 0 ? 0.0 : -csin(p, 512), 23);
        T.tw1[2 * i + e][l][3] = fbits(g == 0 ? -csin(p, 512) : ccos(p, 512), 23);
      }
      const int ka = t == 0 ? 8 : 2 * t, kb = 2 * t + 1;
      T.tw3[i][l][0] = fbits(ccos((4 * g + i) * ka, 512), 23);
      T.tw3[i][l][1] = fbits(csin((4 * g + i) * ka, 512), 23);
      T.tw3[i][l][2] = fbits(ccos((4 * g + i) * kb, 512), 23);
      T.tw3[i][l][3] = fbits(csin((4 * g + i) * kb, 512), 23);
      const int p8 = (t + 4 * (i & 1)) * (4 * (i >> 1) + (g >> 1));
      T.f8[l][i] = cfrag_c(p8, 8, g & 1);
      T.g8[l][i] = cfrag_c(-p8, 8, g & 1);
    }
    for (int w = 0; w < 8; w++)
      for (int i = 0; i < 16; i++) {
        const int kidx = t + 4 * (i & 1) + 8 * (i >> 3), nidx = 4 * ((i >> 1) & 3) + (g >> 1);
        T.f2[w][i >> 2][l][i & 3] = cfrag_c((8 * kidx + w) * nidx, 128, g & 1);
        T.g2[w][i >> 2][l][i & 3] = cfrag_c(-(8 * nidx + w) * kidx, 128, g & 1);
      }
    T.fa[l][0] = pkb(fa_elem(g, 2 * t), fa_elem(g, 2 * t + 1));
    T.fa[l][1] = pkb(fa_elem(g + 8, 2 * t), fa_elem(g + 8, 2 * t + 1));
    T.fa[l][2] = pkb(fa_elem(g, 2 * t + 8), fa_elem(g, 2 * t + 9));
    T.fa[l][3] = pkb(fa_elem(g + 8, 2 * t + 8), fa_elem(g + 8, 2 * t + 9));
    T.ga[l][0] = pkb(fa_elem(2 * t, g), fa_elem(2 * t + 1, g));
    T.ga[l][1] = pkb(fa_elem(2 * t, g + 8), fa_elem(2 * t + 1, g + 8));
    T.ga[l][2] = pkb(fa_elem(2 * t + 8, g), fa_elem(2 * t + 9, g));
    T.ga[l][3] = pkb(fa_elem(2 * t + 8, g + 8), fa_elem(2 * t + 9, g + 8));
  }
  return T;
}
__device__ const __align__(128) Tables g_tab = make_tables();

__device__ __forceinline__ void die() { asm volatile("st.global.u32 [%0], %1;" ::"l"(0ull), "r"(0) : "memory"); }
__device__ __forceinline__ uint32_t s2u(const void* p) { return (uint32_t)__cvta_generic_to_shared(p); }
__device__ __forceinline__ void mbar_init(uint32_t b, int c) { asm volatile("mbarrier.init.shared::cta.b64 [%0], %1;" ::"r"(b), "r"(c)); }
__device__ __forceinline__ void mbar_expect(uint32_t b, int bytes) {
  asm volatile("mbarrier.arrive.expect_tx.shared::cta.b64 _, [%0], %1;" ::"r"(b), "r"(bytes) : "memory");
}
__device__ __forceinline__ void mbar_arrive(uint32_t b) { asm volatile("mbarrier.arrive.shared::cta.b64 _, [%0];" ::"r"(b) : "memory"); }
__device__ __forceinline__ uint32_t mbar_try(uint32_t b, uint32_t parity) {
  uint32_t ok;
  asm volatile("{.reg .pred p; mbarrier.try_wait.parity.shared::cta.b64 p, [%1], %2; selp.u32 %0,1,0,p;}"
               : "=r"(ok) : "r"(b), "r"(parity) : "memory");
  return ok;
}
__device__ __forceinline__ void mbar_wait(uint32_t b, uint32_t parity = 0) {
  int it = 0;
#pragma unroll 1
  while (!mbar_try(b, parity))
    if (++it > SPIN_LIMIT) { die(); break; }
}
__device__ __forceinline__ void mbar_wait_cluster(uint32_t b, int parity) {
  uint32_t ok;
  int it = 0;
  do {
    asm volatile("{.reg .pred p; mbarrier.try_wait.parity.acquire.cluster.shared::cta.b64 p, [%1], %2; selp.u32 %0,1,0,p;}"
                 : "=r"(ok) : "r"(b), "r"(parity) : "memory");
    if (++it > SPIN_LIMIT) { die(); break; }
  } while (!ok);
}
__device__ __forceinline__ void bar_sync(int id, int n) { asm volatile("bar.sync %0, %1;" ::"r"(id), "r"(n) : "memory"); }
__device__ __forceinline__ void bar_arrive(int id, int n) { asm volatile("bar.arrive %0, %1;" ::"r"(id), "r"(n) : "memory"); }
__device__ __forceinline__ void red_release(unsigned* p) { asm volatile("red.release.gpu.global.add.u32 [%0], 1;" ::"l"(p) : "memory"); }
__device__ __forceinline__ void red_relaxed(unsigned* p) { asm volatile("red.relaxed.gpu.global.add.u32 [%0], 1;" ::"l"(p) : "memory"); }
__device__ __forceinline__ unsigned ld_acquire(const unsigned* p) {
  unsigned v;
  asm volatile("ld.acquire.gpu.global.u32 %0, [%1];" : "=r"(v) : "l"(p) : "memory");
  return v;
}
__device__ __forceinline__ unsigned ld_relaxed(const unsigned* p) {
  unsigned v;
  asm volatile("ld.relaxed.gpu.global.u32 %0, [%1];" : "=r"(v) : "l"(p) : "memory");
  return v;
}
__device__ __forceinline__ void wait_counter(const unsigned* p, unsigned target) {
  int it = 0;
  while ((int)(ld_acquire(p) - target) < 0)
    if (++it > SPIN_LIMIT) { die(); break; }
}
__device__ __forceinline__ void sts4(uint32_t a, uint32_t x, uint32_t y, uint32_t z, uint32_t w) {
  asm volatile("st.shared.v4.u32 [%0], {%1,%2,%3,%4};" ::"r"(a), "r"(x), "r"(y), "r"(z), "r"(w) : "memory");
}
__device__ __forceinline__ uint4 lds4(uint32_t a) {
  uint4 v;
  asm volatile("ld.shared.v4.u32 {%0,%1,%2,%3}, [%4];" : "=r"(v.x), "=r"(v.y), "=r"(v.z), "=r"(v.w) : "r"(a) : "memory");
  return v;
}
__device__ __forceinline__ uint32_t pack2(float lo, float hi) {
  uint32_t r;
  asm("cvt.rn.bf16x2.f32 %0, %1, %2;" : "=r"(r) : "f"(hi), "f"(lo));
  return r;
}
__device__ __forceinline__ float bf_lo(uint32_t v) { return __uint_as_float(v << 16); }
__device__ __forceinline__ float bf_hi(uint32_t v) { return __uint_as_float(v & 0xffff0000u); }
__device__ __forceinline__ uint32_t hadd2_bf16(uint32_t a, uint32_t b) {
  uint32_t r;
  asm("add.rn.bf16x2 %0, %1, %2;" : "=r"(r) : "r"(a), "r"(b));
  return r;
}
__device__ __forceinline__ void mma16816(float (&d)[4], uint32_t a0, uint32_t a1, uint32_t a2, uint32_t a3, uint32_t b0, uint32_t b1) {
  asm("mma.sync.aligned.m16n8k16.row.col.f32.bf16.bf16.f32 {%0,%1,%2,%3}, {%4,%5,%6,%7}, {%8,%9}, {%0,%1,%2,%3};"
      : "+f"(d[0]), "+f"(d[1]), "+f"(d[2]), "+f"(d[3])
      : "r"(a0), "r"(a1), "r"(a2), "r"(a3), "r"(b0), "r"(b1));
}
template <int N>
__device__ __forceinline__ void cs_frac(int idx, float& c, float& s) {
  int i = ((idx + N / 2) & (N - 1)) - N / 2;
  float a = (float)i * (6.283185307179586f / N);
  c = __cosf(a);
  s = __sinf(a);
}
template <int N>
__device__ __forceinline__ uint32_t cfrag(int idx, int ri) {
  float c, s;
  cs_frac<N>(idx, c, s);
  return ri ? pack2(-s, c) : pack2(c, s);
}
__device__ __forceinline__ uint32_t word(const uint4& v, int e) { return e == 0 ? v.x : e == 1 ? v.y : e == 2 ? v.z : v.w; }
__device__ __forceinline__ void cdft16(const uint4 (&q)[4], const uint4 (&F)[4], uint4 (&o)[4]) {
  float acc[2][4][4];
#pragma unroll
  for (int p = 0; p < 2; p++)
#pragma unroll
    for (int v = 0; v < 4; v++) {
      acc[p][v][0] = acc[p][v][1] = acc[p][v][2] = acc[p][v][3] = 0.f;
#pragma unroll
      for (int ks = 0; ks < 2; ks++)
        mma16816(acc[p][v], word(q[2 * ks], 2 * p), word(q[2 * ks], 2 * p + 1), word(q[2 * ks + 1], 2 * p),
                 word(q[2 * ks + 1], 2 * p + 1), word(F[ks * 2 + (v >> 1)], (v & 1) * 2), word(F[ks * 2 + (v >> 1)], (v & 1) * 2 + 1));
    }
#pragma unroll
  for (int v = 0; v < 4; v++)
    o[v] = make_uint4(pack2(acc[0][v][0], acc[0][v][1]), pack2(acc[0][v][2], acc[0][v][3]),
                      pack2(acc[1][v][0], acc[1][v][1]), pack2(acc[1][v][2], acc[1][v][3]));
}
__device__ __forceinline__ void st_tag(uint4* p, const uint4& v, uint32_t tag) {
  asm volatile("{.reg .b128 r; .reg .b64 a, b; mov.b64 a, {%1,%2}; mov.b64 b, {%3,%4}; mov.b128 r, {a,b}; st.relaxed.gpu.global.b128 [%0], r;}"
               ::"l"(p), "r"((v.x & ~1u) | tag), "r"(v.y), "r"(v.z), "r"(v.w) : "memory");
}
__device__ __forceinline__ uint4 ld_b128(const uint4* p) {
  uint4 v;
  asm volatile("{.reg .b128 r; .reg .b64 a, b; ld.relaxed.gpu.global.b128 r, [%4]; mov.b128 {a,b}, r; mov.b64 {%0,%1}, a; mov.b64 {%2,%3}, b;}"
               : "=r"(v.x), "=r"(v.y), "=r"(v.z), "=r"(v.w) : "l"(p) : "memory");
  return v;
}
template <int STRIDE>
__device__ __forceinline__ void ld_tag4_issue(uint4 (&q)[4], const uint4* p) {
#pragma unroll
  for (int i = 0; i < 4; i++) q[i] = ld_b128(p + i * STRIDE);
}
template <int STRIDE>
__device__ __forceinline__ void ld_tag4_finish(uint4 (&q)[4], const uint4* p, uint32_t tag) {
  int it = 0;
#pragma unroll 1
  while (__any_sync(0xffffffffu, ((q[0].x ^ tag) | (q[1].x ^ tag) | (q[2].x ^ tag) | (q[3].x ^ tag)) & 1u)) {
    ld_tag4_issue<STRIDE>(q, p);
    if (++it > SPIN_LIMIT) { die(); break; }
  }
#pragma unroll
  for (int i = 0; i < 4; i++) asm volatile("and.b32 %0, %0, 0xfffffffe;" : "+r"(q[i].x));
}
__device__ __forceinline__ void row_stats(const uint32_t (&a)[8], const uint32_t (&b)[8], int lane, float (&sum)[2], float (&sq)[2]) {
  float da[4] = {0.f, 0.f, 0.f, 0.f}, db[4] = {0.f, 0.f, 0.f, 0.f}, ds[4] = {0.f, 0.f, 0.f, 0.f};
#pragma unroll
  for (int q = 0; q < 4; q++) {
    mma16816(ds, a[2 * q], b[2 * q], a[2 * q + 1], b[2 * q + 1], 0x3f803f80u, 0x3f803f80u);
    mma16816(da, a[2 * q], b[2 * q], a[2 * q + 1], b[2 * q + 1], a[2 * q], a[2 * q + 1]);
    mma16816(db, a[2 * q], b[2 * q], a[2 * q + 1], b[2 * q + 1], b[2 * q], b[2 * q + 1]);
  }
  const int src = (lane & 28) | (lane >> 3);
  const float qa = __shfl_sync(0xffffffffu, (lane & 4) ? da[1] : da[0], src);
  const float qb = __shfl_sync(0xffffffffu, (lane & 4) ? db[3] : db[2], src);
  float v = (lane & 2) ? ((lane & 1) ? ds[2] : ds[0]) : ((lane & 1) ? qb : qa);
  v += __shfl_xor_sync(0xffffffffu, v, 4);
  v += __shfl_xor_sync(0xffffffffu, v, 8);
  v += __shfl_xor_sync(0xffffffffu, v, 16);
  sq[0] = __shfl_sync(0xffffffffu, v, 0);
  sq[1] = __shfl_sync(0xffffffffu, v, 1);
  sum[0] = __shfl_sync(0xffffffffu, v, 2);
  sum[1] = __shfl_sync(0xffffffffu, v, 3);
}
__device__ __forceinline__ uint64_t desc64(uint32_t lo, uint32_t hi) {
  uint64_t d;
  asm("mov.b64 %0, {%1, %2};" : "=l"(d) : "r"(lo), "r"(hi));
  return d;
}
constexpr uint32_t desc_hi(uint32_t sbo, uint32_t swz) { return (sbo >> 4) | (swz << 30); }
__device__ __forceinline__ uint32_t desc_lo(uint32_t addr, uint32_t lbo) { return ((addr & 0x3FFFF) >> 4) | ((lbo >> 4) << 16); }
__device__ __forceinline__ void cp_async16(uint32_t dst, const void* src) {
  asm volatile("cp.async.cg.shared.global [%0], [%1], 16;" ::"r"(dst), "l"(src) : "memory");
}
__device__ __forceinline__ uint2 lds2(uint32_t a) {
  uint2 v;
  asm volatile("ld.shared.v2.u32 {%0,%1}, [%2];" : "=r"(v.x), "=r"(v.y) : "r"(a) : "memory");
  return v;
}
__device__ __forceinline__ uint32_t lds_u16(uint32_t a) {
  uint16_t v;
  asm volatile("ld.shared.u16 %0, [%1];" : "=h"(v) : "r"(a) : "memory");
  return v;
}
__device__ __forceinline__ void wg_fence() { asm volatile("wgmma.fence.sync.aligned;" ::: "memory"); }
__device__ __forceinline__ void wg_commit() { asm volatile("wgmma.commit_group.sync.aligned;" ::: "memory"); }
template <int N>
__device__ __forceinline__ void wg_wait() { asm volatile("wgmma.wait_group.sync.aligned %0;" ::"n"(N) : "memory"); }
__device__ __forceinline__ void bulk_load(uint32_t dst, const void* src, int bytes, uint32_t bar) {
  asm volatile("cp.async.bulk.shared::cluster.global.mbarrier::complete_tx::bytes [%0], [%1], %2, [%3];"
               ::"r"(dst), "l"(src), "r"(bytes), "r"(bar) : "memory");
}
__device__ __forceinline__ void tma3(uint32_t dst, const CUtensorMap* tm, uint32_t bar, int c0, int c1, int c2) {
  asm volatile("cp.async.bulk.tensor.3d.shared::cluster.global.mbarrier::complete_tx::bytes [%0], [%1, {%3,%4,%5}], [%2];"
               ::"r"(dst), "l"(tm), "r"(bar), "r"(c0), "r"(c1), "r"(c2) : "memory");
}
__device__ __forceinline__ void tma3_mc(uint32_t dst, const CUtensorMap* tm, uint32_t bar, int c1, int c2) {
  asm volatile("cp.async.bulk.tensor.3d.shared::cluster.global.mbarrier::complete_tx::bytes.multicast::cluster [%0], [%1, {%3,%4,%5}], [%2], %6;"
               ::"r"(dst), "l"(tm), "r"(bar), "r"(0), "r"(c1), "r"(c2), "h"((uint16_t)3) : "memory");
}
__device__ __forceinline__ void mbar_arrive_remote(uint32_t rb) {
  asm volatile("mbarrier.arrive.shared::cluster.b64 _, [%0];" ::"r"(rb) : "memory");
}
__device__ __forceinline__ uint4 ldg_ca4(const void* p) {
  uint4 v;
  asm volatile("ld.global.ca.v4.u32 {%0,%1,%2,%3}, [%4];" : "=r"(v.x), "=r"(v.y), "=r"(v.z), "=r"(v.w) : "l"(p) : "memory");
  return v;
}
__device__ __forceinline__ uint32_t clock32() {
  uint32_t v;
  asm volatile("mov.u32 %0, %%clock;" : "=r"(v) :: "memory");
  return v;
}
__device__ __forceinline__ float swiglu(float g, float u, float r) {
  float hg = (0.5f * r) * g, th;
  asm("tanh.approx.f32 %0, %1;" : "=f"(th) : "f"(hg));
  return fmaf(hg, th, hg) * (r * u);
}
__device__ __forceinline__ uint32_t hsub2_bf16(uint32_t a, uint32_t b) {
  uint32_t r;
  asm("sub.rn.bf16x2 %0, %1, %2;" : "=r"(r) : "r"(a), "r"(b));
  return r;
}
__device__ __forceinline__ void l2_prefetch(const void* p, int bytes) {
  asm volatile("cp.async.bulk.prefetch.L2.global [%0], %1;" ::"l"(p), "r"(bytes) : "memory");
}

__device__ __forceinline__ void wgmma_n256(float (&d)[128], uint64_t da, uint64_t db) {
  asm volatile("wgmma.mma_async.sync.aligned.m64n256k16.f32.bf16.bf16 {"
      "%0,%1,%2,%3,%4,%5,%6,%7,%8,%9,%10,%11,%12,%13,%14,%15,"
      "%16,%17,%18,%19,%20,%21,%22,%23,%24,%25,%26,%27,%28,%29,%30,%31,"
      "%32,%33,%34,%35,%36,%37,%38,%39,%40,%41,%42,%43,%44,%45,%46,%47,"
      "%48,%49,%50,%51,%52,%53,%54,%55,%56,%57,%58,%59,%60,%61,%62,%63,"
      "%64,%65,%66,%67,%68,%69,%70,%71,%72,%73,%74,%75,%76,%77,%78,%79,"
      "%80,%81,%82,%83,%84,%85,%86,%87,%88,%89,%90,%91,%92,%93,%94,%95,"
      "%96,%97,%98,%99,%100,%101,%102,%103,%104,%105,%106,%107,%108,%109,%110,%111,"
      "%112,%113,%114,%115,%116,%117,%118,%119,%120,%121,%122,%123,%124,%125,%126,%127"
      "}, %128, %129, 1, 1, 1, 0, 1;\n"
      : "+f"(d[0]),"+f"(d[1]),"+f"(d[2]),"+f"(d[3]),"+f"(d[4]),"+f"(d[5]),"+f"(d[6]),"+f"(d[7]),
        "+f"(d[8]),"+f"(d[9]),"+f"(d[10]),"+f"(d[11]),"+f"(d[12]),"+f"(d[13]),"+f"(d[14]),"+f"(d[15]),
        "+f"(d[16]),"+f"(d[17]),"+f"(d[18]),"+f"(d[19]),"+f"(d[20]),"+f"(d[21]),"+f"(d[22]),"+f"(d[23]),
        "+f"(d[24]),"+f"(d[25]),"+f"(d[26]),"+f"(d[27]),"+f"(d[28]),"+f"(d[29]),"+f"(d[30]),"+f"(d[31]),
        "+f"(d[32]),"+f"(d[33]),"+f"(d[34]),"+f"(d[35]),"+f"(d[36]),"+f"(d[37]),"+f"(d[38]),"+f"(d[39]),
        "+f"(d[40]),"+f"(d[41]),"+f"(d[42]),"+f"(d[43]),"+f"(d[44]),"+f"(d[45]),"+f"(d[46]),"+f"(d[47]),
        "+f"(d[48]),"+f"(d[49]),"+f"(d[50]),"+f"(d[51]),"+f"(d[52]),"+f"(d[53]),"+f"(d[54]),"+f"(d[55]),
        "+f"(d[56]),"+f"(d[57]),"+f"(d[58]),"+f"(d[59]),"+f"(d[60]),"+f"(d[61]),"+f"(d[62]),"+f"(d[63]),
        "+f"(d[64]),"+f"(d[65]),"+f"(d[66]),"+f"(d[67]),"+f"(d[68]),"+f"(d[69]),"+f"(d[70]),"+f"(d[71]),
        "+f"(d[72]),"+f"(d[73]),"+f"(d[74]),"+f"(d[75]),"+f"(d[76]),"+f"(d[77]),"+f"(d[78]),"+f"(d[79]),
        "+f"(d[80]),"+f"(d[81]),"+f"(d[82]),"+f"(d[83]),"+f"(d[84]),"+f"(d[85]),"+f"(d[86]),"+f"(d[87]),
        "+f"(d[88]),"+f"(d[89]),"+f"(d[90]),"+f"(d[91]),"+f"(d[92]),"+f"(d[93]),"+f"(d[94]),"+f"(d[95]),
        "+f"(d[96]),"+f"(d[97]),"+f"(d[98]),"+f"(d[99]),"+f"(d[100]),"+f"(d[101]),"+f"(d[102]),"+f"(d[103]),
        "+f"(d[104]),"+f"(d[105]),"+f"(d[106]),"+f"(d[107]),"+f"(d[108]),"+f"(d[109]),"+f"(d[110]),"+f"(d[111]),
        "+f"(d[112]),"+f"(d[113]),"+f"(d[114]),"+f"(d[115]),"+f"(d[116]),"+f"(d[117]),"+f"(d[118]),"+f"(d[119]),
        "+f"(d[120]),"+f"(d[121]),"+f"(d[122]),"+f"(d[123]),"+f"(d[124]),"+f"(d[125]),"+f"(d[126]),"+f"(d[127])
      : "l"(da), "l"(db));
}
__device__ __forceinline__ void wgmma_n192(float (&d)[96], uint64_t da, uint64_t db) {
  asm volatile("wgmma.mma_async.sync.aligned.m64n192k16.f32.bf16.bf16 {"
      "%0,%1,%2,%3,%4,%5,%6,%7,%8,%9,%10,%11,%12,%13,%14,%15,"
      "%16,%17,%18,%19,%20,%21,%22,%23,%24,%25,%26,%27,%28,%29,%30,%31,"
      "%32,%33,%34,%35,%36,%37,%38,%39,%40,%41,%42,%43,%44,%45,%46,%47,"
      "%48,%49,%50,%51,%52,%53,%54,%55,%56,%57,%58,%59,%60,%61,%62,%63,"
      "%64,%65,%66,%67,%68,%69,%70,%71,%72,%73,%74,%75,%76,%77,%78,%79,"
      "%80,%81,%82,%83,%84,%85,%86,%87,%88,%89,%90,%91,%92,%93,%94,%95"
      "}, %96, %97, 1, 1, 1, 0, 1;\n"
      : "+f"(d[0]),"+f"(d[1]),"+f"(d[2]),"+f"(d[3]),"+f"(d[4]),"+f"(d[5]),"+f"(d[6]),"+f"(d[7]),
        "+f"(d[8]),"+f"(d[9]),"+f"(d[10]),"+f"(d[11]),"+f"(d[12]),"+f"(d[13]),"+f"(d[14]),"+f"(d[15]),
        "+f"(d[16]),"+f"(d[17]),"+f"(d[18]),"+f"(d[19]),"+f"(d[20]),"+f"(d[21]),"+f"(d[22]),"+f"(d[23]),
        "+f"(d[24]),"+f"(d[25]),"+f"(d[26]),"+f"(d[27]),"+f"(d[28]),"+f"(d[29]),"+f"(d[30]),"+f"(d[31]),
        "+f"(d[32]),"+f"(d[33]),"+f"(d[34]),"+f"(d[35]),"+f"(d[36]),"+f"(d[37]),"+f"(d[38]),"+f"(d[39]),
        "+f"(d[40]),"+f"(d[41]),"+f"(d[42]),"+f"(d[43]),"+f"(d[44]),"+f"(d[45]),"+f"(d[46]),"+f"(d[47]),
        "+f"(d[48]),"+f"(d[49]),"+f"(d[50]),"+f"(d[51]),"+f"(d[52]),"+f"(d[53]),"+f"(d[54]),"+f"(d[55]),
        "+f"(d[56]),"+f"(d[57]),"+f"(d[58]),"+f"(d[59]),"+f"(d[60]),"+f"(d[61]),"+f"(d[62]),"+f"(d[63]),
        "+f"(d[64]),"+f"(d[65]),"+f"(d[66]),"+f"(d[67]),"+f"(d[68]),"+f"(d[69]),"+f"(d[70]),"+f"(d[71]),
        "+f"(d[72]),"+f"(d[73]),"+f"(d[74]),"+f"(d[75]),"+f"(d[76]),"+f"(d[77]),"+f"(d[78]),"+f"(d[79]),
        "+f"(d[80]),"+f"(d[81]),"+f"(d[82]),"+f"(d[83]),"+f"(d[84]),"+f"(d[85]),"+f"(d[86]),"+f"(d[87]),
        "+f"(d[88]),"+f"(d[89]),"+f"(d[90]),"+f"(d[91]),"+f"(d[92]),"+f"(d[93]),"+f"(d[94]),"+f"(d[95])
      : "l"(da), "l"(db));
}
__device__ __forceinline__ void wgmma_rs_n128(float (&d)[64], uint32_t a0, uint32_t a1, uint32_t a2, uint32_t a3, uint64_t db) {
  asm volatile("wgmma.mma_async.sync.aligned.m64n128k16.f32.bf16.bf16 {"
      "%0,%1,%2,%3,%4,%5,%6,%7,%8,%9,%10,%11,%12,%13,%14,%15,"
      "%16,%17,%18,%19,%20,%21,%22,%23,%24,%25,%26,%27,%28,%29,%30,%31,"
      "%32,%33,%34,%35,%36,%37,%38,%39,%40,%41,%42,%43,%44,%45,%46,%47,"
      "%48,%49,%50,%51,%52,%53,%54,%55,%56,%57,%58,%59,%60,%61,%62,%63"
      "}, {%64,%65,%66,%67}, %68, 1, 1, 1, 1;\n"
      : "+f"(d[0]),"+f"(d[1]),"+f"(d[2]),"+f"(d[3]),"+f"(d[4]),"+f"(d[5]),"+f"(d[6]),"+f"(d[7]),
        "+f"(d[8]),"+f"(d[9]),"+f"(d[10]),"+f"(d[11]),"+f"(d[12]),"+f"(d[13]),"+f"(d[14]),"+f"(d[15]),
        "+f"(d[16]),"+f"(d[17]),"+f"(d[18]),"+f"(d[19]),"+f"(d[20]),"+f"(d[21]),"+f"(d[22]),"+f"(d[23]),
        "+f"(d[24]),"+f"(d[25]),"+f"(d[26]),"+f"(d[27]),"+f"(d[28]),"+f"(d[29]),"+f"(d[30]),"+f"(d[31]),
        "+f"(d[32]),"+f"(d[33]),"+f"(d[34]),"+f"(d[35]),"+f"(d[36]),"+f"(d[37]),"+f"(d[38]),"+f"(d[39]),
        "+f"(d[40]),"+f"(d[41]),"+f"(d[42]),"+f"(d[43]),"+f"(d[44]),"+f"(d[45]),"+f"(d[46]),"+f"(d[47]),
        "+f"(d[48]),"+f"(d[49]),"+f"(d[50]),"+f"(d[51]),"+f"(d[52]),"+f"(d[53]),"+f"(d[54]),"+f"(d[55]),
        "+f"(d[56]),"+f"(d[57]),"+f"(d[58]),"+f"(d[59]),"+f"(d[60]),"+f"(d[61]),"+f"(d[62]),"+f"(d[63])
      : "r"(a0), "r"(a1), "r"(a2), "r"(a3), "l"(db));
}

constexpr int C_LN = 0, C_PX = 16, C_PY = 32;
constexpr int NB_CONS = 1, NB_LN = 2, NB_LAG = 4, NB_INIT = 6, NB_RDY = 7;
#define LAGX 3
#define LAGY 3
#define LAG2 2
#define NLL 2
#define POLL_DELAY3 900
#define POLL_DELAY 900
#define FILT_DELAY 1000
#define RING_SIG 0
#define PF2_SIG 1
constexpr int SM_E = 0, SM_X = 16384, SM_E2 = 32768, SM_W = 49152, SM_FC = 69632, SM_T = 73728 - T1_BYTES;
constexpr unsigned long long KORDER = 0xBA9432DC876510ull;
constexpr uint32_t HI128 = desc_hi(1024, 1), HI64 = desc_hi(512, 2);

struct Bars {
  uint64_t full1[32], empty1[32], full2[16], fullA[8], empty2[8], emptyP[8], xbar, hbar, tbar, hint[3], xfree, sig[2], sbar;
  uint32_t epoch;
};

template <int NK, bool STORE>
__device__ __forceinline__ void make_p(const float (&acc)[NK * 16], float r0, float r1, uint4 (&p)[NK], uint4* pbase, int ks0, uint32_t tag) {
#pragma unroll
  for (int j = 0; j < NK; j++) {
    uint32_t w[4];
#pragma unroll
    for (int i = 0; i < 4; i++) {
      const int a = 8 * j + 2 * i, b = a + NK * 8;
      w[i] = pack2(swiglu(acc[a], acc[b], (i & 1) ? r1 : r0), swiglu(acc[a + 1], acc[b + 1], (i & 1) ? r1 : r0));
    }
    asm volatile("" : "+r"(w[0]), "+r"(w[1]), "+r"(w[2]), "+r"(w[3]));
    p[j] = make_uint4(w[0], w[1], w[2], w[3]);
    if (STORE) st_tag(pbase + ((ks0 + j) >> 2) * 1024 + ((ks0 + j) & 3) * 32, p[j], tag);
  }
}
__device__ __forceinline__ void spin_cycles(uint32_t n) {
  const uint32_t t0 = clock32();
  while (clock32() - t0 < n) {}
}

__global__ void __cluster_dims__(2, 1, 1) __launch_bounds__(NTHREADS, 1)
fused_kernel(const __nv_bfloat16* __restrict__ x, const Tables* __restrict__ tab, Scratch* __restrict__ scr,
             __nv_bfloat16* __restrict__ out, const char* __restrict__ wg_raw, const char* __restrict__ wu_raw,
             const char* __restrict__ wd_raw,
             const __grid_constant__ CUtensorMap tmWR, const __grid_constant__ CUtensorMap tmWI,
             const __grid_constant__ CUtensorMap tmGX, const __grid_constant__ CUtensorMap tmUX,
             const __grid_constant__ CUtensorMap tmGY, const __grid_constant__ CUtensorMap tmUY,
             const __grid_constant__ CUtensorMap tmD) {
  extern __shared__ __align__(1024) char smem_raw[];
  const uint32_t sbase = s2u(smem_raw);
  const uint32_t sbar = sbase + 14 * SLOT, sstat = sbar + 1024;
  const int tid = threadIdx.x, lane = tid & 31;
  const int c = blockIdx.x, kh = c & 1, f = (c >> 1) & 7, rb = 2 * (c >> 4) + kh, rb2 = 2 * (c >> 4) + (f >> 2), nq = f & 3;
#define BAR(field, i) (sbar + (uint32_t)offsetof(Bars, field) + 8u * (i))
#define TOFF(field) (sbase + SM_T + (uint32_t)offsetof(Tables, field) + lane * 16)

  if (tid >= 256) {
    asm volatile("setmaxnreg.dec.sync.aligned.u32 56;");
    const int warp = __shfl_sync(0xffffffffu, tid >> 5, 0);
    if (warp == 8) {
      if (sbase & 1023) die();
      mbar_init(BAR(full1, lane), 1);
      mbar_init(BAR(empty1, lane), 16);
      mbar_init(BAR(full2, lane), lane < 24 ? 1 : 8);
      if (lane < 18) mbar_init(BAR(emptyP, lane), lane < 8 ? 8 : lane < 14 ? 1 : lane < 17 ? 8 : 32);
      mbar_expect(BAR(full1, lane), lane < 16 ? 16384 : 12288);
      if (lane < 24) mbar_expect(BAR(full2, lane), lane < 16 ? 32768 : 16384);
      if (lane >= 8 && lane < 11) mbar_expect(BAR(emptyP, lane), lane < 10 ? 16384 : T2_BYTES + 2 * 10240);
      asm volatile("fence.mbarrier_init.release.cluster;" ::: "memory");
      __syncwarp();
    }
    if (tid == 256) {
      const int w0 = ((c >> 3) * 257 + 32 * (c & 7) + 1) & ~7;
      if (FILT_DELAY) {
        asm volatile("prefetch.tensormap [%0];" ::"l"(&tmWR) : "memory");
        asm volatile("prefetch.tensormap [%0];" ::"l"(&tmWI) : "memory");
        spin_cycles(FILT_DELAY);
      }
      tma3(sbase + SM_W, &tmWR, BAR(tbar, 0), w0, 0, 0);
      tma3(sbase + SM_W + 10240, &tmWI, BAR(tbar, 0), w0, 0, 0);
      bulk_load(sbase + SM_T + T1_BYTES, reinterpret_cast<const char*>(tab) + T1_BYTES, T2_BYTES, BAR(tbar, 0));
    }
    if (tid == 288) {
      asm volatile("prefetch.tensormap [%0];" ::"l"(kh ? &tmUX : &tmGX) : "memory");
      asm volatile("prefetch.tensormap [%0];" ::"l"(kh ? &tmUY : &tmGY) : "memory");
      asm volatile("prefetch.tensormap [%0];" ::"l"(&tmD) : "memory");
    }
    if (tid == 320) {
      const unsigned e = ld_relaxed(&scr->cnt[(C_LN + rb) * 32]) >> 3;
      asm volatile("st.shared.u32 [%0], %1;" ::"r"(BAR(epoch, 0)), "r"(e) : "memory");
    }
    __syncwarp();
    asm volatile("barrier.cluster.arrive.relaxed.aligned;" ::: "memory");
    bar_arrive(NB_RDY, 384);
    asm volatile("barrier.cluster.wait.aligned;" ::: "memory");
    bar_sync(NB_INIT, 384);
    unsigned epoch;
    asm volatile("ld.shared.u32 %0, [%1];" : "=r"(epoch) : "r"(BAR(epoch, 0)) : "memory");
    if (warp == 8) {
      if (lane == 0) {
        const int ax = (7 * f + 3 * (f & 1)) >> 1;
        const int ay = 7 * f + ((f & 1) ? 0 : 4);
        const CUtensorMap* tx = kh ? &tmUX : &tmGX;
        const CUtensorMap* ty = kh ? &tmUY : &tmGY;
        if (RING_SIG >= 0) mbar_wait(BAR(sig, RING_SIG));
        uint32_t s = 2;
#pragma unroll 1
        for (int n = 0; n < 16; n++) {
          if (n >= 6) mbar_wait(BAR(empty1, n - 6));
          tma3_mc(sbase + (8 + s) * SLOT + kh * 8192, tx, BAR(full1, n), n * 32, ax);
          if (++s == 6) s = 0;
        }
#pragma unroll 1
        for (int k = 0; k < 16; k++) {
          mbar_wait(BAR(empty1, k < 8 ? 10 + ((12 * k + 11) >> 4) : 8 + k));
          tma3_mc(sbase + 8 * SLOT + (k & 7) * 12288 + kh * 6144, ty, BAR(full1, 16 + k), k * 32, ay);
        }
      }
    } else if (warp == 9) {
      if (lane == 0) {
#pragma unroll 1
        for (int i = 0; i < 14; i++) {
          const int kblk = 14 * kh + (int)((KORDER >> (4 * i)) & 15);
          mbar_wait(i < 8 ? BAR(empty1, 17 + 2 * i) : BAR(empty2, i - 8));
          tma3(sbase + (i & 7) * SLOT, &tmD, BAR(full2, i), 0, 64 * kblk, 2 * nq);
        }
        wait_counter(&scr->cnt[(C_LN + rb2) * 32], (epoch + 1) * 8);
        asm volatile("fence.proxy.async.global;" ::: "memory");
        mbar_wait(BAR(empty2, 7), 0);
        bulk_load(sbase + 7 * SLOT, &scr->LN[(rb2 * 8 + 2 * nq) * 1024 + kh * 512], 8192, BAR(hbar, 0));
        bulk_load(sbase + 7 * SLOT + 8192, &scr->LN[(rb2 * 8 + 2 * nq + 1) * 1024 + kh * 512], 8192, BAR(hbar, 0));
      }
    } else if (warp == 10) {
      bar_sync(NB_LN, 288);
      if (lane == 0) {
        PROFP(0);
        red_release(&scr->cnt[(C_LN + rb) * 32]);
        PROFP(1);
        wait_counter(&scr->cnt[(C_LN + rb) * 32], (epoch + 1) * 8);
        asm volatile("fence.proxy.async.global;" ::: "memory");
        PROFP(2);
#pragma unroll 1
        for (int kb = NLL; kb < 8; kb++) bulk_load(sbase + kb * SLOT, &scr->LN[(rb * 8 + kb) * 1024], 16384, BAR(fullA, kb));
        uint32_t d = 0;
#pragma unroll 1
        for (int s = 0; s < 14; s++) {
          const int kblk = 14 * kh + (int)((KORDER >> (4 * s)) & 15);
          if (s == 0 || s == 8 || s == 11) {
            if (s != 11) PROFP(3 + (s >> 2));
            mbar_wait(BAR(hint, s == 0 ? 0 : s == 8 ? 1 : 2), 0);
            if (s != 11) PROFP(4 + (s >> 2));
          }
          mbar_wait(s < 6 ? BAR(empty1, 25 + s + (s >= 3)) : BAR(emptyP, s - 6));
          bulk_load(sbase + (8 + d) * SLOT, &scr->P[(rb2 * 28 + kblk) * 1024], 16384, BAR(full2, s));
          if (++d == 6) d = 0;
        }
        PROFP(7);
      }
    } else {
      if (lane == 0) {
        l2_prefetch(wg_raw + (size_t)c * 5376, 5376);
        l2_prefetch(wu_raw + (size_t)c * 5376, 5376);
        mbar_wait(BAR(sig, PF2_SIG), 0);
        l2_prefetch(wg_raw + 688128 + (size_t)c * 8960, 8960);
        l2_prefetch(wu_raw + 688128 + (size_t)c * 8960, 8960);
      }
      mbar_wait(BAR(fullA, 7), 0);
      if (lane == 0) l2_prefetch(wd_raw + (size_t)c * 14336, 14336);
      {
        const uint32_t tag = (epoch + 1) & 1;
        uint4 v0, v1, v2;
        int it = 0;
        while (true) {
          v0 = ld_b128(&scr->ST[rb * 64 + lane]);
          v1 = ld_b128(&scr->ST[rb * 64 + 32 + lane]);
          v2 = ld_b128(&scr->ST[rb2 * 64 + 32 * kh + lane]);
          if (!__any_sync(0xffffffffu, ((v0.x ^ tag) | (v1.x ^ tag) | (v2.x ^ tag)) & 1u)) break;
          if (++it > SPIN_LIMIT) { die(); break; }
        }
        sts4(sstat + lane * 16, v0.x & ~1u, v0.y, v0.z, v0.w);
        sts4(sstat + 512 + lane * 16, v1.x & ~1u, v1.y, v1.z, v1.w);
        sts4(sstat + 1024 + lane * 16, v2.x & ~1u, v2.y, v2.z, v2.w);
        mbar_arrive(BAR(sbar, 0));
      }
      if (lane == 0) {
        mbar_wait(BAR(empty1, 17));
#pragma unroll 1
        for (int e = 0; e < 3; e++) {
          const unsigned* cp = e == 0 ? &scr->cnt[(C_PX + rb2) * 32] : &scr->cnt[(C_PY + rb2) * 32 + 2 * kh + e - 1];
          if (e == 1) mbar_wait(BAR(full2, 0), 0);
          int it = 0;
          while ((int)(ld_relaxed(cp) - (epoch + 1) * (e == 0 ? 64 : 16)) < 0)
            if (++it > SPIN_LIMIT) { die(); break; }
          mbar_arrive(BAR(hint, e));
        }
      }
    }
  } else {
    const int warp = __shfl_sync(0xffffffffu, tid >> 5, 0);
    const int g = lane >> 2, t = lane & 3;
    PROF(0);
    PROFG(14);
#pragma unroll
    for (int i = 0; i < 4; i++) {
      const int r = i >> 1, ch = (i & 1) * 32 + lane;
      cp_async16(sbase + SM_X + (2 * warp + r) * 1024 + ((ch ^ ((ch >> 2) & 6)) * 16),
                 x + (size_t)(c + 128 * (2 * warp + r)) * 512 + ch * 8);
    }
    asm volatile("cp.async.commit_group;" ::: "memory");
    asm volatile("barrier.cluster.arrive.relaxed.aligned;" ::: "memory");
    uint4 tw[8], fb[16];
    const uint4 fa = ldg_ca4(&tab->fa[lane][0]);
#pragma unroll
    for (int i = 0; i < 8; i++) tw[i] = ldg_ca4(&tab->tw1[i][lane][0]);
#pragma unroll
    for (int i = 0; i < 16; i++) fb[i] = ldg_ca4(&tab->fb[i][lane][0]);
    uint32_t rbar;
    asm volatile("mapa.shared::cluster.u32 %0, %1, %2;" : "=r"(rbar) : "r"(sbar), "r"(kh ^ 1));
#define RBAR(field, i) (rbar + (uint32_t)offsetof(Bars, field) + 8u * (i))
    {
      const int ln = (tid >> 1) & 31, lg = ln >> 2, lt = ln & 3, i = 4 * (tid >> 6) + 2 * (tid & 1);
      const int kidx = lt + 8 * (i >> 3), nidx = 4 * ((i >> 1) & 3) + (lg >> 1);
      const uint32_t a0 = cfrag<2048>((c + 128 * kidx) * nidx, lg & 1), a1 = cfrag<2048>((c + 128 * (kidx + 4)) * nidx, lg & 1);
      const uint32_t b0 = cfrag<2048>(-(c + 128 * nidx) * kidx, lg & 1), b1 = cfrag<2048>(-(c + 128 * nidx) * (kidx + 4), lg & 1);
      asm volatile("st.shared.v2.u32 [%0], {%1,%2};" ::"r"(sbase + SM_FC + tid * 8), "r"(a0), "r"(a1) : "memory");
      asm volatile("st.shared.v2.u32 [%0], {%1,%2};" ::"r"(sbase + SM_FC + 2048 + tid * 8), "r"(b0), "r"(b1) : "memory");
    }
    asm volatile("cp.async.wait_group 0;" ::: "memory");
    __syncwarp();
    bar_arrive(NB_INIT, 384);
    PROF(13);
    uint32_t tag;
    uint4 q[4], o[4];
    {
      uint32_t v[2][8];
#pragma unroll
      for (int r = 0; r < 2; r++)
#pragma unroll
        for (int q = 0; q < 4; q++) {
          const uint2 u = lds2(sbase + SM_X + (2 * warp + r) * 1024 + (t + 4 * (q >> 1)) * 128 + (((4 * (q & 1) + (g >> 1)) ^ (2 * t)) * 16) + (g & 1) * 8);
          v[r][2 * q] = u.x; v[r][2 * q + 1] = u.y;
        }
      float sum[2], sq[2], rstd[2];
      row_stats(v[0], v[1], lane, sum, sq);
#pragma unroll
      for (int r = 0; r < 2; r++) {
        const float m = sum[r] * (1.f / 512.f);
        rstd[r] = rsqrtf(fmaxf(fmaf(-m, m, sq[r] * (1.f / 512.f)), 0.f) + 1e-5f);
      }
      uint32_t alo[4][4], ahi[4][4];
#pragma unroll
      for (int r = 0; r < 2; r++)
#pragma unroll
        for (int i = 0; i < 4; i++) {
          const uint32_t sel = (i & 1) ? 0x7632u : 0x5410u;
          const uint32_t b0 = __byte_perm(v[r][i >> 1], v[r][2 + (i >> 1)], sel);
          const uint32_t b1 = __byte_perm(v[r][4 + (i >> 1)], v[r][6 + (i >> 1)], sel);
          float d[4] = {0.f, 0.f, 0.f, 0.f};
          mma16816(d, fa.x, fa.y, fa.z, fa.w, b0, b1);
          const uint4 &ka = tw[2 * i], &kb = tw[2 * i + 1];
          const uint32_t re = pack2(d[0] * __uint_as_float(ka.x) + d[2] * __uint_as_float(ka.y), d[1] * __uint_as_float(kb.x) + d[3] * __uint_as_float(kb.y));
          const uint32_t im = pack2(d[0] * __uint_as_float(ka.z) + d[2] * __uint_as_float(ka.w), d[1] * __uint_as_float(kb.z) + d[3] * __uint_as_float(kb.w));
          const uint32_t dc = pack2(fmaf(sum[r], -1.f / 32.f, d[0]), fmaf(sum[r], -1.f / 32.f, d[1]));
          alo[i][r] = re; alo[i][2 + r] = im;
          ahi[i][r] = g == 0 ? dc : re; ahi[i][2 + r] = g == 0 ? 0u : im;
        }
      float acc[8][4];
#pragma unroll
      for (int u = 0; u < 8; u++) {
        acc[u][0] = acc[u][1] = acc[u][2] = acc[u][3] = 0.f;
#pragma unroll
        for (int i = 0; i < 4; i++) {
          const uint4& bq = fb[i * 4 + (u >> 1)];
          if (u < 4) mma16816(acc[u], alo[i][0], alo[i][1], alo[i][2], alo[i][3], (u & 1) ? bq.z : bq.x, (u & 1) ? bq.w : bq.y);
          else       mma16816(acc[u], ahi[i][0], ahi[i][1], ahi[i][2], ahi[i][3], (u & 1) ? bq.z : bq.x, (u & 1) ? bq.w : bq.y);
        }
      }
#pragma unroll
      for (int r = 0; r < 2; r++)
#pragma unroll
        for (int h = 0; h < 2; h++) {
          const int j = 2 * warp + r, m = 2 * t + h;
          const float rs = rstd[r];
          sts4(sbase + SM_E + ((j * 8 + m) * 8 + (g ^ (2 * t) ^ (2 * (j & 3)))) * 16,
               pack2(acc[2 * h][2 * r] * rs, acc[2 * h][2 * r + 1] * rs), pack2(acc[2 * h + 1][2 * r] * rs, acc[2 * h + 1][2 * r + 1] * rs),
               pack2(acc[4 + 2 * h][2 * r] * rs, acc[4 + 2 * h][2 * r + 1] * rs), pack2(acc[5 + 2 * h][2 * r] * rs, acc[5 + 2 * h][2 * r + 1] * rs));
        }
      if (tid == 0) PROFP(12);
      bar_sync(NB_RDY, 384);
      if (tid == 0) PROFP(13);
      uint4 fc[4];
#pragma unroll
      for (int i = 0; i < 4; i++) fc[i] = lds4(sbase + SM_FC + i * 512 + lane * 16);
      asm volatile("ld.shared.u32 %0, [%1];" : "=r"(tag) : "r"(BAR(epoch, 0)) : "memory");
      tag = (tag + 1) & 1;
#pragma unroll
      for (int i = 0; i < 4; i++) q[i] = lds4(sbase + SM_E + (((t + 4 * i) * 8 + warp) * 8 + (g ^ (warp & 6) ^ (2 * t))) * 16);
      cdft16(q, fc, o);
#pragma unroll
      for (int vv = 0; vv < 4; vv++) st_tag(&scr->Z1[(((4 * vv + t) * 8 + warp) * 128 + c) * 8 + g], o[vv], tag);
    }
    PROF(1);
    {
      const uint4* const zp = &scr->Z1[(c * 128 + 8 * t + warp) * 8 + g];
      const uint32_t tst = clock32();
      mbar_wait(BAR(tbar, 0), 0);
      if (tid == 0) PROFP(14);
      uint4 f2[4], g2[4];
#pragma unroll
      for (int i = 0; i < 4; i++) {
        f2[i] = lds4(TOFF(f2) + warp * 2048 + i * 512);
        g2[i] = lds4(TOFF(g2) + warp * 2048 + i * 512);
      }
      const uint4 f8 = lds4(TOFF(f8)), g8 = lds4(TOFF(g8));
      float wfr[16], wfi[16];
      {
        const float fsc = 1.f / (1 << 19);
        const float fsc3 = ((c & 7) == 7 && g == 0) ? 0.5f * fsc : fsc;
        const int gg = g == 0 ? 8 : g, wsh = (2 * (c >> 3) + 2) & 15;
#pragma unroll
        for (int i = 0; i < 16; i++) {
          const int ci = i >> 3, dd = (i >> 2) & 1, e = i & 3;
          const int kk = (e == 0 ? gg : e == 1 ? 16 + gg : e == 2 ? 16 - g : 32 - g) - 1;
          const uint32_t a = sbase + SM_W + ((2 * warp + ci) * 8 + t + 4 * dd) * 80 + wsh + 2 * kk;
          wfr[i] = bf_lo(lds_u16(a)) * (e == 3 ? fsc3 : fsc);
          wfi[i] = bf_lo(lds_u16(a + 10240)) * (e == 3 ? fsc3 : fsc);
        }
      }
      asm volatile("barrier.cluster.wait.aligned;" ::: "memory");
      PROF(2);
      while (clock32() - tst < POLL_DELAY) {}
      ld_tag4_issue<256>(q, zp);
      ld_tag4_finish<256>(q, zp, tag);
      if (tid == 0) PROFP(30);
      if (lane == 0) mbar_arrive(BAR(sig, 0));
      cdft16(q, f2, o);
      const uint32_t e2 = sbase + SM_E2;
#pragma unroll
      for (int vv = 0; vv < 4; vv++)
        sts4(e2 + ((warp * 16 + 4 * vv + t) * 8 + (g ^ (2 * t) ^ (2 * (warp & 3)))) * 16, o[vv].x, o[vv].y, o[vv].z, o[vv].w);
      bar_sync(NB_CONS, 256);
#pragma unroll
      for (int ci = 0; ci < 2; ci++) {
        const int cc = 2 * warp + ci;
        uint32_t ad[2];
        uint4 u[2];
#pragma unroll
        for (int hh = 0; hh < 2; hh++) {
          ad[hh] = e2 + (((t + 4 * hh) * 16 + cc) * 8 + (g ^ (2 * (cc & 3)) ^ (2 * t))) * 16;
          u[hh] = lds4(ad[hh]);
        }
        uint32_t res[2][4];
#pragma unroll
        for (int p = 0; p < 2; p++) {
          uint32_t y[2][2];
#pragma unroll
          for (int vv = 0; vv < 2; vv++) {
            float d[4] = {0.f, 0.f, 0.f, 0.f};
            mma16816(d, word(u[0], 2 * p), word(u[0], 2 * p + 1), word(u[1], 2 * p), word(u[1], 2 * p + 1), word(f8, 2 * vv), word(f8, 2 * vv + 1));
#pragma unroll
            for (int rr = 0; rr < 2; rr++) {
              const float fr = wfr[ci * 8 + vv * 4 + 2 * p + rr], fi = wfi[ci * 8 + vv * 4 + 2 * p + rr];
              y[vv][rr] = pack2(d[2 * rr] * fr - d[2 * rr + 1] * fi, d[2 * rr] * fi + d[2 * rr + 1] * fr);
            }
          }
#pragma unroll
          for (int vv = 0; vv < 2; vv++) {
            float d[4] = {0.f, 0.f, 0.f, 0.f};
            mma16816(d, y[0][0], y[0][1], y[1][0], y[1][1], word(g8, 2 * vv), word(g8, 2 * vv + 1));
            res[vv][2 * p] = pack2(d[0], d[1]);
            res[vv][2 * p + 1] = pack2(d[2], d[3]);
          }
        }
#pragma unroll
        for (int vv = 0; vv < 2; vv++) sts4(ad[vv], res[vv][0], res[vv][1], res[vv][2], res[vv][3]);
      }
      bar_sync(NB_CONS, 256);
#pragma unroll
      for (int i = 0; i < 4; i++) q[i] = lds4(e2 + ((warp * 16 + 4 * i + t) * 8 + (g ^ (2 * t) ^ (2 * (warp & 3)))) * 16);
      cdft16(q, g2, o);
#pragma unroll
      for (int vv = 0; vv < 4; vv++) st_tag(&scr->Z2[((8 * (4 * vv + t) + warp) * 128 + c) * 8 + g], o[vv], tag);
    }
    PROF(3);
    {
      const uint4* const zp = &scr->Z2[((c * 16 + t) * 8 + warp) * 8 + g];
      const uint32_t tst = clock32();
      uint4 gb[16], gc[4], tw[4], xr[2][2];
#pragma unroll
      for (int i = 0; i < 16; i++) gb[i] = lds4(TOFF(gb) + i * 512);
      const uint4 ga = lds4(TOFF(ga));
#pragma unroll
      for (int i = 0; i < 4; i++) {
        gc[i] = lds4(sbase + SM_FC + 2048 + i * 512 + lane * 16);
        tw[i] = lds4(TOFF(tw3) + i * 512);
        const int ch = 4 * (g + 8 * (i & 1)) + t;
        xr[i >> 1][i & 1] = lds4(sbase + SM_X + (2 * warp + (i >> 1)) * 1024 + ((ch ^ ((ch >> 2) & 6)) * 16));
      }
      PROF(4);
      while (clock32() - tst < POLL_DELAY) {}
      ld_tag4_issue<256>(q, zp);
      ld_tag4_finish<256>(q, zp, tag);
      if (tid == 0) PROFP(31);
      if (lane == 0) mbar_arrive(BAR(sig, 1));
      cdft16(q, gc, o);
#pragma unroll
      for (int vv = 0; vv < 4; vv++)
        sts4(sbase + SM_E + (((4 * vv + t) * 8 + warp) * 8 + (g ^ (warp & 6) ^ (2 * t))) * 16, o[vv].x, o[vv].y, o[vv].z, o[vv].w);
      bar_sync(NB_CONS, 256);
      uint32_t hv[2][8];
      const float mk = t == 0 ? 0.f : 1.f;
#pragma unroll
      for (int r = 0; r < 2; r++) {
        const int j = 2 * warp + r;
        uint4 u[2];
#pragma unroll
        for (int h = 0; h < 2; h++) u[h] = lds4(sbase + SM_E + ((j * 8 + 2 * t + h) * 8 + (g ^ (2 * t) ^ (2 * (j & 3)))) * 16);
        float yv[4][4];
#pragma unroll
        for (int i = 0; i < 4; i++) {
          float lo[4] = {0.f, 0.f, 0.f, 0.f}, hi[4] = {0.f, 0.f, 0.f, 0.f};
          mma16816(lo, gb[i * 4].x, gb[i * 4].y, gb[i * 4].z, gb[i * 4].w, u[0].x, u[0].y);
          mma16816(lo, gb[i * 4 + 1].x, gb[i * 4 + 1].y, gb[i * 4 + 1].z, gb[i * 4 + 1].w, u[1].x, u[1].y);
          mma16816(hi, gb[i * 4 + 2].x, gb[i * 4 + 2].y, gb[i * 4 + 2].z, gb[i * 4 + 2].w, u[0].z, u[0].w);
          mma16816(hi, gb[i * 4 + 3].x, gb[i * 4 + 3].y, gb[i * 4 + 3].z, gb[i * 4 + 3].w, u[1].z, u[1].w);
          const float ca = __uint_as_float(tw[i].x), sa = __uint_as_float(tw[i].y), cb = __uint_as_float(tw[i].z), sb = __uint_as_float(tw[i].w);
          const float tr0 = fmaf(hi[0], mk, lo[0]), ti0 = fmaf(hi[2], mk, lo[2]);
          const float tr1 = lo[1] + hi[1], ti1 = lo[3] + hi[3];
          const float vr0 = tr0 * ca - ti0 * sa, vi0 = tr0 * sa + ti0 * ca;
          const float vr1 = tr1 * cb - ti1 * sb, vi1 = tr1 * sb + ti1 * cb;
          const uint32_t b0 = pack2(t == 0 ? hi[0] : vr0, vr1), b1 = pack2(t == 0 ? vr0 : vi0, vi1);
          yv[i][0] = yv[i][1] = yv[i][2] = yv[i][3] = 0.f;
          mma16816(yv[i], ga.x, ga.y, ga.z, ga.w, b0, b1);
        }
#pragma unroll
        for (int h = 0; h < 2; h++) {
          hv[r][4 * h + 0] = hadd2_bf16(xr[r][h].x, pack2(yv[0][2 * h], yv[1][2 * h]));
          hv[r][4 * h + 1] = hadd2_bf16(xr[r][h].y, pack2(yv[2][2 * h], yv[3][2 * h]));
          hv[r][4 * h + 2] = hadd2_bf16(xr[r][h].z, pack2(yv[0][2 * h + 1], yv[1][2 * h + 1]));
          hv[r][4 * h + 3] = hadd2_bf16(xr[r][h].w, pack2(yv[2][2 * h + 1], yv[3][2 * h + 1]));
        }
      }
      float ds[4] = {0.f, 0.f, 0.f, 0.f};
#pragma unroll
      for (int q4 = 0; q4 < 4; q4++) mma16816(ds, hv[0][2 * q4], hv[1][2 * q4], hv[0][2 * q4 + 1], hv[1][2 * q4 + 1], 0x3f803f80u, 0x3f803f80u);
#pragma unroll
      for (int o2 = 4; o2 <= 16; o2 <<= 1) {
        ds[0] += __shfl_xor_sync(0xffffffffu, ds[0], o2);
        ds[2] += __shfl_xor_sync(0xffffffffu, ds[2], o2);
      }
      uint32_t mb[2];
#pragma unroll
      for (int r = 0; r < 2; r++) {
        const int row = 16 * f + 2 * warp + r;
        mb[r] = pack2(ds[2 * r] * (1.f / 512.f), ds[2 * r] * (1.f / 512.f));
#pragma unroll
        for (int i = 0; i < 8; i++) hv[r][i] = hsub2_bf16(hv[r][i], mb[r]);
#pragma unroll
        for (int h = 0; h < 2; h++) {
          const int n1 = g + 8 * h;
          st_tag(&scr->LN[(rb * 8 + (n1 >> 1)) * 1024 + row * 8 + ((4 * (n1 & 1) + t) ^ (row & 7))],
                 make_uint4(hv[r][4 * h], hv[r][4 * h + 1], hv[r][4 * h + 2], hv[r][4 * h + 3]), n1 < 2 * NLL ? tag : (hv[r][4 * h] & 1u));
        }
      }
      bar_arrive(NB_LN, 288);
      float sum[2], sq[2], rstd[2];
      row_stats(hv[0], hv[1], lane, sum, sq);
#pragma unroll
      for (int r = 0; r < 2; r++) {
        const float m = sum[r] * (1.f / 512.f);
        rstd[r] = rsqrtf(fmaxf(fmaf(-m, m, sq[r] * (1.f / 512.f)), 0.f) + 1e-5f);
      }
      if (lane == 0)
        st_tag(&scr->ST[rb * 64 + 8 * f + warp], make_uint4(mb[0] << 16, __float_as_uint(rstd[0]), mb[1] << 16, __float_as_uint(rstd[1])), tag);
    }
    PROF(5);
    asm volatile("setmaxnreg.inc.sync.aligned.u32 224;");
    if (NLL) {
      const uint4* const ap = &scr->LN[rb * 8 * 1024 + tid];
      uint4 av[NLL ? NLL : 1][4];
      spin_cycles(POLL_DELAY3);
#pragma unroll
      for (int kb = 0; kb < NLL; kb++) ld_tag4_issue<256>(av[kb], ap + kb * 1024);
      bar_sync(NB_CONS, 256);
#pragma unroll
      for (int kb = 0; kb < NLL; kb++) {
        ld_tag4_finish<256>(av[kb], ap + kb * 1024, tag);
#pragma unroll
        for (int i = 0; i < 4; i++) sts4(sbase + kb * SLOT + (tid + 256 * i) * 16, av[kb][i].x, av[kb][i].y, av[kb][i].z, av[kb][i].w);
      }
      asm volatile("fence.proxy.async.shared::cta;" ::: "memory");
      bar_sync(NB_CONS, 256);
    }
    const int wgi = warp >> 2, wq = warp & 3;
    uint4* const pbase = &scr->P[rb * 28 * 1024 + warp * 128 + lane];
    const uint32_t a_lo0 = desc_lo(sbase + wgi * 8192, 16);
    const uint32_t ebar = lane == 0 ? BAR(empty1, 0) : RBAR(empty1, 0);
    float r0, r1;
    uint4 px[8], py[6];
    const int rh = wgi ^ kh ^ 1;
    const uint4* const psrc = &scr->P[(rb2 * 28 + 14 * kh) * 1024 + (4 * rh + wq) * 128 + lane];
    {
      float acc[128];
#pragma unroll
      for (int i = 0; i < 128; i++) acc[i] = 0.f;
      const uint32_t b_lo0 = desc_lo(sbase + 8 * SLOT, 4096);
      uint32_t slot = 2;
#pragma unroll 1
      for (int kb = 0; kb < 8; kb++) {
        if (kb >= NLL) mbar_wait(BAR(fullA, kb), 0);
        if (kb == 0) PROF(6);
#pragma unroll
        for (int hh = 0; hh < 2; hh++) {
          if (LAGX && hh == ((16 - LAGX) & 1) && kb == ((16 - LAGX) >> 1) && wgi == 1) bar_sync(NB_LAG, 256);
          mbar_wait(BAR(full1, 2 * kb + hh));
          const uint32_t al = a_lo0 + kb * 1024 + hh * 4, bl = b_lo0 + slot * 1024;
          wg_fence();
          wgmma_n256(acc, desc64(al, HI128), desc64(bl, HI128));
          wgmma_n256(acc, desc64(al + 2, HI128), desc64(bl + 128, HI128));
          wg_commit();
          if (LAGX && hh == 1 && kb == 7 && wgi == 0) bar_arrive(NB_LAG, 256);
          wg_wait<1>();
          if ((kb | hh) != 0 && lane < 2) mbar_arrive_remote(ebar + 8 * (2 * kb + hh - 1));
          if (++slot == 6) slot = 0;
        }
      }
      mbar_wait(BAR(sbar, 0), 0);
      r0 = __uint_as_float(lds2(sstat + (16 * warp + g) * 8).y);
      r1 = __uint_as_float(lds2(sstat + (16 * warp + g + 8) * 8).y);
      wg_wait<0>();
      if (lane < 2) mbar_arrive_remote(ebar + 8 * 15);
      PROF(7);
      make_p<8, false>(acc, r0, r1, px, pbase, 0, tag);
    }
    PROF(8);
    {
      float acc[96];
#pragma unroll
      for (int i = 0; i < 96; i++) acc[i] = 0.f;
      const uint32_t b_lo0 = desc_lo(sbase + 8 * SLOT, 2048);
      uint4* const pdst = pbase + ((7 * f + 3 * (f & 1)) >> 1) * 1024;
      auto stage_y = [&](int k) {
        if (LAGY && k == 16 - LAGY && wgi == 1) bar_sync(NB_LAG, 256);
        mbar_wait(BAR(full1, 16 + k));
        const uint32_t al = a_lo0 + (k >> 1) * 1024 + (k & 1) * 4, bl = b_lo0 + (k & 7) * 768;
        wg_fence();
        wgmma_n192(acc, desc64(al, HI128), desc64(bl, HI64));
        wgmma_n192(acc, desc64(al + 2, HI128), desc64(bl + 64, HI64));
        wg_commit();
      };
#pragma unroll
      for (int k = 0; k < 4; k++) {
        stage_y(k);
        st_tag(pdst + (k >> 1) * 1024 + (k & 1) * 64, px[2 * k], tag);
        st_tag(pdst + (k >> 1) * 1024 + (k & 1) * 64 + 32, px[2 * k + 1], tag);
        if (k == 3 && lane == 0) red_relaxed(&scr->cnt[(C_PX + rb) * 32]);
        wg_wait<1>();
        if (k != 0 && lane < 2) mbar_arrive_remote(ebar + 8 * (15 + k));
      }
#pragma unroll 1
      for (int k = 4; k < 16; k++) {
        stage_y(k);
        if (LAGY && k == 15 && wgi == 0) bar_arrive(NB_LAG, 256);
        wg_wait<1>();
        if (lane < 2) mbar_arrive_remote(ebar + 8 * (15 + k));
      }
      wg_wait<0>();
      if (lane < 2) mbar_arrive_remote(ebar + 8 * 31);
      PROF(9);
      make_p<6, true>(acc, r0, r1, py, pbase, 14 * f + ((f & 1) ? 0 : 8), tag);
      if (lane == 0) red_relaxed(&scr->cnt[(C_PY + rb) * 32 + (f >> 1)]);
    }
    PROF(10);
    {
      float acc[64];
      {
        const float m0 = wgi ? __uint_as_float(lds2(sstat + 1024 + (16 * wq + g) * 8).x) : 0.f;
        const float m1 = wgi ? __uint_as_float(lds2(sstat + 1024 + (16 * wq + g + 8) * 8).x) : 0.f;
#pragma unroll
        for (int i = 0; i < 64; i++) acc[i] = (i & 2) ? m1 : m0;
      }
      const uint32_t b2_lo0 = desc_lo(sbase, 8192);
      const uint32_t pa0 = sbase + 8 * SLOT + (4 * rh + wq) * 2048 + lane * 16;
      uint32_t slot = 0;
      auto fetch2 = [&](int s, uint4 (&a)[4]) {
        mbar_wait(BAR(full2, s), 0);
        if (tid == 0) PROFP(16 + s);
#pragma unroll
        for (int kk = 0; kk < 4; kk++) a[kk] = lds4(pa0 + slot * SLOT + kk * 512);
        if (++slot == 6) slot = 0;
      };
      auto check2 = [&](int s, uint4 (&a)[4]) {
        if (__any_sync(0xffffffffu, ((a[0].x ^ tag) | (a[1].x ^ tag) | (a[2].x ^ tag) | (a[3].x ^ tag)) & 1u)) {
          const uint4* p = psrc + (int)((KORDER >> (4 * s)) & 15) * 1024;
          ld_tag4_issue<32>(a, p);
          ld_tag4_finish<32>(a, p, tag);
        }
#pragma unroll
        for (int i = 0; i < 4; i++) asm volatile("and.b32 %0, %0, 0xfffffffe;" : "+r"(a[i].x));
        if (s < 8 && lane == 0) mbar_arrive(BAR(emptyP, s));
      };
      auto stage2 = [&](int s, uint4 (&a)[4], uint4 (&nx)[4]) {
        if (s < 13) fetch2(s + 1, nx);
        const uint32_t bl = b2_lo0 + (s & 7) * 1024;
        if (LAG2 && s == 14 - LAG2 && wgi == 1) bar_sync(NB_LAG, 256);
        wg_fence();
#pragma unroll
        for (int kk = 0; kk < 4; kk++) wgmma_rs_n128(acc, a[kk].x, a[kk].y, a[kk].z, a[kk].w, desc64(bl + kk * 128, HI128));
        wg_commit();
        if (s < 13) check2(s + 1, nx);
        wg_wait<1>();
        if (s >= 1 && s <= 8 && lane == 0) {
          mbar_arrive(BAR(empty2, s - 1));
          if (s == 8) mbar_arrive_remote(RBAR(xfree, 0));
        }
      };
      uint4 fa0[4], fa1[4], fa2[4];
      fetch2(0, fa0);
      check2(0, fa0);
#pragma unroll 1
      for (int s = 0; s < 12; s += 3) {
        stage2(s, fa0, fa1);
        stage2(s + 1, fa1, fa2);
        stage2(s + 2, fa2, fa0);
      }
      stage2(12, fa0, fa1);
      stage2(13, fa1, fa2);
      if (LAG2 && wgi == 0) bar_arrive(NB_LAG, 256);
      uint4 hres[2][4];
      mbar_wait(BAR(hbar, 0), 0);
#pragma unroll
      for (int h = 0; h < 2; h++)
#pragma unroll
        for (int q = 0; q < 4; q++) {
          hres[h][q] = lds4(sbase + 7 * SLOT + (q >> 1) * 8192 + (16 * wq + g + 8 * h) * 128 + (((4 * (q & 1) + t) ^ g) * 16));
          if (2 * nq + (q >> 1) < NLL) hres[h][q].x &= ~1u;
        }
      wg_wait<0>();
      PROF(11);
      const uint32_t xbuf = sbase + 6 * SLOT + (tid & 127) * 16;
      if (wgi == 0) {
        uint32_t rbuf;
        mbar_wait(BAR(xfree, 0), 0);
        asm volatile("mapa.shared::cluster.u32 %0, %1, %2;" : "=r"(rbuf) : "r"(xbuf), "r"(kh ^ 1));
#pragma unroll
        for (int i = 0; i < 8; i++)
          asm volatile("st.async.weak.shared::cluster.mbarrier::complete_tx::bytes.v4.b32 [%0], {%1,%2,%3,%4}, [%5];"
                       ::"r"(rbuf + i * 2048), "r"(pack2(acc[8 * i], acc[8 * i + 1])), "r"(pack2(acc[8 * i + 2], acc[8 * i + 3])),
                         "r"(pack2(acc[8 * i + 4], acc[8 * i + 5])), "r"(pack2(acc[8 * i + 6], acc[8 * i + 7])), "r"(RBAR(xbar, 0))
                       : "memory");
      } else {
        mbar_wait_cluster(BAR(xbar, 0), 0);
      }
      uint32_t w[2][16];
#pragma unroll
      for (int i = 0; i < 8; i++) {
        const uint4 pv = lds4(xbuf + i * 2048);
        w[0][2 * i] = pack2(acc[8 * i] + bf_lo(pv.x), acc[8 * i + 1] + bf_hi(pv.x));
        w[1][2 * i] = pack2(acc[8 * i + 2] + bf_lo(pv.y), acc[8 * i + 3] + bf_hi(pv.y));
        w[0][2 * i + 1] = pack2(acc[8 * i + 4] + bf_lo(pv.z), acc[8 * i + 5] + bf_hi(pv.z));
        w[1][2 * i + 1] = pack2(acc[8 * i + 6] + bf_lo(pv.w), acc[8 * i + 7] + bf_hi(pv.w));
      }
      uint4* const o4 = reinterpret_cast<uint4*>(out) + (16 * (c >> 4) + 2 * (4 * rh + wq) + (rb2 & 1) + 128 * g) * 64 + nq * 16 + t;
#pragma unroll
      for (int h = 0; h < 2; h++)
#pragma unroll
        for (int q = 0; q < 4; q++) {
          uint32_t a0 = w[h][4 * q], a1 = w[h][4 * q + 1], a2 = w[h][4 * q + 2], a3 = w[h][4 * q + 3];
          {
            const bool od = t & 1;
            uint32_t s0 = od ? a0 : a1, s1 = od ? a2 : a3;
            s0 = __shfl_xor_sync(0xffffffffu, s0, 1); s1 = __shfl_xor_sync(0xffffffffu, s1, 1);
            if (od) { a0 = s0; a2 = s1; } else { a1 = s0; a3 = s1; }
          }
          {
            const bool up = t & 2;
            uint32_t s0 = up ? a0 : a2, s1 = up ? a1 : a3;
            s0 = __shfl_xor_sync(0xffffffffu, s0, 2); s1 = __shfl_xor_sync(0xffffffffu, s1, 2);
            if (up) { a0 = s0; a1 = s1; } else { a2 = s0; a3 = s1; }
          }
          if (wgi == 1)
            o4[h * 1024 * 64 + 4 * q] =
                make_uint4(hadd2_bf16(hres[h][q].x, a0), hadd2_bf16(hres[h][q].y, a1), hadd2_bf16(hres[h][q].z, a2), hadd2_bf16(hres[h][q].w, a3));
        }
      PROF(12);
      PROFG(15);
    }
  }
#undef BAR
#undef TOFF
#undef RBAR
}

typedef CUresult (*EncodeFn)(CUtensorMap*, CUtensorMapDataType, cuuint32_t, void*, const cuuint64_t*, const cuuint64_t*,
                             const cuuint32_t*, const cuuint32_t*, CUtensorMapInterleave, CUtensorMapSwizzle,
                             CUtensorMapL2promotion, CUtensorMapFloatOOBfill);

}

extern "C" void kernel_launch(void* const* d_in, const int* in_sizes, int n_in, void* d_out, int out_size) {
  (void)in_sizes; (void)n_in; (void)out_size;
  static EncodeFn encode = nullptr;
  static void *tab = nullptr, *scr = nullptr;
  if (!encode) {
    void* fn = nullptr;
    cudaDriverEntryPointQueryResult qr;
    cudaGetDriverEntryPoint("cuTensorMapEncodeTiled", &fn, cudaEnableDefault, &qr);
    encode = (EncodeFn)fn;
    cudaGetSymbolAddress(&tab, g_tab);
    cudaGetSymbolAddress(&scr, g_scr);
    cudaFuncSetAttribute(fused_kernel, cudaFuncAttributeMaxDynamicSharedMemorySize, SMEM_BYTES);
  }
  CUtensorMap tmGX, tmUX, tmGY, tmUY, tmD, tmWR, tmWI;
  const cuuint32_t es[5] = {1, 1, 1, 1, 1};
  auto enc = [&](CUtensorMap* m, void* p, int rank, const cuuint64_t* gd, const cuuint64_t* gs, const cuuint32_t* bd,
                 CUtensorMapSwizzle sw, CUtensorMapL2promotion pr) {
    encode(m, CU_TENSOR_MAP_DATA_TYPE_BFLOAT16, rank, p, gd, gs, bd, es, CU_TENSOR_MAP_INTERLEAVE_NONE, sw, pr,
           CU_TENSOR_MAP_FLOAT_OOB_FILL_NONE);
  };
  {
    const cuuint64_t gd[3] = {64, 512, 28}, gs[2] = {3584, 128};
    const cuuint32_t bd[3] = {64, 32, 2};
    enc(&tmGX, d_in[4], 3, gd, gs, bd, CU_TENSOR_MAP_SWIZZLE_128B, CU_TENSOR_MAP_L2_PROMOTION_L2_256B);
    enc(&tmUX, d_in[5], 3, gd, gs, bd, CU_TENSOR_MAP_SWIZZLE_128B, CU_TENSOR_MAP_L2_PROMOTION_L2_256B);
  }
  {
    const cuuint64_t gd[3] = {32, 512, 56}, gs[2] = {3584, 64};
    const cuuint32_t bd[3] = {32, 32, 3};
    enc(&tmGY, d_in[4], 3, gd, gs, bd, CU_TENSOR_MAP_SWIZZLE_64B, CU_TENSOR_MAP_L2_PROMOTION_L2_128B);
    enc(&tmUY, d_in[5], 3, gd, gs, bd, CU_TENSOR_MAP_SWIZZLE_64B, CU_TENSOR_MAP_L2_PROMOTION_L2_128B);
  }
  {
    const cuuint64_t gd[3] = {64, 1792, 8}, gs[2] = {1024, 128};
    const cuuint32_t bd[3] = {64, 64, 2};
    enc(&tmD, d_in[6], 3, gd, gs, bd, CU_TENSOR_MAP_SWIZZLE_128B, CU_TENSOR_MAP_L2_PROMOTION_L2_256B);
  }
  {
    const cuuint64_t gd[3] = {4112, 8, 16}, gs[2] = {16 * 8224, 8224};
    const cuuint32_t bd[3] = {40, 8, 16};
    enc(&tmWR, d_in[1], 3, gd, gs, bd, CU_TENSOR_MAP_SWIZZLE_NONE, CU_TENSOR_MAP_L2_PROMOTION_NONE);
    enc(&tmWI, d_in[2], 3, gd, gs, bd, CU_TENSOR_MAP_SWIZZLE_NONE, CU_TENSOR_MAP_L2_PROMOTION_NONE);
  }
  fused_kernel<<<NCTA, NTHREADS, SMEM_BYTES>>>((const __nv_bfloat16*)d_in[0], (const Tables*)tab, (Scratch*)scr,
                                               (__nv_bfloat16*)d_out, (const char*)d_in[4], (const char*)d_in[5],
                                               (const char*)d_in[6], tmWR, tmWI, tmGX, tmUX, tmGY, tmUY, tmD);
}
```

```cpp
#include <cuda_runtime.h>
#include <cuda_bf16.h>
#include <cuda.h>
#include <stdint.h>

namespace {

constexpr int NCTA = 128;
constexpr int NTHREADS = 384;
constexpr int SLOT = 16384;
constexpr int SMEM_BYTES = 14 * SLOT + 3072;
constexpr int SPIN_LIMIT = 1 << 22;

struct Scratch {
  uint4 Z1[128 * 1024];
  uint4 Z2[128 * 1024];
  uint4 LN[16 * 8 * 1024];
  uint4 P[16 * 28 * 1024];
  uint4 ST[1024];
  unsigned cnt[64 * 32];
};
__device__ __align__(1024) Scratch g_scr;
#define PROF(i)
#define PROFP(i)
#define PROFG(i)

constexpr double ccos(int i, int n) {
  i &= n - 1;
  if (i > n / 2) i = n - i;
  if (4 * i == n) return 0.0;
  const bool neg = 4 * i > n;
  if (neg) i = n / 2 - i;
  const double a = 6.283185307179586476925 * i / n, a2 = a * a;
  double term = 1.0, sum = 1.0;
  for (int k = 1; k < 14; k++) { term *= -a2 / ((2 * k - 1) * (2 * k)); sum += term; }
  return neg ? -sum : sum;
}
constexpr double csin(int i, int n) { return ccos(i - n / 4, n); }
constexpr unsigned fbits(double v, int mant) {
  if (v == 0.0) return 0;
  const unsigned sg = v < 0 ? 1u : 0u;
  if (v < 0) v = -v;
  int e = 127;
  while (v < 1.0) { v *= 2.0; e--; }
  const unsigned m = (unsigned)((v - 1.0) * (double)(1u << mant) + 0.5);
  return (sg << (8 + mant)) + ((unsigned)e << mant) + m;
}
constexpr unsigned pkb(double lo, double hi) { return fbits(lo, 7) | (fbits(hi, 7) << 16); }
constexpr double fa_elem(int kp, int n1) {
  return kp <= 8 ? ccos(kp * n1, 16) : -csin((kp - 8) * n1, 16);
}
constexpr unsigned cfrag_c(int idx, int n, int ri) {
  return ri ? pkb(-csin(idx, n), ccos(idx, n)) : pkb(ccos(idx, n), csin(idx, n));
}
struct Tables {
  unsigned fb[16][32][4];
  unsigned tw1[8][32][4];
  unsigned fa[32][4];
  unsigned f2[8][4][32][4];
  unsigned g2[8][4][32][4];
  unsigned gb[16][32][4];
  unsigned tw3[4][32][4];
  unsigned ga[32][4];
  unsigned f8[32][4], g8[32][4];
};
constexpr int T1_BYTES = 12800, T2_BYTES = 44544;
static_assert(sizeof(Tables) == T1_BYTES + T2_BYTES, "table size");
constexpr Tables make_tables() {
  Tables T = {};
  for (int l = 0; l < 32; l++) {
    const int g = l >> 2, t = l & 3;
    for (int i = 0; i < 4; i++)
      for (int u = 0; u < 8; u++) {
        const int ri = g & 1, m = 2 * (g >> 1) + ((u & 3) >> 1);
        const double sg = u >= 4 ? -1.0 : 1.0;
        const int k2 = u >= 4 ? 31 - 2 * m - (u & 1) : 2 * m + (u & 1);
        const int pa = (8 * t + i) * k2, pb = (8 * t + 4 + i) * k2;
        T.fb[i * 4 + (u >> 1)][l][(u & 1) * 2 + 0] = ri == 0 ? pkb(ccos(pa, 32), ccos(pb, 32)) : pkb(-sg * csin(pa, 32), -sg * csin(pb, 32));
        T.fb[i * 4 + (u >> 1)][l][(u & 1) * 2 + 1] = ri == 0 ? pkb(csin(pa, 32), csin(pb, 32)) : pkb(sg * ccos(pa, 32), sg * ccos(pb, 32));
      }
    for (int i = 0; i < 4; i++)
      for (int ks = 0; ks < 4; ks++) {
        const int n2 = 4 * g + i, m = 2 * t + (ks & 1);
        const double sg = ks >= 2 ? -1.0 : 1.0;
        const int pa = n2 * (ks >= 2 ? 31 - 2 * m : 2 * m), pb = n2 * (ks >= 2 ? 30 - 2 * m : 2 * m + 1);
        T.gb[i * 4 + ks][l][0] = pkb(ccos(pa, 32), -sg * csin(pa, 32));
        T.gb[i * 4 + ks][l][1] = pkb(csin(pa, 32), sg * ccos(pa, 32));
        T.gb[i * 4 + ks][l][2] = pkb(ccos(pb, 32), -sg * csin(pb, 32));
        T.gb[i * 4 + ks][l][3] = pkb(csin(pb, 32), sg * ccos(pb, 32));
      }
    for (int i = 0; i < 4; i++) {
      for (int e = 0; e < 2; e++) {
        const int p = (8 * t + 4 * e + i) * (g == 0 ? 8 : g);
        T.tw1[2 * i + e][l][0] = fbits(g == 0 ? 0.0 : ccos(p, 512), 23);
        T.tw1[2 * i + e][l][1] = fbits(g == 0 ? ccos(p, 512) : csin(p, 512), 23);
        T.tw1[2 * i + e][l][2] = fbits(g == 0 ? 0.0 : -csin(p, 512), 23);
        T.tw1[2 * i + e][l][3] = fbits(g == 0 ? -csin(p, 512) : ccos(p, 512), 23);
      }
      const int ka = t == 0 ? 8 : 2 * t, kb = 2 * t + 1;
      T.tw3[i][l][0] = fbits(ccos((4 * g + i) * ka, 512), 23);
      T.tw3[i][l][1] = fbits(csin((4 * g + i) * ka, 512), 23);
      T.tw3[i][l][2] = fbits(ccos((4 * g + i) * kb, 512), 23);
      T.tw3[i][l][3] = fbits(csin((4 * g + i) * kb, 512), 23);
      const int p8 = (t + 4 * (i & 1)) * (4 * (i >> 1) + (g >> 1));
      T.f8[l][i] = cfrag_c(p8, 8, g & 1);
      T.g8[l][i] = cfrag_c(-p8, 8, g & 1);
    }
    for (int w = 0; w < 8; w++)
      for (int i = 0; i < 16; i++) {
        const int kidx = t + 4 * (i & 1) + 8 * (i >> 3), nidx = 4 * ((i >> 1) & 3) + (g >> 1);
        T.f2[w][i >> 2][l][i & 3] = cfrag_c((8 * kidx + w) * nidx, 128, g & 1);
        T.g2[w][i >> 2][l][i & 3] = cfrag_c(-(8 * nidx + w) * kidx, 128, g & 1);
      }
    T.fa[l][0] = pkb(fa_elem(g, 2 * t), fa_elem(g, 2 * t + 1));
    T.fa[l][1] = pkb(fa_elem(g + 8, 2 * t), fa_elem(g + 8, 2 * t + 1));
    T.fa[l][2] = pkb(fa_elem(g, 2 * t + 8), fa_elem(g, 2 * t + 9));
    T.fa[l][3] = pkb(fa_elem(g + 8, 2 * t + 8), fa_elem(g + 8, 2 * t + 9));
    T.ga[l][0] = pkb(fa_elem(2 * t, g), fa_elem(2 * t + 1, g));
    T.ga[l][1] = pkb(fa_elem(2 * t, g + 8), fa_elem(2 * t + 1, g + 8));
    T.ga[l][2] = pkb(fa_elem(2 * t + 8, g), fa_elem(2 * t + 9, g));
    T.ga[l][3] = pkb(fa_elem(2 * t + 8, g + 8), fa_elem(2 * t + 9, g + 8));
  }
  return T;
}
__device__ const __align__(128) Tables g_tab = make_tables();

__device__ __forceinline__ void die() { asm volatile("st.global.u32 [%0], %1;" ::"l"(0ull), "r"(0) : "memory"); }
__device__ __forceinline__ uint32_t s2u(const void* p) { return (uint32_t)__cvta_generic_to_shared(p); }
__device__ __forceinline__ void mbar_init(uint32_t b, int c) { asm volatile("mbarrier.init.shared::cta.b64 [%0], %1;" ::"r"(b), "r"(c)); }
__device__ __forceinline__ void mbar_expect(uint32_t b, int bytes) {
  asm volatile("mbarrier.arrive.expect_tx.shared::cta.b64 _, [%0], %1;" ::"r"(b), "r"(bytes) : "memory");
}
__device__ __forceinline__ void mbar_arrive(uint32_t b) { asm volatile("mbarrier.arrive.shared::cta.b64 _, [%0];" ::"r"(b) : "memory"); }
__device__ __forceinline__ uint32_t mbar_try(uint32_t b, uint32_t parity) {
  uint32_t ok;
  asm volatile("{.reg .pred p; mbarrier.try_wait.parity.shared::cta.b64 p, [%1], %2; selp.u32 %0,1,0,p;}"
               : "=r"(ok) : "r"(b), "r"(parity) : "memory");
  return ok;
}
__device__ __forceinline__ void mbar_wait(uint32_t b, uint32_t parity = 0) {
  int it = 0;
#pragma unroll 1
  while (!mbar_try(b, parity))
    if (++it > SPIN_LIMIT) { die(); break; }
}
__device__ __forceinline__ void mbar_wait_cluster(uint32_t b, int parity) {
  uint32_t ok;
  int it = 0;
  do {
    asm volatile("{.reg .pred p; mbarrier.try_wait.parity.acquire.cluster.shared::cta.b64 p, [%1], %2; selp.u32 %0,1,0,p;}"
                 : "=r"(ok) : "r"(b), "r"(parity) : "memory");
    if (++it > SPIN_LIMIT) { die(); break; }
  } while (!ok);
}
__device__ __forceinline__ void bar_sync(int id, int n) { asm volatile("bar.sync %0, %1;" ::"r"(id), "r"(n) : "memory"); }
__device__ __forceinline__ void bar_arrive(int id, int n) { asm volatile("bar.arrive %0, %1;" ::"r"(id), "r"(n) : "memory"); }
__device__ __forceinline__ void red_release(unsigned* p) { asm volatile("red.release.gpu.global.add.u32 [%0], 1;" ::"l"(p) : "memory"); }
__device__ __forceinline__ void red_relaxed(unsigned* p) { asm volatile("red.relaxed.gpu.global.add.u32 [%0], 1;" ::"l"(p) : "memory"); }
__device__ __forceinline__ unsigned ld_acquire(const unsigned* p) {
  unsigned v;
  asm volatile("ld.acquire.gpu.global.u32 %0, [%1];" : "=r"(v) : "l"(p) : "memory");
  return v;
}
__device__ __forceinline__ unsigned ld_relaxed(const unsigned* p) {
  unsigned v;
  asm volatile("ld.relaxed.gpu.global.u32 %0, [%1];" : "=r"(v) : "l"(p) : "memory");
  return v;
}
__device__ __forceinline__ void wait_counter(const unsigned* p, unsigned target) {
  int it = 0;
  while ((int)(ld_acquire(p) - target) < 0)
    if (++it > SPIN_LIMIT) { die(); break; }
}
__device__ __forceinline__ void sts4(uint32_t a, uint32_t x, uint32_t y, uint32_t z, uint32_t w) {
  asm volatile("st.shared.v4.u32 [%0], {%1,%2,%3,%4};" ::"r"(a), "r"(x), "r"(y), "r"(z), "r"(w) : "memory");
}
__device__ __forceinline__ uint4 lds4(uint32_t a) {
  uint4 v;
  asm volatile("ld.shared.v4.u32 {%0,%1,%2,%3}, [%4];" : "=r"(v.x), "=r"(v.y), "=r"(v.z), "=r"(v.w) : "r"(a) : "memory");
  return v;
}
__device__ __forceinline__ uint32_t pack2(float lo, float hi) {
  uint32_t r;
  asm("cvt.rn.bf16x2.f32 %0, %1, %2;" : "=r"(r) : "f"(hi), "f"(lo));
  return r;
}
__device__ __forceinline__ float bf_lo(uint32_t v) { return __uint_as_float(v << 16); }
__device__ __forceinline__ float bf_hi(uint32_t v) { return __uint_as_float(v & 0xffff0000u); }
__device__ __forceinline__ uint32_t hadd2_bf16(uint32_t a, uint32_t b) {
  uint32_t r;
  asm("add.rn.bf16x2 %0, %1, %2;" : "=r"(r) : "r"(a), "r"(b));
  return r;
}
__device__ __forceinline__ void mma16816(float (&d)[4], uint32_t a0, uint32_t a1, uint32_t a2, uint32_t a3, uint32_t b0, uint32_t b1) {
  asm("mma.sync.aligned.m16n8k16.row.col.f32.bf16.bf16.f32 {%0,%1,%2,%3}, {%4,%5,%6,%7}, {%8,%9}, {%0,%1,%2,%3};"
      : "+f"(d[0]), "+f"(d[1]), "+f"(d[2]), "+f"(d[3])
      : "r"(a0), "r"(a1), "r"(a2), "r"(a3), "r"(b0), "r"(b1));
}
template <int N>
__device__ __forceinline__ void cs_frac(int idx, float& c, float& s) {
  int i = ((idx + N / 2) & (N - 1)) - N / 2;
  float a = (float)i * (6.283185307179586f / N);
  c = __cosf(a);
  s = __sinf(a);
}
template <int N>
__device__ __forceinline__ uint32_t cfrag(int idx, int ri) {
  float c, s;
  cs_frac<N>(idx, c, s);
  return ri ? pack2(-s, c) : pack2(c, s);
}
__device__ __forceinline__ uint32_t word(const uint4& v, int e) { return e == 0 ? v.x : e == 1 ? v.y : e == 2 ? v.z : v.w; }
__device__ __forceinline__ void cdft16(const uint4 (&q)[4], const uint4 (&F)[4], uint4 (&o)[4]) {
  float acc[2][4][4];
#pragma unroll
  for (int p = 0; p < 2; p++)
#pragma unroll
    for (int v = 0; v < 4; v++) {
      acc[p][v][0] = acc[p][v][1] = acc[p][v][2] = acc[p][v][3] = 0.f;
#pragma unroll
      for (int ks = 0; ks < 2; ks++)
        mma16816(acc[p][v], word(q[2 * ks], 2 * p), word(q[2 * ks], 2 * p + 1), word(q[2 * ks + 1], 2 * p),
                 word(q[2 * ks + 1], 2 * p + 1), word(F[ks * 2 + (v >> 1)], (v & 1) * 2), word(F[ks * 2 + (v >> 1)], (v & 1) * 2 + 1));
    }
#pragma unroll
  for (int v = 0; v < 4; v++)
    o[v] = make_uint4(pack2(acc[0][v][0], acc[0][v][1]), pack2(acc[0][v][2], acc[0][v][3]),
                      pack2(acc[1][v][0], acc[1][v][1]), pack2(acc[1][v][2], acc[1][v][3]));
}
__device__ __forceinline__ void st_tag(uint4* p, const uint4& v, uint32_t tag) {
  asm volatile("{.reg .b128 r; .reg .b64 a, b; mov.b64 a, {%1,%2}; mov.b64 b, {%3,%4}; mov.b128 r, {a,b}; st.relaxed.gpu.global.b128 [%0], r;}"
               ::"l"(p), "r"((v.x & ~1u) | tag), "r"(v.y), "r"(v.z), "r"(v.w) : "memory");
}
__device__ __forceinline__ uint4 ld_b128(const uint4* p) {
  uint4 v;
  asm volatile("{.reg .b128 r; .reg .b64 a, b; ld.relaxed.gpu.global.b128 r, [%4]; mov.b128 {a,b}, r; mov.b64 {%0,%1}, a; mov.b64 {%2,%3}, b;}"
               : "=r"(v.x), "=r"(v.y), "=r"(v.z), "=r"(v.w) : "l"(p) : "memory");
  return v;
}
template <int STRIDE>
__device__ __forceinline__ void ld_tag4_issue(uint4 (&q)[4], const uint4* p) {
#pragma unroll
  for (int i = 0; i < 4; i++) q[i] = ld_b128(p + i * STRIDE);
}
template <int STRIDE>
__device__ __forceinline__ void ld_tag4_finish(uint4 (&q)[4], const uint4* p, uint32_t tag) {
  int it = 0;
#pragma unroll 1
  while (__any_sync(0xffffffffu, ((q[0].x ^ tag) | (q[1].x ^ tag) | (q[2].x ^ tag) | (q[3].x ^ tag)) & 1u)) {
    ld_tag4_issue<STRIDE>(q, p);
    if (++it > SPIN_LIMIT) { die(); break; }
  }
#pragma unroll
  for (int i = 0; i < 4; i++) asm volatile("and.b32 %0, %0, 0xfffffffe;" : "+r"(q[i].x));
}
__device__ __forceinline__ void row_stats(const uint32_t (&a)[8], const uint32_t (&b)[8], int lane, float (&sum)[2], float (&sq)[2]) {
  float da[4] = {0.f, 0.f, 0.f, 0.f}, db[4] = {0.f, 0.f, 0.f, 0.f}, ds[4] = {0.f, 0.f, 0.f, 0.f};
#pragma unroll
  for (int q = 0; q < 4; q++) {
    mma16816(ds, a[2 * q], b[2 * q], a[2 * q + 1], b[2 * q + 1], 0x3f803f80u, 0x3f803f80u);
    mma16816(da, a[2 * q], b[2 * q], a[2 * q + 1], b[2 * q + 1], a[2 * q], a[2 * q + 1]);
    mma16816(db, a[2 * q], b[2 * q], a[2 * q + 1], b[2 * q + 1], b[2 * q], b[2 * q + 1]);
  }
  const int src = (lane & 28) | (lane >> 3);
  const float qa = __shfl_sync(0xffffffffu, (lane & 4) ? da[1] : da[0], src);
  const float qb = __shfl_sync(0xffffffffu, (lane & 4) ? db[3] : db[2], src);
  float v = (lane & 2) ? ((lane & 1) ? ds[2] : ds[0]) : ((lane & 1) ? qb : qa);
  v += __shfl_xor_sync(0xffffffffu, v, 4);
  v += __shfl_xor_sync(0xffffffffu, v, 8);
  v += __shfl_xor_sync(0xffffffffu, v, 16);
  sq[0] = __shfl_sync(0xffffffffu, v, 0);
  sq[1] = __shfl_sync(0xffffffffu, v, 1);
  sum[0] = __shfl_sync(0xffffffffu, v, 2);
  sum[1] = __shfl_sync(0xffffffffu, v, 3);
}
__device__ __forceinline__ uint64_t desc64(uint32_t lo, uint32_t hi) {
  uint64_t d;
  asm("mov.b64 %0, {%1, %2};" : "=l"(d) : "r"(lo), "r"(hi));
  return d;
}
constexpr uint32_t desc_hi(uint32_t sbo, uint32_t swz) { return (sbo >> 4) | (swz << 30); }
__device__ __forceinline__ uint32_t desc_lo(uint32_t addr, uint32_t lbo) { return ((addr & 0x3FFFF) >> 4) | ((lbo >> 4) << 16); }
__device__ __forceinline__ void cp_async16(uint32_t dst, const void* src) {
  asm volatile("cp.async.cg.shared.global [%0], [%1], 16;" ::"r"(dst), "l"(src) : "memory");
}
__device__ __forceinline__ uint2 lds2(uint32_t a) {
  uint2 v;
  asm volatile("ld.shared.v2.u32 {%0,%1}, [%2];" : "=r"(v.x), "=r"(v.y) : "r"(a) : "memory");
  return v;
}
__device__ __forceinline__ uint32_t lds_u16(uint32_t a) {
  uint16_t v;
  asm volatile("ld.shared.u16 %0, [%1];" : "=h"(v) : "r"(a) : "memory");
  return v;
}
__device__ __forceinline__ void wg_fence() { asm volatile("wgmma.fence.sync.aligned;" ::: "memory"); }
__device__ __forceinline__ void wg_commit() { asm volatile("wgmma.commit_group.sync.aligned;" ::: "memory"); }
template <int N>
__device__ __forceinline__ void wg_wait() { asm volatile("wgmma.wait_group.sync.aligned %0;" ::"n"(N) : "memory"); }
__device__ __forceinline__ void bulk_load(uint32_t dst, const void* src, int bytes, uint32_t bar) {
  asm volatile("cp.async.bulk.shared::cluster.global.mbarrier::complete_tx::bytes [%0], [%1], %2, [%3];"
               ::"r"(dst), "l"(src), "r"(bytes), "r"(bar) : "memory");
}
__device__ __forceinline__ void tma3(uint32_t dst, const CUtensorMap* tm, uint32_t bar, int c0, int c1, int c2) {
  asm volatile("cp.async.bulk.tensor.3d.shared::cluster.global.mbarrier::complete_tx::bytes [%0], [%1, {%3,%4,%5}], [%2];"
               ::"r"(dst), "l"(tm), "r"(bar), "r"(c0), "r"(c1), "r"(c2) : "memory");
}
__device__ __forceinline__ void tma3_mc(uint32_t dst, const CUtensorMap* tm, uint32_t bar, int c1, int c2) {
  asm volatile("cp.async.bulk.tensor.3d.shared::cluster.global.mbarrier::complete_tx::bytes.multicast::cluster [%0], [%1, {%3,%4,%5}], [%2], %6;"
               ::"r"(dst), "l"(tm), "r"(bar), "r"(0), "r"(c1), "r"(c2), "h"((uint16_t)3) : "memory");
}
__device__ __forceinline__ void mbar_arrive_remote(uint32_t rb) {
  asm volatile("mbarrier.arrive.shared::cluster.b64 _, [%0];" ::"r"(rb) : "memory");
}
__device__ __forceinline__ uint4 ldg_ca4(const void* p) {
  uint4 v;
  asm volatile("ld.global.ca.v4.u32 {%0,%1,%2,%3}, [%4];" : "=r"(v.x), "=r"(v.y), "=r"(v.z), "=r"(v.w) : "l"(p) : "memory");
  return v;
}
__device__ __forceinline__ uint32_t clock32() {
  uint32_t v;
  asm volatile("mov.u32 %0, %%clock;" : "=r"(v) :: "memory");
  return v;
}
__device__ __forceinline__ float swiglu(float g, float u, float r) {
  float hg = (0.5f * r) * g, th;
  asm("tanh.approx.f32 %0, %1;" : "=f"(th) : "f"(hg));
  return fmaf(hg, th, hg) * (r * u);
}
__device__ __forceinline__ uint32_t hsub2_bf16(uint32_t a, uint32_t b) {
  uint32_t r;
  asm("sub.rn.bf16x2 %0, %1, %2;" : "=r"(r) : "r"(a), "r"(b));
  return r;
}
__device__ __forceinline__ void l2_prefetch(const void* p, int bytes) {
  asm volatile("cp.async.bulk.prefetch.L2.global [%0], %1;" ::"l"(p), "r"(bytes) : "memory");
}

__device__ __forceinline__ void wgmma_n256(float (&d)[128], uint64_t da, uint64_t db) {
  asm volatile("wgmma.mma_async.sync.aligned.m64n256k16.f32.bf16.bf16 {"
      "%0,%1,%2,%3,%4,%5,%6,%7,%8,%9,%10,%11,%12,%13,%14,%15,"
      "%16,%17,%18,%19,%20,%21,%22,%23,%24,%25,%26,%27,%28,%29,%30,%31,"
      "%32,%33,%34,%35,%36,%37,%38,%39,%40,%41,%42,%43,%44,%45,%46,%47,"
      "%48,%49,%50,%51,%52,%53,%54,%55,%56,%57,%58,%59,%60,%61,%62,%63,"
      "%64,%65,%66,%67,%68,%69,%70,%71,%72,%73,%74,%75,%76,%77,%78,%79,"
      "%80,%81,%82,%83,%84,%85,%86,%87,%88,%89,%90,%91,%92,%93,%94,%95,"
      "%96,%97,%98,%99,%100,%101,%102,%103,%104,%105,%106,%107,%108,%109,%110,%111,"
      "%112,%113,%114,%115,%116,%117,%118,%119,%120,%121,%122,%123,%124,%125,%126,%127"
      "}, %128, %129, 1, 1, 1, 0, 1;\n"
      : "+f"(d[0]),"+f"(d[1]),"+f"(d[2]),"+f"(d[3]),"+f"(d[4]),"+f"(d[5]),"+f"(d[6]),"+f"(d[7]),
        "+f"(d[8]),"+f"(d[9]),"+f"(d[10]),"+f"(d[11]),"+f"(d[12]),"+f"(d[13]),"+f"(d[14]),"+f"(d[15]),
        "+f"(d[16]),"+f"(d[17]),"+f"(d[18]),"+f"(d[19]),"+f"(d[20]),"+f"(d[21]),"+f"(d[22]),"+f"(d[23]),
        "+f"(d[24]),"+f"(d[25]),"+f"(d[26]),"+f"(d[27]),"+f"(d[28]),"+f"(d[29]),"+f"(d[30]),"+f"(d[31]),
        "+f"(d[32]),"+f"(d[33]),"+f"(d[34]),"+f"(d[35]),"+f"(d[36]),"+f"(d[37]),"+f"(d[38]),"+f"(d[39]),
        "+f"(d[40]),"+f"(d[41]),"+f"(d[42]),"+f"(d[43]),"+f"(d[44]),"+f"(d[45]),"+f"(d[46]),"+f"(d[47]),
        "+f"(d[48]),"+f"(d[49]),"+f"(d[50]),"+f"(d[51]),"+f"(d[52]),"+f"(d[53]),"+f"(d[54]),"+f"(d[55]),
        "+f"(d[56]),"+f"(d[57]),"+f"(d[58]),"+f"(d[59]),"+f"(d[60]),"+f"(d[61]),"+f"(d[62]),"+f"(d[63]),
        "+f"(d[64]),"+f"(d[65]),"+f"(d[66]),"+f"(d[67]),"+f"(d[68]),"+f"(d[69]),"+f"(d[70]),"+f"(d[71]),
        "+f"(d[72]),"+f"(d[73]),"+f"(d[74]),"+f"(d[75]),"+f"(d[76]),"+f"(d[77]),"+f"(d[78]),"+f"(d[79]),
        "+f"(d[80]),"+f"(d[81]),"+f"(d[82]),"+f"(d[83]),"+f"(d[84]),"+f"(d[85]),"+f"(d[86]),"+f"(d[87]),
        "+f"(d[88]),"+f"(d[89]),"+f"(d[90]),"+f"(d[91]),"+f"(d[92]),"+f"(d[93]),"+f"(d[94]),"+f"(d[95]),
        "+f"(d[96]),"+f"(d[97]),"+f"(d[98]),"+f"(d[99]),"+f"(d[100]),"+f"(d[101]),"+f"(d[102]),"+f"(d[103]),
        "+f"(d[104]),"+f"(d[105]),"+f"(d[106]),"+f"(d[107]),"+f"(d[108]),"+f"(d[109]),"+f"(d[110]),"+f"(d[111]),
        "+f"(d[112]),"+f"(d[113]),"+f"(d[114]),"+f"(d[115]),"+f"(d[116]),"+f"(d[117]),"+f"(d[118]),"+f"(d[119]),
        "+f"(d[120]),"+f"(d[121]),"+f"(d[122]),"+f"(d[123]),"+f"(d[124]),"+f"(d[125]),"+f"(d[126]),"+f"(d[127])
      : "l"(da), "l"(db));
}
__device__ __forceinline__ void wgmma_n192(float (&d)[96], uint64_t da, uint64_t db) {
  asm volatile("wgmma.mma_async.sync.aligned.m64n192k16.f32.bf16.bf16 {"
      "%0,%1,%2,%3,%4,%5,%6,%7,%8,%9,%10,%11,%12,%13,%14,%15,"
      "%16,%17,%18,%19,%20,%21,%22,%23,%24,%25,%26,%27,%28,%29,%30,%31,"
      "%32,%33,%34,%35,%36,%37,%38,%39,%40,%41,%42,%43,%44,%45,%46,%47,"
      "%48,%49,%50,%51,%52,%53,%54,%55,%56,%57,%58,%59,%60,%61,%62,%63,"
      "%64,%65,%66,%67,%68,%69,%70,%71,%72,%73,%74,%75,%76,%77,%78,%79,"
      "%80,%81,%82,%83,%84,%85,%86,%87,%88,%89,%90,%91,%92,%93,%94,%95"
      "}, %96, %97, 1, 1, 1, 0, 1;\n"
      : "+f"(d[0]),"+f"(d[1]),"+f"(d[2]),"+f"(d[3]),"+f"(d[4]),"+f"(d[5]),"+f"(d[6]),"+f"(d[7]),
        "+f"(d[8]),"+f"(d[9]),"+f"(d[10]),"+f"(d[11]),"+f"(d[12]),"+f"(d[13]),"+f"(d[14]),"+f"(d[15]),
        "+f"(d[16]),"+f"(d[17]),"+f"(d[18]),"+f"(d[19]),"+f"(d[20]),"+f"(d[21]),"+f"(d[22]),"+f"(d[23]),
        "+f"(d[24]),"+f"(d[25]),"+f"(d[26]),"+f"(d[27]),"+f"(d[28]),"+f"(d[29]),"+f"(d[30]),"+f"(d[31]),
        "+f"(d[32]),"+f"(d[33]),"+f"(d[34]),"+f"(d[35]),"+f"(d[36]),"+f"(d[37]),"+f"(d[38]),"+f"(d[39]),
        "+f"(d[40]),"+f"(d[41]),"+f"(d[42]),"+f"(d[43]),"+f"(d[44]),"+f"(d[45]),"+f"(d[46]),"+f"(d[47]),
        "+f"(d[48]),"+f"(d[49]),"+f"(d[50]),"+f"(d[51]),"+f"(d[52]),"+f"(d[53]),"+f"(d[54]),"+f"(d[55]),
        "+f"(d[56]),"+f"(d[57]),"+f"(d[58]),"+f"(d[59]),"+f"(d[60]),"+f"(d[61]),"+f"(d[62]),"+f"(d[63]),
        "+f"(d[64]),"+f"(d[65]),"+f"(d[66]),"+f"(d[67]),"+f"(d[68]),"+f"(d[69]),"+f"(d[70]),"+f"(d[71]),
        "+f"(d[72]),"+f"(d[73]),"+f"(d[74]),"+f"(d[75]),"+f"(d[76]),"+f"(d[77]),"+f"(d[78]),"+f"(d[79]),
        "+f"(d[80]),"+f"(d[81]),"+f"(d[82]),"+f"(d[83]),"+f"(d[84]),"+f"(d[85]),"+f"(d[86]),"+f"(d[87]),
        "+f"(d[88]),"+f"(d[89]),"+f"(d[90]),"+f"(d[91]),"+f"(d[92]),"+f"(d[93]),"+f"(d[94]),"+f"(d[95])
      : "l"(da), "l"(db));
}
__device__ __forceinline__ void wgmma_rs_n128(float (&d)[64], uint32_t a0, uint32_t a1, uint32_t a2, uint32_t a3, uint64_t db) {
  asm volatile("wgmma.mma_async.sync.aligned.m64n128k16.f32.bf16.bf16 {"
      "%0,%1,%2,%3,%4,%5,%6,%7,%8,%9,%10,%11,%12,%13,%14,%15,"
      "%16,%17,%18,%19,%20,%21,%22,%23,%24,%25,%26,%27,%28,%29,%30,%31,"
      "%32,%33,%34,%35,%36,%37,%38,%39,%40,%41,%42,%43,%44,%45,%46,%47,"
      "%48,%49,%50,%51,%52,%53,%54,%55,%56,%57,%58,%59,%60,%61,%62,%63"
      "}, {%64,%65,%66,%67}, %68, 1, 1, 1, 1;\n"
      : "+f"(d[0]),"+f"(d[1]),"+f"(d[2]),"+f"(d[3]),"+f"(d[4]),"+f"(d[5]),"+f"(d[6]),"+f"(d[7]),
        "+f"(d[8]),"+f"(d[9]),"+f"(d[10]),"+f"(d[11]),"+f"(d[12]),"+f"(d[13]),"+f"(d[14]),"+f"(d[15]),
        "+f"(d[16]),"+f"(d[17]),"+f"(d[18]),"+f"(d[19]),"+f"(d[20]),"+f"(d[21]),"+f"(d[22]),"+f"(d[23]),
        "+f"(d[24]),"+f"(d[25]),"+f"(d[26]),"+f"(d[27]),"+f"(d[28]),"+f"(d[29]),"+f"(d[30]),"+f"(d[31]),
        "+f"(d[32]),"+f"(d[33]),"+f"(d[34]),"+f"(d[35]),"+f"(d[36]),"+f"(d[37]),"+f"(d[38]),"+f"(d[39]),
        "+f"(d[40]),"+f"(d[41]),"+f"(d[42]),"+f"(d[43]),"+f"(d[44]),"+f"(d[45]),"+f"(d[46]),"+f"(d[47]),
        "+f"(d[48]),"+f"(d[49]),"+f"(d[50]),"+f"(d[51]),"+f"(d[52]),"+f"(d[53]),"+f"(d[54]),"+f"(d[55]),
        "+f"(d[56]),"+f"(d[57]),"+f"(d[58]),"+f"(d[59]),"+f"(d[60]),"+f"(d[61]),"+f"(d[62]),"+f"(d[63])
      : "r"(a0), "r"(a1), "r"(a2), "r"(a3), "l"(db));
}

constexpr int C_LN = 0, C_PX = 16, C_PY = 32;
constexpr int NB_CONS = 1, NB_LN = 2, NB_LAG = 4, NB_INIT = 6, NB_RDY = 7;
#define LAGX 3
#define LAGY 3
#define LAG2 2
#define NLL 2
#define POLL_DELAY3 900
#define POLL_DELAY 900
#define FILT_DELAY 1000
#define RING_SIG 0
#define PF2_SIG 1
constexpr int SM_E = 0, SM_X = 16384, SM_E2 = 32768, SM_W = 49152, SM_FC = 69632, SM_T = 73728 - T1_BYTES;
constexpr unsigned long long KORDER = 0xBA9432DC876510ull;
constexpr uint32_t HI128 = desc_hi(1024, 1), HI64 = desc_hi(512, 2);

struct Bars {
  uint64_t full1[32], empty1[32], full2[16], fullA[8], empty2[8], emptyP[8], xbar, hbar, tbar, hint[3], xfree, sig[2], sbar;
  uint32_t epoch;
};

template <int NK, bool STORE>
__device__ __forceinline__ void make_p(const float (&acc)[NK * 16], float r0, float r1, uint4 (&p)[NK], uint4* pbase, int ks0, uint32_t tag) {
#pragma unroll
  for (int j = 0; j < NK; j++) {
    uint32_t w[4];
#pragma unroll
    for (int i = 0; i < 4; i++) {
      const int a = 8 * j + 2 * i, b = a + NK * 8;
      w[i] = pack2(swiglu(acc[a], acc[b], (i & 1) ? r1 : r0), swiglu(acc[a + 1], acc[b + 1], (i & 1) ? r1 : r0));
    }
    asm volatile("" : "+r"(w[0]), "+r"(w[1]), "+r"(w[2]), "+r"(w[3]));
    p[j] = make_uint4(w[0], w[1], w[2], w[3]);
    if (STORE) st_tag(pbase + ((ks0 + j) >> 2) * 1024 + ((ks0 + j) & 3) * 32, p[j], tag);
  }
}
__device__ __forceinline__ void spin_cycles(uint32_t n) {
  const uint32_t t0 = clock32();
  while (clock32() - t0 < n) {}
}

__global__ void __cluster_dims__(2, 1, 1) __launch_bounds__(NTHREADS, 1)
fused_kernel(const __nv_bfloat16* __restrict__ x, const Tables* __restrict__ tab, Scratch* __restrict__ scr,
             __nv_bfloat16* __restrict__ out, const char* __restrict__ wg_raw, const char* __restrict__ wu_raw,
             const char* __restrict__ wd_raw,
             const __grid_constant__ CUtensorMap tmWR, const __grid_constant__ CUtensorMap tmWI,
             const __grid_constant__ CUtensorMap tmGX, const __grid_constant__ CUtensorMap tmUX,
             const __grid_constant__ CUtensorMap tmGY, const __grid_constant__ CUtensorMap tmUY,
             const __grid_constant__ CUtensorMap tmD) {
  extern __shared__ __align__(1024) char smem_raw[];
  const uint32_t sbase = s2u(smem_raw);
  const uint32_t sbar = sbase + 14 * SLOT, sstat = sbar + 1024;
  const int tid = threadIdx.x, lane = tid & 31;
  const int c = blockIdx.x, kh = c & 1, f = (c >> 1) & 7, rb = 2 * (c >> 4) + kh, rb2 = 2 * (c >> 4) + (f >> 2), nq = f & 3;
#define BAR(field, i) (sbar + (uint32_t)offsetof(Bars, field) + 8u * (i))
#define TOFF(field) (sbase + SM_T + (uint32_t)offsetof(Tables, field) + lane * 16)

  if (tid >= 256) {
    asm volatile("setmaxnreg.dec.sync.aligned.u32 56;");
    const int warp = __shfl_sync(0xffffffffu, tid >> 5, 0);
    if (lane == 0) {
      if (warp == 8) {
        if (sbase & 1023) die();
#pragma unroll
        for (int i = 0; i < 18; i++) mbar_init(BAR(emptyP, i), i < 8 ? 8 : i < 14 ? 1 : i < 17 ? 8 : 32);
        mbar_expect(BAR(tbar, 0), T2_BYTES + 2 * 10240);
        mbar_expect(BAR(xbar, 0), 16384);
        mbar_expect(BAR(hbar, 0), 16384);
      } else if (warp == 9) {
#pragma unroll
        for (int i = 0; i < 32; i++) mbar_init(BAR(full1, i), 1);
#pragma unroll
        for (int i = 0; i < 32; i++) mbar_expect(BAR(full1, i), i < 16 ? 16384 : 12288);
      } else if (warp == 10) {
#pragma unroll
        for (int i = 0; i < 32; i++) mbar_init(BAR(empty1, i), 16);
      } else {
#pragma unroll
        for (int i = 0; i < 32; i++) mbar_init(BAR(full2, i), i < 24 ? 1 : 8);
#pragma unroll
        for (int i = 0; i < 24; i++) mbar_expect(BAR(full2, i), i < 16 ? 32768 : 16384);
      }
      asm volatile("fence.mbarrier_init.release.cluster;" ::: "memory");
    }
    if (tid == 256) {
      const int w0 = ((c >> 3) * 257 + 32 * (c & 7) + 1) & ~7;
      if (FILT_DELAY) {
        asm volatile("prefetch.tensormap [%0];" ::"l"(&tmWR) : "memory");
        asm volatile("prefetch.tensormap [%0];" ::"l"(&tmWI) : "memory");
        spin_cycles(FILT_DELAY);
      }
      tma3(sbase + SM_W, &tmWR, BAR(tbar, 0), w0, 0, 0);
      tma3(sbase + SM_W + 10240, &tmWI, BAR(tbar, 0), w0, 0, 0);
      bulk_load(sbase + SM_T + T1_BYTES, reinterpret_cast<const char*>(tab) + T1_BYTES, T2_BYTES, BAR(tbar, 0));
    }
    if (tid == 288) {
      asm volatile("prefetch.tensormap [%0];" ::"l"(kh ? &tmUX : &tmGX) : "memory");
      asm volatile("prefetch.tensormap [%0];" ::"l"(kh ? &tmUY : &tmGY) : "memory");
      asm volatile("prefetch.tensormap [%0];" ::"l"(&tmD) : "memory");
    }
    if (tid == 320) {
      const unsigned e = ld_relaxed(&scr->cnt[(C_LN + rb) * 32]) >> 3;
      asm volatile("st.shared.u32 [%0], %1;" ::"r"(BAR(epoch, 0)), "r"(e) : "memory");
    }
    __syncwarp();
    asm volatile("barrier.cluster.arrive.relaxed.aligned;" ::: "memory");
    bar_arrive(NB_RDY, 384);
    asm volatile("barrier.cluster.wait.aligned;" ::: "memory");
    bar_sync(NB_INIT, 384);
    unsigned epoch;
    asm volatile("ld.shared.u32 %0, [%1];" : "=r"(epoch) : "r"(BAR(epoch, 0)) : "memory");
    if (warp == 8) {
      if (lane == 0) {
        const int ax = (7 * f + 3 * (f & 1)) >> 1;
        const int ay = 7 * f + ((f & 1) ? 0 : 4);
        const CUtensorMap* tx = kh ? &tmUX : &tmGX;
        const CUtensorMap* ty = kh ? &tmUY : &tmGY;
        if (RING_SIG >= 0) mbar_wait(BAR(sig, RING_SIG));
        uint32_t s = 2;
#pragma unroll 1
        for (int n = 0; n < 16; n++) {
          if (n >= 6) mbar_wait(BAR(empty1, n - 6));
          tma3_mc(sbase + (8 + s) * SLOT + kh * 8192, tx, BAR(full1, n), n * 32, ax);
          if (++s == 6) s = 0;
        }
#pragma unroll 1
        for (int k = 0; k < 16; k++) {
          mbar_wait(BAR(empty1, k < 8 ? 10 + ((12 * k + 11) >> 4) : 8 + k));
          tma3_mc(sbase + 8 * SLOT + (k & 7) * 12288 + kh * 6144, ty, BAR(full1, 16 + k), k * 32, ay);
        }
      }
    } else if (warp == 9) {
      if (lane == 0) {
#pragma unroll 1
        for (int i = 0; i < 14; i++) {
          const int kblk = 14 * kh + (int)((KORDER >> (4 * i)) & 15);
          mbar_wait(i < 8 ? BAR(empty1, 17 + 2 * i) : BAR(empty2, i - 8));
          tma3(sbase + (i & 7) * SLOT, &tmD, BAR(full2, i), 0, 64 * kblk, 2 * nq);
        }
        wait_counter(&scr->cnt[(C_LN + rb2) * 32], (epoch + 1) * 8);
        asm volatile("fence.proxy.async.global;" ::: "memory");
        mbar_wait(BAR(empty2, 7), 0);
        bulk_load(sbase + 7 * SLOT, &scr->LN[(rb2 * 8 + 2 * nq) * 1024 + kh * 512], 8192, BAR(hbar, 0));
        bulk_load(sbase + 7 * SLOT + 8192, &scr->LN[(rb2 * 8 + 2 * nq + 1) * 1024 + kh * 512], 8192, BAR(hbar, 0));
      }
    } else if (warp == 10) {
      bar_sync(NB_LN, 288);
      if (lane == 0) {
        PROFP(0);
        red_release(&scr->cnt[(C_LN + rb) * 32]);
        PROFP(1);
        wait_counter(&scr->cnt[(C_LN + rb) * 32], (epoch + 1) * 8);
        asm volatile("fence.proxy.async.global;" ::: "memory");
        PROFP(2);
#pragma unroll 1
        for (int kb = NLL; kb < 8; kb++) bulk_load(sbase + kb * SLOT, &scr->LN[(rb * 8 + kb) * 1024], 16384, BAR(fullA, kb));
        uint32_t d = 0;
#pragma unroll 1
        for (int s = 0; s < 14; s++) {
          const int kblk = 14 * kh + (int)((KORDER >> (4 * s)) & 15);
          if (s == 0 || s == 8 || s == 11) {
            if (s != 11) PROFP(3 + (s >> 2));
            mbar_wait(BAR(hint, s == 0 ? 0 : s == 8 ? 1 : 2), 0);
            if (s != 11) PROFP(4 + (s >> 2));
          }
          mbar_wait(s < 6 ? BAR(empty1, 25 + s + (s >= 3)) : BAR(emptyP, s - 6));
          bulk_load(sbase + (8 + d) * SLOT, &scr->P[(rb2 * 28 + kblk) * 1024], 16384, BAR(full2, s));
          if (++d == 6) d = 0;
        }
        PROFP(7);
      }
    } else {
      if (lane == 0) {
        l2_prefetch(wg_raw + (size_t)c * 5376, 5376);
        l2_prefetch(wu_raw + (size_t)c * 5376, 5376);
        mbar_wait(BAR(sig, PF2_SIG), 0);
        l2_prefetch(wg_raw + 688128 + (size_t)c * 8960, 8960);
        l2_prefetch(wu_raw + 688128 + (size_t)c * 8960, 8960);
      }
      mbar_wait(BAR(fullA, 7), 0);
      if (lane == 0) l2_prefetch(wd_raw + (size_t)c * 14336, 14336);
      {
        const uint32_t tag = (epoch + 1) & 1;
        uint4 v0, v1, v2;
        int it = 0;
        while (true) {
          v0 = ld_b128(&scr->ST[rb * 64 + lane]);
          v1 = ld_b128(&scr->ST[rb * 64 + 32 + lane]);
          v2 = ld_b128(&scr->ST[rb2 * 64 + 32 * kh + lane]);
          if (!__any_sync(0xffffffffu, ((v0.x ^ tag) | (v1.x ^ tag) | (v2.x ^ tag)) & 1u)) break;
          if (++it > SPIN_LIMIT) { die(); break; }
        }
        sts4(sstat + lane * 16, v0.x & ~1u, v0.y, v0.z, v0.w);
        sts4(sstat + 512 + lane * 16, v1.x & ~1u, v1.y, v1.z, v1.w);
        sts4(sstat + 1024 + lane * 16, v2.x & ~1u, v2.y, v2.z, v2.w);
        mbar_arrive(BAR(sbar, 0));
      }
      if (lane == 0) {
        mbar_wait(BAR(empty1, 17));
#pragma unroll 1
        for (int e = 0; e < 3; e++) {
          const unsigned* cp = e == 0 ? &scr->cnt[(C_PX + rb2) * 32] : &scr->cnt[(C_PY + rb2) * 32 + 2 * kh + e - 1];
          if (e == 1) mbar_wait(BAR(full2, 0), 0);
          int it = 0;
          while ((int)(ld_relaxed(cp) - (epoch + 1) * (e == 0 ? 64 : 16)) < 0)
            if (++it > SPIN_LIMIT) { die(); break; }
          mbar_arrive(BAR(hint, e));
        }
      }
    }
  } else {
    const int warp = __shfl_sync(0xffffffffu, tid >> 5, 0);
    const int g = lane >> 2, t = lane & 3;
    PROF(0);
    PROFG(14);
#pragma unroll
    for (int i = 0; i < 4; i++) {
      const int r = i >> 1, ch = (i & 1) * 32 + lane;
      cp_async16(sbase + SM_X + (2 * warp + r) * 1024 + ((ch ^ ((ch >> 2) & 6)) * 16),
                 x + (size_t)(c + 128 * (2 * warp + r)) * 512 + ch * 8);
    }
    asm volatile("cp.async.commit_group;" ::: "memory");
    asm volatile("barrier.cluster.arrive.relaxed.aligned;" ::: "memory");
    uint4 tw[8], fb[16];
    const uint4 fa = ldg_ca4(&tab->fa[lane][0]);
#pragma unroll
    for (int i = 0; i < 8; i++) tw[i] = ldg_ca4(&tab->tw1[i][lane][0]);
#pragma unroll
    for (int i = 0; i < 16; i++) fb[i] = ldg_ca4(&tab->fb[i][lane][0]);
    uint32_t rbar;
    asm volatile("mapa.shared::cluster.u32 %0, %1, %2;" : "=r"(rbar) : "r"(sbar), "r"(kh ^ 1));
#define RBAR(field, i) (rbar + (uint32_t)offsetof(Bars, field) + 8u * (i))
    {
      const int ln = (tid >> 1) & 31, lg = ln >> 2, lt = ln & 3, i = 4 * (tid >> 6) + 2 * (tid & 1);
      const int kidx = lt + 8 * (i >> 3), nidx = 4 * ((i >> 1) & 3) + (lg >> 1);
      const uint32_t a0 = cfrag<2048>((c + 128 * kidx) * nidx, lg & 1), a1 = cfrag<2048>((c + 128 * (kidx + 4)) * nidx, lg & 1);
      const uint32_t b0 = cfrag<2048>(-(c + 128 * nidx) * kidx, lg & 1), b1 = cfrag<2048>(-(c + 128 * nidx) * (kidx + 4), lg & 1);
      asm volatile("st.shared.v2.u32 [%0], {%1,%2};" ::"r"(sbase + SM_FC + tid * 8), "r"(a0), "r"(a1) : "memory");
      asm volatile("st.shared.v2.u32 [%0], {%1,%2};" ::"r"(sbase + SM_FC + 2048 + tid * 8), "r"(b0), "r"(b1) : "memory");
    }
    asm volatile("cp.async.wait_group 0;" ::: "memory");
    __syncwarp();
    bar_arrive(NB_INIT, 384);
    PROF(13);
    uint32_t tag;
    uint4 q[4], o[4];
    {
      uint32_t v[2][8];
#pragma unroll
      for (int r = 0; r < 2; r++)
#pragma unroll
        for (int q = 0; q < 4; q++) {
          const uint2 u = lds2(sbase + SM_X + (2 * warp + r) * 1024 + (t + 4 * (q >> 1)) * 128 + (((4 * (q & 1) + (g >> 1)) ^ (2 * t)) * 16) + (g & 1) * 8);
          v[r][2 * q] = u.x; v[r][2 * q + 1] = u.y;
        }
      float sum[2], sq[2], rstd[2];
      row_stats(v[0], v[1], lane, sum, sq);
#pragma unroll
      for (int r = 0; r < 2; r++) {
        const float m = sum[r] * (1.f / 512.f);
        rstd[r] = rsqrtf(fmaxf(fmaf(-m, m, sq[r] * (1.f / 512.f)), 0.f) + 1e-5f);
      }
      uint32_t alo[4][4], ahi[4][4];
#pragma unroll
      for (int r = 0; r < 2; r++)
#pragma unroll
        for (int i = 0; i < 4; i++) {
          const uint32_t sel = (i & 1) ? 0x7632u : 0x5410u;
          const uint32_t b0 = __byte_perm(v[r][i >> 1], v[r][2 + (i >> 1)], sel);
          const uint32_t b1 = __byte_perm(v[r][4 + (i >> 1)], v[r][6 + (i >> 1)], sel);
          float d[4] = {0.f, 0.f, 0.f, 0.f};
          mma16816(d, fa.x, fa.y, fa.z, fa.w, b0, b1);
          const uint4 &ka = tw[2 * i], &kb = tw[2 * i + 1];
          const uint32_t re = pack2(d[0] * __uint_as_float(ka.x) + d[2] * __uint_as_float(ka.y), d[1] * __uint_as_float(kb.x) + d[3] * __uint_as_float(kb.y));
          const uint32_t im = pack2(d[0] * __uint_as_float(ka.z) + d[2] * __uint_as_float(ka.w), d[1] * __uint_as_float(kb.z) + d[3] * __uint_as_float(kb.w));
          const uint32_t dc = pack2(fmaf(sum[r], -1.f / 32.f, d[0]), fmaf(sum[r], -1.f / 32.f, d[1]));
          alo[i][r] = re; alo[i][2 + r] = im;
          ahi[i][r] = g == 0 ? dc : re; ahi[i][2 + r] = g == 0 ? 0u : im;
        }
      float acc[8][4];
#pragma unroll
      for (int u = 0; u < 8; u++) {
        acc[u][0] = acc[u][1] = acc[u][2] = acc[u][3] = 0.f;
#pragma unroll
        for (int i = 0; i < 4; i++) {
          const uint4& bq = fb[i * 4 + (u >> 1)];
          if (u < 4) mma16816(acc[u], alo[i][0], alo[i][1], alo[i][2], alo[i][3], (u & 1) ? bq.z : bq.x, (u & 1) ? bq.w : bq.y);
          else       mma16816(acc[u], ahi[i][0], ahi[i][1], ahi[i][2], ahi[i][3], (u & 1) ? bq.z : bq.x, (u & 1) ? bq.w : bq.y);
        }
      }
#pragma unroll
      for (int r = 0; r < 2; r++)
#pragma unroll
        for (int h = 0; h < 2; h++) {
          const int j = 2 * warp + r, m = 2 * t + h;
          const float rs = rstd[r];
          sts4(sbase + SM_E + ((j * 8 + m) * 8 + (g ^ (2 * t) ^ (2 * (j & 3)))) * 16,
               pack2(acc[2 * h][2 * r] * rs, acc[2 * h][2 * r + 1] * rs), pack2(acc[2 * h + 1][2 * r] * rs, acc[2 * h + 1][2 * r + 1] * rs),
               pack2(acc[4 + 2 * h][2 * r] * rs, acc[4 + 2 * h][2 * r + 1] * rs), pack2(acc[5 + 2 * h][2 * r] * rs, acc[5 + 2 * h][2 * r + 1] * rs));
        }
      if (tid == 0) PROFP(12);
      bar_sync(NB_RDY, 384);
      if (tid == 0) PROFP(13);
      uint4 fc[4];
#pragma unroll
      for (int i = 0; i < 4; i++) fc[i] = lds4(sbase + SM_FC + i * 512 + lane * 16);
      asm volatile("ld.shared.u32 %0, [%1];" : "=r"(tag) : "r"(BAR(epoch, 0)) : "memory");
      tag = (tag + 1) & 1;
#pragma unroll
      for (int i = 0; i < 4; i++) q[i] = lds4(sbase + SM_E + (((t + 4 * i) * 8 + warp) * 8 + (g ^ (warp & 6) ^ (2 * t))) * 16);
      cdft16(q, fc, o);
#pragma unroll
      for (int vv = 0; vv < 4; vv++) st_tag(&scr->Z1[(((4 * vv + t) * 8 + warp) * 128 + c) * 8 + g], o[vv], tag);
    }
    PROF(1);
    {
      const uint4* const zp = &scr->Z1[(c * 128 + 8 * t + warp) * 8 + g];
      const uint32_t tst = clock32();
      mbar_wait(BAR(tbar, 0), 0);
      if (tid == 0) PROFP(14);
      uint4 f2[4], g2[4];
#pragma unroll
      for (int i = 0; i < 4; i++) {
        f2[i] = lds4(TOFF(f2) + warp * 2048 + i * 512);
        g2[i] = lds4(TOFF(g2) + warp * 2048 + i * 512);
      }
      const uint4 f8 = lds4(TOFF(f8)), g8 = lds4(TOFF(g8));
      float wfr[16], wfi[16];
      {
        const float fsc = 1.f / (1 << 19);
        const float fsc3 = ((c & 7) == 7 && g == 0) ? 0.5f * fsc : fsc;
        const int gg = g == 0 ? 8 : g, wsh = (2 * (c >> 3) + 2) & 15;
#pragma unroll
        for (int i = 0; i < 16; i++) {
          const int ci = i >> 3, dd = (i >> 2) & 1, e = i & 3;
          const int kk = (e == 0 ? gg : e == 1 ? 16 + gg : e == 2 ? 16 - g : 32 - g) - 1;
          const uint32_t a = sbase + SM_W + ((2 * warp + ci) * 8 + t + 4 * dd) * 80 + wsh + 2 * kk;
          wfr[i] = bf_lo(lds_u16(a)) * (e == 3 ? fsc3 : fsc);
          wfi[i] = bf_lo(lds_u16(a + 10240)) * (e == 3 ? fsc3 : fsc);
        }
      }
      asm volatile("barrier.cluster.wait.aligned;" ::: "memory");
      PROF(2);
      while (clock32() - tst < POLL_DELAY) {}
      ld_tag4_issue<256>(q, zp);
      ld_tag4_finish<256>(q, zp, tag);
      if (tid == 0) PROFP(30);
      if (lane == 0) mbar_arrive(BAR(sig, 0));
      cdft16(q, f2, o);
      const uint32_t e2 = sbase + SM_E2;
#pragma unroll
      for (int vv = 0; vv < 4; vv++)
        sts4(e2 + ((warp * 16 + 4 * vv + t) * 8 + (g ^ (2 * t) ^ (2 * (warp & 3)))) * 16, o[vv].x, o[vv].y, o[vv].z, o[vv].w);
      bar_sync(NB_CONS, 256);
#pragma unroll
      for (int ci = 0; ci < 2; ci++) {
        const int cc = 2 * warp + ci;
        uint32_t ad[2];
        uint4 u[2];
#pragma unroll
        for (int hh = 0; hh < 2; hh++) {
          ad[hh] = e2 + (((t + 4 * hh) * 16 + cc) * 8 + (g ^ (2 * (cc & 3)) ^ (2 * t))) * 16;
          u[hh] = lds4(ad[hh]);
        }
        uint32_t res[2][4];
#pragma unroll
        for (int p = 0; p < 2; p++) {
          uint32_t y[2][2];
#pragma unroll
          for (int vv = 0; vv < 2; vv++) {
            float d[4] = {0.f, 0.f, 0.f, 0.f};
            mma16816(d, word(u[0], 2 * p), word(u[0], 2 * p + 1), word(u[1], 2 * p), word(u[1], 2 * p + 1), word(f8, 2 * vv), word(f8, 2 * vv + 1));
#pragma unroll
            for (int rr = 0; rr < 2; rr++) {
              const float fr = wfr[ci * 8 + vv * 4 + 2 * p + rr], fi = wfi[ci * 8 + vv * 4 + 2 * p + rr];
              y[vv][rr] = pack2(d[2 * rr] * fr - d[2 * rr + 1] * fi, d[2 * rr] * fi + d[2 * rr + 1] * fr);
            }
          }
#pragma unroll
          for (int vv = 0; vv < 2; vv++) {
            float d[4] = {0.f, 0.f, 0.f, 0.f};
            mma16816(d, y[0][0], y[0][1], y[1][0], y[1][1], word(g8, 2 * vv), word(g8, 2 * vv + 1));
            res[vv][2 * p] = pack2(d[0], d[1]);
            res[vv][2 * p + 1] = pack2(d[2], d[3]);
          }
        }
#pragma unroll
        for (int vv = 0; vv < 2; vv++) sts4(ad[vv], res[vv][0], res[vv][1], res[vv][2], res[vv][3]);
      }
      bar_sync(NB_CONS, 256);
#pragma unroll
      for (int i = 0; i < 4; i++) q[i] = lds4(e2 + ((warp * 16 + 4 * i + t) * 8 + (g ^ (2 * t) ^ (2 * (warp & 3)))) * 16);
      cdft16(q, g2, o);
#pragma unroll
      for (int vv = 0; vv < 4; vv++) st_tag(&scr->Z2[((8 * (4 * vv + t) + warp) * 128 + c) * 8 + g], o[vv], tag);
    }
    PROF(3);
    {
      const uint4* const zp = &scr->Z2[((c * 16 + t) * 8 + warp) * 8 + g];
      const uint32_t tst = clock32();
      uint4 gb[16], gc[4], tw[4], xr[2][2];
#pragma unroll
      for (int i = 0; i < 16; i++) gb[i] = lds4(TOFF(gb) + i * 512);
      const uint4 ga = lds4(TOFF(ga));
#pragma unroll
      for (int i = 0; i < 4; i++) {
        gc[i] = lds4(sbase + SM_FC + 2048 + i * 512 + lane * 16);
        tw[i] = lds4(TOFF(tw3) + i * 512);
        const int ch = 4 * (g + 8 * (i & 1)) + t;
        xr[i >> 1][i & 1] = lds4(sbase + SM_X + (2 * warp + (i >> 1)) * 1024 + ((ch ^ ((ch >> 2) & 6)) * 16));
      }
      PROF(4);
      while (clock32() - tst < POLL_DELAY) {}
      ld_tag4_issue<256>(q, zp);
      ld_tag4_finish<256>(q, zp, tag);
      if (tid == 0) PROFP(31);
      if (lane == 0) mbar_arrive(BAR(sig, 1));
      cdft16(q, gc, o);
#pragma unroll
      for (int vv = 0; vv < 4; vv++)
        sts4(sbase + SM_E + (((4 * vv + t) * 8 + warp) * 8 + (g ^ (warp & 6) ^ (2 * t))) * 16, o[vv].x, o[vv].y, o[vv].z, o[vv].w);
      bar_sync(NB_CONS, 256);
      uint32_t hv[2][8];
      const float mk = t == 0 ? 0.f : 1.f;
#pragma unroll
      for (int r = 0; r < 2; r++) {
        const int j = 2 * warp + r;
        uint4 u[2];
#pragma unroll
        for (int h = 0; h < 2; h++) u[h] = lds4(sbase + SM_E + ((j * 8 + 2 * t + h) * 8 + (g ^ (2 * t) ^ (2 * (j & 3)))) * 16);
        float yv[4][4];
#pragma unroll
        for (int i = 0; i < 4; i++) {
          float lo[4] = {0.f, 0.f, 0.f, 0.f}, hi[4] = {0.f, 0.f, 0.f, 0.f};
          mma16816(lo, gb[i * 4].x, gb[i * 4].y, gb[i * 4].z, gb[i * 4].w, u[0].x, u[0].y);
          mma16816(lo, gb[i * 4 + 1].x, gb[i * 4 + 1].y, gb[i * 4 + 1].z, gb[i * 4 + 1].w, u[1].x, u[1].y);
          mma16816(hi, gb[i * 4 + 2].x, gb[i * 4 + 2].y, gb[i * 4 + 2].z, gb[i * 4 + 2].w, u[0].z, u[0].w);
          mma16816(hi, gb[i * 4 + 3].x, gb[i * 4 + 3].y, gb[i * 4 + 3].z, gb[i * 4 + 3].w, u[1].z, u[1].w);
          const float ca = __uint_as_float(tw[i].x), sa = __uint_as_float(tw[i].y), cb = __uint_as_float(tw[i].z), sb = __uint_as_float(tw[i].w);
          const float tr0 = fmaf(hi[0], mk, lo[0]), ti0 = fmaf(hi[2], mk, lo[2]);
          const float tr1 = lo[1] + hi[1], ti1 = lo[3] + hi[3];
          const float vr0 = tr0 * ca - ti0 * sa, vi0 = tr0 * sa + ti0 * ca;
          const float vr1 = tr1 * cb - ti1 * sb, vi1 = tr1 * sb + ti1 * cb;
          const uint32_t b0 = pack2(t == 0 ? hi[0] : vr0, vr1), b1 = pack2(t == 0 ? vr0 : vi0, vi1);
          yv[i][0] = yv[i][1] = yv[i][2] = yv[i][3] = 0.f;
          mma16816(yv[i], ga.x, ga.y, ga.z, ga.w, b0, b1);
        }
#pragma unroll
        for (int h = 0; h < 2; h++) {
          hv[r][4 * h + 0] = hadd2_bf16(xr[r][h].x, pack2(yv[0][2 * h], yv[1][2 * h]));
          hv[r][4 * h + 1] = hadd2_bf16(xr[r][h].y, pack2(yv[2][2 * h], yv[3][2 * h]));
          hv[r][4 * h + 2] = hadd2_bf16(xr[r][h].z, pack2(yv[0][2 * h + 1], yv[1][2 * h + 1]));
          hv[r][4 * h + 3] = hadd2_bf16(xr[r][h].w, pack2(yv[2][2 * h + 1], yv[3][2 * h + 1]));
        }
      }
      float ds[4] = {0.f, 0.f, 0.f, 0.f};
#pragma unroll
      for (int q4 = 0; q4 < 4; q4++) mma16816(ds, hv[0][2 * q4], hv[1][2 * q4], hv[0][2 * q4 + 1], hv[1][2 * q4 + 1], 0x3f803f80u, 0x3f803f80u);
#pragma unroll
      for (int o2 = 4; o2 <= 16; o2 <<= 1) {
        ds[0] += __shfl_xor_sync(0xffffffffu, ds[0], o2);
        ds[2] += __shfl_xor_sync(0xffffffffu, ds[2], o2);
      }
      uint32_t mb[2];
#pragma unroll
      for (int r = 0; r < 2; r++) {
        const int row = 16 * f + 2 * warp + r;
        mb[r] = pack2(ds[2 * r] * (1.f / 512.f), ds[2 * r] * (1.f / 512.f));
#pragma unroll
        for (int i = 0; i < 8; i++) hv[r][i] = hsub2_bf16(hv[r][i], mb[r]);
#pragma unroll
        for (int h = 0; h < 2; h++) {
          const int n1 = g + 8 * h;
          st_tag(&scr->LN[(rb * 8 + (n1 >> 1)) * 1024 + row * 8 + ((4 * (n1 & 1) + t) ^ (row & 7))],
                 make_uint4(hv[r][4 * h], hv[r][4 * h + 1], hv[r][4 * h + 2], hv[r][4 * h + 3]), n1 < 2 * NLL ? tag : (hv[r][4 * h] & 1u));
        }
      }
      bar_arrive(NB_LN, 288);
      float sum[2], sq[2], rstd[2];
      row_stats(hv[0], hv[1], lane, sum, sq);
#pragma unroll
      for (int r = 0; r < 2; r++) {
        const float m = sum[r] * (1.f / 512.f);
        rstd[r] = rsqrtf(fmaxf(fmaf(-m, m, sq[r] * (1.f / 512.f)), 0.f) + 1e-5f);
      }
      if (lane == 0)
        st_tag(&scr->ST[rb * 64 + 8 * f + warp], make_uint4(mb[0] << 16, __float_as_uint(rstd[0]), mb[1] << 16, __float_as_uint(rstd[1])), tag);
    }
    PROF(5);
    asm volatile("setmaxnreg.inc.sync.aligned.u32 224;");
    if (NLL) {
      const uint4* const ap = &scr->LN[rb * 8 * 1024 + tid];
      uint4 av[NLL ? NLL : 1][4];
      spin_cycles(POLL_DELAY3);
#pragma unroll
      for (int kb = 0; kb < NLL; kb++) ld_tag4_issue<256>(av[kb], ap + kb * 1024);
      bar_sync(NB_CONS, 256);
#pragma unroll
      for (int kb = 0; kb < NLL; kb++) {
        ld_tag4_finish<256>(av[kb], ap + kb * 1024, tag);
#pragma unroll
        for (int i = 0; i < 4; i++) sts4(sbase + kb * SLOT + (tid + 256 * i) * 16, av[kb][i].x, av[kb][i].y, av[kb][i].z, av[kb][i].w);
      }
      asm volatile("fence.proxy.async.shared::cta;" ::: "memory");
      bar_sync(NB_CONS, 256);
    }
    const int wgi = warp >> 2, wq = warp & 3;
    uint4* const pbase = &scr->P[rb * 28 * 1024 + warp * 128 + lane];
    const uint32_t a_lo0 = desc_lo(sbase + wgi * 8192, 16);
    const uint32_t ebar = lane == 0 ? BAR(empty1, 0) : RBAR(empty1, 0);
    float r0, r1;
    uint4 px[8], py[6];
    const int rh = wgi ^ kh ^ 1;
    const uint4* const psrc = &scr->P[(rb2 * 28 + 14 * kh) * 1024 + (4 * rh + wq) * 128 + lane];
    {
      float acc[128];
#pragma unroll
      for (int i = 0; i < 128; i++) acc[i] = 0.f;
      const uint32_t b_lo0 = desc_lo(sbase + 8 * SLOT, 4096);
      uint32_t slot = 2;
#pragma unroll 1
      for (int kb = 0; kb < 8; kb++) {
        if (kb >= NLL) mbar_wait(BAR(fullA, kb), 0);
        if (kb == 0) PROF(6);
#pragma unroll
        for (int hh = 0; hh < 2; hh++) {
          if (LAGX && hh == ((16 - LAGX) & 1) && kb == ((16 - LAGX) >> 1) && wgi == 1) bar_sync(NB_LAG, 256);
          mbar_wait(BAR(full1, 2 * kb + hh));
          const uint32_t al = a_lo0 + kb * 1024 + hh * 4, bl = b_lo0 + slot * 1024;
          wg_fence();
          wgmma_n256(acc, desc64(al, HI128), desc64(bl, HI128));
          wgmma_n256(acc, desc64(al + 2, HI128), desc64(bl + 128, HI128));
          wg_commit();
          if (LAGX && hh == 1 && kb == 7 && wgi == 0) bar_arrive(NB_LAG, 256);
          wg_wait<1>();
          if ((kb | hh) != 0 && lane < 2) mbar_arrive_remote(ebar + 8 * (2 * kb + hh - 1));
          if (++slot == 6) slot = 0;
        }
      }
      mbar_wait(BAR(sbar, 0), 0);
      r0 = __uint_as_float(lds2(sstat + (16 * warp + g) * 8).y);
      r1 = __uint_as_float(lds2(sstat + (16 * warp + g + 8) * 8).y);
      wg_wait<0>();
      if (lane < 2) mbar_arrive_remote(ebar + 8 * 15);
      PROF(7);
      make_p<8, false>(acc, r0, r1, px, pbase, 0, tag);
    }
    PROF(8);
    {
      float acc[96];
#pragma unroll
      for (int i = 0; i < 96; i++) acc[i] = 0.f;
      const uint32_t b_lo0 = desc_lo(sbase + 8 * SLOT, 2048);
      uint4* const pdst = pbase + ((7 * f + 3 * (f & 1)) >> 1) * 1024;
      auto stage_y = [&](int k) {
        if (LAGY && k == 16 - LAGY && wgi == 1) bar_sync(NB_LAG, 256);
        mbar_wait(BAR(full1, 16 + k));
        const uint32_t al = a_lo0 + (k >> 1) * 1024 + (k & 1) * 4, bl = b_lo0 + (k & 7) * 768;
        wg_fence();
        wgmma_n192(acc, desc64(al, HI128), desc64(bl, HI64));
        wgmma_n192(acc, desc64(al + 2, HI128), desc64(bl + 64, HI64));
        wg_commit();
      };
#pragma unroll
      for (int k = 0; k < 4; k++) {
        stage_y(k);
        st_tag(pdst + (k >> 1) * 1024 + (k & 1) * 64, px[2 * k], tag);
        st_tag(pdst + (k >> 1) * 1024 + (k & 1) * 64 + 32, px[2 * k + 1], tag);
        if (k == 3 && lane == 0) red_relaxed(&scr->cnt[(C_PX + rb) * 32]);
        wg_wait<1>();
        if (k != 0 && lane < 2) mbar_arrive_remote(ebar + 8 * (15 + k));
      }
#pragma unroll 1
      for (int k = 4; k < 16; k++) {
        stage_y(k);
        if (LAGY && k == 15 && wgi == 0) bar_arrive(NB_LAG, 256);
        wg_wait<1>();
        if (lane < 2) mbar_arrive_remote(ebar + 8 * (15 + k));
      }
      wg_wait<0>();
      if (lane < 2) mbar_arrive_remote(ebar + 8 * 31);
      PROF(9);
      make_p<6, true>(acc, r0, r1, py, pbase, 14 * f + ((f & 1) ? 0 : 8), tag);
      if (lane == 0) red_relaxed(&scr->cnt[(C_PY + rb) * 32 + (f >> 1)]);
    }
    PROF(10);
    {
      float acc[64];
      {
        const float m0 = wgi ? __uint_as_float(lds2(sstat + 1024 + (16 * wq + g) * 8).x) : 0.f;
        const float m1 = wgi ? __uint_as_float(lds2(sstat + 1024 + (16 * wq + g + 8) * 8).x) : 0.f;
#pragma unroll
        for (int i = 0; i < 64; i++) acc[i] = (i & 2) ? m1 : m0;
      }
      const uint32_t b2_lo0 = desc_lo(sbase, 8192);
      const uint32_t pa0 = sbase + 8 * SLOT + (4 * rh + wq) * 2048 + lane * 16;
      uint32_t slot = 0;
      auto fetch2 = [&](int s, uint4 (&a)[4]) {
        mbar_wait(BAR(full2, s), 0);
        if (tid == 0) PROFP(16 + s);
#pragma unroll
        for (int kk = 0; kk < 4; kk++) a[kk] = lds4(pa0 + slot * SLOT + kk * 512);
        if (++slot == 6) slot = 0;
      };
      auto check2 = [&](int s, uint4 (&a)[4]) {
        if (__any_sync(0xffffffffu, ((a[0].x ^ tag) | (a[1].x ^ tag) | (a[2].x ^ tag) | (a[3].x ^ tag)) & 1u)) {
          const uint4* p = psrc + (int)((KORDER >> (4 * s)) & 15) * 1024;
          ld_tag4_issue<32>(a, p);
          ld_tag4_finish<32>(a, p, tag);
        }
#pragma unroll
        for (int i = 0; i < 4; i++) asm volatile("and.b32 %0, %0, 0xfffffffe;" : "+r"(a[i].x));
        if (s < 8 && lane == 0) mbar_arrive(BAR(emptyP, s));
      };
      auto stage2 = [&](int s, uint4 (&a)[4], uint4 (&nx)[4]) {
        if (s < 13) fetch2(s + 1, nx);
        const uint32_t bl = b2_lo0 + (s & 7) * 1024;
        if (LAG2 && s == 14 - LAG2 && wgi == 1) bar_sync(NB_LAG, 256);
        wg_fence();
#pragma unroll
        for (int kk = 0; kk < 4; kk++) wgmma_rs_n128(acc, a[kk].x, a[kk].y, a[kk].z, a[kk].w, desc64(bl + kk * 128, HI128));
        wg_commit();
        if (s < 13) check2(s + 1, nx);
        wg_wait<1>();
        if (s >= 1 && s <= 8 && lane == 0) {
          mbar_arrive(BAR(empty2, s - 1));
          if (s == 8) mbar_arrive_remote(RBAR(xfree, 0));
        }
      };
      uint4 fa0[4], fa1[4], fa2[4];
      fetch2(0, fa0);
      check2(0, fa0);
#pragma unroll 1
      for (int s = 0; s < 12; s += 3) {
        stage2(s, fa0, fa1);
        stage2(s + 1, fa1, fa2);
        stage2(s + 2, fa2, fa0);
      }
      stage2(12, fa0, fa1);
      stage2(13, fa1, fa2);
      if (LAG2 && wgi == 0) bar_arrive(NB_LAG, 256);
      uint4 hres[2][4];
      mbar_wait(BAR(hbar, 0), 0);
#pragma unroll
      for (int h = 0; h < 2; h++)
#pragma unroll
        for (int q = 0; q < 4; q++) {
          hres[h][q] = lds4(sbase + 7 * SLOT + (q >> 1) * 8192 + (16 * wq + g + 8 * h) * 128 + (((4 * (q & 1) + t) ^ g) * 16));
          if (2 * nq + (q >> 1) < NLL) hres[h][q].x &= ~1u;
        }
      wg_wait<0>();
      PROF(11);
      const uint32_t xbuf = sbase + 6 * SLOT + (tid & 127) * 16;
      if (wgi == 0) {
        uint32_t rbuf;
        mbar_wait(BAR(xfree, 0), 0);
        asm volatile("mapa.shared::cluster.u32 %0, %1, %2;" : "=r"(rbuf) : "r"(xbuf), "r"(kh ^ 1));
#pragma unroll
        for (int i = 0; i < 8; i++)
          asm volatile("st.async.weak.shared::cluster.mbarrier::complete_tx::bytes.v4.b32 [%0], {%1,%2,%3,%4}, [%5];"
                       ::"r"(rbuf + i * 2048), "r"(pack2(acc[8 * i], acc[8 * i + 1])), "r"(pack2(acc[8 * i + 2], acc[8 * i + 3])),
                         "r"(pack2(acc[8 * i + 4], acc[8 * i + 5])), "r"(pack2(acc[8 * i + 6], acc[8 * i + 7])), "r"(RBAR(xbar, 0))
                       : "memory");
      } else {
        mbar_wait_cluster(BAR(xbar, 0), 0);
      }
      uint32_t w[2][16];
#pragma unroll
      for (int i = 0; i < 8; i++) {
        const uint4 pv = lds4(xbuf + i * 2048);
        w[0][2 * i] = pack2(acc[8 * i] + bf_lo(pv.x), acc[8 * i + 1] + bf_hi(pv.x));
        w[1][2 * i] = pack2(acc[8 * i + 2] + bf_lo(pv.y), acc[8 * i + 3] + bf_hi(pv.y));
        w[0][2 * i + 1] = pack2(acc[8 * i + 4] + bf_lo(pv.z), acc[8 * i + 5] + bf_hi(pv.z));
        w[1][2 * i + 1] = pack2(acc[8 * i + 6] + bf_lo(pv.w), acc[8 * i + 7] + bf_hi(pv.w));
      }
      uint4* const o4 = reinterpret_cast<uint4*>(out) + (16 * (c >> 4) + 2 * (4 * rh + wq) + (rb2 & 1) + 128 * g) * 64 + nq * 16 + t;
#pragma unroll
      for (int h = 0; h < 2; h++)
#pragma unroll
        for (int q = 0; q < 4; q++) {
          uint32_t a0 = w[h][4 * q], a1 = w[h][4 * q + 1], a2 = w[h][4 * q + 2], a3 = w[h][4 * q + 3];
          {
            const bool od = t & 1;
            uint32_t s0 = od ? a0 : a1, s1 = od ? a2 : a3;
            s0 = __shfl_xor_sync(0xffffffffu, s0, 1); s1 = __shfl_xor_sync(0xffffffffu, s1, 1);
            if (od) { a0 = s0; a2 = s1; } else { a1 = s0; a3 = s1; }
          }
          {
            const bool up = t & 2;
            uint32_t s0 = up ? a0 : a2, s1 = up ? a1 : a3;
            s0 = __shfl_xor_sync(0xffffffffu, s0, 2); s1 = __shfl_xor_sync(0xffffffffu, s1, 2);
            if (up) { a0 = s0; a1 = s1; } else { a2 = s0; a3 = s1; }
          }
          if (wgi == 1)
            o4[h * 1024 * 64 + 4 * q] =
                make_uint4(hadd2_bf16(hres[h][q].x, a0), hadd2_bf16(hres[h][q].y, a1), hadd2_bf16(hres[h][q].z, a2), hadd2_bf16(hres[h][q].w, a3));
        }
      PROF(12);
      PROFG(15);
    }
  }
#undef BAR
#undef TOFF
#undef RBAR
}

typedef CUresult (*EncodeFn)(CUtensorMap*, CUtensorMapDataType, cuuint32_t, void*, const cuuint64_t*, const cuuint64_t*,
                             const cuuint32_t*, const cuuint32_t*, CUtensorMapInterleave, CUtensorMapSwizzle,
                             CUtensorMapL2promotion, CUtensorMapFloatOOBfill);

}

extern "C" void kernel_launch(void* const* d_in, const int* in_sizes, int n_in, void* d_out, int out_size) {
  (void)in_sizes; (void)n_in; (void)out_size;
  static EncodeFn encode = nullptr;
  static void *tab = nullptr, *scr = nullptr;
  if (!encode) {
    void* fn = nullptr;
    cudaDriverEntryPointQueryResult qr;
    cudaGetDriverEntryPoint("cuTensorMapEncodeTiled", &fn, cudaEnableDefault, &qr);
    encode = (EncodeFn)fn;
    cudaGetSymbolAddress(&tab, g_tab);
    cudaGetSymbolAddress(&scr, g_scr);
    cudaFuncSetAttribute(fused_kernel, cudaFuncAttributeMaxDynamicSharedMemorySize, SMEM_BYTES);
  }
  CUtensorMap tmGX, tmUX, tmGY, tmUY, tmD, tmWR, tmWI;
  const cuuint32_t es[5] = {1, 1, 1, 1, 1};
  auto enc = [&](CUtensorMap* m, void* p, int rank, const cuuint64_t* gd, const cuuint64_t* gs, const cuuint32_t* bd,
                 CUtensorMapSwizzle sw, CUtensorMapL2promotion pr) {
    encode(m, CU_TENSOR_MAP_DATA_TYPE_BFLOAT16, rank, p, gd, gs, bd, es, CU_TENSOR_MAP_INTERLEAVE_NONE, sw, pr,
           CU_TENSOR_MAP_FLOAT_OOB_FILL_NONE);
  };
  {
    const cuuint64_t gd[3] = {64, 512, 28}, gs[2] = {3584, 128};
    const cuuint32_t bd[3] = {64, 32, 2};
    enc(&tmGX, d_in[4], 3, gd, gs, bd, CU_TENSOR_MAP_SWIZZLE_128B, CU_TENSOR_MAP_L2_PROMOTION_L2_256B);
    enc(&tmUX, d_in[5], 3, gd, gs, bd, CU_TENSOR_MAP_SWIZZLE_128B, CU_TENSOR_MAP_L2_PROMOTION_L2_256B);
  }
  {
    const cuuint64_t gd[3] = {32, 512, 56}, gs[2] = {3584, 64};
    const cuuint32_t bd[3] = {32, 32, 3};
    enc(&tmGY, d_in[4], 3, gd, gs, bd, CU_TENSOR_MAP_SWIZZLE_64B, CU_TENSOR_MAP_L2_PROMOTION_L2_128B);
    enc(&tmUY, d_in[5], 3, gd, gs, bd, CU_TENSOR_MAP_SWIZZLE_64B, CU_TENSOR_MAP_L2_PROMOTION_L2_128B);
  }
  {
    const cuuint64_t gd[3] = {64, 1792, 8}, gs[2] = {1024, 128};
    const cuuint32_t bd[3] = {64, 64, 2};
    enc(&tmD, d_in[6], 3, gd, gs, bd, CU_TENSOR_MAP_SWIZZLE_128B, CU_TENSOR_MAP_L2_PROMOTION_L2_256B);
  }
  {
    const cuuint64_t gd[3] = {4112, 8, 16}, gs[2] = {16 * 8224, 8224};
    const cuuint32_t bd[3] = {40, 8, 16};
    enc(&tmWR, d_in[1], 3, gd, gs, bd, CU_TENSOR_MAP_SWIZZLE_NONE, CU_TENSOR_MAP_L2_PROMOTION_NONE);
    enc(&tmWI, d_in[2], 3, gd, gs, bd, CU_TENSOR_MAP_SWIZZLE_NONE, CU_TENSOR_MAP_L2_PROMOTION_NONE);
  }
  fused_kernel<<<NCTA, NTHREADS, SMEM_BYTES>>>((const __nv_bfloat16*)d_in[0], (const Tables*)tab, (Scratch*)scr,
                                               (__nv_bfloat16*)d_out, (const char*)d_in[4], (const char*)d_in[5],
                                               (const char*)d_in[6], tmWR, tmWI, tmGX, tmUX, tmGY, tmUY, tmD);
}
```

```cpp
#include <cuda_runtime.h>
#include <cuda_bf16.h>
#include <cuda.h>
#include <stdint.h>

namespace {

constexpr int NCTA = 128;
constexpr int NTHREADS = 384;
constexpr int SLOT = 16384;
constexpr int SMEM_BYTES = 14 * SLOT + 3072;
constexpr int SPIN_LIMIT = 1 << 22;

struct Scratch {
  uint4 Z1[128 * 1024];
  uint4 Z2[128 * 1024];
  uint4 LN[16 * 8 * 1024];
  uint4 P[16 * 28 * 1024];
  uint4 ST[1024];
  unsigned cnt[64 * 32];
};
__device__ __align__(1024) Scratch g_scr;
#define PROF(i)
#define PROFP(i)
#define PROFG(i)

constexpr double ccos(int i, int n) {
  i &= n - 1;
  if (i > n / 2) i = n - i;
  if (4 * i == n) return 0.0;
  const bool neg = 4 * i > n;
  if (neg) i = n / 2 - i;
  const double a = 6.283185307179586476925 * i / n, a2 = a * a;
  double term = 1.0, sum = 1.0;
  for (int k = 1; k < 14; k++) { term *= -a2 / ((2 * k - 1) * (2 * k)); sum += term; }
  return neg ? -sum : sum;
}
constexpr double csin(int i, int n) { return ccos(i - n / 4, n); }
constexpr unsigned fbits(double v, int mant) {
  if (v == 0.0) return 0;
  const unsigned sg = v < 0 ? 1u : 0u;
  if (v < 0) v = -v;
  int e = 127;
  while (v < 1.0) { v *= 2.0; e--; }
  const unsigned m = (unsigned)((v - 1.0) * (double)(1u << mant) + 0.5);
  return (sg << (8 + mant)) + ((unsigned)e << mant) + m;
}
constexpr unsigned pkb(double lo, double hi) { return fbits(lo, 7) | (fbits(hi, 7) << 16); }
constexpr double fa_elem(int kp, int n1) {
  return kp <= 8 ? ccos(kp * n1, 16) : -csin((kp - 8) * n1, 16);
}
constexpr unsigned cfrag_c(int idx, int n, int ri) {
  return ri ? pkb(-csin(idx, n), ccos(idx, n)) : pkb(ccos(idx, n), csin(idx, n));
}
struct Tables {
  unsigned fb[16][32][4];
  unsigned tw1[8][32][4];
  unsigned fa[32][4];
  unsigned f2[8][4][32][4];
  unsigned g2[8][4][32][4];
  unsigned gb[16][32][4];
  unsigned tw3[4][32][4];
  unsigned ga[32][4];
  unsigned f8[32][4], g8[32][4];
};
constexpr int T1_BYTES = 12800, T2_BYTES = 44544;
static_assert(sizeof(Tables) == T1_BYTES + T2_BYTES, "table size");
constexpr Tables make_tables() {
  Tables T = {};
  for (int l = 0; l < 32; l++) {
    const int g = l >> 2, t = l & 3;
    for (int i = 0; i < 4; i++)
      for (int u = 0; u < 8; u++) {
        const int ri = g & 1, m = 2 * (g >> 1) + ((u & 3) >> 1);
        const double sg = u >= 4 ? -1.0 : 1.0;
        const int k2 = u >= 4 ? 31 - 2 * m - (u & 1) : 2 * m + (u & 1);
        const int pa = (8 * t + i) * k2, pb = (8 * t + 4 + i) * k2;
        T.fb[i * 4 + (u >> 1)][l][(u & 1) * 2 + 0] = ri == 0 ? pkb(ccos(pa, 32), ccos(pb, 32)) : pkb(-sg * csin(pa, 32), -sg * csin(pb, 32));
        T.fb[i * 4 + (u >> 1)][l][(u & 1) * 2 + 1] = ri == 0 ? pkb(csin(pa, 32), csin(pb, 32)) : pkb(sg * ccos(pa, 32), sg * ccos(pb, 32));
      }
    for (int i = 0; i < 4; i++)
      for (int ks = 0; ks < 4; ks++) {
        const int n2 = 4 * g + i, m = 2 * t + (ks & 1);
        const double sg = ks >= 2 ? -1.0 : 1.0;
        const int pa = n2 * (ks >= 2 ? 31 - 2 * m : 2 * m), pb = n2 * (ks >= 2 ? 30 - 2 * m : 2 * m + 1);
        T.gb[i * 4 + ks][l][0] = pkb(ccos(pa, 32), -sg * csin(pa, 32));
        T.gb[i * 4 + ks][l][1] = pkb(csin(pa, 32), sg * ccos(pa, 32));
        T.gb[i * 4 + ks][l][2] = pkb(ccos(pb, 32), -sg * csin(pb, 32));
        T.gb[i * 4 + ks][l][3] = pkb(csin(pb, 32), sg * ccos(pb, 32));
      }
    for (int i = 0; i < 4; i++) {
      for (int e = 0; e < 2; e++) {
        const int p = (8 * t + 4 * e + i) * (g == 0 ? 8 : g);
        T.tw1[2 * i + e][l][0] = fbits(g == 0 ? 0.0 : ccos(p, 512), 23);
        T.tw1[2 * i + e][l][1] = fbits(g == 0 ? ccos(p, 512) : csin(p, 512), 23);
        T.tw1[2 * i + e][l][2] = fbits(g == 0 ? 0.0 : -csin(p, 512), 23);
        T.tw1[2 * i + e][l][3] = fbits(g == 0 ? -csin(p, 512) : ccos(p, 512), 23);
      }
      const int ka = t == 0 ? 8 : 2 * t, kb = 2 * t + 1;
      T.tw3[i][l][0] = fbits(ccos((4 * g + i) * ka, 512), 23);
      T.tw3[i][l][1] = fbits(csin((4 * g + i) * ka, 512), 23);
      T.tw3[i][l][2] = fbits(ccos((4 * g + i) * kb, 512), 23);
      T.tw3[i][l][3] = fbits(csin((4 * g + i) * kb, 512), 23);
      const int p8 = (t + 4 * (i & 1)) * (4 * (i >> 1) + (g >> 1));
      T.f8[l][i] = cfrag_c(p8, 8, g & 1);
      T.g8[l][i] = cfrag_c(-p8, 8, g & 1);
    }
    for (int w = 0; w < 8; w++)
      for (int i = 0; i < 16; i++) {
        const int kidx = t + 4 * (i & 1) + 8 * (i >> 3), nidx = 4 * ((i >> 1) & 3) + (g >> 1);
        T.f2[w][i >> 2][l][i & 3] = cfrag_c((8 * kidx + w) * nidx, 128, g & 1);
        T.g2[w][i >> 2][l][i & 3] = cfrag_c(-(8 * nidx + w) * kidx, 128, g & 1);
      }
    T.fa[l][0] = pkb(fa_elem(g, 2 * t), fa_elem(g, 2 * t + 1));
    T.fa[l][1] = pkb(fa_elem(g + 8, 2 * t), fa_elem(g + 8, 2 * t + 1));
    T.fa[l][2] = pkb(fa_elem(g, 2 * t + 8), fa_elem(g, 2 * t + 9));
    T.fa[l][3] = pkb(fa_elem(g + 8, 2 * t + 8), fa_elem(g + 8, 2 * t + 9));
    T.ga[l][0] = pkb(fa_elem(2 * t, g), fa_elem(2 * t + 1, g));
    T.ga[l][1] = pkb(fa_elem(2 * t, g + 8), fa_elem(2 * t + 1, g + 8));
    T.ga[l][2] = pkb(fa_elem(2 * t + 8, g), fa_elem(2 * t + 9, g));
    T.ga[l][3] = pkb(fa_elem(2 * t + 8, g + 8), fa_elem(2 * t + 9, g + 8));
  }
  return T;
}
__device__ const __align__(128) Tables g_tab = make_tables();

__device__ __forceinline__ void die() { asm volatile("st.global.u32 [%0], %1;" ::"l"(0ull), "r"(0) : "memory"); }
__device__ __forceinline__ uint32_t s2u(const void* p) { return (uint32_t)__cvta_generic_to_shared(p); }
__device__ __forceinline__ void mbar_init(uint32_t b, int c) { asm volatile("mbarrier.init.shared::cta.b64 [%0], %1;" ::"r"(b), "r"(c)); }
__device__ __forceinline__ void mbar_expect(uint32_t b, int bytes) {
  asm volatile("mbarrier.arrive.expect_tx.shared::cta.b64 _, [%0], %1;" ::"r"(b), "r"(bytes) : "memory");
}
__device__ __forceinline__ void mbar_arrive(uint32_t b) { asm volatile("mbarrier.arrive.shared::cta.b64 _, [%0];" ::"r"(b) : "memory"); }
__device__ __forceinline__ uint32_t mbar_try(uint32_t b, uint32_t parity) {
  uint32_t ok;
  asm volatile("{.reg .pred p; mbarrier.try_wait.parity.shared::cta.b64 p, [%1], %2; selp.u32 %0,1,0,p;}"
               : "=r"(ok) : "r"(b), "r"(parity) : "memory");
  return ok;
}
__device__ __forceinline__ void mbar_wait(uint32_t b, uint32_t parity = 0) {
  int it = 0;
#pragma unroll 1
  while (!mbar_try(b, parity))
    if (++it > SPIN_LIMIT) { die(); break; }
}
__device__ __forceinline__ void mbar_wait_cluster(uint32_t b, int parity) {
  uint32_t ok;
  int it = 0;
  do {
    asm volatile("{.reg .pred p; mbarrier.try_wait.parity.acquire.cluster.shared::cta.b64 p, [%1], %2; selp.u32 %0,1,0,p;}"
                 : "=r"(ok) : "r"(b), "r"(parity) : "memory");
    if (++it > SPIN_LIMIT) { die(); break; }
  } while (!ok);
}
__device__ __forceinline__ void bar_sync(int id, int n) { asm volatile("bar.sync %0, %1;" ::"r"(id), "r"(n) : "memory"); }
__device__ __forceinline__ void bar_arrive(int id, int n) { asm volatile("bar.arrive %0, %1;" ::"r"(id), "r"(n) : "memory"); }
__device__ __forceinline__ void red_release(unsigned* p) { asm volatile("red.release.gpu.global.add.u32 [%0], 1;" ::"l"(p) : "memory"); }
__device__ __forceinline__ void red_relaxed(unsigned* p) { asm volatile("red.relaxed.gpu.global.add.u32 [%0], 1;" ::"l"(p) : "memory"); }
__device__ __forceinline__ unsigned ld_acquire(const unsigned* p) {
  unsigned v;
  asm volatile("ld.acquire.gpu.global.u32 %0, [%1];" : "=r"(v) : "l"(p) : "memory");
  return v;
}
__device__ __forceinline__ unsigned ld_relaxed(const unsigned* p) {
  unsigned v;
  asm volatile("ld.relaxed.gpu.global.u32 %0, [%1];" : "=r"(v) : "l"(p) : "memory");
  return v;
}
__device__ __forceinline__ void wait_counter(const unsigned* p, unsigned target) {
  int it = 0;
  while ((int)(ld_acquire(p) - target) < 0)
    if (++it > SPIN_LIMIT) { die(); break; }
}
__device__ __forceinline__ void sts4(uint32_t a, uint32_t x, uint32_t y, uint32_t z, uint32_t w) {
  asm volatile("st.shared.v4.u32 [%0], {%1,%2,%3,%4};" ::"r"(a), "r"(x), "r"(y), "r"(z), "r"(w) : "memory");
}
__device__ __forceinline__ uint4 lds4(uint32_t a) {
  uint4 v;
  asm volatile("ld.shared.v4.u32 {%0,%1,%2,%3}, [%4];" : "=r"(v.x), "=r"(v.y), "=r"(v.z), "=r"(v.w) : "r"(a) : "memory");
  return v;
}
__device__ __forceinline__ uint32_t pack2(float lo, float hi) {
  uint32_t r;
  asm("cvt.rn.bf16x2.f32 %0, %1, %2;" : "=r"(r) : "f"(hi), "f"(lo));
  return r;
}
__device__ __forceinline__ float bf_lo(uint32_t v) { return __uint_as_float(v << 16); }
__device__ __forceinline__ float bf_hi(uint32_t v) { return __uint_as_float(v & 0xffff0000u); }
__device__ __forceinline__ uint32_t hadd2_bf16(uint32_t a, uint32_t b) {
  uint32_t r;
  asm("add.rn.bf16x2 %0, %1, %2;" : "=r"(r) : "r"(a), "r"(b));
  return r;
}
__device__ __forceinline__ void mma16816(float (&d)[4], uint32_t a0, uint32_t a1, uint32_t a2, uint32_t a3, uint32_t b0, uint32_t b1) {
  asm("mma.sync.aligned.m16n8k16.row.col.f32.bf16.bf16.f32 {%0,%1,%2,%3}, {%4,%5,%6,%7}, {%8,%9}, {%0,%1,%2,%3};"
      : "+f"(d[0]), "+f"(d[1]), "+f"(d[2]), "+f"(d[3])
      : "r"(a0), "r"(a1), "r"(a2), "r"(a3), "r"(b0), "r"(b1));
}
template <int N>
__device__ __forceinline__ void cs_frac(int idx, float& c, float& s) {
  int i = ((idx + N / 2) & (N - 1)) - N / 2;
  float a = (float)i * (6.283185307179586f / N);
  c = __cosf(a);
  s = __sinf(a);
}
template <int N>
__device__ __forceinline__ uint32_t cfrag(int idx, int ri) {
  float c, s;
  cs_frac<N>(idx, c, s);
  return ri ? pack2(-s, c) : pack2(c, s);
}
__device__ __forceinline__ uint32_t word(const uint4& v, int e) { return e == 0 ? v.x : e == 1 ? v.y : e == 2 ? v.z : v.w; }
__device__ __forceinline__ void cdft16(const uint4 (&q)[4], const uint4 (&F)[4], uint4 (&o)[4]) {
  float acc[2][4][4];
#pragma unroll
  for (int p = 0; p < 2; p++)
#pragma unroll
    for (int v = 0; v < 4; v++) {
      acc[p][v][0] = acc[p][v][1] = acc[p][v][2] = acc[p][v][3] = 0.f;
#pragma unroll
      for (int ks = 0; ks < 2; ks++)
        mma16816(acc[p][v], word(q[2 * ks], 2 * p), word(q[2 * ks], 2 * p + 1), word(q[2 * ks + 1], 2 * p),
                 word(q[2 * ks + 1], 2 * p + 1), word(F[ks * 2 + (v >> 1)], (v & 1) * 2), word(F[ks * 2 + (v >> 1)], (v & 1) * 2 + 1));
    }
#pragma unroll
  for (int v = 0; v < 4; v++)
    o[v] = make_uint4(pack2(acc[0][v][0], acc[0][v][1]), pack2(acc[0][v][2], acc[0][v][3]),
                      pack2(acc[1][v][0], acc[1][v][1]), pack2(acc[1][v][2], acc[1][v][3]));
}
__device__ __forceinline__ void st_tag(uint4* p, const uint4& v, uint32_t tag) {
  asm volatile("{.reg .b128 r; .reg .b64 a, b; mov.b64 a, {%1,%2}; mov.b64 b, {%3,%4}; mov.b128 r, {a,b}; st.relaxed.gpu.global.b128 [%0], r;}"
               ::"l"(p), "r"((v.x & ~1u) | tag), "r"(v.y), "r"(v.z), "r"(v.w) : "memory");
}
__device__ __forceinline__ uint4 ld_b128(const uint4* p) {
  uint4 v;
  asm volatile("{.reg .b128 r; .reg .b64 a, b; ld.relaxed.gpu.global.b128 r, [%4]; mov.b128 {a,b}, r; mov.b64 {%0,%1}, a; mov.b64 {%2,%3}, b;}"
               : "=r"(v.x), "=r"(v.y), "=r"(v.z), "=r"(v.w) : "l"(p) : "memory");
  return v;
}
template <int STRIDE>
__device__ __forceinline__ void ld_tag4_issue(uint4 (&q)[4], const uint4* p) {
#pragma unroll
  for (int i = 0; i < 4; i++) q[i] = ld_b128(p + i * STRIDE);
}
template <int STRIDE>
__device__ __forceinline__ void ld_tag4_finish(uint4 (&q)[4], const uint4* p, uint32_t tag) {
  int it = 0;
#pragma unroll 1
  while (__any_sync(0xffffffffu, ((q[0].x ^ tag) | (q[1].x ^ tag) | (q[2].x ^ tag) | (q[3].x ^ tag)) & 1u)) {
    ld_tag4_issue<STRIDE>(q, p);
    if (++it > SPIN_LIMIT) { die(); break; }
  }
#pragma unroll
  for (int i = 0; i < 4; i++) asm volatile("and.b32 %0, %0, 0xfffffffe;" : "+r"(q[i].x));
}
__device__ __forceinline__ void row_stats(const uint32_t (&a)[8], const uint32_t (&b)[8], int lane, float (&sum)[2], float (&sq)[2]) {
  float da[4] = {0.f, 0.f, 0.f, 0.f}, db[4] = {0.f, 0.f, 0.f, 0.f}, ds[4] = {0.f, 0.f, 0.f, 0.f};
#pragma unroll
  for (int q = 0; q < 4; q++) {
    mma16816(ds, a[2 * q], b[2 * q], a[2 * q + 1], b[2 * q + 1], 0x3f803f80u, 0x3f803f80u);
    mma16816(da, a[2 * q], b[2 * q], a[2 * q + 1], b[2 * q + 1], a[2 * q], a[2 * q + 1]);
    mma16816(db, a[2 * q], b[2 * q], a[2 * q + 1], b[2 * q + 1], b[2 * q], b[2 * q + 1]);
  }
  const int src = (lane & 28) | (lane >> 3);
  const float qa = __shfl_sync(0xffffffffu, (lane & 4) ? da[1] : da[0], src);
  const float qb = __shfl_sync(0xffffffffu, (lane & 4) ? db[3] : db[2], src);
  float v = (lane & 2) ? ((lane & 1) ? ds[2] : ds[0]) : ((lane & 1) ? qb : qa);
  v += __shfl_xor_sync(0xffffffffu, v, 4);
  v += __shfl_xor_sync(0xffffffffu, v, 8);
  v += __shfl_xor_sync(0xffffffffu, v, 16);
  sq[0] = __shfl_sync(0xffffffffu, v, 0);
  sq[1] = __shfl_sync(0xffffffffu, v, 1);
  sum[0] = __shfl_sync(0xffffffffu, v, 2);
  sum[1] = __shfl_sync(0xffffffffu, v, 3);
}
__device__ __forceinline__ uint64_t desc64(uint32_t lo, uint32_t hi) {
  uint64_t d;
  asm("mov.b64 %0, {%1, %2};" : "=l"(d) : "r"(lo), "r"(hi));
  return d;
}
constexpr uint32_t desc_hi(uint32_t sbo, uint32_t swz) { return (sbo >> 4) | (swz << 30); }
__device__ __forceinline__ uint32_t desc_lo(uint32_t addr, uint32_t lbo) { return ((addr & 0x3FFFF) >> 4) | ((lbo >> 4) << 16); }
__device__ __forceinline__ void cp_async16(uint32_t dst, const void* src) {
  asm volatile("cp.async.cg.shared.global [%0], [%1], 16;" ::"r"(dst), "l"(src) : "memory");
}
__device__ __forceinline__ uint2 lds2(uint32_t a) {
  uint2 v;
  asm volatile("ld.shared.v2.u32 {%0,%1}, [%2];" : "=r"(v.x), "=r"(v.y) : "r"(a) : "memory");
  return v;
}
__device__ __forceinline__ uint32_t lds_u16(uint32_t a) {
  uint16_t v;
  asm volatile("ld.shared.u16 %0, [%1];" : "=h"(v) : "r"(a) : "memory");
  return v;
}
__device__ __forceinline__ void wg_fence() { asm volatile("wgmma.fence.sync.aligned;" ::: "memory"); }
__device__ __forceinline__ void wg_commit() { asm volatile("wgmma.commit_group.sync.aligned;" ::: "memory"); }
template <int N>
__device__ __forceinline__ void wg_wait() { asm volatile("wgmma.wait_group.sync.aligned %0;" ::"n"(N) : "memory"); }
__device__ __forceinline__ void bulk_load(uint32_t dst, const void* src, int bytes, uint32_t bar) {
  asm volatile("cp.async.bulk.shared::cluster.global.mbarrier::complete_tx::bytes [%0], [%1], %2, [%3];"
               ::"r"(dst), "l"(src), "r"(bytes), "r"(bar) : "memory");
}
__device__ __forceinline__ void tma3(uint32_t dst, const CUtensorMap* tm, uint32_t bar, int c0, int c1, int c2) {
  asm volatile("cp.async.bulk.tensor.3d.shared::cluster.global.mbarrier::complete_tx::bytes [%0], [%1, {%3,%4,%5}], [%2];"
               ::"r"(dst), "l"(tm), "r"(bar), "r"(c0), "r"(c1), "r"(c2) : "memory");
}
__device__ __forceinline__ void tma3_mc(uint32_t dst, const CUtensorMap* tm, uint32_t bar, int c1, int c2) {
  asm volatile("cp.async.bulk.tensor.3d.shared::cluster.global.mbarrier::complete_tx::bytes.multicast::cluster [%0], [%1, {%3,%4,%5}], [%2], %6;"
               ::"r"(dst), "l"(tm), "r"(bar), "r"(0), "r"(c1), "r"(c2), "h"((uint16_t)3) : "memory");
}
__device__ __forceinline__ void mbar_arrive_remote(uint32_t rb) {
  asm volatile("mbarrier.arrive.shared::cluster.b64 _, [%0];" ::"r"(rb) : "memory");
}
__device__ __forceinline__ uint4 ldg_ca4(const void* p) {
  uint4 v;
  asm volatile("ld.global.ca.v4.u32 {%0,%1,%2,%3}, [%4];" : "=r"(v.x), "=r"(v.y), "=r"(v.z), "=r"(v.w) : "l"(p) : "memory");
  return v;
}
__device__ __forceinline__ uint32_t clock32() {
  uint32_t v;
  asm volatile("mov.u32 %0, %%clock;" : "=r"(v) :: "memory");
  return v;
}
__device__ __forceinline__ float swiglu(float g, float u, float r) {
  float hg = (0.5f * r) * g, th;
  asm("tanh.approx.f32 %0, %1;" : "=f"(th) : "f"(hg));
  return fmaf(hg, th, hg) * (r * u);
}
__device__ __forceinline__ uint32_t hsub2_bf16(uint32_t a, uint32_t b) {
  uint32_t r;
  asm("sub.rn.bf16x2 %0, %1, %2;" : "=r"(r) : "r"(a), "r"(b));
  return r;
}
__device__ __forceinline__ void l2_prefetch(const void* p, int bytes) {
  asm volatile("cp.async.bulk.prefetch.L2.global [%0], %1;" ::"l"(p), "r"(bytes) : "memory");
}

__device__ __forceinline__ void wgmma_n256(float (&d)[128], uint64_t da, uint64_t db) {
  asm volatile("wgmma.mma_async.sync.aligned.m64n256k16.f32.bf16.bf16 {"
      "%0,%1,%2,%3,%4,%5,%6,%7,%8,%9,%10,%11,%12,%13,%14,%15,"
      "%16,%17,%18,%19,%20,%21,%22,%23,%24,%25,%26,%27,%28,%29,%30,%31,"
      "%32,%33,%34,%35,%36,%37,%38,%39,%40,%41,%42,%43,%44,%45,%46,%47,"
      "%48,%49,%50,%51,%52,%53,%54,%55,%56,%57,%58,%59,%60,%61,%62,%63,"
      "%64,%65,%66,%67,%68,%69,%70,%71,%72,%73,%74,%75,%76,%77,%78,%79,"
      "%80,%81,%82,%83,%84,%85,%86,%87,%88,%89,%90,%91,%92,%93,%94,%95,"
      "%96,%97,%98,%99,%100,%101,%102,%103,%104,%105,%106,%107,%108,%109,%110,%111,"
      "%112,%113,%114,%115,%116,%117,%118,%119,%120,%121,%122,%123,%124,%125,%126,%127"
      "}, %128, %129, 1, 1, 1, 0, 1;\n"
      : "+f"(d[0]),"+f"(d[1]),"+f"(d[2]),"+f"(d[3]),"+f"(d[4]),"+f"(d[5]),"+f"(d[6]),"+f"(d[7]),
        "+f"(d[8]),"+f"(d[9]),"+f"(d[10]),"+f"(d[11]),"+f"(d[12]),"+f"(d[13]),"+f"(d[14]),"+f"(d[15]),
        "+f"(d[16]),"+f"(d[17]),"+f"(d[18]),"+f"(d[19]),"+f"(d[20]),"+f"(d[21]),"+f"(d[22]),"+f"(d[23]),
        "+f"(d[24]),"+f"(d[25]),"+f"(d[26]),"+f"(d[27]),"+f"(d[28]),"+f"(d[29]),"+f"(d[30]),"+f"(d[31]),
        "+f"(d[32]),"+f"(d[33]),"+f"(d[34]),"+f"(d[35]),"+f"(d[36]),"+f"(d[37]),"+f"(d[38]),"+f"(d[39]),
        "+f"(d[40]),"+f"(d[41]),"+f"(d[42]),"+f"(d[43]),"+f"(d[44]),"+f"(d[45]),"+f"(d[46]),"+f"(d[47]),
        "+f"(d[48]),"+f"(d[49]),"+f"(d[50]),"+f"(d[51]),"+f"(d[52]),"+f"(d[53]),"+f"(d[54]),"+f"(d[55]),
        "+f"(d[56]),"+f"(d[57]),"+f"(d[58]),"+f"(d[59]),"+f"(d[60]),"+f"(d[61]),"+f"(d[62]),"+f"(d[63]),
        "+f"(d[64]),"+f"(d[65]),"+f"(d[66]),"+f"(d[67]),"+f"(d[68]),"+f"(d[69]),"+f"(d[70]),"+f"(d[71]),
        "+f"(d[72]),"+f"(d[73]),"+f"(d[74]),"+f"(d[75]),"+f"(d[76]),"+f"(d[77]),"+f"(d[78]),"+f"(d[79]),
        "+f"(d[80]),"+f"(d[81]),"+f"(d[82]),"+f"(d[83]),"+f"(d[84]),"+f"(d[85]),"+f"(d[86]),"+f"(d[87]),
        "+f"(d[88]),"+f"(d[89]),"+f"(d[90]),"+f"(d[91]),"+f"(d[92]),"+f"(d[93]),"+f"(d[94]),"+f"(d[95]),
        "+f"(d[96]),"+f"(d[97]),"+f"(d[98]),"+f"(d[99]),"+f"(d[100]),"+f"(d[101]),"+f"(d[102]),"+f"(d[103]),
        "+f"(d[104]),"+f"(d[105]),"+f"(d[106]),"+f"(d[107]),"+f"(d[108]),"+f"(d[109]),"+f"(d[110]),"+f"(d[111]),
        "+f"(d[112]),"+f"(d[113]),"+f"(d[114]),"+f"(d[115]),"+f"(d[116]),"+f"(d[117]),"+f"(d[118]),"+f"(d[119]),
        "+f"(d[120]),"+f"(d[121]),"+f"(d[122]),"+f"(d[123]),"+f"(d[124]),"+f"(d[125]),"+f"(d[126]),"+f"(d[127])
      : "l"(da), "l"(db));
}
__device__ __forceinline__ void wgmma_n192(float (&d)[96], uint64_t da, uint64_t db) {
  asm volatile("wgmma.mma_async.sync.aligned.m64n192k16.f32.bf16.bf16 {"
      "%0,%1,%2,%3,%4,%5,%6,%7,%8,%9,%10,%11,%12,%13,%14,%15,"
      "%16,%17,%18,%19,%20,%21,%22,%23,%24,%25,%26,%27,%28,%29,%30,%31,"
      "%32,%33,%34,%35,%36,%37,%38,%39,%40,%41,%42,%43,%44,%45,%46,%47,"
      "%48,%49,%50,%51,%52,%53,%54,%55,%56,%57,%58,%59,%60,%61,%62,%63,"
      "%64,%65,%66,%67,%68,%69,%70,%71,%72,%73,%74,%75,%76,%77,%78,%79,"
      "%80,%81,%82,%83,%84,%85,%86,%87,%88,%89,%90,%91,%92,%93,%94,%95"
      "}, %96, %97, 1, 1, 1, 0, 1;\n"
      : "+f"(d[0]),"+f"(d[1]),"+f"(d[2]),"+f"(d[3]),"+f"(d[4]),"+f"(d[5]),"+f"(d[6]),"+f"(d[7]),
        "+f"(d[8]),"+f"(d[9]),"+f"(d[10]),"+f"(d[11]),"+f"(d[12]),"+f"(d[13]),"+f"(d[14]),"+f"(d[15]),
        "+f"(d[16]),"+f"(d[17]),"+f"(d[18]),"+f"(d[19]),"+f"(d[20]),"+f"(d[21]),"+f"(d[22]),"+f"(d[23]),
        "+f"(d[24]),"+f"(d[25]),"+f"(d[26]),"+f"(d[27]),"+f"(d[28]),"+f"(d[29]),"+f"(d[30]),"+f"(d[31]),
        "+f"(d[32]),"+f"(d[33]),"+f"(d[34]),"+f"(d[35]),"+f"(d[36]),"+f"(d[37]),"+f"(d[38]),"+f"(d[39]),
        "+f"(d[40]),"+f"(d[41]),"+f"(d[42]),"+f"(d[43]),"+f"(d[44]),"+f"(d[45]),"+f"(d[46]),"+f"(d[47]),
        "+f"(d[48]),"+f"(d[49]),"+f"(d[50]),"+f"(d[51]),"+f"(d[52]),"+f"(d[53]),"+f"(d[54]),"+f"(d[55]),
        "+f"(d[56]),"+f"(d[57]),"+f"(d[58]),"+f"(d[59]),"+f"(d[60]),"+f"(d[61]),"+f"(d[62]),"+f"(d[63]),
        "+f"(d[64]),"+f"(d[65]),"+f"(d[66]),"+f"(d[67]),"+f"(d[68]),"+f"(d[69]),"+f"(d[70]),"+f"(d[71]),
        "+f"(d[72]),"+f"(d[73]),"+f"(d[74]),"+f"(d[75]),"+f"(d[76]),"+f"(d[77]),"+f"(d[78]),"+f"(d[79]),
        "+f"(d[80]),"+f"(d[81]),"+f"(d[82]),"+f"(d[83]),"+f"(d[84]),"+f"(d[85]),"+f"(d[86]),"+f"(d[87]),
        "+f"(d[88]),"+f"(d[89]),"+f"(d[90]),"+f"(d[91]),"+f"(d[92]),"+f"(d[93]),"+f"(d[94]),"+f"(d[95])
      : "l"(da), "l"(db));
}
__device__ __forceinline__ void wgmma_rs_n128(float (&d)[64], uint32_t a0, uint32_t a1, uint32_t a2, uint32_t a3, uint64_t db) {
  asm volatile("wgmma.mma_async.sync.aligned.m64n128k16.f32.bf16.bf16 {"
      "%0,%1,%2,%3,%4,%5,%6,%7,%8,%9,%10,%11,%12,%13,%14,%15,"
      "%16,%17,%18,%19,%20,%21,%22,%23,%24,%25,%26,%27,%28,%29,%30,%31,"
      "%32,%33,%34,%35,%36,%37,%38,%39,%40,%41,%42,%43,%44,%45,%46,%47,"
      "%48,%49,%50,%51,%52,%53,%54,%55,%56,%57,%58,%59,%60,%61,%62,%63"
      "}, {%64,%65,%66,%67}, %68, 1, 1, 1, 1;\n"
      : "+f"(d[0]),"+f"(d[1]),"+f"(d[2]),"+f"(d[3]),"+f"(d[4]),"+f"(d[5]),"+f"(d[6]),"+f"(d[7]),
        "+f"(d[8]),"+f"(d[9]),"+f"(d[10]),"+f"(d[11]),"+f"(d[12]),"+f"(d[13]),"+f"(d[14]),"+f"(d[15]),
        "+f"(d[16]),"+f"(d[17]),"+f"(d[18]),"+f"(d[19]),"+f"(d[20]),"+f"(d[21]),"+f"(d[22]),"+f"(d[23]),
        "+f"(d[24]),"+f"(d[25]),"+f"(d[26]),"+f"(d[27]),"+f"(d[28]),"+f"(d[29]),"+f"(d[30]),"+f"(d[31]),
        "+f"(d[32]),"+f"(d[33]),"+f"(d[34]),"+f"(d[35]),"+f"(d[36]),"+f"(d[37]),"+f"(d[38]),"+f"(d[39]),
        "+f"(d[40]),"+f"(d[41]),"+f"(d[42]),"+f"(d[43]),"+f"(d[44]),"+f"(d[45]),"+f"(d[46]),"+f"(d[47]),
        "+f"(d[48]),"+f"(d[49]),"+f"(d[50]),"+f"(d[51]),"+f"(d[52]),"+f"(d[53]),"+f"(d[54]),"+f"(d[55]),
        "+f"(d[56]),"+f"(d[57]),"+f"(d[58]),"+f"(d[59]),"+f"(d[60]),"+f"(d[61]),"+f"(d[62]),"+f"(d[63])
      : "r"(a0), "r"(a1), "r"(a2), "r"(a3), "l"(db));
}

constexpr int C_LN = 0, C_PX = 16, C_PY = 32;
constexpr int NB_CONS = 1, NB_LN = 2, NB_LAG = 4, NB_INIT = 6, NB_RDY = 7;
#define LAGX 3
#define LAGY 3
#define LAG2 3
#define NLL 2
#define POLL_DELAY3 900
#define POLL_DELAY 900
#define FILT_DELAY 1000
#define RING_SIG 0
#define PF2_SIG 1
constexpr int SM_E = 0, SM_X = 16384, SM_E2 = 32768, SM_W = 49152, SM_FC = 69632, SM_T = 73728 - T1_BYTES;
constexpr unsigned long long KORDER = 0xBA9432DC876510ull;
constexpr unsigned long long BSLOT = 0x76532107653210ull, PSLOT = 0xDCBA984DCBA984ull;
constexpr uint32_t HI128 = desc_hi(1024, 1), HI64 = desc_hi(512, 2);

struct Bars {
  uint64_t full1[32], empty1[32], full2[16], fullA[8], empty2[8], emptyP[8], xbar, hbar, tbar, hint[3], xfree, sig[2], sbar;
  uint32_t epoch;
};

template <int NK, bool STORE>
__device__ __forceinline__ void make_p(const float (&acc)[NK * 16], float r0, float r1, uint4 (&p)[NK], uint4* pbase, int ks0, uint32_t tag) {
#pragma unroll
  for (int j = 0; j < NK; j++) {
    uint32_t w[4];
#pragma unroll
    for (int i = 0; i < 4; i++) {
      const int a = 8 * j + 2 * i, b = a + NK * 8;
      w[i] = pack2(swiglu(acc[a], acc[b], (i & 1) ? r1 : r0), swiglu(acc[a + 1], acc[b + 1], (i & 1) ? r1 : r0));
    }
    asm volatile("" : "+r"(w[0]), "+r"(w[1]), "+r"(w[2]), "+r"(w[3]));
    p[j] = make_uint4(w[0], w[1], w[2], w[3]);
    if (STORE) st_tag(pbase + ((ks0 + j) >> 2) * 1024 + ((ks0 + j) & 3) * 32, p[j], tag);
  }
}
__device__ __forceinline__ void spin_cycles(uint32_t n) {
  const uint32_t t0 = clock32();
  while (clock32() - t0 < n) {}
}

__global__ void __cluster_dims__(2, 1, 1) __launch_bounds__(NTHREADS, 1)
fused_kernel(const __nv_bfloat16* __restrict__ x, const Tables* __restrict__ tab, Scratch* __restrict__ scr,
             __nv_bfloat16* __restrict__ out, const char* __restrict__ wg_raw, const char* __restrict__ wu_raw,
             const char* __restrict__ wd_raw,
             const __grid_constant__ CUtensorMap tmWR, const __grid_constant__ CUtensorMap tmWI,
             const __grid_constant__ CUtensorMap tmGX, const __grid_constant__ CUtensorMap tmUX,
             const __grid_constant__ CUtensorMap tmGY, const __grid_constant__ CUtensorMap tmUY,
             const __grid_constant__ CUtensorMap tmD) {
  extern __shared__ __align__(1024) char smem_raw[];
  const uint32_t sbase = s2u(smem_raw);
  const uint32_t sbar = sbase + 14 * SLOT, sstat = sbar + 1024;
  const int tid = threadIdx.x, lane = tid & 31;
  const int c = blockIdx.x, kh = c & 1, f = (c >> 1) & 7, rb = 2 * (c >> 4) + kh, rb2 = 2 * (c >> 4) + (f >> 2), nq = f & 3;
#define BAR(field, i) (sbar + (uint32_t)offsetof(Bars, field) + 8u * (i))
#define TOFF(field) (sbase + SM_T + (uint32_t)offsetof(Tables, field) + lane * 16)

  if (tid >= 256) {
    asm volatile("setmaxnreg.dec.sync.aligned.u32 56;");
    const int warp = __shfl_sync(0xffffffffu, tid >> 5, 0);
    if (lane == 0) {
      if (warp == 8) {
        if (sbase & 1023) die();
#pragma unroll
        for (int i = 0; i < 18; i++) mbar_init(BAR(emptyP, i), i < 8 ? 8 : i < 14 ? 1 : i < 17 ? 8 : 32);
        mbar_expect(BAR(tbar, 0), T2_BYTES + 2 * 10240);
        mbar_expect(BAR(xbar, 0), 16384);
        mbar_expect(BAR(hbar, 0), 16384);
      } else if (warp == 9) {
#pragma unroll
        for (int i = 0; i < 32; i++) mbar_init(BAR(full1, i), 1);
#pragma unroll
        for (int i = 0; i < 32; i++) mbar_expect(BAR(full1, i), i < 16 ? 16384 : 12288);
      } else if (warp == 10) {
#pragma unroll
        for (int i = 0; i < 32; i++) mbar_init(BAR(empty1, i), 16);
      } else {
#pragma unroll
        for (int i = 0; i < 32; i++) mbar_init(BAR(full2, i), i < 24 ? 1 : 8);
#pragma unroll
        for (int i = 0; i < 24; i++) mbar_expect(BAR(full2, i), i < 16 ? 32768 : 16384);
      }
      asm volatile("fence.mbarrier_init.release.cluster;" ::: "memory");
    }
    if (tid == 256) {
      const int w0 = ((c >> 3) * 257 + 32 * (c & 7) + 1) & ~7;
      if (FILT_DELAY) {
        asm volatile("prefetch.tensormap [%0];" ::"l"(&tmWR) : "memory");
        asm volatile("prefetch.tensormap [%0];" ::"l"(&tmWI) : "memory");
        spin_cycles(FILT_DELAY);
      }
      tma3(sbase + SM_W, &tmWR, BAR(tbar, 0), w0, 0, 0);
      tma3(sbase + SM_W + 10240, &tmWI, BAR(tbar, 0), w0, 0, 0);
      bulk_load(sbase + SM_T + T1_BYTES, reinterpret_cast<const char*>(tab) + T1_BYTES, T2_BYTES, BAR(tbar, 0));
    }
    if (tid == 288) {
      asm volatile("prefetch.tensormap [%0];" ::"l"(kh ? &tmUX : &tmGX) : "memory");
      asm volatile("prefetch.tensormap [%0];" ::"l"(kh ? &tmUY : &tmGY) : "memory");
      asm volatile("prefetch.tensormap [%0];" ::"l"(&tmD) : "memory");
    }
    if (tid == 320) {
      const unsigned e = ld_relaxed(&scr->cnt[(C_LN + rb) * 32]) >> 3;
      asm volatile("st.shared.u32 [%0], %1;" ::"r"(BAR(epoch, 0)), "r"(e) : "memory");
    }
    __syncwarp();
    asm volatile("barrier.cluster.arrive.relaxed.aligned;" ::: "memory");
    bar_arrive(NB_RDY, 384);
    asm volatile("barrier.cluster.wait.aligned;" ::: "memory");
    bar_sync(NB_INIT, 384);
    unsigned epoch;
    asm volatile("ld.shared.u32 %0, [%1];" : "=r"(epoch) : "r"(BAR(epoch, 0)) : "memory");
    if (warp == 8) {
      if (lane == 0) {
        const int ax = (7 * f + 3 * (f & 1)) >> 1;
        const int ay = 7 * f + ((f & 1) ? 0 : 4);
        const CUtensorMap* tx = kh ? &tmUX : &tmGX;
        const CUtensorMap* ty = kh ? &tmUY : &tmGY;
        if (RING_SIG >= 0) mbar_wait(BAR(sig, RING_SIG));
        uint32_t s = 2;
#pragma unroll 1
        for (int n = 0; n < 16; n++) {
          if (n >= 6) mbar_wait(BAR(empty1, n - 6));
          tma3_mc(sbase + (8 + s) * SLOT + kh * 8192, tx, BAR(full1, n), n * 32, ax);
          if (++s == 6) s = 0;
        }
#pragma unroll 1
        for (int k = 0; k < 16; k++) {
          mbar_wait(BAR(empty1, k < 8 ? 10 + ((12 * k + 11) >> 4) : 8 + k));
          tma3_mc(sbase + 8 * SLOT + (k & 7) * 12288 + kh * 6144, ty, BAR(full1, 16 + k), k * 32, ay);
        }
      }
    } else if (warp == 9) {
      if (lane == 0) {
#pragma unroll 1
        for (int i = 0; i < 14; i++) {
          const int kblk = 14 * kh + (int)((KORDER >> (4 * i)) & 15);
          const int j = i < 7 ? i : i - 7, sl = j + (j >= 4);
          mbar_wait(i < 7 ? BAR(empty1, 17 + 2 * sl) : BAR(empty2, j));
          tma3(sbase + sl * SLOT, &tmD, BAR(full2, i), 0, 64 * kblk, 2 * nq);
        }
        wait_counter(&scr->cnt[(C_LN + rb2) * 32], (epoch + 1) * 8);
        asm volatile("fence.proxy.async.global;" ::: "memory");
        mbar_wait(BAR(emptyP, 7));
        bulk_load(sbase + 4 * SLOT, &scr->LN[(rb2 * 8 + 2 * nq) * 1024 + (kh ^ 1) * 512], 8192, BAR(hbar, 0));
        bulk_load(sbase + 4 * SLOT + 8192, &scr->LN[(rb2 * 8 + 2 * nq + 1) * 1024 + (kh ^ 1) * 512], 8192, BAR(hbar, 0));
      }
    } else if (warp == 10) {
      bar_sync(NB_LN, 288);
      if (lane == 0) {
        PROFP(0);
        red_release(&scr->cnt[(C_LN + rb) * 32]);
        PROFP(1);
        wait_counter(&scr->cnt[(C_LN + rb) * 32], (epoch + 1) * 8);
        asm volatile("fence.proxy.async.global;" ::: "memory");
        PROFP(2);
#pragma unroll 1
        for (int kb = NLL; kb < 8; kb++) bulk_load(sbase + kb * SLOT, &scr->LN[(rb * 8 + kb) * 1024], 16384, BAR(fullA, kb));
#pragma unroll 1
        for (int s = 0; s < 14; s++) {
          const int kblk = 14 * kh + (int)((KORDER >> (4 * s)) & 15);
          if (s == 0 || s == 8 || s == 11) {
            if (s != 11) PROFP(3 + (s >> 2));
            mbar_wait(BAR(hint, s == 0 ? 0 : s == 8 ? 1 : 2), 0);
            if (s != 11) PROFP(4 + (s >> 2));
          }
          const int j = s < 7 ? s : s - 7;
          mbar_wait(s < 7 ? BAR(empty1, 24 + s + (s == 0) + (s >= 4)) : BAR(emptyP, j));
          bulk_load(sbase + (j ? 7 + j : 4) * SLOT, &scr->P[(rb2 * 28 + kblk) * 1024], 16384, BAR(full2, s));
        }
        PROFP(7);
      }
    } else {
      if (lane == 0) {
        l2_prefetch(wg_raw + (size_t)c * 5376, 5376);
        l2_prefetch(wu_raw + (size_t)c * 5376, 5376);
        mbar_wait(BAR(sig, PF2_SIG), 0);
        l2_prefetch(wg_raw + 688128 + (size_t)c * 8960, 8960);
        l2_prefetch(wu_raw + 688128 + (size_t)c * 8960, 8960);
      }
      mbar_wait(BAR(fullA, 7), 0);
      if (lane == 0) l2_prefetch(wd_raw + (size_t)c * 14336, 14336);
      {
        const uint32_t tag = (epoch + 1) & 1;
        uint4 v0, v1, v2;
        int it = 0;
        while (true) {
          v0 = ld_b128(&scr->ST[rb * 64 + lane]);
          v1 = ld_b128(&scr->ST[rb * 64 + 32 + lane]);
          v2 = ld_b128(&scr->ST[rb2 * 64 + 32 * (kh ^ 1) + lane]);
          if (!__any_sync(0xffffffffu, ((v0.x ^ tag) | (v1.x ^ tag) | (v2.x ^ tag)) & 1u)) break;
          if (++it > SPIN_LIMIT) { die(); break; }
        }
        sts4(sstat + lane * 16, v0.x & ~1u, v0.y, v0.z, v0.w);
        sts4(sstat + 512 + lane * 16, v1.x & ~1u, v1.y, v1.z, v1.w);
        sts4(sstat + 1024 + lane * 16, v2.x & ~1u, v2.y, v2.z, v2.w);
        mbar_arrive(BAR(sbar, 0));
      }
      if (lane == 0) {
        mbar_wait(BAR(empty1, 17));
#pragma unroll 1
        for (int e = 0; e < 3; e++) {
          const unsigned* cp = e == 0 ? &scr->cnt[(C_PX + rb2) * 32] : &scr->cnt[(C_PY + rb2) * 32 + 2 * kh + e - 1];
          if (e == 1) mbar_wait(BAR(full2, 0), 0);
          int it = 0;
          while ((int)(ld_relaxed(cp) - (epoch + 1) * (e == 0 ? 64 : 16)) < 0)
            if (++it > SPIN_LIMIT) { die(); break; }
          mbar_arrive(BAR(hint, e));
        }
      }
    }
  } else {
    const int warp = __shfl_sync(0xffffffffu, tid >> 5, 0);
    const int g = lane >> 2, t = lane & 3;
    PROF(0);
    PROFG(14);
#pragma unroll
    for (int i = 0; i < 4; i++) {
      const int r = i >> 1, ch = (i & 1) * 32 + lane;
      cp_async16(sbase + SM_X + (2 * warp + r) * 1024 + ((ch ^ ((ch >> 2) & 6)) * 16),
                 x + (size_t)(c + 128 * (2 * warp + r)) * 512 + ch * 8);
    }
    asm volatile("cp.async.commit_group;" ::: "memory");
    asm volatile("barrier.cluster.arrive.relaxed.aligned;" ::: "memory");
    uint4 tw[8], fb[16];
    const uint4 fa = ldg_ca4(&tab->fa[lane][0]);
#pragma unroll
    for (int i = 0; i < 8; i++) tw[i] = ldg_ca4(&tab->tw1[i][lane][0]);
#pragma unroll
    for (int i = 0; i < 16; i++) fb[i] = ldg_ca4(&tab->fb[i][lane][0]);
    uint32_t rbar;
    asm volatile("mapa.shared::cluster.u32 %0, %1, %2;" : "=r"(rbar) : "r"(sbar), "r"(kh ^ 1));
#define RBAR(field, i) (rbar + (uint32_t)offsetof(Bars, field) + 8u * (i))
    {
      const int ln = (tid >> 1) & 31, lg = ln >> 2, lt = ln & 3, i = 4 * (tid >> 6) + 2 * (tid & 1);
      const int kidx = lt + 8 * (i >> 3), nidx = 4 * ((i >> 1) & 3) + (lg >> 1);
      const uint32_t a0 = cfrag<2048>((c + 128 * kidx) * nidx, lg & 1), a1 = cfrag<2048>((c + 128 * (kidx + 4)) * nidx, lg & 1);
      const uint32_t b0 = cfrag<2048>(-(c + 128 * nidx) * kidx, lg & 1), b1 = cfrag<2048>(-(c + 128 * nidx) * (kidx + 4), lg & 1);
      asm volatile("st.shared.v2.u32 [%0], {%1,%2};" ::"r"(sbase + SM_FC + tid * 8), "r"(a0), "r"(a1) : "memory");
      asm volatile("st.shared.v2.u32 [%0], {%1,%2};" ::"r"(sbase + SM_FC + 2048 + tid * 8), "r"(b0), "r"(b1) : "memory");
    }
    asm volatile("cp.async.wait_group 0;" ::: "memory");
    __syncwarp();
    bar_arrive(NB_INIT, 384);
    PROF(13);
    uint32_t tag;
    uint4 q[4], o[4];
    {
      uint32_t v[2][8];
#pragma unroll
      for (int r = 0; r < 2; r++)
#pragma unroll
        for (int q = 0; q < 4; q++) {
          const uint2 u = lds2(sbase + SM_X + (2 * warp + r) * 1024 + (t + 4 * (q >> 1)) * 128 + (((4 * (q & 1) + (g >> 1)) ^ (2 * t)) * 16) + (g & 1) * 8);
          v[r][2 * q] = u.x; v[r][2 * q + 1] = u.y;
        }
      float sum[2], sq[2], rstd[2];
      row_stats(v[0], v[1], lane, sum, sq);
#pragma unroll
      for (int r = 0; r < 2; r++) {
        const float m = sum[r] * (1.f / 512.f);
        rstd[r] = rsqrtf(fmaxf(fmaf(-m, m, sq[r] * (1.f / 512.f)), 0.f) + 1e-5f);
      }
      uint32_t alo[4][4], ahi[4][4];
#pragma unroll
      for (int r = 0; r < 2; r++)
#pragma unroll
        for (int i = 0; i < 4; i++) {
          const uint32_t sel = (i & 1) ? 0x7632u : 0x5410u;
          const uint32_t b0 = __byte_perm(v[r][i >> 1], v[r][2 + (i >> 1)], sel);
          const uint32_t b1 = __byte_perm(v[r][4 + (i >> 1)], v[r][6 + (i >> 1)], sel);
          float d[4] = {0.f, 0.f, 0.f, 0.f};
          mma16816(d, fa.x, fa.y, fa.z, fa.w, b0, b1);
          const uint4 &ka = tw[2 * i], &kb = tw[2 * i + 1];
          const uint32_t re = pack2(d[0] * __uint_as_float(ka.x) + d[2] * __uint_as_float(ka.y), d[1] * __uint_as_float(kb.x) + d[3] * __uint_as_float(kb.y));
          const uint32_t im = pack2(d[0] * __uint_as_float(ka.z) + d[2] * __uint_as_float(ka.w), d[1] * __uint_as_float(kb.z) + d[3] * __uint_as_float(kb.w));
          const uint32_t dc = pack2(fmaf(sum[r], -1.f / 32.f, d[0]), fmaf(sum[r], -1.f / 32.f, d[1]));
          alo[i][r] = re; alo[i][2 + r] = im;
          ahi[i][r] = g == 0 ? dc : re; ahi[i][2 + r] = g == 0 ? 0u : im;
        }
      float acc[8][4];
#pragma unroll
      for (int u = 0; u < 8; u++) {
        acc[u][0] = acc[u][1] = acc[u][2] = acc[u][3] = 0.f;
#pragma unroll
        for (int i = 0; i < 4; i++) {
          const uint4& bq = fb[i * 4 + (u >> 1)];
          if (u < 4) mma16816(acc[u], alo[i][0], alo[i][1], alo[i][2], alo[i][3], (u & 1) ? bq.z : bq.x, (u & 1) ? bq.w : bq.y);
          else       mma16816(acc[u], ahi[i][0], ahi[i][1], ahi[i][2], ahi[i][3], (u & 1) ? bq.z : bq.x, (u & 1) ? bq.w : bq.y);
        }
      }
#pragma unroll
      for (int r = 0; r < 2; r++)
#pragma unroll
        for (int h = 0; h < 2; h++) {
          const int j = 2 * warp + r, m = 2 * t + h;
          const float rs = rstd[r];
          sts4(sbase + SM_E + ((j * 8 + m) * 8 + (g ^ (2 * t) ^ (2 * (j & 3)))) * 16,
               pack2(acc[2 * h][2 * r] * rs, acc[2 * h][2 * r + 1] * rs), pack2(acc[2 * h + 1][2 * r] * rs, acc[2 * h + 1][2 * r + 1] * rs),
               pack2(acc[4 + 2 * h][2 * r] * rs, acc[4 + 2 * h][2 * r + 1] * rs), pack2(acc[5 + 2 * h][2 * r] * rs, acc[5 + 2 * h][2 * r + 1] * rs));
        }
      if (tid == 0) PROFP(12);
      bar_sync(NB_RDY, 384);
      if (tid == 0) PROFP(13);
      uint4 fc[4];
#pragma unroll
      for (int i = 0; i < 4; i++) fc[i] = lds4(sbase + SM_FC + i * 512 + lane * 16);
      asm volatile("ld.shared.u32 %0, [%1];" : "=r"(tag) : "r"(BAR(epoch, 0)) : "memory");
      tag = (tag + 1) & 1;
#pragma unroll
      for (int i = 0; i < 4; i++) q[i] = lds4(sbase + SM_E + (((t + 4 * i) * 8 + warp) * 8 + (g ^ (warp & 6) ^ (2 * t))) * 16);
      cdft16(q, fc, o);
#pragma unroll
      for (int vv = 0; vv < 4; vv++) st_tag(&scr->Z1[(((4 * vv + t) * 8 + warp) * 128 + c) * 8 + g], o[vv], tag);
    }
    PROF(1);
    {
      const uint4* const zp = &scr->Z1[(c * 128 + 8 * t + warp) * 8 + g];
      const uint32_t tst = clock32();
      mbar_wait(BAR(tbar, 0), 0);
      if (tid == 0) PROFP(14);
      uint4 f2[4], g2[4];
#pragma unroll
      for (int i = 0; i < 4; i++) {
        f2[i] = lds4(TOFF(f2) + warp * 2048 + i * 512);
        g2[i] = lds4(TOFF(g2) + warp * 2048 + i * 512);
      }
      const uint4 f8 = lds4(TOFF(f8)), g8 = lds4(TOFF(g8));
      float wfr[16], wfi[16];
      {
        const float fsc = 1.f / (1 << 19);
        const float fsc3 = ((c & 7) == 7 && g == 0) ? 0.5f * fsc : fsc;
        const int gg = g == 0 ? 8 : g, wsh = (2 * (c >> 3) + 2) & 15;
#pragma unroll
        for (int i = 0; i < 16; i++) {
          const int ci = i >> 3, dd = (i >> 2) & 1, e = i & 3;
          const int kk = (e == 0 ? gg : e == 1 ? 16 + gg : e == 2 ? 16 - g : 32 - g) - 1;
          const uint32_t a = sbase + SM_W + ((2 * warp + ci) * 8 + t + 4 * dd) * 80 + wsh + 2 * kk;
          wfr[i] = bf_lo(lds_u16(a)) * (e == 3 ? fsc3 : fsc);
          wfi[i] = bf_lo(lds_u16(a + 10240)) * (e == 3 ? fsc3 : fsc);
        }
      }
      asm volatile("barrier.cluster.wait.aligned;" ::: "memory");
      PROF(2);
      while (clock32() - tst < POLL_DELAY) {}
      ld_tag4_issue<256>(q, zp);
      ld_tag4_finish<256>(q, zp, tag);
      if (tid == 0) PROFP(30);
      if (lane == 0) mbar_arrive(BAR(sig, 0));
      cdft16(q, f2, o);
      const uint32_t e2 = sbase + SM_E2;
#pragma unroll
      for (int vv = 0; vv < 4; vv++)
        sts4(e2 + ((warp * 16 + 4 * vv + t) * 8 + (g ^ (2 * t) ^ (2 * (warp & 3)))) * 16, o[vv].x, o[vv].y, o[vv].z, o[vv].w);
      bar_sync(NB_CONS, 256);
#pragma unroll
      for (int ci = 0; ci < 2; ci++) {
        const int cc = 2 * warp + ci;
        uint32_t ad[2];
        uint4 u[2];
#pragma unroll
        for (int hh = 0; hh < 2; hh++) {
          ad[hh] = e2 + (((t + 4 * hh) * 16 + cc) * 8 + (g ^ (2 * (cc & 3)) ^ (2 * t))) * 16;
          u[hh] = lds4(ad[hh]);
        }
        uint32_t res[2][4];
#pragma unroll
        for (int p = 0; p < 2; p++) {
          uint32_t y[2][2];
#pragma unroll
          for (int vv = 0; vv < 2; vv++) {
            float d[4] = {0.f, 0.f, 0.f, 0.f};
            mma16816(d, word(u[0], 2 * p), word(u[0], 2 * p + 1), word(u[1], 2 * p), word(u[1], 2 * p + 1), word(f8, 2 * vv), word(f8, 2 * vv + 1));
#pragma unroll
            for (int rr = 0; rr < 2; rr++) {
              const float fr = wfr[ci * 8 + vv * 4 + 2 * p + rr], fi = wfi[ci * 8 + vv * 4 + 2 * p + rr];
              y[vv][rr] = pack2(d[2 * rr] * fr - d[2 * rr + 1] * fi, d[2 * rr] * fi + d[2 * rr + 1] * fr);
            }
          }
#pragma unroll
          for (int vv = 0; vv < 2; vv++) {
            float d[4] = {0.f, 0.f, 0.f, 0.f};
            mma16816(d, y[0][0], y[0][1], y[1][0], y[1][1], word(g8, 2 * vv), word(g8, 2 * vv + 1));
            res[vv][2 * p] = pack2(d[0], d[1]);
            res[vv][2 * p + 1] = pack2(d[2], d[3]);
          }
        }
#pragma unroll
        for (int vv = 0; vv < 2; vv++) sts4(ad[vv], res[vv][0], res[vv][1], res[vv][2], res[vv][3]);
      }
      bar_sync(NB_CONS, 256);
#pragma unroll
      for (int i = 0; i < 4; i++) q[i] = lds4(e2 + ((warp * 16 + 4 * i + t) * 8 + (g ^ (2 * t) ^ (2 * (warp & 3)))) * 16);
      cdft16(q, g2, o);
#pragma unroll
      for (int vv = 0; vv < 4; vv++) st_tag(&scr->Z2[((8 * (4 * vv + t) + warp) * 128 + c) * 8 + g], o[vv], tag);
    }
    PROF(3);
    {
      const uint4* const zp = &scr->Z2[((c * 16 + t) * 8 + warp) * 8 + g];
      const uint32_t tst = clock32();
      uint4 gb[16], gc[4], tw[4], xr[2][2];
#pragma unroll
      for (int i = 0; i < 16; i++) gb[i] = lds4(TOFF(gb) + i * 512);
      const uint4 ga = lds4(TOFF(ga));
#pragma unroll
      for (int i = 0; i < 4; i++) {
        gc[i] = lds4(sbase + SM_FC + 2048 + i * 512 + lane * 16);
        tw[i] = lds4(TOFF(tw3) + i * 512);
        const int ch = 4 * (g + 8 * (i & 1)) + t;
        xr[i >> 1][i & 1] = lds4(sbase + SM_X + (2 * warp + (i >> 1)) * 1024 + ((ch ^ ((ch >> 2) & 6)) * 16));
      }
      PROF(4);
      while (clock32() - tst < POLL_DELAY) {}
      ld_tag4_issue<256>(q, zp);
      ld_tag4_finish<256>(q, zp, tag);
      if (tid == 0) PROFP(31);
      if (lane == 0) mbar_arrive(BAR(sig, 1));
      cdft16(q, gc, o);
#pragma unroll
      for (int vv = 0; vv < 4; vv++)
        sts4(sbase + SM_E + (((4 * vv + t) * 8 + warp) * 8 + (g ^ (warp & 6) ^ (2 * t))) * 16, o[vv].x, o[vv].y, o[vv].z, o[vv].w);
      bar_sync(NB_CONS, 256);
      uint32_t hv[2][8];
      const float mk = t == 0 ? 0.f : 1.f;
#pragma unroll
      for (int r = 0; r < 2; r++) {
        const int j = 2 * warp + r;
        uint4 u[2];
#pragma unroll
        for (int h = 0; h < 2; h++) u[h] = lds4(sbase + SM_E + ((j * 8 + 2 * t + h) * 8 + (g ^ (2 * t) ^ (2 * (j & 3)))) * 16);
        float yv[4][4];
#pragma unroll
        for (int i = 0; i < 4; i++) {
          float lo[4] = {0.f, 0.f, 0.f, 0.f}, hi[4] = {0.f, 0.f, 0.f, 0.f};
          mma16816(lo, gb[i * 4].x, gb[i * 4].y, gb[i * 4].z, gb[i * 4].w, u[0].x, u[0].y);
          mma16816(lo, gb[i * 4 + 1].x, gb[i * 4 + 1].y, gb[i * 4 + 1].z, gb[i * 4 + 1].w, u[1].x, u[1].y);
          mma16816(hi, gb[i * 4 + 2].x, gb[i * 4 + 2].y, gb[i * 4 + 2].z, gb[i * 4 + 2].w, u[0].z, u[0].w);
          mma16816(hi, gb[i * 4 + 3].x, gb[i * 4 + 3].y, gb[i * 4 + 3].z, gb[i * 4 + 3].w, u[1].z, u[1].w);
          const float ca = __uint_as_float(tw[i].x), sa = __uint_as_float(tw[i].y), cb = __uint_as_float(tw[i].z), sb = __uint_as_float(tw[i].w);
          const float tr0 = fmaf(hi[0], mk, lo[0]), ti0 = fmaf(hi[2], mk, lo[2]);
          const float tr1 = lo[1] + hi[1], ti1 = lo[3] + hi[3];
          const float vr0 = tr0 * ca - ti0 * sa, vi0 = tr0 * sa + ti0 * ca;
          const float vr1 = tr1 * cb - ti1 * sb, vi1 = tr1 * sb + ti1 * cb;
          const uint32_t b0 = pack2(t == 0 ? hi[0] : vr0, vr1), b1 = pack2(t == 0 ? vr0 : vi0, vi1);
          yv[i][0] = yv[i][1] = yv[i][2] = yv[i][3] = 0.f;
          mma16816(yv[i], ga.x, ga.y, ga.z, ga.w, b0, b1);
        }
#pragma unroll
        for (int h = 0; h < 2; h++) {
          hv[r][4 * h + 0] = hadd2_bf16(xr[r][h].x, pack2(yv[0][2 * h], yv[1][2 * h]));
          hv[r][4 * h + 1] = hadd2_bf16(xr[r][h].y, pack2(yv[2][2 * h], yv[3][2 * h]));
          hv[r][4 * h + 2] = hadd2_bf16(xr[r][h].z, pack2(yv[0][2 * h + 1], yv[1][2 * h + 1]));
          hv[r][4 * h + 3] = hadd2_bf16(xr[r][h].w, pack2(yv[2][2 * h + 1], yv[3][2 * h + 1]));
        }
      }
      float ds[4] = {0.f, 0.f, 0.f, 0.f};
#pragma unroll
      for (int q4 = 0; q4 < 4; q4++) mma16816(ds, hv[0][2 * q4], hv[1][2 * q4], hv[0][2 * q4 + 1], hv[1][2 * q4 + 1], 0x3f803f80u, 0x3f803f80u);
#pragma unroll
      for (int o2 = 4; o2 <= 16; o2 <<= 1) {
        ds[0] += __shfl_xor_sync(0xffffffffu, ds[0], o2);
        ds[2] += __shfl_xor_sync(0xffffffffu, ds[2], o2);
      }
      uint32_t mb[2];
#pragma unroll
      for (int r = 0; r < 2; r++) {
        const int row = 16 * f + 2 * warp + r;
        mb[r] = pack2(ds[2 * r] * (1.f / 512.f), ds[2 * r] * (1.f / 512.f));
#pragma unroll
        for (int i = 0; i < 8; i++) hv[r][i] = hsub2_bf16(hv[r][i], mb[r]);
#pragma unroll
        for (int h = 0; h < 2; h++) {
          const int n1 = g + 8 * h;
          st_tag(&scr->LN[(rb * 8 + (n1 >> 1)) * 1024 + row * 8 + ((4 * (n1 & 1) + t) ^ (row & 7))],
                 make_uint4(hv[r][4 * h], hv[r][4 * h + 1], hv[r][4 * h + 2], hv[r][4 * h + 3]), n1 < 2 * NLL ? tag : (hv[r][4 * h] & 1u));
        }
      }
      bar_arrive(NB_LN, 288);
      float sum[2], sq[2], rstd[2];
      row_stats(hv[0], hv[1], lane, sum, sq);
#pragma unroll
      for (int r = 0; r < 2; r++) {
        const float m = sum[r] * (1.f / 512.f);
        rstd[r] = rsqrtf(fmaxf(fmaf(-m, m, sq[r] * (1.f / 512.f)), 0.f) + 1e-5f);
      }
      if (lane == 0)
        st_tag(&scr->ST[rb * 64 + 8 * f + warp], make_uint4(mb[0] << 16, __float_as_uint(rstd[0]), mb[1] << 16, __float_as_uint(rstd[1])), tag);
    }
    PROF(5);
    asm volatile("setmaxnreg.inc.sync.aligned.u32 224;");
    if (NLL) {
      const uint4* const ap = &scr->LN[rb * 8 * 1024 + tid];
      uint4 av[NLL ? NLL : 1][4];
      spin_cycles(POLL_DELAY3);
#pragma unroll
      for (int kb = 0; kb < NLL; kb++) ld_tag4_issue<256>(av[kb], ap + kb * 1024);
      bar_sync(NB_CONS, 256);
#pragma unroll
      for (int kb = 0; kb < NLL; kb++) {
        ld_tag4_finish<256>(av[kb], ap + kb * 1024, tag);
#pragma unroll
        for (int i = 0; i < 4; i++) sts4(sbase + kb * SLOT + (tid + 256 * i) * 16, av[kb][i].x, av[kb][i].y, av[kb][i].z, av[kb][i].w);
      }
      asm volatile("fence.proxy.async.shared::cta;" ::: "memory");
      bar_sync(NB_CONS, 256);
    }
    const int wgi = warp >> 2, wq = warp & 3;
    uint4* const pbase = &scr->P[rb * 28 * 1024 + warp * 128 + lane];
    const uint32_t a_lo0 = desc_lo(sbase + wgi * 8192, 16);
    const uint32_t ebar = lane == 0 ? BAR(empty1, 0) : RBAR(empty1, 0);
    float r0, r1;
    uint4 px[8], py[6];
    const int rh = wgi ^ kh ^ 1;
    const uint4* const psrc = &scr->P[(rb2 * 28 + 14 * kh) * 1024 + (4 * rh + wq) * 128 + lane];
    {
      float acc[128];
#pragma unroll
      for (int i = 0; i < 128; i++) acc[i] = 0.f;
      const uint32_t b_lo0 = desc_lo(sbase + 8 * SLOT, 4096);
      uint32_t slot = 2;
#pragma unroll 1
      for (int kb = 0; kb < 8; kb++) {
        if (kb >= NLL) mbar_wait(BAR(fullA, kb), 0);
        if (kb == 0) PROF(6);
#pragma unroll
        for (int hh = 0; hh < 2; hh++) {
          if (LAGX && hh == ((16 - LAGX) & 1) && kb == ((16 - LAGX) >> 1) && wgi == 1) bar_sync(NB_LAG, 256);
          mbar_wait(BAR(full1, 2 * kb + hh));
          const uint32_t al = a_lo0 + kb * 1024 + hh * 4, bl = b_lo0 + slot * 1024;
          wg_fence();
          wgmma_n256(acc, desc64(al, HI128), desc64(bl, HI128));
          wgmma_n256(acc, desc64(al + 2, HI128), desc64(bl + 128, HI128));
          wg_commit();
          if (LAGX && hh == 1 && kb == 7 && wgi == 0) bar_arrive(NB_LAG, 256);
          wg_wait<1>();
          if ((kb | hh) != 0 && lane < 2) mbar_arrive_remote(ebar + 8 * (2 * kb + hh - 1));
          if (++slot == 6) slot = 0;
        }
      }
      mbar_wait(BAR(sbar, 0), 0);
      r0 = __uint_as_float(lds2(sstat + (16 * warp + g) * 8).y);
      r1 = __uint_as_float(lds2(sstat + (16 * warp + g + 8) * 8).y);
      wg_wait<0>();
      if (lane < 2) mbar_arrive_remote(ebar + 8 * 15);
      PROF(7);
      make_p<8, false>(acc, r0, r1, px, pbase, 0, tag);
    }
    PROF(8);
    {
      float acc[96];
#pragma unroll
      for (int i = 0; i < 96; i++) acc[i] = 0.f;
      const uint32_t b_lo0 = desc_lo(sbase + 8 * SLOT, 2048);
      uint4* const pdst = pbase + ((7 * f + 3 * (f & 1)) >> 1) * 1024;
      auto stage_y = [&](int k) {
        if (LAGY && k == 16 - LAGY && wgi == 1) bar_sync(NB_LAG, 256);
        mbar_wait(BAR(full1, 16 + k));
        const uint32_t al = a_lo0 + (k >> 1) * 1024 + (k & 1) * 4, bl = b_lo0 + (k & 7) * 768;
        wg_fence();
        wgmma_n192(acc, desc64(al, HI128), desc64(bl, HI64));
        wgmma_n192(acc, desc64(al + 2, HI128), desc64(bl + 64, HI64));
        wg_commit();
      };
#pragma unroll
      for (int k = 0; k < 4; k++) {
        stage_y(k);
        st_tag(pdst + (k >> 1) * 1024 + (k & 1) * 64, px[2 * k], tag);
        st_tag(pdst + (k >> 1) * 1024 + (k & 1) * 64 + 32, px[2 * k + 1], tag);
        if (k == 3 && lane == 0) red_relaxed(&scr->cnt[(C_PX + rb) * 32]);
        wg_wait<1>();
        if (k != 0 && lane < 2) mbar_arrive_remote(ebar + 8 * (15 + k));
      }
#pragma unroll 1
      for (int k = 4; k < 16; k++) {
        stage_y(k);
        if (LAGY && k == 15 && wgi == 0) bar_arrive(NB_LAG, 256);
        wg_wait<1>();
        if (lane < 2) mbar_arrive_remote(ebar + 8 * (15 + k));
      }
      wg_wait<0>();
      if (lane < 2) mbar_arrive_remote(ebar + 8 * 31);
      PROF(9);
      make_p<6, true>(acc, r0, r1, py, pbase, 14 * f + ((f & 1) ? 0 : 8), tag);
      if (lane == 0) red_relaxed(&scr->cnt[(C_PY + rb) * 32 + (f >> 1)]);
    }
    PROF(10);
    {
      float acc[64];
      {
        const float m0 = wgi ? 0.f : __uint_as_float(lds2(sstat + 1024 + (16 * wq + g) * 8).x);
        const float m1 = wgi ? 0.f : __uint_as_float(lds2(sstat + 1024 + (16 * wq + g + 8) * 8).x);
#pragma unroll
        for (int i = 0; i < 64; i++) acc[i] = (i & 2) ? m1 : m0;
      }
      const uint32_t b2_lo0 = desc_lo(sbase, 8192);
      const uint32_t pa0 = sbase + (4 * rh + wq) * 2048;
      auto fetch2 = [&](int s, uint4 (&a)[4]) {
        mbar_wait(BAR(full2, s), 0);
        if (tid == 0) PROFP(16 + s);
#pragma unroll
        for (int kk = 0; kk < 4; kk++) a[kk] = lds4(pa0 + (uint32_t)((PSLOT >> (4 * s)) & 15) * SLOT + kk * 512 + lane * 16);
      };
      auto check2 = [&](int s, uint4 (&a)[4]) {
        if (__any_sync(0xffffffffu, ((a[0].x ^ tag) | (a[1].x ^ tag) | (a[2].x ^ tag) | (a[3].x ^ tag)) & 1u)) {
          const uint4* p = psrc + (int)((KORDER >> (4 * s)) & 15) * 1024;
          ld_tag4_issue<32>(a, p);
          ld_tag4_finish<32>(a, p, tag);
        }
#pragma unroll
        for (int i = 0; i < 4; i++) asm volatile("and.b32 %0, %0, 0xfffffffe;" : "+r"(a[i].x));
        if (lane == 0) {
          if (s < 8) mbar_arrive(BAR(emptyP, s));
          if (s == 8) mbar_arrive_remote(RBAR(xfree, 0));
        }
      };
      auto stage2 = [&](int s, uint4 (&a)[4], uint4 (&nx)[4]) {
        if (s < 13) fetch2(s + 1, nx);
        const uint32_t bl = b2_lo0 + (uint32_t)((BSLOT >> (4 * s)) & 15) * 1024;
        if (LAG2 && s == 14 - LAG2 && wgi == 1) bar_sync(NB_LAG, 256);
        wg_fence();
#pragma unroll
        for (int kk = 0; kk < 4; kk++) wgmma_rs_n128(acc, a[kk].x, a[kk].y, a[kk].z, a[kk].w, desc64(bl + kk * 128, HI128));
        wg_commit();
        if (s < 13) check2(s + 1, nx);
        wg_wait<1>();
        if (s >= 1 && s <= 7 && lane == 0) mbar_arrive(BAR(empty2, s - 1));
      };
      uint4 fa0[4], fa1[4], fa2[4];
      fetch2(0, fa0);
      check2(0, fa0);
#pragma unroll 1
      for (int s = 0; s < 12; s += 3) {
        stage2(s, fa0, fa1);
        stage2(s + 1, fa1, fa2);
        stage2(s + 2, fa2, fa0);
      }
      stage2(12, fa0, fa1);
      stage2(13, fa1, fa2);
      if (LAG2 && wgi == 0) bar_arrive(NB_LAG, 256);
      wg_wait<0>();
      PROF(11);
#pragma unroll
      for (int h = 0; h < 2; h++)
#pragma unroll
        for (int q = 0; q < 4; q++)
          asm volatile("stmatrix.sync.aligned.m8n8.x4.shared.b16 [%0], {%1,%2,%3,%4};"
                       ::"r"(pa0 + (9 + h) * SLOT + (lane & 7) * 256 + (((4 * q + (lane >> 3)) ^ (lane & 7)) * 16)),
                         "r"(pack2(acc[16 * q + 2 * h], acc[16 * q + 2 * h + 1])), "r"(pack2(acc[16 * q + 4 + 2 * h], acc[16 * q + 5 + 2 * h])),
                         "r"(pack2(acc[16 * q + 8 + 2 * h], acc[16 * q + 9 + 2 * h])), "r"(pack2(acc[16 * q + 12 + 2 * h], acc[16 * q + 13 + 2 * h]))
                       : "memory");
      __syncwarp();
      uint4 w[8];
#pragma unroll
      for (int i = 0; i < 8; i++) {
        const int r = 2 * (i & 3) + (lane >> 4);
        w[i] = lds4(pa0 + (9 + (i >> 2)) * SLOT + r * 256 + (((lane & 15) ^ r) * 16));
      }
      const uint32_t xbuf = sbase + 8 * SLOT + (tid & 127) * 16;
      uint32_t oth = xbuf, ostr = 2048;
      if (wgi == 0) {
        mbar_wait(BAR(hbar, 0));
        mbar_wait(BAR(xfree, 0));
        oth = sbase + 4 * SLOT + ((lane >> 3) & 1) * 8192 + (16 * wq + (lane >> 4)) * 128;
        ostr = 256;
      } else {
        mbar_wait_cluster(BAR(xbar, 0), 0);
      }
      const uint32_t hmask = (wgi == 0 && 2 * nq + ((lane >> 3) & 1) < NLL) ? ~1u : ~0u;
      uint32_t rbuf;
      asm volatile("mapa.shared::cluster.u32 %0, %1, %2;" : "=r"(rbuf) : "r"(xbuf), "r"(kh ^ 1));
      uint4* const o4 = reinterpret_cast<uint4*>(out) + (16 * (c >> 4) + 2 * (4 * rh + wq) + (rb2 & 1) + 128 * (lane >> 4)) * 64 + nq * 16 + (lane & 15);
#pragma unroll
      for (int i = 0; i < 8; i++) {
        const uint4 pv = lds4(oth + i * ostr + (wgi ? 0 : (((lane & 7) ^ ((2 * i + (lane >> 4)) & 7)) * 16)));
        const uint4 v = make_uint4(hadd2_bf16(w[i].x, pv.x & hmask), hadd2_bf16(w[i].y, pv.y), hadd2_bf16(w[i].z, pv.z), hadd2_bf16(w[i].w, pv.w));
        if (wgi == 0)
          asm volatile("st.async.weak.shared::cluster.mbarrier::complete_tx::bytes.v4.b32 [%0], {%1,%2,%3,%4}, [%5];"
                       ::"r"(rbuf + i * 2048), "r"(v.x), "r"(v.y), "r"(v.z), "r"(v.w), "r"(RBAR(xbar, 0)) : "memory");
        else
          o4[i * 256 * 64] = v;
      }
      PROF(12);
      PROFG(15);
    }
  }
#undef BAR
#undef TOFF
#undef RBAR
}

typedef CUresult (*EncodeFn)(CUtensorMap*, CUtensorMapDataType, cuuint32_t, void*, const cuuint64_t*, const cuuint64_t*,
                             const cuuint32_t*, const cuuint32_t*, CUtensorMapInterleave, CUtensorMapSwizzle,
                             CUtensorMapL2promotion, CUtensorMapFloatOOBfill);

}

extern "C" void kernel_launch(void* const* d_in, const int* in_sizes, int n_in, void* d_out, int out_size) {
  (void)in_sizes; (void)n_in; (void)out_size;
  static EncodeFn encode = nullptr;
  static void *tab = nullptr, *scr = nullptr;
  if (!encode) {
    void* fn = nullptr;
    cudaDriverEntryPointQueryResult qr;
    cudaGetDriverEntryPoint("cuTensorMapEncodeTiled", &fn, cudaEnableDefault, &qr);
    encode = (EncodeFn)fn;
    cudaGetSymbolAddress(&tab, g_tab);
    cudaGetSymbolAddress(&scr, g_scr);
    cudaFuncSetAttribute(fused_kernel, cudaFuncAttributeMaxDynamicSharedMemorySize, SMEM_BYTES);
  }
  CUtensorMap tmGX, tmUX, tmGY, tmUY, tmD, tmWR, tmWI;
  const cuuint32_t es[5] = {1, 1, 1, 1, 1};
  auto enc = [&](CUtensorMap* m, void* p, int rank, const cuuint64_t* gd, const cuuint64_t* gs, const cuuint32_t* bd,
                 CUtensorMapSwizzle sw, CUtensorMapL2promotion pr) {
    encode(m, CU_TENSOR_MAP_DATA_TYPE_BFLOAT16, rank, p, gd, gs, bd, es, CU_TENSOR_MAP_INTERLEAVE_NONE, sw, pr,
           CU_TENSOR_MAP_FLOAT_OOB_FILL_NONE);
  };
  {
    const cuuint64_t gd[3] = {64, 512, 28}, gs[2] = {3584, 128};
    const cuuint32_t bd[3] = {64, 32, 2};
    enc(&tmGX, d_in[4], 3, gd, gs, bd, CU_TENSOR_MAP_SWIZZLE_128B, CU_TENSOR_MAP_L2_PROMOTION_L2_256B);
    enc(&tmUX, d_in[5], 3, gd, gs, bd, CU_TENSOR_MAP_SWIZZLE_128B, CU_TENSOR_MAP_L2_PROMOTION_L2_256B);
  }
  {
    const cuuint64_t gd[3] = {32, 512, 56}, gs[2] = {3584, 64};
    const cuuint32_t bd[3] = {32, 32, 3};
    enc(&tmGY, d_in[4], 3, gd, gs, bd, CU_TENSOR_MAP_SWIZZLE_64B, CU_TENSOR_MAP_L2_PROMOTION_L2_128B);
    enc(&tmUY, d_in[5], 3, gd, gs, bd, CU_TENSOR_MAP_SWIZZLE_64B, CU_TENSOR_MAP_L2_PROMOTION_L2_128B);
  }
  {
    const cuuint64_t gd[3] = {64, 1792, 8}, gs[2] = {1024, 128};
    const cuuint32_t bd[3] = {64, 64, 2};
    enc(&tmD, d_in[6], 3, gd, gs, bd, CU_TENSOR_MAP_SWIZZLE_128B, CU_TENSOR_MAP_L2_PROMOTION_L2_256B);
  }
  {
    const cuuint64_t gd[3] = {4112, 8, 16}, gs[2] = {16 * 8224, 8224};
    const cuuint32_t bd[3] = {40, 8, 16};
    enc(&tmWR, d_in[1], 3, gd, gs, bd, CU_TENSOR_MAP_SWIZZLE_NONE, CU_TENSOR_MAP_L2_PROMOTION_NONE);
    enc(&tmWI, d_in[2], 3, gd, gs, bd, CU_TENSOR_MAP_SWIZZLE_NONE, CU_TENSOR_MAP_L2_PROMOTION_NONE);
  }
  fused_kernel<<<NCTA, NTHREADS, SMEM_BYTES>>>((const __nv_bfloat16*)d_in[0], (const Tables*)tab, (Scratch*)scr,
                                               (__nv_bfloat16*)d_out, (const char*)d_in[4], (const char*)d_in[5],
                                               (const char*)d_in[6], tmWR, tmWI, tmGX, tmUX, tmGY, tmUY, tmD);
}
```

```cpp
#include <cuda_runtime.h>
#include <cuda_bf16.h>
#include <cuda.h>
#include <stdint.h>

namespace {

constexpr int NCTA = 128;
constexpr int NTHREADS = 384;
constexpr int SLOT = 16384;
constexpr int SMEM_BYTES = 14 * SLOT + 3072;
constexpr int SPIN_LIMIT = 1 << 22;

struct Scratch {
  uint4 Z1[128 * 1024];
  uint4 Z2[128 * 1024];
  uint4 LN[16 * 8 * 1024];
  uint4 P[16 * 28 * 1024];
  uint4 XP[128 * 1024];
  uint4 ST[1024];
  unsigned cnt[64 * 32];
};
__device__ __align__(1024) Scratch g_scr;
#define PROF(i)
#define PROFP(i)
#define PROFG(i)

constexpr double ccos(int i, int n) {
  i &= n - 1;
  if (i > n / 2) i = n - i;
  if (4 * i == n) return 0.0;
  const bool neg = 4 * i > n;
  if (neg) i = n / 2 - i;
  const double a = 6.283185307179586476925 * i / n, a2 = a * a;
  double term = 1.0, sum = 1.0;
  for (int k = 1; k < 14; k++) { term *= -a2 / ((2 * k - 1) * (2 * k)); sum += term; }
  return neg ? -sum : sum;
}
constexpr double csin(int i, int n) { return ccos(i - n / 4, n); }
constexpr unsigned fbits(double v, int mant) {
  if (v == 0.0) return 0;
  const unsigned sg = v < 0 ? 1u : 0u;
  if (v < 0) v = -v;
  int e = 127;
  while (v < 1.0) { v *= 2.0; e--; }
  const unsigned m = (unsigned)((v - 1.0) * (double)(1u << mant) + 0.5);
  return (sg << (8 + mant)) + ((unsigned)e << mant) + m;
}
constexpr unsigned pkb(double lo, double hi) { return fbits(lo, 7) | (fbits(hi, 7) << 16); }
constexpr double fa_elem(int kp, int n1) {
  return kp <= 8 ? ccos(kp * n1, 16) : -csin((kp - 8) * n1, 16);
}
constexpr unsigned cfrag_c(int idx, int n, int ri) {
  return ri ? pkb(-csin(idx, n), ccos(idx, n)) : pkb(ccos(idx, n), csin(idx, n));
}
struct Tables {
  unsigned fb[16][32][4];
  unsigned tw1[8][32][4];
  unsigned fa[32][4];
  unsigned f2[8][4][32][4];
  unsigned g2[8][4][32][4];
  unsigned gb[16][32][4];
  unsigned tw3[4][32][4];
  unsigned ga[32][4];
  unsigned f8[32][4], g8[32][4];
};
constexpr int T1_BYTES = 12800, T2_BYTES = 44544;
static_assert(sizeof(Tables) == T1_BYTES + T2_BYTES, "table size");
constexpr Tables make_tables() {
  Tables T = {};
  for (int l = 0; l < 32; l++) {
    const int g = l >> 2, t = l & 3;
    for (int i = 0; i < 4; i++)
      for (int u = 0; u < 8; u++) {
        const int ri = g & 1, m = 2 * (g >> 1) + ((u & 3) >> 1);
        const double sg = u >= 4 ? -1.0 : 1.0;
        const int k2 = u >= 4 ? 31 - 2 * m - (u & 1) : 2 * m + (u & 1);
        const int pa = (8 * t + i) * k2, pb = (8 * t + 4 + i) * k2;
        T.fb[i * 4 + (u >> 1)][l][(u & 1) * 2 + 0] = ri == 0 ? pkb(ccos(pa, 32), ccos(pb, 32)) : pkb(-sg * csin(pa, 32), -sg * csin(pb, 32));
        T.fb[i * 4 + (u >> 1)][l][(u & 1) * 2 + 1] = ri == 0 ? pkb(csin(pa, 32), csin(pb, 32)) : pkb(sg * ccos(pa, 32), sg * ccos(pb, 32));
      }
    for (int i = 0; i < 4; i++)
      for (int ks = 0; ks < 4; ks++) {
        const int n2 = 4 * g + i, m = 2 * t + (ks & 1);
        const double sg = ks >= 2 ? -1.0 : 1.0;
        const int pa = n2 * (ks >= 2 ? 31 - 2 * m : 2 * m), pb = n2 * (ks >= 2 ? 30 - 2 * m : 2 * m + 1);
        T.gb[i * 4 + ks][l][0] = pkb(ccos(pa, 32), -sg * csin(pa, 32));
        T.gb[i * 4 + ks][l][1] = pkb(csin(pa, 32), sg * ccos(pa, 32));
        T.gb[i * 4 + ks][l][2] = pkb(ccos(pb, 32), -sg * csin(pb, 32));
        T.gb[i * 4 + ks][l][3] = pkb(csin(pb, 32), sg * ccos(pb, 32));
      }
    for (int i = 0; i < 4; i++) {
      for (int e = 0; e < 2; e++) {
        const int p = (8 * t + 4 * e + i) * (g == 0 ? 8 : g);
        T.tw1[2 * i + e][l][0] = fbits(g == 0 ? 0.0 : ccos(p, 512), 23);
        T.tw1[2 * i + e][l][1] = fbits(g == 0 ? ccos(p, 512) : csin(p, 512), 23);
        T.tw1[2 * i + e][l][2] = fbits(g == 0 ? 0.0 : -csin(p, 512), 23);
        T.tw1[2 * i + e][l][3] = fbits(g == 0 ? -csin(p, 512) : ccos(p, 512), 23);
      }
      const int ka = t == 0 ? 8 : 2 * t, kb = 2 * t + 1;
      T.tw3[i][l][0] = fbits(ccos((4 * g + i) * ka, 512), 23);
      T.tw3[i][l][1] = fbits(csin((4 * g + i) * ka, 512), 23);
      T.tw3[i][l][2] = fbits(ccos((4 * g + i) * kb, 512), 23);
      T.tw3[i][l][3] = fbits(csin((4 * g + i) * kb, 512), 23);
      const int p8 = (t + 4 * (i & 1)) * (4 * (i >> 1) + (g >> 1));
      T.f8[l][i] = cfrag_c(p8, 8, g & 1);
      T.g8[l][i] = cfrag_c(-p8, 8, g & 1);
    }
    for (int w = 0; w < 8; w++)
      for (int i = 0; i < 16; i++) {
        const int kidx = t + 4 * (i & 1) + 8 * (i >> 3), nidx = 4 * ((i >> 1) & 3) + (g >> 1);
        T.f2[w][i >> 2][l][i & 3] = cfrag_c((8 * kidx + w) * nidx, 128, g & 1);
        T.g2[w][i >> 2][l][i & 3] = cfrag_c(-(8 * nidx + w) * kidx, 128, g & 1);
      }
    T.fa[l][0] = pkb(fa_elem(g, 2 * t), fa_elem(g, 2 * t + 1));
    T.fa[l][1] = pkb(fa_elem(g + 8, 2 * t), fa_elem(g + 8, 2 * t + 1));
    T.fa[l][2] = pkb(fa_elem(g, 2 * t + 8), fa_elem(g, 2 * t + 9));
    T.fa[l][3] = pkb(fa_elem(g + 8, 2 * t + 8), fa_elem(g + 8, 2 * t + 9));
    T.ga[l][0] = pkb(fa_elem(2 * t, g), fa_elem(2 * t + 1, g));
    T.ga[l][1] = pkb(fa_elem(2 * t, g + 8), fa_elem(2 * t + 1, g + 8));
    T.ga[l][2] = pkb(fa_elem(2 * t + 8, g), fa_elem(2 * t + 9, g));
    T.ga[l][3] = pkb(fa_elem(2 * t + 8, g + 8), fa_elem(2 * t + 9, g + 8));
  }
  return T;
}
__device__ const __align__(128) Tables g_tab = make_tables();

__device__ __forceinline__ void die() { asm volatile("st.global.u32 [%0], %1;" ::"l"(0ull), "r"(0) : "memory"); }
__device__ __forceinline__ uint32_t s2u(const void* p) { return (uint32_t)__cvta_generic_to_shared(p); }
__device__ __forceinline__ void mbar_init(uint32_t b, int c) { asm volatile("mbarrier.init.shared::cta.b64 [%0], %1;" ::"r"(b), "r"(c)); }
__device__ __forceinline__ void mbar_expect(uint32_t b, int bytes) {
  asm volatile("mbarrier.arrive.expect_tx.shared::cta.b64 _, [%0], %1;" ::"r"(b), "r"(bytes) : "memory");
}
__device__ __forceinline__ void mbar_arrive(uint32_t b) { asm volatile("mbarrier.arrive.shared::cta.b64 _, [%0];" ::"r"(b) : "memory"); }
__device__ __forceinline__ uint32_t mbar_try(uint32_t b, uint32_t parity) {
  uint32_t ok;
  asm volatile("{.reg .pred p; mbarrier.try_wait.parity.shared::cta.b64 p, [%1], %2; selp.u32 %0,1,0,p;}"
               : "=r"(ok) : "r"(b), "r"(parity) : "memory");
  return ok;
}
__device__ __forceinline__ void mbar_wait(uint32_t b, uint32_t parity = 0) {
  int it = 0;
#pragma unroll 1
  while (!mbar_try(b, parity))
    if (++it > SPIN_LIMIT) { die(); break; }
}
__device__ __forceinline__ void bar_sync(int id, int n) { asm volatile("bar.sync %0, %1;" ::"r"(id), "r"(n) : "memory"); }
__device__ __forceinline__ void bar_arrive(int id, int n) { asm volatile("bar.arrive %0, %1;" ::"r"(id), "r"(n) : "memory"); }
__device__ __forceinline__ void red_release(unsigned* p) { asm volatile("red.release.gpu.global.add.u32 [%0], 1;" ::"l"(p) : "memory"); }
__device__ __forceinline__ void red_relaxed(unsigned* p) { asm volatile("red.relaxed.gpu.global.add.u32 [%0], 1;" ::"l"(p) : "memory"); }
__device__ __forceinline__ unsigned ld_acquire(const unsigned* p) {
  unsigned v;
  asm volatile("ld.acquire.gpu.global.u32 %0, [%1];" : "=r"(v) : "l"(p) : "memory");
  return v;
}
__device__ __forceinline__ unsigned ld_relaxed(const unsigned* p) {
  unsigned v;
  asm volatile("ld.relaxed.gpu.global.u32 %0, [%1];" : "=r"(v) : "l"(p) : "memory");
  return v;
}
__device__ __forceinline__ void wait_counter(const unsigned* p, unsigned target) {
  int it = 0;
  while ((int)(ld_acquire(p) - target) < 0)
    if (++it > SPIN_LIMIT) { die(); break; }
}
__device__ __forceinline__ void sts4(uint32_t a, uint32_t x, uint32_t y, uint32_t z, uint32_t w) {
  asm volatile("st.shared.v4.u32 [%0], {%1,%2,%3,%4};" ::"r"(a), "r"(x), "r"(y), "r"(z), "r"(w) : "memory");
}
__device__ __forceinline__ uint4 lds4(uint32_t a) {
  uint4 v;
  asm volatile("ld.shared.v4.u32 {%0,%1,%2,%3}, [%4];" : "=r"(v.x), "=r"(v.y), "=r"(v.z), "=r"(v.w) : "r"(a) : "memory");
  return v;
}
__device__ __forceinline__ uint32_t pack2(float lo, float hi) {
  uint32_t r;
  asm("cvt.rn.bf16x2.f32 %0, %1, %2;" : "=r"(r) : "f"(hi), "f"(lo));
  return r;
}
__device__ __forceinline__ float bf_lo(uint32_t v) { return __uint_as_float(v << 16); }
__device__ __forceinline__ uint32_t hadd2_bf16(uint32_t a, uint32_t b) {
  uint32_t r;
  asm("add.rn.bf16x2 %0, %1, %2;" : "=r"(r) : "r"(a), "r"(b));
  return r;
}
__device__ __forceinline__ void mma16816(float (&d)[4], uint32_t a0, uint32_t a1, uint32_t a2, uint32_t a3, uint32_t b0, uint32_t b1) {
  asm("mma.sync.aligned.m16n8k16.row.col.f32.bf16.bf16.f32 {%0,%1,%2,%3}, {%4,%5,%6,%7}, {%8,%9}, {%0,%1,%2,%3};"
      : "+f"(d[0]), "+f"(d[1]), "+f"(d[2]), "+f"(d[3])
      : "r"(a0), "r"(a1), "r"(a2), "r"(a3), "r"(b0), "r"(b1));
}
template <int N>
__device__ __forceinline__ void cs_frac(int idx, float& c, float& s) {
  int i = ((idx + N / 2) & (N - 1)) - N / 2;
  float a = (float)i * (6.283185307179586f / N);
  c = __cosf(a);
  s = __sinf(a);
}
template <int N>
__device__ __forceinline__ uint32_t cfrag(int idx, int ri) {
  float c, s;
  cs_frac<N>(idx, c, s);
  return ri ? pack2(-s, c) : pack2(c, s);
}
__device__ __forceinline__ uint32_t word(const uint4& v, int e) { return e == 0 ? v.x : e == 1 ? v.y : e == 2 ? v.z : v.w; }
__device__ __forceinline__ void cdft16(const uint4 (&q)[4], const uint4 (&F)[4], uint4 (&o)[4]) {
  float acc[2][4][4];
#pragma unroll
  for (int p = 0; p < 2; p++)
#pragma unroll
    for (int v = 0; v < 4; v++) {
      acc[p][v][0] = acc[p][v][1] = acc[p][v][2] = acc[p][v][3] = 0.f;
#pragma unroll
      for (int ks = 0; ks < 2; ks++)
        mma16816(acc[p][v], word(q[2 * ks], 2 * p), word(q[2 * ks], 2 * p + 1), word(q[2 * ks + 1], 2 * p),
                 word(q[2 * ks + 1], 2 * p + 1), word(F[ks * 2 + (v >> 1)], (v & 1) * 2), word(F[ks * 2 + (v >> 1)], (v & 1) * 2 + 1));
    }
#pragma unroll
  for (int v = 0; v < 4; v++)
    o[v] = make_uint4(pack2(acc[0][v][0], acc[0][v][1]), pack2(acc[0][v][2], acc[0][v][3]),
                      pack2(acc[1][v][0], acc[1][v][1]), pack2(acc[1][v][2], acc[1][v][3]));
}
__device__ __forceinline__ void st_tag(uint4* p, const uint4& v, uint32_t tag) {
  asm volatile("{.reg .b128 r; .reg .b64 a, b; mov.b64 a, {%1,%2}; mov.b64 b, {%3,%4}; mov.b128 r, {a,b}; st.relaxed.gpu.global.b128 [%0], r;}"
               ::"l"(p), "r"((v.x & ~1u) | tag), "r"(v.y), "r"(v.z), "r"(v.w) : "memory");
}
__device__ __forceinline__ uint4 ld_b128(const uint4* p) {
  uint4 v;
  asm volatile("{.reg .b128 r; .reg .b64 a, b; ld.relaxed.gpu.global.b128 r, [%4]; mov.b128 {a,b}, r; mov.b64 {%0,%1}, a; mov.b64 {%2,%3}, b;}"
               : "=r"(v.x), "=r"(v.y), "=r"(v.z), "=r"(v.w) : "l"(p) : "memory");
  return v;
}
template <int STRIDE>
__device__ __forceinline__ void ld_tag4_issue(uint4 (&q)[4], const uint4* p) {
#pragma unroll
  for (int i = 0; i < 4; i++) q[i] = ld_b128(p + i * STRIDE);
}
template <int STRIDE>
__device__ __forceinline__ void ld_tag4_finish(uint4 (&q)[4], const uint4* p, uint32_t tag) {
  int it = 0;
#pragma unroll 1
  while (__any_sync(0xffffffffu, ((q[0].x ^ tag) | (q[1].x ^ tag) | (q[2].x ^ tag) | (q[3].x ^ tag)) & 1u)) {
    ld_tag4_issue<STRIDE>(q, p);
    if (++it > SPIN_LIMIT) { die(); break; }
  }
#pragma unroll
  for (int i = 0; i < 4; i++) asm volatile("and.b32 %0, %0, 0xfffffffe;" : "+r"(q[i].x));
}
__device__ __forceinline__ void row_stats(const uint32_t (&a)[8], const uint32_t (&b)[8], int lane, float (&sum)[2], float (&sq)[2]) {
  float da[4] = {0.f, 0.f, 0.f, 0.f}, db[4] = {0.f, 0.f, 0.f, 0.f}, ds[4] = {0.f, 0.f, 0.f, 0.f};
#pragma unroll
  for (int q = 0; q < 4; q++) {
    mma16816(ds, a[2 * q], b[2 * q], a[2 * q + 1], b[2 * q + 1], 0x3f803f80u, 0x3f803f80u);
    mma16816(da, a[2 * q], b[2 * q], a[2 * q + 1], b[2 * q + 1], a[2 * q], a[2 * q + 1]);
    mma16816(db, a[2 * q], b[2 * q], a[2 * q + 1], b[2 * q + 1], b[2 * q], b[2 * q + 1]);
  }
  const int src = (lane & 28) | (lane >> 3);
  const float qa = __shfl_sync(0xffffffffu, (lane & 4) ? da[1] : da[0], src);
  const float qb = __shfl_sync(0xffffffffu, (lane & 4) ? db[3] : db[2], src);
  float v = (lane & 2) ? ((lane & 1) ? ds[2] : ds[0]) : ((lane & 1) ? qb : qa);
  v += __shfl_xor_sync(0xffffffffu, v, 4);
  v += __shfl_xor_sync(0xffffffffu, v, 8);
  v += __shfl_xor_sync(0xffffffffu, v, 16);
  sq[0] = __shfl_sync(0xffffffffu, v, 0);
  sq[1] = __shfl_sync(0xffffffffu, v, 1);
  sum[0] = __shfl_sync(0xffffffffu, v, 2);
  sum[1] = __shfl_sync(0xffffffffu, v, 3);
}
__device__ __forceinline__ uint64_t desc64(uint32_t lo, uint32_t hi) {
  uint64_t d;
  asm("mov.b64 %0, {%1, %2};" : "=l"(d) : "r"(lo), "r"(hi));
  return d;
}
constexpr uint32_t desc_hi(uint32_t sbo, uint32_t swz) { return (sbo >> 4) | (swz << 30); }
__device__ __forceinline__ uint32_t desc_lo(uint32_t addr, uint32_t lbo) { return ((addr & 0x3FFFF) >> 4) | ((lbo >> 4) << 16); }
__device__ __forceinline__ void cp_async16(uint32_t dst, const void* src) {
  asm volatile("cp.async.cg.shared.global [%0], [%1], 16;" ::"r"(dst), "l"(src) : "memory");
}
__device__ __forceinline__ uint2 lds2(uint32_t a) {
  uint2 v;
  asm volatile("ld.shared.v2.u32 {%0,%1}, [%2];" : "=r"(v.x), "=r"(v.y) : "r"(a) : "memory");
  return v;
}
__device__ __forceinline__ uint32_t lds_u16(uint32_t a) {
  uint16_t v;
  asm volatile("ld.shared.u16 %0, [%1];" : "=h"(v) : "r"(a) : "memory");
  return v;
}
__device__ __forceinline__ void wg_fence() { asm volatile("wgmma.fence.sync.aligned;" ::: "memory"); }
__device__ __forceinline__ void wg_commit() { asm volatile("wgmma.commit_group.sync.aligned;" ::: "memory"); }
template <int N>
__device__ __forceinline__ void wg_wait() { asm volatile("wgmma.wait_group.sync.aligned %0;" ::"n"(N) : "memory"); }
__device__ __forceinline__ void bulk_load(uint32_t dst, const void* src, int bytes, uint32_t bar) {
  asm volatile("cp.async.bulk.shared::cluster.global.mbarrier::complete_tx::bytes [%0], [%1], %2, [%3];"
               ::"r"(dst), "l"(src), "r"(bytes), "r"(bar) : "memory");
}
__device__ __forceinline__ void bulk_load_mc(uint32_t dst, const void* src, int bytes, uint32_t bar) {
  asm volatile("cp.async.bulk.shared::cluster.global.mbarrier::complete_tx::bytes.multicast::cluster [%0], [%1], %2, [%3], %4;"
               ::"r"(dst), "l"(src), "r"(bytes), "r"(bar), "h"((uint16_t)3) : "memory");
}
__device__ __forceinline__ void tma3(uint32_t dst, const CUtensorMap* tm, uint32_t bar, int c0, int c1, int c2) {
  asm volatile("cp.async.bulk.tensor.3d.shared::cluster.global.mbarrier::complete_tx::bytes [%0], [%1, {%3,%4,%5}], [%2];"
               ::"r"(dst), "l"(tm), "r"(bar), "r"(c0), "r"(c1), "r"(c2) : "memory");
}
__device__ __forceinline__ void tma3_mc(uint32_t dst, const CUtensorMap* tm, uint32_t bar, int c1, int c2) {
  asm volatile("cp.async.bulk.tensor.3d.shared::cluster.global.mbarrier::complete_tx::bytes.multicast::cluster [%0], [%1, {%3,%4,%5}], [%2], %6;"
               ::"r"(dst), "l"(tm), "r"(bar), "r"(0), "r"(c1), "r"(c2), "h"((uint16_t)3) : "memory");
}
__device__ __forceinline__ void mbar_arrive_remote(uint32_t rb) {
  asm volatile("mbarrier.arrive.shared::cluster.b64 _, [%0];" ::"r"(rb) : "memory");
}
__device__ __forceinline__ uint4 ldg_ca4(const void* p) {
  uint4 v;
  asm volatile("ld.global.ca.v4.u32 {%0,%1,%2,%3}, [%4];" : "=r"(v.x), "=r"(v.y), "=r"(v.z), "=r"(v.w) : "l"(p) : "memory");
  return v;
}
__device__ __forceinline__ uint32_t clock32() {
  uint32_t v;
  asm volatile("mov.u32 %0, %%clock;" : "=r"(v) :: "memory");
  return v;
}
__device__ __forceinline__ float swiglu(float g, float u, float r) {
  float hg = (0.5f * r) * g, th;
  asm("tanh.approx.f32 %0, %1;" : "=f"(th) : "f"(hg));
  return fmaf(hg, th, hg) * (r * u);
}
__device__ __forceinline__ uint32_t hsub2_bf16(uint32_t a, uint32_t b) {
  uint32_t r;
  asm("sub.rn.bf16x2 %0, %1, %2;" : "=r"(r) : "r"(a), "r"(b));
  return r;
}
__device__ __forceinline__ void l2_prefetch(const void* p, int bytes) {
  asm volatile("cp.async.bulk.prefetch.L2.global [%0], %1;" ::"l"(p), "r"(bytes) : "memory");
}

__device__ __forceinline__ void wgmma_n256(float (&d)[128], uint64_t da, uint64_t db) {
  asm volatile("wgmma.mma_async.sync.aligned.m64n256k16.f32.bf16.bf16 {"
      "%0,%1,%2,%3,%4,%5,%6,%7,%8,%9,%10,%11,%12,%13,%14,%15,"
      "%16,%17,%18,%19,%20,%21,%22,%23,%24,%25,%26,%27,%28,%29,%30,%31,"
      "%32,%33,%34,%35,%36,%37,%38,%39,%40,%41,%42,%43,%44,%45,%46,%47,"
      "%48,%49,%50,%51,%52,%53,%54,%55,%56,%57,%58,%59,%60,%61,%62,%63,"
      "%64,%65,%66,%67,%68,%69,%70,%71,%72,%73,%74,%75,%76,%77,%78,%79,"
      "%80,%81,%82,%83,%84,%85,%86,%87,%88,%89,%90,%91,%92,%93,%94,%95,"
      "%96,%97,%98,%99,%100,%101,%102,%103,%104,%105,%106,%107,%108,%109,%110,%111,"
      "%112,%113,%114,%115,%116,%117,%118,%119,%120,%121,%122,%123,%124,%125,%126,%127"
      "}, %128, %129, 1, 1, 1, 0, 1;\n"
      : "+f"(d[0]),"+f"(d[1]),"+f"(d[2]),"+f"(d[3]),"+f"(d[4]),"+f"(d[5]),"+f"(d[6]),"+f"(d[7]),
        "+f"(d[8]),"+f"(d[9]),"+f"(d[10]),"+f"(d[11]),"+f"(d[12]),"+f"(d[13]),"+f"(d[14]),"+f"(d[15]),
        "+f"(d[16]),"+f"(d[17]),"+f"(d[18]),"+f"(d[19]),"+f"(d[20]),"+f"(d[21]),"+f"(d[22]),"+f"(d[23]),
        "+f"(d[24]),"+f"(d[25]),"+f"(d[26]),"+f"(d[27]),"+f"(d[28]),"+f"(d[29]),"+f"(d[30]),"+f"(d[31]),
        "+f"(d[32]),"+f"(d[33]),"+f"(d[34]),"+f"(d[35]),"+f"(d[36]),"+f"(d[37]),"+f"(d[38]),"+f"(d[39]),
        "+f"(d[40]),"+f"(d[41]),"+f"(d[42]),"+f"(d[43]),"+f"(d[44]),"+f"(d[45]),"+f"(d[46]),"+f"(d[47]),
        "+f"(d[48]),"+f"(d[49]),"+f"(d[50]),"+f"(d[51]),"+f"(d[52]),"+f"(d[53]),"+f"(d[54]),"+f"(d[55]),
        "+f"(d[56]),"+f"(d[57]),"+f"(d[58]),"+f"(d[59]),"+f"(d[60]),"+f"(d[61]),"+f"(d[62]),"+f"(d[63]),
        "+f"(d[64]),"+f"(d[65]),"+f"(d[66]),"+f"(d[67]),"+f"(d[68]),"+f"(d[69]),"+f"(d[70]),"+f"(d[71]),
        "+f"(d[72]),"+f"(d[73]),"+f"(d[74]),"+f"(d[75]),"+f"(d[76]),"+f"(d[77]),"+f"(d[78]),"+f"(d[79]),
        "+f"(d[80]),"+f"(d[81]),"+f"(d[82]),"+f"(d[83]),"+f"(d[84]),"+f"(d[85]),"+f"(d[86]),"+f"(d[87]),
        "+f"(d[88]),"+f"(d[89]),"+f"(d[90]),"+f"(d[91]),"+f"(d[92]),"+f"(d[93]),"+f"(d[94]),"+f"(d[95]),
        "+f"(d[96]),"+f"(d[97]),"+f"(d[98]),"+f"(d[99]),"+f"(d[100]),"+f"(d[101]),"+f"(d[102]),"+f"(d[103]),
        "+f"(d[104]),"+f"(d[105]),"+f"(d[106]),"+f"(d[107]),"+f"(d[108]),"+f"(d[109]),"+f"(d[110]),"+f"(d[111]),
        "+f"(d[112]),"+f"(d[113]),"+f"(d[114]),"+f"(d[115]),"+f"(d[116]),"+f"(d[117]),"+f"(d[118]),"+f"(d[119]),
        "+f"(d[120]),"+f"(d[121]),"+f"(d[122]),"+f"(d[123]),"+f"(d[124]),"+f"(d[125]),"+f"(d[126]),"+f"(d[127])
      : "l"(da), "l"(db));
}
__device__ __forceinline__ void wgmma_n192(float (&d)[96], uint64_t da, uint64_t db) {
  asm volatile("wgmma.mma_async.sync.aligned.m64n192k16.f32.bf16.bf16 {"
      "%0,%1,%2,%3,%4,%5,%6,%7,%8,%9,%10,%11,%12,%13,%14,%15,"
      "%16,%17,%18,%19,%20,%21,%22,%23,%24,%25,%26,%27,%28,%29,%30,%31,"
      "%32,%33,%34,%35,%36,%37,%38,%39,%40,%41,%42,%43,%44,%45,%46,%47,"
      "%48,%49,%50,%51,%52,%53,%54,%55,%56,%57,%58,%59,%60,%61,%62,%63,"
      "%64,%65,%66,%67,%68,%69,%70,%71,%72,%73,%74,%75,%76,%77,%78,%79,"
      "%80,%81,%82,%83,%84,%85,%86,%87,%88,%89,%90,%91,%92,%93,%94,%95"
      "}, %96, %97, 1, 1, 1, 0, 1;\n"
      : "+f"(d[0]),"+f"(d[1]),"+f"(d[2]),"+f"(d[3]),"+f"(d[4]),"+f"(d[5]),"+f"(d[6]),"+f"(d[7]),
        "+f"(d[8]),"+f"(d[9]),"+f"(d[10]),"+f"(d[11]),"+f"(d[12]),"+f"(d[13]),"+f"(d[14]),"+f"(d[15]),
        "+f"(d[16]),"+f"(d[17]),"+f"(d[18]),"+f"(d[19]),"+f"(d[20]),"+f"(d[21]),"+f"(d[22]),"+f"(d[23]),
        "+f"(d[24]),"+f"(d[25]),"+f"(d[26]),"+f"(d[27]),"+f"(d[28]),"+f"(d[29]),"+f"(d[30]),"+f"(d[31]),
        "+f"(d[32]),"+f"(d[33]),"+f"(d[34]),"+f"(d[35]),"+f"(d[36]),"+f"(d[37]),"+f"(d[38]),"+f"(d[39]),
        "+f"(d[40]),"+f"(d[41]),"+f"(d[42]),"+f"(d[43]),"+f"(d[44]),"+f"(d[45]),"+f"(d[46]),"+f"(d[47]),
        "+f"(d[48]),"+f"(d[49]),"+f"(d[50]),"+f"(d[51]),"+f"(d[52]),"+f"(d[53]),"+f"(d[54]),"+f"(d[55]),
        "+f"(d[56]),"+f"(d[57]),"+f"(d[58]),"+f"(d[59]),"+f"(d[60]),"+f"(d[61]),"+f"(d[62]),"+f"(d[63]),
        "+f"(d[64]),"+f"(d[65]),"+f"(d[66]),"+f"(d[67]),"+f"(d[68]),"+f"(d[69]),"+f"(d[70]),"+f"(d[71]),
        "+f"(d[72]),"+f"(d[73]),"+f"(d[74]),"+f"(d[75]),"+f"(d[76]),"+f"(d[77]),"+f"(d[78]),"+f"(d[79]),
        "+f"(d[80]),"+f"(d[81]),"+f"(d[82]),"+f"(d[83]),"+f"(d[84]),"+f"(d[85]),"+f"(d[86]),"+f"(d[87]),
        "+f"(d[88]),"+f"(d[89]),"+f"(d[90]),"+f"(d[91]),"+f"(d[92]),"+f"(d[93]),"+f"(d[94]),"+f"(d[95])
      : "l"(da), "l"(db));
}
__device__ __forceinline__ void wgmma_rs_n128(float (&d)[64], uint32_t a0, uint32_t a1, uint32_t a2, uint32_t a3, uint64_t db) {
  asm volatile("wgmma.mma_async.sync.aligned.m64n128k16.f32.bf16.bf16 {"
      "%0,%1,%2,%3,%4,%5,%6,%7,%8,%9,%10,%11,%12,%13,%14,%15,"
      "%16,%17,%18,%19,%20,%21,%22,%23,%24,%25,%26,%27,%28,%29,%30,%31,"
      "%32,%33,%34,%35,%36,%37,%38,%39,%40,%41,%42,%43,%44,%45,%46,%47,"
      "%48,%49,%50,%51,%52,%53,%54,%55,%56,%57,%58,%59,%60,%61,%62,%63"
      "}, {%64,%65,%66,%67}, %68, 1, 1, 1, 1;\n"
      : "+f"(d[0]),"+f"(d[1]),"+f"(d[2]),"+f"(d[3]),"+f"(d[4]),"+f"(d[5]),"+f"(d[6]),"+f"(d[7]),
        "+f"(d[8]),"+f"(d[9]),"+f"(d[10]),"+f"(d[11]),"+f"(d[12]),"+f"(d[13]),"+f"(d[14]),"+f"(d[15]),
        "+f"(d[16]),"+f"(d[17]),"+f"(d[18]),"+f"(d[19]),"+f"(d[20]),"+f"(d[21]),"+f"(d[22]),"+f"(d[23]),
        "+f"(d[24]),"+f"(d[25]),"+f"(d[26]),"+f"(d[27]),"+f"(d[28]),"+f"(d[29]),"+f"(d[30]),"+f"(d[31]),
        "+f"(d[32]),"+f"(d[33]),"+f"(d[34]),"+f"(d[35]),"+f"(d[36]),"+f"(d[37]),"+f"(d[38]),"+f"(d[39]),
        "+f"(d[40]),"+f"(d[41]),"+f"(d[42]),"+f"(d[43]),"+f"(d[44]),"+f"(d[45]),"+f"(d[46]),"+f"(d[47]),
        "+f"(d[48]),"+f"(d[49]),"+f"(d[50]),"+f"(d[51]),"+f"(d[52]),"+f"(d[53]),"+f"(d[54]),"+f"(d[55]),
        "+f"(d[56]),"+f"(d[57]),"+f"(d[58]),"+f"(d[59]),"+f"(d[60]),"+f"(d[61]),"+f"(d[62]),"+f"(d[63])
      : "r"(a0), "r"(a1), "r"(a2), "r"(a3), "l"(db));
}

constexpr int C_LN = 0, C_PX = 16, C_PY = 32;
constexpr int NB_CONS = 1, NB_LN = 2, NB_LAG = 4, NB_INIT = 6, NB_RDY = 7;
#define LAGX 3
#define LAGY 2
#define LAG2 4
#define NLL 2
#define POLL_DELAY3 900
#define POLL_DELAY 900
#define FILT_DELAY 1000
#define THR_B 0
#define THR_P 0
#define SPEC -1
#define RING_SIG 0
#define PF2_SIG 1
constexpr int SM_E = 0, SM_X = 16384, SM_E2 = 32768, SM_W = 49152, SM_FC = 69632, SM_T = 73728 - T1_BYTES;
constexpr unsigned long long KORDER = 0xBA9432DC876510ull;
constexpr unsigned long long BSLOT = 0x76532107653210ull, PSLOT = 0xDCBA984DCBA984ull;
constexpr uint32_t HI128 = desc_hi(1024, 1), HI64 = desc_hi(512, 2);

struct Bars {
  uint64_t full1[32], empty1[32], full2[16], fullA[8], empty2[8], fullP[16], emptyP[8], hbar, tbar, hint[3], sig[2], sbar;
  uint32_t epoch;
};

template <int NK, bool STORE>
__device__ __forceinline__ void make_p(const float (&acc)[NK * 16], float r0, float r1, uint4 (&p)[NK], uint4* pbase, int ks0, uint32_t tag) {
#pragma unroll
  for (int j = 0; j < NK; j++) {
    uint32_t w[4];
#pragma unroll
    for (int i = 0; i < 4; i++) {
      const int a = 8 * j + 2 * i, b = a + NK * 8;
      w[i] = pack2(swiglu(acc[a], acc[b], (i & 1) ? r1 : r0), swiglu(acc[a + 1], acc[b + 1], (i & 1) ? r1 : r0));
    }
    asm volatile("" : "+r"(w[0]), "+r"(w[1]), "+r"(w[2]), "+r"(w[3]));
    p[j] = make_uint4(w[0], w[1], w[2], w[3]);
    if (STORE) st_tag(pbase + ((ks0 + j) >> 2) * 1024 + ((ks0 + j) & 3) * 32, p[j], tag);
  }
}
__device__ __forceinline__ void spin_cycles(uint32_t n) {
  const uint32_t t0 = clock32();
  while (clock32() - t0 < n) {}
}

__global__ void __cluster_dims__(2, 1, 1) __launch_bounds__(NTHREADS, 1)
fused_kernel(const __nv_bfloat16* __restrict__ x, const Tables* __restrict__ tab, Scratch* __restrict__ scr,
             __nv_bfloat16* __restrict__ out, const char* __restrict__ wg_raw, const char* __restrict__ wu_raw,
             const char* __restrict__ wd_raw,
             const __grid_constant__ CUtensorMap tmWR, const __grid_constant__ CUtensorMap tmWI,
             const __grid_constant__ CUtensorMap tmGX, const __grid_constant__ CUtensorMap tmUX,
             const __grid_constant__ CUtensorMap tmGY, const __grid_constant__ CUtensorMap tmUY,
             const __grid_constant__ CUtensorMap tmD) {
  extern __shared__ __align__(1024) char smem_raw[];
  const uint32_t sbase = s2u(smem_raw);
  const uint32_t sbar = sbase + 14 * SLOT, sstat = sbar + 1280;
  const int tid = threadIdx.x, lane = tid & 31;
  const int c = blockIdx.x, rk = c & 1, f = (c >> 1) & 7, rb = 2 * (c >> 4) + rk;
  const int rb2 = 2 * (c >> 4) + (f >> 2), kh = (f >> 1) & 1, nq = 2 * (f & 1) + rk;
#define BAR(field, i) (sbar + (uint32_t)offsetof(Bars, field) + 8u * (i))
#define TOFF(field) (sbase + SM_T + (uint32_t)offsetof(Tables, field) + lane * 16)

  if (tid >= 256) {
    asm volatile("setmaxnreg.dec.sync.aligned.u32 56;");
    const int warp = __shfl_sync(0xffffffffu, tid >> 5, 0);
    if (lane == 0) {
      if (warp == 8) {
        if (sbase & 1023) die();
#pragma unroll
        for (int i = 0; i < 16; i++) mbar_init(BAR(emptyP, i), i < 7 ? 16 : i < 8 ? 8 : i < 13 ? 1 : i < 15 ? 8 : 32);
        mbar_expect(BAR(tbar, 0), T2_BYTES + 2 * 10240);
        mbar_expect(BAR(hbar, 0), 16384);
      } else if (warp == 9) {
#pragma unroll
        for (int i = 0; i < 32; i++) mbar_init(BAR(full1, i), 1);
#pragma unroll
        for (int i = 0; i < 32; i++) mbar_expect(BAR(full1, i), i < 16 ? 16384 : 12288);
      } else if (warp == 10) {
#pragma unroll
        for (int i = 0; i < 32; i++) mbar_init(BAR(empty1, i), 16);
#pragma unroll
        for (int i = 0; i < 14; i++) mbar_init(BAR(fullP, i), 1);
#pragma unroll
        for (int i = 0; i < 14; i++) mbar_expect(BAR(fullP, i), 16384);
      } else {
#pragma unroll
        for (int i = 0; i < 32; i++) mbar_init(BAR(full2, i), i < 24 ? 1 : 8);
#pragma unroll
        for (int i = 0; i < 24; i++) mbar_expect(BAR(full2, i), 16384);
      }
      asm volatile("fence.mbarrier_init.release.cluster;" ::: "memory");
    }
    if (tid == 256) {
      const int w0 = ((c >> 3) * 257 + 32 * (c & 7) + 1) & ~7;
      if (FILT_DELAY) {
        asm volatile("prefetch.tensormap [%0];" ::"l"(&tmWR) : "memory");
        asm volatile("prefetch.tensormap [%0];" ::"l"(&tmWI) : "memory");
        spin_cycles(FILT_DELAY);
      }
      tma3(sbase + SM_W, &tmWR, BAR(tbar, 0), w0, 0, 0);
      tma3(sbase + SM_W + 10240, &tmWI, BAR(tbar, 0), w0, 0, 0);
      bulk_load(sbase + SM_T + T1_BYTES, reinterpret_cast<const char*>(tab) + T1_BYTES, T2_BYTES, BAR(tbar, 0));
    }
    if (tid == 288) {
      asm volatile("prefetch.tensormap [%0];" ::"l"(rk ? &tmUX : &tmGX) : "memory");
      asm volatile("prefetch.tensormap [%0];" ::"l"(rk ? &tmUY : &tmGY) : "memory");
      asm volatile("prefetch.tensormap [%0];" ::"l"(&tmD) : "memory");
    }
    if (tid == 320) {
      const unsigned e = ld_relaxed(&scr->cnt[(C_LN + rb) * 32]) >> 3;
      asm volatile("st.shared.u32 [%0], %1;" ::"r"(BAR(epoch, 0)), "r"(e) : "memory");
    }
    __syncwarp();
    asm volatile("barrier.cluster.arrive.relaxed.aligned;" ::: "memory");
    bar_arrive(NB_RDY, 384);
    asm volatile("barrier.cluster.wait.aligned;" ::: "memory");
    bar_sync(NB_INIT, 384);
    unsigned epoch;
    asm volatile("ld.shared.u32 %0, [%1];" : "=r"(epoch) : "r"(BAR(epoch, 0)) : "memory");
    if (warp == 8) {
      if (lane == 0) {
        const int ax = (7 * f + 3 * (f & 1)) >> 1;
        const int ay = 7 * f + ((f & 1) ? 0 : 4);
        const CUtensorMap* tx = rk ? &tmUX : &tmGX;
        const CUtensorMap* ty = rk ? &tmUY : &tmGY;
        if (RING_SIG >= 0) mbar_wait(BAR(sig, RING_SIG));
        uint32_t s = 2;
#pragma unroll 1
        for (int n = 0; n < 16; n++) {
          if (n >= 6) mbar_wait(BAR(empty1, n - 6));
          tma3_mc(sbase + (8 + s) * SLOT + rk * 8192, tx, BAR(full1, n), n * 32, ax);
          if (++s == 6) s = 0;
        }
#pragma unroll 1
        for (int k = 0; k < 16; k++) {
          mbar_wait(BAR(empty1, k < 8 ? 10 + ((12 * k + 11) >> 4) : 8 + k));
          tma3_mc(sbase + 8 * SLOT + (k & 7) * 12288 + rk * 6144, ty, BAR(full1, 16 + k), k * 32, ay);
        }
      }
    } else if (warp == 9) {
      if (lane == 0) {
#pragma unroll 1
        for (int i = 0; i < 14; i++) {
          const int kblk = 14 * kh + (int)((KORDER >> (4 * i)) & 15);
          const int j = i < 7 ? i : i - 7, sl = j + (j >= 4);
          mbar_wait(i < 7 ? BAR(empty1, 17 + 2 * sl) : BAR(empty2, j));
          if (THR_B && i >= THR_B) mbar_wait(BAR(full2, i - THR_B));
          tma3(sbase + sl * SLOT, &tmD, BAR(full2, i), 0, 64 * kblk, 2 * nq);
        }
        wait_counter(&scr->cnt[(C_LN + rb2) * 32], (epoch + 1) * 8);
        asm volatile("fence.proxy.async.global;" ::: "memory");
        mbar_wait(BAR(emptyP, 7));
        bulk_load(sbase + 4 * SLOT, &scr->LN[(rb2 * 8 + 2 * nq) * 1024 + (kh ^ 1) * 512], 8192, BAR(hbar, 0));
        bulk_load(sbase + 4 * SLOT + 8192, &scr->LN[(rb2 * 8 + 2 * nq + 1) * 1024 + (kh ^ 1) * 512], 8192, BAR(hbar, 0));
      }
    } else if (warp == 10) {
      bar_sync(NB_LN, 288);
      if (lane == 0) {
        PROFP(0);
        red_release(&scr->cnt[(C_LN + rb) * 32]);
        PROFP(1);
        wait_counter(&scr->cnt[(C_LN + rb) * 32], (epoch + 1) * 8);
        asm volatile("fence.proxy.async.global;" ::: "memory");
        PROFP(2);
#pragma unroll 1
        for (int kb = NLL; kb < 8; kb++) bulk_load(sbase + kb * SLOT, &scr->LN[(rb * 8 + kb) * 1024], 16384, BAR(fullA, kb));
#pragma unroll 1
        for (int s = 0; s < 14; s++) {
          const int kblk = 14 * kh + (int)((KORDER >> (4 * s)) & 15);
          if (s == 0 || (SPEC < 0 && (s == 8 || s == 11))) {
            if (s != 11) PROFP(3 + (s >> 2));
            mbar_wait(BAR(hint, s == 0 ? 0 : s == 8 ? 1 : 2), 0);
            if (s != 11) PROFP(4 + (s >> 2));
          }
          const int j = s < 7 ? s : s - 7;
          mbar_wait(s < 7 ? BAR(empty1, 24 + s + (s == 0) + (s >= 4)) : BAR(emptyP, j));
          if (THR_P && s >= THR_P) mbar_wait(BAR(fullP, s - THR_P));
          if (SPEC >= 0 && s == 8) mbar_wait(BAR(emptyP, SPEC));
          bulk_load_mc(sbase + (j ? 7 + j : 4) * SLOT + rk * 8192, &scr->P[(rb2 * 28 + kblk) * 1024 + rk * 512], 8192, BAR(fullP, s));
        }
        PROFP(7);
      }
    } else {
      if (lane == 0) {
        l2_prefetch(wg_raw + (size_t)c * 5376, 5376);
        l2_prefetch(wu_raw + (size_t)c * 5376, 5376);
        mbar_wait(BAR(sig, PF2_SIG), 0);
        l2_prefetch(wg_raw + 688128 + (size_t)c * 8960, 8960);
        l2_prefetch(wu_raw + 688128 + (size_t)c * 8960, 8960);
      }
      mbar_wait(BAR(fullA, 7), 0);
      if (lane == 0) l2_prefetch(wd_raw + (size_t)c * 14336, 14336);
      {
        const uint32_t tag = (epoch + 1) & 1;
        uint4 v0, v1, v2;
        int it = 0;
        while (true) {
          v0 = ld_b128(&scr->ST[rb * 64 + lane]);
          v1 = ld_b128(&scr->ST[rb * 64 + 32 + lane]);
          v2 = ld_b128(&scr->ST[rb2 * 64 + 32 * (kh ^ 1) + lane]);
          if (!__any_sync(0xffffffffu, ((v0.x ^ tag) | (v1.x ^ tag) | (v2.x ^ tag)) & 1u)) break;
          if (++it > SPIN_LIMIT) { die(); break; }
        }
        sts4(sstat + lane * 16, v0.x & ~1u, v0.y, v0.z, v0.w);
        sts4(sstat + 512 + lane * 16, v1.x & ~1u, v1.y, v1.z, v1.w);
        sts4(sstat + 1024 + lane * 16, v2.x & ~1u, v2.y, v2.z, v2.w);
        mbar_arrive(BAR(sbar, 0));
      }
      if (lane == 0) {
        mbar_wait(BAR(empty1, 17));
#pragma unroll 1
        for (int e = 0; e < (SPEC < 0 ? 3 : 1); e++) {
          const unsigned* cp = e == 0 ? &scr->cnt[(C_PX + rb2) * 32] : &scr->cnt[(C_PY + rb2) * 32 + 2 * kh + e - 1];
          if (e == 1) mbar_wait(BAR(fullP, 0), 0);
          int it = 0;
          while ((int)(ld_relaxed(cp) - (epoch + 1) * (e == 0 ? 64 : 16)) < 0)
            if (++it > SPIN_LIMIT) { die(); break; }
          mbar_arrive(BAR(hint, e));
        }
      }
    }
  } else {
    const int warp = __shfl_sync(0xffffffffu, tid >> 5, 0);
    const int g = lane >> 2, t = lane & 3;
    PROF(0);
    PROFG(14);
#pragma unroll
    for (int i = 0; i < 4; i++) {
      const int r = i >> 1, ch = (i & 1) * 32 + lane;
      cp_async16(sbase + SM_X + (2 * warp + r) * 1024 + ((ch ^ ((ch >> 2) & 6)) * 16),
                 x + (size_t)(c + 128 * (2 * warp + r)) * 512 + ch * 8);
    }
    asm volatile("cp.async.commit_group;" ::: "memory");
    asm volatile("barrier.cluster.arrive.relaxed.aligned;" ::: "memory");
    uint4 tw[8], fb[16];
    const uint4 fa = ldg_ca4(&tab->fa[lane][0]);
#pragma unroll
    for (int i = 0; i < 8; i++) tw[i] = ldg_ca4(&tab->tw1[i][lane][0]);
#pragma unroll
    for (int i = 0; i < 16; i++) fb[i] = ldg_ca4(&tab->fb[i][lane][0]);
    uint32_t rbar;
    asm volatile("mapa.shared::cluster.u32 %0, %1, %2;" : "=r"(rbar) : "r"(sbar), "r"(rk ^ 1));
#define RBAR(field, i) (rbar + (uint32_t)offsetof(Bars, field) + 8u * (i))
    {
      const int ln = (tid >> 1) & 31, lg = ln >> 2, lt = ln & 3, i = 4 * (tid >> 6) + 2 * (tid & 1);
      const int kidx = lt + 8 * (i >> 3), nidx = 4 * ((i >> 1) & 3) + (lg >> 1);
      const uint32_t a0 = cfrag<2048>((c + 128 * kidx) * nidx, lg & 1), a1 = cfrag<2048>((c + 128 * (kidx + 4)) * nidx, lg & 1);
      const uint32_t b0 = cfrag<2048>(-(c + 128 * nidx) * kidx, lg & 1), b1 = cfrag<2048>(-(c + 128 * nidx) * (kidx + 4), lg & 1);
      asm volatile("st.shared.v2.u32 [%0], {%1,%2};" ::"r"(sbase + SM_FC + tid * 8), "r"(a0), "r"(a1) : "memory");
      asm volatile("st.shared.v2.u32 [%0], {%1,%2};" ::"r"(sbase + SM_FC + 2048 + tid * 8), "r"(b0), "r"(b1) : "memory");
    }
    asm volatile("cp.async.wait_group 0;" ::: "memory");
    __syncwarp();
    bar_arrive(NB_INIT, 384);
    PROF(13);
    uint32_t tag;
    uint4 q[4], o[4];
    {
      uint32_t v[2][8];
#pragma unroll
      for (int r = 0; r < 2; r++)
#pragma unroll
        for (int q = 0; q < 4; q++) {
          const uint2 u = lds2(sbase + SM_X + (2 * warp + r) * 1024 + (t + 4 * (q >> 1)) * 128 + (((4 * (q & 1) + (g >> 1)) ^ (2 * t)) * 16) + (g & 1) * 8);
          v[r][2 * q] = u.x; v[r][2 * q + 1] = u.y;
        }
      float sum[2], sq[2], rstd[2];
      row_stats(v[0], v[1], lane, sum, sq);
#pragma unroll
      for (int r = 0; r < 2; r++) {
        const float m = sum[r] * (1.f / 512.f);
        rstd[r] = rsqrtf(fmaxf(fmaf(-m, m, sq[r] * (1.f / 512.f)), 0.f) + 1e-5f);
      }
      uint32_t alo[4][4], ahi[4][4];
#pragma unroll
      for (int r = 0; r < 2; r++)
#pragma unroll
        for (int i = 0; i < 4; i++) {
          const uint32_t sel = (i & 1) ? 0x7632u : 0x5410u;
          const uint32_t b0 = __byte_perm(v[r][i >> 1], v[r][2 + (i >> 1)], sel);
          const uint32_t b1 = __byte_perm(v[r][4 + (i >> 1)], v[r][6 + (i >> 1)], sel);
          float d[4] = {0.f, 0.f, 0.f, 0.f};
          mma16816(d, fa.x, fa.y, fa.z, fa.w, b0, b1);
          const uint4 &ka = tw[2 * i], &kb = tw[2 * i + 1];
          const uint32_t re = pack2(d[0] * __uint_as_float(ka.x) + d[2] * __uint_as_float(ka.y), d[1] * __uint_as_float(kb.x) + d[3] * __uint_as_float(kb.y));
          const uint32_t im = pack2(d[0] * __uint_as_float(ka.z) + d[2] * __uint_as_float(ka.w), d[1] * __uint_as_float(kb.z) + d[3] * __uint_as_float(kb.w));
          const uint32_t dc = pack2(fmaf(sum[r], -1.f / 32.f, d[0]), fmaf(sum[r], -1.f / 32.f, d[1]));
          alo[i][r] = re; alo[i][2 + r] = im;
          ahi[i][r] = g == 0 ? dc : re; ahi[i][2 + r] = g == 0 ? 0u : im;
        }
      float acc[8][4];
#pragma unroll
      for (int u = 0; u < 8; u++) {
        acc[u][0] = acc[u][1] = acc[u][2] = acc[u][3] = 0.f;
#pragma unroll
        for (int i = 0; i < 4; i++) {
          const uint4& bq = fb[i * 4 + (u >> 1)];
          if (u < 4) mma16816(acc[u], alo[i][0], alo[i][1], alo[i][2], alo[i][3], (u & 1) ? bq.z : bq.x, (u & 1) ? bq.w : bq.y);
          else       mma16816(acc[u], ahi[i][0], ahi[i][1], ahi[i][2], ahi[i][3], (u & 1) ? bq.z : bq.x, (u & 1) ? bq.w : bq.y);
        }
      }
#pragma unroll
      for (int r = 0; r < 2; r++)
#pragma unroll
        for (int h = 0; h < 2; h++) {
          const int j = 2 * warp + r, m = 2 * t + h;
          const float rs = rstd[r];
          sts4(sbase + SM_E + ((j * 8 + m) * 8 + (g ^ (2 * t) ^ (2 * (j & 3)))) * 16,
               pack2(acc[2 * h][2 * r] * rs, acc[2 * h][2 * r + 1] * rs), pack2(acc[2 * h + 1][2 * r] * rs, acc[2 * h + 1][2 * r + 1] * rs),
               pack2(acc[4 + 2 * h][2 * r] * rs, acc[4 + 2 * h][2 * r + 1] * rs), pack2(acc[5 + 2 * h][2 * r] * rs, acc[5 + 2 * h][2 * r + 1] * rs));
        }
      if (tid == 0) PROFP(12);
      bar_sync(NB_RDY, 384);
      if (tid == 0) PROFP(13);
      uint4 fc[4];
#pragma unroll
      for (int i = 0; i < 4; i++) fc[i] = lds4(sbase + SM_FC + i * 512 + lane * 16);
      asm volatile("ld.shared.u32 %0, [%1];" : "=r"(tag) : "r"(BAR(epoch, 0)) : "memory");
      tag = (tag + 1) & 1;
#pragma unroll
      for (int i = 0; i < 4; i++) q[i] = lds4(sbase + SM_E + (((t + 4 * i) * 8 + warp) * 8 + (g ^ (warp & 6) ^ (2 * t))) * 16);
      cdft16(q, fc, o);
#pragma unroll
      for (int vv = 0; vv < 4; vv++) st_tag(&scr->Z1[(((4 * vv + t) * 8 + warp) * 128 + c) * 8 + g], o[vv], tag);
    }
    PROF(1);
    {
      const uint4* const zp = &scr->Z1[(c * 128 + 8 * t + warp) * 8 + g];
      const uint32_t tst = clock32();
      mbar_wait(BAR(tbar, 0), 0);
      if (tid == 0) PROFP(14);
      uint4 f2[4], g2[4];
#pragma unroll
      for (int i = 0; i < 4; i++) {
        f2[i] = lds4(TOFF(f2) + warp * 2048 + i * 512);
        g2[i] = lds4(TOFF(g2) + warp * 2048 + i * 512);
      }
      const uint4 f8 = lds4(TOFF(f8)), g8 = lds4(TOFF(g8));
      float wfr[16], wfi[16];
      {
        const float fsc = 1.f / (1 << 19);
        const float fsc3 = ((c & 7) == 7 && g == 0) ? 0.5f * fsc : fsc;
        const int gg = g == 0 ? 8 : g, wsh = (2 * (c >> 3) + 2) & 15;
#pragma unroll
        for (int i = 0; i < 16; i++) {
          const int ci = i >> 3, dd = (i >> 2) & 1, e = i & 3;
          const int kk = (e == 0 ? gg : e == 1 ? 16 + gg : e == 2 ? 16 - g : 32 - g) - 1;
          const uint32_t a = sbase + SM_W + ((2 * warp + ci) * 8 + t + 4 * dd) * 80 + wsh + 2 * kk;
          wfr[i] = bf_lo(lds_u16(a)) * (e == 3 ? fsc3 : fsc);
          wfi[i] = bf_lo(lds_u16(a + 10240)) * (e == 3 ? fsc3 : fsc);
        }
      }
      asm volatile("barrier.cluster.wait.aligned;" ::: "memory");
      PROF(2);
      while (clock32() - tst < POLL_DELAY) {}
      ld_tag4_issue<256>(q, zp);
      ld_tag4_finish<256>(q, zp, tag);
      if (tid == 0) PROFP(30);
      if (lane == 0) mbar_arrive(BAR(sig, 0));
      cdft16(q, f2, o);
      const uint32_t e2 = sbase + SM_E2;
#pragma unroll
      for (int vv = 0; vv < 4; vv++)
        sts4(e2 + ((warp * 16 + 4 * vv + t) * 8 + (g ^ (2 * t) ^ (2 * (warp & 3)))) * 16, o[vv].x, o[vv].y, o[vv].z, o[vv].w);
      bar_sync(NB_CONS, 256);
#pragma unroll
      for (int ci = 0; ci < 2; ci++) {
        const int cc = 2 * warp + ci;
        uint32_t ad[2];
        uint4 u[2];
#pragma unroll
        for (int hh = 0; hh < 2; hh++) {
          ad[hh] = e2 + (((t + 4 * hh) * 16 + cc) * 8 + (g ^ (2 * (cc & 3)) ^ (2 * t))) * 16;
          u[hh] = lds4(ad[hh]);
        }
        uint32_t res[2][4];
#pragma unroll
        for (int p = 0; p < 2; p++) {
          uint32_t y[2][2];
#pragma unroll
          for (int vv = 0; vv < 2; vv++) {
            float d[4] = {0.f, 0.f, 0.f, 0.f};
            mma16816(d, word(u[0], 2 * p), word(u[0], 2 * p + 1), word(u[1], 2 * p), word(u[1], 2 * p + 1), word(f8, 2 * vv), word(f8, 2 * vv + 1));
#pragma unroll
            for (int rr = 0; rr < 2; rr++) {
              const float fr = wfr[ci * 8 + vv * 4 + 2 * p + rr], fi = wfi[ci * 8 + vv * 4 + 2 * p + rr];
              y[vv][rr] = pack2(d[2 * rr] * fr - d[2 * rr + 1] * fi, d[2 * rr] * fi + d[2 * rr + 1] * fr);
            }
          }
#pragma unroll
          for (int vv = 0; vv < 2; vv++) {
            float d[4] = {0.f, 0.f, 0.f, 0.f};
            mma16816(d, y[0][0], y[0][1], y[1][0], y[1][1], word(g8, 2 * vv), word(g8, 2 * vv + 1));
            res[vv][2 * p] = pack2(d[0], d[1]);
            res[vv][2 * p + 1] = pack2(d[2], d[3]);
          }
        }
#pragma unroll
        for (int vv = 0; vv < 2; vv++) sts4(ad[vv], res[vv][0], res[vv][1], res[vv][2], res[vv][3]);
      }
      bar_sync(NB_CONS, 256);
#pragma unroll
      for (int i = 0; i < 4; i++) q[i] = lds4(e2 + ((warp * 16 + 4 * i + t) * 8 + (g ^ (2 * t) ^ (2 * (warp & 3)))) * 16);
      cdft16(q, g2, o);
#pragma unroll
      for (int vv = 0; vv < 4; vv++) st_tag(&scr->Z2[((8 * (4 * vv + t) + warp) * 128 + c) * 8 + g], o[vv], tag);
    }
    PROF(3);
    {
      const uint4* const zp = &scr->Z2[((c * 16 + t) * 8 + warp) * 8 + g];
      const uint32_t tst = clock32();
      uint4 gb[16], gc[4], tw[4], xr[2][2];
#pragma unroll
      for (int i = 0; i < 16; i++) gb[i] = lds4(TOFF(gb) + i * 512);
      const uint4 ga = lds4(TOFF(ga));
#pragma unroll
      for (int i = 0; i < 4; i++) {
        gc[i] = lds4(sbase + SM_FC + 2048 + i * 512 + lane * 16);
        tw[i] = lds4(TOFF(tw3) + i * 512);
        const int ch = 4 * (g + 8 * (i & 1)) + t;
        xr[i >> 1][i & 1] = lds4(sbase + SM_X + (2 * warp + (i >> 1)) * 1024 + ((ch ^ ((ch >> 2) & 6)) * 16));
      }
      PROF(4);
      while (clock32() - tst < POLL_DELAY) {}
      ld_tag4_issue<256>(q, zp);
      ld_tag4_finish<256>(q, zp, tag);
      if (tid == 0) PROFP(31);
      if (lane == 0) mbar_arrive(BAR(sig, 1));
      cdft16(q, gc, o);
#pragma unroll
      for (int vv = 0; vv < 4; vv++)
        sts4(sbase + SM_E + (((4 * vv + t) * 8 + warp) * 8 + (g ^ (warp & 6) ^ (2 * t))) * 16, o[vv].x, o[vv].y, o[vv].z, o[vv].w);
      bar_sync(NB_CONS, 256);
      uint32_t hv[2][8];
      const float mk = t == 0 ? 0.f : 1.f;
#pragma unroll
      for (int r = 0; r < 2; r++) {
        const int j = 2 * warp + r;
        uint4 u[2];
#pragma unroll
        for (int h = 0; h < 2; h++) u[h] = lds4(sbase + SM_E + ((j * 8 + 2 * t + h) * 8 + (g ^ (2 * t) ^ (2 * (j & 3)))) * 16);
        float yv[4][4];
#pragma unroll
        for (int i = 0; i < 4; i++) {
          float lo[4] = {0.f, 0.f, 0.f, 0.f}, hi[4] = {0.f, 0.f, 0.f, 0.f};
          mma16816(lo, gb[i * 4].x, gb[i * 4].y, gb[i * 4].z, gb[i * 4].w, u[0].x, u[0].y);
          mma16816(lo, gb[i * 4 + 1].x, gb[i * 4 + 1].y, gb[i * 4 + 1].z, gb[i * 4 + 1].w, u[1].x, u[1].y);
          mma16816(hi, gb[i * 4 + 2].x, gb[i * 4 + 2].y, gb[i * 4 + 2].z, gb[i * 4 + 2].w, u[0].z, u[0].w);
          mma16816(hi, gb[i * 4 + 3].x, gb[i * 4 + 3].y, gb[i * 4 + 3].z, gb[i * 4 + 3].w, u[1].z, u[1].w);
          const float ca = __uint_as_float(tw[i].x), sa = __uint_as_float(tw[i].y), cb = __uint_as_float(tw[i].z), sb = __uint_as_float(tw[i].w);
          const float tr0 = fmaf(hi[0], mk, lo[0]), ti0 = fmaf(hi[2], mk, lo[2]);
          const float tr1 = lo[1] + hi[1], ti1 = lo[3] + hi[3];
          const float vr0 = tr0 * ca - ti0 * sa, vi0 = tr0 * sa + ti0 * ca;
          const float vr1 = tr1 * cb - ti1 * sb, vi1 = tr1 * sb + ti1 * cb;
          const uint32_t b0 = pack2(t == 0 ? hi[0] : vr0, vr1), b1 = pack2(t == 0 ? vr0 : vi0, vi1);
          yv[i][0] = yv[i][1] = yv[i][2] = yv[i][3] = 0.f;
          mma16816(yv[i], ga.x, ga.y, ga.z, ga.w, b0, b1);
        }
#pragma unroll
        for (int h = 0; h < 2; h++) {
          hv[r][4 * h + 0] = hadd2_bf16(xr[r][h].x, pack2(yv[0][2 * h], yv[1][2 * h]));
          hv[r][4 * h + 1] = hadd2_bf16(xr[r][h].y, pack2(yv[2][2 * h], yv[3][2 * h]));
          hv[r][4 * h + 2] = hadd2_bf16(xr[r][h].z, pack2(yv[0][2 * h + 1], yv[1][2 * h + 1]));
          hv[r][4 * h + 3] = hadd2_bf16(xr[r][h].w, pack2(yv[2][2 * h + 1], yv[3][2 * h + 1]));
        }
      }
      float ds[4] = {0.f, 0.f, 0.f, 0.f};
#pragma unroll
      for (int q4 = 0; q4 < 4; q4++) mma16816(ds, hv[0][2 * q4], hv[1][2 * q4], hv[0][2 * q4 + 1], hv[1][2 * q4 + 1], 0x3f803f80u, 0x3f803f80u);
#pragma unroll
      for (int o2 = 4; o2 <= 16; o2 <<= 1) {
        ds[0] += __shfl_xor_sync(0xffffffffu, ds[0], o2);
        ds[2] += __shfl_xor_sync(0xffffffffu, ds[2], o2);
      }
      uint32_t mb[2];
#pragma unroll
      for (int r = 0; r < 2; r++) {
        const int row = 16 * f + 2 * warp + r;
        mb[r] = pack2(ds[2 * r] * (1.f / 512.f), ds[2 * r] * (1.f / 512.f));
#pragma unroll
        for (int i = 0; i < 8; i++) hv[r][i] = hsub2_bf16(hv[r][i], mb[r]);
#pragma unroll
        for (int h = 0; h < 2; h++) {
          const int n1 = g + 8 * h;
          st_tag(&scr->LN[(rb * 8 + (n1 >> 1)) * 1024 + row * 8 + ((4 * (n1 & 1) + t) ^ (row & 7))],
                 make_uint4(hv[r][4 * h], hv[r][4 * h + 1], hv[r][4 * h + 2], hv[r][4 * h + 3]), n1 < 2 * NLL ? tag : (hv[r][4 * h] & 1u));
        }
      }
      bar_arrive(NB_LN, 288);
      float sum[2], sq[2], rstd[2];
      row_stats(hv[0], hv[1], lane, sum, sq);
#pragma unroll
      for (int r = 0; r < 2; r++) {
        const float m = sum[r] * (1.f / 512.f);
        rstd[r] = rsqrtf(fmaxf(fmaf(-m, m, sq[r] * (1.f / 512.f)), 0.f) + 1e-5f);
      }
      if (lane == 0)
        st_tag(&scr->ST[rb * 64 + 8 * f + warp], make_uint4(mb[0] << 16, __float_as_uint(rstd[0]), mb[1] << 16, __float_as_uint(rstd[1])), tag);
    }
    PROF(5);
    asm volatile("setmaxnreg.inc.sync.aligned.u32 224;");
    if (NLL) {
      const uint4* const ap = &scr->LN[rb * 8 * 1024 + tid];
      uint4 av[NLL ? NLL : 1][4];
      spin_cycles(POLL_DELAY3);
#pragma unroll
      for (int kb = 0; kb < NLL; kb++) ld_tag4_issue<256>(av[kb], ap + kb * 1024);
      bar_sync(NB_CONS, 256);
#pragma unroll
      for (int kb = 0; kb < NLL; kb++) {
        ld_tag4_finish<256>(av[kb], ap + kb * 1024, tag);
#pragma unroll
        for (int i = 0; i < 4; i++) sts4(sbase + kb * SLOT + (tid + 256 * i) * 16, av[kb][i].x, av[kb][i].y, av[kb][i].z, av[kb][i].w);
      }
      asm volatile("fence.proxy.async.shared::cta;" ::: "memory");
      bar_sync(NB_CONS, 256);
    }
    const int wgi = warp >> 2, wq = warp & 3;
    uint4* const pbase = &scr->P[rb * 28 * 1024 + warp * 128 + lane];
    const uint32_t a_lo0 = desc_lo(sbase + wgi * 8192, 16);
    const uint32_t ebar = lane == 0 ? BAR(empty1, 0) : RBAR(empty1, 0);
    float r0, r1;
    uint4 px[8], py[6];
    const int rh = wgi ^ kh ^ 1;
    const uint4* const psrc = &scr->P[(rb2 * 28 + 14 * kh) * 1024 + (4 * rh + wq) * 128 + lane];
    {
      float acc[128];
#pragma unroll
      for (int i = 0; i < 128; i++) acc[i] = 0.f;
      const uint32_t b_lo0 = desc_lo(sbase + 8 * SLOT, 4096);
      if (wgi == 0) {
#pragma unroll
        for (int i = 0; i < 8; i++) st_tag(&scr->XP[(c ^ 4) * 1024 + i * 128 + tid], make_uint4(0, 0, 0, 0), tag ^ 1);
      }
      uint32_t slot = 2;
#pragma unroll 1
      for (int kb = 0; kb < 8; kb++) {
        if (kb >= NLL) mbar_wait(BAR(fullA, kb), 0);
        if (kb == 0) PROF(6);
#pragma unroll
        for (int hh = 0; hh < 2; hh++) {
          if (LAGX && hh == ((16 - LAGX) & 1) && kb == ((16 - LAGX) >> 1) && wgi == 1) bar_sync(NB_LAG, 256);
          mbar_wait(BAR(full1, 2 * kb + hh));
          const uint32_t al = a_lo0 + kb * 1024 + hh * 4, bl = b_lo0 + slot * 1024;
          wg_fence();
          wgmma_n256(acc, desc64(al, HI128), desc64(bl, HI128));
          wgmma_n256(acc, desc64(al + 2, HI128), desc64(bl + 128, HI128));
          wg_commit();
          if (LAGX && hh == 1 && kb == 7 && wgi == 0) bar_arrive(NB_LAG, 256);
          wg_wait<1>();
          if ((kb | hh) != 0 && lane < 2) mbar_arrive_remote(ebar + 8 * (2 * kb + hh - 1));
          if (++slot == 6) slot = 0;
        }
      }
      mbar_wait(BAR(sbar, 0), 0);
      r0 = __uint_as_float(lds2(sstat + (16 * warp + g) * 8).y);
      r1 = __uint_as_float(lds2(sstat + (16 * warp + g + 8) * 8).y);
      wg_wait<0>();
      if (lane < 2) mbar_arrive_remote(ebar + 8 * 15);
      PROF(7);
      make_p<8, false>(acc, r0, r1, px, pbase, 0, tag);
    }
    PROF(8);
    {
      float acc[96];
#pragma unroll
      for (int i = 0; i < 96; i++) acc[i] = 0.f;
      const uint32_t b_lo0 = desc_lo(sbase + 8 * SLOT, 2048);
      uint4* const pdst = pbase + ((7 * f + 3 * (f & 1)) >> 1) * 1024;
      auto stage_y = [&](int k) {
        if (LAGY && k == 16 - LAGY && wgi == 1) bar_sync(NB_LAG, 256);
        mbar_wait(BAR(full1, 16 + k));
        const uint32_t al = a_lo0 + (k >> 1) * 1024 + (k & 1) * 4, bl = b_lo0 + (k & 7) * 768;
        wg_fence();
        wgmma_n192(acc, desc64(al, HI128), desc64(bl, HI64));
        wgmma_n192(acc, desc64(al + 2, HI128), desc64(bl + 64, HI64));
        wg_commit();
      };
#pragma unroll
      for (int k = 0; k < 4; k++) {
        stage_y(k);
        st_tag(pdst + (k >> 1) * 1024 + (k & 1) * 64, px[2 * k], tag);
        st_tag(pdst + (k >> 1) * 1024 + (k & 1) * 64 + 32, px[2 * k + 1], tag);
        if (k == 3 && lane == 0) red_relaxed(&scr->cnt[(C_PX + rb) * 32]);
        wg_wait<1>();
        if (k != 0 && lane < 2) mbar_arrive_remote(ebar + 8 * (15 + k));
      }
#pragma unroll 1
      for (int k = 4; k < 16; k++) {
        stage_y(k);
        if (LAGY && k == 15 && wgi == 0) bar_arrive(NB_LAG, 256);
        wg_wait<1>();
        if (lane < 2) mbar_arrive_remote(ebar + 8 * (15 + k));
      }
      wg_wait<0>();
      if (lane < 2) mbar_arrive_remote(ebar + 8 * 31);
      PROF(9);
      make_p<6, true>(acc, r0, r1, py, pbase, 14 * f + ((f & 1) ? 0 : 8), tag);
      if (lane == 0) red_relaxed(&scr->cnt[(C_PY + rb) * 32 + (f >> 1)]);
    }
    PROF(10);
    {
      float acc[64];
      {
        const float m0 = wgi ? 0.f : __uint_as_float(lds2(sstat + 1024 + (16 * wq + g) * 8).x);
        const float m1 = wgi ? 0.f : __uint_as_float(lds2(sstat + 1024 + (16 * wq + g + 8) * 8).x);
#pragma unroll
        for (int i = 0; i < 64; i++) acc[i] = (i & 2) ? m1 : m0;
      }
      const uint32_t b2_lo0 = desc_lo(sbase, 8192);
      const uint32_t pa0 = sbase + (4 * rh + wq) * 2048;
      auto fetch2 = [&](int s, uint4 (&a)[4]) {
        mbar_wait(BAR(fullP, s));
        if (tid == 0) PROFP(16 + s);
#pragma unroll
        for (int kk = 0; kk < 4; kk++) a[kk] = lds4(pa0 + (uint32_t)((PSLOT >> (4 * s)) & 15) * SLOT + kk * 512 + lane * 16);
      };
      auto check2 = [&](int s, uint4 (&a)[4]) {
        if (__any_sync(0xffffffffu, ((a[0].x ^ tag) | (a[1].x ^ tag) | (a[2].x ^ tag) | (a[3].x ^ tag)) & 1u)) {
          const uint4* p = psrc + (int)((KORDER >> (4 * s)) & 15) * 1024;
          ld_tag4_issue<32>(a, p);
          ld_tag4_finish<32>(a, p, tag);
        }
#pragma unroll
        for (int i = 0; i < 4; i++) asm volatile("and.b32 %0, %0, 0xfffffffe;" : "+r"(a[i].x));
        if (s < 8 && lane < (s < 7 ? 2 : 1))
          mbar_arrive_remote(ebar + (uint32_t)(offsetof(Bars, emptyP) - offsetof(Bars, empty1)) + 8 * s);
      };
      auto stage2 = [&](int s, uint4 (&a)[4], uint4 (&nx)[4]) {
        if (s < 13) fetch2(s + 1, nx);
        const uint32_t bl = b2_lo0 + (uint32_t)((BSLOT >> (4 * s)) & 15) * 1024;
        if (LAG2 && s == 14 - LAG2 && wgi == 1) bar_sync(NB_LAG, 256);
        mbar_wait(BAR(full2, s));
        wg_fence();
#pragma unroll
        for (int kk = 0; kk < 4; kk++) wgmma_rs_n128(acc, a[kk].x, a[kk].y, a[kk].z, a[kk].w, desc64(bl + kk * 128, HI128));
        wg_commit();
        if (s < 13) check2(s + 1, nx);
        wg_wait<1>();
        if (s >= 1 && s <= 7 && lane == 0) mbar_arrive(BAR(empty2, s - 1));
      };
      uint4 fa0[4], fa1[4], fa2[4];
      fetch2(0, fa0);
      check2(0, fa0);
#pragma unroll 1
      for (int s = 0; s < 12; s += 3) {
        stage2(s, fa0, fa1);
        stage2(s + 1, fa1, fa2);
        stage2(s + 2, fa2, fa0);
      }
      stage2(12, fa0, fa1);
      stage2(13, fa1, fa2);
      if (LAG2 && wgi == 0) bar_arrive(NB_LAG, 256);
      uint4 pv[2][4];
      const uint4* const xsrc = &scr->XP[c * 1024 + (tid & 127)];
      if (wgi == 1) {
        ld_tag4_issue<128>(pv[0], xsrc);
        ld_tag4_issue<128>(pv[1], xsrc + 512);
      }
      wg_wait<0>();
      PROF(11);
#pragma unroll
      for (int h = 0; h < 2; h++)
#pragma unroll
        for (int q = 0; q < 4; q++)
          asm volatile("stmatrix.sync.aligned.m8n8.x4.shared.b16 [%0], {%1,%2,%3,%4};"
                       ::"r"(pa0 + (9 + h) * SLOT + (lane & 7) * 256 + (((4 * q + (lane >> 3)) ^ (lane & 7)) * 16)),
                         "r"(pack2(acc[16 * q + 2 * h], acc[16 * q + 2 * h + 1])), "r"(pack2(acc[16 * q + 4 + 2 * h], acc[16 * q + 5 + 2 * h])),
                         "r"(pack2(acc[16 * q + 8 + 2 * h], acc[16 * q + 9 + 2 * h])), "r"(pack2(acc[16 * q + 12 + 2 * h], acc[16 * q + 13 + 2 * h]))
                       : "memory");
      __syncwarp();
      uint4 w[8];
#pragma unroll
      for (int i = 0; i < 8; i++) {
        const int r = 2 * (i & 3) + (lane >> 4);
        w[i] = lds4(pa0 + (9 + (i >> 2)) * SLOT + r * 256 + (((lane & 15) ^ r) * 16));
      }
      uint4* dst;
      int dstr;
      if (wgi == 0) {
        mbar_wait(BAR(hbar, 0));
        const uint32_t hb = sbase + 4 * SLOT + ((lane >> 3) & 1) * 8192 + (16 * wq + (lane >> 4)) * 128;
#pragma unroll
        for (int i = 0; i < 8; i++) {
          pv[i >> 2][i & 3] = lds4(hb + i * 256 + (((lane & 7) ^ ((2 * i + (lane >> 4)) & 7)) * 16));
          if (2 * nq + ((lane >> 3) & 1) < NLL) pv[i >> 2][i & 3].x &= ~1u;
        }
        dst = &scr->XP[(c ^ 4) * 1024 + tid];
        dstr = 128;
      } else {
        ld_tag4_finish<128>(pv[0], xsrc, tag);
        ld_tag4_finish<128>(pv[1], xsrc + 512, tag);
        dst = reinterpret_cast<uint4*>(out) + (16 * (c >> 4) + 2 * (4 * rh + wq) + (rb2 & 1) + 128 * (lane >> 4)) * 64 + nq * 16 + (lane & 15);
        dstr = 256 * 64;
      }
#pragma unroll
      for (int i = 0; i < 8; i++) {
        const uint4& p = pv[i >> 2][i & 3];
        const uint4 v = make_uint4(hadd2_bf16(w[i].x, p.x), hadd2_bf16(w[i].y, p.y), hadd2_bf16(w[i].z, p.z), hadd2_bf16(w[i].w, p.w));
        st_tag(dst + i * dstr, v, wgi ? (v.x & 1u) : tag);
      }
      PROF(12);
      PROFG(15);
    }
  }
#undef BAR
#undef TOFF
#undef RBAR
}

typedef CUresult (*EncodeFn)(CUtensorMap*, CUtensorMapDataType, cuuint32_t, void*, const cuuint64_t*, const cuuint64_t*,
                             const cuuint32_t*, const cuuint32_t*, CUtensorMapInterleave, CUtensorMapSwizzle,
                             CUtensorMapL2promotion, CUtensorMapFloatOOBfill);

}

extern "C" void kernel_launch(void* const* d_in, const int* in_sizes, int n_in, void* d_out, int out_size) {
  (void)in_sizes; (void)n_in; (void)out_size;
  static EncodeFn encode = nullptr;
  static void *tab = nullptr, *scr = nullptr;
  if (!encode) {
    void* fn = nullptr;
    cudaDriverEntryPointQueryResult qr;
    cudaGetDriverEntryPoint("cuTensorMapEncodeTiled", &fn, cudaEnableDefault, &qr);
    encode = (EncodeFn)fn;
    cudaGetSymbolAddress(&tab, g_tab);
    cudaGetSymbolAddress(&scr, g_scr);
    cudaFuncSetAttribute(fused_kernel, cudaFuncAttributeMaxDynamicSharedMemorySize, SMEM_BYTES);
  }
  CUtensorMap tmGX, tmUX, tmGY, tmUY, tmD, tmWR, tmWI;
  const cuuint32_t es[5] = {1, 1, 1, 1, 1};
  auto enc = [&](CUtensorMap* m, void* p, int rank, const cuuint64_t* gd, const cuuint64_t* gs, const cuuint32_t* bd,
                 CUtensorMapSwizzle sw, CUtensorMapL2promotion pr) {
    encode(m, CU_TENSOR_MAP_DATA_TYPE_BFLOAT16, rank, p, gd, gs, bd, es, CU_TENSOR_MAP_INTERLEAVE_NONE, sw, pr,
           CU_TENSOR_MAP_FLOAT_OOB_FILL_NONE);
  };
  {
    const cuuint64_t gd[3] = {64, 512, 28}, gs[2] = {3584, 128};
    const cuuint32_t bd[3] = {64, 32, 2};
    enc(&tmGX, d_in[4], 3, gd, gs, bd, CU_TENSOR_MAP_SWIZZLE_128B, CU_TENSOR_MAP_L2_PROMOTION_L2_256B);
    enc(&tmUX, d_in[5], 3, gd, gs, bd, CU_TENSOR_MAP_SWIZZLE_128B, CU_TENSOR_MAP_L2_PROMOTION_L2_256B);
  }
  {
    const cuuint64_t gd[3] = {32, 512, 56}, gs[2] = {3584, 64};
    const cuuint32_t bd[3] = {32, 32, 3};
    enc(&tmGY, d_in[4], 3, gd, gs, bd, CU_TENSOR_MAP_SWIZZLE_64B, CU_TENSOR_MAP_L2_PROMOTION_L2_128B);
    enc(&tmUY, d_in[5], 3, gd, gs, bd, CU_TENSOR_MAP_SWIZZLE_64B, CU_TENSOR_MAP_L2_PROMOTION_L2_128B);
  }
  {
    const cuuint64_t gd[3] = {64, 1792, 8}, gs[2] = {1024, 128};
    const cuuint32_t bd[3] = {64, 64, 2};
    enc(&tmD, d_in[6], 3, gd, gs, bd, CU_TENSOR_MAP_SWIZZLE_128B, CU_TENSOR_MAP_L2_PROMOTION_L2_256B);
  }
  {
    const cuuint64_t gd[3] = {4112, 8, 16}, gs[2] = {16 * 8224, 8224};
    const cuuint32_t bd[3] = {40, 8, 16};
    enc(&tmWR, d_in[1], 3, gd, gs, bd, CU_TENSOR_MAP_SWIZZLE_NONE, CU_TENSOR_MAP_L2_PROMOTION_NONE);
    enc(&tmWI, d_in[2], 3, gd, gs, bd, CU_TENSOR_MAP_SWIZZLE_NONE, CU_TENSOR_MAP_L2_PROMOTION_NONE);
  }
  fused_kernel<<<NCTA, NTHREADS, SMEM_BYTES>>>((const __nv_bfloat16*)d_in[0], (const Tables*)tab, (Scratch*)scr,
                                               (__nv_bfloat16*)d_out, (const char*)d_in[4], (const char*)d_in[5],
                                               (const char*)d_in[6], tmWR, tmWI, tmGX, tmUX, tmGY, tmUY, tmD);
}
```

```cpp
#include <cuda_runtime.h>
#include <cuda_bf16.h>
#include <cuda.h>
#include <stdint.h>

namespace {

constexpr int NCTA = 128;
constexpr int NTHREADS = 384;
constexpr int SLOT = 16384;
constexpr int SMEM_BYTES = 14 * SLOT + 3072;
constexpr int SPIN_LIMIT = 1 << 22;

struct Scratch {
  uint4 Z1[128 * 1024];
  uint4 Z2[128 * 1024];
  uint4 LN[16 * 8 * 1024];
  uint4 P[16 * 28 * 1024];
  uint4 XP[128 * 1024];
  uint4 ST[1024];
  unsigned cnt[64 * 32];
};
__device__ __align__(1024) Scratch g_scr;
#define PROF(i)
#define PROFP(i)
#define PROFG(i)

constexpr double ccos(int i, int n) {
  i &= n - 1;
  if (i > n / 2) i = n - i;
  if (4 * i == n) return 0.0;
  const bool neg = 4 * i > n;
  if (neg) i = n / 2 - i;
  const double a = 6.283185307179586476925 * i / n, a2 = a * a;
  double term = 1.0, sum = 1.0;
  for (int k = 1; k < 14; k++) { term *= -a2 / ((2 * k - 1) * (2 * k)); sum += term; }
  return neg ? -sum : sum;
}
constexpr double csin(int i, int n) { return ccos(i - n / 4, n); }
constexpr unsigned fbits(double v, int mant) {
  if (v == 0.0) return 0;
  const unsigned sg = v < 0 ? 1u : 0u;
  if (v < 0) v = -v;
  int e = 127;
  while (v < 1.0) { v *= 2.0; e--; }
  const unsigned m = (unsigned)((v - 1.0) * (double)(1u << mant) + 0.5);
  return (sg << (8 + mant)) + ((unsigned)e << mant) + m;
}
constexpr unsigned pkb(double lo, double hi) { return fbits(lo, 7) | (fbits(hi, 7) << 16); }
constexpr double fa_elem(int kp, int n1) {
  return kp <= 8 ? ccos(kp * n1, 16) : -csin((kp - 8) * n1, 16);
}
constexpr unsigned cfrag_c(int idx, int n, int ri) {
  return ri ? pkb(-csin(idx, n), ccos(idx, n)) : pkb(ccos(idx, n), csin(idx, n));
}
struct Tables {
  unsigned fb[16][32][4];
  unsigned tw1[8][32][4];
  unsigned fa[32][4];
  unsigned f2[8][4][32][4];
  unsigned g2[8][4][32][4];
  unsigned gb[16][32][4];
  unsigned tw3[4][32][4];
  unsigned ga[32][4];
  unsigned f8[32][4], g8[32][4];
};
constexpr int T1_BYTES = 12800, T2_BYTES = 44544;
static_assert(sizeof(Tables) == T1_BYTES + T2_BYTES, "table size");
constexpr Tables make_tables() {
  Tables T = {};
  for (int l = 0; l < 32; l++) {
    const int g = l >> 2, t = l & 3;
    for (int i = 0; i < 4; i++)
      for (int u = 0; u < 8; u++) {
        const int ri = g & 1, m = 2 * (g >> 1) + ((u & 3) >> 1);
        const double sg = u >= 4 ? -1.0 : 1.0;
        const int k2 = u >= 4 ? 31 - 2 * m - (u & 1) : 2 * m + (u & 1);
        const int pa = (8 * t + i) * k2, pb = (8 * t + 4 + i) * k2;
        T.fb[i * 4 + (u >> 1)][l][(u & 1) * 2 + 0] = ri == 0 ? pkb(ccos(pa, 32), ccos(pb, 32)) : pkb(-sg * csin(pa, 32), -sg * csin(pb, 32));
        T.fb[i * 4 + (u >> 1)][l][(u & 1) * 2 + 1] = ri == 0 ? pkb(csin(pa, 32), csin(pb, 32)) : pkb(sg * ccos(pa, 32), sg * ccos(pb, 32));
      }
    for (int i = 0; i < 4; i++)
      for (int ks = 0; ks < 4; ks++) {
        const int n2 = 4 * g + i, m = 2 * t + (ks & 1);
        const double sg = ks >= 2 ? -1.0 : 1.0;
        const int pa = n2 * (ks >= 2 ? 31 - 2 * m : 2 * m), pb = n2 * (ks >= 2 ? 30 - 2 * m : 2 * m + 1);
        T.gb[i * 4 + ks][l][0] = pkb(ccos(pa, 32), -sg * csin(pa, 32));
        T.gb[i * 4 + ks][l][1] = pkb(csin(pa, 32), sg * ccos(pa, 32));
        T.gb[i * 4 + ks][l][2] = pkb(ccos(pb, 32), -sg * csin(pb, 32));
        T.gb[i * 4 + ks][l][3] = pkb(csin(pb, 32), sg * ccos(pb, 32));
      }
    for (int i = 0; i < 4; i++) {
      for (int e = 0; e < 2; e++) {
        const int p = (8 * t + 4 * e + i) * (g == 0 ? 8 : g);
        T.tw1[2 * i + e][l][0] = fbits(g == 0 ? 0.0 : ccos(p, 512), 23);
        T.tw1[2 * i + e][l][1] = fbits(g == 0 ? ccos(p, 512) : csin(p, 512), 23);
        T.tw1[2 * i + e][l][2] = fbits(g == 0 ? 0.0 : -csin(p, 512), 23);
        T.tw1[2 * i + e][l][3] = fbits(g == 0 ? -csin(p, 512) : ccos(p, 512), 23);
      }
      const int ka = t == 0 ? 8 : 2 * t, kb = 2 * t + 1;
      T.tw3[i][l][0] = fbits(ccos((4 * g + i) * ka, 512), 23);
      T.tw3[i][l][1] = fbits(csin((4 * g + i) * ka, 512), 23);
      T.tw3[i][l][2] = fbits(ccos((4 * g + i) * kb, 512), 23);
      T.tw3[i][l][3] = fbits(csin((4 * g + i) * kb, 512), 23);
      const int p8 = (t + 4 * (i & 1)) * (4 * (i >> 1) + (g >> 1));
      T.f8[l][i] = cfrag_c(p8, 8, g & 1);
      T.g8[l][i] = cfrag_c(-p8, 8, g & 1);
    }
    for (int w = 0; w < 8; w++)
      for (int i = 0; i < 16; i++) {
        const int kidx = t + 4 * (i & 1) + 8 * (i >> 3), nidx = 4 * ((i >> 1) & 3) + (g >> 1);
        T.f2[w][i >> 2][l][i & 3] = cfrag_c((8 * kidx + w) * nidx, 128, g & 1);
        T.g2[w][i >> 2][l][i & 3] = cfrag_c(-(8 * nidx + w) * kidx, 128, g & 1);
      }
    T.fa[l][0] = pkb(fa_elem(g, 2 * t), fa_elem(g, 2 * t + 1));
    T.fa[l][1] = pkb(fa_elem(g + 8, 2 * t), fa_elem(g + 8, 2 * t + 1));
    T.fa[l][2] = pkb(fa_elem(g, 2 * t + 8), fa_elem(g, 2 * t + 9));
    T.fa[l][3] = pkb(fa_elem(g + 8, 2 * t + 8), fa_elem(g + 8, 2 * t + 9));
    T.ga[l][0] = pkb(fa_elem(2 * t, g), fa_elem(2 * t + 1, g));
    T.ga[l][1] = pkb(fa_elem(2 * t, g + 8), fa_elem(2 * t + 1, g + 8));
    T.ga[l][2] = pkb(fa_elem(2 * t + 8, g), fa_elem(2 * t + 9, g));
    T.ga[l][3] = pkb(fa_elem(2 * t + 8, g + 8), fa_elem(2 * t + 9, g + 8));
  }
  return T;
}
__device__ const __align__(128) Tables g_tab = make_tables();

__device__ __forceinline__ void die() { asm volatile("st.global.u32 [%0], %1;" ::"l"(0ull), "r"(0) : "memory"); }
__device__ __forceinline__ uint32_t s2u(const void* p) { return (uint32_t)__cvta_generic_to_shared(p); }
__device__ __forceinline__ void mbar_init(uint32_t b, int c) { asm volatile("mbarrier.init.shared::cta.b64 [%0], %1;" ::"r"(b), "r"(c)); }
__device__ __forceinline__ void mbar_expect(uint32_t b, int bytes) {
  asm volatile("mbarrier.arrive.expect_tx.shared::cta.b64 _, [%0], %1;" ::"r"(b), "r"(bytes) : "memory");
}
__device__ __forceinline__ void mbar_arrive(uint32_t b) { asm volatile("mbarrier.arrive.shared::cta.b64 _, [%0];" ::"r"(b) : "memory"); }
__device__ __forceinline__ uint32_t mbar_try(uint32_t b, uint32_t parity) {
  uint32_t ok;
  asm volatile("{.reg .pred p; mbarrier.try_wait.parity.shared::cta.b64 p, [%1], %2; selp.u32 %0,1,0,p;}"
               : "=r"(ok) : "r"(b), "r"(parity) : "memory");
  return ok;
}
__device__ __forceinline__ void mbar_wait(uint32_t b, uint32_t parity = 0) {
  int it = 0;
#pragma unroll 1
  while (!mbar_try(b, parity))
    if (++it > SPIN_LIMIT) { die(); break; }
}
__device__ __forceinline__ void bar_sync(int id, int n) { asm volatile("bar.sync %0, %1;" ::"r"(id), "r"(n) : "memory"); }
__device__ __forceinline__ void bar_arrive(int id, int n) { asm volatile("bar.arrive %0, %1;" ::"r"(id), "r"(n) : "memory"); }
__device__ __forceinline__ void red_release(unsigned* p) { asm volatile("red.release.gpu.global.add.u32 [%0], 1;" ::"l"(p) : "memory"); }
__device__ __forceinline__ void red_relaxed(unsigned* p) { asm volatile("red.relaxed.gpu.global.add.u32 [%0], 1;" ::"l"(p) : "memory"); }
__device__ __forceinline__ unsigned ld_acquire(const unsigned* p) {
  unsigned v;
  asm volatile("ld.acquire.gpu.global.u32 %0, [%1];" : "=r"(v) : "l"(p) : "memory");
  return v;
}
__device__ __forceinline__ unsigned ld_relaxed(const unsigned* p) {
  unsigned v;
  asm volatile("ld.relaxed.gpu.global.u32 %0, [%1];" : "=r"(v) : "l"(p) : "memory");
  return v;
}
__device__ __forceinline__ void wait_counter(const unsigned* p, unsigned target) {
  int it = 0;
  while ((int)(ld_acquire(p) - target) < 0)
    if (++it > SPIN_LIMIT) { die(); break; }
}
__device__ __forceinline__ void sts4(uint32_t a, uint32_t x, uint32_t y, uint32_t z, uint32_t w) {
  asm volatile("st.shared.v4.u32 [%0], {%1,%2,%3,%4};" ::"r"(a), "r"(x), "r"(y), "r"(z), "r"(w) : "memory");
}
__device__ __forceinline__ uint4 lds4(uint32_t a) {
  uint4 v;
  asm volatile("ld.shared.v4.u32 {%0,%1,%2,%3}, [%4];" : "=r"(v.x), "=r"(v.y), "=r"(v.z), "=r"(v.w) : "r"(a) : "memory");
  return v;
}
__device__ __forceinline__ uint32_t pack2(float lo, float hi) {
  uint32_t r;
  asm("cvt.rn.bf16x2.f32 %0, %1, %2;" : "=r"(r) : "f"(hi), "f"(lo));
  return r;
}
__device__ __forceinline__ float bf_lo(uint32_t v) { return __uint_as_float(v << 16); }
__device__ __forceinline__ uint32_t hadd2_bf16(uint32_t a, uint32_t b) {
  uint32_t r;
  asm("add.rn.bf16x2 %0, %1, %2;" : "=r"(r) : "r"(a), "r"(b));
  return r;
}
__device__ __forceinline__ void mma16816(float (&d)[4], uint32_t a0, uint32_t a1, uint32_t a2, uint32_t a3, uint32_t b0, uint32_t b1) {
  asm("mma.sync.aligned.m16n8k16.row.col.f32.bf16.bf16.f32 {%0,%1,%2,%3}, {%4,%5,%6,%7}, {%8,%9}, {%0,%1,%2,%3};"
      : "+f"(d[0]), "+f"(d[1]), "+f"(d[2]), "+f"(d[3])
      : "r"(a0), "r"(a1), "r"(a2), "r"(a3), "r"(b0), "r"(b1));
}
template <int N>
__device__ __forceinline__ void cs_frac(int idx, float& c, float& s) {
  int i = ((idx + N / 2) & (N - 1)) - N / 2;
  float a = (float)i * (6.283185307179586f / N);
  c = __cosf(a);
  s = __sinf(a);
}
template <int N>
__device__ __forceinline__ uint32_t cfrag(int idx, int ri) {
  float c, s;
  cs_frac<N>(idx, c, s);
  return ri ? pack2(-s, c) : pack2(c, s);
}
__device__ __forceinline__ uint32_t word(const uint4& v, int e) { return e == 0 ? v.x : e == 1 ? v.y : e == 2 ? v.z : v.w; }
__device__ __forceinline__ void cdft16(const uint4 (&q)[4], const uint4 (&F)[4], uint4 (&o)[4]) {
  float acc[2][4][4];
#pragma unroll
  for (int p = 0; p < 2; p++)
#pragma unroll
    for (int v = 0; v < 4; v++) {
      acc[p][v][0] = acc[p][v][1] = acc[p][v][2] = acc[p][v][3] = 0.f;
#pragma unroll
      for (int ks = 0; ks < 2; ks++)
        mma16816(acc[p][v], word(q[2 * ks], 2 * p), word(q[2 * ks], 2 * p + 1), word(q[2 * ks + 1], 2 * p),
                 word(q[2 * ks + 1], 2 * p + 1), word(F[ks * 2 + (v >> 1)], (v & 1) * 2), word(F[ks * 2 + (v >> 1)], (v & 1) * 2 + 1));
    }
#pragma unroll
  for (int v = 0; v < 4; v++)
    o[v] = make_uint4(pack2(acc[0][v][0], acc[0][v][1]), pack2(acc[0][v][2], acc[0][v][3]),
                      pack2(acc[1][v][0], acc[1][v][1]), pack2(acc[1][v][2], acc[1][v][3]));
}
__device__ __forceinline__ void st_tag(uint4* p, const uint4& v, uint32_t tag) {
  asm volatile("{.reg .b128 r; .reg .b64 a, b; mov.b64 a, {%1,%2}; mov.b64 b, {%3,%4}; mov.b128 r, {a,b}; st.relaxed.gpu.global.b128 [%0], r;}"
               ::"l"(p), "r"((v.x & ~1u) | tag), "r"(v.y), "r"(v.z), "r"(v.w) : "memory");
}
__device__ __forceinline__ uint4 ld_b128(const uint4* p) {
  uint4 v;
  asm volatile("{.reg .b128 r; .reg .b64 a, b; ld.relaxed.gpu.global.b128 r, [%4]; mov.b128 {a,b}, r; mov.b64 {%0,%1}, a; mov.b64 {%2,%3}, b;}"
               : "=r"(v.x), "=r"(v.y), "=r"(v.z), "=r"(v.w) : "l"(p) : "memory");
  return v;
}
template <int STRIDE>
__device__ __forceinline__ void ld_tag4_issue(uint4 (&q)[4], const uint4* p) {
#pragma unroll
  for (int i = 0; i < 4; i++) q[i] = ld_b128(p + i * STRIDE);
}
template <int STRIDE>
__device__ __forceinline__ void ld_tag4_finish(uint4 (&q)[4], const uint4* p, uint32_t tag) {
  int it = 0;
#pragma unroll 1
  while (__any_sync(0xffffffffu, ((q[0].x ^ tag) | (q[1].x ^ tag) | (q[2].x ^ tag) | (q[3].x ^ tag)) & 1u)) {
    ld_tag4_issue<STRIDE>(q, p);
    if (++it > SPIN_LIMIT) { die(); break; }
  }
#pragma unroll
  for (int i = 0; i < 4; i++) asm volatile("and.b32 %0, %0, 0xfffffffe;" : "+r"(q[i].x));
}
__device__ __forceinline__ void row_stats(const uint32_t (&a)[8], const uint32_t (&b)[8], int lane, float (&sum)[2], float (&sq)[2]) {
  float da[4] = {0.f, 0.f, 0.f, 0.f}, db[4] = {0.f, 0.f, 0.f, 0.f}, ds[4] = {0.f, 0.f, 0.f, 0.f};
#pragma unroll
  for (int q = 0; q < 4; q++) {
    mma16816(ds, a[2 * q], b[2 * q], a[2 * q + 1], b[2 * q + 1], 0x3f803f80u, 0x3f803f80u);
    mma16816(da, a[2 * q], b[2 * q], a[2 * q + 1], b[2 * q + 1], a[2 * q], a[2 * q + 1]);
    mma16816(db, a[2 * q], b[2 * q], a[2 * q + 1], b[2 * q + 1], b[2 * q], b[2 * q + 1]);
  }
  const int src = (lane & 28) | (lane >> 3);
  const float qa = __shfl_sync(0xffffffffu, (lane & 4) ? da[1] : da[0], src);
  const float qb = __shfl_sync(0xffffffffu, (lane & 4) ? db[3] : db[2], src);
  float v = (lane & 2) ? ((lane & 1) ? ds[2] : ds[0]) : ((lane & 1) ? qb : qa);
  v += __shfl_xor_sync(0xffffffffu, v, 4);
  v += __shfl_xor_sync(0xffffffffu, v, 8);
  v += __shfl_xor_sync(0xffffffffu, v, 16);
  sq[0] = __shfl_sync(0xffffffffu, v, 0);
  sq[1] = __shfl_sync(0xffffffffu, v, 1);
  sum[0] = __shfl_sync(0xffffffffu, v, 2);
  sum[1] = __shfl_sync(0xffffffffu, v, 3);
}
__device__ __forceinline__ uint64_t desc64(uint32_t lo, uint32_t hi) {
  uint64_t d;
  asm("mov.b64 %0, {%1, %2};" : "=l"(d) : "r"(lo), "r"(hi));
  return d;
}
constexpr uint32_t desc_hi(uint32_t sbo, uint32_t swz) { return (sbo >> 4) | (swz << 30); }
__device__ __forceinline__ uint32_t desc_lo(uint32_t addr, uint32_t lbo) { return ((addr & 0x3FFFF) >> 4) | ((lbo >> 4) << 16); }
__device__ __forceinline__ void cp_async16(uint32_t dst, const void* src) {
  asm volatile("cp.async.cg.shared.global [%0], [%1], 16;" ::"r"(dst), "l"(src) : "memory");
}
__device__ __forceinline__ uint2 lds2(uint32_t a) {
  uint2 v;
  asm volatile("ld.shared.v2.u32 {%0,%1}, [%2];" : "=r"(v.x), "=r"(v.y) : "r"(a) : "memory");
  return v;
}
__device__ __forceinline__ uint32_t lds_u16(uint32_t a) {
  uint16_t v;
  asm volatile("ld.shared.u16 %0, [%1];" : "=h"(v) : "r"(a) : "memory");
  return v;
}
__device__ __forceinline__ void wg_fence() { asm volatile("wgmma.fence.sync.aligned;" ::: "memory"); }
__device__ __forceinline__ void wg_commit() { asm volatile("wgmma.commit_group.sync.aligned;" ::: "memory"); }
template <int N>
__device__ __forceinline__ void wg_wait() { asm volatile("wgmma.wait_group.sync.aligned %0;" ::"n"(N) : "memory"); }
__device__ __forceinline__ void bulk_load(uint32_t dst, const void* src, int bytes, uint32_t bar) {
  asm volatile("cp.async.bulk.shared::cluster.global.mbarrier::complete_tx::bytes [%0], [%1], %2, [%3];"
               ::"r"(dst), "l"(src), "r"(bytes), "r"(bar) : "memory");
}
__device__ __forceinline__ void bulk_load_mc(uint32_t dst, const void* src, int bytes, uint32_t bar) {
  asm volatile("cp.async.bulk.shared::cluster.global.mbarrier::complete_tx::bytes.multicast::cluster [%0], [%1], %2, [%3], %4;"
               ::"r"(dst), "l"(src), "r"(bytes), "r"(bar), "h"((uint16_t)3) : "memory");
}
__device__ __forceinline__ void tma3(uint32_t dst, const CUtensorMap* tm, uint32_t bar, int c0, int c1, int c2) {
  asm volatile("cp.async.bulk.tensor.3d.shared::cluster.global.mbarrier::complete_tx::bytes [%0], [%1, {%3,%4,%5}], [%2];"
               ::"r"(dst), "l"(tm), "r"(bar), "r"(c0), "r"(c1), "r"(c2) : "memory");
}
__device__ __forceinline__ void tma3_mc(uint32_t dst, const CUtensorMap* tm, uint32_t bar, int c1, int c2) {
  asm volatile("cp.async.bulk.tensor.3d.shared::cluster.global.mbarrier::complete_tx::bytes.multicast::cluster [%0], [%1, {%3,%4,%5}], [%2], %6;"
               ::"r"(dst), "l"(tm), "r"(bar), "r"(0), "r"(c1), "r"(c2), "h"((uint16_t)3) : "memory");
}
__device__ __forceinline__ void mbar_arrive_remote(uint32_t rb) {
  asm volatile("mbarrier.arrive.shared::cluster.b64 _, [%0];" ::"r"(rb) : "memory");
}
__device__ __forceinline__ uint4 ldg_ca4(const void* p) {
  uint4 v;
  asm volatile("ld.global.ca.v4.u32 {%0,%1,%2,%3}, [%4];" : "=r"(v.x), "=r"(v.y), "=r"(v.z), "=r"(v.w) : "l"(p) : "memory");
  return v;
}
__device__ __forceinline__ uint32_t clock32() {
  uint32_t v;
  asm volatile("mov.u32 %0, %%clock;" : "=r"(v) :: "memory");
  return v;
}
__device__ __forceinline__ float swiglu(float g, float u, float r) {
  float hg = (0.5f * r) * g, th;
  asm("tanh.approx.f32 %0, %1;" : "=f"(th) : "f"(hg));
  return fmaf(hg, th, hg) * (r * u);
}
__device__ __forceinline__ uint32_t hsub2_bf16(uint32_t a, uint32_t b) {
  uint32_t r;
  asm("sub.rn.bf16x2 %0, %1, %2;" : "=r"(r) : "r"(a), "r"(b));
  return r;
}
__device__ __forceinline__ void l2_prefetch(const void* p, int bytes) {
  asm volatile("cp.async.bulk.prefetch.L2.global [%0], %1;" ::"l"(p), "r"(bytes) : "memory");
}

__device__ __forceinline__ void wgmma_n256(float (&d)[128], uint64_t da, uint64_t db) {
  asm volatile("wgmma.mma_async.sync.aligned.m64n256k16.f32.bf16.bf16 {"
      "%0,%1,%2,%3,%4,%5,%6,%7,%8,%9,%10,%11,%12,%13,%14,%15,"
      "%16,%17,%18,%19,%20,%21,%22,%23,%24,%25,%26,%27,%28,%29,%30,%31,"
      "%32,%33,%34,%35,%36,%37,%38,%39,%40,%41,%42,%43,%44,%45,%46,%47,"
      "%48,%49,%50,%51,%52,%53,%54,%55,%56,%57,%58,%59,%60,%61,%62,%63,"
      "%64,%65,%66,%67,%68,%69,%70,%71,%72,%73,%74,%75,%76,%77,%78,%79,"
      "%80,%81,%82,%83,%84,%85,%86,%87,%88,%89,%90,%91,%92,%93,%94,%95,"
      "%96,%97,%98,%99,%100,%101,%102,%103,%104,%105,%106,%107,%108,%109,%110,%111,"
      "%112,%113,%114,%115,%116,%117,%118,%119,%120,%121,%122,%123,%124,%125,%126,%127"
      "}, %128, %129, 1, 1, 1, 0, 1;\n"
      : "+f"(d[0]),"+f"(d[1]),"+f"(d[2]),"+f"(d[3]),"+f"(d[4]),"+f"(d[5]),"+f"(d[6]),"+f"(d[7]),
        "+f"(d[8]),"+f"(d[9]),"+f"(d[10]),"+f"(d[11]),"+f"(d[12]),"+f"(d[13]),"+f"(d[14]),"+f"(d[15]),
        "+f"(d[16]),"+f"(d[17]),"+f"(d[18]),"+f"(d[19]),"+f"(d[20]),"+f"(d[21]),"+f"(d[22]),"+f"(d[23]),
        "+f"(d[24]),"+f"(d[25]),"+f"(d[26]),"+f"(d[27]),"+f"(d[28]),"+f"(d[29]),"+f"(d[30]),"+f"(d[31]),
        "+f"(d[32]),"+f"(d[33]),"+f"(d[34]),"+f"(d[35]),"+f"(d[36]),"+f"(d[37]),"+f"(d[38]),"+f"(d[39]),
        "+f"(d[40]),"+f"(d[41]),"+f"(d[42]),"+f"(d[43]),"+f"(d[44]),"+f"(d[45]),"+f"(d[46]),"+f"(d[47]),
        "+f"(d[48]),"+f"(d[49]),"+f"(d[50]),"+f"(d[51]),"+f"(d[52]),"+f"(d[53]),"+f"(d[54]),"+f"(d[55]),
        "+f"(d[56]),"+f"(d[57]),"+f"(d[58]),"+f"(d[59]),"+f"(d[60]),"+f"(d[61]),"+f"(d[62]),"+f"(d[63]),
        "+f"(d[64]),"+f"(d[65]),"+f"(d[66]),"+f"(d[67]),"+f"(d[68]),"+f"(d[69]),"+f"(d[70]),"+f"(d[71]),
        "+f"(d[72]),"+f"(d[73]),"+f"(d[74]),"+f"(d[75]),"+f"(d[76]),"+f"(d[77]),"+f"(d[78]),"+f"(d[79]),
        "+f"(d[80]),"+f"(d[81]),"+f"(d[82]),"+f"(d[83]),"+f"(d[84]),"+f"(d[85]),"+f"(d[86]),"+f"(d[87]),
        "+f"(d[88]),"+f"(d[89]),"+f"(d[90]),"+f"(d[91]),"+f"(d[92]),"+f"(d[93]),"+f"(d[94]),"+f"(d[95]),
        "+f"(d[96]),"+f"(d[97]),"+f"(d[98]),"+f"(d[99]),"+f"(d[100]),"+f"(d[101]),"+f"(d[102]),"+f"(d[103]),
        "+f"(d[104]),"+f"(d[105]),"+f"(d[106]),"+f"(d[107]),"+f"(d[108]),"+f"(d[109]),"+f"(d[110]),"+f"(d[111]),
        "+f"(d[112]),"+f"(d[113]),"+f"(d[114]),"+f"(d[115]),"+f"(d[116]),"+f"(d[117]),"+f"(d[118]),"+f"(d[119]),
        "+f"(d[120]),"+f"(d[121]),"+f"(d[122]),"+f"(d[123]),"+f"(d[124]),"+f"(d[125]),"+f"(d[126]),"+f"(d[127])
      : "l"(da), "l"(db));
}
__device__ __forceinline__ void wgmma_n192(float (&d)[96], uint64_t da, uint64_t db) {
  asm volatile("wgmma.mma_async.sync.aligned.m64n192k16.f32.bf16.bf16 {"
      "%0,%1,%2,%3,%4,%5,%6,%7,%8,%9,%10,%11,%12,%13,%14,%15,"
      "%16,%17,%18,%19,%20,%21,%22,%23,%24,%25,%26,%27,%28,%29,%30,%31,"
      "%32,%33,%34,%35,%36,%37,%38,%39,%40,%41,%42,%43,%44,%45,%46,%47,"
      "%48,%49,%50,%51,%52,%53,%54,%55,%56,%57,%58,%59,%60,%61,%62,%63,"
      "%64,%65,%66,%67,%68,%69,%70,%71,%72,%73,%74,%75,%76,%77,%78,%79,"
      "%80,%81,%82,%83,%84,%85,%86,%87,%88,%89,%90,%91,%92,%93,%94,%95"
      "}, %96, %97, 1, 1, 1, 0, 1;\n"
      : "+f"(d[0]),"+f"(d[1]),"+f"(d[2]),"+f"(d[3]),"+f"(d[4]),"+f"(d[5]),"+f"(d[6]),"+f"(d[7]),
        "+f"(d[8]),"+f"(d[9]),"+f"(d[10]),"+f"(d[11]),"+f"(d[12]),"+f"(d[13]),"+f"(d[14]),"+f"(d[15]),
        "+f"(d[16]),"+f"(d[17]),"+f"(d[18]),"+f"(d[19]),"+f"(d[20]),"+f"(d[21]),"+f"(d[22]),"+f"(d[23]),
        "+f"(d[24]),"+f"(d[25]),"+f"(d[26]),"+f"(d[27]),"+f"(d[28]),"+f"(d[29]),"+f"(d[30]),"+f"(d[31]),
        "+f"(d[32]),"+f"(d[33]),"+f"(d[34]),"+f"(d[35]),"+f"(d[36]),"+f"(d[37]),"+f"(d[38]),"+f"(d[39]),
        "+f"(d[40]),"+f"(d[41]),"+f"(d[42]),"+f"(d[43]),"+f"(d[44]),"+f"(d[45]),"+f"(d[46]),"+f"(d[47]),
        "+f"(d[48]),"+f"(d[49]),"+f"(d[50]),"+f"(d[51]),"+f"(d[52]),"+f"(d[53]),"+f"(d[54]),"+f"(d[55]),
        "+f"(d[56]),"+f"(d[57]),"+f"(d[58]),"+f"(d[59]),"+f"(d[60]),"+f"(d[61]),"+f"(d[62]),"+f"(d[63]),
        "+f"(d[64]),"+f"(d[65]),"+f"(d[66]),"+f"(d[67]),"+f"(d[68]),"+f"(d[69]),"+f"(d[70]),"+f"(d[71]),
        "+f"(d[72]),"+f"(d[73]),"+f"(d[74]),"+f"(d[75]),"+f"(d[76]),"+f"(d[77]),"+f"(d[78]),"+f"(d[79]),
        "+f"(d[80]),"+f"(d[81]),"+f"(d[82]),"+f"(d[83]),"+f"(d[84]),"+f"(d[85]),"+f"(d[86]),"+f"(d[87]),
        "+f"(d[88]),"+f"(d[89]),"+f"(d[90]),"+f"(d[91]),"+f"(d[92]),"+f"(d[93]),"+f"(d[94]),"+f"(d[95])
      : "l"(da), "l"(db));
}
__device__ __forceinline__ void wgmma_rs_n128(float (&d)[64], uint32_t a0, uint32_t a1, uint32_t a2, uint32_t a3, uint64_t db) {
  asm volatile("wgmma.mma_async.sync.aligned.m64n128k16.f32.bf16.bf16 {"
      "%0,%1,%2,%3,%4,%5,%6,%7,%8,%9,%10,%11,%12,%13,%14,%15,"
      "%16,%17,%18,%19,%20,%21,%22,%23,%24,%25,%26,%27,%28,%29,%30,%31,"
      "%32,%33,%34,%35,%36,%37,%38,%39,%40,%41,%42,%43,%44,%45,%46,%47,"
      "%48,%49,%50,%51,%52,%53,%54,%55,%56,%57,%58,%59,%60,%61,%62,%63"
      "}, {%64,%65,%66,%67}, %68, 1, 1, 1, 1;\n"
      : "+f"(d[0]),"+f"(d[1]),"+f"(d[2]),"+f"(d[3]),"+f"(d[4]),"+f"(d[5]),"+f"(d[6]),"+f"(d[7]),
        "+f"(d[8]),"+f"(d[9]),"+f"(d[10]),"+f"(d[11]),"+f"(d[12]),"+f"(d[13]),"+f"(d[14]),"+f"(d[15]),
        "+f"(d[16]),"+f"(d[17]),"+f"(d[18]),"+f"(d[19]),"+f"(d[20]),"+f"(d[21]),"+f"(d[22]),"+f"(d[23]),
        "+f"(d[24]),"+f"(d[25]),"+f"(d[26]),"+f"(d[27]),"+f"(d[28]),"+f"(d[29]),"+f"(d[30]),"+f"(d[31]),
        "+f"(d[32]),"+f"(d[33]),"+f"(d[34]),"+f"(d[35]),"+f"(d[36]),"+f"(d[37]),"+f"(d[38]),"+f"(d[39]),
        "+f"(d[40]),"+f"(d[41]),"+f"(d[42]),"+f"(d[43]),"+f"(d[44]),"+f"(d[45]),"+f"(d[46]),"+f"(d[47]),
        "+f"(d[48]),"+f"(d[49]),"+f"(d[50]),"+f"(d[51]),"+f"(d[52]),"+f"(d[53]),"+f"(d[54]),"+f"(d[55]),
        "+f"(d[56]),"+f"(d[57]),"+f"(d[58]),"+f"(d[59]),"+f"(d[60]),"+f"(d[61]),"+f"(d[62]),"+f"(d[63])
      : "r"(a0), "r"(a1), "r"(a2), "r"(a3), "l"(db));
}

constexpr int C_LN = 0, C_PX = 16, C_PY = 32;
constexpr int NB_CONS = 1, NB_LN = 2, NB_LAG = 4, NB_INIT = 6, NB_RDY = 7;
#define LAGX 3
#define LAGY 3
#define LAG2 4
#define NLL 2
#define POLL_DELAY3 900
#define POLL_DELAY 900
#define FILT_DELAY 1000
#define THR_B 0
#define THR_P 0
#define SPEC -1
#define RING_SIG 0
#define PF2_SIG 1
constexpr int SM_E = 0, SM_X = 16384, SM_E2 = 32768, SM_W = 49152, SM_FC = 69632, SM_T = 73728 - T1_BYTES;
constexpr unsigned long long KORDER = 0xBA9432DC876510ull;
constexpr unsigned long long BSLOT = 0x76532107653210ull, PSLOT = 0xDCBA984DCBA984ull;
constexpr uint32_t HI128 = desc_hi(1024, 1), HI64 = desc_hi(512, 2);

struct Bars {
  uint64_t full1[32], empty1[32], full2[16], fullA[8], empty2[8], fullP[16], emptyP[8], hbar, tbar, hint[3], sig[2], sbar;
  uint32_t epoch;
};

template <int NK, bool STORE>
__device__ __forceinline__ void make_p(const float (&acc)[NK * 16], float r0, float r1, uint4 (&p)[NK], uint4* pbase, int ks0, uint32_t tag) {
#pragma unroll
  for (int j = 0; j < NK; j++) {
    uint32_t w[4];
#pragma unroll
    for (int i = 0; i < 4; i++) {
      const int a = 8 * j + 2 * i, b = a + NK * 8;
      w[i] = pack2(swiglu(acc[a], acc[b], (i & 1) ? r1 : r0), swiglu(acc[a + 1], acc[b + 1], (i & 1) ? r1 : r0));
    }
    asm volatile("" : "+r"(w[0]), "+r"(w[1]), "+r"(w[2]), "+r"(w[3]));
    p[j] = make_uint4(w[0], w[1], w[2], w[3]);
    if (STORE) st_tag(pbase + ((ks0 + j) >> 2) * 1024 + ((ks0 + j) & 3) * 32, p[j], tag);
  }
}
__device__ __forceinline__ void spin_cycles(uint32_t n) {
  const uint32_t t0 = clock32();
  while (clock32() - t0 < n) {}
}

__global__ void __cluster_dims__(2, 1, 1) __launch_bounds__(NTHREADS, 1)
fused_kernel(const __nv_bfloat16* __restrict__ x, const Tables* __restrict__ tab, Scratch* __restrict__ scr,
             __nv_bfloat16* __restrict__ out, const char* __restrict__ wg_raw, const char* __restrict__ wu_raw,
             const char* __restrict__ wd_raw,
             const __grid_constant__ CUtensorMap tmWR, const __grid_constant__ CUtensorMap tmWI,
             const __grid_constant__ CUtensorMap tmGX, const __grid_constant__ CUtensorMap tmUX,
             const __grid_constant__ CUtensorMap tmGY, const __grid_constant__ CUtensorMap tmUY,
             const __grid_constant__ CUtensorMap tmD) {
  extern __shared__ __align__(1024) char smem_raw[];
  const uint32_t sbase = s2u(smem_raw);
  const uint32_t sbar = sbase + 14 * SLOT, sstat = sbar + 1280;
  const int tid = threadIdx.x, lane = tid & 31;
  const int c = blockIdx.x, rk = c & 1, f = (c >> 1) & 7, rb = 2 * (c >> 4) + rk;
  const int rb2 = 2 * (c >> 4) + (f >> 2), kh = (f >> 1) & 1, nq = 2 * (f & 1) + rk;
#define BAR(field, i) (sbar + (uint32_t)offsetof(Bars, field) + 8u * (i))
#define TOFF(field) (sbase + SM_T + (uint32_t)offsetof(Tables, field) + lane * 16)

  if (tid >= 256) {
    asm volatile("setmaxnreg.dec.sync.aligned.u32 56;");
    const int warp = __shfl_sync(0xffffffffu, tid >> 5, 0);
    if (lane == 0) {
      if (warp == 8) {
        if (sbase & 1023) die();
#pragma unroll
        for (int i = 0; i < 16; i++) mbar_init(BAR(emptyP, i), i < 7 ? 16 : i < 8 ? 8 : i < 13 ? 1 : i < 15 ? 8 : 32);
        mbar_expect(BAR(tbar, 0), T2_BYTES + 2 * 10240);
        mbar_expect(BAR(hbar, 0), 16384);
      } else if (warp == 9) {
#pragma unroll
        for (int i = 0; i < 32; i++) mbar_init(BAR(full1, i), 1);
#pragma unroll
        for (int i = 0; i < 32; i++) mbar_expect(BAR(full1, i), i < 16 ? 16384 : 12288);
      } else if (warp == 10) {
#pragma unroll
        for (int i = 0; i < 32; i++) mbar_init(BAR(empty1, i), 16);
#pragma unroll
        for (int i = 0; i < 14; i++) mbar_init(BAR(fullP, i), 1);
#pragma unroll
        for (int i = 0; i < 14; i++) mbar_expect(BAR(fullP, i), 16384);
      } else {
#pragma unroll
        for (int i = 0; i < 32; i++) mbar_init(BAR(full2, i), i < 24 ? 1 : 8);
#pragma unroll
        for (int i = 0; i < 24; i++) mbar_expect(BAR(full2, i), 16384);
      }
      asm volatile("fence.mbarrier_init.release.cluster;" ::: "memory");
    }
    if (tid == 256) {
      const int w0 = ((c >> 3) * 257 + 32 * (c & 7) + 1) & ~7;
      if (FILT_DELAY) {
        asm volatile("prefetch.tensormap [%0];" ::"l"(&tmWR) : "memory");
        asm volatile("prefetch.tensormap [%0];" ::"l"(&tmWI) : "memory");
        spin_cycles(FILT_DELAY);
      }
      tma3(sbase + SM_W, &tmWR, BAR(tbar, 0), w0, 0, 0);
      tma3(sbase + SM_W + 10240, &tmWI, BAR(tbar, 0), w0, 0, 0);
      bulk_load(sbase + SM_T + T1_BYTES, reinterpret_cast<const char*>(tab) + T1_BYTES, T2_BYTES, BAR(tbar, 0));
    }
    if (tid == 288) {
      asm volatile("prefetch.tensormap [%0];" ::"l"(rk ? &tmUX : &tmGX) : "memory");
      asm volatile("prefetch.tensormap [%0];" ::"l"(rk ? &tmUY : &tmGY) : "memory");
      asm volatile("prefetch.tensormap [%0];" ::"l"(&tmD) : "memory");
    }
    if (tid == 320) {
      const unsigned e = ld_relaxed(&scr->cnt[(C_LN + rb) * 32]) >> 3;
      asm volatile("st.shared.u32 [%0], %1;" ::"r"(BAR(epoch, 0)), "r"(e) : "memory");
    }
    __syncwarp();
    asm volatile("barrier.cluster.arrive.relaxed.aligned;" ::: "memory");
    bar_arrive(NB_RDY, 384);
    asm volatile("barrier.cluster.wait.aligned;" ::: "memory");
    bar_sync(NB_INIT, 384);
    unsigned epoch;
    asm volatile("ld.shared.u32 %0, [%1];" : "=r"(epoch) : "r"(BAR(epoch, 0)) : "memory");
    if (warp == 8) {
      if (lane == 0) {
        const int ax = (7 * f + 3 * (f & 1)) >> 1;
        const int ay = 7 * f + ((f & 1) ? 0 : 4);
        const CUtensorMap* tx = rk ? &tmUX : &tmGX;
        const CUtensorMap* ty = rk ? &tmUY : &tmGY;
        if (RING_SIG >= 0) mbar_wait(BAR(sig, RING_SIG));
        uint32_t s = 2;
#pragma unroll 1
        for (int n = 0; n < 16; n++) {
          if (n >= 6) mbar_wait(BAR(empty1, n - 6));
          tma3_mc(sbase + (8 + s) * SLOT + rk * 8192, tx, BAR(full1, n), n * 32, ax);
          if (++s == 6) s = 0;
        }
#pragma unroll 1
        for (int k = 0; k < 16; k++) {
          mbar_wait(BAR(empty1, k < 8 ? 10 + ((12 * k + 11) >> 4) : 8 + k));
          tma3_mc(sbase + 8 * SLOT + (k & 7) * 12288 + rk * 6144, ty, BAR(full1, 16 + k), k * 32, ay);
        }
      }
    } else if (warp == 9) {
      if (lane == 0) {
#pragma unroll 1
        for (int i = 0; i < 14; i++) {
          const int kblk = 14 * kh + (int)((KORDER >> (4 * i)) & 15);
          const int j = i < 7 ? i : i - 7, sl = j + (j >= 4);
          mbar_wait(i < 7 ? BAR(empty1, 17 + 2 * sl) : BAR(empty2, j));
          if (THR_B && i >= THR_B) mbar_wait(BAR(full2, i - THR_B));
          tma3(sbase + sl * SLOT, &tmD, BAR(full2, i), 0, 64 * kblk, 2 * nq);
        }
        wait_counter(&scr->cnt[(C_LN + rb2) * 32], (epoch + 1) * 8);
        asm volatile("fence.proxy.async.global;" ::: "memory");
        mbar_wait(BAR(emptyP, 7));
        bulk_load(sbase + 4 * SLOT, &scr->LN[(rb2 * 8 + 2 * nq) * 1024 + (kh ^ 1) * 512], 8192, BAR(hbar, 0));
        bulk_load(sbase + 4 * SLOT + 8192, &scr->LN[(rb2 * 8 + 2 * nq + 1) * 1024 + (kh ^ 1) * 512], 8192, BAR(hbar, 0));
      }
    } else if (warp == 10) {
      bar_sync(NB_LN, 288);
      if (lane == 0) {
        PROFP(0);
        red_release(&scr->cnt[(C_LN + rb) * 32]);
        PROFP(1);
        wait_counter(&scr->cnt[(C_LN + rb) * 32], (epoch + 1) * 8);
        asm volatile("fence.proxy.async.global;" ::: "memory");
        PROFP(2);
#pragma unroll 1
        for (int kb = NLL; kb < 8; kb++) bulk_load(sbase + kb * SLOT, &scr->LN[(rb * 8 + kb) * 1024], 16384, BAR(fullA, kb));
#pragma unroll 1
        for (int s = 0; s < 14; s++) {
          const int kblk = 14 * kh + (int)((KORDER >> (4 * s)) & 15);
          if (s == 0 || (SPEC < 0 && (s == 8 || s == 11))) {
            if (s != 11) PROFP(3 + (s >> 2));
            mbar_wait(BAR(hint, s == 0 ? 0 : s == 8 ? 1 : 2), 0);
            if (s != 11) PROFP(4 + (s >> 2));
          }
          const int j = s < 7 ? s : s - 7;
          mbar_wait(s < 7 ? BAR(empty1, 24 + s + (s == 0) + (s >= 4)) : BAR(emptyP, j));
          if (THR_P && s >= THR_P) mbar_wait(BAR(fullP, s - THR_P));
          if (SPEC >= 0 && s == 8) mbar_wait(BAR(emptyP, SPEC & 7));
          bulk_load_mc(sbase + (j ? 7 + j : 4) * SLOT + rk * 8192, &scr->P[(rb2 * 28 + kblk) * 1024 + rk * 512], 8192, BAR(fullP, s));
        }
        PROFP(7);
      }
    } else {
      if (lane == 0) {
        l2_prefetch(wg_raw + (size_t)c * 5376, 5376);
        l2_prefetch(wu_raw + (size_t)c * 5376, 5376);
        mbar_wait(BAR(sig, PF2_SIG), 0);
        l2_prefetch(wg_raw + 688128 + (size_t)c * 8960, 8960);
        l2_prefetch(wu_raw + 688128 + (size_t)c * 8960, 8960);
      }
      mbar_wait(BAR(fullA, 7), 0);
      if (lane == 0) l2_prefetch(wd_raw + (size_t)c * 14336, 14336);
      {
        const uint32_t tag = (epoch + 1) & 1;
        uint4 v0, v1, v2;
        int it = 0;
        while (true) {
          v0 = ld_b128(&scr->ST[rb * 64 + lane]);
          v1 = ld_b128(&scr->ST[rb * 64 + 32 + lane]);
          v2 = ld_b128(&scr->ST[rb2 * 64 + 32 * (kh ^ 1) + lane]);
          if (!__any_sync(0xffffffffu, ((v0.x ^ tag) | (v1.x ^ tag) | (v2.x ^ tag)) & 1u)) break;
          if (++it > SPIN_LIMIT) { die(); break; }
        }
        sts4(sstat + lane * 16, v0.x & ~1u, v0.y, v0.z, v0.w);
        sts4(sstat + 512 + lane * 16, v1.x & ~1u, v1.y, v1.z, v1.w);
        sts4(sstat + 1024 + lane * 16, v2.x & ~1u, v2.y, v2.z, v2.w);
        mbar_arrive(BAR(sbar, 0));
      }
      if (lane == 0) {
        mbar_wait(BAR(empty1, 17));
#pragma unroll 1
        for (int e = 0; e < (SPEC < 0 ? 3 : 1); e++) {
          const unsigned* cp = e == 0 ? &scr->cnt[(C_PX + rb2) * 32] : &scr->cnt[(C_PY + rb2) * 32 + 2 * kh + e - 1];
          if (e == 1) mbar_wait(BAR(fullP, 0), 0);
          int it = 0;
          while ((int)(ld_relaxed(cp) - (epoch + 1) * (e == 0 ? 64 : 16)) < 0)
            if (++it > SPIN_LIMIT) { die(); break; }
          mbar_arrive(BAR(hint, e));
        }
      }
    }
  } else {
    const int warp = __shfl_sync(0xffffffffu, tid >> 5, 0);
    const int g = lane >> 2, t = lane & 3;
    PROF(0);
    PROFG(14);
#pragma unroll
    for (int i = 0; i < 4; i++) {
      const int r = i >> 1, ch = (i & 1) * 32 + lane;
      cp_async16(sbase + SM_X + (2 * warp + r) * 1024 + ((ch ^ ((ch >> 2) & 6)) * 16),
                 x + (size_t)(c + 128 * (2 * warp + r)) * 512 + ch * 8);
    }
    asm volatile("cp.async.commit_group;" ::: "memory");
    asm volatile("barrier.cluster.arrive.relaxed.aligned;" ::: "memory");
    uint4 tw[8], fb[16];
    const uint4 fa = ldg_ca4(&tab->fa[lane][0]);
#pragma unroll
    for (int i = 0; i < 8; i++) tw[i] = ldg_ca4(&tab->tw1[i][lane][0]);
#pragma unroll
    for (int i = 0; i < 16; i++) fb[i] = ldg_ca4(&tab->fb[i][lane][0]);
    uint32_t rbar;
    asm volatile("mapa.shared::cluster.u32 %0, %1, %2;" : "=r"(rbar) : "r"(sbar), "r"(rk ^ 1));
#define RBAR(field, i) (rbar + (uint32_t)offsetof(Bars, field) + 8u * (i))
    {
      const int ln = (tid >> 1) & 31, lg = ln >> 2, lt = ln & 3, i = 4 * (tid >> 6) + 2 * (tid & 1);
      const int kidx = lt + 8 * (i >> 3), nidx = 4 * ((i >> 1) & 3) + (lg >> 1);
      const uint32_t a0 = cfrag<2048>((c + 128 * kidx) * nidx, lg & 1), a1 = cfrag<2048>((c + 128 * (kidx + 4)) * nidx, lg & 1);
      const uint32_t b0 = cfrag<2048>(-(c + 128 * nidx) * kidx, lg & 1), b1 = cfrag<2048>(-(c + 128 * nidx) * (kidx + 4), lg & 1);
      asm volatile("st.shared.v2.u32 [%0], {%1,%2};" ::"r"(sbase + SM_FC + tid * 8), "r"(a0), "r"(a1) : "memory");
      asm volatile("st.shared.v2.u32 [%0], {%1,%2};" ::"r"(sbase + SM_FC + 2048 + tid * 8), "r"(b0), "r"(b1) : "memory");
    }
    asm volatile("cp.async.wait_group 0;" ::: "memory");
    __syncwarp();
    bar_arrive(NB_INIT, 384);
    PROF(13);
    uint32_t tag;
    uint4 q[4], o[4];
    {
      uint32_t v[2][8];
#pragma unroll
      for (int r = 0; r < 2; r++)
#pragma unroll
        for (int q = 0; q < 4; q++) {
          const uint2 u = lds2(sbase + SM_X + (2 * warp + r) * 1024 + (t + 4 * (q >> 1)) * 128 + (((4 * (q & 1) + (g >> 1)) ^ (2 * t)) * 16) + (g & 1) * 8);
          v[r][2 * q] = u.x; v[r][2 * q + 1] = u.y;
        }
      float sum[2], sq[2], rstd[2];
      row_stats(v[0], v[1], lane, sum, sq);
#pragma unroll
      for (int r = 0; r < 2; r++) {
        const float m = sum[r] * (1.f / 512.f);
        rstd[r] = rsqrtf(fmaxf(fmaf(-m, m, sq[r] * (1.f / 512.f)), 0.f) + 1e-5f);
      }
      uint32_t alo[4][4], ahi[4][4];
#pragma unroll
      for (int r = 0; r < 2; r++)
#pragma unroll
        for (int i = 0; i < 4; i++) {
          const uint32_t sel = (i & 1) ? 0x7632u : 0x5410u;
          const uint32_t b0 = __byte_perm(v[r][i >> 1], v[r][2 + (i >> 1)], sel);
          const uint32_t b1 = __byte_perm(v[r][4 + (i >> 1)], v[r][6 + (i >> 1)], sel);
          float d[4] = {0.f, 0.f, 0.f, 0.f};
          mma16816(d, fa.x, fa.y, fa.z, fa.w, b0, b1);
          const uint4 &ka = tw[2 * i], &kb = tw[2 * i + 1];
          const uint32_t re = pack2(d[0] * __uint_as_float(ka.x) + d[2] * __uint_as_float(ka.y), d[1] * __uint_as_float(kb.x) + d[3] * __uint_as_float(kb.y));
          const uint32_t im = pack2(d[0] * __uint_as_float(ka.z) + d[2] * __uint_as_float(ka.w), d[1] * __uint_as_float(kb.z) + d[3] * __uint_as_float(kb.w));
          const uint32_t dc = pack2(fmaf(sum[r], -1.f / 32.f, d[0]), fmaf(sum[r], -1.f / 32.f, d[1]));
          alo[i][r] = re; alo[i][2 + r] = im;
          ahi[i][r] = g == 0 ? dc : re; ahi[i][2 + r] = g == 0 ? 0u : im;
        }
      float acc[8][4];
#pragma unroll
      for (int u = 0; u < 8; u++) {
        acc[u][0] = acc[u][1] = acc[u][2] = acc[u][3] = 0.f;
#pragma unroll
        for (int i = 0; i < 4; i++) {
          const uint4& bq = fb[i * 4 + (u >> 1)];
          if (u < 4) mma16816(acc[u], alo[i][0], alo[i][1], alo[i][2], alo[i][3], (u & 1) ? bq.z : bq.x, (u & 1) ? bq.w : bq.y);
          else       mma16816(acc[u], ahi[i][0], ahi[i][1], ahi[i][2], ahi[i][3], (u & 1) ? bq.z : bq.x, (u & 1) ? bq.w : bq.y);
        }
      }
#pragma unroll
      for (int r = 0; r < 2; r++)
#pragma unroll
        for (int h = 0; h < 2; h++) {
          const int j = 2 * warp + r, m = 2 * t + h;
          const float rs = rstd[r];
          sts4(sbase + SM_E + ((j * 8 + m) * 8 + (g ^ (2 * t) ^ (2 * (j & 3)))) * 16,
               pack2(acc[2 * h][2 * r] * rs, acc[2 * h][2 * r + 1] * rs), pack2(acc[2 * h + 1][2 * r] * rs, acc[2 * h + 1][2 * r + 1] * rs),
               pack2(acc[4 + 2 * h][2 * r] * rs, acc[4 + 2 * h][2 * r + 1] * rs), pack2(acc[5 + 2 * h][2 * r] * rs, acc[5 + 2 * h][2 * r + 1] * rs));
        }
      if (tid == 0) PROFP(12);
      bar_sync(NB_RDY, 384);
      if (tid == 0) PROFP(13);
      uint4 fc[4];
#pragma unroll
      for (int i = 0; i < 4; i++) fc[i] = lds4(sbase + SM_FC + i * 512 + lane * 16);
      asm volatile("ld.shared.u32 %0, [%1];" : "=r"(tag) : "r"(BAR(epoch, 0)) : "memory");
      tag = (tag + 1) & 1;
#pragma unroll
      for (int i = 0; i < 4; i++) q[i] = lds4(sbase + SM_E + (((t + 4 * i) * 8 + warp) * 8 + (g ^ (warp & 6) ^ (2 * t))) * 16);
      cdft16(q, fc, o);
#pragma unroll
      for (int vv = 0; vv < 4; vv++) st_tag(&scr->Z1[(((4 * vv + t) * 8 + warp) * 128 + c) * 8 + g], o[vv], tag);
    }
    PROF(1);
    {
      const uint4* const zp = &scr->Z1[(c * 128 + 8 * t + warp) * 8 + g];
      const uint32_t tst = clock32();
      mbar_wait(BAR(tbar, 0), 0);
      if (tid == 0) PROFP(14);
      uint4 f2[4], g2[4];
#pragma unroll
      for (int i = 0; i < 4; i++) {
        f2[i] = lds4(TOFF(f2) + warp * 2048 + i * 512);
        g2[i] = lds4(TOFF(g2) + warp * 2048 + i * 512);
      }
      const uint4 f8 = lds4(TOFF(f8)), g8 = lds4(TOFF(g8));
      float wfr[16], wfi[16];
      {
        const float fsc = 1.f / (1 << 19);
        const float fsc3 = ((c & 7) == 7 && g == 0) ? 0.5f * fsc : fsc;
        const int gg = g == 0 ? 8 : g, wsh = (2 * (c >> 3) + 2) & 15;
#pragma unroll
        for (int i = 0; i < 16; i++) {
          const int ci = i >> 3, dd = (i >> 2) & 1, e = i & 3;
          const int kk = (e == 0 ? gg : e == 1 ? 16 + gg : e == 2 ? 16 - g : 32 - g) - 1;
          const uint32_t a = sbase + SM_W + ((2 * warp + ci) * 8 + t + 4 * dd) * 80 + wsh + 2 * kk;
          wfr[i] = bf_lo(lds_u16(a)) * (e == 3 ? fsc3 : fsc);
          wfi[i] = bf_lo(lds_u16(a + 10240)) * (e == 3 ? fsc3 : fsc);
        }
      }
      asm volatile("barrier.cluster.wait.aligned;" ::: "memory");
      PROF(2);
      while (clock32() - tst < POLL_DELAY) {}
      ld_tag4_issue<256>(q, zp);
      ld_tag4_finish<256>(q, zp, tag);
      if (tid == 0) PROFP(30);
      if (lane == 0) mbar_arrive(BAR(sig, 0));
      cdft16(q, f2, o);
      const uint32_t e2 = sbase + SM_E2;
#pragma unroll
      for (int vv = 0; vv < 4; vv++)
        sts4(e2 + ((warp * 16 + 4 * vv + t) * 8 + (g ^ (2 * t) ^ (2 * (warp & 3)))) * 16, o[vv].x, o[vv].y, o[vv].z, o[vv].w);
      bar_sync(NB_CONS, 256);
#pragma unroll
      for (int ci = 0; ci < 2; ci++) {
        const int cc = 2 * warp + ci;
        uint32_t ad[2];
        uint4 u[2];
#pragma unroll
        for (int hh = 0; hh < 2; hh++) {
          ad[hh] = e2 + (((t + 4 * hh) * 16 + cc) * 8 + (g ^ (2 * (cc & 3)) ^ (2 * t))) * 16;
          u[hh] = lds4(ad[hh]);
        }
        uint32_t res[2][4];
#pragma unroll
        for (int p = 0; p < 2; p++) {
          uint32_t y[2][2];
#pragma unroll
          for (int vv = 0; vv < 2; vv++) {
            float d[4] = {0.f, 0.f, 0.f, 0.f};
            mma16816(d, word(u[0], 2 * p), word(u[0], 2 * p + 1), word(u[1], 2 * p), word(u[1], 2 * p + 1), word(f8, 2 * vv), word(f8, 2 * vv + 1));
#pragma unroll
            for (int rr = 0; rr < 2; rr++) {
              const float fr = wfr[ci * 8 + vv * 4 + 2 * p + rr], fi = wfi[ci * 8 + vv * 4 + 2 * p + rr];
              y[vv][rr] = pack2(d[2 * rr] * fr - d[2 * rr + 1] * fi, d[2 * rr] * fi + d[2 * rr + 1] * fr);
            }
          }
#pragma unroll
          for (int vv = 0; vv < 2; vv++) {
            float d[4] = {0.f, 0.f, 0.f, 0.f};
            mma16816(d, y[0][0], y[0][1], y[1][0], y[1][1], word(g8, 2 * vv), word(g8, 2 * vv + 1));
            res[vv][2 * p] = pack2(d[0], d[1]);
            res[vv][2 * p + 1] = pack2(d[2], d[3]);
          }
        }
#pragma unroll
        for (int vv = 0; vv < 2; vv++) sts4(ad[vv], res[vv][0], res[vv][1], res[vv][2], res[vv][3]);
      }
      bar_sync(NB_CONS, 256);
#pragma unroll
      for (int i = 0; i < 4; i++) q[i] = lds4(e2 + ((warp * 16 + 4 * i + t) * 8 + (g ^ (2 * t) ^ (2 * (warp & 3)))) * 16);
      cdft16(q, g2, o);
#pragma unroll
      for (int vv = 0; vv < 4; vv++) st_tag(&scr->Z2[((8 * (4 * vv + t) + warp) * 128 + c) * 8 + g], o[vv], tag);
    }
    PROF(3);
    {
      const uint4* const zp = &scr->Z2[((c * 16 + t) * 8 + warp) * 8 + g];
      const uint32_t tst = clock32();
      uint4 gb[16], gc[4], tw[4], xr[2][2];
#pragma unroll
      for (int i = 0; i < 16; i++) gb[i] = lds4(TOFF(gb) + i * 512);
      const uint4 ga = lds4(TOFF(ga));
#pragma unroll
      for (int i = 0; i < 4; i++) {
        gc[i] = lds4(sbase + SM_FC + 2048 + i * 512 + lane * 16);
        tw[i] = lds4(TOFF(tw3) + i * 512);
        const int ch = 4 * (g + 8 * (i & 1)) + t;
        xr[i >> 1][i & 1] = lds4(sbase + SM_X + (2 * warp + (i >> 1)) * 1024 + ((ch ^ ((ch >> 2) & 6)) * 16));
      }
      PROF(4);
      while (clock32() - tst < POLL_DELAY) {}
      ld_tag4_issue<256>(q, zp);
      ld_tag4_finish<256>(q, zp, tag);
      if (tid == 0) PROFP(31);
      if (lane == 0) mbar_arrive(BAR(sig, 1));
      cdft16(q, gc, o);
#pragma unroll
      for (int vv = 0; vv < 4; vv++)
        sts4(sbase + SM_E + (((4 * vv + t) * 8 + warp) * 8 + (g ^ (warp & 6) ^ (2 * t))) * 16, o[vv].x, o[vv].y, o[vv].z, o[vv].w);
      bar_sync(NB_CONS, 256);
      uint32_t hv[2][8];
      const float mk = t == 0 ? 0.f : 1.f;
#pragma unroll
      for (int r = 0; r < 2; r++) {
        const int j = 2 * warp + r;
        uint4 u[2];
#pragma unroll
        for (int h = 0; h < 2; h++) u[h] = lds4(sbase + SM_E + ((j * 8 + 2 * t + h) * 8 + (g ^ (2 * t) ^ (2 * (j & 3)))) * 16);
        float yv[4][4];
#pragma unroll
        for (int i = 0; i < 4; i++) {
          float lo[4] = {0.f, 0.f, 0.f, 0.f}, hi[4] = {0.f, 0.f, 0.f, 0.f};
          mma16816(lo, gb[i * 4].x, gb[i * 4].y, gb[i * 4].z, gb[i * 4].w, u[0].x, u[0].y);
          mma16816(lo, gb[i * 4 + 1].x, gb[i * 4 + 1].y, gb[i * 4 + 1].z, gb[i * 4 + 1].w, u[1].x, u[1].y);
          mma16816(hi, gb[i * 4 + 2].x, gb[i * 4 + 2].y, gb[i * 4 + 2].z, gb[i * 4 + 2].w, u[0].z, u[0].w);
          mma16816(hi, gb[i * 4 + 3].x, gb[i * 4 + 3].y, gb[i * 4 + 3].z, gb[i * 4 + 3].w, u[1].z, u[1].w);
          const float ca = __uint_as_float(tw[i].x), sa = __uint_as_float(tw[i].y), cb = __uint_as_float(tw[i].z), sb = __uint_as_float(tw[i].w);
          const float tr0 = fmaf(hi[0], mk, lo[0]), ti0 = fmaf(hi[2], mk, lo[2]);
          const float tr1 = lo[1] + hi[1], ti1 = lo[3] + hi[3];
          const float vr0 = tr0 * ca - ti0 * sa, vi0 = tr0 * sa + ti0 * ca;
          const float vr1 = tr1 * cb - ti1 * sb, vi1 = tr1 * sb + ti1 * cb;
          const uint32_t b0 = pack2(t == 0 ? hi[0] : vr0, vr1), b1 = pack2(t == 0 ? vr0 : vi0, vi1);
          yv[i][0] = yv[i][1] = yv[i][2] = yv[i][3] = 0.f;
          mma16816(yv[i], ga.x, ga.y, ga.z, ga.w, b0, b1);
        }
#pragma unroll
        for (int h = 0; h < 2; h++) {
          hv[r][4 * h + 0] = hadd2_bf16(xr[r][h].x, pack2(yv[0][2 * h], yv[1][2 * h]));
          hv[r][4 * h + 1] = hadd2_bf16(xr[r][h].y, pack2(yv[2][2 * h], yv[3][2 * h]));
          hv[r][4 * h + 2] = hadd2_bf16(xr[r][h].z, pack2(yv[0][2 * h + 1], yv[1][2 * h + 1]));
          hv[r][4 * h + 3] = hadd2_bf16(xr[r][h].w, pack2(yv[2][2 * h + 1], yv[3][2 * h + 1]));
        }
      }
      float ds[4] = {0.f, 0.f, 0.f, 0.f};
#pragma unroll
      for (int q4 = 0; q4 < 4; q4++) mma16816(ds, hv[0][2 * q4], hv[1][2 * q4], hv[0][2 * q4 + 1], hv[1][2 * q4 + 1], 0x3f803f80u, 0x3f803f80u);
#pragma unroll
      for (int o2 = 4; o2 <= 16; o2 <<= 1) {
        ds[0] += __shfl_xor_sync(0xffffffffu, ds[0], o2);
        ds[2] += __shfl_xor_sync(0xffffffffu, ds[2], o2);
      }
      uint32_t mb[2];
#pragma unroll
      for (int r = 0; r < 2; r++) {
        const int row = 16 * f + 2 * warp + r;
        mb[r] = pack2(ds[2 * r] * (1.f / 512.f), ds[2 * r] * (1.f / 512.f));
#pragma unroll
        for (int i = 0; i < 8; i++) hv[r][i] = hsub2_bf16(hv[r][i], mb[r]);
#pragma unroll
        for (int h = 0; h < 2; h++) {
          const int n1 = g + 8 * h;
          st_tag(&scr->LN[(rb * 8 + (n1 >> 1)) * 1024 + row * 8 + ((4 * (n1 & 1) + t) ^ (row & 7))],
                 make_uint4(hv[r][4 * h], hv[r][4 * h + 1], hv[r][4 * h + 2], hv[r][4 * h + 3]), n1 < 2 * NLL ? tag : (hv[r][4 * h] & 1u));
        }
      }
      bar_arrive(NB_LN, 288);
      float sum[2], sq[2], rstd[2];
      row_stats(hv[0], hv[1], lane, sum, sq);
#pragma unroll
      for (int r = 0; r < 2; r++) {
        const float m = sum[r] * (1.f / 512.f);
        rstd[r] = rsqrtf(fmaxf(fmaf(-m, m, sq[r] * (1.f / 512.f)), 0.f) + 1e-5f);
      }
      if (lane == 0)
        st_tag(&scr->ST[rb * 64 + 8 * f + warp], make_uint4(mb[0] << 16, __float_as_uint(rstd[0]), mb[1] << 16, __float_as_uint(rstd[1])), tag);
    }
    PROF(5);
    asm volatile("setmaxnreg.inc.sync.aligned.u32 224;");
    if (NLL) {
      const uint4* const ap = &scr->LN[rb * 8 * 1024 + tid];
      uint4 av[NLL ? NLL : 1][4];
      spin_cycles(POLL_DELAY3);
#pragma unroll
      for (int kb = 0; kb < NLL; kb++) ld_tag4_issue<256>(av[kb], ap + kb * 1024);
      bar_sync(NB_CONS, 256);
#pragma unroll
      for (int kb = 0; kb < NLL; kb++) {
        ld_tag4_finish<256>(av[kb], ap + kb * 1024, tag);
#pragma unroll
        for (int i = 0; i < 4; i++) sts4(sbase + kb * SLOT + (tid + 256 * i) * 16, av[kb][i].x, av[kb][i].y, av[kb][i].z, av[kb][i].w);
      }
      asm volatile("fence.proxy.async.shared::cta;" ::: "memory");
      bar_sync(NB_CONS, 256);
    }
    const int wgi = warp >> 2, wq = warp & 3;
    uint4* const pbase = &scr->P[rb * 28 * 1024 + warp * 128 + lane];
    const uint32_t a_lo0 = desc_lo(sbase + wgi * 8192, 16);
    const uint32_t ebar = lane == 0 ? BAR(empty1, 0) : RBAR(empty1, 0);
    float r0, r1;
    uint4 px[8], py[6];
    const int rh = wgi ^ kh ^ 1;
    const uint4* const psrc = &scr->P[(rb2 * 28 + 14 * kh) * 1024 + (4 * rh + wq) * 128 + lane];
    {
      float acc[128];
#pragma unroll
      for (int i = 0; i < 128; i++) acc[i] = 0.f;
      const uint32_t b_lo0 = desc_lo(sbase + 8 * SLOT, 4096);
      if (wgi == 0) {
#pragma unroll
        for (int i = 0; i < 8; i++) st_tag(&scr->XP[(c ^ 4) * 1024 + i * 128 + tid], make_uint4(0, 0, 0, 0), tag ^ 1);
      }
      uint32_t slot = 2;
#pragma unroll 1
      for (int kb = 0; kb < 8; kb++) {
        if (kb >= NLL) mbar_wait(BAR(fullA, kb), 0);
        if (kb == 0) PROF(6);
#pragma unroll
        for (int hh = 0; hh < 2; hh++) {
          if (LAGX && hh == ((16 - LAGX) & 1) && kb == ((16 - LAGX) >> 1) && wgi == 1) bar_sync(NB_LAG, 256);
          mbar_wait(BAR(full1, 2 * kb + hh));
          const uint32_t al = a_lo0 + kb * 1024 + hh * 4, bl = b_lo0 + slot * 1024;
          wg_fence();
          wgmma_n256(acc, desc64(al, HI128), desc64(bl, HI128));
          wgmma_n256(acc, desc64(al + 2, HI128), desc64(bl + 128, HI128));
          wg_commit();
          if (LAGX && hh == 1 && kb == 7 && wgi == 0) bar_arrive(NB_LAG, 256);
          wg_wait<1>();
          if ((kb | hh) != 0 && lane < 2) mbar_arrive_remote(ebar + 8 * (2 * kb + hh - 1));
          if (++slot == 6) slot = 0;
        }
      }
      mbar_wait(BAR(sbar, 0), 0);
      r0 = __uint_as_float(lds2(sstat + (16 * warp + g) * 8).y);
      r1 = __uint_as_float(lds2(sstat + (16 * warp + g + 8) * 8).y);
      wg_wait<0>();
      if (lane < 2) mbar_arrive_remote(ebar + 8 * 15);
      PROF(7);
      make_p<8, false>(acc, r0, r1, px, pbase, 0, tag);
    }
    PROF(8);
    {
      float acc[96];
#pragma unroll
      for (int i = 0; i < 96; i++) acc[i] = 0.f;
      const uint32_t b_lo0 = desc_lo(sbase + 8 * SLOT, 2048);
      uint4* const pdst = pbase + ((7 * f + 3 * (f & 1)) >> 1) * 1024;
      auto stage_y = [&](int k) {
        if (LAGY && k == 16 - LAGY && wgi == 1) bar_sync(NB_LAG, 256);
        mbar_wait(BAR(full1, 16 + k));
        const uint32_t al = a_lo0 + (k >> 1) * 1024 + (k & 1) * 4, bl = b_lo0 + (k & 7) * 768;
        wg_fence();
        wgmma_n192(acc, desc64(al, HI128), desc64(bl, HI64));
        wgmma_n192(acc, desc64(al + 2, HI128), desc64(bl + 64, HI64));
        wg_commit();
      };
#pragma unroll
      for (int k = 0; k < 4; k++) {
        stage_y(k);
        st_tag(pdst + (k >> 1) * 1024 + (k & 1) * 64, px[2 * k], tag);
        st_tag(pdst + (k >> 1) * 1024 + (k & 1) * 64 + 32, px[2 * k + 1], tag);
        if (k == 3 && lane == 0) red_relaxed(&scr->cnt[(C_PX + rb) * 32]);
        wg_wait<1>();
        if (k != 0 && lane < 2) mbar_arrive_remote(ebar + 8 * (15 + k));
      }
#pragma unroll 1
      for (int k = 4; k < 16; k++) {
        stage_y(k);
        if (LAGY && k == 15 && wgi == 0) bar_arrive(NB_LAG, 256);
        wg_wait<1>();
        if (lane < 2) mbar_arrive_remote(ebar + 8 * (15 + k));
      }
      wg_wait<0>();
      if (lane < 2) mbar_arrive_remote(ebar + 8 * 31);
      PROF(9);
      make_p<6, true>(acc, r0, r1, py, pbase, 14 * f + ((f & 1) ? 0 : 8), tag);
      if (lane == 0) red_relaxed(&scr->cnt[(C_PY + rb) * 32 + (f >> 1)]);
    }
    PROF(10);
    {
      float acc[64];
      {
        const float m0 = wgi ? 0.f : __uint_as_float(lds2(sstat + 1024 + (16 * wq + g) * 8).x);
        const float m1 = wgi ? 0.f : __uint_as_float(lds2(sstat + 1024 + (16 * wq + g + 8) * 8).x);
#pragma unroll
        for (int i = 0; i < 64; i++) acc[i] = (i & 2) ? m1 : m0;
      }
      const uint32_t b2_lo0 = desc_lo(sbase, 8192);
      const uint32_t pa0 = sbase + (4 * rh + wq) * 2048;
      const uint32_t pbar = ebar + (uint32_t)(offsetof(Bars, emptyP) - offsetof(Bars, empty1));
      uint4 fa[3][4];
      mbar_wait(BAR(fullP, 0));
#pragma unroll
      for (int kk = 0; kk < 4; kk++) fa[0][kk] = lds4(pa0 + 4 * SLOT + kk * 512 + lane * 16);
#pragma unroll
      for (int s = 0; s < 14; s++) {
        uint4 (&a)[4] = fa[s % 3];
        ld_tag4_finish<32>(a, psrc + (int)((KORDER >> (4 * s)) & 15) * 1024, tag);
        if (s < 8 && lane < (s < 7 ? 2 : 1)) mbar_arrive_remote(pbar + 8 * s);
        if (s >= 2) {
          wg_wait<1>();
          if (s <= 8 && lane == 0) mbar_arrive(BAR(empty2, s - 2));
        }
        if (s < 13) mbar_wait(BAR(fullP, s + 1));
        mbar_wait(BAR(full2, s));
        if (tid == 0) PROFP(16 + s);
        if (LAG2 && s == 14 - LAG2 && wgi == 1) bar_sync(NB_LAG, 256);
        const uint32_t bl = b2_lo0 + (uint32_t)((BSLOT >> (4 * s)) & 15) * 1024;
        wg_fence();
        if (s < 13) {
#pragma unroll
          for (int kk = 0; kk < 4; kk++)
            fa[(s + 1) % 3][kk] = lds4(pa0 + (uint32_t)((PSLOT >> (4 * (s + 1))) & 15) * SLOT + kk * 512 + lane * 16);
        }
#pragma unroll
        for (int kk = 0; kk < 4; kk++) wgmma_rs_n128(acc, a[kk].x, a[kk].y, a[kk].z, a[kk].w, desc64(bl + kk * 128, HI128));
        wg_commit();
      }
      if (LAG2 && wgi == 0) bar_arrive(NB_LAG, 256);
      uint4 pv[2][4];
      const uint4* const xsrc = &scr->XP[c * 1024 + (tid & 127)];
      if (wgi == 1) {
        ld_tag4_issue<128>(pv[0], xsrc);
        ld_tag4_issue<128>(pv[1], xsrc + 512);
      }
      wg_wait<0>();
      PROF(11);
#pragma unroll
      for (int h = 0; h < 2; h++)
#pragma unroll
        for (int q = 0; q < 4; q++)
          asm volatile("stmatrix.sync.aligned.m8n8.x4.shared.b16 [%0], {%1,%2,%3,%4};"
                       ::"r"(pa0 + (9 + h) * SLOT + (lane & 7) * 256 + (((4 * q + (lane >> 3)) ^ (lane & 7)) * 16)),
                         "r"(pack2(acc[16 * q + 2 * h], acc[16 * q + 2 * h + 1])), "r"(pack2(acc[16 * q + 4 + 2 * h], acc[16 * q + 5 + 2 * h])),
                         "r"(pack2(acc[16 * q + 8 + 2 * h], acc[16 * q + 9 + 2 * h])), "r"(pack2(acc[16 * q + 12 + 2 * h], acc[16 * q + 13 + 2 * h]))
                       : "memory");
      __syncwarp();
      uint4 w[8];
#pragma unroll
      for (int i = 0; i < 8; i++) {
        const int r = 2 * (i & 3) + (lane >> 4);
        w[i] = lds4(pa0 + (9 + (i >> 2)) * SLOT + r * 256 + (((lane & 15) ^ r) * 16));
      }
      uint4* dst;
      int dstr;
      if (wgi == 0) {
        mbar_wait(BAR(hbar, 0));
        const uint32_t hb = sbase + 4 * SLOT + ((lane >> 3) & 1) * 8192 + (16 * wq + (lane >> 4)) * 128;
#pragma unroll
        for (int i = 0; i < 8; i++) {
          pv[i >> 2][i & 3] = lds4(hb + i * 256 + (((lane & 7) ^ ((2 * i + (lane >> 4)) & 7)) * 16));
          if (2 * nq + ((lane >> 3) & 1) < NLL) pv[i >> 2][i & 3].x &= ~1u;
        }
        dst = &scr->XP[(c ^ 4) * 1024 + tid];
        dstr = 128;
      } else {
        ld_tag4_finish<128>(pv[0], xsrc, tag);
        ld_tag4_finish<128>(pv[1], xsrc + 512, tag);
        dst = reinterpret_cast<uint4*>(out) + (16 * (c >> 4) + 2 * (4 * rh + wq) + (rb2 & 1) + 128 * (lane >> 4)) * 64 + nq * 16 + (lane & 15);
        dstr = 256 * 64;
      }
#pragma unroll
      for (int i = 0; i < 8; i++) {
        const uint4& p = pv[i >> 2][i & 3];
        const uint4 v = make_uint4(hadd2_bf16(w[i].x, p.x), hadd2_bf16(w[i].y, p.y), hadd2_bf16(w[i].z, p.z), hadd2_bf16(w[i].w, p.w));
        st_tag(dst + i * dstr, v, wgi ? (v.x & 1u) : tag);
      }
      PROF(12);
      PROFG(15);
    }
  }
#undef BAR
#undef TOFF
#undef RBAR
}

typedef CUresult (*EncodeFn)(CUtensorMap*, CUtensorMapDataType, cuuint32_t, void*, const cuuint64_t*, const cuuint64_t*,
                             const cuuint32_t*, const cuuint32_t*, CUtensorMapInterleave, CUtensorMapSwizzle,
                             CUtensorMapL2promotion, CUtensorMapFloatOOBfill);

}

extern "C" void kernel_launch(void* const* d_in, const int* in_sizes, int n_in, void* d_out, int out_size) {
  (void)in_sizes; (void)n_in; (void)out_size;
  static EncodeFn encode = nullptr;
  static void *tab = nullptr, *scr = nullptr;
  if (!encode) {
    void* fn = nullptr;
    cudaDriverEntryPointQueryResult qr;
    cudaGetDriverEntryPoint("cuTensorMapEncodeTiled", &fn, cudaEnableDefault, &qr);
    encode = (EncodeFn)fn;
    cudaGetSymbolAddress(&tab, g_tab);
    cudaGetSymbolAddress(&scr, g_scr);
    cudaFuncSetAttribute(fused_kernel, cudaFuncAttributeMaxDynamicSharedMemorySize, SMEM_BYTES);
  }
  CUtensorMap tmGX, tmUX, tmGY, tmUY, tmD, tmWR, tmWI;
  const cuuint32_t es[5] = {1, 1, 1, 1, 1};
  auto enc = [&](CUtensorMap* m, void* p, int rank, const cuuint64_t* gd, const cuuint64_t* gs, const cuuint32_t* bd,
                 CUtensorMapSwizzle sw, CUtensorMapL2promotion pr) {
    encode(m, CU_TENSOR_MAP_DATA_TYPE_BFLOAT16, rank, p, gd, gs, bd, es, CU_TENSOR_MAP_INTERLEAVE_NONE, sw, pr,
           CU_TENSOR_MAP_FLOAT_OOB_FILL_NONE);
  };
  {
    const cuuint64_t gd[3] = {64, 512, 28}, gs[2] = {3584, 128};
    const cuuint32_t bd[3] = {64, 32, 2};
    enc(&tmGX, d_in[4], 3, gd, gs, bd, CU_TENSOR_MAP_SWIZZLE_128B, CU_TENSOR_MAP_L2_PROMOTION_L2_256B);
    enc(&tmUX, d_in[5], 3, gd, gs, bd, CU_TENSOR_MAP_SWIZZLE_128B, CU_TENSOR_MAP_L2_PROMOTION_L2_256B);
  }
  {
    const cuuint64_t gd[3] = {32, 512, 56}, gs[2] = {3584, 64};
    const cuuint32_t bd[3] = {32, 32, 3};
    enc(&tmGY, d_in[4], 3, gd, gs, bd, CU_TENSOR_MAP_SWIZZLE_64B, CU_TENSOR_MAP_L2_PROMOTION_L2_128B);
    enc(&tmUY, d_in[5], 3, gd, gs, bd, CU_TENSOR_MAP_SWIZZLE_64B, CU_TENSOR_MAP_L2_PROMOTION_L2_128B);
  }
  {
    const cuuint64_t gd[3] = {64, 1792, 8}, gs[2] = {1024, 128};
    const cuuint32_t bd[3] = {64, 64, 2};
    enc(&tmD, d_in[6], 3, gd, gs, bd, CU_TENSOR_MAP_SWIZZLE_128B, CU_TENSOR_MAP_L2_PROMOTION_L2_256B);
  }
  {
    const cuuint64_t gd[3] = {4112, 8, 16}, gs[2] = {16 * 8224, 8224};
    const cuuint32_t bd[3] = {40, 8, 16};
    enc(&tmWR, d_in[1], 3, gd, gs, bd, CU_TENSOR_MAP_SWIZZLE_NONE, CU_TENSOR_MAP_L2_PROMOTION_NONE);
    enc(&tmWI, d_in[2], 3, gd, gs, bd, CU_TENSOR_MAP_SWIZZLE_NONE, CU_TENSOR_MAP_L2_PROMOTION_NONE);
  }
  fused_kernel<<<NCTA, NTHREADS, SMEM_BYTES>>>((const __nv_bfloat16*)d_in[0], (const Tables*)tab, (Scratch*)scr,
                                               (__nv_bfloat16*)d_out, (const char*)d_in[4], (const char*)d_in[5],
                                               (const char*)d_in[6], tmWR, tmWI, tmGX, tmUX, tmGY, tmUY, tmD);
}
```

```cpp
#include <cuda_runtime.h>
#include <cuda_bf16.h>
#include <cuda.h>
#include <stdint.h>

namespace {

constexpr int NCTA = 128;
constexpr int NTHREADS = 384;
constexpr int SLOT = 16384;
constexpr int SMEM_BYTES = 14 * SLOT + 3072;
constexpr int SPIN_LIMIT = 1 << 22;

struct Scratch {
  uint4 Z1[128 * 1024];
  uint4 Z2[128 * 1024];
  uint4 LN[16 * 8 * 1024];
  uint4 P[16 * 28 * 1024];
  uint4 XP[128 * 1024];
  uint4 ST[1024];
  unsigned cnt[64 * 32];
};
__device__ __align__(1024) Scratch g_scr;
#define PROF(i)
#define PROFP(i)
#define PROFG(i)

constexpr double ccos(int i, int n) {
  i &= n - 1;
  if (i > n / 2) i = n - i;
  if (4 * i == n) return 0.0;
  const bool neg = 4 * i > n;
  if (neg) i = n / 2 - i;
  const double a = 6.283185307179586476925 * i / n, a2 = a * a;
  double term = 1.0, sum = 1.0;
  for (int k = 1; k < 14; k++) { term *= -a2 / ((2 * k - 1) * (2 * k)); sum += term; }
  return neg ? -sum : sum;
}
constexpr double csin(int i, int n) { return ccos(i - n / 4, n); }
constexpr unsigned fbits(double v, int mant) {
  if (v == 0.0) return 0;
  const unsigned sg = v < 0 ? 1u : 0u;
  if (v < 0) v = -v;
  int e = 127;
  while (v < 1.0) { v *= 2.0; e--; }
  const unsigned m = (unsigned)((v - 1.0) * (double)(1u << mant) + 0.5);
  return (sg << (8 + mant)) + ((unsigned)e << mant) + m;
}
constexpr unsigned pkb(double lo, double hi) { return fbits(lo, 7) | (fbits(hi, 7) << 16); }
constexpr double fa_elem(int kp, int n1) {
  return kp <= 8 ? ccos(kp * n1, 16) : -csin((kp - 8) * n1, 16);
}
constexpr unsigned cfrag_c(int idx, int n, int ri) {
  return ri ? pkb(-csin(idx, n), ccos(idx, n)) : pkb(ccos(idx, n), csin(idx, n));
}
struct Tables {
  unsigned fb[16][32][4];
  unsigned tw1[8][32][4];
  unsigned fa[32][4];
  unsigned f2[8][4][32][4];
  unsigned g2[8][4][32][4];
  unsigned gb[16][32][4];
  unsigned tw3[4][32][4];
  unsigned ga[32][4];
  unsigned f8[32][4], g8[32][4];
};
constexpr int T1_BYTES = 12800, T2_BYTES = 44544;
static_assert(sizeof(Tables) == T1_BYTES + T2_BYTES, "table size");
constexpr Tables make_tables() {
  Tables T = {};
  for (int l = 0; l < 32; l++) {
    const int g = l >> 2, t = l & 3;
    for (int i = 0; i < 4; i++)
      for (int u = 0; u < 8; u++) {
        const int ri = g & 1, m = 2 * (g >> 1) + ((u & 3) >> 1);
        const double sg = u >= 4 ? -1.0 : 1.0;
        const int k2 = u >= 4 ? 31 - 2 * m - (u & 1) : 2 * m + (u & 1);
        const int pa = (8 * t + i) * k2, pb = (8 * t + 4 + i) * k2;
        T.fb[i * 4 + (u >> 1)][l][(u & 1) * 2 + 0] = ri == 0 ? pkb(ccos(pa, 32), ccos(pb, 32)) : pkb(-sg * csin(pa, 32), -sg * csin(pb, 32));
        T.fb[i * 4 + (u >> 1)][l][(u & 1) * 2 + 1] = ri == 0 ? pkb(csin(pa, 32), csin(pb, 32)) : pkb(sg * ccos(pa, 32), sg * ccos(pb, 32));
      }
    for (int i = 0; i < 4; i++)
      for (int ks = 0; ks < 4; ks++) {
        const int n2 = 4 * g + i, m = 2 * t + (ks & 1);
        const double sg = ks >= 2 ? -1.0 : 1.0;
        const int pa = n2 * (ks >= 2 ? 31 - 2 * m : 2 * m), pb = n2 * (ks >= 2 ? 30 - 2 * m : 2 * m + 1);
        T.gb[i * 4 + ks][l][0] = pkb(ccos(pa, 32), -sg * csin(pa, 32));
        T.gb[i * 4 + ks][l][1] = pkb(csin(pa, 32), sg * ccos(pa, 32));
        T.gb[i * 4 + ks][l][2] = pkb(ccos(pb, 32), -sg * csin(pb, 32));
        T.gb[i * 4 + ks][l][3] = pkb(csin(pb, 32), sg * ccos(pb, 32));
      }
    for (int i = 0; i < 4; i++) {
      for (int e = 0; e < 2; e++) {
        const int p = (8 * t + 4 * e + i) * (g == 0 ? 8 : g);
        T.tw1[2 * i + e][l][0] = fbits(g == 0 ? 0.0 : ccos(p, 512), 23);
        T.tw1[2 * i + e][l][1] = fbits(g == 0 ? ccos(p, 512) : csin(p, 512), 23);
        T.tw1[2 * i + e][l][2] = fbits(g == 0 ? 0.0 : -csin(p, 512), 23);
        T.tw1[2 * i + e][l][3] = fbits(g == 0 ? -csin(p, 512) : ccos(p, 512), 23);
      }
      const int ka = t == 0 ? 8 : 2 * t, kb = 2 * t + 1;
      T.tw3[i][l][0] = fbits(ccos((4 * g + i) * ka, 512), 23);
      T.tw3[i][l][1] = fbits(csin((4 * g + i) * ka, 512), 23);
      T.tw3[i][l][2] = fbits(ccos((4 * g + i) * kb, 512), 23);
      T.tw3[i][l][3] = fbits(csin((4 * g + i) * kb, 512), 23);
      const int p8 = (t + 4 * (i & 1)) * (4 * (i >> 1) + (g >> 1));
      T.f8[l][i] = cfrag_c(p8, 8, g & 1);
      T.g8[l][i] = cfrag_c(-p8, 8, g & 1);
    }
    for (int w = 0; w < 8; w++)
      for (int i = 0; i < 16; i++) {
        const int kidx = t + 4 * (i & 1) + 8 * (i >> 3), nidx = 4 * ((i >> 1) & 3) + (g >> 1);
        T.f2[w][i >> 2][l][i & 3] = cfrag_c((8 * kidx + w) * nidx, 128, g & 1);
        T.g2[w][i >> 2][l][i & 3] = cfrag_c(-(8 * nidx + w) * kidx, 128, g & 1);
      }
    T.fa[l][0] = pkb(fa_elem(g, 2 * t), fa_elem(g, 2 * t + 1));
    T.fa[l][1] = pkb(fa_elem(g + 8, 2 * t), fa_elem(g + 8, 2 * t + 1));
    T.fa[l][2] = pkb(fa_elem(g, 2 * t + 8), fa_elem(g, 2 * t + 9));
    T.fa[l][3] = pkb(fa_elem(g + 8, 2 * t + 8), fa_elem(g + 8, 2 * t + 9));
    T.ga[l][0] = pkb(fa_elem(2 * t, g), fa_elem(2 * t + 1, g));
    T.ga[l][1] = pkb(fa_elem(2 * t, g + 8), fa_elem(2 * t + 1, g + 8));
    T.ga[l][2] = pkb(fa_elem(2 * t + 8, g), fa_elem(2 * t + 9, g));
    T.ga[l][3] = pkb(fa_elem(2 * t + 8, g + 8), fa_elem(2 * t + 9, g + 8));
  }
  return T;
}
__device__ const __align__(128) Tables g_tab = make_tables();

__device__ __forceinline__ void die() { asm volatile("st.global.u32 [%0], %1;" ::"l"(0ull), "r"(0) : "memory"); }
__device__ __forceinline__ uint32_t s2u(const void* p) { return (uint32_t)__cvta_generic_to_shared(p); }
__device__ __forceinline__ void mbar_init(uint32_t b, int c) { asm volatile("mbarrier.init.shared::cta.b64 [%0], %1;" ::"r"(b), "r"(c)); }
__device__ __forceinline__ void mbar_expect(uint32_t b, int bytes) {
  asm volatile("mbarrier.arrive.expect_tx.shared::cta.b64 _, [%0], %1;" ::"r"(b), "r"(bytes) : "memory");
}
__device__ __forceinline__ void mbar_arrive(uint32_t b) { asm volatile("mbarrier.arrive.shared::cta.b64 _, [%0];" ::"r"(b) : "memory"); }
__device__ __forceinline__ uint32_t mbar_try(uint32_t b, uint32_t parity) {
  uint32_t ok;
  asm volatile("{.reg .pred p; mbarrier.try_wait.parity.shared::cta.b64 p, [%1], %2; selp.u32 %0,1,0,p;}"
               : "=r"(ok) : "r"(b), "r"(parity) : "memory");
  return ok;
}
__device__ __forceinline__ uint32_t mbar_test(uint32_t b) {
  uint32_t ok;
  asm volatile("{.reg .pred p; mbarrier.test_wait.parity.shared::cta.b64 p, [%1], 0; selp.u32 %0,1,0,p;}" : "=r"(ok) : "r"(b) : "memory");
  return ok;
}
__device__ __forceinline__ void mbar_wait(uint32_t b, uint32_t parity = 0) {
  int it = 0;
#pragma unroll 1
  while (!mbar_try(b, parity))
    if (++it > SPIN_LIMIT) { die(); break; }
}
__device__ __forceinline__ void bar_sync(int id, int n) { asm volatile("bar.sync %0, %1;" ::"r"(id), "r"(n) : "memory"); }
__device__ __forceinline__ void bar_arrive(int id, int n) { asm volatile("bar.arrive %0, %1;" ::"r"(id), "r"(n) : "memory"); }
__device__ __forceinline__ void red_release(unsigned* p) { asm volatile("red.release.gpu.global.add.u32 [%0], 1;" ::"l"(p) : "memory"); }
__device__ __forceinline__ void red_relaxed(unsigned* p) { asm volatile("red.relaxed.gpu.global.add.u32 [%0], 1;" ::"l"(p) : "memory"); }
__device__ __forceinline__ unsigned ld_acquire(const unsigned* p) {
  unsigned v;
  asm volatile("ld.acquire.gpu.global.u32 %0, [%1];" : "=r"(v) : "l"(p) : "memory");
  return v;
}
__device__ __forceinline__ unsigned ld_relaxed(const unsigned* p) {
  unsigned v;
  asm volatile("ld.relaxed.gpu.global.u32 %0, [%1];" : "=r"(v) : "l"(p) : "memory");
  return v;
}
__device__ __forceinline__ void wait_counter(const unsigned* p, unsigned target) {
  int it = 0;
  while ((int)(ld_acquire(p) - target) < 0)
    if (++it > SPIN_LIMIT) { die(); break; }
}
__device__ __forceinline__ void sts4(uint32_t a, uint32_t x, uint32_t y, uint32_t z, uint32_t w) {
  asm volatile("st.shared.v4.u32 [%0], {%1,%2,%3,%4};" ::"r"(a), "r"(x), "r"(y), "r"(z), "r"(w) : "memory");
}
__device__ __forceinline__ uint4 lds4(uint32_t a) {
  uint4 v;
  asm volatile("ld.shared.v4.u32 {%0,%1,%2,%3}, [%4];" : "=r"(v.x), "=r"(v.y), "=r"(v.z), "=r"(v.w) : "r"(a) : "memory");
  return v;
}
__device__ __forceinline__ uint32_t pack2(float lo, float hi) {
  uint32_t r;
  asm("cvt.rn.bf16x2.f32 %0, %1, %2;" : "=r"(r) : "f"(hi), "f"(lo));
  return r;
}
__device__ __forceinline__ float bf_lo(uint32_t v) { return __uint_as_float(v << 16); }
__device__ __forceinline__ uint32_t hadd2_bf16(uint32_t a, uint32_t b) {
  uint32_t r;
  asm("add.rn.bf16x2 %0, %1, %2;" : "=r"(r) : "r"(a), "r"(b));
  return r;
}
__device__ __forceinline__ void mma16816(float (&d)[4], uint32_t a0, uint32_t a1, uint32_t a2, uint32_t a3, uint32_t b0, uint32_t b1) {
  asm("mma.sync.aligned.m16n8k16.row.col.f32.bf16.bf16.f32 {%0,%1,%2,%3}, {%4,%5,%6,%7}, {%8,%9}, {%0,%1,%2,%3};"
      : "+f"(d[0]), "+f"(d[1]), "+f"(d[2]), "+f"(d[3])
      : "r"(a0), "r"(a1), "r"(a2), "r"(a3), "r"(b0), "r"(b1));
}
template <int N>
__device__ __forceinline__ void cs_frac(int idx, float& c, float& s) {
  int i = ((idx + N / 2) & (N - 1)) - N / 2;
  float a = (float)i * (6.283185307179586f / N);
  c = __cosf(a);
  s = __sinf(a);
}
template <int N>
__device__ __forceinline__ uint32_t cfrag(int idx, int ri) {
  float c, s;
  cs_frac<N>(idx, c, s);
  return ri ? pack2(-s, c) : pack2(c, s);
}
__device__ __forceinline__ uint32_t word(const uint4& v, int e) { return e == 0 ? v.x : e == 1 ? v.y : e == 2 ? v.z : v.w; }
__device__ __forceinline__ void cdft16(const uint4 (&q)[4], const uint4 (&F)[4], uint4 (&o)[4]) {
  float acc[2][4][4];
#pragma unroll
  for (int p = 0; p < 2; p++)
#pragma unroll
    for (int v = 0; v < 4; v++) {
      acc[p][v][0] = acc[p][v][1] = acc[p][v][2] = acc[p][v][3] = 0.f;
#pragma unroll
      for (int ks = 0; ks < 2; ks++)
        mma16816(acc[p][v], word(q[2 * ks], 2 * p), word(q[2 * ks], 2 * p + 1), word(q[2 * ks + 1], 2 * p),
                 word(q[2 * ks + 1], 2 * p + 1), word(F[ks * 2 + (v >> 1)], (v & 1) * 2), word(F[ks * 2 + (v >> 1)], (v & 1) * 2 + 1));
    }
#pragma unroll
  for (int v = 0; v < 4; v++)
    o[v] = make_uint4(pack2(acc[0][v][0], acc[0][v][1]), pack2(acc[0][v][2], acc[0][v][3]),
                      pack2(acc[1][v][0], acc[1][v][1]), pack2(acc[1][v][2], acc[1][v][3]));
}
__device__ __forceinline__ void st_tag(uint4* p, const uint4& v, uint32_t tag) {
  asm volatile("{.reg .b128 r; .reg .b64 a, b; mov.b64 a, {%1,%2}; mov.b64 b, {%3,%4}; mov.b128 r, {a,b}; st.relaxed.gpu.global.b128 [%0], r;}"
               ::"l"(p), "r"((v.x & ~1u) | tag), "r"(v.y), "r"(v.z), "r"(v.w) : "memory");
}
__device__ __forceinline__ void st_tag_pred(uint4* p, const uint4& v, uint32_t tag, bool en) {
  asm volatile("{.reg .b128 r; .reg .b64 a, b; .reg .pred q; setp.ne.b32 q, %5, 0; mov.b64 a, {%1,%2}; mov.b64 b, {%3,%4}; mov.b128 r, {a,b};\n"
               "@q st.relaxed.gpu.global.b128 [%0], r;}"
               ::"l"(p), "r"((v.x & ~1u) | tag), "r"(v.y), "r"(v.z), "r"(v.w), "r"((int)en) : "memory");
}
__device__ __forceinline__ uint4 ld_b128(const uint4* p) {
  uint4 v;
  asm volatile("{.reg .b128 r; .reg .b64 a, b; ld.relaxed.gpu.global.b128 r, [%4]; mov.b128 {a,b}, r; mov.b64 {%0,%1}, a; mov.b64 {%2,%3}, b;}"
               : "=r"(v.x), "=r"(v.y), "=r"(v.z), "=r"(v.w) : "l"(p) : "memory");
  return v;
}
template <int STRIDE>
__device__ __forceinline__ void ld_tag4_issue(uint4 (&q)[4], const uint4* p) {
#pragma unroll
  for (int i = 0; i < 4; i++) q[i] = ld_b128(p + i * STRIDE);
}
template <int STRIDE>
__device__ __forceinline__ void ld_tag4_finish(uint4 (&q)[4], const uint4* p, uint32_t tag) {
  int it = 0;
#pragma unroll 1
  while (__any_sync(0xffffffffu, ((q[0].x ^ tag) | (q[1].x ^ tag) | (q[2].x ^ tag) | (q[3].x ^ tag)) & 1u)) {
    ld_tag4_issue<STRIDE>(q, p);
    if (++it > SPIN_LIMIT) { die(); break; }
  }
#pragma unroll
  for (int i = 0; i < 4; i++) asm volatile("and.b32 %0, %0, 0xfffffffe;" : "+r"(q[i].x));
}
__device__ __forceinline__ void row_stats(const uint32_t (&a)[8], const uint32_t (&b)[8], int lane, float (&sum)[2], float (&sq)[2]) {
  float da[4] = {0.f, 0.f, 0.f, 0.f}, db[4] = {0.f, 0.f, 0.f, 0.f}, ds[4] = {0.f, 0.f, 0.f, 0.f};
#pragma unroll
  for (int q = 0; q < 4; q++) {
    mma16816(ds, a[2 * q], b[2 * q], a[2 * q + 1], b[2 * q + 1], 0x3f803f80u, 0x3f803f80u);
    mma16816(da, a[2 * q], b[2 * q], a[2 * q + 1], b[2 * q + 1], a[2 * q], a[2 * q + 1]);
    mma16816(db, a[2 * q], b[2 * q], a[2 * q + 1], b[2 * q + 1], b[2 * q], b[2 * q + 1]);
  }
  const int src = (lane & 28) | (lane >> 3);
  const float qa = __shfl_sync(0xffffffffu, (lane & 4) ? da[1] : da[0], src);
  const float qb = __shfl_sync(0xffffffffu, (lane & 4) ? db[3] : db[2], src);
  float v = (lane & 2) ? ((lane & 1) ? ds[2] : ds[0]) : ((lane & 1) ? qb : qa);
  v += __shfl_xor_sync(0xffffffffu, v, 4);
  v += __shfl_xor_sync(0xffffffffu, v, 8);
  v += __shfl_xor_sync(0xffffffffu, v, 16);
  sq[0] = __shfl_sync(0xffffffffu, v, 0);
  sq[1] = __shfl_sync(0xffffffffu, v, 1);
  sum[0] = __shfl_sync(0xffffffffu, v, 2);
  sum[1] = __shfl_sync(0xffffffffu, v, 3);
}
__device__ __forceinline__ uint64_t desc64(uint32_t lo, uint32_t hi) {
  uint64_t d;
  asm("mov.b64 %0, {%1, %2};" : "=l"(d) : "r"(lo), "r"(hi));
  return d;
}
constexpr uint32_t desc_hi(uint32_t sbo, uint32_t swz) { return (sbo >> 4) | (swz << 30); }
__device__ __forceinline__ uint32_t desc_lo(uint32_t addr, uint32_t lbo) { return ((addr & 0x3FFFF) >> 4) | ((lbo >> 4) << 16); }
__device__ __forceinline__ void cp_async16(uint32_t dst, const void* src) {
  asm volatile("cp.async.cg.shared.global [%0], [%1], 16;" ::"r"(dst), "l"(src) : "memory");
}
__device__ __forceinline__ uint2 lds2(uint32_t a) {
  uint2 v;
  asm volatile("ld.shared.v2.u32 {%0,%1}, [%2];" : "=r"(v.x), "=r"(v.y) : "r"(a) : "memory");
  return v;
}
__device__ __forceinline__ uint32_t lds_u16(uint32_t a) {
  uint16_t v;
  asm volatile("ld.shared.u16 %0, [%1];" : "=h"(v) : "r"(a) : "memory");
  return v;
}
__device__ __forceinline__ void wg_fence() { asm volatile("wgmma.fence.sync.aligned;" ::: "memory"); }
__device__ __forceinline__ void wg_commit() { asm volatile("wgmma.commit_group.sync.aligned;" ::: "memory"); }
template <int N>
__device__ __forceinline__ void wg_wait() { asm volatile("wgmma.wait_group.sync.aligned %0;" ::"n"(N) : "memory"); }
__device__ __forceinline__ void bulk_load(uint32_t dst, const void* src, int bytes, uint32_t bar) {
  asm volatile("cp.async.bulk.shared::cluster.global.mbarrier::complete_tx::bytes [%0], [%1], %2, [%3];"
               ::"r"(dst), "l"(src), "r"(bytes), "r"(bar) : "memory");
}
__device__ __forceinline__ void bulk_load_mc(uint32_t dst, const void* src, int bytes, uint32_t bar) {
  asm volatile("cp.async.bulk.shared::cluster.global.mbarrier::complete_tx::bytes.multicast::cluster [%0], [%1], %2, [%3], %4;"
               ::"r"(dst), "l"(src), "r"(bytes), "r"(bar), "h"((uint16_t)3) : "memory");
}
__device__ __forceinline__ void tma3(uint32_t dst, const CUtensorMap* tm, uint32_t bar, int c0, int c1, int c2) {
  asm volatile("cp.async.bulk.tensor.3d.shared::cluster.global.mbarrier::complete_tx::bytes [%0], [%1, {%3,%4,%5}], [%2];"
               ::"r"(dst), "l"(tm), "r"(bar), "r"(c0), "r"(c1), "r"(c2) : "memory");
}
__device__ __forceinline__ void tma3_mc(uint32_t dst, const CUtensorMap* tm, uint32_t bar, int c1, int c2) {
  asm volatile("cp.async.bulk.tensor.3d.shared::cluster.global.mbarrier::complete_tx::bytes.multicast::cluster [%0], [%1, {%3,%4,%5}], [%2], %6;"
               ::"r"(dst), "l"(tm), "r"(bar), "r"(0), "r"(c1), "r"(c2), "h"((uint16_t)3) : "memory");
}
__device__ __forceinline__ void mbar_arrive_remote(uint32_t rb) {
  asm volatile("mbarrier.arrive.shared::cluster.b64 _, [%0];" ::"r"(rb) : "memory");
}
__device__ __forceinline__ uint4 ldg_ca4(const void* p) {
  uint4 v;
  asm volatile("ld.global.ca.v4.u32 {%0,%1,%2,%3}, [%4];" : "=r"(v.x), "=r"(v.y), "=r"(v.z), "=r"(v.w) : "l"(p) : "memory");
  return v;
}
__device__ __forceinline__ uint32_t clock32() {
  uint32_t v;
  asm volatile("mov.u32 %0, %%clock;" : "=r"(v) :: "memory");
  return v;
}
__device__ __forceinline__ float swiglu(float g, float u, float r) {
  float hg = (0.5f * r) * g, th;
  asm("tanh.approx.f32 %0, %1;" : "=f"(th) : "f"(hg));
  return fmaf(hg, th, hg) * (r * u);
}
__device__ __forceinline__ uint32_t hsub2_bf16(uint32_t a, uint32_t b) {
  uint32_t r;
  asm("sub.rn.bf16x2 %0, %1, %2;" : "=r"(r) : "r"(a), "r"(b));
  return r;
}
__device__ __forceinline__ void l2_prefetch(const void* p, int bytes) {
  asm volatile("cp.async.bulk.prefetch.L2.global [%0], %1;" ::"l"(p), "r"(bytes) : "memory");
}

__device__ __forceinline__ void wgmma_n256(float (&d)[128], uint64_t da, uint64_t db) {
  asm volatile("wgmma.mma_async.sync.aligned.m64n256k16.f32.bf16.bf16 {"
      "%0,%1,%2,%3,%4,%5,%6,%7,%8,%9,%10,%11,%12,%13,%14,%15,"
      "%16,%17,%18,%19,%20,%21,%22,%23,%24,%25,%26,%27,%28,%29,%30,%31,"
      "%32,%33,%34,%35,%36,%37,%38,%39,%40,%41,%42,%43,%44,%45,%46,%47,"
      "%48,%49,%50,%51,%52,%53,%54,%55,%56,%57,%58,%59,%60,%61,%62,%63,"
      "%64,%65,%66,%67,%68,%69,%70,%71,%72,%73,%74,%75,%76,%77,%78,%79,"
      "%80,%81,%82,%83,%84,%85,%86,%87,%88,%89,%90,%91,%92,%93,%94,%95,"
      "%96,%97,%98,%99,%100,%101,%102,%103,%104,%105,%106,%107,%108,%109,%110,%111,"
      "%112,%113,%114,%115,%116,%117,%118,%119,%120,%121,%122,%123,%124,%125,%126,%127"
      "}, %128, %129, 1, 1, 1, 0, 1;\n"
      : "+f"(d[0]),"+f"(d[1]),"+f"(d[2]),"+f"(d[3]),"+f"(d[4]),"+f"(d[5]),"+f"(d[6]),"+f"(d[7]),
        "+f"(d[8]),"+f"(d[9]),"+f"(d[10]),"+f"(d[11]),"+f"(d[12]),"+f"(d[13]),"+f"(d[14]),"+f"(d[15]),
        "+f"(d[16]),"+f"(d[17]),"+f"(d[18]),"+f"(d[19]),"+f"(d[20]),"+f"(d[21]),"+f"(d[22]),"+f"(d[23]),
        "+f"(d[24]),"+f"(d[25]),"+f"(d[26]),"+f"(d[27]),"+f"(d[28]),"+f"(d[29]),"+f"(d[30]),"+f"(d[31]),
        "+f"(d[32]),"+f"(d[33]),"+f"(d[34]),"+f"(d[35]),"+f"(d[36]),"+f"(d[37]),"+f"(d[38]),"+f"(d[39]),
        "+f"(d[40]),"+f"(d[41]),"+f"(d[42]),"+f"(d[43]),"+f"(d[44]),"+f"(d[45]),"+f"(d[46]),"+f"(d[47]),
        "+f"(d[48]),"+f"(d[49]),"+f"(d[50]),"+f"(d[51]),"+f"(d[52]),"+f"(d[53]),"+f"(d[54]),"+f"(d[55]),
        "+f"(d[56]),"+f"(d[57]),"+f"(d[58]),"+f"(d[59]),"+f"(d[60]),"+f"(d[61]),"+f"(d[62]),"+f"(d[63]),
        "+f"(d[64]),"+f"(d[65]),"+f"(d[66]),"+f"(d[67]),"+f"(d[68]),"+f"(d[69]),"+f"(d[70]),"+f"(d[71]),
        "+f"(d[72]),"+f"(d[73]),"+f"(d[74]),"+f"(d[75]),"+f"(d[76]),"+f"(d[77]),"+f"(d[78]),"+f"(d[79]),
        "+f"(d[80]),"+f"(d[81]),"+f"(d[82]),"+f"(d[83]),"+f"(d[84]),"+f"(d[85]),"+f"(d[86]),"+f"(d[87]),
        "+f"(d[88]),"+f"(d[89]),"+f"(d[90]),"+f"(d[91]),"+f"(d[92]),"+f"(d[93]),"+f"(d[94]),"+f"(d[95]),
        "+f"(d[96]),"+f"(d[97]),"+f"(d[98]),"+f"(d[99]),"+f"(d[100]),"+f"(d[101]),"+f"(d[102]),"+f"(d[103]),
        "+f"(d[104]),"+f"(d[105]),"+f"(d[106]),"+f"(d[107]),"+f"(d[108]),"+f"(d[109]),"+f"(d[110]),"+f"(d[111]),
        "+f"(d[112]),"+f"(d[113]),"+f"(d[114]),"+f"(d[115]),"+f"(d[116]),"+f"(d[117]),"+f"(d[118]),"+f"(d[119]),
        "+f"(d[120]),"+f"(d[121]),"+f"(d[122]),"+f"(d[123]),"+f"(d[124]),"+f"(d[125]),"+f"(d[126]),"+f"(d[127])
      : "l"(da), "l"(db));
}
__device__ __forceinline__ void wgmma_n192(float (&d)[96], uint64_t da, uint64_t db) {
  asm volatile("wgmma.mma_async.sync.aligned.m64n192k16.f32.bf16.bf16 {"
      "%0,%1,%2,%3,%4,%5,%6,%7,%8,%9,%10,%11,%12,%13,%14,%15,"
      "%16,%17,%18,%19,%20,%21,%22,%23,%24,%25,%26,%27,%28,%29,%30,%31,"
      "%32,%33,%34,%35,%36,%37,%38,%39,%40,%41,%42,%43,%44,%45,%46,%47,"
      "%48,%49,%50,%51,%52,%53,%54,%55,%56,%57,%58,%59,%60,%61,%62,%63,"
      "%64,%65,%66,%67,%68,%69,%70,%71,%72,%73,%74,%75,%76,%77,%78,%79,"
      "%80,%81,%82,%83,%84,%85,%86,%87,%88,%89,%90,%91,%92,%93,%94,%95"
      "}, %96, %97, 1, 1, 1, 0, 1;\n"
      : "+f"(d[0]),"+f"(d[1]),"+f"(d[2]),"+f"(d[3]),"+f"(d[4]),"+f"(d[5]),"+f"(d[6]),"+f"(d[7]),
        "+f"(d[8]),"+f"(d[9]),"+f"(d[10]),"+f"(d[11]),"+f"(d[12]),"+f"(d[13]),"+f"(d[14]),"+f"(d[15]),
        "+f"(d[16]),"+f"(d[17]),"+f"(d[18]),"+f"(d[19]),"+f"(d[20]),"+f"(d[21]),"+f"(d[22]),"+f"(d[23]),
        "+f"(d[24]),"+f"(d[25]),"+f"(d[26]),"+f"(d[27]),"+f"(d[28]),"+f"(d[29]),"+f"(d[30]),"+f"(d[31]),
        "+f"(d[32]),"+f"(d[33]),"+f"(d[34]),"+f"(d[35]),"+f"(d[36]),"+f"(d[37]),"+f"(d[38]),"+f"(d[39]),
        "+f"(d[40]),"+f"(d[41]),"+f"(d[42]),"+f"(d[43]),"+f"(d[44]),"+f"(d[45]),"+f"(d[46]),"+f"(d[47]),
        "+f"(d[48]),"+f"(d[49]),"+f"(d[50]),"+f"(d[51]),"+f"(d[52]),"+f"(d[53]),"+f"(d[54]),"+f"(d[55]),
        "+f"(d[56]),"+f"(d[57]),"+f"(d[58]),"+f"(d[59]),"+f"(d[60]),"+f"(d[61]),"+f"(d[62]),"+f"(d[63]),
        "+f"(d[64]),"+f"(d[65]),"+f"(d[66]),"+f"(d[67]),"+f"(d[68]),"+f"(d[69]),"+f"(d[70]),"+f"(d[71]),
        "+f"(d[72]),"+f"(d[73]),"+f"(d[74]),"+f"(d[75]),"+f"(d[76]),"+f"(d[77]),"+f"(d[78]),"+f"(d[79]),
        "+f"(d[80]),"+f"(d[81]),"+f"(d[82]),"+f"(d[83]),"+f"(d[84]),"+f"(d[85]),"+f"(d[86]),"+f"(d[87]),
        "+f"(d[88]),"+f"(d[89]),"+f"(d[90]),"+f"(d[91]),"+f"(d[92]),"+f"(d[93]),"+f"(d[94]),"+f"(d[95])
      : "l"(da), "l"(db));
}
__device__ __forceinline__ void wgmma_rs_n128(float (&d)[64], uint32_t a0, uint32_t a1, uint32_t a2, uint32_t a3, uint64_t db) {
  asm volatile("wgmma.mma_async.sync.aligned.m64n128k16.f32.bf16.bf16 {"
      "%0,%1,%2,%3,%4,%5,%6,%7,%8,%9,%10,%11,%12,%13,%14,%15,"
      "%16,%17,%18,%19,%20,%21,%22,%23,%24,%25,%26,%27,%28,%29,%30,%31,"
      "%32,%33,%34,%35,%36,%37,%38,%39,%40,%41,%42,%43,%44,%45,%46,%47,"
      "%48,%49,%50,%51,%52,%53,%54,%55,%56,%57,%58,%59,%60,%61,%62,%63"
      "}, {%64,%65,%66,%67}, %68, 1, 1, 1, 1;\n"
      : "+f"(d[0]),"+f"(d[1]),"+f"(d[2]),"+f"(d[3]),"+f"(d[4]),"+f"(d[5]),"+f"(d[6]),"+f"(d[7]),
        "+f"(d[8]),"+f"(d[9]),"+f"(d[10]),"+f"(d[11]),"+f"(d[12]),"+f"(d[13]),"+f"(d[14]),"+f"(d[15]),
        "+f"(d[16]),"+f"(d[17]),"+f"(d[18]),"+f"(d[19]),"+f"(d[20]),"+f"(d[21]),"+f"(d[22]),"+f"(d[23]),
        "+f"(d[24]),"+f"(d[25]),"+f"(d[26]),"+f"(d[27]),"+f"(d[28]),"+f"(d[29]),"+f"(d[30]),"+f"(d[31]),
        "+f"(d[32]),"+f"(d[33]),"+f"(d[34]),"+f"(d[35]),"+f"(d[36]),"+f"(d[37]),"+f"(d[38]),"+f"(d[39]),
        "+f"(d[40]),"+f"(d[41]),"+f"(d[42]),"+f"(d[43]),"+f"(d[44]),"+f"(d[45]),"+f"(d[46]),"+f"(d[47]),
        "+f"(d[48]),"+f"(d[49]),"+f"(d[50]),"+f"(d[51]),"+f"(d[52]),"+f"(d[53]),"+f"(d[54]),"+f"(d[55]),
        "+f"(d[56]),"+f"(d[57]),"+f"(d[58]),"+f"(d[59]),"+f"(d[60]),"+f"(d[61]),"+f"(d[62]),"+f"(d[63])
      : "r"(a0), "r"(a1), "r"(a2), "r"(a3), "l"(db));
}

constexpr int C_LN = 0, C_PX = 16, C_PY = 32;
constexpr int NB_CONS = 1, NB_LN = 2, NB_LAG = 4, NB_INIT = 6, NB_RDY = 7;
#define LAGX 3
#define LAGY 3
#define LAG2 5
#define NLL 2
#define POLL_DELAY3 900
#define POLL_DELAY 900
#define FILT_DELAY 1000
#define THR_B 0
#define THR_P 0
#define SPEC -1
#define RING_SIG 1
#define PF2_SIG 1
constexpr int SM_E = 0, SM_X = 16384, SM_E2 = 32768, SM_W = 49152, SM_FC = 69632, SM_T = 73728 - T1_BYTES;
constexpr unsigned long long KORDER = 0xBA9432DC876510ull;
constexpr unsigned long long BSLOT = 0x76532107653210ull, PSLOT = 0xDCBA984DCBA984ull;
constexpr uint32_t HI128 = desc_hi(1024, 1), HI64 = desc_hi(512, 2);

struct Bars {
  uint64_t full1[32], empty1[32], full2[16], fullA[8], empty2[8], fullP[16], emptyP[8], hbar, tbar, hint[3], sig[2], sbar;
  uint32_t epoch;
};

template <int NK, bool STORE>
__device__ __forceinline__ void make_p(const float (&acc)[NK * 16], float r0, float r1, uint4 (&p)[NK], uint4* pbase, int ks0, uint32_t tag) {
#pragma unroll
  for (int j = 0; j < NK; j++) {
    uint32_t w[4];
#pragma unroll
    for (int i = 0; i < 4; i++) {
      const int a = 8 * j + 2 * i, b = a + NK * 8;
      w[i] = pack2(swiglu(acc[a], acc[b], (i & 1) ? r1 : r0), swiglu(acc[a + 1], acc[b + 1], (i & 1) ? r1 : r0));
    }
    asm volatile("" : "+r"(w[0]), "+r"(w[1]), "+r"(w[2]), "+r"(w[3]));
    p[j] = make_uint4(w[0], w[1], w[2], w[3]);
    if (STORE) st_tag(pbase + ((ks0 + j) >> 2) * 1024 + ((ks0 + j) & 3) * 32, p[j], tag);
  }
}
__device__ __forceinline__ void spin_cycles(uint32_t n) {
  const uint32_t t0 = clock32();
  while (clock32() - t0 < n) {}
}

__global__ void __cluster_dims__(2, 1, 1) __launch_bounds__(NTHREADS, 1)
fused_kernel(const __nv_bfloat16* __restrict__ x, const Tables* __restrict__ tab, Scratch* __restrict__ scr,
             __nv_bfloat16* __restrict__ out, const char* __restrict__ wg_raw, const char* __restrict__ wu_raw,
             const char* __restrict__ wd_raw,
             const __grid_constant__ CUtensorMap tmWR, const __grid_constant__ CUtensorMap tmWI,
             const __grid_constant__ CUtensorMap tmGX, const __grid_constant__ CUtensorMap tmUX,
             const __grid_constant__ CUtensorMap tmGY, const __grid_constant__ CUtensorMap tmUY,
             const __grid_constant__ CUtensorMap tmD) {
  extern __shared__ __align__(1024) char smem_raw[];
  const uint32_t sbase = s2u(smem_raw);
  const uint32_t sbar = sbase + 14 * SLOT, sstat = sbar + 1280;
  const int tid = threadIdx.x, lane = tid & 31;
  const int c = blockIdx.x, rk = c & 1, f = (c >> 1) & 7, rb = 2 * (c >> 4) + rk;
  const int rb2 = 2 * (c >> 4) + (f >> 2), kh = (f >> 1) & 1, nq = 2 * (f & 1) + rk;
#define BAR(field, i) (sbar + (uint32_t)offsetof(Bars, field) + 8u * (i))
#define TOFF(field) (sbase + SM_T + (uint32_t)offsetof(Tables, field) + lane * 16)

  if (tid >= 256) {
    asm volatile("setmaxnreg.dec.sync.aligned.u32 56;");
    const int warp = __shfl_sync(0xffffffffu, tid >> 5, 0);
    if (lane == 0) {
      if (warp == 8) {
        if (sbase & 1023) die();
#pragma unroll
        for (int i = 0; i < 16; i++) mbar_init(BAR(emptyP, i), i < 7 ? 16 : i < 8 ? 8 : i < 13 ? 1 : i < 15 ? 8 : 32);
        mbar_expect(BAR(tbar, 0), T2_BYTES + 2 * 10240);
        mbar_expect(BAR(hbar, 0), 16384);
      } else if (warp == 9) {
#pragma unroll
        for (int i = 0; i < 32; i++) mbar_init(BAR(full1, i), 1);
#pragma unroll
        for (int i = 0; i < 32; i++) mbar_expect(BAR(full1, i), i < 16 ? 16384 : 12288);
      } else if (warp == 10) {
#pragma unroll
        for (int i = 0; i < 32; i++) mbar_init(BAR(empty1, i), 16);
#pragma unroll
        for (int i = 0; i < 14; i++) mbar_init(BAR(fullP, i), 1);
#pragma unroll
        for (int i = 0; i < 14; i++) mbar_expect(BAR(fullP, i), 16384);
      } else {
#pragma unroll
        for (int i = 0; i < 32; i++) mbar_init(BAR(full2, i), i < 24 ? 1 : 8);
#pragma unroll
        for (int i = 0; i < 24; i++) mbar_expect(BAR(full2, i), 16384);
      }
      asm volatile("fence.mbarrier_init.release.cluster;" ::: "memory");
    }
    if (tid == 256) {
      const int w0 = ((c >> 3) * 257 + 32 * (c & 7) + 1) & ~7;
      if (FILT_DELAY) {
        asm volatile("prefetch.tensormap [%0];" ::"l"(&tmWR) : "memory");
        asm volatile("prefetch.tensormap [%0];" ::"l"(&tmWI) : "memory");
        spin_cycles(FILT_DELAY);
      }
      tma3(sbase + SM_W, &tmWR, BAR(tbar, 0), w0, 0, 0);
      tma3(sbase + SM_W + 10240, &tmWI, BAR(tbar, 0), w0, 0, 0);
      bulk_load(sbase + SM_T + T1_BYTES, reinterpret_cast<const char*>(tab) + T1_BYTES, T2_BYTES, BAR(tbar, 0));
    }
    if (tid == 288) {
      asm volatile("prefetch.tensormap [%0];" ::"l"(rk ? &tmUX : &tmGX) : "memory");
      asm volatile("prefetch.tensormap [%0];" ::"l"(rk ? &tmUY : &tmGY) : "memory");
      asm volatile("prefetch.tensormap [%0];" ::"l"(&tmD) : "memory");
    }
    if (tid == 320) {
      const unsigned e = ld_relaxed(&scr->cnt[(C_LN + rb) * 32]) >> 3;
      asm volatile("st.shared.u32 [%0], %1;" ::"r"(BAR(epoch, 0)), "r"(e) : "memory");
    }
    __syncwarp();
    asm volatile("barrier.cluster.arrive.relaxed.aligned;" ::: "memory");
    bar_arrive(NB_RDY, 384);
    asm volatile("barrier.cluster.wait.aligned;" ::: "memory");
    bar_sync(NB_INIT, 384);
    unsigned epoch;
    asm volatile("ld.shared.u32 %0, [%1];" : "=r"(epoch) : "r"(BAR(epoch, 0)) : "memory");
    if (warp == 8) {
      if (lane == 0) {
        const int ax = (7 * f + 3 * (f & 1)) >> 1;
        const int ay = 7 * f + ((f & 1) ? 0 : 4);
        const CUtensorMap* tx = rk ? &tmUX : &tmGX;
        const CUtensorMap* ty = rk ? &tmUY : &tmGY;
        if (RING_SIG >= 0) mbar_wait(BAR(sig, RING_SIG));
        uint32_t s = 2;
#pragma unroll 1
        for (int n = 0; n < 16; n++) {
          if (n >= 6) mbar_wait(BAR(empty1, n - 6));
          tma3_mc(sbase + (8 + s) * SLOT + rk * 8192, tx, BAR(full1, n), n * 32, ax);
          if (++s == 6) s = 0;
        }
#pragma unroll 1
        for (int k = 0; k < 16; k++) {
          mbar_wait(BAR(empty1, k < 8 ? 10 + ((12 * k + 11) >> 4) : 8 + k));
          tma3_mc(sbase + 8 * SLOT + (k & 7) * 12288 + rk * 6144, ty, BAR(full1, 16 + k), k * 32, ay);
        }
      }
    } else if (warp == 9) {
      if (lane == 0) {
#pragma unroll 1
        for (int i = 0; i < 14; i++) {
          const int kblk = 14 * kh + (int)((KORDER >> (4 * i)) & 15);
          const int j = i < 7 ? i : i - 7, sl = j + (j >= 4);
          mbar_wait(i < 7 ? BAR(empty1, 17 + 2 * sl) : BAR(empty2, j));
          if (THR_B && i >= THR_B) mbar_wait(BAR(full2, i - THR_B));
          tma3(sbase + sl * SLOT, &tmD, BAR(full2, i), 0, 64 * kblk, 2 * nq);
        }
        wait_counter(&scr->cnt[(C_LN + rb2) * 32], (epoch + 1) * 8);
        asm volatile("fence.proxy.async.global;" ::: "memory");
        mbar_wait(BAR(emptyP, 7));
        bulk_load(sbase + 4 * SLOT, &scr->LN[(rb2 * 8 + 2 * nq) * 1024 + (kh ^ 1) * 512], 8192, BAR(hbar, 0));
        bulk_load(sbase + 4 * SLOT + 8192, &scr->LN[(rb2 * 8 + 2 * nq + 1) * 1024 + (kh ^ 1) * 512], 8192, BAR(hbar, 0));
      }
    } else if (warp == 10) {
      bar_sync(NB_LN, 288);
      if (lane == 0) {
        PROFP(0);
        red_release(&scr->cnt[(C_LN + rb) * 32]);
        PROFP(1);
        wait_counter(&scr->cnt[(C_LN + rb) * 32], (epoch + 1) * 8);
        asm volatile("fence.proxy.async.global;" ::: "memory");
        PROFP(2);
#pragma unroll 1
        for (int kb = NLL; kb < 8; kb++) bulk_load(sbase + kb * SLOT, &scr->LN[(rb * 8 + kb) * 1024], 16384, BAR(fullA, kb));
#pragma unroll 1
        for (int s = 0; s < 14; s++) {
          const int kblk = 14 * kh + (int)((KORDER >> (4 * s)) & 15);
          if (s == 0 || (SPEC < 0 && (s == 8 || s == 11))) {
            if (s != 11) PROFP(3 + (s >> 2));
            mbar_wait(BAR(hint, s == 0 ? 0 : s == 8 ? 1 : 2), 0);
            if (s != 11) PROFP(4 + (s >> 2));
          }
          const int j = s < 7 ? s : s - 7;
          mbar_wait(s < 7 ? BAR(empty1, 24 + s + (s == 0) + (s >= 4)) : BAR(emptyP, j));
          if (THR_P && s >= THR_P) mbar_wait(BAR(fullP, s - THR_P));
          if (SPEC >= 0 && s == 8) mbar_wait(BAR(emptyP, SPEC & 7));
          bulk_load_mc(sbase + (j ? 7 + j : 4) * SLOT + rk * 8192, &scr->P[(rb2 * 28 + kblk) * 1024 + rk * 512], 8192, BAR(fullP, s));
        }
        PROFP(7);
      }
    } else {
      if (lane == 0) {
        l2_prefetch(wg_raw + (size_t)c * 5376, 5376);
        l2_prefetch(wu_raw + (size_t)c * 5376, 5376);
        mbar_wait(BAR(sig, PF2_SIG), 0);
        l2_prefetch(wg_raw + 688128 + (size_t)c * 8960, 8960);
        l2_prefetch(wu_raw + 688128 + (size_t)c * 8960, 8960);
      }
      mbar_wait(BAR(fullA, 7), 0);
      if (lane == 0) l2_prefetch(wd_raw + (size_t)c * 14336, 14336);
      {
        const uint32_t tag = (epoch + 1) & 1;
        uint4 v0, v1, v2;
        int it = 0;
        while (true) {
          v0 = ld_b128(&scr->ST[rb * 64 + lane]);
          v1 = ld_b128(&scr->ST[rb * 64 + 32 + lane]);
          v2 = ld_b128(&scr->ST[rb2 * 64 + 32 * (kh ^ 1) + lane]);
          if (!__any_sync(0xffffffffu, ((v0.x ^ tag) | (v1.x ^ tag) | (v2.x ^ tag)) & 1u)) break;
          if (++it > SPIN_LIMIT) { die(); break; }
        }
        sts4(sstat + lane * 16, v0.x & ~1u, v0.y, v0.z, v0.w);
        sts4(sstat + 512 + lane * 16, v1.x & ~1u, v1.y, v1.z, v1.w);
        sts4(sstat + 1024 + lane * 16, v2.x & ~1u, v2.y, v2.z, v2.w);
#pragma unroll 4
        for (int i = 0; i < 32; i++)
          st_tag(&scr->XP[(c ^ 4) * 1024 + i * 32 + lane], make_uint4(0, 0, 0, 0), tag ^ 1);
        mbar_arrive(BAR(sbar, 0));
      }
      if (lane == 0) {
        mbar_wait(BAR(empty1, 17));
#pragma unroll 1
        for (int e = 0; e < (SPEC < 0 ? 3 : 1); e++) {
          const unsigned* cp = e == 0 ? &scr->cnt[(C_PX + rb2) * 32] : &scr->cnt[(C_PY + rb2) * 32 + 2 * kh + e - 1];
          if (e == 1) mbar_wait(BAR(fullP, 0), 0);
          int it = 0;
          while ((int)(ld_relaxed(cp) - (epoch + 1) * (e == 0 ? 64 : 16)) < 0)
            if (++it > SPIN_LIMIT) { die(); break; }
          mbar_arrive(BAR(hint, e));
        }
      }
    }
  } else {
    const int warp = __shfl_sync(0xffffffffu, tid >> 5, 0);
    const int g = lane >> 2, t = lane & 3;
    PROF(0);
    PROFG(14);
#pragma unroll
    for (int i = 0; i < 4; i++) {
      const int r = i >> 1, ch = (i & 1) * 32 + lane;
      cp_async16(sbase + SM_X + (2 * warp + r) * 1024 + ((ch ^ ((ch >> 2) & 6)) * 16),
                 x + (size_t)(c + 128 * (2 * warp + r)) * 512 + ch * 8);
    }
    asm volatile("cp.async.commit_group;" ::: "memory");
    asm volatile("barrier.cluster.arrive.relaxed.aligned;" ::: "memory");
    uint4 tw[8], fb[16];
    const uint4 fa = ldg_ca4(&tab->fa[lane][0]);
#pragma unroll
    for (int i = 0; i < 8; i++) tw[i] = ldg_ca4(&tab->tw1[i][lane][0]);
#pragma unroll
    for (int i = 0; i < 16; i++) fb[i] = ldg_ca4(&tab->fb[i][lane][0]);
    uint32_t rbar;
    asm volatile("mapa.shared::cluster.u32 %0, %1, %2;" : "=r"(rbar) : "r"(sbar), "r"(rk ^ 1));
#define RBAR(field, i) (rbar + (uint32_t)offsetof(Bars, field) + 8u * (i))
    {
      const int ln = (tid >> 1) & 31, lg = ln >> 2, lt = ln & 3, i = 4 * (tid >> 6) + 2 * (tid & 1);
      const int kidx = lt + 8 * (i >> 3), nidx = 4 * ((i >> 1) & 3) + (lg >> 1);
      const uint32_t a0 = cfrag<2048>((c + 128 * kidx) * nidx, lg & 1), a1 = cfrag<2048>((c + 128 * (kidx + 4)) * nidx, lg & 1);
      const uint32_t b0 = cfrag<2048>(-(c + 128 * nidx) * kidx, lg & 1), b1 = cfrag<2048>(-(c + 128 * nidx) * (kidx + 4), lg & 1);
      asm volatile("st.shared.v2.u32 [%0], {%1,%2};" ::"r"(sbase + SM_FC + tid * 8), "r"(a0), "r"(a1) : "memory");
      asm volatile("st.shared.v2.u32 [%0], {%1,%2};" ::"r"(sbase + SM_FC + 2048 + tid * 8), "r"(b0), "r"(b1) : "memory");
    }
    asm volatile("cp.async.wait_group 0;" ::: "memory");
    __syncwarp();
    bar_arrive(NB_INIT, 384);
    PROF(13);
    uint32_t tag;
    uint4 q[4], o[4];
    {
      uint32_t v[2][8];
#pragma unroll
      for (int r = 0; r < 2; r++)
#pragma unroll
        for (int q = 0; q < 4; q++) {
          const uint2 u = lds2(sbase + SM_X + (2 * warp + r) * 1024 + (t + 4 * (q >> 1)) * 128 + (((4 * (q & 1) + (g >> 1)) ^ (2 * t)) * 16) + (g & 1) * 8);
          v[r][2 * q] = u.x; v[r][2 * q + 1] = u.y;
        }
      float sum[2], sq[2], rstd[2];
      row_stats(v[0], v[1], lane, sum, sq);
#pragma unroll
      for (int r = 0; r < 2; r++) {
        const float m = sum[r] * (1.f / 512.f);
        rstd[r] = rsqrtf(fmaxf(fmaf(-m, m, sq[r] * (1.f / 512.f)), 0.f) + 1e-5f);
      }
      uint32_t alo[4][4], ahi[4][4];
#pragma unroll
      for (int r = 0; r < 2; r++)
#pragma unroll
        for (int i = 0; i < 4; i++) {
          const uint32_t sel = (i & 1) ? 0x7632u : 0x5410u;
          const uint32_t b0 = __byte_perm(v[r][i >> 1], v[r][2 + (i >> 1)], sel);
          const uint32_t b1 = __byte_perm(v[r][4 + (i >> 1)], v[r][6 + (i >> 1)], sel);
          float d[4] = {0.f, 0.f, 0.f, 0.f};
          mma16816(d, fa.x, fa.y, fa.z, fa.w, b0, b1);
          const uint4 &ka = tw[2 * i], &kb = tw[2 * i + 1];
          const uint32_t re = pack2(d[0] * __uint_as_float(ka.x) + d[2] * __uint_as_float(ka.y), d[1] * __uint_as_float(kb.x) + d[3] * __uint_as_float(kb.y));
          const uint32_t im = pack2(d[0] * __uint_as_float(ka.z) + d[2] * __uint_as_float(ka.w), d[1] * __uint_as_float(kb.z) + d[3] * __uint_as_float(kb.w));
          const uint32_t dc = pack2(fmaf(sum[r], -1.f / 32.f, d[0]), fmaf(sum[r], -1.f / 32.f, d[1]));
          alo[i][r] = re; alo[i][2 + r] = im;
          ahi[i][r] = g == 0 ? dc : re; ahi[i][2 + r] = g == 0 ? 0u : im;
        }
      float acc[8][4];
#pragma unroll
      for (int u = 0; u < 8; u++) {
        acc[u][0] = acc[u][1] = acc[u][2] = acc[u][3] = 0.f;
#pragma unroll
        for (int i = 0; i < 4; i++) {
          const uint4& bq = fb[i * 4 + (u >> 1)];
          if (u < 4) mma16816(acc[u], alo[i][0], alo[i][1], alo[i][2], alo[i][3], (u & 1) ? bq.z : bq.x, (u & 1) ? bq.w : bq.y);
          else       mma16816(acc[u], ahi[i][0], ahi[i][1], ahi[i][2], ahi[i][3], (u & 1) ? bq.z : bq.x, (u & 1) ? bq.w : bq.y);
        }
      }
#pragma unroll
      for (int r = 0; r < 2; r++)
#pragma unroll
        for (int h = 0; h < 2; h++) {
          const int j = 2 * warp + r, m = 2 * t + h;
          const float rs = rstd[r];
          sts4(sbase + SM_E + ((j * 8 + m) * 8 + (g ^ (2 * t) ^ (2 * (j & 3)))) * 16,
               pack2(acc[2 * h][2 * r] * rs, acc[2 * h][2 * r + 1] * rs), pack2(acc[2 * h + 1][2 * r] * rs, acc[2 * h + 1][2 * r + 1] * rs),
               pack2(acc[4 + 2 * h][2 * r] * rs, acc[4 + 2 * h][2 * r + 1] * rs), pack2(acc[5 + 2 * h][2 * r] * rs, acc[5 + 2 * h][2 * r + 1] * rs));
        }
      if (tid == 0) PROFP(12);
      bar_sync(NB_RDY, 384);
      if (tid == 0) PROFP(13);
      uint4 fc[4];
#pragma unroll
      for (int i = 0; i < 4; i++) fc[i] = lds4(sbase + SM_FC + i * 512 + lane * 16);
      asm volatile("ld.shared.u32 %0, [%1];" : "=r"(tag) : "r"(BAR(epoch, 0)) : "memory");
      tag = __shfl_sync(0xffffffffu, (tag + 1) & 1, 0);
#pragma unroll
      for (int i = 0; i < 4; i++) q[i] = lds4(sbase + SM_E + (((t + 4 * i) * 8 + warp) * 8 + (g ^ (warp & 6) ^ (2 * t))) * 16);
      cdft16(q, fc, o);
#pragma unroll
      for (int vv = 0; vv < 4; vv++) st_tag(&scr->Z1[(((4 * vv + t) * 8 + warp) * 128 + c) * 8 + g], o[vv], tag);
    }
    PROF(1);
    asm volatile("setmaxnreg.inc.sync.aligned.u32 224;");
    {
      const uint4* const zp = &scr->Z1[(c * 128 + 8 * t + warp) * 8 + g];
      const uint32_t tst = clock32();
      mbar_wait(BAR(tbar, 0), 0);
      if (tid == 0) PROFP(14);
      uint4 f2[4], g2[4];
#pragma unroll
      for (int i = 0; i < 4; i++) {
        f2[i] = lds4(TOFF(f2) + warp * 2048 + i * 512);
        g2[i] = lds4(TOFF(g2) + warp * 2048 + i * 512);
      }
      const uint4 f8 = lds4(TOFF(f8)), g8 = lds4(TOFF(g8));
      float wfr[16], wfi[16];
      {
        const float fsc = 1.f / (1 << 19);
        const float fsc3 = ((c & 7) == 7 && g == 0) ? 0.5f * fsc : fsc;
        const int gg = g == 0 ? 8 : g, wsh = (2 * (c >> 3) + 2) & 15;
#pragma unroll
        for (int i = 0; i < 16; i++) {
          const int ci = i >> 3, dd = (i >> 2) & 1, e = i & 3;
          const int kk = (e == 0 ? gg : e == 1 ? 16 + gg : e == 2 ? 16 - g : 32 - g) - 1;
          const uint32_t a = sbase + SM_W + ((2 * warp + ci) * 8 + t + 4 * dd) * 80 + wsh + 2 * kk;
          wfr[i] = bf_lo(lds_u16(a)) * (e == 3 ? fsc3 : fsc);
          wfi[i] = bf_lo(lds_u16(a + 10240)) * (e == 3 ? fsc3 : fsc);
        }
      }
      asm volatile("barrier.cluster.wait.aligned;" ::: "memory");
      PROF(2);
      while (clock32() - tst < POLL_DELAY) {}
      ld_tag4_issue<256>(q, zp);
      ld_tag4_finish<256>(q, zp, tag);
      if (tid == 0) PROFP(30);
      if (lane == 0) mbar_arrive(BAR(sig, 0));
      cdft16(q, f2, o);
      const uint32_t e2 = sbase + SM_E2;
#pragma unroll
      for (int vv = 0; vv < 4; vv++)
        sts4(e2 + ((warp * 16 + 4 * vv + t) * 8 + (g ^ (2 * t) ^ (2 * (warp & 3)))) * 16, o[vv].x, o[vv].y, o[vv].z, o[vv].w);
      bar_sync(NB_CONS, 256);
#pragma unroll
      for (int ci = 0; ci < 2; ci++) {
        const int cc = 2 * warp + ci;
        uint32_t ad[2];
        uint4 u[2];
#pragma unroll
        for (int hh = 0; hh < 2; hh++) {
          ad[hh] = e2 + (((t + 4 * hh) * 16 + cc) * 8 + (g ^ (2 * (cc & 3)) ^ (2 * t))) * 16;
          u[hh] = lds4(ad[hh]);
        }
        uint32_t res[2][4];
#pragma unroll
        for (int p = 0; p < 2; p++) {
          uint32_t y[2][2];
#pragma unroll
          for (int vv = 0; vv < 2; vv++) {
            float d[4] = {0.f, 0.f, 0.f, 0.f};
            mma16816(d, word(u[0], 2 * p), word(u[0], 2 * p + 1), word(u[1], 2 * p), word(u[1], 2 * p + 1), word(f8, 2 * vv), word(f8, 2 * vv + 1));
#pragma unroll
            for (int rr = 0; rr < 2; rr++) {
              const float fr = wfr[ci * 8 + vv * 4 + 2 * p + rr], fi = wfi[ci * 8 + vv * 4 + 2 * p + rr];
              y[vv][rr] = pack2(d[2 * rr] * fr - d[2 * rr + 1] * fi, d[2 * rr] * fi + d[2 * rr + 1] * fr);
            }
          }
#pragma unroll
          for (int vv = 0; vv < 2; vv++) {
            float d[4] = {0.f, 0.f, 0.f, 0.f};
            mma16816(d, y[0][0], y[0][1], y[1][0], y[1][1], word(g8, 2 * vv), word(g8, 2 * vv + 1));
            res[vv][2 * p] = pack2(d[0], d[1]);
            res[vv][2 * p + 1] = pack2(d[2], d[3]);
          }
        }
#pragma unroll
        for (int vv = 0; vv < 2; vv++) sts4(ad[vv], res[vv][0], res[vv][1], res[vv][2], res[vv][3]);
      }
      bar_sync(NB_CONS, 256);
#pragma unroll
      for (int i = 0; i < 4; i++) q[i] = lds4(e2 + ((warp * 16 + 4 * i + t) * 8 + (g ^ (2 * t) ^ (2 * (warp & 3)))) * 16);
      cdft16(q, g2, o);
#pragma unroll
      for (int vv = 0; vv < 4; vv++) st_tag(&scr->Z2[((8 * (4 * vv + t) + warp) * 128 + c) * 8 + g], o[vv], tag);
    }
    PROF(3);
    {
      const uint4* const zp = &scr->Z2[((c * 16 + t) * 8 + warp) * 8 + g];
      const uint32_t tst = clock32();
      uint4 gb[16], gc[4], tw[4], xr[2][2];
#pragma unroll
      for (int i = 0; i < 16; i++) gb[i] = lds4(TOFF(gb) + i * 512);
      const uint4 ga = lds4(TOFF(ga));
#pragma unroll
      for (int i = 0; i < 4; i++) {
        gc[i] = lds4(sbase + SM_FC + 2048 + i * 512 + lane * 16);
        tw[i] = lds4(TOFF(tw3) + i * 512);
        const int ch = 4 * (g + 8 * (i & 1)) + t;
        xr[i >> 1][i & 1] = lds4(sbase + SM_X + (2 * warp + (i >> 1)) * 1024 + ((ch ^ ((ch >> 2) & 6)) * 16));
      }
      PROF(4);
      while (clock32() - tst < POLL_DELAY) {}
      ld_tag4_issue<256>(q, zp);
      ld_tag4_finish<256>(q, zp, tag);
      if (tid == 0) PROFP(31);
      if (lane == 0) mbar_arrive(BAR(sig, 1));
      cdft16(q, gc, o);
#pragma unroll
      for (int vv = 0; vv < 4; vv++)
        sts4(sbase + SM_E + (((4 * vv + t) * 8 + warp) * 8 + (g ^ (warp & 6) ^ (2 * t))) * 16, o[vv].x, o[vv].y, o[vv].z, o[vv].w);
      if (tid == 0) PROFP(8);
      bar_sync(NB_CONS, 256);
      if (tid == 0) PROFP(9);
      uint32_t hv[2][8];
      const float mk = t == 0 ? 0.f : 1.f;
#pragma unroll
      for (int r = 0; r < 2; r++) {
        const int j = 2 * warp + r;
        uint4 u[2];
#pragma unroll
        for (int h = 0; h < 2; h++) u[h] = lds4(sbase + SM_E + ((j * 8 + 2 * t + h) * 8 + (g ^ (2 * t) ^ (2 * (j & 3)))) * 16);
        float yv[4][4];
#pragma unroll
        for (int i = 0; i < 4; i++) {
          float lo[4] = {0.f, 0.f, 0.f, 0.f}, hi[4] = {0.f, 0.f, 0.f, 0.f};
          mma16816(lo, gb[i * 4].x, gb[i * 4].y, gb[i * 4].z, gb[i * 4].w, u[0].x, u[0].y);
          mma16816(lo, gb[i * 4 + 1].x, gb[i * 4 + 1].y, gb[i * 4 + 1].z, gb[i * 4 + 1].w, u[1].x, u[1].y);
          mma16816(hi, gb[i * 4 + 2].x, gb[i * 4 + 2].y, gb[i * 4 + 2].z, gb[i * 4 + 2].w, u[0].z, u[0].w);
          mma16816(hi, gb[i * 4 + 3].x, gb[i * 4 + 3].y, gb[i * 4 + 3].z, gb[i * 4 + 3].w, u[1].z, u[1].w);
          const float ca = __uint_as_float(tw[i].x), sa = __uint_as_float(tw[i].y), cb = __uint_as_float(tw[i].z), sb = __uint_as_float(tw[i].w);
          const float tr0 = fmaf(hi[0], mk, lo[0]), ti0 = fmaf(hi[2], mk, lo[2]);
          const float tr1 = lo[1] + hi[1], ti1 = lo[3] + hi[3];
          const float vr0 = tr0 * ca - ti0 * sa, vi0 = tr0 * sa + ti0 * ca;
          const float vr1 = tr1 * cb - ti1 * sb, vi1 = tr1 * sb + ti1 * cb;
          const uint32_t b0 = pack2(t == 0 ? hi[0] : vr0, vr1), b1 = pack2(t == 0 ? vr0 : vi0, vi1);
          yv[i][0] = yv[i][1] = yv[i][2] = yv[i][3] = 0.f;
          mma16816(yv[i], ga.x, ga.y, ga.z, ga.w, b0, b1);
        }
#pragma unroll
        for (int h = 0; h < 2; h++) {
          hv[r][4 * h + 0] = hadd2_bf16(xr[r][h].x, pack2(yv[0][2 * h], yv[1][2 * h]));
          hv[r][4 * h + 1] = hadd2_bf16(xr[r][h].y, pack2(yv[2][2 * h], yv[3][2 * h]));
          hv[r][4 * h + 2] = hadd2_bf16(xr[r][h].z, pack2(yv[0][2 * h + 1], yv[1][2 * h + 1]));
          hv[r][4 * h + 3] = hadd2_bf16(xr[r][h].w, pack2(yv[2][2 * h + 1], yv[3][2 * h + 1]));
        }
      }
      if (tid == 0 && hv[0][0] != 0x12345 && hv[1][7] != 0x12345) PROFP(10);
      float ds[4] = {0.f, 0.f, 0.f, 0.f};
#pragma unroll
      for (int q4 = 0; q4 < 4; q4++) mma16816(ds, hv[0][2 * q4], hv[1][2 * q4], hv[0][2 * q4 + 1], hv[1][2 * q4 + 1], 0x3f803f80u, 0x3f803f80u);
#pragma unroll
      for (int o2 = 4; o2 <= 16; o2 <<= 1) {
        ds[0] += __shfl_xor_sync(0xffffffffu, ds[0], o2);
        ds[2] += __shfl_xor_sync(0xffffffffu, ds[2], o2);
      }
      uint32_t mb[2];
#pragma unroll
      for (int r = 0; r < 2; r++) {
        const int row = 16 * f + 2 * warp + r;
        mb[r] = pack2(ds[2 * r] * (1.f / 512.f), ds[2 * r] * (1.f / 512.f));
#pragma unroll
        for (int i = 0; i < 8; i++) hv[r][i] = hsub2_bf16(hv[r][i], mb[r]);
#pragma unroll
        for (int h = 0; h < 2; h++) {
          const int n1 = g + 8 * h;
          st_tag(&scr->LN[(rb * 8 + (n1 >> 1)) * 1024 + row * 8 + ((4 * (n1 & 1) + t) ^ (row & 7))],
                 make_uint4(hv[r][4 * h], hv[r][4 * h + 1], hv[r][4 * h + 2], hv[r][4 * h + 3]), n1 < 2 * NLL ? tag : (hv[r][4 * h] & 1u));
        }
      }
      if (tid == 0) PROFP(11);
      bar_arrive(NB_LN, 288);
      float sum[2], sq[2], rstd[2];
      row_stats(hv[0], hv[1], lane, sum, sq);
#pragma unroll
      for (int r = 0; r < 2; r++) {
        const float m = sum[r] * (1.f / 512.f);
        rstd[r] = rsqrtf(fmaxf(fmaf(-m, m, sq[r] * (1.f / 512.f)), 0.f) + 1e-5f);
      }
      if (lane == 0)
        st_tag(&scr->ST[rb * 64 + 8 * f + warp], make_uint4(mb[0] << 16, __float_as_uint(rstd[0]), mb[1] << 16, __float_as_uint(rstd[1])), tag);
    }
    PROF(5);
    if (NLL) {
      const uint4* const ap = &scr->LN[rb * 8 * 1024 + tid];
      uint4 av[NLL ? NLL : 1][4];
      spin_cycles(POLL_DELAY3);
#pragma unroll
      for (int kb = 0; kb < NLL; kb++) ld_tag4_issue<256>(av[kb], ap + kb * 1024);
      bar_sync(NB_CONS, 256);
#pragma unroll
      for (int kb = 0; kb < NLL; kb++) {
        ld_tag4_finish<256>(av[kb], ap + kb * 1024, tag);
#pragma unroll
        for (int i = 0; i < 4; i++) sts4(sbase + kb * SLOT + (tid + 256 * i) * 16, av[kb][i].x, av[kb][i].y, av[kb][i].z, av[kb][i].w);
      }
      asm volatile("fence.proxy.async.shared::cta;" ::: "memory");
      bar_sync(NB_CONS, 256);
    }
    const int wgi = warp >> 2, wq = warp & 3;
    uint4* const pbase = &scr->P[rb * 28 * 1024 + warp * 128 + lane];
    const uint32_t a_lo0 = desc_lo(sbase + wgi * 8192, 16);
    const uint32_t ebar = lane == 0 ? BAR(empty1, 0) : RBAR(empty1, 0);
    float r0, r1;
    uint4 px[8], py[6];
    const int rh = wgi ^ kh ^ 1;
    const uint4* const psrc = &scr->P[(rb2 * 28 + 14 * kh) * 1024 + (4 * rh + wq) * 128 + lane];
    {
      float acc[128];
#pragma unroll
      for (int i = 0; i < 128; i++) acc[i] = 0.f;
      const uint32_t b_lo0 = desc_lo(sbase + 8 * SLOT, 4096);
      uint32_t slot = 2;
#pragma unroll 1
      for (int kb = 0; kb < 8; kb++) {
        if (kb >= NLL) mbar_wait(BAR(fullA, kb), 0);
        if (kb == 0) PROF(6);
#pragma unroll
        for (int hh = 0; hh < 2; hh++) {
          if (LAGX && hh == ((16 - LAGX) & 1) && kb == ((16 - LAGX) >> 1) && wgi == 1) bar_sync(NB_LAG, 256);
          mbar_wait(BAR(full1, 2 * kb + hh));
          const uint32_t al = a_lo0 + kb * 1024 + hh * 4, bl = b_lo0 + slot * 1024;
          wg_fence();
          wgmma_n256(acc, desc64(al, HI128), desc64(bl, HI128));
          wgmma_n256(acc, desc64(al + 2, HI128), desc64(bl + 128, HI128));
          wg_commit();
          if (LAGX && hh == 1 && kb == 7 && wgi == 0) bar_arrive(NB_LAG, 256);
          wg_wait<1>();
          if ((kb | hh) != 0 && lane < 2) mbar_arrive_remote(ebar + 8 * (2 * kb + hh - 1));
          if (++slot == 6) slot = 0;
        }
      }
      mbar_wait(BAR(sbar, 0), 0);
      r0 = __uint_as_float(lds2(sstat + (16 * warp + g) * 8).y);
      r1 = __uint_as_float(lds2(sstat + (16 * warp + g + 8) * 8).y);
      wg_wait<0>();
      if (lane < 2) mbar_arrive_remote(ebar + 8 * 15);
      PROF(7);
      make_p<8, false>(acc, r0, r1, px, pbase, 0, tag);
    }
    PROF(8);
    {
      float acc[96];
#pragma unroll
      for (int i = 0; i < 96; i++) acc[i] = 0.f;
      const uint32_t b_lo0 = desc_lo(sbase + 8 * SLOT, 2048);
      uint4* const pdst = pbase + ((7 * f + 3 * (f & 1)) >> 1) * 1024;
      auto stage_y = [&](int k) {
        if (LAGY && k == 16 - LAGY && wgi == 1) bar_sync(NB_LAG, 256);
        mbar_wait(BAR(full1, 16 + k));
        const uint32_t al = a_lo0 + (k >> 1) * 1024 + (k & 1) * 4, bl = b_lo0 + (k & 7) * 768;
        wg_fence();
        wgmma_n192(acc, desc64(al, HI128), desc64(bl, HI64));
        wgmma_n192(acc, desc64(al + 2, HI128), desc64(bl + 64, HI64));
        wg_commit();
      };
#pragma unroll
      for (int k = 0; k < 4; k++) {
        stage_y(k);
        st_tag(pdst + (k >> 1) * 1024 + (k & 1) * 64, px[2 * k], tag);
        st_tag(pdst + (k >> 1) * 1024 + (k & 1) * 64 + 32, px[2 * k + 1], tag);
        if (k == 3 && lane == 0) red_relaxed(&scr->cnt[(C_PX + rb) * 32]);
        wg_wait<1>();
        if (k != 0 && lane < 2) mbar_arrive_remote(ebar + 8 * (15 + k));
      }
#pragma unroll 1
      for (int k = 4; k < 16; k++) {
        stage_y(k);
        if (LAGY && k == 15 && wgi == 0) bar_arrive(NB_LAG, 256);
        wg_wait<1>();
        if (lane < 2) mbar_arrive_remote(ebar + 8 * (15 + k));
      }
      wg_wait<0>();
      if (lane < 2) mbar_arrive_remote(ebar + 8 * 31);
      PROF(9);
      make_p<6, true>(acc, r0, r1, py, pbase, 14 * f + ((f & 1) ? 0 : 8), tag);
      if (lane == 0) red_relaxed(&scr->cnt[(C_PY + rb) * 32 + (f >> 1)]);
    }
    PROF(10);
    {
      float acc[64];
      {
        const float m0 = wgi ? 0.f : __uint_as_float(lds2(sstat + 1024 + (16 * wq + g) * 8).x);
        const float m1 = wgi ? 0.f : __uint_as_float(lds2(sstat + 1024 + (16 * wq + g + 8) * 8).x);
#pragma unroll
        for (int i = 0; i < 64; i++) acc[i] = (i & 2) ? m1 : m0;
      }
      const uint32_t b2_lo0 = desc_lo(sbase, 8192);
      const uint32_t pa0 = sbase + (4 * rh + wq) * 2048;
      const uint32_t pbar = ebar + (uint32_t)(offsetof(Bars, emptyP) - offsetof(Bars, empty1));
      uint4 fa[3][4];
      uint32_t rdy = 0;
      mbar_wait(BAR(fullP, 0));
#pragma unroll
      for (int kk = 0; kk < 4; kk++) fa[0][kk] = lds4(pa0 + 4 * SLOT + kk * 512 + lane * 16);
      auto stage2 = [&](const int s) {
        uint4 (&a)[4] = fa[s % 3];
        ld_tag4_finish<32>(a, psrc + (int)((KORDER >> (4 * s)) & 15) * 1024, tag);
        if (s < 8 && lane < (s < 7 ? 2 : 1)) mbar_arrive_remote(pbar + 8 * s);
        if (s >= 2) {
          wg_wait<1>();
          if (s <= 8 && lane == 0) mbar_arrive(BAR(empty2, s - 2));
        }
        if (!rdy) {
          if (s < 13) mbar_wait(BAR(fullP, s + 1));
          mbar_wait(BAR(full2, s));
        }
        if (tid == 0) PROFP(16 + s);
        const uint32_t bl = b2_lo0 + (uint32_t)((BSLOT >> (4 * s)) & 15) * 1024;
        wg_fence();
        if (s < 13) {
#pragma unroll
          for (int kk = 0; kk < 4; kk++)
            fa[(s + 1) % 3][kk] = lds4(pa0 + (uint32_t)((PSLOT >> (4 * (s + 1))) & 15) * SLOT + kk * 512 + lane * 16);
          rdy = mbar_test(BAR(full2, s + 1));
          if (s < 12) rdy &= mbar_test(BAR(fullP, s + 2));
        }
#pragma unroll
        for (int kk = 0; kk < 4; kk++) wgmma_rs_n128(acc, a[kk].x, a[kk].y, a[kk].z, a[kk].w, desc64(bl + kk * 128, HI128));
        wg_commit();
      };
#pragma unroll
      for (int s = 0; s < 14 - LAG2; s++) stage2(s);
      bool dry = wgi == 1;
      const uint4* const xsrc = &scr->XP[c * 1024 + (tid & 127)];
#pragma unroll 1
      while (true) {
        uint4 pv[2][4];
        if (!dry) {
#pragma unroll
          for (int s = 14 - LAG2; s < 14; s++) stage2(s);
          if (wgi == 0) {
            bar_arrive(NB_LAG, 256);
          } else {
            ld_tag4_issue<128>(pv[0], xsrc);
            ld_tag4_issue<128>(pv[1], xsrc + 512);
          }
        }
        wg_wait<0>();
        PROF(11);
        int ln = lane;
        asm volatile("" : "+r"(ln));
#pragma unroll
        for (int h = 0; h < 2; h++)
#pragma unroll
          for (int q = 0; q < 4; q++)
            asm volatile("stmatrix.sync.aligned.m8n8.x4.shared.b16 [%0], {%1,%2,%3,%4};"
                         ::"r"(pa0 + (8 + h) * SLOT + (ln & 7) * 256 + (((4 * q + (ln >> 3)) ^ (ln & 7)) * 16)),
                           "r"(pack2(acc[16 * q + 2 * h], acc[16 * q + 2 * h + 1])), "r"(pack2(acc[16 * q + 4 + 2 * h], acc[16 * q + 5 + 2 * h])),
                           "r"(pack2(acc[16 * q + 8 + 2 * h], acc[16 * q + 9 + 2 * h])), "r"(pack2(acc[16 * q + 12 + 2 * h], acc[16 * q + 13 + 2 * h]))
                         : "memory");
        __syncwarp();
        uint4 w[8];
#pragma unroll
        for (int i = 0; i < 8; i++) {
          const int r = 2 * (i & 3) + (ln >> 4);
          w[i] = lds4(pa0 + (8 + (i >> 2)) * SLOT + r * 256 + (((ln & 15) ^ r) * 16));
        }
        uint4* dst;
        int dstr;
        if (wgi == 0 || dry) {
          if (!dry) mbar_wait(BAR(hbar, 0));
          const uint32_t hb = sbase + 4 * SLOT + ((ln >> 3) & 1) * 8192 + (16 * wq + (ln >> 4)) * 128;
#pragma unroll
          for (int i = 0; i < 8; i++) {
            pv[i >> 2][i & 3] = lds4(hb + i * 256 + (((ln & 7) ^ ((2 * i + (ln >> 4)) & 7)) * 16));
            if (2 * nq + ((ln >> 3) & 1) < NLL) pv[i >> 2][i & 3].x &= ~1u;
          }
          dst = &scr->XP[(c ^ 4) * 1024 + 32 * wq + ln];
          dstr = 128;
        } else {
          ld_tag4_finish<128>(pv[0], xsrc, tag);
          ld_tag4_finish<128>(pv[1], xsrc + 512, tag);
          dst = reinterpret_cast<uint4*>(out) + (16 * (c >> 4) + 2 * (4 * rh + wq) + (rb2 & 1) + 128 * (ln >> 4)) * 64 + nq * 16 + (ln & 15);
          dstr = 256 * 64;
        }
#pragma unroll
        for (int i = 0; i < 8; i++) {
          const uint4& p = pv[i >> 2][i & 3];
          const uint4 v = make_uint4(hadd2_bf16(w[i].x, p.x), hadd2_bf16(w[i].y, p.y), hadd2_bf16(w[i].z, p.z), hadd2_bf16(w[i].w, p.w));
          st_tag_pred(dst + i * dstr, v, wgi ? (v.x & 1u) : tag, !dry);
        }
        if (!dry) break;
        dry = false;
        bar_sync(NB_LAG, 256);
      }
      PROF(12);
      PROFG(15);
    }
  }
#undef BAR
#undef TOFF
#undef RBAR
}

typedef CUresult (*EncodeFn)(CUtensorMap*, CUtensorMapDataType, cuuint32_t, void*, const cuuint64_t*, const cuuint64_t*,
                             const cuuint32_t*, const cuuint32_t*, CUtensorMapInterleave, CUtensorMapSwizzle,
                             CUtensorMapL2promotion, CUtensorMapFloatOOBfill);

}

extern "C" void kernel_launch(void* const* d_in, const int* in_sizes, int n_in, void* d_out, int out_size) {
  (void)in_sizes; (void)n_in; (void)out_size;
  static EncodeFn encode = nullptr;
  static void *tab = nullptr, *scr = nullptr;
  if (!encode) {
    void* fn = nullptr;
    cudaDriverEntryPointQueryResult qr;
    cudaGetDriverEntryPoint("cuTensorMapEncodeTiled", &fn, cudaEnableDefault, &qr);
    encode = (EncodeFn)fn;
    cudaGetSymbolAddress(&tab, g_tab);
    cudaGetSymbolAddress(&scr, g_scr);
    cudaFuncSetAttribute(fused_kernel, cudaFuncAttributeMaxDynamicSharedMemorySize, SMEM_BYTES);
  }
  CUtensorMap tmGX, tmUX, tmGY, tmUY, tmD, tmWR, tmWI;
  const cuuint32_t es[5] = {1, 1, 1, 1, 1};
  auto enc = [&](CUtensorMap* m, void* p, int rank, const cuuint64_t* gd, const cuuint64_t* gs, const cuuint32_t* bd,
                 CUtensorMapSwizzle sw, CUtensorMapL2promotion pr) {
    encode(m, CU_TENSOR_MAP_DATA_TYPE_BFLOAT16, rank, p, gd, gs, bd, es, CU_TENSOR_MAP_INTERLEAVE_NONE, sw, pr,
           CU_TENSOR_MAP_FLOAT_OOB_FILL_NONE);
  };
  {
    const cuuint64_t gd[3] = {64, 512, 28}, gs[2] = {3584, 128};
    const cuuint32_t bd[3] = {64, 32, 2};
    enc(&tmGX, d_in[4], 3, gd, gs, bd, CU_TENSOR_MAP_SWIZZLE_128B, CU_TENSOR_MAP_L2_PROMOTION_L2_256B);
    enc(&tmUX, d_in[5], 3, gd, gs, bd, CU_TENSOR_MAP_SWIZZLE_128B, CU_TENSOR_MAP_L2_PROMOTION_L2_256B);
  }
  {
    const cuuint64_t gd[3] = {32, 512, 56}, gs[2] = {3584, 64};
    const cuuint32_t bd[3] = {32, 32, 3};
    enc(&tmGY, d_in[4], 3, gd, gs, bd, CU_TENSOR_MAP_SWIZZLE_64B, CU_TENSOR_MAP_L2_PROMOTION_L2_128B);
    enc(&tmUY, d_in[5], 3, gd, gs, bd, CU_TENSOR_MAP_SWIZZLE_64B, CU_TENSOR_MAP_L2_PROMOTION_L2_128B);
  }
  {
    const cuuint64_t gd[3] = {64, 1792, 8}, gs[2] = {1024, 128};
    const cuuint32_t bd[3] = {64, 64, 2};
    enc(&tmD, d_in[6], 3, gd, gs, bd, CU_TENSOR_MAP_SWIZZLE_128B, CU_TENSOR_MAP_L2_PROMOTION_L2_256B);
  }
  {
    const cuuint64_t gd[3] = {4112, 8, 16}, gs[2] = {16 * 8224, 8224};
    const cuuint32_t bd[3] = {40, 8, 16};
    enc(&tmWR, d_in[1], 3, gd, gs, bd, CU_TENSOR_MAP_SWIZZLE_NONE, CU_TENSOR_MAP_L2_PROMOTION_NONE);
    enc(&tmWI, d_in[2], 3, gd, gs, bd, CU_TENSOR_MAP_SWIZZLE_NONE, CU_TENSOR_MAP_L2_PROMOTION_NONE);
  }
  fused_kernel<<<NCTA, NTHREADS, SMEM_BYTES>>>((const __nv_bfloat16*)d_in[0], (const Tables*)tab, (Scratch*)scr,
                                               (__nv_bfloat16*)d_out, (const char*)d_in[4], (const char*)d_in[5],
                                               (const char*)d_in[6], tmWR, tmWI, tmGX, tmUX, tmGY, tmUY, tmD);
}
```

```cpp
#include <cuda_runtime.h>
#include <cuda_bf16.h>
#include <cuda.h>
#include <stdint.h>

namespace {

constexpr int NCTA = 128;
constexpr int NTHREADS = 384;
constexpr int SLOT = 16384;
constexpr int SMEM_BYTES = 14 * SLOT + 3072;
constexpr int SPIN_LIMIT = 1 << 22;

struct Scratch {
  uint4 Z1[128 * 1024];
  uint4 Z2[128 * 1024];
  uint4 LN[16 * 8 * 1024];
  uint4 P[16 * 28 * 1024];
  uint4 XP[128 * 1024];
  uint4 ST[1024];
  unsigned cnt[64 * 32];
};
__device__ __align__(1024) Scratch g_scr;
#define PROF(i)
#define PROFP(i)
#define PROFG(i)

constexpr double ccos(int i, int n) {
  i &= n - 1;
  if (i > n / 2) i = n - i;
  if (4 * i == n) return 0.0;
  const bool neg = 4 * i > n;
  if (neg) i = n / 2 - i;
  const double a = 6.283185307179586476925 * i / n, a2 = a * a;
  double term = 1.0, sum = 1.0;
  for (int k = 1; k < 14; k++) { term *= -a2 / ((2 * k - 1) * (2 * k)); sum += term; }
  return neg ? -sum : sum;
}
constexpr double csin(int i, int n) { return ccos(i - n / 4, n); }
constexpr unsigned fbits(double v, int mant) {
  if (v == 0.0) return 0;
  const unsigned sg = v < 0 ? 1u : 0u;
  if (v < 0) v = -v;
  int e = 127;
  while (v < 1.0) { v *= 2.0; e--; }
  const unsigned m = (unsigned)((v - 1.0) * (double)(1u << mant) + 0.5);
  return (sg << (8 + mant)) + ((unsigned)e << mant) + m;
}
constexpr unsigned pkb(double lo, double hi) { return fbits(lo, 7) | (fbits(hi, 7) << 16); }
constexpr double fa_elem(int kp, int n1) {
  return kp <= 8 ? ccos(kp * n1, 16) : -csin((kp - 8) * n1, 16);
}
constexpr unsigned cfrag_c(int idx, int n, int ri) {
  return ri ? pkb(-csin(idx, n), ccos(idx, n)) : pkb(ccos(idx, n), csin(idx, n));
}
struct Tables {
  unsigned fb[16][32][4];
  unsigned tw1[8][32][4];
  unsigned fa[32][4];
  unsigned f2[8][4][32][4];
  unsigned g2[8][4][32][4];
  unsigned gb[16][32][4];
  unsigned tw3[4][32][4];
  unsigned ga[32][4];
  unsigned f8[32][4], g8[32][4];
};
constexpr int T1_BYTES = 12800, T2_BYTES = 44544;
static_assert(sizeof(Tables) == T1_BYTES + T2_BYTES, "table size");
constexpr Tables make_tables() {
  Tables T = {};
  for (int l = 0; l < 32; l++) {
    const int g = l >> 2, t = l & 3;
    for (int i = 0; i < 4; i++)
      for (int u = 0; u < 8; u++) {
        const int ri = g & 1, m = 2 * (g >> 1) + ((u & 3) >> 1);
        const double sg = u >= 4 ? -1.0 : 1.0;
        const int k2 = u >= 4 ? 31 - 2 * m - (u & 1) : 2 * m + (u & 1);
        const int pa = (8 * t + i) * k2, pb = (8 * t + 4 + i) * k2;
        T.fb[i * 4 + (u >> 1)][l][(u & 1) * 2 + 0] = ri == 0 ? pkb(ccos(pa, 32), ccos(pb, 32)) : pkb(-sg * csin(pa, 32), -sg * csin(pb, 32));
        T.fb[i * 4 + (u >> 1)][l][(u & 1) * 2 + 1] = ri == 0 ? pkb(csin(pa, 32), csin(pb, 32)) : pkb(sg * ccos(pa, 32), sg * ccos(pb, 32));
      }
    for (int i = 0; i < 4; i++)
      for (int ks = 0; ks < 4; ks++) {
        const int n2 = 4 * g + i, m = 2 * t + (ks & 1);
        const double sg = ks >= 2 ? -1.0 : 1.0;
        const int pa = n2 * (ks >= 2 ? 31 - 2 * m : 2 * m), pb = n2 * (ks >= 2 ? 30 - 2 * m : 2 * m + 1);
        T.gb[i * 4 + ks][l][0] = pkb(ccos(pa, 32), -sg * csin(pa, 32));
        T.gb[i * 4 + ks][l][1] = pkb(csin(pa, 32), sg * ccos(pa, 32));
        T.gb[i * 4 + ks][l][2] = pkb(ccos(pb, 32), -sg * csin(pb, 32));
        T.gb[i * 4 + ks][l][3] = pkb(csin(pb, 32), sg * ccos(pb, 32));
      }
    for (int i = 0; i < 4; i++) {
      for (int e = 0; e < 2; e++) {
        const int p = (8 * t + 4 * e + i) * (g == 0 ? 8 : g);
        T.tw1[2 * i + e][l][0] = fbits(g == 0 ? 0.0 : ccos(p, 512), 23);
        T.tw1[2 * i + e][l][1] = fbits(g == 0 ? ccos(p, 512) : csin(p, 512), 23);
        T.tw1[2 * i + e][l][2] = fbits(g == 0 ? 0.0 : -csin(p, 512), 23);
        T.tw1[2 * i + e][l][3] = fbits(g == 0 ? -csin(p, 512) : ccos(p, 512), 23);
      }
      const int ka = t == 0 ? 8 : 2 * t, kb = 2 * t + 1;
      T.tw3[i][l][0] = fbits(ccos((4 * g + i) * ka, 512), 23);
      T.tw3[i][l][1] = fbits(csin((4 * g + i) * ka, 512), 23);
      T.tw3[i][l][2] = fbits(ccos((4 * g + i) * kb, 512), 23);
      T.tw3[i][l][3] = fbits(csin((4 * g + i) * kb, 512), 23);
      const int p8 = (t + 4 * (i & 1)) * (4 * (i >> 1) + (g >> 1));
      T.f8[l][i] = cfrag_c(p8, 8, g & 1);
      T.g8[l][i] = cfrag_c(-p8, 8, g & 1);
    }
    for (int w = 0; w < 8; w++)
      for (int i = 0; i < 16; i++) {
        const int kidx = t + 4 * (i & 1) + 8 * (i >> 3), nidx = 4 * ((i >> 1) & 3) + (g >> 1);
        T.f2[w][i >> 2][l][i & 3] = cfrag_c((8 * kidx + w) * nidx, 128, g & 1);
        T.g2[w][i >> 2][l][i & 3] = cfrag_c(-(8 * nidx + w) * kidx, 128, g & 1);
      }
    T.fa[l][0] = pkb(fa_elem(g, 2 * t), fa_elem(g, 2 * t + 1));
    T.fa[l][1] = pkb(fa_elem(g + 8, 2 * t), fa_elem(g + 8, 2 * t + 1));
    T.fa[l][2] = pkb(fa_elem(g, 2 * t + 8), fa_elem(g, 2 * t + 9));
    T.fa[l][3] = pkb(fa_elem(g + 8, 2 * t + 8), fa_elem(g + 8, 2 * t + 9));
    T.ga[l][0] = pkb(fa_elem(2 * t, g), fa_elem(2 * t + 1, g));
    T.ga[l][1] = pkb(fa_elem(2 * t, g + 8), fa_elem(2 * t + 1, g + 8));
    T.ga[l][2] = pkb(fa_elem(2 * t + 8, g), fa_elem(2 * t + 9, g));
    T.ga[l][3] = pkb(fa_elem(2 * t + 8, g + 8), fa_elem(2 * t + 9, g + 8));
  }
  return T;
}
__device__ const __align__(128) Tables g_tab = make_tables();

__device__ __forceinline__ void die() { asm volatile("st.global.u32 [%0], %1;" ::"l"(0ull), "r"(0) : "memory"); }
__device__ __forceinline__ uint32_t s2u(const void* p) { return (uint32_t)__cvta_generic_to_shared(p); }
__device__ __forceinline__ void mbar_init(uint32_t b, int c) { asm volatile("mbarrier.init.shared::cta.b64 [%0], %1;" ::"r"(b), "r"(c)); }
__device__ __forceinline__ void mbar_expect(uint32_t b, int bytes) {
  asm volatile("mbarrier.arrive.expect_tx.shared::cta.b64 _, [%0], %1;" ::"r"(b), "r"(bytes) : "memory");
}
__device__ __forceinline__ void mbar_arrive(uint32_t b) { asm volatile("mbarrier.arrive.shared::cta.b64 _, [%0];" ::"r"(b) : "memory"); }
__device__ __forceinline__ uint32_t mbar_try(uint32_t b, uint32_t parity) {
  uint32_t ok;
  asm volatile("{.reg .pred p; mbarrier.try_wait.parity.shared::cta.b64 p, [%1], %2; selp.u32 %0,1,0,p;}"
               : "=r"(ok) : "r"(b), "r"(parity) : "memory");
  return ok;
}
__device__ __forceinline__ uint32_t mbar_test(uint32_t b) {
  uint32_t ok;
  asm volatile("{.reg .pred p; mbarrier.test_wait.parity.shared::cta.b64 p, [%1], 0; selp.u32 %0,1,0,p;}" : "=r"(ok) : "r"(b) : "memory");
  return ok;
}
__device__ __forceinline__ void mbar_wait(uint32_t b, uint32_t parity = 0) {
  int it = 0;
#pragma unroll 1
  while (!mbar_try(b, parity))
    if (++it > SPIN_LIMIT) { die(); break; }
}
__device__ __forceinline__ void bar_sync(int id, int n) { asm volatile("bar.sync %0, %1;" ::"r"(id), "r"(n) : "memory"); }
__device__ __forceinline__ void bar_arrive(int id, int n) { asm volatile("bar.arrive %0, %1;" ::"r"(id), "r"(n) : "memory"); }
__device__ __forceinline__ void red_release(unsigned* p) { asm volatile("red.release.gpu.global.add.u32 [%0], 1;" ::"l"(p) : "memory"); }
__device__ __forceinline__ void red_relaxed(unsigned* p) { asm volatile("red.relaxed.gpu.global.add.u32 [%0], 1;" ::"l"(p) : "memory"); }
__device__ __forceinline__ unsigned ld_acquire(const unsigned* p) {
  unsigned v;
  asm volatile("ld.acquire.gpu.global.u32 %0, [%1];" : "=r"(v) : "l"(p) : "memory");
  return v;
}
__device__ __forceinline__ unsigned ld_relaxed(const unsigned* p) {
  unsigned v;
  asm volatile("ld.relaxed.gpu.global.u32 %0, [%1];" : "=r"(v) : "l"(p) : "memory");
  return v;
}
__device__ __forceinline__ void wait_counter(const unsigned* p, unsigned target) {
  int it = 0;
  while ((int)(ld_acquire(p) - target) < 0)
    if (++it > SPIN_LIMIT) { die(); break; }
}
__device__ __forceinline__ void sts4(uint32_t a, uint32_t x, uint32_t y, uint32_t z, uint32_t w) {
  asm volatile("st.shared.v4.u32 [%0], {%1,%2,%3,%4};" ::"r"(a), "r"(x), "r"(y), "r"(z), "r"(w) : "memory");
}
__device__ __forceinline__ uint4 lds4(uint32_t a) {
  uint4 v;
  asm volatile("ld.shared.v4.u32 {%0,%1,%2,%3}, [%4];" : "=r"(v.x), "=r"(v.y), "=r"(v.z), "=r"(v.w) : "r"(a) : "memory");
  return v;
}
__device__ __forceinline__ uint32_t pack2(float lo, float hi) {
  uint32_t r;
  asm("cvt.rn.bf16x2.f32 %0, %1, %2;" : "=r"(r) : "f"(hi), "f"(lo));
  return r;
}
__device__ __forceinline__ float bf_lo(uint32_t v) { return __uint_as_float(v << 16); }
__device__ __forceinline__ uint32_t hadd2_bf16(uint32_t a, uint32_t b) {
  uint32_t r;
  asm("add.rn.bf16x2 %0, %1, %2;" : "=r"(r) : "r"(a), "r"(b));
  return r;
}
__device__ __forceinline__ void mma16816(float (&d)[4], uint32_t a0, uint32_t a1, uint32_t a2, uint32_t a3, uint32_t b0, uint32_t b1) {
  asm("mma.sync.aligned.m16n8k16.row.col.f32.bf16.bf16.f32 {%0,%1,%2,%3}, {%4,%5,%6,%7}, {%8,%9}, {%0,%1,%2,%3};"
      : "+f"(d[0]), "+f"(d[1]), "+f"(d[2]), "+f"(d[3])
      : "r"(a0), "r"(a1), "r"(a2), "r"(a3), "r"(b0), "r"(b1));
}
template <int N>
__device__ __forceinline__ void cs_frac(int idx, float& c, float& s) {
  int i = ((idx + N / 2) & (N - 1)) - N / 2;
  float a = (float)i * (6.283185307179586f / N);
  c = __cosf(a);
  s = __sinf(a);
}
template <int N>
__device__ __forceinline__ uint32_t cfrag(int idx, int ri) {
  float c, s;
  cs_frac<N>(idx, c, s);
  return ri ? pack2(-s, c) : pack2(c, s);
}
__device__ __forceinline__ uint32_t word(const uint4& v, int e) { return e == 0 ? v.x : e == 1 ? v.y : e == 2 ? v.z : v.w; }
__device__ __forceinline__ void cdft16(const uint4 (&q)[4], const uint4 (&F)[4], uint4 (&o)[4]) {
  float acc[2][4][4];
#pragma unroll
  for (int p = 0; p < 2; p++)
#pragma unroll
    for (int v = 0; v < 4; v++) {
      acc[p][v][0] = acc[p][v][1] = acc[p][v][2] = acc[p][v][3] = 0.f;
#pragma unroll
      for (int ks = 0; ks < 2; ks++)
        mma16816(acc[p][v], word(q[2 * ks], 2 * p), word(q[2 * ks], 2 * p + 1), word(q[2 * ks + 1], 2 * p),
                 word(q[2 * ks + 1], 2 * p + 1), word(F[ks * 2 + (v >> 1)], (v & 1) * 2), word(F[ks * 2 + (v >> 1)], (v & 1) * 2 + 1));
    }
#pragma unroll
  for (int v = 0; v < 4; v++)
    o[v] = make_uint4(pack2(acc[0][v][0], acc[0][v][1]), pack2(acc[0][v][2], acc[0][v][3]),
                      pack2(acc[1][v][0], acc[1][v][1]), pack2(acc[1][v][2], acc[1][v][3]));
}
__device__ __forceinline__ void st_tag(uint4* p, const uint4& v, uint32_t tag) {
  asm volatile("{.reg .b128 r; .reg .b64 a, b; mov.b64 a, {%1,%2}; mov.b64 b, {%3,%4}; mov.b128 r, {a,b}; st.relaxed.gpu.global.b128 [%0], r;}"
               ::"l"(p), "r"((v.x & ~1u) | tag), "r"(v.y), "r"(v.z), "r"(v.w) : "memory");
}
__device__ __forceinline__ uint4 ld_b128(const uint4* p) {
  uint4 v;
  asm volatile("{.reg .b128 r; .reg .b64 a, b; ld.relaxed.gpu.global.b128 r, [%4]; mov.b128 {a,b}, r; mov.b64 {%0,%1}, a; mov.b64 {%2,%3}, b;}"
               : "=r"(v.x), "=r"(v.y), "=r"(v.z), "=r"(v.w) : "l"(p) : "memory");
  return v;
}
template <int STRIDE>
__device__ __forceinline__ void ld_tag4_issue(uint4 (&q)[4], const uint4* p) {
#pragma unroll
  for (int i = 0; i < 4; i++) q[i] = ld_b128(p + i * STRIDE);
}
template <int STRIDE>
__device__ __forceinline__ void ld_tag4_finish(uint4 (&q)[4], const uint4* p, uint32_t tag) {
  int it = 0;
#pragma unroll 1
  while (__any_sync(0xffffffffu, ((q[0].x ^ tag) | (q[1].x ^ tag) | (q[2].x ^ tag) | (q[3].x ^ tag)) & 1u)) {
    ld_tag4_issue<STRIDE>(q, p);
    if (++it > SPIN_LIMIT) { die(); break; }
  }
#pragma unroll
  for (int i = 0; i < 4; i++) asm volatile("and.b32 %0, %0, 0xfffffffe;" : "+r"(q[i].x));
}
__device__ __forceinline__ void row_stats(const uint32_t (&a)[8], const uint32_t (&b)[8], int lane, float (&sum)[2], float (&sq)[2]) {
  float da[4] = {0.f, 0.f, 0.f, 0.f}, db[4] = {0.f, 0.f, 0.f, 0.f}, ds[4] = {0.f, 0.f, 0.f, 0.f};
#pragma unroll
  for (int q = 0; q < 4; q++) {
    mma16816(ds, a[2 * q], b[2 * q], a[2 * q + 1], b[2 * q + 1], 0x3f803f80u, 0x3f803f80u);
    mma16816(da, a[2 * q], b[2 * q], a[2 * q + 1], b[2 * q + 1], a[2 * q], a[2 * q + 1]);
    mma16816(db, a[2 * q], b[2 * q], a[2 * q + 1], b[2 * q + 1], b[2 * q], b[2 * q + 1]);
  }
  const int src = (lane & 28) | (lane >> 3);
  const float qa = __shfl_sync(0xffffffffu, (lane & 4) ? da[1] : da[0], src);
  const float qb = __shfl_sync(0xffffffffu, (lane & 4) ? db[3] : db[2], src);
  float v = (lane & 2) ? ((lane & 1) ? ds[2] : ds[0]) : ((lane & 1) ? qb : qa);
  v += __shfl_xor_sync(0xffffffffu, v, 4);
  v += __shfl_xor_sync(0xffffffffu, v, 8);
  v += __shfl_xor_sync(0xffffffffu, v, 16);
  sq[0] = __shfl_sync(0xffffffffu, v, 0);
  sq[1] = __shfl_sync(0xffffffffu, v, 1);
  sum[0] = __shfl_sync(0xffffffffu, v, 2);
  sum[1] = __shfl_sync(0xffffffffu, v, 3);
}
__device__ __forceinline__ uint64_t desc64(uint32_t lo, uint32_t hi) {
  uint64_t d;
  asm("mov.b64 %0, {%1, %2};" : "=l"(d) : "r"(lo), "r"(hi));
  return d;
}
constexpr uint32_t desc_hi(uint32_t sbo, uint32_t swz) { return (sbo >> 4) | (swz << 30); }
__device__ __forceinline__ uint32_t desc_lo(uint32_t addr, uint32_t lbo) { return ((addr & 0x3FFFF) >> 4) | ((lbo >> 4) << 16); }
__device__ __forceinline__ void cp_async16(uint32_t dst, const void* src) {
  asm volatile("cp.async.cg.shared.global [%0], [%1], 16;" ::"r"(dst), "l"(src) : "memory");
}
__device__ __forceinline__ uint2 lds2(uint32_t a) {
  uint2 v;
  asm volatile("ld.shared.v2.u32 {%0,%1}, [%2];" : "=r"(v.x), "=r"(v.y) : "r"(a) : "memory");
  return v;
}
__device__ __forceinline__ uint32_t lds_u16(uint32_t a) {
  uint16_t v;
  asm volatile("ld.shared.u16 %0, [%1];" : "=h"(v) : "r"(a) : "memory");
  return v;
}
__device__ __forceinline__ void wg_fence() { asm volatile("wgmma.fence.sync.aligned;" ::: "memory"); }
__device__ __forceinline__ void wg_commit() { asm volatile("wgmma.commit_group.sync.aligned;" ::: "memory"); }
template <int N>
__device__ __forceinline__ void wg_wait() { asm volatile("wgmma.wait_group.sync.aligned %0;" ::"n"(N) : "memory"); }
__device__ __forceinline__ void bulk_load(uint32_t dst, const void* src, int bytes, uint32_t bar) {
  asm volatile("cp.async.bulk.shared::cluster.global.mbarrier::complete_tx::bytes [%0], [%1], %2, [%3];"
               ::"r"(dst), "l"(src), "r"(bytes), "r"(bar) : "memory");
}
__device__ __forceinline__ void bulk_load_mc(uint32_t dst, const void* src, int bytes, uint32_t bar) {
  asm volatile("cp.async.bulk.shared::cluster.global.mbarrier::complete_tx::bytes.multicast::cluster [%0], [%1], %2, [%3], %4;"
               ::"r"(dst), "l"(src), "r"(bytes), "r"(bar), "h"((uint16_t)3) : "memory");
}
__device__ __forceinline__ void tma3(uint32_t dst, const CUtensorMap* tm, uint32_t bar, int c0, int c1, int c2) {
  asm volatile("cp.async.bulk.tensor.3d.shared::cluster.global.mbarrier::complete_tx::bytes [%0], [%1, {%3,%4,%5}], [%2];"
               ::"r"(dst), "l"(tm), "r"(bar), "r"(c0), "r"(c1), "r"(c2) : "memory");
}
__device__ __forceinline__ void tma3_mc(uint32_t dst, const CUtensorMap* tm, uint32_t bar, int c1, int c2) {
  asm volatile("cp.async.bulk.tensor.3d.shared::cluster.global.mbarrier::complete_tx::bytes.multicast::cluster [%0], [%1, {%3,%4,%5}], [%2], %6;"
               ::"r"(dst), "l"(tm), "r"(bar), "r"(0), "r"(c1), "r"(c2), "h"((uint16_t)3) : "memory");
}
__device__ __forceinline__ void mbar_arrive_remote(uint32_t rb) {
  asm volatile("mbarrier.arrive.shared::cluster.b64 _, [%0];" ::"r"(rb) : "memory");
}
__device__ __forceinline__ uint4 ldg_ca4(const void* p) {
  uint4 v;
  asm volatile("ld.global.ca.v4.u32 {%0,%1,%2,%3}, [%4];" : "=r"(v.x), "=r"(v.y), "=r"(v.z), "=r"(v.w) : "l"(p) : "memory");
  return v;
}
__device__ __forceinline__ uint32_t clock32() {
  uint32_t v;
  asm volatile("mov.u32 %0, %%clock;" : "=r"(v) :: "memory");
  return v;
}
__device__ __forceinline__ float swiglu(float g, float u, float r) {
  float hg = (0.5f * r) * g, th;
  asm("tanh.approx.f32 %0, %1;" : "=f"(th) : "f"(hg));
  return fmaf(hg, th, hg) * (r * u);
}
__device__ __forceinline__ uint32_t hsub2_bf16(uint32_t a, uint32_t b) {
  uint32_t r;
  asm("sub.rn.bf16x2 %0, %1, %2;" : "=r"(r) : "r"(a), "r"(b));
  return r;
}
__device__ __forceinline__ void l2_prefetch(const void* p, int bytes) {
  asm volatile("cp.async.bulk.prefetch.L2.global [%0], %1;" ::"l"(p), "r"(bytes) : "memory");
}

__device__ __forceinline__ void wgmma_n256(float (&d)[128], uint64_t da, uint64_t db, int sd = 1) {
  asm volatile("{.reg .pred p; setp.ne.b32 p, %130, 0;\n"
      "wgmma.mma_async.sync.aligned.m64n256k16.f32.bf16.bf16 {"
      "%0,%1,%2,%3,%4,%5,%6,%7,%8,%9,%10,%11,%12,%13,%14,%15,"
      "%16,%17,%18,%19,%20,%21,%22,%23,%24,%25,%26,%27,%28,%29,%30,%31,"
      "%32,%33,%34,%35,%36,%37,%38,%39,%40,%41,%42,%43,%44,%45,%46,%47,"
      "%48,%49,%50,%51,%52,%53,%54,%55,%56,%57,%58,%59,%60,%61,%62,%63,"
      "%64,%65,%66,%67,%68,%69,%70,%71,%72,%73,%74,%75,%76,%77,%78,%79,"
      "%80,%81,%82,%83,%84,%85,%86,%87,%88,%89,%90,%91,%92,%93,%94,%95,"
      "%96,%97,%98,%99,%100,%101,%102,%103,%104,%105,%106,%107,%108,%109,%110,%111,"
      "%112,%113,%114,%115,%116,%117,%118,%119,%120,%121,%122,%123,%124,%125,%126,%127"
      "}, %128, %129, p, 1, 1, 0, 1;}\n"
      : "+f"(d[0]),"+f"(d[1]),"+f"(d[2]),"+f"(d[3]),"+f"(d[4]),"+f"(d[5]),"+f"(d[6]),"+f"(d[7]),
        "+f"(d[8]),"+f"(d[9]),"+f"(d[10]),"+f"(d[11]),"+f"(d[12]),"+f"(d[13]),"+f"(d[14]),"+f"(d[15]),
        "+f"(d[16]),"+f"(d[17]),"+f"(d[18]),"+f"(d[19]),"+f"(d[20]),"+f"(d[21]),"+f"(d[22]),"+f"(d[23]),
        "+f"(d[24]),"+f"(d[25]),"+f"(d[26]),"+f"(d[27]),"+f"(d[28]),"+f"(d[29]),"+f"(d[30]),"+f"(d[31]),
        "+f"(d[32]),"+f"(d[33]),"+f"(d[34]),"+f"(d[35]),"+f"(d[36]),"+f"(d[37]),"+f"(d[38]),"+f"(d[39]),
        "+f"(d[40]),"+f"(d[41]),"+f"(d[42]),"+f"(d[43]),"+f"(d[44]),"+f"(d[45]),"+f"(d[46]),"+f"(d[47]),
        "+f"(d[48]),"+f"(d[49]),"+f"(d[50]),"+f"(d[51]),"+f"(d[52]),"+f"(d[53]),"+f"(d[54]),"+f"(d[55]),
        "+f"(d[56]),"+f"(d[57]),"+f"(d[58]),"+f"(d[59]),"+f"(d[60]),"+f"(d[61]),"+f"(d[62]),"+f"(d[63]),
        "+f"(d[64]),"+f"(d[65]),"+f"(d[66]),"+f"(d[67]),"+f"(d[68]),"+f"(d[69]),"+f"(d[70]),"+f"(d[71]),
        "+f"(d[72]),"+f"(d[73]),"+f"(d[74]),"+f"(d[75]),"+f"(d[76]),"+f"(d[77]),"+f"(d[78]),"+f"(d[79]),
        "+f"(d[80]),"+f"(d[81]),"+f"(d[82]),"+f"(d[83]),"+f"(d[84]),"+f"(d[85]),"+f"(d[86]),"+f"(d[87]),
        "+f"(d[88]),"+f"(d[89]),"+f"(d[90]),"+f"(d[91]),"+f"(d[92]),"+f"(d[93]),"+f"(d[94]),"+f"(d[95]),
        "+f"(d[96]),"+f"(d[97]),"+f"(d[98]),"+f"(d[99]),"+f"(d[100]),"+f"(d[101]),"+f"(d[102]),"+f"(d[103]),
        "+f"(d[104]),"+f"(d[105]),"+f"(d[106]),"+f"(d[107]),"+f"(d[108]),"+f"(d[109]),"+f"(d[110]),"+f"(d[111]),
        "+f"(d[112]),"+f"(d[113]),"+f"(d[114]),"+f"(d[115]),"+f"(d[116]),"+f"(d[117]),"+f"(d[118]),"+f"(d[119]),
        "+f"(d[120]),"+f"(d[121]),"+f"(d[122]),"+f"(d[123]),"+f"(d[124]),"+f"(d[125]),"+f"(d[126]),"+f"(d[127])
      : "l"(da), "l"(db), "r"(sd));
}
__device__ __forceinline__ void wgmma_n192(float (&d)[96], uint64_t da, uint64_t db) {
  asm volatile("wgmma.mma_async.sync.aligned.m64n192k16.f32.bf16.bf16 {"
      "%0,%1,%2,%3,%4,%5,%6,%7,%8,%9,%10,%11,%12,%13,%14,%15,"
      "%16,%17,%18,%19,%20,%21,%22,%23,%24,%25,%26,%27,%28,%29,%30,%31,"
      "%32,%33,%34,%35,%36,%37,%38,%39,%40,%41,%42,%43,%44,%45,%46,%47,"
      "%48,%49,%50,%51,%52,%53,%54,%55,%56,%57,%58,%59,%60,%61,%62,%63,"
      "%64,%65,%66,%67,%68,%69,%70,%71,%72,%73,%74,%75,%76,%77,%78,%79,"
      "%80,%81,%82,%83,%84,%85,%86,%87,%88,%89,%90,%91,%92,%93,%94,%95"
      "}, %96, %97, 1, 1, 1, 0, 1;\n"
      : "+f"(d[0]),"+f"(d[1]),"+f"(d[2]),"+f"(d[3]),"+f"(d[4]),"+f"(d[5]),"+f"(d[6]),"+f"(d[7]),
        "+f"(d[8]),"+f"(d[9]),"+f"(d[10]),"+f"(d[11]),"+f"(d[12]),"+f"(d[13]),"+f"(d[14]),"+f"(d[15]),
        "+f"(d[16]),"+f"(d[17]),"+f"(d[18]),"+f"(d[19]),"+f"(d[20]),"+f"(d[21]),"+f"(d[22]),"+f"(d[23]),
        "+f"(d[24]),"+f"(d[25]),"+f"(d[26]),"+f"(d[27]),"+f"(d[28]),"+f"(d[29]),"+f"(d[30]),"+f"(d[31]),
        "+f"(d[32]),"+f"(d[33]),"+f"(d[34]),"+f"(d[35]),"+f"(d[36]),"+f"(d[37]),"+f"(d[38]),"+f"(d[39]),
        "+f"(d[40]),"+f"(d[41]),"+f"(d[42]),"+f"(d[43]),"+f"(d[44]),"+f"(d[45]),"+f"(d[46]),"+f"(d[47]),
        "+f"(d[48]),"+f"(d[49]),"+f"(d[50]),"+f"(d[51]),"+f"(d[52]),"+f"(d[53]),"+f"(d[54]),"+f"(d[55]),
        "+f"(d[56]),"+f"(d[57]),"+f"(d[58]),"+f"(d[59]),"+f"(d[60]),"+f"(d[61]),"+f"(d[62]),"+f"(d[63]),
        "+f"(d[64]),"+f"(d[65]),"+f"(d[66]),"+f"(d[67]),"+f"(d[68]),"+f"(d[69]),"+f"(d[70]),"+f"(d[71]),
        "+f"(d[72]),"+f"(d[73]),"+f"(d[74]),"+f"(d[75]),"+f"(d[76]),"+f"(d[77]),"+f"(d[78]),"+f"(d[79]),
        "+f"(d[80]),"+f"(d[81]),"+f"(d[82]),"+f"(d[83]),"+f"(d[84]),"+f"(d[85]),"+f"(d[86]),"+f"(d[87]),
        "+f"(d[88]),"+f"(d[89]),"+f"(d[90]),"+f"(d[91]),"+f"(d[92]),"+f"(d[93]),"+f"(d[94]),"+f"(d[95])
      : "l"(da), "l"(db));
}
template <int SD>
__device__ __forceinline__ void wgmma_rs_n128(float (&d)[64], uint32_t a0, uint32_t a1, uint32_t a2, uint32_t a3, uint64_t db) {
  asm volatile("wgmma.mma_async.sync.aligned.m64n128k16.f32.bf16.bf16 {"
      "%0,%1,%2,%3,%4,%5,%6,%7,%8,%9,%10,%11,%12,%13,%14,%15,"
      "%16,%17,%18,%19,%20,%21,%22,%23,%24,%25,%26,%27,%28,%29,%30,%31,"
      "%32,%33,%34,%35,%36,%37,%38,%39,%40,%41,%42,%43,%44,%45,%46,%47,"
      "%48,%49,%50,%51,%52,%53,%54,%55,%56,%57,%58,%59,%60,%61,%62,%63"
      "}, {%64,%65,%66,%67}, %68, %69, 1, 1, 1;\n"
      : "+f"(d[0]),"+f"(d[1]),"+f"(d[2]),"+f"(d[3]),"+f"(d[4]),"+f"(d[5]),"+f"(d[6]),"+f"(d[7]),
        "+f"(d[8]),"+f"(d[9]),"+f"(d[10]),"+f"(d[11]),"+f"(d[12]),"+f"(d[13]),"+f"(d[14]),"+f"(d[15]),
        "+f"(d[16]),"+f"(d[17]),"+f"(d[18]),"+f"(d[19]),"+f"(d[20]),"+f"(d[21]),"+f"(d[22]),"+f"(d[23]),
        "+f"(d[24]),"+f"(d[25]),"+f"(d[26]),"+f"(d[27]),"+f"(d[28]),"+f"(d[29]),"+f"(d[30]),"+f"(d[31]),
        "+f"(d[32]),"+f"(d[33]),"+f"(d[34]),"+f"(d[35]),"+f"(d[36]),"+f"(d[37]),"+f"(d[38]),"+f"(d[39]),
        "+f"(d[40]),"+f"(d[41]),"+f"(d[42]),"+f"(d[43]),"+f"(d[44]),"+f"(d[45]),"+f"(d[46]),"+f"(d[47]),
        "+f"(d[48]),"+f"(d[49]),"+f"(d[50]),"+f"(d[51]),"+f"(d[52]),"+f"(d[53]),"+f"(d[54]),"+f"(d[55]),
        "+f"(d[56]),"+f"(d[57]),"+f"(d[58]),"+f"(d[59]),"+f"(d[60]),"+f"(d[61]),"+f"(d[62]),"+f"(d[63])
      : "r"(a0), "r"(a1), "r"(a2), "r"(a3), "l"(db), "n"(SD));
}

constexpr int C_LN = 0, C_PX = 16, C_PY = 32;
constexpr int NB_CONS = 1, NB_LN = 2, NB_LAG = 4, NB_INIT = 6, NB_RDY = 7;
#define LAGX 3
#define LAGY 3
#define LAG2 5
#define NLL 2
#define POLL_DELAY3 1200
#define POLL_DELAY 1100
#define FILT_DELAY 1000
#define THR_B 0
#define THR_P 0
#define SPEC -1
#define WARM 4
#define HWARM 0
#define POLL_DELAY2 POLL_DELAY
#define RING_SIG 1
#define PF2_SIG 1
constexpr int SM_E = 0, SM_X = 16384, SM_E2 = 32768, SM_W = 49152, SM_FC = 69632, SM_T = 73728 - T1_BYTES;
constexpr unsigned long long KORDER = 0xBA9432DC876510ull;
constexpr unsigned long long BSLOT = 0x76532107653210ull, PSLOT = 0xDCBA984DCBA984ull;
constexpr uint32_t HI128 = desc_hi(1024, 1), HI64 = desc_hi(512, 2);

struct Bars {
  uint64_t full1[32], empty1[32], full2[16], fullA[8], empty2[8], fullP[16], emptyP[8], hbar, tbar, hint[3], sig[2], sbar;
  uint32_t epoch;
};

template <int NK, bool STORE>
__device__ __forceinline__ void make_p(const float (&acc)[NK * 16], float r0, float r1, uint4 (&p)[NK], uint4* pbase, int ks0, uint32_t tag) {
#pragma unroll
  for (int j = 0; j < NK; j++) {
    uint32_t w[4];
#pragma unroll
    for (int i = 0; i < 4; i++) {
      const int a = 8 * j + 2 * i, b = a + NK * 8;
      w[i] = pack2(swiglu(acc[a], acc[b], (i & 1) ? r1 : r0), swiglu(acc[a + 1], acc[b + 1], (i & 1) ? r1 : r0));
    }
    asm volatile("" : "+r"(w[0]), "+r"(w[1]), "+r"(w[2]), "+r"(w[3]));
    p[j] = make_uint4(w[0], w[1], w[2], w[3]);
    if (STORE) st_tag(pbase + ((ks0 + j) >> 2) * 1024 + ((ks0 + j) & 3) * 32, p[j], tag);
  }
}
__device__ __forceinline__ void spin_cycles(uint32_t n) {
  const uint32_t t0 = clock32();
  while (clock32() - t0 < n) {}
}

__device__ __forceinline__ void spin_until(uint32_t t) {
  float d[4] = {0.f, 0.f, 0.f, 0.f};
  while ((int)(clock32() - t) < 0) {
    if (HWARM) asm volatile("mma.sync.aligned.m16n8k16.row.col.f32.bf16.bf16.f32 {%0,%1,%2,%3}, {%4,%4,%4,%4}, {%4,%4}, {%0,%1,%2,%3};"
                            : "+f"(d[0]), "+f"(d[1]), "+f"(d[2]), "+f"(d[3]) : "r"(t));
  }
}

__global__ void __cluster_dims__(2, 1, 1) __launch_bounds__(NTHREADS, 1)
fused_kernel(const __nv_bfloat16* __restrict__ x, const Tables* __restrict__ tab, Scratch* __restrict__ scr,
             __nv_bfloat16* __restrict__ out, const char* __restrict__ wg_raw, const char* __restrict__ wu_raw,
             const char* __restrict__ wd_raw,
             const __grid_constant__ CUtensorMap tmWR, const __grid_constant__ CUtensorMap tmWI,
             const __grid_constant__ CUtensorMap tmGX, const __grid_constant__ CUtensorMap tmUX,
             const __grid_constant__ CUtensorMap tmGY, const __grid_constant__ CUtensorMap tmUY,
             const __grid_constant__ CUtensorMap tmD) {
  extern __shared__ __align__(1024) char smem_raw[];
  const uint32_t sbase = s2u(smem_raw);
  const uint32_t sbar = sbase + 14 * SLOT, sstat = sbar + 1280;
  const int tid = threadIdx.x, lane = tid & 31;
  const int c = blockIdx.x, rk = c & 1, f = (c >> 1) & 7, rb = 2 * (c >> 4) + rk;
  const int rb2 = 2 * (c >> 4) + (f >> 2), kh = (f >> 1) & 1, nq = 2 * (f & 1) + rk;
#define BAR(field, i) (sbar + (uint32_t)offsetof(Bars, field) + 8u * (i))
#define TOFF(field) (sbase + SM_T + (uint32_t)offsetof(Tables, field) + lane * 16)

  if (tid >= 256) {
    asm volatile("setmaxnreg.dec.sync.aligned.u32 56;");
    const int warp = __shfl_sync(0xffffffffu, tid >> 5, 0);
    const unsigned epoch = ld_relaxed(&scr->cnt[(C_LN + rb) * 32]) >> 3;
    if (lane == 0) {
      if (warp == 8) {
        if (sbase & 1023) die();
#pragma unroll
        for (int i = 0; i < 16; i++) mbar_init(BAR(emptyP, i), i < 7 ? 16 : i < 8 ? 8 : i < 13 ? 1 : i < 15 ? 8 : 32);
        mbar_expect(BAR(tbar, 0), T2_BYTES + 2 * 10240);
        mbar_expect(BAR(hbar, 0), 16384);
      } else if (warp == 9) {
#pragma unroll
        for (int i = 0; i < 32; i++) mbar_init(BAR(full1, i), 1);
#pragma unroll
        for (int i = 0; i < 32; i++) mbar_expect(BAR(full1, i), i < 16 ? 16384 : 12288);
      } else if (warp == 10) {
#pragma unroll
        for (int i = 0; i < 32; i++) mbar_init(BAR(empty1, i), 16);
#pragma unroll
        for (int i = 0; i < 14; i++) mbar_init(BAR(fullP, i), 1);
#pragma unroll
        for (int i = 0; i < 14; i++) mbar_expect(BAR(fullP, i), 16384);
      } else {
#pragma unroll
        for (int i = 0; i < 32; i++) mbar_init(BAR(full2, i), i < 24 ? 1 : 8);
#pragma unroll
        for (int i = 0; i < 24; i++) mbar_expect(BAR(full2, i), 16384);
      }
      asm volatile("fence.mbarrier_init.release.cluster;" ::: "memory");
    }
    if (tid == 256) {
      const int w0 = ((c >> 3) * 257 + 32 * (c & 7) + 1) & ~7;
      if (FILT_DELAY) {
        asm volatile("prefetch.tensormap [%0];" ::"l"(&tmWR) : "memory");
        asm volatile("prefetch.tensormap [%0];" ::"l"(&tmWI) : "memory");
        spin_cycles(FILT_DELAY);
      }
      tma3(sbase + SM_W, &tmWR, BAR(tbar, 0), w0, 0, 0);
      tma3(sbase + SM_W + 10240, &tmWI, BAR(tbar, 0), w0, 0, 0);
      bulk_load(sbase + SM_T + T1_BYTES, reinterpret_cast<const char*>(tab) + T1_BYTES, T2_BYTES, BAR(tbar, 0));
    }
    if (tid == 288) {
      asm volatile("prefetch.tensormap [%0];" ::"l"(rk ? &tmUX : &tmGX) : "memory");
      asm volatile("prefetch.tensormap [%0];" ::"l"(rk ? &tmUY : &tmGY) : "memory");
      asm volatile("prefetch.tensormap [%0];" ::"l"(&tmD) : "memory");
    }
    if (tid == 320) asm volatile("st.shared.u32 [%0], %1;" ::"r"(BAR(epoch, 0)), "r"(epoch) : "memory");
    __syncwarp();
    asm volatile("barrier.cluster.arrive.relaxed.aligned;" ::: "memory");
    bar_arrive(NB_RDY, 384);
    asm volatile("barrier.cluster.wait.aligned;" ::: "memory");
    bar_sync(NB_INIT, 384);
    if (warp == 8) {
      if (lane == 0) {
        const int ax = (7 * f + 3 * (f & 1)) >> 1;
        const int ay = 7 * f + ((f & 1) ? 0 : 4);
        const CUtensorMap* tx = rk ? &tmUX : &tmGX;
        const CUtensorMap* ty = rk ? &tmUY : &tmGY;
        if (RING_SIG >= 0) mbar_wait(BAR(sig, RING_SIG));
        uint32_t s = 2;
#pragma unroll 1
        for (int n = 0; n < 16; n++) {
          if (n >= 6) mbar_wait(BAR(empty1, n - 6));
          tma3_mc(sbase + (8 + s) * SLOT + rk * 8192, tx, BAR(full1, n), n * 32, ax);
          if (++s == 6) s = 0;
        }
#pragma unroll 1
        for (int k = 0; k < 16; k++) {
          mbar_wait(BAR(empty1, k < 8 ? 10 + ((12 * k + 11) >> 4) : 8 + k));
          tma3_mc(sbase + 8 * SLOT + (k & 7) * 12288 + rk * 6144, ty, BAR(full1, 16 + k), k * 32, ay);
        }
      }
    } else if (warp == 9) {
      if (lane == 0) {
#pragma unroll 1
        for (int i = 0; i < 14; i++) {
          const int kblk = 14 * kh + (int)((KORDER >> (4 * i)) & 15);
          const int j = i < 7 ? i : i - 7, sl = j + (j >= 4);
          mbar_wait(i < 7 ? BAR(empty1, 17 + 2 * sl) : BAR(empty2, j));
          if (THR_B && i >= THR_B) mbar_wait(BAR(full2, i - THR_B));
          tma3(sbase + sl * SLOT, &tmD, BAR(full2, i), 0, 64 * kblk, 2 * nq);
        }
        wait_counter(&scr->cnt[(C_LN + rb2) * 32], (epoch + 1) * 8);
        asm volatile("fence.proxy.async.global;" ::: "memory");
        mbar_wait(BAR(emptyP, 7));
        bulk_load(sbase + 4 * SLOT, &scr->LN[(rb2 * 8 + 2 * nq) * 1024 + (kh ^ 1) * 512], 8192, BAR(hbar, 0));
        bulk_load(sbase + 4 * SLOT + 8192, &scr->LN[(rb2 * 8 + 2 * nq + 1) * 1024 + (kh ^ 1) * 512], 8192, BAR(hbar, 0));
      }
    } else if (warp == 10) {
      bar_sync(NB_LN, 288);
      if (lane == 0) {
        PROFP(0);
        red_release(&scr->cnt[(C_LN + rb) * 32]);
        PROFP(1);
        wait_counter(&scr->cnt[(C_LN + rb) * 32], (epoch + 1) * 8);
        asm volatile("fence.proxy.async.global;" ::: "memory");
        PROFP(2);
#pragma unroll 1
        for (int kb = NLL; kb < 8; kb++) bulk_load(sbase + kb * SLOT, &scr->LN[(rb * 8 + kb) * 1024], 16384, BAR(fullA, kb));
#pragma unroll 1
        for (int s = 0; s < 14; s++) {
          const int kblk = 14 * kh + (int)((KORDER >> (4 * s)) & 15);
          if (s == 0 || (SPEC < 0 && (s == 8 || s == 11))) {
            if (s != 11) PROFP(3 + (s >> 2));
            mbar_wait(BAR(hint, s == 0 ? 0 : s == 8 ? 1 : 2), 0);
            if (s != 11) PROFP(4 + (s >> 2));
          }
          const int j = s < 7 ? s : s - 7;
          mbar_wait(s < 7 ? BAR(empty1, 24 + s + (s == 0) + (s >= 4)) : BAR(emptyP, j));
          if (THR_P && s >= THR_P) mbar_wait(BAR(fullP, s - THR_P));
          if (SPEC >= 0 && s == 8) mbar_wait(BAR(emptyP, SPEC & 7));
          bulk_load_mc(sbase + (j ? 7 + j : 4) * SLOT + rk * 8192, &scr->P[(rb2 * 28 + kblk) * 1024 + rk * 512], 8192, BAR(fullP, s));
        }
        PROFP(7);
      }
    } else {
      if (lane == 0) {
        l2_prefetch(wg_raw + (size_t)c * 5376, 5376);
        l2_prefetch(wu_raw + (size_t)c * 5376, 5376);
        mbar_wait(BAR(sig, PF2_SIG), 0);
        l2_prefetch(wg_raw + 688128 + (size_t)c * 8960, 8960);
        l2_prefetch(wu_raw + 688128 + (size_t)c * 8960, 8960);
      }
      mbar_wait(BAR(fullA, 7), 0);
      if (lane == 0) l2_prefetch(wd_raw + (size_t)c * 14336, 14336);
      {
        const uint32_t tag = (epoch + 1) & 1;
        uint4 v0, v1, v2;
        int it = 0;
        while (true) {
          v0 = ld_b128(&scr->ST[rb * 64 + lane]);
          v1 = ld_b128(&scr->ST[rb * 64 + 32 + lane]);
          v2 = ld_b128(&scr->ST[rb2 * 64 + 32 * (kh ^ 1) + lane]);
          if (!__any_sync(0xffffffffu, ((v0.x ^ tag) | (v1.x ^ tag) | (v2.x ^ tag)) & 1u)) break;
          if (++it > SPIN_LIMIT) { die(); break; }
        }
        sts4(sstat + lane * 16, v0.x & ~1u, v0.y, v0.z, v0.w);
        sts4(sstat + 512 + lane * 16, v1.x & ~1u, v1.y, v1.z, v1.w);
        sts4(sstat + 1024 + lane * 16, v2.x & ~1u, v2.y, v2.z, v2.w);
#pragma unroll 4
        for (int i = 0; i < 32; i++)
          st_tag(&scr->XP[(c ^ 4) * 1024 + i * 32 + lane], make_uint4(0, 0, 0, 0), tag ^ 1);
        mbar_arrive(BAR(sbar, 0));
      }
      if (lane == 0) {
        mbar_wait(BAR(empty1, 17));
#pragma unroll 1
        for (int e = 0; e < (SPEC < 0 ? 3 : 1); e++) {
          const unsigned* cp = e == 0 ? &scr->cnt[(C_PX + rb2) * 32] : &scr->cnt[(C_PY + rb2) * 32 + 2 * kh + e - 1];
          if (e == 1) mbar_wait(BAR(fullP, 0), 0);
          int it = 0;
          while ((int)(ld_relaxed(cp) - (epoch + 1) * (e == 0 ? 64 : 16)) < 0)
            if (++it > SPIN_LIMIT) { die(); break; }
          mbar_arrive(BAR(hint, e));
        }
      }
    }
  } else {
    const int warp = __shfl_sync(0xffffffffu, tid >> 5, 0);
    const int g = lane >> 2, t = lane & 3;
    PROF(0);
    PROFG(14);
#pragma unroll
    for (int i = 0; i < 4; i++) {
      const int r = i >> 1, ch = (i & 1) * 32 + lane;
      cp_async16(sbase + SM_X + (2 * warp + r) * 1024 + ((ch ^ ((ch >> 2) & 6)) * 16),
                 x + (size_t)(c + 128 * (2 * warp + r)) * 512 + ch * 8);
    }
    asm volatile("cp.async.commit_group;" ::: "memory");
    asm volatile("barrier.cluster.arrive.relaxed.aligned;" ::: "memory");
    uint4 tw[8], fb[16];
    const uint4 fa = ldg_ca4(&tab->fa[lane][0]);
#pragma unroll
    for (int i = 0; i < 8; i++) tw[i] = ldg_ca4(&tab->tw1[i][lane][0]);
#pragma unroll
    for (int i = 0; i < 16; i++) fb[i] = ldg_ca4(&tab->fb[i][lane][0]);
    uint32_t rbar;
    asm volatile("mapa.shared::cluster.u32 %0, %1, %2;" : "=r"(rbar) : "r"(sbar), "r"(rk ^ 1));
#define RBAR(field, i) (rbar + (uint32_t)offsetof(Bars, field) + 8u * (i))
    {
      const int ln = (tid >> 1) & 31, lg = ln >> 2, lt = ln & 3, i = 4 * (tid >> 6) + 2 * (tid & 1);
      const int kidx = lt + 8 * (i >> 3), nidx = 4 * ((i >> 1) & 3) + (lg >> 1);
      const uint32_t a0 = cfrag<2048>((c + 128 * kidx) * nidx, lg & 1), a1 = cfrag<2048>((c + 128 * (kidx + 4)) * nidx, lg & 1);
      const uint32_t b0 = cfrag<2048>(-(c + 128 * nidx) * kidx, lg & 1), b1 = cfrag<2048>(-(c + 128 * nidx) * (kidx + 4), lg & 1);
      asm volatile("st.shared.v2.u32 [%0], {%1,%2};" ::"r"(sbase + SM_FC + tid * 8), "r"(a0), "r"(a1) : "memory");
      asm volatile("st.shared.v2.u32 [%0], {%1,%2};" ::"r"(sbase + SM_FC + 2048 + tid * 8), "r"(b0), "r"(b1) : "memory");
    }
    asm volatile("cp.async.wait_group 0;" ::: "memory");
    __syncwarp();
    bar_arrive(NB_INIT, 384);
    PROF(13);
    uint32_t tag;
    uint4 q[4], o[4];
    {
      uint32_t v[2][8];
#pragma unroll
      for (int r = 0; r < 2; r++)
#pragma unroll
        for (int q = 0; q < 4; q++) {
          const uint2 u = lds2(sbase + SM_X + (2 * warp + r) * 1024 + (t + 4 * (q >> 1)) * 128 + (((4 * (q & 1) + (g >> 1)) ^ (2 * t)) * 16) + (g & 1) * 8);
          v[r][2 * q] = u.x; v[r][2 * q + 1] = u.y;
        }
      float sum[2], sq[2], rstd[2];
      row_stats(v[0], v[1], lane, sum, sq);
#pragma unroll
      for (int r = 0; r < 2; r++) {
        const float m = sum[r] * (1.f / 512.f);
        rstd[r] = rsqrtf(fmaxf(fmaf(-m, m, sq[r] * (1.f / 512.f)), 0.f) + 1e-5f);
      }
      uint32_t alo[4][4], ahi[4][4];
#pragma unroll
      for (int r = 0; r < 2; r++)
#pragma unroll
        for (int i = 0; i < 4; i++) {
          const uint32_t sel = (i & 1) ? 0x7632u : 0x5410u;
          const uint32_t b0 = __byte_perm(v[r][i >> 1], v[r][2 + (i >> 1)], sel);
          const uint32_t b1 = __byte_perm(v[r][4 + (i >> 1)], v[r][6 + (i >> 1)], sel);
          float d[4] = {0.f, 0.f, 0.f, 0.f};
          mma16816(d, fa.x, fa.y, fa.z, fa.w, b0, b1);
          const uint4 &ka = tw[2 * i], &kb = tw[2 * i + 1];
          const uint32_t re = pack2(d[0] * __uint_as_float(ka.x) + d[2] * __uint_as_float(ka.y), d[1] * __uint_as_float(kb.x) + d[3] * __uint_as_float(kb.y));
          const uint32_t im = pack2(d[0] * __uint_as_float(ka.z) + d[2] * __uint_as_float(ka.w), d[1] * __uint_as_float(kb.z) + d[3] * __uint_as_float(kb.w));
          const uint32_t dc = pack2(fmaf(sum[r], -1.f / 32.f, d[0]), fmaf(sum[r], -1.f / 32.f, d[1]));
          alo[i][r] = re; alo[i][2 + r] = im;
          ahi[i][r] = g == 0 ? dc : re; ahi[i][2 + r] = g == 0 ? 0u : im;
        }
      float acc[8][4];
#pragma unroll
      for (int u = 0; u < 8; u++) {
        acc[u][0] = acc[u][1] = acc[u][2] = acc[u][3] = 0.f;
#pragma unroll
        for (int i = 0; i < 4; i++) {
          const uint4& bq = fb[i * 4 + (u >> 1)];
          if (u < 4) mma16816(acc[u], alo[i][0], alo[i][1], alo[i][2], alo[i][3], (u & 1) ? bq.z : bq.x, (u & 1) ? bq.w : bq.y);
          else       mma16816(acc[u], ahi[i][0], ahi[i][1], ahi[i][2], ahi[i][3], (u & 1) ? bq.z : bq.x, (u & 1) ? bq.w : bq.y);
        }
      }
#pragma unroll
      for (int r = 0; r < 2; r++)
#pragma unroll
        for (int h = 0; h < 2; h++) {
          const int j = 2 * warp + r, m = 2 * t + h;
          const float rs = rstd[r];
          sts4(sbase + SM_E + ((j * 8 + m) * 8 + (g ^ (2 * t) ^ (2 * (j & 3)))) * 16,
               pack2(acc[2 * h][2 * r] * rs, acc[2 * h][2 * r + 1] * rs), pack2(acc[2 * h + 1][2 * r] * rs, acc[2 * h + 1][2 * r + 1] * rs),
               pack2(acc[4 + 2 * h][2 * r] * rs, acc[4 + 2 * h][2 * r + 1] * rs), pack2(acc[5 + 2 * h][2 * r] * rs, acc[5 + 2 * h][2 * r + 1] * rs));
        }
      if (tid == 0) PROFP(12);
      bar_sync(NB_RDY, 384);
      if (tid == 0) PROFP(13);
      uint4 fc[4];
#pragma unroll
      for (int i = 0; i < 4; i++) fc[i] = lds4(sbase + SM_FC + i * 512 + lane * 16);
      asm volatile("ld.shared.u32 %0, [%1];" : "=r"(tag) : "r"(BAR(epoch, 0)) : "memory");
      tag = (tag + 1) & 1;
#pragma unroll
      for (int i = 0; i < 4; i++) q[i] = lds4(sbase + SM_E + (((t + 4 * i) * 8 + warp) * 8 + (g ^ (warp & 6) ^ (2 * t))) * 16);
      cdft16(q, fc, o);
#pragma unroll
      for (int vv = 0; vv < 4; vv++) st_tag(&scr->Z1[(((4 * vv + t) * 8 + warp) * 128 + c) * 8 + g], o[vv], tag);
    }
    PROF(1);
    asm volatile("setmaxnreg.inc.sync.aligned.u32 224;");
    {
      const uint4* const zp = &scr->Z1[(c * 128 + 8 * t + warp) * 8 + g];
      const uint32_t tst = clock32();
      mbar_wait(BAR(tbar, 0), 0);
      if (tid == 0) PROFP(14);
      uint4 f2[4], g2[4];
#pragma unroll
      for (int i = 0; i < 4; i++) {
        f2[i] = lds4(TOFF(f2) + warp * 2048 + i * 512);
        g2[i] = lds4(TOFF(g2) + warp * 2048 + i * 512);
      }
      const uint4 f8 = lds4(TOFF(f8)), g8 = lds4(TOFF(g8));
      float wfr[16], wfi[16];
      {
        const float fsc = 1.f / (1 << 19);
        const float fsc3 = ((c & 7) == 7 && g == 0) ? 0.5f * fsc : fsc;
        const int gg = g == 0 ? 8 : g, wsh = (2 * (c >> 3) + 2) & 15;
#pragma unroll
        for (int i = 0; i < 16; i++) {
          const int ci = i >> 3, dd = (i >> 2) & 1, e = i & 3;
          const int kk = (e == 0 ? gg : e == 1 ? 16 + gg : e == 2 ? 16 - g : 32 - g) - 1;
          const uint32_t a = sbase + SM_W + ((2 * warp + ci) * 8 + t + 4 * dd) * 80 + wsh + 2 * kk;
          wfr[i] = bf_lo(lds_u16(a)) * (e == 3 ? fsc3 : fsc);
          wfi[i] = bf_lo(lds_u16(a + 10240)) * (e == 3 ? fsc3 : fsc);
        }
      }
      asm volatile("barrier.cluster.wait.aligned;" ::: "memory");
      PROF(2);
      spin_until(tst + POLL_DELAY);
      ld_tag4_issue<256>(q, zp);
      ld_tag4_finish<256>(q, zp, tag);
      if (tid == 0) PROFP(30);
      if (lane == 0) mbar_arrive(BAR(sig, 0));
      cdft16(q, f2, o);
      const uint32_t e2 = sbase + SM_E2;
#pragma unroll
      for (int vv = 0; vv < 4; vv++)
        sts4(e2 + ((warp * 16 + 4 * vv + t) * 8 + (g ^ (2 * t) ^ (2 * (warp & 3)))) * 16, o[vv].x, o[vv].y, o[vv].z, o[vv].w);
      bar_sync(NB_CONS, 256);
#pragma unroll
      for (int ci = 0; ci < 2; ci++) {
        const int cc = 2 * warp + ci;
        uint32_t ad[2];
        uint4 u[2];
#pragma unroll
        for (int hh = 0; hh < 2; hh++) {
          ad[hh] = e2 + (((t + 4 * hh) * 16 + cc) * 8 + (g ^ (2 * (cc & 3)) ^ (2 * t))) * 16;
          u[hh] = lds4(ad[hh]);
        }
        uint32_t res[2][4];
#pragma unroll
        for (int p = 0; p < 2; p++) {
          uint32_t y[2][2];
#pragma unroll
          for (int vv = 0; vv < 2; vv++) {
            float d[4] = {0.f, 0.f, 0.f, 0.f};
            mma16816(d, word(u[0], 2 * p), word(u[0], 2 * p + 1), word(u[1], 2 * p), word(u[1], 2 * p + 1), word(f8, 2 * vv), word(f8, 2 * vv + 1));
#pragma unroll
            for (int rr = 0; rr < 2; rr++) {
              const float fr = wfr[ci * 8 + vv * 4 + 2 * p + rr], fi = wfi[ci * 8 + vv * 4 + 2 * p + rr];
              y[vv][rr] = pack2(d[2 * rr] * fr - d[2 * rr + 1] * fi, d[2 * rr] * fi + d[2 * rr + 1] * fr);
            }
          }
#pragma unroll
          for (int vv = 0; vv < 2; vv++) {
            float d[4] = {0.f, 0.f, 0.f, 0.f};
            mma16816(d, y[0][0], y[0][1], y[1][0], y[1][1], word(g8, 2 * vv), word(g8, 2 * vv + 1));
            res[vv][2 * p] = pack2(d[0], d[1]);
            res[vv][2 * p + 1] = pack2(d[2], d[3]);
          }
        }
#pragma unroll
        for (int vv = 0; vv < 2; vv++) sts4(ad[vv], res[vv][0], res[vv][1], res[vv][2], res[vv][3]);
      }
      bar_sync(NB_CONS, 256);
#pragma unroll
      for (int i = 0; i < 4; i++) q[i] = lds4(e2 + ((warp * 16 + 4 * i + t) * 8 + (g ^ (2 * t) ^ (2 * (warp & 3)))) * 16);
      cdft16(q, g2, o);
#pragma unroll
      for (int vv = 0; vv < 4; vv++) st_tag(&scr->Z2[((8 * (4 * vv + t) + warp) * 128 + c) * 8 + g], o[vv], tag);
    }
    PROF(3);
    {
      const uint4* const zp = &scr->Z2[((c * 16 + t) * 8 + warp) * 8 + g];
      const uint32_t tst = clock32();
      uint4 gb[16], gc[4], tw[4], xr[2][2];
#pragma unroll
      for (int i = 0; i < 16; i++) gb[i] = lds4(TOFF(gb) + i * 512);
      const uint4 ga = lds4(TOFF(ga));
#pragma unroll
      for (int i = 0; i < 4; i++) {
        gc[i] = lds4(sbase + SM_FC + 2048 + i * 512 + lane * 16);
        tw[i] = lds4(TOFF(tw3) + i * 512);
        const int ch = 4 * (g + 8 * (i & 1)) + t;
        xr[i >> 1][i & 1] = lds4(sbase + SM_X + (2 * warp + (i >> 1)) * 1024 + ((ch ^ ((ch >> 2) & 6)) * 16));
      }
      PROF(4);
      spin_until(tst + POLL_DELAY2);
      ld_tag4_issue<256>(q, zp);
      ld_tag4_finish<256>(q, zp, tag);
      if (tid == 0) PROFP(31);
      if (lane == 0) mbar_arrive(BAR(sig, 1));
      cdft16(q, gc, o);
#pragma unroll
      for (int vv = 0; vv < 4; vv++)
        sts4(sbase + SM_E + (((4 * vv + t) * 8 + warp) * 8 + (g ^ (warp & 6) ^ (2 * t))) * 16, o[vv].x, o[vv].y, o[vv].z, o[vv].w);
      if (tid == 0) PROFP(8);
      bar_sync(NB_CONS, 256);
      if (tid == 0) PROFP(9);
      uint32_t hv[2][8];
      const float mk = t == 0 ? 0.f : 1.f;
#pragma unroll
      for (int r = 0; r < 2; r++) {
        const int j = 2 * warp + r;
        uint4 u[2];
#pragma unroll
        for (int h = 0; h < 2; h++) u[h] = lds4(sbase + SM_E + ((j * 8 + 2 * t + h) * 8 + (g ^ (2 * t) ^ (2 * (j & 3)))) * 16);
        float yv[4][4];
#pragma unroll
        for (int i = 0; i < 4; i++) {
          float lo[4] = {0.f, 0.f, 0.f, 0.f}, hi[4] = {0.f, 0.f, 0.f, 0.f};
          mma16816(lo, gb[i * 4].x, gb[i * 4].y, gb[i * 4].z, gb[i * 4].w, u[0].x, u[0].y);
          mma16816(lo, gb[i * 4 + 1].x, gb[i * 4 + 1].y, gb[i * 4 + 1].z, gb[i * 4 + 1].w, u[1].x, u[1].y);
          mma16816(hi, gb[i * 4 + 2].x, gb[i * 4 + 2].y, gb[i * 4 + 2].z, gb[i * 4 + 2].w, u[0].z, u[0].w);
          mma16816(hi, gb[i * 4 + 3].x, gb[i * 4 + 3].y, gb[i * 4 + 3].z, gb[i * 4 + 3].w, u[1].z, u[1].w);
          const float ca = __uint_as_float(tw[i].x), sa = __uint_as_float(tw[i].y), cb = __uint_as_float(tw[i].z), sb = __uint_as_float(tw[i].w);
          const float tr0 = fmaf(hi[0], mk, lo[0]), ti0 = fmaf(hi[2], mk, lo[2]);
          const float tr1 = lo[1] + hi[1], ti1 = lo[3] + hi[3];
          const float vr0 = tr0 * ca - ti0 * sa, vi0 = tr0 * sa + ti0 * ca;
          const float vr1 = tr1 * cb - ti1 * sb, vi1 = tr1 * sb + ti1 * cb;
          const uint32_t b0 = pack2(t == 0 ? hi[0] : vr0, vr1), b1 = pack2(t == 0 ? vr0 : vi0, vi1);
          yv[i][0] = yv[i][1] = yv[i][2] = yv[i][3] = 0.f;
          mma16816(yv[i], ga.x, ga.y, ga.z, ga.w, b0, b1);
        }
#pragma unroll
        for (int h = 0; h < 2; h++) {
          hv[r][4 * h + 0] = hadd2_bf16(xr[r][h].x, pack2(yv[0][2 * h], yv[1][2 * h]));
          hv[r][4 * h + 1] = hadd2_bf16(xr[r][h].y, pack2(yv[2][2 * h], yv[3][2 * h]));
          hv[r][4 * h + 2] = hadd2_bf16(xr[r][h].z, pack2(yv[0][2 * h + 1], yv[1][2 * h + 1]));
          hv[r][4 * h + 3] = hadd2_bf16(xr[r][h].w, pack2(yv[2][2 * h + 1], yv[3][2 * h + 1]));
        }
      }
      if (tid == 0 && hv[0][0] != 0x12345 && hv[1][7] != 0x12345) PROFP(10);
      float ds[4] = {0.f, 0.f, 0.f, 0.f};
#pragma unroll
      for (int q4 = 0; q4 < 4; q4++) mma16816(ds, hv[0][2 * q4], hv[1][2 * q4], hv[0][2 * q4 + 1], hv[1][2 * q4 + 1], 0x3f803f80u, 0x3f803f80u);
#pragma unroll
      for (int o2 = 4; o2 <= 16; o2 <<= 1) {
        ds[0] += __shfl_xor_sync(0xffffffffu, ds[0], o2);
        ds[2] += __shfl_xor_sync(0xffffffffu, ds[2], o2);
      }
      uint32_t mb[2];
#pragma unroll
      for (int r = 0; r < 2; r++) {
        const int row = 16 * f + 2 * warp + r;
        mb[r] = pack2(ds[2 * r] * (1.f / 512.f), ds[2 * r] * (1.f / 512.f));
#pragma unroll
        for (int i = 0; i < 8; i++) hv[r][i] = hsub2_bf16(hv[r][i], mb[r]);
#pragma unroll
        for (int h = 0; h < 2; h++) {
          const int n1 = g + 8 * h;
          st_tag(&scr->LN[(rb * 8 + (n1 >> 1)) * 1024 + row * 8 + ((4 * (n1 & 1) + t) ^ (row & 7))],
                 make_uint4(hv[r][4 * h], hv[r][4 * h + 1], hv[r][4 * h + 2], hv[r][4 * h + 3]), n1 < 2 * NLL ? tag : (hv[r][4 * h] & 1u));
        }
      }
      if (tid == 0) PROFP(11);
      bar_arrive(NB_LN, 288);
      float sum[2], sq[2], rstd[2];
      row_stats(hv[0], hv[1], lane, sum, sq);
#pragma unroll
      for (int r = 0; r < 2; r++) {
        const float m = sum[r] * (1.f / 512.f);
        rstd[r] = rsqrtf(fmaxf(fmaf(-m, m, sq[r] * (1.f / 512.f)), 0.f) + 1e-5f);
      }
      if (lane == 0)
        st_tag(&scr->ST[rb * 64 + 8 * f + warp], make_uint4(mb[0] << 16, __float_as_uint(rstd[0]), mb[1] << 16, __float_as_uint(rstd[1])), tag);
    }
    PROF(5);
    const int wgi = warp >> 2, wq = warp & 3;
    uint4* const pbase = &scr->P[rb * 28 * 1024 + warp * 128 + lane];
    const uint32_t a_lo0 = desc_lo(sbase + wgi * 8192, 16);
    const uint32_t ebar = lane == 0 ? BAR(empty1, 0) : RBAR(empty1, 0);
    float r0, r1;
    uint4 px[8], py[6];
    const int rh = wgi ^ kh ^ 1;
    const uint4* const psrc = &scr->P[(rb2 * 28 + 14 * kh) * 1024 + (4 * rh + wq) * 128 + lane];
    const uint32_t pa0 = sbase + (4 * rh + wq) * 2048;
    uint4 pf[LAG2 > 3 ? LAG2 : 3][4];
    uint32_t rdy;
    auto fetch2 = [&](int s, uint4 (&a)[4]) {
#pragma unroll
      for (int kk = 0; kk < 4; kk++) a[kk] = lds4(pa0 + (uint32_t)((PSLOT >> (4 * s)) & 15) * SLOT + kk * 512 + lane * 16);
    };
    {
      float acc[128];
#pragma unroll
      for (int i = 0; i < 128; i++) acc[i] = 0.f;
      const uint32_t b_lo0 = desc_lo(sbase + 8 * SLOT, 4096);
      const uint32_t t3 = clock32();
      if (WARM) {
        wg_fence();
#pragma unroll
        for (int i = 0; i < WARM; i++) wgmma_n256(acc, desc64(a_lo0 + 6 * 1024, HI128), desc64(b_lo0, HI128));
        wg_commit();
      }
      if (NLL) {
        const uint4* const ap = &scr->LN[rb * 8 * 1024 + tid];
        uint4 av[NLL ? NLL : 1][4];
        while (clock32() - t3 < POLL_DELAY3) {}
  #pragma unroll
        for (int kb = 0; kb < NLL; kb++) ld_tag4_issue<256>(av[kb], ap + kb * 1024);
        bar_sync(NB_CONS, 256);
  #pragma unroll
        for (int kb = 0; kb < NLL; kb++) {
          ld_tag4_finish<256>(av[kb], ap + kb * 1024, tag);
  #pragma unroll
          for (int i = 0; i < 4; i++) sts4(sbase + kb * SLOT + (tid + 256 * i) * 16, av[kb][i].x, av[kb][i].y, av[kb][i].z, av[kb][i].w);
        }
        asm volatile("fence.proxy.async.shared::cta;" ::: "memory");
        bar_sync(NB_CONS, 256);
      }
      uint32_t slot = 2;
#pragma unroll 1
      for (int kb = 0; kb < 8; kb++) {
        if (kb >= NLL) mbar_wait(BAR(fullA, kb), 0);
        if (kb == 0) PROF(6);
#pragma unroll
        for (int hh = 0; hh < 2; hh++) {
          if (LAGX && hh == ((16 - LAGX) & 1) && kb == ((16 - LAGX) >> 1) && wgi == 1) bar_sync(NB_LAG, 256);
          mbar_wait(BAR(full1, 2 * kb + hh));
          const uint32_t al = a_lo0 + kb * 1024 + hh * 4, bl = b_lo0 + slot * 1024;
          wg_fence();
          wgmma_n256(acc, desc64(al, HI128), desc64(bl, HI128), (kb | hh) != 0);
          wgmma_n256(acc, desc64(al + 2, HI128), desc64(bl + 128, HI128));
          wg_commit();
          if (LAGX && hh == 1 && kb == 7 && wgi == 0) bar_arrive(NB_LAG, 256);
          wg_wait<1>();
          if ((kb | hh) != 0 && lane < 2) mbar_arrive_remote(ebar + 8 * (2 * kb + hh - 1));
          if (++slot == 6) slot = 0;
        }
      }
      mbar_wait(BAR(sbar, 0), 0);
      r0 = __uint_as_float(lds2(sstat + (16 * warp + g) * 8).y);
      r1 = __uint_as_float(lds2(sstat + (16 * warp + g + 8) * 8).y);
      wg_wait<0>();
      if (lane < 2) mbar_arrive_remote(ebar + 8 * 15);
      PROF(7);
      make_p<8, false>(acc, r0, r1, px, pbase, 0, tag);
    }
    PROF(8);
    {
      float acc[96];
#pragma unroll
      for (int i = 0; i < 96; i++) acc[i] = 0.f;
      const uint32_t b_lo0 = desc_lo(sbase + 8 * SLOT, 2048);
      uint4* const pdst = pbase + ((7 * f + 3 * (f & 1)) >> 1) * 1024;
      auto stage_y = [&](int k) {
        if (LAGY && k == 16 - LAGY && wgi == 1) bar_sync(NB_LAG, 256);
        mbar_wait(BAR(full1, 16 + k));
        const uint32_t al = a_lo0 + (k >> 1) * 1024 + (k & 1) * 4, bl = b_lo0 + (k & 7) * 768;
        wg_fence();
        wgmma_n192(acc, desc64(al, HI128), desc64(bl, HI64));
        wgmma_n192(acc, desc64(al + 2, HI128), desc64(bl + 64, HI64));
        wg_commit();
      };
#pragma unroll
      for (int k = 0; k < 4; k++) {
        stage_y(k);
        st_tag(pdst + (k >> 1) * 1024 + (k & 1) * 64, px[2 * k], tag);
        st_tag(pdst + (k >> 1) * 1024 + (k & 1) * 64 + 32, px[2 * k + 1], tag);
        if (k == 3 && lane == 0) red_relaxed(&scr->cnt[(C_PX + rb) * 32]);
        wg_wait<1>();
        if (k != 0 && lane < 2) mbar_arrive_remote(ebar + 8 * (15 + k));
      }
#pragma unroll 1
      for (int k = 4; k < 16; k++) {
        stage_y(k);
        if (LAGY && k == 15 && wgi == 0) bar_arrive(NB_LAG, 256);
        wg_wait<1>();
        if (lane < 2) mbar_arrive_remote(ebar + 8 * (15 + k));
      }
      mbar_wait(BAR(fullP, 0));
      fetch2(0, pf[0]);
      rdy = mbar_test(BAR(full2, 0)) & mbar_test(BAR(fullP, 1));
      wg_wait<0>();
      if (lane < 2) mbar_arrive_remote(ebar + 8 * 31);
      PROF(9);
      make_p<6, true>(acc, r0, r1, py, pbase, 14 * f + ((f & 1) ? 0 : 8), tag);
      if (lane == 0) red_relaxed(&scr->cnt[(C_PY + rb) * 32 + (f >> 1)]);
    }
    PROF(10);
    {
      float acc[64];
      const uint32_t b2_lo0 = desc_lo(sbase, 8192);
      const uint32_t pbar = ebar + (uint32_t)(offsetof(Bars, emptyP) - offsetof(Bars, empty1));
      constexpr int S1 = 14 - LAG2;
      constexpr int NF = LAG2 > 3 ? LAG2 : 3;
      auto check2 = [&](int s) {
        ld_tag4_finish<32>(pf[s % NF], psrc + (int)((KORDER >> (4 * s)) & 15) * 1024, tag);
      };
      auto mma2 = [&](int s) {
        const uint32_t bl = b2_lo0 + (uint32_t)((BSLOT >> (4 * s)) & 15) * 1024;
        const uint4 (&a)[4] = pf[s % NF];
        if (s == 0) wgmma_rs_n128<0>(acc, a[0].x, a[0].y, a[0].z, a[0].w, desc64(bl, HI128));
        else wgmma_rs_n128<1>(acc, a[0].x, a[0].y, a[0].z, a[0].w, desc64(bl, HI128));
#pragma unroll
        for (int kk = 1; kk < 4; kk++) wgmma_rs_n128<1>(acc, a[kk].x, a[kk].y, a[kk].z, a[kk].w, desc64(bl + kk * 128, HI128));
      };
#pragma unroll
      for (int s = 0; s < S1; s++) {
        check2(s);
        if (s < 8 && lane < (s < 7 ? 2 : 1)) mbar_arrive_remote(pbar + 8 * s);
        if (s >= 2) {
          wg_wait<1>();
          if (s <= 8 && lane == 0) mbar_arrive(BAR(empty2, s - 2));
        }
        if (!rdy) {
          mbar_wait(BAR(fullP, s + 1));
          mbar_wait(BAR(full2, s));
        }
        if (tid == 0) PROFP(16 + s);
        wg_fence();
        fetch2(s + 1, pf[(s + 1) % NF]);
        rdy = mbar_test(BAR(full2, s + 1)) & mbar_test(BAR(fullP, s + 2));
        mma2(s);
        wg_commit();
      }
      wg_wait<0>();
#pragma unroll
      for (int s = S1 + 1; s < 14; s++) {
        mbar_wait(BAR(fullP, s));
        fetch2(s, pf[s % NF]);
      }
#pragma unroll
      for (int s = S1; s < 14; s++) {
        check2(s);
        mbar_wait(BAR(full2, s));
      }
      if (tid == 0) PROFP(16 + S1);
      if (wgi == 1) bar_sync(NB_LAG, 256);
      wg_fence();
#pragma unroll
      for (int s = S1; s < 14; s++) mma2(s);
      wg_commit();
      if (wgi == 0) bar_arrive(NB_LAG, 256);
      uint4 pv[2][4];
      const uint4* const xsrc = &scr->XP[c * 1024 + (tid & 127)];
      if (wgi == 0) {
        mbar_wait(BAR(hbar, 0));
        const uint32_t hb = sbase + 4 * SLOT + ((lane >> 3) & 1) * 8192 + (16 * wq + (lane >> 4)) * 128;
#pragma unroll
        for (int i = 0; i < 8; i++) {
          uint4 v = lds4(hb + i * 256 + (((lane & 7) ^ ((2 * i + (lane >> 4)) & 7)) * 16));
          if (2 * nq + ((lane >> 3) & 1) < NLL) v.x &= ~1u;
          const uint32_t m = __byte_perm(lds2(sstat + 1024 + (16 * wq + 2 * i + (lane >> 4)) * 8).x, 0, 0x3232);
          pv[i >> 2][i & 3] = make_uint4(hadd2_bf16(v.x, m), hadd2_bf16(v.y, m), hadd2_bf16(v.z, m), hadd2_bf16(v.w, m));
        }
      } else {
        ld_tag4_issue<128>(pv[0], xsrc);
        ld_tag4_issue<128>(pv[1], xsrc + 512);
      }
      wg_wait<0>();
      PROF(11);
#pragma unroll
      for (int h = 0; h < 2; h++)
#pragma unroll
        for (int q = 0; q < 4; q++)
          asm volatile("stmatrix.sync.aligned.m8n8.x4.shared.b16 [%0], {%1,%2,%3,%4};"
                       ::"r"(pa0 + (9 + h) * SLOT + (lane & 7) * 256 + (((4 * q + (lane >> 3)) ^ (lane & 7)) * 16)),
                         "r"(pack2(acc[16 * q + 2 * h], acc[16 * q + 2 * h + 1])), "r"(pack2(acc[16 * q + 4 + 2 * h], acc[16 * q + 5 + 2 * h])),
                         "r"(pack2(acc[16 * q + 8 + 2 * h], acc[16 * q + 9 + 2 * h])), "r"(pack2(acc[16 * q + 12 + 2 * h], acc[16 * q + 13 + 2 * h]))
                       : "memory");
      __syncwarp();
      uint4 w[8];
#pragma unroll
      for (int i = 0; i < 8; i++) {
        const int r = 2 * (i & 3) + (lane >> 4);
        w[i] = lds4(pa0 + (9 + (i >> 2)) * SLOT + r * 256 + (((lane & 15) ^ r) * 16));
      }
      uint4* dst;
      int dstr;
      if (wgi == 0) {
        dst = &scr->XP[(c ^ 4) * 1024 + tid];
        dstr = 128;
      } else {
        ld_tag4_finish<128>(pv[0], xsrc, tag);
        ld_tag4_finish<128>(pv[1], xsrc + 512, tag);
        dst = reinterpret_cast<uint4*>(out) + (16 * (c >> 4) + 2 * (4 * rh + wq) + (rb2 & 1) + 128 * (lane >> 4)) * 64 + nq * 16 + (lane & 15);
        dstr = 256 * 64;
      }
#pragma unroll
      for (int i = 0; i < 8; i++) {
        const uint4& p = pv[i >> 2][i & 3];
        const uint4 v = make_uint4(hadd2_bf16(w[i].x, p.x), hadd2_bf16(w[i].y, p.y), hadd2_bf16(w[i].z, p.z), hadd2_bf16(w[i].w, p.w));
        st_tag(dst + i * dstr, v, wgi ? (v.x & 1u) : tag);
      }
      PROF(12);
      PROFG(15);
    }
  }
#undef BAR
#undef TOFF
#undef RBAR
}

typedef CUresult (*EncodeFn)(CUtensorMap*, CUtensorMapDataType, cuuint32_t, void*, const cuuint64_t*, const cuuint64_t*,
                             const cuuint32_t*, const cuuint32_t*, CUtensorMapInterleave, CUtensorMapSwizzle,
                             CUtensorMapL2promotion, CUtensorMapFloatOOBfill);

}

extern "C" void kernel_launch(void* const* d_in, const int* in_sizes, int n_in, void* d_out, int out_size) {
  (void)in_sizes; (void)n_in; (void)out_size;
  static EncodeFn encode = nullptr;
  static void *tab = nullptr, *scr = nullptr;
  if (!encode) {
    void* fn = nullptr;
    cudaDriverEntryPointQueryResult qr;
    cudaGetDriverEntryPoint("cuTensorMapEncodeTiled", &fn, cudaEnableDefault, &qr);
    encode = (EncodeFn)fn;
    cudaGetSymbolAddress(&tab, g_tab);
    cudaGetSymbolAddress(&scr, g_scr);
    cudaFuncSetAttribute(fused_kernel, cudaFuncAttributeMaxDynamicSharedMemorySize, SMEM_BYTES);
  }
  CUtensorMap tmGX, tmUX, tmGY, tmUY, tmD, tmWR, tmWI;
  const cuuint32_t es[5] = {1, 1, 1, 1, 1};
  auto enc = [&](CUtensorMap* m, void* p, int rank, const cuuint64_t* gd, const cuuint64_t* gs, const cuuint32_t* bd,
                 CUtensorMapSwizzle sw, CUtensorMapL2promotion pr) {
    encode(m, CU_TENSOR_MAP_DATA_TYPE_BFLOAT16, rank, p, gd, gs, bd, es, CU_TENSOR_MAP_INTERLEAVE_NONE, sw, pr,
           CU_TENSOR_MAP_FLOAT_OOB_FILL_NONE);
  };
  {
    const cuuint64_t gd[3] = {64, 512, 28}, gs[2] = {3584, 128};
    const cuuint32_t bd[3] = {64, 32, 2};
    enc(&tmGX, d_in[4], 3, gd, gs, bd, CU_TENSOR_MAP_SWIZZLE_128B, CU_TENSOR_MAP_L2_PROMOTION_L2_256B);
    enc(&tmUX, d_in[5], 3, gd, gs, bd, CU_TENSOR_MAP_SWIZZLE_128B, CU_TENSOR_MAP_L2_PROMOTION_L2_256B);
  }
  {
    const cuuint64_t gd[3] = {32, 512, 56}, gs[2] = {3584, 64};
    const cuuint32_t bd[3] = {32, 32, 3};
    enc(&tmGY, d_in[4], 3, gd, gs, bd, CU_TENSOR_MAP_SWIZZLE_64B, CU_TENSOR_MAP_L2_PROMOTION_L2_128B);
    enc(&tmUY, d_in[5], 3, gd, gs, bd, CU_TENSOR_MAP_SWIZZLE_64B, CU_TENSOR_MAP_L2_PROMOTION_L2_128B);
  }
  {
    const cuuint64_t gd[3] = {64, 1792, 8}, gs[2] = {1024, 128};
    const cuuint32_t bd[3] = {64, 64, 2};
    enc(&tmD, d_in[6], 3, gd, gs, bd, CU_TENSOR_MAP_SWIZZLE_128B, CU_TENSOR_MAP_L2_PROMOTION_L2_256B);
  }
  {
    const cuuint64_t gd[3] = {4112, 8, 16}, gs[2] = {16 * 8224, 8224};
    const cuuint32_t bd[3] = {40, 8, 16};
    enc(&tmWR, d_in[1], 3, gd, gs, bd, CU_TENSOR_MAP_SWIZZLE_NONE, CU_TENSOR_MAP_L2_PROMOTION_NONE);
    enc(&tmWI, d_in[2], 3, gd, gs, bd, CU_TENSOR_MAP_SWIZZLE_NONE, CU_TENSOR_MAP_L2_PROMOTION_NONE);
  }
  fused_kernel<<<NCTA, NTHREADS, SMEM_BYTES>>>((const __nv_bfloat16*)d_in[0], (const Tables*)tab, (Scratch*)scr,
                                               (__nv_bfloat16*)d_out, (const char*)d_in[4], (const char*)d_in[5],
                                               (const char*)d_in[6], tmWR, tmWI, tmGX, tmUX, tmGY, tmUY, tmD);
}
```

```cpp
#include <cuda_runtime.h>
#include <cuda_bf16.h>
#include <cuda.h>
#include <stdint.h>

namespace {

constexpr int NCTA = 128;
constexpr int NTHREADS = 384;
constexpr int SLOT = 16384;
constexpr int SMEM_BYTES = 14 * SLOT + 3072;
constexpr int SPIN_LIMIT = 1 << 22;

struct Scratch {
  uint4 Z1[128 * 1024];
  uint4 Z2[128 * 1024];
  uint4 LN[16 * 8 * 1024];
  uint4 P[16 * 28 * 1024];
  uint4 XP[128 * 1024];
  uint4 ST[1024];
  unsigned cnt[64 * 32];
};
__device__ __align__(1024) Scratch g_scr;
#define PROF(i)
#define PROFP(i)
#define PROFG(i)

constexpr double ccos(int i, int n) {
  i &= n - 1;
  if (i > n / 2) i = n - i;
  if (4 * i == n) return 0.0;
  const bool neg = 4 * i > n;
  if (neg) i = n / 2 - i;
  const double a = 6.283185307179586476925 * i / n, a2 = a * a;
  double term = 1.0, sum = 1.0;
  for (int k = 1; k < 14; k++) { term *= -a2 / ((2 * k - 1) * (2 * k)); sum += term; }
  return neg ? -sum : sum;
}
constexpr double csin(int i, int n) { return ccos(i - n / 4, n); }
constexpr unsigned fbits(double v, int mant) {
  if (v == 0.0) return 0;
  const unsigned sg = v < 0 ? 1u : 0u;
  if (v < 0) v = -v;
  int e = 127;
  while (v < 1.0) { v *= 2.0; e--; }
  const unsigned m = (unsigned)((v - 1.0) * (double)(1u << mant) + 0.5);
  return (sg << (8 + mant)) + ((unsigned)e << mant) + m;
}
constexpr unsigned pkb(double lo, double hi) { return fbits(lo, 7) | (fbits(hi, 7) << 16); }
constexpr double fa_elem(int kp, int n1) {
  return kp <= 8 ? ccos(kp * n1, 16) : -csin((kp - 8) * n1, 16);
}
constexpr unsigned cfrag_c(int idx, int n, int ri) {
  return ri ? pkb(-csin(idx, n), ccos(idx, n)) : pkb(ccos(idx, n), csin(idx, n));
}
struct Tables {
  unsigned fb[16][32][4];
  unsigned tw1[8][32][4];
  unsigned fa[32][4];
  unsigned f2[8][4][32][4];
  unsigned g2[8][4][32][4];
  unsigned gb[16][32][4];
  unsigned tw3[4][32][4];
  unsigned ga[32][4];
  unsigned f8[32][4], g8[32][4];
};
constexpr int T1_BYTES = 12800, T2_BYTES = 44544;
static_assert(sizeof(Tables) == T1_BYTES + T2_BYTES, "table size");
constexpr Tables make_tables() {
  Tables T = {};
  for (int l = 0; l < 32; l++) {
    const int g = l >> 2, t = l & 3;
    for (int i = 0; i < 4; i++)
      for (int u = 0; u < 8; u++) {
        const int ri = g & 1, m = 2 * (g >> 1) + ((u & 3) >> 1);
        const double sg = u >= 4 ? -1.0 : 1.0;
        const int k2 = u >= 4 ? 31 - 2 * m - (u & 1) : 2 * m + (u & 1);
        const int pa = (8 * t + i) * k2, pb = (8 * t + 4 + i) * k2;
        T.fb[i * 4 + (u >> 1)][l][(u & 1) * 2 + 0] = ri == 0 ? pkb(ccos(pa, 32), ccos(pb, 32)) : pkb(-sg * csin(pa, 32), -sg * csin(pb, 32));
        T.fb[i * 4 + (u >> 1)][l][(u & 1) * 2 + 1] = ri == 0 ? pkb(csin(pa, 32), csin(pb, 32)) : pkb(sg * ccos(pa, 32), sg * ccos(pb, 32));
      }
    for (int i = 0; i < 4; i++)
      for (int ks = 0; ks < 4; ks++) {
        const int n2 = 4 * g + i, m = 2 * t + (ks & 1);
        const double sg = ks >= 2 ? -1.0 : 1.0;
        const int pa = n2 * (ks >= 2 ? 31 - 2 * m : 2 * m), pb = n2 * (ks >= 2 ? 30 - 2 * m : 2 * m + 1);
        T.gb[i * 4 + ks][l][0] = pkb(ccos(pa, 32), -sg * csin(pa, 32));
        T.gb[i * 4 + ks][l][1] = pkb(csin(pa, 32), sg * ccos(pa, 32));
        T.gb[i * 4 + ks][l][2] = pkb(ccos(pb, 32), -sg * csin(pb, 32));
        T.gb[i * 4 + ks][l][3] = pkb(csin(pb, 32), sg * ccos(pb, 32));
      }
    for (int i = 0; i < 4; i++) {
      for (int e = 0; e < 2; e++) {
        const int p = (8 * t + 4 * e + i) * (g == 0 ? 8 : g);
        T.tw1[2 * i + e][l][0] = fbits(g == 0 ? 0.0 : ccos(p, 512), 23);
        T.tw1[2 * i + e][l][1] = fbits(g == 0 ? ccos(p, 512) : csin(p, 512), 23);
        T.tw1[2 * i + e][l][2] = fbits(g == 0 ? 0.0 : -csin(p, 512), 23);
        T.tw1[2 * i + e][l][3] = fbits(g == 0 ? -csin(p, 512) : ccos(p, 512), 23);
      }
      const int ka = t == 0 ? 8 : 2 * t, kb = 2 * t + 1;
      T.tw3[i][l][0] = fbits(ccos((4 * g + i) * ka, 512), 23);
      T.tw3[i][l][1] = fbits(csin((4 * g + i) * ka, 512), 23);
      T.tw3[i][l][2] = fbits(ccos((4 * g + i) * kb, 512), 23);
      T.tw3[i][l][3] = fbits(csin((4 * g + i) * kb, 512), 23);
      const int p8 = (t + 4 * (i & 1)) * (4 * (i >> 1) + (g >> 1));
      T.f8[l][i] = cfrag_c(p8, 8, g & 1);
      T.g8[l][i] = cfrag_c(-p8, 8, g & 1);
    }
    for (int w = 0; w < 8; w++)
      for (int i = 0; i < 16; i++) {
        const int kidx = t + 4 * (i & 1) + 8 * (i >> 3), nidx = 4 * ((i >> 1) & 3) + (g >> 1);
        T.f2[w][i >> 2][l][i & 3] = cfrag_c((8 * kidx + w) * nidx, 128, g & 1);
        T.g2[w][i >> 2][l][i & 3] = cfrag_c(-(8 * nidx + w) * kidx, 128, g & 1);
      }
    T.fa[l][0] = pkb(fa_elem(g, 2 * t), fa_elem(g, 2 * t + 1));
    T.fa[l][1] = pkb(fa_elem(g + 8, 2 * t), fa_elem(g + 8, 2 * t + 1));
    T.fa[l][2] = pkb(fa_elem(g, 2 * t + 8), fa_elem(g, 2 * t + 9));
    T.fa[l][3] = pkb(fa_elem(g + 8, 2 * t + 8), fa_elem(g + 8, 2 * t + 9));
    T.ga[l][0] = pkb(fa_elem(2 * t, g), fa_elem(2 * t + 1, g));
    T.ga[l][1] = pkb(fa_elem(2 * t, g + 8), fa_elem(2 * t + 1, g + 8));
    T.ga[l][2] = pkb(fa_elem(2 * t + 8, g), fa_elem(2 * t + 9, g));
    T.ga[l][3] = pkb(fa_elem(2 * t + 8, g + 8), fa_elem(2 * t + 9, g + 8));
  }
  return T;
}
__device__ const __align__(128) Tables g_tab = make_tables();

__device__ __forceinline__ void die() { asm volatile("st.global.u32 [%0], %1;" ::"l"(0ull), "r"(0) : "memory"); }
__device__ __forceinline__ uint32_t s2u(const void* p) { return (uint32_t)__cvta_generic_to_shared(p); }
__device__ __forceinline__ void mbar_init(uint32_t b, int c) { asm volatile("mbarrier.init.shared::cta.b64 [%0], %1;" ::"r"(b), "r"(c)); }
__device__ __forceinline__ void mbar_expect(uint32_t b, int bytes) {
  asm volatile("mbarrier.arrive.expect_tx.shared::cta.b64 _, [%0], %1;" ::"r"(b), "r"(bytes) : "memory");
}
__device__ __forceinline__ void mbar_arrive(uint32_t b) { asm volatile("mbarrier.arrive.shared::cta.b64 _, [%0];" ::"r"(b) : "memory"); }
__device__ __forceinline__ uint32_t mbar_try(uint32_t b, uint32_t parity) {
  uint32_t ok;
  asm volatile("{.reg .pred p; mbarrier.try_wait.parity.shared::cta.b64 p, [%1], %2; selp.u32 %0,1,0,p;}"
               : "=r"(ok) : "r"(b), "r"(parity) : "memory");
  return ok;
}
__device__ __forceinline__ uint32_t mbar_test(uint32_t b) {
  uint32_t ok;
  asm volatile("{.reg .pred p; mbarrier.test_wait.parity.shared::cta.b64 p, [%1], 0; selp.u32 %0,1,0,p;}" : "=r"(ok) : "r"(b) : "memory");
  return ok;
}
__device__ __forceinline__ void mbar_wait(uint32_t b, uint32_t parity = 0) {
  int it = 0;
#pragma unroll 1
  while (!mbar_try(b, parity))
    if (++it > SPIN_LIMIT) { die(); break; }
}
__device__ __forceinline__ void bar_sync(int id, int n) { asm volatile("bar.sync %0, %1;" ::"r"(id), "r"(n) : "memory"); }
__device__ __forceinline__ void bar_arrive(int id, int n) { asm volatile("bar.arrive %0, %1;" ::"r"(id), "r"(n) : "memory"); }
__device__ __forceinline__ void red_release(unsigned* p) { asm volatile("red.release.gpu.global.add.u32 [%0], 1;" ::"l"(p) : "memory"); }
__device__ __forceinline__ void red_relaxed(unsigned* p) { asm volatile("red.relaxed.gpu.global.add.u32 [%0], 1;" ::"l"(p) : "memory"); }
__device__ __forceinline__ unsigned ld_acquire(const unsigned* p) {
  unsigned v;
  asm volatile("ld.acquire.gpu.global.u32 %0, [%1];" : "=r"(v) : "l"(p) : "memory");
  return v;
}
__device__ __forceinline__ unsigned ld_relaxed(const unsigned* p) {
  unsigned v;
  asm volatile("ld.relaxed.gpu.global.u32 %0, [%1];" : "=r"(v) : "l"(p) : "memory");
  return v;
}
__device__ __forceinline__ void wait_counter(const unsigned* p, unsigned target) {
  int it = 0;
  while ((int)(ld_acquire(p) - target) < 0)
    if (++it > SPIN_LIMIT) { die(); break; }
}
__device__ __forceinline__ void sts4(uint32_t a, uint32_t x, uint32_t y, uint32_t z, uint32_t w) {
  asm volatile("st.shared.v4.u32 [%0], {%1,%2,%3,%4};" ::"r"(a), "r"(x), "r"(y), "r"(z), "r"(w) : "memory");
}
__device__ __forceinline__ uint4 lds4(uint32_t a) {
  uint4 v;
  asm volatile("ld.shared.v4.u32 {%0,%1,%2,%3}, [%4];" : "=r"(v.x), "=r"(v.y), "=r"(v.z), "=r"(v.w) : "r"(a) : "memory");
  return v;
}
__device__ __forceinline__ uint32_t pack2(float lo, float hi) {
  uint32_t r;
  asm("cvt.rn.bf16x2.f32 %0, %1, %2;" : "=r"(r) : "f"(hi), "f"(lo));
  return r;
}
__device__ __forceinline__ float bf_lo(uint32_t v) { return __uint_as_float(v << 16); }
__device__ __forceinline__ uint32_t hadd2_bf16(uint32_t a, uint32_t b) {
  uint32_t r;
  asm("add.rn.bf16x2 %0, %1, %2;" : "=r"(r) : "r"(a), "r"(b));
  return r;
}
__device__ __forceinline__ void mma16816(float (&d)[4], uint32_t a0, uint32_t a1, uint32_t a2, uint32_t a3, uint32_t b0, uint32_t b1) {
  asm("mma.sync.aligned.m16n8k16.row.col.f32.bf16.bf16.f32 {%0,%1,%2,%3}, {%4,%5,%6,%7}, {%8,%9}, {%0,%1,%2,%3};"
      : "+f"(d[0]), "+f"(d[1]), "+f"(d[2]), "+f"(d[3])
      : "r"(a0), "r"(a1), "r"(a2), "r"(a3), "r"(b0), "r"(b1));
}
template <int N>
__device__ __forceinline__ void cs_frac(int idx, float& c, float& s) {
  int i = ((idx + N / 2) & (N - 1)) - N / 2;
  float a = (float)i * (6.283185307179586f / N);
  c = __cosf(a);
  s = __sinf(a);
}
template <int N>
__device__ __forceinline__ uint32_t cfrag(int idx, int ri) {
  float c, s;
  cs_frac<N>(idx, c, s);
  return ri ? pack2(-s, c) : pack2(c, s);
}
__device__ __forceinline__ uint32_t word(const uint4& v, int e) { return e == 0 ? v.x : e == 1 ? v.y : e == 2 ? v.z : v.w; }
__device__ __forceinline__ void cdft16(const uint4 (&q)[4], const uint4 (&F)[4], uint4 (&o)[4]) {
  float acc[2][4][4];
#pragma unroll
  for (int p = 0; p < 2; p++)
#pragma unroll
    for (int v = 0; v < 4; v++) {
      acc[p][v][0] = acc[p][v][1] = acc[p][v][2] = acc[p][v][3] = 0.f;
#pragma unroll
      for (int ks = 0; ks < 2; ks++)
        mma16816(acc[p][v], word(q[2 * ks], 2 * p), word(q[2 * ks], 2 * p + 1), word(q[2 * ks + 1], 2 * p),
                 word(q[2 * ks + 1], 2 * p + 1), word(F[ks * 2 + (v >> 1)], (v & 1) * 2), word(F[ks * 2 + (v >> 1)], (v & 1) * 2 + 1));
    }
#pragma unroll
  for (int v = 0; v < 4; v++)
    o[v] = make_uint4(pack2(acc[0][v][0], acc[0][v][1]), pack2(acc[0][v][2], acc[0][v][3]),
                      pack2(acc[1][v][0], acc[1][v][1]), pack2(acc[1][v][2], acc[1][v][3]));
}
__device__ __forceinline__ void st_tag(uint4* p, const uint4& v, uint32_t tag) {
  asm volatile("{.reg .b128 r; .reg .b64 a, b; mov.b64 a, {%1,%2}; mov.b64 b, {%3,%4}; mov.b128 r, {a,b}; st.relaxed.gpu.global.b128 [%0], r;}"
               ::"l"(p), "r"((v.x & ~1u) | tag), "r"(v.y), "r"(v.z), "r"(v.w) : "memory");
}
__device__ __forceinline__ uint4 ld_b128(const uint4* p) {
  uint4 v;
  asm volatile("{.reg .b128 r; .reg .b64 a, b; ld.relaxed.gpu.global.b128 r, [%4]; mov.b128 {a,b}, r; mov.b64 {%0,%1}, a; mov.b64 {%2,%3}, b;}"
               : "=r"(v.x), "=r"(v.y), "=r"(v.z), "=r"(v.w) : "l"(p) : "memory");
  return v;
}
template <int STRIDE>
__device__ __forceinline__ void ld_tag4_issue(uint4 (&q)[4], const uint4* p) {
#pragma unroll
  for (int i = 0; i < 4; i++) q[i] = ld_b128(p + i * STRIDE);
}
template <int STRIDE>
__device__ __forceinline__ void ld_tag4_finish(uint4 (&q)[4], const uint4* p, uint32_t tag) {
  int it = 0;
#pragma unroll 1
  while (__any_sync(0xffffffffu, ((q[0].x ^ tag) | (q[1].x ^ tag) | (q[2].x ^ tag) | (q[3].x ^ tag)) & 1u)) {
    ld_tag4_issue<STRIDE>(q, p);
    if (++it > SPIN_LIMIT) { die(); break; }
  }
#pragma unroll
  for (int i = 0; i < 4; i++) asm volatile("and.b32 %0, %0, 0xfffffffe;" : "+r"(q[i].x));
}
__device__ __forceinline__ void row_stats(const uint32_t (&a)[8], const uint32_t (&b)[8], int lane, float (&sum)[2], float (&sq)[2]) {
  float da[4] = {0.f, 0.f, 0.f, 0.f}, db[4] = {0.f, 0.f, 0.f, 0.f}, ds[4] = {0.f, 0.f, 0.f, 0.f};
#pragma unroll
  for (int q = 0; q < 4; q++) {
    mma16816(ds, a[2 * q], b[2 * q], a[2 * q + 1], b[2 * q + 1], 0x3f803f80u, 0x3f803f80u);
    mma16816(da, a[2 * q], b[2 * q], a[2 * q + 1], b[2 * q + 1], a[2 * q], a[2 * q + 1]);
    mma16816(db, a[2 * q], b[2 * q], a[2 * q + 1], b[2 * q + 1], b[2 * q], b[2 * q + 1]);
  }
  const int src = (lane & 28) | (lane >> 3);
  const float qa = __shfl_sync(0xffffffffu, (lane & 4) ? da[1] : da[0], src);
  const float qb = __shfl_sync(0xffffffffu, (lane & 4) ? db[3] : db[2], src);
  float v = (lane & 2) ? ((lane & 1) ? ds[2] : ds[0]) : ((lane & 1) ? qb : qa);
  v += __shfl_xor_sync(0xffffffffu, v, 4);
  v += __shfl_xor_sync(0xffffffffu, v, 8);
  v += __shfl_xor_sync(0xffffffffu, v, 16);
  sq[0] = __shfl_sync(0xffffffffu, v, 0);
  sq[1] = __shfl_sync(0xffffffffu, v, 1);
  sum[0] = __shfl_sync(0xffffffffu, v, 2);
  sum[1] = __shfl_sync(0xffffffffu, v, 3);
}
__device__ __forceinline__ uint64_t desc64(uint32_t lo, uint32_t hi) {
  uint64_t d;
  asm("mov.b64 %0, {%1, %2};" : "=l"(d) : "r"(lo), "r"(hi));
  return d;
}
constexpr uint32_t desc_hi(uint32_t sbo, uint32_t swz) { return (sbo >> 4) | (swz << 30); }
__device__ __forceinline__ uint32_t desc_lo(uint32_t addr, uint32_t lbo) { return ((addr & 0x3FFFF) >> 4) | ((lbo >> 4) << 16); }
__device__ __forceinline__ void cp_async16(uint32_t dst, const void* src) {
  asm volatile("cp.async.cg.shared.global [%0], [%1], 16;" ::"r"(dst), "l"(src) : "memory");
}
__device__ __forceinline__ uint2 lds2(uint32_t a) {
  uint2 v;
  asm volatile("ld.shared.v2.u32 {%0,%1}, [%2];" : "=r"(v.x), "=r"(v.y) : "r"(a) : "memory");
  return v;
}
__device__ __forceinline__ uint32_t lds_u16(uint32_t a) {
  uint16_t v;
  asm volatile("ld.shared.u16 %0, [%1];" : "=h"(v) : "r"(a) : "memory");
  return v;
}
__device__ __forceinline__ void wg_fence() { asm volatile("wgmma.fence.sync.aligned;" ::: "memory"); }
__device__ __forceinline__ void wg_commit() { asm volatile("wgmma.commit_group.sync.aligned;" ::: "memory"); }
template <int N>
__device__ __forceinline__ void wg_wait() { asm volatile("wgmma.wait_group.sync.aligned %0;" ::"n"(N) : "memory"); }
__device__ __forceinline__ void bulk_load(uint32_t dst, const void* src, int bytes, uint32_t bar) {
  asm volatile("cp.async.bulk.shared::cluster.global.mbarrier::complete_tx::bytes [%0], [%1], %2, [%3];"
               ::"r"(dst), "l"(src), "r"(bytes), "r"(bar) : "memory");
}
__device__ __forceinline__ void bulk_load_mc(uint32_t dst, const void* src, int bytes, uint32_t bar) {
  asm volatile("cp.async.bulk.shared::cluster.global.mbarrier::complete_tx::bytes.multicast::cluster [%0], [%1], %2, [%3], %4;"
               ::"r"(dst), "l"(src), "r"(bytes), "r"(bar), "h"((uint16_t)3) : "memory");
}
__device__ __forceinline__ void tma3(uint32_t dst, const CUtensorMap* tm, uint32_t bar, int c0, int c1, int c2) {
  asm volatile("cp.async.bulk.tensor.3d.shared::cluster.global.mbarrier::complete_tx::bytes [%0], [%1, {%3,%4,%5}], [%2];"
               ::"r"(dst), "l"(tm), "r"(bar), "r"(c0), "r"(c1), "r"(c2) : "memory");
}
__device__ __forceinline__ void tma3_mc(uint32_t dst, const CUtensorMap* tm, uint32_t bar, int c1, int c2) {
  asm volatile("cp.async.bulk.tensor.3d.shared::cluster.global.mbarrier::complete_tx::bytes.multicast::cluster [%0], [%1, {%3,%4,%5}], [%2], %6;"
               ::"r"(dst), "l"(tm), "r"(bar), "r"(0), "r"(c1), "r"(c2), "h"((uint16_t)3) : "memory");
}
__device__ __forceinline__ void mbar_arrive_remote(uint32_t rb) {
  asm volatile("mbarrier.arrive.shared::cluster.b64 _, [%0];" ::"r"(rb) : "memory");
}
__device__ __forceinline__ uint4 ldg_ca4(const void* p) {
  uint4 v;
  asm volatile("ld.global.ca.v4.u32 {%0,%1,%2,%3}, [%4];" : "=r"(v.x), "=r"(v.y), "=r"(v.z), "=r"(v.w) : "l"(p) : "memory");
  return v;
}
__device__ __forceinline__ uint32_t clock32() {
  uint32_t v;
  asm volatile("mov.u32 %0, %%clock;" : "=r"(v) :: "memory");
  return v;
}
__device__ __forceinline__ float swiglu(float g, float u, float r) {
  float hg = (0.5f * r) * g, th;
  asm("tanh.approx.f32 %0, %1;" : "=f"(th) : "f"(hg));
  return fmaf(hg, th, hg) * (r * u);
}
__device__ __forceinline__ uint32_t hsub2_bf16(uint32_t a, uint32_t b) {
  uint32_t r;
  asm("sub.rn.bf16x2 %0, %1, %2;" : "=r"(r) : "r"(a), "r"(b));
  return r;
}
__device__ __forceinline__ void l2_prefetch(const void* p, int bytes) {
  asm volatile("cp.async.bulk.prefetch.L2.global [%0], %1;" ::"l"(p), "r"(bytes) : "memory");
}

__device__ __forceinline__ void wgmma_n256(float (&d)[128], uint64_t da, uint64_t db, int sd = 1) {
  asm volatile("{.reg .pred p; setp.ne.b32 p, %130, 0;\n"
      "wgmma.mma_async.sync.aligned.m64n256k16.f32.bf16.bf16 {"
      "%0,%1,%2,%3,%4,%5,%6,%7,%8,%9,%10,%11,%12,%13,%14,%15,"
      "%16,%17,%18,%19,%20,%21,%22,%23,%24,%25,%26,%27,%28,%29,%30,%31,"
      "%32,%33,%34,%35,%36,%37,%38,%39,%40,%41,%42,%43,%44,%45,%46,%47,"
      "%48,%49,%50,%51,%52,%53,%54,%55,%56,%57,%58,%59,%60,%61,%62,%63,"
      "%64,%65,%66,%67,%68,%69,%70,%71,%72,%73,%74,%75,%76,%77,%78,%79,"
      "%80,%81,%82,%83,%84,%85,%86,%87,%88,%89,%90,%91,%92,%93,%94,%95,"
      "%96,%97,%98,%99,%100,%101,%102,%103,%104,%105,%106,%107,%108,%109,%110,%111,"
      "%112,%113,%114,%115,%116,%117,%118,%119,%120,%121,%122,%123,%124,%125,%126,%127"
      "}, %128, %129, p, 1, 1, 0, 1;}\n"
      : "+f"(d[0]),"+f"(d[1]),"+f"(d[2]),"+f"(d[3]),"+f"(d[4]),"+f"(d[5]),"+f"(d[6]),"+f"(d[7]),
        "+f"(d[8]),"+f"(d[9]),"+f"(d[10]),"+f"(d[11]),"+f"(d[12]),"+f"(d[13]),"+f"(d[14]),"+f"(d[15]),
        "+f"(d[16]),"+f"(d[17]),"+f"(d[18]),"+f"(d[19]),"+f"(d[20]),"+f"(d[21]),"+f"(d[22]),"+f"(d[23]),
        "+f"(d[24]),"+f"(d[25]),"+f"(d[26]),"+f"(d[27]),"+f"(d[28]),"+f"(d[29]),"+f"(d[30]),"+f"(d[31]),
        "+f"(d[32]),"+f"(d[33]),"+f"(d[34]),"+f"(d[35]),"+f"(d[36]),"+f"(d[37]),"+f"(d[38]),"+f"(d[39]),
        "+f"(d[40]),"+f"(d[41]),"+f"(d[42]),"+f"(d[43]),"+f"(d[44]),"+f"(d[45]),"+f"(d[46]),"+f"(d[47]),
        "+f"(d[48]),"+f"(d[49]),"+f"(d[50]),"+f"(d[51]),"+f"(d[52]),"+f"(d[53]),"+f"(d[54]),"+f"(d[55]),
        "+f"(d[56]),"+f"(d[57]),"+f"(d[58]),"+f"(d[59]),"+f"(d[60]),"+f"(d[61]),"+f"(d[62]),"+f"(d[63]),
        "+f"(d[64]),"+f"(d[65]),"+f"(d[66]),"+f"(d[67]),"+f"(d[68]),"+f"(d[69]),"+f"(d[70]),"+f"(d[71]),
        "+f"(d[72]),"+f"(d[73]),"+f"(d[74]),"+f"(d[75]),"+f"(d[76]),"+f"(d[77]),"+f"(d[78]),"+f"(d[79]),
        "+f"(d[80]),"+f"(d[81]),"+f"(d[82]),"+f"(d[83]),"+f"(d[84]),"+f"(d[85]),"+f"(d[86]),"+f"(d[87]),
        "+f"(d[88]),"+f"(d[89]),"+f"(d[90]),"+f"(d[91]),"+f"(d[92]),"+f"(d[93]),"+f"(d[94]),"+f"(d[95]),
        "+f"(d[96]),"+f"(d[97]),"+f"(d[98]),"+f"(d[99]),"+f"(d[100]),"+f"(d[101]),"+f"(d[102]),"+f"(d[103]),
        "+f"(d[104]),"+f"(d[105]),"+f"(d[106]),"+f"(d[107]),"+f"(d[108]),"+f"(d[109]),"+f"(d[110]),"+f"(d[111]),
        "+f"(d[112]),"+f"(d[113]),"+f"(d[114]),"+f"(d[115]),"+f"(d[116]),"+f"(d[117]),"+f"(d[118]),"+f"(d[119]),
        "+f"(d[120]),"+f"(d[121]),"+f"(d[122]),"+f"(d[123]),"+f"(d[124]),"+f"(d[125]),"+f"(d[126]),"+f"(d[127])
      : "l"(da), "l"(db), "r"(sd));
}
__device__ __forceinline__ void wgmma_n192(float (&d)[96], uint64_t da, uint64_t db) {
  asm volatile("wgmma.mma_async.sync.aligned.m64n192k16.f32.bf16.bf16 {"
      "%0,%1,%2,%3,%4,%5,%6,%7,%8,%9,%10,%11,%12,%13,%14,%15,"
      "%16,%17,%18,%19,%20,%21,%22,%23,%24,%25,%26,%27,%28,%29,%30,%31,"
      "%32,%33,%34,%35,%36,%37,%38,%39,%40,%41,%42,%43,%44,%45,%46,%47,"
      "%48,%49,%50,%51,%52,%53,%54,%55,%56,%57,%58,%59,%60,%61,%62,%63,"
      "%64,%65,%66,%67,%68,%69,%70,%71,%72,%73,%74,%75,%76,%77,%78,%79,"
      "%80,%81,%82,%83,%84,%85,%86,%87,%88,%89,%90,%91,%92,%93,%94,%95"
      "}, %96, %97, 1, 1, 1, 0, 1;\n"
      : "+f"(d[0]),"+f"(d[1]),"+f"(d[2]),"+f"(d[3]),"+f"(d[4]),"+f"(d[5]),"+f"(d[6]),"+f"(d[7]),
        "+f"(d[8]),"+f"(d[9]),"+f"(d[10]),"+f"(d[11]),"+f"(d[12]),"+f"(d[13]),"+f"(d[14]),"+f"(d[15]),
        "+f"(d[16]),"+f"(d[17]),"+f"(d[18]),"+f"(d[19]),"+f"(d[20]),"+f"(d[21]),"+f"(d[22]),"+f"(d[23]),
        "+f"(d[24]),"+f"(d[25]),"+f"(d[26]),"+f"(d[27]),"+f"(d[28]),"+f"(d[29]),"+f"(d[30]),"+f"(d[31]),
        "+f"(d[32]),"+f"(d[33]),"+f"(d[34]),"+f"(d[35]),"+f"(d[36]),"+f"(d[37]),"+f"(d[38]),"+f"(d[39]),
        "+f"(d[40]),"+f"(d[41]),"+f"(d[42]),"+f"(d[43]),"+f"(d[44]),"+f"(d[45]),"+f"(d[46]),"+f"(d[47]),
        "+f"(d[48]),"+f"(d[49]),"+f"(d[50]),"+f"(d[51]),"+f"(d[52]),"+f"(d[53]),"+f"(d[54]),"+f"(d[55]),
        "+f"(d[56]),"+f"(d[57]),"+f"(d[58]),"+f"(d[59]),"+f"(d[60]),"+f"(d[61]),"+f"(d[62]),"+f"(d[63]),
        "+f"(d[64]),"+f"(d[65]),"+f"(d[66]),"+f"(d[67]),"+f"(d[68]),"+f"(d[69]),"+f"(d[70]),"+f"(d[71]),
        "+f"(d[72]),"+f"(d[73]),"+f"(d[74]),"+f"(d[75]),"+f"(d[76]),"+f"(d[77]),"+f"(d[78]),"+f"(d[79]),
        "+f"(d[80]),"+f"(d[81]),"+f"(d[82]),"+f"(d[83]),"+f"(d[84]),"+f"(d[85]),"+f"(d[86]),"+f"(d[87]),
        "+f"(d[88]),"+f"(d[89]),"+f"(d[90]),"+f"(d[91]),"+f"(d[92]),"+f"(d[93]),"+f"(d[94]),"+f"(d[95])
      : "l"(da), "l"(db));
}
template <int SD>
__device__ __forceinline__ void wgmma_rs_n128(float (&d)[64], uint32_t a0, uint32_t a1, uint32_t a2, uint32_t a3, uint64_t db) {
  asm volatile("wgmma.mma_async.sync.aligned.m64n128k16.f32.bf16.bf16 {"
      "%0,%1,%2,%3,%4,%5,%6,%7,%8,%9,%10,%11,%12,%13,%14,%15,"
      "%16,%17,%18,%19,%20,%21,%22,%23,%24,%25,%26,%27,%28,%29,%30,%31,"
      "%32,%33,%34,%35,%36,%37,%38,%39,%40,%41,%42,%43,%44,%45,%46,%47,"
      "%48,%49,%50,%51,%52,%53,%54,%55,%56,%57,%58,%59,%60,%61,%62,%63"
      "}, {%64,%65,%66,%67}, %68, %69, 1, 1, 1;\n"
      : "+f"(d[0]),"+f"(d[1]),"+f"(d[2]),"+f"(d[3]),"+f"(d[4]),"+f"(d[5]),"+f"(d[6]),"+f"(d[7]),
        "+f"(d[8]),"+f"(d[9]),"+f"(d[10]),"+f"(d[11]),"+f"(d[12]),"+f"(d[13]),"+f"(d[14]),"+f"(d[15]),
        "+f"(d[16]),"+f"(d[17]),"+f"(d[18]),"+f"(d[19]),"+f"(d[20]),"+f"(d[21]),"+f"(d[22]),"+f"(d[23]),
        "+f"(d[24]),"+f"(d[25]),"+f"(d[26]),"+f"(d[27]),"+f"(d[28]),"+f"(d[29]),"+f"(d[30]),"+f"(d[31]),
        "+f"(d[32]),"+f"(d[33]),"+f"(d[34]),"+f"(d[35]),"+f"(d[36]),"+f"(d[37]),"+f"(d[38]),"+f"(d[39]),
        "+f"(d[40]),"+f"(d[41]),"+f"(d[42]),"+f"(d[43]),"+f"(d[44]),"+f"(d[45]),"+f"(d[46]),"+f"(d[47]),
        "+f"(d[48]),"+f"(d[49]),"+f"(d[50]),"+f"(d[51]),"+f"(d[52]),"+f"(d[53]),"+f"(d[54]),"+f"(d[55]),
        "+f"(d[56]),"+f"(d[57]),"+f"(d[58]),"+f"(d[59]),"+f"(d[60]),"+f"(d[61]),"+f"(d[62]),"+f"(d[63])
      : "r"(a0), "r"(a1), "r"(a2), "r"(a3), "l"(db), "n"(SD));
}

constexpr int C_LN = 0, C_PX = 16, C_PY = 32;
constexpr int NB_CONS = 1, NB_LN = 2, NB_LAG = 4, NB_INIT = 6, NB_RDY = 7;
#define LAGX 3
#define LAGY 3
#define LAG2 5
#define NLL 2
#define POLL_DELAY3 1200
#define POLL_DELAY 1100
#define FILT_DELAY 1000
#define THR_B 0
#define THR_P 0
#define SPEC -1
#define WARM 4
#define HWARM 0
#define POLL_DELAY2 POLL_DELAY
#define XNOW false
#define RING_SIG 1
#define PF2_SIG 1
constexpr int SM_E = 0, SM_X = 16384, SM_E2 = 32768, SM_W = 49152, SM_FC = 69632, SM_T = 73728 - T1_BYTES;
constexpr unsigned long long KORDER = 0xBA9432DC876510ull;
constexpr unsigned long long BSLOT = 0x76532107653210ull, PSLOT = 0xDCBA984DCBA984ull;
constexpr uint32_t HI128 = desc_hi(1024, 1), HI64 = desc_hi(512, 2);

struct Bars {
  uint64_t full1[32], empty1[32], full2[16], fullA[8], empty2[8], fullP[16], emptyP[8], hbar, tbar, hint[3], sig[2], sbar;
  uint32_t epoch;
};

template <int NK, bool STORE>
__device__ __forceinline__ void make_p(const float (&acc)[NK * 16], float r0, float r1, uint4 (&p)[NK], uint4* pbase, int ks0, uint32_t tag) {
#pragma unroll
  for (int j = 0; j < NK; j++) {
    uint32_t w[4];
#pragma unroll
    for (int i = 0; i < 4; i++) {
      const int a = 8 * j + 2 * i, b = a + NK * 8;
      w[i] = pack2(swiglu(acc[a], acc[b], (i & 1) ? r1 : r0), swiglu(acc[a + 1], acc[b + 1], (i & 1) ? r1 : r0));
    }
    asm volatile("" : "+r"(w[0]), "+r"(w[1]), "+r"(w[2]), "+r"(w[3]));
    p[j] = make_uint4(w[0], w[1], w[2], w[3]);
    if (STORE) st_tag(pbase + ((ks0 + j) >> 2) * 1024 + ((ks0 + j) & 3) * 32, p[j], tag);
  }
}
__device__ __forceinline__ void spin_cycles(uint32_t n) {
  const uint32_t t0 = clock32();
  while (clock32() - t0 < n) {}
}

__device__ __forceinline__ void spin_until(uint32_t t) {
  float d[4] = {0.f, 0.f, 0.f, 0.f};
  while ((int)(clock32() - t) < 0) {
    if (HWARM) asm volatile("mma.sync.aligned.m16n8k16.row.col.f32.bf16.bf16.f32 {%0,%1,%2,%3}, {%4,%4,%4,%4}, {%4,%4}, {%0,%1,%2,%3};"
                            : "+f"(d[0]), "+f"(d[1]), "+f"(d[2]), "+f"(d[3]) : "r"(t));
  }
}

__global__ void __cluster_dims__(2, 1, 1) __launch_bounds__(NTHREADS, 1)
fused_kernel(const __nv_bfloat16* __restrict__ x, const Tables* __restrict__ tab, Scratch* __restrict__ scr,
             __nv_bfloat16* __restrict__ out, const char* __restrict__ wg_raw, const char* __restrict__ wu_raw,
             const char* __restrict__ wd_raw,
             const __grid_constant__ CUtensorMap tmWR, const __grid_constant__ CUtensorMap tmWI,
             const __grid_constant__ CUtensorMap tmGX, const __grid_constant__ CUtensorMap tmUX,
             const __grid_constant__ CUtensorMap tmGY, const __grid_constant__ CUtensorMap tmUY,
             const __grid_constant__ CUtensorMap tmD) {
  extern __shared__ __align__(1024) char smem_raw[];
  const uint32_t sbase = s2u(smem_raw);
  const uint32_t sbar = sbase + 14 * SLOT, sstat = sbar + 1280;
  const int tid = threadIdx.x, lane = tid & 31;
  const int c = blockIdx.x, rk = c & 1, f = (c >> 1) & 7, rb = 2 * (c >> 4) + rk;
  const int rb2 = 2 * (c >> 4) + (f >> 2), kh = (f >> 1) & 1, nq = 2 * (f & 1) + rk;
#define BAR(field, i) (sbar + (uint32_t)offsetof(Bars, field) + 8u * (i))
#define TOFF(field) (sbase + SM_T + (uint32_t)offsetof(Tables, field) + lane * 16)

  if (tid >= 256) {
    asm volatile("setmaxnreg.dec.sync.aligned.u32 56;");
    const int warp = __shfl_sync(0xffffffffu, tid >> 5, 0);
    const unsigned epoch = ld_relaxed(&scr->cnt[(C_LN + rb) * 32]) >> 3;
    if (lane == 0) {
      if (warp == 8) {
        if (sbase & 1023) die();
#pragma unroll
        for (int i = 0; i < 16; i++) mbar_init(BAR(emptyP, i), i < 7 ? 16 : i < 8 ? 8 : i < 13 ? 1 : i < 15 ? 8 : 32);
        mbar_expect(BAR(tbar, 0), T2_BYTES + 2 * 10240);
        mbar_expect(BAR(hbar, 0), 16384);
      } else if (warp == 9) {
#pragma unroll
        for (int i = 0; i < 32; i++) mbar_init(BAR(full1, i), 1);
#pragma unroll
        for (int i = 0; i < 32; i++) mbar_expect(BAR(full1, i), i < 16 ? 16384 : 12288);
      } else if (warp == 10) {
#pragma unroll
        for (int i = 0; i < 32; i++) mbar_init(BAR(empty1, i), 16);
#pragma unroll
        for (int i = 0; i < 14; i++) mbar_init(BAR(fullP, i), 1);
#pragma unroll
        for (int i = 0; i < 14; i++) mbar_expect(BAR(fullP, i), 16384);
      } else {
#pragma unroll
        for (int i = 0; i < 32; i++) mbar_init(BAR(full2, i), i < 24 ? 1 : 8);
#pragma unroll
        for (int i = 0; i < 24; i++) mbar_expect(BAR(full2, i), 16384);
      }
      asm volatile("fence.mbarrier_init.release.cluster;" ::: "memory");
    }
    if (tid == 256) {
      const int w0 = ((c >> 3) * 257 + 32 * (c & 7) + 1) & ~7;
      if (FILT_DELAY) {
        asm volatile("prefetch.tensormap [%0];" ::"l"(&tmWR) : "memory");
        asm volatile("prefetch.tensormap [%0];" ::"l"(&tmWI) : "memory");
        spin_cycles(FILT_DELAY);
      }
      tma3(sbase + SM_W, &tmWR, BAR(tbar, 0), w0, 0, 0);
      tma3(sbase + SM_W + 10240, &tmWI, BAR(tbar, 0), w0, 0, 0);
      bulk_load(sbase + SM_T + T1_BYTES, reinterpret_cast<const char*>(tab) + T1_BYTES, T2_BYTES, BAR(tbar, 0));
    }
    if (tid == 288) {
      asm volatile("prefetch.tensormap [%0];" ::"l"(rk ? &tmUX : &tmGX) : "memory");
      asm volatile("prefetch.tensormap [%0];" ::"l"(rk ? &tmUY : &tmGY) : "memory");
      asm volatile("prefetch.tensormap [%0];" ::"l"(&tmD) : "memory");
    }
    if (tid == 320) asm volatile("st.shared.u32 [%0], %1;" ::"r"(BAR(epoch, 0)), "r"(epoch) : "memory");
    __syncwarp();
    asm volatile("barrier.cluster.arrive.relaxed.aligned;" ::: "memory");
    bar_arrive(NB_RDY, 384);
    asm volatile("barrier.cluster.wait.aligned;" ::: "memory");
    bar_sync(NB_INIT, 384);
    if (warp == 8) {
      if (lane == 0) {
        const int ax = (7 * f + 3 * (f & 1)) >> 1;
        const int ay = 7 * f + ((f & 1) ? 0 : 4);
        const CUtensorMap* tx = rk ? &tmUX : &tmGX;
        const CUtensorMap* ty = rk ? &tmUY : &tmGY;
        if (RING_SIG >= 0) mbar_wait(BAR(sig, RING_SIG));
        uint32_t s = 2;
#pragma unroll 1
        for (int n = 0; n < 16; n++) {
          if (n >= 6) mbar_wait(BAR(empty1, n - 6));
          tma3_mc(sbase + (8 + s) * SLOT + rk * 8192, tx, BAR(full1, n), n * 32, ax);
          if (++s == 6) s = 0;
        }
#pragma unroll 1
        for (int k = 0; k < 16; k++) {
          mbar_wait(BAR(empty1, k < 8 ? 10 + ((12 * k + 11) >> 4) : 8 + k));
          tma3_mc(sbase + 8 * SLOT + (k & 7) * 12288 + rk * 6144, ty, BAR(full1, 16 + k), k * 32, ay);
        }
      }
    } else if (warp == 9) {
      if (lane == 0) {
#pragma unroll 1
        for (int i = 0; i < 14; i++) {
          const int kblk = 14 * kh + (int)((KORDER >> (4 * i)) & 15);
          const int j = i < 7 ? i : i - 7, sl = j + (j >= 4);
          mbar_wait(i < 7 ? BAR(empty1, 17 + 2 * sl) : BAR(empty2, j));
          if (THR_B && i >= THR_B) mbar_wait(BAR(full2, i - THR_B));
          tma3(sbase + sl * SLOT, &tmD, BAR(full2, i), 0, 64 * kblk, 2 * nq);
        }
        wait_counter(&scr->cnt[(C_LN + rb2) * 32], (epoch + 1) * 8);
        asm volatile("fence.proxy.async.global;" ::: "memory");
        mbar_wait(BAR(emptyP, 7));
        bulk_load(sbase + 4 * SLOT, &scr->LN[(rb2 * 8 + 2 * nq) * 1024 + (kh ^ 1) * 512], 8192, BAR(hbar, 0));
        bulk_load(sbase + 4 * SLOT + 8192, &scr->LN[(rb2 * 8 + 2 * nq + 1) * 1024 + (kh ^ 1) * 512], 8192, BAR(hbar, 0));
      }
    } else if (warp == 10) {
      bar_sync(NB_LN, 288);
      if (lane == 0) {
        PROFP(0);
        red_release(&scr->cnt[(C_LN + rb) * 32]);
        PROFP(1);
        wait_counter(&scr->cnt[(C_LN + rb) * 32], (epoch + 1) * 8);
        asm volatile("fence.proxy.async.global;" ::: "memory");
        PROFP(2);
#pragma unroll 1
        for (int kb = NLL; kb < 8; kb++) bulk_load(sbase + kb * SLOT, &scr->LN[(rb * 8 + kb) * 1024], 16384, BAR(fullA, kb));
#pragma unroll 1
        for (int s = 0; s < 14; s++) {
          const int kblk = 14 * kh + (int)((KORDER >> (4 * s)) & 15);
          if (s == 0 || (SPEC < 0 && (s == 8 || s == 11))) {
            if (s != 11) PROFP(3 + (s >> 2));
            mbar_wait(BAR(hint, s == 0 ? 0 : s == 8 ? 1 : 2), 0);
            if (s != 11) PROFP(4 + (s >> 2));
          }
          const int j = s < 7 ? s : s - 7;
          mbar_wait(s < 7 ? BAR(empty1, 24 + s + (s == 0) + (s >= 4)) : BAR(emptyP, j));
          if (THR_P && s >= THR_P) mbar_wait(BAR(fullP, s - THR_P));
          if (SPEC >= 0 && s == 8) mbar_wait(BAR(emptyP, SPEC & 7));
          bulk_load_mc(sbase + (j ? 7 + j : 4) * SLOT + rk * 8192, &scr->P[(rb2 * 28 + kblk) * 1024 + rk * 512], 8192, BAR(fullP, s));
        }
        PROFP(7);
      }
    } else {
      if (lane == 0) {
        l2_prefetch(wg_raw + (size_t)c * 5376, 5376);
        l2_prefetch(wu_raw + (size_t)c * 5376, 5376);
        mbar_wait(BAR(sig, PF2_SIG), 0);
        l2_prefetch(wg_raw + 688128 + (size_t)c * 8960, 8960);
        l2_prefetch(wu_raw + 688128 + (size_t)c * 8960, 8960);
      }
      mbar_wait(BAR(fullA, 7), 0);
      if (lane == 0) l2_prefetch(wd_raw + (size_t)c * 14336, 14336);
      {
        const uint32_t tag = (epoch + 1) & 1;
        uint4 v0, v1, v2;
        int it = 0;
        while (true) {
          v0 = ld_b128(&scr->ST[rb * 64 + lane]);
          v1 = ld_b128(&scr->ST[rb * 64 + 32 + lane]);
          v2 = ld_b128(&scr->ST[rb2 * 64 + 32 * (kh ^ 1) + lane]);
          if (!__any_sync(0xffffffffu, ((v0.x ^ tag) | (v1.x ^ tag) | (v2.x ^ tag)) & 1u)) break;
          if (++it > SPIN_LIMIT) { die(); break; }
        }
        sts4(sstat + lane * 16, v0.x & ~1u, v0.y, v0.z, v0.w);
        sts4(sstat + 512 + lane * 16, v1.x & ~1u, v1.y, v1.z, v1.w);
        sts4(sstat + 1024 + lane * 16, v2.x & ~1u, v2.y, v2.z, v2.w);
#pragma unroll 4
        for (int i = 0; i < 32; i++)
          st_tag(&scr->XP[(c ^ 4) * 1024 + i * 32 + lane], make_uint4(0, 0, 0, 0), tag ^ 1);
        mbar_arrive(BAR(sbar, 0));
      }
      if (lane == 0) {
        mbar_wait(BAR(empty1, 17));
#pragma unroll 1
        for (int e = 0; e < (SPEC < 0 ? 3 : 1); e++) {
          const unsigned* cp = e == 0 ? &scr->cnt[(C_PX + rb2) * 32 + kh] : &scr->cnt[(C_PY + rb2) * 32 + 2 * kh + e - 1];
          if (e == 1) mbar_wait(BAR(fullP, 0), 0);
          int it = 0;
          while ((int)(ld_relaxed(cp) - (epoch + 1) * (e == 0 ? 32 : 16)) < 0)
            if (++it > SPIN_LIMIT) { die(); break; }
          mbar_arrive(BAR(hint, e));
        }
      }
    }
  } else {
    const int warp = __shfl_sync(0xffffffffu, tid >> 5, 0);
    const int g = lane >> 2, t = lane & 3;
    PROF(0);
    PROFG(14);
#pragma unroll
    for (int i = 0; i < 4; i++) {
      const int r = i >> 1, ch = (i & 1) * 32 + lane;
      cp_async16(sbase + SM_X + (2 * warp + r) * 1024 + ((ch ^ ((ch >> 2) & 6)) * 16),
                 x + (size_t)(c + 128 * (2 * warp + r)) * 512 + ch * 8);
    }
    asm volatile("cp.async.commit_group;" ::: "memory");
    asm volatile("barrier.cluster.arrive.relaxed.aligned;" ::: "memory");
    uint4 tw[8], fb[16];
    const uint4 fa = ldg_ca4(&tab->fa[lane][0]);
#pragma unroll
    for (int i = 0; i < 8; i++) tw[i] = ldg_ca4(&tab->tw1[i][lane][0]);
#pragma unroll
    for (int i = 0; i < 16; i++) fb[i] = ldg_ca4(&tab->fb[i][lane][0]);
    uint32_t rbar;
    asm volatile("mapa.shared::cluster.u32 %0, %1, %2;" : "=r"(rbar) : "r"(sbar), "r"(rk ^ 1));
#define RBAR(field, i) (rbar + (uint32_t)offsetof(Bars, field) + 8u * (i))
    {
      const int ln = (tid >> 1) & 31, lg = ln >> 2, lt = ln & 3, i = 4 * (tid >> 6) + 2 * (tid & 1);
      const int kidx = lt + 8 * (i >> 3), nidx = 4 * ((i >> 1) & 3) + (lg >> 1);
      const uint32_t a0 = cfrag<2048>((c + 128 * kidx) * nidx, lg & 1), a1 = cfrag<2048>((c + 128 * (kidx + 4)) * nidx, lg & 1);
      const uint32_t b0 = cfrag<2048>(-(c + 128 * nidx) * kidx, lg & 1), b1 = cfrag<2048>(-(c + 128 * nidx) * (kidx + 4), lg & 1);
      asm volatile("st.shared.v2.u32 [%0], {%1,%2};" ::"r"(sbase + SM_FC + tid * 8), "r"(a0), "r"(a1) : "memory");
      asm volatile("st.shared.v2.u32 [%0], {%1,%2};" ::"r"(sbase + SM_FC + 2048 + tid * 8), "r"(b0), "r"(b1) : "memory");
    }
    asm volatile("cp.async.wait_group 0;" ::: "memory");
    __syncwarp();
    bar_arrive(NB_INIT, 384);
    PROF(13);
    uint32_t tag;
    uint4 q[4], o[4];
    {
      uint32_t v[2][8];
#pragma unroll
      for (int r = 0; r < 2; r++)
#pragma unroll
        for (int q = 0; q < 4; q++) {
          const uint2 u = lds2(sbase + SM_X + (2 * warp + r) * 1024 + (t + 4 * (q >> 1)) * 128 + (((4 * (q & 1) + (g >> 1)) ^ (2 * t)) * 16) + (g & 1) * 8);
          v[r][2 * q] = u.x; v[r][2 * q + 1] = u.y;
        }
      float sum[2], sq[2], rstd[2];
      row_stats(v[0], v[1], lane, sum, sq);
#pragma unroll
      for (int r = 0; r < 2; r++) {
        const float m = sum[r] * (1.f / 512.f);
        rstd[r] = rsqrtf(fmaxf(fmaf(-m, m, sq[r] * (1.f / 512.f)), 0.f) + 1e-5f);
      }
      uint32_t alo[4][4], ahi[4][4];
#pragma unroll
      for (int r = 0; r < 2; r++)
#pragma unroll
        for (int i = 0; i < 4; i++) {
          const uint32_t sel = (i & 1) ? 0x7632u : 0x5410u;
          const uint32_t b0 = __byte_perm(v[r][i >> 1], v[r][2 + (i >> 1)], sel);
          const uint32_t b1 = __byte_perm(v[r][4 + (i >> 1)], v[r][6 + (i >> 1)], sel);
          float d[4] = {0.f, 0.f, 0.f, 0.f};
          mma16816(d, fa.x, fa.y, fa.z, fa.w, b0, b1);
          const uint4 &ka = tw[2 * i], &kb = tw[2 * i + 1];
          const uint32_t re = pack2(d[0] * __uint_as_float(ka.x) + d[2] * __uint_as_float(ka.y), d[1] * __uint_as_float(kb.x) + d[3] * __uint_as_float(kb.y));
          const uint32_t im = pack2(d[0] * __uint_as_float(ka.z) + d[2] * __uint_as_float(ka.w), d[1] * __uint_as_float(kb.z) + d[3] * __uint_as_float(kb.w));
          const uint32_t dc = pack2(fmaf(sum[r], -1.f / 32.f, d[0]), fmaf(sum[r], -1.f / 32.f, d[1]));
          alo[i][r] = re; alo[i][2 + r] = im;
          ahi[i][r] = g == 0 ? dc : re; ahi[i][2 + r] = g == 0 ? 0u : im;
        }
      float acc[8][4];
#pragma unroll
      for (int u = 0; u < 8; u++) {
        acc[u][0] = acc[u][1] = acc[u][2] = acc[u][3] = 0.f;
#pragma unroll
        for (int i = 0; i < 4; i++) {
          const uint4& bq = fb[i * 4 + (u >> 1)];
          if (u < 4) mma16816(acc[u], alo[i][0], alo[i][1], alo[i][2], alo[i][3], (u & 1) ? bq.z : bq.x, (u & 1) ? bq.w : bq.y);
          else       mma16816(acc[u], ahi[i][0], ahi[i][1], ahi[i][2], ahi[i][3], (u & 1) ? bq.z : bq.x, (u & 1) ? bq.w : bq.y);
        }
      }
#pragma unroll
      for (int r = 0; r < 2; r++)
#pragma unroll
        for (int h = 0; h < 2; h++) {
          const int j = 2 * warp + r, m = 2 * t + h;
          const float rs = rstd[r];
          sts4(sbase + SM_E + ((j * 8 + m) * 8 + (g ^ (2 * t) ^ (2 * (j & 3)))) * 16,
               pack2(acc[2 * h][2 * r] * rs, acc[2 * h][2 * r + 1] * rs), pack2(acc[2 * h + 1][2 * r] * rs, acc[2 * h + 1][2 * r + 1] * rs),
               pack2(acc[4 + 2 * h][2 * r] * rs, acc[4 + 2 * h][2 * r + 1] * rs), pack2(acc[5 + 2 * h][2 * r] * rs, acc[5 + 2 * h][2 * r + 1] * rs));
        }
      if (tid == 0) PROFP(12);
      bar_sync(NB_RDY, 384);
      if (tid == 0) PROFP(13);
      uint4 fc[4];
#pragma unroll
      for (int i = 0; i < 4; i++) fc[i] = lds4(sbase + SM_FC + i * 512 + lane * 16);
      asm volatile("ld.shared.u32 %0, [%1];" : "=r"(tag) : "r"(BAR(epoch, 0)) : "memory");
      tag = (tag + 1) & 1;
#pragma unroll
      for (int i = 0; i < 4; i++) q[i] = lds4(sbase + SM_E + (((t + 4 * i) * 8 + warp) * 8 + (g ^ (warp & 6) ^ (2 * t))) * 16);
      cdft16(q, fc, o);
#pragma unroll
      for (int vv = 0; vv < 4; vv++) st_tag(&scr->Z1[(((4 * vv + t) * 8 + warp) * 128 + c) * 8 + g], o[vv], tag);
    }
    PROF(1);
    asm volatile("setmaxnreg.inc.sync.aligned.u32 224;");
    {
      const uint4* const zp = &scr->Z1[(c * 128 + 8 * t + warp) * 8 + g];
      const uint32_t tst = clock32();
      mbar_wait(BAR(tbar, 0), 0);
      if (tid == 0) PROFP(14);
      uint4 f2[4], g2[4];
#pragma unroll
      for (int i = 0; i < 4; i++) {
        f2[i] = lds4(TOFF(f2) + warp * 2048 + i * 512);
        g2[i] = lds4(TOFF(g2) + warp * 2048 + i * 512);
      }
      const uint4 f8 = lds4(TOFF(f8)), g8 = lds4(TOFF(g8));
      float wfr[16], wfi[16];
      {
        const float fsc = 1.f / (1 << 19);
        const float fsc3 = ((c & 7) == 7 && g == 0) ? 0.5f * fsc : fsc;
        const int gg = g == 0 ? 8 : g, wsh = (2 * (c >> 3) + 2) & 15;
#pragma unroll
        for (int i = 0; i < 16; i++) {
          const int ci = i >> 3, dd = (i >> 2) & 1, e = i & 3;
          const int kk = (e == 0 ? gg : e == 1 ? 16 + gg : e == 2 ? 16 - g : 32 - g) - 1;
          const uint32_t a = sbase + SM_W + ((2 * warp + ci) * 8 + t + 4 * dd) * 80 + wsh + 2 * kk;
          wfr[i] = bf_lo(lds_u16(a)) * (e == 3 ? fsc3 : fsc);
          wfi[i] = bf_lo(lds_u16(a + 10240)) * (e == 3 ? fsc3 : fsc);
        }
      }
      asm volatile("barrier.cluster.wait.aligned;" ::: "memory");
      PROF(2);
      spin_until(tst + POLL_DELAY);
      ld_tag4_issue<256>(q, zp);
      ld_tag4_finish<256>(q, zp, tag);
      if (tid == 0) PROFP(30);
      if (lane == 0) mbar_arrive(BAR(sig, 0));
      cdft16(q, f2, o);
      const uint32_t e2 = sbase + SM_E2;
#pragma unroll
      for (int vv = 0; vv < 4; vv++)
        sts4(e2 + ((warp * 16 + 4 * vv + t) * 8 + (g ^ (2 * t) ^ (2 * (warp & 3)))) * 16, o[vv].x, o[vv].y, o[vv].z, o[vv].w);
      bar_sync(NB_CONS, 256);
#pragma unroll
      for (int ci = 0; ci < 2; ci++) {
        const int cc = 2 * warp + ci;
        uint32_t ad[2];
        uint4 u[2];
#pragma unroll
        for (int hh = 0; hh < 2; hh++) {
          ad[hh] = e2 + (((t + 4 * hh) * 16 + cc) * 8 + (g ^ (2 * (cc & 3)) ^ (2 * t))) * 16;
          u[hh] = lds4(ad[hh]);
        }
        uint32_t res[2][4];
#pragma unroll
        for (int p = 0; p < 2; p++) {
          uint32_t y[2][2];
#pragma unroll
          for (int vv = 0; vv < 2; vv++) {
            float d[4] = {0.f, 0.f, 0.f, 0.f};
            mma16816(d, word(u[0], 2 * p), word(u[0], 2 * p + 1), word(u[1], 2 * p), word(u[1], 2 * p + 1), word(f8, 2 * vv), word(f8, 2 * vv + 1));
#pragma unroll
            for (int rr = 0; rr < 2; rr++) {
              const float fr = wfr[ci * 8 + vv * 4 + 2 * p + rr], fi = wfi[ci * 8 + vv * 4 + 2 * p + rr];
              y[vv][rr] = pack2(d[2 * rr] * fr - d[2 * rr + 1] * fi, d[2 * rr] * fi + d[2 * rr + 1] * fr);
            }
          }
#pragma unroll
          for (int vv = 0; vv < 2; vv++) {
            float d[4] = {0.f, 0.f, 0.f, 0.f};
            mma16816(d, y[0][0], y[0][1], y[1][0], y[1][1], word(g8, 2 * vv), word(g8, 2 * vv + 1));
            res[vv][2 * p] = pack2(d[0], d[1]);
            res[vv][2 * p + 1] = pack2(d[2], d[3]);
          }
        }
#pragma unroll
        for (int vv = 0; vv < 2; vv++) sts4(ad[vv], res[vv][0], res[vv][1], res[vv][2], res[vv][3]);
      }
      bar_sync(NB_CONS, 256);
#pragma unroll
      for (int i = 0; i < 4; i++) q[i] = lds4(e2 + ((warp * 16 + 4 * i + t) * 8 + (g ^ (2 * t) ^ (2 * (warp & 3)))) * 16);
      cdft16(q, g2, o);
#pragma unroll
      for (int vv = 0; vv < 4; vv++) st_tag(&scr->Z2[((8 * (4 * vv + t) + warp) * 128 + c) * 8 + g], o[vv], tag);
    }
    PROF(3);
    {
      const uint4* const zp = &scr->Z2[((c * 16 + t) * 8 + warp) * 8 + g];
      const uint32_t tst = clock32();
      uint4 gb[16], gc[4], tw[4], xr[2][2];
#pragma unroll
      for (int i = 0; i < 16; i++) gb[i] = lds4(TOFF(gb) + i * 512);
      const uint4 ga = lds4(TOFF(ga));
#pragma unroll
      for (int i = 0; i < 4; i++) {
        gc[i] = lds4(sbase + SM_FC + 2048 + i * 512 + lane * 16);
        tw[i] = lds4(TOFF(tw3) + i * 512);
        const int ch = 4 * (g + 8 * (i & 1)) + t;
        xr[i >> 1][i & 1] = lds4(sbase + SM_X + (2 * warp + (i >> 1)) * 1024 + ((ch ^ ((ch >> 2) & 6)) * 16));
      }
      PROF(4);
      spin_until(tst + POLL_DELAY2);
      ld_tag4_issue<256>(q, zp);
      ld_tag4_finish<256>(q, zp, tag);
      if (tid == 0) PROFP(31);
      if (lane == 0) mbar_arrive(BAR(sig, 1));
      cdft16(q, gc, o);
#pragma unroll
      for (int vv = 0; vv < 4; vv++)
        sts4(sbase + SM_E + (((4 * vv + t) * 8 + warp) * 8 + (g ^ (warp & 6) ^ (2 * t))) * 16, o[vv].x, o[vv].y, o[vv].z, o[vv].w);
      if (tid == 0) PROFP(8);
      bar_sync(NB_CONS, 256);
      if (tid == 0) PROFP(9);
      uint32_t hv[2][8];
      const float mk = t == 0 ? 0.f : 1.f;
#pragma unroll
      for (int r = 0; r < 2; r++) {
        const int j = 2 * warp + r;
        uint4 u[2];
#pragma unroll
        for (int h = 0; h < 2; h++) u[h] = lds4(sbase + SM_E + ((j * 8 + 2 * t + h) * 8 + (g ^ (2 * t) ^ (2 * (j & 3)))) * 16);
        float yv[4][4];
#pragma unroll
        for (int i = 0; i < 4; i++) {
          float lo[4] = {0.f, 0.f, 0.f, 0.f}, hi[4] = {0.f, 0.f, 0.f, 0.f};
          mma16816(lo, gb[i * 4].x, gb[i * 4].y, gb[i * 4].z, gb[i * 4].w, u[0].x, u[0].y);
          mma16816(lo, gb[i * 4 + 1].x, gb[i * 4 + 1].y, gb[i * 4 + 1].z, gb[i * 4 + 1].w, u[1].x, u[1].y);
          mma16816(hi, gb[i * 4 + 2].x, gb[i * 4 + 2].y, gb[i * 4 + 2].z, gb[i * 4 + 2].w, u[0].z, u[0].w);
          mma16816(hi, gb[i * 4 + 3].x, gb[i * 4 + 3].y, gb[i * 4 + 3].z, gb[i * 4 + 3].w, u[1].z, u[1].w);
          const float ca = __uint_as_float(tw[i].x), sa = __uint_as_float(tw[i].y), cb = __uint_as_float(tw[i].z), sb = __uint_as_float(tw[i].w);
          const float tr0 = fmaf(hi[0], mk, lo[0]), ti0 = fmaf(hi[2], mk, lo[2]);
          const float tr1 = lo[1] + hi[1], ti1 = lo[3] + hi[3];
          const float vr0 = tr0 * ca - ti0 * sa, vi0 = tr0 * sa + ti0 * ca;
          const float vr1 = tr1 * cb - ti1 * sb, vi1 = tr1 * sb + ti1 * cb;
          const uint32_t b0 = pack2(t == 0 ? hi[0] : vr0, vr1), b1 = pack2(t == 0 ? vr0 : vi0, vi1);
          yv[i][0] = yv[i][1] = yv[i][2] = yv[i][3] = 0.f;
          mma16816(yv[i], ga.x, ga.y, ga.z, ga.w, b0, b1);
        }
#pragma unroll
        for (int h = 0; h < 2; h++) {
          hv[r][4 * h + 0] = hadd2_bf16(xr[r][h].x, pack2(yv[0][2 * h], yv[1][2 * h]));
          hv[r][4 * h + 1] = hadd2_bf16(xr[r][h].y, pack2(yv[2][2 * h], yv[3][2 * h]));
          hv[r][4 * h + 2] = hadd2_bf16(xr[r][h].z, pack2(yv[0][2 * h + 1], yv[1][2 * h + 1]));
          hv[r][4 * h + 3] = hadd2_bf16(xr[r][h].w, pack2(yv[2][2 * h + 1], yv[3][2 * h + 1]));
        }
      }
      if (tid == 0 && hv[0][0] != 0x12345 && hv[1][7] != 0x12345) PROFP(10);
      float ds[4] = {0.f, 0.f, 0.f, 0.f};
#pragma unroll
      for (int q4 = 0; q4 < 4; q4++) mma16816(ds, hv[0][2 * q4], hv[1][2 * q4], hv[0][2 * q4 + 1], hv[1][2 * q4 + 1], 0x3f803f80u, 0x3f803f80u);
#pragma unroll
      for (int o2 = 4; o2 <= 16; o2 <<= 1) {
        ds[0] += __shfl_xor_sync(0xffffffffu, ds[0], o2);
        ds[2] += __shfl_xor_sync(0xffffffffu, ds[2], o2);
      }
      uint32_t mb[2];
#pragma unroll
      for (int r = 0; r < 2; r++) {
        const int row = 16 * f + 2 * warp + r;
        mb[r] = pack2(ds[2 * r] * (1.f / 512.f), ds[2 * r] * (1.f / 512.f));
#pragma unroll
        for (int i = 0; i < 8; i++) hv[r][i] = hsub2_bf16(hv[r][i], mb[r]);
#pragma unroll
        for (int h = 0; h < 2; h++) {
          const int n1 = g + 8 * h;
          st_tag(&scr->LN[(rb * 8 + (n1 >> 1)) * 1024 + row * 8 + ((4 * (n1 & 1) + t) ^ (row & 7))],
                 make_uint4(hv[r][4 * h], hv[r][4 * h + 1], hv[r][4 * h + 2], hv[r][4 * h + 3]), n1 < 2 * NLL ? tag : (hv[r][4 * h] & 1u));
        }
      }
      if (tid == 0) PROFP(11);
      bar_arrive(NB_LN, 288);
      float sum[2], sq[2], rstd[2];
      row_stats(hv[0], hv[1], lane, sum, sq);
#pragma unroll
      for (int r = 0; r < 2; r++) {
        const float m = sum[r] * (1.f / 512.f);
        rstd[r] = rsqrtf(fmaxf(fmaf(-m, m, sq[r] * (1.f / 512.f)), 0.f) + 1e-5f);
      }
      if (lane == 0)
        st_tag(&scr->ST[rb * 64 + 8 * f + warp], make_uint4(mb[0] << 16, __float_as_uint(rstd[0]), mb[1] << 16, __float_as_uint(rstd[1])), tag);
    }
    PROF(5);
    const int wgi = warp >> 2, wq = warp & 3;
    uint4* const pbase = &scr->P[rb * 28 * 1024 + warp * 128 + lane];
    const uint32_t a_lo0 = desc_lo(sbase + wgi * 8192, 16);
    const uint32_t ebar = lane == 0 ? BAR(empty1, 0) : RBAR(empty1, 0);
    float r0, r1;
    uint4 px[8], py[6];
    const int rh = wgi ^ kh ^ 1;
    const uint4* const psrc = &scr->P[(rb2 * 28 + 14 * kh) * 1024 + (4 * rh + wq) * 128 + lane];
    const uint32_t pa0 = sbase + (4 * rh + wq) * 2048;
    uint4 pf[LAG2 > 3 ? LAG2 : 3][4];
    uint32_t rdy;
    auto fetch2 = [&](int s, uint4 (&a)[4]) {
#pragma unroll
      for (int kk = 0; kk < 4; kk++) a[kk] = lds4(pa0 + (uint32_t)((PSLOT >> (4 * s)) & 15) * SLOT + kk * 512 + lane * 16);
    };
    {
      float acc[128];
#pragma unroll
      for (int i = 0; i < 128; i++) acc[i] = 0.f;
      const uint32_t b_lo0 = desc_lo(sbase + 8 * SLOT, 4096);
      const uint32_t t3 = clock32();
      if (WARM) {
        wg_fence();
#pragma unroll
        for (int i = 0; i < WARM; i++) wgmma_n256(acc, desc64(a_lo0 + 6 * 1024, HI128), desc64(b_lo0, HI128));
        wg_commit();
      }
      if (NLL) {
        const uint4* const ap = &scr->LN[rb * 8 * 1024 + tid];
        uint4 av[NLL ? NLL : 1][4];
        while (clock32() - t3 < POLL_DELAY3) {}
  #pragma unroll
        for (int kb = 0; kb < NLL; kb++) ld_tag4_issue<256>(av[kb], ap + kb * 1024);
        bar_sync(NB_CONS, 256);
  #pragma unroll
        for (int kb = 0; kb < NLL; kb++) {
          ld_tag4_finish<256>(av[kb], ap + kb * 1024, tag);
  #pragma unroll
          for (int i = 0; i < 4; i++) sts4(sbase + kb * SLOT + (tid + 256 * i) * 16, av[kb][i].x, av[kb][i].y, av[kb][i].z, av[kb][i].w);
        }
        asm volatile("fence.proxy.async.shared::cta;" ::: "memory");
        bar_sync(NB_CONS, 256);
      }
      uint32_t slot = 2;
#pragma unroll 1
      for (int kb = 0; kb < 8; kb++) {
        if (kb >= NLL) mbar_wait(BAR(fullA, kb), 0);
        if (kb == 0) PROF(6);
#pragma unroll
        for (int hh = 0; hh < 2; hh++) {
          if (LAGX && hh == ((16 - LAGX) & 1) && kb == ((16 - LAGX) >> 1) && wgi == 1) bar_sync(NB_LAG, 256);
          mbar_wait(BAR(full1, 2 * kb + hh));
          const uint32_t al = a_lo0 + kb * 1024 + hh * 4, bl = b_lo0 + slot * 1024;
          wg_fence();
          wgmma_n256(acc, desc64(al, HI128), desc64(bl, HI128), (kb | hh) != 0);
          wgmma_n256(acc, desc64(al + 2, HI128), desc64(bl + 128, HI128));
          wg_commit();
          if (LAGX && hh == 1 && kb == 7 && wgi == 0) bar_arrive(NB_LAG, 256);
          wg_wait<1>();
          if ((kb | hh) != 0 && lane < 2) mbar_arrive_remote(ebar + 8 * (2 * kb + hh - 1));
          if (++slot == 6) slot = 0;
        }
      }
      mbar_wait(BAR(sbar, 0), 0);
      r0 = __uint_as_float(lds2(sstat + (16 * warp + g) * 8).y);
      r1 = __uint_as_float(lds2(sstat + (16 * warp + g + 8) * 8).y);
      wg_wait<0>();
      if (lane < 2) mbar_arrive_remote(ebar + 8 * 15);
      PROF(7);
      make_p<8, XNOW>(acc, r0, r1, px, pbase, 14 * f + 6 * (f & 1), tag);
      if (XNOW && lane == 0) red_relaxed(&scr->cnt[(C_PX + rb) * 32 + (f >> 2)]);
    }
    PROF(8);
    {
      float acc[96];
#pragma unroll
      for (int i = 0; i < 96; i++) acc[i] = 0.f;
      const uint32_t b_lo0 = desc_lo(sbase + 8 * SLOT, 2048);
      uint4* const pdst = pbase + ((7 * f + 3 * (f & 1)) >> 1) * 1024;
      auto stage_y = [&](int k) {
        if (LAGY && k == 16 - LAGY && wgi == 1) bar_sync(NB_LAG, 256);
        mbar_wait(BAR(full1, 16 + k));
        const uint32_t al = a_lo0 + (k >> 1) * 1024 + (k & 1) * 4, bl = b_lo0 + (k & 7) * 768;
        wg_fence();
        wgmma_n192(acc, desc64(al, HI128), desc64(bl, HI64));
        wgmma_n192(acc, desc64(al + 2, HI128), desc64(bl + 64, HI64));
        wg_commit();
      };
#pragma unroll
      for (int k = 0; k < 4; k++) {
        stage_y(k);
        if (!XNOW) st_tag(pdst + (k >> 1) * 1024 + (k & 1) * 64, px[2 * k], tag);
        if (!XNOW) st_tag(pdst + (k >> 1) * 1024 + (k & 1) * 64 + 32, px[2 * k + 1], tag);
        if (!XNOW && k == 3 && lane == 0) red_relaxed(&scr->cnt[(C_PX + rb) * 32 + (f >> 2)]);
        wg_wait<1>();
        if (k != 0 && lane < 2) mbar_arrive_remote(ebar + 8 * (15 + k));
      }
#pragma unroll 1
      for (int k = 4; k < 16; k++) {
        stage_y(k);
        if (LAGY && k == 15 && wgi == 0) bar_arrive(NB_LAG, 256);
        wg_wait<1>();
        if (lane < 2) mbar_arrive_remote(ebar + 8 * (15 + k));
      }
      rdy = __all_sync(0xffffffffu, mbar_test(BAR(fullP, 0)) & mbar_test(BAR(full2, 0)) & mbar_test(BAR(fullP, 1)));
      if (rdy) fetch2(0, pf[0]);
      wg_wait<0>();
      if (lane < 2) mbar_arrive_remote(ebar + 8 * 31);
      PROF(9);
      make_p<6, true>(acc, r0, r1, py, pbase, 14 * f + ((f & 1) ? 0 : 8), tag);
      if (lane == 0) red_relaxed(&scr->cnt[(C_PY + rb) * 32 + (f >> 1)]);
    }
    PROF(10);
    {
      float acc[64];
      const uint32_t b2_lo0 = desc_lo(sbase, 8192);
      const uint32_t pbar = ebar + (uint32_t)(offsetof(Bars, emptyP) - offsetof(Bars, empty1));
      constexpr int S1 = 14 - LAG2;
      constexpr int NF = LAG2 > 3 ? LAG2 : 3;
      auto check2 = [&](int s) {
        ld_tag4_finish<32>(pf[s % NF], psrc + (int)((KORDER >> (4 * s)) & 15) * 1024, tag);
      };
      auto mma2 = [&](int s) {
        const uint32_t bl = b2_lo0 + (uint32_t)((BSLOT >> (4 * s)) & 15) * 1024;
        const uint4 (&a)[4] = pf[s % NF];
        if (s == 0) wgmma_rs_n128<0>(acc, a[0].x, a[0].y, a[0].z, a[0].w, desc64(bl, HI128));
        else wgmma_rs_n128<1>(acc, a[0].x, a[0].y, a[0].z, a[0].w, desc64(bl, HI128));
#pragma unroll
        for (int kk = 1; kk < 4; kk++) wgmma_rs_n128<1>(acc, a[kk].x, a[kk].y, a[kk].z, a[kk].w, desc64(bl + kk * 128, HI128));
      };
      auto stage2 = [&](int s) {
        check2(s);
        if (s < 8 && lane < (s < 7 ? 2 : 1)) mbar_arrive_remote(pbar + 8 * s);
        if (s >= 2) {
          wg_wait<1>();
          if (s <= 8 && lane == 0) mbar_arrive(BAR(empty2, s - 2));
        }
        if (!rdy) {
          if (s < 13) mbar_wait(BAR(fullP, s + 1));
          mbar_wait(BAR(full2, s));
        }
        if (tid == 0) PROFP(16 + s);
        wg_fence();
        if (s < 13) {
          fetch2(s + 1, pf[(s + 1) % NF]);
          rdy = mbar_test(BAR(full2, s + 1));
          if (s < 12) rdy &= mbar_test(BAR(fullP, s + 2));
        }
        mma2(s);
        wg_commit();
      };
      if (!rdy) {
        mbar_wait(BAR(fullP, 0));
        fetch2(0, pf[0]);
      }
#pragma unroll
      for (int s = 0; s < S1; s++) stage2(s);
      if (wgi == 0) {
#pragma unroll
        for (int s = S1; s < 14; s++) stage2(s);
        bar_arrive(NB_LAG, 256);
      } else {
        wg_wait<0>();
#pragma unroll
        for (int s = S1 + 1; s < 14; s++) {
          mbar_wait(BAR(fullP, s));
          fetch2(s, pf[s % NF]);
        }
#pragma unroll
        for (int s = S1; s < 14; s++) {
          check2(s);
          mbar_wait(BAR(full2, s));
        }
        bar_sync(NB_LAG, 256);
        wg_fence();
#pragma unroll
        for (int s = S1; s < 14; s++) mma2(s);
        wg_commit();
      }
      uint4 pv[2][4];
      const uint4* const xsrc = &scr->XP[c * 1024 + (tid & 127)];
      if (wgi == 0) {
        mbar_wait(BAR(hbar, 0));
        const uint32_t hb = sbase + 4 * SLOT + ((lane >> 3) & 1) * 8192 + (16 * wq + (lane >> 4)) * 128;
#pragma unroll
        for (int i = 0; i < 8; i++) {
          uint4 v = lds4(hb + i * 256 + (((lane & 7) ^ ((2 * i + (lane >> 4)) & 7)) * 16));
          if (2 * nq + ((lane >> 3) & 1) < NLL) v.x &= ~1u;
          const uint32_t m = __byte_perm(lds2(sstat + 1024 + (16 * wq + 2 * i + (lane >> 4)) * 8).x, 0, 0x3232);
          pv[i >> 2][i & 3] = make_uint4(hadd2_bf16(v.x, m), hadd2_bf16(v.y, m), hadd2_bf16(v.z, m), hadd2_bf16(v.w, m));
        }
      } else {
        ld_tag4_issue<128>(pv[0], xsrc);
        ld_tag4_issue<128>(pv[1], xsrc + 512);
      }
      wg_wait<0>();
      PROF(11);
#pragma unroll
      for (int h = 0; h < 2; h++)
#pragma unroll
        for (int q = 0; q < 4; q++)
          asm volatile("stmatrix.sync.aligned.m8n8.x4.shared.b16 [%0], {%1,%2,%3,%4};"
                       ::"r"(pa0 + (9 + h) * SLOT + (lane & 7) * 256 + (((4 * q + (lane >> 3)) ^ (lane & 7)) * 16)),
                         "r"(pack2(acc[16 * q + 2 * h], acc[16 * q + 2 * h + 1])), "r"(pack2(acc[16 * q + 4 + 2 * h], acc[16 * q + 5 + 2 * h])),
                         "r"(pack2(acc[16 * q + 8 + 2 * h], acc[16 * q + 9 + 2 * h])), "r"(pack2(acc[16 * q + 12 + 2 * h], acc[16 * q + 13 + 2 * h]))
                       : "memory");
      __syncwarp();
      uint4 w[8];
#pragma unroll
      for (int i = 0; i < 8; i++) {
        const int r = 2 * (i & 3) + (lane >> 4);
        w[i] = lds4(pa0 + (9 + (i >> 2)) * SLOT + r * 256 + (((lane & 15) ^ r) * 16));
      }
      uint4* dst;
      int dstr;
      if (wgi == 0) {
        dst = &scr->XP[(c ^ 4) * 1024 + tid];
        dstr = 128;
      } else {
        ld_tag4_finish<128>(pv[0], xsrc, tag);
        ld_tag4_finish<128>(pv[1], xsrc + 512, tag);
        dst = reinterpret_cast<uint4*>(out) + (16 * (c >> 4) + 2 * (4 * rh + wq) + (rb2 & 1) + 128 * (lane >> 4)) * 64 + nq * 16 + (lane & 15);
        dstr = 256 * 64;
      }
#pragma unroll
      for (int i = 0; i < 8; i++) {
        const uint4& p = pv[i >> 2][i & 3];
        const uint4 v = make_uint4(hadd2_bf16(w[i].x, p.x), hadd2_bf16(w[i].y, p.y), hadd2_bf16(w[i].z, p.z), hadd2_bf16(w[i].w, p.w));
        st_tag(dst + i * dstr, v, wgi ? (v.x & 1u) : tag);
      }
      PROF(12);
      PROFG(15);
    }
  }
#undef BAR
#undef TOFF
#undef RBAR
}

typedef CUresult (*EncodeFn)(CUtensorMap*, CUtensorMapDataType, cuuint32_t, void*, const cuuint64_t*, const cuuint64_t*,
                             const cuuint32_t*, const cuuint32_t*, CUtensorMapInterleave, CUtensorMapSwizzle,
                             CUtensorMapL2promotion, CUtensorMapFloatOOBfill);

}

extern "C" void kernel_launch(void* const* d_in, const int* in_sizes, int n_in, void* d_out, int out_size) {
  (void)in_sizes; (void)n_in; (void)out_size;
  static EncodeFn encode = nullptr;
  static void *tab = nullptr, *scr = nullptr;
  if (!encode) {
    void* fn = nullptr;
    cudaDriverEntryPointQueryResult qr;
    cudaGetDriverEntryPoint("cuTensorMapEncodeTiled", &fn, cudaEnableDefault, &qr);
    encode = (EncodeFn)fn;
    cudaGetSymbolAddress(&tab, g_tab);
    cudaGetSymbolAddress(&scr, g_scr);
    cudaFuncSetAttribute(fused_kernel, cudaFuncAttributeMaxDynamicSharedMemorySize, SMEM_BYTES);
  }
  CUtensorMap tmGX, tmUX, tmGY, tmUY, tmD, tmWR, tmWI;
  const cuuint32_t es[5] = {1, 1, 1, 1, 1};
  auto enc = [&](CUtensorMap* m, void* p, int rank, const cuuint64_t* gd, const cuuint64_t* gs, const cuuint32_t* bd,
                 CUtensorMapSwizzle sw, CUtensorMapL2promotion pr) {
    encode(m, CU_TENSOR_MAP_DATA_TYPE_BFLOAT16, rank, p, gd, gs, bd, es, CU_TENSOR_MAP_INTERLEAVE_NONE, sw, pr,
           CU_TENSOR_MAP_FLOAT_OOB_FILL_NONE);
  };
  {
    const cuuint64_t gd[3] = {64, 512, 28}, gs[2] = {3584, 128};
    const cuuint32_t bd[3] = {64, 32, 2};
    enc(&tmGX, d_in[4], 3, gd, gs, bd, CU_TENSOR_MAP_SWIZZLE_128B, CU_TENSOR_MAP_L2_PROMOTION_L2_256B);
    enc(&tmUX, d_in[5], 3, gd, gs, bd, CU_TENSOR_MAP_SWIZZLE_128B, CU_TENSOR_MAP_L2_PROMOTION_L2_256B);
  }
  {
    const cuuint64_t gd[3] = {32, 512, 56}, gs[2] = {3584, 64};
    const cuuint32_t bd[3] = {32, 32, 3};
    enc(&tmGY, d_in[4], 3, gd, gs, bd, CU_TENSOR_MAP_SWIZZLE_64B, CU_TENSOR_MAP_L2_PROMOTION_L2_128B);
    enc(&tmUY, d_in[5], 3, gd, gs, bd, CU_TENSOR_MAP_SWIZZLE_64B, CU_TENSOR_MAP_L2_PROMOTION_L2_128B);
  }
  {
    const cuuint64_t gd[3] = {64, 1792, 8}, gs[2] = {1024, 128};
    const cuuint32_t bd[3] = {64, 64, 2};
    enc(&tmD, d_in[6], 3, gd, gs, bd, CU_TENSOR_MAP_SWIZZLE_128B, CU_TENSOR_MAP_L2_PROMOTION_L2_256B);
  }
  {
    const cuuint64_t gd[3] = {4112, 8, 16}, gs[2] = {16 * 8224, 8224};
    const cuuint32_t bd[3] = {40, 8, 16};
    enc(&tmWR, d_in[1], 3, gd, gs, bd, CU_TENSOR_MAP_SWIZZLE_NONE, CU_TENSOR_MAP_L2_PROMOTION_NONE);
    enc(&tmWI, d_in[2], 3, gd, gs, bd, CU_TENSOR_MAP_SWIZZLE_NONE, CU_TENSOR_MAP_L2_PROMOTION_NONE);
  }
  fused_kernel<<<NCTA, NTHREADS, SMEM_BYTES>>>((const __nv_bfloat16*)d_in[0], (const Tables*)tab, (Scratch*)scr,
                                               (__nv_bfloat16*)d_out, (const char*)d_in[4], (const char*)d_in[5],
                                               (const char*)d_in[6], tmWR, tmWI, tmGX, tmUX, tmGY, tmUY, tmD);
}
```

```cpp
#include <cuda_runtime.h>
#include <cuda_bf16.h>
#include <cuda.h>
#include <stdint.h>

namespace {

constexpr int NCTA = 128;
constexpr int NTHREADS = 384;
constexpr int SLOT = 16384;
constexpr int SMEM_BYTES = 14 * SLOT + 3072;
constexpr int SPIN_LIMIT = 1 << 22;

struct Scratch {
  uint4 Z1[128 * 1024];
  uint4 Z2[128 * 1024];
  uint4 LN[16 * 8 * 1024];
  uint4 P[16 * 28 * 1024];
  uint4 XP[128 * 1024];
  uint4 ST[1024];
  unsigned cnt[64 * 32];
};
__device__ __align__(1024) Scratch g_scr;
#define PROF(i)
#define PROFP(i)
#define PROFG(i)

constexpr double ccos(int i, int n) {
  i &= n - 1;
  if (i > n / 2) i = n - i;
  if (4 * i == n) return 0.0;
  const bool neg = 4 * i > n;
  if (neg) i = n / 2 - i;
  const double a = 6.283185307179586476925 * i / n, a2 = a * a;
  double term = 1.0, sum = 1.0;
  for (int k = 1; k < 14; k++) { term *= -a2 / ((2 * k - 1) * (2 * k)); sum += term; }
  return neg ? -sum : sum;
}
constexpr double csin(int i, int n) { return ccos(i - n / 4, n); }
constexpr unsigned fbits(double v, int mant) {
  if (v == 0.0) return 0;
  const unsigned sg = v < 0 ? 1u : 0u;
  if (v < 0) v = -v;
  int e = 127;
  while (v < 1.0) { v *= 2.0; e--; }
  const unsigned m = (unsigned)((v - 1.0) * (double)(1u << mant) + 0.5);
  return (sg << (8 + mant)) + ((unsigned)e << mant) + m;
}
constexpr unsigned pkb(double lo, double hi) { return fbits(lo, 7) | (fbits(hi, 7) << 16); }
constexpr double fa_elem(int kp, int n1) {
  return kp <= 8 ? ccos(kp * n1, 16) : -csin((kp - 8) * n1, 16);
}
constexpr unsigned cfrag_c(int idx, int n, int ri) {
  return ri ? pkb(-csin(idx, n), ccos(idx, n)) : pkb(ccos(idx, n), csin(idx, n));
}
struct Tables {
  unsigned fb[16][32][4];
  unsigned tw1[8][32][4];
  unsigned fa[32][4];
  unsigned f2[8][4][32][4];
  unsigned g2[8][4][32][4];
  unsigned gb[16][32][4];
  unsigned tw3[4][32][4];
  unsigned ga[32][4];
  unsigned f8[32][4], g8[32][4];
};
constexpr int T1_BYTES = 12800, T2_BYTES = 44544;
static_assert(sizeof(Tables) == T1_BYTES + T2_BYTES, "table size");
constexpr Tables make_tables() {
  Tables T = {};
  for (int l = 0; l < 32; l++) {
    const int g = l >> 2, t = l & 3;
    for (int i = 0; i < 4; i++)
      for (int u = 0; u < 8; u++) {
        const int ri = g & 1, m = 2 * (g >> 1) + ((u & 3) >> 1);
        const double sg = u >= 4 ? -1.0 : 1.0;
        const int k2 = u >= 4 ? 31 - 2 * m - (u & 1) : 2 * m + (u & 1);
        const int pa = (8 * t + i) * k2, pb = (8 * t + 4 + i) * k2;
        T.fb[i * 4 + (u >> 1)][l][(u & 1) * 2 + 0] = ri == 0 ? pkb(ccos(pa, 32), ccos(pb, 32)) : pkb(-sg * csin(pa, 32), -sg * csin(pb, 32));
        T.fb[i * 4 + (u >> 1)][l][(u & 1) * 2 + 1] = ri == 0 ? pkb(csin(pa, 32), csin(pb, 32)) : pkb(sg * ccos(pa, 32), sg * ccos(pb, 32));
      }
    for (int i = 0; i < 4; i++)
      for (int ks = 0; ks < 4; ks++) {
        const int n2 = 4 * g + i, m = 2 * t + (ks & 1);
        const double sg = ks >= 2 ? -1.0 : 1.0;
        const int pa = n2 * (ks >= 2 ? 31 - 2 * m : 2 * m), pb = n2 * (ks >= 2 ? 30 - 2 * m : 2 * m + 1);
        T.gb[i * 4 + ks][l][0] = pkb(ccos(pa, 32), -sg * csin(pa, 32));
        T.gb[i * 4 + ks][l][1] = pkb(csin(pa, 32), sg * ccos(pa, 32));
        T.gb[i * 4 + ks][l][2] = pkb(ccos(pb, 32), -sg * csin(pb, 32));
        T.gb[i * 4 + ks][l][3] = pkb(csin(pb, 32), sg * ccos(pb, 32));
      }
    for (int i = 0; i < 4; i++) {
      for (int e = 0; e < 2; e++) {
        const int p = (8 * t + 4 * e + i) * (g == 0 ? 8 : g);
        T.tw1[2 * i + e][l][0] = fbits(g == 0 ? 0.0 : ccos(p, 512), 23);
        T.tw1[2 * i + e][l][1] = fbits(g == 0 ? ccos(p, 512) : csin(p, 512), 23);
        T.tw1[2 * i + e][l][2] = fbits(g == 0 ? 0.0 : -csin(p, 512), 23);
        T.tw1[2 * i + e][l][3] = fbits(g == 0 ? -csin(p, 512) : ccos(p, 512), 23);
      }
      const int ka = t == 0 ? 8 : 2 * t, kb = 2 * t + 1;
      T.tw3[i][l][0] = fbits(ccos((4 * g + i) * ka, 512), 23);
      T.tw3[i][l][1] = fbits(csin((4 * g + i) * ka, 512), 23);
      T.tw3[i][l][2] = fbits(ccos((4 * g + i) * kb, 512), 23);
      T.tw3[i][l][3] = fbits(csin((4 * g + i) * kb, 512), 23);
      const int p8 = (t + 4 * (i & 1)) * (4 * (i >> 1) + (g >> 1));
      T.f8[l][i] = cfrag_c(p8, 8, g & 1);
      T.g8[l][i] = cfrag_c(-p8, 8, g & 1);
    }
    for (int w = 0; w < 8; w++)
      for (int i = 0; i < 16; i++) {
        const int kidx = t + 4 * (i & 1) + 8 * (i >> 3), nidx = 4 * ((i >> 1) & 3) + (g >> 1);
        T.f2[w][i >> 2][l][i & 3] = cfrag_c((8 * kidx + w) * nidx, 128, g & 1);
        T.g2[w][i >> 2][l][i & 3] = cfrag_c(-(8 * nidx + w) * kidx, 128, g & 1);
      }
    T.fa[l][0] = pkb(fa_elem(g, 2 * t), fa_elem(g, 2 * t + 1));
    T.fa[l][1] = pkb(fa_elem(g + 8, 2 * t), fa_elem(g + 8, 2 * t + 1));
    T.fa[l][2] = pkb(fa_elem(g, 2 * t + 8), fa_elem(g, 2 * t + 9));
    T.fa[l][3] = pkb(fa_elem(g + 8, 2 * t + 8), fa_elem(g + 8, 2 * t + 9));
    T.ga[l][0] = pkb(fa_elem(2 * t, g), fa_elem(2 * t + 1, g));
    T.ga[l][1] = pkb(fa_elem(2 * t, g + 8), fa_elem(2 * t + 1, g + 8));
    T.ga[l][2] = pkb(fa_elem(2 * t + 8, g), fa_elem(2 * t + 9, g));
    T.ga[l][3] = pkb(fa_elem(2 * t + 8, g + 8), fa_elem(2 * t + 9, g + 8));
  }
  return T;
}
__device__ const __align__(128) Tables g_tab = make_tables();

__device__ __forceinline__ void die() { asm volatile("st.global.u32 [%0], %1;" ::"l"(0ull), "r"(0) : "memory"); }
__device__ __forceinline__ uint32_t s2u(const void* p) { return (uint32_t)__cvta_generic_to_shared(p); }
__device__ __forceinline__ void mbar_init(uint32_t b, int c) { asm volatile("mbarrier.init.shared::cta.b64 [%0], %1;" ::"r"(b), "r"(c)); }
__device__ __forceinline__ void mbar_expect(uint32_t b, int bytes) {
  asm volatile("mbarrier.arrive.expect_tx.shared::cta.b64 _, [%0], %1;" ::"r"(b), "r"(bytes) : "memory");
}
__device__ __forceinline__ void mbar_arrive(uint32_t b) { asm volatile("mbarrier.arrive.shared::cta.b64 _, [%0];" ::"r"(b) : "memory"); }
__device__ __forceinline__ uint32_t mbar_try(uint32_t b, uint32_t parity) {
  uint32_t ok;
  asm volatile("{.reg .pred p; mbarrier.try_wait.parity.shared::cta.b64 p, [%1], %2; selp.u32 %0,1,0,p;}"
               : "=r"(ok) : "r"(b), "r"(parity) : "memory");
  return ok;
}
__device__ __forceinline__ uint32_t mbar_test(uint32_t b) {
  uint32_t ok;
  asm volatile("{.reg .pred p; mbarrier.test_wait.parity.shared::cta.b64 p, [%1], 0; selp.u32 %0,1,0,p;}" : "=r"(ok) : "r"(b) : "memory");
  return ok;
}
__device__ __forceinline__ void mbar_wait(uint32_t b, uint32_t parity = 0) {
  int it = 0;
#pragma unroll 1
  while (!mbar_try(b, parity))
    if (++it > SPIN_LIMIT) { die(); break; }
}
__device__ __forceinline__ void bar_sync(int id, int n) { asm volatile("bar.sync %0, %1;" ::"r"(id), "r"(n) : "memory"); }
__device__ __forceinline__ void bar_arrive(int id, int n) { asm volatile("bar.arrive %0, %1;" ::"r"(id), "r"(n) : "memory"); }
__device__ __forceinline__ void red_release(unsigned* p) { asm volatile("red.release.gpu.global.add.u32 [%0], 1;" ::"l"(p) : "memory"); }
__device__ __forceinline__ void red_relaxed(unsigned* p) { asm volatile("red.relaxed.gpu.global.add.u32 [%0], 1;" ::"l"(p) : "memory"); }
__device__ __forceinline__ unsigned ld_acquire(const unsigned* p) {
  unsigned v;
  asm volatile("ld.acquire.gpu.global.u32 %0, [%1];" : "=r"(v) : "l"(p) : "memory");
  return v;
}
__device__ __forceinline__ unsigned ld_relaxed(const unsigned* p) {
  unsigned v;
  asm volatile("ld.relaxed.gpu.global.u32 %0, [%1];" : "=r"(v) : "l"(p) : "memory");
  return v;
}
__device__ __forceinline__ void wait_counter(const unsigned* p, unsigned target) {
  int it = 0;
  while ((int)(ld_acquire(p) - target) < 0)
    if (++it > SPIN_LIMIT) { die(); break; }
}
__device__ __forceinline__ void sts4(uint32_t a, uint32_t x, uint32_t y, uint32_t z, uint32_t w) {
  asm volatile("st.shared.v4.u32 [%0], {%1,%2,%3,%4};" ::"r"(a), "r"(x), "r"(y), "r"(z), "r"(w) : "memory");
}
__device__ __forceinline__ uint4 lds4(uint32_t a) {
  uint4 v;
  asm volatile("ld.shared.v4.u32 {%0,%1,%2,%3}, [%4];" : "=r"(v.x), "=r"(v.y), "=r"(v.z), "=r"(v.w) : "r"(a) : "memory");
  return v;
}
__device__ __forceinline__ uint32_t pack2(float lo, float hi) {
  uint32_t r;
  asm("cvt.rn.bf16x2.f32 %0, %1, %2;" : "=r"(r) : "f"(hi), "f"(lo));
  return r;
}
__device__ __forceinline__ float bf_lo(uint32_t v) { return __uint_as_float(v << 16); }
__device__ __forceinline__ uint32_t hadd2_bf16(uint32_t a, uint32_t b) {
  uint32_t r;
  asm("add.rn.bf16x2 %0, %1, %2;" : "=r"(r) : "r"(a), "r"(b));
  return r;
}
__device__ __forceinline__ void mma16816(float (&d)[4], uint32_t a0, uint32_t a1, uint32_t a2, uint32_t a3, uint32_t b0, uint32_t b1) {
  asm("mma.sync.aligned.m16n8k16.row.col.f32.bf16.bf16.f32 {%0,%1,%2,%3}, {%4,%5,%6,%7}, {%8,%9}, {%0,%1,%2,%3};"
      : "+f"(d[0]), "+f"(d[1]), "+f"(d[2]), "+f"(d[3])
      : "r"(a0), "r"(a1), "r"(a2), "r"(a3), "r"(b0), "r"(b1));
}
template <int N>
__device__ __forceinline__ void cs_frac(int idx, float& c, float& s) {
  int i = ((idx + N / 2) & (N - 1)) - N / 2;
  float a = (float)i * (6.283185307179586f / N);
  c = __cosf(a);
  s = __sinf(a);
}
template <int N>
__device__ __forceinline__ uint32_t cfrag(int idx, int ri) {
  float c, s;
  cs_frac<N>(idx, c, s);
  return ri ? pack2(-s, c) : pack2(c, s);
}
__device__ __forceinline__ uint32_t word(const uint4& v, int e) { return e == 0 ? v.x : e == 1 ? v.y : e == 2 ? v.z : v.w; }
__device__ __forceinline__ void cdft16(const uint4 (&q)[4], const uint4 (&F)[4], uint4 (&o)[4]) {
  float acc[2][4][4];
#pragma unroll
  for (int p = 0; p < 2; p++)
#pragma unroll
    for (int v = 0; v < 4; v++) {
      acc[p][v][0] = acc[p][v][1] = acc[p][v][2] = acc[p][v][3] = 0.f;
#pragma unroll
      for (int ks = 0; ks < 2; ks++)
        mma16816(acc[p][v], word(q[2 * ks], 2 * p), word(q[2 * ks], 2 * p + 1), word(q[2 * ks + 1], 2 * p),
                 word(q[2 * ks + 1], 2 * p + 1), word(F[ks * 2 + (v >> 1)], (v & 1) * 2), word(F[ks * 2 + (v >> 1)], (v & 1) * 2 + 1));
    }
#pragma unroll
  for (int v = 0; v < 4; v++)
    o[v] = make_uint4(pack2(acc[0][v][0], acc[0][v][1]), pack2(acc[0][v][2], acc[0][v][3]),
                      pack2(acc[1][v][0], acc[1][v][1]), pack2(acc[1][v][2], acc[1][v][3]));
}
__device__ __forceinline__ void st_tag(uint4* p, const uint4& v, uint32_t tag) {
  asm volatile("{.reg .b128 r; .reg .b64 a, b; mov.b64 a, {%1,%2}; mov.b64 b, {%3,%4}; mov.b128 r, {a,b}; st.relaxed.gpu.global.b128 [%0], r;}"
               ::"l"(p), "r"((v.x & ~1u) | tag), "r"(v.y), "r"(v.z), "r"(v.w) : "memory");
}
__device__ __forceinline__ uint4 ld_b128(const uint4* p) {
  uint4 v;
  asm volatile("{.reg .b128 r; .reg .b64 a, b; ld.relaxed.gpu.global.b128 r, [%4]; mov.b128 {a,b}, r; mov.b64 {%0,%1}, a; mov.b64 {%2,%3}, b;}"
               : "=r"(v.x), "=r"(v.y), "=r"(v.z), "=r"(v.w) : "l"(p) : "memory");
  return v;
}
template <int STRIDE>
__device__ __forceinline__ void ld_tag4_issue(uint4 (&q)[4], const uint4* p) {
#pragma unroll
  for (int i = 0; i < 4; i++) q[i] = ld_b128(p + i * STRIDE);
}
template <int STRIDE>
__device__ __forceinline__ void ld_tag4_finish(uint4 (&q)[4], const uint4* p, uint32_t tag) {
  int it = 0;
#pragma unroll 1
  while (__any_sync(0xffffffffu, ((q[0].x ^ tag) | (q[1].x ^ tag) | (q[2].x ^ tag) | (q[3].x ^ tag)) & 1u)) {
    ld_tag4_issue<STRIDE>(q, p);
    if (++it > SPIN_LIMIT) { die(); break; }
  }
#pragma unroll
  for (int i = 0; i < 4; i++) asm volatile("and.b32 %0, %0, 0xfffffffe;" : "+r"(q[i].x));
}
__device__ __forceinline__ void row_stats(const uint32_t (&a)[8], const uint32_t (&b)[8], int lane, float (&sum)[2], float (&sq)[2]) {
  float da[4] = {0.f, 0.f, 0.f, 0.f}, db[4] = {0.f, 0.f, 0.f, 0.f}, ds[4] = {0.f, 0.f, 0.f, 0.f};
#pragma unroll
  for (int q = 0; q < 4; q++) {
    mma16816(ds, a[2 * q], b[2 * q], a[2 * q + 1], b[2 * q + 1], 0x3f803f80u, 0x3f803f80u);
    mma16816(da, a[2 * q], b[2 * q], a[2 * q + 1], b[2 * q + 1], a[2 * q], a[2 * q + 1]);
    mma16816(db, a[2 * q], b[2 * q], a[2 * q + 1], b[2 * q + 1], b[2 * q], b[2 * q + 1]);
  }
  const int src = (lane & 28) | (lane >> 3);
  const float qa = __shfl_sync(0xffffffffu, (lane & 4) ? da[1] : da[0], src);
  const float qb = __shfl_sync(0xffffffffu, (lane & 4) ? db[3] : db[2], src);
  float v = (lane & 2) ? ((lane & 1) ? ds[2] : ds[0]) : ((lane & 1) ? qb : qa);
  v += __shfl_xor_sync(0xffffffffu, v, 4);
  v += __shfl_xor_sync(0xffffffffu, v, 8);
  v += __shfl_xor_sync(0xffffffffu, v, 16);
  sq[0] = __shfl_sync(0xffffffffu, v, 0);
  sq[1] = __shfl_sync(0xffffffffu, v, 1);
  sum[0] = __shfl_sync(0xffffffffu, v, 2);
  sum[1] = __shfl_sync(0xffffffffu, v, 3);
}
__device__ __forceinline__ uint64_t desc64(uint32_t lo, uint32_t hi) {
  uint64_t d;
  asm("mov.b64 %0, {%1, %2};" : "=l"(d) : "r"(lo), "r"(hi));
  return d;
}
constexpr uint32_t desc_hi(uint32_t sbo, uint32_t swz) { return (sbo >> 4) | (swz << 30); }
__device__ __forceinline__ uint32_t desc_lo(uint32_t addr, uint32_t lbo) { return ((addr & 0x3FFFF) >> 4) | ((lbo >> 4) << 16); }
__device__ __forceinline__ void cp_async16(uint32_t dst, const void* src) {
  asm volatile("cp.async.cg.shared.global [%0], [%1], 16;" ::"r"(dst), "l"(src) : "memory");
}
__device__ __forceinline__ uint2 lds2(uint32_t a) {
  uint2 v;
  asm volatile("ld.shared.v2.u32 {%0,%1}, [%2];" : "=r"(v.x), "=r"(v.y) : "r"(a) : "memory");
  return v;
}
__device__ __forceinline__ uint32_t lds_u16(uint32_t a) {
  uint16_t v;
  asm volatile("ld.shared.u16 %0, [%1];" : "=h"(v) : "r"(a) : "memory");
  return v;
}
__device__ __forceinline__ void wg_fence() { asm volatile("wgmma.fence.sync.aligned;" ::: "memory"); }
__device__ __forceinline__ void wg_commit() { asm volatile("wgmma.commit_group.sync.aligned;" ::: "memory"); }
template <int N>
__device__ __forceinline__ void wg_wait() { asm volatile("wgmma.wait_group.sync.aligned %0;" ::"n"(N) : "memory"); }
__device__ __forceinline__ void bulk_load(uint32_t dst, const void* src, int bytes, uint32_t bar) {
  asm volatile("cp.async.bulk.shared::cluster.global.mbarrier::complete_tx::bytes [%0], [%1], %2, [%3];"
               ::"r"(dst), "l"(src), "r"(bytes), "r"(bar) : "memory");
}
__device__ __forceinline__ void bulk_load_mc(uint32_t dst, const void* src, int bytes, uint32_t bar) {
  asm volatile("cp.async.bulk.shared::cluster.global.mbarrier::complete_tx::bytes.multicast::cluster [%0], [%1], %2, [%3], %4;"
               ::"r"(dst), "l"(src), "r"(bytes), "r"(bar), "h"((uint16_t)3) : "memory");
}
__device__ __forceinline__ void tma3(uint32_t dst, const CUtensorMap* tm, uint32_t bar, int c0, int c1, int c2) {
  asm volatile("cp.async.bulk.tensor.3d.shared::cluster.global.mbarrier::complete_tx::bytes [%0], [%1, {%3,%4,%5}], [%2];"
               ::"r"(dst), "l"(tm), "r"(bar), "r"(c0), "r"(c1), "r"(c2) : "memory");
}
__device__ __forceinline__ void tma3_mc(uint32_t dst, const CUtensorMap* tm, uint32_t bar, int c1, int c2) {
  asm volatile("cp.async.bulk.tensor.3d.shared::cluster.global.mbarrier::complete_tx::bytes.multicast::cluster [%0], [%1, {%3,%4,%5}], [%2], %6;"
               ::"r"(dst), "l"(tm), "r"(bar), "r"(0), "r"(c1), "r"(c2), "h"((uint16_t)3) : "memory");
}
__device__ __forceinline__ void mbar_arrive_remote(uint32_t rb) {
  asm volatile("mbarrier.arrive.shared::cluster.b64 _, [%0];" ::"r"(rb) : "memory");
}
__device__ __forceinline__ uint4 ldg_ca4(const void* p) {
  uint4 v;
  asm volatile("ld.global.ca.v4.u32 {%0,%1,%2,%3}, [%4];" : "=r"(v.x), "=r"(v.y), "=r"(v.z), "=r"(v.w) : "l"(p) : "memory");
  return v;
}
__device__ __forceinline__ uint32_t clock32() {
  uint32_t v;
  asm volatile("mov.u32 %0, %%clock;" : "=r"(v) :: "memory");
  return v;
}
__device__ __forceinline__ float swiglu(float g, float u, float r) {
  float hg = (0.5f * r) * g, th;
  asm("tanh.approx.f32 %0, %1;" : "=f"(th) : "f"(hg));
  return fmaf(hg, th, hg) * (r * u);
}
__device__ __forceinline__ uint32_t hsub2_bf16(uint32_t a, uint32_t b) {
  uint32_t r;
  asm("sub.rn.bf16x2 %0, %1, %2;" : "=r"(r) : "r"(a), "r"(b));
  return r;
}
__device__ __forceinline__ void l2_prefetch(const void* p, int bytes) {
  asm volatile("cp.async.bulk.prefetch.L2.global [%0], %1;" ::"l"(p), "r"(bytes) : "memory");
}

__device__ __forceinline__ void wgmma_n256(float (&d)[128], uint64_t da, uint64_t db, int sd = 1) {
  asm volatile("{.reg .pred p; setp.ne.b32 p, %130, 0;\n"
      "wgmma.mma_async.sync.aligned.m64n256k16.f32.bf16.bf16 {"
      "%0,%1,%2,%3,%4,%5,%6,%7,%8,%9,%10,%11,%12,%13,%14,%15,"
      "%16,%17,%18,%19,%20,%21,%22,%23,%24,%25,%26,%27,%28,%29,%30,%31,"
      "%32,%33,%34,%35,%36,%37,%38,%39,%40,%41,%42,%43,%44,%45,%46,%47,"
      "%48,%49,%50,%51,%52,%53,%54,%55,%56,%57,%58,%59,%60,%61,%62,%63,"
      "%64,%65,%66,%67,%68,%69,%70,%71,%72,%73,%74,%75,%76,%77,%78,%79,"
      "%80,%81,%82,%83,%84,%85,%86,%87,%88,%89,%90,%91,%92,%93,%94,%95,"
      "%96,%97,%98,%99,%100,%101,%102,%103,%104,%105,%106,%107,%108,%109,%110,%111,"
      "%112,%113,%114,%115,%116,%117,%118,%119,%120,%121,%122,%123,%124,%125,%126,%127"
      "}, %128, %129, p, 1, 1, 0, 1;}\n"
      : "+f"(d[0]),"+f"(d[1]),"+f"(d[2]),"+f"(d[3]),"+f"(d[4]),"+f"(d[5]),"+f"(d[6]),"+f"(d[7]),
        "+f"(d[8]),"+f"(d[9]),"+f"(d[10]),"+f"(d[11]),"+f"(d[12]),"+f"(d[13]),"+f"(d[14]),"+f"(d[15]),
        "+f"(d[16]),"+f"(d[17]),"+f"(d[18]),"+f"(d[19]),"+f"(d[20]),"+f"(d[21]),"+f"(d[22]),"+f"(d[23]),
        "+f"(d[24]),"+f"(d[25]),"+f"(d[26]),"+f"(d[27]),"+f"(d[28]),"+f"(d[29]),"+f"(d[30]),"+f"(d[31]),
        "+f"(d[32]),"+f"(d[33]),"+f"(d[34]),"+f"(d[35]),"+f"(d[36]),"+f"(d[37]),"+f"(d[38]),"+f"(d[39]),
        "+f"(d[40]),"+f"(d[41]),"+f"(d[42]),"+f"(d[43]),"+f"(d[44]),"+f"(d[45]),"+f"(d[46]),"+f"(d[47]),
        "+f"(d[48]),"+f"(d[49]),"+f"(d[50]),"+f"(d[51]),"+f"(d[52]),"+f"(d[53]),"+f"(d[54]),"+f"(d[55]),
        "+f"(d[56]),"+f"(d[57]),"+f"(d[58]),"+f"(d[59]),"+f"(d[60]),"+f"(d[61]),"+f"(d[62]),"+f"(d[63]),
        "+f"(d[64]),"+f"(d[65]),"+f"(d[66]),"+f"(d[67]),"+f"(d[68]),"+f"(d[69]),"+f"(d[70]),"+f"(d[71]),
        "+f"(d[72]),"+f"(d[73]),"+f"(d[74]),"+f"(d[75]),"+f"(d[76]),"+f"(d[77]),"+f"(d[78]),"+f"(d[79]),
        "+f"(d[80]),"+f"(d[81]),"+f"(d[82]),"+f"(d[83]),"+f"(d[84]),"+f"(d[85]),"+f"(d[86]),"+f"(d[87]),
        "+f"(d[88]),"+f"(d[89]),"+f"(d[90]),"+f"(d[91]),"+f"(d[92]),"+f"(d[93]),"+f"(d[94]),"+f"(d[95]),
        "+f"(d[96]),"+f"(d[97]),"+f"(d[98]),"+f"(d[99]),"+f"(d[100]),"+f"(d[101]),"+f"(d[102]),"+f"(d[103]),
        "+f"(d[104]),"+f"(d[105]),"+f"(d[106]),"+f"(d[107]),"+f"(d[108]),"+f"(d[109]),"+f"(d[110]),"+f"(d[111]),
        "+f"(d[112]),"+f"(d[113]),"+f"(d[114]),"+f"(d[115]),"+f"(d[116]),"+f"(d[117]),"+f"(d[118]),"+f"(d[119]),
        "+f"(d[120]),"+f"(d[121]),"+f"(d[122]),"+f"(d[123]),"+f"(d[124]),"+f"(d[125]),"+f"(d[126]),"+f"(d[127])
      : "l"(da), "l"(db), "r"(sd));
}
__device__ __forceinline__ void wgmma_n192(float (&d)[96], uint64_t da, uint64_t db) {
  asm volatile("wgmma.mma_async.sync.aligned.m64n192k16.f32.bf16.bf16 {"
      "%0,%1,%2,%3,%4,%5,%6,%7,%8,%9,%10,%11,%12,%13,%14,%15,"
      "%16,%17,%18,%19,%20,%21,%22,%23,%24,%25,%26,%27,%28,%29,%30,%31,"
      "%32,%33,%34,%35,%36,%37,%38,%39,%40,%41,%42,%43,%44,%45,%46,%47,"
      "%48,%49,%50,%51,%52,%53,%54,%55,%56,%57,%58,%59,%60,%61,%62,%63,"
      "%64,%65,%66,%67,%68,%69,%70,%71,%72,%73,%74,%75,%76,%77,%78,%79,"
      "%80,%81,%82,%83,%84,%85,%86,%87,%88,%89,%90,%91,%92,%93,%94,%95"
      "}, %96, %97, 1, 1, 1, 0, 1;\n"
      : "+f"(d[0]),"+f"(d[1]),"+f"(d[2]),"+f"(d[3]),"+f"(d[4]),"+f"(d[5]),"+f"(d[6]),"+f"(d[7]),
        "+f"(d[8]),"+f"(d[9]),"+f"(d[10]),"+f"(d[11]),"+f"(d[12]),"+f"(d[13]),"+f"(d[14]),"+f"(d[15]),
        "+f"(d[16]),"+f"(d[17]),"+f"(d[18]),"+f"(d[19]),"+f"(d[20]),"+f"(d[21]),"+f"(d[22]),"+f"(d[23]),
        "+f"(d[24]),"+f"(d[25]),"+f"(d[26]),"+f"(d[27]),"+f"(d[28]),"+f"(d[29]),"+f"(d[30]),"+f"(d[31]),
        "+f"(d[32]),"+f"(d[33]),"+f"(d[34]),"+f"(d[35]),"+f"(d[36]),"+f"(d[37]),"+f"(d[38]),"+f"(d[39]),
        "+f"(d[40]),"+f"(d[41]),"+f"(d[42]),"+f"(d[43]),"+f"(d[44]),"+f"(d[45]),"+f"(d[46]),"+f"(d[47]),
        "+f"(d[48]),"+f"(d[49]),"+f"(d[50]),"+f"(d[51]),"+f"(d[52]),"+f"(d[53]),"+f"(d[54]),"+f"(d[55]),
        "+f"(d[56]),"+f"(d[57]),"+f"(d[58]),"+f"(d[59]),"+f"(d[60]),"+f"(d[61]),"+f"(d[62]),"+f"(d[63]),
        "+f"(d[64]),"+f"(d[65]),"+f"(d[66]),"+f"(d[67]),"+f"(d[68]),"+f"(d[69]),"+f"(d[70]),"+f"(d[71]),
        "+f"(d[72]),"+f"(d[73]),"+f"(d[74]),"+f"(d[75]),"+f"(d[76]),"+f"(d[77]),"+f"(d[78]),"+f"(d[79]),
        "+f"(d[80]),"+f"(d[81]),"+f"(d[82]),"+f"(d[83]),"+f"(d[84]),"+f"(d[85]),"+f"(d[86]),"+f"(d[87]),
        "+f"(d[88]),"+f"(d[89]),"+f"(d[90]),"+f"(d[91]),"+f"(d[92]),"+f"(d[93]),"+f"(d[94]),"+f"(d[95])
      : "l"(da), "l"(db));
}
template <int SD>
__device__ __forceinline__ void wgmma_rs_n128(float (&d)[64], uint32_t a0, uint32_t a1, uint32_t a2, uint32_t a3, uint64_t db) {
  asm volatile("wgmma.mma_async.sync.aligned.m64n128k16.f32.bf16.bf16 {"
      "%0,%1,%2,%3,%4,%5,%6,%7,%8,%9,%10,%11,%12,%13,%14,%15,"
      "%16,%17,%18,%19,%20,%21,%22,%23,%24,%25,%26,%27,%28,%29,%30,%31,"
      "%32,%33,%34,%35,%36,%37,%38,%39,%40,%41,%42,%43,%44,%45,%46,%47,"
      "%48,%49,%50,%51,%52,%53,%54,%55,%56,%57,%58,%59,%60,%61,%62,%63"
      "}, {%64,%65,%66,%67}, %68, %69, 1, 1, 1;\n"
      : "+f"(d[0]),"+f"(d[1]),"+f"(d[2]),"+f"(d[3]),"+f"(d[4]),"+f"(d[5]),"+f"(d[6]),"+f"(d[7]),
        "+f"(d[8]),"+f"(d[9]),"+f"(d[10]),"+f"(d[11]),"+f"(d[12]),"+f"(d[13]),"+f"(d[14]),"+f"(d[15]),
        "+f"(d[16]),"+f"(d[17]),"+f"(d[18]),"+f"(d[19]),"+f"(d[20]),"+f"(d[21]),"+f"(d[22]),"+f"(d[23]),
        "+f"(d[24]),"+f"(d[25]),"+f"(d[26]),"+f"(d[27]),"+f"(d[28]),"+f"(d[29]),"+f"(d[30]),"+f"(d[31]),
        "+f"(d[32]),"+f"(d[33]),"+f"(d[34]),"+f"(d[35]),"+f"(d[36]),"+f"(d[37]),"+f"(d[38]),"+f"(d[39]),
        "+f"(d[40]),"+f"(d[41]),"+f"(d[42]),"+f"(d[43]),"+f"(d[44]),"+f"(d[45]),"+f"(d[46]),"+f"(d[47]),
        "+f"(d[48]),"+f"(d[49]),"+f"(d[50]),"+f"(d[51]),"+f"(d[52]),"+f"(d[53]),"+f"(d[54]),"+f"(d[55]),
        "+f"(d[56]),"+f"(d[57]),"+f"(d[58]),"+f"(d[59]),"+f"(d[60]),"+f"(d[61]),"+f"(d[62]),"+f"(d[63])
      : "r"(a0), "r"(a1), "r"(a2), "r"(a3), "l"(db), "n"(SD));
}

constexpr int C_LN = 0, C_PX = 16, C_PY = 32;
constexpr int NB_CONS = 1, NB_LN = 2, NB_LAG = 4, NB_INIT = 6, NB_RDY = 7;
#define LAGX 3
#define LAGY 3
#define LAG2 6
#define NLL 2
#define POLL_DELAY3 1000
#define POLL_DELAY 1100
#define FILT_DELAY 1000
#define THR_B 0
#define THR_P 0
#define SPEC -1
#define WARM 4
#define HWARM 0
#define POLL_DELAY2 POLL_DELAY
#define XNOW false
#define POLL_DELAY4 1500
#define RING_SIG 1
#define PF2_SIG 1
constexpr int SM_E = 0, SM_X = 16384, SM_E2 = 32768, SM_W = 49152, SM_FC = 69632, SM_T = 73728 - T1_BYTES;
constexpr unsigned long long KORDER = 0xBA9432DC876510ull;
constexpr unsigned long long BSLOT = 0x76532107653210ull, PSLOT = 0xDCBA984DCBA984ull;
constexpr uint32_t HI128 = desc_hi(1024, 1), HI64 = desc_hi(512, 2);

struct Bars {
  uint64_t full1[32], empty1[32], full2[16], fullA[8], empty2[8], fullP[16], emptyP[8], hbar, tbar, hint[3], sig[2], sbar;
  uint32_t epoch;
};

template <int NK, bool STORE>
__device__ __forceinline__ void make_p(const float (&acc)[NK * 16], float r0, float r1, uint4 (&p)[NK], uint4* pbase, int ks0, uint32_t tag) {
#pragma unroll
  for (int j = 0; j < NK; j++) {
    uint32_t w[4];
#pragma unroll
    for (int i = 0; i < 4; i++) {
      const int a = 8 * j + 2 * i, b = a + NK * 8;
      w[i] = pack2(swiglu(acc[a], acc[b], (i & 1) ? r1 : r0), swiglu(acc[a + 1], acc[b + 1], (i & 1) ? r1 : r0));
    }
    asm volatile("" : "+r"(w[0]), "+r"(w[1]), "+r"(w[2]), "+r"(w[3]));
    p[j] = make_uint4(w[0], w[1], w[2], w[3]);
    if (STORE) st_tag(pbase + ((ks0 + j) >> 2) * 1024 + ((ks0 + j) & 3) * 32, p[j], tag);
  }
}
__device__ __forceinline__ void spin_cycles(uint32_t n) {
  const uint32_t t0 = clock32();
  while (clock32() - t0 < n) {}
}

__device__ __forceinline__ void spin_until(uint32_t t) {
  float d[4] = {0.f, 0.f, 0.f, 0.f};
  while ((int)(clock32() - t) < 0) {
    if (HWARM) asm volatile("mma.sync.aligned.m16n8k16.row.col.f32.bf16.bf16.f32 {%0,%1,%2,%3}, {%4,%4,%4,%4}, {%4,%4}, {%0,%1,%2,%3};"
                            : "+f"(d[0]), "+f"(d[1]), "+f"(d[2]), "+f"(d[3]) : "r"(t));
  }
}

__global__ void __cluster_dims__(2, 1, 1) __launch_bounds__(NTHREADS, 1)
fused_kernel(const __nv_bfloat16* __restrict__ x, const Tables* __restrict__ tab, Scratch* __restrict__ scr,
             __nv_bfloat16* __restrict__ out, const char* __restrict__ wg_raw, const char* __restrict__ wu_raw,
             const char* __restrict__ wd_raw,
             const __grid_constant__ CUtensorMap tmWR, const __grid_constant__ CUtensorMap tmWI,
             const __grid_constant__ CUtensorMap tmGX, const __grid_constant__ CUtensorMap tmUX,
             const __grid_constant__ CUtensorMap tmGY, const __grid_constant__ CUtensorMap tmUY,
             const __grid_constant__ CUtensorMap tmD) {
  extern __shared__ __align__(1024) char smem_raw[];
  const uint32_t sbase = s2u(smem_raw);
  const uint32_t sbar = sbase + 14 * SLOT, sstat = sbar + 1280;
  const int tid = threadIdx.x, lane = tid & 31;
  const int c = blockIdx.x, rk = c & 1, f = (c >> 1) & 7, rb = 2 * (c >> 4) + rk;
  const int rb2 = 2 * (c >> 4) + (f >> 2), kh = (f >> 1) & 1, nq = 2 * (f & 1) + rk;
#define BAR(field, i) (sbar + (uint32_t)offsetof(Bars, field) + 8u * (i))
#define TOFF(field) (sbase + SM_T + (uint32_t)offsetof(Tables, field) + lane * 16)

  if (tid >= 256) {
    asm volatile("setmaxnreg.dec.sync.aligned.u32 56;");
    const int warp = __shfl_sync(0xffffffffu, tid >> 5, 0);
    const unsigned epoch = ld_relaxed(&scr->cnt[(C_LN + rb) * 32]) >> 3;
    if (lane == 0) {
      if (warp == 8) {
        if (sbase & 1023) die();
#pragma unroll
        for (int i = 0; i < 16; i++) mbar_init(BAR(emptyP, i), i < 7 ? 16 : i < 8 ? 8 : i < 13 ? 1 : i < 15 ? 8 : 32);
        mbar_expect(BAR(tbar, 0), T2_BYTES + 2 * 10240);
        mbar_expect(BAR(hbar, 0), 16384);
      } else if (warp == 9) {
#pragma unroll
        for (int i = 0; i < 32; i++) mbar_init(BAR(full1, i), 1);
#pragma unroll
        for (int i = 0; i < 32; i++) mbar_expect(BAR(full1, i), i < 16 ? 16384 : 12288);
      } else if (warp == 10) {
#pragma unroll
        for (int i = 0; i < 32; i++) mbar_init(BAR(empty1, i), 16);
#pragma unroll
        for (int i = 0; i < 14; i++) mbar_init(BAR(fullP, i), 1);
#pragma unroll
        for (int i = 0; i < 14; i++) mbar_expect(BAR(fullP, i), 16384);
      } else {
#pragma unroll
        for (int i = 0; i < 32; i++) mbar_init(BAR(full2, i), i < 24 ? 1 : 8);
#pragma unroll
        for (int i = 0; i < 24; i++) mbar_expect(BAR(full2, i), 16384);
      }
      asm volatile("fence.mbarrier_init.release.cluster;" ::: "memory");
    }
    if (tid == 256) {
      const int w0 = ((c >> 3) * 257 + 32 * (c & 7) + 1) & ~7;
      if (FILT_DELAY) {
        asm volatile("prefetch.tensormap [%0];" ::"l"(&tmWR) : "memory");
        asm volatile("prefetch.tensormap [%0];" ::"l"(&tmWI) : "memory");
        spin_cycles(FILT_DELAY);
      }
      tma3(sbase + SM_W, &tmWR, BAR(tbar, 0), w0, 0, 0);
      tma3(sbase + SM_W + 10240, &tmWI, BAR(tbar, 0), w0, 0, 0);
      bulk_load(sbase + SM_T + T1_BYTES, reinterpret_cast<const char*>(tab) + T1_BYTES, T2_BYTES, BAR(tbar, 0));
    }
    if (tid == 288) {
      asm volatile("prefetch.tensormap [%0];" ::"l"(rk ? &tmUX : &tmGX) : "memory");
      asm volatile("prefetch.tensormap [%0];" ::"l"(rk ? &tmUY : &tmGY) : "memory");
      asm volatile("prefetch.tensormap [%0];" ::"l"(&tmD) : "memory");
    }
    if (tid == 320) asm volatile("st.shared.u32 [%0], %1;" ::"r"(BAR(epoch, 0)), "r"(epoch) : "memory");
    __syncwarp();
    asm volatile("barrier.cluster.arrive.relaxed.aligned;" ::: "memory");
    bar_arrive(NB_RDY, 384);
    asm volatile("barrier.cluster.wait.aligned;" ::: "memory");
    bar_sync(NB_INIT, 384);
    if (warp == 8) {
      if (lane == 0) {
        const int ax = (7 * f + 3 * (f & 1)) >> 1;
        const int ay = 7 * f + ((f & 1) ? 0 : 4);
        const CUtensorMap* tx = rk ? &tmUX : &tmGX;
        const CUtensorMap* ty = rk ? &tmUY : &tmGY;
        if (RING_SIG >= 0) mbar_wait(BAR(sig, RING_SIG));
        uint32_t s = 2;
#pragma unroll 1
        for (int n = 0; n < 16; n++) {
          if (n >= 6) mbar_wait(BAR(empty1, n - 6));
          tma3_mc(sbase + (8 + s) * SLOT + rk * 8192, tx, BAR(full1, n), n * 32, ax);
          if (++s == 6) s = 0;
        }
#pragma unroll 1
        for (int k = 0; k < 16; k++) {
          mbar_wait(BAR(empty1, k < 8 ? 10 + ((12 * k + 11) >> 4) : 8 + k));
          tma3_mc(sbase + 8 * SLOT + (k & 7) * 12288 + rk * 6144, ty, BAR(full1, 16 + k), k * 32, ay);
        }
      }
    } else if (warp == 9) {
      if (lane == 0) {
#pragma unroll 1
        for (int i = 0; i < 14; i++) {
          const int kblk = 14 * kh + (int)((KORDER >> (4 * i)) & 15);
          const int j = i < 7 ? i : i - 7, sl = j + (j >= 4);
          mbar_wait(i < 7 ? BAR(empty1, 17 + 2 * sl) : BAR(empty2, j));
          if (THR_B && i >= THR_B) mbar_wait(BAR(full2, i - THR_B));
          tma3(sbase + sl * SLOT, &tmD, BAR(full2, i), 0, 64 * kblk, 2 * nq);
        }
        wait_counter(&scr->cnt[(C_LN + rb2) * 32], (epoch + 1) * 8);
        asm volatile("fence.proxy.async.global;" ::: "memory");
        mbar_wait(BAR(emptyP, 7));
        bulk_load(sbase + 4 * SLOT, &scr->LN[(rb2 * 8 + 2 * nq) * 1024 + kh * 512], 8192, BAR(hbar, 0));
        bulk_load(sbase + 4 * SLOT + 8192, &scr->LN[(rb2 * 8 + 2 * nq + 1) * 1024 + kh * 512], 8192, BAR(hbar, 0));
      }
    } else if (warp == 10) {
      bar_sync(NB_LN, 288);
      if (lane == 0) {
        PROFP(0);
        red_release(&scr->cnt[(C_LN + rb) * 32]);
        PROFP(1);
        wait_counter(&scr->cnt[(C_LN + rb) * 32], (epoch + 1) * 8);
        asm volatile("fence.proxy.async.global;" ::: "memory");
        PROFP(2);
#pragma unroll 1
        for (int kb = NLL; kb < 8; kb++) bulk_load(sbase + kb * SLOT, &scr->LN[(rb * 8 + kb) * 1024], 16384, BAR(fullA, kb));
#pragma unroll 1
        for (int s = 0; s < 14; s++) {
          const int kblk = 14 * kh + (int)((KORDER >> (4 * s)) & 15);
          if (s == 0 || (SPEC < 0 && (s == 8 || s == 11))) {
            if (s != 11) PROFP(3 + (s >> 2));
            mbar_wait(BAR(hint, s == 0 ? 0 : s == 8 ? 1 : 2), 0);
            if (s != 11) PROFP(4 + (s >> 2));
          }
          const int j = s < 7 ? s : s - 7;
          mbar_wait(s < 7 ? BAR(empty1, 24 + s + (s == 0) + (s >= 4)) : BAR(emptyP, j));
          if (THR_P && s >= THR_P) mbar_wait(BAR(fullP, s - THR_P));
          if (SPEC >= 0 && s == 8) mbar_wait(BAR(emptyP, SPEC & 7));
          bulk_load_mc(sbase + (j ? 7 + j : 4) * SLOT + rk * 8192, &scr->P[(rb2 * 28 + kblk) * 1024 + rk * 512], 8192, BAR(fullP, s));
        }
        PROFP(7);
      }
    } else {
      if (lane == 0) {
        l2_prefetch(wg_raw + (size_t)c * 5376, 5376);
        l2_prefetch(wu_raw + (size_t)c * 5376, 5376);
        mbar_wait(BAR(sig, PF2_SIG), 0);
        l2_prefetch(wg_raw + 688128 + (size_t)c * 8960, 8960);
        l2_prefetch(wu_raw + 688128 + (size_t)c * 8960, 8960);
      }
      mbar_wait(BAR(fullA, 7), 0);
      if (lane == 0) l2_prefetch(wd_raw + (size_t)c * 14336, 14336);
      {
        const uint32_t tag = (epoch + 1) & 1;
        uint4 v0, v1, v2;
        int it = 0;
        while (true) {
          v0 = ld_b128(&scr->ST[rb * 64 + lane]);
          v1 = ld_b128(&scr->ST[rb * 64 + 32 + lane]);
          v2 = ld_b128(&scr->ST[rb2 * 64 + 32 * kh + lane]);
          if (!__any_sync(0xffffffffu, ((v0.x ^ tag) | (v1.x ^ tag) | (v2.x ^ tag)) & 1u)) break;
          if (++it > SPIN_LIMIT) { die(); break; }
        }
        sts4(sstat + lane * 16, v0.x & ~1u, v0.y, v0.z, v0.w);
        sts4(sstat + 512 + lane * 16, v1.x & ~1u, v1.y, v1.z, v1.w);
        sts4(sstat + 1024 + lane * 16, v2.x & ~1u, v2.y, v2.z, v2.w);
#pragma unroll 4
        for (int i = 0; i < 32; i++)
          st_tag(&scr->XP[(c ^ 4) * 1024 + i * 32 + lane], make_uint4(0, 0, 0, 0), tag ^ 1);
        mbar_arrive(BAR(sbar, 0));
      }
      if (lane == 0) {
        mbar_wait(BAR(empty1, 17));
#pragma unroll 1
        for (int e = 0; e < (SPEC < 0 ? 3 : 1); e++) {
          const unsigned* cp = e == 0 ? &scr->cnt[(C_PX + rb2) * 32 + kh] : &scr->cnt[(C_PY + rb2) * 32 + 2 * kh + e - 1];
          if (e == 1) mbar_wait(BAR(fullP, 0), 0);
          int it = 0;
          while ((int)(ld_relaxed(cp) - (epoch + 1) * (e == 0 ? 32 : 16)) < 0)
            if (++it > SPIN_LIMIT) { die(); break; }
          mbar_arrive(BAR(hint, e));
        }
      }
    }
  } else {
    const int warp = __shfl_sync(0xffffffffu, tid >> 5, 0);
    const int g = lane >> 2, t = lane & 3;
    PROF(0);
    PROFG(14);
#pragma unroll
    for (int i = 0; i < 4; i++) {
      const int r = i >> 1, ch = (i & 1) * 32 + lane;
      cp_async16(sbase + SM_X + (2 * warp + r) * 1024 + ((ch ^ ((ch >> 2) & 6)) * 16),
                 x + (size_t)(c + 128 * (2 * warp + r)) * 512 + ch * 8);
    }
    asm volatile("cp.async.commit_group;" ::: "memory");
    asm volatile("barrier.cluster.arrive.relaxed.aligned;" ::: "memory");
    uint4 tw[8], fb[16];
    const uint4 fa = ldg_ca4(&tab->fa[lane][0]);
#pragma unroll
    for (int i = 0; i < 8; i++) tw[i] = ldg_ca4(&tab->tw1[i][lane][0]);
#pragma unroll
    for (int i = 0; i < 16; i++) fb[i] = ldg_ca4(&tab->fb[i][lane][0]);
    uint32_t rbar;
    asm volatile("mapa.shared::cluster.u32 %0, %1, %2;" : "=r"(rbar) : "r"(sbar), "r"(rk ^ 1));
#define RBAR(field, i) (rbar + (uint32_t)offsetof(Bars, field) + 8u * (i))
    {
      const int ln = (tid >> 1) & 31, lg = ln >> 2, lt = ln & 3, i = 4 * (tid >> 6) + 2 * (tid & 1);
      const int kidx = lt + 8 * (i >> 3), nidx = 4 * ((i >> 1) & 3) + (lg >> 1);
      const uint32_t a0 = cfrag<2048>((c + 128 * kidx) * nidx, lg & 1), a1 = cfrag<2048>((c + 128 * (kidx + 4)) * nidx, lg & 1);
      const uint32_t b0 = cfrag<2048>(-(c + 128 * nidx) * kidx, lg & 1), b1 = cfrag<2048>(-(c + 128 * nidx) * (kidx + 4), lg & 1);
      asm volatile("st.shared.v2.u32 [%0], {%1,%2};" ::"r"(sbase + SM_FC + tid * 8), "r"(a0), "r"(a1) : "memory");
      asm volatile("st.shared.v2.u32 [%0], {%1,%2};" ::"r"(sbase + SM_FC + 2048 + tid * 8), "r"(b0), "r"(b1) : "memory");
    }
    asm volatile("cp.async.wait_group 0;" ::: "memory");
    __syncwarp();
    bar_arrive(NB_INIT, 384);
    PROF(13);
    uint32_t tag;
    uint4 q[4], o[4];
    {
      uint32_t v[2][8];
#pragma unroll
      for (int r = 0; r < 2; r++)
#pragma unroll
        for (int q = 0; q < 4; q++) {
          const uint2 u = lds2(sbase + SM_X + (2 * warp + r) * 1024 + (t + 4 * (q >> 1)) * 128 + (((4 * (q & 1) + (g >> 1)) ^ (2 * t)) * 16) + (g & 1) * 8);
          v[r][2 * q] = u.x; v[r][2 * q + 1] = u.y;
        }
      float sum[2], sq[2], rstd[2];
      row_stats(v[0], v[1], lane, sum, sq);
#pragma unroll
      for (int r = 0; r < 2; r++) {
        const float m = sum[r] * (1.f / 512.f);
        rstd[r] = rsqrtf(fmaxf(fmaf(-m, m, sq[r] * (1.f / 512.f)), 0.f) + 1e-5f);
      }
      uint32_t alo[4][4], ahi[4][4];
#pragma unroll
      for (int r = 0; r < 2; r++)
#pragma unroll
        for (int i = 0; i < 4; i++) {
          const uint32_t sel = (i & 1) ? 0x7632u : 0x5410u;
          const uint32_t b0 = __byte_perm(v[r][i >> 1], v[r][2 + (i >> 1)], sel);
          const uint32_t b1 = __byte_perm(v[r][4 + (i >> 1)], v[r][6 + (i >> 1)], sel);
          float d[4] = {0.f, 0.f, 0.f, 0.f};
          mma16816(d, fa.x, fa.y, fa.z, fa.w, b0, b1);
          const uint4 &ka = tw[2 * i], &kb = tw[2 * i + 1];
          const uint32_t re = pack2(d[0] * __uint_as_float(ka.x) + d[2] * __uint_as_float(ka.y), d[1] * __uint_as_float(kb.x) + d[3] * __uint_as_float(kb.y));
          const uint32_t im = pack2(d[0] * __uint_as_float(ka.z) + d[2] * __uint_as_float(ka.w), d[1] * __uint_as_float(kb.z) + d[3] * __uint_as_float(kb.w));
          const uint32_t dc = pack2(fmaf(sum[r], -1.f / 32.f, d[0]), fmaf(sum[r], -1.f / 32.f, d[1]));
          alo[i][r] = re; alo[i][2 + r] = im;
          ahi[i][r] = g == 0 ? dc : re; ahi[i][2 + r] = g == 0 ? 0u : im;
        }
      float acc[8][4];
#pragma unroll
      for (int u = 0; u < 8; u++) {
        acc[u][0] = acc[u][1] = acc[u][2] = acc[u][3] = 0.f;
#pragma unroll
        for (int i = 0; i < 4; i++) {
          const uint4& bq = fb[i * 4 + (u >> 1)];
          if (u < 4) mma16816(acc[u], alo[i][0], alo[i][1], alo[i][2], alo[i][3], (u & 1) ? bq.z : bq.x, (u & 1) ? bq.w : bq.y);
          else       mma16816(acc[u], ahi[i][0], ahi[i][1], ahi[i][2], ahi[i][3], (u & 1) ? bq.z : bq.x, (u & 1) ? bq.w : bq.y);
        }
      }
#pragma unroll
      for (int r = 0; r < 2; r++)
#pragma unroll
        for (int h = 0; h < 2; h++) {
          const int j = 2 * warp + r, m = 2 * t + h;
          const float rs = rstd[r];
          sts4(sbase + SM_E + ((j * 8 + m) * 8 + (g ^ (2 * t) ^ (2 * (j & 3)))) * 16,
               pack2(acc[2 * h][2 * r] * rs, acc[2 * h][2 * r + 1] * rs), pack2(acc[2 * h + 1][2 * r] * rs, acc[2 * h + 1][2 * r + 1] * rs),
               pack2(acc[4 + 2 * h][2 * r] * rs, acc[4 + 2 * h][2 * r + 1] * rs), pack2(acc[5 + 2 * h][2 * r] * rs, acc[5 + 2 * h][2 * r + 1] * rs));
        }
      if (tid == 0) PROFP(12);
      bar_sync(NB_RDY, 384);
      if (tid == 0) PROFP(13);
      uint4 fc[4];
#pragma unroll
      for (int i = 0; i < 4; i++) fc[i] = lds4(sbase + SM_FC + i * 512 + lane * 16);
      asm volatile("ld.shared.u32 %0, [%1];" : "=r"(tag) : "r"(BAR(epoch, 0)) : "memory");
      tag = (tag + 1) & 1;
#pragma unroll
      for (int i = 0; i < 4; i++) q[i] = lds4(sbase + SM_E + (((t + 4 * i) * 8 + warp) * 8 + (g ^ (warp & 6) ^ (2 * t))) * 16);
      cdft16(q, fc, o);
#pragma unroll
      for (int vv = 0; vv < 4; vv++) st_tag(&scr->Z1[(((4 * vv + t) * 8 + warp) * 128 + c) * 8 + g], o[vv], tag);
    }
    PROF(1);
    asm volatile("setmaxnreg.inc.sync.aligned.u32 224;");
    {
      const uint4* const zp = &scr->Z1[(c * 128 + 8 * t + warp) * 8 + g];
      const uint32_t tst = clock32();
      mbar_wait(BAR(tbar, 0), 0);
      if (tid == 0) PROFP(14);
      uint4 f2[4], g2[4];
#pragma unroll
      for (int i = 0; i < 4; i++) {
        f2[i] = lds4(TOFF(f2) + warp * 2048 + i * 512);
        g2[i] = lds4(TOFF(g2) + warp * 2048 + i * 512);
      }
      const uint4 f8 = lds4(TOFF(f8)), g8 = lds4(TOFF(g8));
      float wfr[16], wfi[16];
      {
        const float fsc = 1.f / (1 << 19);
        const float fsc3 = ((c & 7) == 7 && g == 0) ? 0.5f * fsc : fsc;
        const int gg = g == 0 ? 8 : g, wsh = (2 * (c >> 3) + 2) & 15;
#pragma unroll
        for (int i = 0; i < 16; i++) {
          const int ci = i >> 3, dd = (i >> 2) & 1, e = i & 3;
          const int kk = (e == 0 ? gg : e == 1 ? 16 + gg : e == 2 ? 16 - g : 32 - g) - 1;
          const uint32_t a = sbase + SM_W + ((2 * warp + ci) * 8 + t + 4 * dd) * 80 + wsh + 2 * kk;
          wfr[i] = bf_lo(lds_u16(a)) * (e == 3 ? fsc3 : fsc);
          wfi[i] = bf_lo(lds_u16(a + 10240)) * (e == 3 ? fsc3 : fsc);
        }
      }
      asm volatile("barrier.cluster.wait.aligned;" ::: "memory");
      PROF(2);
      spin_until(tst + POLL_DELAY);
      ld_tag4_issue<256>(q, zp);
      ld_tag4_finish<256>(q, zp, tag);
      if (tid == 0) PROFP(30);
      if (lane == 0) mbar_arrive(BAR(sig, 0));
      cdft16(q, f2, o);
      const uint32_t e2 = sbase + SM_E2;
#pragma unroll
      for (int vv = 0; vv < 4; vv++)
        sts4(e2 + ((warp * 16 + 4 * vv + t) * 8 + (g ^ (2 * t) ^ (2 * (warp & 3)))) * 16, o[vv].x, o[vv].y, o[vv].z, o[vv].w);
      bar_sync(NB_CONS, 256);
#pragma unroll
      for (int ci = 0; ci < 2; ci++) {
        const int cc = 2 * warp + ci;
        uint32_t ad[2];
        uint4 u[2];
#pragma unroll
        for (int hh = 0; hh < 2; hh++) {
          ad[hh] = e2 + (((t + 4 * hh) * 16 + cc) * 8 + (g ^ (2 * (cc & 3)) ^ (2 * t))) * 16;
          u[hh] = lds4(ad[hh]);
        }
        uint32_t res[2][4];
#pragma unroll
        for (int p = 0; p < 2; p++) {
          uint32_t y[2][2];
#pragma unroll
          for (int vv = 0; vv < 2; vv++) {
            float d[4] = {0.f, 0.f, 0.f, 0.f};
            mma16816(d, word(u[0], 2 * p), word(u[0], 2 * p + 1), word(u[1], 2 * p), word(u[1], 2 * p + 1), word(f8, 2 * vv), word(f8, 2 * vv + 1));
#pragma unroll
            for (int rr = 0; rr < 2; rr++) {
              const float fr = wfr[ci * 8 + vv * 4 + 2 * p + rr], fi = wfi[ci * 8 + vv * 4 + 2 * p + rr];
              y[vv][rr] = pack2(d[2 * rr] * fr - d[2 * rr + 1] * fi, d[2 * rr] * fi + d[2 * rr + 1] * fr);
            }
          }
#pragma unroll
          for (int vv = 0; vv < 2; vv++) {
            float d[4] = {0.f, 0.f, 0.f, 0.f};
            mma16816(d, y[0][0], y[0][1], y[1][0], y[1][1], word(g8, 2 * vv), word(g8, 2 * vv + 1));
            res[vv][2 * p] = pack2(d[0], d[1]);
            res[vv][2 * p + 1] = pack2(d[2], d[3]);
          }
        }
#pragma unroll
        for (int vv = 0; vv < 2; vv++) sts4(ad[vv], res[vv][0], res[vv][1], res[vv][2], res[vv][3]);
      }
      bar_sync(NB_CONS, 256);
#pragma unroll
      for (int i = 0; i < 4; i++) q[i] = lds4(e2 + ((warp * 16 + 4 * i + t) * 8 + (g ^ (2 * t) ^ (2 * (warp & 3)))) * 16);
      cdft16(q, g2, o);
#pragma unroll
      for (int vv = 0; vv < 4; vv++) st_tag(&scr->Z2[((8 * (4 * vv + t) + warp) * 128 + c) * 8 + g], o[vv], tag);
    }
    PROF(3);
    {
      const uint4* const zp = &scr->Z2[((c * 16 + t) * 8 + warp) * 8 + g];
      const uint32_t tst = clock32();
      uint4 gb[16], gc[4], tw[4], xr[2][2];
#pragma unroll
      for (int i = 0; i < 16; i++) gb[i] = lds4(TOFF(gb) + i * 512);
      const uint4 ga = lds4(TOFF(ga));
#pragma unroll
      for (int i = 0; i < 4; i++) {
        gc[i] = lds4(sbase + SM_FC + 2048 + i * 512 + lane * 16);
        tw[i] = lds4(TOFF(tw3) + i * 512);
        const int ch = 4 * (g + 8 * (i & 1)) + t;
        xr[i >> 1][i & 1] = lds4(sbase + SM_X + (2 * warp + (i >> 1)) * 1024 + ((ch ^ ((ch >> 2) & 6)) * 16));
      }
      PROF(4);
      spin_until(tst + POLL_DELAY2);
      ld_tag4_issue<256>(q, zp);
      ld_tag4_finish<256>(q, zp, tag);
      if (tid == 0) PROFP(31);
      if (lane == 0) mbar_arrive(BAR(sig, 1));
      cdft16(q, gc, o);
#pragma unroll
      for (int vv = 0; vv < 4; vv++)
        sts4(sbase + SM_E + (((4 * vv + t) * 8 + warp) * 8 + (g ^ (warp & 6) ^ (2 * t))) * 16, o[vv].x, o[vv].y, o[vv].z, o[vv].w);
      if (tid == 0) PROFP(8);
      bar_sync(NB_CONS, 256);
      if (tid == 0) PROFP(9);
      uint32_t hv[2][8];
      const float mk = t == 0 ? 0.f : 1.f;
#pragma unroll
      for (int r = 0; r < 2; r++) {
        const int j = 2 * warp + r;
        uint4 u[2];
#pragma unroll
        for (int h = 0; h < 2; h++) u[h] = lds4(sbase + SM_E + ((j * 8 + 2 * t + h) * 8 + (g ^ (2 * t) ^ (2 * (j & 3)))) * 16);
        float yv[4][4];
#pragma unroll
        for (int i = 0; i < 4; i++) {
          float lo[4] = {0.f, 0.f, 0.f, 0.f}, hi[4] = {0.f, 0.f, 0.f, 0.f};
          mma16816(lo, gb[i * 4].x, gb[i * 4].y, gb[i * 4].z, gb[i * 4].w, u[0].x, u[0].y);
          mma16816(lo, gb[i * 4 + 1].x, gb[i * 4 + 1].y, gb[i * 4 + 1].z, gb[i * 4 + 1].w, u[1].x, u[1].y);
          mma16816(hi, gb[i * 4 + 2].x, gb[i * 4 + 2].y, gb[i * 4 + 2].z, gb[i * 4 + 2].w, u[0].z, u[0].w);
          mma16816(hi, gb[i * 4 + 3].x, gb[i * 4 + 3].y, gb[i * 4 + 3].z, gb[i * 4 + 3].w, u[1].z, u[1].w);
          const float ca = __uint_as_float(tw[i].x), sa = __uint_as_float(tw[i].y), cb = __uint_as_float(tw[i].z), sb = __uint_as_float(tw[i].w);
          const float tr0 = fmaf(hi[0], mk, lo[0]), ti0 = fmaf(hi[2], mk, lo[2]);
          const float tr1 = lo[1] + hi[1], ti1 = lo[3] + hi[3];
          const float vr0 = tr0 * ca - ti0 * sa, vi0 = tr0 * sa + ti0 * ca;
          const float vr1 = tr1 * cb - ti1 * sb, vi1 = tr1 * sb + ti1 * cb;
          const uint32_t b0 = pack2(t == 0 ? hi[0] : vr0, vr1), b1 = pack2(t == 0 ? vr0 : vi0, vi1);
          yv[i][0] = yv[i][1] = yv[i][2] = yv[i][3] = 0.f;
          mma16816(yv[i], ga.x, ga.y, ga.z, ga.w, b0, b1);
        }
#pragma unroll
        for (int h = 0; h < 2; h++) {
          hv[r][4 * h + 0] = hadd2_bf16(xr[r][h].x, pack2(yv[0][2 * h], yv[1][2 * h]));
          hv[r][4 * h + 1] = hadd2_bf16(xr[r][h].y, pack2(yv[2][2 * h], yv[3][2 * h]));
          hv[r][4 * h + 2] = hadd2_bf16(xr[r][h].z, pack2(yv[0][2 * h + 1], yv[1][2 * h + 1]));
          hv[r][4 * h + 3] = hadd2_bf16(xr[r][h].w, pack2(yv[2][2 * h + 1], yv[3][2 * h + 1]));
        }
      }
      if (tid == 0 && hv[0][0] != 0x12345 && hv[1][7] != 0x12345) PROFP(10);
      float ds[4] = {0.f, 0.f, 0.f, 0.f};
#pragma unroll
      for (int q4 = 0; q4 < 4; q4++) mma16816(ds, hv[0][2 * q4], hv[1][2 * q4], hv[0][2 * q4 + 1], hv[1][2 * q4 + 1], 0x3f803f80u, 0x3f803f80u);
#pragma unroll
      for (int o2 = 4; o2 <= 16; o2 <<= 1) {
        ds[0] += __shfl_xor_sync(0xffffffffu, ds[0], o2);
        ds[2] += __shfl_xor_sync(0xffffffffu, ds[2], o2);
      }
      uint32_t mb[2];
#pragma unroll
      for (int r = 0; r < 2; r++) {
        const int row = 16 * f + 2 * warp + r;
        mb[r] = pack2(ds[2 * r] * (1.f / 512.f), ds[2 * r] * (1.f / 512.f));
#pragma unroll
        for (int i = 0; i < 8; i++) hv[r][i] = hsub2_bf16(hv[r][i], mb[r]);
#pragma unroll
        for (int h = 0; h < 2; h++) {
          const int n1 = g + 8 * h;
          st_tag(&scr->LN[(rb * 8 + (n1 >> 1)) * 1024 + row * 8 + ((4 * (n1 & 1) + t) ^ (row & 7))],
                 make_uint4(hv[r][4 * h], hv[r][4 * h + 1], hv[r][4 * h + 2], hv[r][4 * h + 3]), n1 < 2 * NLL ? tag : (hv[r][4 * h] & 1u));
        }
      }
      if (tid == 0) PROFP(11);
      bar_arrive(NB_LN, 288);
      float sum[2], sq[2], rstd[2];
      row_stats(hv[0], hv[1], lane, sum, sq);
#pragma unroll
      for (int r = 0; r < 2; r++) {
        const float m = sum[r] * (1.f / 512.f);
        rstd[r] = rsqrtf(fmaxf(fmaf(-m, m, sq[r] * (1.f / 512.f)), 0.f) + 1e-5f);
      }
      if (lane == 0)
        st_tag(&scr->ST[rb * 64 + 8 * f + warp], make_uint4(mb[0] << 16, __float_as_uint(rstd[0]), mb[1] << 16, __float_as_uint(rstd[1])), tag);
    }
    PROF(5);
    const int wgi = warp >> 2, wq = warp & 3;
    uint4* const pbase = &scr->P[rb * 28 * 1024 + warp * 128 + lane];
    const uint32_t a_lo0 = desc_lo(sbase + wgi * 8192, 16);
    const uint32_t ebar = lane == 0 ? BAR(empty1, 0) : RBAR(empty1, 0);
    float r0, r1;
    uint4 px[8], py[6];
    const int rh = wgi ^ kh ^ 1;
    const uint4* const psrc = &scr->P[(rb2 * 28 + 14 * kh) * 1024 + (4 * rh + wq) * 128 + lane];
    const uint32_t pa0 = sbase + (4 * rh + wq) * 2048;
    uint4 pf[LAG2 > 3 ? LAG2 : 3][4];
    uint32_t rdy;
    auto fetch2 = [&](int s, uint4 (&a)[4]) {
#pragma unroll
      for (int kk = 0; kk < 4; kk++) a[kk] = lds4(pa0 + (uint32_t)((PSLOT >> (4 * s)) & 15) * SLOT + kk * 512 + lane * 16);
    };
    {
      float acc[128];
#pragma unroll
      for (int i = 0; i < 128; i++) acc[i] = 0.f;
      const uint32_t b_lo0 = desc_lo(sbase + 8 * SLOT, 4096);
      const uint32_t t3 = clock32();
      if (WARM) {
        wg_fence();
#pragma unroll
        for (int i = 0; i < WARM; i++) wgmma_n256(acc, desc64(a_lo0 + 6 * 1024, HI128), desc64(b_lo0, HI128));
        wg_commit();
      }
      if (NLL) {
        const uint4* const ap = &scr->LN[rb * 8 * 1024 + tid];
        uint4 av[NLL ? NLL : 1][4];
        while (clock32() - t3 < POLL_DELAY3) {}
  #pragma unroll
        for (int kb = 0; kb < NLL; kb++) ld_tag4_issue<256>(av[kb], ap + kb * 1024);
        bar_sync(NB_CONS, 256);
  #pragma unroll
        for (int kb = 0; kb < NLL; kb++) {
          ld_tag4_finish<256>(av[kb], ap + kb * 1024, tag);
  #pragma unroll
          for (int i = 0; i < 4; i++) sts4(sbase + kb * SLOT + (tid + 256 * i) * 16, av[kb][i].x, av[kb][i].y, av[kb][i].z, av[kb][i].w);
        }
        asm volatile("fence.proxy.async.shared::cta;" ::: "memory");
        bar_sync(NB_CONS, 256);
      }
      uint32_t slot = 2;
#pragma unroll 1
      for (int kb = 0; kb < 8; kb++) {
        if (kb >= NLL) mbar_wait(BAR(fullA, kb), 0);
        if (kb == 0) PROF(6);
#pragma unroll
        for (int hh = 0; hh < 2; hh++) {
          if (LAGX && hh == ((16 - LAGX) & 1) && kb == ((16 - LAGX) >> 1) && wgi == 1) bar_sync(NB_LAG, 256);
          mbar_wait(BAR(full1, 2 * kb + hh));
          const uint32_t al = a_lo0 + kb * 1024 + hh * 4, bl = b_lo0 + slot * 1024;
          wg_fence();
          wgmma_n256(acc, desc64(al, HI128), desc64(bl, HI128), (kb | hh) != 0);
          wgmma_n256(acc, desc64(al + 2, HI128), desc64(bl + 128, HI128));
          wg_commit();
          if (LAGX && hh == 1 && kb == 7 && wgi == 0) bar_arrive(NB_LAG, 256);
          wg_wait<1>();
          if ((kb | hh) != 0 && lane < 2) mbar_arrive_remote(ebar + 8 * (2 * kb + hh - 1));
          if (++slot == 6) slot = 0;
        }
      }
      mbar_wait(BAR(sbar, 0), 0);
      r0 = __uint_as_float(lds2(sstat + (16 * warp + g) * 8).y);
      r1 = __uint_as_float(lds2(sstat + (16 * warp + g + 8) * 8).y);
      wg_wait<0>();
      if (lane < 2) mbar_arrive_remote(ebar + 8 * 15);
      PROF(7);
      make_p<8, XNOW>(acc, r0, r1, px, pbase, 14 * f + 6 * (f & 1), tag);
      if (XNOW && lane == 0) red_relaxed(&scr->cnt[(C_PX + rb) * 32 + (f >> 2)]);
    }
    PROF(8);
    {
      float acc[96];
#pragma unroll
      for (int i = 0; i < 96; i++) acc[i] = 0.f;
      const uint32_t b_lo0 = desc_lo(sbase + 8 * SLOT, 2048);
      uint4* const pdst = pbase + ((7 * f + 3 * (f & 1)) >> 1) * 1024;
      auto stage_y = [&](int k) {
        if (LAGY && k == 16 - LAGY && wgi == 1) bar_sync(NB_LAG, 256);
        mbar_wait(BAR(full1, 16 + k));
        const uint32_t al = a_lo0 + (k >> 1) * 1024 + (k & 1) * 4, bl = b_lo0 + (k & 7) * 768;
        wg_fence();
        wgmma_n192(acc, desc64(al, HI128), desc64(bl, HI64));
        wgmma_n192(acc, desc64(al + 2, HI128), desc64(bl + 64, HI64));
        wg_commit();
      };
#pragma unroll
      for (int k = 0; k < 4; k++) {
        stage_y(k);
        if (!XNOW) st_tag(pdst + (k >> 1) * 1024 + (k & 1) * 64, px[2 * k], tag);
        if (!XNOW) st_tag(pdst + (k >> 1) * 1024 + (k & 1) * 64 + 32, px[2 * k + 1], tag);
        if (!XNOW && k == 3 && lane == 0) red_relaxed(&scr->cnt[(C_PX + rb) * 32 + (f >> 2)]);
        wg_wait<1>();
        if (k != 0 && lane < 2) mbar_arrive_remote(ebar + 8 * (15 + k));
      }
#pragma unroll 1
      for (int k = 4; k < 16; k++) {
        stage_y(k);
        if (LAGY && k == 15 && wgi == 0) bar_arrive(NB_LAG, 256);
        wg_wait<1>();
        if (lane < 2) mbar_arrive_remote(ebar + 8 * (15 + k));
      }
      rdy = __all_sync(0xffffffffu, mbar_test(BAR(fullP, 0)) & mbar_test(BAR(full2, 0)) & mbar_test(BAR(fullP, 1)));
      if (rdy) fetch2(0, pf[0]);
      wg_wait<0>();
      if (lane < 2) mbar_arrive_remote(ebar + 8 * 31);
      PROF(9);
      make_p<6, true>(acc, r0, r1, py, pbase, 14 * f + ((f & 1) ? 0 : 8), tag);
      if (lane == 0) red_relaxed(&scr->cnt[(C_PY + rb) * 32 + (f >> 1)]);
    }
    PROF(10);
    {
      float acc[64];
      const uint32_t b2_lo0 = desc_lo(sbase, 8192);
      const uint32_t pbar = ebar + (uint32_t)(offsetof(Bars, emptyP) - offsetof(Bars, empty1));
      constexpr int S1 = 14 - LAG2;
      constexpr int NF = LAG2 > 3 ? LAG2 : 3;
      auto check2 = [&](int s) {
        ld_tag4_finish<32>(pf[s % NF], psrc + (int)((KORDER >> (4 * s)) & 15) * 1024, tag);
      };
      auto mma2 = [&](int s) {
        const uint32_t bl = b2_lo0 + (uint32_t)((BSLOT >> (4 * s)) & 15) * 1024;
        const uint4 (&a)[4] = pf[s % NF];
        if (s == 0) wgmma_rs_n128<0>(acc, a[0].x, a[0].y, a[0].z, a[0].w, desc64(bl, HI128));
        else wgmma_rs_n128<1>(acc, a[0].x, a[0].y, a[0].z, a[0].w, desc64(bl, HI128));
#pragma unroll
        for (int kk = 1; kk < 4; kk++) wgmma_rs_n128<1>(acc, a[kk].x, a[kk].y, a[kk].z, a[kk].w, desc64(bl + kk * 128, HI128));
      };
      auto stage2 = [&](int s) {
        check2(s);
        if (s < 8 && lane < (s < 7 ? 2 : 1)) mbar_arrive_remote(pbar + 8 * s);
        if (s >= 2) {
          wg_wait<1>();
          if (s <= 8 && lane == 0) mbar_arrive(BAR(empty2, s - 2));
        }
        if (!rdy) {
          if (s < 13) mbar_wait(BAR(fullP, s + 1));
          mbar_wait(BAR(full2, s));
        }
        if (tid == 0) PROFP(16 + s);
        wg_fence();
        if (s < 13) {
          fetch2(s + 1, pf[(s + 1) % NF]);
          rdy = mbar_test(BAR(full2, s + 1));
          if (s < 12) rdy &= mbar_test(BAR(fullP, s + 2));
        }
        mma2(s);
        wg_commit();
      };
      if (!rdy) {
        mbar_wait(BAR(fullP, 0));
        fetch2(0, pf[0]);
      }
#pragma unroll
      for (int s = 0; s < S1; s++) stage2(s);
      if (wgi == 0) {
#pragma unroll
        for (int s = S1; s < 14; s++) stage2(s);
        bar_arrive(NB_LAG, 256);
        uint4* const dst = &scr->XP[(c ^ 4) * 1024 + tid];
        wg_wait<0>();
        PROF(11);
#pragma unroll
        for (int i = 0; i < 8; i++)
          st_tag(dst + i * 128, make_uint4(pack2(acc[8 * i], acc[8 * i + 1]), pack2(acc[8 * i + 2], acc[8 * i + 3]),
                                           pack2(acc[8 * i + 4], acc[8 * i + 5]), pack2(acc[8 * i + 6], acc[8 * i + 7])), tag);
      } else {
        wg_wait<0>();
        if (lane == 0) {
#pragma unroll
          for (int s = S1 - 2; s < S1; s++)
            if (s <= 6) mbar_arrive(BAR(empty2, s));
        }
#pragma unroll
        for (int s = S1; s < 14; s++) {
          if (s > S1) {
            mbar_wait(BAR(fullP, s));
            fetch2(s, pf[s % NF]);
          }
          check2(s);
          if (s == 7 && lane == 0) mbar_arrive(BAR(emptyP, 7));
        }
        {
          const float m0 = __uint_as_float(lds2(sstat + 1024 + (16 * wq + g) * 8).x);
          const float m1 = __uint_as_float(lds2(sstat + 1024 + (16 * wq + g + 8) * 8).x);
          const uint32_t hb = sbase + 4 * SLOT + (16 * wq + (lane & 15)) * 128;
          mbar_wait(BAR(hbar, 0));
#pragma unroll
          for (int i = 0; i < 8; i++) {
            uint32_t h[4];
            asm volatile("ldmatrix.sync.aligned.m8n8.x4.shared.b16 {%0,%1,%2,%3}, [%4];"
                         : "=r"(h[0]), "=r"(h[1]), "=r"(h[2]), "=r"(h[3])
                         : "r"(hb + (i >> 2) * 8192 + (((2 * (i & 3) + (lane >> 4)) ^ (lane & 7)) * 16)) : "memory");
            const uint32_t mk = (t == 0 && 2 * nq + (i >> 2) < NLL) ? ~1u : ~0u;
#pragma unroll
            for (int e = 0; e < 4; e++) {
              acc[8 * i + 2 * e] += bf_lo(h[e] & mk) + ((e & 1) ? m1 : m0);
              acc[8 * i + 2 * e + 1] += __uint_as_float(h[e] & 0xffff0000u) + ((e & 1) ? m1 : m0);
            }
          }
        }
#pragma unroll
        for (int s = S1; s < 14; s++) mbar_wait(BAR(full2, s));
        bar_sync(NB_LAG, 256);
        const uint32_t t4 = clock32();
        wg_fence();
#pragma unroll
        for (int s = S1; s < 14; s++) mma2(s);
        wg_commit();
        uint4 pv[2][4];
        const uint4* const xsrc = &scr->XP[c * 1024 + (tid & 127)];
        while (clock32() - t4 < POLL_DELAY4) {}
        ld_tag4_issue<128>(pv[0], xsrc);
        ld_tag4_issue<128>(pv[1], xsrc + 512);
        wg_wait<0>();
        PROF(11);
        uint32_t w[32];
#pragma unroll
        for (int i = 0; i < 32; i++) w[i] = pack2(acc[2 * i], acc[2 * i + 1]);
        ld_tag4_finish<128>(pv[0], xsrc, tag);
        ld_tag4_finish<128>(pv[1], xsrc + 512, tag);
#pragma unroll
        for (int i = 0; i < 8; i++) {
          const uint4& p = pv[i >> 2][i & 3];
          asm volatile("stmatrix.sync.aligned.m8n8.x4.shared.b16 [%0], {%1,%2,%3,%4};"
                       ::"r"(pa0 + (9 + ((lane >> 3) & 1)) * SLOT + (lane & 7) * 256 + (((2 * i + (lane >> 4)) ^ (lane & 7)) * 16)),
                         "r"(hadd2_bf16(w[4 * i], p.x)), "r"(hadd2_bf16(w[4 * i + 1], p.y)), "r"(hadd2_bf16(w[4 * i + 2], p.z)),
                         "r"(hadd2_bf16(w[4 * i + 3], p.w)) : "memory");
        }
        __syncwarp();
        uint4* const dst = reinterpret_cast<uint4*>(out) + (16 * (c >> 4) + 2 * (4 * rh + wq) + (rb2 & 1) + 128 * (lane >> 4)) * 64 + nq * 16 + (lane & 15);
#pragma unroll
        for (int i = 0; i < 8; i++) {
          const int r = 2 * (i & 3) + (lane >> 4);
          dst[i * 256 * 64] = lds4(pa0 + (9 + (i >> 2)) * SLOT + r * 256 + (((lane & 15) ^ r) * 16));
        }
      }
      PROF(12);
      PROFG(15);
    }
  }
#undef BAR
#undef TOFF
#undef RBAR
}

typedef CUresult (*EncodeFn)(CUtensorMap*, CUtensorMapDataType, cuuint32_t, void*, const cuuint64_t*, const cuuint64_t*,
                             const cuuint32_t*, const cuuint32_t*, CUtensorMapInterleave, CUtensorMapSwizzle,
                             CUtensorMapL2promotion, CUtensorMapFloatOOBfill);

}

extern "C" void kernel_launch(void* const* d_in, const int* in_sizes, int n_in, void* d_out, int out_size) {
  (void)in_sizes; (void)n_in; (void)out_size;
  static EncodeFn encode = nullptr;
  static void *tab = nullptr, *scr = nullptr;
  if (!encode) {
    void* fn = nullptr;
    cudaDriverEntryPointQueryResult qr;
    cudaGetDriverEntryPoint("cuTensorMapEncodeTiled", &fn, cudaEnableDefault, &qr);
    encode = (EncodeFn)fn;
    cudaGetSymbolAddress(&tab, g_tab);
    cudaGetSymbolAddress(&scr, g_scr);
    cudaFuncSetAttribute(fused_kernel, cudaFuncAttributeMaxDynamicSharedMemorySize, SMEM_BYTES);
  }
  CUtensorMap tmGX, tmUX, tmGY, tmUY, tmD, tmWR, tmWI;
  const cuuint32_t es[5] = {1, 1, 1, 1, 1};
  auto enc = [&](CUtensorMap* m, void* p, int rank, const cuuint64_t* gd, const cuuint64_t* gs, const cuuint32_t* bd,
                 CUtensorMapSwizzle sw, CUtensorMapL2promotion pr) {
    encode(m, CU_TENSOR_MAP_DATA_TYPE_BFLOAT16, rank, p, gd, gs, bd, es, CU_TENSOR_MAP_INTERLEAVE_NONE, sw, pr,
           CU_TENSOR_MAP_FLOAT_OOB_FILL_NONE);
  };
  {
    const cuuint64_t gd[3] = {64, 512, 28}, gs[2] = {3584, 128};
    const cuuint32_t bd[3] = {64, 32, 2};
    enc(&tmGX, d_in[4], 3, gd, gs, bd, CU_TENSOR_MAP_SWIZZLE_128B, CU_TENSOR_MAP_L2_PROMOTION_L2_256B);
    enc(&tmUX, d_in[5], 3, gd, gs, bd, CU_TENSOR_MAP_SWIZZLE_128B, CU_TENSOR_MAP_L2_PROMOTION_L2_256B);
  }
  {
    const cuuint64_t gd[3] = {32, 512, 56}, gs[2] = {3584, 64};
    const cuuint32_t bd[3] = {32, 32, 3};
    enc(&tmGY, d_in[4], 3, gd, gs, bd, CU_TENSOR_MAP_SWIZZLE_64B, CU_TENSOR_MAP_L2_PROMOTION_L2_128B);
    enc(&tmUY, d_in[5], 3, gd, gs, bd, CU_TENSOR_MAP_SWIZZLE_64B, CU_TENSOR_MAP_L2_PROMOTION_L2_128B);
  }
  {
    const cuuint64_t gd[3] = {64, 1792, 8}, gs[2] = {1024, 128};
    const cuuint32_t bd[3] = {64, 64, 2};
    enc(&tmD, d_in[6], 3, gd, gs, bd, CU_TENSOR_MAP_SWIZZLE_128B, CU_TENSOR_MAP_L2_PROMOTION_L2_256B);
  }
  {
    const cuuint64_t gd[3] = {4112, 8, 16}, gs[2] = {16 * 8224, 8224};
    const cuuint32_t bd[3] = {40, 8, 16};
    enc(&tmWR, d_in[1], 3, gd, gs, bd, CU_TENSOR_MAP_SWIZZLE_NONE, CU_TENSOR_MAP_L2_PROMOTION_NONE);
    enc(&tmWI, d_in[2], 3, gd, gs, bd, CU_TENSOR_MAP_SWIZZLE_NONE, CU_TENSOR_MAP_L2_PROMOTION_NONE);
  }
  fused_kernel<<<NCTA, NTHREADS, SMEM_BYTES>>>((const __nv_bfloat16*)d_in[0], (const Tables*)tab, (Scratch*)scr,
                                               (__nv_bfloat16*)d_out, (const char*)d_in[4], (const char*)d_in[5],
                                               (const char*)d_in[6], tmWR, tmWI, tmGX, tmUX, tmGY, tmUY, tmD);
}
```

```cpp
#include <cuda_runtime.h>
#include <cuda_bf16.h>
#include <cuda.h>
#include <stdint.h>

namespace {

constexpr int NCTA = 128;
constexpr int NTHREADS = 384;
constexpr int SLOT = 16384;
constexpr int SMEM_BYTES = 14 * SLOT + 3072;
constexpr int SPIN_LIMIT = 1 << 22;

struct Scratch {
  uint4 Z1[128 * 1024];
  uint4 Z2[128 * 1024];
  uint4 LN[16 * 8 * 1024];
  uint4 P[16 * 28 * 1024];
  uint4 XP[128 * 1024];
  uint4 ST[1024];
  unsigned cnt[64 * 32];
};
__device__ __align__(1024) Scratch g_scr;
#define PROF(i)
#define PROFP(i)
#define PROFG(i)

constexpr double ccos(int i, int n) {
  i &= n - 1;
  if (i > n / 2) i = n - i;
  if (4 * i == n) return 0.0;
  const bool neg = 4 * i > n;
  if (neg) i = n / 2 - i;
  const double a = 6.283185307179586476925 * i / n, a2 = a * a;
  double term = 1.0, sum = 1.0;
  for (int k = 1; k < 14; k++) { term *= -a2 / ((2 * k - 1) * (2 * k)); sum += term; }
  return neg ? -sum : sum;
}
constexpr double csin(int i, int n) { return ccos(i - n / 4, n); }
constexpr unsigned fbits(double v, int mant) {
  if (v == 0.0) return 0;
  const unsigned sg = v < 0 ? 1u : 0u;
  if (v < 0) v = -v;
  int e = 127;
  while (v < 1.0) { v *= 2.0; e--; }
  const unsigned m = (unsigned)((v - 1.0) * (double)(1u << mant) + 0.5);
  return (sg << (8 + mant)) + ((unsigned)e << mant) + m;
}
constexpr unsigned pkb(double lo, double hi) { return fbits(lo, 7) | (fbits(hi, 7) << 16); }
constexpr double fa_elem(int kp, int n1) {
  return kp <= 8 ? ccos(kp * n1, 16) : -csin((kp - 8) * n1, 16);
}
constexpr unsigned cfrag_c(int idx, int n, int ri) {
  return ri ? pkb(-csin(idx, n), ccos(idx, n)) : pkb(ccos(idx, n), csin(idx, n));
}
struct Tables {
  unsigned fb[16][32][4];
  unsigned tw1[8][32][4];
  unsigned fa[32][4];
  unsigned f2[8][4][32][4];
  unsigned g2[8][4][32][4];
  unsigned gb[16][32][4];
  unsigned tw3[4][32][4];
  unsigned ga[32][4];
  unsigned f8[32][4], g8[32][4];
};
constexpr int T1_BYTES = 12800, T2_BYTES = 44544;
static_assert(sizeof(Tables) == T1_BYTES + T2_BYTES, "table size");
constexpr Tables make_tables() {
  Tables T = {};
  for (int l = 0; l < 32; l++) {
    const int g = l >> 2, t = l & 3;
    for (int i = 0; i < 4; i++)
      for (int u = 0; u < 8; u++) {
        const int ri = g & 1, m = 2 * (g >> 1) + ((u & 3) >> 1);
        const double sg = u >= 4 ? -1.0 : 1.0;
        const int k2 = u >= 4 ? 31 - 2 * m - (u & 1) : 2 * m + (u & 1);
        const int pa = (8 * t + i) * k2, pb = (8 * t + 4 + i) * k2;
        T.fb[i * 4 + (u >> 1)][l][(u & 1) * 2 + 0] = ri == 0 ? pkb(ccos(pa, 32), ccos(pb, 32)) : pkb(-sg * csin(pa, 32), -sg * csin(pb, 32));
        T.fb[i * 4 + (u >> 1)][l][(u & 1) * 2 + 1] = ri == 0 ? pkb(csin(pa, 32), csin(pb, 32)) : pkb(sg * ccos(pa, 32), sg * ccos(pb, 32));
      }
    for (int i = 0; i < 4; i++)
      for (int ks = 0; ks < 4; ks++) {
        const int n2 = 4 * g + i, m = 2 * t + (ks & 1);
        const double sg = ks >= 2 ? -1.0 : 1.0;
        const int pa = n2 * (ks >= 2 ? 31 - 2 * m : 2 * m), pb = n2 * (ks >= 2 ? 30 - 2 * m : 2 * m + 1);
        T.gb[i * 4 + ks][l][0] = pkb(ccos(pa, 32), -sg * csin(pa, 32));
        T.gb[i * 4 + ks][l][1] = pkb(csin(pa, 32), sg * ccos(pa, 32));
        T.gb[i * 4 + ks][l][2] = pkb(ccos(pb, 32), -sg * csin(pb, 32));
        T.gb[i * 4 + ks][l][3] = pkb(csin(pb, 32), sg * ccos(pb, 32));
      }
    for (int i = 0; i < 4; i++) {
      for (int e = 0; e < 2; e++) {
        const int p = (8 * t + 4 * e + i) * (g == 0 ? 8 : g);
        T.tw1[2 * i + e][l][0] = fbits(g == 0 ? 0.0 : ccos(p, 512), 23);
        T.tw1[2 * i + e][l][1] = fbits(g == 0 ? ccos(p, 512) : csin(p, 512), 23);
        T.tw1[2 * i + e][l][2] = fbits(g == 0 ? 0.0 : -csin(p, 512), 23);
        T.tw1[2 * i + e][l][3] = fbits(g == 0 ? -csin(p, 512) : ccos(p, 512), 23);
      }
      const int ka = t == 0 ? 8 : 2 * t, kb = 2 * t + 1;
      T.tw3[i][l][0] = fbits(ccos((4 * g + i) * ka, 512), 23);
      T.tw3[i][l][1] = fbits(csin((4 * g + i) * ka, 512), 23);
      T.tw3[i][l][2] = fbits(ccos((4 * g + i) * kb, 512), 23);
      T.tw3[i][l][3] = fbits(csin((4 * g + i) * kb, 512), 23);
      const int p8 = (t + 4 * (i & 1)) * (4 * (i >> 1) + (g >> 1));
      T.f8[l][i] = cfrag_c(p8, 8, g & 1);
      T.g8[l][i] = cfrag_c(-p8, 8, g & 1);
    }
    for (int w = 0; w < 8; w++)
      for (int i = 0; i < 16; i++) {
        const int kidx = t + 4 * (i & 1) + 8 * (i >> 3), nidx = 4 * ((i >> 1) & 3) + (g >> 1);
        T.f2[w][i >> 2][l][i & 3] = cfrag_c((8 * kidx + w) * nidx, 128, g & 1);
        T.g2[w][i >> 2][l][i & 3] = cfrag_c(-(8 * nidx + w) * kidx, 128, g & 1);
      }
    T.fa[l][0] = pkb(fa_elem(g, 2 * t), fa_elem(g, 2 * t + 1));
    T.fa[l][1] = pkb(fa_elem(g + 8, 2 * t), fa_elem(g + 8, 2 * t + 1));
    T.fa[l][2] = pkb(fa_elem(g, 2 * t + 8), fa_elem(g, 2 * t + 9));
    T.fa[l][3] = pkb(fa_elem(g + 8, 2 * t + 8), fa_elem(g + 8, 2 * t + 9));
    T.ga[l][0] = pkb(fa_elem(2 * t, g), fa_elem(2 * t + 1, g));
    T.ga[l][1] = pkb(fa_elem(2 * t, g + 8), fa_elem(2 * t + 1, g + 8));
    T.ga[l][2] = pkb(fa_elem(2 * t + 8, g), fa_elem(2 * t + 9, g));
    T.ga[l][3] = pkb(fa_elem(2 * t + 8, g + 8), fa_elem(2 * t + 9, g + 8));
  }
  return T;
}
__device__ const __align__(128) Tables g_tab = make_tables();

__device__ __forceinline__ void die() { asm volatile("st.global.u32 [%0], %1;" ::"l"(0ull), "r"(0) : "memory"); }
__device__ __forceinline__ uint32_t s2u(const void* p) { return (uint32_t)__cvta_generic_to_shared(p); }
__device__ __forceinline__ void mbar_init(uint32_t b, int c) { asm volatile("mbarrier.init.shared::cta.b64 [%0], %1;" ::"r"(b), "r"(c)); }
__device__ __forceinline__ void mbar_expect(uint32_t b, int bytes) {
  asm volatile("mbarrier.arrive.expect_tx.shared::cta.b64 _, [%0], %1;" ::"r"(b), "r"(bytes) : "memory");
}
__device__ __forceinline__ void mbar_arrive(uint32_t b) { asm volatile("mbarrier.arrive.shared::cta.b64 _, [%0];" ::"r"(b) : "memory"); }
__device__ __forceinline__ uint32_t mbar_try(uint32_t b, uint32_t parity) {
  uint32_t ok;
  asm volatile("{.reg .pred p; mbarrier.try_wait.parity.shared::cta.b64 p, [%1], %2; selp.u32 %0,1,0,p;}"
               : "=r"(ok) : "r"(b), "r"(parity) : "memory");
  return ok;
}
__device__ __forceinline__ uint32_t mbar_test(uint32_t b) {
  uint32_t ok;
  asm volatile("{.reg .pred p; mbarrier.test_wait.parity.shared::cta.b64 p, [%1], 0; selp.u32 %0,1,0,p;}" : "=r"(ok) : "r"(b) : "memory");
  return ok;
}
__device__ __forceinline__ void mbar_wait(uint32_t b, uint32_t parity = 0) {
  int it = 0;
#pragma unroll 1
  while (!mbar_try(b, parity))
    if (++it > SPIN_LIMIT) { die(); break; }
}
__device__ __forceinline__ void bar_sync(int id, int n) { asm volatile("bar.sync %0, %1;" ::"r"(id), "r"(n) : "memory"); }
__device__ __forceinline__ void bar_arrive(int id, int n) { asm volatile("bar.arrive %0, %1;" ::"r"(id), "r"(n) : "memory"); }
__device__ __forceinline__ void red_release(unsigned* p) { asm volatile("red.release.gpu.global.add.u32 [%0], 1;" ::"l"(p) : "memory"); }
__device__ __forceinline__ void red_relaxed(unsigned* p) { asm volatile("red.relaxed.gpu.global.add.u32 [%0], 1;" ::"l"(p) : "memory"); }
__device__ __forceinline__ unsigned ld_acquire(const unsigned* p) {
  unsigned v;
  asm volatile("ld.acquire.gpu.global.u32 %0, [%1];" : "=r"(v) : "l"(p) : "memory");
  return v;
}
__device__ __forceinline__ unsigned ld_relaxed(const unsigned* p) {
  unsigned v;
  asm volatile("ld.relaxed.gpu.global.u32 %0, [%1];" : "=r"(v) : "l"(p) : "memory");
  return v;
}
__device__ __forceinline__ void wait_counter(const unsigned* p, unsigned target) {
  int it = 0;
  while ((int)(ld_acquire(p) - target) < 0)
    if (++it > SPIN_LIMIT) { die(); break; }
}
__device__ __forceinline__ void sts4(uint32_t a, uint32_t x, uint32_t y, uint32_t z, uint32_t w) {
  asm volatile("st.shared.v4.u32 [%0], {%1,%2,%3,%4};" ::"r"(a), "r"(x), "r"(y), "r"(z), "r"(w) : "memory");
}
__device__ __forceinline__ uint4 lds4(uint32_t a) {
  uint4 v;
  asm volatile("ld.shared.v4.u32 {%0,%1,%2,%3}, [%4];" : "=r"(v.x), "=r"(v.y), "=r"(v.z), "=r"(v.w) : "r"(a) : "memory");
  return v;
}
__device__ __forceinline__ uint32_t pack2(float lo, float hi) {
  uint32_t r;
  asm("cvt.rn.bf16x2.f32 %0, %1, %2;" : "=r"(r) : "f"(hi), "f"(lo));
  return r;
}
__device__ __forceinline__ float bf_lo(uint32_t v) { return __uint_as_float(v << 16); }
__device__ __forceinline__ uint32_t hadd2_bf16(uint32_t a, uint32_t b) {
  uint32_t r;
  asm("add.rn.bf16x2 %0, %1, %2;" : "=r"(r) : "r"(a), "r"(b));
  return r;
}
__device__ __forceinline__ void mma16816(float (&d)[4], uint32_t a0, uint32_t a1, uint32_t a2, uint32_t a3, uint32_t b0, uint32_t b1) {
  asm("mma.sync.aligned.m16n8k16.row.col.f32.bf16.bf16.f32 {%0,%1,%2,%3}, {%4,%5,%6,%7}, {%8,%9}, {%0,%1,%2,%3};"
      : "+f"(d[0]), "+f"(d[1]), "+f"(d[2]), "+f"(d[3])
      : "r"(a0), "r"(a1), "r"(a2), "r"(a3), "r"(b0), "r"(b1));
}
template <int N>
__device__ __forceinline__ void cs_frac(int idx, float& c, float& s) {
  int i = ((idx + N / 2) & (N - 1)) - N / 2;
  float a = (float)i * (6.283185307179586f / N);
  c = __cosf(a);
  s = __sinf(a);
}
template <int N>
__device__ __forceinline__ uint32_t cfrag(int idx, int ri) {
  float c, s;
  cs_frac<N>(idx, c, s);
  return ri ? pack2(-s, c) : pack2(c, s);
}
__device__ __forceinline__ uint32_t word(const uint4& v, int e) { return e == 0 ? v.x : e == 1 ? v.y : e == 2 ? v.z : v.w; }
__device__ __forceinline__ void cdft16(const uint4 (&q)[4], const uint4 (&F)[4], uint4 (&o)[4]) {
  float acc[2][4][4];
#pragma unroll
  for (int p = 0; p < 2; p++)
#pragma unroll
    for (int v = 0; v < 4; v++) {
      acc[p][v][0] = acc[p][v][1] = acc[p][v][2] = acc[p][v][3] = 0.f;
#pragma unroll
      for (int ks = 0; ks < 2; ks++)
        mma16816(acc[p][v], word(q[2 * ks], 2 * p), word(q[2 * ks], 2 * p + 1), word(q[2 * ks + 1], 2 * p),
                 word(q[2 * ks + 1], 2 * p + 1), word(F[ks * 2 + (v >> 1)], (v & 1) * 2), word(F[ks * 2 + (v >> 1)], (v & 1) * 2 + 1));
    }
#pragma unroll
  for (int v = 0; v < 4; v++)
    o[v] = make_uint4(pack2(acc[0][v][0], acc[0][v][1]), pack2(acc[0][v][2], acc[0][v][3]),
                      pack2(acc[1][v][0], acc[1][v][1]), pack2(acc[1][v][2], acc[1][v][3]));
}
__device__ __forceinline__ void st_tag(uint4* p, const uint4& v, uint32_t tag) {
  asm volatile("{.reg .b128 r; .reg .b64 a, b; mov.b64 a, {%1,%2}; mov.b64 b, {%3,%4}; mov.b128 r, {a,b}; st.relaxed.gpu.global.b128 [%0], r;}"
               ::"l"(p), "r"((v.x & ~1u) | tag), "r"(v.y), "r"(v.z), "r"(v.w) : "memory");
}
__device__ __forceinline__ void st_tag_p(int en, uint4* p, const uint4& v, uint32_t tag) {
  asm volatile("{.reg .b128 r; .reg .b64 a, b; .reg .pred q; setp.ne.b32 q, %5, 0; mov.b64 a, {%1,%2}; mov.b64 b, {%3,%4}; mov.b128 r, {a,b};\n"
               "@q st.relaxed.gpu.global.b128 [%0], r;}"
               ::"l"(p), "r"((v.x & ~1u) | tag), "r"(v.y), "r"(v.z), "r"(v.w), "r"(en) : "memory");
}
__device__ __forceinline__ void sts4_p(int en, uint32_t a, uint32_t x, uint32_t y, uint32_t z, uint32_t w) {
  asm volatile("{.reg .pred q; setp.ne.b32 q, %5, 0; @q st.shared.v4.u32 [%0], {%1,%2,%3,%4};}"
               ::"r"(a), "r"(x), "r"(y), "r"(z), "r"(w), "r"(en) : "memory");
}
__device__ __forceinline__ uint4 ld_b128(const uint4* p) {
  uint4 v;
  asm volatile("{.reg .b128 r; .reg .b64 a, b; ld.relaxed.gpu.global.b128 r, [%4]; mov.b128 {a,b}, r; mov.b64 {%0,%1}, a; mov.b64 {%2,%3}, b;}"
               : "=r"(v.x), "=r"(v.y), "=r"(v.z), "=r"(v.w) : "l"(p) : "memory");
  return v;
}
template <int STRIDE>
__device__ __forceinline__ void ld_tag4_issue(uint4 (&q)[4], const uint4* p) {
#pragma unroll
  for (int i = 0; i < 4; i++) q[i] = ld_b128(p + i * STRIDE);
}
template <int STRIDE>
__device__ __forceinline__ void ld_tag4_finish(uint4 (&q)[4], const uint4* p, uint32_t tag) {
  int it = 0;
#pragma unroll 1
  while (__any_sync(0xffffffffu, ((q[0].x ^ tag) | (q[1].x ^ tag) | (q[2].x ^ tag) | (q[3].x ^ tag)) & 1u)) {
    ld_tag4_issue<STRIDE>(q, p);
    if (++it > SPIN_LIMIT) { die(); break; }
  }
#pragma unroll
  for (int i = 0; i < 4; i++) asm volatile("and.b32 %0, %0, 0xfffffffe;" : "+r"(q[i].x));
}
__device__ __forceinline__ void row_stats(const uint32_t (&a)[8], const uint32_t (&b)[8], int lane, float (&sum)[2], float (&sq)[2]) {
  float da[4] = {0.f, 0.f, 0.f, 0.f}, db[4] = {0.f, 0.f, 0.f, 0.f}, ds[4] = {0.f, 0.f, 0.f, 0.f};
#pragma unroll
  for (int q = 0; q < 4; q++) {
    mma16816(ds, a[2 * q], b[2 * q], a[2 * q + 1], b[2 * q + 1], 0x3f803f80u, 0x3f803f80u);
    mma16816(da, a[2 * q], b[2 * q], a[2 * q + 1], b[2 * q + 1], a[2 * q], a[2 * q + 1]);
    mma16816(db, a[2 * q], b[2 * q], a[2 * q + 1], b[2 * q + 1], b[2 * q], b[2 * q + 1]);
  }
  const int src = (lane & 28) | (lane >> 3);
  const float qa = __shfl_sync(0xffffffffu, (lane & 4) ? da[1] : da[0], src);
  const float qb = __shfl_sync(0xffffffffu, (lane & 4) ? db[3] : db[2], src);
  float v = (lane & 2) ? ((lane & 1) ? ds[2] : ds[0]) : ((lane & 1) ? qb : qa);
  v += __shfl_xor_sync(0xffffffffu, v, 4);
  v += __shfl_xor_sync(0xffffffffu, v, 8);
  v += __shfl_xor_sync(0xffffffffu, v, 16);
  sq[0] = __shfl_sync(0xffffffffu, v, 0);
  sq[1] = __shfl_sync(0xffffffffu, v, 1);
  sum[0] = __shfl_sync(0xffffffffu, v, 2);
  sum[1] = __shfl_sync(0xffffffffu, v, 3);
}
__device__ __forceinline__ uint64_t desc64(uint32_t lo, uint32_t hi) {
  uint64_t d;
  asm("mov.b64 %0, {%1, %2};" : "=l"(d) : "r"(lo), "r"(hi));
  return d;
}
constexpr uint32_t desc_hi(uint32_t sbo, uint32_t swz) { return (sbo >> 4) | (swz << 30); }
__device__ __forceinline__ uint32_t desc_lo(uint32_t addr, uint32_t lbo) { return ((addr & 0x3FFFF) >> 4) | ((lbo >> 4) << 16); }
__device__ __forceinline__ void cp_async16(uint32_t dst, const void* src) {
  asm volatile("cp.async.cg.shared.global [%0], [%1], 16;" ::"r"(dst), "l"(src) : "memory");
}
__device__ __forceinline__ uint2 lds2(uint32_t a) {
  uint2 v;
  asm volatile("ld.shared.v2.u32 {%0,%1}, [%2];" : "=r"(v.x), "=r"(v.y) : "r"(a) : "memory");
  return v;
}
__device__ __forceinline__ uint32_t lds_u16(uint32_t a) {
  uint16_t v;
  asm volatile("ld.shared.u16 %0, [%1];" : "=h"(v) : "r"(a) : "memory");
  return v;
}
__device__ __forceinline__ void wg_fence() { asm volatile("wgmma.fence.sync.aligned;" ::: "memory"); }
__device__ __forceinline__ void wg_commit() { asm volatile("wgmma.commit_group.sync.aligned;" ::: "memory"); }
template <int N>
__device__ __forceinline__ void wg_wait() { asm volatile("wgmma.wait_group.sync.aligned %0;" ::"n"(N) : "memory"); }
__device__ __forceinline__ void bulk_load(uint32_t dst, const void* src, int bytes, uint32_t bar) {
  asm volatile("cp.async.bulk.shared::cluster.global.mbarrier::complete_tx::bytes [%0], [%1], %2, [%3];"
               ::"r"(dst), "l"(src), "r"(bytes), "r"(bar) : "memory");
}
__device__ __forceinline__ void bulk_load_mc(uint32_t dst, const void* src, int bytes, uint32_t bar) {
  asm volatile("cp.async.bulk.shared::cluster.global.mbarrier::complete_tx::bytes.multicast::cluster [%0], [%1], %2, [%3], %4;"
               ::"r"(dst), "l"(src), "r"(bytes), "r"(bar), "h"((uint16_t)3) : "memory");
}
__device__ __forceinline__ void tma3(uint32_t dst, const CUtensorMap* tm, uint32_t bar, int c0, int c1, int c2) {
  asm volatile("cp.async.bulk.tensor.3d.shared::cluster.global.mbarrier::complete_tx::bytes [%0], [%1, {%3,%4,%5}], [%2];"
               ::"r"(dst), "l"(tm), "r"(bar), "r"(c0), "r"(c1), "r"(c2) : "memory");
}
__device__ __forceinline__ void tma3_mc(uint32_t dst, const CUtensorMap* tm, uint32_t bar, int c1, int c2) {
  asm volatile("cp.async.bulk.tensor.3d.shared::cluster.global.mbarrier::complete_tx::bytes.multicast::cluster [%0], [%1, {%3,%4,%5}], [%2], %6;"
               ::"r"(dst), "l"(tm), "r"(bar), "r"(0), "r"(c1), "r"(c2), "h"((uint16_t)3) : "memory");
}
__device__ __forceinline__ void mbar_arrive_remote(uint32_t rb) {
  asm volatile("mbarrier.arrive.shared::cluster.b64 _, [%0];" ::"r"(rb) : "memory");
}
__device__ __forceinline__ uint4 ldg_ca4_p(int en, const void* p) {
  uint4 v;
  asm volatile("{.reg .pred q; setp.ne.b32 q, %5, 0; @q ld.global.ca.v4.u32 {%0,%1,%2,%3}, [%4];}"
               : "=r"(v.x), "=r"(v.y), "=r"(v.z), "=r"(v.w) : "l"(p), "r"(en) : "memory");
  return v;
}
__device__ __forceinline__ uint32_t clock32() {
  uint32_t v;
  asm volatile("mov.u32 %0, %%clock;" : "=r"(v) :: "memory");
  return v;
}
__device__ __forceinline__ float swiglu(float g, float u, float r) {
  float hg = (0.5f * r) * g, th;
  asm("tanh.approx.f32 %0, %1;" : "=f"(th) : "f"(hg));
  return fmaf(hg, th, hg) * (r * u);
}
__device__ __forceinline__ uint32_t hsub2_bf16(uint32_t a, uint32_t b) {
  uint32_t r;
  asm("sub.rn.bf16x2 %0, %1, %2;" : "=r"(r) : "r"(a), "r"(b));
  return r;
}
__device__ __forceinline__ void l2_prefetch(const void* p, int bytes) {
  asm volatile("cp.async.bulk.prefetch.L2.global [%0], %1;" ::"l"(p), "r"(bytes) : "memory");
}

__device__ __forceinline__ void wgmma_n256(float (&d)[128], uint64_t da, uint64_t db, int sd = 1) {
  asm volatile("{.reg .pred p; setp.ne.b32 p, %130, 0;\n"
      "wgmma.mma_async.sync.aligned.m64n256k16.f32.bf16.bf16 {"
      "%0,%1,%2,%3,%4,%5,%6,%7,%8,%9,%10,%11,%12,%13,%14,%15,"
      "%16,%17,%18,%19,%20,%21,%22,%23,%24,%25,%26,%27,%28,%29,%30,%31,"
      "%32,%33,%34,%35,%36,%37,%38,%39,%40,%41,%42,%43,%44,%45,%46,%47,"
      "%48,%49,%50,%51,%52,%53,%54,%55,%56,%57,%58,%59,%60,%61,%62,%63,"
      "%64,%65,%66,%67,%68,%69,%70,%71,%72,%73,%74,%75,%76,%77,%78,%79,"
      "%80,%81,%82,%83,%84,%85,%86,%87,%88,%89,%90,%91,%92,%93,%94,%95,"
      "%96,%97,%98,%99,%100,%101,%102,%103,%104,%105,%106,%107,%108,%109,%110,%111,"
      "%112,%113,%114,%115,%116,%117,%118,%119,%120,%121,%122,%123,%124,%125,%126,%127"
      "}, %128, %129, p, 1, 1, 0, 1;}\n"
      : "+f"(d[0]),"+f"(d[1]),"+f"(d[2]),"+f"(d[3]),"+f"(d[4]),"+f"(d[5]),"+f"(d[6]),"+f"(d[7]),
        "+f"(d[8]),"+f"(d[9]),"+f"(d[10]),"+f"(d[11]),"+f"(d[12]),"+f"(d[13]),"+f"(d[14]),"+f"(d[15]),
        "+f"(d[16]),"+f"(d[17]),"+f"(d[18]),"+f"(d[19]),"+f"(d[20]),"+f"(d[21]),"+f"(d[22]),"+f"(d[23]),
        "+f"(d[24]),"+f"(d[25]),"+f"(d[26]),"+f"(d[27]),"+f"(d[28]),"+f"(d[29]),"+f"(d[30]),"+f"(d[31]),
        "+f"(d[32]),"+f"(d[33]),"+f"(d[34]),"+f"(d[35]),"+f"(d[36]),"+f"(d[37]),"+f"(d[38]),"+f"(d[39]),
        "+f"(d[40]),"+f"(d[41]),"+f"(d[42]),"+f"(d[43]),"+f"(d[44]),"+f"(d[45]),"+f"(d[46]),"+f"(d[47]),
        "+f"(d[48]),"+f"(d[49]),"+f"(d[50]),"+f"(d[51]),"+f"(d[52]),"+f"(d[53]),"+f"(d[54]),"+f"(d[55]),
        "+f"(d[56]),"+f"(d[57]),"+f"(d[58]),"+f"(d[59]),"+f"(d[60]),"+f"(d[61]),"+f"(d[62]),"+f"(d[63]),
        "+f"(d[64]),"+f"(d[65]),"+f"(d[66]),"+f"(d[67]),"+f"(d[68]),"+f"(d[69]),"+f"(d[70]),"+f"(d[71]),
        "+f"(d[72]),"+f"(d[73]),"+f"(d[74]),"+f"(d[75]),"+f"(d[76]),"+f"(d[77]),"+f"(d[78]),"+f"(d[79]),
        "+f"(d[80]),"+f"(d[81]),"+f"(d[82]),"+f"(d[83]),"+f"(d[84]),"+f"(d[85]),"+f"(d[86]),"+f"(d[87]),
        "+f"(d[88]),"+f"(d[89]),"+f"(d[90]),"+f"(d[91]),"+f"(d[92]),"+f"(d[93]),"+f"(d[94]),"+f"(d[95]),
        "+f"(d[96]),"+f"(d[97]),"+f"(d[98]),"+f"(d[99]),"+f"(d[100]),"+f"(d[101]),"+f"(d[102]),"+f"(d[103]),
        "+f"(d[104]),"+f"(d[105]),"+f"(d[106]),"+f"(d[107]),"+f"(d[108]),"+f"(d[109]),"+f"(d[110]),"+f"(d[111]),
        "+f"(d[112]),"+f"(d[113]),"+f"(d[114]),"+f"(d[115]),"+f"(d[116]),"+f"(d[117]),"+f"(d[118]),"+f"(d[119]),
        "+f"(d[120]),"+f"(d[121]),"+f"(d[122]),"+f"(d[123]),"+f"(d[124]),"+f"(d[125]),"+f"(d[126]),"+f"(d[127])
      : "l"(da), "l"(db), "r"(sd));
}
__device__ __forceinline__ void wgmma_n192(float (&d)[96], uint64_t da, uint64_t db) {
  asm volatile("wgmma.mma_async.sync.aligned.m64n192k16.f32.bf16.bf16 {"
      "%0,%1,%2,%3,%4,%5,%6,%7,%8,%9,%10,%11,%12,%13,%14,%15,"
      "%16,%17,%18,%19,%20,%21,%22,%23,%24,%25,%26,%27,%28,%29,%30,%31,"
      "%32,%33,%34,%35,%36,%37,%38,%39,%40,%41,%42,%43,%44,%45,%46,%47,"
      "%48,%49,%50,%51,%52,%53,%54,%55,%56,%57,%58,%59,%60,%61,%62,%63,"
      "%64,%65,%66,%67,%68,%69,%70,%71,%72,%73,%74,%75,%76,%77,%78,%79,"
      "%80,%81,%82,%83,%84,%85,%86,%87,%88,%89,%90,%91,%92,%93,%94,%95"
      "}, %96, %97, 1, 1, 1, 0, 1;\n"
      : "+f"(d[0]),"+f"(d[1]),"+f"(d[2]),"+f"(d[3]),"+f"(d[4]),"+f"(d[5]),"+f"(d[6]),"+f"(d[7]),
        "+f"(d[8]),"+f"(d[9]),"+f"(d[10]),"+f"(d[11]),"+f"(d[12]),"+f"(d[13]),"+f"(d[14]),"+f"(d[15]),
        "+f"(d[16]),"+f"(d[17]),"+f"(d[18]),"+f"(d[19]),"+f"(d[20]),"+f"(d[21]),"+f"(d[22]),"+f"(d[23]),
        "+f"(d[24]),"+f"(d[25]),"+f"(d[26]),"+f"(d[27]),"+f"(d[28]),"+f"(d[29]),"+f"(d[30]),"+f"(d[31]),
        "+f"(d[32]),"+f"(d[33]),"+f"(d[34]),"+f"(d[35]),"+f"(d[36]),"+f"(d[37]),"+f"(d[38]),"+f"(d[39]),
        "+f"(d[40]),"+f"(d[41]),"+f"(d[42]),"+f"(d[43]),"+f"(d[44]),"+f"(d[45]),"+f"(d[46]),"+f"(d[47]),
        "+f"(d[48]),"+f"(d[49]),"+f"(d[50]),"+f"(d[51]),"+f"(d[52]),"+f"(d[53]),"+f"(d[54]),"+f"(d[55]),
        "+f"(d[56]),"+f"(d[57]),"+f"(d[58]),"+f"(d[59]),"+f"(d[60]),"+f"(d[61]),"+f"(d[62]),"+f"(d[63]),
        "+f"(d[64]),"+f"(d[65]),"+f"(d[66]),"+f"(d[67]),"+f"(d[68]),"+f"(d[69]),"+f"(d[70]),"+f"(d[71]),
        "+f"(d[72]),"+f"(d[73]),"+f"(d[74]),"+f"(d[75]),"+f"(d[76]),"+f"(d[77]),"+f"(d[78]),"+f"(d[79]),
        "+f"(d[80]),"+f"(d[81]),"+f"(d[82]),"+f"(d[83]),"+f"(d[84]),"+f"(d[85]),"+f"(d[86]),"+f"(d[87]),
        "+f"(d[88]),"+f"(d[89]),"+f"(d[90]),"+f"(d[91]),"+f"(d[92]),"+f"(d[93]),"+f"(d[94]),"+f"(d[95])
      : "l"(da), "l"(db));
}
template <int SD>
__device__ __forceinline__ void wgmma_rs_n128(float (&d)[64], uint32_t a0, uint32_t a1, uint32_t a2, uint32_t a3, uint64_t db) {
  asm volatile("wgmma.mma_async.sync.aligned.m64n128k16.f32.bf16.bf16 {"
      "%0,%1,%2,%3,%4,%5,%6,%7,%8,%9,%10,%11,%12,%13,%14,%15,"
      "%16,%17,%18,%19,%20,%21,%22,%23,%24,%25,%26,%27,%28,%29,%30,%31,"
      "%32,%33,%34,%35,%36,%37,%38,%39,%40,%41,%42,%43,%44,%45,%46,%47,"
      "%48,%49,%50,%51,%52,%53,%54,%55,%56,%57,%58,%59,%60,%61,%62,%63"
      "}, {%64,%65,%66,%67}, %68, %69, 1, 1, 1;\n"
      : "+f"(d[0]),"+f"(d[1]),"+f"(d[2]),"+f"(d[3]),"+f"(d[4]),"+f"(d[5]),"+f"(d[6]),"+f"(d[7]),
        "+f"(d[8]),"+f"(d[9]),"+f"(d[10]),"+f"(d[11]),"+f"(d[12]),"+f"(d[13]),"+f"(d[14]),"+f"(d[15]),
        "+f"(d[16]),"+f"(d[17]),"+f"(d[18]),"+f"(d[19]),"+f"(d[20]),"+f"(d[21]),"+f"(d[22]),"+f"(d[23]),
        "+f"(d[24]),"+f"(d[25]),"+f"(d[26]),"+f"(d[27]),"+f"(d[28]),"+f"(d[29]),"+f"(d[30]),"+f"(d[31]),
        "+f"(d[32]),"+f"(d[33]),"+f"(d[34]),"+f"(d[35]),"+f"(d[36]),"+f"(d[37]),"+f"(d[38]),"+f"(d[39]),
        "+f"(d[40]),"+f"(d[41]),"+f"(d[42]),"+f"(d[43]),"+f"(d[44]),"+f"(d[45]),"+f"(d[46]),"+f"(d[47]),
        "+f"(d[48]),"+f"(d[49]),"+f"(d[50]),"+f"(d[51]),"+f"(d[52]),"+f"(d[53]),"+f"(d[54]),"+f"(d[55]),
        "+f"(d[56]),"+f"(d[57]),"+f"(d[58]),"+f"(d[59]),"+f"(d[60]),"+f"(d[61]),"+f"(d[62]),"+f"(d[63])
      : "r"(a0), "r"(a1), "r"(a2), "r"(a3), "l"(db), "n"(SD));
}

constexpr int C_LN = 0, C_PX = 16, C_PY = 32;
constexpr int NB_CONS = 1, NB_LN = 2, NB_LAG = 4, NB_INIT = 6, NB_RDY = 7;
#define LAGX 3
#define LAGY 3
#define LAG2 4
#define NLL 2
#define POLL_DELAY3 1000
#define POLL_DELAY 1100
#define FILT_DELAY 1000
#define THR_B 0
#define THR_P 0
#define SPEC -1
#define WARM 4
#define HWARM 0
#define POLL_DELAY2 POLL_DELAY
#define POLL_DELAY4 1200
#define DRY_T1 4200
#define RING_SIG 1
#define PF2_SIG 1
constexpr int SM_E = 0, SM_X = 16384, SM_E2 = 32768, SM_W = 49152, SM_FC = 69632, SM_T = 73728 - T1_BYTES;
constexpr unsigned long long KORDER = 0xBA9432DC876510ull;
constexpr unsigned long long BSLOT = 0x76532107653210ull, PSLOT = 0xDCBA984DCBA984ull;
constexpr uint32_t HI128 = desc_hi(1024, 1), HI64 = desc_hi(512, 2);

struct Bars {
  uint64_t full1[32], empty1[32], full2[16], fullA[8], empty2[8], fullP[16], emptyP[8], hbar, tbar, hint[3], sig[2], sbar;
  uint32_t epoch;
};

template <int NK>
__device__ __forceinline__ void store_p(int en, const float (&acc)[NK * 16], float r0, float r1, uint4* pbase, int ks0, uint32_t tag) {
#pragma unroll
  for (int j = 0; j < NK; j++) {
    uint32_t w[4];
#pragma unroll
    for (int i = 0; i < 4; i++) {
      const int a = 8 * j + 2 * i, b = a + NK * 8;
      w[i] = pack2(swiglu(acc[a], acc[b], (i & 1) ? r1 : r0), swiglu(acc[a + 1], acc[b + 1], (i & 1) ? r1 : r0));
    }
    st_tag_p(en, pbase + ((ks0 + j) >> 2) * 1024 + ((ks0 + j) & 3) * 32, make_uint4(w[0], w[1], w[2], w[3]), tag);
  }
}
__device__ __forceinline__ void spin_cycles(uint32_t n) {
  const uint32_t t0 = clock32();
  while (clock32() - t0 < n) {}
}

__device__ __forceinline__ void spin_until(uint32_t t) {
  float d[4] = {0.f, 0.f, 0.f, 0.f};
  while ((int)(clock32() - t) < 0) {
    if (HWARM) asm volatile("mma.sync.aligned.m16n8k16.row.col.f32.bf16.bf16.f32 {%0,%1,%2,%3}, {%4,%4,%4,%4}, {%4,%4}, {%0,%1,%2,%3};"
                            : "+f"(d[0]), "+f"(d[1]), "+f"(d[2]), "+f"(d[3]) : "r"(t));
  }
}

__global__ void __cluster_dims__(2, 1, 1) __launch_bounds__(NTHREADS, 1)
fused_kernel(const __nv_bfloat16* __restrict__ x, const Tables* __restrict__ tab, Scratch* __restrict__ scr,
             __nv_bfloat16* __restrict__ out, const char* __restrict__ wg_raw, const char* __restrict__ wu_raw,
             const char* __restrict__ wd_raw,
             const __grid_constant__ CUtensorMap tmWR, const __grid_constant__ CUtensorMap tmWI,
             const __grid_constant__ CUtensorMap tmGX, const __grid_constant__ CUtensorMap tmUX,
             const __grid_constant__ CUtensorMap tmGY, const __grid_constant__ CUtensorMap tmUY,
             const __grid_constant__ CUtensorMap tmD) {
  extern __shared__ __align__(1024) char smem_raw[];
  const uint32_t sbase = s2u(smem_raw);
  const uint32_t sbar = sbase + 14 * SLOT, sstat = sbar + 1280;
  const int tid = threadIdx.x, lane = tid & 31;
  const int c = blockIdx.x, rk = c & 1, f = (c >> 1) & 7, rb = 2 * (c >> 4) + rk;
  const int rb2 = 2 * (c >> 4) + (f >> 2), kh = (f >> 1) & 1, nq = 2 * (f & 1) + rk;
#define BAR(field, i) (sbar + (uint32_t)offsetof(Bars, field) + 8u * (i))
#define TOFF(field) (sbase + SM_T + (uint32_t)offsetof(Tables, field) + lane * 16)

  if (tid >= 256 && tid < 352) {
    const int warp = __shfl_sync(0xffffffffu, tid >> 5, 0);
    const unsigned epoch = ld_relaxed(&scr->cnt[(C_LN + rb) * 32]) >> 3;
    if (lane == 0) {
      if (warp == 8) {
        if (sbase & 1023) die();
#pragma unroll
        for (int i = 0; i < 16; i++) mbar_init(BAR(emptyP, i), i < 7 ? 16 : i < 8 ? 8 : i < 13 ? 1 : i < 15 ? 8 : 32);
        mbar_expect(BAR(tbar, 0), T2_BYTES + 2 * 10240);
        mbar_expect(BAR(hbar, 0), 16384);
#pragma unroll
        for (int i = 0; i < 32; i++) mbar_init(BAR(full2, i), i < 24 ? 1 : 8);
#pragma unroll
        for (int i = 0; i < 24; i++) mbar_expect(BAR(full2, i), 16384);
      } else if (warp == 9) {
#pragma unroll
        for (int i = 0; i < 32; i++) mbar_init(BAR(full1, i), 1);
#pragma unroll
        for (int i = 0; i < 32; i++) mbar_expect(BAR(full1, i), i < 16 ? 16384 : 12288);
      } else {
#pragma unroll
        for (int i = 0; i < 32; i++) mbar_init(BAR(empty1, i), 16);
#pragma unroll
        for (int i = 0; i < 14; i++) mbar_init(BAR(fullP, i), 1);
#pragma unroll
        for (int i = 0; i < 14; i++) mbar_expect(BAR(fullP, i), 16384);
      }
      asm volatile("fence.mbarrier_init.release.cluster;" ::: "memory");
    }
    if (tid == 256) {
      const int w0 = ((c >> 3) * 257 + 32 * (c & 7) + 1) & ~7;
      if (FILT_DELAY) {
        asm volatile("prefetch.tensormap [%0];" ::"l"(&tmWR) : "memory");
        asm volatile("prefetch.tensormap [%0];" ::"l"(&tmWI) : "memory");
        spin_cycles(FILT_DELAY);
      }
      tma3(sbase + SM_W, &tmWR, BAR(tbar, 0), w0, 0, 0);
      tma3(sbase + SM_W + 10240, &tmWI, BAR(tbar, 0), w0, 0, 0);
      bulk_load(sbase + SM_T + T1_BYTES, reinterpret_cast<const char*>(tab) + T1_BYTES, T2_BYTES, BAR(tbar, 0));
    }
    if (tid == 288) {
      asm volatile("prefetch.tensormap [%0];" ::"l"(rk ? &tmUX : &tmGX) : "memory");
      asm volatile("prefetch.tensormap [%0];" ::"l"(rk ? &tmUY : &tmGY) : "memory");
      asm volatile("prefetch.tensormap [%0];" ::"l"(&tmD) : "memory");
    }
    __syncwarp();
    asm volatile("barrier.cluster.arrive.relaxed.aligned;" ::: "memory");
    bar_arrive(NB_RDY, 384);
    asm volatile("barrier.cluster.wait.aligned;" ::: "memory");
    bar_sync(NB_INIT, 384);
    if (warp == 8) {
      if (lane == 0) {
        const int ax = (7 * f + 3 * (f & 1)) >> 1;
        const int ay = 7 * f + ((f & 1) ? 0 : 4);
        const CUtensorMap* tx = rk ? &tmUX : &tmGX;
        const CUtensorMap* ty = rk ? &tmUY : &tmGY;
        if (RING_SIG >= 0) mbar_wait(BAR(sig, RING_SIG));
        uint32_t s = 2;
#pragma unroll 1
        for (int n = 0; n < 16; n++) {
          if (n >= 6) mbar_wait(BAR(empty1, n - 6));
          tma3_mc(sbase + (8 + s) * SLOT + rk * 8192, tx, BAR(full1, n), n * 32, ax);
          if (++s == 6) s = 0;
        }
#pragma unroll 1
        for (int k = 0; k < 16; k++) {
          mbar_wait(BAR(empty1, k < 8 ? 10 + ((12 * k + 11) >> 4) : 8 + k));
          tma3_mc(sbase + 8 * SLOT + (k & 7) * 12288 + rk * 6144, ty, BAR(full1, 16 + k), k * 32, ay);
        }
      }
    } else if (warp == 9) {
      if (lane == 0) {
        l2_prefetch(wg_raw + (size_t)c * 5376, 5376);
        l2_prefetch(wu_raw + (size_t)c * 5376, 5376);
        mbar_wait(BAR(sig, PF2_SIG));
        l2_prefetch(wg_raw + 688128 + (size_t)c * 8960, 8960);
        l2_prefetch(wu_raw + 688128 + (size_t)c * 8960, 8960);
        mbar_wait(BAR(fullA, 7));
        l2_prefetch(wd_raw + (size_t)c * 14336, 14336);
#pragma unroll 1
        for (int i = 0; i < 14; i++) {
          const int kblk = 14 * kh + (int)((KORDER >> (4 * i)) & 15);
          const int j = i < 7 ? i : i - 7, sl = j + (j >= 4);
          mbar_wait(i < 7 ? BAR(empty1, 17 + 2 * sl) : BAR(empty2, j));
          if (THR_B && i >= THR_B) mbar_wait(BAR(full2, i - THR_B));
          tma3(sbase + sl * SLOT, &tmD, BAR(full2, i), 0, 64 * kblk, 2 * nq);
        }
        wait_counter(&scr->cnt[(C_LN + rb2) * 32], (epoch + 1) * 8);
        asm volatile("fence.proxy.async.global;" ::: "memory");
        mbar_wait(BAR(emptyP, 7));
        bulk_load(sbase + 4 * SLOT, &scr->LN[(rb2 * 8 + 2 * nq) * 1024 + kh * 512], 8192, BAR(hbar, 0));
        bulk_load(sbase + 4 * SLOT + 8192, &scr->LN[(rb2 * 8 + 2 * nq + 1) * 1024 + kh * 512], 8192, BAR(hbar, 0));
      }
    } else {
      bar_sync(NB_LN, 288);
      if (lane == 0) {
        PROFP(0);
        red_release(&scr->cnt[(C_LN + rb) * 32]);
        PROFP(1);
        wait_counter(&scr->cnt[(C_LN + rb) * 32], (epoch + 1) * 8);
        asm volatile("fence.proxy.async.global;" ::: "memory");
        PROFP(2);
#pragma unroll 1
        for (int kb = NLL; kb < 8; kb++) bulk_load(sbase + kb * SLOT, &scr->LN[(rb * 8 + kb) * 1024], 16384, BAR(fullA, kb));
#pragma unroll 1
        for (int s = 0; s < 14; s++) {
          const int kblk = 14 * kh + (int)((KORDER >> (4 * s)) & 15);
          if (s == 0 || (SPEC < 0 && (s == 8 || s == 11))) {
            if (s != 11) PROFP(3 + (s >> 2));
            mbar_wait(BAR(hint, s == 0 ? 0 : s == 8 ? 1 : 2), 0);
            if (s != 11) PROFP(4 + (s >> 2));
          }
          const int j = s < 7 ? s : s - 7;
          mbar_wait(s < 7 ? BAR(empty1, 24 + s + (s == 0) + (s >= 4)) : BAR(emptyP, j));
          if (THR_P && s >= THR_P) mbar_wait(BAR(fullP, s - THR_P));
          if (SPEC >= 0 && s == 8) mbar_wait(BAR(emptyP, SPEC & 7));
          bulk_load_mc(sbase + (j ? 7 + j : 4) * SLOT + rk * 8192, &scr->P[(rb2 * 28 + kblk) * 1024 + rk * 512], 8192, BAR(fullP, s));
        }
      }
    }
  } else {
    const int wfull = __shfl_sync(0xffffffffu, tid >> 5, 0), warp = wfull & 7;
    const int en = wfull < 8;
    const uint32_t t0 = clock32();
    uint32_t tag = 0;
    if (!en) tag = ld_relaxed(&scr->cnt[(C_LN + rb) * 32]) >> 3;
    const int g = lane >> 2, t = lane & 3;
    PROF(0);
    PROFG(14);
#pragma unroll
    for (int i = 0; i < 4; i++) {
      const int r = i >> 1, ch = (i & 1) * 32 + lane;
      if (en) cp_async16(sbase + SM_X + (2 * warp + r) * 1024 + ((ch ^ ((ch >> 2) & 6)) * 16),
                 x + (size_t)(c + 128 * (2 * warp + r)) * 512 + ch * 8);
    }
    asm volatile("cp.async.commit_group;" ::: "memory");
    asm volatile("barrier.cluster.arrive.relaxed.aligned;" ::: "memory");
    uint4 tw[8], fb[16];
    const uint4 fa = ldg_ca4_p(en, &tab->fa[lane][0]);
#pragma unroll
    for (int i = 0; i < 8; i++) tw[i] = ldg_ca4_p(en, &tab->tw1[i][lane][0]);
#pragma unroll
    for (int i = 0; i < 16; i++) fb[i] = ldg_ca4_p(en, &tab->fb[i][lane][0]);
    uint32_t rbar;
    asm volatile("mapa.shared::cluster.u32 %0, %1, %2;" : "=r"(rbar) : "r"(sbar), "r"(rk ^ 1));
#define RBAR(field, i) (rbar + (uint32_t)offsetof(Bars, field) + 8u * (i))
    if (en) {
      const int ln = (tid >> 1) & 31, lg = ln >> 2, lt = ln & 3, i = 4 * (tid >> 6) + 2 * (tid & 1);
      const int kidx = lt + 8 * (i >> 3), nidx = 4 * ((i >> 1) & 3) + (lg >> 1);
      const uint32_t a0 = cfrag<2048>((c + 128 * kidx) * nidx, lg & 1), a1 = cfrag<2048>((c + 128 * (kidx + 4)) * nidx, lg & 1);
      const uint32_t b0 = cfrag<2048>(-(c + 128 * nidx) * kidx, lg & 1), b1 = cfrag<2048>(-(c + 128 * nidx) * (kidx + 4), lg & 1);
      asm volatile("st.shared.v2.u32 [%0], {%1,%2};" ::"r"(sbase + SM_FC + tid * 8), "r"(a0), "r"(a1) : "memory");
      asm volatile("st.shared.v2.u32 [%0], {%1,%2};" ::"r"(sbase + SM_FC + 2048 + tid * 8), "r"(b0), "r"(b1) : "memory");
    }
    asm volatile("cp.async.wait_group 0;" ::: "memory");
    __syncwarp();
    bar_arrive(NB_INIT, 384);
    PROF(13);
    uint4 q[4], o[4];
    {
      uint32_t v[2][8];
#pragma unroll
      for (int r = 0; r < 2; r++)
#pragma unroll
        for (int q = 0; q < 4; q++) {
          const uint2 u = lds2(sbase + SM_X + (2 * warp + r) * 1024 + (t + 4 * (q >> 1)) * 128 + (((4 * (q & 1) + (g >> 1)) ^ (2 * t)) * 16) + (g & 1) * 8);
          v[r][2 * q] = u.x; v[r][2 * q + 1] = u.y;
        }
      float sum[2], sq[2], rstd[2];
      row_stats(v[0], v[1], lane, sum, sq);
#pragma unroll
      for (int r = 0; r < 2; r++) {
        const float m = sum[r] * (1.f / 512.f);
        rstd[r] = rsqrtf(fmaxf(fmaf(-m, m, sq[r] * (1.f / 512.f)), 0.f) + 1e-5f);
      }
      uint32_t alo[4][4], ahi[4][4];
#pragma unroll
      for (int r = 0; r < 2; r++)
#pragma unroll
        for (int i = 0; i < 4; i++) {
          const uint32_t sel = (i & 1) ? 0x7632u : 0x5410u;
          const uint32_t b0 = __byte_perm(v[r][i >> 1], v[r][2 + (i >> 1)], sel);
          const uint32_t b1 = __byte_perm(v[r][4 + (i >> 1)], v[r][6 + (i >> 1)], sel);
          float d[4] = {0.f, 0.f, 0.f, 0.f};
          mma16816(d, fa.x, fa.y, fa.z, fa.w, b0, b1);
          const uint4 &ka = tw[2 * i], &kb = tw[2 * i + 1];
          const uint32_t re = pack2(d[0] * __uint_as_float(ka.x) + d[2] * __uint_as_float(ka.y), d[1] * __uint_as_float(kb.x) + d[3] * __uint_as_float(kb.y));
          const uint32_t im = pack2(d[0] * __uint_as_float(ka.z) + d[2] * __uint_as_float(ka.w), d[1] * __uint_as_float(kb.z) + d[3] * __uint_as_float(kb.w));
          const uint32_t dc = pack2(fmaf(sum[r], -1.f / 32.f, d[0]), fmaf(sum[r], -1.f / 32.f, d[1]));
          alo[i][r] = re; alo[i][2 + r] = im;
          ahi[i][r] = g == 0 ? dc : re; ahi[i][2 + r] = g == 0 ? 0u : im;
        }
      float acc[8][4];
#pragma unroll
      for (int u = 0; u < 8; u++) {
        acc[u][0] = acc[u][1] = acc[u][2] = acc[u][3] = 0.f;
#pragma unroll
        for (int i = 0; i < 4; i++) {
          const uint4& bq = fb[i * 4 + (u >> 1)];
          if (u < 4) mma16816(acc[u], alo[i][0], alo[i][1], alo[i][2], alo[i][3], (u & 1) ? bq.z : bq.x, (u & 1) ? bq.w : bq.y);
          else       mma16816(acc[u], ahi[i][0], ahi[i][1], ahi[i][2], ahi[i][3], (u & 1) ? bq.z : bq.x, (u & 1) ? bq.w : bq.y);
        }
      }
#pragma unroll
      for (int r = 0; r < 2; r++)
#pragma unroll
        for (int h = 0; h < 2; h++) {
          const int j = 2 * warp + r, m = 2 * t + h;
          const float rs = rstd[r];
          sts4_p(en, sbase + SM_E + ((j * 8 + m) * 8 + (g ^ (2 * t) ^ (2 * (j & 3)))) * 16,
               pack2(acc[2 * h][2 * r] * rs, acc[2 * h][2 * r + 1] * rs), pack2(acc[2 * h + 1][2 * r] * rs, acc[2 * h + 1][2 * r + 1] * rs),
               pack2(acc[4 + 2 * h][2 * r] * rs, acc[4 + 2 * h][2 * r + 1] * rs), pack2(acc[5 + 2 * h][2 * r] * rs, acc[5 + 2 * h][2 * r + 1] * rs));
        }
      if (tid == 0) PROFP(12);
      if (en) {
        bar_sync(NB_RDY, 384);
      } else {
        asm volatile("st.shared.u32 [%0], %1;" ::"r"(BAR(epoch, 0)), "r"(tag) : "memory");
        bar_arrive(NB_RDY, 384);
      }
      if (tid == 0) PROFP(13);
      uint4 fc[4];
#pragma unroll
      for (int i = 0; i < 4; i++) fc[i] = lds4(sbase + SM_FC + i * 512 + lane * 16);
      asm volatile("ld.shared.u32 %0, [%1];" : "=r"(tag) : "r"(BAR(epoch, 0)) : "memory");
      tag = (tag + 1) & 1;
#pragma unroll
      for (int i = 0; i < 4; i++) q[i] = lds4(sbase + SM_E + (((t + 4 * i) * 8 + warp) * 8 + (g ^ (warp & 6) ^ (2 * t))) * 16);
      cdft16(q, fc, o);
#pragma unroll
      for (int vv = 0; vv < 4; vv++) st_tag_p(en, &scr->Z1[(((4 * vv + t) * 8 + warp) * 128 + c) * 8 + g], o[vv], tag);
    }
    PROF(1);
    if (!en) spin_until(t0 + DRY_T1);
    {
      const uint4* const zp = &scr->Z1[(c * 128 + 8 * t + warp) * 8 + g];
      const uint32_t tst = clock32();
      if (en) mbar_wait(BAR(tbar, 0), 0);
      if (tid == 0) PROFP(14);
      uint4 f2[4], g2[4];
#pragma unroll
      for (int i = 0; i < 4; i++) {
        f2[i] = lds4(TOFF(f2) + warp * 2048 + i * 512);
        g2[i] = lds4(TOFF(g2) + warp * 2048 + i * 512);
      }
      const uint4 f8 = lds4(TOFF(f8)), g8 = lds4(TOFF(g8));
      float wfr[16], wfi[16];
      {
        const float fsc = 1.f / (1 << 19);
        const float fsc3 = ((c & 7) == 7 && g == 0) ? 0.5f * fsc : fsc;
        const int gg = g == 0 ? 8 : g, wsh = (2 * (c >> 3) + 2) & 15;
#pragma unroll
        for (int i = 0; i < 16; i++) {
          const int ci = i >> 3, dd = (i >> 2) & 1, e = i & 3;
          const int kk = (e == 0 ? gg : e == 1 ? 16 + gg : e == 2 ? 16 - g : 32 - g) - 1;
          const uint32_t a = sbase + SM_W + ((2 * warp + ci) * 8 + t + 4 * dd) * 80 + wsh + 2 * kk;
          wfr[i] = bf_lo(lds_u16(a)) * (e == 3 ? fsc3 : fsc);
          wfi[i] = bf_lo(lds_u16(a + 10240)) * (e == 3 ? fsc3 : fsc);
        }
      }
      asm volatile("barrier.cluster.wait.aligned;" ::: "memory");
      PROF(2);
      if (en) {
        spin_until(tst + POLL_DELAY);
        ld_tag4_issue<256>(q, zp);
        ld_tag4_finish<256>(q, zp, tag);
      }
      if (tid == 0) PROFP(30);
      if (en && lane == 0) mbar_arrive(BAR(sig, 0));
      cdft16(q, f2, o);
      const uint32_t e2 = sbase + SM_E2;
#pragma unroll
      for (int vv = 0; vv < 4; vv++)
        sts4_p(en, e2 + ((warp * 16 + 4 * vv + t) * 8 + (g ^ (2 * t) ^ (2 * (warp & 3)))) * 16, o[vv].x, o[vv].y, o[vv].z, o[vv].w);
      if (en) bar_sync(NB_CONS, 256);
#pragma unroll
      for (int ci = 0; ci < 2; ci++) {
        const int cc = 2 * warp + ci;
        uint32_t ad[2];
        uint4 u[2];
#pragma unroll
        for (int hh = 0; hh < 2; hh++) {
          ad[hh] = e2 + (((t + 4 * hh) * 16 + cc) * 8 + (g ^ (2 * (cc & 3)) ^ (2 * t))) * 16;
          u[hh] = lds4(ad[hh]);
        }
        uint32_t res[2][4];
#pragma unroll
        for (int p = 0; p < 2; p++) {
          uint32_t y[2][2];
#pragma unroll
          for (int vv = 0; vv < 2; vv++) {
            float d[4] = {0.f, 0.f, 0.f, 0.f};
            mma16816(d, word(u[0], 2 * p), word(u[0], 2 * p + 1), word(u[1], 2 * p), word(u[1], 2 * p + 1), word(f8, 2 * vv), word(f8, 2 * vv + 1));
#pragma unroll
            for (int rr = 0; rr < 2; rr++) {
              const float fr = wfr[ci * 8 + vv * 4 + 2 * p + rr], fi = wfi[ci * 8 + vv * 4 + 2 * p + rr];
              y[vv][rr] = pack2(d[2 * rr] * fr - d[2 * rr + 1] * fi, d[2 * rr] * fi + d[2 * rr + 1] * fr);
            }
          }
#pragma unroll
          for (int vv = 0; vv < 2; vv++) {
            float d[4] = {0.f, 0.f, 0.f, 0.f};
            mma16816(d, y[0][0], y[0][1], y[1][0], y[1][1], word(g8, 2 * vv), word(g8, 2 * vv + 1));
            res[vv][2 * p] = pack2(d[0], d[1]);
            res[vv][2 * p + 1] = pack2(d[2], d[3]);
          }
        }
#pragma unroll
        for (int vv = 0; vv < 2; vv++) sts4_p(en, ad[vv], res[vv][0], res[vv][1], res[vv][2], res[vv][3]);
      }
      if (en) bar_sync(NB_CONS, 256);
#pragma unroll
      for (int i = 0; i < 4; i++) q[i] = lds4(e2 + ((warp * 16 + 4 * i + t) * 8 + (g ^ (2 * t) ^ (2 * (warp & 3)))) * 16);
      cdft16(q, g2, o);
#pragma unroll
      for (int vv = 0; vv < 4; vv++) st_tag_p(en, &scr->Z2[((8 * (4 * vv + t) + warp) * 128 + c) * 8 + g], o[vv], tag);
    }
    PROF(3);
    {
      const uint4* const zp = &scr->Z2[((c * 16 + t) * 8 + warp) * 8 + g];
      const uint32_t tst = clock32();
      uint4 gb[16], gc[4], tw[4], xr[2][2];
#pragma unroll
      for (int i = 0; i < 16; i++) gb[i] = lds4(TOFF(gb) + i * 512);
      const uint4 ga = lds4(TOFF(ga));
#pragma unroll
      for (int i = 0; i < 4; i++) {
        gc[i] = lds4(sbase + SM_FC + 2048 + i * 512 + lane * 16);
        tw[i] = lds4(TOFF(tw3) + i * 512);
        const int ch = 4 * (g + 8 * (i & 1)) + t;
        xr[i >> 1][i & 1] = lds4(sbase + SM_X + (2 * warp + (i >> 1)) * 1024 + ((ch ^ ((ch >> 2) & 6)) * 16));
      }
      PROF(4);
      if (en) {
        spin_until(tst + POLL_DELAY2);
        ld_tag4_issue<256>(q, zp);
        ld_tag4_finish<256>(q, zp, tag);
      }
      if (tid == 0) PROFP(31);
      if (en && lane == 0) mbar_arrive(BAR(sig, 1));
      cdft16(q, gc, o);
#pragma unroll
      for (int vv = 0; vv < 4; vv++)
        sts4_p(en, sbase + SM_E + (((4 * vv + t) * 8 + warp) * 8 + (g ^ (warp & 6) ^ (2 * t))) * 16, o[vv].x, o[vv].y, o[vv].z, o[vv].w);
      if (tid == 0) PROFP(8);
      if (en) bar_sync(NB_CONS, 256);
      if (tid == 0) PROFP(9);
      uint32_t hv[2][8];
      const float mk = t == 0 ? 0.f : 1.f;
#pragma unroll
      for (int r = 0; r < 2; r++) {
        const int j = 2 * warp + r;
        uint4 u[2];
#pragma unroll
        for (int h = 0; h < 2; h++) u[h] = lds4(sbase + SM_E + ((j * 8 + 2 * t + h) * 8 + (g ^ (2 * t) ^ (2 * (j & 3)))) * 16);
        float yv[4][4];
#pragma unroll
        for (int i = 0; i < 4; i++) {
          float lo[4] = {0.f, 0.f, 0.f, 0.f}, hi[4] = {0.f, 0.f, 0.f, 0.f};
          mma16816(lo, gb[i * 4].x, gb[i * 4].y, gb[i * 4].z, gb[i * 4].w, u[0].x, u[0].y);
          mma16816(lo, gb[i * 4 + 1].x, gb[i * 4 + 1].y, gb[i * 4 + 1].z, gb[i * 4 + 1].w, u[1].x, u[1].y);
          mma16816(hi, gb[i * 4 + 2].x, gb[i * 4 + 2].y, gb[i * 4 + 2].z, gb[i * 4 + 2].w, u[0].z, u[0].w);
          mma16816(hi, gb[i * 4 + 3].x, gb[i * 4 + 3].y, gb[i * 4 + 3].z, gb[i * 4 + 3].w, u[1].z, u[1].w);
          const float ca = __uint_as_float(tw[i].x), sa = __uint_as_float(tw[i].y), cb = __uint_as_float(tw[i].z), sb = __uint_as_float(tw[i].w);
          const float tr0 = fmaf(hi[0], mk, lo[0]), ti0 = fmaf(hi[2], mk, lo[2]);
          const float tr1 = lo[1] + hi[1], ti1 = lo[3] + hi[3];
          const float vr0 = tr0 * ca - ti0 * sa, vi0 = tr0 * sa + ti0 * ca;
          const float vr1 = tr1 * cb - ti1 * sb, vi1 = tr1 * sb + ti1 * cb;
          const uint32_t b0 = pack2(t == 0 ? hi[0] : vr0, vr1), b1 = pack2(t == 0 ? vr0 : vi0, vi1);
          yv[i][0] = yv[i][1] = yv[i][2] = yv[i][3] = 0.f;
          mma16816(yv[i], ga.x, ga.y, ga.z, ga.w, b0, b1);
        }
#pragma unroll
        for (int h = 0; h < 2; h++) {
          hv[r][4 * h + 0] = hadd2_bf16(xr[r][h].x, pack2(yv[0][2 * h], yv[1][2 * h]));
          hv[r][4 * h + 1] = hadd2_bf16(xr[r][h].y, pack2(yv[2][2 * h], yv[3][2 * h]));
          hv[r][4 * h + 2] = hadd2_bf16(xr[r][h].z, pack2(yv[0][2 * h + 1], yv[1][2 * h + 1]));
          hv[r][4 * h + 3] = hadd2_bf16(xr[r][h].w, pack2(yv[2][2 * h + 1], yv[3][2 * h + 1]));
        }
      }
      if (tid == 0 && hv[0][0] != 0x12345 && hv[1][7] != 0x12345) PROFP(10);
      float ds[4] = {0.f, 0.f, 0.f, 0.f};
#pragma unroll
      for (int q4 = 0; q4 < 4; q4++) mma16816(ds, hv[0][2 * q4], hv[1][2 * q4], hv[0][2 * q4 + 1], hv[1][2 * q4 + 1], 0x3f803f80u, 0x3f803f80u);
#pragma unroll
      for (int o2 = 4; o2 <= 16; o2 <<= 1) {
        ds[0] += __shfl_xor_sync(0xffffffffu, ds[0], o2);
        ds[2] += __shfl_xor_sync(0xffffffffu, ds[2], o2);
      }
      uint32_t mb[2];
#pragma unroll
      for (int r = 0; r < 2; r++) {
        const int row = 16 * f + 2 * warp + r;
        mb[r] = pack2(ds[2 * r] * (1.f / 512.f), ds[2 * r] * (1.f / 512.f));
#pragma unroll
        for (int i = 0; i < 8; i++) hv[r][i] = hsub2_bf16(hv[r][i], mb[r]);
#pragma unroll
        for (int h = 0; h < 2; h++) {
          const int n1 = g + 8 * h;
          st_tag_p(en, &scr->LN[(rb * 8 + (n1 >> 1)) * 1024 + row * 8 + ((4 * (n1 & 1) + t) ^ (row & 7))],
                 make_uint4(hv[r][4 * h], hv[r][4 * h + 1], hv[r][4 * h + 2], hv[r][4 * h + 3]), n1 < 2 * NLL ? tag : (hv[r][4 * h] & 1u));
        }
      }
      if (tid == 0) PROFP(11);
      if (en) bar_arrive(NB_LN, 288);
      float sum[2], sq[2], rstd[2];
      row_stats(hv[0], hv[1], lane, sum, sq);
#pragma unroll
      for (int r = 0; r < 2; r++) {
        const float m = sum[r] * (1.f / 512.f);
        rstd[r] = rsqrtf(fmaxf(fmaf(-m, m, sq[r] * (1.f / 512.f)), 0.f) + 1e-5f);
      }
      st_tag_p(en && lane == 0, &scr->ST[rb * 64 + 8 * f + warp], make_uint4(mb[0] << 16, __float_as_uint(rstd[0]), mb[1] << 16, __float_as_uint(rstd[1])), tag);
    }
    PROF(5);
    const int wgi = warp >> 2, wq = warp & 3;
    uint4* const pbase = &scr->P[rb * 28 * 1024 + warp * 128 + lane];
    const uint32_t a_lo0 = desc_lo(sbase + wgi * 8192, 16);
    const uint32_t ebar = lane == 0 ? BAR(empty1, 0) : RBAR(empty1, 0);
    float r0, r1;
    const int rh = wgi ^ kh ^ 1;
    const uint4* const psrc = &scr->P[(rb2 * 28 + 14 * kh) * 1024 + (4 * rh + wq) * 128 + lane];
    const uint32_t pa0 = sbase + (4 * rh + wq) * 2048;
    uint4 pf[LAG2 > 3 ? LAG2 : 3][4];
    uint32_t rdy = 0;
    auto fetch2 = [&](int s, uint4 (&a)[4]) {
#pragma unroll
      for (int kk = 0; kk < 4; kk++) a[kk] = lds4(pa0 + (uint32_t)((PSLOT >> (4 * s)) & 15) * SLOT + kk * 512 + lane * 16);
    };
    {
      float acc[128];
#pragma unroll
      for (int i = 0; i < 128; i++) acc[i] = 0.f;
      if (en) {
        const uint32_t b_lo0 = desc_lo(sbase + 8 * SLOT, 4096);
        const uint32_t t3 = clock32();
        if (WARM) {
          wg_fence();
#pragma unroll
          for (int i = 0; i < WARM; i++) wgmma_n256(acc, desc64(a_lo0 + 6 * 1024, HI128), desc64(b_lo0, HI128));
          wg_commit();
        }
        if (NLL) {
          const uint4* const ap = &scr->LN[rb * 8 * 1024 + tid];
          uint4 av[NLL ? NLL : 1][4];
          while (clock32() - t3 < POLL_DELAY3) {}
#pragma unroll
          for (int kb = 0; kb < NLL; kb++) ld_tag4_issue<256>(av[kb], ap + kb * 1024);
          bar_sync(NB_CONS, 256);
#pragma unroll
          for (int kb = 0; kb < NLL; kb++) {
            ld_tag4_finish<256>(av[kb], ap + kb * 1024, tag);
#pragma unroll
            for (int i = 0; i < 4; i++) sts4(sbase + kb * SLOT + (tid + 256 * i) * 16, av[kb][i].x, av[kb][i].y, av[kb][i].z, av[kb][i].w);
          }
          asm volatile("fence.proxy.async.shared::cta;" ::: "memory");
          bar_sync(NB_CONS, 256);
        }
        uint32_t slot = 2;
#pragma unroll 1
        for (int kb = 0; kb < 8; kb++) {
          if (kb >= NLL) mbar_wait(BAR(fullA, kb), 0);
          if (kb == 0) PROF(6);
#pragma unroll
          for (int hh = 0; hh < 2; hh++) {
            if (LAGX && hh == ((16 - LAGX) & 1) && kb == ((16 - LAGX) >> 1) && wgi == 1) bar_sync(NB_LAG, 256);
            mbar_wait(BAR(full1, 2 * kb + hh));
            const uint32_t al = a_lo0 + kb * 1024 + hh * 4, bl = b_lo0 + slot * 1024;
            wg_fence();
            wgmma_n256(acc, desc64(al, HI128), desc64(bl, HI128), (kb | hh) != 0);
            wgmma_n256(acc, desc64(al + 2, HI128), desc64(bl + 128, HI128));
            wg_commit();
            if (LAGX && hh == 1 && kb == 7 && wgi == 0) bar_arrive(NB_LAG, 256);
            wg_wait<1>();
            if ((kb | hh) != 0 && lane < 2) mbar_arrive_remote(ebar + 8 * (2 * kb + hh - 1));
            if (++slot == 6) slot = 0;
          }
        }
        mbar_wait(BAR(sbar, 0), 0);
        wg_wait<0>();
        if (lane < 2) mbar_arrive_remote(ebar + 8 * 15);
      }
      r0 = __uint_as_float(lds2(sstat + (16 * warp + g) * 8).y);
      r1 = __uint_as_float(lds2(sstat + (16 * warp + g + 8) * 8).y);
      PROF(7);
      store_p<8>(en, acc, r0, r1, pbase, 14 * f + 6 * (f & 1), tag);
      if (en && lane == 0) red_relaxed(&scr->cnt[(C_PX + rb) * 32 + (f >> 2)]);
    }
    PROF(8);
    {
      float acc[96];
#pragma unroll
      for (int i = 0; i < 96; i++) acc[i] = 0.f;
      if (en) {
        const uint32_t b_lo0 = desc_lo(sbase + 8 * SLOT, 2048);
#pragma unroll 1
        for (int k = 0; k < 16; k++) {
          if (LAGY && k == 16 - LAGY && wgi == 1) bar_sync(NB_LAG, 256);
          mbar_wait(BAR(full1, 16 + k));
          const uint32_t al = a_lo0 + (k >> 1) * 1024 + (k & 1) * 4, bl = b_lo0 + (k & 7) * 768;
          wg_fence();
          wgmma_n192(acc, desc64(al, HI128), desc64(bl, HI64));
          wgmma_n192(acc, desc64(al + 2, HI128), desc64(bl + 64, HI64));
          wg_commit();
          if (LAGY && k == 15 && wgi == 0) bar_arrive(NB_LAG, 256);
          wg_wait<1>();
          if (k != 0 && lane < 2) mbar_arrive_remote(ebar + 8 * (15 + k));
        }
        rdy = __all_sync(0xffffffffu, mbar_test(BAR(fullP, 0)) & mbar_test(BAR(full2, 0)) & mbar_test(BAR(fullP, 1)));
        if (rdy) fetch2(0, pf[0]);
        wg_wait<0>();
        if (lane < 2) mbar_arrive_remote(ebar + 8 * 31);
      }
      PROF(9);
      store_p<6>(en, acc, r0, r1, pbase, 14 * f + ((f & 1) ? 0 : 8), tag);
      if (en && lane == 0) red_relaxed(&scr->cnt[(C_PY + rb) * 32 + (f >> 1)]);
    }
    PROF(10);
    if (!en) {
      if (lane == 0) PROFP(7);
      unsigned epoch;
      asm volatile("ld.shared.u32 %0, [%1];" : "=r"(epoch) : "r"(BAR(epoch, 0)) : "memory");
      mbar_wait(BAR(fullA, 7), 0);
      {
        uint4 v0, v1, v2;
        int it = 0;
        while (true) {
          v0 = ld_b128(&scr->ST[rb * 64 + lane]);
          v1 = ld_b128(&scr->ST[rb * 64 + 32 + lane]);
          v2 = ld_b128(&scr->ST[rb2 * 64 + 32 * kh + lane]);
          if (!__any_sync(0xffffffffu, ((v0.x ^ tag) | (v1.x ^ tag) | (v2.x ^ tag)) & 1u)) break;
          if (++it > SPIN_LIMIT) { die(); break; }
        }
        sts4(sstat + lane * 16, v0.x & ~1u, v0.y, v0.z, v0.w);
        sts4(sstat + 512 + lane * 16, v1.x & ~1u, v1.y, v1.z, v1.w);
        sts4(sstat + 1024 + lane * 16, v2.x & ~1u, v2.y, v2.z, v2.w);
#pragma unroll 4
        for (int i = 0; i < 32; i++)
          st_tag(&scr->XP[(c ^ 4) * 1024 + i * 32 + lane], make_uint4(0, 0, 0, 0), tag ^ 1);
        mbar_arrive(BAR(sbar, 0));
      }
      if (lane == 0) {
        mbar_wait(BAR(empty1, 17));
#pragma unroll 1
        for (int e = 0; e < (SPEC < 0 ? 3 : 1); e++) {
          const unsigned* cp = e == 0 ? &scr->cnt[(C_PX + rb2) * 32 + kh] : &scr->cnt[(C_PY + rb2) * 32 + 2 * kh + e - 1];
          if (e == 1) mbar_wait(BAR(fullP, 0), 0);
          int it = 0;
          while ((int)(ld_relaxed(cp) - (epoch + 1) * (e == 0 ? 32 : 16)) < 0)
            if (++it > SPIN_LIMIT) { die(); break; }
          mbar_arrive(BAR(hint, e));
        }
      }
    } else
    {
      float acc[64];
      const uint32_t b2_lo0 = desc_lo(sbase, 8192);
      const uint32_t pbar = ebar + (uint32_t)(offsetof(Bars, emptyP) - offsetof(Bars, empty1));
      constexpr int S1 = 14 - LAG2;
      constexpr int NF = LAG2 > 3 ? LAG2 : 3;
      auto check2 = [&](int s) {
        ld_tag4_finish<32>(pf[s % NF], psrc + (int)((KORDER >> (4 * s)) & 15) * 1024, tag);
      };
      auto mma2 = [&](int s) {
        const uint32_t bl = b2_lo0 + (uint32_t)((BSLOT >> (4 * s)) & 15) * 1024;
        const uint4 (&a)[4] = pf[s % NF];
        if (s == 0) wgmma_rs_n128<0>(acc, a[0].x, a[0].y, a[0].z, a[0].w, desc64(bl, HI128));
        else wgmma_rs_n128<1>(acc, a[0].x, a[0].y, a[0].z, a[0].w, desc64(bl, HI128));
#pragma unroll
        for (int kk = 1; kk < 4; kk++) wgmma_rs_n128<1>(acc, a[kk].x, a[kk].y, a[kk].z, a[kk].w, desc64(bl + kk * 128, HI128));
      };
      auto stage2 = [&](int s) {
        check2(s);
        if (s < 8 && lane < (s < 7 ? 2 : 1)) mbar_arrive_remote(pbar + 8 * s);
        if (s >= 2) {
          wg_wait<1>();
          if (s <= 8 && lane == 0) mbar_arrive(BAR(empty2, s - 2));
        }
        if (!rdy) {
          if (s < 13) mbar_wait(BAR(fullP, s + 1));
          mbar_wait(BAR(full2, s));
        }
        if (tid == 0) PROFP(16 + s);
        wg_fence();
        if (s < 13) {
          fetch2(s + 1, pf[(s + 1) % NF]);
          rdy = mbar_test(BAR(full2, s + 1));
          if (s < 12) rdy &= mbar_test(BAR(fullP, s + 2));
        }
        mma2(s);
        wg_commit();
      };
      if (!rdy) {
        mbar_wait(BAR(fullP, 0));
        fetch2(0, pf[0]);
      }
#pragma unroll
      for (int s = 0; s < S1; s++) stage2(s);
      if (wgi == 0) {
#pragma unroll
        for (int s = S1; s < 14; s++) stage2(s);
        bar_arrive(NB_LAG, 256);
        uint4* const dst = &scr->XP[(c ^ 4) * 1024 + tid];
        wg_wait<0>();
        PROF(11);
#pragma unroll
        for (int i = 0; i < 8; i++)
          st_tag(dst + i * 128, make_uint4(pack2(acc[8 * i], acc[8 * i + 1]), pack2(acc[8 * i + 2], acc[8 * i + 3]),
                                           pack2(acc[8 * i + 4], acc[8 * i + 5]), pack2(acc[8 * i + 6], acc[8 * i + 7])), tag);
      } else {
        wg_wait<0>();
        if (lane == 0) {
#pragma unroll
          for (int s = S1 - 2; s < S1; s++)
            if (s <= 6) mbar_arrive(BAR(empty2, s));
        }
#pragma unroll
        for (int s = S1; s < 14; s++) {
          if (s > S1) {
            mbar_wait(BAR(fullP, s));
            fetch2(s, pf[s % NF]);
          }
          check2(s);
          if (s == 7 && lane == 0) mbar_arrive(BAR(emptyP, 7));
        }
        {
          const float m0 = __uint_as_float(lds2(sstat + 1024 + (16 * wq + g) * 8).x);
          const float m1 = __uint_as_float(lds2(sstat + 1024 + (16 * wq + g + 8) * 8).x);
          const uint32_t hb = sbase + 4 * SLOT + (16 * wq + (lane & 15)) * 128;
          mbar_wait(BAR(hbar, 0));
#pragma unroll
          for (int i = 0; i < 8; i++) {
            uint32_t h[4];
            asm volatile("ldmatrix.sync.aligned.m8n8.x4.shared.b16 {%0,%1,%2,%3}, [%4];"
                         : "=r"(h[0]), "=r"(h[1]), "=r"(h[2]), "=r"(h[3])
                         : "r"(hb + (i >> 2) * 8192 + (((2 * (i & 3) + (lane >> 4)) ^ (lane & 7)) * 16)) : "memory");
            const uint32_t mk = (t == 0 && 2 * nq + (i >> 2) < NLL) ? ~1u : ~0u;
#pragma unroll
            for (int e = 0; e < 4; e++) {
              acc[8 * i + 2 * e] += bf_lo(h[e] & mk) + ((e & 1) ? m1 : m0);
              acc[8 * i + 2 * e + 1] += __uint_as_float(h[e] & 0xffff0000u) + ((e & 1) ? m1 : m0);
            }
          }
        }
#pragma unroll
        for (int s = S1; s < 14; s++) mbar_wait(BAR(full2, s));
        bar_sync(NB_LAG, 256);
        const uint32_t t4 = clock32();
        wg_fence();
#pragma unroll
        for (int s = S1; s < 14; s++) mma2(s);
        wg_commit();
        uint4 pv[2][4];
        const uint4* const xsrc = &scr->XP[c * 1024 + (tid & 127)];
        while (clock32() - t4 < POLL_DELAY4) {}
        ld_tag4_issue<128>(pv[0], xsrc);
        ld_tag4_issue<128>(pv[1], xsrc + 512);
        wg_wait<0>();
        PROF(11);
        uint32_t w[32];
#pragma unroll
        for (int i = 0; i < 32; i++) w[i] = pack2(acc[2 * i], acc[2 * i + 1]);
        ld_tag4_finish<128>(pv[0], xsrc, tag);
        ld_tag4_finish<128>(pv[1], xsrc + 512, tag);
#pragma unroll
        for (int i = 0; i < 8; i++) {
          const uint4& p = pv[i >> 2][i & 3];
          asm volatile("stmatrix.sync.aligned.m8n8.x4.shared.b16 [%0], {%1,%2,%3,%4};"
                       ::"r"(pa0 + (9 + ((lane >> 3) & 1)) * SLOT + (lane & 7) * 256 + (((2 * i + (lane >> 4)) ^ (lane & 7)) * 16)),
                         "r"(hadd2_bf16(w[4 * i], p.x)), "r"(hadd2_bf16(w[4 * i + 1], p.y)), "r"(hadd2_bf16(w[4 * i + 2], p.z)),
                         "r"(hadd2_bf16(w[4 * i + 3], p.w)) : "memory");
        }
        __syncwarp();
        uint4* const dst = reinterpret_cast<uint4*>(out) + (16 * (c >> 4) + 2 * (4 * rh + wq) + (rb2 & 1) + 128 * (lane >> 4)) * 64 + nq * 16 + (lane & 15);
#pragma unroll
        for (int i = 0; i < 8; i++) {
          const int r = 2 * (i & 3) + (lane >> 4);
          dst[i * 256 * 64] = lds4(pa0 + (9 + (i >> 2)) * SLOT + r * 256 + (((lane & 15) ^ r) * 16));
        }
      }
      PROF(12);
      PROFG(15);
    }
  }
#undef BAR
#undef TOFF
#undef RBAR
}

typedef CUresult (*EncodeFn)(CUtensorMap*, CUtensorMapDataType, cuuint32_t, void*, const cuuint64_t*, const cuuint64_t*,
                             const cuuint32_t*, const cuuint32_t*, CUtensorMapInterleave, CUtensorMapSwizzle,
                             CUtensorMapL2promotion, CUtensorMapFloatOOBfill);

}

extern "C" void kernel_launch(void* const* d_in, const int* in_sizes, int n_in, void* d_out, int out_size) {
  (void)in_sizes; (void)n_in; (void)out_size;
  static EncodeFn encode = nullptr;
  static void *tab = nullptr, *scr = nullptr;
  if (!encode) {
    void* fn = nullptr;
    cudaDriverEntryPointQueryResult qr;
    cudaGetDriverEntryPoint("cuTensorMapEncodeTiled", &fn, cudaEnableDefault, &qr);
    encode = (EncodeFn)fn;
    cudaGetSymbolAddress(&tab, g_tab);
    cudaGetSymbolAddress(&scr, g_scr);
    cudaFuncSetAttribute(fused_kernel, cudaFuncAttributeMaxDynamicSharedMemorySize, SMEM_BYTES);
  }
  CUtensorMap tmGX, tmUX, tmGY, tmUY, tmD, tmWR, tmWI;
  const cuuint32_t es[5] = {1, 1, 1, 1, 1};
  auto enc = [&](CUtensorMap* m, void* p, int rank, const cuuint64_t* gd, const cuuint64_t* gs, const cuuint32_t* bd,
                 CUtensorMapSwizzle sw, CUtensorMapL2promotion pr) {
    encode(m, CU_TENSOR_MAP_DATA_TYPE_BFLOAT16, rank, p, gd, gs, bd, es, CU_TENSOR_MAP_INTERLEAVE_NONE, sw, pr,
           CU_TENSOR_MAP_FLOAT_OOB_FILL_NONE);
  };
  {
    const cuuint64_t gd[3] = {64, 512, 28}, gs[2] = {3584, 128};
    const cuuint32_t bd[3] = {64, 32, 2};
    enc(&tmGX, d_in[4], 3, gd, gs, bd, CU_TENSOR_MAP_SWIZZLE_128B, CU_TENSOR_MAP_L2_PROMOTION_L2_256B);
    enc(&tmUX, d_in[5], 3, gd, gs, bd, CU_TENSOR_MAP_SWIZZLE_128B, CU_TENSOR_MAP_L2_PROMOTION_L2_256B);
  }
  {
    const cuuint64_t gd[3] = {32, 512, 56}, gs[2] = {3584, 64};
    const cuuint32_t bd[3] = {32, 32, 3};
    enc(&tmGY, d_in[4], 3, gd, gs, bd, CU_TENSOR_MAP_SWIZZLE_64B, CU_TENSOR_MAP_L2_PROMOTION_L2_128B);
    enc(&tmUY, d_in[5], 3, gd, gs, bd, CU_TENSOR_MAP_SWIZZLE_64B, CU_TENSOR_MAP_L2_PROMOTION_L2_128B);
  }
  {
    const cuuint64_t gd[3] = {64, 1792, 8}, gs[2] = {1024, 128};
    const cuuint32_t bd[3] = {64, 64, 2};
    enc(&tmD, d_in[6], 3, gd, gs, bd, CU_TENSOR_MAP_SWIZZLE_128B, CU_TENSOR_MAP_L2_PROMOTION_L2_256B);
  }
  {
    const cuuint64_t gd[3] = {4112, 8, 16}, gs[2] = {16 * 8224, 8224};
    const cuuint32_t bd[3] = {40, 8, 16};
    enc(&tmWR, d_in[1], 3, gd, gs, bd, CU_TENSOR_MAP_SWIZZLE_NONE, CU_TENSOR_MAP_L2_PROMOTION_NONE);
    enc(&tmWI, d_in[2], 3, gd, gs, bd, CU_TENSOR_MAP_SWIZZLE_NONE, CU_TENSOR_MAP_L2_PROMOTION_NONE);
  }
  fused_kernel<<<NCTA, NTHREADS, SMEM_BYTES>>>((const __nv_bfloat16*)d_in[0], (const Tables*)tab, (Scratch*)scr,
                                               (__nv_bfloat16*)d_out, (const char*)d_in[4], (const char*)d_in[5],
                                               (const char*)d_in[6], tmWR, tmWI, tmGX, tmUX, tmGY, tmUY, tmD);
}
```

```cpp
#include <cuda_runtime.h>
#include <cuda_bf16.h>
#include <cuda.h>
#include <stdint.h>

namespace {

constexpr int NCTA = 128;
constexpr int NTHREADS = 384;
constexpr int SLOT = 16384;
constexpr int SMEM_BYTES = 14 * SLOT + 3072;
constexpr int SPIN_LIMIT = 1 << 22;

struct Scratch {
  uint4 Z1[128 * 1024];
  uint4 Z2[128 * 1024];
  uint4 LN[16 * 8 * 1024];
  uint4 P[16 * 28 * 1024];
  uint4 XP[128 * 1024];
  uint4 ST[1024];
  unsigned cnt[64 * 32];
};
__device__ __align__(1024) Scratch g_scr;
#define PROF(i)
#define PROFP(i)
#define PROFG(i)

constexpr double ccos(int i, int n) {
  i &= n - 1;
  if (i > n / 2) i = n - i;
  if (4 * i == n) return 0.0;
  const bool neg = 4 * i > n;
  if (neg) i = n / 2 - i;
  const double a = 6.283185307179586476925 * i / n, a2 = a * a;
  double term = 1.0, sum = 1.0;
  for (int k = 1; k < 14; k++) { term *= -a2 / ((2 * k - 1) * (2 * k)); sum += term; }
  return neg ? -sum : sum;
}
constexpr double csin(int i, int n) { return ccos(i - n / 4, n); }
constexpr unsigned fbits(double v, int mant) {
  if (v == 0.0) return 0;
  const unsigned sg = v < 0 ? 1u : 0u;
  if (v < 0) v = -v;
  int e = 127;
  while (v < 1.0) { v *= 2.0; e--; }
  const unsigned m = (unsigned)((v - 1.0) * (double)(1u << mant) + 0.5);
  return (sg << (8 + mant)) + ((unsigned)e << mant) + m;
}
constexpr unsigned pkb(double lo, double hi) { return fbits(lo, 7) | (fbits(hi, 7) << 16); }
constexpr double fa_elem(int kp, int n1) {
  return kp <= 8 ? ccos(kp * n1, 16) : -csin((kp - 8) * n1, 16);
}
constexpr unsigned cfrag_c(int idx, int n, int ri) {
  return ri ? pkb(-csin(idx, n), ccos(idx, n)) : pkb(ccos(idx, n), csin(idx, n));
}
struct Tables {
  unsigned fb[16][32][4];
  unsigned tw1[8][32][4];
  unsigned fa[32][4];
  unsigned f2[8][4][32][4];
  unsigned g2[8][4][32][4];
  unsigned gb[16][32][4];
  unsigned tw3[4][32][4];
  unsigned ga[32][4];
  unsigned f8[32][4], g8[32][4];
};
constexpr int T1_BYTES = 12800, T2_BYTES = 44544;
static_assert(sizeof(Tables) == T1_BYTES + T2_BYTES, "table size");
constexpr Tables make_tables() {
  Tables T = {};
  for (int l = 0; l < 32; l++) {
    const int g = l >> 2, t = l & 3;
    for (int i = 0; i < 4; i++)
      for (int u = 0; u < 8; u++) {
        const int ri = g & 1, m = 2 * (g >> 1) + ((u & 3) >> 1);
        const double sg = u >= 4 ? -1.0 : 1.0;
        const int k2 = u >= 4 ? 31 - 2 * m - (u & 1) : 2 * m + (u & 1);
        const int pa = (8 * t + i) * k2, pb = (8 * t + 4 + i) * k2;
        T.fb[i * 4 + (u >> 1)][l][(u & 1) * 2 + 0] = ri == 0 ? pkb(ccos(pa, 32), ccos(pb, 32)) : pkb(-sg * csin(pa, 32), -sg * csin(pb, 32));
        T.fb[i * 4 + (u >> 1)][l][(u & 1) * 2 + 1] = ri == 0 ? pkb(csin(pa, 32), csin(pb, 32)) : pkb(sg * ccos(pa, 32), sg * ccos(pb, 32));
      }
    for (int i = 0; i < 4; i++)
      for (int ks = 0; ks < 4; ks++) {
        const int n2 = 4 * g + i, m = 2 * t + (ks & 1);
        const double sg = ks >= 2 ? -1.0 : 1.0;
        const int pa = n2 * (ks >= 2 ? 31 - 2 * m : 2 * m), pb = n2 * (ks >= 2 ? 30 - 2 * m : 2 * m + 1);
        T.gb[i * 4 + ks][l][0] = pkb(ccos(pa, 32), -sg * csin(pa, 32));
        T.gb[i * 4 + ks][l][1] = pkb(csin(pa, 32), sg * ccos(pa, 32));
        T.gb[i * 4 + ks][l][2] = pkb(ccos(pb, 32), -sg * csin(pb, 32));
        T.gb[i * 4 + ks][l][3] = pkb(csin(pb, 32), sg * ccos(pb, 32));
      }
    for (int i = 0; i < 4; i++) {
      for (int e = 0; e < 2; e++) {
        const int p = (8 * t + 4 * e + i) * (g == 0 ? 8 : g);
        T.tw1[2 * i + e][l][0] = fbits(g == 0 ? 0.0 : ccos(p, 512), 23);
        T.tw1[2 * i + e][l][1] = fbits(g == 0 ? ccos(p, 512) : csin(p, 512), 23);
        T.tw1[2 * i + e][l][2] = fbits(g == 0 ? 0.0 : -csin(p, 512), 23);
        T.tw1[2 * i + e][l][3] = fbits(g == 0 ? -csin(p, 512) : ccos(p, 512), 23);
      }
      const int ka = t == 0 ? 8 : 2 * t, kb = 2 * t + 1;
      T.tw3[i][l][0] = fbits(ccos((4 * g + i) * ka, 512), 23);
      T.tw3[i][l][1] = fbits(csin((4 * g + i) * ka, 512), 23);
      T.tw3[i][l][2] = fbits(ccos((4 * g + i) * kb, 512), 23);
      T.tw3[i][l][3] = fbits(csin((4 * g + i) * kb, 512), 23);
      const int p8 = (t + 4 * (i & 1)) * (4 * (i >> 1) + (g >> 1));
      T.f8[l][i] = cfrag_c(p8, 8, g & 1);
      T.g8[l][i] = cfrag_c(-p8, 8, g & 1);
    }
    for (int w = 0; w < 8; w++)
      for (int i = 0; i < 16; i++) {
        const int kidx = t + 4 * (i & 1) + 8 * (i >> 3), nidx = 4 * ((i >> 1) & 3) + (g >> 1);
        T.f2[w][i >> 2][l][i & 3] = cfrag_c((8 * kidx + w) * nidx, 128, g & 1);
        T.g2[w][i >> 2][l][i & 3] = cfrag_c(-(8 * nidx + w) * kidx, 128, g & 1);
      }
    T.fa[l][0] = pkb(fa_elem(g, 2 * t), fa_elem(g, 2 * t + 1));
    T.fa[l][1] = pkb(fa_elem(g + 8, 2 * t), fa_elem(g + 8, 2 * t + 1));
    T.fa[l][2] = pkb(fa_elem(g, 2 * t + 8), fa_elem(g, 2 * t + 9));
    T.fa[l][3] = pkb(fa_elem(g + 8, 2 * t + 8), fa_elem(g + 8, 2 * t + 9));
    T.ga[l][0] = pkb(fa_elem(2 * t, g), fa_elem(2 * t + 1, g));
    T.ga[l][1] = pkb(fa_elem(2 * t, g + 8), fa_elem(2 * t + 1, g + 8));
    T.ga[l][2] = pkb(fa_elem(2 * t + 8, g), fa_elem(2 * t + 9, g));
    T.ga[l][3] = pkb(fa_elem(2 * t + 8, g + 8), fa_elem(2 * t + 9, g + 8));
  }
  return T;
}
__device__ const __align__(128) Tables g_tab = make_tables();

__device__ __forceinline__ void die() { asm volatile("st.global.u32 [%0], %1;" ::"l"(0ull), "r"(0) : "memory"); }
__device__ __forceinline__ uint32_t s2u(const void* p) { return (uint32_t)__cvta_generic_to_shared(p); }
__device__ __forceinline__ void mbar_init(uint32_t b, int c) { asm volatile("mbarrier.init.shared::cta.b64 [%0], %1;" ::"r"(b), "r"(c)); }
__device__ __forceinline__ void mbar_expect(uint32_t b, int bytes) {
  asm volatile("mbarrier.arrive.expect_tx.shared::cta.b64 _, [%0], %1;" ::"r"(b), "r"(bytes) : "memory");
}
__device__ __forceinline__ void mbar_arrive(uint32_t b) { asm volatile("mbarrier.arrive.shared::cta.b64 _, [%0];" ::"r"(b) : "memory"); }
__device__ __forceinline__ uint32_t mbar_try(uint32_t b, uint32_t parity) {
  uint32_t ok;
  asm volatile("{.reg .pred p; mbarrier.try_wait.parity.shared::cta.b64 p, [%1], %2; selp.u32 %0,1,0,p;}"
               : "=r"(ok) : "r"(b), "r"(parity) : "memory");
  return ok;
}
__device__ __forceinline__ uint32_t mbar_test(uint32_t b) {
  uint32_t ok;
  asm volatile("{.reg .pred p; mbarrier.test_wait.parity.shared::cta.b64 p, [%1], 0; selp.u32 %0,1,0,p;}" : "=r"(ok) : "r"(b) : "memory");
  return ok;
}
__device__ __forceinline__ void mbar_wait(uint32_t b, uint32_t parity = 0) {
  int it = 0;
#pragma unroll 1
  while (!mbar_try(b, parity))
    if (++it > SPIN_LIMIT) { die(); break; }
}
__device__ __forceinline__ void bar_sync(int id, int n) { asm volatile("bar.sync %0, %1;" ::"r"(id), "r"(n) : "memory"); }
__device__ __forceinline__ void bar_arrive(int id, int n) { asm volatile("bar.arrive %0, %1;" ::"r"(id), "r"(n) : "memory"); }
__device__ __forceinline__ void red_release(unsigned* p) { asm volatile("red.release.gpu.global.add.u32 [%0], 1;" ::"l"(p) : "memory"); }
__device__ __forceinline__ void red_relaxed(unsigned* p) { asm volatile("red.relaxed.gpu.global.add.u32 [%0], 1;" ::"l"(p) : "memory"); }
__device__ __forceinline__ unsigned ld_acquire(const unsigned* p) {
  unsigned v;
  asm volatile("ld.acquire.gpu.global.u32 %0, [%1];" : "=r"(v) : "l"(p) : "memory");
  return v;
}
__device__ __forceinline__ unsigned ld_relaxed(const unsigned* p) {
  unsigned v;
  asm volatile("ld.relaxed.gpu.global.u32 %0, [%1];" : "=r"(v) : "l"(p) : "memory");
  return v;
}
__device__ __forceinline__ void wait_counter(const unsigned* p, unsigned target) {
  int it = 0;
  while ((int)(ld_acquire(p) - target) < 0)
    if (++it > SPIN_LIMIT) { die(); break; }
}
__device__ __forceinline__ void sts4(uint32_t a, uint32_t x, uint32_t y, uint32_t z, uint32_t w) {
  asm volatile("st.shared.v4.u32 [%0], {%1,%2,%3,%4};" ::"r"(a), "r"(x), "r"(y), "r"(z), "r"(w) : "memory");
}
__device__ __forceinline__ uint4 lds4(uint32_t a) {
  uint4 v;
  asm volatile("ld.shared.v4.u32 {%0,%1,%2,%3}, [%4];" : "=r"(v.x), "=r"(v.y), "=r"(v.z), "=r"(v.w) : "r"(a) : "memory");
  return v;
}
__device__ __forceinline__ uint32_t pack2(float lo, float hi) {
  uint32_t r;
  asm("cvt.rn.bf16x2.f32 %0, %1, %2;" : "=r"(r) : "f"(hi), "f"(lo));
  return r;
}
__device__ __forceinline__ float bf_lo(uint32_t v) { return __uint_as_float(v << 16); }
__device__ __forceinline__ uint32_t hadd2_bf16(uint32_t a, uint32_t b) {
  uint32_t r;
  asm("add.rn.bf16x2 %0, %1, %2;" : "=r"(r) : "r"(a), "r"(b));
  return r;
}
__device__ __forceinline__ void mma16816(float (&d)[4], uint32_t a0, uint32_t a1, uint32_t a2, uint32_t a3, uint32_t b0, uint32_t b1) {
  asm("mma.sync.aligned.m16n8k16.row.col.f32.bf16.bf16.f32 {%0,%1,%2,%3}, {%4,%5,%6,%7}, {%8,%9}, {%0,%1,%2,%3};"
      : "+f"(d[0]), "+f"(d[1]), "+f"(d[2]), "+f"(d[3])
      : "r"(a0), "r"(a1), "r"(a2), "r"(a3), "r"(b0), "r"(b1));
}
template <int N>
__device__ __forceinline__ void cs_frac(int idx, float& c, float& s) {
  int i = ((idx + N / 2) & (N - 1)) - N / 2;
  float a = (float)i * (6.283185307179586f / N);
  c = __cosf(a);
  s = __sinf(a);
}
template <int N>
__device__ __forceinline__ uint32_t cfrag(int idx, int ri) {
  float c, s;
  cs_frac<N>(idx, c, s);
  return ri ? pack2(-s, c) : pack2(c, s);
}
__device__ __forceinline__ uint32_t word(const uint4& v, int e) { return e == 0 ? v.x : e == 1 ? v.y : e == 2 ? v.z : v.w; }
__device__ __forceinline__ void cdft16(const uint4 (&q)[4], const uint4 (&F)[4], uint4 (&o)[4]) {
  float acc[2][4][4];
#pragma unroll
  for (int p = 0; p < 2; p++)
#pragma unroll
    for (int v = 0; v < 4; v++) {
      acc[p][v][0] = acc[p][v][1] = acc[p][v][2] = acc[p][v][3] = 0.f;
#pragma unroll
      for (int ks = 0; ks < 2; ks++)
        mma16816(acc[p][v], word(q[2 * ks], 2 * p), word(q[2 * ks], 2 * p + 1), word(q[2 * ks + 1], 2 * p),
                 word(q[2 * ks + 1], 2 * p + 1), word(F[ks * 2 + (v >> 1)], (v & 1) * 2), word(F[ks * 2 + (v >> 1)], (v & 1) * 2 + 1));
    }
#pragma unroll
  for (int v = 0; v < 4; v++)
    o[v] = make_uint4(pack2(acc[0][v][0], acc[0][v][1]), pack2(acc[0][v][2], acc[0][v][3]),
                      pack2(acc[1][v][0], acc[1][v][1]), pack2(acc[1][v][2], acc[1][v][3]));
}
__device__ __forceinline__ void st_tag(uint4* p, const uint4& v, uint32_t tag) {
  asm volatile("{.reg .b128 r; .reg .b64 a, b; mov.b64 a, {%1,%2}; mov.b64 b, {%3,%4}; mov.b128 r, {a,b}; st.relaxed.gpu.global.b128 [%0], r;}"
               ::"l"(p), "r"((v.x & ~1u) | tag), "r"(v.y), "r"(v.z), "r"(v.w) : "memory");
}
__device__ __forceinline__ void st_tag_p(int en, uint4* p, const uint4& v, uint32_t tag) {
  asm volatile("{.reg .b128 r; .reg .b64 a, b; .reg .pred q; setp.ne.b32 q, %5, 0; mov.b64 a, {%1,%2}; mov.b64 b, {%3,%4}; mov.b128 r, {a,b};\n"
               "@q st.relaxed.gpu.global.b128 [%0], r;}"
               ::"l"(p), "r"((v.x & ~1u) | tag), "r"(v.y), "r"(v.z), "r"(v.w), "r"(en) : "memory");
}
__device__ __forceinline__ void sts4_p(int en, uint32_t a, uint32_t x, uint32_t y, uint32_t z, uint32_t w) {
  asm volatile("{.reg .pred q; setp.ne.b32 q, %5, 0; @q st.shared.v4.u32 [%0], {%1,%2,%3,%4};}"
               ::"r"(a), "r"(x), "r"(y), "r"(z), "r"(w), "r"(en) : "memory");
}
__device__ __forceinline__ uint4 ld_b128(const uint4* p) {
  uint4 v;
  asm volatile("{.reg .b128 r; .reg .b64 a, b; ld.relaxed.gpu.global.b128 r, [%4]; mov.b128 {a,b}, r; mov.b64 {%0,%1}, a; mov.b64 {%2,%3}, b;}"
               : "=r"(v.x), "=r"(v.y), "=r"(v.z), "=r"(v.w) : "l"(p) : "memory");
  return v;
}
template <int STRIDE>
__device__ __forceinline__ void ld_tag4_issue(uint4 (&q)[4], const uint4* p) {
#pragma unroll
  for (int i = 0; i < 4; i++) q[i] = ld_b128(p + i * STRIDE);
}
template <int STRIDE>
__device__ __forceinline__ void ld_tag4_finish(uint4 (&q)[4], const uint4* p, uint32_t tag) {
  int it = 0;
#pragma unroll 1
  while (__any_sync(0xffffffffu, ((q[0].x ^ tag) | (q[1].x ^ tag) | (q[2].x ^ tag) | (q[3].x ^ tag)) & 1u)) {
    ld_tag4_issue<STRIDE>(q, p);
    if (++it > SPIN_LIMIT) { die(); break; }
  }
#pragma unroll
  for (int i = 0; i < 4; i++) asm volatile("and.b32 %0, %0, 0xfffffffe;" : "+r"(q[i].x));
}
__device__ __forceinline__ void row_stats(const uint32_t (&a)[8], const uint32_t (&b)[8], int lane, float (&sum)[2], float (&sq)[2]) {
  float da[4] = {0.f, 0.f, 0.f, 0.f}, db[4] = {0.f, 0.f, 0.f, 0.f}, ds[4] = {0.f, 0.f, 0.f, 0.f};
#pragma unroll
  for (int q = 0; q < 4; q++) {
    mma16816(ds, a[2 * q], b[2 * q], a[2 * q + 1], b[2 * q + 1], 0x3f803f80u, 0x3f803f80u);
    mma16816(da, a[2 * q], b[2 * q], a[2 * q + 1], b[2 * q + 1], a[2 * q], a[2 * q + 1]);
    mma16816(db, a[2 * q], b[2 * q], a[2 * q + 1], b[2 * q + 1], b[2 * q], b[2 * q + 1]);
  }
  const int src = (lane & 28) | (lane >> 3);
  const float qa = __shfl_sync(0xffffffffu, (lane & 4) ? da[1] : da[0], src);
  const float qb = __shfl_sync(0xffffffffu, (lane & 4) ? db[3] : db[2], src);
  float v = (lane & 2) ? ((lane & 1) ? ds[2] : ds[0]) : ((lane & 1) ? qb : qa);
  v += __shfl_xor_sync(0xffffffffu, v, 4);
  v += __shfl_xor_sync(0xffffffffu, v, 8);
  v += __shfl_xor_sync(0xffffffffu, v, 16);
  sq[0] = __shfl_sync(0xffffffffu, v, 0);
  sq[1] = __shfl_sync(0xffffffffu, v, 1);
  sum[0] = __shfl_sync(0xffffffffu, v, 2);
  sum[1] = __shfl_sync(0xffffffffu, v, 3);
}
__device__ __forceinline__ uint64_t desc64(uint32_t lo, uint32_t hi) {
  uint64_t d;
  asm("mov.b64 %0, {%1, %2};" : "=l"(d) : "r"(lo), "r"(hi));
  return d;
}
constexpr uint32_t desc_hi(uint32_t sbo, uint32_t swz) { return (sbo >> 4) | (swz << 30); }
__device__ __forceinline__ uint32_t desc_lo(uint32_t addr, uint32_t lbo) { return ((addr & 0x3FFFF) >> 4) | ((lbo >> 4) << 16); }
__device__ __forceinline__ void cp_async16(uint32_t dst, const void* src) {
  asm volatile("cp.async.cg.shared.global [%0], [%1], 16;" ::"r"(dst), "l"(src) : "memory");
}
__device__ __forceinline__ uint2 lds2(uint32_t a) {
  uint2 v;
  asm volatile("ld.shared.v2.u32 {%0,%1}, [%2];" : "=r"(v.x), "=r"(v.y) : "r"(a) : "memory");
  return v;
}
__device__ __forceinline__ uint32_t lds_u16(uint32_t a) {
  uint16_t v;
  asm volatile("ld.shared.u16 %0, [%1];" : "=h"(v) : "r"(a) : "memory");
  return v;
}
__device__ __forceinline__ void wg_fence() { asm volatile("wgmma.fence.sync.aligned;" ::: "memory"); }
__device__ __forceinline__ void wg_commit() { asm volatile("wgmma.commit_group.sync.aligned;" ::: "memory"); }
template <int N>
__device__ __forceinline__ void wg_wait() { asm volatile("wgmma.wait_group.sync.aligned %0;" ::"n"(N) : "memory"); }
__device__ __forceinline__ void bulk_load(uint32_t dst, const void* src, int bytes, uint32_t bar) {
  asm volatile("cp.async.bulk.shared::cluster.global.mbarrier::complete_tx::bytes [%0], [%1], %2, [%3];"
               ::"r"(dst), "l"(src), "r"(bytes), "r"(bar) : "memory");
}
__device__ __forceinline__ void bulk_load_mc(uint32_t dst, const void* src, int bytes, uint32_t bar) {
  asm volatile("cp.async.bulk.shared::cluster.global.mbarrier::complete_tx::bytes.multicast::cluster [%0], [%1], %2, [%3], %4;"
               ::"r"(dst), "l"(src), "r"(bytes), "r"(bar), "h"((uint16_t)3) : "memory");
}
__device__ __forceinline__ void tma3(uint32_t dst, const CUtensorMap* tm, uint32_t bar, int c0, int c1, int c2) {
  asm volatile("cp.async.bulk.tensor.3d.shared::cluster.global.mbarrier::complete_tx::bytes [%0], [%1, {%3,%4,%5}], [%2];"
               ::"r"(dst), "l"(tm), "r"(bar), "r"(c0), "r"(c1), "r"(c2) : "memory");
}
__device__ __forceinline__ void tma3_mc(uint32_t dst, const CUtensorMap* tm, uint32_t bar, int c1, int c2) {
  asm volatile("cp.async.bulk.tensor.3d.shared::cluster.global.mbarrier::complete_tx::bytes.multicast::cluster [%0], [%1, {%3,%4,%5}], [%2], %6;"
               ::"r"(dst), "l"(tm), "r"(bar), "r"(0), "r"(c1), "r"(c2), "h"((uint16_t)3) : "memory");
}
__device__ __forceinline__ void mbar_arrive_remote(uint32_t rb) {
  asm volatile("mbarrier.arrive.shared::cluster.b64 _, [%0];" ::"r"(rb) : "memory");
}
__device__ __forceinline__ uint4 ldg_ca4_p(int en, const void* p) {
  uint4 v;
  asm volatile("{.reg .pred q; setp.ne.b32 q, %5, 0; @q ld.global.ca.v4.u32 {%0,%1,%2,%3}, [%4];}"
               : "=r"(v.x), "=r"(v.y), "=r"(v.z), "=r"(v.w) : "l"(p), "r"(en) : "memory");
  return v;
}
__device__ __forceinline__ uint32_t clock32() {
  uint32_t v;
  asm volatile("mov.u32 %0, %%clock;" : "=r"(v) :: "memory");
  return v;
}
__device__ __forceinline__ float swiglu(float g, float u, float r) {
  float hg = (0.5f * r) * g, th;
  asm("tanh.approx.f32 %0, %1;" : "=f"(th) : "f"(hg));
  return fmaf(hg, th, hg) * (r * u);
}
__device__ __forceinline__ uint32_t hsub2_bf16(uint32_t a, uint32_t b) {
  uint32_t r;
  asm("sub.rn.bf16x2 %0, %1, %2;" : "=r"(r) : "r"(a), "r"(b));
  return r;
}
__device__ __forceinline__ void l2_prefetch(const void* p, int bytes) {
  asm volatile("cp.async.bulk.prefetch.L2.global [%0], %1;" ::"l"(p), "r"(bytes) : "memory");
}

__device__ __forceinline__ void wgmma_n256(float (&d)[128], uint64_t da, uint64_t db, int sd = 1) {
  asm volatile("{.reg .pred p; setp.ne.b32 p, %130, 0;\n"
      "wgmma.mma_async.sync.aligned.m64n256k16.f32.bf16.bf16 {"
      "%0,%1,%2,%3,%4,%5,%6,%7,%8,%9,%10,%11,%12,%13,%14,%15,"
      "%16,%17,%18,%19,%20,%21,%22,%23,%24,%25,%26,%27,%28,%29,%30,%31,"
      "%32,%33,%34,%35,%36,%37,%38,%39,%40,%41,%42,%43,%44,%45,%46,%47,"
      "%48,%49,%50,%51,%52,%53,%54,%55,%56,%57,%58,%59,%60,%61,%62,%63,"
      "%64,%65,%66,%67,%68,%69,%70,%71,%72,%73,%74,%75,%76,%77,%78,%79,"
      "%80,%81,%82,%83,%84,%85,%86,%87,%88,%89,%90,%91,%92,%93,%94,%95,"
      "%96,%97,%98,%99,%100,%101,%102,%103,%104,%105,%106,%107,%108,%109,%110,%111,"
      "%112,%113,%114,%115,%116,%117,%118,%119,%120,%121,%122,%123,%124,%125,%126,%127"
      "}, %128, %129, p, 1, 1, 0, 1;}\n"
      : "+f"(d[0]),"+f"(d[1]),"+f"(d[2]),"+f"(d[3]),"+f"(d[4]),"+f"(d[5]),"+f"(d[6]),"+f"(d[7]),
        "+f"(d[8]),"+f"(d[9]),"+f"(d[10]),"+f"(d[11]),"+f"(d[12]),"+f"(d[13]),"+f"(d[14]),"+f"(d[15]),
        "+f"(d[16]),"+f"(d[17]),"+f"(d[18]),"+f"(d[19]),"+f"(d[20]),"+f"(d[21]),"+f"(d[22]),"+f"(d[23]),
        "+f"(d[24]),"+f"(d[25]),"+f"(d[26]),"+f"(d[27]),"+f"(d[28]),"+f"(d[29]),"+f"(d[30]),"+f"(d[31]),
        "+f"(d[32]),"+f"(d[33]),"+f"(d[34]),"+f"(d[35]),"+f"(d[36]),"+f"(d[37]),"+f"(d[38]),"+f"(d[39]),
        "+f"(d[40]),"+f"(d[41]),"+f"(d[42]),"+f"(d[43]),"+f"(d[44]),"+f"(d[45]),"+f"(d[46]),"+f"(d[47]),
        "+f"(d[48]),"+f"(d[49]),"+f"(d[50]),"+f"(d[51]),"+f"(d[52]),"+f"(d[53]),"+f"(d[54]),"+f"(d[55]),
        "+f"(d[56]),"+f"(d[57]),"+f"(d[58]),"+f"(d[59]),"+f"(d[60]),"+f"(d[61]),"+f"(d[62]),"+f"(d[63]),
        "+f"(d[64]),"+f"(d[65]),"+f"(d[66]),"+f"(d[67]),"+f"(d[68]),"+f"(d[69]),"+f"(d[70]),"+f"(d[71]),
        "+f"(d[72]),"+f"(d[73]),"+f"(d[74]),"+f"(d[75]),"+f"(d[76]),"+f"(d[77]),"+f"(d[78]),"+f"(d[79]),
        "+f"(d[80]),"+f"(d[81]),"+f"(d[82]),"+f"(d[83]),"+f"(d[84]),"+f"(d[85]),"+f"(d[86]),"+f"(d[87]),
        "+f"(d[88]),"+f"(d[89]),"+f"(d[90]),"+f"(d[91]),"+f"(d[92]),"+f"(d[93]),"+f"(d[94]),"+f"(d[95]),
        "+f"(d[96]),"+f"(d[97]),"+f"(d[98]),"+f"(d[99]),"+f"(d[100]),"+f"(d[101]),"+f"(d[102]),"+f"(d[103]),
        "+f"(d[104]),"+f"(d[105]),"+f"(d[106]),"+f"(d[107]),"+f"(d[108]),"+f"(d[109]),"+f"(d[110]),"+f"(d[111]),
        "+f"(d[112]),"+f"(d[113]),"+f"(d[114]),"+f"(d[115]),"+f"(d[116]),"+f"(d[117]),"+f"(d[118]),"+f"(d[119]),
        "+f"(d[120]),"+f"(d[121]),"+f"(d[122]),"+f"(d[123]),"+f"(d[124]),"+f"(d[125]),"+f"(d[126]),"+f"(d[127])
      : "l"(da), "l"(db), "r"(sd));
}
__device__ __forceinline__ void wgmma_n192(float (&d)[96], uint64_t da, uint64_t db) {
  asm volatile("wgmma.mma_async.sync.aligned.m64n192k16.f32.bf16.bf16 {"
      "%0,%1,%2,%3,%4,%5,%6,%7,%8,%9,%10,%11,%12,%13,%14,%15,"
      "%16,%17,%18,%19,%20,%21,%22,%23,%24,%25,%26,%27,%28,%29,%30,%31,"
      "%32,%33,%34,%35,%36,%37,%38,%39,%40,%41,%42,%43,%44,%45,%46,%47,"
      "%48,%49,%50,%51,%52,%53,%54,%55,%56,%57,%58,%59,%60,%61,%62,%63,"
      "%64,%65,%66,%67,%68,%69,%70,%71,%72,%73,%74,%75,%76,%77,%78,%79,"
      "%80,%81,%82,%83,%84,%85,%86,%87,%88,%89,%90,%91,%92,%93,%94,%95"
      "}, %96, %97, 1, 1, 1, 0, 1;\n"
      : "+f"(d[0]),"+f"(d[1]),"+f"(d[2]),"+f"(d[3]),"+f"(d[4]),"+f"(d[5]),"+f"(d[6]),"+f"(d[7]),
        "+f"(d[8]),"+f"(d[9]),"+f"(d[10]),"+f"(d[11]),"+f"(d[12]),"+f"(d[13]),"+f"(d[14]),"+f"(d[15]),
        "+f"(d[16]),"+f"(d[17]),"+f"(d[18]),"+f"(d[19]),"+f"(d[20]),"+f"(d[21]),"+f"(d[22]),"+f"(d[23]),
        "+f"(d[24]),"+f"(d[25]),"+f"(d[26]),"+f"(d[27]),"+f"(d[28]),"+f"(d[29]),"+f"(d[30]),"+f"(d[31]),
        "+f"(d[32]),"+f"(d[33]),"+f"(d[34]),"+f"(d[35]),"+f"(d[36]),"+f"(d[37]),"+f"(d[38]),"+f"(d[39]),
        "+f"(d[40]),"+f"(d[41]),"+f"(d[42]),"+f"(d[43]),"+f"(d[44]),"+f"(d[45]),"+f"(d[46]),"+f"(d[47]),
        "+f"(d[48]),"+f"(d[49]),"+f"(d[50]),"+f"(d[51]),"+f"(d[52]),"+f"(d[53]),"+f"(d[54]),"+f"(d[55]),
        "+f"(d[56]),"+f"(d[57]),"+f"(d[58]),"+f"(d[59]),"+f"(d[60]),"+f"(d[61]),"+f"(d[62]),"+f"(d[63]),
        "+f"(d[64]),"+f"(d[65]),"+f"(d[66]),"+f"(d[67]),"+f"(d[68]),"+f"(d[69]),"+f"(d[70]),"+f"(d[71]),
        "+f"(d[72]),"+f"(d[73]),"+f"(d[74]),"+f"(d[75]),"+f"(d[76]),"+f"(d[77]),"+f"(d[78]),"+f"(d[79]),
        "+f"(d[80]),"+f"(d[81]),"+f"(d[82]),"+f"(d[83]),"+f"(d[84]),"+f"(d[85]),"+f"(d[86]),"+f"(d[87]),
        "+f"(d[88]),"+f"(d[89]),"+f"(d[90]),"+f"(d[91]),"+f"(d[92]),"+f"(d[93]),"+f"(d[94]),"+f"(d[95])
      : "l"(da), "l"(db));
}
template <int SD>
__device__ __forceinline__ void wgmma_rs_n128(float (&d)[64], uint32_t a0, uint32_t a1, uint32_t a2, uint32_t a3, uint64_t db) {
  asm volatile("wgmma.mma_async.sync.aligned.m64n128k16.f32.bf16.bf16 {"
      "%0,%1,%2,%3,%4,%5,%6,%7,%8,%9,%10,%11,%12,%13,%14,%15,"
      "%16,%17,%18,%19,%20,%21,%22,%23,%24,%25,%26,%27,%28,%29,%30,%31,"
      "%32,%33,%34,%35,%36,%37,%38,%39,%40,%41,%42,%43,%44,%45,%46,%47,"
      "%48,%49,%50,%51,%52,%53,%54,%55,%56,%57,%58,%59,%60,%61,%62,%63"
      "}, {%64,%65,%66,%67}, %68, %69, 1, 1, 1;\n"
      : "+f"(d[0]),"+f"(d[1]),"+f"(d[2]),"+f"(d[3]),"+f"(d[4]),"+f"(d[5]),"+f"(d[6]),"+f"(d[7]),
        "+f"(d[8]),"+f"(d[9]),"+f"(d[10]),"+f"(d[11]),"+f"(d[12]),"+f"(d[13]),"+f"(d[14]),"+f"(d[15]),
        "+f"(d[16]),"+f"(d[17]),"+f"(d[18]),"+f"(d[19]),"+f"(d[20]),"+f"(d[21]),"+f"(d[22]),"+f"(d[23]),
        "+f"(d[24]),"+f"(d[25]),"+f"(d[26]),"+f"(d[27]),"+f"(d[28]),"+f"(d[29]),"+f"(d[30]),"+f"(d[31]),
        "+f"(d[32]),"+f"(d[33]),"+f"(d[34]),"+f"(d[35]),"+f"(d[36]),"+f"(d[37]),"+f"(d[38]),"+f"(d[39]),
        "+f"(d[40]),"+f"(d[41]),"+f"(d[42]),"+f"(d[43]),"+f"(d[44]),"+f"(d[45]),"+f"(d[46]),"+f"(d[47]),
        "+f"(d[48]),"+f"(d[49]),"+f"(d[50]),"+f"(d[51]),"+f"(d[52]),"+f"(d[53]),"+f"(d[54]),"+f"(d[55]),
        "+f"(d[56]),"+f"(d[57]),"+f"(d[58]),"+f"(d[59]),"+f"(d[60]),"+f"(d[61]),"+f"(d[62]),"+f"(d[63])
      : "r"(a0), "r"(a1), "r"(a2), "r"(a3), "l"(db), "n"(SD));
}

constexpr int C_LN = 0, C_PX = 16, C_PY = 32;
constexpr int NB_CONS = 1, NB_LN = 2, NB_LAG = 4, NB_INIT = 6, NB_RDY = 7;
#define LAGX 3
#define LAGY 3
#define LAG2 5
#define NLL 2
#define POLL_DELAY3 900
#define POLL_DELAY 1100
#define FILT_DELAY 1000
#define THR_B 0
#define THR_P 0
#define SPEC -1
#define WARM 4
#define HWARM 0
#define DRY 1
#define RING_SIG 1
#define PF2_SIG 1
constexpr int SM_E = 0, SM_X = 16384, SM_E2 = 32768, SM_W = 49152, SM_FC = 69632, SM_T = 73728 - T1_BYTES;
constexpr unsigned long long KORDER = 0xBA9432DC876510ull;
constexpr unsigned long long BSLOT = 0x76532107653210ull, PSLOT = 0xDCBA984DCBA984ull;
constexpr uint32_t HI128 = desc_hi(1024, 1), HI64 = desc_hi(512, 2);

struct Bars {
  uint64_t full1[32], empty1[32], full2[16], fullA[8], empty2[8], fullP[16], emptyP[8], hbar, tbar, hint[3], sig[2], sbar;
  uint32_t epoch;
};

template <int NK, bool STORE>
__device__ __forceinline__ void make_p(const float (&acc)[NK * 16], float r0, float r1, uint4 (&p)[NK], uint4* pbase, int ks0, uint32_t tag) {
#pragma unroll
  for (int j = 0; j < NK; j++) {
    uint32_t w[4];
#pragma unroll
    for (int i = 0; i < 4; i++) {
      const int a = 8 * j + 2 * i, b = a + NK * 8;
      w[i] = pack2(swiglu(acc[a], acc[b], (i & 1) ? r1 : r0), swiglu(acc[a + 1], acc[b + 1], (i & 1) ? r1 : r0));
    }
    asm volatile("" : "+r"(w[0]), "+r"(w[1]), "+r"(w[2]), "+r"(w[3]));
    p[j] = make_uint4(w[0], w[1], w[2], w[3]);
    if (STORE) st_tag(pbase + ((ks0 + j) >> 2) * 1024 + ((ks0 + j) & 3) * 32, p[j], tag);
  }
}
__device__ __forceinline__ void spin_cycles(uint32_t n) {
  const uint32_t t0 = clock32();
  while (clock32() - t0 < n) {}
}

__device__ __forceinline__ void spin_until(uint32_t t) {
  float d[4] = {0.f, 0.f, 0.f, 0.f};
  while ((int)(clock32() - t) < 0) {
    if (HWARM) asm volatile("mma.sync.aligned.m16n8k16.row.col.f32.bf16.bf16.f32 {%0,%1,%2,%3}, {%4,%4,%4,%4}, {%4,%4}, {%0,%1,%2,%3};"
                            : "+f"(d[0]), "+f"(d[1]), "+f"(d[2]), "+f"(d[3]) : "r"(t));
  }
}

__global__ void __cluster_dims__(2, 1, 1) __launch_bounds__(NTHREADS, 1)
fused_kernel(const __nv_bfloat16* __restrict__ x, const Tables* __restrict__ tab, Scratch* __restrict__ scr,
             __nv_bfloat16* __restrict__ out, const char* __restrict__ wg_raw, const char* __restrict__ wu_raw,
             const char* __restrict__ wd_raw,
             const __grid_constant__ CUtensorMap tmWR, const __grid_constant__ CUtensorMap tmWI,
             const __grid_constant__ CUtensorMap tmGX, const __grid_constant__ CUtensorMap tmUX,
             const __grid_constant__ CUtensorMap tmGY, const __grid_constant__ CUtensorMap tmUY,
             const __grid_constant__ CUtensorMap tmD) {
  extern __shared__ __align__(1024) char smem_raw[];
  const uint32_t sbase = s2u(smem_raw);
  const uint32_t sbar = sbase + 14 * SLOT, sstat = sbar + 1280;
  const int tid = threadIdx.x, lane = tid & 31;
  const int c = blockIdx.x, rk = c & 1, f = (c >> 1) & 7, rb = 2 * (c >> 4) + rk;
  const int rb2 = 2 * (c >> 4) + (f >> 2), kh = (f >> 1) & 1, nq = 2 * (f & 1) + rk;
#define BAR(field, i) (sbar + (uint32_t)offsetof(Bars, field) + 8u * (i))
#define TOFF(field) (sbase + SM_T + (uint32_t)offsetof(Tables, field) + lane * 16)

  uint32_t tag = 0;
  if (tid < 256 || (DRY && tid >= 352)) {
    const int wfull = __shfl_sync(0xffffffffu, tid >> 5, 0), warp = wfull & 7, en = wfull < 8;
    const int g = lane >> 2, t = lane & 3;
    PROF(0);
    PROFG(14);
#pragma unroll
    for (int i = 0; i < 4; i++) {
      const int r = i >> 1, ch = (i & 1) * 32 + lane;
      if (en) cp_async16(sbase + SM_X + (2 * warp + r) * 1024 + ((ch ^ ((ch >> 2) & 6)) * 16),
                 x + (size_t)(c + 128 * (2 * warp + r)) * 512 + ch * 8);
    }
    asm volatile("cp.async.commit_group;" ::: "memory");
    if (en) asm volatile("barrier.cluster.arrive.relaxed.aligned;" ::: "memory");
    uint4 tw[8], fb[16];
    const uint4 fa = ldg_ca4_p(en, &tab->fa[lane][0]);
#pragma unroll
    for (int i = 0; i < 8; i++) tw[i] = ldg_ca4_p(en, &tab->tw1[i][lane][0]);
#pragma unroll
    for (int i = 0; i < 16; i++) fb[i] = ldg_ca4_p(en, &tab->fb[i][lane][0]);
    if (en) {
      const int ln = (tid >> 1) & 31, lg = ln >> 2, lt = ln & 3, i = 4 * (tid >> 6) + 2 * (tid & 1);
      const int kidx = lt + 8 * (i >> 3), nidx = 4 * ((i >> 1) & 3) + (lg >> 1);
      const uint32_t a0 = cfrag<2048>((c + 128 * kidx) * nidx, lg & 1), a1 = cfrag<2048>((c + 128 * (kidx + 4)) * nidx, lg & 1);
      const uint32_t b0 = cfrag<2048>(-(c + 128 * nidx) * kidx, lg & 1), b1 = cfrag<2048>(-(c + 128 * nidx) * (kidx + 4), lg & 1);
      asm volatile("st.shared.v2.u32 [%0], {%1,%2};" ::"r"(sbase + SM_FC + tid * 8), "r"(a0), "r"(a1) : "memory");
      asm volatile("st.shared.v2.u32 [%0], {%1,%2};" ::"r"(sbase + SM_FC + 2048 + tid * 8), "r"(b0), "r"(b1) : "memory");
    }
    asm volatile("cp.async.wait_group 0;" ::: "memory");
    __syncwarp();
    if (en) bar_arrive(NB_INIT, 384);
    PROF(13);
    uint4 q[4], o[4];
    {
      uint32_t v[2][8];
#pragma unroll
      for (int r = 0; r < 2; r++)
#pragma unroll
        for (int q = 0; q < 4; q++) {
          const uint2 u = lds2(sbase + SM_X + (2 * warp + r) * 1024 + (t + 4 * (q >> 1)) * 128 + (((4 * (q & 1) + (g >> 1)) ^ (2 * t)) * 16) + (g & 1) * 8);
          v[r][2 * q] = u.x; v[r][2 * q + 1] = u.y;
        }
      float sum[2], sq[2], rstd[2];
      row_stats(v[0], v[1], lane, sum, sq);
#pragma unroll
      for (int r = 0; r < 2; r++) {
        const float m = sum[r] * (1.f / 512.f);
        rstd[r] = rsqrtf(fmaxf(fmaf(-m, m, sq[r] * (1.f / 512.f)), 0.f) + 1e-5f);
      }
      uint32_t alo[4][4], ahi[4][4];
#pragma unroll
      for (int r = 0; r < 2; r++)
#pragma unroll
        for (int i = 0; i < 4; i++) {
          const uint32_t sel = (i & 1) ? 0x7632u : 0x5410u;
          const uint32_t b0 = __byte_perm(v[r][i >> 1], v[r][2 + (i >> 1)], sel);
          const uint32_t b1 = __byte_perm(v[r][4 + (i >> 1)], v[r][6 + (i >> 1)], sel);
          float d[4] = {0.f, 0.f, 0.f, 0.f};
          mma16816(d, fa.x, fa.y, fa.z, fa.w, b0, b1);
          const uint4 &ka = tw[2 * i], &kb = tw[2 * i + 1];
          const uint32_t re = pack2(d[0] * __uint_as_float(ka.x) + d[2] * __uint_as_float(ka.y), d[1] * __uint_as_float(kb.x) + d[3] * __uint_as_float(kb.y));
          const uint32_t im = pack2(d[0] * __uint_as_float(ka.z) + d[2] * __uint_as_float(ka.w), d[1] * __uint_as_float(kb.z) + d[3] * __uint_as_float(kb.w));
          const uint32_t dc = pack2(fmaf(sum[r], -1.f / 32.f, d[0]), fmaf(sum[r], -1.f / 32.f, d[1]));
          alo[i][r] = re; alo[i][2 + r] = im;
          ahi[i][r] = g == 0 ? dc : re; ahi[i][2 + r] = g == 0 ? 0u : im;
        }
      float acc[8][4];
#pragma unroll
      for (int u = 0; u < 8; u++) {
        acc[u][0] = acc[u][1] = acc[u][2] = acc[u][3] = 0.f;
#pragma unroll
        for (int i = 0; i < 4; i++) {
          const uint4& bq = fb[i * 4 + (u >> 1)];
          if (u < 4) mma16816(acc[u], alo[i][0], alo[i][1], alo[i][2], alo[i][3], (u & 1) ? bq.z : bq.x, (u & 1) ? bq.w : bq.y);
          else       mma16816(acc[u], ahi[i][0], ahi[i][1], ahi[i][2], ahi[i][3], (u & 1) ? bq.z : bq.x, (u & 1) ? bq.w : bq.y);
        }
      }
#pragma unroll
      for (int r = 0; r < 2; r++)
#pragma unroll
        for (int h = 0; h < 2; h++) {
          const int j = 2 * warp + r, m = 2 * t + h;
          const float rs = rstd[r];
          sts4_p(en, sbase + SM_E + ((j * 8 + m) * 8 + (g ^ (2 * t) ^ (2 * (j & 3)))) * 16,
               pack2(acc[2 * h][2 * r] * rs, acc[2 * h][2 * r + 1] * rs), pack2(acc[2 * h + 1][2 * r] * rs, acc[2 * h + 1][2 * r + 1] * rs),
               pack2(acc[4 + 2 * h][2 * r] * rs, acc[4 + 2 * h][2 * r + 1] * rs), pack2(acc[5 + 2 * h][2 * r] * rs, acc[5 + 2 * h][2 * r + 1] * rs));
        }
      if (tid == 0) PROFP(12);
      if (en) bar_sync(NB_RDY, 352);
      if (tid == 0) PROFP(13);
      uint4 fc[4];
#pragma unroll
      for (int i = 0; i < 4; i++) fc[i] = lds4(sbase + SM_FC + i * 512 + lane * 16);
      asm volatile("ld.shared.u32 %0, [%1];" : "=r"(tag) : "r"(BAR(epoch, 0)) : "memory");
      tag = (tag + 1) & 1;
#pragma unroll
      for (int i = 0; i < 4; i++) q[i] = lds4(sbase + SM_E + (((t + 4 * i) * 8 + warp) * 8 + (g ^ (warp & 6) ^ (2 * t))) * 16);
      cdft16(q, fc, o);
#pragma unroll
      for (int vv = 0; vv < 4; vv++) st_tag_p(en, &scr->Z1[(((4 * vv + t) * 8 + warp) * 128 + c) * 8 + g], o[vv], tag);
    }
  }
  if (tid >= 256) {
    asm volatile("setmaxnreg.dec.sync.aligned.u32 56;");
    const int warp = __shfl_sync(0xffffffffu, tid >> 5, 0);
    if (lane == 0) {
      if (warp == 8) {
        if (sbase & 1023) die();
#pragma unroll
        for (int i = 0; i < 16; i++) mbar_init(BAR(emptyP, i), i < 7 ? 16 : i < 8 ? 8 : i < 13 ? 1 : i < 15 ? 8 : 32);
        mbar_expect(BAR(tbar, 0), T2_BYTES + 2 * 10240);
        mbar_expect(BAR(hbar, 0), 16384);
#pragma unroll
        for (int i = 0; i < 32; i++) mbar_init(BAR(full2, i), i < 24 ? 1 : 8);
#pragma unroll
        for (int i = 0; i < 24; i++) mbar_expect(BAR(full2, i), 16384);
      } else if (warp == 9) {
#pragma unroll
        for (int i = 0; i < 32; i++) mbar_init(BAR(full1, i), 1);
#pragma unroll
        for (int i = 0; i < 32; i++) mbar_expect(BAR(full1, i), i < 16 ? 16384 : 12288);
      } else if (warp == 10) {
#pragma unroll
        for (int i = 0; i < 32; i++) mbar_init(BAR(empty1, i), 16);
#pragma unroll
        for (int i = 0; i < 14; i++) mbar_init(BAR(fullP, i), 1);
#pragma unroll
        for (int i = 0; i < 14; i++) mbar_expect(BAR(fullP, i), 16384);
      }
      asm volatile("fence.mbarrier_init.release.cluster;" ::: "memory");
    }
    if (tid == 256) {
      const int w0 = ((c >> 3) * 257 + 32 * (c & 7) + 1) & ~7;
      if (FILT_DELAY) {
        asm volatile("prefetch.tensormap [%0];" ::"l"(&tmWR) : "memory");
        asm volatile("prefetch.tensormap [%0];" ::"l"(&tmWI) : "memory");
        spin_cycles(FILT_DELAY);
      }
      tma3(sbase + SM_W, &tmWR, BAR(tbar, 0), w0, 0, 0);
      tma3(sbase + SM_W + 10240, &tmWI, BAR(tbar, 0), w0, 0, 0);
      bulk_load(sbase + SM_T + T1_BYTES, reinterpret_cast<const char*>(tab) + T1_BYTES, T2_BYTES, BAR(tbar, 0));
    }
    if (tid == 288) {
      asm volatile("prefetch.tensormap [%0];" ::"l"(rk ? &tmUX : &tmGX) : "memory");
      asm volatile("prefetch.tensormap [%0];" ::"l"(rk ? &tmUY : &tmGY) : "memory");
      asm volatile("prefetch.tensormap [%0];" ::"l"(&tmD) : "memory");
    }
    if (tid == 320) {
      const unsigned e = ld_relaxed(&scr->cnt[(C_LN + rb) * 32]) >> 3;
      asm volatile("st.shared.u32 [%0], %1;" ::"r"(BAR(epoch, 0)), "r"(e) : "memory");
    }
    __syncwarp();
    asm volatile("barrier.cluster.arrive.relaxed.aligned;" ::: "memory");
    if (warp != 11) bar_arrive(NB_RDY, 352);
    asm volatile("barrier.cluster.wait.aligned;" ::: "memory");
    bar_sync(NB_INIT, 384);
    unsigned epoch;
    asm volatile("ld.shared.u32 %0, [%1];" : "=r"(epoch) : "r"(BAR(epoch, 0)) : "memory");
    if (warp == 8) {
      if (lane == 0) {
        const int ax = (7 * f + 3 * (f & 1)) >> 1;
        const int ay = 7 * f + ((f & 1) ? 0 : 4);
        const CUtensorMap* tx = rk ? &tmUX : &tmGX;
        const CUtensorMap* ty = rk ? &tmUY : &tmGY;
        if (RING_SIG >= 0) mbar_wait(BAR(sig, RING_SIG));
        uint32_t s = 2;
#pragma unroll 1
        for (int n = 0; n < 16; n++) {
          if (n >= 6) mbar_wait(BAR(empty1, n - 6));
          tma3_mc(sbase + (8 + s) * SLOT + rk * 8192, tx, BAR(full1, n), n * 32, ax);
          if (++s == 6) s = 0;
        }
#pragma unroll 1
        for (int k = 0; k < 16; k++) {
          mbar_wait(BAR(empty1, k < 8 ? 10 + ((12 * k + 11) >> 4) : 8 + k));
          tma3_mc(sbase + 8 * SLOT + (k & 7) * 12288 + rk * 6144, ty, BAR(full1, 16 + k), k * 32, ay);
        }
      }
    } else if (warp == 9) {
      if (lane == 0) {
#pragma unroll 1
        for (int i = 0; i < 14; i++) {
          const int kblk = 14 * kh + (int)((KORDER >> (4 * i)) & 15);
          const int j = i < 7 ? i : i - 7, sl = j + (j >= 4);
          mbar_wait(i < 7 ? BAR(empty1, 17 + 2 * sl) : BAR(empty2, j));
          if (THR_B && i >= THR_B) mbar_wait(BAR(full2, i - THR_B));
          tma3(sbase + sl * SLOT, &tmD, BAR(full2, i), 0, 64 * kblk, 2 * nq);
        }
        wait_counter(&scr->cnt[(C_LN + rb2) * 32], (epoch + 1) * 8);
        asm volatile("fence.proxy.async.global;" ::: "memory");
        mbar_wait(BAR(emptyP, 7));
        bulk_load(sbase + 4 * SLOT, &scr->LN[(rb2 * 8 + 2 * nq) * 1024 + (kh ^ 1) * 512], 8192, BAR(hbar, 0));
        bulk_load(sbase + 4 * SLOT + 8192, &scr->LN[(rb2 * 8 + 2 * nq + 1) * 1024 + (kh ^ 1) * 512], 8192, BAR(hbar, 0));
      }
    } else if (warp == 10) {
      bar_sync(NB_LN, 288);
      if (lane == 0) {
        PROFP(0);
        red_release(&scr->cnt[(C_LN + rb) * 32]);
        PROFP(1);
        wait_counter(&scr->cnt[(C_LN + rb) * 32], (epoch + 1) * 8);
        asm volatile("fence.proxy.async.global;" ::: "memory");
        PROFP(2);
#pragma unroll 1
        for (int kb = NLL; kb < 8; kb++) bulk_load(sbase + kb * SLOT, &scr->LN[(rb * 8 + kb) * 1024], 16384, BAR(fullA, kb));
#pragma unroll 1
        for (int s = 0; s < 14; s++) {
          const int kblk = 14 * kh + (int)((KORDER >> (4 * s)) & 15);
          if (s == 0 || (SPEC < 0 && (s == 8 || s == 11))) {
            if (s != 11) PROFP(3 + (s >> 2));
            mbar_wait(BAR(hint, s == 0 ? 0 : s == 8 ? 1 : 2), 0);
            if (s != 11) PROFP(4 + (s >> 2));
          }
          const int j = s < 7 ? s : s - 7;
          mbar_wait(s < 7 ? BAR(empty1, 24 + s + (s == 0) + (s >= 4)) : BAR(emptyP, j));
          if (THR_P && s >= THR_P) mbar_wait(BAR(fullP, s - THR_P));
          if (SPEC >= 0 && s == 8) mbar_wait(BAR(emptyP, SPEC & 7));
          bulk_load_mc(sbase + (j ? 7 + j : 4) * SLOT + rk * 8192, &scr->P[(rb2 * 28 + kblk) * 1024 + rk * 512], 8192, BAR(fullP, s));
        }
        PROFP(7);
      }
    } else {
      if (lane == 0) {
        l2_prefetch(wg_raw + (size_t)c * 5376, 5376);
        l2_prefetch(wu_raw + (size_t)c * 5376, 5376);
        mbar_wait(BAR(sig, PF2_SIG), 0);
        l2_prefetch(wg_raw + 688128 + (size_t)c * 8960, 8960);
        l2_prefetch(wu_raw + 688128 + (size_t)c * 8960, 8960);
      }
      mbar_wait(BAR(fullA, 7), 0);
      if (lane == 0) l2_prefetch(wd_raw + (size_t)c * 14336, 14336);
      {
        tag = (epoch + 1) & 1;
        uint4 v0, v1, v2;
        int it = 0;
        while (true) {
          v0 = ld_b128(&scr->ST[rb * 64 + lane]);
          v1 = ld_b128(&scr->ST[rb * 64 + 32 + lane]);
          v2 = ld_b128(&scr->ST[rb2 * 64 + 32 * (kh ^ 1) + lane]);
          if (!__any_sync(0xffffffffu, ((v0.x ^ tag) | (v1.x ^ tag) | (v2.x ^ tag)) & 1u)) break;
          if (++it > SPIN_LIMIT) { die(); break; }
        }
        sts4(sstat + lane * 16, v0.x & ~1u, v0.y, v0.z, v0.w);
        sts4(sstat + 512 + lane * 16, v1.x & ~1u, v1.y, v1.z, v1.w);
        sts4(sstat + 1024 + lane * 16, v2.x & ~1u, v2.y, v2.z, v2.w);
#pragma unroll 4
        for (int i = 0; i < 32; i++)
          st_tag(&scr->XP[(c ^ 4) * 1024 + i * 32 + lane], make_uint4(0, 0, 0, 0), tag ^ 1);
        mbar_arrive(BAR(sbar, 0));
      }
      if (lane == 0) {
        mbar_wait(BAR(empty1, 17));
#pragma unroll 1
        for (int e = 0; e < (SPEC < 0 ? 3 : 1); e++) {
          const unsigned* cp = e == 0 ? &scr->cnt[(C_PX + rb2) * 32] : &scr->cnt[(C_PY + rb2) * 32 + 2 * kh + e - 1];
          if (e == 1) mbar_wait(BAR(fullP, 0), 0);
          int it = 0;
          while ((int)(ld_relaxed(cp) - (epoch + 1) * (e == 0 ? 64 : 16)) < 0)
            if (++it > SPIN_LIMIT) { die(); break; }
          mbar_arrive(BAR(hint, e));
        }
      }
    }
  } else {
    const int warp = __shfl_sync(0xffffffffu, tid >> 5, 0);
    const int g = lane >> 2, t = lane & 3;
    uint4 q[4], o[4];
    uint32_t rbar;
    asm volatile("mapa.shared::cluster.u32 %0, %1, %2;" : "=r"(rbar) : "r"(sbar), "r"(rk ^ 1));
#define RBAR(field, i) (rbar + (uint32_t)offsetof(Bars, field) + 8u * (i))
    PROF(1);
    asm volatile("setmaxnreg.inc.sync.aligned.u32 224;");
    {
      const uint4* const zp = &scr->Z1[(c * 128 + 8 * t + warp) * 8 + g];
      const uint32_t tst = clock32();
      mbar_wait(BAR(tbar, 0), 0);
      if (tid == 0) PROFP(14);
      uint4 f2[4], g2[4];
#pragma unroll
      for (int i = 0; i < 4; i++) {
        f2[i] = lds4(TOFF(f2) + warp * 2048 + i * 512);
        g2[i] = lds4(TOFF(g2) + warp * 2048 + i * 512);
      }
      const uint4 f8 = lds4(TOFF(f8)), g8 = lds4(TOFF(g8));
      float wfr[16], wfi[16];
      {
        const float fsc = 1.f / (1 << 19);
        const float fsc3 = ((c & 7) == 7 && g == 0) ? 0.5f * fsc : fsc;
        const int gg = g == 0 ? 8 : g, wsh = (2 * (c >> 3) + 2) & 15;
#pragma unroll
        for (int i = 0; i < 16; i++) {
          const int ci = i >> 3, dd = (i >> 2) & 1, e = i & 3;
          const int kk = (e == 0 ? gg : e == 1 ? 16 + gg : e == 2 ? 16 - g : 32 - g) - 1;
          const uint32_t a = sbase + SM_W + ((2 * warp + ci) * 8 + t + 4 * dd) * 80 + wsh + 2 * kk;
          wfr[i] = bf_lo(lds_u16(a)) * (e == 3 ? fsc3 : fsc);
          wfi[i] = bf_lo(lds_u16(a + 10240)) * (e == 3 ? fsc3 : fsc);
        }
      }
      asm volatile("barrier.cluster.wait.aligned;" ::: "memory");
      PROF(2);
      spin_until(tst + POLL_DELAY);
      ld_tag4_issue<256>(q, zp);
      ld_tag4_finish<256>(q, zp, tag);
      if (tid == 0) PROFP(30);
      if (lane == 0) mbar_arrive(BAR(sig, 0));
      cdft16(q, f2, o);
      const uint32_t e2 = sbase + SM_E2;
#pragma unroll
      for (int vv = 0; vv < 4; vv++)
        sts4(e2 + ((warp * 16 + 4 * vv + t) * 8 + (g ^ (2 * t) ^ (2 * (warp & 3)))) * 16, o[vv].x, o[vv].y, o[vv].z, o[vv].w);
      bar_sync(NB_CONS, 256);
#pragma unroll
      for (int ci = 0; ci < 2; ci++) {
        const int cc = 2 * warp + ci;
        uint32_t ad[2];
        uint4 u[2];
#pragma unroll
        for (int hh = 0; hh < 2; hh++) {
          ad[hh] = e2 + (((t + 4 * hh) * 16 + cc) * 8 + (g ^ (2 * (cc & 3)) ^ (2 * t))) * 16;
          u[hh] = lds4(ad[hh]);
        }
        uint32_t res[2][4];
#pragma unroll
        for (int p = 0; p < 2; p++) {
          uint32_t y[2][2];
#pragma unroll
          for (int vv = 0; vv < 2; vv++) {
            float d[4] = {0.f, 0.f, 0.f, 0.f};
            mma16816(d, word(u[0], 2 * p), word(u[0], 2 * p + 1), word(u[1], 2 * p), word(u[1], 2 * p + 1), word(f8, 2 * vv), word(f8, 2 * vv + 1));
#pragma unroll
            for (int rr = 0; rr < 2; rr++) {
              const float fr = wfr[ci * 8 + vv * 4 + 2 * p + rr], fi = wfi[ci * 8 + vv * 4 + 2 * p + rr];
              y[vv][rr] = pack2(d[2 * rr] * fr - d[2 * rr + 1] * fi, d[2 * rr] * fi + d[2 * rr + 1] * fr);
            }
          }
#pragma unroll
          for (int vv = 0; vv < 2; vv++) {
            float d[4] = {0.f, 0.f, 0.f, 0.f};
            mma16816(d, y[0][0], y[0][1], y[1][0], y[1][1], word(g8, 2 * vv), word(g8, 2 * vv + 1));
            res[vv][2 * p] = pack2(d[0], d[1]);
            res[vv][2 * p + 1] = pack2(d[2], d[3]);
          }
        }
#pragma unroll
        for (int vv = 0; vv < 2; vv++) sts4(ad[vv], res[vv][0], res[vv][1], res[vv][2], res[vv][3]);
      }
      bar_sync(NB_CONS, 256);
#pragma unroll
      for (int i = 0; i < 4; i++) q[i] = lds4(e2 + ((warp * 16 + 4 * i + t) * 8 + (g ^ (2 * t) ^ (2 * (warp & 3)))) * 16);
      cdft16(q, g2, o);
#pragma unroll
      for (int vv = 0; vv < 4; vv++) st_tag(&scr->Z2[((8 * (4 * vv + t) + warp) * 128 + c) * 8 + g], o[vv], tag);
    }
    PROF(3);
    {
      const uint4* const zp = &scr->Z2[((c * 16 + t) * 8 + warp) * 8 + g];
      const uint32_t tst = clock32();
      uint4 gb[16], gc[4], tw[4], xr[2][2];
#pragma unroll
      for (int i = 0; i < 16; i++) gb[i] = lds4(TOFF(gb) + i * 512);
      const uint4 ga = lds4(TOFF(ga));
#pragma unroll
      for (int i = 0; i < 4; i++) {
        gc[i] = lds4(sbase + SM_FC + 2048 + i * 512 + lane * 16);
        tw[i] = lds4(TOFF(tw3) + i * 512);
        const int ch = 4 * (g + 8 * (i & 1)) + t;
        xr[i >> 1][i & 1] = lds4(sbase + SM_X + (2 * warp + (i >> 1)) * 1024 + ((ch ^ ((ch >> 2) & 6)) * 16));
      }
      PROF(4);
      spin_until(tst + POLL_DELAY);
      ld_tag4_issue<256>(q, zp);
      ld_tag4_finish<256>(q, zp, tag);
      if (tid == 0) PROFP(31);
      if (lane == 0) mbar_arrive(BAR(sig, 1));
      cdft16(q, gc, o);
#pragma unroll
      for (int vv = 0; vv < 4; vv++)
        sts4(sbase + SM_E + (((4 * vv + t) * 8 + warp) * 8 + (g ^ (warp & 6) ^ (2 * t))) * 16, o[vv].x, o[vv].y, o[vv].z, o[vv].w);
      if (tid == 0) PROFP(8);
      bar_sync(NB_CONS, 256);
      if (tid == 0) PROFP(9);
      uint32_t hv[2][8];
      const float mk = t == 0 ? 0.f : 1.f;
#pragma unroll
      for (int r = 0; r < 2; r++) {
        const int j = 2 * warp + r;
        uint4 u[2];
#pragma unroll
        for (int h = 0; h < 2; h++) u[h] = lds4(sbase + SM_E + ((j * 8 + 2 * t + h) * 8 + (g ^ (2 * t) ^ (2 * (j & 3)))) * 16);
        float yv[4][4];
#pragma unroll
        for (int i = 0; i < 4; i++) {
          float lo[4] = {0.f, 0.f, 0.f, 0.f}, hi[4] = {0.f, 0.f, 0.f, 0.f};
          mma16816(lo, gb[i * 4].x, gb[i * 4].y, gb[i * 4].z, gb[i * 4].w, u[0].x, u[0].y);
          mma16816(lo, gb[i * 4 + 1].x, gb[i * 4 + 1].y, gb[i * 4 + 1].z, gb[i * 4 + 1].w, u[1].x, u[1].y);
          mma16816(hi, gb[i * 4 + 2].x, gb[i * 4 + 2].y, gb[i * 4 + 2].z, gb[i * 4 + 2].w, u[0].z, u[0].w);
          mma16816(hi, gb[i * 4 + 3].x, gb[i * 4 + 3].y, gb[i * 4 + 3].z, gb[i * 4 + 3].w, u[1].z, u[1].w);
          const float ca = __uint_as_float(tw[i].x), sa = __uint_as_float(tw[i].y), cb = __uint_as_float(tw[i].z), sb = __uint_as_float(tw[i].w);
          const float tr0 = fmaf(hi[0], mk, lo[0]), ti0 = fmaf(hi[2], mk, lo[2]);
          const float tr1 = lo[1] + hi[1], ti1 = lo[3] + hi[3];
          const float vr0 = tr0 * ca - ti0 * sa, vi0 = tr0 * sa + ti0 * ca;
          const float vr1 = tr1 * cb - ti1 * sb, vi1 = tr1 * sb + ti1 * cb;
          const uint32_t b0 = pack2(t == 0 ? hi[0] : vr0, vr1), b1 = pack2(t == 0 ? vr0 : vi0, vi1);
          yv[i][0] = yv[i][1] = yv[i][2] = yv[i][3] = 0.f;
          mma16816(yv[i], ga.x, ga.y, ga.z, ga.w, b0, b1);
        }
#pragma unroll
        for (int h = 0; h < 2; h++) {
          hv[r][4 * h + 0] = hadd2_bf16(xr[r][h].x, pack2(yv[0][2 * h], yv[1][2 * h]));
          hv[r][4 * h + 1] = hadd2_bf16(xr[r][h].y, pack2(yv[2][2 * h], yv[3][2 * h]));
          hv[r][4 * h + 2] = hadd2_bf16(xr[r][h].z, pack2(yv[0][2 * h + 1], yv[1][2 * h + 1]));
          hv[r][4 * h + 3] = hadd2_bf16(xr[r][h].w, pack2(yv[2][2 * h + 1], yv[3][2 * h + 1]));
        }
      }
      if (tid == 0 && hv[0][0] != 0x12345 && hv[1][7] != 0x12345) PROFP(10);
      float ds[4] = {0.f, 0.f, 0.f, 0.f};
#pragma unroll
      for (int q4 = 0; q4 < 4; q4++) mma16816(ds, hv[0][2 * q4], hv[1][2 * q4], hv[0][2 * q4 + 1], hv[1][2 * q4 + 1], 0x3f803f80u, 0x3f803f80u);
#pragma unroll
      for (int o2 = 4; o2 <= 16; o2 <<= 1) {
        ds[0] += __shfl_xor_sync(0xffffffffu, ds[0], o2);
        ds[2] += __shfl_xor_sync(0xffffffffu, ds[2], o2);
      }
      uint32_t mb[2];
#pragma unroll
      for (int r = 0; r < 2; r++) {
        const int row = 16 * f + 2 * warp + r;
        mb[r] = pack2(ds[2 * r] * (1.f / 512.f), ds[2 * r] * (1.f / 512.f));
#pragma unroll
        for (int i = 0; i < 8; i++) hv[r][i] = hsub2_bf16(hv[r][i], mb[r]);
#pragma unroll
        for (int h = 0; h < 2; h++) {
          const int n1 = g + 8 * h;
          st_tag(&scr->LN[(rb * 8 + (n1 >> 1)) * 1024 + row * 8 + ((4 * (n1 & 1) + t) ^ (row & 7))],
                 make_uint4(hv[r][4 * h], hv[r][4 * h + 1], hv[r][4 * h + 2], hv[r][4 * h + 3]), n1 < 2 * NLL ? tag : (hv[r][4 * h] & 1u));
        }
      }
      if (tid == 0) PROFP(11);
      bar_arrive(NB_LN, 288);
      float sum[2], sq[2], rstd[2];
      row_stats(hv[0], hv[1], lane, sum, sq);
#pragma unroll
      for (int r = 0; r < 2; r++) {
        const float m = sum[r] * (1.f / 512.f);
        rstd[r] = rsqrtf(fmaxf(fmaf(-m, m, sq[r] * (1.f / 512.f)), 0.f) + 1e-5f);
      }
      if (lane == 0)
        st_tag(&scr->ST[rb * 64 + 8 * f + warp], make_uint4(mb[0] << 16, __float_as_uint(rstd[0]), mb[1] << 16, __float_as_uint(rstd[1])), tag);
    }
    PROF(5);
    const int wgi = warp >> 2, wq = warp & 3;
    uint4* const pbase = &scr->P[rb * 28 * 1024 + warp * 128 + lane];
    const uint32_t a_lo0 = desc_lo(sbase + wgi * 8192, 16);
    const uint32_t ebar = lane == 0 ? BAR(empty1, 0) : RBAR(empty1, 0);
    float r0, r1;
    uint4 px[8], py[6];
    const int rh = wgi ^ kh ^ 1;
    const uint4* const psrc = &scr->P[(rb2 * 28 + 14 * kh) * 1024 + (4 * rh + wq) * 128 + lane];
    {
      float acc[128];
#pragma unroll
      for (int i = 0; i < 128; i++) acc[i] = 0.f;
      const uint32_t b_lo0 = desc_lo(sbase + 8 * SLOT, 4096);
      const uint32_t t3 = clock32();
      if (WARM) {
        wg_fence();
#pragma unroll
        for (int i = 0; i < WARM; i++) wgmma_n256(acc, desc64(a_lo0 + 6 * 1024, HI128), desc64(b_lo0, HI128));
        wg_commit();
      }
      if (NLL) {
        const uint4* const ap = &scr->LN[rb * 8 * 1024 + tid];
        uint4 av[NLL ? NLL : 1][4];
        while (clock32() - t3 < POLL_DELAY3) {}
  #pragma unroll
        for (int kb = 0; kb < NLL; kb++) ld_tag4_issue<256>(av[kb], ap + kb * 1024);
        bar_sync(NB_CONS, 256);
  #pragma unroll
        for (int kb = 0; kb < NLL; kb++) {
          ld_tag4_finish<256>(av[kb], ap + kb * 1024, tag);
  #pragma unroll
          for (int i = 0; i < 4; i++) sts4(sbase + kb * SLOT + (tid + 256 * i) * 16, av[kb][i].x, av[kb][i].y, av[kb][i].z, av[kb][i].w);
        }
        asm volatile("fence.proxy.async.shared::cta;" ::: "memory");
        bar_sync(NB_CONS, 256);
      }
      uint32_t slot = 2;
#pragma unroll 1
      for (int kb = 0; kb < 8; kb++) {
        if (kb >= NLL) mbar_wait(BAR(fullA, kb), 0);
        if (kb == 0) PROF(6);
#pragma unroll
        for (int hh = 0; hh < 2; hh++) {
          if (LAGX && hh == ((16 - LAGX) & 1) && kb == ((16 - LAGX) >> 1) && wgi == 1) bar_sync(NB_LAG, 256);
          mbar_wait(BAR(full1, 2 * kb + hh));
          const uint32_t al = a_lo0 + kb * 1024 + hh * 4, bl = b_lo0 + slot * 1024;
          wg_fence();
          wgmma_n256(acc, desc64(al, HI128), desc64(bl, HI128), (kb | hh) != 0);
          wgmma_n256(acc, desc64(al + 2, HI128), desc64(bl + 128, HI128));
          wg_commit();
          if (LAGX && hh == 1 && kb == 7 && wgi == 0) bar_arrive(NB_LAG, 256);
          wg_wait<1>();
          if ((kb | hh) != 0 && lane < 2) mbar_arrive_remote(ebar + 8 * (2 * kb + hh - 1));
          if (++slot == 6) slot = 0;
        }
      }
      mbar_wait(BAR(sbar, 0), 0);
      r0 = __uint_as_float(lds2(sstat + (16 * warp + g) * 8).y);
      r1 = __uint_as_float(lds2(sstat + (16 * warp + g + 8) * 8).y);
      wg_wait<0>();
      if (lane < 2) mbar_arrive_remote(ebar + 8 * 15);
      PROF(7);
      make_p<8, false>(acc, r0, r1, px, pbase, 0, tag);
    }
    PROF(8);
    {
      float acc[96];
#pragma unroll
      for (int i = 0; i < 96; i++) acc[i] = 0.f;
      const uint32_t b_lo0 = desc_lo(sbase + 8 * SLOT, 2048);
      uint4* const pdst = pbase + ((7 * f + 3 * (f & 1)) >> 1) * 1024;
      auto stage_y = [&](int k) {
        if (LAGY && k == 16 - LAGY && wgi == 1) bar_sync(NB_LAG, 256);
        mbar_wait(BAR(full1, 16 + k));
        const uint32_t al = a_lo0 + (k >> 1) * 1024 + (k & 1) * 4, bl = b_lo0 + (k & 7) * 768;
        wg_fence();
        wgmma_n192(acc, desc64(al, HI128), desc64(bl, HI64));
        wgmma_n192(acc, desc64(al + 2, HI128), desc64(bl + 64, HI64));
        wg_commit();
      };
#pragma unroll
      for (int k = 0; k < 4; k++) {
        stage_y(k);
        st_tag(pdst + (k >> 1) * 1024 + (k & 1) * 64, px[2 * k], tag);
        st_tag(pdst + (k >> 1) * 1024 + (k & 1) * 64 + 32, px[2 * k + 1], tag);
        if (k == 3 && lane == 0) red_relaxed(&scr->cnt[(C_PX + rb) * 32]);
        wg_wait<1>();
        if (k != 0 && lane < 2) mbar_arrive_remote(ebar + 8 * (15 + k));
      }
#pragma unroll 1
      for (int k = 4; k < 16; k++) {
        stage_y(k);
        if (LAGY && k == 15 && wgi == 0) bar_arrive(NB_LAG, 256);
        wg_wait<1>();
        if (lane < 2) mbar_arrive_remote(ebar + 8 * (15 + k));
      }
      wg_wait<0>();
      if (lane < 2) mbar_arrive_remote(ebar + 8 * 31);
      PROF(9);
      make_p<6, true>(acc, r0, r1, py, pbase, 14 * f + ((f & 1) ? 0 : 8), tag);
      if (lane == 0) red_relaxed(&scr->cnt[(C_PY + rb) * 32 + (f >> 1)]);
    }
    PROF(10);
    {
      float acc[64];
      {
        const float m0 = wgi ? 0.f : __uint_as_float(lds2(sstat + 1024 + (16 * wq + g) * 8).x);
        const float m1 = wgi ? 0.f : __uint_as_float(lds2(sstat + 1024 + (16 * wq + g + 8) * 8).x);
#pragma unroll
        for (int i = 0; i < 64; i++) acc[i] = (i & 2) ? m1 : m0;
      }
      const uint32_t b2_lo0 = desc_lo(sbase, 8192);
      const uint32_t pa0 = sbase + (4 * rh + wq) * 2048;
      const uint32_t pbar = ebar + (uint32_t)(offsetof(Bars, emptyP) - offsetof(Bars, empty1));
      uint4 fa[3][4];
      uint32_t rdy = 0;
      mbar_wait(BAR(fullP, 0));
#pragma unroll
      for (int kk = 0; kk < 4; kk++) fa[0][kk] = lds4(pa0 + 4 * SLOT + kk * 512 + lane * 16);
#pragma unroll
      for (int s = 0; s < 14; s++) {
        uint4 (&a)[4] = fa[s % 3];
        ld_tag4_finish<32>(a, psrc + (int)((KORDER >> (4 * s)) & 15) * 1024, tag);
        if (s < 8 && lane < (s < 7 ? 2 : 1)) mbar_arrive_remote(pbar + 8 * s);
        if (s >= 2) {
          wg_wait<1>();
          if (s <= 8 && lane == 0) mbar_arrive(BAR(empty2, s - 2));
        }
        if (!rdy) {
          if (s < 13) mbar_wait(BAR(fullP, s + 1));
          mbar_wait(BAR(full2, s));
        }
        if (tid == 0) PROFP(16 + s);
        if (LAG2 && s == 14 - LAG2 && wgi == 1) bar_sync(NB_LAG, 256);
        const uint32_t bl = b2_lo0 + (uint32_t)((BSLOT >> (4 * s)) & 15) * 1024;
        wg_fence();
        if (s < 13) {
#pragma unroll
          for (int kk = 0; kk < 4; kk++)
            fa[(s + 1) % 3][kk] = lds4(pa0 + (uint32_t)((PSLOT >> (4 * (s + 1))) & 15) * SLOT + kk * 512 + lane * 16);
          rdy = mbar_test(BAR(full2, s + 1));
          if (s < 12) rdy &= mbar_test(BAR(fullP, s + 2));
        }
#pragma unroll
        for (int kk = 0; kk < 4; kk++) wgmma_rs_n128<1>(acc, a[kk].x, a[kk].y, a[kk].z, a[kk].w, desc64(bl + kk * 128, HI128));
        wg_commit();
      }
      if (LAG2 && wgi == 0) bar_arrive(NB_LAG, 256);
      uint4 pv[2][4];
      const uint4* const xsrc = &scr->XP[c * 1024 + (tid & 127)];
      if (wgi == 1) {
        ld_tag4_issue<128>(pv[0], xsrc);
        ld_tag4_issue<128>(pv[1], xsrc + 512);
      }
      wg_wait<0>();
      PROF(11);
#pragma unroll
      for (int h = 0; h < 2; h++)
#pragma unroll
        for (int q = 0; q < 4; q++)
          asm volatile("stmatrix.sync.aligned.m8n8.x4.shared.b16 [%0], {%1,%2,%3,%4};"
                       ::"r"(pa0 + (9 + h) * SLOT + (lane & 7) * 256 + (((4 * q + (lane >> 3)) ^ (lane & 7)) * 16)),
                         "r"(pack2(acc[16 * q + 2 * h], acc[16 * q + 2 * h + 1])), "r"(pack2(acc[16 * q + 4 + 2 * h], acc[16 * q + 5 + 2 * h])),
                         "r"(pack2(acc[16 * q + 8 + 2 * h], acc[16 * q + 9 + 2 * h])), "r"(pack2(acc[16 * q + 12 + 2 * h], acc[16 * q + 13 + 2 * h]))
                       : "memory");
      __syncwarp();
      uint4 w[8];
#pragma unroll
      for (int i = 0; i < 8; i++) {
        const int r = 2 * (i & 3) + (lane >> 4);
        w[i] = lds4(pa0 + (9 + (i >> 2)) * SLOT + r * 256 + (((lane & 15) ^ r) * 16));
      }
      uint4* dst;
      int dstr;
      if (wgi == 0) {
        mbar_wait(BAR(hbar, 0));
        const uint32_t hb = sbase + 4 * SLOT + ((lane >> 3) & 1) * 8192 + (16 * wq + (lane >> 4)) * 128;
#pragma unroll
        for (int i = 0; i < 8; i++) {
          pv[i >> 2][i & 3] = lds4(hb + i * 256 + (((lane & 7) ^ ((2 * i + (lane >> 4)) & 7)) * 16));
          if (2 * nq + ((lane >> 3) & 1) < NLL) pv[i >> 2][i & 3].x &= ~1u;
        }
        dst = &scr->XP[(c ^ 4) * 1024 + tid];
        dstr = 128;
      } else {
        ld_tag4_finish<128>(pv[0], xsrc, tag);
        ld_tag4_finish<128>(pv[1], xsrc + 512, tag);
        dst = reinterpret_cast<uint4*>(out) + (16 * (c >> 4) + 2 * (4 * rh + wq) + (rb2 & 1) + 128 * (lane >> 4)) * 64 + nq * 16 + (lane & 15);
        dstr = 256 * 64;
      }
#pragma unroll
      for (int i = 0; i < 8; i++) {
        const uint4& p = pv[i >> 2][i & 3];
        const uint4 v = make_uint4(hadd2_bf16(w[i].x, p.x), hadd2_bf16(w[i].y, p.y), hadd2_bf16(w[i].z, p.z), hadd2_bf16(w[i].w, p.w));
        st_tag(dst + i * dstr, v, wgi ? (v.x & 1u) : tag);
      }
      PROF(12);
      PROFG(15);
    }
  }
#undef BAR
#undef TOFF
#undef RBAR
}

typedef CUresult (*EncodeFn)(CUtensorMap*, CUtensorMapDataType, cuuint32_t, void*, const cuuint64_t*, const cuuint64_t*,
                             const cuuint32_t*, const cuuint32_t*, CUtensorMapInterleave, CUtensorMapSwizzle,
                             CUtensorMapL2promotion, CUtensorMapFloatOOBfill);

}

extern "C" void kernel_launch(void* const* d_in, const int* in_sizes, int n_in, void* d_out, int out_size) {
  (void)in_sizes; (void)n_in; (void)out_size;
  static EncodeFn encode = nullptr;
  static void *tab = nullptr, *scr = nullptr;
  if (!encode) {
    void* fn = nullptr;
    cudaDriverEntryPointQueryResult qr;
    cudaGetDriverEntryPoint("cuTensorMapEncodeTiled", &fn, cudaEnableDefault, &qr);
    encode = (EncodeFn)fn;
    cudaGetSymbolAddress(&tab, g_tab);
    cudaGetSymbolAddress(&scr, g_scr);
    cudaFuncSetAttribute(fused_kernel, cudaFuncAttributeMaxDynamicSharedMemorySize, SMEM_BYTES);
  }
  CUtensorMap tmGX, tmUX, tmGY, tmUY, tmD, tmWR, tmWI;
  const cuuint32_t es[5] = {1, 1, 1, 1, 1};
  auto enc = [&](CUtensorMap* m, void* p, int rank, const cuuint64_t* gd, const cuuint64_t* gs, const cuuint32_t* bd,
                 CUtensorMapSwizzle sw, CUtensorMapL2promotion pr) {
    encode(m, CU_TENSOR_MAP_DATA_TYPE_BFLOAT16, rank, p, gd, gs, bd, es, CU_TENSOR_MAP_INTERLEAVE_NONE, sw, pr,
           CU_TENSOR_MAP_FLOAT_OOB_FILL_NONE);
  };
  {
    const cuuint64_t gd[3] = {64, 512, 28}, gs[2] = {3584, 128};
    const cuuint32_t bd[3] = {64, 32, 2};
    enc(&tmGX, d_in[4], 3, gd, gs, bd, CU_TENSOR_MAP_SWIZZLE_128B, CU_TENSOR_MAP_L2_PROMOTION_L2_256B);
    enc(&tmUX, d_in[5], 3, gd, gs, bd, CU_TENSOR_MAP_SWIZZLE_128B, CU_TENSOR_MAP_L2_PROMOTION_L2_256B);
  }
  {
    const cuuint64_t gd[3] = {32, 512, 56}, gs[2] = {3584, 64};
    const cuuint32_t bd[3] = {32, 32, 3};
    enc(&tmGY, d_in[4], 3, gd, gs, bd, CU_TENSOR_MAP_SWIZZLE_64B, CU_TENSOR_MAP_L2_PROMOTION_L2_128B);
    enc(&tmUY, d_in[5], 3, gd, gs, bd, CU_TENSOR_MAP_SWIZZLE_64B, CU_TENSOR_MAP_L2_PROMOTION_L2_128B);
  }
  {
    const cuuint64_t gd[3] = {64, 1792, 8}, gs[2] = {1024, 128};
    const cuuint32_t bd[3] = {64, 64, 2};
    enc(&tmD, d_in[6], 3, gd, gs, bd, CU_TENSOR_MAP_SWIZZLE_128B, CU_TENSOR_MAP_L2_PROMOTION_L2_256B);
  }
  {
    const cuuint64_t gd[3] = {4112, 8, 16}, gs[2] = {16 * 8224, 8224};
    const cuuint32_t bd[3] = {40, 8, 16};
    enc(&tmWR, d_in[1], 3, gd, gs, bd, CU_TENSOR_MAP_SWIZZLE_NONE, CU_TENSOR_MAP_L2_PROMOTION_NONE);
    enc(&tmWI, d_in[2], 3, gd, gs, bd, CU_TENSOR_MAP_SWIZZLE_NONE, CU_TENSOR_MAP_L2_PROMOTION_NONE);
  }
  fused_kernel<<<NCTA, NTHREADS, SMEM_BYTES>>>((const __nv_bfloat16*)d_in[0], (const Tables*)tab, (Scratch*)scr,
                                               (__nv_bfloat16*)d_out, (const char*)d_in[4], (const char*)d_in[5],
                                               (const char*)d_in[6], tmWR, tmWI, tmGX, tmUX, tmGY, tmUY, tmD);
}
```

```cpp
#include <cuda_runtime.h>
#include <cuda_bf16.h>
#include <cuda.h>
#include <stdint.h>

namespace {

constexpr int NCTA = 128;
constexpr int NTHREADS = 384;
constexpr int SLOT = 16384;
constexpr int SMEM_BYTES = 14 * SLOT + 3072;
constexpr int SPIN_LIMIT = 1 << 22;

struct Scratch {
  uint4 Z1[128 * 1024];
  uint4 Z2[128 * 1024];
  uint4 LN[16 * 8 * 1024];
  uint4 P[16 * 28 * 1024];
  uint4 XP[128 * 1024];
  uint4 ST[1024];
  unsigned cnt[64 * 32];
};
__device__ __align__(1024) Scratch g_scr;
#define PROF(i)
#define PROFP(i)
#define PROFG(i)

constexpr double ccos(int i, int n) {
  i &= n - 1;
  if (i > n / 2) i = n - i;
  if (4 * i == n) return 0.0;
  const bool neg = 4 * i > n;
  if (neg) i = n / 2 - i;
  const double a = 6.283185307179586476925 * i / n, a2 = a * a;
  double term = 1.0, sum = 1.0;
  for (int k = 1; k < 14; k++) { term *= -a2 / ((2 * k - 1) * (2 * k)); sum += term; }
  return neg ? -sum : sum;
}
constexpr double csin(int i, int n) { return ccos(i - n / 4, n); }
constexpr unsigned fbits(double v, int mant) {
  if (v == 0.0) return 0;
  const unsigned sg = v < 0 ? 1u : 0u;
  if (v < 0) v = -v;
  int e = 127;
  while (v < 1.0) { v *= 2.0; e--; }
  const unsigned m = (unsigned)((v - 1.0) * (double)(1u << mant) + 0.5);
  return (sg << (8 + mant)) + ((unsigned)e << mant) + m;
}
constexpr unsigned pkb(double lo, double hi) { return fbits(lo, 7) | (fbits(hi, 7) << 16); }
constexpr double fa_elem(int kp, int n1) {
  return kp <= 8 ? ccos(kp * n1, 16) : -csin((kp - 8) * n1, 16);
}
constexpr unsigned cfrag_c(int idx, int n, int ri) {
  return ri ? pkb(-csin(idx, n), ccos(idx, n)) : pkb(ccos(idx, n), csin(idx, n));
}
struct Tables {
  unsigned fb[16][32][4];
  unsigned tw1[8][32][4];
  unsigned fa[32][4];
  unsigned f2[8][4][32][4];
  unsigned g2[8][4][32][4];
  unsigned gb[16][32][4];
  unsigned tw3[4][32][4];
  unsigned ga[32][4];
  unsigned f8[32][4], g8[32][4];
};
constexpr int T1_BYTES = 12800, T2_BYTES = 44544;
static_assert(sizeof(Tables) == T1_BYTES + T2_BYTES, "table size");
constexpr Tables make_tables() {
  Tables T = {};
  for (int l = 0; l < 32; l++) {
    const int g = l >> 2, t = l & 3;
    for (int i = 0; i < 4; i++)
      for (int u = 0; u < 8; u++) {
        const int ri = g & 1, m = 2 * (g >> 1) + ((u & 3) >> 1);
        const double sg = u >= 4 ? -1.0 : 1.0;
        const int k2 = u >= 4 ? 31 - 2 * m - (u & 1) : 2 * m + (u & 1);
        const int pa = (8 * t + i) * k2, pb = (8 * t + 4 + i) * k2;
        T.fb[i * 4 + (u >> 1)][l][(u & 1) * 2 + 0] = ri == 0 ? pkb(ccos(pa, 32), ccos(pb, 32)) : pkb(-sg * csin(pa, 32), -sg * csin(pb, 32));
        T.fb[i * 4 + (u >> 1)][l][(u & 1) * 2 + 1] = ri == 0 ? pkb(csin(pa, 32), csin(pb, 32)) : pkb(sg * ccos(pa, 32), sg * ccos(pb, 32));
      }
    for (int i = 0; i < 4; i++)
      for (int ks = 0; ks < 4; ks++) {
        const int n2 = 4 * g + i, m = 2 * t + (ks & 1);
        const double sg = ks >= 2 ? -1.0 : 1.0;
        const int pa = n2 * (ks >= 2 ? 31 - 2 * m : 2 * m), pb = n2 * (ks >= 2 ? 30 - 2 * m : 2 * m + 1);
        T.gb[i * 4 + ks][l][0] = pkb(ccos(pa, 32), -sg * csin(pa, 32));
        T.gb[i * 4 + ks][l][1] = pkb(csin(pa, 32), sg * ccos(pa, 32));
        T.gb[i * 4 + ks][l][2] = pkb(ccos(pb, 32), -sg * csin(pb, 32));
        T.gb[i * 4 + ks][l][3] = pkb(csin(pb, 32), sg * ccos(pb, 32));
      }
    for (int i = 0; i < 4; i++) {
      for (int e = 0; e < 2; e++) {
        const int p = (8 * t + 4 * e + i) * (g == 0 ? 8 : g);
        T.tw1[2 * i + e][l][0] = fbits(g == 0 ? 0.0 : ccos(p, 512), 23);
        T.tw1[2 * i + e][l][1] = fbits(g == 0 ? ccos(p, 512) : csin(p, 512), 23);
        T.tw1[2 * i + e][l][2] = fbits(g == 0 ? 0.0 : -csin(p, 512), 23);
        T.tw1[2 * i + e][l][3] = fbits(g == 0 ? -csin(p, 512) : ccos(p, 512), 23);
      }
      const int ka = t == 0 ? 8 : 2 * t, kb = 2 * t + 1;
      T.tw3[i][l][0] = fbits(ccos((4 * g + i) * ka, 512), 23);
      T.tw3[i][l][1] = fbits(csin((4 * g + i) * ka, 512), 23);
      T.tw3[i][l][2] = fbits(ccos((4 * g + i) * kb, 512), 23);
      T.tw3[i][l][3] = fbits(csin((4 * g + i) * kb, 512), 23);
      const int p8 = (t + 4 * (i & 1)) * (4 * (i >> 1) + (g >> 1));
      T.f8[l][i] = cfrag_c(p8, 8, g & 1);
      T.g8[l][i] = cfrag_c(-p8, 8, g & 1);
    }
    for (int w = 0; w < 8; w++)
      for (int i = 0; i < 16; i++) {
        const int kidx = t + 4 * (i & 1) + 8 * (i >> 3), nidx = 4 * ((i >> 1) & 3) + (g >> 1);
        T.f2[w][i >> 2][l][i & 3] = cfrag_c((8 * kidx + w) * nidx, 128, g & 1);
        T.g2[w][i >> 2][l][i & 3] = cfrag_c(-(8 * nidx + w) * kidx, 128, g & 1);
      }
    T.fa[l][0] = pkb(fa_elem(g, 2 * t), fa_elem(g, 2 * t + 1));
    T.fa[l][1] = pkb(fa_elem(g + 8, 2 * t), fa_elem(g + 8, 2 * t + 1));
    T.fa[l][2] = pkb(fa_elem(g, 2 * t + 8), fa_elem(g, 2 * t + 9));
    T.fa[l][3] = pkb(fa_elem(g + 8, 2 * t + 8), fa_elem(g + 8, 2 * t + 9));
    T.ga[l][0] = pkb(fa_elem(2 * t, g), fa_elem(2 * t + 1, g));
    T.ga[l][1] = pkb(fa_elem(2 * t, g + 8), fa_elem(2 * t + 1, g + 8));
    T.ga[l][2] = pkb(fa_elem(2 * t + 8, g), fa_elem(2 * t + 9, g));
    T.ga[l][3] = pkb(fa_elem(2 * t + 8, g + 8), fa_elem(2 * t + 9, g + 8));
  }
  return T;
}
__device__ const __align__(128) Tables g_tab = make_tables();

__device__ __forceinline__ void die() { asm volatile("st.global.u32 [%0], %1;" ::"l"(0ull), "r"(0) : "memory"); }
__device__ __forceinline__ uint32_t s2u(const void* p) { return (uint32_t)__cvta_generic_to_shared(p); }
__device__ __forceinline__ void mbar_init(uint32_t b, int c) { asm volatile("mbarrier.init.shared::cta.b64 [%0], %1;" ::"r"(b), "r"(c)); }
__device__ __forceinline__ void mbar_expect(uint32_t b, int bytes) {
  asm volatile("mbarrier.arrive.expect_tx.shared::cta.b64 _, [%0], %1;" ::"r"(b), "r"(bytes) : "memory");
}
__device__ __forceinline__ void mbar_arrive(uint32_t b) { asm volatile("mbarrier.arrive.shared::cta.b64 _, [%0];" ::"r"(b) : "memory"); }
__device__ __forceinline__ uint32_t mbar_try(uint32_t b, uint32_t parity) {
  uint32_t ok;
  asm volatile("{.reg .pred p; mbarrier.try_wait.parity.shared::cta.b64 p, [%1], %2; selp.u32 %0,1,0,p;}"
               : "=r"(ok) : "r"(b), "r"(parity) : "memory");
  return ok;
}
__device__ __forceinline__ uint32_t mbar_test(uint32_t b) {
  uint32_t ok;
  asm volatile("{.reg .pred p; mbarrier.test_wait.parity.shared::cta.b64 p, [%1], 0; selp.u32 %0,1,0,p;}" : "=r"(ok) : "r"(b) : "memory");
  return ok;
}
__device__ __forceinline__ void mbar_wait(uint32_t b, uint32_t parity = 0) {
  int it = 0;
#pragma unroll 1
  while (!mbar_try(b, parity))
    if (++it > SPIN_LIMIT) { die(); break; }
}
__device__ __forceinline__ void bar_sync(int id, int n) { asm volatile("bar.sync %0, %1;" ::"r"(id), "r"(n) : "memory"); }
__device__ __forceinline__ void bar_arrive(int id, int n) { asm volatile("bar.arrive %0, %1;" ::"r"(id), "r"(n) : "memory"); }
__device__ __forceinline__ void red_release(unsigned* p) { asm volatile("red.release.gpu.global.add.u32 [%0], 1;" ::"l"(p) : "memory"); }
__device__ __forceinline__ void red_relaxed(unsigned* p) { asm volatile("red.relaxed.gpu.global.add.u32 [%0], 1;" ::"l"(p) : "memory"); }
__device__ __forceinline__ unsigned ld_acquire(const unsigned* p) {
  unsigned v;
  asm volatile("ld.acquire.gpu.global.u32 %0, [%1];" : "=r"(v) : "l"(p) : "memory");
  return v;
}
__device__ __forceinline__ unsigned ld_relaxed(const unsigned* p) {
  unsigned v;
  asm volatile("ld.relaxed.gpu.global.u32 %0, [%1];" : "=r"(v) : "l"(p) : "memory");
  return v;
}
__device__ __forceinline__ void wait_counter(const unsigned* p, unsigned target) {
  int it = 0;
  while ((int)(ld_acquire(p) - target) < 0)
    if (++it > SPIN_LIMIT) { die(); break; }
}
__device__ __forceinline__ void sts4(uint32_t a, uint32_t x, uint32_t y, uint32_t z, uint32_t w) {
  asm volatile("st.shared.v4.u32 [%0], {%1,%2,%3,%4};" ::"r"(a), "r"(x), "r"(y), "r"(z), "r"(w) : "memory");
}
__device__ __forceinline__ uint4 lds4(uint32_t a) {
  uint4 v;
  asm volatile("ld.shared.v4.u32 {%0,%1,%2,%3}, [%4];" : "=r"(v.x), "=r"(v.y), "=r"(v.z), "=r"(v.w) : "r"(a) : "memory");
  return v;
}
__device__ __forceinline__ uint32_t pack2(float lo, float hi) {
  uint32_t r;
  asm("cvt.rn.bf16x2.f32 %0, %1, %2;" : "=r"(r) : "f"(hi), "f"(lo));
  return r;
}
__device__ __forceinline__ float bf_lo(uint32_t v) { return __uint_as_float(v << 16); }
__device__ __forceinline__ uint32_t hadd2_bf16(uint32_t a, uint32_t b) {
  uint32_t r;
  asm("add.rn.bf16x2 %0, %1, %2;" : "=r"(r) : "r"(a), "r"(b));
  return r;
}
__device__ __forceinline__ void mma16816(float (&d)[4], uint32_t a0, uint32_t a1, uint32_t a2, uint32_t a3, uint32_t b0, uint32_t b1) {
  asm("mma.sync.aligned.m16n8k16.row.col.f32.bf16.bf16.f32 {%0,%1,%2,%3}, {%4,%5,%6,%7}, {%8,%9}, {%0,%1,%2,%3};"
      : "+f"(d[0]), "+f"(d[1]), "+f"(d[2]), "+f"(d[3])
      : "r"(a0), "r"(a1), "r"(a2), "r"(a3), "r"(b0), "r"(b1));
}
template <int N>
__device__ __forceinline__ void cs_frac(int idx, float& c, float& s) {
  int i = ((idx + N / 2) & (N - 1)) - N / 2;
  float a = (float)i * (6.283185307179586f / N);
  c = __cosf(a);
  s = __sinf(a);
}
template <int N>
__device__ __forceinline__ uint32_t cfrag(int idx, int ri) {
  float c, s;
  cs_frac<N>(idx, c, s);
  return ri ? pack2(-s, c) : pack2(c, s);
}
__device__ __forceinline__ uint32_t word(const uint4& v, int e) { return e == 0 ? v.x : e == 1 ? v.y : e == 2 ? v.z : v.w; }
__device__ __forceinline__ void cdft16(const uint4 (&q)[4], const uint4 (&F)[4], uint4 (&o)[4]) {
  float acc[2][4][4];
#pragma unroll
  for (int p = 0; p < 2; p++)
#pragma unroll
    for (int v = 0; v < 4; v++) {
      acc[p][v][0] = acc[p][v][1] = acc[p][v][2] = acc[p][v][3] = 0.f;
#pragma unroll
      for (int ks = 0; ks < 2; ks++)
        mma16816(acc[p][v], word(q[2 * ks], 2 * p), word(q[2 * ks], 2 * p + 1), word(q[2 * ks + 1], 2 * p),
                 word(q[2 * ks + 1], 2 * p + 1), word(F[ks * 2 + (v >> 1)], (v & 1) * 2), word(F[ks * 2 + (v >> 1)], (v & 1) * 2 + 1));
    }
#pragma unroll
  for (int v = 0; v < 4; v++)
    o[v] = make_uint4(pack2(acc[0][v][0], acc[0][v][1]), pack2(acc[0][v][2], acc[0][v][3]),
                      pack2(acc[1][v][0], acc[1][v][1]), pack2(acc[1][v][2], acc[1][v][3]));
}
__device__ __forceinline__ void st_tag(uint4* p, const uint4& v, uint32_t tag) {
  asm volatile("{.reg .b128 r; .reg .b64 a, b; mov.b64 a, {%1,%2}; mov.b64 b, {%3,%4}; mov.b128 r, {a,b}; st.relaxed.gpu.global.b128 [%0], r;}"
               ::"l"(p), "r"((v.x & ~1u) | tag), "r"(v.y), "r"(v.z), "r"(v.w) : "memory");
}
__device__ __forceinline__ void st_tag_p(int en, uint4* p, const uint4& v, uint32_t tag) {
  asm volatile("{.reg .b128 r; .reg .b64 a, b; .reg .pred q; setp.ne.b32 q, %5, 0; mov.b64 a, {%1,%2}; mov.b64 b, {%3,%4}; mov.b128 r, {a,b};\n"
               "@q st.relaxed.gpu.global.b128 [%0], r;}"
               ::"l"(p), "r"((v.x & ~1u) | tag), "r"(v.y), "r"(v.z), "r"(v.w), "r"(en) : "memory");
}
__device__ __forceinline__ void sts4_p(int en, uint32_t a, uint32_t x, uint32_t y, uint32_t z, uint32_t w) {
  asm volatile("{.reg .pred q; setp.ne.b32 q, %5, 0; @q st.shared.v4.u32 [%0], {%1,%2,%3,%4};}"
               ::"r"(a), "r"(x), "r"(y), "r"(z), "r"(w), "r"(en) : "memory");
}
__device__ __forceinline__ uint4 ld_b128(const uint4* p) {
  uint4 v;
  asm volatile("{.reg .b128 r; .reg .b64 a, b; ld.relaxed.gpu.global.b128 r, [%4]; mov.b128 {a,b}, r; mov.b64 {%0,%1}, a; mov.b64 {%2,%3}, b;}"
               : "=r"(v.x), "=r"(v.y), "=r"(v.z), "=r"(v.w) : "l"(p) : "memory");
  return v;
}
template <int STRIDE>
__device__ __forceinline__ void ld_tag4_issue(uint4 (&q)[4], const uint4* p) {
#pragma unroll
  for (int i = 0; i < 4; i++) q[i] = ld_b128(p + i * STRIDE);
}
template <int STRIDE>
__device__ __forceinline__ void ld_tag4_finish(uint4 (&q)[4], const uint4* p, uint32_t tag) {
  int it = 0;
#pragma unroll 1
  while (__any_sync(0xffffffffu, ((q[0].x ^ tag) | (q[1].x ^ tag) | (q[2].x ^ tag) | (q[3].x ^ tag)) & 1u)) {
    ld_tag4_issue<STRIDE>(q, p);
    if (++it > SPIN_LIMIT) { die(); break; }
  }
#pragma unroll
  for (int i = 0; i < 4; i++) asm volatile("and.b32 %0, %0, 0xfffffffe;" : "+r"(q[i].x));
}
__device__ __forceinline__ void row_stats(const uint32_t (&a)[8], const uint32_t (&b)[8], int lane, float (&sum)[2], float (&sq)[2]) {
  float da[4] = {0.f, 0.f, 0.f, 0.f}, db[4] = {0.f, 0.f, 0.f, 0.f}, ds[4] = {0.f, 0.f, 0.f, 0.f};
#pragma unroll
  for (int q = 0; q < 4; q++) {
    mma16816(ds, a[2 * q], b[2 * q], a[2 * q + 1], b[2 * q + 1], 0x3f803f80u, 0x3f803f80u);
    mma16816(da, a[2 * q], b[2 * q], a[2 * q + 1], b[2 * q + 1], a[2 * q], a[2 * q + 1]);
    mma16816(db, a[2 * q], b[2 * q], a[2 * q + 1], b[2 * q + 1], b[2 * q], b[2 * q + 1]);
  }
  const int src = (lane & 28) | (lane >> 3);
  const float qa = __shfl_sync(0xffffffffu, (lane & 4) ? da[1] : da[0], src);
  const float qb = __shfl_sync(0xffffffffu, (lane & 4) ? db[3] : db[2], src);
  float v = (lane & 2) ? ((lane & 1) ? ds[2] : ds[0]) : ((lane & 1) ? qb : qa);
  v += __shfl_xor_sync(0xffffffffu, v, 4);
  v += __shfl_xor_sync(0xffffffffu, v, 8);
  v += __shfl_xor_sync(0xffffffffu, v, 16);
  sq[0] = __shfl_sync(0xffffffffu, v, 0);
  sq[1] = __shfl_sync(0xffffffffu, v, 1);
  sum[0] = __shfl_sync(0xffffffffu, v, 2);
  sum[1] = __shfl_sync(0xffffffffu, v, 3);
}
__device__ __forceinline__ uint64_t desc64(uint32_t lo, uint32_t hi) {
  uint64_t d;
  asm("mov.b64 %0, {%1, %2};" : "=l"(d) : "r"(lo), "r"(hi));
  return d;
}
constexpr uint32_t desc_hi(uint32_t sbo, uint32_t swz) { return (sbo >> 4) | (swz << 30); }
__device__ __forceinline__ uint32_t desc_lo(uint32_t addr, uint32_t lbo) { return ((addr & 0x3FFFF) >> 4) | ((lbo >> 4) << 16); }
__device__ __forceinline__ void cp_async16(uint32_t dst, const void* src) {
  asm volatile("cp.async.cg.shared.global [%0], [%1], 16;" ::"r"(dst), "l"(src) : "memory");
}
__device__ __forceinline__ uint2 lds2(uint32_t a) {
  uint2 v;
  asm volatile("ld.shared.v2.u32 {%0,%1}, [%2];" : "=r"(v.x), "=r"(v.y) : "r"(a) : "memory");
  return v;
}
__device__ __forceinline__ uint32_t lds_u16(uint32_t a) {
  uint16_t v;
  asm volatile("ld.shared.u16 %0, [%1];" : "=h"(v) : "r"(a) : "memory");
  return v;
}
__device__ __forceinline__ void wg_fence() { asm volatile("wgmma.fence.sync.aligned;" ::: "memory"); }
__device__ __forceinline__ void wg_commit() { asm volatile("wgmma.commit_group.sync.aligned;" ::: "memory"); }
template <int N>
__device__ __forceinline__ void wg_wait() { asm volatile("wgmma.wait_group.sync.aligned %0;" ::"n"(N) : "memory"); }
__device__ __forceinline__ void bulk_load(uint32_t dst, const void* src, int bytes, uint32_t bar) {
  asm volatile("cp.async.bulk.shared::cluster.global.mbarrier::complete_tx::bytes [%0], [%1], %2, [%3];"
               ::"r"(dst), "l"(src), "r"(bytes), "r"(bar) : "memory");
}
__device__ __forceinline__ void bulk_load_mc(uint32_t dst, const void* src, int bytes, uint32_t bar) {
  asm volatile("cp.async.bulk.shared::cluster.global.mbarrier::complete_tx::bytes.multicast::cluster [%0], [%1], %2, [%3], %4;"
               ::"r"(dst), "l"(src), "r"(bytes), "r"(bar), "h"((uint16_t)3) : "memory");
}
__device__ __forceinline__ void tma3(uint32_t dst, const CUtensorMap* tm, uint32_t bar, int c0, int c1, int c2) {
  asm volatile("cp.async.bulk.tensor.3d.shared::cluster.global.mbarrier::complete_tx::bytes [%0], [%1, {%3,%4,%5}], [%2];"
               ::"r"(dst), "l"(tm), "r"(bar), "r"(c0), "r"(c1), "r"(c2) : "memory");
}
__device__ __forceinline__ void tma3_mc(uint32_t dst, const CUtensorMap* tm, uint32_t bar, int c1, int c2) {
  asm volatile("cp.async.bulk.tensor.3d.shared::cluster.global.mbarrier::complete_tx::bytes.multicast::cluster [%0], [%1, {%3,%4,%5}], [%2], %6;"
               ::"r"(dst), "l"(tm), "r"(bar), "r"(0), "r"(c1), "r"(c2), "h"((uint16_t)3) : "memory");
}
__device__ __forceinline__ void mbar_arrive_remote(uint32_t rb) {
  asm volatile("mbarrier.arrive.shared::cluster.b64 _, [%0];" ::"r"(rb) : "memory");
}
__device__ __forceinline__ uint4 ldg_ca4_p(int en, const void* p) {
  uint4 v;
  asm volatile("{.reg .pred q; setp.ne.b32 q, %5, 0; @q ld.global.ca.v4.u32 {%0,%1,%2,%3}, [%4];}"
               : "=r"(v.x), "=r"(v.y), "=r"(v.z), "=r"(v.w) : "l"(p), "r"(en) : "memory");
  return v;
}
__device__ __forceinline__ uint32_t clock32() {
  uint32_t v;
  asm volatile("mov.u32 %0, %%clock;" : "=r"(v) :: "memory");
  return v;
}
__device__ __forceinline__ float swiglu(float g, float u, float r) {
  float hg = (0.5f * r) * g, th;
  asm("tanh.approx.f32 %0, %1;" : "=f"(th) : "f"(hg));
  return fmaf(hg, th, hg) * (r * u);
}
__device__ __forceinline__ uint32_t hsub2_bf16(uint32_t a, uint32_t b) {
  uint32_t r;
  asm("sub.rn.bf16x2 %0, %1, %2;" : "=r"(r) : "r"(a), "r"(b));
  return r;
}
__device__ __forceinline__ void l2_prefetch(const void* p, int bytes) {
  asm volatile("cp.async.bulk.prefetch.L2.global [%0], %1;" ::"l"(p), "r"(bytes) : "memory");
}

__device__ __forceinline__ void wgmma_n256(float (&d)[128], uint64_t da, uint64_t db, int sd = 1) {
  asm volatile("{.reg .pred p; setp.ne.b32 p, %130, 0;\n"
      "wgmma.mma_async.sync.aligned.m64n256k16.f32.bf16.bf16 {"
      "%0,%1,%2,%3,%4,%5,%6,%7,%8,%9,%10,%11,%12,%13,%14,%15,"
      "%16,%17,%18,%19,%20,%21,%22,%23,%24,%25,%26,%27,%28,%29,%30,%31,"
      "%32,%33,%34,%35,%36,%37,%38,%39,%40,%41,%42,%43,%44,%45,%46,%47,"
      "%48,%49,%50,%51,%52,%53,%54,%55,%56,%57,%58,%59,%60,%61,%62,%63,"
      "%64,%65,%66,%67,%68,%69,%70,%71,%72,%73,%74,%75,%76,%77,%78,%79,"
      "%80,%81,%82,%83,%84,%85,%86,%87,%88,%89,%90,%91,%92,%93,%94,%95,"
      "%96,%97,%98,%99,%100,%101,%102,%103,%104,%105,%106,%107,%108,%109,%110,%111,"
      "%112,%113,%114,%115,%116,%117,%118,%119,%120,%121,%122,%123,%124,%125,%126,%127"
      "}, %128, %129, p, 1, 1, 0, 1;}\n"
      : "+f"(d[0]),"+f"(d[1]),"+f"(d[2]),"+f"(d[3]),"+f"(d[4]),"+f"(d[5]),"+f"(d[6]),"+f"(d[7]),
        "+f"(d[8]),"+f"(d[9]),"+f"(d[10]),"+f"(d[11]),"+f"(d[12]),"+f"(d[13]),"+f"(d[14]),"+f"(d[15]),
        "+f"(d[16]),"+f"(d[17]),"+f"(d[18]),"+f"(d[19]),"+f"(d[20]),"+f"(d[21]),"+f"(d[22]),"+f"(d[23]),
        "+f"(d[24]),"+f"(d[25]),"+f"(d[26]),"+f"(d[27]),"+f"(d[28]),"+f"(d[29]),"+f"(d[30]),"+f"(d[31]),
        "+f"(d[32]),"+f"(d[33]),"+f"(d[34]),"+f"(d[35]),"+f"(d[36]),"+f"(d[37]),"+f"(d[38]),"+f"(d[39]),
        "+f"(d[40]),"+f"(d[41]),"+f"(d[42]),"+f"(d[43]),"+f"(d[44]),"+f"(d[45]),"+f"(d[46]),"+f"(d[47]),
        "+f"(d[48]),"+f"(d[49]),"+f"(d[50]),"+f"(d[51]),"+f"(d[52]),"+f"(d[53]),"+f"(d[54]),"+f"(d[55]),
        "+f"(d[56]),"+f"(d[57]),"+f"(d[58]),"+f"(d[59]),"+f"(d[60]),"+f"(d[61]),"+f"(d[62]),"+f"(d[63]),
        "+f"(d[64]),"+f"(d[65]),"+f"(d[66]),"+f"(d[67]),"+f"(d[68]),"+f"(d[69]),"+f"(d[70]),"+f"(d[71]),
        "+f"(d[72]),"+f"(d[73]),"+f"(d[74]),"+f"(d[75]),"+f"(d[76]),"+f"(d[77]),"+f"(d[78]),"+f"(d[79]),
        "+f"(d[80]),"+f"(d[81]),"+f"(d[82]),"+f"(d[83]),"+f"(d[84]),"+f"(d[85]),"+f"(d[86]),"+f"(d[87]),
        "+f"(d[88]),"+f"(d[89]),"+f"(d[90]),"+f"(d[91]),"+f"(d[92]),"+f"(d[93]),"+f"(d[94]),"+f"(d[95]),
        "+f"(d[96]),"+f"(d[97]),"+f"(d[98]),"+f"(d[99]),"+f"(d[100]),"+f"(d[101]),"+f"(d[102]),"+f"(d[103]),
        "+f"(d[104]),"+f"(d[105]),"+f"(d[106]),"+f"(d[107]),"+f"(d[108]),"+f"(d[109]),"+f"(d[110]),"+f"(d[111]),
        "+f"(d[112]),"+f"(d[113]),"+f"(d[114]),"+f"(d[115]),"+f"(d[116]),"+f"(d[117]),"+f"(d[118]),"+f"(d[119]),
        "+f"(d[120]),"+f"(d[121]),"+f"(d[122]),"+f"(d[123]),"+f"(d[124]),"+f"(d[125]),"+f"(d[126]),"+f"(d[127])
      : "l"(da), "l"(db), "r"(sd));
}
__device__ __forceinline__ void wgmma_n192(float (&d)[96], uint64_t da, uint64_t db) {
  asm volatile("wgmma.mma_async.sync.aligned.m64n192k16.f32.bf16.bf16 {"
      "%0,%1,%2,%3,%4,%5,%6,%7,%8,%9,%10,%11,%12,%13,%14,%15,"
      "%16,%17,%18,%19,%20,%21,%22,%23,%24,%25,%26,%27,%28,%29,%30,%31,"
      "%32,%33,%34,%35,%36,%37,%38,%39,%40,%41,%42,%43,%44,%45,%46,%47,"
      "%48,%49,%50,%51,%52,%53,%54,%55,%56,%57,%58,%59,%60,%61,%62,%63,"
      "%64,%65,%66,%67,%68,%69,%70,%71,%72,%73,%74,%75,%76,%77,%78,%79,"
      "%80,%81,%82,%83,%84,%85,%86,%87,%88,%89,%90,%91,%92,%93,%94,%95"
      "}, %96, %97, 1, 1, 1, 0, 1;\n"
      : "+f"(d[0]),"+f"(d[1]),"+f"(d[2]),"+f"(d[3]),"+f"(d[4]),"+f"(d[5]),"+f"(d[6]),"+f"(d[7]),
        "+f"(d[8]),"+f"(d[9]),"+f"(d[10]),"+f"(d[11]),"+f"(d[12]),"+f"(d[13]),"+f"(d[14]),"+f"(d[15]),
        "+f"(d[16]),"+f"(d[17]),"+f"(d[18]),"+f"(d[19]),"+f"(d[20]),"+f"(d[21]),"+f"(d[22]),"+f"(d[23]),
        "+f"(d[24]),"+f"(d[25]),"+f"(d[26]),"+f"(d[27]),"+f"(d[28]),"+f"(d[29]),"+f"(d[30]),"+f"(d[31]),
        "+f"(d[32]),"+f"(d[33]),"+f"(d[34]),"+f"(d[35]),"+f"(d[36]),"+f"(d[37]),"+f"(d[38]),"+f"(d[39]),
        "+f"(d[40]),"+f"(d[41]),"+f"(d[42]),"+f"(d[43]),"+f"(d[44]),"+f"(d[45]),"+f"(d[46]),"+f"(d[47]),
        "+f"(d[48]),"+f"(d[49]),"+f"(d[50]),"+f"(d[51]),"+f"(d[52]),"+f"(d[53]),"+f"(d[54]),"+f"(d[55]),
        "+f"(d[56]),"+f"(d[57]),"+f"(d[58]),"+f"(d[59]),"+f"(d[60]),"+f"(d[61]),"+f"(d[62]),"+f"(d[63]),
        "+f"(d[64]),"+f"(d[65]),"+f"(d[66]),"+f"(d[67]),"+f"(d[68]),"+f"(d[69]),"+f"(d[70]),"+f"(d[71]),
        "+f"(d[72]),"+f"(d[73]),"+f"(d[74]),"+f"(d[75]),"+f"(d[76]),"+f"(d[77]),"+f"(d[78]),"+f"(d[79]),
        "+f"(d[80]),"+f"(d[81]),"+f"(d[82]),"+f"(d[83]),"+f"(d[84]),"+f"(d[85]),"+f"(d[86]),"+f"(d[87]),
        "+f"(d[88]),"+f"(d[89]),"+f"(d[90]),"+f"(d[91]),"+f"(d[92]),"+f"(d[93]),"+f"(d[94]),"+f"(d[95])
      : "l"(da), "l"(db));
}
template <int SD>
__device__ __forceinline__ void wgmma_rs_n128(float (&d)[64], uint32_t a0, uint32_t a1, uint32_t a2, uint32_t a3, uint64_t db) {
  asm volatile("wgmma.mma_async.sync.aligned.m64n128k16.f32.bf16.bf16 {"
      "%0,%1,%2,%3,%4,%5,%6,%7,%8,%9,%10,%11,%12,%13,%14,%15,"
      "%16,%17,%18,%19,%20,%21,%22,%23,%24,%25,%26,%27,%28,%29,%30,%31,"
      "%32,%33,%34,%35,%36,%37,%38,%39,%40,%41,%42,%43,%44,%45,%46,%47,"
      "%48,%49,%50,%51,%52,%53,%54,%55,%56,%57,%58,%59,%60,%61,%62,%63"
      "}, {%64,%65,%66,%67}, %68, %69, 1, 1, 1;\n"
      : "+f"(d[0]),"+f"(d[1]),"+f"(d[2]),"+f"(d[3]),"+f"(d[4]),"+f"(d[5]),"+f"(d[6]),"+f"(d[7]),
        "+f"(d[8]),"+f"(d[9]),"+f"(d[10]),"+f"(d[11]),"+f"(d[12]),"+f"(d[13]),"+f"(d[14]),"+f"(d[15]),
        "+f"(d[16]),"+f"(d[17]),"+f"(d[18]),"+f"(d[19]),"+f"(d[20]),"+f"(d[21]),"+f"(d[22]),"+f"(d[23]),
        "+f"(d[24]),"+f"(d[25]),"+f"(d[26]),"+f"(d[27]),"+f"(d[28]),"+f"(d[29]),"+f"(d[30]),"+f"(d[31]),
        "+f"(d[32]),"+f"(d[33]),"+f"(d[34]),"+f"(d[35]),"+f"(d[36]),"+f"(d[37]),"+f"(d[38]),"+f"(d[39]),
        "+f"(d[40]),"+f"(d[41]),"+f"(d[42]),"+f"(d[43]),"+f"(d[44]),"+f"(d[45]),"+f"(d[46]),"+f"(d[47]),
        "+f"(d[48]),"+f"(d[49]),"+f"(d[50]),"+f"(d[51]),"+f"(d[52]),"+f"(d[53]),"+f"(d[54]),"+f"(d[55]),
        "+f"(d[56]),"+f"(d[57]),"+f"(d[58]),"+f"(d[59]),"+f"(d[60]),"+f"(d[61]),"+f"(d[62]),"+f"(d[63])
      : "r"(a0), "r"(a1), "r"(a2), "r"(a3), "l"(db), "n"(SD));
}

constexpr int C_LN = 0, C_PX = 16, C_PY = 32;
constexpr int NB_CONS = 1, NB_LN = 2, NB_LAG = 4, NB_INIT = 6, NB_RDY = 7, NB_WG = 8;
#define LAGX 3
#define LAGY 3
#define LAG2 5
#define NLL 2
#define POLL_DELAY3 900
#define POLL_DELAY 1100
#define FILT_DELAY 1000
#define THR_B 0
#define THR_P 0
#define SPEC -1
#define WARM 4
#define HWARM 0
#define RING_SIG 1
#define PF2_SIG 1
constexpr int SM_E = 0, SM_X = 16384, SM_E2 = 32768, SM_W = 49152, SM_FC = 69632, SM_T = 73728 - T1_BYTES;
constexpr unsigned long long KORDER = 0xBA9432DC876510ull;
constexpr unsigned long long BSLOT = 0x76532107653210ull, PSLOT = 0xDCBA984DCBA984ull;
constexpr uint32_t HI128 = desc_hi(1024, 1), HI64 = desc_hi(512, 2);

struct Bars {
  uint64_t full1[32], empty1[32], full2[16], fullA[8], empty2[8], fullP[16], emptyP[8], hbar, tbar, hint[3], sig[2], sbar;
  uint32_t epoch;
};

template <int NK, bool STORE>
__device__ __forceinline__ void make_p(const float (&acc)[NK * 16], float r0, float r1, uint4 (&p)[NK], uint4* pbase, int ks0, uint32_t tag) {
#pragma unroll
  for (int j = 0; j < NK; j++) {
    uint32_t w[4];
#pragma unroll
    for (int i = 0; i < 4; i++) {
      const int a = 8 * j + 2 * i, b = a + NK * 8;
      w[i] = pack2(swiglu(acc[a], acc[b], (i & 1) ? r1 : r0), swiglu(acc[a + 1], acc[b + 1], (i & 1) ? r1 : r0));
    }
    asm volatile("" : "+r"(w[0]), "+r"(w[1]), "+r"(w[2]), "+r"(w[3]));
    p[j] = make_uint4(w[0], w[1], w[2], w[3]);
    if (STORE) st_tag(pbase + ((ks0 + j) >> 2) * 1024 + ((ks0 + j) & 3) * 32, p[j], tag);
  }
}
__device__ __forceinline__ void spin_cycles(uint32_t n) {
  const uint32_t t0 = clock32();
  while (clock32() - t0 < n) {}
}

__device__ __forceinline__ void spin_until(uint32_t t) {
  float d[4] = {0.f, 0.f, 0.f, 0.f};
  while ((int)(clock32() - t) < 0) {
    if (HWARM) asm volatile("mma.sync.aligned.m16n8k16.row.col.f32.bf16.bf16.f32 {%0,%1,%2,%3}, {%4,%4,%4,%4}, {%4,%4}, {%0,%1,%2,%3};"
                            : "+f"(d[0]), "+f"(d[1]), "+f"(d[2]), "+f"(d[3]) : "r"(t));
  }
}

__global__ void __cluster_dims__(2, 1, 1) __launch_bounds__(NTHREADS, 1)
fused_kernel(const __nv_bfloat16* __restrict__ x, const Tables* __restrict__ tab, Scratch* __restrict__ scr,
             __nv_bfloat16* __restrict__ out, const char* __restrict__ wg_raw, const char* __restrict__ wu_raw,
             const char* __restrict__ wd_raw,
             const __grid_constant__ CUtensorMap tmWR, const __grid_constant__ CUtensorMap tmWI,
             const __grid_constant__ CUtensorMap tmGX, const __grid_constant__ CUtensorMap tmUX,
             const __grid_constant__ CUtensorMap tmGY, const __grid_constant__ CUtensorMap tmUY,
             const __grid_constant__ CUtensorMap tmD) {
  extern __shared__ __align__(1024) char smem_raw[];
  const uint32_t sbase = s2u(smem_raw);
  const uint32_t sbar = sbase + 14 * SLOT, sstat = sbar + 1280;
  const int tid = threadIdx.x, lane = tid & 31;
  const int c = blockIdx.x, rk = c & 1, f = (c >> 1) & 7, rb = 2 * (c >> 4) + rk;
  const int rb2 = 2 * (c >> 4) + (f >> 2), kh = (f >> 1) & 1, nq = 2 * (f & 1) + rk;
#define BAR(field, i) (sbar + (uint32_t)offsetof(Bars, field) + 8u * (i))
#define TOFF(field) (sbase + SM_T + (uint32_t)offsetof(Tables, field) + lane * 16)

  if (tid >= 256) {
    asm volatile("setmaxnreg.dec.sync.aligned.u32 56;");
    const int warp = __shfl_sync(0xffffffffu, tid >> 5, 0);
    if (lane == 0) {
      if (warp == 8) {
        if (sbase & 1023) die();
#pragma unroll
        for (int i = 0; i < 16; i++) mbar_init(BAR(emptyP, i), i < 7 ? 16 : i < 8 ? 8 : i < 13 ? 1 : i < 15 ? 8 : 32);
        mbar_expect(BAR(tbar, 0), T2_BYTES + 2 * 10240);
        mbar_expect(BAR(hbar, 0), 16384);
      } else if (warp == 9) {
#pragma unroll
        for (int i = 0; i < 32; i++) mbar_init(BAR(full1, i), 1);
#pragma unroll
        for (int i = 0; i < 32; i++) mbar_expect(BAR(full1, i), i < 16 ? 16384 : 12288);
      } else if (warp == 10) {
#pragma unroll
        for (int i = 0; i < 32; i++) mbar_init(BAR(empty1, i), 16);
#pragma unroll
        for (int i = 0; i < 14; i++) mbar_init(BAR(fullP, i), 1);
#pragma unroll
        for (int i = 0; i < 14; i++) mbar_expect(BAR(fullP, i), 16384);
      } else {
#pragma unroll
        for (int i = 0; i < 32; i++) mbar_init(BAR(full2, i), i < 24 ? 1 : 8);
#pragma unroll
        for (int i = 0; i < 24; i++) mbar_expect(BAR(full2, i), 16384);
      }
      asm volatile("fence.mbarrier_init.release.cluster;" ::: "memory");
    }
    if (tid == 256) {
      const int w0 = ((c >> 3) * 257 + 32 * (c & 7) + 1) & ~7;
      if (FILT_DELAY) {
        asm volatile("prefetch.tensormap [%0];" ::"l"(&tmWR) : "memory");
        asm volatile("prefetch.tensormap [%0];" ::"l"(&tmWI) : "memory");
        spin_cycles(FILT_DELAY);
      }
      tma3(sbase + SM_W, &tmWR, BAR(tbar, 0), w0, 0, 0);
      tma3(sbase + SM_W + 10240, &tmWI, BAR(tbar, 0), w0, 0, 0);
      bulk_load(sbase + SM_T + T1_BYTES, reinterpret_cast<const char*>(tab) + T1_BYTES, T2_BYTES, BAR(tbar, 0));
    }
    if (tid == 288) {
      asm volatile("prefetch.tensormap [%0];" ::"l"(rk ? &tmUX : &tmGX) : "memory");
      asm volatile("prefetch.tensormap [%0];" ::"l"(rk ? &tmUY : &tmGY) : "memory");
      asm volatile("prefetch.tensormap [%0];" ::"l"(&tmD) : "memory");
    }
    if (tid == 320) {
      const unsigned e = ld_relaxed(&scr->cnt[(C_LN + rb) * 32]) >> 3;
      asm volatile("st.shared.u32 [%0], %1;" ::"r"(BAR(epoch, 0)), "r"(e) : "memory");
    }
    __syncwarp();
    asm volatile("barrier.cluster.arrive.relaxed.aligned;" ::: "memory");
    bar_arrive(NB_RDY, 384);
    asm volatile("barrier.cluster.wait.aligned;" ::: "memory");
    bar_sync(NB_INIT, 384);
    unsigned epoch;
    asm volatile("ld.shared.u32 %0, [%1];" : "=r"(epoch) : "r"(BAR(epoch, 0)) : "memory");
    if (warp == 8) {
      if (lane == 0) {
        const int ax = (7 * f + 3 * (f & 1)) >> 1;
        const int ay = 7 * f + ((f & 1) ? 0 : 4);
        const CUtensorMap* tx = rk ? &tmUX : &tmGX;
        const CUtensorMap* ty = rk ? &tmUY : &tmGY;
        if (RING_SIG >= 0) mbar_wait(BAR(sig, RING_SIG));
        uint32_t s = 2;
#pragma unroll 1
        for (int n = 0; n < 16; n++) {
          if (n >= 6) mbar_wait(BAR(empty1, n - 6));
          tma3_mc(sbase + (8 + s) * SLOT + rk * 8192, tx, BAR(full1, n), n * 32, ax);
          if (++s == 6) s = 0;
        }
#pragma unroll 1
        for (int k = 0; k < 16; k++) {
          mbar_wait(BAR(empty1, k < 8 ? 10 + ((12 * k + 11) >> 4) : 8 + k));
          tma3_mc(sbase + 8 * SLOT + (k & 7) * 12288 + rk * 6144, ty, BAR(full1, 16 + k), k * 32, ay);
        }
      }
    } else if (warp == 9) {
      if (lane == 0) {
#pragma unroll 1
        for (int i = 0; i < 14; i++) {
          const int kblk = 14 * kh + (int)((KORDER >> (4 * i)) & 15);
          const int j = i < 7 ? i : i - 7, sl = j + (j >= 4);
          mbar_wait(i < 7 ? BAR(empty1, 17 + 2 * sl) : BAR(empty2, j));
          if (THR_B && i >= THR_B) mbar_wait(BAR(full2, i - THR_B));
          tma3(sbase + sl * SLOT, &tmD, BAR(full2, i), 0, 64 * kblk, 2 * nq);
        }
        wait_counter(&scr->cnt[(C_LN + rb2) * 32], (epoch + 1) * 8);
        asm volatile("fence.proxy.async.global;" ::: "memory");
        mbar_wait(BAR(emptyP, 7));
        bulk_load(sbase + 4 * SLOT, &scr->LN[(rb2 * 8 + 2 * nq) * 1024 + (kh ^ 1) * 512], 8192, BAR(hbar, 0));
        bulk_load(sbase + 4 * SLOT + 8192, &scr->LN[(rb2 * 8 + 2 * nq + 1) * 1024 + (kh ^ 1) * 512], 8192, BAR(hbar, 0));
      }
    } else if (warp == 10) {
      bar_sync(NB_LN, 288);
      if (lane == 0) {
        PROFP(0);
        red_release(&scr->cnt[(C_LN + rb) * 32]);
        PROFP(1);
        wait_counter(&scr->cnt[(C_LN + rb) * 32], (epoch + 1) * 8);
        asm volatile("fence.proxy.async.global;" ::: "memory");
        PROFP(2);
#pragma unroll 1
        for (int kb = NLL; kb < 8; kb++) bulk_load(sbase + kb * SLOT, &scr->LN[(rb * 8 + kb) * 1024], 16384, BAR(fullA, kb));
#pragma unroll 1
        for (int s = 0; s < 14; s++) {
          const int kblk = 14 * kh + (int)((KORDER >> (4 * s)) & 15);
          if (s == 0 || (SPEC < 0 && (s == 8 || s == 11))) {
            if (s != 11) PROFP(3 + (s >> 2));
            mbar_wait(BAR(hint, s == 0 ? 0 : s == 8 ? 1 : 2), 0);
            if (s != 11) PROFP(4 + (s >> 2));
          }
          const int j = s < 7 ? s : s - 7;
          mbar_wait(s < 7 ? BAR(empty1, 24 + s + (s == 0) + (s >= 4)) : BAR(emptyP, j));
          if (THR_P && s >= THR_P) mbar_wait(BAR(fullP, s - THR_P));
          if (SPEC >= 0 && s == 8) mbar_wait(BAR(emptyP, SPEC & 7));
          bulk_load_mc(sbase + (j ? 7 + j : 4) * SLOT + rk * 8192, &scr->P[(rb2 * 28 + kblk) * 1024 + rk * 512], 8192, BAR(fullP, s));
        }
        PROFP(7);
      }
    } else {
      if (lane == 0) {
        l2_prefetch(wg_raw + (size_t)c * 5376, 5376);
        l2_prefetch(wu_raw + (size_t)c * 5376, 5376);
        mbar_wait(BAR(sig, PF2_SIG), 0);
        l2_prefetch(wg_raw + 688128 + (size_t)c * 8960, 8960);
        l2_prefetch(wu_raw + 688128 + (size_t)c * 8960, 8960);
      }
      mbar_wait(BAR(fullA, 7), 0);
      if (lane == 0) l2_prefetch(wd_raw + (size_t)c * 14336, 14336);
      {
        const uint32_t tag = (epoch + 1) & 1;
        uint4 v0, v1, v2;
        int it = 0;
        while (true) {
          v0 = ld_b128(&scr->ST[rb * 64 + lane]);
          v1 = ld_b128(&scr->ST[rb * 64 + 32 + lane]);
          v2 = ld_b128(&scr->ST[rb2 * 64 + 32 * (kh ^ 1) + lane]);
          if (!__any_sync(0xffffffffu, ((v0.x ^ tag) | (v1.x ^ tag) | (v2.x ^ tag)) & 1u)) break;
          if (++it > SPIN_LIMIT) { die(); break; }
        }
        sts4(sstat + lane * 16, v0.x & ~1u, v0.y, v0.z, v0.w);
        sts4(sstat + 512 + lane * 16, v1.x & ~1u, v1.y, v1.z, v1.w);
        sts4(sstat + 1024 + lane * 16, v2.x & ~1u, v2.y, v2.z, v2.w);
#pragma unroll 4
        for (int i = 0; i < 32; i++)
          st_tag(&scr->XP[(c ^ 4) * 1024 + i * 32 + lane], make_uint4(0, 0, 0, 0), tag ^ 1);
        mbar_arrive(BAR(sbar, 0));
      }
      if (lane == 0) {
        mbar_wait(BAR(empty1, 17));
#pragma unroll 1
        for (int e = 0; e < (SPEC < 0 ? 3 : 1); e++) {
          const unsigned* cp = e == 0 ? &scr->cnt[(C_PX + rb2) * 32] : &scr->cnt[(C_PY + rb2) * 32 + 2 * kh + e - 1];
          if (e == 1) mbar_wait(BAR(fullP, 0), 0);
          int it = 0;
          while ((int)(ld_relaxed(cp) - (epoch + 1) * (e == 0 ? 64 : 16)) < 0)
            if (++it > SPIN_LIMIT) { die(); break; }
          mbar_arrive(BAR(hint, e));
        }
      }
    }
  } else {
    const int warp = __shfl_sync(0xffffffffu, tid >> 5, 0);
    const int g = lane >> 2, t = lane & 3;
    PROF(0);
    PROFG(14);
#pragma unroll
    for (int i = 0; i < 4; i++) {
      const int r = i >> 1, ch = (i & 1) * 32 + lane;
      cp_async16(sbase + SM_X + (2 * warp + r) * 1024 + ((ch ^ ((ch >> 2) & 6)) * 16),
                 x + (size_t)(c + 128 * (2 * warp + r)) * 512 + ch * 8);
    }
    asm volatile("cp.async.commit_group;" ::: "memory");
    asm volatile("barrier.cluster.arrive.relaxed.aligned;" ::: "memory");
    uint4 tw[8], fb[16];
    const uint4 fa = ldg_ca4_p(1, &tab->fa[lane][0]);
#pragma unroll
    for (int i = 0; i < 8; i++) tw[i] = ldg_ca4_p(1, &tab->tw1[i][lane][0]);
#pragma unroll
    for (int i = 0; i < 16; i++) fb[i] = ldg_ca4_p(1, &tab->fb[i][lane][0]);
    uint32_t rbar;
    asm volatile("mapa.shared::cluster.u32 %0, %1, %2;" : "=r"(rbar) : "r"(sbar), "r"(rk ^ 1));
#define RBAR(field, i) (rbar + (uint32_t)offsetof(Bars, field) + 8u * (i))
    {
      const int ln = (tid >> 1) & 31, lg = ln >> 2, lt = ln & 3, i = 4 * (tid >> 6) + 2 * (tid & 1);
      const int kidx = lt + 8 * (i >> 3), nidx = 4 * ((i >> 1) & 3) + (lg >> 1);
      const uint32_t a0 = cfrag<2048>((c + 128 * kidx) * nidx, lg & 1), a1 = cfrag<2048>((c + 128 * (kidx + 4)) * nidx, lg & 1);
      const uint32_t b0 = cfrag<2048>(-(c + 128 * nidx) * kidx, lg & 1), b1 = cfrag<2048>(-(c + 128 * nidx) * (kidx + 4), lg & 1);
      asm volatile("st.shared.v2.u32 [%0], {%1,%2};" ::"r"(sbase + SM_FC + tid * 8), "r"(a0), "r"(a1) : "memory");
      asm volatile("st.shared.v2.u32 [%0], {%1,%2};" ::"r"(sbase + SM_FC + 2048 + tid * 8), "r"(b0), "r"(b1) : "memory");
    }
    asm volatile("cp.async.wait_group 0;" ::: "memory");
    __syncwarp();
    bar_arrive(NB_INIT, 384);
    PROF(13);
    uint32_t tag;
    uint4 q[4], o[4];
    {
      uint32_t v[2][8];
#pragma unroll
      for (int r = 0; r < 2; r++)
#pragma unroll
        for (int q = 0; q < 4; q++) {
          const uint2 u = lds2(sbase + SM_X + (2 * warp + r) * 1024 + (t + 4 * (q >> 1)) * 128 + (((4 * (q & 1) + (g >> 1)) ^ (2 * t)) * 16) + (g & 1) * 8);
          v[r][2 * q] = u.x; v[r][2 * q + 1] = u.y;
        }
      float sum[2], sq[2], rstd[2];
      row_stats(v[0], v[1], lane, sum, sq);
#pragma unroll
      for (int r = 0; r < 2; r++) {
        const float m = sum[r] * (1.f / 512.f);
        rstd[r] = rsqrtf(fmaxf(fmaf(-m, m, sq[r] * (1.f / 512.f)), 0.f) + 1e-5f);
      }
      uint32_t alo[4][4], ahi[4][4];
#pragma unroll
      for (int r = 0; r < 2; r++)
#pragma unroll
        for (int i = 0; i < 4; i++) {
          const uint32_t sel = (i & 1) ? 0x7632u : 0x5410u;
          const uint32_t b0 = __byte_perm(v[r][i >> 1], v[r][2 + (i >> 1)], sel);
          const uint32_t b1 = __byte_perm(v[r][4 + (i >> 1)], v[r][6 + (i >> 1)], sel);
          float d[4] = {0.f, 0.f, 0.f, 0.f};
          mma16816(d, fa.x, fa.y, fa.z, fa.w, b0, b1);
          const uint4 &ka = tw[2 * i], &kb = tw[2 * i + 1];
          const uint32_t re = pack2(d[0] * __uint_as_float(ka.x) + d[2] * __uint_as_float(ka.y), d[1] * __uint_as_float(kb.x) + d[3] * __uint_as_float(kb.y));
          const uint32_t im = pack2(d[0] * __uint_as_float(ka.z) + d[2] * __uint_as_float(ka.w), d[1] * __uint_as_float(kb.z) + d[3] * __uint_as_float(kb.w));
          const uint32_t dc = pack2(fmaf(sum[r], -1.f / 32.f, d[0]), fmaf(sum[r], -1.f / 32.f, d[1]));
          alo[i][r] = re; alo[i][2 + r] = im;
          ahi[i][r] = g == 0 ? dc : re; ahi[i][2 + r] = g == 0 ? 0u : im;
        }
      float acc[8][4];
#pragma unroll
      for (int u = 0; u < 8; u++) {
        acc[u][0] = acc[u][1] = acc[u][2] = acc[u][3] = 0.f;
#pragma unroll
        for (int i = 0; i < 4; i++) {
          const uint4& bq = fb[i * 4 + (u >> 1)];
          if (u < 4) mma16816(acc[u], alo[i][0], alo[i][1], alo[i][2], alo[i][3], (u & 1) ? bq.z : bq.x, (u & 1) ? bq.w : bq.y);
          else       mma16816(acc[u], ahi[i][0], ahi[i][1], ahi[i][2], ahi[i][3], (u & 1) ? bq.z : bq.x, (u & 1) ? bq.w : bq.y);
        }
      }
#pragma unroll
      for (int r = 0; r < 2; r++)
#pragma unroll
        for (int h = 0; h < 2; h++) {
          const int j = 2 * warp + r, m = 2 * t + h;
          const float rs = rstd[r];
          sts4(sbase + SM_E + ((j * 8 + m) * 8 + (g ^ (2 * t) ^ (2 * (j & 3)))) * 16,
               pack2(acc[2 * h][2 * r] * rs, acc[2 * h][2 * r + 1] * rs), pack2(acc[2 * h + 1][2 * r] * rs, acc[2 * h + 1][2 * r + 1] * rs),
               pack2(acc[4 + 2 * h][2 * r] * rs, acc[4 + 2 * h][2 * r + 1] * rs), pack2(acc[5 + 2 * h][2 * r] * rs, acc[5 + 2 * h][2 * r + 1] * rs));
        }
      if (tid == 0) PROFP(12);
      bar_sync(NB_RDY, 384);
      if (tid == 0) PROFP(13);
      uint4 fc[4];
#pragma unroll
      for (int i = 0; i < 4; i++) fc[i] = lds4(sbase + SM_FC + i * 512 + lane * 16);
      asm volatile("ld.shared.u32 %0, [%1];" : "=r"(tag) : "r"(BAR(epoch, 0)) : "memory");
      tag = (tag + 1) & 1;
#pragma unroll
      for (int i = 0; i < 4; i++) q[i] = lds4(sbase + SM_E + (((t + 4 * i) * 8 + warp) * 8 + (g ^ (warp & 6) ^ (2 * t))) * 16);
      cdft16(q, fc, o);
#pragma unroll
      for (int vv = 0; vv < 4; vv++) st_tag(&scr->Z1[(((4 * vv + t) * 8 + warp) * 128 + c) * 8 + g], o[vv], tag);
    }
    PROF(1);
    asm volatile("setmaxnreg.inc.sync.aligned.u32 224;");
    {
      const uint4* const zp = &scr->Z1[(c * 128 + 8 * t + warp) * 8 + g];
      const uint32_t tst = clock32();
      mbar_wait(BAR(tbar, 0), 0);
      if (tid == 0) PROFP(14);
      uint4 f2[4], g2[4];
#pragma unroll
      for (int i = 0; i < 4; i++) {
        f2[i] = lds4(TOFF(f2) + warp * 2048 + i * 512);
        g2[i] = lds4(TOFF(g2) + warp * 2048 + i * 512);
      }
      const uint4 f8 = lds4(TOFF(f8)), g8 = lds4(TOFF(g8));
      float wfr[16], wfi[16];
      {
        const float fsc = 1.f / (1 << 19);
        const float fsc3 = ((c & 7) == 7 && g == 0) ? 0.5f * fsc : fsc;
        const int gg = g == 0 ? 8 : g, wsh = (2 * (c >> 3) + 2) & 15;
#pragma unroll
        for (int i = 0; i < 16; i++) {
          const int ci = i >> 3, dd = (i >> 2) & 1, e = i & 3;
          const int kk = (e == 0 ? gg : e == 1 ? 16 + gg : e == 2 ? 16 - g : 32 - g) - 1;
          const uint32_t a = sbase + SM_W + ((2 * warp + ci) * 8 + t + 4 * dd) * 80 + wsh + 2 * kk;
          wfr[i] = bf_lo(lds_u16(a)) * (e == 3 ? fsc3 : fsc);
          wfi[i] = bf_lo(lds_u16(a + 10240)) * (e == 3 ? fsc3 : fsc);
        }
      }
      asm volatile("barrier.cluster.wait.aligned;" ::: "memory");
      PROF(2);
      spin_until(tst + POLL_DELAY);
      ld_tag4_issue<256>(q, zp);
      ld_tag4_finish<256>(q, zp, tag);
      if (tid == 0) PROFP(30);
      if (lane == 0) mbar_arrive(BAR(sig, 0));
      cdft16(q, f2, o);
      const uint32_t e2 = sbase + SM_E2;
#pragma unroll
      for (int vv = 0; vv < 4; vv++)
        sts4(e2 + ((warp * 16 + 4 * vv + t) * 8 + (g ^ (2 * t) ^ (2 * (warp & 3)))) * 16, o[vv].x, o[vv].y, o[vv].z, o[vv].w);
      bar_sync(NB_CONS, 256);
#pragma unroll
      for (int ci = 0; ci < 2; ci++) {
        const int cc = 2 * warp + ci;
        uint32_t ad[2];
        uint4 u[2];
#pragma unroll
        for (int hh = 0; hh < 2; hh++) {
          ad[hh] = e2 + (((t + 4 * hh) * 16 + cc) * 8 + (g ^ (2 * (cc & 3)) ^ (2 * t))) * 16;
          u[hh] = lds4(ad[hh]);
        }
        uint32_t res[2][4];
#pragma unroll
        for (int p = 0; p < 2; p++) {
          uint32_t y[2][2];
#pragma unroll
          for (int vv = 0; vv < 2; vv++) {
            float d[4] = {0.f, 0.f, 0.f, 0.f};
            mma16816(d, word(u[0], 2 * p), word(u[0], 2 * p + 1), word(u[1], 2 * p), word(u[1], 2 * p + 1), word(f8, 2 * vv), word(f8, 2 * vv + 1));
#pragma unroll
            for (int rr = 0; rr < 2; rr++) {
              const float fr = wfr[ci * 8 + vv * 4 + 2 * p + rr], fi = wfi[ci * 8 + vv * 4 + 2 * p + rr];
              y[vv][rr] = pack2(d[2 * rr] * fr - d[2 * rr + 1] * fi, d[2 * rr] * fi + d[2 * rr + 1] * fr);
            }
          }
#pragma unroll
          for (int vv = 0; vv < 2; vv++) {
            float d[4] = {0.f, 0.f, 0.f, 0.f};
            mma16816(d, y[0][0], y[0][1], y[1][0], y[1][1], word(g8, 2 * vv), word(g8, 2 * vv + 1));
            res[vv][2 * p] = pack2(d[0], d[1]);
            res[vv][2 * p + 1] = pack2(d[2], d[3]);
          }
        }
#pragma unroll
        for (int vv = 0; vv < 2; vv++) sts4(ad[vv], res[vv][0], res[vv][1], res[vv][2], res[vv][3]);
      }
      bar_sync(NB_CONS, 256);
#pragma unroll
      for (int i = 0; i < 4; i++) q[i] = lds4(e2 + ((warp * 16 + 4 * i + t) * 8 + (g ^ (2 * t) ^ (2 * (warp & 3)))) * 16);
      cdft16(q, g2, o);
#pragma unroll
      for (int vv = 0; vv < 4; vv++) st_tag(&scr->Z2[((8 * (4 * vv + t) + warp) * 128 + c) * 8 + g], o[vv], tag);
    }
    PROF(3);
    {
      const uint4* const zp = &scr->Z2[((c * 16 + t) * 8 + warp) * 8 + g];
      const uint32_t tst = clock32();
      uint4 gb[16], gc[4], tw[4], xr[2][2];
#pragma unroll
      for (int i = 0; i < 16; i++) gb[i] = lds4(TOFF(gb) + i * 512);
      const uint4 ga = lds4(TOFF(ga));
#pragma unroll
      for (int i = 0; i < 4; i++) {
        gc[i] = lds4(sbase + SM_FC + 2048 + i * 512 + lane * 16);
        tw[i] = lds4(TOFF(tw3) + i * 512);
        const int ch = 4 * (g + 8 * (i & 1)) + t;
        xr[i >> 1][i & 1] = lds4(sbase + SM_X + (2 * warp + (i >> 1)) * 1024 + ((ch ^ ((ch >> 2) & 6)) * 16));
      }
      PROF(4);
      spin_until(tst + POLL_DELAY);
      ld_tag4_issue<256>(q, zp);
      ld_tag4_finish<256>(q, zp, tag);
      if (tid == 0) PROFP(31);
      if (lane == 0) mbar_arrive(BAR(sig, 1));
      cdft16(q, gc, o);
#pragma unroll
      for (int vv = 0; vv < 4; vv++)
        sts4(sbase + SM_E + (((4 * vv + t) * 8 + warp) * 8 + (g ^ (warp & 6) ^ (2 * t))) * 16, o[vv].x, o[vv].y, o[vv].z, o[vv].w);
      if (tid == 0) PROFP(8);
      bar_sync(NB_CONS, 256);
      if (tid == 0) PROFP(9);
      uint32_t hv[2][8];
      const float mk = t == 0 ? 0.f : 1.f;
#pragma unroll
      for (int r = 0; r < 2; r++) {
        const int j = 2 * warp + r;
        uint4 u[2];
#pragma unroll
        for (int h = 0; h < 2; h++) u[h] = lds4(sbase + SM_E + ((j * 8 + 2 * t + h) * 8 + (g ^ (2 * t) ^ (2 * (j & 3)))) * 16);
        float yv[4][4];
#pragma unroll
        for (int i = 0; i < 4; i++) {
          float lo[4] = {0.f, 0.f, 0.f, 0.f}, hi[4] = {0.f, 0.f, 0.f, 0.f};
          mma16816(lo, gb[i * 4].x, gb[i * 4].y, gb[i * 4].z, gb[i * 4].w, u[0].x, u[0].y);
          mma16816(lo, gb[i * 4 + 1].x, gb[i * 4 + 1].y, gb[i * 4 + 1].z, gb[i * 4 + 1].w, u[1].x, u[1].y);
          mma16816(hi, gb[i * 4 + 2].x, gb[i * 4 + 2].y, gb[i * 4 + 2].z, gb[i * 4 + 2].w, u[0].z, u[0].w);
          mma16816(hi, gb[i * 4 + 3].x, gb[i * 4 + 3].y, gb[i * 4 + 3].z, gb[i * 4 + 3].w, u[1].z, u[1].w);
          const float ca = __uint_as_float(tw[i].x), sa = __uint_as_float(tw[i].y), cb = __uint_as_float(tw[i].z), sb = __uint_as_float(tw[i].w);
          const float tr0 = fmaf(hi[0], mk, lo[0]), ti0 = fmaf(hi[2], mk, lo[2]);
          const float tr1 = lo[1] + hi[1], ti1 = lo[3] + hi[3];
          const float vr0 = tr0 * ca - ti0 * sa, vi0 = tr0 * sa + ti0 * ca;
          const float vr1 = tr1 * cb - ti1 * sb, vi1 = tr1 * sb + ti1 * cb;
          const uint32_t b0 = pack2(t == 0 ? hi[0] : vr0, vr1), b1 = pack2(t == 0 ? vr0 : vi0, vi1);
          yv[i][0] = yv[i][1] = yv[i][2] = yv[i][3] = 0.f;
          mma16816(yv[i], ga.x, ga.y, ga.z, ga.w, b0, b1);
        }
#pragma unroll
        for (int h = 0; h < 2; h++) {
          hv[r][4 * h + 0] = hadd2_bf16(xr[r][h].x, pack2(yv[0][2 * h], yv[1][2 * h]));
          hv[r][4 * h + 1] = hadd2_bf16(xr[r][h].y, pack2(yv[2][2 * h], yv[3][2 * h]));
          hv[r][4 * h + 2] = hadd2_bf16(xr[r][h].z, pack2(yv[0][2 * h + 1], yv[1][2 * h + 1]));
          hv[r][4 * h + 3] = hadd2_bf16(xr[r][h].w, pack2(yv[2][2 * h + 1], yv[3][2 * h + 1]));
        }
      }
      if (tid == 0 && hv[0][0] != 0x12345 && hv[1][7] != 0x12345) PROFP(10);
      float ds[4] = {0.f, 0.f, 0.f, 0.f};
#pragma unroll
      for (int q4 = 0; q4 < 4; q4++) mma16816(ds, hv[0][2 * q4], hv[1][2 * q4], hv[0][2 * q4 + 1], hv[1][2 * q4 + 1], 0x3f803f80u, 0x3f803f80u);
#pragma unroll
      for (int o2 = 4; o2 <= 16; o2 <<= 1) {
        ds[0] += __shfl_xor_sync(0xffffffffu, ds[0], o2);
        ds[2] += __shfl_xor_sync(0xffffffffu, ds[2], o2);
      }
      uint32_t mb[2];
#pragma unroll
      for (int r = 0; r < 2; r++) mb[r] = pack2(ds[2 * r] * (1.f / 512.f), ds[2 * r] * (1.f / 512.f));
#pragma unroll
      for (int h = 0; h < 2; h++)
#pragma unroll
        for (int r = 0; r < 2; r++) {
          const int row = 16 * f + 2 * warp + r, n1 = g + 8 * h;
#pragma unroll
          for (int i = 0; i < 4; i++) hv[r][4 * h + i] = hsub2_bf16(hv[r][4 * h + i], mb[r]);
          st_tag(&scr->LN[(rb * 8 + (n1 >> 1)) * 1024 + row * 8 + ((4 * (n1 & 1) + t) ^ (row & 7))],
                 make_uint4(hv[r][4 * h], hv[r][4 * h + 1], hv[r][4 * h + 2], hv[r][4 * h + 3]), n1 < 2 * NLL ? tag : (hv[r][4 * h] & 1u));
        }
      if (tid == 0) PROFP(11);
      bar_arrive(NB_LN, 288);
      float sum[2], sq[2], rstd[2];
      row_stats(hv[0], hv[1], lane, sum, sq);
#pragma unroll
      for (int r = 0; r < 2; r++) {
        const float m = sum[r] * (1.f / 512.f);
        rstd[r] = rsqrtf(fmaxf(fmaf(-m, m, sq[r] * (1.f / 512.f)), 0.f) + 1e-5f);
      }
      if (lane == 0)
        st_tag(&scr->ST[rb * 64 + 8 * f + warp], make_uint4(mb[0] << 16, __float_as_uint(rstd[0]), mb[1] << 16, __float_as_uint(rstd[1])), tag);
    }
    PROF(5);
    const int wgi = warp >> 2, wq = warp & 3;
    uint4* const pbase = &scr->P[rb * 28 * 1024 + warp * 128 + lane];
    const uint32_t a_lo0 = desc_lo(sbase + wgi * 8192, 16);
    const uint32_t ebar = lane == 0 ? BAR(empty1, 0) : RBAR(empty1, 0);
    float r0, r1;
    uint4 px[8], py[6];
    const int rh = wgi ^ kh ^ 1;
    const uint4* const psrc = &scr->P[(rb2 * 28 + 14 * kh) * 1024 + (4 * rh + wq) * 128 + lane];
    {
      float acc[128];
#pragma unroll
      for (int i = 0; i < 128; i++) acc[i] = 0.f;
      const uint32_t b_lo0 = desc_lo(sbase + 8 * SLOT, 4096);
      const uint32_t t3 = clock32();
      if (WARM) {
        wg_fence();
#pragma unroll
        for (int i = 0; i < WARM; i++) wgmma_n256(acc, desc64(a_lo0 + 6 * 1024, HI128), desc64(b_lo0, HI128));
        wg_commit();
      }
      const uint4* const ap = &scr->LN[rb * 8 * 1024 + wgi * 512 + (tid & 127)];
      uint4 av[NLL][4];
      while (clock32() - t3 < POLL_DELAY3) {}
#pragma unroll
      for (int kb = 0; kb < NLL; kb++) ld_tag4_issue<128>(av[kb], ap + kb * 1024);
      bar_sync(NB_CONS, 256);
      uint32_t slot = 2;
      auto stage_x = [&](int kb, int hh) {
        if (LAGX && hh == ((16 - LAGX) & 1) && kb == ((16 - LAGX) >> 1) && wgi == 1) bar_sync(NB_LAG, 256);
        mbar_wait(BAR(full1, 2 * kb + hh));
        const uint32_t al = a_lo0 + kb * 1024 + hh * 4, bl = b_lo0 + slot * 1024;
        wg_fence();
        wgmma_n256(acc, desc64(al, HI128), desc64(bl, HI128), (kb | hh) != 0);
        wgmma_n256(acc, desc64(al + 2, HI128), desc64(bl + 128, HI128));
        wg_commit();
        if (LAGX && hh == 1 && kb == 7 && wgi == 0) bar_arrive(NB_LAG, 256);
        wg_wait<1>();
        if ((kb | hh) != 0 && lane < 2) mbar_arrive_remote(ebar + 8 * (2 * kb + hh - 1));
        if (++slot == 6) slot = 0;
      };
#pragma unroll
      for (int kb = 0; kb < NLL; kb++) {
        ld_tag4_finish<128>(av[kb], ap + kb * 1024, tag);
#pragma unroll
        for (int i = 0; i < 4; i++)
          sts4(sbase + kb * SLOT + wgi * 8192 + ((tid & 127) + 128 * i) * 16, av[kb][i].x, av[kb][i].y, av[kb][i].z, av[kb][i].w);
        asm volatile("fence.proxy.async.shared::cta;" ::: "memory");
        bar_sync(NB_WG + wgi, 128);
        if (kb > 0) stage_x(kb - 1, 1);
        if (kb == 0) PROF(6);
        stage_x(kb, 0);
      }
      stage_x(NLL - 1, 1);
#pragma unroll 1
      for (int kb = NLL; kb < 8; kb++) {
        mbar_wait(BAR(fullA, kb));
        stage_x(kb, 0);
        stage_x(kb, 1);
      }
      mbar_wait(BAR(sbar, 0), 0);
      r0 = __uint_as_float(lds2(sstat + (16 * warp + g) * 8).y);
      r1 = __uint_as_float(lds2(sstat + (16 * warp + g + 8) * 8).y);
      wg_wait<0>();
      if (lane < 2) mbar_arrive_remote(ebar + 8 * 15);
      PROF(7);
      make_p<8, false>(acc, r0, r1, px, pbase, 0, tag);
    }
    PROF(8);
    {
      float acc[96];
#pragma unroll
      for (int i = 0; i < 96; i++) acc[i] = 0.f;
      const uint32_t b_lo0 = desc_lo(sbase + 8 * SLOT, 2048);
      uint4* const pdst = pbase + ((7 * f + 3 * (f & 1)) >> 1) * 1024;
      auto stage_y = [&](int k) {
        if (LAGY && k == 16 - LAGY && wgi == 1) bar_sync(NB_LAG, 256);
        mbar_wait(BAR(full1, 16 + k));
        const uint32_t al = a_lo0 + (k >> 1) * 1024 + (k & 1) * 4, bl = b_lo0 + (k & 7) * 768;
        wg_fence();
        wgmma_n192(acc, desc64(al, HI128), desc64(bl, HI64));
        wgmma_n192(acc, desc64(al + 2, HI128), desc64(bl + 64, HI64));
        wg_commit();
      };
#pragma unroll
      for (int k = 0; k < 4; k++) {
        stage_y(k);
        st_tag(pdst + (k >> 1) * 1024 + (k & 1) * 64, px[2 * k], tag);
        st_tag(pdst + (k >> 1) * 1024 + (k & 1) * 64 + 32, px[2 * k + 1], tag);
        if (k == 3 && lane == 0) red_relaxed(&scr->cnt[(C_PX + rb) * 32]);
        wg_wait<1>();
        if (k != 0 && lane < 2) mbar_arrive_remote(ebar + 8 * (15 + k));
      }
#pragma unroll 1
      for (int k = 4; k < 16; k++) {
        stage_y(k);
        if (LAGY && k == 15 && wgi == 0) bar_arrive(NB_LAG, 256);
        wg_wait<1>();
        if (lane < 2) mbar_arrive_remote(ebar + 8 * (15 + k));
      }
      wg_wait<0>();
      if (lane < 2) mbar_arrive_remote(ebar + 8 * 31);
      PROF(9);
      make_p<6, true>(acc, r0, r1, py, pbase, 14 * f + ((f & 1) ? 0 : 8), tag);
      if (lane == 0) red_relaxed(&scr->cnt[(C_PY + rb) * 32 + (f >> 1)]);
    }
    PROF(10);
    {
      float acc[64];
      {
        const float m0 = wgi ? 0.f : __uint_as_float(lds2(sstat + 1024 + (16 * wq + g) * 8).x);
        const float m1 = wgi ? 0.f : __uint_as_float(lds2(sstat + 1024 + (16 * wq + g + 8) * 8).x);
#pragma unroll
        for (int i = 0; i < 64; i++) acc[i] = (i & 2) ? m1 : m0;
      }
      const uint32_t b2_lo0 = desc_lo(sbase, 8192);
      const uint32_t pa0 = sbase + (4 * rh + wq) * 2048;
      const uint32_t pbar = ebar + (uint32_t)(offsetof(Bars, emptyP) - offsetof(Bars, empty1));
      uint4 fa[3][4];
      uint32_t rdy = 0;
      mbar_wait(BAR(fullP, 0));
#pragma unroll
      for (int kk = 0; kk < 4; kk++) fa[0][kk] = lds4(pa0 + 4 * SLOT + kk * 512 + lane * 16);
#pragma unroll
      for (int s = 0; s < 14; s++) {
        uint4 (&a)[4] = fa[s % 3];
        ld_tag4_finish<32>(a, psrc + (int)((KORDER >> (4 * s)) & 15) * 1024, tag);
        if (s < 8 && lane < (s < 7 ? 2 : 1)) mbar_arrive_remote(pbar + 8 * s);
        if (s >= 2) {
          wg_wait<1>();
          if (s <= 8 && lane == 0) mbar_arrive(BAR(empty2, s - 2));
        }
        if (!rdy) {
          if (s < 13) mbar_wait(BAR(fullP, s + 1));
          mbar_wait(BAR(full2, s));
        }
        if (tid == 0) PROFP(16 + s);
        if (LAG2 && s == 14 - LAG2 && wgi == 1) bar_sync(NB_LAG, 256);
        const uint32_t bl = b2_lo0 + (uint32_t)((BSLOT >> (4 * s)) & 15) * 1024;
        wg_fence();
        if (s < 13) {
#pragma unroll
          for (int kk = 0; kk < 4; kk++)
            fa[(s + 1) % 3][kk] = lds4(pa0 + (uint32_t)((PSLOT >> (4 * (s + 1))) & 15) * SLOT + kk * 512 + lane * 16);
          rdy = mbar_test(BAR(full2, s + 1));
          if (s < 12) rdy &= mbar_test(BAR(fullP, s + 2));
        }
#pragma unroll
        for (int kk = 0; kk < 4; kk++) wgmma_rs_n128<1>(acc, a[kk].x, a[kk].y, a[kk].z, a[kk].w, desc64(bl + kk * 128, HI128));
        wg_commit();
      }
      if (LAG2 && wgi == 0) bar_arrive(NB_LAG, 256);
      uint4 pv[2][4];
      const uint4* const xsrc = &scr->XP[c * 1024 + (tid & 127)];
      if (wgi == 1) {
        ld_tag4_issue<128>(pv[0], xsrc);
        ld_tag4_issue<128>(pv[1], xsrc + 512);
      }
      wg_wait<0>();
      PROF(11);
#pragma unroll
      for (int h = 0; h < 2; h++)
#pragma unroll
        for (int q = 0; q < 4; q++)
          asm volatile("stmatrix.sync.aligned.m8n8.x4.shared.b16 [%0], {%1,%2,%3,%4};"
                       ::"r"(pa0 + (9 + h) * SLOT + (lane & 7) * 256 + (((4 * q + (lane >> 3)) ^ (lane & 7)) * 16)),
                         "r"(pack2(acc[16 * q + 2 * h], acc[16 * q + 2 * h + 1])), "r"(pack2(acc[16 * q + 4 + 2 * h], acc[16 * q + 5 + 2 * h])),
                         "r"(pack2(acc[16 * q + 8 + 2 * h], acc[16 * q + 9 + 2 * h])), "r"(pack2(acc[16 * q + 12 + 2 * h], acc[16 * q + 13 + 2 * h]))
                       : "memory");
      __syncwarp();
      uint4 w[8];
#pragma unroll
      for (int i = 0; i < 8; i++) {
        const int r = 2 * (i & 3) + (lane >> 4);
        w[i] = lds4(pa0 + (9 + (i >> 2)) * SLOT + r * 256 + (((lane & 15) ^ r) * 16));
      }
      uint4* dst;
      int dstr;
      if (wgi == 0) {
        mbar_wait(BAR(hbar, 0));
        const uint32_t hb = sbase + 4 * SLOT + ((lane >> 3) & 1) * 8192 + (16 * wq + (lane >> 4)) * 128;
#pragma unroll
        for (int i = 0; i < 8; i++) {
          pv[i >> 2][i & 3] = lds4(hb + i * 256 + (((lane & 7) ^ ((2 * i + (lane >> 4)) & 7)) * 16));
          if (2 * nq + ((lane >> 3) & 1) < NLL) pv[i >> 2][i & 3].x &= ~1u;
        }
        dst = &scr->XP[(c ^ 4) * 1024 + tid];
        dstr = 128;
      } else {
        ld_tag4_finish<128>(pv[0], xsrc, tag);
        ld_tag4_finish<128>(pv[1], xsrc + 512, tag);
        dst = reinterpret_cast<uint4*>(out) + (16 * (c >> 4) + 2 * (4 * rh + wq) + (rb2 & 1) + 128 * (lane >> 4)) * 64 + nq * 16 + (lane & 15);
        dstr = 256 * 64;
      }
#pragma unroll
      for (int i = 0; i < 8; i++) {
        const uint4& p = pv[i >> 2][i & 3];
        const uint4 v = make_uint4(hadd2_bf16(w[i].x, p.x), hadd2_bf16(w[i].y, p.y), hadd2_bf16(w[i].z, p.z), hadd2_bf16(w[i].w, p.w));
        st_tag(dst + i * dstr, v, wgi ? (v.x & 1u) : tag);
      }
      PROF(12);
      PROFG(15);
    }
  }
#undef BAR
#undef TOFF
#undef RBAR
}

typedef CUresult (*EncodeFn)(CUtensorMap*, CUtensorMapDataType, cuuint32_t, void*, const cuuint64_t*, const cuuint64_t*,
                             const cuuint32_t*, const cuuint32_t*, CUtensorMapInterleave, CUtensorMapSwizzle,
                             CUtensorMapL2promotion, CUtensorMapFloatOOBfill);

}

extern "C" void kernel_launch(void* const* d_in, const int* in_sizes, int n_in, void* d_out, int out_size) {
  (void)in_sizes; (void)n_in; (void)out_size;
  static EncodeFn encode = nullptr;
  static void *tab = nullptr, *scr = nullptr;
  if (!encode) {
    void* fn = nullptr;
    cudaDriverEntryPointQueryResult qr;
    cudaGetDriverEntryPoint("cuTensorMapEncodeTiled", &fn, cudaEnableDefault, &qr);
    encode = (EncodeFn)fn;
    cudaGetSymbolAddress(&tab, g_tab);
    cudaGetSymbolAddress(&scr, g_scr);
    cudaFuncSetAttribute(fused_kernel, cudaFuncAttributeMaxDynamicSharedMemorySize, SMEM_BYTES);
  }
  CUtensorMap tmGX, tmUX, tmGY, tmUY, tmD, tmWR, tmWI;
  const cuuint32_t es[5] = {1, 1, 1, 1, 1};
  auto enc = [&](CUtensorMap* m, void* p, int rank, const cuuint64_t* gd, const cuuint64_t* gs, const cuuint32_t* bd,
                 CUtensorMapSwizzle sw, CUtensorMapL2promotion pr) {
    encode(m, CU_TENSOR_MAP_DATA_TYPE_BFLOAT16, rank, p, gd, gs, bd, es, CU_TENSOR_MAP_INTERLEAVE_NONE, sw, pr,
           CU_TENSOR_MAP_FLOAT_OOB_FILL_NONE);
  };
  {
    const cuuint64_t gd[3] = {64, 512, 28}, gs[2] = {3584, 128};
    const cuuint32_t bd[3] = {64, 32, 2};
    enc(&tmGX, d_in[4], 3, gd, gs, bd, CU_TENSOR_MAP_SWIZZLE_128B, CU_TENSOR_MAP_L2_PROMOTION_L2_256B);
    enc(&tmUX, d_in[5], 3, gd, gs, bd, CU_TENSOR_MAP_SWIZZLE_128B, CU_TENSOR_MAP_L2_PROMOTION_L2_256B);
  }
  {
    const cuuint64_t gd[3] = {32, 512, 56}, gs[2] = {3584, 64};
    const cuuint32_t bd[3] = {32, 32, 3};
    enc(&tmGY, d_in[4], 3, gd, gs, bd, CU_TENSOR_MAP_SWIZZLE_64B, CU_TENSOR_MAP_L2_PROMOTION_L2_128B);
    enc(&tmUY, d_in[5], 3, gd, gs, bd, CU_TENSOR_MAP_SWIZZLE_64B, CU_TENSOR_MAP_L2_PROMOTION_L2_128B);
  }
  {
    const cuuint64_t gd[3] = {64, 1792, 8}, gs[2] = {1024, 128};
    const cuuint32_t bd[3] = {64, 64, 2};
    enc(&tmD, d_in[6], 3, gd, gs, bd, CU_TENSOR_MAP_SWIZZLE_128B, CU_TENSOR_MAP_L2_PROMOTION_L2_256B);
  }
  {
    const cuuint64_t gd[3] = {4112, 8, 16}, gs[2] = {16 * 8224, 8224};
    const cuuint32_t bd[3] = {40, 8, 16};
    enc(&tmWR, d_in[1], 3, gd, gs, bd, CU_TENSOR_MAP_SWIZZLE_NONE, CU_TENSOR_MAP_L2_PROMOTION_NONE);
    enc(&tmWI, d_in[2], 3, gd, gs, bd, CU_TENSOR_MAP_SWIZZLE_NONE, CU_TENSOR_MAP_L2_PROMOTION_NONE);
  }
  fused_kernel<<<NCTA, NTHREADS, SMEM_BYTES>>>((const __nv_bfloat16*)d_in[0], (const Tables*)tab, (Scratch*)scr,
                                               (__nv_bfloat16*)d_out, (const char*)d_in[4], (const char*)d_in[5],
                                               (const char*)d_in[6], tmWR, tmWI, tmGX, tmUX, tmGY, tmUY, tmD);
}
```

```cpp
#include <cuda_runtime.h>
#include <cuda_bf16.h>
#include <cuda.h>
#include <stdint.h>

namespace {

constexpr int NCTA = 128;
constexpr int NTHREADS = 384;
constexpr int SLOT = 16384;
constexpr int SMEM_BYTES = 14 * SLOT + 3072;
constexpr int SPIN_LIMIT = 1 << 22;

struct Scratch {
  uint4 Z1[128 * 1024];
  uint4 Z2[128 * 1024];
  uint4 LN[16 * 8 * 1024];
  uint4 P[16 * 28 * 1024];
  uint4 XP[128 * 1024];
  uint4 ST[1024];
  unsigned cnt[64 * 32];
};
__device__ __align__(1024) Scratch g_scr;
#define PROF(i)
#define PROFP(i)
#define PROFG(i)

constexpr double ccos(int i, int n) {
  i &= n - 1;
  if (i > n / 2) i = n - i;
  if (4 * i == n) return 0.0;
  const bool neg = 4 * i > n;
  if (neg) i = n / 2 - i;
  const double a = 6.283185307179586476925 * i / n, a2 = a * a;
  double term = 1.0, sum = 1.0;
  for (int k = 1; k < 14; k++) { term *= -a2 / ((2 * k - 1) * (2 * k)); sum += term; }
  return neg ? -sum : sum;
}
constexpr double csin(int i, int n) { return ccos(i - n / 4, n); }
constexpr unsigned fbits(double v, int mant) {
  if (v == 0.0) return 0;
  const unsigned sg = v < 0 ? 1u : 0u;
  if (v < 0) v = -v;
  int e = 127;
  while (v < 1.0) { v *= 2.0; e--; }
  const unsigned m = (unsigned)((v - 1.0) * (double)(1u << mant) + 0.5);
  return (sg << (8 + mant)) + ((unsigned)e << mant) + m;
}
constexpr unsigned pkb(double lo, double hi) { return fbits(lo, 7) | (fbits(hi, 7) << 16); }
constexpr double fa_elem(int kp, int n1) {
  return kp <= 8 ? ccos(kp * n1, 16) : -csin((kp - 8) * n1, 16);
}
constexpr unsigned cfrag_c(int idx, int n, int ri) {
  return ri ? pkb(-csin(idx, n), ccos(idx, n)) : pkb(ccos(idx, n), csin(idx, n));
}
struct Tables {
  unsigned fb[16][32][4];
  unsigned tw1[8][32][4];
  unsigned fa[32][4];
  unsigned f2[8][4][32][4];
  unsigned g2[8][4][32][4];
  unsigned gb[16][32][4];
  unsigned tw3[4][32][4];
  unsigned ga[32][4];
  unsigned f8[32][4], g8[32][4];
};
constexpr int T1_BYTES = 12800, T2_BYTES = 44544;
static_assert(sizeof(Tables) == T1_BYTES + T2_BYTES, "table size");
constexpr Tables make_tables() {
  Tables T = {};
  for (int l = 0; l < 32; l++) {
    const int g = l >> 2, t = l & 3;
    for (int i = 0; i < 4; i++)
      for (int u = 0; u < 8; u++) {
        const int ri = g & 1, m = 2 * (g >> 1) + ((u & 3) >> 1);
        const double sg = u >= 4 ? -1.0 : 1.0;
        const int k2 = u >= 4 ? 31 - 2 * m - (u & 1) : 2 * m + (u & 1);
        const int pa = (8 * t + i) * k2, pb = (8 * t + 4 + i) * k2;
        T.fb[i * 4 + (u >> 1)][l][(u & 1) * 2 + 0] = ri == 0 ? pkb(ccos(pa, 32), ccos(pb, 32)) : pkb(-sg * csin(pa, 32), -sg * csin(pb, 32));
        T.fb[i * 4 + (u >> 1)][l][(u & 1) * 2 + 1] = ri == 0 ? pkb(csin(pa, 32), csin(pb, 32)) : pkb(sg * ccos(pa, 32), sg * ccos(pb, 32));
      }
    for (int i = 0; i < 4; i++)
      for (int ks = 0; ks < 4; ks++) {
        const int n2 = 4 * g + i, m = 2 * t + (ks & 1);
        const double sg = ks >= 2 ? -1.0 : 1.0;
        const int pa = n2 * (ks >= 2 ? 31 - 2 * m : 2 * m), pb = n2 * (ks >= 2 ? 30 - 2 * m : 2 * m + 1);
        T.gb[i * 4 + ks][l][0] = pkb(ccos(pa, 32), -sg * csin(pa, 32));
        T.gb[i * 4 + ks][l][1] = pkb(csin(pa, 32), sg * ccos(pa, 32));
        T.gb[i * 4 + ks][l][2] = pkb(ccos(pb, 32), -sg * csin(pb, 32));
        T.gb[i * 4 + ks][l][3] = pkb(csin(pb, 32), sg * ccos(pb, 32));
      }
    for (int i = 0; i < 4; i++) {
      for (int e = 0; e < 2; e++) {
        const int p = (8 * t + 4 * e + i) * (g == 0 ? 8 : g);
        T.tw1[2 * i + e][l][0] = fbits(g == 0 ? 0.0 : ccos(p, 512), 23);
        T.tw1[2 * i + e][l][1] = fbits(g == 0 ? ccos(p, 512) : csin(p, 512), 23);
        T.tw1[2 * i + e][l][2] = fbits(g == 0 ? 0.0 : -csin(p, 512), 23);
        T.tw1[2 * i + e][l][3] = fbits(g == 0 ? -csin(p, 512) : ccos(p, 512), 23);
      }
      const int ka = t == 0 ? 8 : 2 * t, kb = 2 * t + 1;
      T.tw3[i][l][0] = fbits(ccos((4 * g + i) * ka, 512), 23);
      T.tw3[i][l][1] = fbits(csin((4 * g + i) * ka, 512), 23);
      T.tw3[i][l][2] = fbits(ccos((4 * g + i) * kb, 512), 23);
      T.tw3[i][l][3] = fbits(csin((4 * g + i) * kb, 512), 23);
      const int p8 = (t + 4 * (i & 1)) * (4 * (i >> 1) + (g >> 1));
      T.f8[l][i] = cfrag_c(p8, 8, g & 1);
      T.g8[l][i] = cfrag_c(-p8, 8, g & 1);
    }
    for (int w = 0; w < 8; w++)
      for (int i = 0; i < 16; i++) {
        const int kidx = t + 4 * (i & 1) + 8 * (i >> 3), nidx = 4 * ((i >> 1) & 3) + (g >> 1);
        T.f2[w][i >> 2][l][i & 3] = cfrag_c((8 * kidx + w) * nidx, 128, g & 1);
        T.g2[w][i >> 2][l][i & 3] = cfrag_c(-(8 * nidx + w) * kidx, 128, g & 1);
      }
    T.fa[l][0] = pkb(fa_elem(g, 2 * t), fa_elem(g, 2 * t + 1));
    T.fa[l][1] = pkb(fa_elem(g + 8, 2 * t), fa_elem(g + 8, 2 * t + 1));
    T.fa[l][2] = pkb(fa_elem(g, 2 * t + 8), fa_elem(g, 2 * t + 9));
    T.fa[l][3] = pkb(fa_elem(g + 8, 2 * t + 8), fa_elem(g + 8, 2 * t + 9));
    T.ga[l][0] = pkb(fa_elem(2 * t, g), fa_elem(2 * t + 1, g));
    T.ga[l][1] = pkb(fa_elem(2 * t, g + 8), fa_elem(2 * t + 1, g + 8));
    T.ga[l][2] = pkb(fa_elem(2 * t + 8, g), fa_elem(2 * t + 9, g));
    T.ga[l][3] = pkb(fa_elem(2 * t + 8, g + 8), fa_elem(2 * t + 9, g + 8));
  }
  return T;
}
__device__ const __align__(128) Tables g_tab = make_tables();

__device__ __forceinline__ void die() { asm volatile("st.global.u32 [%0], %1;" ::"l"(0ull), "r"(0) : "memory"); }
__device__ __forceinline__ uint32_t s2u(const void* p) { return (uint32_t)__cvta_generic_to_shared(p); }
__device__ __forceinline__ void mbar_init(uint32_t b, int c) { asm volatile("mbarrier.init.shared::cta.b64 [%0], %1;" ::"r"(b), "r"(c)); }
__device__ __forceinline__ void mbar_expect(uint32_t b, int bytes) {
  asm volatile("mbarrier.arrive.expect_tx.shared::cta.b64 _, [%0], %1;" ::"r"(b), "r"(bytes) : "memory");
}
__device__ __forceinline__ void mbar_arrive(uint32_t b) { asm volatile("mbarrier.arrive.shared::cta.b64 _, [%0];" ::"r"(b) : "memory"); }
__device__ __forceinline__ uint32_t mbar_try(uint32_t b, uint32_t parity) {
  uint32_t ok;
  asm volatile("{.reg .pred p; mbarrier.try_wait.parity.shared::cta.b64 p, [%1], %2; selp.u32 %0,1,0,p;}"
               : "=r"(ok) : "r"(b), "r"(parity) : "memory");
  return ok;
}
__device__ __forceinline__ uint32_t mbar_test(uint32_t b) {
  uint32_t ok;
  asm volatile("{.reg .pred p; mbarrier.test_wait.parity.shared::cta.b64 p, [%1], 0; selp.u32 %0,1,0,p;}" : "=r"(ok) : "r"(b) : "memory");
  return ok;
}
__device__ __forceinline__ void mbar_wait(uint32_t b, uint32_t parity = 0) {
  int it = 0;
#pragma unroll 1
  while (!mbar_try(b, parity))
    if (++it > SPIN_LIMIT) { die(); break; }
}
__device__ __forceinline__ void bar_sync(int id, int n) { asm volatile("bar.sync %0, %1;" ::"r"(id), "r"(n) : "memory"); }
__device__ __forceinline__ void bar_arrive(int id, int n) { asm volatile("bar.arrive %0, %1;" ::"r"(id), "r"(n) : "memory"); }
__device__ __forceinline__ void red_release(unsigned* p) { asm volatile("red.release.gpu.global.add.u32 [%0], 1;" ::"l"(p) : "memory"); }
__device__ __forceinline__ void red_relaxed(unsigned* p) { asm volatile("red.relaxed.gpu.global.add.u32 [%0], 1;" ::"l"(p) : "memory"); }
__device__ __forceinline__ unsigned ld_acquire(const unsigned* p) {
  unsigned v;
  asm volatile("ld.acquire.gpu.global.u32 %0, [%1];" : "=r"(v) : "l"(p) : "memory");
  return v;
}
__device__ __forceinline__ unsigned ld_relaxed(const unsigned* p) {
  unsigned v;
  asm volatile("ld.relaxed.gpu.global.u32 %0, [%1];" : "=r"(v) : "l"(p) : "memory");
  return v;
}
__device__ __forceinline__ void wait_counter(const unsigned* p, unsigned target) {
  int it = 0;
  while ((int)(ld_acquire(p) - target) < 0)
    if (++it > SPIN_LIMIT) { die(); break; }
}
__device__ __forceinline__ void sts4(uint32_t a, uint32_t x, uint32_t y, uint32_t z, uint32_t w) {
  asm volatile("st.shared.v4.u32 [%0], {%1,%2,%3,%4};" ::"r"(a), "r"(x), "r"(y), "r"(z), "r"(w) : "memory");
}
__device__ __forceinline__ uint4 lds4(uint32_t a) {
  uint4 v;
  asm volatile("ld.shared.v4.u32 {%0,%1,%2,%3}, [%4];" : "=r"(v.x), "=r"(v.y), "=r"(v.z), "=r"(v.w) : "r"(a) : "memory");
  return v;
}
__device__ __forceinline__ uint32_t pack2(float lo, float hi) {
  uint32_t r;
  asm("cvt.rn.bf16x2.f32 %0, %1, %2;" : "=r"(r) : "f"(hi), "f"(lo));
  return r;
}
__device__ __forceinline__ float bf_lo(uint32_t v) { return __uint_as_float(v << 16); }
__device__ __forceinline__ uint32_t hadd2_bf16(uint32_t a, uint32_t b) {
  uint32_t r;
  asm("add.rn.bf16x2 %0, %1, %2;" : "=r"(r) : "r"(a), "r"(b));
  return r;
}
__device__ __forceinline__ void mma16816(float (&d)[4], uint32_t a0, uint32_t a1, uint32_t a2, uint32_t a3, uint32_t b0, uint32_t b1) {
  asm("mma.sync.aligned.m16n8k16.row.col.f32.bf16.bf16.f32 {%0,%1,%2,%3}, {%4,%5,%6,%7}, {%8,%9}, {%0,%1,%2,%3};"
      : "+f"(d[0]), "+f"(d[1]), "+f"(d[2]), "+f"(d[3])
      : "r"(a0), "r"(a1), "r"(a2), "r"(a3), "r"(b0), "r"(b1));
}
template <int N>
__device__ __forceinline__ void cs_frac(int idx, float& c, float& s) {
  int i = ((idx + N / 2) & (N - 1)) - N / 2;
  float a = (float)i * (6.283185307179586f / N);
  c = __cosf(a);
  s = __sinf(a);
}
template <int N>
__device__ __forceinline__ uint32_t cfrag(int idx, int ri) {
  float c, s;
  cs_frac<N>(idx, c, s);
  return ri ? pack2(-s, c) : pack2(c, s);
}
__device__ __forceinline__ uint32_t word(const uint4& v, int e) { return e == 0 ? v.x : e == 1 ? v.y : e == 2 ? v.z : v.w; }
__device__ __forceinline__ void cdft16(const uint4 (&q)[4], const uint4 (&F)[4], uint4 (&o)[4]) {
  float acc[2][4][4];
#pragma unroll
  for (int p = 0; p < 2; p++)
#pragma unroll
    for (int v = 0; v < 4; v++) {
      acc[p][v][0] = acc[p][v][1] = acc[p][v][2] = acc[p][v][3] = 0.f;
#pragma unroll
      for (int ks = 0; ks < 2; ks++)
        mma16816(acc[p][v], word(q[2 * ks], 2 * p), word(q[2 * ks], 2 * p + 1), word(q[2 * ks + 1], 2 * p),
                 word(q[2 * ks + 1], 2 * p + 1), word(F[ks * 2 + (v >> 1)], (v & 1) * 2), word(F[ks * 2 + (v >> 1)], (v & 1) * 2 + 1));
    }
#pragma unroll
  for (int v = 0; v < 4; v++)
    o[v] = make_uint4(pack2(acc[0][v][0], acc[0][v][1]), pack2(acc[0][v][2], acc[0][v][3]),
                      pack2(acc[1][v][0], acc[1][v][1]), pack2(acc[1][v][2], acc[1][v][3]));
}
__device__ __forceinline__ void st_tag(uint4* p, const uint4& v, uint32_t tag) {
  asm volatile("{.reg .b128 r; .reg .b64 a, b; mov.b64 a, {%1,%2}; mov.b64 b, {%3,%4}; mov.b128 r, {a,b}; st.relaxed.gpu.global.b128 [%0], r;}"
               ::"l"(p), "r"((v.x & ~1u) | tag), "r"(v.y), "r"(v.z), "r"(v.w) : "memory");
}
__device__ __forceinline__ void st_tag_p(int en, uint4* p, const uint4& v, uint32_t tag) {
  asm volatile("{.reg .b128 r; .reg .b64 a, b; .reg .pred q; setp.ne.b32 q, %5, 0; mov.b64 a, {%1,%2}; mov.b64 b, {%3,%4}; mov.b128 r, {a,b};\n"
               "@q st.relaxed.gpu.global.b128 [%0], r;}"
               ::"l"(p), "r"((v.x & ~1u) | tag), "r"(v.y), "r"(v.z), "r"(v.w), "r"(en) : "memory");
}
__device__ __forceinline__ void sts4_p(int en, uint32_t a, uint32_t x, uint32_t y, uint32_t z, uint32_t w) {
  asm volatile("{.reg .pred q; setp.ne.b32 q, %5, 0; @q st.shared.v4.u32 [%0], {%1,%2,%3,%4};}"
               ::"r"(a), "r"(x), "r"(y), "r"(z), "r"(w), "r"(en) : "memory");
}
__device__ __forceinline__ uint4 ld_b128(const uint4* p) {
  uint4 v;
  asm volatile("{.reg .b128 r; .reg .b64 a, b; ld.relaxed.gpu.global.b128 r, [%4]; mov.b128 {a,b}, r; mov.b64 {%0,%1}, a; mov.b64 {%2,%3}, b;}"
               : "=r"(v.x), "=r"(v.y), "=r"(v.z), "=r"(v.w) : "l"(p) : "memory");
  return v;
}
template <int STRIDE>
__device__ __forceinline__ void ld_tag4_issue(uint4 (&q)[4], const uint4* p) {
#pragma unroll
  for (int i = 0; i < 4; i++) q[i] = ld_b128(p + i * STRIDE);
}
template <int STRIDE>
__device__ __forceinline__ void ld_tag4_finish(uint4 (&q)[4], const uint4* p, uint32_t tag) {
  int it = 0;
#pragma unroll 1
  while (__any_sync(0xffffffffu, ((q[0].x ^ tag) | (q[1].x ^ tag) | (q[2].x ^ tag) | (q[3].x ^ tag)) & 1u)) {
    ld_tag4_issue<STRIDE>(q, p);
    if (++it > SPIN_LIMIT) { die(); break; }
  }
#pragma unroll
  for (int i = 0; i < 4; i++) asm volatile("and.b32 %0, %0, 0xfffffffe;" : "+r"(q[i].x));
}
__device__ __forceinline__ void row_stats(const uint32_t (&a)[8], const uint32_t (&b)[8], int lane, float (&sum)[2], float (&sq)[2]) {
  float da[4] = {0.f, 0.f, 0.f, 0.f}, db[4] = {0.f, 0.f, 0.f, 0.f}, ds[4] = {0.f, 0.f, 0.f, 0.f};
#pragma unroll
  for (int q = 0; q < 4; q++) {
    mma16816(ds, a[2 * q], b[2 * q], a[2 * q + 1], b[2 * q + 1], 0x3f803f80u, 0x3f803f80u);
    mma16816(da, a[2 * q], b[2 * q], a[2 * q + 1], b[2 * q + 1], a[2 * q], a[2 * q + 1]);
    mma16816(db, a[2 * q], b[2 * q], a[2 * q + 1], b[2 * q + 1], b[2 * q], b[2 * q + 1]);
  }
  const int src = (lane & 28) | (lane >> 3);
  const float qa = __shfl_sync(0xffffffffu, (lane & 4) ? da[1] : da[0], src);
  const float qb = __shfl_sync(0xffffffffu, (lane & 4) ? db[3] : db[2], src);
  float v = (lane & 2) ? ((lane & 1) ? ds[2] : ds[0]) : ((lane & 1) ? qb : qa);
  v += __shfl_xor_sync(0xffffffffu, v, 4);
  v += __shfl_xor_sync(0xffffffffu, v, 8);
  v += __shfl_xor_sync(0xffffffffu, v, 16);
  sq[0] = __shfl_sync(0xffffffffu, v, 0);
  sq[1] = __shfl_sync(0xffffffffu, v, 1);
  sum[0] = __shfl_sync(0xffffffffu, v, 2);
  sum[1] = __shfl_sync(0xffffffffu, v, 3);
}
__device__ __forceinline__ uint64_t desc64(uint32_t lo, uint32_t hi) {
  uint64_t d;
  asm("mov.b64 %0, {%1, %2};" : "=l"(d) : "r"(lo), "r"(hi));
  return d;
}
constexpr uint32_t desc_hi(uint32_t sbo, uint32_t swz) { return (sbo >> 4) | (swz << 30); }
__device__ __forceinline__ uint32_t desc_lo(uint32_t addr, uint32_t lbo) { return ((addr & 0x3FFFF) >> 4) | ((lbo >> 4) << 16); }
__device__ __forceinline__ void cp_async16(uint32_t dst, const void* src) {
  asm volatile("cp.async.cg.shared.global [%0], [%1], 16;" ::"r"(dst), "l"(src) : "memory");
}
__device__ __forceinline__ uint2 lds2(uint32_t a) {
  uint2 v;
  asm volatile("ld.shared.v2.u32 {%0,%1}, [%2];" : "=r"(v.x), "=r"(v.y) : "r"(a) : "memory");
  return v;
}
__device__ __forceinline__ uint32_t lds_u16(uint32_t a) {
  uint16_t v;
  asm volatile("ld.shared.u16 %0, [%1];" : "=h"(v) : "r"(a) : "memory");
  return v;
}
__device__ __forceinline__ void wg_fence() { asm volatile("wgmma.fence.sync.aligned;" ::: "memory"); }
__device__ __forceinline__ void wg_commit() { asm volatile("wgmma.commit_group.sync.aligned;" ::: "memory"); }
template <int N>
__device__ __forceinline__ void wg_wait() { asm volatile("wgmma.wait_group.sync.aligned %0;" ::"n"(N) : "memory"); }
__device__ __forceinline__ void bulk_load(uint32_t dst, const void* src, int bytes, uint32_t bar) {
  asm volatile("cp.async.bulk.shared::cluster.global.mbarrier::complete_tx::bytes [%0], [%1], %2, [%3];"
               ::"r"(dst), "l"(src), "r"(bytes), "r"(bar) : "memory");
}
__device__ __forceinline__ void bulk_load_mc(uint32_t dst, const void* src, int bytes, uint32_t bar) {
  asm volatile("cp.async.bulk.shared::cluster.global.mbarrier::complete_tx::bytes.multicast::cluster [%0], [%1], %2, [%3], %4;"
               ::"r"(dst), "l"(src), "r"(bytes), "r"(bar), "h"((uint16_t)3) : "memory");
}
__device__ __forceinline__ void tma3(uint32_t dst, const CUtensorMap* tm, uint32_t bar, int c0, int c1, int c2) {
  asm volatile("cp.async.bulk.tensor.3d.shared::cluster.global.mbarrier::complete_tx::bytes [%0], [%1, {%3,%4,%5}], [%2];"
               ::"r"(dst), "l"(tm), "r"(bar), "r"(c0), "r"(c1), "r"(c2) : "memory");
}
__device__ __forceinline__ void tma3_mc(uint32_t dst, const CUtensorMap* tm, uint32_t bar, int c1, int c2) {
  asm volatile("cp.async.bulk.tensor.3d.shared::cluster.global.mbarrier::complete_tx::bytes.multicast::cluster [%0], [%1, {%3,%4,%5}], [%2], %6;"
               ::"r"(dst), "l"(tm), "r"(bar), "r"(0), "r"(c1), "r"(c2), "h"((uint16_t)3) : "memory");
}
__device__ __forceinline__ void mbar_arrive_remote(uint32_t rb) {
  asm volatile("mbarrier.arrive.shared::cluster.b64 _, [%0];" ::"r"(rb) : "memory");
}
__device__ __forceinline__ uint4 ldg_ca4_p(int en, const void* p) {
  uint4 v;
  asm volatile("{.reg .pred q; setp.ne.b32 q, %5, 0; @q ld.global.ca.v4.u32 {%0,%1,%2,%3}, [%4];}"
               : "=r"(v.x), "=r"(v.y), "=r"(v.z), "=r"(v.w) : "l"(p), "r"(en) : "memory");
  return v;
}
__device__ __forceinline__ uint32_t clock32() {
  uint32_t v;
  asm volatile("mov.u32 %0, %%clock;" : "=r"(v) :: "memory");
  return v;
}
__device__ __forceinline__ float swiglu(float g, float u, float r) {
  float hg = (0.5f * r) * g, th;
  asm("tanh.approx.f32 %0, %1;" : "=f"(th) : "f"(hg));
  return fmaf(hg, th, hg) * (r * u);
}
__device__ __forceinline__ uint32_t hsub2_bf16(uint32_t a, uint32_t b) {
  uint32_t r;
  asm("sub.rn.bf16x2 %0, %1, %2;" : "=r"(r) : "r"(a), "r"(b));
  return r;
}
__device__ __forceinline__ void l2_prefetch(const void* p, int bytes) {
  asm volatile("cp.async.bulk.prefetch.L2.global [%0], %1;" ::"l"(p), "r"(bytes) : "memory");
}

__device__ __forceinline__ void wgmma_n256(float (&d)[128], uint64_t da, uint64_t db, int sd = 1) {
  asm volatile("{.reg .pred p; setp.ne.b32 p, %130, 0;\n"
      "wgmma.mma_async.sync.aligned.m64n256k16.f32.bf16.bf16 {"
      "%0,%1,%2,%3,%4,%5,%6,%7,%8,%9,%10,%11,%12,%13,%14,%15,"
      "%16,%17,%18,%19,%20,%21,%22,%23,%24,%25,%26,%27,%28,%29,%30,%31,"
      "%32,%33,%34,%35,%36,%37,%38,%39,%40,%41,%42,%43,%44,%45,%46,%47,"
      "%48,%49,%50,%51,%52,%53,%54,%55,%56,%57,%58,%59,%60,%61,%62,%63,"
      "%64,%65,%66,%67,%68,%69,%70,%71,%72,%73,%74,%75,%76,%77,%78,%79,"
      "%80,%81,%82,%83,%84,%85,%86,%87,%88,%89,%90,%91,%92,%93,%94,%95,"
      "%96,%97,%98,%99,%100,%101,%102,%103,%104,%105,%106,%107,%108,%109,%110,%111,"
      "%112,%113,%114,%115,%116,%117,%118,%119,%120,%121,%122,%123,%124,%125,%126,%127"
      "}, %128, %129, p, 1, 1, 0, 1;}\n"
      : "+f"(d[0]),"+f"(d[1]),"+f"(d[2]),"+f"(d[3]),"+f"(d[4]),"+f"(d[5]),"+f"(d[6]),"+f"(d[7]),
        "+f"(d[8]),"+f"(d[9]),"+f"(d[10]),"+f"(d[11]),"+f"(d[12]),"+f"(d[13]),"+f"(d[14]),"+f"(d[15]),
        "+f"(d[16]),"+f"(d[17]),"+f"(d[18]),"+f"(d[19]),"+f"(d[20]),"+f"(d[21]),"+f"(d[22]),"+f"(d[23]),
        "+f"(d[24]),"+f"(d[25]),"+f"(d[26]),"+f"(d[27]),"+f"(d[28]),"+f"(d[29]),"+f"(d[30]),"+f"(d[31]),
        "+f"(d[32]),"+f"(d[33]),"+f"(d[34]),"+f"(d[35]),"+f"(d[36]),"+f"(d[37]),"+f"(d[38]),"+f"(d[39]),
        "+f"(d[40]),"+f"(d[41]),"+f"(d[42]),"+f"(d[43]),"+f"(d[44]),"+f"(d[45]),"+f"(d[46]),"+f"(d[47]),
        "+f"(d[48]),"+f"(d[49]),"+f"(d[50]),"+f"(d[51]),"+f"(d[52]),"+f"(d[53]),"+f"(d[54]),"+f"(d[55]),
        "+f"(d[56]),"+f"(d[57]),"+f"(d[58]),"+f"(d[59]),"+f"(d[60]),"+f"(d[61]),"+f"(d[62]),"+f"(d[63]),
        "+f"(d[64]),"+f"(d[65]),"+f"(d[66]),"+f"(d[67]),"+f"(d[68]),"+f"(d[69]),"+f"(d[70]),"+f"(d[71]),
        "+f"(d[72]),"+f"(d[73]),"+f"(d[74]),"+f"(d[75]),"+f"(d[76]),"+f"(d[77]),"+f"(d[78]),"+f"(d[79]),
        "+f"(d[80]),"+f"(d[81]),"+f"(d[82]),"+f"(d[83]),"+f"(d[84]),"+f"(d[85]),"+f"(d[86]),"+f"(d[87]),
        "+f"(d[88]),"+f"(d[89]),"+f"(d[90]),"+f"(d[91]),"+f"(d[92]),"+f"(d[93]),"+f"(d[94]),"+f"(d[95]),
        "+f"(d[96]),"+f"(d[97]),"+f"(d[98]),"+f"(d[99]),"+f"(d[100]),"+f"(d[101]),"+f"(d[102]),"+f"(d[103]),
        "+f"(d[104]),"+f"(d[105]),"+f"(d[106]),"+f"(d[107]),"+f"(d[108]),"+f"(d[109]),"+f"(d[110]),"+f"(d[111]),
        "+f"(d[112]),"+f"(d[113]),"+f"(d[114]),"+f"(d[115]),"+f"(d[116]),"+f"(d[117]),"+f"(d[118]),"+f"(d[119]),
        "+f"(d[120]),"+f"(d[121]),"+f"(d[122]),"+f"(d[123]),"+f"(d[124]),"+f"(d[125]),"+f"(d[126]),"+f"(d[127])
      : "l"(da), "l"(db), "r"(sd));
}
__device__ __forceinline__ void wgmma_n192(float (&d)[96], uint64_t da, uint64_t db) {
  asm volatile("wgmma.mma_async.sync.aligned.m64n192k16.f32.bf16.bf16 {"
      "%0,%1,%2,%3,%4,%5,%6,%7,%8,%9,%10,%11,%12,%13,%14,%15,"
      "%16,%17,%18,%19,%20,%21,%22,%23,%24,%25,%26,%27,%28,%29,%30,%31,"
      "%32,%33,%34,%35,%36,%37,%38,%39,%40,%41,%42,%43,%44,%45,%46,%47,"
      "%48,%49,%50,%51,%52,%53,%54,%55,%56,%57,%58,%59,%60,%61,%62,%63,"
      "%64,%65,%66,%67,%68,%69,%70,%71,%72,%73,%74,%75,%76,%77,%78,%79,"
      "%80,%81,%82,%83,%84,%85,%86,%87,%88,%89,%90,%91,%92,%93,%94,%95"
      "}, %96, %97, 1, 1, 1, 0, 1;\n"
      : "+f"(d[0]),"+f"(d[1]),"+f"(d[2]),"+f"(d[3]),"+f"(d[4]),"+f"(d[5]),"+f"(d[6]),"+f"(d[7]),
        "+f"(d[8]),"+f"(d[9]),"+f"(d[10]),"+f"(d[11]),"+f"(d[12]),"+f"(d[13]),"+f"(d[14]),"+f"(d[15]),
        "+f"(d[16]),"+f"(d[17]),"+f"(d[18]),"+f"(d[19]),"+f"(d[20]),"+f"(d[21]),"+f"(d[22]),"+f"(d[23]),
        "+f"(d[24]),"+f"(d[25]),"+f"(d[26]),"+f"(d[27]),"+f"(d[28]),"+f"(d[29]),"+f"(d[30]),"+f"(d[31]),
        "+f"(d[32]),"+f"(d[33]),"+f"(d[34]),"+f"(d[35]),"+f"(d[36]),"+f"(d[37]),"+f"(d[38]),"+f"(d[39]),
        "+f"(d[40]),"+f"(d[41]),"+f"(d[42]),"+f"(d[43]),"+f"(d[44]),"+f"(d[45]),"+f"(d[46]),"+f"(d[47]),
        "+f"(d[48]),"+f"(d[49]),"+f"(d[50]),"+f"(d[51]),"+f"(d[52]),"+f"(d[53]),"+f"(d[54]),"+f"(d[55]),
        "+f"(d[56]),"+f"(d[57]),"+f"(d[58]),"+f"(d[59]),"+f"(d[60]),"+f"(d[61]),"+f"(d[62]),"+f"(d[63]),
        "+f"(d[64]),"+f"(d[65]),"+f"(d[66]),"+f"(d[67]),"+f"(d[68]),"+f"(d[69]),"+f"(d[70]),"+f"(d[71]),
        "+f"(d[72]),"+f"(d[73]),"+f"(d[74]),"+f"(d[75]),"+f"(d[76]),"+f"(d[77]),"+f"(d[78]),"+f"(d[79]),
        "+f"(d[80]),"+f"(d[81]),"+f"(d[82]),"+f"(d[83]),"+f"(d[84]),"+f"(d[85]),"+f"(d[86]),"+f"(d[87]),
        "+f"(d[88]),"+f"(d[89]),"+f"(d[90]),"+f"(d[91]),"+f"(d[92]),"+f"(d[93]),"+f"(d[94]),"+f"(d[95])
      : "l"(da), "l"(db));
}
template <int SD>
__device__ __forceinline__ void wgmma_rs_n128(float (&d)[64], uint32_t a0, uint32_t a1, uint32_t a2, uint32_t a3, uint64_t db) {
  asm volatile("wgmma.mma_async.sync.aligned.m64n128k16.f32.bf16.bf16 {"
      "%0,%1,%2,%3,%4,%5,%6,%7,%8,%9,%10,%11,%12,%13,%14,%15,"
      "%16,%17,%18,%19,%20,%21,%22,%23,%24,%25,%26,%27,%28,%29,%30,%31,"
      "%32,%33,%34,%35,%36,%37,%38,%39,%40,%41,%42,%43,%44,%45,%46,%47,"
      "%48,%49,%50,%51,%52,%53,%54,%55,%56,%57,%58,%59,%60,%61,%62,%63"
      "}, {%64,%65,%66,%67}, %68, %69, 1, 1, 1;\n"
      : "+f"(d[0]),"+f"(d[1]),"+f"(d[2]),"+f"(d[3]),"+f"(d[4]),"+f"(d[5]),"+f"(d[6]),"+f"(d[7]),
        "+f"(d[8]),"+f"(d[9]),"+f"(d[10]),"+f"(d[11]),"+f"(d[12]),"+f"(d[13]),"+f"(d[14]),"+f"(d[15]),
        "+f"(d[16]),"+f"(d[17]),"+f"(d[18]),"+f"(d[19]),"+f"(d[20]),"+f"(d[21]),"+f"(d[22]),"+f"(d[23]),
        "+f"(d[24]),"+f"(d[25]),"+f"(d[26]),"+f"(d[27]),"+f"(d[28]),"+f"(d[29]),"+f"(d[30]),"+f"(d[31]),
        "+f"(d[32]),"+f"(d[33]),"+f"(d[34]),"+f"(d[35]),"+f"(d[36]),"+f"(d[37]),"+f"(d[38]),"+f"(d[39]),
        "+f"(d[40]),"+f"(d[41]),"+f"(d[42]),"+f"(d[43]),"+f"(d[44]),"+f"(d[45]),"+f"(d[46]),"+f"(d[47]),
        "+f"(d[48]),"+f"(d[49]),"+f"(d[50]),"+f"(d[51]),"+f"(d[52]),"+f"(d[53]),"+f"(d[54]),"+f"(d[55]),
        "+f"(d[56]),"+f"(d[57]),"+f"(d[58]),"+f"(d[59]),"+f"(d[60]),"+f"(d[61]),"+f"(d[62]),"+f"(d[63])
      : "r"(a0), "r"(a1), "r"(a2), "r"(a3), "l"(db), "n"(SD));
}

constexpr int C_LN = 0, C_PX = 16, C_PY = 32;
constexpr int NB_CONS = 1, NB_LN = 2, NB_LAG = 4, NB_INIT = 6, NB_RDY = 7, NB_WG = 8;
#define LAGX 3
#define LAGY 3
#define LAG2 5
#define NLL 2
#define POLL_DELAY3 600
#define POLL_DELAY 1100
#define FILT_DELAY 1000
#define THR_B 0
#define THR_P 0
#define SPEC -1
#define WARM 4
#define HWARM 0
#define TOUCH 1
#define ALEAD 6
#define RING_SIG 1
#define PF2_SIG 1
constexpr int SM_E = 0, SM_X = 16384, SM_E2 = 32768, SM_W = 49152, SM_FC = 69632, SM_T = 73728 - T1_BYTES;
constexpr unsigned long long KORDER = 0xBA9432DC876510ull;
constexpr unsigned long long BSLOT = 0x76532107653210ull, PSLOT = 0xDCBA984DCBA984ull;
constexpr uint32_t HI128 = desc_hi(1024, 1), HI64 = desc_hi(512, 2);

struct Bars {
  uint64_t full1[32], empty1[32], full2[16], fullA[8], empty2[8], fullP[16], emptyP[8], hbar, tbar, hint[3], sig[2], sbar;
  uint32_t epoch;
};

template <int NK, bool STORE>
__device__ __forceinline__ void make_p(const float (&acc)[NK * 16], float r0, float r1, uint4 (&p)[NK], uint4* pbase, int ks0, uint32_t tag) {
#pragma unroll
  for (int j = 0; j < NK; j++) {
    uint32_t w[4];
#pragma unroll
    for (int i = 0; i < 4; i++) {
      const int a = 8 * j + 2 * i, b = a + NK * 8;
      w[i] = pack2(swiglu(acc[a], acc[b], (i & 1) ? r1 : r0), swiglu(acc[a + 1], acc[b + 1], (i & 1) ? r1 : r0));
    }
    asm volatile("" : "+r"(w[0]), "+r"(w[1]), "+r"(w[2]), "+r"(w[3]));
    p[j] = make_uint4(w[0], w[1], w[2], w[3]);
    if (STORE) st_tag(pbase + ((ks0 + j) >> 2) * 1024 + ((ks0 + j) & 3) * 32, p[j], tag);
  }
}
__device__ __forceinline__ void spin_cycles(uint32_t n) {
  const uint32_t t0 = clock32();
  while (clock32() - t0 < n) {}
}

__device__ __forceinline__ void spin_until(uint32_t t) {
  float d[4] = {0.f, 0.f, 0.f, 0.f};
  while ((int)(clock32() - t) < 0) {
    if (HWARM) asm volatile("mma.sync.aligned.m16n8k16.row.col.f32.bf16.bf16.f32 {%0,%1,%2,%3}, {%4,%4,%4,%4}, {%4,%4}, {%0,%1,%2,%3};"
                            : "+f"(d[0]), "+f"(d[1]), "+f"(d[2]), "+f"(d[3]) : "r"(t));
  }
}

__global__ void __cluster_dims__(2, 1, 1) __launch_bounds__(NTHREADS, 1)
fused_kernel(const __nv_bfloat16* __restrict__ x, const Tables* __restrict__ tab, Scratch* __restrict__ scr,
             __nv_bfloat16* __restrict__ out, const char* __restrict__ wg_raw, const char* __restrict__ wu_raw,
             const char* __restrict__ wd_raw,
             const __grid_constant__ CUtensorMap tmWR, const __grid_constant__ CUtensorMap tmWI,
             const __grid_constant__ CUtensorMap tmGX, const __grid_constant__ CUtensorMap tmUX,
             const __grid_constant__ CUtensorMap tmGY, const __grid_constant__ CUtensorMap tmUY,
             const __grid_constant__ CUtensorMap tmD) {
  extern __shared__ __align__(1024) char smem_raw[];
  const uint32_t sbase = s2u(smem_raw);
  const uint32_t sbar = sbase + 14 * SLOT, sstat = sbar + 1280;
  const int tid = threadIdx.x, lane = tid & 31;
  const int c = blockIdx.x, rk = c & 1, f = (c >> 1) & 7, rb = 2 * (c >> 4) + rk;
  const int rb2 = 2 * (c >> 4) + (f >> 2), kh = (f >> 1) & 1, nq = 2 * (f & 1) + rk;
#define BAR(field, i) (sbar + (uint32_t)offsetof(Bars, field) + 8u * (i))
#define TOFF(field) (sbase + SM_T + (uint32_t)offsetof(Tables, field) + lane * 16)

  if (tid >= 256) {
    asm volatile("setmaxnreg.dec.sync.aligned.u32 56;");
    const int warp = __shfl_sync(0xffffffffu, tid >> 5, 0);
    if (lane == 0) {
      if (warp == 8) {
        if (sbase & 1023) die();
#pragma unroll
        for (int i = 0; i < 16; i++) mbar_init(BAR(emptyP, i), i < 7 ? 16 : i < 8 ? 8 : i == 9 ? 1 + 32 * TOUCH : i < 13 ? 1 : i < 15 ? 8 : 32);
        mbar_expect(BAR(tbar, 0), T2_BYTES + 2 * 10240);
        mbar_expect(BAR(hbar, 0), 16384);
      } else if (warp == 9) {
#pragma unroll
        for (int i = 0; i < 32; i++) mbar_init(BAR(full1, i), 1);
#pragma unroll
        for (int i = 0; i < 32; i++) mbar_expect(BAR(full1, i), i < 16 ? 16384 : 12288);
      } else if (warp == 10) {
#pragma unroll
        for (int i = 0; i < 32; i++) mbar_init(BAR(empty1, i), 16);
#pragma unroll
        for (int i = 0; i < 14; i++) mbar_init(BAR(fullP, i), 1);
#pragma unroll
        for (int i = 0; i < 14; i++) mbar_expect(BAR(fullP, i), 16384);
      } else {
#pragma unroll
        for (int i = 0; i < 32; i++) mbar_init(BAR(full2, i), i < 24 ? 1 : 8);
#pragma unroll
        for (int i = 0; i < 24; i++) mbar_expect(BAR(full2, i), 16384);
      }
      asm volatile("fence.mbarrier_init.release.cluster;" ::: "memory");
    }
    if (tid == 256) {
      const int w0 = ((c >> 3) * 257 + 32 * (c & 7) + 1) & ~7;
      if (FILT_DELAY) {
        asm volatile("prefetch.tensormap [%0];" ::"l"(&tmWR) : "memory");
        asm volatile("prefetch.tensormap [%0];" ::"l"(&tmWI) : "memory");
        spin_cycles(FILT_DELAY);
      }
      tma3(sbase + SM_W, &tmWR, BAR(tbar, 0), w0, 0, 0);
      tma3(sbase + SM_W + 10240, &tmWI, BAR(tbar, 0), w0, 0, 0);
      bulk_load(sbase + SM_T + T1_BYTES, reinterpret_cast<const char*>(tab) + T1_BYTES, T2_BYTES, BAR(tbar, 0));
    }
    if (tid == 288) {
      asm volatile("prefetch.tensormap [%0];" ::"l"(rk ? &tmUX : &tmGX) : "memory");
      asm volatile("prefetch.tensormap [%0];" ::"l"(rk ? &tmUY : &tmGY) : "memory");
      asm volatile("prefetch.tensormap [%0];" ::"l"(&tmD) : "memory");
    }
    if (tid == 320) {
      const unsigned e = ld_relaxed(&scr->cnt[(C_LN + rb) * 32]) >> 3;
      asm volatile("st.shared.u32 [%0], %1;" ::"r"(BAR(epoch, 0)), "r"(e) : "memory");
    }
    __syncwarp();
    asm volatile("barrier.cluster.arrive.relaxed.aligned;" ::: "memory");
    bar_arrive(NB_RDY, 384);
    asm volatile("barrier.cluster.wait.aligned;" ::: "memory");
    bar_sync(NB_INIT, 384);
    unsigned epoch;
    asm volatile("ld.shared.u32 %0, [%1];" : "=r"(epoch) : "r"(BAR(epoch, 0)) : "memory");
    if (warp == 8) {
      if (lane == 0) {
        const int ax = (7 * f + 3 * (f & 1)) >> 1;
        const int ay = 7 * f + ((f & 1) ? 0 : 4);
        const CUtensorMap* tx = rk ? &tmUX : &tmGX;
        const CUtensorMap* ty = rk ? &tmUY : &tmGY;
        if (RING_SIG >= 0) mbar_wait(BAR(sig, RING_SIG));
        uint32_t s = 2;
#pragma unroll 1
        for (int n = 0; n < 16; n++) {
          if (n >= 6) mbar_wait(BAR(empty1, n - 6));
          tma3_mc(sbase + (8 + s) * SLOT + rk * 8192, tx, BAR(full1, n), n * 32, ax);
          if (++s == 6) s = 0;
        }
#pragma unroll 1
        for (int k = 0; k < 16; k++) {
          mbar_wait(BAR(empty1, k < 8 ? 10 + ((12 * k + 11) >> 4) : 8 + k));
          tma3_mc(sbase + 8 * SLOT + (k & 7) * 12288 + rk * 6144, ty, BAR(full1, 16 + k), k * 32, ay);
        }
      }
    } else if (warp == 9) {
      if (lane == 0) {
#pragma unroll 1
        for (int i = 0; i < 14; i++) {
          const int kblk = 14 * kh + (int)((KORDER >> (4 * i)) & 15);
          const int j = i < 7 ? i : i - 7, sl = j + (j >= 4);
          mbar_wait(i < 7 ? BAR(empty1, 17 + 2 * sl) : BAR(empty2, j));
          if (THR_B && i >= THR_B) mbar_wait(BAR(full2, i - THR_B));
          tma3(sbase + sl * SLOT, &tmD, BAR(full2, i), 0, 64 * kblk, 2 * nq);
        }
        wait_counter(&scr->cnt[(C_LN + rb2) * 32], (epoch + 1) * 8);
        asm volatile("fence.proxy.async.global;" ::: "memory");
        mbar_wait(BAR(emptyP, 7));
        bulk_load(sbase + 4 * SLOT, &scr->LN[(rb2 * 8 + 2 * nq) * 1024 + kh * 512], 8192, BAR(hbar, 0));
        bulk_load(sbase + 4 * SLOT + 8192, &scr->LN[(rb2 * 8 + 2 * nq + 1) * 1024 + kh * 512], 8192, BAR(hbar, 0));
      }
    } else if (warp == 10) {
      bar_sync(NB_LN, 288);
      if (lane == 0) {
        PROFP(0);
        red_release(&scr->cnt[(C_LN + rb) * 32]);
        PROFP(1);
        wait_counter(&scr->cnt[(C_LN + rb) * 32], (epoch + 1) * 8);
        asm volatile("fence.proxy.async.global;" ::: "memory");
        PROFP(2);
#pragma unroll 1
        for (int kb = NLL; kb < 8; kb++) {
          if (2 * kb >= ALEAD) mbar_wait(BAR(empty1, 2 * kb - ALEAD));
          bulk_load(sbase + kb * SLOT, &scr->LN[(rb * 8 + kb) * 1024], 16384, BAR(fullA, kb));
        }
#pragma unroll 1
        for (int s = 0; s < 14; s++) {
          const int kblk = 14 * kh + (int)((KORDER >> (4 * s)) & 15);
          if (s == 0 || (SPEC < 0 && (s == 8 || s == 11))) {
            if (s != 11) PROFP(3 + (s >> 2));
            mbar_wait(BAR(hint, s == 0 ? 0 : s == 8 ? 1 : 2), 0);
            if (s != 11) PROFP(4 + (s >> 2));
          }
          const int j = s < 7 ? s : s - 7;
          mbar_wait(s < 7 ? BAR(empty1, 24 + s + (s == 0) + (s >= 4)) : BAR(emptyP, j));
          if (THR_P && s >= THR_P) mbar_wait(BAR(fullP, s - THR_P));
          if (SPEC >= 0 && s == 8) mbar_wait(BAR(emptyP, SPEC & 7));
          bulk_load_mc(sbase + (j ? 7 + j : 4) * SLOT + rk * 8192, &scr->P[(rb2 * 28 + kblk) * 1024 + rk * 512], 8192, BAR(fullP, s));
        }
        PROFP(7);
      }
    } else {
      if (TOUCH) {
#pragma unroll
        for (int i = 0; i < 4 * NLL; i++)
          st_tag(&scr->LN[(rb * 8 + (i >> 2)) * 1024 + f * 128 + (i & 3) * 32 + lane], make_uint4(0, 0, 0, 0), epoch & 1);
        mbar_arrive(BAR(tbar, 0));
      }
      if (lane == 0) {
        l2_prefetch(wg_raw + (size_t)c * 5376, 5376);
        l2_prefetch(wu_raw + (size_t)c * 5376, 5376);
        mbar_wait(BAR(sig, PF2_SIG), 0);
        l2_prefetch(wg_raw + 688128 + (size_t)c * 8960, 8960);
        l2_prefetch(wu_raw + 688128 + (size_t)c * 8960, 8960);
      }
      mbar_wait(BAR(fullA, 4), 0);
      if (lane == 0) l2_prefetch(wd_raw + (size_t)c * 14336, 14336);
      {
        const uint32_t tag = (epoch + 1) & 1;
        uint4 v0, v1, v2;
        int it = 0;
        while (true) {
          v0 = ld_b128(&scr->ST[rb * 64 + lane]);
          v1 = ld_b128(&scr->ST[rb * 64 + 32 + lane]);
          v2 = ld_b128(&scr->ST[rb2 * 64 + 32 * kh + lane]);
          if (!__any_sync(0xffffffffu, ((v0.x ^ tag) | (v1.x ^ tag) | (v2.x ^ tag)) & 1u)) break;
          if (++it > SPIN_LIMIT) { die(); break; }
        }
        sts4(sstat + lane * 16, v0.x & ~1u, v0.y, v0.z, v0.w);
        sts4(sstat + 512 + lane * 16, v1.x & ~1u, v1.y, v1.z, v1.w);
        sts4(sstat + 1024 + lane * 16, v2.x & ~1u, v2.y, v2.z, v2.w);
#pragma unroll 4
        for (int i = 0; i < 32; i++)
          st_tag(&scr->XP[(c ^ 4) * 1024 + i * 32 + lane], make_uint4(0, 0, 0, 0), tag ^ 1);
        mbar_arrive(BAR(sbar, 0));
      }
      if (lane == 0) {
        mbar_wait(BAR(empty1, 17));
#pragma unroll 1
        for (int e = 0; e < (SPEC < 0 ? 3 : 1); e++) {
          const unsigned* cp = e == 0 ? &scr->cnt[(C_PX + rb2) * 32] : &scr->cnt[(C_PY + rb2) * 32 + 2 * kh + e - 1];
          if (e == 1) mbar_wait(BAR(fullP, 0), 0);
          int it = 0;
          while ((int)(ld_relaxed(cp) - (epoch + 1) * (e == 0 ? 64 : 16)) < 0)
            if (++it > SPIN_LIMIT) { die(); break; }
          mbar_arrive(BAR(hint, e));
        }
      }
    }
  } else {
    const int warp = __shfl_sync(0xffffffffu, tid >> 5, 0);
    const int g = lane >> 2, t = lane & 3;
    PROF(0);
    PROFG(14);
#pragma unroll
    for (int i = 0; i < 4; i++) {
      const int r = i >> 1, ch = (i & 1) * 32 + lane;
      cp_async16(sbase + SM_X + (2 * warp + r) * 1024 + ((ch ^ ((ch >> 2) & 6)) * 16),
                 x + (size_t)(c + 128 * (2 * warp + r)) * 512 + ch * 8);
    }
    asm volatile("cp.async.commit_group;" ::: "memory");
    asm volatile("barrier.cluster.arrive.relaxed.aligned;" ::: "memory");
    uint4 tw[8], fb[16];
    const uint4 fa = ldg_ca4_p(1, &tab->fa[lane][0]);
#pragma unroll
    for (int i = 0; i < 8; i++) tw[i] = ldg_ca4_p(1, &tab->tw1[i][lane][0]);
#pragma unroll
    for (int i = 0; i < 16; i++) fb[i] = ldg_ca4_p(1, &tab->fb[i][lane][0]);
    uint32_t rbar;
    asm volatile("mapa.shared::cluster.u32 %0, %1, %2;" : "=r"(rbar) : "r"(sbar), "r"(rk ^ 1));
#define RBAR(field, i) (rbar + (uint32_t)offsetof(Bars, field) + 8u * (i))
    {
      const int ln = (tid >> 1) & 31, lg = ln >> 2, lt = ln & 3, i = 4 * (tid >> 6) + 2 * (tid & 1);
      const int kidx = lt + 8 * (i >> 3), nidx = 4 * ((i >> 1) & 3) + (lg >> 1);
      const uint32_t a0 = cfrag<2048>((c + 128 * kidx) * nidx, lg & 1), a1 = cfrag<2048>((c + 128 * (kidx + 4)) * nidx, lg & 1);
      const uint32_t b0 = cfrag<2048>(-(c + 128 * nidx) * kidx, lg & 1), b1 = cfrag<2048>(-(c + 128 * nidx) * (kidx + 4), lg & 1);
      asm volatile("st.shared.v2.u32 [%0], {%1,%2};" ::"r"(sbase + SM_FC + tid * 8), "r"(a0), "r"(a1) : "memory");
      asm volatile("st.shared.v2.u32 [%0], {%1,%2};" ::"r"(sbase + SM_FC + 2048 + tid * 8), "r"(b0), "r"(b1) : "memory");
    }
    asm volatile("cp.async.wait_group 0;" ::: "memory");
    __syncwarp();
    bar_arrive(NB_INIT, 384);
    PROF(13);
    uint32_t tag;
    uint4 q[4], o[4];
    {
      uint32_t v[2][8];
#pragma unroll
      for (int r = 0; r < 2; r++)
#pragma unroll
        for (int q = 0; q < 4; q++) {
          const uint2 u = lds2(sbase + SM_X + (2 * warp + r) * 1024 + (t + 4 * (q >> 1)) * 128 + (((4 * (q & 1) + (g >> 1)) ^ (2 * t)) * 16) + (g & 1) * 8);
          v[r][2 * q] = u.x; v[r][2 * q + 1] = u.y;
        }
      float sum[2], sq[2], rstd[2];
      row_stats(v[0], v[1], lane, sum, sq);
#pragma unroll
      for (int r = 0; r < 2; r++) {
        const float m = sum[r] * (1.f / 512.f);
        rstd[r] = rsqrtf(fmaxf(fmaf(-m, m, sq[r] * (1.f / 512.f)), 0.f) + 1e-5f);
      }
      uint32_t alo[4][4], ahi[4][4];
#pragma unroll
      for (int r = 0; r < 2; r++)
#pragma unroll
        for (int i = 0; i < 4; i++) {
          const uint32_t sel = (i & 1) ? 0x7632u : 0x5410u;
          const uint32_t b0 = __byte_perm(v[r][i >> 1], v[r][2 + (i >> 1)], sel);
          const uint32_t b1 = __byte_perm(v[r][4 + (i >> 1)], v[r][6 + (i >> 1)], sel);
          float d[4] = {0.f, 0.f, 0.f, 0.f};
          mma16816(d, fa.x, fa.y, fa.z, fa.w, b0, b1);
          const uint4 &ka = tw[2 * i], &kb = tw[2 * i + 1];
          const uint32_t re = pack2(d[0] * __uint_as_float(ka.x) + d[2] * __uint_as_float(ka.y), d[1] * __uint_as_float(kb.x) + d[3] * __uint_as_float(kb.y));
          const uint32_t im = pack2(d[0] * __uint_as_float(ka.z) + d[2] * __uint_as_float(ka.w), d[1] * __uint_as_float(kb.z) + d[3] * __uint_as_float(kb.w));
          const uint32_t dc = pack2(fmaf(sum[r], -1.f / 32.f, d[0]), fmaf(sum[r], -1.f / 32.f, d[1]));
          alo[i][r] = re; alo[i][2 + r] = im;
          ahi[i][r] = g == 0 ? dc : re; ahi[i][2 + r] = g == 0 ? 0u : im;
        }
      float acc[8][4];
#pragma unroll
      for (int u = 0; u < 8; u++) {
        acc[u][0] = acc[u][1] = acc[u][2] = acc[u][3] = 0.f;
#pragma unroll
        for (int i = 0; i < 4; i++) {
          const uint4& bq = fb[i * 4 + (u >> 1)];
          if (u < 4) mma16816(acc[u], alo[i][0], alo[i][1], alo[i][2], alo[i][3], (u & 1) ? bq.z : bq.x, (u & 1) ? bq.w : bq.y);
          else       mma16816(acc[u], ahi[i][0], ahi[i][1], ahi[i][2], ahi[i][3], (u & 1) ? bq.z : bq.x, (u & 1) ? bq.w : bq.y);
        }
      }
#pragma unroll
      for (int r = 0; r < 2; r++)
#pragma unroll
        for (int h = 0; h < 2; h++) {
          const int j = 2 * warp + r, m = 2 * t + h;
          const float rs = rstd[r];
          sts4(sbase + SM_E + ((j * 8 + m) * 8 + (g ^ (2 * t) ^ (2 * (j & 3)))) * 16,
               pack2(acc[2 * h][2 * r] * rs, acc[2 * h][2 * r + 1] * rs), pack2(acc[2 * h + 1][2 * r] * rs, acc[2 * h + 1][2 * r + 1] * rs),
               pack2(acc[4 + 2 * h][2 * r] * rs, acc[4 + 2 * h][2 * r + 1] * rs), pack2(acc[5 + 2 * h][2 * r] * rs, acc[5 + 2 * h][2 * r + 1] * rs));
        }
      if (tid == 0) PROFP(12);
      bar_sync(NB_RDY, 384);
      if (tid == 0) PROFP(13);
      uint4 fc[4];
#pragma unroll
      for (int i = 0; i < 4; i++) fc[i] = lds4(sbase + SM_FC + i * 512 + lane * 16);
      asm volatile("ld.shared.u32 %0, [%1];" : "=r"(tag) : "r"(BAR(epoch, 0)) : "memory");
      tag = (tag + 1) & 1;
#pragma unroll
      for (int i = 0; i < 4; i++) q[i] = lds4(sbase + SM_E + (((t + 4 * i) * 8 + warp) * 8 + (g ^ (warp & 6) ^ (2 * t))) * 16);
      cdft16(q, fc, o);
#pragma unroll
      for (int vv = 0; vv < 4; vv++) st_tag(&scr->Z1[(((4 * vv + t) * 8 + warp) * 128 + c) * 8 + g], o[vv], tag);
    }
    PROF(1);
    asm volatile("setmaxnreg.inc.sync.aligned.u32 224;");
    {
      const uint4* const zp = &scr->Z1[(c * 128 + 8 * t + warp) * 8 + g];
      const uint32_t tst = clock32();
      mbar_wait(BAR(tbar, 0), 0);
      if (tid == 0) PROFP(14);
      uint4 f2[4], g2[4];
#pragma unroll
      for (int i = 0; i < 4; i++) {
        f2[i] = lds4(TOFF(f2) + warp * 2048 + i * 512);
        g2[i] = lds4(TOFF(g2) + warp * 2048 + i * 512);
      }
      const uint4 f8 = lds4(TOFF(f8)), g8 = lds4(TOFF(g8));
      float wfr[16], wfi[16];
      {
        const float fsc = 1.f / (1 << 19);
        const float fsc3 = ((c & 7) == 7 && g == 0) ? 0.5f * fsc : fsc;
        const int gg = g == 0 ? 8 : g, wsh = (2 * (c >> 3) + 2) & 15;
#pragma unroll
        for (int i = 0; i < 16; i++) {
          const int ci = i >> 3, dd = (i >> 2) & 1, e = i & 3;
          const int kk = (e == 0 ? gg : e == 1 ? 16 + gg : e == 2 ? 16 - g : 32 - g) - 1;
          const uint32_t a = sbase + SM_W + ((2 * warp + ci) * 8 + t + 4 * dd) * 80 + wsh + 2 * kk;
          wfr[i] = bf_lo(lds_u16(a)) * (e == 3 ? fsc3 : fsc);
          wfi[i] = bf_lo(lds_u16(a + 10240)) * (e == 3 ? fsc3 : fsc);
        }
      }
      asm volatile("barrier.cluster.wait.aligned;" ::: "memory");
      PROF(2);
      spin_until(tst + POLL_DELAY);
      ld_tag4_issue<256>(q, zp);
      ld_tag4_finish<256>(q, zp, tag);
      if (tid == 0) PROFP(30);
      if (lane == 0) mbar_arrive(BAR(sig, 0));
      cdft16(q, f2, o);
      const uint32_t e2 = sbase + SM_E2;
#pragma unroll
      for (int vv = 0; vv < 4; vv++)
        sts4(e2 + ((warp * 16 + 4 * vv + t) * 8 + (g ^ (2 * t) ^ (2 * (warp & 3)))) * 16, o[vv].x, o[vv].y, o[vv].z, o[vv].w);
      bar_sync(NB_CONS, 256);
#pragma unroll
      for (int ci = 0; ci < 2; ci++) {
        const int cc = 2 * warp + ci;
        uint32_t ad[2];
        uint4 u[2];
#pragma unroll
        for (int hh = 0; hh < 2; hh++) {
          ad[hh] = e2 + (((t + 4 * hh) * 16 + cc) * 8 + (g ^ (2 * (cc & 3)) ^ (2 * t))) * 16;
          u[hh] = lds4(ad[hh]);
        }
        uint32_t res[2][4];
#pragma unroll
        for (int p = 0; p < 2; p++) {
          uint32_t y[2][2];
#pragma unroll
          for (int vv = 0; vv < 2; vv++) {
            float d[4] = {0.f, 0.f, 0.f, 0.f};
            mma16816(d, word(u[0], 2 * p), word(u[0], 2 * p + 1), word(u[1], 2 * p), word(u[1], 2 * p + 1), word(f8, 2 * vv), word(f8, 2 * vv + 1));
#pragma unroll
            for (int rr = 0; rr < 2; rr++) {
              const float fr = wfr[ci * 8 + vv * 4 + 2 * p + rr], fi = wfi[ci * 8 + vv * 4 + 2 * p + rr];
              y[vv][rr] = pack2(d[2 * rr] * fr - d[2 * rr + 1] * fi, d[2 * rr] * fi + d[2 * rr + 1] * fr);
            }
          }
#pragma unroll
          for (int vv = 0; vv < 2; vv++) {
            float d[4] = {0.f, 0.f, 0.f, 0.f};
            mma16816(d, y[0][0], y[0][1], y[1][0], y[1][1], word(g8, 2 * vv), word(g8, 2 * vv + 1));
            res[vv][2 * p] = pack2(d[0], d[1]);
            res[vv][2 * p + 1] = pack2(d[2], d[3]);
          }
        }
#pragma unroll
        for (int vv = 0; vv < 2; vv++) sts4(ad[vv], res[vv][0], res[vv][1], res[vv][2], res[vv][3]);
      }
      bar_sync(NB_CONS, 256);
#pragma unroll
      for (int i = 0; i < 4; i++) q[i] = lds4(e2 + ((warp * 16 + 4 * i + t) * 8 + (g ^ (2 * t) ^ (2 * (warp & 3)))) * 16);
      cdft16(q, g2, o);
#pragma unroll
      for (int vv = 0; vv < 4; vv++) st_tag(&scr->Z2[((8 * (4 * vv + t) + warp) * 128 + c) * 8 + g], o[vv], tag);
    }
    PROF(3);
    {
      const uint4* const zp = &scr->Z2[((c * 16 + t) * 8 + warp) * 8 + g];
      const uint32_t tst = clock32();
      uint4 gb[16], gc[4], tw[4], xr[2][2];
#pragma unroll
      for (int i = 0; i < 16; i++) gb[i] = lds4(TOFF(gb) + i * 512);
      const uint4 ga = lds4(TOFF(ga));
#pragma unroll
      for (int i = 0; i < 4; i++) {
        gc[i] = lds4(sbase + SM_FC + 2048 + i * 512 + lane * 16);
        tw[i] = lds4(TOFF(tw3) + i * 512);
        const int ch = 4 * (g + 8 * (i & 1)) + t;
        xr[i >> 1][i & 1] = lds4(sbase + SM_X + (2 * warp + (i >> 1)) * 1024 + ((ch ^ ((ch >> 2) & 6)) * 16));
      }
      PROF(4);
      spin_until(tst + POLL_DELAY);
      ld_tag4_issue<256>(q, zp);
      ld_tag4_finish<256>(q, zp, tag);
      if (tid == 0) PROFP(31);
      if (lane == 0) mbar_arrive(BAR(sig, 1));
      cdft16(q, gc, o);
#pragma unroll
      for (int vv = 0; vv < 4; vv++)
        sts4(sbase + SM_E + (((4 * vv + t) * 8 + warp) * 8 + (g ^ (warp & 6) ^ (2 * t))) * 16, o[vv].x, o[vv].y, o[vv].z, o[vv].w);
      if (tid == 0) PROFP(8);
      bar_sync(NB_CONS, 256);
      if (tid == 0) PROFP(9);
      uint32_t hv[2][8];
      const float mk = t == 0 ? 0.f : 1.f;
#pragma unroll
      for (int r = 0; r < 2; r++) {
        const int j = 2 * warp + r;
        uint4 u[2];
#pragma unroll
        for (int h = 0; h < 2; h++) u[h] = lds4(sbase + SM_E + ((j * 8 + 2 * t + h) * 8 + (g ^ (2 * t) ^ (2 * (j & 3)))) * 16);
        float yv[4][4];
#pragma unroll
        for (int i = 0; i < 4; i++) {
          float lo[4] = {0.f, 0.f, 0.f, 0.f}, hi[4] = {0.f, 0.f, 0.f, 0.f};
          mma16816(lo, gb[i * 4].x, gb[i * 4].y, gb[i * 4].z, gb[i * 4].w, u[0].x, u[0].y);
          mma16816(lo, gb[i * 4 + 1].x, gb[i * 4 + 1].y, gb[i * 4 + 1].z, gb[i * 4 + 1].w, u[1].x, u[1].y);
          mma16816(hi, gb[i * 4 + 2].x, gb[i * 4 + 2].y, gb[i * 4 + 2].z, gb[i * 4 + 2].w, u[0].z, u[0].w);
          mma16816(hi, gb[i * 4 + 3].x, gb[i * 4 + 3].y, gb[i * 4 + 3].z, gb[i * 4 + 3].w, u[1].z, u[1].w);
          const float ca = __uint_as_float(tw[i].x), sa = __uint_as_float(tw[i].y), cb = __uint_as_float(tw[i].z), sb = __uint_as_float(tw[i].w);
          const float tr0 = fmaf(hi[0], mk, lo[0]), ti0 = fmaf(hi[2], mk, lo[2]);
          const float tr1 = lo[1] + hi[1], ti1 = lo[3] + hi[3];
          const float vr0 = tr0 * ca - ti0 * sa, vi0 = tr0 * sa + ti0 * ca;
          const float vr1 = tr1 * cb - ti1 * sb, vi1 = tr1 * sb + ti1 * cb;
          const uint32_t b0 = pack2(t == 0 ? hi[0] : vr0, vr1), b1 = pack2(t == 0 ? vr0 : vi0, vi1);
          yv[i][0] = yv[i][1] = yv[i][2] = yv[i][3] = 0.f;
          mma16816(yv[i], ga.x, ga.y, ga.z, ga.w, b0, b1);
        }
#pragma unroll
        for (int h = 0; h < 2; h++) {
          hv[r][4 * h + 0] = hadd2_bf16(xr[r][h].x, pack2(yv[0][2 * h], yv[1][2 * h]));
          hv[r][4 * h + 1] = hadd2_bf16(xr[r][h].y, pack2(yv[2][2 * h], yv[3][2 * h]));
          hv[r][4 * h + 2] = hadd2_bf16(xr[r][h].z, pack2(yv[0][2 * h + 1], yv[1][2 * h + 1]));
          hv[r][4 * h + 3] = hadd2_bf16(xr[r][h].w, pack2(yv[2][2 * h + 1], yv[3][2 * h + 1]));
        }
      }
      if (tid == 0 && hv[0][0] != 0x12345 && hv[1][7] != 0x12345) PROFP(10);
      float ds[4] = {0.f, 0.f, 0.f, 0.f};
#pragma unroll
      for (int q4 = 0; q4 < 4; q4++) mma16816(ds, hv[0][2 * q4], hv[1][2 * q4], hv[0][2 * q4 + 1], hv[1][2 * q4 + 1], 0x3f803f80u, 0x3f803f80u);
#pragma unroll
      for (int o2 = 4; o2 <= 16; o2 <<= 1) {
        ds[0] += __shfl_xor_sync(0xffffffffu, ds[0], o2);
        ds[2] += __shfl_xor_sync(0xffffffffu, ds[2], o2);
      }
      uint32_t mb[2];
#pragma unroll
      for (int r = 0; r < 2; r++) mb[r] = pack2(ds[2 * r] * (1.f / 512.f), ds[2 * r] * (1.f / 512.f));
#pragma unroll
      for (int h = 0; h < 2; h++)
#pragma unroll
        for (int r = 0; r < 2; r++) {
          const int row = 16 * f + 2 * warp + r, n1 = g + 8 * h;
#pragma unroll
          for (int i = 0; i < 4; i++) hv[r][4 * h + i] = hsub2_bf16(hv[r][4 * h + i], mb[r]);
          st_tag(&scr->LN[(rb * 8 + (n1 >> 1)) * 1024 + row * 8 + ((4 * (n1 & 1) + t) ^ (row & 7))],
                 make_uint4(hv[r][4 * h], hv[r][4 * h + 1], hv[r][4 * h + 2], hv[r][4 * h + 3]), n1 < 2 * NLL ? tag : (hv[r][4 * h] & 1u));
        }
      if (tid == 0) PROFP(11);
      bar_arrive(NB_LN, 288);
      float sum[2], sq[2], rstd[2];
      row_stats(hv[0], hv[1], lane, sum, sq);
#pragma unroll
      for (int r = 0; r < 2; r++) {
        const float m = sum[r] * (1.f / 512.f);
        rstd[r] = rsqrtf(fmaxf(fmaf(-m, m, sq[r] * (1.f / 512.f)), 0.f) + 1e-5f);
      }
      if (lane == 0)
        st_tag(&scr->ST[rb * 64 + 8 * f + warp], make_uint4(mb[0] << 16, __float_as_uint(rstd[0]), mb[1] << 16, __float_as_uint(rstd[1])), tag);
    }
    PROF(5);
    const int wgi = warp >> 2, wq = warp & 3;
    uint4* const pbase = &scr->P[rb * 28 * 1024 + warp * 128 + lane];
    const uint32_t a_lo0 = desc_lo(sbase + wgi * 8192, 16);
    const uint32_t ebar = lane == 0 ? BAR(empty1, 0) : RBAR(empty1, 0);
    float r0, r1;
    uint4 px[8], py[6];
    const int rh = wgi ^ kh ^ 1;
    const uint4* const psrc = &scr->P[(rb2 * 28 + 14 * kh) * 1024 + (4 * rh + wq) * 128 + lane];
    {
      float acc[128];
#pragma unroll
      for (int i = 0; i < 128; i++) acc[i] = 0.f;
      const uint32_t b_lo0 = desc_lo(sbase + 8 * SLOT, 4096);
      const uint32_t t3 = clock32();
      if (WARM) {
        wg_fence();
#pragma unroll
        for (int i = 0; i < WARM; i++) wgmma_n256(acc, desc64(a_lo0 + 6 * 1024, HI128), desc64(b_lo0, HI128));
        wg_commit();
      }
      const uint4* const ap = &scr->LN[rb * 8 * 1024 + wgi * 512 + (tid & 127)];
      uint4 av[NLL][4];
      while (clock32() - t3 < POLL_DELAY3) {}
#pragma unroll
      for (int kb = 0; kb < NLL; kb++) ld_tag4_issue<128>(av[kb], ap + kb * 1024);
      bar_sync(NB_CONS, 256);
      uint32_t slot = 2;
      auto stage_x = [&](int kb, int hh) {
        if (LAGX && hh == ((16 - LAGX) & 1) && kb == ((16 - LAGX) >> 1) && wgi == 1) bar_sync(NB_LAG, 256);
        mbar_wait(BAR(full1, 2 * kb + hh));
        const uint32_t al = a_lo0 + kb * 1024 + hh * 4, bl = b_lo0 + slot * 1024;
        wg_fence();
        wgmma_n256(acc, desc64(al, HI128), desc64(bl, HI128), (kb | hh) != 0);
        wgmma_n256(acc, desc64(al + 2, HI128), desc64(bl + 128, HI128));
        wg_commit();
        if (LAGX && hh == 1 && kb == 7 && wgi == 0) bar_arrive(NB_LAG, 256);
        wg_wait<1>();
        if ((kb | hh) != 0 && lane < 2) mbar_arrive_remote(ebar + 8 * (2 * kb + hh - 1));
        if (++slot == 6) slot = 0;
      };
#pragma unroll
      for (int kb = 0; kb < NLL; kb++) {
        ld_tag4_finish<128>(av[kb], ap + kb * 1024, tag);
#pragma unroll
        for (int i = 0; i < 4; i++)
          sts4(sbase + kb * SLOT + wgi * 8192 + ((tid & 127) + 128 * i) * 16, av[kb][i].x, av[kb][i].y, av[kb][i].z, av[kb][i].w);
        asm volatile("fence.proxy.async.shared::cta;" ::: "memory");
        bar_sync(NB_WG + wgi, 128);
        if (kb > 0) stage_x(kb - 1, 1);
        if (kb == 0) PROF(6);
        stage_x(kb, 0);
      }
      stage_x(NLL - 1, 1);
#pragma unroll 1
      for (int kb = NLL; kb < 8; kb++) {
        mbar_wait(BAR(fullA, kb));
        stage_x(kb, 0);
        stage_x(kb, 1);
      }
      mbar_wait(BAR(sbar, 0), 0);
      r0 = __uint_as_float(lds2(sstat + (16 * warp + g) * 8).y);
      r1 = __uint_as_float(lds2(sstat + (16 * warp + g + 8) * 8).y);
      wg_wait<0>();
      if (lane < 2) mbar_arrive_remote(ebar + 8 * 15);
      PROF(7);
      make_p<8, false>(acc, r0, r1, px, pbase, 0, tag);
    }
    PROF(8);
    {
      float acc[96];
#pragma unroll
      for (int i = 0; i < 96; i++) acc[i] = 0.f;
      const uint32_t b_lo0 = desc_lo(sbase + 8 * SLOT, 2048);
      uint4* const pdst = pbase + ((7 * f + 3 * (f & 1)) >> 1) * 1024;
      auto stage_y = [&](int k) {
        if (LAGY && k == 16 - LAGY && wgi == 1) bar_sync(NB_LAG, 256);
        mbar_wait(BAR(full1, 16 + k));
        const uint32_t al = a_lo0 + (k >> 1) * 1024 + (k & 1) * 4, bl = b_lo0 + (k & 7) * 768;
        wg_fence();
        wgmma_n192(acc, desc64(al, HI128), desc64(bl, HI64));
        wgmma_n192(acc, desc64(al + 2, HI128), desc64(bl + 64, HI64));
        wg_commit();
      };
#pragma unroll
      for (int k = 0; k < 4; k++) {
        stage_y(k);
        st_tag(pdst + (k >> 1) * 1024 + (k & 1) * 64, px[2 * k], tag);
        st_tag(pdst + (k >> 1) * 1024 + (k & 1) * 64 + 32, px[2 * k + 1], tag);
        if (k == 3 && lane == 0) red_relaxed(&scr->cnt[(C_PX + rb) * 32]);
        wg_wait<1>();
        if (k != 0 && lane < 2) mbar_arrive_remote(ebar + 8 * (15 + k));
      }
#pragma unroll 1
      for (int k = 4; k < 16; k++) {
        stage_y(k);
        if (LAGY && k == 15 && wgi == 0) bar_arrive(NB_LAG, 256);
        wg_wait<1>();
        if (lane < 2) mbar_arrive_remote(ebar + 8 * (15 + k));
      }
      wg_wait<0>();
      if (lane < 2) mbar_arrive_remote(ebar + 8 * 31);
      PROF(9);
      make_p<6, true>(acc, r0, r1, py, pbase, 14 * f + ((f & 1) ? 0 : 8), tag);
      if (lane == 0) red_relaxed(&scr->cnt[(C_PY + rb) * 32 + (f >> 1)]);
    }
    PROF(10);
    {
      float acc[64];
      const uint32_t b2_lo0 = desc_lo(sbase, 8192);
      const uint32_t pa0 = sbase + (4 * rh + wq) * 2048;
      const uint32_t pbar = ebar + (uint32_t)(offsetof(Bars, emptyP) - offsetof(Bars, empty1));
      uint4 fa[3][4];
      uint32_t rdy = 0;
      mbar_wait(BAR(fullP, 0));
#pragma unroll
      for (int kk = 0; kk < 4; kk++) fa[0][kk] = lds4(pa0 + 4 * SLOT + kk * 512 + lane * 16);
#pragma unroll
      for (int s = 0; s < 14; s++) {
        uint4 (&a)[4] = fa[s % 3];
        ld_tag4_finish<32>(a, psrc + (int)((KORDER >> (4 * s)) & 15) * 1024, tag);
        if (s < 8 && lane < (s < 7 ? 2 : 1)) mbar_arrive_remote(pbar + 8 * s);
        if (s >= 2) {
          wg_wait<1>();
          if (s <= 8 && lane == 0) mbar_arrive(BAR(empty2, s - 2));
        }
        if (!rdy) {
          if (s < 13) mbar_wait(BAR(fullP, s + 1));
          mbar_wait(BAR(full2, s));
        }
        if (tid == 0) PROFP(16 + s);
        if (s == 14 - LAG2 && wgi == 1) {
          const float m0 = __uint_as_float(lds2(sstat + 1024 + (16 * wq + g) * 8).x);
          const float m1 = __uint_as_float(lds2(sstat + 1024 + (16 * wq + g + 8) * 8).x);
          const uint32_t hb = sbase + 4 * SLOT + (16 * wq + (lane & 15)) * 128;
          wg_wait<0>();
          mbar_wait(BAR(hbar, 0));
#pragma unroll
          for (int i = 0; i < 8; i++) {
            uint32_t h[4];
            asm volatile("ldmatrix.sync.aligned.m8n8.x4.shared.b16 {%0,%1,%2,%3}, [%4];"
                         : "=r"(h[0]), "=r"(h[1]), "=r"(h[2]), "=r"(h[3])
                         : "r"(hb + (i >> 2) * 8192 + (((2 * (i & 3) + (lane >> 4)) ^ (lane & 7)) * 16)) : "memory");
            const uint32_t mk = (t == 0 && 2 * nq + (i >> 2) < NLL) ? ~1u : ~0u;
#pragma unroll
            for (int e = 0; e < 4; e++) {
              acc[8 * i + 2 * e] += bf_lo(h[e] & mk) + ((e & 1) ? m1 : m0);
              acc[8 * i + 2 * e + 1] += __uint_as_float(h[e] & 0xffff0000u) + ((e & 1) ? m1 : m0);
            }
          }
          bar_sync(NB_LAG, 256);
        }
        const uint32_t bl = b2_lo0 + (uint32_t)((BSLOT >> (4 * s)) & 15) * 1024;
        wg_fence();
        if (s < 13) {
#pragma unroll
          for (int kk = 0; kk < 4; kk++)
            fa[(s + 1) % 3][kk] = lds4(pa0 + (uint32_t)((PSLOT >> (4 * (s + 1))) & 15) * SLOT + kk * 512 + lane * 16);
          rdy = mbar_test(BAR(full2, s + 1));
          if (s < 12) rdy &= mbar_test(BAR(fullP, s + 2));
        }
        if (s == 0) wgmma_rs_n128<0>(acc, a[0].x, a[0].y, a[0].z, a[0].w, desc64(bl, HI128));
        else wgmma_rs_n128<1>(acc, a[0].x, a[0].y, a[0].z, a[0].w, desc64(bl, HI128));
#pragma unroll
        for (int kk = 1; kk < 4; kk++) wgmma_rs_n128<1>(acc, a[kk].x, a[kk].y, a[kk].z, a[kk].w, desc64(bl + kk * 128, HI128));
        wg_commit();
      }
      if (wgi == 0) {
        bar_arrive(NB_LAG, 256);
        uint4* const dst = &scr->XP[(c ^ 4) * 1024 + tid];
        wg_wait<0>();
        PROF(11);
#pragma unroll
        for (int i = 0; i < 8; i++)
          st_tag(dst + i * 128, make_uint4(pack2(acc[8 * i], acc[8 * i + 1]), pack2(acc[8 * i + 2], acc[8 * i + 3]),
                                           pack2(acc[8 * i + 4], acc[8 * i + 5]), pack2(acc[8 * i + 6], acc[8 * i + 7])), tag);
      } else {
        uint4 pv[2][4];
        const uint4* const xsrc = &scr->XP[c * 1024 + (tid & 127)];
        ld_tag4_issue<128>(pv[0], xsrc);
        ld_tag4_issue<128>(pv[1], xsrc + 512);
        wg_wait<0>();
        PROF(11);
        uint32_t w[32];
#pragma unroll
        for (int i = 0; i < 32; i++) w[i] = pack2(acc[2 * i], acc[2 * i + 1]);
        ld_tag4_finish<128>(pv[0], xsrc, tag);
        ld_tag4_finish<128>(pv[1], xsrc + 512, tag);
#pragma unroll
        for (int i = 0; i < 8; i++) {
          const uint4& p = pv[i >> 2][i & 3];
          asm volatile("stmatrix.sync.aligned.m8n8.x4.shared.b16 [%0], {%1,%2,%3,%4};"
                       ::"r"(pa0 + (9 + ((lane >> 3) & 1)) * SLOT + (lane & 7) * 256 + (((2 * i + (lane >> 4)) ^ (lane & 7)) * 16)),
                         "r"(hadd2_bf16(w[4 * i], p.x)), "r"(hadd2_bf16(w[4 * i + 1], p.y)), "r"(hadd2_bf16(w[4 * i + 2], p.z)),
                         "r"(hadd2_bf16(w[4 * i + 3], p.w)) : "memory");
        }
        __syncwarp();
        uint4* const dst = reinterpret_cast<uint4*>(out) + (16 * (c >> 4) + 2 * (4 * rh + wq) + (rb2 & 1) + 128 * (lane >> 4)) * 64 + nq * 16 + (lane & 15);
#pragma unroll
        for (int i = 0; i < 8; i++) {
          const int r = 2 * (i & 3) + (lane >> 4);
          dst[i * 256 * 64] = lds4(pa0 + (9 + (i >> 2)) * SLOT + r * 256 + (((lane & 15) ^ r) * 16));
        }
      }
      PROF(12);
      PROFG(15);
    }
  }
#undef BAR
#undef TOFF
#undef RBAR
}

typedef CUresult (*EncodeFn)(CUtensorMap*, CUtensorMapDataType, cuuint32_t, void*, const cuuint64_t*, const cuuint64_t*,
                             const cuuint32_t*, const cuuint32_t*, CUtensorMapInterleave, CUtensorMapSwizzle,
                             CUtensorMapL2promotion, CUtensorMapFloatOOBfill);

}

extern "C" void kernel_launch(void* const* d_in, const int* in_sizes, int n_in, void* d_out, int out_size) {
  (void)in_sizes; (void)n_in; (void)out_size;
  static EncodeFn encode = nullptr;
  static void *tab = nullptr, *scr = nullptr;
  if (!encode) {
    void* fn = nullptr;
    cudaDriverEntryPointQueryResult qr;
    cudaGetDriverEntryPoint("cuTensorMapEncodeTiled", &fn, cudaEnableDefault, &qr);
    encode = (EncodeFn)fn;
    cudaGetSymbolAddress(&tab, g_tab);
    cudaGetSymbolAddress(&scr, g_scr);
    cudaFuncSetAttribute(fused_kernel, cudaFuncAttributeMaxDynamicSharedMemorySize, SMEM_BYTES);
  }
  CUtensorMap tmGX, tmUX, tmGY, tmUY, tmD, tmWR, tmWI;
  const cuuint32_t es[5] = {1, 1, 1, 1, 1};
  auto enc = [&](CUtensorMap* m, void* p, int rank, const cuuint64_t* gd, const cuuint64_t* gs, const cuuint32_t* bd,
                 CUtensorMapSwizzle sw, CUtensorMapL2promotion pr) {
    encode(m, CU_TENSOR_MAP_DATA_TYPE_BFLOAT16, rank, p, gd, gs, bd, es, CU_TENSOR_MAP_INTERLEAVE_NONE, sw, pr,
           CU_TENSOR_MAP_FLOAT_OOB_FILL_NONE);
  };
  {
    const cuuint64_t gd[3] = {64, 512, 28}, gs[2] = {3584, 128};
    const cuuint32_t bd[3] = {64, 32, 2};
    enc(&tmGX, d_in[4], 3, gd, gs, bd, CU_TENSOR_MAP_SWIZZLE_128B, CU_TENSOR_MAP_L2_PROMOTION_L2_256B);
    enc(&tmUX, d_in[5], 3, gd, gs, bd, CU_TENSOR_MAP_SWIZZLE_128B, CU_TENSOR_MAP_L2_PROMOTION_L2_256B);
  }
  {
    const cuuint64_t gd[3] = {32, 512, 56}, gs[2] = {3584, 64};
    const cuuint32_t bd[3] = {32, 32, 3};
    enc(&tmGY, d_in[4], 3, gd, gs, bd, CU_TENSOR_MAP_SWIZZLE_64B, CU_TENSOR_MAP_L2_PROMOTION_L2_128B);
    enc(&tmUY, d_in[5], 3, gd, gs, bd, CU_TENSOR_MAP_SWIZZLE_64B, CU_TENSOR_MAP_L2_PROMOTION_L2_128B);
  }
  {
    const cuuint64_t gd[3] = {64, 1792, 8}, gs[2] = {1024, 128};
    const cuuint32_t bd[3] = {64, 64, 2};
    enc(&tmD, d_in[6], 3, gd, gs, bd, CU_TENSOR_MAP_SWIZZLE_128B, CU_TENSOR_MAP_L2_PROMOTION_L2_256B);
  }
  {
    const cuuint64_t gd[3] = {4112, 8, 16}, gs[2] = {16 * 8224, 8224};
    const cuuint32_t bd[3] = {40, 8, 16};
    enc(&tmWR, d_in[1], 3, gd, gs, bd, CU_TENSOR_MAP_SWIZZLE_NONE, CU_TENSOR_MAP_L2_PROMOTION_NONE);
    enc(&tmWI, d_in[2], 3, gd, gs, bd, CU_TENSOR_MAP_SWIZZLE_NONE, CU_TENSOR_MAP_L2_PROMOTION_NONE);
  }
  fused_kernel<<<NCTA, NTHREADS, SMEM_BYTES>>>((const __nv_bfloat16*)d_in[0], (const Tables*)tab, (Scratch*)scr,
                                               (__nv_bfloat16*)d_out, (const char*)d_in[4], (const char*)d_in[5],
                                               (const char*)d_in[6], tmWR, tmWI, tmGX, tmUX, tmGY, tmUY, tmD);
}
```

```cpp
#include <cuda_runtime.h>
#include <cuda_bf16.h>
#include <cuda.h>
#include <stdint.h>

namespace {

constexpr int NCTA = 128;
constexpr int NTHREADS = 384;
constexpr int SLOT = 16384;
constexpr int SMEM_BYTES = 14 * SLOT + 3072;
constexpr int SPIN_LIMIT = 1 << 22;

struct Scratch {
  uint4 Z1[128 * 1024];
  uint4 Z2[128 * 1024];
  uint4 LN[16 * 8 * 1024];
  uint4 P[16 * 28 * 1024];
  uint4 XP[128 * 1024];
  uint4 ST[1024];
  unsigned cnt[64 * 32];
};
__device__ __align__(1024) Scratch g_scr;
#define PROF(i)
#define PROFP(i)
#define PROFG(i)

constexpr double ccos(int i, int n) {
  i &= n - 1;
  if (i > n / 2) i = n - i;
  if (4 * i == n) return 0.0;
  const bool neg = 4 * i > n;
  if (neg) i = n / 2 - i;
  const double a = 6.283185307179586476925 * i / n, a2 = a * a;
  double term = 1.0, sum = 1.0;
  for (int k = 1; k < 14; k++) { term *= -a2 / ((2 * k - 1) * (2 * k)); sum += term; }
  return neg ? -sum : sum;
}
constexpr double csin(int i, int n) { return ccos(i - n / 4, n); }
constexpr unsigned fbits(double v, int mant) {
  if (v == 0.0) return 0;
  const unsigned sg = v < 0 ? 1u : 0u;
  if (v < 0) v = -v;
  int e = 127;
  while (v < 1.0) { v *= 2.0; e--; }
  const unsigned m = (unsigned)((v - 1.0) * (double)(1u << mant) + 0.5);
  return (sg << (8 + mant)) + ((unsigned)e << mant) + m;
}
constexpr unsigned pkb(double lo, double hi) { return fbits(lo, 7) | (fbits(hi, 7) << 16); }
constexpr double fa_elem(int mt, int r, int n1) {
  const int k1 = 8 * mt + (r & 7);
  return r < 8 ? ccos(k1 * n1, 32) : k1 == 0 ? ccos(16 * n1, 32) : -csin(k1 * n1, 32);
}
constexpr unsigned cfrag_c(int idx, int n, int ri) {
  return ri ? pkb(-csin(idx, n), ccos(idx, n)) : pkb(ccos(idx, n), csin(idx, n));
}
struct Tables {
  unsigned fa[4][32][4];
  unsigned fb[4][32][4];
  unsigned tw1[6][32][4];
  unsigned f2[8][4][32][4];
  unsigned g2[8][4][32][4];
  unsigned gb[4][32][4];
  unsigned ga[4][32][4];
  unsigned tw3[4][32][4];
  unsigned f8[32][4], g8[32][4];
};
constexpr int T1_BYTES = 7168, T2_BYTES = 39936;
static_assert(sizeof(Tables) == T1_BYTES + T2_BYTES, "table size");
constexpr Tables make_tables() {
  Tables T = {};
  for (int l = 0; l < 32; l++) {
    const int g = l >> 2, t = l & 3;
    for (int a = 0; a < 2; a++)
      for (int b = 0; b < 2; b++) {
        for (int r = 0; r < 4; r++) {
          const int row = g + 8 * (r & 1), col = 2 * t + 8 * (r >> 1);
          T.fa[2 * a + b][l][r] = pkb(fa_elem(a, row, 16 * b + col), fa_elem(a, row, 16 * b + col + 1));
          T.ga[2 * a + b][l][r] = pkb(fa_elem(b, col, 16 * a + row), fa_elem(b, col + 1, 16 * a + row));
        }
        const double sg = b ? -1.0 : 1.0;
        for (int h = 0; h < 2; h++) {
          const int ri = g & 1, m = 2 * (g >> 1) + h, k2 = b ? 15 - m : m;
          const int pa = (8 * a + 2 * t) * k2, pb = (8 * a + 2 * t + 1) * k2;
          T.fb[2 * a + b][l][2 * h] = ri == 0 ? pkb(ccos(pa, 16), ccos(pb, 16)) : pkb(-sg * csin(pa, 16), -sg * csin(pb, 16));
          T.fb[2 * a + b][l][2 * h + 1] = ri == 0 ? pkb(csin(pa, 16), csin(pb, 16)) : pkb(sg * ccos(pa, 16), sg * ccos(pb, 16));
        }
        const int n2 = 4 * (g >> 1) + 2 * a + (g & 1);
        for (int h = 0; h < 2; h++) {
          const int p = n2 * (b ? 15 - 2 * t - h : 2 * t + h);
          T.gb[2 * a + b][l][2 * h] = pkb(ccos(p, 16), -sg * csin(p, 16));
          T.gb[2 * a + b][l][2 * h + 1] = pkb(csin(p, 16), sg * ccos(p, 16));
          const int k1 = 8 * b + 2 * t + h, q = n2 * (k1 == 0 ? 16 : k1);
          T.tw3[2 * a + b][l][2 * h] = fbits(ccos(q, 512), 23);
          T.tw3[2 * a + b][l][2 * h + 1] = fbits(csin(q, 512), 23);
        }
        const int p = (8 * a + 2 * t + b) * (g == 0 ? 16 : g);
        T.tw1[2 * a + b][l][0] = fbits(g == 0 ? 0.0 : ccos(p, 512), 23);
        T.tw1[2 * a + b][l][1] = fbits(g == 0 ? ccos(p, 512) : csin(p, 512), 23);
        T.tw1[2 * a + b][l][2] = fbits(g == 0 ? 0.0 : -csin(p, 512), 23);
        T.tw1[2 * a + b][l][3] = fbits(g == 0 ? -csin(p, 512) : ccos(p, 512), 23);
        T.tw1[4 + a][l][2 * b] = fbits(ccos((8 * a + 2 * t + b) * (g + 8), 512), 23);
        T.tw1[4 + a][l][2 * b + 1] = fbits(csin((8 * a + 2 * t + b) * (g + 8), 512), 23);
      }
    for (int i = 0; i < 4; i++) {
      const int p8 = (t + 4 * (i & 1)) * (4 * (i >> 1) + (g >> 1));
      T.f8[l][i] = cfrag_c(p8, 8, g & 1);
      T.g8[l][i] = cfrag_c(-p8, 8, g & 1);
    }
    for (int w = 0; w < 8; w++)
      for (int i = 0; i < 16; i++) {
        const int kidx = t + 4 * (i & 1) + 8 * (i >> 3), nidx = 4 * ((i >> 1) & 3) + (g >> 1);
        T.f2[w][i >> 2][l][i & 3] = cfrag_c((8 * kidx + w) * nidx, 128, g & 1);
        T.g2[w][i >> 2][l][i & 3] = cfrag_c(-(8 * nidx + w) * kidx, 128, g & 1);
      }
  }
  return T;
}
__device__ const __align__(128) Tables g_tab = make_tables();

__device__ __forceinline__ void die() { asm volatile("st.global.u32 [%0], %1;" ::"l"(0ull), "r"(0) : "memory"); }
__device__ __forceinline__ uint32_t s2u(const void* p) { return (uint32_t)__cvta_generic_to_shared(p); }
__device__ __forceinline__ void mbar_init(uint32_t b, int c) { asm volatile("mbarrier.init.shared::cta.b64 [%0], %1;" ::"r"(b), "r"(c)); }
__device__ __forceinline__ void mbar_expect(uint32_t b, int bytes) {
  asm volatile("mbarrier.arrive.expect_tx.shared::cta.b64 _, [%0], %1;" ::"r"(b), "r"(bytes) : "memory");
}
__device__ __forceinline__ void mbar_arrive(uint32_t b) { asm volatile("mbarrier.arrive.shared::cta.b64 _, [%0];" ::"r"(b) : "memory"); }
__device__ __forceinline__ uint32_t mbar_try(uint32_t b, uint32_t parity) {
  uint32_t ok;
  asm volatile("{.reg .pred p; mbarrier.try_wait.parity.shared::cta.b64 p, [%1], %2; selp.u32 %0,1,0,p;}"
               : "=r"(ok) : "r"(b), "r"(parity) : "memory");
  return ok;
}
__device__ __forceinline__ uint32_t mbar_test(uint32_t b) {
  uint32_t ok;
  asm volatile("{.reg .pred p; mbarrier.test_wait.parity.shared::cta.b64 p, [%1], 0; selp.u32 %0,1,0,p;}" : "=r"(ok) : "r"(b) : "memory");
  return ok;
}
__device__ __forceinline__ void mbar_wait(uint32_t b, uint32_t parity = 0) {
  int it = 0;
#pragma unroll 1
  while (!mbar_try(b, parity))
    if (++it > SPIN_LIMIT) { die(); break; }
}
__device__ __forceinline__ void bar_sync(int id, int n) { asm volatile("bar.sync %0, %1;" ::"r"(id), "r"(n) : "memory"); }
__device__ __forceinline__ void bar_arrive(int id, int n) { asm volatile("bar.arrive %0, %1;" ::"r"(id), "r"(n) : "memory"); }
__device__ __forceinline__ void red_release(unsigned* p) { asm volatile("red.release.gpu.global.add.u32 [%0], 1;" ::"l"(p) : "memory"); }
__device__ __forceinline__ void red_relaxed(unsigned* p) { asm volatile("red.relaxed.gpu.global.add.u32 [%0], 1;" ::"l"(p) : "memory"); }
__device__ __forceinline__ unsigned ld_acquire(const unsigned* p) {
  unsigned v;
  asm volatile("ld.acquire.gpu.global.u32 %0, [%1];" : "=r"(v) : "l"(p) : "memory");
  return v;
}
__device__ __forceinline__ unsigned ld_relaxed(const unsigned* p) {
  unsigned v;
  asm volatile("ld.relaxed.gpu.global.u32 %0, [%1];" : "=r"(v) : "l"(p) : "memory");
  return v;
}
__device__ __forceinline__ void wait_counter(const unsigned* p, unsigned target) {
  int it = 0;
  while ((int)(ld_acquire(p) - target) < 0)
    if (++it > SPIN_LIMIT) { die(); break; }
}
__device__ __forceinline__ void sts4(uint32_t a, uint32_t x, uint32_t y, uint32_t z, uint32_t w) {
  asm volatile("st.shared.v4.u32 [%0], {%1,%2,%3,%4};" ::"r"(a), "r"(x), "r"(y), "r"(z), "r"(w) : "memory");
}
__device__ __forceinline__ uint4 lds4(uint32_t a) {
  uint4 v;
  asm volatile("ld.shared.v4.u32 {%0,%1,%2,%3}, [%4];" : "=r"(v.x), "=r"(v.y), "=r"(v.z), "=r"(v.w) : "r"(a) : "memory");
  return v;
}
__device__ __forceinline__ uint32_t pack2(float lo, float hi) {
  uint32_t r;
  asm("cvt.rn.bf16x2.f32 %0, %1, %2;" : "=r"(r) : "f"(hi), "f"(lo));
  return r;
}
__device__ __forceinline__ float bf_lo(uint32_t v) { return __uint_as_float(v << 16); }
__device__ __forceinline__ uint32_t hadd2_bf16(uint32_t a, uint32_t b) {
  uint32_t r;
  asm("add.rn.bf16x2 %0, %1, %2;" : "=r"(r) : "r"(a), "r"(b));
  return r;
}
__device__ __forceinline__ void mma16816(float (&d)[4], uint32_t a0, uint32_t a1, uint32_t a2, uint32_t a3, uint32_t b0, uint32_t b1) {
  asm("mma.sync.aligned.m16n8k16.row.col.f32.bf16.bf16.f32 {%0,%1,%2,%3}, {%4,%5,%6,%7}, {%8,%9}, {%0,%1,%2,%3};"
      : "+f"(d[0]), "+f"(d[1]), "+f"(d[2]), "+f"(d[3])
      : "r"(a0), "r"(a1), "r"(a2), "r"(a3), "r"(b0), "r"(b1));
}
template <int N>
__device__ __forceinline__ void cs_frac(int idx, float& c, float& s) {
  int i = ((idx + N / 2) & (N - 1)) - N / 2;
  float a = (float)i * (6.283185307179586f / N);
  c = __cosf(a);
  s = __sinf(a);
}
template <int N>
__device__ __forceinline__ uint32_t cfrag(int idx, int ri) {
  float c, s;
  cs_frac<N>(idx, c, s);
  return ri ? pack2(-s, c) : pack2(c, s);
}
__device__ __forceinline__ uint32_t word(const uint4& v, int e) { return e == 0 ? v.x : e == 1 ? v.y : e == 2 ? v.z : v.w; }
__device__ __forceinline__ void cdft16(const uint4 (&q)[4], const uint4 (&F)[4], uint4 (&o)[4]) {
  float acc[2][4][4];
#pragma unroll
  for (int p = 0; p < 2; p++)
#pragma unroll
    for (int v = 0; v < 4; v++) {
      acc[p][v][0] = acc[p][v][1] = acc[p][v][2] = acc[p][v][3] = 0.f;
#pragma unroll
      for (int ks = 0; ks < 2; ks++)
        mma16816(acc[p][v], word(q[2 * ks], 2 * p), word(q[2 * ks], 2 * p + 1), word(q[2 * ks + 1], 2 * p),
                 word(q[2 * ks + 1], 2 * p + 1), word(F[ks * 2 + (v >> 1)], (v & 1) * 2), word(F[ks * 2 + (v >> 1)], (v & 1) * 2 + 1));
    }
#pragma unroll
  for (int v = 0; v < 4; v++)
    o[v] = make_uint4(pack2(acc[0][v][0], acc[0][v][1]), pack2(acc[0][v][2], acc[0][v][3]),
                      pack2(acc[1][v][0], acc[1][v][1]), pack2(acc[1][v][2], acc[1][v][3]));
}
__device__ __forceinline__ void st_tag(uint4* p, const uint4& v, uint32_t tag) {
  asm volatile("{.reg .b128 r; .reg .b64 a, b; mov.b64 a, {%1,%2}; mov.b64 b, {%3,%4}; mov.b128 r, {a,b}; st.relaxed.gpu.global.b128 [%0], r;}"
               ::"l"(p), "r"((v.x & ~1u) | tag), "r"(v.y), "r"(v.z), "r"(v.w) : "memory");
}
__device__ __forceinline__ void st_tag8(void* p, uint32_t x, uint32_t y, uint32_t tag) {
  asm volatile("{.reg .b64 a; mov.b64 a, {%1,%2}; st.relaxed.gpu.global.b64 [%0], a;}" ::"l"(p), "r"((x & ~1u) | tag), "r"(y) : "memory");
}
__device__ __forceinline__ uint4 ld_b128(const uint4* p) {
  uint4 v;
  asm volatile("{.reg .b128 r; .reg .b64 a, b; ld.relaxed.gpu.global.b128 r, [%4]; mov.b128 {a,b}, r; mov.b64 {%0,%1}, a; mov.b64 {%2,%3}, b;}"
               : "=r"(v.x), "=r"(v.y), "=r"(v.z), "=r"(v.w) : "l"(p) : "memory");
  return v;
}
template <int STRIDE>
__device__ __forceinline__ void ld_tag4_issue(uint4 (&q)[4], const uint4* p) {
#pragma unroll
  for (int i = 0; i < 4; i++) q[i] = ld_b128(p + i * STRIDE);
}
template <int STRIDE, bool HALVES = false>
__device__ __forceinline__ void ld_tag4_finish(uint4 (&q)[4], const uint4* p, uint32_t tag) {
  int it = 0;
#pragma unroll 1
  while (__any_sync(0xffffffffu, ((q[0].x ^ tag) | (q[1].x ^ tag) | (q[2].x ^ tag) | (q[3].x ^ tag) |
                                  (HALVES ? (q[0].z ^ tag) | (q[1].z ^ tag) | (q[2].z ^ tag) | (q[3].z ^ tag) : 0u)) & 1u)) {
    ld_tag4_issue<STRIDE>(q, p);
    if (++it > SPIN_LIMIT) { die(); break; }
  }
#pragma unroll
  for (int i = 0; i < 4; i++) {
    asm volatile("and.b32 %0, %0, 0xfffffffe;" : "+r"(q[i].x));
    if (HALVES) q[i].z &= ~1u;
  }
}
__device__ __forceinline__ void row_stats(const uint32_t (&a)[8], const uint32_t (&b)[8], int lane, float (&sum)[2], float (&sq)[2]) {
  float da[4] = {0.f, 0.f, 0.f, 0.f}, db[4] = {0.f, 0.f, 0.f, 0.f}, ds[4] = {0.f, 0.f, 0.f, 0.f};
#pragma unroll
  for (int q = 0; q < 4; q++) {
    mma16816(ds, a[2 * q], b[2 * q], a[2 * q + 1], b[2 * q + 1], 0x3f803f80u, 0x3f803f80u);
    mma16816(da, a[2 * q], b[2 * q], a[2 * q + 1], b[2 * q + 1], a[2 * q], a[2 * q + 1]);
    mma16816(db, a[2 * q], b[2 * q], a[2 * q + 1], b[2 * q + 1], b[2 * q], b[2 * q + 1]);
  }
  const int src = (lane & 28) | (lane >> 3);
  const float qa = __shfl_sync(0xffffffffu, (lane & 4) ? da[1] : da[0], src);
  const float qb = __shfl_sync(0xffffffffu, (lane & 4) ? db[3] : db[2], src);
  float v = (lane & 2) ? ((lane & 1) ? ds[2] : ds[0]) : ((lane & 1) ? qb : qa);
  v += __shfl_xor_sync(0xffffffffu, v, 4);
  v += __shfl_xor_sync(0xffffffffu, v, 8);
  v += __shfl_xor_sync(0xffffffffu, v, 16);
  sq[0] = __shfl_sync(0xffffffffu, v, 0);
  sq[1] = __shfl_sync(0xffffffffu, v, 1);
  sum[0] = __shfl_sync(0xffffffffu, v, 2);
  sum[1] = __shfl_sync(0xffffffffu, v, 3);
}
__device__ __forceinline__ uint64_t desc64(uint32_t lo, uint32_t hi) {
  uint64_t d;
  asm("mov.b64 %0, {%1, %2};" : "=l"(d) : "r"(lo), "r"(hi));
  return d;
}
constexpr uint32_t desc_hi(uint32_t sbo, uint32_t swz) { return (sbo >> 4) | (swz << 30); }
__device__ __forceinline__ uint32_t desc_lo(uint32_t addr, uint32_t lbo) { return ((addr & 0x3FFFF) >> 4) | ((lbo >> 4) << 16); }
__device__ __forceinline__ void cp_async16(uint32_t dst, const void* src) {
  asm volatile("cp.async.cg.shared.global [%0], [%1], 16;" ::"r"(dst), "l"(src) : "memory");
}
__device__ __forceinline__ uint2 lds2(uint32_t a) {
  uint2 v;
  asm volatile("ld.shared.v2.u32 {%0,%1}, [%2];" : "=r"(v.x), "=r"(v.y) : "r"(a) : "memory");
  return v;
}
__device__ __forceinline__ uint32_t lds_u16(uint32_t a) {
  uint16_t v;
  asm volatile("ld.shared.u16 %0, [%1];" : "=h"(v) : "r"(a) : "memory");
  return v;
}
__device__ __forceinline__ void wg_fence() { asm volatile("wgmma.fence.sync.aligned;" ::: "memory"); }
__device__ __forceinline__ void wg_commit() { asm volatile("wgmma.commit_group.sync.aligned;" ::: "memory"); }
template <int N>
__device__ __forceinline__ void wg_wait() { asm volatile("wgmma.wait_group.sync.aligned %0;" ::"n"(N) : "memory"); }
__device__ __forceinline__ void bulk_load(uint32_t dst, const void* src, int bytes, uint32_t bar) {
  asm volatile("cp.async.bulk.shared::cluster.global.mbarrier::complete_tx::bytes [%0], [%1], %2, [%3];"
               ::"r"(dst), "l"(src), "r"(bytes), "r"(bar) : "memory");
}
__device__ __forceinline__ void bulk_load_mc(uint32_t dst, const void* src, int bytes, uint32_t bar) {
  asm volatile("cp.async.bulk.shared::cluster.global.mbarrier::complete_tx::bytes.multicast::cluster [%0], [%1], %2, [%3], %4;"
               ::"r"(dst), "l"(src), "r"(bytes), "r"(bar), "h"((uint16_t)3) : "memory");
}
__device__ __forceinline__ void tma3(uint32_t dst, const CUtensorMap* tm, uint32_t bar, int c0, int c1, int c2) {
  asm volatile("cp.async.bulk.tensor.3d.shared::cluster.global.mbarrier::complete_tx::bytes [%0], [%1, {%3,%4,%5}], [%2];"
               ::"r"(dst), "l"(tm), "r"(bar), "r"(c0), "r"(c1), "r"(c2) : "memory");
}
__device__ __forceinline__ void tma3_mc(uint32_t dst, const CUtensorMap* tm, uint32_t bar, int c1, int c2) {
  asm volatile("cp.async.bulk.tensor.3d.shared::cluster.global.mbarrier::complete_tx::bytes.multicast::cluster [%0], [%1, {%3,%4,%5}], [%2], %6;"
               ::"r"(dst), "l"(tm), "r"(bar), "r"(0), "r"(c1), "r"(c2), "h"((uint16_t)3) : "memory");
}
__device__ __forceinline__ void mbar_arrive_remote(uint32_t rb) {
  asm volatile("mbarrier.arrive.shared::cluster.b64 _, [%0];" ::"r"(rb) : "memory");
}
__device__ __forceinline__ uint4 ldg_ca4(const void* p) {
  uint4 v;
  asm volatile("ld.global.ca.v4.u32 {%0,%1,%2,%3}, [%4];" : "=r"(v.x), "=r"(v.y), "=r"(v.z), "=r"(v.w) : "l"(p) : "memory");
  return v;
}
__device__ __forceinline__ float u2f(uint32_t v) { return __uint_as_float(v); }
__device__ __forceinline__ void mma_a(float (&d)[4], const uint4& a, uint32_t b0, uint32_t b1) { mma16816(d, a.x, a.y, a.z, a.w, b0, b1); }
__device__ __forceinline__ uint32_t clock32() {
  uint32_t v;
  asm volatile("mov.u32 %0, %%clock;" : "=r"(v) :: "memory");
  return v;
}
__device__ __forceinline__ float swiglu(float g, float u, float r) {
  float hg = (0.5f * r) * g, th;
  asm("tanh.approx.f32 %0, %1;" : "=f"(th) : "f"(hg));
  return fmaf(hg, th, hg) * (r * u);
}
__device__ __forceinline__ uint32_t hsub2_bf16(uint32_t a, uint32_t b) {
  uint32_t r;
  asm("sub.rn.bf16x2 %0, %1, %2;" : "=r"(r) : "r"(a), "r"(b));
  return r;
}
__device__ __forceinline__ void l2_prefetch(const void* p, int bytes) {
  asm volatile("cp.async.bulk.prefetch.L2.global [%0], %1;" ::"l"(p), "r"(bytes) : "memory");
}

__device__ __forceinline__ void wgmma_n256(float (&d)[128], uint64_t da, uint64_t db, int sd = 1) {
  asm volatile("{.reg .pred p; setp.ne.b32 p, %130, 0;\n"
      "wgmma.mma_async.sync.aligned.m64n256k16.f32.bf16.bf16 {"
      "%0,%1,%2,%3,%4,%5,%6,%7,%8,%9,%10,%11,%12,%13,%14,%15,"
      "%16,%17,%18,%19,%20,%21,%22,%23,%24,%25,%26,%27,%28,%29,%30,%31,"
      "%32,%33,%34,%35,%36,%37,%38,%39,%40,%41,%42,%43,%44,%45,%46,%47,"
      "%48,%49,%50,%51,%52,%53,%54,%55,%56,%57,%58,%59,%60,%61,%62,%63,"
      "%64,%65,%66,%67,%68,%69,%70,%71,%72,%73,%74,%75,%76,%77,%78,%79,"
      "%80,%81,%82,%83,%84,%85,%86,%87,%88,%89,%90,%91,%92,%93,%94,%95,"
      "%96,%97,%98,%99,%100,%101,%102,%103,%104,%105,%106,%107,%108,%109,%110,%111,"
      "%112,%113,%114,%115,%116,%117,%118,%119,%120,%121,%122,%123,%124,%125,%126,%127"
      "}, %128, %129, p, 1, 1, 0, 1;}\n"
      : "+f"(d[0]),"+f"(d[1]),"+f"(d[2]),"+f"(d[3]),"+f"(d[4]),"+f"(d[5]),"+f"(d[6]),"+f"(d[7]),
        "+f"(d[8]),"+f"(d[9]),"+f"(d[10]),"+f"(d[11]),"+f"(d[12]),"+f"(d[13]),"+f"(d[14]),"+f"(d[15]),
        "+f"(d[16]),"+f"(d[17]),"+f"(d[18]),"+f"(d[19]),"+f"(d[20]),"+f"(d[21]),"+f"(d[22]),"+f"(d[23]),
        "+f"(d[24]),"+f"(d[25]),"+f"(d[26]),"+f"(d[27]),"+f"(d[28]),"+f"(d[29]),"+f"(d[30]),"+f"(d[31]),
        "+f"(d[32]),"+f"(d[33]),"+f"(d[34]),"+f"(d[35]),"+f"(d[36]),"+f"(d[37]),"+f"(d[38]),"+f"(d[39]),
        "+f"(d[40]),"+f"(d[41]),"+f"(d[42]),"+f"(d[43]),"+f"(d[44]),"+f"(d[45]),"+f"(d[46]),"+f"(d[47]),
        "+f"(d[48]),"+f"(d[49]),"+f"(d[50]),"+f"(d[51]),"+f"(d[52]),"+f"(d[53]),"+f"(d[54]),"+f"(d[55]),
        "+f"(d[56]),"+f"(d[57]),"+f"(d[58]),"+f"(d[59]),"+f"(d[60]),"+f"(d[61]),"+f"(d[62]),"+f"(d[63]),
        "+f"(d[64]),"+f"(d[65]),"+f"(d[66]),"+f"(d[67]),"+f"(d[68]),"+f"(d[69]),"+f"(d[70]),"+f"(d[71]),
        "+f"(d[72]),"+f"(d[73]),"+f"(d[74]),"+f"(d[75]),"+f"(d[76]),"+f"(d[77]),"+f"(d[78]),"+f"(d[79]),
        "+f"(d[80]),"+f"(d[81]),"+f"(d[82]),"+f"(d[83]),"+f"(d[84]),"+f"(d[85]),"+f"(d[86]),"+f"(d[87]),
        "+f"(d[88]),"+f"(d[89]),"+f"(d[90]),"+f"(d[91]),"+f"(d[92]),"+f"(d[93]),"+f"(d[94]),"+f"(d[95]),
        "+f"(d[96]),"+f"(d[97]),"+f"(d[98]),"+f"(d[99]),"+f"(d[100]),"+f"(d[101]),"+f"(d[102]),"+f"(d[103]),
        "+f"(d[104]),"+f"(d[105]),"+f"(d[106]),"+f"(d[107]),"+f"(d[108]),"+f"(d[109]),"+f"(d[110]),"+f"(d[111]),
        "+f"(d[112]),"+f"(d[113]),"+f"(d[114]),"+f"(d[115]),"+f"(d[116]),"+f"(d[117]),"+f"(d[118]),"+f"(d[119]),
        "+f"(d[120]),"+f"(d[121]),"+f"(d[122]),"+f"(d[123]),"+f"(d[124]),"+f"(d[125]),"+f"(d[126]),"+f"(d[127])
      : "l"(da), "l"(db), "r"(sd));
}
__device__ __forceinline__ void wgmma_n192(float (&d)[96], uint64_t da, uint64_t db) {
  asm volatile("wgmma.mma_async.sync.aligned.m64n192k16.f32.bf16.bf16 {"
      "%0,%1,%2,%3,%4,%5,%6,%7,%8,%9,%10,%11,%12,%13,%14,%15,"
      "%16,%17,%18,%19,%20,%21,%22,%23,%24,%25,%26,%27,%28,%29,%30,%31,"
      "%32,%33,%34,%35,%36,%37,%38,%39,%40,%41,%42,%43,%44,%45,%46,%47,"
      "%48,%49,%50,%51,%52,%53,%54,%55,%56,%57,%58,%59,%60,%61,%62,%63,"
      "%64,%65,%66,%67,%68,%69,%70,%71,%72,%73,%74,%75,%76,%77,%78,%79,"
      "%80,%81,%82,%83,%84,%85,%86,%87,%88,%89,%90,%91,%92,%93,%94,%95"
      "}, %96, %97, 1, 1, 1, 0, 1;\n"
      : "+f"(d[0]),"+f"(d[1]),"+f"(d[2]),"+f"(d[3]),"+f"(d[4]),"+f"(d[5]),"+f"(d[6]),"+f"(d[7]),
        "+f"(d[8]),"+f"(d[9]),"+f"(d[10]),"+f"(d[11]),"+f"(d[12]),"+f"(d[13]),"+f"(d[14]),"+f"(d[15]),
        "+f"(d[16]),"+f"(d[17]),"+f"(d[18]),"+f"(d[19]),"+f"(d[20]),"+f"(d[21]),"+f"(d[22]),"+f"(d[23]),
        "+f"(d[24]),"+f"(d[25]),"+f"(d[26]),"+f"(d[27]),"+f"(d[28]),"+f"(d[29]),"+f"(d[30]),"+f"(d[31]),
        "+f"(d[32]),"+f"(d[33]),"+f"(d[34]),"+f"(d[35]),"+f"(d[36]),"+f"(d[37]),"+f"(d[38]),"+f"(d[39]),
        "+f"(d[40]),"+f"(d[41]),"+f"(d[42]),"+f"(d[43]),"+f"(d[44]),"+f"(d[45]),"+f"(d[46]),"+f"(d[47]),
        "+f"(d[48]),"+f"(d[49]),"+f"(d[50]),"+f"(d[51]),"+f"(d[52]),"+f"(d[53]),"+f"(d[54]),"+f"(d[55]),
        "+f"(d[56]),"+f"(d[57]),"+f"(d[58]),"+f"(d[59]),"+f"(d[60]),"+f"(d[61]),"+f"(d[62]),"+f"(d[63]),
        "+f"(d[64]),"+f"(d[65]),"+f"(d[66]),"+f"(d[67]),"+f"(d[68]),"+f"(d[69]),"+f"(d[70]),"+f"(d[71]),
        "+f"(d[72]),"+f"(d[73]),"+f"(d[74]),"+f"(d[75]),"+f"(d[76]),"+f"(d[77]),"+f"(d[78]),"+f"(d[79]),
        "+f"(d[80]),"+f"(d[81]),"+f"(d[82]),"+f"(d[83]),"+f"(d[84]),"+f"(d[85]),"+f"(d[86]),"+f"(d[87]),
        "+f"(d[88]),"+f"(d[89]),"+f"(d[90]),"+f"(d[91]),"+f"(d[92]),"+f"(d[93]),"+f"(d[94]),"+f"(d[95])
      : "l"(da), "l"(db));
}
template <int SD>
__device__ __forceinline__ void wgmma_rs_n128(float (&d)[64], uint32_t a0, uint32_t a1, uint32_t a2, uint32_t a3, uint64_t db) {
  asm volatile("wgmma.mma_async.sync.aligned.m64n128k16.f32.bf16.bf16 {"
      "%0,%1,%2,%3,%4,%5,%6,%7,%8,%9,%10,%11,%12,%13,%14,%15,"
      "%16,%17,%18,%19,%20,%21,%22,%23,%24,%25,%26,%27,%28,%29,%30,%31,"
      "%32,%33,%34,%35,%36,%37,%38,%39,%40,%41,%42,%43,%44,%45,%46,%47,"
      "%48,%49,%50,%51,%52,%53,%54,%55,%56,%57,%58,%59,%60,%61,%62,%63"
      "}, {%64,%65,%66,%67}, %68, %69, 1, 1, 1;\n"
      : "+f"(d[0]),"+f"(d[1]),"+f"(d[2]),"+f"(d[3]),"+f"(d[4]),"+f"(d[5]),"+f"(d[6]),"+f"(d[7]),
        "+f"(d[8]),"+f"(d[9]),"+f"(d[10]),"+f"(d[11]),"+f"(d[12]),"+f"(d[13]),"+f"(d[14]),"+f"(d[15]),
        "+f"(d[16]),"+f"(d[17]),"+f"(d[18]),"+f"(d[19]),"+f"(d[20]),"+f"(d[21]),"+f"(d[22]),"+f"(d[23]),
        "+f"(d[24]),"+f"(d[25]),"+f"(d[26]),"+f"(d[27]),"+f"(d[28]),"+f"(d[29]),"+f"(d[30]),"+f"(d[31]),
        "+f"(d[32]),"+f"(d[33]),"+f"(d[34]),"+f"(d[35]),"+f"(d[36]),"+f"(d[37]),"+f"(d[38]),"+f"(d[39]),
        "+f"(d[40]),"+f"(d[41]),"+f"(d[42]),"+f"(d[43]),"+f"(d[44]),"+f"(d[45]),"+f"(d[46]),"+f"(d[47]),
        "+f"(d[48]),"+f"(d[49]),"+f"(d[50]),"+f"(d[51]),"+f"(d[52]),"+f"(d[53]),"+f"(d[54]),"+f"(d[55]),
        "+f"(d[56]),"+f"(d[57]),"+f"(d[58]),"+f"(d[59]),"+f"(d[60]),"+f"(d[61]),"+f"(d[62]),"+f"(d[63])
      : "r"(a0), "r"(a1), "r"(a2), "r"(a3), "l"(db), "n"(SD));
}

constexpr int C_LN = 0, C_PX = 16, C_PY = 32;
constexpr int NB_CONS = 1, NB_LN = 2, NB_LAG = 4, NB_INIT = 6, NB_RDY = 7, NB_WG = 8;
#define LAGX 3
#define LAGY 3
#define LAG2 5
constexpr int NLL = 2;
#define POLL_DELAY3 600
#define POLL_DELAY 1100
#define FILT_DELAY 1000
#define THR_B 0
#define THR_P 0
#define SPEC -1
#define WARM 4
#define HWARM 0
#define TOUCH 1
#define ALEAD 6
#define RING_SIG 1
#define PF2_SIG 1
constexpr int SM_E = 0, SM_X = 16384, SM_E2 = 32768, SM_W = 49152, SM_FC = 69632, SM_T = 73728 - T1_BYTES;
constexpr unsigned long long KORDER = 0xBA9432DC876510ull;
constexpr unsigned long long BSLOT = 0x76532107653210ull, PSLOT = 0xDCBA984DCBA984ull;
constexpr uint32_t HI128 = desc_hi(1024, 1), HI64 = desc_hi(512, 2);

struct Bars {
  uint64_t full1[32], empty1[32], full2[16], fullA[8], empty2[8], fullP[16], emptyP[8], hbar, tbar, hint[3], sig[2], sbar;
  uint32_t epoch;
};

template <int NK, bool STORE>
__device__ __forceinline__ void make_p(const float (&acc)[NK * 16], float r0, float r1, uint4 (&p)[NK], uint4* pbase, int ks0, uint32_t tag) {
#pragma unroll
  for (int j = 0; j < NK; j++) {
    uint32_t w[4];
#pragma unroll
    for (int i = 0; i < 4; i++) {
      const int a = 8 * j + 2 * i, b = a + NK * 8;
      w[i] = pack2(swiglu(acc[a], acc[b], (i & 1) ? r1 : r0), swiglu(acc[a + 1], acc[b + 1], (i & 1) ? r1 : r0));
    }
    asm volatile("" : "+r"(w[0]), "+r"(w[1]), "+r"(w[2]), "+r"(w[3]));
    p[j] = make_uint4(w[0], w[1], w[2], w[3]);
    if (STORE) st_tag(pbase + ((ks0 + j) >> 2) * 1024 + ((ks0 + j) & 3) * 32, p[j], tag);
  }
}
__device__ __forceinline__ void spin_cycles(uint32_t n) {
  const uint32_t t0 = clock32();
  while (clock32() - t0 < n) {}
}

__device__ __forceinline__ void spin_until(uint32_t t) {
  float d[4] = {0.f, 0.f, 0.f, 0.f};
  while ((int)(clock32() - t) < 0) {
    if (HWARM) asm volatile("mma.sync.aligned.m16n8k16.row.col.f32.bf16.bf16.f32 {%0,%1,%2,%3}, {%4,%4,%4,%4}, {%4,%4}, {%0,%1,%2,%3};"
                            : "+f"(d[0]), "+f"(d[1]), "+f"(d[2]), "+f"(d[3]) : "r"(t));
  }
}

__global__ void __cluster_dims__(2, 1, 1) __launch_bounds__(NTHREADS, 1)
fused_kernel(const __nv_bfloat16* __restrict__ x, const Tables* __restrict__ tab, Scratch* __restrict__ scr,
             __nv_bfloat16* __restrict__ out, const char* __restrict__ wg_raw, const char* __restrict__ wu_raw,
             const char* __restrict__ wd_raw,
             const __grid_constant__ CUtensorMap tmWR, const __grid_constant__ CUtensorMap tmWI,
             const __grid_constant__ CUtensorMap tmGX, const __grid_constant__ CUtensorMap tmUX,
             const __grid_constant__ CUtensorMap tmGY, const __grid_constant__ CUtensorMap tmUY,
             const __grid_constant__ CUtensorMap tmD) {
  extern __shared__ __align__(1024) char smem_raw[];
  const uint32_t sbase = s2u(smem_raw);
  const uint32_t sbar = sbase + 14 * SLOT, sstat = sbar + 1280;
  const int tid = threadIdx.x, lane = tid & 31;
  const int c = blockIdx.x, rk = c & 1, f = (c >> 1) & 7, rb = 2 * (c >> 4) + rk;
  const int rb2 = 2 * (c >> 4) + (f >> 2), kh = (f >> 1) & 1, nq = 2 * (f & 1) + rk;
#define BAR(field, i) (sbar + (uint32_t)offsetof(Bars, field) + 8u * (i))
#define TOFF(field) (sbase + SM_T + (uint32_t)offsetof(Tables, field) + lane * 16)

  if (tid >= 256) {
    asm volatile("setmaxnreg.dec.sync.aligned.u32 56;");
    const int warp = __shfl_sync(0xffffffffu, tid >> 5, 0);
    if (lane == 0) {
      if (warp == 8) {
        if (sbase & 1023) die();
#pragma unroll
        for (int i = 0; i < 16; i++) mbar_init(BAR(emptyP, i), i < 7 ? 16 : i < 8 ? 8 : i == 9 ? 1 + 32 * TOUCH : i < 13 ? 1 : i < 15 ? 8 : 32);
        mbar_expect(BAR(tbar, 0), T2_BYTES + 2 * 10240);
        mbar_expect(BAR(hbar, 0), 16384);
      } else if (warp == 9) {
#pragma unroll
        for (int i = 0; i < 32; i++) mbar_init(BAR(full1, i), 1);
#pragma unroll
        for (int i = 0; i < 32; i++) mbar_expect(BAR(full1, i), i < 16 ? 16384 : 12288);
      } else if (warp == 10) {
#pragma unroll
        for (int i = 0; i < 32; i++) mbar_init(BAR(empty1, i), 16);
#pragma unroll
        for (int i = 0; i < 14; i++) mbar_init(BAR(fullP, i), 1);
#pragma unroll
        for (int i = 0; i < 14; i++) mbar_expect(BAR(fullP, i), 16384);
      } else {
#pragma unroll
        for (int i = 0; i < 32; i++) mbar_init(BAR(full2, i), i < 24 ? 1 : 8);
#pragma unroll
        for (int i = 0; i < 24; i++) mbar_expect(BAR(full2, i), 16384);
      }
      asm volatile("fence.mbarrier_init.release.cluster;" ::: "memory");
    }
    if (tid == 256) {
      const int w0 = ((c >> 3) * 257 + 32 * (c & 7) + 1) & ~7;
      if (FILT_DELAY) {
        asm volatile("prefetch.tensormap [%0];" ::"l"(&tmWR) : "memory");
        asm volatile("prefetch.tensormap [%0];" ::"l"(&tmWI) : "memory");
        spin_cycles(FILT_DELAY);
      }
      tma3(sbase + SM_W, &tmWR, BAR(tbar, 0), w0, 0, 0);
      tma3(sbase + SM_W + 10240, &tmWI, BAR(tbar, 0), w0, 0, 0);
      bulk_load(sbase + SM_T + T1_BYTES, reinterpret_cast<const char*>(tab) + T1_BYTES, T2_BYTES, BAR(tbar, 0));
    }
    if (tid == 288) {
      asm volatile("prefetch.tensormap [%0];" ::"l"(rk ? &tmUX : &tmGX) : "memory");
      asm volatile("prefetch.tensormap [%0];" ::"l"(rk ? &tmUY : &tmGY) : "memory");
      asm volatile("prefetch.tensormap [%0];" ::"l"(&tmD) : "memory");
    }
    if (tid == 320) {
      const unsigned e = ld_relaxed(&scr->cnt[(C_LN + rb) * 32]) >> 3;
      asm volatile("st.shared.u32 [%0], %1;" ::"r"(BAR(epoch, 0)), "r"(e) : "memory");
    }
    __syncwarp();
    asm volatile("barrier.cluster.arrive.relaxed.aligned;" ::: "memory");
    bar_arrive(NB_RDY, 384);
    asm volatile("barrier.cluster.wait.aligned;" ::: "memory");
    bar_sync(NB_INIT, 384);
    unsigned epoch;
    asm volatile("ld.shared.u32 %0, [%1];" : "=r"(epoch) : "r"(BAR(epoch, 0)) : "memory");
    if (warp == 8) {
      if (lane == 0) {
        const int ax = (7 * f + 3 * (f & 1)) >> 1;
        const int ay = 7 * f + ((f & 1) ? 0 : 4);
        const CUtensorMap* tx = rk ? &tmUX : &tmGX;
        const CUtensorMap* ty = rk ? &tmUY : &tmGY;
        if (RING_SIG >= 0) mbar_wait(BAR(sig, RING_SIG));
        uint32_t s = 2;
#pragma unroll 1
        for (int n = 0; n < 16; n++) {
          if (n >= 6) mbar_wait(BAR(empty1, n - 6));
          tma3_mc(sbase + (8 + s) * SLOT + rk * 8192, tx, BAR(full1, n), n * 32, ax);
          if (++s == 6) s = 0;
        }
#pragma unroll 1
        for (int k = 0; k < 16; k++) {
          mbar_wait(BAR(empty1, k < 8 ? 10 + ((12 * k + 11) >> 4) : 8 + k));
          tma3_mc(sbase + 8 * SLOT + (k & 7) * 12288 + rk * 6144, ty, BAR(full1, 16 + k), k * 32, ay);
        }
      }
    } else if (warp == 9) {
      if (lane == 0) {
#pragma unroll 1
        for (int i = 0; i < 14; i++) {
          const int kblk = 14 * kh + (int)((KORDER >> (4 * i)) & 15);
          const int j = i < 7 ? i : i - 7, sl = j + (j >= 4);
          mbar_wait(i < 7 ? BAR(empty1, 17 + 2 * sl) : BAR(empty2, j));
          if (THR_B && i >= THR_B) mbar_wait(BAR(full2, i - THR_B));
          tma3(sbase + sl * SLOT, &tmD, BAR(full2, i), 0, 64 * kblk, 2 * nq);
        }
        wait_counter(&scr->cnt[(C_LN + rb2) * 32], (epoch + 1) * 8);
        asm volatile("fence.proxy.async.global;" ::: "memory");
        mbar_wait(BAR(emptyP, 7));
        bulk_load(sbase + 4 * SLOT, &scr->LN[(rb2 * 8 + 2 * nq) * 1024 + kh * 512], 8192, BAR(hbar, 0));
        bulk_load(sbase + 4 * SLOT + 8192, &scr->LN[(rb2 * 8 + 2 * nq + 1) * 1024 + kh * 512], 8192, BAR(hbar, 0));
      }
    } else if (warp == 10) {
      bar_sync(NB_LN, 288);
      if (lane == 0) {
        PROFP(0);
        red_release(&scr->cnt[(C_LN + rb) * 32]);
        PROFP(1);
        wait_counter(&scr->cnt[(C_LN + rb) * 32], (epoch + 1) * 8);
        asm volatile("fence.proxy.async.global;" ::: "memory");
        PROFP(2);
#pragma unroll 1
        for (int kb = NLL; kb < 8; kb++) {
          if (2 * kb >= ALEAD) mbar_wait(BAR(empty1, 2 * kb - ALEAD));
          bulk_load(sbase + kb * SLOT, &scr->LN[(rb * 8 + kb) * 1024], 16384, BAR(fullA, kb));
        }
#pragma unroll 1
        for (int s = 0; s < 14; s++) {
          const int kblk = 14 * kh + (int)((KORDER >> (4 * s)) & 15);
          if (s == 0 || (SPEC < 0 && (s == 8 || s == 11))) {
            if (s != 11) PROFP(3 + (s >> 2));
            mbar_wait(BAR(hint, s == 0 ? 0 : s == 8 ? 1 : 2), 0);
            if (s != 11) PROFP(4 + (s >> 2));
          }
          const int j = s < 7 ? s : s - 7;
          mbar_wait(s < 7 ? BAR(empty1, 24 + s + (s == 0) + (s >= 4)) : BAR(emptyP, j));
          if (THR_P && s >= THR_P) mbar_wait(BAR(fullP, s - THR_P));
          if (SPEC >= 0 && s == 8) mbar_wait(BAR(emptyP, SPEC & 7));
          bulk_load_mc(sbase + (j ? 7 + j : 4) * SLOT + rk * 8192, &scr->P[(rb2 * 28 + kblk) * 1024 + rk * 512], 8192, BAR(fullP, s));
        }
        PROFP(7);
      }
    } else {
      if (TOUCH) {
#pragma unroll
        for (int i = 0; i < 4 * NLL; i++)
          st_tag(&scr->LN[(rb * 8 + (i >> 2)) * 1024 + f * 128 + (i & 3) * 32 + lane], make_uint4(0, 0, epoch & 1, 0), epoch & 1);
        mbar_arrive(BAR(tbar, 0));
      }
      if (lane == 0) {
        l2_prefetch(wg_raw + (size_t)c * 5376, 5376);
        l2_prefetch(wu_raw + (size_t)c * 5376, 5376);
        mbar_wait(BAR(sig, PF2_SIG), 0);
        l2_prefetch(wg_raw + 688128 + (size_t)c * 8960, 8960);
        l2_prefetch(wu_raw + 688128 + (size_t)c * 8960, 8960);
      }
      mbar_wait(BAR(fullA, 4), 0);
      if (lane == 0) l2_prefetch(wd_raw + (size_t)c * 14336, 14336);
      {
        const uint32_t tag = (epoch + 1) & 1;
        uint4 v0, v1, v2;
        int it = 0;
        while (true) {
          v0 = ld_b128(&scr->ST[rb * 64 + lane]);
          v1 = ld_b128(&scr->ST[rb * 64 + 32 + lane]);
          v2 = ld_b128(&scr->ST[rb2 * 64 + 32 * kh + lane]);
          if (!__any_sync(0xffffffffu, ((v0.x ^ tag) | (v1.x ^ tag) | (v2.x ^ tag)) & 1u)) break;
          if (++it > SPIN_LIMIT) { die(); break; }
        }
        sts4(sstat + lane * 16, v0.x & ~1u, v0.y, v0.z, v0.w);
        sts4(sstat + 512 + lane * 16, v1.x & ~1u, v1.y, v1.z, v1.w);
        sts4(sstat + 1024 + lane * 16, v2.x & ~1u, v2.y, v2.z, v2.w);
#pragma unroll 4
        for (int i = 0; i < 32; i++)
          st_tag(&scr->XP[(c ^ 4) * 1024 + i * 32 + lane], make_uint4(0, 0, 0, 0), tag ^ 1);
        mbar_arrive(BAR(sbar, 0));
      }
      if (lane == 0) {
        mbar_wait(BAR(empty1, 17));
#pragma unroll 1
        for (int e = 0; e < (SPEC < 0 ? 3 : 1); e++) {
          const unsigned* cp = e == 0 ? &scr->cnt[(C_PX + rb2) * 32] : &scr->cnt[(C_PY + rb2) * 32 + 2 * kh + e - 1];
          if (e == 1) mbar_wait(BAR(fullP, 0), 0);
          int it = 0;
          while ((int)(ld_relaxed(cp) - (epoch + 1) * (e == 0 ? 64 : 16)) < 0)
            if (++it > SPIN_LIMIT) { die(); break; }
          mbar_arrive(BAR(hint, e));
        }
      }
    }
  } else {
    const int warp = __shfl_sync(0xffffffffu, tid >> 5, 0);
    const int g = lane >> 2, t = lane & 3;
    PROF(0);
    PROFG(14);
#pragma unroll
    for (int i = 0; i < 4; i++) {
      const int r = i >> 1, ch = (i & 1) * 32 + lane;
      cp_async16(sbase + SM_X + (2 * warp + r) * 1024 + ((ch ^ ((ch >> 3) & 1)) * 16),
                 x + (size_t)(c + 128 * (2 * warp + r)) * 512 + ch * 8);
    }
    asm volatile("cp.async.commit_group;" ::: "memory");
    asm volatile("barrier.cluster.arrive.relaxed.aligned;" ::: "memory");
    uint4 fa[4], fb[4], tw[6];
#pragma unroll
    for (int i = 0; i < 4; i++) fa[i] = ldg_ca4(&tab->fa[i][lane][0]);
#pragma unroll
    for (int i = 0; i < 6; i++) tw[i] = ldg_ca4(&tab->tw1[i][lane][0]);
#pragma unroll
    for (int i = 0; i < 4; i++) fb[i] = ldg_ca4(&tab->fb[i][lane][0]);
    uint32_t rbar;
    asm volatile("mapa.shared::cluster.u32 %0, %1, %2;" : "=r"(rbar) : "r"(sbar), "r"(rk ^ 1));
#define RBAR(field, i) (rbar + (uint32_t)offsetof(Bars, field) + 8u * (i))
    {
      const int ln = (tid >> 1) & 31, lg = ln >> 2, lt = ln & 3, i = 4 * (tid >> 6) + 2 * (tid & 1);
      const int kidx = lt + 8 * (i >> 3), nidx = 4 * ((i >> 1) & 3) + (lg >> 1);
      const uint32_t a0 = cfrag<2048>((c + 128 * kidx) * nidx, lg & 1), a1 = cfrag<2048>((c + 128 * (kidx + 4)) * nidx, lg & 1);
      const uint32_t b0 = cfrag<2048>(-(c + 128 * nidx) * kidx, lg & 1), b1 = cfrag<2048>(-(c + 128 * nidx) * (kidx + 4), lg & 1);
      asm volatile("st.shared.v2.u32 [%0], {%1,%2};" ::"r"(sbase + SM_FC + tid * 8), "r"(a0), "r"(a1) : "memory");
      asm volatile("st.shared.v2.u32 [%0], {%1,%2};" ::"r"(sbase + SM_FC + 2048 + tid * 8), "r"(b0), "r"(b1) : "memory");
    }
    asm volatile("cp.async.wait_group 0;" ::: "memory");
    __syncwarp();
    bar_arrive(NB_INIT, 384);
    PROF(13);
    uint32_t tag;
    uint4 q[4], o[4];
    {
      uint32_t v[2][8];
#pragma unroll
      for (int r = 0; r < 2; r++)
#pragma unroll
        for (int ks = 0; ks < 2; ks++) {
          const int ch = 32 * ks + 2 * (lane & 15) + (lane >> 4);
          asm volatile("ldmatrix.sync.aligned.m8n8.x4.trans.shared.b16 {%0,%1,%2,%3}, [%4];"
                       : "=r"(v[r][4 * ks]), "=r"(v[r][4 * ks + 1]), "=r"(v[r][4 * ks + 2]), "=r"(v[r][4 * ks + 3])
                       : "r"(sbase + SM_X + (2 * warp + r) * 1024 + ((ch ^ ((ch >> 3) & 1)) * 16)) : "memory");
        }
      float sum[2], sq[2];
      row_stats(v[0], v[1], lane, sum, sq);
#pragma unroll
      for (int r = 0; r < 2; r++) {
        const float mean = sum[r] * (1.f / 512.f);
        const float rs = rsqrtf(fmaxf(fmaf(-mean, mean, sq[r] * (1.f / 512.f)), 0.f) + 1e-5f);
        float acc[4][4];
#pragma unroll
        for (int u = 0; u < 4; u++) acc[u][0] = acc[u][1] = acc[u][2] = acc[u][3] = 0.f;
#pragma unroll
        for (int nt = 0; nt < 2; nt++) {
          float d[4] = {0.f, 0.f, 0.f, 0.f}, e[4] = {0.f, 0.f, 0.f, 0.f};
          mma_a(d, fa[0], v[r][2 * nt], v[r][2 * nt + 1]);
          mma_a(e, fa[2], v[r][2 * nt], v[r][2 * nt + 1]);
          mma_a(d, fa[1], v[r][4 + 2 * nt], v[r][5 + 2 * nt]);
          mma_a(e, fa[3], v[r][4 + 2 * nt], v[r][5 + 2 * nt]);
          const uint4 &ka = tw[2 * nt], &kb = tw[2 * nt + 1], &kc = tw[4 + nt];
          const uint32_t a0 = pack2(d[0] * u2f(ka.x) + d[2] * u2f(ka.y), d[1] * u2f(kb.x) + d[3] * u2f(kb.y));
          const uint32_t a2 = pack2(d[0] * u2f(ka.z) + d[2] * u2f(ka.w), d[1] * u2f(kb.z) + d[3] * u2f(kb.w));
          const uint32_t a1 = pack2(e[0] * u2f(kc.x) + e[2] * u2f(kc.y), e[1] * u2f(kc.z) + e[3] * u2f(kc.w));
          const uint32_t a3 = pack2(e[2] * u2f(kc.x) - e[0] * u2f(kc.y), e[3] * u2f(kc.z) - e[1] * u2f(kc.w));
          const uint32_t dc = pack2(fmaf(mean, -32.f, d[0]), fmaf(mean, -32.f, d[1]));
          const uint32_t h0 = g == 0 ? dc : a0, h2 = g == 0 ? 0u : a2;
          mma16816(acc[0], a0, a1, a2, a3, fb[2 * nt].x, fb[2 * nt].y);
          mma16816(acc[1], a0, a1, a2, a3, fb[2 * nt].z, fb[2 * nt].w);
          mma16816(acc[2], h0, a1, h2, a3, fb[2 * nt + 1].x, fb[2 * nt + 1].y);
          mma16816(acc[3], h0, a1, h2, a3, fb[2 * nt + 1].z, fb[2 * nt + 1].w);
        }
#pragma unroll
        for (int h = 0; h < 2; h++) {
          const int j = 2 * warp + r, m = 2 * t + h;
          sts4(sbase + SM_E + ((j * 8 + m) * 8 + (g ^ (2 * t) ^ (2 * (j & 3)))) * 16,
               pack2(acc[h][0] * rs, acc[h][1] * rs), pack2(acc[h][2] * rs, acc[h][3] * rs),
               pack2(acc[2 + h][0] * rs, acc[2 + h][1] * rs), pack2(acc[2 + h][2] * rs, acc[2 + h][3] * rs));
        }
      }
      if (tid == 0) PROFP(12);
      bar_sync(NB_RDY, 384);
      if (tid == 0) PROFP(13);
      uint4 fc[4];
#pragma unroll
      for (int i = 0; i < 4; i++) fc[i] = lds4(sbase + SM_FC + i * 512 + lane * 16);
      asm volatile("ld.shared.u32 %0, [%1];" : "=r"(tag) : "r"(BAR(epoch, 0)) : "memory");
      tag = (tag + 1) & 1;
#pragma unroll
      for (int i = 0; i < 4; i++) q[i] = lds4(sbase + SM_E + (((t + 4 * i) * 8 + warp) * 8 + (g ^ (warp & 6) ^ (2 * t))) * 16);
      cdft16(q, fc, o);
#pragma unroll
      for (int vv = 0; vv < 4; vv++) st_tag(&scr->Z1[(((4 * vv + t) * 8 + warp) * 128 + c) * 8 + g], o[vv], tag);
    }
    PROF(1);
    asm volatile("setmaxnreg.inc.sync.aligned.u32 224;");
    {
      const uint4* const zp = &scr->Z1[(c * 128 + 8 * t + warp) * 8 + g];
      const uint32_t tst = clock32();
      mbar_wait(BAR(tbar, 0), 0);
      if (tid == 0) PROFP(14);
      uint4 f2[4], g2[4];
#pragma unroll
      for (int i = 0; i < 4; i++) {
        f2[i] = lds4(TOFF(f2) + warp * 2048 + i * 512);
        g2[i] = lds4(TOFF(g2) + warp * 2048 + i * 512);
      }
      const uint4 f8 = lds4(TOFF(f8)), g8 = lds4(TOFF(g8));
      float wfr[16], wfi[16];
      {
        const float fsc = 1.f / (1 << 19);
        const float fsc3 = ((c & 7) == 7 && g == 0) ? 0.5f * fsc : fsc;
        const int gg = g == 0 ? 16 : g, wsh = (2 * (c >> 3) + 2) & 15;
#pragma unroll
        for (int i = 0; i < 16; i++) {
          const int ci = i >> 3, dd = (i >> 2) & 1, e = i & 3;
          const int kk = (e == 0 ? gg : e == 1 ? g + 8 : e == 2 ? 32 - g : 24 - g) - 1;
          const uint32_t a = sbase + SM_W + ((2 * warp + ci) * 8 + t + 4 * dd) * 80 + wsh + 2 * kk;
          wfr[i] = bf_lo(lds_u16(a)) * (e == 2 ? fsc3 : fsc);
          wfi[i] = bf_lo(lds_u16(a + 10240)) * (e == 2 ? fsc3 : fsc);
        }
      }
      asm volatile("barrier.cluster.wait.aligned;" ::: "memory");
      PROF(2);
      spin_until(tst + POLL_DELAY);
      ld_tag4_issue<256>(q, zp);
      ld_tag4_finish<256>(q, zp, tag);
      if (tid == 0) PROFP(30);
      if (lane == 0) mbar_arrive(BAR(sig, 0));
      cdft16(q, f2, o);
      const uint32_t e2 = sbase + SM_E2;
#pragma unroll
      for (int vv = 0; vv < 4; vv++)
        sts4(e2 + ((warp * 16 + 4 * vv + t) * 8 + (g ^ (2 * t) ^ (2 * (warp & 3)))) * 16, o[vv].x, o[vv].y, o[vv].z, o[vv].w);
      bar_sync(NB_CONS, 256);
#pragma unroll
      for (int ci = 0; ci < 2; ci++) {
        const int cc = 2 * warp + ci;
        uint32_t ad[2];
        uint4 u[2];
#pragma unroll
        for (int hh = 0; hh < 2; hh++) {
          ad[hh] = e2 + (((t + 4 * hh) * 16 + cc) * 8 + (g ^ (2 * (cc & 3)) ^ (2 * t))) * 16;
          u[hh] = lds4(ad[hh]);
        }
        uint32_t res[2][4];
#pragma unroll
        for (int p = 0; p < 2; p++) {
          uint32_t y[2][2];
#pragma unroll
          for (int vv = 0; vv < 2; vv++) {
            float d[4] = {0.f, 0.f, 0.f, 0.f};
            mma16816(d, word(u[0], 2 * p), word(u[0], 2 * p + 1), word(u[1], 2 * p), word(u[1], 2 * p + 1), word(f8, 2 * vv), word(f8, 2 * vv + 1));
#pragma unroll
            for (int rr = 0; rr < 2; rr++) {
              const float fr = wfr[ci * 8 + vv * 4 + 2 * p + rr], fi = wfi[ci * 8 + vv * 4 + 2 * p + rr];
              y[vv][rr] = pack2(d[2 * rr] * fr - d[2 * rr + 1] * fi, d[2 * rr] * fi + d[2 * rr + 1] * fr);
            }
          }
#pragma unroll
          for (int vv = 0; vv < 2; vv++) {
            float d[4] = {0.f, 0.f, 0.f, 0.f};
            mma16816(d, y[0][0], y[0][1], y[1][0], y[1][1], word(g8, 2 * vv), word(g8, 2 * vv + 1));
            res[vv][2 * p] = pack2(d[0], d[1]);
            res[vv][2 * p + 1] = pack2(d[2], d[3]);
          }
        }
#pragma unroll
        for (int vv = 0; vv < 2; vv++) sts4(ad[vv], res[vv][0], res[vv][1], res[vv][2], res[vv][3]);
      }
      bar_sync(NB_CONS, 256);
#pragma unroll
      for (int i = 0; i < 4; i++) q[i] = lds4(e2 + ((warp * 16 + 4 * i + t) * 8 + (g ^ (2 * t) ^ (2 * (warp & 3)))) * 16);
      cdft16(q, g2, o);
#pragma unroll
      for (int vv = 0; vv < 4; vv++) st_tag(&scr->Z2[((8 * (4 * vv + t) + warp) * 128 + c) * 8 + g], o[vv], tag);
    }
    PROF(3);
    {
      const uint4* const zp = &scr->Z2[((c * 16 + t) * 8 + warp) * 8 + g];
      const uint32_t tst = clock32();
      uint4 gb[4], ga[4], gc[4], tw[4];
      uint2 xr[2][4];
#pragma unroll
      for (int i = 0; i < 4; i++) {
        gc[i] = lds4(sbase + SM_FC + 2048 + i * 512 + lane * 16);
        gb[i] = lds4(TOFF(gb) + i * 512);
        ga[i] = lds4(TOFF(ga) + i * 512);
        tw[i] = lds4(TOFF(tw3) + i * 512);
        const int ch = 2 * (g + 8 * i) + (t >> 1);
#pragma unroll
        for (int r = 0; r < 2; r++) xr[r][i] = lds2(sbase + SM_X + (2 * warp + r) * 1024 + ((ch ^ ((ch >> 3) & 1)) * 16) + (t & 1) * 8);
      }
      PROF(4);
      spin_until(tst + POLL_DELAY);
      ld_tag4_issue<256>(q, zp);
      ld_tag4_finish<256>(q, zp, tag);
      if (tid == 0) PROFP(31);
      if (lane == 0) mbar_arrive(BAR(sig, 1));
      cdft16(q, gc, o);
#pragma unroll
      for (int vv = 0; vv < 4; vv++)
        sts4(sbase + SM_E + (((4 * vv + t) * 8 + warp) * 8 + (g ^ (warp & 6) ^ (2 * t))) * 16, o[vv].x, o[vv].y, o[vv].z, o[vv].w);
      if (tid == 0) PROFP(8);
      bar_sync(NB_CONS, 256);
      if (tid == 0) PROFP(9);
      uint32_t hv[2][8];
      const float mk = t == 0 ? 0.f : 1.f;
#pragma unroll
      for (int r = 0; r < 2; r++) {
        const int j = 2 * warp + r;
        uint4 u[2];
#pragma unroll
        for (int h = 0; h < 2; h++) u[h] = lds4(sbase + SM_E + ((j * 8 + 2 * t + h) * 8 + (g ^ (2 * t) ^ (2 * (j & 3)))) * 16);
        float y[2][2][4];
#pragma unroll
        for (int i = 0; i < 2; i++) {
          float lo[4] = {0.f, 0.f, 0.f, 0.f}, hi[4] = {0.f, 0.f, 0.f, 0.f}, e[4] = {0.f, 0.f, 0.f, 0.f};
          mma_a(lo, gb[2 * i], u[0].x, u[1].x);
          mma_a(hi, gb[2 * i + 1], u[0].z, u[1].z);
          mma_a(e, gb[2 * i], u[0].y, u[1].y);
          mma_a(e, gb[2 * i + 1], u[0].w, u[1].w);
          const uint4 &ka = tw[2 * i], &kb = tw[2 * i + 1];
          const float tr0 = fmaf(hi[0], mk, lo[0]), ti0 = fmaf(hi[2], mk, lo[2]);
          const float tr1 = lo[1] + hi[1], ti1 = lo[3] + hi[3];
          const float vr0 = tr0 * u2f(ka.x) - ti0 * u2f(ka.y), vi0 = tr0 * u2f(ka.y) + ti0 * u2f(ka.x);
          const float vr1 = tr1 * u2f(ka.z) - ti1 * u2f(ka.w), vi1 = tr1 * u2f(ka.w) + ti1 * u2f(ka.z);
          const uint32_t b0 = pack2(t == 0 ? hi[0] : vr0, vr1), b1 = pack2(t == 0 ? vr0 : vi0, vi1);
          const uint32_t b2 = pack2(e[0] * u2f(kb.x) - e[2] * u2f(kb.y), e[1] * u2f(kb.z) - e[3] * u2f(kb.w));
          const uint32_t b3 = pack2(e[0] * u2f(kb.y) + e[2] * u2f(kb.x), e[1] * u2f(kb.w) + e[3] * u2f(kb.z));
#pragma unroll
          for (int mt = 0; mt < 2; mt++) {
            y[mt][i][0] = y[mt][i][1] = y[mt][i][2] = y[mt][i][3] = 0.f;
            mma_a(y[mt][i], ga[2 * mt], b0, b1);
            mma_a(y[mt][i], ga[2 * mt + 1], b2, b3);
          }
        }
#pragma unroll
        for (int i = 0; i < 4; i++) {
          hv[r][2 * i] = hadd2_bf16(xr[r][i].x, pack2(y[i >> 1][0][2 * (i & 1)], y[i >> 1][0][2 * (i & 1) + 1]));
          hv[r][2 * i + 1] = hadd2_bf16(xr[r][i].y, pack2(y[i >> 1][1][2 * (i & 1)], y[i >> 1][1][2 * (i & 1) + 1]));
        }
      }
      if (tid == 0 && hv[0][0] != 0x12345 && hv[1][7] != 0x12345) PROFP(10);
      float ds[4] = {0.f, 0.f, 0.f, 0.f};
#pragma unroll
      for (int q4 = 0; q4 < 4; q4++) mma16816(ds, hv[0][2 * q4], hv[1][2 * q4], hv[0][2 * q4 + 1], hv[1][2 * q4 + 1], 0x3f803f80u, 0x3f803f80u);
#pragma unroll
      for (int o2 = 4; o2 <= 16; o2 <<= 1) {
        ds[0] += __shfl_xor_sync(0xffffffffu, ds[0], o2);
        ds[2] += __shfl_xor_sync(0xffffffffu, ds[2], o2);
      }
      uint32_t mb[2];
#pragma unroll
      for (int r = 0; r < 2; r++) mb[r] = pack2(ds[2 * r] * (1.f / 512.f), ds[2 * r] * (1.f / 512.f));
#pragma unroll
      for (int i = 0; i < 4; i++)
#pragma unroll
        for (int r = 0; r < 2; r++) {
          const int row = 16 * f + 2 * warp + r;
          hv[r][2 * i] = hsub2_bf16(hv[r][2 * i], mb[r]);
          hv[r][2 * i + 1] = hsub2_bf16(hv[r][2 * i + 1], mb[r]);
          st_tag8(reinterpret_cast<uint2*>(&scr->LN[(rb * 8 + 2 * i + (g >> 2)) * 1024 + row * 8 + ((2 * (g & 3) + (t >> 1)) ^ (row & 7))]) + (t & 1),
                  hv[r][2 * i], hv[r][2 * i + 1], i == 0 ? tag : (hv[r][2 * i] & 1u));
        }
      if (tid == 0) PROFP(11);
      bar_arrive(NB_LN, 288);
      float sum[2], sq[2], rstd[2];
      row_stats(hv[0], hv[1], lane, sum, sq);
#pragma unroll
      for (int r = 0; r < 2; r++) {
        const float m = sum[r] * (1.f / 512.f);
        rstd[r] = rsqrtf(fmaxf(fmaf(-m, m, sq[r] * (1.f / 512.f)), 0.f) + 1e-5f);
      }
      if (lane == 0)
        st_tag(&scr->ST[rb * 64 + 8 * f + warp], make_uint4(mb[0] << 16, __float_as_uint(rstd[0]), mb[1] << 16, __float_as_uint(rstd[1])), tag);
    }
    PROF(5);
    const int wgi = warp >> 2, wq = warp & 3;
    uint4* const pbase = &scr->P[rb * 28 * 1024 + warp * 128 + lane];
    const uint32_t a_lo0 = desc_lo(sbase + wgi * 8192, 16);
    const uint32_t ebar = lane == 0 ? BAR(empty1, 0) : RBAR(empty1, 0);
    float r0, r1;
    uint4 px[8], py[6];
    const int rh = wgi ^ kh ^ 1;
    const uint4* const psrc = &scr->P[(rb2 * 28 + 14 * kh) * 1024 + (4 * rh + wq) * 128 + lane];
    {
      float acc[128];
#pragma unroll
      for (int i = 0; i < 128; i++) acc[i] = 0.f;
      const uint32_t b_lo0 = desc_lo(sbase + 8 * SLOT, 4096);
      const uint32_t t3 = clock32();
      if (WARM) {
        wg_fence();
#pragma unroll
        for (int i = 0; i < WARM; i++) wgmma_n256(acc, desc64(a_lo0 + 6 * 1024, HI128), desc64(b_lo0, HI128));
        wg_commit();
      }
      const uint4* const ap = &scr->LN[rb * 8 * 1024 + wgi * 512 + (tid & 127)];
      uint4 av[NLL][4];
      while (clock32() - t3 < POLL_DELAY3) {}
#pragma unroll
      for (int kb = 0; kb < NLL; kb++) ld_tag4_issue<128>(av[kb], ap + kb * 1024);
      bar_sync(NB_CONS, 256);
      uint32_t slot = 2;
      auto stage_x = [&](int kb, int hh) {
        if (LAGX && hh == ((16 - LAGX) & 1) && kb == ((16 - LAGX) >> 1) && wgi == 1) bar_sync(NB_LAG, 256);
        mbar_wait(BAR(full1, 2 * kb + hh));
        const uint32_t al = a_lo0 + kb * 1024 + hh * 4, bl = b_lo0 + slot * 1024;
        wg_fence();
        wgmma_n256(acc, desc64(al, HI128), desc64(bl, HI128), (kb | hh) != 0);
        wgmma_n256(acc, desc64(al + 2, HI128), desc64(bl + 128, HI128));
        wg_commit();
        if (LAGX && hh == 1 && kb == 7 && wgi == 0) bar_arrive(NB_LAG, 256);
        wg_wait<1>();
        if ((kb | hh) != 0 && lane < 2) mbar_arrive_remote(ebar + 8 * (2 * kb + hh - 1));
        if (++slot == 6) slot = 0;
      };
#pragma unroll
      for (int kb = 0; kb < NLL; kb++) {
        ld_tag4_finish<128, true>(av[kb], ap + kb * 1024, tag);
#pragma unroll
        for (int i = 0; i < 4; i++)
          sts4(sbase + kb * SLOT + wgi * 8192 + ((tid & 127) + 128 * i) * 16, av[kb][i].x, av[kb][i].y, av[kb][i].z, av[kb][i].w);
        asm volatile("fence.proxy.async.shared::cta;" ::: "memory");
        bar_sync(NB_WG + wgi, 128);
        if (kb > 0) stage_x(kb - 1, 1);
        if (kb == 0) PROF(6);
        stage_x(kb, 0);
      }
      stage_x(NLL - 1, 1);
#pragma unroll 1
      for (int kb = NLL; kb < 8; kb++) {
        mbar_wait(BAR(fullA, kb));
        stage_x(kb, 0);
        stage_x(kb, 1);
      }
      mbar_wait(BAR(sbar, 0), 0);
      r0 = __uint_as_float(lds2(sstat + (16 * warp + g) * 8).y);
      r1 = __uint_as_float(lds2(sstat + (16 * warp + g + 8) * 8).y);
      wg_wait<0>();
      if (lane < 2) mbar_arrive_remote(ebar + 8 * 15);
      PROF(7);
      make_p<8, false>(acc, r0, r1, px, pbase, 0, tag);
    }
    PROF(8);
    {
      float acc[96];
#pragma unroll
      for (int i = 0; i < 96; i++) acc[i] = 0.f;
      const uint32_t b_lo0 = desc_lo(sbase + 8 * SLOT, 2048);
      uint4* const pdst = pbase + ((7 * f + 3 * (f & 1)) >> 1) * 1024;
      auto stage_y = [&](int k) {
        if (LAGY && k == 16 - LAGY && wgi == 1) bar_sync(NB_LAG, 256);
        mbar_wait(BAR(full1, 16 + k));
        const uint32_t al = a_lo0 + (k >> 1) * 1024 + (k & 1) * 4, bl = b_lo0 + (k & 7) * 768;
        wg_fence();
        wgmma_n192(acc, desc64(al, HI128), desc64(bl, HI64));
        wgmma_n192(acc, desc64(al + 2, HI128), desc64(bl + 64, HI64));
        wg_commit();
      };
#pragma unroll
      for (int k = 0; k < 4; k++) {
        stage_y(k);
        st_tag(pdst + (k >> 1) * 1024 + (k & 1) * 64, px[2 * k], tag);
        st_tag(pdst + (k >> 1) * 1024 + (k & 1) * 64 + 32, px[2 * k + 1], tag);
        if (k == 3 && lane == 0) red_relaxed(&scr->cnt[(C_PX + rb) * 32]);
        wg_wait<1>();
        if (k != 0 && lane < 2) mbar_arrive_remote(ebar + 8 * (15 + k));
      }
#pragma unroll 1
      for (int k = 4; k < 16; k++) {
        stage_y(k);
        if (LAGY && k == 15 && wgi == 0) bar_arrive(NB_LAG, 256);
        wg_wait<1>();
        if (lane < 2) mbar_arrive_remote(ebar + 8 * (15 + k));
      }
      wg_wait<0>();
      if (lane < 2) mbar_arrive_remote(ebar + 8 * 31);
      PROF(9);
      make_p<6, true>(acc, r0, r1, py, pbase, 14 * f + ((f & 1) ? 0 : 8), tag);
      if (lane == 0) red_relaxed(&scr->cnt[(C_PY + rb) * 32 + (f >> 1)]);
    }
    PROF(10);
    {
      float acc[64];
      const uint32_t b2_lo0 = desc_lo(sbase, 8192);
      const uint32_t pa0 = sbase + (4 * rh + wq) * 2048;
      const uint32_t pbar = ebar + (uint32_t)(offsetof(Bars, emptyP) - offsetof(Bars, empty1));
      uint4 pf[3][4];
      uint32_t rdy = 0;
      mbar_wait(BAR(fullP, 0));
#pragma unroll
      for (int kk = 0; kk < 4; kk++) pf[0][kk] = lds4(pa0 + 4 * SLOT + kk * 512 + lane * 16);
#pragma unroll
      for (int s = 0; s < 14; s++) {
        uint4 (&a)[4] = pf[s % 3];
        ld_tag4_finish<32>(a, psrc + (int)((KORDER >> (4 * s)) & 15) * 1024, tag);
        if (s < 8 && lane < (s < 7 ? 2 : 1)) mbar_arrive_remote(pbar + 8 * s);
        if (s >= 2) {
          wg_wait<1>();
          if (s <= 8 && lane == 0) mbar_arrive(BAR(empty2, s - 2));
        }
        if (!rdy) {
          if (s < 13) mbar_wait(BAR(fullP, s + 1));
          mbar_wait(BAR(full2, s));
        }
        if (tid == 0) PROFP(16 + s);
        if (s == 14 - LAG2 && wgi == 1) {
          const float m0 = __uint_as_float(lds2(sstat + 1024 + (16 * wq + g) * 8).x);
          const float m1 = __uint_as_float(lds2(sstat + 1024 + (16 * wq + g + 8) * 8).x);
          const uint32_t hb = sbase + 4 * SLOT + (16 * wq + (lane & 15)) * 128;
          wg_wait<0>();
          mbar_wait(BAR(hbar, 0));
#pragma unroll
          for (int i = 0; i < 8; i++) {
            uint32_t h[4];
            asm volatile("ldmatrix.sync.aligned.m8n8.x4.shared.b16 {%0,%1,%2,%3}, [%4];"
                         : "=r"(h[0]), "=r"(h[1]), "=r"(h[2]), "=r"(h[3])
                         : "r"(hb + (i >> 2) * 8192 + (((2 * (i & 3) + (lane >> 4)) ^ (lane & 7)) * 16)) : "memory");
            const uint32_t mk = ((t & 1) == 0 && nq == 0) ? ~1u : ~0u;
#pragma unroll
            for (int e = 0; e < 4; e++) {
              acc[8 * i + 2 * e] += bf_lo(h[e] & mk) + ((e & 1) ? m1 : m0);
              acc[8 * i + 2 * e + 1] += __uint_as_float(h[e] & 0xffff0000u) + ((e & 1) ? m1 : m0);
            }
          }
          bar_sync(NB_LAG, 256);
        }
        const uint32_t bl = b2_lo0 + (uint32_t)((BSLOT >> (4 * s)) & 15) * 1024;
        wg_fence();
        if (s < 13) {
#pragma unroll
          for (int kk = 0; kk < 4; kk++)
            pf[(s + 1) % 3][kk] = lds4(pa0 + (uint32_t)((PSLOT >> (4 * (s + 1))) & 15) * SLOT + kk * 512 + lane * 16);
          rdy = mbar_test(BAR(full2, s + 1));
          if (s < 12) rdy &= mbar_test(BAR(fullP, s + 2));
        }
        if (s == 0) wgmma_rs_n128<0>(acc, a[0].x, a[0].y, a[0].z, a[0].w, desc64(bl, HI128));
        else wgmma_rs_n128<1>(acc, a[0].x, a[0].y, a[0].z, a[0].w, desc64(bl, HI128));
#pragma unroll
        for (int kk = 1; kk < 4; kk++) wgmma_rs_n128<1>(acc, a[kk].x, a[kk].y, a[kk].z, a[kk].w, desc64(bl + kk * 128, HI128));
        wg_commit();
      }
      if (wgi == 0) {
        bar_arrive(NB_LAG, 256);
        uint4* const dst = &scr->XP[(c ^ 4) * 1024 + tid];
        wg_wait<0>();
        PROF(11);
#pragma unroll
        for (int i = 0; i < 8; i++)
          st_tag(dst + i * 128, make_uint4(pack2(acc[8 * i], acc[8 * i + 1]), pack2(acc[8 * i + 2], acc[8 * i + 3]),
                                           pack2(acc[8 * i + 4], acc[8 * i + 5]), pack2(acc[8 * i + 6], acc[8 * i + 7])), tag);
      } else {
        uint4 pv[2][4];
        const uint4* const xsrc = &scr->XP[c * 1024 + (tid & 127)];
        ld_tag4_issue<128>(pv[0], xsrc);
        ld_tag4_issue<128>(pv[1], xsrc + 512);
        wg_wait<0>();
        PROF(11);
        uint32_t w[32];
#pragma unroll
        for (int i = 0; i < 32; i++) w[i] = pack2(acc[2 * i], acc[2 * i + 1]);
        ld_tag4_finish<128>(pv[0], xsrc, tag);
        ld_tag4_finish<128>(pv[1], xsrc + 512, tag);
#pragma unroll
        for (int i = 0; i < 8; i++) {
          const uint4& p = pv[i >> 2][i & 3];
          asm volatile("stmatrix.sync.aligned.m8n8.x4.shared.b16 [%0], {%1,%2,%3,%4};"
                       ::"r"(pa0 + (9 + ((lane >> 3) & 1)) * SLOT + (lane & 7) * 256 + (((2 * i + (lane >> 4)) ^ (lane & 7)) * 16)),
                         "r"(hadd2_bf16(w[4 * i], p.x)), "r"(hadd2_bf16(w[4 * i + 1], p.y)), "r"(hadd2_bf16(w[4 * i + 2], p.z)),
                         "r"(hadd2_bf16(w[4 * i + 3], p.w)) : "memory");
        }
        __syncwarp();
        uint4* const dst = reinterpret_cast<uint4*>(out) + (16 * (c >> 4) + 2 * (4 * rh + wq) + (rb2 & 1) + 128 * (lane >> 4)) * 64 + nq * 16 + (lane & 15);
#pragma unroll
        for (int i = 0; i < 8; i++) {
          const int r = 2 * (i & 3) + (lane >> 4);
          dst[i * 256 * 64] = lds4(pa0 + (9 + (i >> 2)) * SLOT + r * 256 + (((lane & 15) ^ r) * 16));
        }
      }
      PROF(12);
      PROFG(15);
    }
  }
#undef BAR
#undef TOFF
#undef RBAR
}

typedef CUresult (*EncodeFn)(CUtensorMap*, CUtensorMapDataType, cuuint32_t, void*, const cuuint64_t*, const cuuint64_t*,
                             const cuuint32_t*, const cuuint32_t*, CUtensorMapInterleave, CUtensorMapSwizzle,
                             CUtensorMapL2promotion, CUtensorMapFloatOOBfill);

}

extern "C" void kernel_launch(void* const* d_in, const int* in_sizes, int n_in, void* d_out, int out_size) {
  (void)in_sizes; (void)n_in; (void)out_size;
  static EncodeFn encode = nullptr;
  static void *tab = nullptr, *scr = nullptr;
  if (!encode) {
    void* fn = nullptr;
    cudaDriverEntryPointQueryResult qr;
    cudaGetDriverEntryPoint("cuTensorMapEncodeTiled", &fn, cudaEnableDefault, &qr);
    encode = (EncodeFn)fn;
    cudaGetSymbolAddress(&tab, g_tab);
    cudaGetSymbolAddress(&scr, g_scr);
    cudaFuncSetAttribute(fused_kernel, cudaFuncAttributeMaxDynamicSharedMemorySize, SMEM_BYTES);
  }
  CUtensorMap tmGX, tmUX, tmGY, tmUY, tmD, tmWR, tmWI;
  const cuuint32_t es[5] = {1, 1, 1, 1, 1};
  auto enc = [&](CUtensorMap* m, void* p, int rank, const cuuint64_t* gd, const cuuint64_t* gs, const cuuint32_t* bd,
                 CUtensorMapSwizzle sw, CUtensorMapL2promotion pr) {
    encode(m, CU_TENSOR_MAP_DATA_TYPE_BFLOAT16, rank, p, gd, gs, bd, es, CU_TENSOR_MAP_INTERLEAVE_NONE, sw, pr,
           CU_TENSOR_MAP_FLOAT_OOB_FILL_NONE);
  };
  {
    const cuuint64_t gd[3] = {64, 512, 28}, gs[2] = {3584, 128};
    const cuuint32_t bd[3] = {64, 32, 2};
    enc(&tmGX, d_in[4], 3, gd, gs, bd, CU_TENSOR_MAP_SWIZZLE_128B, CU_TENSOR_MAP_L2_PROMOTION_L2_256B);
    enc(&tmUX, d_in[5], 3, gd, gs, bd, CU_TENSOR_MAP_SWIZZLE_128B, CU_TENSOR_MAP_L2_PROMOTION_L2_256B);
  }
  {
    const cuuint64_t gd[3] = {32, 512, 56}, gs[2] = {3584, 64};
    const cuuint32_t bd[3] = {32, 32, 3};
    enc(&tmGY, d_in[4], 3, gd, gs, bd, CU_TENSOR_MAP_SWIZZLE_64B, CU_TENSOR_MAP_L2_PROMOTION_L2_128B);
    enc(&tmUY, d_in[5], 3, gd, gs, bd, CU_TENSOR_MAP_SWIZZLE_64B, CU_TENSOR_MAP_L2_PROMOTION_L2_128B);
  }
  {
    const cuuint64_t gd[3] = {64, 1792, 8}, gs[2] = {1024, 128};
    const cuuint32_t bd[3] = {64, 64, 2};
    enc(&tmD, d_in[6], 3, gd, gs, bd, CU_TENSOR_MAP_SWIZZLE_128B, CU_TENSOR_MAP_L2_PROMOTION_L2_256B);
  }
  {
    const cuuint64_t gd[3] = {4112, 8, 16}, gs[2] = {16 * 8224, 8224};
    const cuuint32_t bd[3] = {40, 8, 16};
    enc(&tmWR, d_in[1], 3, gd, gs, bd, CU_TENSOR_MAP_SWIZZLE_NONE, CU_TENSOR_MAP_L2_PROMOTION_NONE);
    enc(&tmWI, d_in[2], 3, gd, gs, bd, CU_TENSOR_MAP_SWIZZLE_NONE, CU_TENSOR_MAP_L2_PROMOTION_NONE);
  }
  fused_kernel<<<NCTA, NTHREADS, SMEM_BYTES>>>((const __nv_bfloat16*)d_in[0], (const Tables*)tab, (Scratch*)scr,
                                               (__nv_bfloat16*)d_out, (const char*)d_in[4], (const char*)d_in[5],
                                               (const char*)d_in[6], tmWR, tmWI, tmGX, tmUX, tmGY, tmUY, tmD);
}
```

```cpp
#include <cuda_runtime.h>
#include <cuda_bf16.h>
#include <cuda.h>
#include <stdint.h>

namespace {

constexpr int NCTA = 128;
constexpr int NTHREADS = 384;
constexpr int SLOT = 16384;
constexpr int SMEM_BYTES = 14 * SLOT + 3072;
constexpr int SPIN_LIMIT = 1 << 22;

struct Scratch {
  uint4 Z1[128 * 1024];
  uint4 Z2[128 * 1024];
  uint4 LN[16 * 8 * 1024];
  uint4 P[16 * 28 * 1024];
  uint4 XP[128 * 1024];
  uint4 ST[1024];
  unsigned cnt[64 * 32];
};
__device__ __align__(1024) Scratch g_scr;
#define PROF(i)
#define PROFP(i)
#define PROFG(i)

constexpr double ccos(int i, int n) {
  i &= n - 1;
  if (i > n / 2) i = n - i;
  if (4 * i == n) return 0.0;
  const bool neg = 4 * i > n;
  if (neg) i = n / 2 - i;
  const double a = 6.283185307179586476925 * i / n, a2 = a * a;
  double term = 1.0, sum = 1.0;
  for (int k = 1; k < 14; k++) { term *= -a2 / ((2 * k - 1) * (2 * k)); sum += term; }
  return neg ? -sum : sum;
}
constexpr double csin(int i, int n) { return ccos(i - n / 4, n); }
constexpr unsigned fbits(double v, int mant) {
  if (v == 0.0) return 0;
  const unsigned sg = v < 0 ? 1u : 0u;
  if (v < 0) v = -v;
  int e = 127;
  while (v < 1.0) { v *= 2.0; e--; }
  const unsigned m = (unsigned)((v - 1.0) * (double)(1u << mant) + 0.5);
  return (sg << (8 + mant)) + ((unsigned)e << mant) + m;
}
constexpr unsigned pkb(double lo, double hi) { return fbits(lo, 7) | (fbits(hi, 7) << 16); }
constexpr double fa_elem(int mt, int r, int n1) {
  const int k1 = 8 * mt + (r & 7);
  return r < 8 ? ccos(k1 * n1, 32) : k1 == 0 ? ccos(16 * n1, 32) : -csin(k1 * n1, 32);
}
constexpr unsigned cfrag_c(int idx, int n, int ri, double s = 1.0) {
  return ri ? pkb(-s * csin(idx, n), s * ccos(idx, n)) : pkb(s * ccos(idx, n), s * csin(idx, n));
}
struct Tables {
  unsigned fa[4][32][4];
  unsigned fb[4][32][4];
  unsigned tw1[6][32][4];
  unsigned f2[8][4][32][4];
  unsigned g2[8][4][32][4];
  unsigned gb[4][32][4];
  unsigned ga[4][32][4];
  unsigned tw3[4][32][4];
  unsigned f8[32][4], g8[32][4];
};
constexpr int T1_BYTES = 7168, T2_BYTES = 39936;
static_assert(sizeof(Tables) == T1_BYTES + T2_BYTES, "table size");
constexpr Tables make_tables() {
  Tables T = {};
  for (int l = 0; l < 32; l++) {
    const int g = l >> 2, t = l & 3;
    for (int a = 0; a < 2; a++)
      for (int b = 0; b < 2; b++) {
        for (int r = 0; r < 4; r++) {
          const int row = g + 8 * (r & 1), col = 2 * t + 8 * (r >> 1);
          T.fa[2 * a + b][l][r] = pkb(fa_elem(a, row, 16 * b + col), fa_elem(a, row, 16 * b + col + 1));
          T.ga[2 * a + b][l][r] = pkb(fa_elem(b, col, 16 * a + row), fa_elem(b, col + 1, 16 * a + row));
        }
        const double sg = b ? -1.0 : 1.0;
        for (int h = 0; h < 2; h++) {
          const int ri = g & 1, m = 2 * (g >> 1) + h, k2 = b ? 15 - m : m;
          const int pa = (8 * a + 2 * t) * k2, pb = (8 * a + 2 * t + 1) * k2;
          T.fb[2 * a + b][l][2 * h] = ri == 0 ? pkb(ccos(pa, 16), ccos(pb, 16)) : pkb(-sg * csin(pa, 16), -sg * csin(pb, 16));
          T.fb[2 * a + b][l][2 * h + 1] = ri == 0 ? pkb(csin(pa, 16), csin(pb, 16)) : pkb(sg * ccos(pa, 16), sg * ccos(pb, 16));
        }
        const int n2 = 4 * (g >> 1) + 2 * a + (g & 1);
        for (int h = 0; h < 2; h++) {
          const int p = n2 * (b ? 15 - 2 * t - h : 2 * t + h);
          T.gb[2 * a + b][l][2 * h] = pkb(ccos(p, 16), -sg * csin(p, 16));
          T.gb[2 * a + b][l][2 * h + 1] = pkb(csin(p, 16), sg * ccos(p, 16));
          const int k1 = 8 * b + 2 * t + h, q = n2 * (k1 == 0 ? 16 : k1);
          T.tw3[2 * a + b][l][2 * h] = fbits(ccos(q, 512), 23);
          T.tw3[2 * a + b][l][2 * h + 1] = fbits(csin(q, 512), 23);
        }
        const int p = (8 * a + 2 * t + b) * (g == 0 ? 16 : g);
        T.tw1[2 * a + b][l][0] = fbits(g == 0 ? 0.0 : ccos(p, 512), 23);
        T.tw1[2 * a + b][l][1] = fbits(g == 0 ? ccos(p, 512) : csin(p, 512), 23);
        T.tw1[2 * a + b][l][2] = fbits(g == 0 ? 0.0 : -csin(p, 512), 23);
        T.tw1[2 * a + b][l][3] = fbits(g == 0 ? -csin(p, 512) : ccos(p, 512), 23);
        T.tw1[4 + a][l][2 * b] = fbits(ccos((8 * a + 2 * t + b) * (g + 8), 512), 23);
        T.tw1[4 + a][l][2 * b + 1] = fbits(csin((8 * a + 2 * t + b) * (g + 8), 512), 23);
      }
    for (int i = 0; i < 4; i++) {
      const int p8 = (t + 4 * (i & 1)) * (4 * (i >> 1) + (g >> 1));
      T.f8[l][i] = cfrag_c(p8, 8, g & 1);
      T.g8[l][i] = cfrag_c(-p8, 8, g & 1, 1.0 / (1 << 19));
    }
    for (int w = 0; w < 8; w++)
      for (int i = 0; i < 16; i++) {
        const int kidx = t + 4 * (i & 1) + 8 * (i >> 3), nidx = 4 * ((i >> 1) & 3) + (g >> 1);
        T.f2[w][i >> 2][l][i & 3] = cfrag_c((8 * kidx + w) * nidx, 128, g & 1);
        T.g2[w][i >> 2][l][i & 3] = cfrag_c(-(8 * nidx + w) * kidx, 128, g & 1);
      }
  }
  return T;
}
__device__ const __align__(128) Tables g_tab = make_tables();

__device__ __forceinline__ void die() { asm volatile("st.global.u32 [%0], %1;" ::"l"(0ull), "r"(0) : "memory"); }
__device__ __forceinline__ uint32_t s2u(const void* p) { return (uint32_t)__cvta_generic_to_shared(p); }
__device__ __forceinline__ void mbar_init(uint32_t b, int c) { asm volatile("mbarrier.init.shared::cta.b64 [%0], %1;" ::"r"(b), "r"(c)); }
__device__ __forceinline__ void mbar_expect(uint32_t b, int bytes) {
  asm volatile("mbarrier.arrive.expect_tx.shared::cta.b64 _, [%0], %1;" ::"r"(b), "r"(bytes) : "memory");
}
__device__ __forceinline__ void mbar_arrive(uint32_t b) { asm volatile("mbarrier.arrive.shared::cta.b64 _, [%0];" ::"r"(b) : "memory"); }
__device__ __forceinline__ uint32_t mbar_try(uint32_t b, uint32_t parity) {
  uint32_t ok;
  asm volatile("{.reg .pred p; mbarrier.try_wait.parity.shared::cta.b64 p, [%1], %2; selp.u32 %0,1,0,p;}"
               : "=r"(ok) : "r"(b), "r"(parity) : "memory");
  return ok;
}
__device__ __forceinline__ uint32_t mbar_test(uint32_t b) {
  uint32_t ok;
  asm volatile("{.reg .pred p; mbarrier.test_wait.parity.shared::cta.b64 p, [%1], 0; selp.u32 %0,1,0,p;}" : "=r"(ok) : "r"(b) : "memory");
  return ok;
}
__device__ __forceinline__ void mbar_wait(uint32_t b, uint32_t parity = 0) {
  int it = 0;
#pragma unroll 1
  while (!mbar_try(b, parity))
    if (++it > SPIN_LIMIT) { die(); break; }
}
__device__ __forceinline__ void bar_sync(int id, int n) { asm volatile("bar.sync %0, %1;" ::"r"(id), "r"(n) : "memory"); }
__device__ __forceinline__ void bar_arrive(int id, int n) { asm volatile("bar.arrive %0, %1;" ::"r"(id), "r"(n) : "memory"); }
__device__ __forceinline__ void red_release(unsigned* p) { asm volatile("red.release.gpu.global.add.u32 [%0], 1;" ::"l"(p) : "memory"); }
__device__ __forceinline__ void red_relaxed(unsigned* p) { asm volatile("red.relaxed.gpu.global.add.u32 [%0], 1;" ::"l"(p) : "memory"); }
__device__ __forceinline__ unsigned ld_acquire(const unsigned* p) {
  unsigned v;
  asm volatile("ld.acquire.gpu.global.u32 %0, [%1];" : "=r"(v) : "l"(p) : "memory");
  return v;
}
__device__ __forceinline__ unsigned ld_relaxed(const unsigned* p) {
  unsigned v;
  asm volatile("ld.relaxed.gpu.global.u32 %0, [%1];" : "=r"(v) : "l"(p) : "memory");
  return v;
}
__device__ __forceinline__ void wait_counter(const unsigned* p, unsigned target) {
  int it = 0;
  while ((int)(ld_acquire(p) - target) < 0)
    if (++it > SPIN_LIMIT) { die(); break; }
}
__device__ __forceinline__ void sts4(uint32_t a, uint32_t x, uint32_t y, uint32_t z, uint32_t w) {
  asm volatile("st.shared.v4.u32 [%0], {%1,%2,%3,%4};" ::"r"(a), "r"(x), "r"(y), "r"(z), "r"(w) : "memory");
}
__device__ __forceinline__ uint4 lds4(uint32_t a) {
  uint4 v;
  asm volatile("ld.shared.v4.u32 {%0,%1,%2,%3}, [%4];" : "=r"(v.x), "=r"(v.y), "=r"(v.z), "=r"(v.w) : "r"(a) : "memory");
  return v;
}
__device__ __forceinline__ uint32_t pack2(float lo, float hi) {
  uint32_t r;
  asm("cvt.rn.bf16x2.f32 %0, %1, %2;" : "=r"(r) : "f"(hi), "f"(lo));
  return r;
}
__device__ __forceinline__ float bf_lo(uint32_t v) { return __uint_as_float(v << 16); }
__device__ __forceinline__ uint32_t hadd2_bf16(uint32_t a, uint32_t b) {
  uint32_t r;
  asm("add.rn.bf16x2 %0, %1, %2;" : "=r"(r) : "r"(a), "r"(b));
  return r;
}
__device__ __forceinline__ void mma16816(float (&d)[4], uint32_t a0, uint32_t a1, uint32_t a2, uint32_t a3, uint32_t b0, uint32_t b1) {
  asm("mma.sync.aligned.m16n8k16.row.col.f32.bf16.bf16.f32 {%0,%1,%2,%3}, {%4,%5,%6,%7}, {%8,%9}, {%0,%1,%2,%3};"
      : "+f"(d[0]), "+f"(d[1]), "+f"(d[2]), "+f"(d[3])
      : "r"(a0), "r"(a1), "r"(a2), "r"(a3), "r"(b0), "r"(b1));
}
__device__ __forceinline__ void mma16816_z(float (&d)[4], uint32_t a0, uint32_t a1, uint32_t a2, uint32_t a3, uint32_t b0, uint32_t b1) {
  asm("{.reg .f32 z; mov.f32 z, 0f00000000;\n"
      "mma.sync.aligned.m16n8k16.row.col.f32.bf16.bf16.f32 {%0,%1,%2,%3}, {%4,%5,%6,%7}, {%8,%9}, {z,z,z,z};}"
      : "=f"(d[0]), "=f"(d[1]), "=f"(d[2]), "=f"(d[3])
      : "r"(a0), "r"(a1), "r"(a2), "r"(a3), "r"(b0), "r"(b1));
}
template <int N>
__device__ __forceinline__ void cs_frac(int idx, float& c, float& s) {
  int i = ((idx + N / 2) & (N - 1)) - N / 2;
  float a = (float)i * (6.283185307179586f / N);
  c = __cosf(a);
  s = __sinf(a);
}
template <int N>
__device__ __forceinline__ uint32_t cfrag(int idx, int ri) {
  float c, s;
  cs_frac<N>(idx, c, s);
  return ri ? pack2(-s, c) : pack2(c, s);
}
__device__ __forceinline__ uint32_t word(const uint4& v, int e) { return e == 0 ? v.x : e == 1 ? v.y : e == 2 ? v.z : v.w; }
__device__ __forceinline__ void cdft16(const uint4 (&A)[4], const uint4 (&F)[4], uint4 (&o)[4]) {
  float acc[2][4][4];
#pragma unroll
  for (int ks = 0; ks < 2; ks++)
#pragma unroll
    for (int p = 0; p < 2; p++)
#pragma unroll
      for (int v = 0; v < 4; v++) {
        const uint4& a = A[2 * ks + p];
        const uint32_t b0 = word(F[ks * 2 + (v >> 1)], (v & 1) * 2), b1 = word(F[ks * 2 + (v >> 1)], (v & 1) * 2 + 1);
        if (ks == 0) mma16816_z(acc[p][v], a.x, a.y, a.z, a.w, b0, b1);
        else mma16816(acc[p][v], a.x, a.y, a.z, a.w, b0, b1);
      }
#pragma unroll
  for (int v = 0; v < 4; v++)
    o[v] = make_uint4(pack2(acc[0][v][0], acc[0][v][1]), pack2(acc[0][v][2], acc[0][v][3]),
                      pack2(acc[1][v][0], acc[1][v][1]), pack2(acc[1][v][2], acc[1][v][3]));
}
__device__ __forceinline__ void lds_frag(uint4& f0, uint4& f1, uint32_t a0, uint32_t a1) {
  asm volatile("ld.volatile.shared.v2.u32 {%0,%1}, [%8]; ld.volatile.shared.v2.u32 {%2,%3}, [%9];\n"
               "ld.volatile.shared.v2.u32 {%4,%5}, [%8+8]; ld.volatile.shared.v2.u32 {%6,%7}, [%9+8];"
               : "=r"(f0.x), "=r"(f0.y), "=r"(f0.z), "=r"(f0.w), "=r"(f1.x), "=r"(f1.y), "=r"(f1.z), "=r"(f1.w) : "r"(a0), "r"(a1) : "memory");
}
__device__ __forceinline__ void reg_frag(uint4 (&q)[4], uint32_t ones) {
#pragma unroll
  for (int ks = 0; ks < 2; ks++) {
    const uint4 a = q[2 * ks], b = q[2 * ks + 1];
    q[2 * ks] = make_uint4(a.x, a.y, b.x & ones, b.y & ones);
    q[2 * ks + 1] = make_uint4(a.z & ones, a.w & ones, b.z, b.w);
  }
}
__device__ __forceinline__ void st_tag(uint4* p, const uint4& v, uint32_t tag) {
  asm volatile("st.relaxed.gpu.global.v4.b32 [%0], {%1,%2,%3,%4};"
               ::"l"(p), "r"((v.x & ~1u) | tag), "r"(v.y), "r"(v.z), "r"(v.w) : "memory");
}
__device__ __forceinline__ void st_tag8(void* p, uint32_t x, uint32_t y, uint32_t tag) {
  asm volatile("st.relaxed.gpu.global.v2.b32 [%0], {%1,%2};" ::"l"(p), "r"((x & ~1u) | tag), "r"(y) : "memory");
}
__device__ __forceinline__ uint4 ld_b128(const uint4* p) {
  uint4 v;
  asm volatile("ld.relaxed.gpu.global.v4.b32 {%0,%1,%2,%3}, [%4];"
               : "=r"(v.x), "=r"(v.y), "=r"(v.z), "=r"(v.w) : "l"(p) : "memory");
  return v;
}
template <int STRIDE>
__device__ __forceinline__ void ld_tag4_issue(uint4 (&q)[4], const uint4* p) {
#pragma unroll
  for (int i = 0; i < 4; i++) q[i] = ld_b128(p + i * STRIDE);
}
template <int STRIDE, bool HALVES = false>
__device__ __forceinline__ void ld_tag4_finish(uint4 (&q)[4], const uint4* p, uint32_t tag) {
  int it = 0;
#pragma unroll 1
  while (__any_sync(0xffffffffu, ((q[0].x ^ tag) | (q[1].x ^ tag) | (q[2].x ^ tag) | (q[3].x ^ tag) |
                                  (HALVES ? (q[0].z ^ tag) | (q[1].z ^ tag) | (q[2].z ^ tag) | (q[3].z ^ tag) : 0u)) & 1u)) {
    ld_tag4_issue<STRIDE>(q, p);
    if (++it > SPIN_LIMIT) { die(); break; }
  }
#pragma unroll
  for (int i = 0; i < 4; i++) {
    asm volatile("and.b32 %0, %0, 0xfffffffe;" : "+r"(q[i].x));
    if (HALVES) q[i].z &= ~1u;
  }
}
__device__ __forceinline__ float quad_sum(const uint32_t (&a)[8]) {
  float d[4];
  mma16816_z(d, a[0], a[1], a[2], a[3], 0x3f803f80u, 0x3f803f80u);
  mma16816(d, a[4], a[5], a[6], a[7], 0x3f803f80u, 0x3f803f80u);
  return d[0] + d[2];
}
__device__ __forceinline__ float sum_groups(float v) {
  v += __shfl_xor_sync(0xffffffffu, v, 4);
  v += __shfl_xor_sync(0xffffffffu, v, 8);
  v += __shfl_xor_sync(0xffffffffu, v, 16);
  return v;
}
__device__ __forceinline__ uint32_t hsub2_bf16(uint32_t a, uint32_t b) {
  uint32_t r;
  asm("sub.rn.bf16x2 %0, %1, %2;" : "=r"(r) : "r"(a), "r"(b));
  return r;
}
__device__ __forceinline__ float row_rstd(const uint32_t (&c)[8], float delta) {
  uint32_t s[8];
#pragma unroll
  for (int i = 0; i < 8; i++) asm("mul.rn.bf16x2 %0, %1, %1;" : "=r"(s[i]) : "r"(c[i]));
  return rsqrtf(fmaxf(fmaf(-delta, delta, sum_groups(quad_sum(s)) * (1.f / 512.f)), 0.f) + 1e-5f);
}
__device__ __forceinline__ uint64_t desc64(uint32_t lo, uint32_t hi) {
  uint64_t d;
  asm("mov.b64 %0, {%1, %2};" : "=l"(d) : "r"(lo), "r"(hi));
  return d;
}
constexpr uint32_t desc_hi(uint32_t sbo, uint32_t swz) { return (sbo >> 4) | (swz << 30); }
__device__ __forceinline__ uint32_t desc_lo(uint32_t addr, uint32_t lbo) { return ((addr & 0x3FFFF) >> 4) | ((lbo >> 4) << 16); }
__device__ __forceinline__ void cp_async16(uint32_t dst, const void* src) {
  asm volatile("cp.async.cg.shared.global [%0], [%1], 16;" ::"r"(dst), "l"(src) : "memory");
}
__device__ __forceinline__ uint2 lds2(uint32_t a) {
  uint2 v;
  asm volatile("ld.shared.v2.u32 {%0,%1}, [%2];" : "=r"(v.x), "=r"(v.y) : "r"(a) : "memory");
  return v;
}
__device__ __forceinline__ uint32_t lds_u16(uint32_t a) {
  uint16_t v;
  asm volatile("ld.shared.u16 %0, [%1];" : "=h"(v) : "r"(a) : "memory");
  return v;
}
__device__ __forceinline__ void wg_fence() { asm volatile("wgmma.fence.sync.aligned;" ::: "memory"); }
__device__ __forceinline__ void wg_commit() { asm volatile("wgmma.commit_group.sync.aligned;" ::: "memory"); }
template <int N>
__device__ __forceinline__ void wg_wait() { asm volatile("wgmma.wait_group.sync.aligned %0;" ::"n"(N) : "memory"); }
__device__ __forceinline__ void bulk_load(uint32_t dst, const void* src, int bytes, uint32_t bar) {
  asm volatile("cp.async.bulk.shared::cluster.global.mbarrier::complete_tx::bytes [%0], [%1], %2, [%3];"
               ::"r"(dst), "l"(src), "r"(bytes), "r"(bar) : "memory");
}
__device__ __forceinline__ void bulk_load_mc(uint32_t dst, const void* src, int bytes, uint32_t bar) {
  asm volatile("cp.async.bulk.shared::cluster.global.mbarrier::complete_tx::bytes.multicast::cluster [%0], [%1], %2, [%3], %4;"
               ::"r"(dst), "l"(src), "r"(bytes), "r"(bar), "h"((uint16_t)3) : "memory");
}
__device__ __forceinline__ void tma3(uint32_t dst, const CUtensorMap* tm, uint32_t bar, int c0, int c1, int c2) {
  asm volatile("cp.async.bulk.tensor.3d.shared::cluster.global.mbarrier::complete_tx::bytes [%0], [%1, {%3,%4,%5}], [%2];"
               ::"r"(dst), "l"(tm), "r"(bar), "r"(c0), "r"(c1), "r"(c2) : "memory");
}
__device__ __forceinline__ void tma3_mc(uint32_t dst, const CUtensorMap* tm, uint32_t bar, int c1, int c2) {
  asm volatile("cp.async.bulk.tensor.3d.shared::cluster.global.mbarrier::complete_tx::bytes.multicast::cluster [%0], [%1, {%3,%4,%5}], [%2], %6;"
               ::"r"(dst), "l"(tm), "r"(bar), "r"(0), "r"(c1), "r"(c2), "h"((uint16_t)3) : "memory");
}
__device__ __forceinline__ void mbar_arrive_remote(uint32_t rb) {
  asm volatile("mbarrier.arrive.shared::cluster.b64 _, [%0];" ::"r"(rb) : "memory");
}
__device__ __forceinline__ uint4 ldg_ca4(const void* p) {
  uint4 v;
  asm volatile("ld.global.ca.v4.u32 {%0,%1,%2,%3}, [%4];" : "=r"(v.x), "=r"(v.y), "=r"(v.z), "=r"(v.w) : "l"(p) : "memory");
  return v;
}
__device__ __forceinline__ float u2f(uint32_t v) { return __uint_as_float(v); }
__device__ __forceinline__ void mma_az(float (&d)[4], const uint4& a, uint32_t b0, uint32_t b1) { mma16816_z(d, a.x, a.y, a.z, a.w, b0, b1); }
__device__ __forceinline__ void mma_a(float (&d)[4], const uint4& a, uint32_t b0, uint32_t b1) { mma16816(d, a.x, a.y, a.z, a.w, b0, b1); }
__device__ __forceinline__ uint32_t clock32() {
  uint32_t v;
  asm volatile("mov.u32 %0, %%clock;" : "=r"(v) :: "memory");
  return v;
}
__device__ __forceinline__ float swiglu(float g, float u, float r) {
  float hg = (0.5f * r) * g, th;
  asm("tanh.approx.f32 %0, %1;" : "=f"(th) : "f"(hg));
  return fmaf(hg, th, hg) * (r * u);
}
__device__ __forceinline__ void l2_prefetch(const void* p, int bytes) {
  asm volatile("cp.async.bulk.prefetch.L2.global [%0], %1;" ::"l"(p), "r"(bytes) : "memory");
}

__device__ __forceinline__ void wgmma_n256(float (&d)[128], uint64_t da, uint64_t db, int sd = 1) {
  asm volatile("{.reg .pred p; setp.ne.b32 p, %130, 0;\n"
      "wgmma.mma_async.sync.aligned.m64n256k16.f32.bf16.bf16 {"
      "%0,%1,%2,%3,%4,%5,%6,%7,%8,%9,%10,%11,%12,%13,%14,%15,"
      "%16,%17,%18,%19,%20,%21,%22,%23,%24,%25,%26,%27,%28,%29,%30,%31,"
      "%32,%33,%34,%35,%36,%37,%38,%39,%40,%41,%42,%43,%44,%45,%46,%47,"
      "%48,%49,%50,%51,%52,%53,%54,%55,%56,%57,%58,%59,%60,%61,%62,%63,"
      "%64,%65,%66,%67,%68,%69,%70,%71,%72,%73,%74,%75,%76,%77,%78,%79,"
      "%80,%81,%82,%83,%84,%85,%86,%87,%88,%89,%90,%91,%92,%93,%94,%95,"
      "%96,%97,%98,%99,%100,%101,%102,%103,%104,%105,%106,%107,%108,%109,%110,%111,"
      "%112,%113,%114,%115,%116,%117,%118,%119,%120,%121,%122,%123,%124,%125,%126,%127"
      "}, %128, %129, p, 1, 1, 0, 1;}\n"
      : "+f"(d[0]),"+f"(d[1]),"+f"(d[2]),"+f"(d[3]),"+f"(d[4]),"+f"(d[5]),"+f"(d[6]),"+f"(d[7]),
        "+f"(d[8]),"+f"(d[9]),"+f"(d[10]),"+f"(d[11]),"+f"(d[12]),"+f"(d[13]),"+f"(d[14]),"+f"(d[15]),
        "+f"(d[16]),"+f"(d[17]),"+f"(d[18]),"+f"(d[19]),"+f"(d[20]),"+f"(d[21]),"+f"(d[22]),"+f"(d[23]),
        "+f"(d[24]),"+f"(d[25]),"+f"(d[26]),"+f"(d[27]),"+f"(d[28]),"+f"(d[29]),"+f"(d[30]),"+f"(d[31]),
        "+f"(d[32]),"+f"(d[33]),"+f"(d[34]),"+f"(d[35]),"+f"(d[36]),"+f"(d[37]),"+f"(d[38]),"+f"(d[39]),
        "+f"(d[40]),"+f"(d[41]),"+f"(d[42]),"+f"(d[43]),"+f"(d[44]),"+f"(d[45]),"+f"(d[46]),"+f"(d[47]),
        "+f"(d[48]),"+f"(d[49]),"+f"(d[50]),"+f"(d[51]),"+f"(d[52]),"+f"(d[53]),"+f"(d[54]),"+f"(d[55]),
        "+f"(d[56]),"+f"(d[57]),"+f"(d[58]),"+f"(d[59]),"+f"(d[60]),"+f"(d[61]),"+f"(d[62]),"+f"(d[63]),
        "+f"(d[64]),"+f"(d[65]),"+f"(d[66]),"+f"(d[67]),"+f"(d[68]),"+f"(d[69]),"+f"(d[70]),"+f"(d[71]),
        "+f"(d[72]),"+f"(d[73]),"+f"(d[74]),"+f"(d[75]),"+f"(d[76]),"+f"(d[77]),"+f"(d[78]),"+f"(d[79]),
        "+f"(d[80]),"+f"(d[81]),"+f"(d[82]),"+f"(d[83]),"+f"(d[84]),"+f"(d[85]),"+f"(d[86]),"+f"(d[87]),
        "+f"(d[88]),"+f"(d[89]),"+f"(d[90]),"+f"(d[91]),"+f"(d[92]),"+f"(d[93]),"+f"(d[94]),"+f"(d[95]),
        "+f"(d[96]),"+f"(d[97]),"+f"(d[98]),"+f"(d[99]),"+f"(d[100]),"+f"(d[101]),"+f"(d[102]),"+f"(d[103]),
        "+f"(d[104]),"+f"(d[105]),"+f"(d[106]),"+f"(d[107]),"+f"(d[108]),"+f"(d[109]),"+f"(d[110]),"+f"(d[111]),
        "+f"(d[112]),"+f"(d[113]),"+f"(d[114]),"+f"(d[115]),"+f"(d[116]),"+f"(d[117]),"+f"(d[118]),"+f"(d[119]),
        "+f"(d[120]),"+f"(d[121]),"+f"(d[122]),"+f"(d[123]),"+f"(d[124]),"+f"(d[125]),"+f"(d[126]),"+f"(d[127])
      : "l"(da), "l"(db), "r"(sd));
}
__device__ __forceinline__ void wgmma_n192(float (&d)[96], uint64_t da, uint64_t db) {
  asm volatile("wgmma.mma_async.sync.aligned.m64n192k16.f32.bf16.bf16 {"
      "%0,%1,%2,%3,%4,%5,%6,%7,%8,%9,%10,%11,%12,%13,%14,%15,"
      "%16,%17,%18,%19,%20,%21,%22,%23,%24,%25,%26,%27,%28,%29,%30,%31,"
      "%32,%33,%34,%35,%36,%37,%38,%39,%40,%41,%42,%43,%44,%45,%46,%47,"
      "%48,%49,%50,%51,%52,%53,%54,%55,%56,%57,%58,%59,%60,%61,%62,%63,"
      "%64,%65,%66,%67,%68,%69,%70,%71,%72,%73,%74,%75,%76,%77,%78,%79,"
      "%80,%81,%82,%83,%84,%85,%86,%87,%88,%89,%90,%91,%92,%93,%94,%95"
      "}, %96, %97, 1, 1, 1, 0, 1;\n"
      : "+f"(d[0]),"+f"(d[1]),"+f"(d[2]),"+f"(d[3]),"+f"(d[4]),"+f"(d[5]),"+f"(d[6]),"+f"(d[7]),
        "+f"(d[8]),"+f"(d[9]),"+f"(d[10]),"+f"(d[11]),"+f"(d[12]),"+f"(d[13]),"+f"(d[14]),"+f"(d[15]),
        "+f"(d[16]),"+f"(d[17]),"+f"(d[18]),"+f"(d[19]),"+f"(d[20]),"+f"(d[21]),"+f"(d[22]),"+f"(d[23]),
        "+f"(d[24]),"+f"(d[25]),"+f"(d[26]),"+f"(d[27]),"+f"(d[28]),"+f"(d[29]),"+f"(d[30]),"+f"(d[31]),
        "+f"(d[32]),"+f"(d[33]),"+f"(d[34]),"+f"(d[35]),"+f"(d[36]),"+f"(d[37]),"+f"(d[38]),"+f"(d[39]),
        "+f"(d[40]),"+f"(d[41]),"+f"(d[42]),"+f"(d[43]),"+f"(d[44]),"+f"(d[45]),"+f"(d[46]),"+f"(d[47]),
        "+f"(d[48]),"+f"(d[49]),"+f"(d[50]),"+f"(d[51]),"+f"(d[52]),"+f"(d[53]),"+f"(d[54]),"+f"(d[55]),
        "+f"(d[56]),"+f"(d[57]),"+f"(d[58]),"+f"(d[59]),"+f"(d[60]),"+f"(d[61]),"+f"(d[62]),"+f"(d[63]),
        "+f"(d[64]),"+f"(d[65]),"+f"(d[66]),"+f"(d[67]),"+f"(d[68]),"+f"(d[69]),"+f"(d[70]),"+f"(d[71]),
        "+f"(d[72]),"+f"(d[73]),"+f"(d[74]),"+f"(d[75]),"+f"(d[76]),"+f"(d[77]),"+f"(d[78]),"+f"(d[79]),
        "+f"(d[80]),"+f"(d[81]),"+f"(d[82]),"+f"(d[83]),"+f"(d[84]),"+f"(d[85]),"+f"(d[86]),"+f"(d[87]),
        "+f"(d[88]),"+f"(d[89]),"+f"(d[90]),"+f"(d[91]),"+f"(d[92]),"+f"(d[93]),"+f"(d[94]),"+f"(d[95])
      : "l"(da), "l"(db));
}
template <int SD>
__device__ __forceinline__ void wgmma_rs_n128(float (&d)[64], uint32_t a0, uint32_t a1, uint32_t a2, uint32_t a3, uint64_t db) {
  asm volatile("wgmma.mma_async.sync.aligned.m64n128k16.f32.bf16.bf16 {"
      "%0,%1,%2,%3,%4,%5,%6,%7,%8,%9,%10,%11,%12,%13,%14,%15,"
      "%16,%17,%18,%19,%20,%21,%22,%23,%24,%25,%26,%27,%28,%29,%30,%31,"
      "%32,%33,%34,%35,%36,%37,%38,%39,%40,%41,%42,%43,%44,%45,%46,%47,"
      "%48,%49,%50,%51,%52,%53,%54,%55,%56,%57,%58,%59,%60,%61,%62,%63"
      "}, {%64,%65,%66,%67}, %68, %69, 1, 1, 1;\n"
      : "+f"(d[0]),"+f"(d[1]),"+f"(d[2]),"+f"(d[3]),"+f"(d[4]),"+f"(d[5]),"+f"(d[6]),"+f"(d[7]),
        "+f"(d[8]),"+f"(d[9]),"+f"(d[10]),"+f"(d[11]),"+f"(d[12]),"+f"(d[13]),"+f"(d[14]),"+f"(d[15]),
        "+f"(d[16]),"+f"(d[17]),"+f"(d[18]),"+f"(d[19]),"+f"(d[20]),"+f"(d[21]),"+f"(d[22]),"+f"(d[23]),
        "+f"(d[24]),"+f"(d[25]),"+f"(d[26]),"+f"(d[27]),"+f"(d[28]),"+f"(d[29]),"+f"(d[30]),"+f"(d[31]),
        "+f"(d[32]),"+f"(d[33]),"+f"(d[34]),"+f"(d[35]),"+f"(d[36]),"+f"(d[37]),"+f"(d[38]),"+f"(d[39]),
        "+f"(d[40]),"+f"(d[41]),"+f"(d[42]),"+f"(d[43]),"+f"(d[44]),"+f"(d[45]),"+f"(d[46]),"+f"(d[47]),
        "+f"(d[48]),"+f"(d[49]),"+f"(d[50]),"+f"(d[51]),"+f"(d[52]),"+f"(d[53]),"+f"(d[54]),"+f"(d[55]),
        "+f"(d[56]),"+f"(d[57]),"+f"(d[58]),"+f"(d[59]),"+f"(d[60]),"+f"(d[61]),"+f"(d[62]),"+f"(d[63])
      : "r"(a0), "r"(a1), "r"(a2), "r"(a3), "l"(db), "n"(SD));
}

constexpr int C_LN = 0, C_PX = 16, C_PY = 32;
constexpr int NB_CONS = 1, NB_LN = 2, NB_LAG = 4, NB_INIT = 6, NB_RDY = 7, NB_WG = 8;
#define LAGX 3
#define LAGY 3
#define LAG2 5
constexpr int NLL = 2;
#define POLL_DELAY3 600
#define POLL_DELAY 1200
#define FILT_DELAY 600
#define THR_B 0
#define THR_P 0
#define SPEC -1
#define WARM 4
#define HWARM 0
#define TOUCH 1
#define ALEAD 6
#define POLL_DELAY2 1200
#define PF1_WAIT 1
#define RING_SIG 1
#define PF2_SIG 1
constexpr int SM_E = 0, SM_X = 16384, SM_E2 = 32768, SM_W = 49152, SM_FC = 69632, SM_T = 73728 - T1_BYTES;
constexpr unsigned long long KORDER = 0xBA9432DC876510ull;
constexpr unsigned long long BSLOT = 0x76532107653210ull, PSLOT = 0xDCBA984DCBA984ull;
constexpr uint32_t HI128 = desc_hi(1024, 1), HI64 = desc_hi(512, 2);

struct Bars {
  uint64_t full1[32], empty1[32], full2[16], fullA[8], empty2[8], fullP[16], emptyP[8], hbar, tbar, hint[3], sig[2], sbar;
  uint32_t epoch, pad;
};

template <int NK, bool STORE>
__device__ __forceinline__ void make_p(const float (&acc)[NK * 16], float r0, float r1, uint4 (&p)[NK], uint4* pbase, int ks0, uint32_t tag) {
#pragma unroll
  for (int j = 0; j < NK; j++) {
    uint32_t w[4];
#pragma unroll
    for (int i = 0; i < 4; i++) {
      const int a = 8 * j + 2 * i, b = a + NK * 8;
      w[i] = pack2(swiglu(acc[a], acc[b], (i & 1) ? r1 : r0), swiglu(acc[a + 1], acc[b + 1], (i & 1) ? r1 : r0));
    }
    asm volatile("" : "+r"(w[0]), "+r"(w[1]), "+r"(w[2]), "+r"(w[3]));
    p[j] = make_uint4(w[0], w[1], w[2], w[3]);
    if (STORE) st_tag(pbase + ((ks0 + j) >> 2) * 1024 + ((ks0 + j) & 3) * 32, p[j], tag);
  }
}
__device__ __forceinline__ void spin_cycles(uint32_t n) {
  const uint32_t t0 = clock32();
  while (clock32() - t0 < n) {}
}

__device__ __forceinline__ void spin_until(uint32_t t) {
  float d[4] = {0.f, 0.f, 0.f, 0.f};
  while ((int)(clock32() - t) < 0) {
    if (HWARM) asm volatile("mma.sync.aligned.m16n8k16.row.col.f32.bf16.bf16.f32 {%0,%1,%2,%3}, {%4,%4,%4,%4}, {%4,%4}, {%0,%1,%2,%3};"
                            : "+f"(d[0]), "+f"(d[1]), "+f"(d[2]), "+f"(d[3]) : "r"(t));
  }
}

__global__ void __cluster_dims__(2, 1, 1) __launch_bounds__(NTHREADS, 1)
fused_kernel(const __nv_bfloat16* __restrict__ x, const Tables* __restrict__ tab, Scratch* __restrict__ scr,
             __nv_bfloat16* __restrict__ out, const char* __restrict__ wg_raw, const char* __restrict__ wu_raw,
             const char* __restrict__ wd_raw,
             const __grid_constant__ CUtensorMap tmWR, const __grid_constant__ CUtensorMap tmWI,
             const __grid_constant__ CUtensorMap tmGX, const __grid_constant__ CUtensorMap tmUX,
             const __grid_constant__ CUtensorMap tmGY, const __grid_constant__ CUtensorMap tmUY,
             const __grid_constant__ CUtensorMap tmD) {
  extern __shared__ __align__(1024) char smem_raw[];
  const uint32_t sbase = s2u(smem_raw);
  const uint32_t sbar = sbase + 14 * SLOT, sstat = sbar + 1280;
  const int tid = threadIdx.x, lane = tid & 31;
  const int c = blockIdx.x, rk = c & 1, f = (c >> 1) & 7, rb = 2 * (c >> 4) + rk;
  const int rb2 = 2 * (c >> 4) + (f >> 2), kh = (f >> 1) & 1, nq = 2 * (f & 1) + rk;
#define BAR(field, i) (sbar + (uint32_t)offsetof(Bars, field) + 8u * (i))
#define TOFF(field) (sbase + SM_T + (uint32_t)offsetof(Tables, field) + lane * 16)

  if (tid >= 256) {
    asm volatile("setmaxnreg.dec.sync.aligned.u32 56;");
    const int warp = __shfl_sync(0xffffffffu, tid >> 5, 0);
    if (lane == 0) {
      if (warp == 8) {
        if (sbase & 1023) die();
#pragma unroll
        for (int i = 0; i < 16; i++) mbar_init(BAR(emptyP, i), i < 7 ? 16 : i < 8 ? 8 : i == 9 ? 1 + 32 * TOUCH : i < 13 ? 1 : i < 15 ? 8 : 32);
        mbar_expect(BAR(tbar, 0), T2_BYTES + 2 * 10240);
        mbar_expect(BAR(hbar, 0), 16384);
      } else if (warp == 9) {
#pragma unroll
        for (int i = 0; i < 32; i++) mbar_init(BAR(full1, i), 1);
#pragma unroll
        for (int i = 0; i < 32; i++) mbar_expect(BAR(full1, i), i < 16 ? 16384 : 12288);
      } else if (warp == 10) {
#pragma unroll
        for (int i = 0; i < 32; i++) mbar_init(BAR(empty1, i), 16);
#pragma unroll
        for (int i = 0; i < 14; i++) mbar_init(BAR(fullP, i), 1);
#pragma unroll
        for (int i = 0; i < 14; i++) mbar_expect(BAR(fullP, i), 16384);
      } else {
#pragma unroll
        for (int i = 0; i < 32; i++) mbar_init(BAR(full2, i), i < 24 ? 1 : 8);
#pragma unroll
        for (int i = 0; i < 24; i++) mbar_expect(BAR(full2, i), 16384);
      }
      asm volatile("fence.mbarrier_init.release.cluster;" ::: "memory");
    }
    if (tid == 256) {
      const int w0 = ((c >> 3) * 257 + 32 * (c & 7) + 1) & ~7;
      if (FILT_DELAY) {
        asm volatile("prefetch.tensormap [%0];" ::"l"(&tmWR) : "memory");
        asm volatile("prefetch.tensormap [%0];" ::"l"(&tmWI) : "memory");
        spin_cycles(FILT_DELAY);
      }
      tma3(sbase + SM_W, &tmWR, BAR(tbar, 0), w0, 0, 0);
      tma3(sbase + SM_W + 10240, &tmWI, BAR(tbar, 0), w0, 0, 0);
      bulk_load(sbase + SM_T + T1_BYTES, reinterpret_cast<const char*>(tab) + T1_BYTES, T2_BYTES, BAR(tbar, 0));
    }
    if (tid == 288) {
      asm volatile("prefetch.tensormap [%0];" ::"l"(rk ? &tmUX : &tmGX) : "memory");
      asm volatile("prefetch.tensormap [%0];" ::"l"(rk ? &tmUY : &tmGY) : "memory");
      asm volatile("prefetch.tensormap [%0];" ::"l"(&tmD) : "memory");
    }
    if (tid == 320) {
      const unsigned e = ld_relaxed(&scr->cnt[(C_LN + rb) * 32]) >> 3;
      asm volatile("st.shared.u32 [%0], %1;" ::"r"(BAR(epoch, 0)), "r"(e) : "memory");
    }
    __syncwarp();
    asm volatile("barrier.cluster.arrive.relaxed.aligned;" ::: "memory");
    bar_arrive(NB_RDY, 384);
    asm volatile("barrier.cluster.wait.aligned;" ::: "memory");
    bar_sync(NB_INIT, 384);
    unsigned epoch;
    asm volatile("ld.shared.u32 %0, [%1];" : "=r"(epoch) : "r"(BAR(epoch, 0)) : "memory");
    if (warp == 8) {
      if (lane == 0) {
        const int ax = (7 * f + 3 * (f & 1)) >> 1;
        const int ay = 7 * f + ((f & 1) ? 0 : 4);
        const CUtensorMap* tx = rk ? &tmUX : &tmGX;
        const CUtensorMap* ty = rk ? &tmUY : &tmGY;
        if (RING_SIG >= 0) mbar_wait(BAR(sig, RING_SIG));
        uint32_t s = 2;
#pragma unroll 1
        for (int n = 0; n < 16; n++) {
          if (n >= 6) mbar_wait(BAR(empty1, n - 6));
          tma3_mc(sbase + (8 + s) * SLOT + rk * 8192, tx, BAR(full1, n), n * 32, ax);
          if (++s == 6) s = 0;
        }
#pragma unroll 1
        for (int k = 0; k < 16; k++) {
          mbar_wait(BAR(empty1, k < 8 ? 10 + ((12 * k + 11) >> 4) : 8 + k));
          tma3_mc(sbase + 8 * SLOT + (k & 7) * 12288 + rk * 6144, ty, BAR(full1, 16 + k), k * 32, ay);
        }
      }
    } else if (warp == 9) {
      if (lane == 0) {
#pragma unroll 1
        for (int i = 0; i < 14; i++) {
          const int kblk = 14 * kh + (int)((KORDER >> (4 * i)) & 15);
          const int j = i < 7 ? i : i - 7, sl = j + (j >= 4);
          mbar_wait(i < 7 ? BAR(empty1, 17 + 2 * sl) : BAR(empty2, j));
          if (THR_B && i >= THR_B) mbar_wait(BAR(full2, i - THR_B));
          tma3(sbase + sl * SLOT, &tmD, BAR(full2, i), 0, 64 * kblk, 2 * nq);
        }
        wait_counter(&scr->cnt[(C_LN + rb2) * 32], (epoch + 1) * 8);
        asm volatile("fence.proxy.async.global;" ::: "memory");
        mbar_wait(BAR(emptyP, 7));
        bulk_load(sbase + 4 * SLOT, &scr->LN[(rb2 * 8 + 2 * nq) * 1024 + kh * 512], 8192, BAR(hbar, 0));
        bulk_load(sbase + 4 * SLOT + 8192, &scr->LN[(rb2 * 8 + 2 * nq + 1) * 1024 + kh * 512], 8192, BAR(hbar, 0));
      }
    } else if (warp == 10) {
      bar_sync(NB_LN, 288);
      if (lane == 0) {
        PROFP(0);
        red_release(&scr->cnt[(C_LN + rb) * 32]);
        PROFP(1);
        wait_counter(&scr->cnt[(C_LN + rb) * 32], (epoch + 1) * 8);
        asm volatile("fence.proxy.async.global;" ::: "memory");
        PROFP(2);
#pragma unroll 1
        for (int kb = NLL; kb < 8; kb++) {
          if (2 * kb >= ALEAD) mbar_wait(BAR(empty1, 2 * kb - ALEAD));
          bulk_load(sbase + kb * SLOT, &scr->LN[(rb * 8 + kb) * 1024], 16384, BAR(fullA, kb));
        }
#pragma unroll 1
        for (int s = 0; s < 14; s++) {
          const int kblk = 14 * kh + (int)((KORDER >> (4 * s)) & 15);
          if (s == 0 || (SPEC < 0 && (s == 8 || s == 11))) {
            if (s != 11) PROFP(3 + (s >> 2));
            mbar_wait(BAR(hint, s == 0 ? 0 : s == 8 ? 1 : 2), 0);
            if (s != 11) PROFP(4 + (s >> 2));
          }
          const int j = s < 7 ? s : s - 7;
          mbar_wait(s < 7 ? BAR(empty1, 24 + s + (s == 0) + (s >= 4)) : BAR(emptyP, j));
          if (THR_P && s >= THR_P) mbar_wait(BAR(fullP, s - THR_P));
          if (SPEC >= 0 && s == 8) mbar_wait(BAR(emptyP, SPEC & 7));
          bulk_load_mc(sbase + (j ? 7 + j : 4) * SLOT + rk * 8192, &scr->P[(rb2 * 28 + kblk) * 1024 + rk * 512], 8192, BAR(fullP, s));
        }
        PROFP(7);
      }
    } else {
      if (TOUCH) {
#pragma unroll
        for (int i = 0; i < 4 * NLL; i++)
          st_tag(&scr->LN[(rb * 8 + (i >> 2)) * 1024 + f * 128 + (i & 3) * 32 + lane], make_uint4(0, 0, epoch & 1, 0), epoch & 1);
        mbar_arrive(BAR(tbar, 0));
      }
      if (lane == 0) {
        if (PF1_WAIT) mbar_wait(BAR(tbar, 0));
        l2_prefetch(wg_raw + (size_t)c * 5376, 5376);
        l2_prefetch(wu_raw + (size_t)c * 5376, 5376);
        mbar_wait(BAR(sig, PF2_SIG), 0);
        l2_prefetch(wg_raw + 688128 + (size_t)c * 8960, 8960);
        l2_prefetch(wu_raw + 688128 + (size_t)c * 8960, 8960);
      }
      mbar_wait(BAR(fullA, 4), 0);
      if (lane == 0) l2_prefetch(wd_raw + (size_t)c * 14336, 14336);
      {
        const uint32_t tag = (epoch + 1) & 1;
        uint4 v0, v1, v2;
        int it = 0;
        while (true) {
          v0 = ld_b128(&scr->ST[rb * 64 + lane]);
          v1 = ld_b128(&scr->ST[rb * 64 + 32 + lane]);
          v2 = ld_b128(&scr->ST[rb2 * 64 + 32 * kh + lane]);
          if (!__any_sync(0xffffffffu, ((v0.x ^ tag) | (v1.x ^ tag) | (v2.x ^ tag)) & 1u)) break;
          if (++it > SPIN_LIMIT) { die(); break; }
        }
        sts4(sstat + lane * 16, v0.x & ~1u, v0.y, v0.z, v0.w);
        sts4(sstat + 512 + lane * 16, v1.x & ~1u, v1.y, v1.z, v1.w);
        sts4(sstat + 1024 + lane * 16, v2.x & ~1u, v2.y, v2.z, v2.w);
#pragma unroll 4
        for (int i = 0; i < 32; i++)
          st_tag(&scr->XP[(c ^ 4) * 1024 + i * 32 + lane], make_uint4(0, 0, 0, 0), tag ^ 1);
        mbar_arrive(BAR(sbar, 0));
      }
      if (lane == 0) {
        mbar_wait(BAR(empty1, 17));
#pragma unroll 1
        for (int e = 0; e < (SPEC < 0 ? 3 : 1); e++) {
          const unsigned* cp = e == 0 ? &scr->cnt[(C_PX + rb2) * 32] : &scr->cnt[(C_PY + rb2) * 32 + 2 * kh + e - 1];
          if (e == 1) mbar_wait(BAR(fullP, 0), 0);
          int it = 0;
          while ((int)(ld_relaxed(cp) - (epoch + 1) * (e == 0 ? 64 : 16)) < 0)
            if (++it > SPIN_LIMIT) { die(); break; }
          mbar_arrive(BAR(hint, e));
        }
      }
    }
  } else {
    const int warp = __shfl_sync(0xffffffffu, tid >> 5, 0);
    const int g = lane >> 2, t = lane & 3;
    PROF(0);
    PROFG(14);
#pragma unroll
    for (int i = 0; i < 4; i++) {
      const int r = i >> 1, ch = (i & 1) * 32 + lane;
      cp_async16(sbase + SM_X + (2 * warp + r) * 1024 + ((ch ^ ((ch >> 3) & 1)) * 16),
                 x + (size_t)(c + 128 * (2 * warp + r)) * 512 + ch * 8);
    }
    asm volatile("cp.async.commit_group;" ::: "memory");
    asm volatile("barrier.cluster.arrive.relaxed.aligned;" ::: "memory");
    uint4 fa[4], fb[4], tw[6];
#pragma unroll
    for (int i = 0; i < 4; i++) fa[i] = ldg_ca4(&tab->fa[i][lane][0]);
#pragma unroll
    for (int i = 0; i < 6; i++) tw[i] = ldg_ca4(&tab->tw1[i][lane][0]);
#pragma unroll
    for (int i = 0; i < 4; i++) fb[i] = ldg_ca4(&tab->fb[i][lane][0]);
    uint32_t rbar;
    asm volatile("mapa.shared::cluster.u32 %0, %1, %2;" : "=r"(rbar) : "r"(sbar), "r"(rk ^ 1));
#define RBAR(field, i) (rbar + (uint32_t)offsetof(Bars, field) + 8u * (i))
    {
      const int ln = (tid >> 1) & 31, lg = ln >> 2, lt = ln & 3, i = 4 * (tid >> 6) + 2 * (tid & 1);
      const int kidx = lt + 8 * (i >> 3), nidx = 4 * ((i >> 1) & 3) + (lg >> 1);
      const uint32_t a0 = cfrag<2048>((c + 128 * kidx) * nidx, lg & 1), a1 = cfrag<2048>((c + 128 * (kidx + 4)) * nidx, lg & 1);
      const uint32_t b0 = cfrag<2048>(-(c + 128 * nidx) * kidx, lg & 1), b1 = cfrag<2048>(-(c + 128 * nidx) * (kidx + 4), lg & 1);
      asm volatile("st.shared.v2.u32 [%0], {%1,%2};" ::"r"(sbase + SM_FC + tid * 8), "r"(a0), "r"(a1) : "memory");
      asm volatile("st.shared.v2.u32 [%0], {%1,%2};" ::"r"(sbase + SM_FC + 2048 + tid * 8), "r"(b0), "r"(b1) : "memory");
    }
    bar_sync(NB_CONS, 256);
    uint4 fc[4];
#pragma unroll
    for (int i = 0; i < 4; i++) fc[i] = lds4(sbase + SM_FC + i * 512 + lane * 16);
    asm volatile("cp.async.wait_group 0;" ::: "memory");
    __syncwarp();
    bar_arrive(NB_INIT, 384);
    PROF(13);
    uint32_t tag, ones;
    uint4 q[4], o[4];
    {
      uint32_t v[2][8];
#pragma unroll
      for (int r = 0; r < 2; r++)
#pragma unroll
        for (int ks = 0; ks < 2; ks++) {
          const int ch = 32 * ks + 2 * (lane & 15) + (lane >> 4);
          asm volatile("ldmatrix.sync.aligned.m8n8.x4.trans.shared.b16 {%0,%1,%2,%3}, [%4];"
                       : "=r"(v[r][4 * ks]), "=r"(v[r][4 * ks + 1]), "=r"(v[r][4 * ks + 2]), "=r"(v[r][4 * ks + 3])
                       : "r"(sbase + SM_X + (2 * warp + r) * 1024 + ((ch ^ ((ch >> 3) & 1)) * 16)) : "memory");
        }
#pragma unroll
      for (int r = 0; r < 2; r++) {
        float dd[2][4], ee[2][4];
#pragma unroll
        for (int nt = 0; nt < 2; nt++) {
          mma_az(dd[nt], fa[0], v[r][2 * nt], v[r][2 * nt + 1]);
          mma_a(dd[nt], fa[1], v[r][4 + 2 * nt], v[r][5 + 2 * nt]);
          mma_az(ee[nt], fa[2], v[r][2 * nt], v[r][2 * nt + 1]);
          mma_a(ee[nt], fa[3], v[r][4 + 2 * nt], v[r][5 + 2 * nt]);
        }
        float mean = (dd[0][0] + dd[0][1]) + (dd[1][0] + dd[1][1]);
        mean += __shfl_xor_sync(0xffffffffu, mean, 1);
        mean += __shfl_xor_sync(0xffffffffu, mean, 2);
        mean = __shfl_sync(0xffffffffu, mean, 0) * (1.f / 512.f);
        const uint32_t mb = pack2(mean, mean);
        uint32_t cv[8];
#pragma unroll
        for (int i = 0; i < 8; i++) cv[i] = hsub2_bf16(v[r][i], mb);
        const float rs = row_rstd(cv, mean - bf_lo(mb));
        float acc[4][4];
#pragma unroll
        for (int nt = 0; nt < 2; nt++) {
          const float (&d)[4] = dd[nt];
          const float (&e)[4] = ee[nt];
          const uint4 &ka = tw[2 * nt], &kb = tw[2 * nt + 1], &kc = tw[4 + nt];
          const uint32_t a0 = pack2(d[0] * u2f(ka.x) + d[2] * u2f(ka.y), d[1] * u2f(kb.x) + d[3] * u2f(kb.y));
          const uint32_t a2 = pack2(d[0] * u2f(ka.z) + d[2] * u2f(ka.w), d[1] * u2f(kb.z) + d[3] * u2f(kb.w));
          const uint32_t a1 = pack2(e[0] * u2f(kc.x) + e[2] * u2f(kc.y), e[1] * u2f(kc.z) + e[3] * u2f(kc.w));
          const uint32_t a3 = pack2(e[2] * u2f(kc.x) - e[0] * u2f(kc.y), e[3] * u2f(kc.z) - e[1] * u2f(kc.w));
          const uint32_t dc = pack2(fmaf(mean, -32.f, d[0]), fmaf(mean, -32.f, d[1]));
          const uint32_t h0 = g == 0 ? dc : a0, h2 = g == 0 ? 0u : a2;
          if (nt == 0) {
            mma16816_z(acc[0], a0, a1, a2, a3, fb[2 * nt].x, fb[2 * nt].y);
            mma16816_z(acc[1], a0, a1, a2, a3, fb[2 * nt].z, fb[2 * nt].w);
            mma16816_z(acc[2], h0, a1, h2, a3, fb[2 * nt + 1].x, fb[2 * nt + 1].y);
            mma16816_z(acc[3], h0, a1, h2, a3, fb[2 * nt + 1].z, fb[2 * nt + 1].w);
          } else {
            mma16816(acc[0], a0, a1, a2, a3, fb[2 * nt].x, fb[2 * nt].y);
            mma16816(acc[1], a0, a1, a2, a3, fb[2 * nt].z, fb[2 * nt].w);
            mma16816(acc[2], h0, a1, h2, a3, fb[2 * nt + 1].x, fb[2 * nt + 1].y);
            mma16816(acc[3], h0, a1, h2, a3, fb[2 * nt + 1].z, fb[2 * nt + 1].w);
          }
        }
#pragma unroll
        for (int h = 0; h < 2; h++) {
          const int j = 2 * warp + r, m = 2 * t + h;
          sts4(sbase + SM_E + ((j * 8 + m) * 8 + (g ^ (2 * t) ^ (2 * (j & 3)))) * 16,
               pack2(acc[h][0] * rs, acc[h][1] * rs), pack2(acc[h][2] * rs, acc[h][3] * rs),
               pack2(acc[2 + h][0] * rs, acc[2 + h][1] * rs), pack2(acc[2 + h][2] * rs, acc[2 + h][3] * rs));
        }
      }
      if (tid == 0) PROFP(12);
      bar_sync(NB_RDY, 384);
      if (tid == 0) PROFP(13);
      const uint32_t ea = sbase + SM_E + ((t * 8 + warp) * 8 + (g ^ (warp & 6) ^ (2 * t))) * 16;
      lds_frag(q[0], q[1], ea, ea + 4096);
      lds_frag(q[2], q[3], ea + 8192, ea + 12288);
      asm volatile("ld.shared.u32 %0, [%1];" : "=r"(tag) : "r"(BAR(epoch, 0)) : "memory");
      ones = ~(tag >> 31);
      tag = (tag + 1) & 1;
      cdft16(q, fc, o);
#pragma unroll
      for (int vv = 0; vv < 4; vv++) st_tag(&scr->Z1[(((4 * vv + t) * 8 + warp) * 128 + c) * 8 + g], o[vv], tag);
    }
    PROF(1);
    asm volatile("setmaxnreg.inc.sync.aligned.u32 224;");
    {
      const uint4* const zp = &scr->Z1[(c * 128 + 8 * t + warp) * 8 + g];
      const uint32_t tst = clock32();
      mbar_wait(BAR(tbar, 0), 0);
      if (tid == 0) PROFP(14);
      uint4 f2[4], g2[4];
#pragma unroll
      for (int i = 0; i < 4; i++) {
        f2[i] = lds4(TOFF(f2) + warp * 2048 + i * 512);
        g2[i] = lds4(TOFF(g2) + warp * 2048 + i * 512);
      }
      const uint4 f8 = lds4(TOFF(f8)), g8 = lds4(TOFF(g8));
      float wfr[16], wfi[16];
      {
        const float nyq = ((c & 7) == 7 && g == 0) ? 0.5f : 1.f;
        const int gg = g == 0 ? 16 : g, wsh = (2 * (c >> 3) + 2) & 15;
#pragma unroll
        for (int i = 0; i < 16; i++) {
          const int ci = i >> 3, dd = (i >> 2) & 1, e = i & 3;
          const int kk = (e == 0 ? gg : e == 1 ? g + 8 : e == 2 ? 32 - g : 24 - g) - 1;
          const uint32_t a = sbase + SM_W + ((2 * warp + ci) * 8 + t + 4 * dd) * 80 + wsh + 2 * kk;
          wfr[i] = bf_lo(lds_u16(a)) * (e == 2 ? nyq : 1.f);
          wfi[i] = bf_lo(lds_u16(a + 10240)) * (e == 2 ? nyq : 1.f);
        }
      }
      asm volatile("barrier.cluster.wait.aligned;" ::: "memory");
      PROF(2);
      spin_until(tst + POLL_DELAY);
      ld_tag4_issue<256>(q, zp);
      ld_tag4_finish<256>(q, zp, tag);
      if (tid == 0) PROFP(30);
      if (lane == 0) mbar_arrive(BAR(sig, 0));
      reg_frag(q, ones);
      cdft16(q, f2, o);
      const uint32_t e2 = sbase + SM_E2;
#pragma unroll
      for (int vv = 0; vv < 4; vv++)
        sts4(e2 + ((warp * 16 + 4 * vv + t) * 8 + (g ^ (2 * t) ^ (2 * (warp & 3)))) * 16, o[vv].x, o[vv].y, o[vv].z, o[vv].w);
      bar_sync(NB_CONS, 256);
      uint32_t ad[2], res[2][2][4];
#pragma unroll
      for (int ci = 0; ci < 2; ci++) {
        const int cc = 2 * warp + ci;
        ad[ci] = e2 + ((t * 16 + cc) * 8 + (g ^ (2 * (cc & 3)) ^ (2 * t))) * 16;
        lds_frag(q[2 * ci], q[2 * ci + 1], ad[ci], ad[ci] + 8192);
      }
#pragma unroll
      for (int ci = 0; ci < 2; ci++)
#pragma unroll
        for (int p = 0; p < 2; p++) {
          uint32_t y[2][2];
#pragma unroll
          for (int vv = 0; vv < 2; vv++) {
            float d[4];
            mma_az(d, q[2 * ci + p], word(f8, 2 * vv), word(f8, 2 * vv + 1));
#pragma unroll
            for (int rr = 0; rr < 2; rr++) {
              const float fr = wfr[ci * 8 + vv * 4 + 2 * p + rr], fi = wfi[ci * 8 + vv * 4 + 2 * p + rr];
              y[vv][rr] = pack2(d[2 * rr] * fr - d[2 * rr + 1] * fi, d[2 * rr] * fi + d[2 * rr + 1] * fr);
            }
          }
#pragma unroll
          for (int vv = 0; vv < 2; vv++) {
            float d[4];
            mma16816_z(d, y[0][0], y[0][1], y[1][0], y[1][1], word(g8, 2 * vv), word(g8, 2 * vv + 1));
            res[ci][vv][2 * p] = pack2(d[0], d[1]);
            res[ci][vv][2 * p + 1] = pack2(d[2], d[3]);
          }
        }
#pragma unroll
      for (int i = 0; i < 4; i++)
        sts4(ad[i >> 1] + (i & 1) * 8192, res[i >> 1][i & 1][0], res[i >> 1][i & 1][1], res[i >> 1][i & 1][2], res[i >> 1][i & 1][3]);
      bar_sync(NB_CONS, 256);
      const uint32_t eb = e2 + ((warp * 16 + t) * 8 + (g ^ (2 * t) ^ (2 * (warp & 3)))) * 16;
      lds_frag(q[0], q[1], eb, eb + 512);
      lds_frag(q[2], q[3], eb + 1024, eb + 1536);
      cdft16(q, g2, o);
#pragma unroll
      for (int vv = 0; vv < 4; vv++) st_tag(&scr->Z2[((8 * (4 * vv + t) + warp) * 128 + c) * 8 + g], o[vv], tag);
    }
    PROF(3);
    {
      const uint4* const zp = &scr->Z2[((c * 16 + t) * 8 + warp) * 8 + g];
      const uint32_t tst = clock32();
      uint4 gb[4], ga[4], gc[4], tw[4];
      uint2 xr[2][4];
      uint2* lnp[2];
#pragma unroll
      for (int r = 0; r < 2; r++) {
        const int row = 16 * f + 2 * warp + r;
        lnp[r] = reinterpret_cast<uint2*>(&scr->LN[(rb * 8 + (g >> 2)) * 1024 + row * 8 + ((2 * (g & 3) + (t >> 1)) ^ (row & 7))]) + (t & 1);
        asm volatile("" : "+l"(lnp[r]));
      }
#pragma unroll
      for (int i = 0; i < 4; i++) {
        gc[i] = lds4(sbase + SM_FC + 2048 + i * 512 + lane * 16);
        gb[i] = lds4(TOFF(gb) + i * 512);
        ga[i] = lds4(TOFF(ga) + i * 512);
        tw[i] = lds4(TOFF(tw3) + i * 512);
        const int ch = 2 * (g + 8 * i) + (t >> 1);
#pragma unroll
        for (int r = 0; r < 2; r++) xr[r][i] = lds2(sbase + SM_X + (2 * warp + r) * 1024 + ((ch ^ ((ch >> 3) & 1)) * 16) + (t & 1) * 8);
      }
      PROF(4);
      spin_until(tst + POLL_DELAY2);
      ld_tag4_issue<256>(q, zp);
      ld_tag4_finish<256>(q, zp, tag);
      if (tid == 0) PROFP(31);
      if (lane == 0) mbar_arrive(BAR(sig, 1));
      reg_frag(q, ones);
      cdft16(q, gc, o);
#pragma unroll
      for (int vv = 0; vv < 4; vv++)
        sts4(sbase + SM_E + (((4 * vv + t) * 8 + warp) * 8 + (g ^ (warp & 6) ^ (2 * t))) * 16, o[vv].x, o[vv].y, o[vv].z, o[vv].w);
      if (tid == 0) PROFP(8);
      bar_sync(NB_CONS, 256);
      if (tid == 0) PROFP(9);
      uint32_t hv[2][8];
      const float mk = t == 0 ? 0.f : 1.f;
#pragma unroll
      for (int r = 0; r < 2; r++) {
        const int j = 2 * warp + r;
        uint4 u[2];
#pragma unroll
        for (int h = 0; h < 2; h++) u[h] = lds4(sbase + SM_E + ((j * 8 + 2 * t + h) * 8 + (g ^ (2 * t) ^ (2 * (j & 3)))) * 16);
        const uint32_t bp[4][2] = {{u[0].x, u[1].x & ones}, {u[0].y & ones, u[1].y}, {u[0].z, u[1].z & ones}, {u[0].w & ones, u[1].w}};
        float y[2][2][4];
#pragma unroll
        for (int i = 0; i < 2; i++) {
          float lo[4], hi[4], e[4];
          mma_az(lo, gb[2 * i], bp[0][0], bp[0][1]);
          mma_az(hi, gb[2 * i + 1], bp[2][0], bp[2][1]);
          mma_az(e, gb[2 * i], bp[1][0], bp[1][1]);
          mma_a(e, gb[2 * i + 1], bp[3][0], bp[3][1]);
          const uint4 &ka = tw[2 * i], &kb = tw[2 * i + 1];
          const float tr0 = fmaf(hi[0], mk, lo[0]), ti0 = fmaf(hi[2], mk, lo[2]);
          const float tr1 = lo[1] + hi[1], ti1 = lo[3] + hi[3];
          const float vr0 = tr0 * u2f(ka.x) - ti0 * u2f(ka.y), vi0 = tr0 * u2f(ka.y) + ti0 * u2f(ka.x);
          const float vr1 = tr1 * u2f(ka.z) - ti1 * u2f(ka.w), vi1 = tr1 * u2f(ka.w) + ti1 * u2f(ka.z);
          const uint32_t b0 = pack2(t == 0 ? hi[0] : vr0, vr1), b1 = pack2(t == 0 ? vr0 : vi0, vi1);
          const uint32_t b2 = pack2(e[0] * u2f(kb.x) - e[2] * u2f(kb.y), e[1] * u2f(kb.z) - e[3] * u2f(kb.w));
          const uint32_t b3 = pack2(e[0] * u2f(kb.y) + e[2] * u2f(kb.x), e[1] * u2f(kb.w) + e[3] * u2f(kb.z));
#pragma unroll
          for (int mt = 0; mt < 2; mt++) {
            mma_az(y[mt][i], ga[2 * mt], b0, b1);
            mma_a(y[mt][i], ga[2 * mt + 1], b2, b3);
          }
        }
#pragma unroll
        for (int i = 0; i < 4; i++) {
          hv[r][2 * i] = hadd2_bf16(xr[r][i].x, pack2(y[i >> 1][0][2 * (i & 1)], y[i >> 1][0][2 * (i & 1) + 1]));
          hv[r][2 * i + 1] = hadd2_bf16(xr[r][i].y, pack2(y[i >> 1][1][2 * (i & 1)], y[i >> 1][1][2 * (i & 1) + 1]));
        }
      }
      if (tid == 0 && hv[0][0] != 0x12345 && hv[1][7] != 0x12345) PROFP(10);
      float mean[2];
      uint32_t mb[2];
#pragma unroll
      for (int r = 0; r < 2; r++) {
        mean[r] = sum_groups(quad_sum(hv[r])) * (1.f / 512.f);
        mb[r] = pack2(mean[r], mean[r]);
      }
#pragma unroll
      for (int i = 0; i < 4; i++)
#pragma unroll
        for (int r = 0; r < 2; r++) {
          hv[r][2 * i] = hsub2_bf16(hv[r][2 * i], mb[r]);
          hv[r][2 * i + 1] = hsub2_bf16(hv[r][2 * i + 1], mb[r]);
          st_tag8(lnp[r] + i * 4096, hv[r][2 * i], hv[r][2 * i + 1], i == 0 ? tag : (hv[r][2 * i] & 1u));
        }
      if (tid == 0) PROFP(11);
      bar_arrive(NB_LN, 288);
      const uint32_t ones2 = ~(lds2(BAR(epoch, 0)).x >> 31);
      float rstd[2];
#pragma unroll
      for (int r = 0; r < 2; r++) {
        hv[r][0] &= ones2;
        rstd[r] = row_rstd(hv[r], mean[r] - bf_lo(mb[r]));
      }
      if (lane == 0)
        st_tag(&scr->ST[rb * 64 + 8 * f + warp], make_uint4(mb[0] << 16, __float_as_uint(rstd[0]), mb[1] << 16, __float_as_uint(rstd[1])), tag);
    }
    PROF(5);
    const int wgi = warp >> 2, wq = warp & 3;
    uint4* const pbase = &scr->P[rb * 28 * 1024 + warp * 128 + lane];
    const uint32_t a_lo0 = desc_lo(sbase + wgi * 8192, 16);
    const uint32_t ebar = lane == 0 ? BAR(empty1, 0) : RBAR(empty1, 0);
    float r0, r1;
    uint4 px[8], py[6];
    const int rh = wgi ^ kh ^ 1;
    const uint4* const psrc = &scr->P[(rb2 * 28 + 14 * kh) * 1024 + (4 * rh + wq) * 128 + lane];
    {
      float acc[128];
#pragma unroll
      for (int i = 0; i < 128; i++) acc[i] = 0.f;
      const uint32_t b_lo0 = desc_lo(sbase + 8 * SLOT, 4096);
      const uint32_t t3 = clock32();
      if (WARM) {
        wg_fence();
#pragma unroll
        for (int i = 0; i < WARM; i++) wgmma_n256(acc, desc64(a_lo0 + 6 * 1024, HI128), desc64(b_lo0, HI128));
        wg_commit();
      }
      const uint4* const ap = &scr->LN[rb * 8 * 1024 + wgi * 512 + (tid & 127)];
      uint4 av[NLL][4];
      while (clock32() - t3 < POLL_DELAY3) {}
#pragma unroll
      for (int kb = 0; kb < NLL; kb++) ld_tag4_issue<128>(av[kb], ap + kb * 1024);
      bar_sync(NB_CONS, 256);
      uint32_t slot = 2;
      auto stage_x = [&](int kb, int hh) {
        if (LAGX && hh == ((16 - LAGX) & 1) && kb == ((16 - LAGX) >> 1) && wgi == 1) bar_sync(NB_LAG, 256);
        mbar_wait(BAR(full1, 2 * kb + hh));
        const uint32_t al = a_lo0 + kb * 1024 + hh * 4, bl = b_lo0 + slot * 1024;
        wg_fence();
        wgmma_n256(acc, desc64(al, HI128), desc64(bl, HI128), (kb | hh) != 0 ? 1 : ~ones);
        wgmma_n256(acc, desc64(al + 2, HI128), desc64(bl + 128, HI128));
        wg_commit();
        if (LAGX && hh == 1 && kb == 7 && wgi == 0) bar_arrive(NB_LAG, 256);
        wg_wait<1>();
        if ((kb | hh) != 0 && lane < 2) mbar_arrive_remote(ebar + 8 * (2 * kb + hh - 1));
        if (++slot == 6) slot = 0;
      };
#pragma unroll
      for (int kb = 0; kb < NLL; kb++) {
        ld_tag4_finish<128, true>(av[kb], ap + kb * 1024, tag);
#pragma unroll
        for (int i = 0; i < 4; i++)
          sts4(sbase + kb * SLOT + wgi * 8192 + ((tid & 127) + 128 * i) * 16, av[kb][i].x, av[kb][i].y, av[kb][i].z, av[kb][i].w);
        asm volatile("fence.proxy.async.shared::cta;" ::: "memory");
        bar_sync(NB_WG + wgi, 128);
        if (kb > 0) stage_x(kb - 1, 1);
        if (kb == 0) PROF(6);
        stage_x(kb, 0);
      }
      stage_x(NLL - 1, 1);
#pragma unroll 1
      for (int kb = NLL; kb < 8; kb++) {
        mbar_wait(BAR(fullA, kb));
        stage_x(kb, 0);
        stage_x(kb, 1);
      }
      mbar_wait(BAR(sbar, 0), 0);
      r0 = __uint_as_float(lds2(sstat + (16 * warp + g) * 8).y);
      r1 = __uint_as_float(lds2(sstat + (16 * warp + g + 8) * 8).y);
      wg_wait<0>();
      if (lane < 2) mbar_arrive_remote(ebar + 8 * 15);
      PROF(7);
      make_p<8, false>(acc, r0, r1, px, pbase, 0, tag);
    }
    PROF(8);
    {
      float acc[96];
#pragma unroll
      for (int i = 0; i < 96; i++) acc[i] = 0.f;
      const uint32_t b_lo0 = desc_lo(sbase + 8 * SLOT, 2048);
      uint4* const pdst = pbase + ((7 * f + 3 * (f & 1)) >> 1) * 1024;
      auto stage_y = [&](int k) {
        if (LAGY && k == 16 - LAGY && wgi == 1) bar_sync(NB_LAG, 256);
        mbar_wait(BAR(full1, 16 + k));
        const uint32_t al = a_lo0 + (k >> 1) * 1024 + (k & 1) * 4, bl = b_lo0 + (k & 7) * 768;
        wg_fence();
        wgmma_n192(acc, desc64(al, HI128), desc64(bl, HI64));
        wgmma_n192(acc, desc64(al + 2, HI128), desc64(bl + 64, HI64));
        wg_commit();
      };
#pragma unroll
      for (int k = 0; k < 4; k++) {
        stage_y(k);
        st_tag(pdst + (k >> 1) * 1024 + (k & 1) * 64, px[2 * k], tag);
        st_tag(pdst + (k >> 1) * 1024 + (k & 1) * 64 + 32, px[2 * k + 1], tag);
        if (k == 3 && lane == 0) red_relaxed(&scr->cnt[(C_PX + rb) * 32]);
        wg_wait<1>();
        if (k != 0 && lane < 2) mbar_arrive_remote(ebar + 8 * (15 + k));
      }
#pragma unroll 1
      for (int k = 4; k < 16; k++) {
        stage_y(k);
        if (LAGY && k == 15 && wgi == 0) bar_arrive(NB_LAG, 256);
        wg_wait<1>();
        if (lane < 2) mbar_arrive_remote(ebar + 8 * (15 + k));
      }
      wg_wait<0>();
      if (lane < 2) mbar_arrive_remote(ebar + 8 * 31);
      PROF(9);
      make_p<6, true>(acc, r0, r1, py, pbase, 14 * f + ((f & 1) ? 0 : 8), tag);
      if (lane == 0) red_relaxed(&scr->cnt[(C_PY + rb) * 32 + (f >> 1)]);
    }
    PROF(10);
    {
      float acc[64];
      const uint32_t b2_lo0 = desc_lo(sbase, 8192);
      const uint32_t pa0 = sbase + (4 * rh + wq) * 2048;
      const uint32_t pbar = ebar + (uint32_t)(offsetof(Bars, emptyP) - offsetof(Bars, empty1));
      uint4 pf[3][4];
      uint32_t rdy = 0;
      mbar_wait(BAR(fullP, 0));
#pragma unroll
      for (int kk = 0; kk < 4; kk++) pf[0][kk] = lds4(pa0 + 4 * SLOT + kk * 512 + lane * 16);
#pragma unroll
      for (int s = 0; s < 14; s++) {
        uint4 (&a)[4] = pf[s % 3];
        ld_tag4_finish<32>(a, psrc + (int)((KORDER >> (4 * s)) & 15) * 1024, tag);
        if (s < 8 && lane < (s < 7 ? 2 : 1)) mbar_arrive_remote(pbar + 8 * s);
        if (s >= 2) {
          wg_wait<1>();
          if (s <= 8 && lane == 0) mbar_arrive(BAR(empty2, s - 2));
        }
        if (!rdy) {
          if (s < 13) mbar_wait(BAR(fullP, s + 1));
          mbar_wait(BAR(full2, s));
        }
        if (tid == 0) PROFP(16 + s);
        if (s == 14 - LAG2 && wgi == 1) {
          const float m0 = __uint_as_float(lds2(sstat + 1024 + (16 * wq + g) * 8).x);
          const float m1 = __uint_as_float(lds2(sstat + 1024 + (16 * wq + g + 8) * 8).x);
          const uint32_t hb = sbase + 4 * SLOT + (16 * wq + (lane & 15)) * 128;
          wg_wait<0>();
          mbar_wait(BAR(hbar, 0));
#pragma unroll
          for (int i = 0; i < 8; i++) {
            uint32_t h[4];
            asm volatile("ldmatrix.sync.aligned.m8n8.x4.shared.b16 {%0,%1,%2,%3}, [%4];"
                         : "=r"(h[0]), "=r"(h[1]), "=r"(h[2]), "=r"(h[3])
                         : "r"(hb + (i >> 2) * 8192 + (((2 * (i & 3) + (lane >> 4)) ^ (lane & 7)) * 16)) : "memory");
            const uint32_t mk = ((t & 1) == 0 && nq == 0) ? ~1u : ~0u;
#pragma unroll
            for (int e = 0; e < 4; e++) {
              acc[8 * i + 2 * e] += bf_lo(h[e] & mk) + ((e & 1) ? m1 : m0);
              acc[8 * i + 2 * e + 1] += __uint_as_float(h[e] & 0xffff0000u) + ((e & 1) ? m1 : m0);
            }
          }
          bar_sync(NB_LAG, 256);
        }
        const uint32_t bl = b2_lo0 + (uint32_t)((BSLOT >> (4 * s)) & 15) * 1024;
        wg_fence();
        if (s < 13) {
#pragma unroll
          for (int kk = 0; kk < 4; kk++)
            pf[(s + 1) % 3][kk] = lds4(pa0 + (uint32_t)((PSLOT >> (4 * (s + 1))) & 15) * SLOT + kk * 512 + lane * 16);
          rdy = mbar_test(BAR(full2, s + 1));
          if (s < 12) rdy &= mbar_test(BAR(fullP, s + 2));
        }
        if (s == 0) wgmma_rs_n128<0>(acc, a[0].x, a[0].y, a[0].z, a[0].w, desc64(bl, HI128));
        else wgmma_rs_n128<1>(acc, a[0].x, a[0].y, a[0].z, a[0].w, desc64(bl, HI128));
#pragma unroll
        for (int kk = 1; kk < 4; kk++) wgmma_rs_n128<1>(acc, a[kk].x, a[kk].y, a[kk].z, a[kk].w, desc64(bl + kk * 128, HI128));
        wg_commit();
      }
      if (wgi == 0) {
        bar_arrive(NB_LAG, 256);
        uint4* const dst = &scr->XP[(c ^ 4) * 1024 + tid];
        wg_wait<0>();
        PROF(11);
#pragma unroll
        for (int i = 0; i < 8; i++)
          st_tag(dst + i * 128, make_uint4(pack2(acc[8 * i], acc[8 * i + 1]), pack2(acc[8 * i + 2], acc[8 * i + 3]),
                                           pack2(acc[8 * i + 4], acc[8 * i + 5]), pack2(acc[8 * i + 6], acc[8 * i + 7])), tag);
      } else {
        uint4 pv[2][4];
        const uint4* const xsrc = &scr->XP[c * 1024 + (tid & 127)];
        ld_tag4_issue<128>(pv[0], xsrc);
        ld_tag4_issue<128>(pv[1], xsrc + 512);
        wg_wait<0>();
        PROF(11);
        uint32_t w[32];
#pragma unroll
        for (int i = 0; i < 32; i++) w[i] = pack2(acc[2 * i], acc[2 * i + 1]);
        ld_tag4_finish<128>(pv[0], xsrc, tag);
        ld_tag4_finish<128>(pv[1], xsrc + 512, tag);
#pragma unroll
        for (int i = 0; i < 8; i++) {
          const uint4& p = pv[i >> 2][i & 3];
          asm volatile("stmatrix.sync.aligned.m8n8.x4.shared.b16 [%0], {%1,%2,%3,%4};"
                       ::"r"(pa0 + (9 + ((lane >> 3) & 1)) * SLOT + (lane & 7) * 256 + (((2 * i + (lane >> 4)) ^ (lane & 7)) * 16)),
                         "r"(hadd2_bf16(w[4 * i], p.x)), "r"(hadd2_bf16(w[4 * i + 1], p.y)), "r"(hadd2_bf16(w[4 * i + 2], p.z)),
                         "r"(hadd2_bf16(w[4 * i + 3], p.w)) : "memory");
        }
        __syncwarp();
        uint4* const dst = reinterpret_cast<uint4*>(out) + (16 * (c >> 4) + 2 * (4 * rh + wq) + (rb2 & 1) + 128 * (lane >> 4)) * 64 + nq * 16 + (lane & 15);
#pragma unroll
        for (int i = 0; i < 8; i++) {
          const int r = 2 * (i & 3) + (lane >> 4);
          dst[i * 256 * 64] = lds4(pa0 + (9 + (i >> 2)) * SLOT + r * 256 + (((lane & 15) ^ r) * 16));
        }
      }
      PROF(12);
      PROFG(15);
    }
  }
#undef BAR
#undef TOFF
#undef RBAR
}

typedef CUresult (*EncodeFn)(CUtensorMap*, CUtensorMapDataType, cuuint32_t, void*, const cuuint64_t*, const cuuint64_t*,
                             const cuuint32_t*, const cuuint32_t*, CUtensorMapInterleave, CUtensorMapSwizzle,
                             CUtensorMapL2promotion, CUtensorMapFloatOOBfill);

}

extern "C" void kernel_launch(void* const* d_in, const int* in_sizes, int n_in, void* d_out, int out_size) {
  (void)in_sizes; (void)n_in; (void)out_size;
  static EncodeFn encode = nullptr;
  static void *tab = nullptr, *scr = nullptr;
  if (!encode) {
    void* fn = nullptr;
    cudaDriverEntryPointQueryResult qr;
    cudaGetDriverEntryPoint("cuTensorMapEncodeTiled", &fn, cudaEnableDefault, &qr);
    encode = (EncodeFn)fn;
    cudaGetSymbolAddress(&tab, g_tab);
    cudaGetSymbolAddress(&scr, g_scr);
    cudaFuncSetAttribute(fused_kernel, cudaFuncAttributeMaxDynamicSharedMemorySize, SMEM_BYTES);
  }
  CUtensorMap tmGX, tmUX, tmGY, tmUY, tmD, tmWR, tmWI;
  const cuuint32_t es[5] = {1, 1, 1, 1, 1};
  auto enc = [&](CUtensorMap* m, void* p, int rank, const cuuint64_t* gd, const cuuint64_t* gs, const cuuint32_t* bd,
                 CUtensorMapSwizzle sw, CUtensorMapL2promotion pr) {
    encode(m, CU_TENSOR_MAP_DATA_TYPE_BFLOAT16, rank, p, gd, gs, bd, es, CU_TENSOR_MAP_INTERLEAVE_NONE, sw, pr,
           CU_TENSOR_MAP_FLOAT_OOB_FILL_NONE);
  };
  {
    const cuuint64_t gd[3] = {64, 512, 28}, gs[2] = {3584, 128};
    const cuuint32_t bd[3] = {64, 32, 2};
    enc(&tmGX, d_in[4], 3, gd, gs, bd, CU_TENSOR_MAP_SWIZZLE_128B, CU_TENSOR_MAP_L2_PROMOTION_L2_256B);
    enc(&tmUX, d_in[5], 3, gd, gs, bd, CU_TENSOR_MAP_SWIZZLE_128B, CU_TENSOR_MAP_L2_PROMOTION_L2_256B);
  }
  {
    const cuuint64_t gd[3] = {32, 512, 56}, gs[2] = {3584, 64};
    const cuuint32_t bd[3] = {32, 32, 3};
    enc(&tmGY, d_in[4], 3, gd, gs, bd, CU_TENSOR_MAP_SWIZZLE_64B, CU_TENSOR_MAP_L2_PROMOTION_L2_128B);
    enc(&tmUY, d_in[5], 3, gd, gs, bd, CU_TENSOR_MAP_SWIZZLE_64B, CU_TENSOR_MAP_L2_PROMOTION_L2_128B);
  }
  {
    const cuuint64_t gd[3] = {64, 1792, 8}, gs[2] = {1024, 128};
    const cuuint32_t bd[3] = {64, 64, 2};
    enc(&tmD, d_in[6], 3, gd, gs, bd, CU_TENSOR_MAP_SWIZZLE_128B, CU_TENSOR_MAP_L2_PROMOTION_L2_256B);
  }
  {
    const cuuint64_t gd[3] = {4112, 8, 16}, gs[2] = {16 * 8224, 8224};
    const cuuint32_t bd[3] = {40, 8, 16};
    enc(&tmWR, d_in[1], 3, gd, gs, bd, CU_TENSOR_MAP_SWIZZLE_NONE, CU_TENSOR_MAP_L2_PROMOTION_NONE);
    enc(&tmWI, d_in[2], 3, gd, gs, bd, CU_TENSOR_MAP_SWIZZLE_NONE, CU_TENSOR_MAP_L2_PROMOTION_NONE);
  }
  fused_kernel<<<NCTA, NTHREADS, SMEM_BYTES>>>((const __nv_bfloat16*)d_in[0], (const Tables*)tab, (Scratch*)scr,
                                               (__nv_bfloat16*)d_out, (const char*)d_in[4], (const char*)d_in[5],
                                               (const char*)d_in[6], tmWR, tmWI, tmGX, tmUX, tmGY, tmUY, tmD);
}
```

```cpp
#include <cuda_runtime.h>
#include <cuda_bf16.h>
#include <cuda.h>
#include <stdint.h>

namespace {

constexpr int NCTA = 128;
constexpr int NTHREADS = 384;
constexpr int SLOT = 16384;
constexpr int SMEM_BYTES = 14 * SLOT + 3072;
constexpr int SPIN_LIMIT = 1 << 22;

struct Scratch {
  uint4 Z1[128 * 1024];
  uint4 Z2[128 * 1024];
  uint4 LN[16 * 8 * 1024];
  uint4 P[16 * 28 * 1024];
  uint4 XP[128 * 1024];
  uint4 ST[1024];
  unsigned cnt[64 * 32];
};
__device__ __align__(1024) Scratch g_scr;
#define PROF(i)
#define PROFP(i)
#define PROFG(i)

constexpr double ccos(int i, int n) {
  i &= n - 1;
  if (i > n / 2) i = n - i;
  if (4 * i == n) return 0.0;
  const bool neg = 4 * i > n;
  if (neg) i = n / 2 - i;
  const double a = 6.283185307179586476925 * i / n, a2 = a * a;
  double term = 1.0, sum = 1.0;
  for (int k = 1; k < 14; k++) { term *= -a2 / ((2 * k - 1) * (2 * k)); sum += term; }
  return neg ? -sum : sum;
}
constexpr double csin(int i, int n) { return ccos(i - n / 4, n); }
constexpr unsigned fbits(double v, int mant) {
  if (v == 0.0) return 0;
  const unsigned sg = v < 0 ? 1u : 0u;
  if (v < 0) v = -v;
  int e = 127;
  while (v < 1.0) { v *= 2.0; e--; }
  const unsigned m = (unsigned)((v - 1.0) * (double)(1u << mant) + 0.5);
  return (sg << (8 + mant)) + ((unsigned)e << mant) + m;
}
constexpr unsigned pkb(double lo, double hi) { return fbits(lo, 7) | (fbits(hi, 7) << 16); }
constexpr double fa_elem(int mt, int r, int n1) {
  const int k1 = 8 * mt + (r & 7);
  return r < 8 ? ccos(k1 * n1, 32) : k1 == 0 ? ccos(16 * n1, 32) : -csin(k1 * n1, 32);
}
constexpr unsigned cfrag_c(int idx, int n, int ri, double s = 1.0) {
  return ri ? pkb(-s * csin(idx, n), s * ccos(idx, n)) : pkb(s * ccos(idx, n), s * csin(idx, n));
}
struct Tables {
  unsigned fa[4][32][4];
  unsigned fb[4][32][4];
  unsigned tw1[6][32][4];
  unsigned f2[8][4][32][4];
  unsigned g2[8][4][32][4];
  unsigned gb[4][32][4];
  unsigned ga[4][32][4];
  unsigned tw3[4][32][4];
  unsigned f8[32][4], g8[32][4];
};
constexpr int T1_BYTES = 7168, T2_BYTES = 39936;
static_assert(sizeof(Tables) == T1_BYTES + T2_BYTES, "table size");
constexpr Tables make_tables() {
  Tables T = {};
  for (int l = 0; l < 32; l++) {
    const int g = l >> 2, t = l & 3;
    for (int a = 0; a < 2; a++)
      for (int b = 0; b < 2; b++) {
        for (int r = 0; r < 4; r++) {
          const int row = g + 8 * (r & 1), col = 2 * t + 8 * (r >> 1);
          T.fa[2 * a + b][l][r] = pkb(fa_elem(a, row, 16 * b + col), fa_elem(a, row, 16 * b + col + 1));
          T.ga[2 * a + b][l][r] = pkb(fa_elem(b, col, 16 * a + row), fa_elem(b, col + 1, 16 * a + row));
        }
        const double sg = b ? -1.0 : 1.0;
        for (int h = 0; h < 2; h++) {
          const int ri = g & 1, m = 2 * (g >> 1) + h, k2 = b ? 15 - m : m;
          const int pa = (8 * a + 2 * t) * k2, pb = (8 * a + 2 * t + 1) * k2;
          T.fb[2 * a + b][l][2 * h] = ri == 0 ? pkb(ccos(pa, 16), ccos(pb, 16)) : pkb(-sg * csin(pa, 16), -sg * csin(pb, 16));
          T.fb[2 * a + b][l][2 * h + 1] = ri == 0 ? pkb(csin(pa, 16), csin(pb, 16)) : pkb(sg * ccos(pa, 16), sg * ccos(pb, 16));
        }
        const int n2 = 4 * (g >> 1) + 2 * a + (g & 1);
        for (int h = 0; h < 2; h++) {
          const int p = n2 * (b ? 15 - 2 * t - h : 2 * t + h);
          T.gb[2 * a + b][l][2 * h] = pkb(ccos(p, 16), -sg * csin(p, 16));
          T.gb[2 * a + b][l][2 * h + 1] = pkb(csin(p, 16), sg * ccos(p, 16));
          const int k1 = 8 * b + 2 * t + h, q = n2 * (k1 == 0 ? 16 : k1);
          T.tw3[2 * a + b][l][2 * h] = fbits(ccos(q, 512), 23);
          T.tw3[2 * a + b][l][2 * h + 1] = fbits(csin(q, 512), 23);
        }
        const int p = (8 * a + 2 * t + b) * (g == 0 ? 16 : g);
        T.tw1[2 * a + b][l][0] = fbits(g == 0 ? 0.0 : ccos(p, 512), 23);
        T.tw1[2 * a + b][l][1] = fbits(g == 0 ? ccos(p, 512) : csin(p, 512), 23);
        T.tw1[2 * a + b][l][2] = fbits(g == 0 ? 0.0 : -csin(p, 512), 23);
        T.tw1[2 * a + b][l][3] = fbits(g == 0 ? -csin(p, 512) : ccos(p, 512), 23);
        T.tw1[4 + a][l][2 * b] = fbits(ccos((8 * a + 2 * t + b) * (g + 8), 512), 23);
        T.tw1[4 + a][l][2 * b + 1] = fbits(csin((8 * a + 2 * t + b) * (g + 8), 512), 23);
      }
    for (int i = 0; i < 4; i++) {
      const int p8 = (t + 4 * (i & 1)) * (4 * (i >> 1) + (g >> 1));
      T.f8[l][i] = cfrag_c(p8, 8, g & 1);
      T.g8[l][i] = cfrag_c(-p8, 8, g & 1, 1.0 / (1 << 19));
    }
    for (int w = 0; w < 8; w++)
      for (int i = 0; i < 16; i++) {
        const int kidx = t + 4 * (i & 1) + 8 * (i >> 3), nidx = 4 * ((i >> 1) & 3) + (g >> 1);
        T.f2[w][i >> 2][l][i & 3] = cfrag_c((8 * kidx + w) * nidx, 128, g & 1);
        T.g2[w][i >> 2][l][i & 3] = cfrag_c(-(8 * nidx + w) * kidx, 128, g & 1);
      }
  }
  return T;
}
__device__ const __align__(128) Tables g_tab = make_tables();

__device__ __forceinline__ void die() { asm volatile("st.global.u32 [%0], %1;" ::"l"(0ull), "r"(0) : "memory"); }
__device__ __forceinline__ uint32_t s2u(const void* p) { return (uint32_t)__cvta_generic_to_shared(p); }
__device__ __forceinline__ void mbar_init(uint32_t b, int c) { asm volatile("mbarrier.init.shared::cta.b64 [%0], %1;" ::"r"(b), "r"(c)); }
__device__ __forceinline__ void mbar_expect(uint32_t b, int bytes) {
  asm volatile("mbarrier.arrive.expect_tx.shared::cta.b64 _, [%0], %1;" ::"r"(b), "r"(bytes) : "memory");
}
__device__ __forceinline__ void mbar_arrive(uint32_t b) { asm volatile("mbarrier.arrive.shared::cta.b64 _, [%0];" ::"r"(b) : "memory"); }
__device__ __forceinline__ uint32_t mbar_try(uint32_t b, uint32_t parity) {
  uint32_t ok;
  asm volatile("{.reg .pred p; mbarrier.try_wait.parity.shared::cta.b64 p, [%1], %2; selp.u32 %0,1,0,p;}"
               : "=r"(ok) : "r"(b), "r"(parity) : "memory");
  return ok;
}
__device__ __forceinline__ uint32_t mbar_test(uint32_t b) {
  uint32_t ok;
  asm volatile("{.reg .pred p; mbarrier.test_wait.parity.shared::cta.b64 p, [%1], 0; selp.u32 %0,1,0,p;}" : "=r"(ok) : "r"(b) : "memory");
  return ok;
}
__device__ __forceinline__ void mbar_wait(uint32_t b, uint32_t parity = 0) {
  int it = 0;
#pragma unroll 1
  while (!mbar_try(b, parity))
    if (++it > SPIN_LIMIT) { die(); break; }
}
__device__ __forceinline__ void bar_sync(int id, int n) { asm volatile("bar.sync %0, %1;" ::"r"(id), "r"(n) : "memory"); }
__device__ __forceinline__ void bar_arrive(int id, int n) { asm volatile("bar.arrive %0, %1;" ::"r"(id), "r"(n) : "memory"); }
__device__ __forceinline__ void red_release(unsigned* p) { asm volatile("red.release.gpu.global.add.u32 [%0], 1;" ::"l"(p) : "memory"); }
__device__ __forceinline__ void red_relaxed(unsigned* p) { asm volatile("red.relaxed.gpu.global.add.u32 [%0], 1;" ::"l"(p) : "memory"); }
__device__ __forceinline__ unsigned ld_acquire(const unsigned* p) {
  unsigned v;
  asm volatile("ld.acquire.gpu.global.u32 %0, [%1];" : "=r"(v) : "l"(p) : "memory");
  return v;
}
__device__ __forceinline__ unsigned ld_relaxed(const unsigned* p) {
  unsigned v;
  asm volatile("ld.relaxed.gpu.global.u32 %0, [%1];" : "=r"(v) : "l"(p) : "memory");
  return v;
}
__device__ __forceinline__ void wait_counter(const unsigned* p, unsigned target) {
  int it = 0;
  while ((int)(ld_acquire(p) - target) < 0)
    if (++it > SPIN_LIMIT) { die(); break; }
}
__device__ __forceinline__ void sts4(uint32_t a, uint32_t x, uint32_t y, uint32_t z, uint32_t w) {
  asm volatile("st.shared.v4.u32 [%0], {%1,%2,%3,%4};" ::"r"(a), "r"(x), "r"(y), "r"(z), "r"(w) : "memory");
}
__device__ __forceinline__ uint4 lds4(uint32_t a) {
  uint4 v;
  asm volatile("ld.shared.v4.u32 {%0,%1,%2,%3}, [%4];" : "=r"(v.x), "=r"(v.y), "=r"(v.z), "=r"(v.w) : "r"(a) : "memory");
  return v;
}
__device__ __forceinline__ uint32_t pack2(float lo, float hi) {
  uint32_t r;
  asm("cvt.rn.bf16x2.f32 %0, %1, %2;" : "=r"(r) : "f"(hi), "f"(lo));
  return r;
}
__device__ __forceinline__ float bf_lo(uint32_t v) { return __uint_as_float(v << 16); }
__device__ __forceinline__ uint32_t hadd2_bf16(uint32_t a, uint32_t b) {
  uint32_t r;
  asm("add.rn.bf16x2 %0, %1, %2;" : "=r"(r) : "r"(a), "r"(b));
  return r;
}
__device__ __forceinline__ void mma16816(float (&d)[4], uint32_t a0, uint32_t a1, uint32_t a2, uint32_t a3, uint32_t b0, uint32_t b1) {
  asm("mma.sync.aligned.m16n8k16.row.col.f32.bf16.bf16.f32 {%0,%1,%2,%3}, {%4,%5,%6,%7}, {%8,%9}, {%0,%1,%2,%3};"
      : "+f"(d[0]), "+f"(d[1]), "+f"(d[2]), "+f"(d[3])
      : "r"(a0), "r"(a1), "r"(a2), "r"(a3), "r"(b0), "r"(b1));
}
__device__ __forceinline__ void mma16816_z(float (&d)[4], uint32_t a0, uint32_t a1, uint32_t a2, uint32_t a3, uint32_t b0, uint32_t b1) {
  asm("{.reg .f32 z; mov.f32 z, 0f00000000;\n"
      "mma.sync.aligned.m16n8k16.row.col.f32.bf16.bf16.f32 {%0,%1,%2,%3}, {%4,%5,%6,%7}, {%8,%9}, {z,z,z,z};}"
      : "=f"(d[0]), "=f"(d[1]), "=f"(d[2]), "=f"(d[3])
      : "r"(a0), "r"(a1), "r"(a2), "r"(a3), "r"(b0), "r"(b1));
}
template <int N>
__device__ __forceinline__ void cs_frac(int idx, float& c, float& s) {
  int i = ((idx + N / 2) & (N - 1)) - N / 2;
  float a = (float)i * (6.283185307179586f / N);
  c = __cosf(a);
  s = __sinf(a);
}
template <int N>
__device__ __forceinline__ uint32_t cfrag(int idx, int ri) {
  float c, s;
  cs_frac<N>(idx, c, s);
  return ri ? pack2(-s, c) : pack2(c, s);
}
__device__ __forceinline__ uint32_t word(const uint4& v, int e) { return e == 0 ? v.x : e == 1 ? v.y : e == 2 ? v.z : v.w; }
__device__ __forceinline__ void cdft16(const uint4 (&A)[4], const uint4 (&F)[4], uint4 (&o)[4]) {
  float acc[2][4][4];
#pragma unroll
  for (int ks = 0; ks < 2; ks++)
#pragma unroll
    for (int p = 0; p < 2; p++)
#pragma unroll
      for (int v = 0; v < 4; v++) {
        const uint4& a = A[2 * ks + p];
        const uint32_t b0 = word(F[ks * 2 + (v >> 1)], (v & 1) * 2), b1 = word(F[ks * 2 + (v >> 1)], (v & 1) * 2 + 1);
        if (ks == 0) mma16816_z(acc[p][v], a.x, a.y, a.z, a.w, b0, b1);
        else mma16816(acc[p][v], a.x, a.y, a.z, a.w, b0, b1);
      }
#pragma unroll
  for (int v = 0; v < 4; v++)
    o[v] = make_uint4(pack2(acc[0][v][0], acc[0][v][1]), pack2(acc[0][v][2], acc[0][v][3]),
                      pack2(acc[1][v][0], acc[1][v][1]), pack2(acc[1][v][2], acc[1][v][3]));
}
__device__ __forceinline__ void lds_frag(uint4& f0, uint4& f1, uint32_t a0, uint32_t a1) {
  asm volatile("ld.volatile.shared.v2.u32 {%0,%1}, [%8]; ld.volatile.shared.v2.u32 {%2,%3}, [%9];\n"
               "ld.volatile.shared.v2.u32 {%4,%5}, [%8+8]; ld.volatile.shared.v2.u32 {%6,%7}, [%9+8];"
               : "=r"(f0.x), "=r"(f0.y), "=r"(f0.z), "=r"(f0.w), "=r"(f1.x), "=r"(f1.y), "=r"(f1.z), "=r"(f1.w) : "r"(a0), "r"(a1) : "memory");
}
__device__ __forceinline__ void reg_frag(uint4 (&q)[4], uint32_t ones) {
#pragma unroll
  for (int ks = 0; ks < 2; ks++) {
    const uint4 a = q[2 * ks], b = q[2 * ks + 1];
    q[2 * ks] = make_uint4(a.x, a.y, b.x & ones, b.y & ones);
    q[2 * ks + 1] = make_uint4(a.z & ones, a.w & ones, b.z, b.w);
  }
}
__device__ __forceinline__ void st_tag(uint4* p, const uint4& v, uint32_t tag) {
  asm volatile("st.relaxed.gpu.global.v4.b32 [%0], {%1,%2,%3,%4};"
               ::"l"(p), "r"((v.x & ~1u) | tag), "r"(v.y), "r"(v.z), "r"(v.w) : "memory");
}
__device__ __forceinline__ void st_tag8(void* p, uint32_t x, uint32_t y, uint32_t tag) {
  asm volatile("st.relaxed.gpu.global.v2.b32 [%0], {%1,%2};" ::"l"(p), "r"((x & ~1u) | tag), "r"(y) : "memory");
}
__device__ __forceinline__ uint4 ld_b128(const uint4* p) {
  uint4 v;
  asm volatile("ld.relaxed.gpu.global.v4.b32 {%0,%1,%2,%3}, [%4];"
               : "=r"(v.x), "=r"(v.y), "=r"(v.z), "=r"(v.w) : "l"(p) : "memory");
  return v;
}
template <int STRIDE>
__device__ __forceinline__ void ld_tag4_issue(uint4 (&q)[4], const uint4* p) {
#pragma unroll
  for (int i = 0; i < 4; i++) q[i] = ld_b128(p + i * STRIDE);
}
template <int STRIDE, bool HALVES = false>
__device__ __forceinline__ void ld_tag4_finish(uint4 (&q)[4], const uint4* p, uint32_t tag) {
  int it = 0;
#pragma unroll 1
  while (__any_sync(0xffffffffu, ((q[0].x ^ tag) | (q[1].x ^ tag) | (q[2].x ^ tag) | (q[3].x ^ tag) |
                                  (HALVES ? (q[0].z ^ tag) | (q[1].z ^ tag) | (q[2].z ^ tag) | (q[3].z ^ tag) : 0u)) & 1u)) {
    ld_tag4_issue<STRIDE>(q, p);
    if (++it > SPIN_LIMIT) { die(); break; }
  }
#pragma unroll
  for (int i = 0; i < 4; i++) {
    asm volatile("and.b32 %0, %0, 0xfffffffe;" : "+r"(q[i].x));
    if (HALVES) q[i].z &= ~1u;
  }
}
__device__ __forceinline__ float quad_sum(const uint32_t (&a)[8]) {
  float d[4];
  mma16816_z(d, a[0], a[1], a[2], a[3], 0x3f803f80u, 0x3f803f80u);
  mma16816(d, a[4], a[5], a[6], a[7], 0x3f803f80u, 0x3f803f80u);
  return d[0] + d[2];
}
__device__ __forceinline__ float sum_groups(float v) {
  v += __shfl_xor_sync(0xffffffffu, v, 4);
  v += __shfl_xor_sync(0xffffffffu, v, 8);
  v += __shfl_xor_sync(0xffffffffu, v, 16);
  return v;
}
__device__ __forceinline__ uint32_t hsub2_bf16(uint32_t a, uint32_t b) {
  uint32_t r;
  asm("sub.rn.bf16x2 %0, %1, %2;" : "=r"(r) : "r"(a), "r"(b));
  return r;
}
__device__ __forceinline__ float row_rstd(const uint32_t (&c)[8], float delta) {
  uint32_t s[8];
#pragma unroll
  for (int i = 0; i < 8; i++) asm("mul.rn.bf16x2 %0, %1, %1;" : "=r"(s[i]) : "r"(c[i]));
  return rsqrtf(fmaxf(fmaf(-delta, delta, sum_groups(quad_sum(s)) * (1.f / 512.f)), 0.f) + 1e-5f);
}
__device__ __forceinline__ uint64_t desc64(uint32_t lo, uint32_t hi) {
  uint64_t d;
  asm("mov.b64 %0, {%1, %2};" : "=l"(d) : "r"(lo), "r"(hi));
  return d;
}
constexpr uint32_t desc_hi(uint32_t sbo, uint32_t swz) { return (sbo >> 4) | (swz << 30); }
__device__ __forceinline__ uint32_t desc_lo(uint32_t addr, uint32_t lbo) { return ((addr & 0x3FFFF) >> 4) | ((lbo >> 4) << 16); }
__device__ __forceinline__ void cp_async16(uint32_t dst, const void* src) {
  asm volatile("cp.async.cg.shared.global [%0], [%1], 16;" ::"r"(dst), "l"(src) : "memory");
}
__device__ __forceinline__ uint2 lds2(uint32_t a) {
  uint2 v;
  asm volatile("ld.shared.v2.u32 {%0,%1}, [%2];" : "=r"(v.x), "=r"(v.y) : "r"(a) : "memory");
  return v;
}
__device__ __forceinline__ uint32_t lds_u16(uint32_t a) {
  uint16_t v;
  asm volatile("ld.shared.u16 %0, [%1];" : "=h"(v) : "r"(a) : "memory");
  return v;
}
__device__ __forceinline__ void wg_fence() { asm volatile("wgmma.fence.sync.aligned;" ::: "memory"); }
__device__ __forceinline__ void wg_commit() { asm volatile("wgmma.commit_group.sync.aligned;" ::: "memory"); }
template <int N>
__device__ __forceinline__ void wg_wait() { asm volatile("wgmma.wait_group.sync.aligned %0;" ::"n"(N) : "memory"); }
__device__ __forceinline__ void bulk_load(uint32_t dst, const void* src, int bytes, uint32_t bar) {
  asm volatile("cp.async.bulk.shared::cluster.global.mbarrier::complete_tx::bytes [%0], [%1], %2, [%3];"
               ::"r"(dst), "l"(src), "r"(bytes), "r"(bar) : "memory");
}
__device__ __forceinline__ void bulk_load_mc(uint32_t dst, const void* src, int bytes, uint32_t bar) {
  asm volatile("cp.async.bulk.shared::cluster.global.mbarrier::complete_tx::bytes.multicast::cluster [%0], [%1], %2, [%3], %4;"
               ::"r"(dst), "l"(src), "r"(bytes), "r"(bar), "h"((uint16_t)3) : "memory");
}
__device__ __forceinline__ void tma3(uint32_t dst, const CUtensorMap* tm, uint32_t bar, int c0, int c1, int c2) {
  asm volatile("cp.async.bulk.tensor.3d.shared::cluster.global.mbarrier::complete_tx::bytes [%0], [%1, {%3,%4,%5}], [%2];"
               ::"r"(dst), "l"(tm), "r"(bar), "r"(c0), "r"(c1), "r"(c2) : "memory");
}
__device__ __forceinline__ void tma3_mc(uint32_t dst, const CUtensorMap* tm, uint32_t bar, int c1, int c2) {
  asm volatile("cp.async.bulk.tensor.3d.shared::cluster.global.mbarrier::complete_tx::bytes.multicast::cluster [%0], [%1, {%3,%4,%5}], [%2], %6;"
               ::"r"(dst), "l"(tm), "r"(bar), "r"(0), "r"(c1), "r"(c2), "h"((uint16_t)3) : "memory");
}
__device__ __forceinline__ void mbar_arrive_remote(uint32_t rb) {
  asm volatile("mbarrier.arrive.shared::cluster.b64 _, [%0];" ::"r"(rb) : "memory");
}
__device__ __forceinline__ uint4 ldg_ca4(const void* p) {
  uint4 v;
  asm volatile("ld.global.ca.v4.u32 {%0,%1,%2,%3}, [%4];" : "=r"(v.x), "=r"(v.y), "=r"(v.z), "=r"(v.w) : "l"(p) : "memory");
  return v;
}
__device__ __forceinline__ float u2f(uint32_t v) { return __uint_as_float(v); }
__device__ __forceinline__ void mma_az(float (&d)[4], const uint4& a, uint32_t b0, uint32_t b1) { mma16816_z(d, a.x, a.y, a.z, a.w, b0, b1); }
__device__ __forceinline__ void mma_a(float (&d)[4], const uint4& a, uint32_t b0, uint32_t b1) { mma16816(d, a.x, a.y, a.z, a.w, b0, b1); }
__device__ __forceinline__ uint32_t clock32() {
  uint32_t v;
  asm volatile("mov.u32 %0, %%clock;" : "=r"(v) :: "memory");
  return v;
}
__device__ __forceinline__ float swiglu(float g, float u, float r) {
  float hg = (0.5f * r) * g, th;
  asm("tanh.approx.f32 %0, %1;" : "=f"(th) : "f"(hg));
  return fmaf(hg, th, hg) * (r * u);
}
__device__ __forceinline__ void l2_prefetch(const void* p, int bytes) {
  asm volatile("cp.async.bulk.prefetch.L2.global [%0], %1;" ::"l"(p), "r"(bytes) : "memory");
}

__device__ __forceinline__ void wgmma_n256(float (&d)[128], uint64_t da, uint64_t db, int sd = 1) {
  asm volatile("{.reg .pred p; setp.ne.b32 p, %130, 0;\n"
      "wgmma.mma_async.sync.aligned.m64n256k16.f32.bf16.bf16 {"
      "%0,%1,%2,%3,%4,%5,%6,%7,%8,%9,%10,%11,%12,%13,%14,%15,"
      "%16,%17,%18,%19,%20,%21,%22,%23,%24,%25,%26,%27,%28,%29,%30,%31,"
      "%32,%33,%34,%35,%36,%37,%38,%39,%40,%41,%42,%43,%44,%45,%46,%47,"
      "%48,%49,%50,%51,%52,%53,%54,%55,%56,%57,%58,%59,%60,%61,%62,%63,"
      "%64,%65,%66,%67,%68,%69,%70,%71,%72,%73,%74,%75,%76,%77,%78,%79,"
      "%80,%81,%82,%83,%84,%85,%86,%87,%88,%89,%90,%91,%92,%93,%94,%95,"
      "%96,%97,%98,%99,%100,%101,%102,%103,%104,%105,%106,%107,%108,%109,%110,%111,"
      "%112,%113,%114,%115,%116,%117,%118,%119,%120,%121,%122,%123,%124,%125,%126,%127"
      "}, %128, %129, p, 1, 1, 0, 1;}\n"
      : "+f"(d[0]),"+f"(d[1]),"+f"(d[2]),"+f"(d[3]),"+f"(d[4]),"+f"(d[5]),"+f"(d[6]),"+f"(d[7]),
        "+f"(d[8]),"+f"(d[9]),"+f"(d[10]),"+f"(d[11]),"+f"(d[12]),"+f"(d[13]),"+f"(d[14]),"+f"(d[15]),
        "+f"(d[16]),"+f"(d[17]),"+f"(d[18]),"+f"(d[19]),"+f"(d[20]),"+f"(d[21]),"+f"(d[22]),"+f"(d[23]),
        "+f"(d[24]),"+f"(d[25]),"+f"(d[26]),"+f"(d[27]),"+f"(d[28]),"+f"(d[29]),"+f"(d[30]),"+f"(d[31]),
        "+f"(d[32]),"+f"(d[33]),"+f"(d[34]),"+f"(d[35]),"+f"(d[36]),"+f"(d[37]),"+f"(d[38]),"+f"(d[39]),
        "+f"(d[40]),"+f"(d[41]),"+f"(d[42]),"+f"(d[43]),"+f"(d[44]),"+f"(d[45]),"+f"(d[46]),"+f"(d[47]),
        "+f"(d[48]),"+f"(d[49]),"+f"(d[50]),"+f"(d[51]),"+f"(d[52]),"+f"(d[53]),"+f"(d[54]),"+f"(d[55]),
        "+f"(d[56]),"+f"(d[57]),"+f"(d[58]),"+f"(d[59]),"+f"(d[60]),"+f"(d[61]),"+f"(d[62]),"+f"(d[63]),
        "+f"(d[64]),"+f"(d[65]),"+f"(d[66]),"+f"(d[67]),"+f"(d[68]),"+f"(d[69]),"+f"(d[70]),"+f"(d[71]),
        "+f"(d[72]),"+f"(d[73]),"+f"(d[74]),"+f"(d[75]),"+f"(d[76]),"+f"(d[77]),"+f"(d[78]),"+f"(d[79]),
        "+f"(d[80]),"+f"(d[81]),"+f"(d[82]),"+f"(d[83]),"+f"(d[84]),"+f"(d[85]),"+f"(d[86]),"+f"(d[87]),
        "+f"(d[88]),"+f"(d[89]),"+f"(d[90]),"+f"(d[91]),"+f"(d[92]),"+f"(d[93]),"+f"(d[94]),"+f"(d[95]),
        "+f"(d[96]),"+f"(d[97]),"+f"(d[98]),"+f"(d[99]),"+f"(d[100]),"+f"(d[101]),"+f"(d[102]),"+f"(d[103]),
        "+f"(d[104]),"+f"(d[105]),"+f"(d[106]),"+f"(d[107]),"+f"(d[108]),"+f"(d[109]),"+f"(d[110]),"+f"(d[111]),
        "+f"(d[112]),"+f"(d[113]),"+f"(d[114]),"+f"(d[115]),"+f"(d[116]),"+f"(d[117]),"+f"(d[118]),"+f"(d[119]),
        "+f"(d[120]),"+f"(d[121]),"+f"(d[122]),"+f"(d[123]),"+f"(d[124]),"+f"(d[125]),"+f"(d[126]),"+f"(d[127])
      : "l"(da), "l"(db), "r"(sd));
}
__device__ __forceinline__ void wgmma_n192(float (&d)[96], uint64_t da, uint64_t db) {
  asm volatile("wgmma.mma_async.sync.aligned.m64n192k16.f32.bf16.bf16 {"
      "%0,%1,%2,%3,%4,%5,%6,%7,%8,%9,%10,%11,%12,%13,%14,%15,"
      "%16,%17,%18,%19,%20,%21,%22,%23,%24,%25,%26,%27,%28,%29,%30,%31,"
      "%32,%33,%34,%35,%36,%37,%38,%39,%40,%41,%42,%43,%44,%45,%46,%47,"
      "%48,%49,%50,%51,%52,%53,%54,%55,%56,%57,%58,%59,%60,%61,%62,%63,"
      "%64,%65,%66,%67,%68,%69,%70,%71,%72,%73,%74,%75,%76,%77,%78,%79,"
      "%80,%81,%82,%83,%84,%85,%86,%87,%88,%89,%90,%91,%92,%93,%94,%95"
      "}, %96, %97, 1, 1, 1, 0, 1;\n"
      : "+f"(d[0]),"+f"(d[1]),"+f"(d[2]),"+f"(d[3]),"+f"(d[4]),"+f"(d[5]),"+f"(d[6]),"+f"(d[7]),
        "+f"(d[8]),"+f"(d[9]),"+f"(d[10]),"+f"(d[11]),"+f"(d[12]),"+f"(d[13]),"+f"(d[14]),"+f"(d[15]),
        "+f"(d[16]),"+f"(d[17]),"+f"(d[18]),"+f"(d[19]),"+f"(d[20]),"+f"(d[21]),"+f"(d[22]),"+f"(d[23]),
        "+f"(d[24]),"+f"(d[25]),"+f"(d[26]),"+f"(d[27]),"+f"(d[28]),"+f"(d[29]),"+f"(d[30]),"+f"(d[31]),
        "+f"(d[32]),"+f"(d[33]),"+f"(d[34]),"+f"(d[35]),"+f"(d[36]),"+f"(d[37]),"+f"(d[38]),"+f"(d[39]),
        "+f"(d[40]),"+f"(d[41]),"+f"(d[42]),"+f"(d[43]),"+f"(d[44]),"+f"(d[45]),"+f"(d[46]),"+f"(d[47]),
        "+f"(d[48]),"+f"(d[49]),"+f"(d[50]),"+f"(d[51]),"+f"(d[52]),"+f"(d[53]),"+f"(d[54]),"+f"(d[55]),
        "+f"(d[56]),"+f"(d[57]),"+f"(d[58]),"+f"(d[59]),"+f"(d[60]),"+f"(d[61]),"+f"(d[62]),"+f"(d[63]),
        "+f"(d[64]),"+f"(d[65]),"+f"(d[66]),"+f"(d[67]),"+f"(d[68]),"+f"(d[69]),"+f"(d[70]),"+f"(d[71]),
        "+f"(d[72]),"+f"(d[73]),"+f"(d[74]),"+f"(d[75]),"+f"(d[76]),"+f"(d[77]),"+f"(d[78]),"+f"(d[79]),
        "+f"(d[80]),"+f"(d[81]),"+f"(d[82]),"+f"(d[83]),"+f"(d[84]),"+f"(d[85]),"+f"(d[86]),"+f"(d[87]),
        "+f"(d[88]),"+f"(d[89]),"+f"(d[90]),"+f"(d[91]),"+f"(d[92]),"+f"(d[93]),"+f"(d[94]),"+f"(d[95])
      : "l"(da), "l"(db));
}
template <int SD>
__device__ __forceinline__ void wgmma_rs_n128(float (&d)[64], uint32_t a0, uint32_t a1, uint32_t a2, uint32_t a3, uint64_t db) {
  asm volatile("wgmma.mma_async.sync.aligned.m64n128k16.f32.bf16.bf16 {"
      "%0,%1,%2,%3,%4,%5,%6,%7,%8,%9,%10,%11,%12,%13,%14,%15,"
      "%16,%17,%18,%19,%20,%21,%22,%23,%24,%25,%26,%27,%28,%29,%30,%31,"
      "%32,%33,%34,%35,%36,%37,%38,%39,%40,%41,%42,%43,%44,%45,%46,%47,"
      "%48,%49,%50,%51,%52,%53,%54,%55,%56,%57,%58,%59,%60,%61,%62,%63"
      "}, {%64,%65,%66,%67}, %68, %69, 1, 1, 1;\n"
      : "+f"(d[0]),"+f"(d[1]),"+f"(d[2]),"+f"(d[3]),"+f"(d[4]),"+f"(d[5]),"+f"(d[6]),"+f"(d[7]),
        "+f"(d[8]),"+f"(d[9]),"+f"(d[10]),"+f"(d[11]),"+f"(d[12]),"+f"(d[13]),"+f"(d[14]),"+f"(d[15]),
        "+f"(d[16]),"+f"(d[17]),"+f"(d[18]),"+f"(d[19]),"+f"(d[20]),"+f"(d[21]),"+f"(d[22]),"+f"(d[23]),
        "+f"(d[24]),"+f"(d[25]),"+f"(d[26]),"+f"(d[27]),"+f"(d[28]),"+f"(d[29]),"+f"(d[30]),"+f"(d[31]),
        "+f"(d[32]),"+f"(d[33]),"+f"(d[34]),"+f"(d[35]),"+f"(d[36]),"+f"(d[37]),"+f"(d[38]),"+f"(d[39]),
        "+f"(d[40]),"+f"(d[41]),"+f"(d[42]),"+f"(d[43]),"+f"(d[44]),"+f"(d[45]),"+f"(d[46]),"+f"(d[47]),
        "+f"(d[48]),"+f"(d[49]),"+f"(d[50]),"+f"(d[51]),"+f"(d[52]),"+f"(d[53]),"+f"(d[54]),"+f"(d[55]),
        "+f"(d[56]),"+f"(d[57]),"+f"(d[58]),"+f"(d[59]),"+f"(d[60]),"+f"(d[61]),"+f"(d[62]),"+f"(d[63])
      : "r"(a0), "r"(a1), "r"(a2), "r"(a3), "l"(db), "n"(SD));
}

constexpr int C_LN = 0, C_PX = 16, C_PY = 32;
constexpr int NB_CONS = 1, NB_LN = 2, NB_LAG = 4, NB_INIT = 6, NB_RDY = 7, NB_WG = 8;
#define LAGX 3
#define LAGY 0
#define LAG2 5
constexpr int NLL = 2;
#define POLL_DELAY3 600
#define POLL_DELAY 1200
#define FILT_DELAY 600
#define THR_B 0
#define THR_P 0
#define SPEC -1
#define WARM 4
#define HWARM 0
#define TOUCH 1
#define ALEAD 6
#define POLL_DELAY2 1200
#define PF1_WAIT 1
#define HPOS 14
#define YEP 2
#define RING_SIG 1
#define PF2_SIG 1
constexpr int SM_E = 0, SM_X = 16384, SM_E2 = 32768, SM_W = 49152, SM_FC = 69632, SM_T = 73728 - T1_BYTES;
constexpr unsigned long long KORDER = 0xBA9432DC876510ull;
constexpr unsigned long long BSLOT = 0x76532107653210ull, PSLOT = 0xDCBA984DCBA984ull;
constexpr uint32_t HI128 = desc_hi(1024, 1), HI64 = desc_hi(512, 2);

struct Bars {
  uint64_t full1[32], empty1[32], full2[16], fullA[8], empty2[8], fullP[16], emptyP[8], hbar, tbar, hint[3], sig[2], sbar;
  uint32_t epoch, pad;
};

template <int NK, bool STORE, int J0 = 0, int J1 = NK>
__device__ __forceinline__ void make_p(const float (&acc)[NK * 16], float r0, float r1, uint4 (&p)[NK], uint4* pbase, int ks0, uint32_t tag) {
#pragma unroll
  for (int j = J0; j < J1; j++) {
    uint32_t w[4];
#pragma unroll
    for (int i = 0; i < 4; i++) {
      const int a = 8 * j + 2 * i, b = a + NK * 8;
      w[i] = pack2(swiglu(acc[a], acc[b], (i & 1) ? r1 : r0), swiglu(acc[a + 1], acc[b + 1], (i & 1) ? r1 : r0));
    }
    asm volatile("" : "+r"(w[0]), "+r"(w[1]), "+r"(w[2]), "+r"(w[3]));
    p[j] = make_uint4(w[0], w[1], w[2], w[3]);
    if (STORE) st_tag(pbase + ((ks0 + j) >> 2) * 1024 + ((ks0 + j) & 3) * 32, p[j], tag);
  }
}
__device__ __forceinline__ void spin_cycles(uint32_t n) {
  const uint32_t t0 = clock32();
  while (clock32() - t0 < n) {}
}

__device__ __forceinline__ void spin_until(uint32_t t) {
  float d[4] = {0.f, 0.f, 0.f, 0.f};
  while ((int)(clock32() - t) < 0) {
    if (HWARM) asm volatile("mma.sync.aligned.m16n8k16.row.col.f32.bf16.bf16.f32 {%0,%1,%2,%3}, {%4,%4,%4,%4}, {%4,%4}, {%0,%1,%2,%3};"
                            : "+f"(d[0]), "+f"(d[1]), "+f"(d[2]), "+f"(d[3]) : "r"(t));
  }
}

__global__ void __cluster_dims__(2, 1, 1) __launch_bounds__(NTHREADS, 1)
fused_kernel(const __nv_bfloat16* __restrict__ x, const Tables* __restrict__ tab, Scratch* __restrict__ scr,
             __nv_bfloat16* __restrict__ out, const char* __restrict__ wg_raw, const char* __restrict__ wu_raw,
             const char* __restrict__ wd_raw,
             const __grid_constant__ CUtensorMap tmWR, const __grid_constant__ CUtensorMap tmWI,
             const __grid_constant__ CUtensorMap tmGX, const __grid_constant__ CUtensorMap tmUX,
             const __grid_constant__ CUtensorMap tmGY, const __grid_constant__ CUtensorMap tmUY,
             const __grid_constant__ CUtensorMap tmD) {
  extern __shared__ __align__(1024) char smem_raw[];
  const uint32_t sbase = s2u(smem_raw);
  const uint32_t sbar = sbase + 14 * SLOT, sstat = sbar + 1280;
  const int tid = threadIdx.x, lane = tid & 31;
  const int c = blockIdx.x, rk = c & 1, f = (c >> 1) & 7, rb = 2 * (c >> 4) + rk;
  const int rb2 = 2 * (c >> 4) + (f >> 2), kh = (f >> 1) & 1, nq = 2 * (f & 1) + rk;
#define BAR(field, i) (sbar + (uint32_t)offsetof(Bars, field) + 8u * (i))
#define TOFF(field) (sbase + SM_T + (uint32_t)offsetof(Tables, field) + lane * 16)

  if (tid >= 256) {
    asm volatile("setmaxnreg.dec.sync.aligned.u32 40;");
    const int warp = __shfl_sync(0xffffffffu, tid >> 5, 0);
    if (lane == 0) {
      if (warp == 8) {
        if (sbase & 1023) die();
#pragma unroll
        for (int i = 0; i < 16; i++) mbar_init(BAR(emptyP, i), i < 7 ? 16 : i < 8 ? 8 : i == 9 ? 1 + 32 * TOUCH : i < 13 ? 1 : i < 15 ? 8 : 32);
        mbar_expect(BAR(tbar, 0), T2_BYTES + 2 * 10240);
        mbar_expect(BAR(hbar, 0), 16384);
      } else if (warp == 9) {
#pragma unroll
        for (int i = 0; i < 32; i++) mbar_init(BAR(full1, i), 1);
#pragma unroll
        for (int i = 0; i < 32; i++) mbar_expect(BAR(full1, i), i < 16 ? 16384 : 12288);
      } else if (warp == 10) {
#pragma unroll
        for (int i = 0; i < 32; i++) mbar_init(BAR(empty1, i), 16);
#pragma unroll
        for (int i = 0; i < 14; i++) mbar_init(BAR(fullP, i), 1);
#pragma unroll
        for (int i = 0; i < 14; i++) mbar_expect(BAR(fullP, i), 16384);
      } else {
#pragma unroll
        for (int i = 0; i < 32; i++) mbar_init(BAR(full2, i), i < 24 ? 1 : 8);
#pragma unroll
        for (int i = 0; i < 24; i++) mbar_expect(BAR(full2, i), 16384);
      }
      asm volatile("fence.mbarrier_init.release.cluster;" ::: "memory");
    }
    if (tid == 256) {
      const int w0 = ((c >> 3) * 257 + 32 * (c & 7) + 1) & ~7;
      if (FILT_DELAY) {
        asm volatile("prefetch.tensormap [%0];" ::"l"(&tmWR) : "memory");
        asm volatile("prefetch.tensormap [%0];" ::"l"(&tmWI) : "memory");
        spin_cycles(FILT_DELAY);
      }
      tma3(sbase + SM_W, &tmWR, BAR(tbar, 0), w0, 0, 0);
      tma3(sbase + SM_W + 10240, &tmWI, BAR(tbar, 0), w0, 0, 0);
      bulk_load(sbase + SM_T + T1_BYTES, reinterpret_cast<const char*>(tab) + T1_BYTES, T2_BYTES, BAR(tbar, 0));
    }
    if (tid == 288) {
      asm volatile("prefetch.tensormap [%0];" ::"l"(rk ? &tmUX : &tmGX) : "memory");
      asm volatile("prefetch.tensormap [%0];" ::"l"(rk ? &tmUY : &tmGY) : "memory");
      asm volatile("prefetch.tensormap [%0];" ::"l"(&tmD) : "memory");
    }
    if (tid == 320) {
      const unsigned e = ld_relaxed(&scr->cnt[(C_LN + rb) * 32]) >> 3;
      asm volatile("st.shared.u32 [%0], %1;" ::"r"(BAR(epoch, 0)), "r"(e) : "memory");
    }
    __syncwarp();
    asm volatile("barrier.cluster.arrive.relaxed.aligned;" ::: "memory");
    bar_arrive(NB_RDY, 384);
    asm volatile("barrier.cluster.wait.aligned;" ::: "memory");
    bar_sync(NB_INIT, 384);
    unsigned epoch;
    asm volatile("ld.shared.u32 %0, [%1];" : "=r"(epoch) : "r"(BAR(epoch, 0)) : "memory");
    if (warp == 8) {
      if (lane == 0) {
        const int ax = (7 * f + 3 * (f & 1)) >> 1;
        const int ay = 7 * f + ((f & 1) ? 0 : 4);
        const CUtensorMap* tx = rk ? &tmUX : &tmGX;
        const CUtensorMap* ty = rk ? &tmUY : &tmGY;
        if (RING_SIG >= 0) mbar_wait(BAR(sig, RING_SIG));
        uint32_t s = 2;
#pragma unroll 1
        for (int n = 0; n < 16; n++) {
          if (n >= 6) mbar_wait(BAR(empty1, n - 6));
          tma3_mc(sbase + (8 + s) * SLOT + rk * 8192, tx, BAR(full1, n), n * 32, ax);
          if (++s == 6) s = 0;
        }
#pragma unroll 1
        for (int k = 0; k < 16; k++) {
          mbar_wait(BAR(empty1, k < 8 ? 10 + ((12 * k + 11) >> 4) : 8 + k));
          tma3_mc(sbase + 8 * SLOT + (k & 7) * 12288 + rk * 6144, ty, BAR(full1, 16 + k), k * 32, ay);
        }
      }
    } else if (warp == 9) {
      if (lane == 0) {
        mbar_wait(BAR(fullA, 4));
        wait_counter(&scr->cnt[(C_LN + rb2) * 32], (epoch + 1) * 8);
        asm volatile("fence.proxy.async.global;" ::: "memory");
#pragma unroll 1
        for (int i = 0; i < 15; i++) {
          const int kblk = 14 * kh + (int)((KORDER >> (4 * i)) & 15);
          const int j = i < 7 ? i : i - 7, sl = j + (j >= 4);
          if (i == HPOS) {
            mbar_wait(BAR(emptyP, 7));
            bulk_load(sbase + 4 * SLOT, &scr->LN[(rb2 * 8 + 2 * nq) * 1024 + kh * 512], 8192, BAR(hbar, 0));
            bulk_load(sbase + 4 * SLOT + 8192, &scr->LN[(rb2 * 8 + 2 * nq + 1) * 1024 + kh * 512], 8192, BAR(hbar, 0));
          }
          if (i == 14) break;
          mbar_wait(i < 7 ? BAR(empty1, 17 + 2 * sl) : BAR(empty2, j));
          if (THR_B && i >= THR_B) mbar_wait(BAR(full2, i - THR_B));
          tma3(sbase + sl * SLOT, &tmD, BAR(full2, i), 0, 64 * kblk, 2 * nq);
        }
      }
    } else if (warp == 10) {
      bar_sync(NB_LN, 288);
      if (lane == 0) {
        PROFP(0);
        red_release(&scr->cnt[(C_LN + rb) * 32]);
        PROFP(1);
        wait_counter(&scr->cnt[(C_LN + rb) * 32], (epoch + 1) * 8);
        asm volatile("fence.proxy.async.global;" ::: "memory");
        PROFP(2);
#pragma unroll 1
        for (int kb = NLL; kb < 8; kb++) {
          if (2 * kb >= ALEAD) mbar_wait(BAR(empty1, 2 * kb - ALEAD));
          bulk_load(sbase + kb * SLOT, &scr->LN[(rb * 8 + kb) * 1024], 16384, BAR(fullA, kb));
        }
#pragma unroll 1
        for (int s = 0; s < 14; s++) {
          const int kblk = 14 * kh + (int)((KORDER >> (4 * s)) & 15);
          if (s == 0 || (SPEC < 0 && (s == 8 || s == 11))) {
            if (s != 11) PROFP(3 + (s >> 2));
            mbar_wait(BAR(hint, s == 0 ? 0 : s == 8 ? 1 : 2), 0);
            if (s != 11) PROFP(4 + (s >> 2));
          }
          const int j = s < 7 ? s : s - 7;
          mbar_wait(s < 7 ? BAR(empty1, 24 + s + (s == 0) + (s >= 4)) : BAR(emptyP, j));
          if (THR_P && s >= THR_P) mbar_wait(BAR(fullP, s - THR_P));
          if (SPEC >= 0 && s == 8) mbar_wait(BAR(emptyP, SPEC & 7));
          bulk_load_mc(sbase + (j ? 7 + j : 4) * SLOT + rk * 8192, &scr->P[(rb2 * 28 + kblk) * 1024 + rk * 512], 8192, BAR(fullP, s));
        }
        PROFP(7);
      }
    } else {
      if (TOUCH) {
#pragma unroll
        for (int i = 0; i < 4 * NLL; i++)
          st_tag(&scr->LN[(rb * 8 + (i >> 2)) * 1024 + f * 128 + (i & 3) * 32 + lane], make_uint4(0, 0, epoch & 1, 0), epoch & 1);
        mbar_arrive(BAR(tbar, 0));
      }
      if (lane == 0) {
        if (PF1_WAIT) mbar_wait(BAR(tbar, 0));
        l2_prefetch(wg_raw + (size_t)c * 5376, 5376);
        l2_prefetch(wu_raw + (size_t)c * 5376, 5376);
        mbar_wait(BAR(sig, PF2_SIG), 0);
        l2_prefetch(wg_raw + 688128 + (size_t)c * 8960, 8960);
        l2_prefetch(wu_raw + 688128 + (size_t)c * 8960, 8960);
      }
      mbar_wait(BAR(fullA, 4), 0);
      if (lane == 0) l2_prefetch(wd_raw + (size_t)c * 14336, 14336);
      {
        const uint32_t tag = (epoch + 1) & 1;
        uint4 v0, v1, v2;
        int it = 0;
        while (true) {
          v0 = ld_b128(&scr->ST[rb * 64 + lane]);
          v1 = ld_b128(&scr->ST[rb * 64 + 32 + lane]);
          v2 = ld_b128(&scr->ST[rb2 * 64 + 32 * kh + lane]);
          if (!__any_sync(0xffffffffu, ((v0.x ^ tag) | (v1.x ^ tag) | (v2.x ^ tag)) & 1u)) break;
          if (++it > SPIN_LIMIT) { die(); break; }
        }
        sts4(sstat + lane * 16, v0.x & ~1u, v0.y, v0.z, v0.w);
        sts4(sstat + 512 + lane * 16, v1.x & ~1u, v1.y, v1.z, v1.w);
        sts4(sstat + 1024 + lane * 16, v2.x & ~1u, v2.y, v2.z, v2.w);
#pragma unroll 4
        for (int i = 0; i < 32; i++)
          st_tag(&scr->XP[(c ^ 4) * 1024 + i * 32 + lane], make_uint4(0, 0, 0, 0), tag ^ 1);
        mbar_arrive(BAR(sbar, 0));
      }
      if (lane == 0) {
        mbar_wait(BAR(empty1, 17));
#pragma unroll 1
        for (int e = 0; e < (SPEC < 0 ? 3 : 1); e++) {
          const unsigned* cp = e == 0 ? &scr->cnt[(C_PX + rb2) * 32 + kh] : &scr->cnt[(C_PY + rb2) * 32 + 2 * kh + e - 1];
          if (e == 1) mbar_wait(BAR(fullP, 0), 0);
          int it = 0;
          while ((int)(ld_relaxed(cp) - (epoch + 1) * (e == 0 ? 32 : 16)) < 0)
            if (++it > SPIN_LIMIT) { die(); break; }
          mbar_arrive(BAR(hint, e));
        }
      }
    }
  } else {
    const int warp = __shfl_sync(0xffffffffu, tid >> 5, 0);
    const int g = lane >> 2, t = lane & 3;
    PROF(0);
    PROFG(14);
    uint4 fa[4], fb[4], tw[6];
#pragma unroll
    for (int i = 0; i < 4; i++) fa[i] = ldg_ca4(&tab->fa[i][lane][0]);
#pragma unroll
    for (int i = 0; i < 6; i++) tw[i] = ldg_ca4(&tab->tw1[i][lane][0]);
#pragma unroll
    for (int i = 0; i < 4; i++) fb[i] = ldg_ca4(&tab->fb[i][lane][0]);
#pragma unroll
    for (int i = 0; i < 4; i++) {
      const int r = i >> 1, ch = (i & 1) * 32 + lane;
      cp_async16(sbase + SM_X + (2 * warp + r) * 1024 + ((ch ^ ((ch >> 3) & 1)) * 16),
                 x + (size_t)(c + 128 * (2 * warp + r)) * 512 + ch * 8);
    }
    asm volatile("cp.async.commit_group;" ::: "memory");
    asm volatile("barrier.cluster.arrive.relaxed.aligned;" ::: "memory");
    uint32_t rbar;
    asm volatile("mapa.shared::cluster.u32 %0, %1, %2;" : "=r"(rbar) : "r"(sbar), "r"(rk ^ 1));
#define RBAR(field, i) (rbar + (uint32_t)offsetof(Bars, field) + 8u * (i))
    {
      const int ln = (tid >> 1) & 31, lg = ln >> 2, lt = ln & 3, i = 4 * (tid >> 6) + 2 * (tid & 1);
      const int kidx = lt + 8 * (i >> 3), nidx = 4 * ((i >> 1) & 3) + (lg >> 1);
      const uint32_t a0 = cfrag<2048>((c + 128 * kidx) * nidx, lg & 1), a1 = cfrag<2048>((c + 128 * (kidx + 4)) * nidx, lg & 1);
      const uint32_t b0 = cfrag<2048>(-(c + 128 * nidx) * kidx, lg & 1), b1 = cfrag<2048>(-(c + 128 * nidx) * (kidx + 4), lg & 1);
      asm volatile("st.shared.v2.u32 [%0], {%1,%2};" ::"r"(sbase + SM_FC + tid * 8), "r"(a0), "r"(a1) : "memory");
      asm volatile("st.shared.v2.u32 [%0], {%1,%2};" ::"r"(sbase + SM_FC + 2048 + tid * 8), "r"(b0), "r"(b1) : "memory");
    }
    bar_sync(NB_CONS, 256);
    uint4 fc[4];
#pragma unroll
    for (int i = 0; i < 4; i++) fc[i] = lds4(sbase + SM_FC + i * 512 + lane * 16);
    asm volatile("cp.async.wait_group 0;" ::: "memory");
    __syncwarp();
    bar_arrive(NB_INIT, 384);
    PROF(13);
    uint32_t tag, ones;
    uint4 q[4], o[4];
    {
      uint32_t v[2][8];
#pragma unroll
      for (int r = 0; r < 2; r++)
#pragma unroll
        for (int ks = 0; ks < 2; ks++) {
          const int ch = 32 * ks + 2 * (lane & 15) + (lane >> 4);
          asm volatile("ldmatrix.sync.aligned.m8n8.x4.trans.shared.b16 {%0,%1,%2,%3}, [%4];"
                       : "=r"(v[r][4 * ks]), "=r"(v[r][4 * ks + 1]), "=r"(v[r][4 * ks + 2]), "=r"(v[r][4 * ks + 3])
                       : "r"(sbase + SM_X + (2 * warp + r) * 1024 + ((ch ^ ((ch >> 3) & 1)) * 16)) : "memory");
        }
      float sq[2];
#pragma unroll
      for (int r = 0; r < 2; r++) {
        float s0 = 0.f, s1 = 0.f;
#pragma unroll
        for (int i = 0; i < 8; i++) {
          const float lo = bf_lo(v[r][i]), hi = u2f(v[r][i] & 0xffff0000u);
          s0 = fmaf(lo, lo, s0);
          s1 = fmaf(hi, hi, s1);
        }
        sq[r] = s0 + s1;
      }
      {
        float w = ((lane & 1) ? sq[1] : sq[0]) + __shfl_xor_sync(0xffffffffu, (lane & 1) ? sq[0] : sq[1], 1);
        w += __shfl_xor_sync(0xffffffffu, w, 2);
        w = sum_groups(w);
        const float o2 = __shfl_xor_sync(0xffffffffu, w, 1);
        sq[0] = (lane & 1) ? o2 : w;
        sq[1] = (lane & 1) ? w : o2;
      }
#pragma unroll
      for (int r = 0; r < 2; r++) {
        float dd[2][4], ee[2][4];
#pragma unroll
        for (int nt = 0; nt < 2; nt++) {
          mma_az(dd[nt], fa[0], v[r][2 * nt], v[r][2 * nt + 1]);
          mma_a(dd[nt], fa[1], v[r][4 + 2 * nt], v[r][5 + 2 * nt]);
          mma_az(ee[nt], fa[2], v[r][2 * nt], v[r][2 * nt + 1]);
          mma_a(ee[nt], fa[3], v[r][4 + 2 * nt], v[r][5 + 2 * nt]);
        }
        float mean = (dd[0][0] + dd[0][1]) + (dd[1][0] + dd[1][1]);
        mean += __shfl_xor_sync(0xffffffffu, mean, 1);
        mean += __shfl_xor_sync(0xffffffffu, mean, 2);
        mean = __shfl_sync(0xffffffffu, mean, 0) * (1.f / 512.f);
        const float rs = rsqrtf(fmaxf(fmaf(-mean, mean, sq[r] * (1.f / 512.f)), 0.f) + 1e-5f);
        float acc[4][4];
#pragma unroll
        for (int nt = 0; nt < 2; nt++) {
          const float (&d)[4] = dd[nt];
          const float (&e)[4] = ee[nt];
          const uint4 &ka = tw[2 * nt], &kb = tw[2 * nt + 1], &kc = tw[4 + nt];
          const uint32_t a0 = pack2(d[0] * u2f(ka.x) + d[2] * u2f(ka.y), d[1] * u2f(kb.x) + d[3] * u2f(kb.y));
          const uint32_t a2 = pack2(d[0] * u2f(ka.z) + d[2] * u2f(ka.w), d[1] * u2f(kb.z) + d[3] * u2f(kb.w));
          const uint32_t a1 = pack2(e[0] * u2f(kc.x) + e[2] * u2f(kc.y), e[1] * u2f(kc.z) + e[3] * u2f(kc.w));
          const uint32_t a3 = pack2(e[2] * u2f(kc.x) - e[0] * u2f(kc.y), e[3] * u2f(kc.z) - e[1] * u2f(kc.w));
          const uint32_t dc = pack2(fmaf(mean, -32.f, d[0]), fmaf(mean, -32.f, d[1]));
          const uint32_t h0 = g == 0 ? dc : a0, h2 = g == 0 ? 0u : a2;
          if (nt == 0) {
            mma16816_z(acc[0], a0, a1, a2, a3, fb[2 * nt].x, fb[2 * nt].y);
            mma16816_z(acc[1], a0, a1, a2, a3, fb[2 * nt].z, fb[2 * nt].w);
            mma16816_z(acc[2], h0, a1, h2, a3, fb[2 * nt + 1].x, fb[2 * nt + 1].y);
            mma16816_z(acc[3], h0, a1, h2, a3, fb[2 * nt + 1].z, fb[2 * nt + 1].w);
          } else {
            mma16816(acc[0], a0, a1, a2, a3, fb[2 * nt].x, fb[2 * nt].y);
            mma16816(acc[1], a0, a1, a2, a3, fb[2 * nt].z, fb[2 * nt].w);
            mma16816(acc[2], h0, a1, h2, a3, fb[2 * nt + 1].x, fb[2 * nt + 1].y);
            mma16816(acc[3], h0, a1, h2, a3, fb[2 * nt + 1].z, fb[2 * nt + 1].w);
          }
        }
#pragma unroll
        for (int h = 0; h < 2; h++) {
          const int j = 2 * warp + r, m = 2 * t + h;
          sts4(sbase + SM_E + ((j * 8 + m) * 8 + (g ^ (2 * t) ^ (2 * (j & 3)))) * 16,
               pack2(acc[h][0] * rs, acc[h][1] * rs), pack2(acc[h][2] * rs, acc[h][3] * rs),
               pack2(acc[2 + h][0] * rs, acc[2 + h][1] * rs), pack2(acc[2 + h][2] * rs, acc[2 + h][3] * rs));
        }
      }
      if (tid == 0) PROFP(12);
      bar_sync(NB_RDY, 384);
      if (tid == 0) PROFP(13);
      const uint32_t ea = sbase + SM_E + ((t * 8 + warp) * 8 + (g ^ (warp & 6) ^ (2 * t))) * 16;
      lds_frag(q[0], q[1], ea, ea + 4096);
      lds_frag(q[2], q[3], ea + 8192, ea + 12288);
      asm volatile("ld.shared.u32 %0, [%1];" : "=r"(tag) : "r"(BAR(epoch, 0)) : "memory");
      ones = ~(tag >> 31);
      tag = (tag + 1) & 1;
      cdft16(q, fc, o);
#pragma unroll
      for (int vv = 0; vv < 4; vv++) st_tag(&scr->Z1[(((4 * vv + t) * 8 + warp) * 128 + c) * 8 + g], o[vv], tag);
    }
    PROF(1);
    asm volatile("setmaxnreg.inc.sync.aligned.u32 232;");
    {
      const uint4* const zp = &scr->Z1[(c * 128 + 8 * t + warp) * 8 + g];
      const uint32_t tst = clock32();
      mbar_wait(BAR(tbar, 0), 0);
      if (tid == 0) PROFP(14);
      uint4 f2[4], g2[4];
#pragma unroll
      for (int i = 0; i < 4; i++) {
        f2[i] = lds4(TOFF(f2) + warp * 2048 + i * 512);
        g2[i] = lds4(TOFF(g2) + warp * 2048 + i * 512);
      }
      const uint4 f8 = lds4(TOFF(f8)), g8 = lds4(TOFF(g8));
      float wfr[16], wfi[16];
      {
        const float nyq = ((c & 7) == 7 && g == 0) ? 0.5f : 1.f;
        const int gg = g == 0 ? 16 : g, wsh = (2 * (c >> 3) + 2) & 15;
#pragma unroll
        for (int i = 0; i < 16; i++) {
          const int ci = i >> 3, dd = (i >> 2) & 1, e = i & 3;
          const int kk = (e == 0 ? gg : e == 1 ? g + 8 : e == 2 ? 32 - g : 24 - g) - 1;
          const uint32_t a = sbase + SM_W + ((2 * warp + ci) * 8 + t + 4 * dd) * 80 + wsh + 2 * kk;
          wfr[i] = bf_lo(lds_u16(a)) * (e == 2 ? nyq : 1.f);
          wfi[i] = bf_lo(lds_u16(a + 10240)) * (e == 2 ? nyq : 1.f);
        }
      }
      asm volatile("barrier.cluster.wait.aligned;" ::: "memory");
      PROF(2);
      spin_until(tst + POLL_DELAY);
      ld_tag4_issue<256>(q, zp);
      ld_tag4_finish<256>(q, zp, tag);
      if (tid == 0) PROFP(30);
      if (lane == 0) mbar_arrive(BAR(sig, 0));
      reg_frag(q, ones);
      cdft16(q, f2, o);
      const uint32_t e2 = sbase + SM_E2;
#pragma unroll
      for (int vv = 0; vv < 4; vv++)
        sts4(e2 + ((warp * 16 + 4 * vv + t) * 8 + (g ^ (2 * t) ^ (2 * (warp & 3)))) * 16, o[vv].x, o[vv].y, o[vv].z, o[vv].w);
      bar_sync(NB_CONS, 256);
      uint32_t ad[2], res[2][2][4];
#pragma unroll
      for (int ci = 0; ci < 2; ci++) {
        const int cc = 2 * warp + ci;
        ad[ci] = e2 + ((t * 16 + cc) * 8 + (g ^ (2 * (cc & 3)) ^ (2 * t))) * 16;
        lds_frag(q[2 * ci], q[2 * ci + 1], ad[ci], ad[ci] + 8192);
      }
#pragma unroll
      for (int ci = 0; ci < 2; ci++)
#pragma unroll
        for (int p = 0; p < 2; p++) {
          uint32_t y[2][2];
#pragma unroll
          for (int vv = 0; vv < 2; vv++) {
            float d[4];
            mma_az(d, q[2 * ci + p], word(f8, 2 * vv), word(f8, 2 * vv + 1));
#pragma unroll
            for (int rr = 0; rr < 2; rr++) {
              const float fr = wfr[ci * 8 + vv * 4 + 2 * p + rr], fi = wfi[ci * 8 + vv * 4 + 2 * p + rr];
              y[vv][rr] = pack2(d[2 * rr] * fr - d[2 * rr + 1] * fi, d[2 * rr] * fi + d[2 * rr + 1] * fr);
            }
          }
#pragma unroll
          for (int vv = 0; vv < 2; vv++) {
            float d[4];
            mma16816_z(d, y[0][0], y[0][1], y[1][0], y[1][1], word(g8, 2 * vv), word(g8, 2 * vv + 1));
            res[ci][vv][2 * p] = pack2(d[0], d[1]);
            res[ci][vv][2 * p + 1] = pack2(d[2], d[3]);
          }
        }
#pragma unroll
      for (int i = 0; i < 4; i++)
        sts4(ad[i >> 1] + (i & 1) * 8192, res[i >> 1][i & 1][0], res[i >> 1][i & 1][1], res[i >> 1][i & 1][2], res[i >> 1][i & 1][3]);
      bar_sync(NB_CONS, 256);
      const uint32_t eb = e2 + ((warp * 16 + t) * 8 + (g ^ (2 * t) ^ (2 * (warp & 3)))) * 16;
      lds_frag(q[0], q[1], eb, eb + 512);
      lds_frag(q[2], q[3], eb + 1024, eb + 1536);
      cdft16(q, g2, o);
#pragma unroll
      for (int vv = 0; vv < 4; vv++) st_tag(&scr->Z2[((8 * (4 * vv + t) + warp) * 128 + c) * 8 + g], o[vv], tag);
    }
    PROF(3);
    {
      const uint4* const zp = &scr->Z2[((c * 16 + t) * 8 + warp) * 8 + g];
      const uint32_t tst = clock32();
      uint4 gb[4], ga[4], gc[4], tw[4];
      uint2 xr[2][4];
      uint2* lnp[2];
#pragma unroll
      for (int r = 0; r < 2; r++) {
        const int row = 16 * f + 2 * warp + r;
        lnp[r] = reinterpret_cast<uint2*>(&scr->LN[(rb * 8 + (g >> 2)) * 1024 + row * 8 + ((2 * (g & 3) + (t >> 1)) ^ (row & 7))]) + (t & 1);
        asm volatile("" : "+l"(lnp[r]));
      }
#pragma unroll
      for (int i = 0; i < 4; i++) {
        gc[i] = lds4(sbase + SM_FC + 2048 + i * 512 + lane * 16);
        gb[i] = lds4(TOFF(gb) + i * 512);
        ga[i] = lds4(TOFF(ga) + i * 512);
        tw[i] = lds4(TOFF(tw3) + i * 512);
        const int ch = 2 * (g + 8 * i) + (t >> 1);
#pragma unroll
        for (int r = 0; r < 2; r++) xr[r][i] = lds2(sbase + SM_X + (2 * warp + r) * 1024 + ((ch ^ ((ch >> 3) & 1)) * 16) + (t & 1) * 8);
      }
      PROF(4);
      spin_until(tst + POLL_DELAY2);
      ld_tag4_issue<256>(q, zp);
      ld_tag4_finish<256>(q, zp, tag);
      if (tid == 0) PROFP(31);
      if (lane == 0) mbar_arrive(BAR(sig, 1));
      reg_frag(q, ones);
      cdft16(q, gc, o);
#pragma unroll
      for (int vv = 0; vv < 4; vv++)
        sts4(sbase + SM_E + (((4 * vv + t) * 8 + warp) * 8 + (g ^ (warp & 6) ^ (2 * t))) * 16, o[vv].x, o[vv].y, o[vv].z, o[vv].w);
      if (tid == 0) PROFP(8);
      bar_sync(NB_CONS, 256);
      if (tid == 0) PROFP(9);
      uint32_t hv[2][8];
      const float mk = t == 0 ? 0.f : 1.f;
#pragma unroll
      for (int r = 0; r < 2; r++) {
        const int j = 2 * warp + r;
        uint4 u[2];
#pragma unroll
        for (int h = 0; h < 2; h++) u[h] = lds4(sbase + SM_E + ((j * 8 + 2 * t + h) * 8 + (g ^ (2 * t) ^ (2 * (j & 3)))) * 16);
        const uint32_t bp[4][2] = {{u[0].x, u[1].x & ones}, {u[0].y & ones, u[1].y}, {u[0].z, u[1].z & ones}, {u[0].w & ones, u[1].w}};
        float y[2][2][4];
#pragma unroll
        for (int i = 0; i < 2; i++) {
          float lo[4], hi[4], e[4];
          mma_az(lo, gb[2 * i], bp[0][0], bp[0][1]);
          mma_az(hi, gb[2 * i + 1], bp[2][0], bp[2][1]);
          mma_az(e, gb[2 * i], bp[1][0], bp[1][1]);
          mma_a(e, gb[2 * i + 1], bp[3][0], bp[3][1]);
          const uint4 &ka = tw[2 * i], &kb = tw[2 * i + 1];
          const float tr0 = fmaf(hi[0], mk, lo[0]), ti0 = fmaf(hi[2], mk, lo[2]);
          const float tr1 = lo[1] + hi[1], ti1 = lo[3] + hi[3];
          const float vr0 = tr0 * u2f(ka.x) - ti0 * u2f(ka.y), vi0 = tr0 * u2f(ka.y) + ti0 * u2f(ka.x);
          const float vr1 = tr1 * u2f(ka.z) - ti1 * u2f(ka.w), vi1 = tr1 * u2f(ka.w) + ti1 * u2f(ka.z);
          const uint32_t b0 = pack2(t == 0 ? hi[0] : vr0, vr1), b1 = pack2(t == 0 ? vr0 : vi0, vi1);
          const uint32_t b2 = pack2(e[0] * u2f(kb.x) - e[2] * u2f(kb.y), e[1] * u2f(kb.z) - e[3] * u2f(kb.w));
          const uint32_t b3 = pack2(e[0] * u2f(kb.y) + e[2] * u2f(kb.x), e[1] * u2f(kb.w) + e[3] * u2f(kb.z));
#pragma unroll
          for (int mt = 0; mt < 2; mt++) {
            mma_az(y[mt][i], ga[2 * mt], b0, b1);
            mma_a(y[mt][i], ga[2 * mt + 1], b2, b3);
          }
        }
#pragma unroll
        for (int i = 0; i < 4; i++) {
          hv[r][2 * i] = hadd2_bf16(xr[r][i].x, pack2(y[i >> 1][0][2 * (i & 1)], y[i >> 1][0][2 * (i & 1) + 1]));
          hv[r][2 * i + 1] = hadd2_bf16(xr[r][i].y, pack2(y[i >> 1][1][2 * (i & 1)], y[i >> 1][1][2 * (i & 1) + 1]));
        }
      }
      if (tid == 0 && hv[0][0] != 0x12345 && hv[1][7] != 0x12345) PROFP(10);
      float mean[2];
      uint32_t mb[2];
#pragma unroll
      for (int r = 0; r < 2; r++) {
        mean[r] = sum_groups(quad_sum(hv[r])) * (1.f / 512.f);
        mb[r] = pack2(mean[r], mean[r]);
      }
#pragma unroll
      for (int i = 0; i < 4; i++)
#pragma unroll
        for (int r = 0; r < 2; r++) {
          hv[r][2 * i] = hsub2_bf16(hv[r][2 * i], mb[r]);
          hv[r][2 * i + 1] = hsub2_bf16(hv[r][2 * i + 1], mb[r]);
          st_tag8(lnp[r] + i * 4096, hv[r][2 * i], hv[r][2 * i + 1], i == 0 ? tag : (hv[r][2 * i] & 1u));
        }
      if (tid == 0) PROFP(11);
      bar_arrive(NB_LN, 288);
      const uint32_t ones2 = ~(lds2(BAR(epoch, 0)).x >> 31);
      float rstd[2];
#pragma unroll
      for (int r = 0; r < 2; r++) {
        hv[r][0] &= ones2;
        rstd[r] = row_rstd(hv[r], mean[r] - bf_lo(mb[r]));
      }
      if (lane == 0)
        st_tag(&scr->ST[rb * 64 + 8 * f + warp], make_uint4(mb[0] << 16, __float_as_uint(rstd[0]), mb[1] << 16, __float_as_uint(rstd[1])), tag);
    }
    PROF(5);
    const int wgi = warp >> 2, wq = warp & 3;
    uint4* const pbase = &scr->P[rb * 28 * 1024 + warp * 128 + lane];
    const uint32_t a_lo0 = desc_lo(sbase + wgi * 8192, 16);
    const uint32_t ebar = lane == 0 ? BAR(empty1, 0) : RBAR(empty1, 0);
    float r0, r1;
    uint4 px[8], py[6];
    const int rh = wgi ^ kh ^ 1;
    const uint4* const psrc = &scr->P[(rb2 * 28 + 14 * kh) * 1024 + (4 * rh + wq) * 128 + lane];
    const uint32_t pa0 = sbase + (4 * rh + wq) * 2048;
    uint4 pf[3][4];
    uint32_t rdy = 0;
    {
      float acc[128];
#pragma unroll
      for (int i = 0; i < 128; i++) acc[i] = 0.f;
      const uint32_t b_lo0 = desc_lo(sbase + 8 * SLOT, 4096);
      const uint32_t t3 = clock32();
      if (WARM) {
        wg_fence();
#pragma unroll
        for (int i = 0; i < WARM; i++) wgmma_n256(acc, desc64(a_lo0 + 6 * 1024, HI128), desc64(b_lo0, HI128));
        wg_commit();
      }
      const uint4* const ap = &scr->LN[rb * 8 * 1024 + wgi * 512 + (tid & 127)];
      uint4 av[NLL][4];
      while (clock32() - t3 < POLL_DELAY3) {}
#pragma unroll
      for (int kb = 0; kb < NLL; kb++) ld_tag4_issue<128>(av[kb], ap + kb * 1024);
      bar_sync(NB_CONS, 256);
      uint32_t slot = 2;
      auto stage_x = [&](int kb, int hh) {
        if (LAGX && hh == ((16 - LAGX) & 1) && kb == ((16 - LAGX) >> 1) && wgi == 1) bar_sync(NB_LAG, 256);
        mbar_wait(BAR(full1, 2 * kb + hh));
        const uint32_t al = a_lo0 + kb * 1024 + hh * 4, bl = b_lo0 + slot * 1024;
        wg_fence();
        wgmma_n256(acc, desc64(al, HI128), desc64(bl, HI128), (kb | hh) != 0 ? 1 : ~ones);
        wgmma_n256(acc, desc64(al + 2, HI128), desc64(bl + 128, HI128));
        wg_commit();
        if (LAGX && hh == 1 && kb == 7 && wgi == 0) bar_arrive(NB_LAG, 256);
        wg_wait<1>();
        if ((kb | hh) != 0 && lane < 2) mbar_arrive_remote(ebar + 8 * (2 * kb + hh - 1));
        if (++slot == 6) slot = 0;
      };
#pragma unroll
      for (int kb = 0; kb < NLL; kb++) {
        ld_tag4_finish<128, true>(av[kb], ap + kb * 1024, tag);
#pragma unroll
        for (int i = 0; i < 4; i++)
          sts4(sbase + kb * SLOT + wgi * 8192 + ((tid & 127) + 128 * i) * 16, av[kb][i].x, av[kb][i].y, av[kb][i].z, av[kb][i].w);
        asm volatile("fence.proxy.async.shared::cta;" ::: "memory");
        bar_sync(NB_WG + wgi, 128);
        if (kb > 0) stage_x(kb - 1, 1);
        if (kb == 0) PROF(6);
        stage_x(kb, 0);
      }
      stage_x(NLL - 1, 1);
#pragma unroll 1
      for (int kb = NLL; kb < 8; kb++) {
        mbar_wait(BAR(fullA, kb));
        stage_x(kb, 0);
        stage_x(kb, 1);
      }
      mbar_wait(BAR(sbar, 0), 0);
      r0 = __uint_as_float(lds2(sstat + (16 * warp + g) * 8).y);
      r1 = __uint_as_float(lds2(sstat + (16 * warp + g + 8) * 8).y);
      wg_wait<0>();
      if (lane < 2) mbar_arrive_remote(ebar + 8 * 15);
      PROF(7);
      make_p<8, false>(acc, r0, r1, px, pbase, 0, tag);
    }
    PROF(8);
    float accy[96];
    {
#pragma unroll
      for (int i = 0; i < 96; i++) accy[i] = 0.f;
      const uint32_t b_lo0 = desc_lo(sbase + 8 * SLOT, 2048);
      uint4* const pdst = pbase + ((7 * f + 3 * (f & 1)) >> 1) * 1024;
      auto stage_y = [&](int k) {
        if (LAGY && k == 16 - LAGY && wgi == 1) bar_sync(NB_LAG, 256);
        mbar_wait(BAR(full1, 16 + k));
        const uint32_t al = a_lo0 + (k >> 1) * 1024 + (k & 1) * 4, bl = b_lo0 + (k & 7) * 768;
        wg_fence();
        wgmma_n192(accy, desc64(al, HI128), desc64(bl, HI64));
        wgmma_n192(accy, desc64(al + 2, HI128), desc64(bl + 64, HI64));
        wg_commit();
      };
#pragma unroll
      for (int k = 0; k < 4; k++) {
        stage_y(k);
        st_tag(pdst + (k >> 1) * 1024 + (k & 1) * 64, px[2 * k], tag);
        st_tag(pdst + (k >> 1) * 1024 + (k & 1) * 64 + 32, px[2 * k + 1], tag);
        if (k == 3 && lane == 0) red_relaxed(&scr->cnt[(C_PX + rb) * 32 + (f >> 2)]);
        wg_wait<1>();
        if (k != 0 && lane < 2) mbar_arrive_remote(ebar + 8 * (15 + k));
      }
#pragma unroll 1
      for (int k = 4; k < 16; k++) {
        stage_y(k);
        if (LAGY && k == 15 && wgi == 0) bar_arrive(NB_LAG, 256);
        wg_wait<1>();
        if (lane < 2) mbar_arrive_remote(ebar + 8 * (15 + k));
      }
    }
    PROF(9);
    {
      float acc[64];
      const uint32_t b2_lo0 = desc_lo(sbase, 8192);
      const uint32_t pbar = ebar + (uint32_t)(offsetof(Bars, emptyP) - offsetof(Bars, empty1));
      if (!rdy) {
        mbar_wait(BAR(fullP, 0));
#pragma unroll
        for (int kk = 0; kk < 4; kk++) pf[0][kk] = lds4(pa0 + 4 * SLOT + kk * 512 + lane * 16);
      }
#pragma unroll
      for (int s = 0; s < 14; s++) {
        uint4 (&a)[4] = pf[s % 3];
        ld_tag4_finish<32>(a, psrc + (int)((KORDER >> (4 * s)) & 15) * 1024, tag);
        if (s < 8 && lane < (s < 7 ? 2 : 1)) mbar_arrive_remote(pbar + 8 * s);
        if (s >= 2) {
          wg_wait<1>();
          if (s <= 8 && lane == 0) mbar_arrive(BAR(empty2, s - 2));
        }
        if (!rdy) {
          if (s < 13) mbar_wait(BAR(fullP, s + 1));
          mbar_wait(BAR(full2, s));
        }
        if (tid == 0) PROFP(16 + s);
        if (s == 14 - LAG2 && wgi == 1) {
          const float m0 = __uint_as_float(lds2(sstat + 1024 + (16 * wq + g) * 8).x);
          const float m1 = __uint_as_float(lds2(sstat + 1024 + (16 * wq + g + 8) * 8).x);
          const uint32_t hb = sbase + 4 * SLOT + (16 * wq + (lane & 15)) * 128;
          wg_wait<0>();
          mbar_wait(BAR(hbar, 0));
#pragma unroll
          for (int i = 0; i < 8; i++) {
            uint32_t h[4];
            asm volatile("ldmatrix.sync.aligned.m8n8.x4.shared.b16 {%0,%1,%2,%3}, [%4];"
                         : "=r"(h[0]), "=r"(h[1]), "=r"(h[2]), "=r"(h[3])
                         : "r"(hb + (i >> 2) * 8192 + (((2 * (i & 3) + (lane >> 4)) ^ (lane & 7)) * 16)) : "memory");
            const uint32_t mk = ((t & 1) == 0 && nq == 0) ? ~1u : ~0u;
#pragma unroll
            for (int e = 0; e < 4; e++) {
              acc[8 * i + 2 * e] += bf_lo(h[e] & mk) + ((e & 1) ? m1 : m0);
              acc[8 * i + 2 * e + 1] += __uint_as_float(h[e] & 0xffff0000u) + ((e & 1) ? m1 : m0);
            }
          }
          bar_sync(NB_LAG, 256);
        }
        const uint32_t bl = b2_lo0 + (uint32_t)((BSLOT >> (4 * s)) & 15) * 1024;
        wg_fence();
        if (s < 13) {
#pragma unroll
          for (int kk = 0; kk < 4; kk++)
            pf[(s + 1) % 3][kk] = lds4(pa0 + (uint32_t)((PSLOT >> (4 * (s + 1))) & 15) * SLOT + kk * 512 + lane * 16);
          rdy = mbar_test(BAR(full2, s + 1));
          if (s < 12) rdy &= mbar_test(BAR(fullP, s + 2));
        }
        if (s == 0) wgmma_rs_n128<0>(acc, a[0].x, a[0].y, a[0].z, a[0].w, desc64(bl, HI128));
        else wgmma_rs_n128<1>(acc, a[0].x, a[0].y, a[0].z, a[0].w, desc64(bl, HI128));
#pragma unroll
        for (int kk = 1; kk < 4; kk++) wgmma_rs_n128<1>(acc, a[kk].x, a[kk].y, a[kk].z, a[kk].w, desc64(bl + kk * 128, HI128));
        wg_commit();
        if (s < YEP) {
          if (s == 0) {
            wg_wait<1>();
            if (lane < 2) mbar_arrive_remote(ebar + 8 * 31);
          }
          const int ks0 = 14 * f + ((f & 1) ? 0 : 8);
          if (s == 0) make_p<6, true, 0, 6 / YEP>(accy, r0, r1, py, pbase, ks0, tag);
          if (s == 1) make_p<6, true, 6 / YEP, 12 / YEP>(accy, r0, r1, py, pbase, ks0, tag);
          if (s == 2) make_p<6, true, 4, 6>(accy, r0, r1, py, pbase, ks0, tag);
          if (s == YEP - 1) {
            if (lane == 0) red_relaxed(&scr->cnt[(C_PY + rb) * 32 + (f >> 1)]);
            PROF(10);
          }
        }
      }
      if (wgi == 0) {
        bar_arrive(NB_LAG, 256);
        uint4* const dst = &scr->XP[(c ^ 4) * 1024 + tid];
        wg_wait<0>();
        PROF(11);
#pragma unroll
        for (int i = 0; i < 8; i++)
          st_tag(dst + i * 128, make_uint4(pack2(acc[8 * i], acc[8 * i + 1]), pack2(acc[8 * i + 2], acc[8 * i + 3]),
                                           pack2(acc[8 * i + 4], acc[8 * i + 5]), pack2(acc[8 * i + 6], acc[8 * i + 7])), tag);
      } else {
        uint4 pv[2][4];
        const uint4* const xsrc = &scr->XP[c * 1024 + (tid & 127)];
        ld_tag4_issue<128>(pv[0], xsrc);
        ld_tag4_issue<128>(pv[1], xsrc + 512);
        wg_wait<0>();
        PROF(11);
        uint32_t w[32];
#pragma unroll
        for (int i = 0; i < 32; i++) w[i] = pack2(acc[2 * i], acc[2 * i + 1]);
        ld_tag4_finish<128>(pv[0], xsrc, tag);
        ld_tag4_finish<128>(pv[1], xsrc + 512, tag);
#pragma unroll
        for (int i = 0; i < 8; i++) {
          const uint4& p = pv[i >> 2][i & 3];
          asm volatile("stmatrix.sync.aligned.m8n8.x4.shared.b16 [%0], {%1,%2,%3,%4};"
                       ::"r"(pa0 + (9 + ((lane >> 3) & 1)) * SLOT + (lane & 7) * 256 + (((2 * i + (lane >> 4)) ^ (lane & 7)) * 16)),
                         "r"(hadd2_bf16(w[4 * i], p.x)), "r"(hadd2_bf16(w[4 * i + 1], p.y)), "r"(hadd2_bf16(w[4 * i + 2], p.z)),
                         "r"(hadd2_bf16(w[4 * i + 3], p.w)) : "memory");
        }
        __syncwarp();
        uint4* const dst = reinterpret_cast<uint4*>(out) + (16 * (c >> 4) + 2 * (4 * rh + wq) + (rb2 & 1) + 128 * (lane >> 4)) * 64 + nq * 16 + (lane & 15);
#pragma unroll
        for (int i = 0; i < 8; i++) {
          const int r = 2 * (i & 3) + (lane >> 4);
          dst[i * 256 * 64] = lds4(pa0 + (9 + (i >> 2)) * SLOT + r * 256 + (((lane & 15) ^ r) * 16));
        }
      }
      PROF(12);
      PROFG(15);
    }
  }
#undef BAR
#undef TOFF
#undef RBAR
}

typedef CUresult (*EncodeFn)(CUtensorMap*, CUtensorMapDataType, cuuint32_t, void*, const cuuint64_t*, const cuuint64_t*,
                             const cuuint32_t*, const cuuint32_t*, CUtensorMapInterleave, CUtensorMapSwizzle,
                             CUtensorMapL2promotion, CUtensorMapFloatOOBfill);

}

extern "C" void kernel_launch(void* const* d_in, const int* in_sizes, int n_in, void* d_out, int out_size) {
  (void)in_sizes; (void)n_in; (void)out_size;
  static EncodeFn encode = nullptr;
  static void *tab = nullptr, *scr = nullptr;
  if (!encode) {
    void* fn = nullptr;
    cudaDriverEntryPointQueryResult qr;
    cudaGetDriverEntryPoint("cuTensorMapEncodeTiled", &fn, cudaEnableDefault, &qr);
    encode = (EncodeFn)fn;
    cudaGetSymbolAddress(&tab, g_tab);
    cudaGetSymbolAddress(&scr, g_scr);
    cudaFuncSetAttribute(fused_kernel, cudaFuncAttributeMaxDynamicSharedMemorySize, SMEM_BYTES);
  }
  CUtensorMap tmGX, tmUX, tmGY, tmUY, tmD, tmWR, tmWI;
  const cuuint32_t es[5] = {1, 1, 1, 1, 1};
  auto enc = [&](CUtensorMap* m, void* p, int rank, const cuuint64_t* gd, const cuuint64_t* gs, const cuuint32_t* bd,
                 CUtensorMapSwizzle sw, CUtensorMapL2promotion pr) {
    encode(m, CU_TENSOR_MAP_DATA_TYPE_BFLOAT16, rank, p, gd, gs, bd, es, CU_TENSOR_MAP_INTERLEAVE_NONE, sw, pr,
           CU_TENSOR_MAP_FLOAT_OOB_FILL_NONE);
  };
  {
    const cuuint64_t gd[3] = {64, 512, 28}, gs[2] = {3584, 128};
    const cuuint32_t bd[3] = {64, 32, 2};
    enc(&tmGX, d_in[4], 3, gd, gs, bd, CU_TENSOR_MAP_SWIZZLE_128B, CU_TENSOR_MAP_L2_PROMOTION_L2_256B);
    enc(&tmUX, d_in[5], 3, gd, gs, bd, CU_TENSOR_MAP_SWIZZLE_128B, CU_TENSOR_MAP_L2_PROMOTION_L2_256B);
  }
  {
    const cuuint64_t gd[3] = {32, 512, 56}, gs[2] = {3584, 64};
    const cuuint32_t bd[3] = {32, 32, 3};
    enc(&tmGY, d_in[4], 3, gd, gs, bd, CU_TENSOR_MAP_SWIZZLE_64B, CU_TENSOR_MAP_L2_PROMOTION_L2_128B);
    enc(&tmUY, d_in[5], 3, gd, gs, bd, CU_TENSOR_MAP_SWIZZLE_64B, CU_TENSOR_MAP_L2_PROMOTION_L2_128B);
  }
  {
    const cuuint64_t gd[3] = {64, 1792, 8}, gs[2] = {1024, 128};
    const cuuint32_t bd[3] = {64, 64, 2};
    enc(&tmD, d_in[6], 3, gd, gs, bd, CU_TENSOR_MAP_SWIZZLE_128B, CU_TENSOR_MAP_L2_PROMOTION_L2_256B);
  }
  {
    const cuuint64_t gd[3] = {4112, 8, 16}, gs[2] = {16 * 8224, 8224};
    const cuuint32_t bd[3] = {40, 8, 16};
    enc(&tmWR, d_in[1], 3, gd, gs, bd, CU_TENSOR_MAP_SWIZZLE_NONE, CU_TENSOR_MAP_L2_PROMOTION_NONE);
    enc(&tmWI, d_in[2], 3, gd, gs, bd, CU_TENSOR_MAP_SWIZZLE_NONE, CU_TENSOR_MAP_L2_PROMOTION_NONE);
  }
  fused_kernel<<<NCTA, NTHREADS, SMEM_BYTES>>>((const __nv_bfloat16*)d_in[0], (const Tables*)tab, (Scratch*)scr,
                                               (__nv_bfloat16*)d_out, (const char*)d_in[4], (const char*)d_in[5],
                                               (const char*)d_in[6], tmWR, tmWI, tmGX, tmUX, tmGY, tmUY, tmD);
}
```

```cpp
#include <cuda_runtime.h>
#include <cuda_bf16.h>
#include <cuda.h>
#include <stdint.h>

namespace {

constexpr int NCTA = 128;
constexpr int NTHREADS = 384;
constexpr int SLOT = 16384;
constexpr int SMEM_BYTES = 14 * SLOT + 3072;
constexpr int SPIN_LIMIT = 1 << 22;

struct Scratch {
  uint4 Z1[128 * 1024];
  uint4 Z2[128 * 1024];
  uint4 LN[16 * 8 * 1024];
  uint4 P[16 * 28 * 1024];
  uint4 XP[128 * 1024];
  uint4 ST[1024];
  unsigned cnt[64 * 32];
};
__device__ __align__(1024) Scratch g_scr;
#define PROF(i)
#define PROFP(i)
#define PROFG(i)

constexpr double ccos(int i, int n) {
  i &= n - 1;
  if (i > n / 2) i = n - i;
  if (4 * i == n) return 0.0;
  const bool neg = 4 * i > n;
  if (neg) i = n / 2 - i;
  const double a = 6.283185307179586476925 * i / n, a2 = a * a;
  double term = 1.0, sum = 1.0;
  for (int k = 1; k < 14; k++) { term *= -a2 / ((2 * k - 1) * (2 * k)); sum += term; }
  return neg ? -sum : sum;
}
constexpr double csin(int i, int n) { return ccos(i - n / 4, n); }
constexpr unsigned fbits(double v, int mant) {
  if (v == 0.0) return 0;
  const unsigned sg = v < 0 ? 1u : 0u;
  if (v < 0) v = -v;
  int e = 127;
  while (v < 1.0) { v *= 2.0; e--; }
  const unsigned m = (unsigned)((v - 1.0) * (double)(1u << mant) + 0.5);
  return (sg << (8 + mant)) + ((unsigned)e << mant) + m;
}
constexpr unsigned pkb(double lo, double hi) { return fbits(lo, 7) | (fbits(hi, 7) << 16); }
constexpr double fa_elem(int mt, int r, int n1) {
  const int k1 = 8 * mt + (r & 7);
  return r < 8 ? ccos(k1 * n1, 32) : k1 == 0 ? ccos(16 * n1, 32) : -csin(k1 * n1, 32);
}
constexpr unsigned cfrag_c(int idx, int n, int ri, double s = 1.0) {
  return ri ? pkb(-s * csin(idx, n), s * ccos(idx, n)) : pkb(s * ccos(idx, n), s * csin(idx, n));
}
struct Tables {
  unsigned fa[4][32][4];
  unsigned fb[4][32][4];
  unsigned tw1[6][32][4];
  unsigned f2[8][4][32][4];
  unsigned g2[8][4][32][4];
  unsigned gb[4][32][4];
  unsigned ga[4][32][4];
  unsigned tw3[4][32][4];
  unsigned f8[32][4], g8[32][4];
};
constexpr int T1_BYTES = 7168, T2_BYTES = 39936;
static_assert(sizeof(Tables) == T1_BYTES + T2_BYTES, "table size");
constexpr Tables make_tables() {
  Tables T = {};
  for (int l = 0; l < 32; l++) {
    const int g = l >> 2, t = l & 3;
    for (int a = 0; a < 2; a++)
      for (int b = 0; b < 2; b++) {
        for (int r = 0; r < 4; r++) {
          const int row = g + 8 * (r & 1), col = 2 * t + 8 * (r >> 1);
          T.fa[2 * a + b][l][r] = pkb(fa_elem(a, row, 16 * b + col), fa_elem(a, row, 16 * b + col + 1));
          T.ga[2 * a + b][l][r] = pkb(fa_elem(b, col, 16 * a + row), fa_elem(b, col + 1, 16 * a + row));
        }
        const double sg = b ? -1.0 : 1.0;
        for (int h = 0; h < 2; h++) {
          const int ri = g & 1, m = 2 * (g >> 1) + h, k2 = b ? 15 - m : m;
          const int pa = (8 * a + 2 * t) * k2, pb = (8 * a + 2 * t + 1) * k2;
          T.fb[2 * a + b][l][2 * h] = ri == 0 ? pkb(ccos(pa, 16), ccos(pb, 16)) : pkb(-sg * csin(pa, 16), -sg * csin(pb, 16));
          T.fb[2 * a + b][l][2 * h + 1] = ri == 0 ? pkb(csin(pa, 16), csin(pb, 16)) : pkb(sg * ccos(pa, 16), sg * ccos(pb, 16));
        }
        const int n2 = 4 * (g >> 1) + 2 * a + (g & 1);
        for (int h = 0; h < 2; h++) {
          const int p = n2 * (b ? 15 - 2 * t - h : 2 * t + h);
          T.gb[2 * a + b][l][2 * h] = pkb(ccos(p, 16), -sg * csin(p, 16));
          T.gb[2 * a + b][l][2 * h + 1] = pkb(csin(p, 16), sg * ccos(p, 16));
          const int k1 = 8 * b + 2 * t + h, q = n2 * (k1 == 0 ? 16 : k1);
          T.tw3[2 * a + b][l][2 * h] = fbits(ccos(q, 512), 23);
          T.tw3[2 * a + b][l][2 * h + 1] = fbits(csin(q, 512), 23);
        }
        const int p = (8 * a + 2 * t + b) * (g == 0 ? 16 : g);
        T.tw1[2 * a + b][l][0] = fbits(g == 0 ? 0.0 : ccos(p, 512), 23);
        T.tw1[2 * a + b][l][1] = fbits(g == 0 ? ccos(p, 512) : csin(p, 512), 23);
        T.tw1[2 * a + b][l][2] = fbits(g == 0 ? 0.0 : -csin(p, 512), 23);
        T.tw1[2 * a + b][l][3] = fbits(g == 0 ? -csin(p, 512) : ccos(p, 512), 23);
        T.tw1[4 + a][l][2 * b] = fbits(ccos((8 * a + 2 * t + b) * (g + 8), 512), 23);
        T.tw1[4 + a][l][2 * b + 1] = fbits(csin((8 * a + 2 * t + b) * (g + 8), 512), 23);
      }
    for (int i = 0; i < 4; i++) {
      const int p8 = (t + 4 * (i & 1)) * (4 * (i >> 1) + (g >> 1));
      T.f8[l][i] = cfrag_c(p8, 8, g & 1);
      T.g8[l][i] = cfrag_c(-p8, 8, g & 1, 1.0 / (1 << 19));
    }
    for (int w = 0; w < 8; w++)
      for (int i = 0; i < 16; i++) {
        const int kidx = t + 4 * (i & 1) + 8 * (i >> 3), nidx = 4 * ((i >> 1) & 3) + (g >> 1);
        T.f2[w][i >> 2][l][i & 3] = cfrag_c((8 * kidx + w) * nidx, 128, g & 1);
        T.g2[w][i >> 2][l][i & 3] = cfrag_c(-(8 * nidx + w) * kidx, 128, g & 1);
      }
  }
  return T;
}
__device__ const __align__(128) Tables g_tab = make_tables();

__device__ __forceinline__ void die() { asm volatile("st.global.u32 [%0], %1;" ::"l"(0ull), "r"(0) : "memory"); }
__device__ __forceinline__ uint32_t s2u(const void* p) { return (uint32_t)__cvta_generic_to_shared(p); }
__device__ __forceinline__ void mbar_init(uint32_t b, int c) { asm volatile("mbarrier.init.shared::cta.b64 [%0], %1;" ::"r"(b), "r"(c)); }
__device__ __forceinline__ void mbar_expect(uint32_t b, int bytes) {
  asm volatile("mbarrier.arrive.expect_tx.shared::cta.b64 _, [%0], %1;" ::"r"(b), "r"(bytes) : "memory");
}
__device__ __forceinline__ void mbar_arrive(uint32_t b) { asm volatile("mbarrier.arrive.shared::cta.b64 _, [%0];" ::"r"(b) : "memory"); }
__device__ __forceinline__ uint32_t mbar_try(uint32_t b, uint32_t parity) {
  uint32_t ok;
  asm volatile("{.reg .pred p; mbarrier.try_wait.parity.shared::cta.b64 p, [%1], %2; selp.u32 %0,1,0,p;}"
               : "=r"(ok) : "r"(b), "r"(parity) : "memory");
  return ok;
}
__device__ __forceinline__ uint32_t mbar_test(uint32_t b) {
  uint32_t ok;
  asm volatile("{.reg .pred p; mbarrier.test_wait.parity.shared::cta.b64 p, [%1], 0; selp.u32 %0,1,0,p;}" : "=r"(ok) : "r"(b) : "memory");
  return ok;
}
__device__ __forceinline__ void mbar_wait(uint32_t b, uint32_t parity = 0) {
  int it = 0;
#pragma unroll 1
  while (!mbar_try(b, parity))
    if (++it > SPIN_LIMIT) { die(); break; }
}
__device__ __forceinline__ void bar_sync(int id, int n) { asm volatile("bar.sync %0, %1;" ::"r"(id), "r"(n) : "memory"); }
__device__ __forceinline__ void bar_arrive(int id, int n) { asm volatile("bar.arrive %0, %1;" ::"r"(id), "r"(n) : "memory"); }
__device__ __forceinline__ void red_release(unsigned* p) { asm volatile("red.release.gpu.global.add.u32 [%0], 1;" ::"l"(p) : "memory"); }
__device__ __forceinline__ void red_relaxed(unsigned* p) { asm volatile("red.relaxed.gpu.global.add.u32 [%0], 1;" ::"l"(p) : "memory"); }
__device__ __forceinline__ unsigned ld_acquire(const unsigned* p) {
  unsigned v;
  asm volatile("ld.acquire.gpu.global.u32 %0, [%1];" : "=r"(v) : "l"(p) : "memory");
  return v;
}
__device__ __forceinline__ unsigned ld_relaxed(const unsigned* p) {
  unsigned v;
  asm volatile("ld.relaxed.gpu.global.u32 %0, [%1];" : "=r"(v) : "l"(p) : "memory");
  return v;
}
__device__ __forceinline__ void wait_counter(const unsigned* p, unsigned target) {
  int it = 0;
  while ((int)(ld_acquire(p) - target) < 0)
    if (++it > SPIN_LIMIT) { die(); break; }
}
__device__ __forceinline__ void sts4(uint32_t a, uint32_t x, uint32_t y, uint32_t z, uint32_t w) {
  asm volatile("st.shared.v4.u32 [%0], {%1,%2,%3,%4};" ::"r"(a), "r"(x), "r"(y), "r"(z), "r"(w) : "memory");
}
__device__ __forceinline__ uint4 lds4(uint32_t a) {
  uint4 v;
  asm volatile("ld.shared.v4.u32 {%0,%1,%2,%3}, [%4];" : "=r"(v.x), "=r"(v.y), "=r"(v.z), "=r"(v.w) : "r"(a) : "memory");
  return v;
}
__device__ __forceinline__ uint32_t pack2(float lo, float hi) {
  uint32_t r;
  asm("cvt.rn.bf16x2.f32 %0, %1, %2;" : "=r"(r) : "f"(hi), "f"(lo));
  return r;
}
__device__ __forceinline__ float bf_lo(uint32_t v) { return __uint_as_float(v << 16); }
__device__ __forceinline__ uint32_t hadd2_bf16(uint32_t a, uint32_t b) {
  uint32_t r;
  asm("add.rn.bf16x2 %0, %1, %2;" : "=r"(r) : "r"(a), "r"(b));
  return r;
}
__device__ __forceinline__ void mma16816(float (&d)[4], uint32_t a0, uint32_t a1, uint32_t a2, uint32_t a3, uint32_t b0, uint32_t b1) {
  asm("mma.sync.aligned.m16n8k16.row.col.f32.bf16.bf16.f32 {%0,%1,%2,%3}, {%4,%5,%6,%7}, {%8,%9}, {%0,%1,%2,%3};"
      : "+f"(d[0]), "+f"(d[1]), "+f"(d[2]), "+f"(d[3])
      : "r"(a0), "r"(a1), "r"(a2), "r"(a3), "r"(b0), "r"(b1));
}
__device__ __forceinline__ void mma16816_z(float (&d)[4], uint32_t a0, uint32_t a1, uint32_t a2, uint32_t a3, uint32_t b0, uint32_t b1) {
  asm("{.reg .f32 z; mov.f32 z, 0f00000000;\n"
      "mma.sync.aligned.m16n8k16.row.col.f32.bf16.bf16.f32 {%0,%1,%2,%3}, {%4,%5,%6,%7}, {%8,%9}, {z,z,z,z};}"
      : "=f"(d[0]), "=f"(d[1]), "=f"(d[2]), "=f"(d[3])
      : "r"(a0), "r"(a1), "r"(a2), "r"(a3), "r"(b0), "r"(b1));
}
template <int N>
__device__ __forceinline__ void cs_frac(int idx, float& c, float& s) {
  int i = ((idx + N / 2) & (N - 1)) - N / 2;
  float a = (float)i * (6.283185307179586f / N);
  c = __cosf(a);
  s = __sinf(a);
}
template <int N>
__device__ __forceinline__ uint32_t cfrag(int idx, int ri) {
  float c, s;
  cs_frac<N>(idx, c, s);
  return ri ? pack2(-s, c) : pack2(c, s);
}
__device__ __forceinline__ uint32_t word(const uint4& v, int e) { return e == 0 ? v.x : e == 1 ? v.y : e == 2 ? v.z : v.w; }
__device__ __forceinline__ void cdft16(const uint4 (&A)[4], const uint4 (&F)[4], uint4 (&o)[4]) {
  float acc[2][4][4];
#pragma unroll
  for (int ks = 0; ks < 2; ks++)
#pragma unroll
    for (int p = 0; p < 2; p++)
#pragma unroll
      for (int v = 0; v < 4; v++) {
        const uint4& a = A[2 * ks + p];
        const uint32_t b0 = word(F[ks * 2 + (v >> 1)], (v & 1) * 2), b1 = word(F[ks * 2 + (v >> 1)], (v & 1) * 2 + 1);
        if (ks == 0) mma16816_z(acc[p][v], a.x, a.y, a.z, a.w, b0, b1);
        else mma16816(acc[p][v], a.x, a.y, a.z, a.w, b0, b1);
      }
#pragma unroll
  for (int v = 0; v < 4; v++)
    o[v] = make_uint4(pack2(acc[0][v][0], acc[0][v][1]), pack2(acc[0][v][2], acc[0][v][3]),
                      pack2(acc[1][v][0], acc[1][v][1]), pack2(acc[1][v][2], acc[1][v][3]));
}
__device__ __forceinline__ void lds_frag(uint4& f0, uint4& f1, uint32_t a0, uint32_t a1) {
  asm volatile("ld.volatile.shared.v2.u32 {%0,%1}, [%8]; ld.volatile.shared.v2.u32 {%2,%3}, [%9];\n"
               "ld.volatile.shared.v2.u32 {%4,%5}, [%8+8]; ld.volatile.shared.v2.u32 {%6,%7}, [%9+8];"
               : "=r"(f0.x), "=r"(f0.y), "=r"(f0.z), "=r"(f0.w), "=r"(f1.x), "=r"(f1.y), "=r"(f1.z), "=r"(f1.w) : "r"(a0), "r"(a1) : "memory");
}
__device__ __forceinline__ void reg_frag(uint4 (&q)[4], uint32_t ones) {
#pragma unroll
  for (int ks = 0; ks < 2; ks++) {
    const uint4 a = q[2 * ks], b = q[2 * ks + 1];
    q[2 * ks] = make_uint4(a.x, a.y, b.x & ones, b.y & ones);
    q[2 * ks + 1] = make_uint4(a.z & ones, a.w & ones, b.z, b.w);
  }
}
__device__ __forceinline__ void st_tag(uint4* p, const uint4& v, uint32_t tag) {
  asm volatile("st.relaxed.gpu.global.v4.b32 [%0], {%1,%2,%3,%4};"
               ::"l"(p), "r"((v.x & ~1u) | tag), "r"(v.y), "r"(v.z), "r"(v.w) : "memory");
}
__device__ __forceinline__ void st_tag8(void* p, uint32_t x, uint32_t y, uint32_t tag) {
  asm volatile("st.relaxed.gpu.global.v2.b32 [%0], {%1,%2};" ::"l"(p), "r"((x & ~1u) | tag), "r"(y) : "memory");
}
__device__ __forceinline__ uint4 ld_b128(const uint4* p) {
  uint4 v;
  asm volatile("ld.relaxed.gpu.global.v4.b32 {%0,%1,%2,%3}, [%4];"
               : "=r"(v.x), "=r"(v.y), "=r"(v.z), "=r"(v.w) : "l"(p) : "memory");
  return v;
}
template <int STRIDE>
__device__ __forceinline__ void ld_tag4_issue(uint4 (&q)[4], const uint4* p) {
#pragma unroll
  for (int i = 0; i < 4; i++) q[i] = ld_b128(p + i * STRIDE);
}
template <int STRIDE, bool HALVES = false>
__device__ __forceinline__ void ld_tag4_finish(uint4 (&q)[4], const uint4* p, uint32_t tag) {
  int it = 0;
#pragma unroll 1
  while (__any_sync(0xffffffffu, ((q[0].x ^ tag) | (q[1].x ^ tag) | (q[2].x ^ tag) | (q[3].x ^ tag) |
                                  (HALVES ? (q[0].z ^ tag) | (q[1].z ^ tag) | (q[2].z ^ tag) | (q[3].z ^ tag) : 0u)) & 1u)) {
    ld_tag4_issue<STRIDE>(q, p);
    if (++it > SPIN_LIMIT) { die(); break; }
  }
#pragma unroll
  for (int i = 0; i < 4; i++) {
    asm volatile("and.b32 %0, %0, 0xfffffffe;" : "+r"(q[i].x));
    if (HALVES) q[i].z &= ~1u;
  }
}
__device__ __forceinline__ float quad_sum(const uint32_t (&a)[8]) {
  float d[4];
  mma16816_z(d, a[0], a[1], a[2], a[3], 0x3f803f80u, 0x3f803f80u);
  mma16816(d, a[4], a[5], a[6], a[7], 0x3f803f80u, 0x3f803f80u);
  return d[0] + d[2];
}
__device__ __forceinline__ float sum_groups(float v) {
  v += __shfl_xor_sync(0xffffffffu, v, 4);
  v += __shfl_xor_sync(0xffffffffu, v, 8);
  v += __shfl_xor_sync(0xffffffffu, v, 16);
  return v;
}
__device__ __forceinline__ uint32_t hsub2_bf16(uint32_t a, uint32_t b) {
  uint32_t r;
  asm("sub.rn.bf16x2 %0, %1, %2;" : "=r"(r) : "r"(a), "r"(b));
  return r;
}
__device__ __forceinline__ float row_rstd(const uint32_t (&c)[8], float delta) {
  uint32_t s[8];
#pragma unroll
  for (int i = 0; i < 8; i++) asm("mul.rn.bf16x2 %0, %1, %1;" : "=r"(s[i]) : "r"(c[i]));
  return rsqrtf(fmaxf(fmaf(-delta, delta, sum_groups(quad_sum(s)) * (1.f / 512.f)), 0.f) + 1e-5f);
}
__device__ __forceinline__ uint64_t desc64(uint32_t lo, uint32_t hi) {
  uint64_t d;
  asm("mov.b64 %0, {%1, %2};" : "=l"(d) : "r"(lo), "r"(hi));
  return d;
}
constexpr uint32_t desc_hi(uint32_t sbo, uint32_t swz) { return (sbo >> 4) | (swz << 30); }
__device__ __forceinline__ uint32_t desc_lo(uint32_t addr, uint32_t lbo) { return ((addr & 0x3FFFF) >> 4) | ((lbo >> 4) << 16); }
__device__ __forceinline__ void cp_async16(uint32_t dst, const void* src) {
  asm volatile("cp.async.cg.shared.global [%0], [%1], 16;" ::"r"(dst), "l"(src) : "memory");
}
__device__ __forceinline__ uint2 lds2(uint32_t a) {
  uint2 v;
  asm volatile("ld.shared.v2.u32 {%0,%1}, [%2];" : "=r"(v.x), "=r"(v.y) : "r"(a) : "memory");
  return v;
}
__device__ __forceinline__ uint32_t lds_u16(uint32_t a) {
  uint16_t v;
  asm volatile("ld.shared.u16 %0, [%1];" : "=h"(v) : "r"(a) : "memory");
  return v;
}
__device__ __forceinline__ void wg_fence() { asm volatile("wgmma.fence.sync.aligned;" ::: "memory"); }
__device__ __forceinline__ void wg_commit() { asm volatile("wgmma.commit_group.sync.aligned;" ::: "memory"); }
template <int N>
__device__ __forceinline__ void wg_wait() { asm volatile("wgmma.wait_group.sync.aligned %0;" ::"n"(N) : "memory"); }
__device__ __forceinline__ void bulk_load(uint32_t dst, const void* src, int bytes, uint32_t bar) {
  asm volatile("cp.async.bulk.shared::cluster.global.mbarrier::complete_tx::bytes [%0], [%1], %2, [%3];"
               ::"r"(dst), "l"(src), "r"(bytes), "r"(bar) : "memory");
}
__device__ __forceinline__ void bulk_load_mc(uint32_t dst, const void* src, int bytes, uint32_t bar) {
  asm volatile("cp.async.bulk.shared::cluster.global.mbarrier::complete_tx::bytes.multicast::cluster [%0], [%1], %2, [%3], %4;"
               ::"r"(dst), "l"(src), "r"(bytes), "r"(bar), "h"((uint16_t)3) : "memory");
}
__device__ __forceinline__ void tma3(uint32_t dst, const CUtensorMap* tm, uint32_t bar, int c0, int c1, int c2) {
  asm volatile("cp.async.bulk.tensor.3d.shared::cluster.global.mbarrier::complete_tx::bytes [%0], [%1, {%3,%4,%5}], [%2];"
               ::"r"(dst), "l"(tm), "r"(bar), "r"(c0), "r"(c1), "r"(c2) : "memory");
}
__device__ __forceinline__ void tma3_mc(uint32_t dst, const CUtensorMap* tm, uint32_t bar, int c1, int c2) {
  asm volatile("cp.async.bulk.tensor.3d.shared::cluster.global.mbarrier::complete_tx::bytes.multicast::cluster [%0], [%1, {%3,%4,%5}], [%2], %6;"
               ::"r"(dst), "l"(tm), "r"(bar), "r"(0), "r"(c1), "r"(c2), "h"((uint16_t)3) : "memory");
}
__device__ __forceinline__ void mbar_arrive_remote(uint32_t rb) {
  asm volatile("mbarrier.arrive.shared::cluster.b64 _, [%0];" ::"r"(rb) : "memory");
}
__device__ __forceinline__ uint4 ldg_ca4(const void* p) {
  uint4 v;
  asm volatile("ld.global.ca.v4.u32 {%0,%1,%2,%3}, [%4];" : "=r"(v.x), "=r"(v.y), "=r"(v.z), "=r"(v.w) : "l"(p) : "memory");
  return v;
}
__device__ __forceinline__ float u2f(uint32_t v) { return __uint_as_float(v); }
__device__ __forceinline__ void mma_az(float (&d)[4], const uint4& a, uint32_t b0, uint32_t b1) { mma16816_z(d, a.x, a.y, a.z, a.w, b0, b1); }
__device__ __forceinline__ void mma_a(float (&d)[4], const uint4& a, uint32_t b0, uint32_t b1) { mma16816(d, a.x, a.y, a.z, a.w, b0, b1); }
__device__ __forceinline__ uint32_t clock32() {
  uint32_t v;
  asm volatile("mov.u32 %0, %%clock;" : "=r"(v) :: "memory");
  return v;
}
__device__ __forceinline__ float swiglu(float g, float u, float r) {
  float hg = (0.5f * r) * g, th;
  asm("tanh.approx.f32 %0, %1;" : "=f"(th) : "f"(hg));
  return fmaf(hg, th, hg) * (r * u);
}
__device__ __forceinline__ void l2_prefetch(const void* p, int bytes) {
  asm volatile("cp.async.bulk.prefetch.L2.global [%0], %1;" ::"l"(p), "r"(bytes) : "memory");
}

__device__ __forceinline__ void wgmma_n256(float (&d)[128], uint64_t da, uint64_t db, int sd = 1) {
  asm volatile("{.reg .pred p; setp.ne.b32 p, %130, 0;\n"
      "wgmma.mma_async.sync.aligned.m64n256k16.f32.bf16.bf16 {"
      "%0,%1,%2,%3,%4,%5,%6,%7,%8,%9,%10,%11,%12,%13,%14,%15,"
      "%16,%17,%18,%19,%20,%21,%22,%23,%24,%25,%26,%27,%28,%29,%30,%31,"
      "%32,%33,%34,%35,%36,%37,%38,%39,%40,%41,%42,%43,%44,%45,%46,%47,"
      "%48,%49,%50,%51,%52,%53,%54,%55,%56,%57,%58,%59,%60,%61,%62,%63,"
      "%64,%65,%66,%67,%68,%69,%70,%71,%72,%73,%74,%75,%76,%77,%78,%79,"
      "%80,%81,%82,%83,%84,%85,%86,%87,%88,%89,%90,%91,%92,%93,%94,%95,"
      "%96,%97,%98,%99,%100,%101,%102,%103,%104,%105,%106,%107,%108,%109,%110,%111,"
      "%112,%113,%114,%115,%116,%117,%118,%119,%120,%121,%122,%123,%124,%125,%126,%127"
      "}, %128, %129, p, 1, 1, 0, 1;}\n"
      : "+f"(d[0]),"+f"(d[1]),"+f"(d[2]),"+f"(d[3]),"+f"(d[4]),"+f"(d[5]),"+f"(d[6]),"+f"(d[7]),
        "+f"(d[8]),"+f"(d[9]),"+f"(d[10]),"+f"(d[11]),"+f"(d[12]),"+f"(d[13]),"+f"(d[14]),"+f"(d[15]),
        "+f"(d[16]),"+f"(d[17]),"+f"(d[18]),"+f"(d[19]),"+f"(d[20]),"+f"(d[21]),"+f"(d[22]),"+f"(d[23]),
        "+f"(d[24]),"+f"(d[25]),"+f"(d[26]),"+f"(d[27]),"+f"(d[28]),"+f"(d[29]),"+f"(d[30]),"+f"(d[31]),
        "+f"(d[32]),"+f"(d[33]),"+f"(d[34]),"+f"(d[35]),"+f"(d[36]),"+f"(d[37]),"+f"(d[38]),"+f"(d[39]),
        "+f"(d[40]),"+f"(d[41]),"+f"(d[42]),"+f"(d[43]),"+f"(d[44]),"+f"(d[45]),"+f"(d[46]),"+f"(d[47]),
        "+f"(d[48]),"+f"(d[49]),"+f"(d[50]),"+f"(d[51]),"+f"(d[52]),"+f"(d[53]),"+f"(d[54]),"+f"(d[55]),
        "+f"(d[56]),"+f"(d[57]),"+f"(d[58]),"+f"(d[59]),"+f"(d[60]),"+f"(d[61]),"+f"(d[62]),"+f"(d[63]),
        "+f"(d[64]),"+f"(d[65]),"+f"(d[66]),"+f"(d[67]),"+f"(d[68]),"+f"(d[69]),"+f"(d[70]),"+f"(d[71]),
        "+f"(d[72]),"+f"(d[73]),"+f"(d[74]),"+f"(d[75]),"+f"(d[76]),"+f"(d[77]),"+f"(d[78]),"+f"(d[79]),
        "+f"(d[80]),"+f"(d[81]),"+f"(d[82]),"+f"(d[83]),"+f"(d[84]),"+f"(d[85]),"+f"(d[86]),"+f"(d[87]),
        "+f"(d[88]),"+f"(d[89]),"+f"(d[90]),"+f"(d[91]),"+f"(d[92]),"+f"(d[93]),"+f"(d[94]),"+f"(d[95]),
        "+f"(d[96]),"+f"(d[97]),"+f"(d[98]),"+f"(d[99]),"+f"(d[100]),"+f"(d[101]),"+f"(d[102]),"+f"(d[103]),
        "+f"(d[104]),"+f"(d[105]),"+f"(d[106]),"+f"(d[107]),"+f"(d[108]),"+f"(d[109]),"+f"(d[110]),"+f"(d[111]),
        "+f"(d[112]),"+f"(d[113]),"+f"(d[114]),"+f"(d[115]),"+f"(d[116]),"+f"(d[117]),"+f"(d[118]),"+f"(d[119]),
        "+f"(d[120]),"+f"(d[121]),"+f"(d[122]),"+f"(d[123]),"+f"(d[124]),"+f"(d[125]),"+f"(d[126]),"+f"(d[127])
      : "l"(da), "l"(db), "r"(sd));
}
__device__ __forceinline__ void wgmma_n192(float (&d)[96], uint64_t da, uint64_t db) {
  asm volatile("wgmma.mma_async.sync.aligned.m64n192k16.f32.bf16.bf16 {"
      "%0,%1,%2,%3,%4,%5,%6,%7,%8,%9,%10,%11,%12,%13,%14,%15,"
      "%16,%17,%18,%19,%20,%21,%22,%23,%24,%25,%26,%27,%28,%29,%30,%31,"
      "%32,%33,%34,%35,%36,%37,%38,%39,%40,%41,%42,%43,%44,%45,%46,%47,"
      "%48,%49,%50,%51,%52,%53,%54,%55,%56,%57,%58,%59,%60,%61,%62,%63,"
      "%64,%65,%66,%67,%68,%69,%70,%71,%72,%73,%74,%75,%76,%77,%78,%79,"
      "%80,%81,%82,%83,%84,%85,%86,%87,%88,%89,%90,%91,%92,%93,%94,%95"
      "}, %96, %97, 1, 1, 1, 0, 1;\n"
      : "+f"(d[0]),"+f"(d[1]),"+f"(d[2]),"+f"(d[3]),"+f"(d[4]),"+f"(d[5]),"+f"(d[6]),"+f"(d[7]),
        "+f"(d[8]),"+f"(d[9]),"+f"(d[10]),"+f"(d[11]),"+f"(d[12]),"+f"(d[13]),"+f"(d[14]),"+f"(d[15]),
        "+f"(d[16]),"+f"(d[17]),"+f"(d[18]),"+f"(d[19]),"+f"(d[20]),"+f"(d[21]),"+f"(d[22]),"+f"(d[23]),
        "+f"(d[24]),"+f"(d[25]),"+f"(d[26]),"+f"(d[27]),"+f"(d[28]),"+f"(d[29]),"+f"(d[30]),"+f"(d[31]),
        "+f"(d[32]),"+f"(d[33]),"+f"(d[34]),"+f"(d[35]),"+f"(d[36]),"+f"(d[37]),"+f"(d[38]),"+f"(d[39]),
        "+f"(d[40]),"+f"(d[41]),"+f"(d[42]),"+f"(d[43]),"+f"(d[44]),"+f"(d[45]),"+f"(d[46]),"+f"(d[47]),
        "+f"(d[48]),"+f"(d[49]),"+f"(d[50]),"+f"(d[51]),"+f"(d[52]),"+f"(d[53]),"+f"(d[54]),"+f"(d[55]),
        "+f"(d[56]),"+f"(d[57]),"+f"(d[58]),"+f"(d[59]),"+f"(d[60]),"+f"(d[61]),"+f"(d[62]),"+f"(d[63]),
        "+f"(d[64]),"+f"(d[65]),"+f"(d[66]),"+f"(d[67]),"+f"(d[68]),"+f"(d[69]),"+f"(d[70]),"+f"(d[71]),
        "+f"(d[72]),"+f"(d[73]),"+f"(d[74]),"+f"(d[75]),"+f"(d[76]),"+f"(d[77]),"+f"(d[78]),"+f"(d[79]),
        "+f"(d[80]),"+f"(d[81]),"+f"(d[82]),"+f"(d[83]),"+f"(d[84]),"+f"(d[85]),"+f"(d[86]),"+f"(d[87]),
        "+f"(d[88]),"+f"(d[89]),"+f"(d[90]),"+f"(d[91]),"+f"(d[92]),"+f"(d[93]),"+f"(d[94]),"+f"(d[95])
      : "l"(da), "l"(db));
}
template <int SD>
__device__ __forceinline__ void wgmma_rs_n128(float (&d)[64], uint32_t a0, uint32_t a1, uint32_t a2, uint32_t a3, uint64_t db) {
  asm volatile("wgmma.mma_async.sync.aligned.m64n128k16.f32.bf16.bf16 {"
      "%0,%1,%2,%3,%4,%5,%6,%7,%8,%9,%10,%11,%12,%13,%14,%15,"
      "%16,%17,%18,%19,%20,%21,%22,%23,%24,%25,%26,%27,%28,%29,%30,%31,"
      "%32,%33,%34,%35,%36,%37,%38,%39,%40,%41,%42,%43,%44,%45,%46,%47,"
      "%48,%49,%50,%51,%52,%53,%54,%55,%56,%57,%58,%59,%60,%61,%62,%63"
      "}, {%64,%65,%66,%67}, %68, %69, 1, 1, 1;\n"
      : "+f"(d[0]),"+f"(d[1]),"+f"(d[2]),"+f"(d[3]),"+f"(d[4]),"+f"(d[5]),"+f"(d[6]),"+f"(d[7]),
        "+f"(d[8]),"+f"(d[9]),"+f"(d[10]),"+f"(d[11]),"+f"(d[12]),"+f"(d[13]),"+f"(d[14]),"+f"(d[15]),
        "+f"(d[16]),"+f"(d[17]),"+f"(d[18]),"+f"(d[19]),"+f"(d[20]),"+f"(d[21]),"+f"(d[22]),"+f"(d[23]),
        "+f"(d[24]),"+f"(d[25]),"+f"(d[26]),"+f"(d[27]),"+f"(d[28]),"+f"(d[29]),"+f"(d[30]),"+f"(d[31]),
        "+f"(d[32]),"+f"(d[33]),"+f"(d[34]),"+f"(d[35]),"+f"(d[36]),"+f"(d[37]),"+f"(d[38]),"+f"(d[39]),
        "+f"(d[40]),"+f"(d[41]),"+f"(d[42]),"+f"(d[43]),"+f"(d[44]),"+f"(d[45]),"+f"(d[46]),"+f"(d[47]),
        "+f"(d[48]),"+f"(d[49]),"+f"(d[50]),"+f"(d[51]),"+f"(d[52]),"+f"(d[53]),"+f"(d[54]),"+f"(d[55]),
        "+f"(d[56]),"+f"(d[57]),"+f"(d[58]),"+f"(d[59]),"+f"(d[60]),"+f"(d[61]),"+f"(d[62]),"+f"(d[63])
      : "r"(a0), "r"(a1), "r"(a2), "r"(a3), "l"(db), "n"(SD));
}

constexpr int C_LN = 0, C_PX = 16, C_PY = 32;
constexpr int NB_CONS = 1, NB_LN = 2, NB_LAG = 4, NB_INIT = 6, NB_RDY = 7, NB_WG = 8;
#define LAGX 3
#define LAGY 3
#define LAG2 6
constexpr int NLL = 2;
#define POLL_DELAY3 600
#define POLL_DELAY 1200
#define FILT_DELAY 600
#define THR_B 0
#define THR_P 0
#define SPEC -1
#define WARM 4
#define HWARM 0
#define TOUCH 1
#define ALEAD 6
#define POLL_DELAY2 1200
#define PF1_WAIT 1
#define HPOS 14
#define RING_SIG 1
#define PF2_SIG 1
constexpr int SM_E = 0, SM_X = 16384, SM_E2 = 32768, SM_W = 49152, SM_FC = 69632, SM_T = 73728 - T1_BYTES;
constexpr unsigned long long KORDER = 0xBA9432DC876510ull;
constexpr unsigned long long BSLOT = 0x76532107653210ull, PSLOT = 0xDCBA984DCBA984ull;
constexpr uint32_t HI128 = desc_hi(1024, 1), HI64 = desc_hi(512, 2);

struct Bars {
  uint64_t full1[32], empty1[32], full2[16], fullA[8], empty2[8], fullP[16], emptyP[8], hbar, tbar, hint[3], sig[2], sbar;
  uint32_t epoch, pad;
};

template <int NK, bool STORE>
__device__ __forceinline__ void make_p(const float (&acc)[NK * 16], float r0, float r1, uint4 (&p)[NK], uint4* pbase, int ks0, uint32_t tag) {
#pragma unroll
  for (int j = 0; j < NK; j++) {
    uint32_t w[4];
#pragma unroll
    for (int i = 0; i < 4; i++) {
      const int a = 8 * j + 2 * i, b = a + NK * 8;
      w[i] = pack2(swiglu(acc[a], acc[b], (i & 1) ? r1 : r0), swiglu(acc[a + 1], acc[b + 1], (i & 1) ? r1 : r0));
    }
    asm volatile("" : "+r"(w[0]), "+r"(w[1]), "+r"(w[2]), "+r"(w[3]));
    p[j] = make_uint4(w[0], w[1], w[2], w[3]);
    if (STORE) st_tag(pbase + ((ks0 + j) >> 2) * 1024 + ((ks0 + j) & 3) * 32, p[j], tag);
  }
}
__device__ __forceinline__ void spin_cycles(uint32_t n) {
  const uint32_t t0 = clock32();
  while (clock32() - t0 < n) {}
}

__device__ __forceinline__ void spin_until(uint32_t t) {
  float d[4] = {0.f, 0.f, 0.f, 0.f};
  while ((int)(clock32() - t) < 0) {
    if (HWARM) asm volatile("mma.sync.aligned.m16n8k16.row.col.f32.bf16.bf16.f32 {%0,%1,%2,%3}, {%4,%4,%4,%4}, {%4,%4}, {%0,%1,%2,%3};"
                            : "+f"(d[0]), "+f"(d[1]), "+f"(d[2]), "+f"(d[3]) : "r"(t));
  }
}

__global__ void __cluster_dims__(2, 1, 1) __launch_bounds__(NTHREADS, 1)
fused_kernel(const __nv_bfloat16* __restrict__ x, const Tables* __restrict__ tab, Scratch* __restrict__ scr,
             __nv_bfloat16* __restrict__ out, const char* __restrict__ wg_raw, const char* __restrict__ wu_raw,
             const char* __restrict__ wd_raw,
             const __grid_constant__ CUtensorMap tmWR, const __grid_constant__ CUtensorMap tmWI,
             const __grid_constant__ CUtensorMap tmGX, const __grid_constant__ CUtensorMap tmUX,
             const __grid_constant__ CUtensorMap tmGY, const __grid_constant__ CUtensorMap tmUY,
             const __grid_constant__ CUtensorMap tmD) {
  extern __shared__ __align__(1024) char smem_raw[];
  const uint32_t sbase = s2u(smem_raw);
  const uint32_t sbar = sbase + 14 * SLOT, sstat = sbar + 1280;
  const int tid = threadIdx.x, lane = tid & 31;
  const int c = blockIdx.x, rk = c & 1, f = (c >> 1) & 7, rb = 2 * (c >> 4) + rk;
  const int rb2 = 2 * (c >> 4) + (f >> 2), kh = (f >> 1) & 1, nq = 2 * (f & 1) + rk;
#define BAR(field, i) (sbar + (uint32_t)offsetof(Bars, field) + 8u * (i))
#define TOFF(field) (sbase + SM_T + (uint32_t)offsetof(Tables, field) + lane * 16)

  if (tid >= 256) {
    asm volatile("setmaxnreg.dec.sync.aligned.u32 56;");
    const int warp = __shfl_sync(0xffffffffu, tid >> 5, 0);
    if (lane == 0) {
      if (warp == 8) {
        if (sbase & 1023) die();
#pragma unroll
        for (int i = 0; i < 16; i++) mbar_init(BAR(emptyP, i), i < 7 ? 16 : i < 8 ? 8 : i == 9 ? 1 + 32 * TOUCH : i < 13 ? 1 : i < 15 ? 8 : 32);
        mbar_expect(BAR(tbar, 0), T2_BYTES + 2 * 10240);
        mbar_expect(BAR(hbar, 0), 16384);
      } else if (warp == 9) {
#pragma unroll
        for (int i = 0; i < 32; i++) mbar_init(BAR(full1, i), 1);
#pragma unroll
        for (int i = 0; i < 32; i++) mbar_expect(BAR(full1, i), i < 16 ? 16384 : 12288);
      } else if (warp == 10) {
#pragma unroll
        for (int i = 0; i < 32; i++) mbar_init(BAR(empty1, i), 16);
#pragma unroll
        for (int i = 0; i < 14; i++) mbar_init(BAR(fullP, i), 1);
#pragma unroll
        for (int i = 0; i < 14; i++) mbar_expect(BAR(fullP, i), 16384);
      } else {
#pragma unroll
        for (int i = 0; i < 32; i++) mbar_init(BAR(full2, i), i < 24 ? 1 : 8);
#pragma unroll
        for (int i = 0; i < 24; i++) mbar_expect(BAR(full2, i), 16384);
      }
      asm volatile("fence.mbarrier_init.release.cluster;" ::: "memory");
    }
    if (tid == 256) {
      const int w0 = ((c >> 3) * 257 + 32 * (c & 7) + 1) & ~7;
      if (FILT_DELAY) {
        asm volatile("prefetch.tensormap [%0];" ::"l"(&tmWR) : "memory");
        asm volatile("prefetch.tensormap [%0];" ::"l"(&tmWI) : "memory");
        spin_cycles(FILT_DELAY);
      }
      tma3(sbase + SM_W, &tmWR, BAR(tbar, 0), w0, 0, 0);
      tma3(sbase + SM_W + 10240, &tmWI, BAR(tbar, 0), w0, 0, 0);
      bulk_load(sbase + SM_T + T1_BYTES, reinterpret_cast<const char*>(tab) + T1_BYTES, T2_BYTES, BAR(tbar, 0));
    }
    if (tid == 288) {
      asm volatile("prefetch.tensormap [%0];" ::"l"(rk ? &tmUX : &tmGX) : "memory");
      asm volatile("prefetch.tensormap [%0];" ::"l"(rk ? &tmUY : &tmGY) : "memory");
      asm volatile("prefetch.tensormap [%0];" ::"l"(&tmD) : "memory");
    }
    if (tid == 320) {
      const unsigned e = ld_relaxed(&scr->cnt[(C_LN + rb) * 32]) >> 3;
      asm volatile("st.shared.u32 [%0], %1;" ::"r"(BAR(epoch, 0)), "r"(e) : "memory");
    }
    __syncwarp();
    asm volatile("barrier.cluster.arrive.relaxed.aligned;" ::: "memory");
    bar_arrive(NB_RDY, 384);
    asm volatile("barrier.cluster.wait.aligned;" ::: "memory");
    bar_sync(NB_INIT, 384);
    unsigned epoch;
    asm volatile("ld.shared.u32 %0, [%1];" : "=r"(epoch) : "r"(BAR(epoch, 0)) : "memory");
    if (warp == 8) {
      if (lane == 0) {
        const int ax = (7 * f + 3 * (f & 1)) >> 1;
        const int ay = 7 * f + ((f & 1) ? 0 : 4);
        const CUtensorMap* tx = rk ? &tmUX : &tmGX;
        const CUtensorMap* ty = rk ? &tmUY : &tmGY;
        if (RING_SIG >= 0) mbar_wait(BAR(sig, RING_SIG));
        uint32_t s = 2;
#pragma unroll 1
        for (int n = 0; n < 16; n++) {
          if (n >= 6) mbar_wait(BAR(empty1, n - 6));
          tma3_mc(sbase + (8 + s) * SLOT + rk * 8192, tx, BAR(full1, n), n * 32, ax);
          if (++s == 6) s = 0;
        }
#pragma unroll 1
        for (int k = 0; k < 16; k++) {
          mbar_wait(BAR(empty1, k < 8 ? 10 + ((12 * k + 11) >> 4) : 8 + k));
          tma3_mc(sbase + 8 * SLOT + (k & 7) * 12288 + rk * 6144, ty, BAR(full1, 16 + k), k * 32, ay);
        }
      }
    } else if (warp == 9) {
      if (lane == 0) {
        mbar_wait(BAR(fullA, 4));
        wait_counter(&scr->cnt[(C_LN + rb2) * 32], (epoch + 1) * 8);
        asm volatile("fence.proxy.async.global;" ::: "memory");
#pragma unroll 1
        for (int i = 0; i < 15; i++) {
          const int kblk = 14 * kh + (int)((KORDER >> (4 * i)) & 15);
          const int j = i < 7 ? i : i - 7, sl = j + (j >= 4);
          if (i == HPOS) {
            mbar_wait(BAR(emptyP, 7));
            bulk_load(sbase + 4 * SLOT, &scr->LN[(rb2 * 8 + 2 * nq) * 1024 + kh * 512], 8192, BAR(hbar, 0));
            bulk_load(sbase + 4 * SLOT + 8192, &scr->LN[(rb2 * 8 + 2 * nq + 1) * 1024 + kh * 512], 8192, BAR(hbar, 0));
          }
          if (i == 14) break;
          mbar_wait(i < 7 ? BAR(empty1, 17 + 2 * sl) : BAR(empty2, j));
          if (THR_B && i >= THR_B) mbar_wait(BAR(full2, i - THR_B));
          tma3(sbase + sl * SLOT, &tmD, BAR(full2, i), 0, 64 * kblk, 2 * nq);
        }
      }
    } else if (warp == 10) {
      bar_sync(NB_LN, 288);
      if (lane == 0) {
        PROFP(0);
        red_release(&scr->cnt[(C_LN + rb) * 32]);
        PROFP(1);
        wait_counter(&scr->cnt[(C_LN + rb) * 32], (epoch + 1) * 8);
        asm volatile("fence.proxy.async.global;" ::: "memory");
        PROFP(2);
#pragma unroll 1
        for (int kb = NLL; kb < 8; kb++) {
          if (2 * kb >= ALEAD) mbar_wait(BAR(empty1, 2 * kb - ALEAD));
          bulk_load(sbase + kb * SLOT, &scr->LN[(rb * 8 + kb) * 1024], 16384, BAR(fullA, kb));
        }
#pragma unroll 1
        for (int s = 0; s < 14; s++) {
          const int kblk = 14 * kh + (int)((KORDER >> (4 * s)) & 15);
          if (s == 0 || (SPEC < 0 && (s == 8 || s == 11))) {
            if (s != 11) PROFP(3 + (s >> 2));
            mbar_wait(BAR(hint, s == 0 ? 0 : s == 8 ? 1 : 2), 0);
            if (s != 11) PROFP(4 + (s >> 2));
          }
          const int j = s < 7 ? s : s - 7;
          mbar_wait(s < 7 ? BAR(empty1, 24 + s + (s == 0) + (s >= 4)) : BAR(emptyP, j));
          if (THR_P && s >= THR_P) mbar_wait(BAR(fullP, s - THR_P));
          if (SPEC >= 0 && s == 8) mbar_wait(BAR(emptyP, SPEC & 7));
          bulk_load_mc(sbase + (j ? 7 + j : 4) * SLOT + rk * 8192, &scr->P[(rb2 * 28 + kblk) * 1024 + rk * 512], 8192, BAR(fullP, s));
        }
        PROFP(7);
      }
    } else {
      if (TOUCH) {
#pragma unroll
        for (int i = 0; i < 4 * NLL; i++)
          st_tag(&scr->LN[(rb * 8 + (i >> 2)) * 1024 + f * 128 + (i & 3) * 32 + lane], make_uint4(0, 0, epoch & 1, 0), epoch & 1);
        mbar_arrive(BAR(tbar, 0));
      }
      if (lane == 0) {
        if (PF1_WAIT) mbar_wait(BAR(tbar, 0));
        l2_prefetch(wg_raw + (size_t)c * 5376, 5376);
        l2_prefetch(wu_raw + (size_t)c * 5376, 5376);
        mbar_wait(BAR(sig, PF2_SIG), 0);
        l2_prefetch(wg_raw + 688128 + (size_t)c * 8960, 8960);
        l2_prefetch(wu_raw + 688128 + (size_t)c * 8960, 8960);
      }
      mbar_wait(BAR(fullA, 4), 0);
      if (lane == 0) l2_prefetch(wd_raw + (size_t)c * 14336, 14336);
      {
        const uint32_t tag = (epoch + 1) & 1;
        uint4 v0, v1, v2;
        int it = 0;
        while (true) {
          v0 = ld_b128(&scr->ST[rb * 64 + lane]);
          v1 = ld_b128(&scr->ST[rb * 64 + 32 + lane]);
          v2 = ld_b128(&scr->ST[rb2 * 64 + 32 * kh + lane]);
          if (!__any_sync(0xffffffffu, ((v0.x ^ tag) | (v1.x ^ tag) | (v2.x ^ tag)) & 1u)) break;
          if (++it > SPIN_LIMIT) { die(); break; }
        }
        sts4(sstat + lane * 16, v0.x & ~1u, v0.y, v0.z, v0.w);
        sts4(sstat + 512 + lane * 16, v1.x & ~1u, v1.y, v1.z, v1.w);
        sts4(sstat + 1024 + lane * 16, v2.x & ~1u, v2.y, v2.z, v2.w);
#pragma unroll 4
        for (int i = 0; i < 32; i++)
          st_tag(&scr->XP[(c ^ 4) * 1024 + i * 32 + lane], make_uint4(0, 0, 0, 0), tag ^ 1);
        mbar_arrive(BAR(sbar, 0));
      }
      if (lane == 0) {
        mbar_wait(BAR(empty1, 17));
#pragma unroll 1
        for (int e = 0; e < (SPEC < 0 ? 3 : 1); e++) {
          const unsigned* cp = e == 0 ? &scr->cnt[(C_PX + rb2) * 32 + kh] : &scr->cnt[(C_PY + rb2) * 32 + 2 * kh + e - 1];
          if (e == 1) mbar_wait(BAR(fullP, 0), 0);
          int it = 0;
          while ((int)(ld_relaxed(cp) - (epoch + 1) * (e == 0 ? 32 : 16)) < 0)
            if (++it > SPIN_LIMIT) { die(); break; }
          mbar_arrive(BAR(hint, e));
        }
      }
    }
  } else {
    const int warp = __shfl_sync(0xffffffffu, tid >> 5, 0);
    const int g = lane >> 2, t = lane & 3;
    PROF(0);
    PROFG(14);
    uint4 fa[4], fb[4], tw[6];
#pragma unroll
    for (int i = 0; i < 4; i++) fa[i] = ldg_ca4(&tab->fa[i][lane][0]);
#pragma unroll
    for (int i = 0; i < 6; i++) tw[i] = ldg_ca4(&tab->tw1[i][lane][0]);
#pragma unroll
    for (int i = 0; i < 4; i++) fb[i] = ldg_ca4(&tab->fb[i][lane][0]);
#pragma unroll
    for (int i = 0; i < 4; i++) {
      const int r = i >> 1, ch = (i & 1) * 32 + lane;
      cp_async16(sbase + SM_X + (2 * warp + r) * 1024 + ((ch ^ ((ch >> 3) & 1)) * 16),
                 x + (size_t)(c + 128 * (2 * warp + r)) * 512 + ch * 8);
    }
    asm volatile("cp.async.commit_group;" ::: "memory");
    asm volatile("barrier.cluster.arrive.relaxed.aligned;" ::: "memory");
    uint32_t rbar;
    asm volatile("mapa.shared::cluster.u32 %0, %1, %2;" : "=r"(rbar) : "r"(sbar), "r"(rk ^ 1));
#define RBAR(field, i) (rbar + (uint32_t)offsetof(Bars, field) + 8u * (i))
    {
      const int ln = (tid >> 1) & 31, lg = ln >> 2, lt = ln & 3, i = 4 * (tid >> 6) + 2 * (tid & 1);
      const int kidx = lt + 8 * (i >> 3), nidx = 4 * ((i >> 1) & 3) + (lg >> 1);
      const uint32_t a0 = cfrag<2048>((c + 128 * kidx) * nidx, lg & 1), a1 = cfrag<2048>((c + 128 * (kidx + 4)) * nidx, lg & 1);
      const uint32_t b0 = cfrag<2048>(-(c + 128 * nidx) * kidx, lg & 1), b1 = cfrag<2048>(-(c + 128 * nidx) * (kidx + 4), lg & 1);
      asm volatile("st.shared.v2.u32 [%0], {%1,%2};" ::"r"(sbase + SM_FC + tid * 8), "r"(a0), "r"(a1) : "memory");
      asm volatile("st.shared.v2.u32 [%0], {%1,%2};" ::"r"(sbase + SM_FC + 2048 + tid * 8), "r"(b0), "r"(b1) : "memory");
    }
    bar_sync(NB_CONS, 256);
    uint4 fc[4];
#pragma unroll
    for (int i = 0; i < 4; i++) fc[i] = lds4(sbase + SM_FC + i * 512 + lane * 16);
    asm volatile("cp.async.wait_group 0;" ::: "memory");
    __syncwarp();
    bar_arrive(NB_INIT, 384);
    PROF(13);
    uint32_t tag, ones;
    uint4 q[4], o[4];
    {
      uint32_t v[2][8];
#pragma unroll
      for (int r = 0; r < 2; r++)
#pragma unroll
        for (int ks = 0; ks < 2; ks++) {
          const int ch = 32 * ks + 2 * (lane & 15) + (lane >> 4);
          asm volatile("ldmatrix.sync.aligned.m8n8.x4.trans.shared.b16 {%0,%1,%2,%3}, [%4];"
                       : "=r"(v[r][4 * ks]), "=r"(v[r][4 * ks + 1]), "=r"(v[r][4 * ks + 2]), "=r"(v[r][4 * ks + 3])
                       : "r"(sbase + SM_X + (2 * warp + r) * 1024 + ((ch ^ ((ch >> 3) & 1)) * 16)) : "memory");
        }
      float sq[2];
#pragma unroll
      for (int r = 0; r < 2; r++) {
        float s0 = 0.f, s1 = 0.f;
#pragma unroll
        for (int i = 0; i < 8; i++) {
          const float lo = bf_lo(v[r][i]), hi = u2f(v[r][i] & 0xffff0000u);
          s0 = fmaf(lo, lo, s0);
          s1 = fmaf(hi, hi, s1);
        }
        sq[r] = s0 + s1;
      }
      {
        float w = ((lane & 1) ? sq[1] : sq[0]) + __shfl_xor_sync(0xffffffffu, (lane & 1) ? sq[0] : sq[1], 1);
        w += __shfl_xor_sync(0xffffffffu, w, 2);
        w = sum_groups(w);
        const float o2 = __shfl_xor_sync(0xffffffffu, w, 1);
        sq[0] = (lane & 1) ? o2 : w;
        sq[1] = (lane & 1) ? w : o2;
      }
#pragma unroll
      for (int r = 0; r < 2; r++) {
        float dd[2][4], ee[2][4];
#pragma unroll
        for (int nt = 0; nt < 2; nt++) {
          mma_az(dd[nt], fa[0], v[r][2 * nt], v[r][2 * nt + 1]);
          mma_a(dd[nt], fa[1], v[r][4 + 2 * nt], v[r][5 + 2 * nt]);
          mma_az(ee[nt], fa[2], v[r][2 * nt], v[r][2 * nt + 1]);
          mma_a(ee[nt], fa[3], v[r][4 + 2 * nt], v[r][5 + 2 * nt]);
        }
        float mean = (dd[0][0] + dd[0][1]) + (dd[1][0] + dd[1][1]);
        mean += __shfl_xor_sync(0xffffffffu, mean, 1);
        mean += __shfl_xor_sync(0xffffffffu, mean, 2);
        mean = __shfl_sync(0xffffffffu, mean, 0) * (1.f / 512.f);
        const float rs = rsqrtf(fmaxf(fmaf(-mean, mean, sq[r] * (1.f / 512.f)), 0.f) + 1e-5f);
        float acc[4][4];
#pragma unroll
        for (int nt = 0; nt < 2; nt++) {
          const float (&d)[4] = dd[nt];
          const float (&e)[4] = ee[nt];
          const uint4 &ka = tw[2 * nt], &kb = tw[2 * nt + 1], &kc = tw[4 + nt];
          const uint32_t a0 = pack2(d[0] * u2f(ka.x) + d[2] * u2f(ka.y), d[1] * u2f(kb.x) + d[3] * u2f(kb.y));
          const uint32_t a2 = pack2(d[0] * u2f(ka.z) + d[2] * u2f(ka.w), d[1] * u2f(kb.z) + d[3] * u2f(kb.w));
          const uint32_t a1 = pack2(e[0] * u2f(kc.x) + e[2] * u2f(kc.y), e[1] * u2f(kc.z) + e[3] * u2f(kc.w));
          const uint32_t a3 = pack2(e[2] * u2f(kc.x) - e[0] * u2f(kc.y), e[3] * u2f(kc.z) - e[1] * u2f(kc.w));
          const uint32_t dc = pack2(fmaf(mean, -32.f, d[0]), fmaf(mean, -32.f, d[1]));
          const uint32_t h0 = g == 0 ? dc : a0, h2 = g == 0 ? 0u : a2;
          if (nt == 0) {
            mma16816_z(acc[0], a0, a1, a2, a3, fb[2 * nt].x, fb[2 * nt].y);
            mma16816_z(acc[1], a0, a1, a2, a3, fb[2 * nt].z, fb[2 * nt].w);
            mma16816_z(acc[2], h0, a1, h2, a3, fb[2 * nt + 1].x, fb[2 * nt + 1].y);
            mma16816_z(acc[3], h0, a1, h2, a3, fb[2 * nt + 1].z, fb[2 * nt + 1].w);
          } else {
            mma16816(acc[0], a0, a1, a2, a3, fb[2 * nt].x, fb[2 * nt].y);
            mma16816(acc[1], a0, a1, a2, a3, fb[2 * nt].z, fb[2 * nt].w);
            mma16816(acc[2], h0, a1, h2, a3, fb[2 * nt + 1].x, fb[2 * nt + 1].y);
            mma16816(acc[3], h0, a1, h2, a3, fb[2 * nt + 1].z, fb[2 * nt + 1].w);
          }
        }
#pragma unroll
        for (int h = 0; h < 2; h++) {
          const int j = 2 * warp + r, m = 2 * t + h;
          sts4(sbase + SM_E + ((j * 8 + m) * 8 + (g ^ (2 * t) ^ (2 * (j & 3)))) * 16,
               pack2(acc[h][0] * rs, acc[h][1] * rs), pack2(acc[h][2] * rs, acc[h][3] * rs),
               pack2(acc[2 + h][0] * rs, acc[2 + h][1] * rs), pack2(acc[2 + h][2] * rs, acc[2 + h][3] * rs));
        }
      }
      if (tid == 0) PROFP(12);
      bar_sync(NB_RDY, 384);
      if (tid == 0) PROFP(13);
      const uint32_t ea = sbase + SM_E + ((t * 8 + warp) * 8 + (g ^ (warp & 6) ^ (2 * t))) * 16;
      lds_frag(q[0], q[1], ea, ea + 4096);
      lds_frag(q[2], q[3], ea + 8192, ea + 12288);
      asm volatile("ld.shared.u32 %0, [%1];" : "=r"(tag) : "r"(BAR(epoch, 0)) : "memory");
      ones = ~(tag >> 31);
      tag = (tag + 1) & 1;
      cdft16(q, fc, o);
#pragma unroll
      for (int vv = 0; vv < 4; vv++) st_tag(&scr->Z1[(((4 * vv + t) * 8 + warp) * 128 + c) * 8 + g], o[vv], tag);
    }
    PROF(1);
    asm volatile("setmaxnreg.inc.sync.aligned.u32 224;");
    {
      const uint4* const zp = &scr->Z1[(c * 128 + 8 * t + warp) * 8 + g];
      const uint32_t tst = clock32();
      mbar_wait(BAR(tbar, 0), 0);
      if (tid == 0) PROFP(14);
      uint4 f2[4], g2[4];
#pragma unroll
      for (int i = 0; i < 4; i++) {
        f2[i] = lds4(TOFF(f2) + warp * 2048 + i * 512);
        g2[i] = lds4(TOFF(g2) + warp * 2048 + i * 512);
      }
      const uint4 f8 = lds4(TOFF(f8)), g8 = lds4(TOFF(g8));
      float wfr[16], wfi[16];
      {
        const float nyq = ((c & 7) == 7 && g == 0) ? 0.5f : 1.f;
        const int gg = g == 0 ? 16 : g, wsh = (2 * (c >> 3) + 2) & 15;
#pragma unroll
        for (int i = 0; i < 16; i++) {
          const int ci = i >> 3, dd = (i >> 2) & 1, e = i & 3;
          const int kk = (e == 0 ? gg : e == 1 ? g + 8 : e == 2 ? 32 - g : 24 - g) - 1;
          const uint32_t a = sbase + SM_W + ((2 * warp + ci) * 8 + t + 4 * dd) * 80 + wsh + 2 * kk;
          wfr[i] = bf_lo(lds_u16(a)) * (e == 2 ? nyq : 1.f);
          wfi[i] = bf_lo(lds_u16(a + 10240)) * (e == 2 ? nyq : 1.f);
        }
      }
      asm volatile("barrier.cluster.wait.aligned;" ::: "memory");
      PROF(2);
      spin_until(tst + POLL_DELAY);
      ld_tag4_issue<256>(q, zp);
      ld_tag4_finish<256>(q, zp, tag);
      if (tid == 0) PROFP(30);
      if (lane == 0) mbar_arrive(BAR(sig, 0));
      reg_frag(q, ones);
      cdft16(q, f2, o);
      const uint32_t e2 = sbase + SM_E2;
#pragma unroll
      for (int vv = 0; vv < 4; vv++)
        sts4(e2 + ((warp * 16 + 4 * vv + t) * 8 + (g ^ (2 * t) ^ (2 * (warp & 3)))) * 16, o[vv].x, o[vv].y, o[vv].z, o[vv].w);
      bar_sync(NB_CONS, 256);
      uint32_t ad[2], res[2][2][4];
#pragma unroll
      for (int ci = 0; ci < 2; ci++) {
        const int cc = 2 * warp + ci;
        ad[ci] = e2 + ((t * 16 + cc) * 8 + (g ^ (2 * (cc & 3)) ^ (2 * t))) * 16;
        lds_frag(q[2 * ci], q[2 * ci + 1], ad[ci], ad[ci] + 8192);
      }
#pragma unroll
      for (int ci = 0; ci < 2; ci++)
#pragma unroll
        for (int p = 0; p < 2; p++) {
          uint32_t y[2][2];
#pragma unroll
          for (int vv = 0; vv < 2; vv++) {
            float d[4];
            mma_az(d, q[2 * ci + p], word(f8, 2 * vv), word(f8, 2 * vv + 1));
#pragma unroll
            for (int rr = 0; rr < 2; rr++) {
              const float fr = wfr[ci * 8 + vv * 4 + 2 * p + rr], fi = wfi[ci * 8 + vv * 4 + 2 * p + rr];
              y[vv][rr] = pack2(d[2 * rr] * fr - d[2 * rr + 1] * fi, d[2 * rr] * fi + d[2 * rr + 1] * fr);
            }
          }
#pragma unroll
          for (int vv = 0; vv < 2; vv++) {
            float d[4];
            mma16816_z(d, y[0][0], y[0][1], y[1][0], y[1][1], word(g8, 2 * vv), word(g8, 2 * vv + 1));
            res[ci][vv][2 * p] = pack2(d[0], d[1]);
            res[ci][vv][2 * p + 1] = pack2(d[2], d[3]);
          }
        }
#pragma unroll
      for (int i = 0; i < 4; i++)
        sts4(ad[i >> 1] + (i & 1) * 8192, res[i >> 1][i & 1][0], res[i >> 1][i & 1][1], res[i >> 1][i & 1][2], res[i >> 1][i & 1][3]);
      bar_sync(NB_CONS, 256);
      const uint32_t eb = e2 + ((warp * 16 + t) * 8 + (g ^ (2 * t) ^ (2 * (warp & 3)))) * 16;
      lds_frag(q[0], q[1], eb, eb + 512);
      lds_frag(q[2], q[3], eb + 1024, eb + 1536);
      cdft16(q, g2, o);
#pragma unroll
      for (int vv = 0; vv < 4; vv++) st_tag(&scr->Z2[((8 * (4 * vv + t) + warp) * 128 + c) * 8 + g], o[vv], tag);
    }
    PROF(3);
    {
      const uint4* const zp = &scr->Z2[((c * 16 + t) * 8 + warp) * 8 + g];
      const uint32_t tst = clock32();
      uint4 gb[4], ga[4], gc[4], tw[4];
      uint2 xr[2][4];
      uint2* lnp[2];
#pragma unroll
      for (int r = 0; r < 2; r++) {
        const int row = 16 * f + 2 * warp + r;
        lnp[r] = reinterpret_cast<uint2*>(&scr->LN[(rb * 8 + (g >> 2)) * 1024 + row * 8 + ((2 * (g & 3) + (t >> 1)) ^ (row & 7))]) + (t & 1);
        asm volatile("" : "+l"(lnp[r]));
      }
#pragma unroll
      for (int i = 0; i < 4; i++) {
        gc[i] = lds4(sbase + SM_FC + 2048 + i * 512 + lane * 16);
        gb[i] = lds4(TOFF(gb) + i * 512);
        ga[i] = lds4(TOFF(ga) + i * 512);
        tw[i] = lds4(TOFF(tw3) + i * 512);
        const int ch = 2 * (g + 8 * i) + (t >> 1);
#pragma unroll
        for (int r = 0; r < 2; r++) xr[r][i] = lds2(sbase + SM_X + (2 * warp + r) * 1024 + ((ch ^ ((ch >> 3) & 1)) * 16) + (t & 1) * 8);
      }
      PROF(4);
      spin_until(tst + POLL_DELAY2);
      ld_tag4_issue<256>(q, zp);
      ld_tag4_finish<256>(q, zp, tag);
      if (tid == 0) PROFP(31);
      if (lane == 0) mbar_arrive(BAR(sig, 1));
      reg_frag(q, ones);
      cdft16(q, gc, o);
#pragma unroll
      for (int vv = 0; vv < 4; vv++)
        sts4(sbase + SM_E + (((4 * vv + t) * 8 + warp) * 8 + (g ^ (warp & 6) ^ (2 * t))) * 16, o[vv].x, o[vv].y, o[vv].z, o[vv].w);
      if (tid == 0) PROFP(8);
      bar_sync(NB_CONS, 256);
      if (tid == 0) PROFP(9);
      uint32_t hv[2][8];
      const float mk = t == 0 ? 0.f : 1.f;
#pragma unroll
      for (int r = 0; r < 2; r++) {
        const int j = 2 * warp + r;
        uint4 u[2];
#pragma unroll
        for (int h = 0; h < 2; h++) u[h] = lds4(sbase + SM_E + ((j * 8 + 2 * t + h) * 8 + (g ^ (2 * t) ^ (2 * (j & 3)))) * 16);
        const uint32_t bp[4][2] = {{u[0].x, u[1].x & ones}, {u[0].y & ones, u[1].y}, {u[0].z, u[1].z & ones}, {u[0].w & ones, u[1].w}};
        float y[2][2][4];
#pragma unroll
        for (int i = 0; i < 2; i++) {
          float lo[4], hi[4], e[4];
          mma_az(lo, gb[2 * i], bp[0][0], bp[0][1]);
          mma_az(hi, gb[2 * i + 1], bp[2][0], bp[2][1]);
          mma_az(e, gb[2 * i], bp[1][0], bp[1][1]);
          mma_a(e, gb[2 * i + 1], bp[3][0], bp[3][1]);
          const uint4 &ka = tw[2 * i], &kb = tw[2 * i + 1];
          const float tr0 = fmaf(hi[0], mk, lo[0]), ti0 = fmaf(hi[2], mk, lo[2]);
          const float tr1 = lo[1] + hi[1], ti1 = lo[3] + hi[3];
          const float vr0 = tr0 * u2f(ka.x) - ti0 * u2f(ka.y), vi0 = tr0 * u2f(ka.y) + ti0 * u2f(ka.x);
          const float vr1 = tr1 * u2f(ka.z) - ti1 * u2f(ka.w), vi1 = tr1 * u2f(ka.w) + ti1 * u2f(ka.z);
          const uint32_t b0 = pack2(t == 0 ? hi[0] : vr0, vr1), b1 = pack2(t == 0 ? vr0 : vi0, vi1);
          const uint32_t b2 = pack2(e[0] * u2f(kb.x) - e[2] * u2f(kb.y), e[1] * u2f(kb.z) - e[3] * u2f(kb.w));
          const uint32_t b3 = pack2(e[0] * u2f(kb.y) + e[2] * u2f(kb.x), e[1] * u2f(kb.w) + e[3] * u2f(kb.z));
#pragma unroll
          for (int mt = 0; mt < 2; mt++) {
            mma_az(y[mt][i], ga[2 * mt], b0, b1);
            mma_a(y[mt][i], ga[2 * mt + 1], b2, b3);
          }
        }
#pragma unroll
        for (int i = 0; i < 4; i++) {
          hv[r][2 * i] = hadd2_bf16(xr[r][i].x, pack2(y[i >> 1][0][2 * (i & 1)], y[i >> 1][0][2 * (i & 1) + 1]));
          hv[r][2 * i + 1] = hadd2_bf16(xr[r][i].y, pack2(y[i >> 1][1][2 * (i & 1)], y[i >> 1][1][2 * (i & 1) + 1]));
        }
      }
      if (tid == 0 && hv[0][0] != 0x12345 && hv[1][7] != 0x12345) PROFP(10);
      float mean[2];
      uint32_t mb[2];
#pragma unroll
      for (int r = 0; r < 2; r++) {
        mean[r] = sum_groups(quad_sum(hv[r])) * (1.f / 512.f);
        mb[r] = pack2(mean[r], mean[r]);
      }
#pragma unroll
      for (int i = 0; i < 4; i++)
#pragma unroll
        for (int r = 0; r < 2; r++) {
          hv[r][2 * i] = hsub2_bf16(hv[r][2 * i], mb[r]);
          hv[r][2 * i + 1] = hsub2_bf16(hv[r][2 * i + 1], mb[r]);
          st_tag8(lnp[r] + i * 4096, hv[r][2 * i], hv[r][2 * i + 1], i == 0 ? tag : (hv[r][2 * i] & 1u));
        }
      if (tid == 0) PROFP(11);
      bar_arrive(NB_LN, 288);
      const uint32_t ones2 = ~(lds2(BAR(epoch, 0)).x >> 31);
      float rstd[2];
#pragma unroll
      for (int r = 0; r < 2; r++) {
        hv[r][0] &= ones2;
        rstd[r] = row_rstd(hv[r], mean[r] - bf_lo(mb[r]));
      }
      if (lane == 0)
        st_tag(&scr->ST[rb * 64 + 8 * f + warp], make_uint4(mb[0] << 16, __float_as_uint(rstd[0]), mb[1] << 16, __float_as_uint(rstd[1])), tag);
    }
    PROF(5);
    const int wgi = warp >> 2, wq = warp & 3;
    uint4* const pbase = &scr->P[rb * 28 * 1024 + warp * 128 + lane];
    const uint32_t a_lo0 = desc_lo(sbase + wgi * 8192, 16);
    const uint32_t ebar = lane == 0 ? BAR(empty1, 0) : RBAR(empty1, 0);
    float r0, r1;
    uint4 px[8], py[6];
    const int rh = wgi ^ kh ^ 1;
    const uint4* const psrc = &scr->P[(rb2 * 28 + 14 * kh) * 1024 + (4 * rh + wq) * 128 + lane];
    const uint32_t pa0 = sbase + (4 * rh + wq) * 2048;
    uint4 pf[6][4];
    uint32_t rdy = 0;
    {
      float acc[128];
#pragma unroll
      for (int i = 0; i < 128; i++) acc[i] = 0.f;
      const uint32_t b_lo0 = desc_lo(sbase + 8 * SLOT, 4096);
      const uint32_t t3 = clock32();
      if (WARM) {
        wg_fence();
#pragma unroll
        for (int i = 0; i < WARM; i++) wgmma_n256(acc, desc64(a_lo0 + 6 * 1024, HI128), desc64(b_lo0, HI128));
        wg_commit();
      }
      const uint4* const ap = &scr->LN[rb * 8 * 1024 + wgi * 512 + (tid & 127)];
      uint4 av[NLL][4];
      while (clock32() - t3 < POLL_DELAY3) {}
#pragma unroll
      for (int kb = 0; kb < NLL; kb++) ld_tag4_issue<128>(av[kb], ap + kb * 1024);
      bar_sync(NB_CONS, 256);
      uint32_t slot = 2;
      auto stage_x = [&](int kb, int hh) {
        if (LAGX && hh == ((16 - LAGX) & 1) && kb == ((16 - LAGX) >> 1) && wgi == 1) bar_sync(NB_LAG, 256);
        mbar_wait(BAR(full1, 2 * kb + hh));
        const uint32_t al = a_lo0 + kb * 1024 + hh * 4, bl = b_lo0 + slot * 1024;
        wg_fence();
        wgmma_n256(acc, desc64(al, HI128), desc64(bl, HI128), (kb | hh) != 0 ? 1 : ~ones);
        wgmma_n256(acc, desc64(al + 2, HI128), desc64(bl + 128, HI128));
        wg_commit();
        if (LAGX && hh == 1 && kb == 7 && wgi == 0) bar_arrive(NB_LAG, 256);
        wg_wait<1>();
        if ((kb | hh) != 0 && lane < 2) mbar_arrive_remote(ebar + 8 * (2 * kb + hh - 1));
        if (++slot == 6) slot = 0;
      };
#pragma unroll
      for (int kb = 0; kb < NLL; kb++) {
        ld_tag4_finish<128, true>(av[kb], ap + kb * 1024, tag);
#pragma unroll
        for (int i = 0; i < 4; i++)
          sts4(sbase + kb * SLOT + wgi * 8192 + ((tid & 127) + 128 * i) * 16, av[kb][i].x, av[kb][i].y, av[kb][i].z, av[kb][i].w);
        asm volatile("fence.proxy.async.shared::cta;" ::: "memory");
        bar_sync(NB_WG + wgi, 128);
        if (kb > 0) stage_x(kb - 1, 1);
        if (kb == 0) PROF(6);
        stage_x(kb, 0);
      }
      stage_x(NLL - 1, 1);
#pragma unroll 1
      for (int kb = NLL; kb < 8; kb++) {
        mbar_wait(BAR(fullA, kb));
        stage_x(kb, 0);
        stage_x(kb, 1);
      }
      mbar_wait(BAR(sbar, 0), 0);
      r0 = __uint_as_float(lds2(sstat + (16 * warp + g) * 8).y);
      r1 = __uint_as_float(lds2(sstat + (16 * warp + g + 8) * 8).y);
      wg_wait<0>();
      if (lane < 2) mbar_arrive_remote(ebar + 8 * 15);
      PROF(7);
      make_p<8, false>(acc, r0, r1, px, pbase, 0, tag);
    }
    PROF(8);
    {
      float acc[96];
#pragma unroll
      for (int i = 0; i < 96; i++) acc[i] = 0.f;
      const uint32_t b_lo0 = desc_lo(sbase + 8 * SLOT, 2048);
      uint4* const pdst = pbase + ((7 * f + 3 * (f & 1)) >> 1) * 1024;
      auto stage_y = [&](int k) {
        if (LAGY && k == 16 - LAGY && wgi == 1) bar_sync(NB_LAG, 256);
        mbar_wait(BAR(full1, 16 + k));
        const uint32_t al = a_lo0 + (k >> 1) * 1024 + (k & 1) * 4, bl = b_lo0 + (k & 7) * 768;
        wg_fence();
        wgmma_n192(acc, desc64(al, HI128), desc64(bl, HI64));
        wgmma_n192(acc, desc64(al + 2, HI128), desc64(bl + 64, HI64));
        wg_commit();
      };
#pragma unroll
      for (int k = 0; k < 4; k++) {
        stage_y(k);
        st_tag(pdst + (k >> 1) * 1024 + (k & 1) * 64, px[2 * k], tag);
        st_tag(pdst + (k >> 1) * 1024 + (k & 1) * 64 + 32, px[2 * k + 1], tag);
        if (k == 3 && lane == 0) red_relaxed(&scr->cnt[(C_PX + rb) * 32 + (f >> 2)]);
        wg_wait<1>();
        if (k != 0 && lane < 2) mbar_arrive_remote(ebar + 8 * (15 + k));
      }
#pragma unroll 1
      for (int k = 4; k < 16; k++) {
        stage_y(k);
        if (LAGY && k == 15 && wgi == 0) bar_arrive(NB_LAG, 256);
        wg_wait<1>();
        if (lane < 2) mbar_arrive_remote(ebar + 8 * (15 + k));
      }
      rdy = __all_sync(0xffffffffu, mbar_test(BAR(fullP, 0)) & mbar_test(BAR(full2, 0)) & mbar_test(BAR(fullP, 1)));
      if (rdy) {
#pragma unroll
        for (int kk = 0; kk < 4; kk++) pf[0][kk] = lds4(pa0 + 4 * SLOT + kk * 512 + lane * 16);
      }
      wg_wait<0>();
      if (lane < 2) mbar_arrive_remote(ebar + 8 * 31);
      PROF(9);
      make_p<6, true>(acc, r0, r1, py, pbase, 14 * f + ((f & 1) ? 0 : 8), tag);
      if (lane == 0) red_relaxed(&scr->cnt[(C_PY + rb) * 32 + (f >> 1)]);
    }
    PROF(10);
    {
      float acc[64];
      const uint32_t b2_lo0 = desc_lo(sbase, 8192);
      const uint32_t pbar = ebar + (uint32_t)(offsetof(Bars, emptyP) - offsetof(Bars, empty1));
      if (!rdy) {
        mbar_wait(BAR(fullP, 0));
#pragma unroll
        for (int kk = 0; kk < 4; kk++) pf[0][kk] = lds4(pa0 + 4 * SLOT + kk * 512 + lane * 16);
      }
      constexpr int S1 = 14 - LAG2;
#pragma unroll
      for (int s = 0; s < 14; s += (s < S1 ? 1 : 2)) {
        const int n = s < S1 ? 1 : 2, sn = s + n, nn = sn >= 14 ? 0 : sn < S1 ? 1 : 2, n3 = sn + nn >= 14 ? 0 : sn + nn < S1 ? 1 : 2;
#pragma unroll
        for (int i = s; i < sn; i++) {
          ld_tag4_finish<32>(pf[i % 6], psrc + (int)((KORDER >> (4 * i)) & 15) * 1024, tag);
          if (i < 8 && lane < (i < 7 ? 2 : 1)) mbar_arrive_remote(pbar + 8 * i);
        }
        if (s >= 2) {
          wg_wait<1>();
          if (s <= 8 && lane == 0) mbar_arrive(BAR(empty2, s - 2));
        }
        if (!rdy) {
#pragma unroll
          for (int i = sn; i < sn + nn; i++) mbar_wait(BAR(fullP, i));
#pragma unroll
          for (int i = s; i < sn; i++) mbar_wait(BAR(full2, i));
        }
        if (tid == 0) PROFP(16 + s);
        if (s == 14 - LAG2 && wgi == 1) {
          const float m0 = __uint_as_float(lds2(sstat + 1024 + (16 * wq + g) * 8).x);
          const float m1 = __uint_as_float(lds2(sstat + 1024 + (16 * wq + g + 8) * 8).x);
          const uint32_t hb = sbase + 4 * SLOT + (16 * wq + (lane & 15)) * 128;
          wg_wait<0>();
          mbar_wait(BAR(hbar, 0));
#pragma unroll
          for (int i = 0; i < 8; i++) {
            uint32_t h[4];
            asm volatile("ldmatrix.sync.aligned.m8n8.x4.shared.b16 {%0,%1,%2,%3}, [%4];"
                         : "=r"(h[0]), "=r"(h[1]), "=r"(h[2]), "=r"(h[3])
                         : "r"(hb + (i >> 2) * 8192 + (((2 * (i & 3) + (lane >> 4)) ^ (lane & 7)) * 16)) : "memory");
            const uint32_t mk = ((t & 1) == 0 && nq == 0) ? ~1u : ~0u;
#pragma unroll
            for (int e = 0; e < 4; e++) {
              acc[8 * i + 2 * e] += bf_lo(h[e] & mk) + ((e & 1) ? m1 : m0);
              acc[8 * i + 2 * e + 1] += __uint_as_float(h[e] & 0xffff0000u) + ((e & 1) ? m1 : m0);
            }
          }
          bar_sync(NB_LAG, 256);
        }
        wg_fence();
        rdy = 1;
#pragma unroll
        for (int i = sn; i < sn + nn; i++) {
#pragma unroll
          for (int kk = 0; kk < 4; kk++) pf[i % 6][kk] = lds4(pa0 + (uint32_t)((PSLOT >> (4 * i)) & 15) * SLOT + kk * 512 + lane * 16);
          rdy &= mbar_test(BAR(full2, i));
        }
#pragma unroll
        for (int i = sn + nn; i < sn + nn + n3; i++) rdy &= mbar_test(BAR(fullP, i));
#pragma unroll
        for (int i = s; i < sn; i++) {
          const uint32_t bl = b2_lo0 + (uint32_t)((BSLOT >> (4 * i)) & 15) * 1024;
          const uint4 (&a)[4] = pf[i % 6];
          if (i == 0) wgmma_rs_n128<0>(acc, a[0].x, a[0].y, a[0].z, a[0].w, desc64(bl, HI128));
          else wgmma_rs_n128<1>(acc, a[0].x, a[0].y, a[0].z, a[0].w, desc64(bl, HI128));
#pragma unroll
          for (int kk = 1; kk < 4; kk++) wgmma_rs_n128<1>(acc, a[kk].x, a[kk].y, a[kk].z, a[kk].w, desc64(bl + kk * 128, HI128));
        }
        wg_commit();
      }
      if (wgi == 0) {
        bar_arrive(NB_LAG, 256);
        uint4* const dst = &scr->XP[(c ^ 4) * 1024 + tid];
        wg_wait<0>();
        PROF(11);
#pragma unroll
        for (int i = 0; i < 8; i++)
          st_tag(dst + i * 128, make_uint4(pack2(acc[8 * i], acc[8 * i + 1]), pack2(acc[8 * i + 2], acc[8 * i + 3]),
                                           pack2(acc[8 * i + 4], acc[8 * i + 5]), pack2(acc[8 * i + 6], acc[8 * i + 7])), tag);
      } else {
        uint4 pv[2][4];
        const uint4* const xsrc = &scr->XP[c * 1024 + (tid & 127)];
        ld_tag4_issue<128>(pv[0], xsrc);
        ld_tag4_issue<128>(pv[1], xsrc + 512);
        wg_wait<0>();
        PROF(11);
        uint32_t w[32];
#pragma unroll
        for (int i = 0; i < 32; i++) w[i] = pack2(acc[2 * i], acc[2 * i + 1]);
        ld_tag4_finish<128>(pv[0], xsrc, tag);
        ld_tag4_finish<128>(pv[1], xsrc + 512, tag);
#pragma unroll
        for (int i = 0; i < 8; i++) {
          const uint4& p = pv[i >> 2][i & 3];
          asm volatile("stmatrix.sync.aligned.m8n8.x4.shared.b16 [%0], {%1,%2,%3,%4};"
                       ::"r"(pa0 + (9 + ((lane >> 3) & 1)) * SLOT + (lane & 7) * 256 + (((2 * i + (lane >> 4)) ^ (lane & 7)) * 16)),
                         "r"(hadd2_bf16(w[4 * i], p.x)), "r"(hadd2_bf16(w[4 * i + 1], p.y)), "r"(hadd2_bf16(w[4 * i + 2], p.z)),
                         "r"(hadd2_bf16(w[4 * i + 3], p.w)) : "memory");
        }
        __syncwarp();
        uint4* const dst = reinterpret_cast<uint4*>(out) + (16 * (c >> 4) + 2 * (4 * rh + wq) + (rb2 & 1) + 128 * (lane >> 4)) * 64 + nq * 16 + (lane & 15);
#pragma unroll
        for (int i = 0; i < 8; i++) {
          const int r = 2 * (i & 3) + (lane >> 4);
          dst[i * 256 * 64] = lds4(pa0 + (9 + (i >> 2)) * SLOT + r * 256 + (((lane & 15) ^ r) * 16));
        }
      }
      PROF(12);
      PROFG(15);
    }
  }
#undef BAR
#undef TOFF
#undef RBAR
}

typedef CUresult (*EncodeFn)(CUtensorMap*, CUtensorMapDataType, cuuint32_t, void*, const cuuint64_t*, const cuuint64_t*,
                             const cuuint32_t*, const cuuint32_t*, CUtensorMapInterleave, CUtensorMapSwizzle,
                             CUtensorMapL2promotion, CUtensorMapFloatOOBfill);

}

extern "C" void kernel_launch(void* const* d_in, const int* in_sizes, int n_in, void* d_out, int out_size) {
  (void)in_sizes; (void)n_in; (void)out_size;
  static EncodeFn encode = nullptr;
  static void *tab = nullptr, *scr = nullptr;
  if (!encode) {
    void* fn = nullptr;
    cudaDriverEntryPointQueryResult qr;
    cudaGetDriverEntryPoint("cuTensorMapEncodeTiled", &fn, cudaEnableDefault, &qr);
    encode = (EncodeFn)fn;
    cudaGetSymbolAddress(&tab, g_tab);
    cudaGetSymbolAddress(&scr, g_scr);
    cudaFuncSetAttribute(fused_kernel, cudaFuncAttributeMaxDynamicSharedMemorySize, SMEM_BYTES);
  }
  CUtensorMap tmGX, tmUX, tmGY, tmUY, tmD, tmWR, tmWI;
  const cuuint32_t es[5] = {1, 1, 1, 1, 1};
  auto enc = [&](CUtensorMap* m, void* p, int rank, const cuuint64_t* gd, const cuuint64_t* gs, const cuuint32_t* bd,
                 CUtensorMapSwizzle sw, CUtensorMapL2promotion pr) {
    encode(m, CU_TENSOR_MAP_DATA_TYPE_BFLOAT16, rank, p, gd, gs, bd, es, CU_TENSOR_MAP_INTERLEAVE_NONE, sw, pr,
           CU_TENSOR_MAP_FLOAT_OOB_FILL_NONE);
  };
  {
    const cuuint64_t gd[3] = {64, 512, 28}, gs[2] = {3584, 128};
    const cuuint32_t bd[3] = {64, 32, 2};
    enc(&tmGX, d_in[4], 3, gd, gs, bd, CU_TENSOR_MAP_SWIZZLE_128B, CU_TENSOR_MAP_L2_PROMOTION_L2_256B);
    enc(&tmUX, d_in[5], 3, gd, gs, bd, CU_TENSOR_MAP_SWIZZLE_128B, CU_TENSOR_MAP_L2_PROMOTION_L2_256B);
  }
  {
    const cuuint64_t gd[3] = {32, 512, 56}, gs[2] = {3584, 64};
    const cuuint32_t bd[3] = {32, 32, 3};
    enc(&tmGY, d_in[4], 3, gd, gs, bd, CU_TENSOR_MAP_SWIZZLE_64B, CU_TENSOR_MAP_L2_PROMOTION_L2_128B);
    enc(&tmUY, d_in[5], 3, gd, gs, bd, CU_TENSOR_MAP_SWIZZLE_64B, CU_TENSOR_MAP_L2_PROMOTION_L2_128B);
  }
  {
    const cuuint64_t gd[3] = {64, 1792, 8}, gs[2] = {1024, 128};
    const cuuint32_t bd[3] = {64, 64, 2};
    enc(&tmD, d_in[6], 3, gd, gs, bd, CU_TENSOR_MAP_SWIZZLE_128B, CU_TENSOR_MAP_L2_PROMOTION_L2_256B);
  }
  {
    const cuuint64_t gd[3] = {4112, 8, 16}, gs[2] = {16 * 8224, 8224};
    const cuuint32_t bd[3] = {40, 8, 16};
    enc(&tmWR, d_in[1], 3, gd, gs, bd, CU_TENSOR_MAP_SWIZZLE_NONE, CU_TENSOR_MAP_L2_PROMOTION_NONE);
    enc(&tmWI, d_in[2], 3, gd, gs, bd, CU_TENSOR_MAP_SWIZZLE_NONE, CU_TENSOR_MAP_L2_PROMOTION_NONE);
  }
  fused_kernel<<<NCTA, NTHREADS, SMEM_BYTES>>>((const __nv_bfloat16*)d_in[0], (const Tables*)tab, (Scratch*)scr,
                                               (__nv_bfloat16*)d_out, (const char*)d_in[4], (const char*)d_in[5],
                                               (const char*)d_in[6], tmWR, tmWI, tmGX, tmUX, tmGY, tmUY, tmD);
}
```

```cpp
#include <cuda_runtime.h>
#include <cuda_bf16.h>
#include <cuda.h>
#include <stdint.h>

namespace {

constexpr int NCTA = 128;
constexpr int NTHREADS = 384;
constexpr int SLOT = 16384;
constexpr int SMEM_BYTES = 14 * SLOT + 3072;
constexpr int SPIN_LIMIT = 1 << 22;

struct Scratch {
  uint4 Z1[128 * 1024];
  uint4 Z2[128 * 1024];
  uint4 LN[16 * 8 * 1024];
  uint4 P[16 * 28 * 1024];
  uint4 ST[1024];
  unsigned cnt[64 * 32];
};
__device__ __align__(1024) Scratch g_scr;
#define PROF(i)
#define PROFP(i)
#define PROFG(i)

constexpr double ccos(int i, int n) {
  i &= n - 1;
  if (i > n / 2) i = n - i;
  if (4 * i == n) return 0.0;
  const bool neg = 4 * i > n;
  if (neg) i = n / 2 - i;
  const double a = 6.283185307179586476925 * i / n, a2 = a * a;
  double term = 1.0, sum = 1.0;
  for (int k = 1; k < 14; k++) { term *= -a2 / ((2 * k - 1) * (2 * k)); sum += term; }
  return neg ? -sum : sum;
}
constexpr double csin(int i, int n) { return ccos(i - n / 4, n); }
constexpr unsigned fbits(double v, int mant) {
  if (v == 0.0) return 0;
  const unsigned sg = v < 0 ? 1u : 0u;
  if (v < 0) v = -v;
  int e = 127;
  while (v < 1.0) { v *= 2.0; e--; }
  const unsigned m = (unsigned)((v - 1.0) * (double)(1u << mant) + 0.5);
  return (sg << (8 + mant)) + ((unsigned)e << mant) + m;
}
constexpr unsigned pkb(double lo, double hi) { return fbits(lo, 7) | (fbits(hi, 7) << 16); }
constexpr double fa_elem(int mt, int r, int n1) {
  const int k1 = 8 * mt + (r & 7);
  return r < 8 ? ccos(k1 * n1, 32) : k1 == 0 ? ccos(16 * n1, 32) : -csin(k1 * n1, 32);
}
constexpr unsigned cfrag_c(int idx, int n, int ri, double s = 1.0) {
  return ri ? pkb(-s * csin(idx, n), s * ccos(idx, n)) : pkb(s * ccos(idx, n), s * csin(idx, n));
}
struct Tables {
  unsigned fa[4][32][4];
  unsigned fb[4][32][4];
  unsigned tw1[6][32][4];
  unsigned f2[8][4][32][4];
  unsigned g2[8][4][32][4];
  unsigned gb[4][32][4];
  unsigned ga[4][32][4];
  unsigned tw3[4][32][4];
  unsigned f8[32][4], g8[32][4];
};
constexpr int T1_BYTES = 7168, T2_BYTES = 39936;
static_assert(sizeof(Tables) == T1_BYTES + T2_BYTES, "table size");
constexpr Tables make_tables() {
  Tables T = {};
  for (int l = 0; l < 32; l++) {
    const int g = l >> 2, t = l & 3;
    for (int a = 0; a < 2; a++)
      for (int b = 0; b < 2; b++) {
        for (int r = 0; r < 4; r++) {
          const int row = g + 8 * (r & 1), col = 2 * t + 8 * (r >> 1);
          T.fa[2 * a + b][l][r] = pkb(fa_elem(a, row, 16 * b + col), fa_elem(a, row, 16 * b + col + 1));
          T.ga[2 * a + b][l][r] = pkb(fa_elem(b, col, 16 * a + row), fa_elem(b, col + 1, 16 * a + row));
        }
        const double sg = b ? -1.0 : 1.0;
        for (int h = 0; h < 2; h++) {
          const int ri = g & 1, m = 2 * (g >> 1) + h, k2 = b ? 15 - m : m;
          const int pa = (8 * a + 2 * t) * k2, pb = (8 * a + 2 * t + 1) * k2;
          T.fb[2 * a + b][l][2 * h] = ri == 0 ? pkb(ccos(pa, 16), ccos(pb, 16)) : pkb(-sg * csin(pa, 16), -sg * csin(pb, 16));
          T.fb[2 * a + b][l][2 * h + 1] = ri == 0 ? pkb(csin(pa, 16), csin(pb, 16)) : pkb(sg * ccos(pa, 16), sg * ccos(pb, 16));
        }
        const int n2 = 4 * (g >> 1) + 2 * a + (g & 1);
        for (int h = 0; h < 2; h++) {
          const int p = n2 * (b ? 15 - 2 * t - h : 2 * t + h);
          T.gb[2 * a + b][l][2 * h] = pkb(ccos(p, 16), -sg * csin(p, 16));
          T.gb[2 * a + b][l][2 * h + 1] = pkb(csin(p, 16), sg * ccos(p, 16));
          const int k1 = 8 * b + 2 * t + h, q = n2 * (k1 == 0 ? 16 : k1);
          T.tw3[2 * a + b][l][2 * h] = fbits(ccos(q, 512), 23);
          T.tw3[2 * a + b][l][2 * h + 1] = fbits(csin(q, 512), 23);
        }
        const int p = (8 * a + 2 * t + b) * (g == 0 ? 16 : g);
        T.tw1[2 * a + b][l][0] = fbits(g == 0 ? 0.0 : ccos(p, 512), 23);
        T.tw1[2 * a + b][l][1] = fbits(g == 0 ? ccos(p, 512) : csin(p, 512), 23);
        T.tw1[2 * a + b][l][2] = fbits(g == 0 ? 0.0 : -csin(p, 512), 23);
        T.tw1[2 * a + b][l][3] = fbits(g == 0 ? -csin(p, 512) : ccos(p, 512), 23);
        T.tw1[4 + a][l][2 * b] = fbits(ccos((8 * a + 2 * t + b) * (g + 8), 512), 23);
        T.tw1[4 + a][l][2 * b + 1] = fbits(csin((8 * a + 2 * t + b) * (g + 8), 512), 23);
      }
    for (int i = 0; i < 4; i++) {
      const int p8 = (t + 4 * (i & 1)) * (4 * (i >> 1) + (g >> 1));
      T.f8[l][i] = cfrag_c(p8, 8, g & 1);
      T.g8[l][i] = cfrag_c(-p8, 8, g & 1, 1.0 / (1 << 19));
    }
    for (int w = 0; w < 8; w++)
      for (int i = 0; i < 16; i++) {
        const int kidx = t + 4 * (i & 1) + 8 * (i >> 3), nidx = 4 * ((i >> 1) & 3) + (g >> 1);
        T.f2[w][i >> 2][l][i & 3] = cfrag_c((8 * kidx + w) * nidx, 128, g & 1);
        T.g2[w][i >> 2][l][i & 3] = cfrag_c(-(8 * nidx + w) * kidx, 128, g & 1);
      }
  }
  return T;
}
__device__ const __align__(128) Tables g_tab = make_tables();

__device__ __forceinline__ void die() { asm volatile("st.global.u32 [%0], %1;" ::"l"(0ull), "r"(0) : "memory"); }
__device__ __forceinline__ uint32_t s2u(const void* p) { return (uint32_t)__cvta_generic_to_shared(p); }
__device__ __forceinline__ void mbar_init(uint32_t b, int c) { asm volatile("mbarrier.init.shared::cta.b64 [%0], %1;" ::"r"(b), "r"(c)); }
__device__ __forceinline__ void mbar_expect(uint32_t b, int bytes) {
  asm volatile("mbarrier.arrive.expect_tx.shared::cta.b64 _, [%0], %1;" ::"r"(b), "r"(bytes) : "memory");
}
__device__ __forceinline__ void mbar_arrive(uint32_t b) { asm volatile("mbarrier.arrive.shared::cta.b64 _, [%0];" ::"r"(b) : "memory"); }
__device__ __forceinline__ uint32_t mbar_try(uint32_t b, uint32_t parity) {
  uint32_t ok;
  asm volatile("{.reg .pred p; mbarrier.try_wait.parity.shared::cta.b64 p, [%1], %2; selp.u32 %0,1,0,p;}"
               : "=r"(ok) : "r"(b), "r"(parity) : "memory");
  return ok;
}
__device__ __forceinline__ uint32_t mbar_test(uint32_t b) {
  uint32_t ok;
  asm volatile("{.reg .pred p; mbarrier.test_wait.parity.shared::cta.b64 p, [%1], 0; selp.u32 %0,1,0,p;}" : "=r"(ok) : "r"(b) : "memory");
  return ok;
}
__device__ __forceinline__ void mbar_wait(uint32_t b, uint32_t parity = 0) {
  int it = 0;
#pragma unroll 1
  while (!mbar_try(b, parity))
    if (++it > SPIN_LIMIT) { die(); break; }
}
__device__ __forceinline__ void bar_sync(int id, int n) { asm volatile("bar.sync %0, %1;" ::"r"(id), "r"(n) : "memory"); }
__device__ __forceinline__ void bar_arrive(int id, int n) { asm volatile("bar.arrive %0, %1;" ::"r"(id), "r"(n) : "memory"); }
__device__ __forceinline__ void red_release(unsigned* p) { asm volatile("red.release.gpu.global.add.u32 [%0], 1;" ::"l"(p) : "memory"); }
__device__ __forceinline__ void red_relaxed(unsigned* p) { asm volatile("red.relaxed.gpu.global.add.u32 [%0], 1;" ::"l"(p) : "memory"); }
__device__ __forceinline__ unsigned ld_acquire(const unsigned* p) {
  unsigned v;
  asm volatile("ld.acquire.gpu.global.u32 %0, [%1];" : "=r"(v) : "l"(p) : "memory");
  return v;
}
__device__ __forceinline__ unsigned ld_relaxed(const unsigned* p) {
  unsigned v;
  asm volatile("ld.relaxed.gpu.global.u32 %0, [%1];" : "=r"(v) : "l"(p) : "memory");
  return v;
}
__device__ __forceinline__ void wait_counter(const unsigned* p, unsigned target) {
  int it = 0;
  while ((int)(ld_acquire(p) - target) < 0)
    if (++it > SPIN_LIMIT) { die(); break; }
}
__device__ __forceinline__ void sts4(uint32_t a, uint32_t x, uint32_t y, uint32_t z, uint32_t w) {
  asm volatile("st.shared.v4.u32 [%0], {%1,%2,%3,%4};" ::"r"(a), "r"(x), "r"(y), "r"(z), "r"(w) : "memory");
}
__device__ __forceinline__ uint4 lds4(uint32_t a) {
  uint4 v;
  asm volatile("ld.shared.v4.u32 {%0,%1,%2,%3}, [%4];" : "=r"(v.x), "=r"(v.y), "=r"(v.z), "=r"(v.w) : "r"(a) : "memory");
  return v;
}
__device__ __forceinline__ uint32_t pack2(float lo, float hi) {
  uint32_t r;
  asm("cvt.rn.bf16x2.f32 %0, %1, %2;" : "=r"(r) : "f"(hi), "f"(lo));
  return r;
}
__device__ __forceinline__ float bf_lo(uint32_t v) { return __uint_as_float(v << 16); }
__device__ __forceinline__ uint32_t hadd2_bf16(uint32_t a, uint32_t b) {
  uint32_t r;
  asm("add.rn.bf16x2 %0, %1, %2;" : "=r"(r) : "r"(a), "r"(b));
  return r;
}
__device__ __forceinline__ void mma16816(float (&d)[4], uint32_t a0, uint32_t a1, uint32_t a2, uint32_t a3, uint32_t b0, uint32_t b1) {
  asm("mma.sync.aligned.m16n8k16.row.col.f32.bf16.bf16.f32 {%0,%1,%2,%3}, {%4,%5,%6,%7}, {%8,%9}, {%0,%1,%2,%3};"
      : "+f"(d[0]), "+f"(d[1]), "+f"(d[2]), "+f"(d[3])
      : "r"(a0), "r"(a1), "r"(a2), "r"(a3), "r"(b0), "r"(b1));
}
__device__ __forceinline__ void mma16816_z(float (&d)[4], uint32_t a0, uint32_t a1, uint32_t a2, uint32_t a3, uint32_t b0, uint32_t b1) {
  asm("{.reg .f32 z; mov.f32 z, 0f00000000;\n"
      "mma.sync.aligned.m16n8k16.row.col.f32.bf16.bf16.f32 {%0,%1,%2,%3}, {%4,%5,%6,%7}, {%8,%9}, {z,z,z,z};}"
      : "=f"(d[0]), "=f"(d[1]), "=f"(d[2]), "=f"(d[3])
      : "r"(a0), "r"(a1), "r"(a2), "r"(a3), "r"(b0), "r"(b1));
}
template <int N>
__device__ __forceinline__ void cs_frac(int idx, float& c, float& s) {
  int i = ((idx + N / 2) & (N - 1)) - N / 2;
  float a = (float)i * (6.283185307179586f / N);
  c = __cosf(a);
  s = __sinf(a);
}
template <int N>
__device__ __forceinline__ uint32_t cfrag(int idx, int ri) {
  float c, s;
  cs_frac<N>(idx, c, s);
  return ri ? pack2(-s, c) : pack2(c, s);
}
__device__ __forceinline__ uint32_t word(const uint4& v, int e) { return e == 0 ? v.x : e == 1 ? v.y : e == 2 ? v.z : v.w; }
__device__ __forceinline__ void cdft16(const uint4 (&A)[4], const uint4 (&F)[4], uint4 (&o)[4]) {
  float acc[2][4][4];
#pragma unroll
  for (int ks = 0; ks < 2; ks++)
#pragma unroll
    for (int p = 0; p < 2; p++)
#pragma unroll
      for (int v = 0; v < 4; v++) {
        const uint4& a = A[2 * ks + p];
        const uint32_t b0 = word(F[ks * 2 + (v >> 1)], (v & 1) * 2), b1 = word(F[ks * 2 + (v >> 1)], (v & 1) * 2 + 1);
        if (ks == 0) mma16816_z(acc[p][v], a.x, a.y, a.z, a.w, b0, b1);
        else mma16816(acc[p][v], a.x, a.y, a.z, a.w, b0, b1);
      }
#pragma unroll
  for (int v = 0; v < 4; v++)
    o[v] = make_uint4(pack2(acc[0][v][0], acc[0][v][1]), pack2(acc[0][v][2], acc[0][v][3]),
                      pack2(acc[1][v][0], acc[1][v][1]), pack2(acc[1][v][2], acc[1][v][3]));
}
__device__ __forceinline__ void lds_frag(uint4& f0, uint4& f1, uint32_t a0, uint32_t a1) {
  asm volatile("ld.volatile.shared.v2.u32 {%0,%1}, [%8]; ld.volatile.shared.v2.u32 {%2,%3}, [%9];\n"
               "ld.volatile.shared.v2.u32 {%4,%5}, [%8+8]; ld.volatile.shared.v2.u32 {%6,%7}, [%9+8];"
               : "=r"(f0.x), "=r"(f0.y), "=r"(f0.z), "=r"(f0.w), "=r"(f1.x), "=r"(f1.y), "=r"(f1.z), "=r"(f1.w) : "r"(a0), "r"(a1) : "memory");
}
__device__ __forceinline__ void reg_frag(uint4 (&q)[4], uint32_t ones) {
#pragma unroll
  for (int ks = 0; ks < 2; ks++) {
    const uint4 a = q[2 * ks], b = q[2 * ks + 1];
    q[2 * ks] = make_uint4(a.x, a.y, b.x & ones, b.y & ones);
    q[2 * ks + 1] = make_uint4(a.z & ones, a.w & ones, b.z, b.w);
  }
}
__device__ __forceinline__ void st_tag(uint4* p, const uint4& v, uint32_t tag) {
  asm volatile("st.relaxed.gpu.global.v4.b32 [%0], {%1,%2,%3,%4};"
               ::"l"(p), "r"((v.x & ~1u) | tag), "r"(v.y), "r"(v.z), "r"(v.w) : "memory");
}
__device__ __forceinline__ void st_tag8(void* p, uint32_t x, uint32_t y, uint32_t tag) {
  asm volatile("st.relaxed.gpu.global.v2.b32 [%0], {%1,%2};" ::"l"(p), "r"((x & ~1u) | tag), "r"(y) : "memory");
}
__device__ __forceinline__ uint4 ld_b128(const uint4* p) {
  uint4 v;
  asm volatile("ld.relaxed.gpu.global.v4.b32 {%0,%1,%2,%3}, [%4];"
               : "=r"(v.x), "=r"(v.y), "=r"(v.z), "=r"(v.w) : "l"(p) : "memory");
  return v;
}
template <int STRIDE>
__device__ __forceinline__ void ld_tag4_issue(uint4 (&q)[4], const uint4* p) {
#pragma unroll
  for (int i = 0; i < 4; i++) q[i] = ld_b128(p + i * STRIDE);
}
template <int STRIDE, bool HALVES = false>
__device__ __forceinline__ void ld_tag4_finish(uint4 (&q)[4], const uint4* p, uint32_t tag) {
  int it = 0;
#pragma unroll 1
  while (__any_sync(0xffffffffu, ((q[0].x ^ tag) | (q[1].x ^ tag) | (q[2].x ^ tag) | (q[3].x ^ tag) |
                                  (HALVES ? (q[0].z ^ tag) | (q[1].z ^ tag) | (q[2].z ^ tag) | (q[3].z ^ tag) : 0u)) & 1u)) {
    ld_tag4_issue<STRIDE>(q, p);
    if (++it > SPIN_LIMIT) { die(); break; }
  }
#pragma unroll
  for (int i = 0; i < 4; i++) {
    asm volatile("and.b32 %0, %0, 0xfffffffe;" : "+r"(q[i].x));
    if (HALVES) q[i].z &= ~1u;
  }
}
__device__ __forceinline__ float quad_sum(const uint32_t (&a)[8]) {
  float d[4];
  mma16816_z(d, a[0], a[1], a[2], a[3], 0x3f803f80u, 0x3f803f80u);
  mma16816(d, a[4], a[5], a[6], a[7], 0x3f803f80u, 0x3f803f80u);
  return d[0] + d[2];
}
__device__ __forceinline__ float sum_groups(float v) {
  v += __shfl_xor_sync(0xffffffffu, v, 4);
  v += __shfl_xor_sync(0xffffffffu, v, 8);
  v += __shfl_xor_sync(0xffffffffu, v, 16);
  return v;
}
__device__ __forceinline__ uint32_t hsub2_bf16(uint32_t a, uint32_t b) {
  uint32_t r;
  asm("sub.rn.bf16x2 %0, %1, %2;" : "=r"(r) : "r"(a), "r"(b));
  return r;
}
__device__ __forceinline__ float row_rstd(const uint32_t (&c)[8], float delta) {
  uint32_t s[8];
#pragma unroll
  for (int i = 0; i < 8; i++) asm("mul.rn.bf16x2 %0, %1, %1;" : "=r"(s[i]) : "r"(c[i]));
  return rsqrtf(fmaxf(fmaf(-delta, delta, sum_groups(quad_sum(s)) * (1.f / 512.f)), 0.f) + 1e-5f);
}
__device__ __forceinline__ uint64_t desc64(uint32_t lo, uint32_t hi) {
  uint64_t d;
  asm("mov.b64 %0, {%1, %2};" : "=l"(d) : "r"(lo), "r"(hi));
  return d;
}
constexpr uint32_t desc_hi(uint32_t sbo, uint32_t swz) { return (sbo >> 4) | (swz << 30); }
__device__ __forceinline__ uint32_t desc_lo(uint32_t addr, uint32_t lbo) { return ((addr & 0x3FFFF) >> 4) | ((lbo >> 4) << 16); }
__device__ __forceinline__ void cp_async16(uint32_t dst, const void* src) {
  asm volatile("cp.async.cg.shared.global [%0], [%1], 16;" ::"r"(dst), "l"(src) : "memory");
}
__device__ __forceinline__ uint2 lds2(uint32_t a) {
  uint2 v;
  asm volatile("ld.shared.v2.u32 {%0,%1}, [%2];" : "=r"(v.x), "=r"(v.y) : "r"(a) : "memory");
  return v;
}
__device__ __forceinline__ uint32_t lds_u16(uint32_t a) {
  uint16_t v;
  asm volatile("ld.shared.u16 %0, [%1];" : "=h"(v) : "r"(a) : "memory");
  return v;
}
__device__ __forceinline__ void wg_fence() { asm volatile("wgmma.fence.sync.aligned;" ::: "memory"); }
__device__ __forceinline__ void wg_commit() { asm volatile("wgmma.commit_group.sync.aligned;" ::: "memory"); }
template <int N>
__device__ __forceinline__ void wg_wait() { asm volatile("wgmma.wait_group.sync.aligned %0;" ::"n"(N) : "memory"); }
__device__ __forceinline__ void bulk_load(uint32_t dst, const void* src, int bytes, uint32_t bar) {
  asm volatile("cp.async.bulk.shared::cluster.global.mbarrier::complete_tx::bytes [%0], [%1], %2, [%3];"
               ::"r"(dst), "l"(src), "r"(bytes), "r"(bar) : "memory");
}
__device__ __forceinline__ void bulk_load_mc(uint32_t dst, const void* src, int bytes, uint32_t bar) {
  asm volatile("cp.async.bulk.shared::cluster.global.mbarrier::complete_tx::bytes.multicast::cluster [%0], [%1], %2, [%3], %4;"
               ::"r"(dst), "l"(src), "r"(bytes), "r"(bar), "h"((uint16_t)3) : "memory");
}
__device__ __forceinline__ void tma3(uint32_t dst, const CUtensorMap* tm, uint32_t bar, int c0, int c1, int c2) {
  asm volatile("cp.async.bulk.tensor.3d.shared::cluster.global.mbarrier::complete_tx::bytes [%0], [%1, {%3,%4,%5}], [%2];"
               ::"r"(dst), "l"(tm), "r"(bar), "r"(c0), "r"(c1), "r"(c2) : "memory");
}
__device__ __forceinline__ void tma3_mc(uint32_t dst, const CUtensorMap* tm, uint32_t bar, int c1, int c2) {
  asm volatile("cp.async.bulk.tensor.3d.shared::cluster.global.mbarrier::complete_tx::bytes.multicast::cluster [%0], [%1, {%3,%4,%5}], [%2], %6;"
               ::"r"(dst), "l"(tm), "r"(bar), "r"(0), "r"(c1), "r"(c2), "h"((uint16_t)3) : "memory");
}
__device__ __forceinline__ void mbar_arrive_remote(uint32_t rb) {
  asm volatile("mbarrier.arrive.shared::cluster.b64 _, [%0];" ::"r"(rb) : "memory");
}
__device__ __forceinline__ uint4 ldg_ca4(const void* p) {
  uint4 v;
  asm volatile("ld.global.ca.v4.u32 {%0,%1,%2,%3}, [%4];" : "=r"(v.x), "=r"(v.y), "=r"(v.z), "=r"(v.w) : "l"(p) : "memory");
  return v;
}
__device__ __forceinline__ float u2f(uint32_t v) { return __uint_as_float(v); }
__device__ __forceinline__ void mma_az(float (&d)[4], const uint4& a, uint32_t b0, uint32_t b1) { mma16816_z(d, a.x, a.y, a.z, a.w, b0, b1); }
__device__ __forceinline__ void mma_a(float (&d)[4], const uint4& a, uint32_t b0, uint32_t b1) { mma16816(d, a.x, a.y, a.z, a.w, b0, b1); }
__device__ __forceinline__ uint32_t clock32() {
  uint32_t v;
  asm volatile("mov.u32 %0, %%clock;" : "=r"(v) :: "memory");
  return v;
}
__device__ __forceinline__ float swiglu(float g, float u, float r) {
  float hg = (0.5f * r) * g, th;
  asm("tanh.approx.f32 %0, %1;" : "=f"(th) : "f"(hg));
  return fmaf(hg, th, hg) * (r * u);
}
__device__ __forceinline__ void l2_prefetch(const void* p, int bytes) {
  asm volatile("cp.async.bulk.prefetch.L2.global [%0], %1;" ::"l"(p), "r"(bytes) : "memory");
}

__device__ __forceinline__ void wgmma_n256(float (&d)[128], uint64_t da, uint64_t db, int sd = 1) {
  asm volatile("{.reg .pred p; setp.ne.b32 p, %130, 0;\n"
      "wgmma.mma_async.sync.aligned.m64n256k16.f32.bf16.bf16 {"
      "%0,%1,%2,%3,%4,%5,%6,%7,%8,%9,%10,%11,%12,%13,%14,%15,"
      "%16,%17,%18,%19,%20,%21,%22,%23,%24,%25,%26,%27,%28,%29,%30,%31,"
      "%32,%33,%34,%35,%36,%37,%38,%39,%40,%41,%42,%43,%44,%45,%46,%47,"
      "%48,%49,%50,%51,%52,%53,%54,%55,%56,%57,%58,%59,%60,%61,%62,%63,"
      "%64,%65,%66,%67,%68,%69,%70,%71,%72,%73,%74,%75,%76,%77,%78,%79,"
      "%80,%81,%82,%83,%84,%85,%86,%87,%88,%89,%90,%91,%92,%93,%94,%95,"
      "%96,%97,%98,%99,%100,%101,%102,%103,%104,%105,%106,%107,%108,%109,%110,%111,"
      "%112,%113,%114,%115,%116,%117,%118,%119,%120,%121,%122,%123,%124,%125,%126,%127"
      "}, %128, %129, p, 1, 1, 0, 1;}\n"
      : "+f"(d[0]),"+f"(d[1]),"+f"(d[2]),"+f"(d[3]),"+f"(d[4]),"+f"(d[5]),"+f"(d[6]),"+f"(d[7]),
        "+f"(d[8]),"+f"(d[9]),"+f"(d[10]),"+f"(d[11]),"+f"(d[12]),"+f"(d[13]),"+f"(d[14]),"+f"(d[15]),
        "+f"(d[16]),"+f"(d[17]),"+f"(d[18]),"+f"(d[19]),"+f"(d[20]),"+f"(d[21]),"+f"(d[22]),"+f"(d[23]),
        "+f"(d[24]),"+f"(d[25]),"+f"(d[26]),"+f"(d[27]),"+f"(d[28]),"+f"(d[29]),"+f"(d[30]),"+f"(d[31]),
        "+f"(d[32]),"+f"(d[33]),"+f"(d[34]),"+f"(d[35]),"+f"(d[36]),"+f"(d[37]),"+f"(d[38]),"+f"(d[39]),
        "+f"(d[40]),"+f"(d[41]),"+f"(d[42]),"+f"(d[43]),"+f"(d[44]),"+f"(d[45]),"+f"(d[46]),"+f"(d[47]),
        "+f"(d[48]),"+f"(d[49]),"+f"(d[50]),"+f"(d[51]),"+f"(d[52]),"+f"(d[53]),"+f"(d[54]),"+f"(d[55]),
        "+f"(d[56]),"+f"(d[57]),"+f"(d[58]),"+f"(d[59]),"+f"(d[60]),"+f"(d[61]),"+f"(d[62]),"+f"(d[63]),
        "+f"(d[64]),"+f"(d[65]),"+f"(d[66]),"+f"(d[67]),"+f"(d[68]),"+f"(d[69]),"+f"(d[70]),"+f"(d[71]),
        "+f"(d[72]),"+f"(d[73]),"+f"(d[74]),"+f"(d[75]),"+f"(d[76]),"+f"(d[77]),"+f"(d[78]),"+f"(d[79]),
        "+f"(d[80]),"+f"(d[81]),"+f"(d[82]),"+f"(d[83]),"+f"(d[84]),"+f"(d[85]),"+f"(d[86]),"+f"(d[87]),
        "+f"(d[88]),"+f"(d[89]),"+f"(d[90]),"+f"(d[91]),"+f"(d[92]),"+f"(d[93]),"+f"(d[94]),"+f"(d[95]),
        "+f"(d[96]),"+f"(d[97]),"+f"(d[98]),"+f"(d[99]),"+f"(d[100]),"+f"(d[101]),"+f"(d[102]),"+f"(d[103]),
        "+f"(d[104]),"+f"(d[105]),"+f"(d[106]),"+f"(d[107]),"+f"(d[108]),"+f"(d[109]),"+f"(d[110]),"+f"(d[111]),
        "+f"(d[112]),"+f"(d[113]),"+f"(d[114]),"+f"(d[115]),"+f"(d[116]),"+f"(d[117]),"+f"(d[118]),"+f"(d[119]),
        "+f"(d[120]),"+f"(d[121]),"+f"(d[122]),"+f"(d[123]),"+f"(d[124]),"+f"(d[125]),"+f"(d[126]),"+f"(d[127])
      : "l"(da), "l"(db), "r"(sd));
}
__device__ __forceinline__ void wgmma_n192(float (&d)[96], uint64_t da, uint64_t db) {
  asm volatile("wgmma.mma_async.sync.aligned.m64n192k16.f32.bf16.bf16 {"
      "%0,%1,%2,%3,%4,%5,%6,%7,%8,%9,%10,%11,%12,%13,%14,%15,"
      "%16,%17,%18,%19,%20,%21,%22,%23,%24,%25,%26,%27,%28,%29,%30,%31,"
      "%32,%33,%34,%35,%36,%37,%38,%39,%40,%41,%42,%43,%44,%45,%46,%47,"
      "%48,%49,%50,%51,%52,%53,%54,%55,%56,%57,%58,%59,%60,%61,%62,%63,"
      "%64,%65,%66,%67,%68,%69,%70,%71,%72,%73,%74,%75,%76,%77,%78,%79,"
      "%80,%81,%82,%83,%84,%85,%86,%87,%88,%89,%90,%91,%92,%93,%94,%95"
      "}, %96, %97, 1, 1, 1, 0, 1;\n"
      : "+f"(d[0]),"+f"(d[1]),"+f"(d[2]),"+f"(d[3]),"+f"(d[4]),"+f"(d[5]),"+f"(d[6]),"+f"(d[7]),
        "+f"(d[8]),"+f"(d[9]),"+f"(d[10]),"+f"(d[11]),"+f"(d[12]),"+f"(d[13]),"+f"(d[14]),"+f"(d[15]),
        "+f"(d[16]),"+f"(d[17]),"+f"(d[18]),"+f"(d[19]),"+f"(d[20]),"+f"(d[21]),"+f"(d[22]),"+f"(d[23]),
        "+f"(d[24]),"+f"(d[25]),"+f"(d[26]),"+f"(d[27]),"+f"(d[28]),"+f"(d[29]),"+f"(d[30]),"+f"(d[31]),
        "+f"(d[32]),"+f"(d[33]),"+f"(d[34]),"+f"(d[35]),"+f"(d[36]),"+f"(d[37]),"+f"(d[38]),"+f"(d[39]),
        "+f"(d[40]),"+f"(d[41]),"+f"(d[42]),"+f"(d[43]),"+f"(d[44]),"+f"(d[45]),"+f"(d[46]),"+f"(d[47]),
        "+f"(d[48]),"+f"(d[49]),"+f"(d[50]),"+f"(d[51]),"+f"(d[52]),"+f"(d[53]),"+f"(d[54]),"+f"(d[55]),
        "+f"(d[56]),"+f"(d[57]),"+f"(d[58]),"+f"(d[59]),"+f"(d[60]),"+f"(d[61]),"+f"(d[62]),"+f"(d[63]),
        "+f"(d[64]),"+f"(d[65]),"+f"(d[66]),"+f"(d[67]),"+f"(d[68]),"+f"(d[69]),"+f"(d[70]),"+f"(d[71]),
        "+f"(d[72]),"+f"(d[73]),"+f"(d[74]),"+f"(d[75]),"+f"(d[76]),"+f"(d[77]),"+f"(d[78]),"+f"(d[79]),
        "+f"(d[80]),"+f"(d[81]),"+f"(d[82]),"+f"(d[83]),"+f"(d[84]),"+f"(d[85]),"+f"(d[86]),"+f"(d[87]),
        "+f"(d[88]),"+f"(d[89]),"+f"(d[90]),"+f"(d[91]),"+f"(d[92]),"+f"(d[93]),"+f"(d[94]),"+f"(d[95])
      : "l"(da), "l"(db));
}
template <int SD>
__device__ __forceinline__ void wgmma_rs_n128(float (&d)[64], uint32_t a0, uint32_t a1, uint32_t a2, uint32_t a3, uint64_t db) {
  asm volatile("wgmma.mma_async.sync.aligned.m64n128k16.f32.bf16.bf16 {"
      "%0,%1,%2,%3,%4,%5,%6,%7,%8,%9,%10,%11,%12,%13,%14,%15,"
      "%16,%17,%18,%19,%20,%21,%22,%23,%24,%25,%26,%27,%28,%29,%30,%31,"
      "%32,%33,%34,%35,%36,%37,%38,%39,%40,%41,%42,%43,%44,%45,%46,%47,"
      "%48,%49,%50,%51,%52,%53,%54,%55,%56,%57,%58,%59,%60,%61,%62,%63"
      "}, {%64,%65,%66,%67}, %68, %69, 1, 1, 1;\n"
      : "+f"(d[0]),"+f"(d[1]),"+f"(d[2]),"+f"(d[3]),"+f"(d[4]),"+f"(d[5]),"+f"(d[6]),"+f"(d[7]),
        "+f"(d[8]),"+f"(d[9]),"+f"(d[10]),"+f"(d[11]),"+f"(d[12]),"+f"(d[13]),"+f"(d[14]),"+f"(d[15]),
        "+f"(d[16]),"+f"(d[17]),"+f"(d[18]),"+f"(d[19]),"+f"(d[20]),"+f"(d[21]),"+f"(d[22]),"+f"(d[23]),
        "+f"(d[24]),"+f"(d[25]),"+f"(d[26]),"+f"(d[27]),"+f"(d[28]),"+f"(d[29]),"+f"(d[30]),"+f"(d[31]),
        "+f"(d[32]),"+f"(d[33]),"+f"(d[34]),"+f"(d[35]),"+f"(d[36]),"+f"(d[37]),"+f"(d[38]),"+f"(d[39]),
        "+f"(d[40]),"+f"(d[41]),"+f"(d[42]),"+f"(d[43]),"+f"(d[44]),"+f"(d[45]),"+f"(d[46]),"+f"(d[47]),
        "+f"(d[48]),"+f"(d[49]),"+f"(d[50]),"+f"(d[51]),"+f"(d[52]),"+f"(d[53]),"+f"(d[54]),"+f"(d[55]),
        "+f"(d[56]),"+f"(d[57]),"+f"(d[58]),"+f"(d[59]),"+f"(d[60]),"+f"(d[61]),"+f"(d[62]),"+f"(d[63])
      : "r"(a0), "r"(a1), "r"(a2), "r"(a3), "l"(db), "n"(SD));
}

constexpr int C_LN = 0, C_PX = 16, C_PY = 32;
constexpr int NB_CONS = 1, NB_LN = 2, NB_LAG = 4, NB_INIT = 6, NB_RDY = 7, NB_WG = 8;
#define LAGX 3
#define LAGY 3
#define LAG2 5
constexpr int NLL = 2;
#define POLL_DELAY3 600
#define POLL_DELAY 1200
#define FILT_DELAY 600
#define WARM 4
#define ALEAD 6
#define POLL_DELAY2 1200
#define HPOS 14
#define REDPOS 1
#define XTRIG 21
#define HTRIG 0
#define RING_SIG 1
#define PF2_SIG 1
constexpr int SM_E = 0, SM_X = 16384, SM_E2 = 32768, SM_W = 49152, SM_FC = 69632, SM_T = 73728 - T1_BYTES;
constexpr unsigned long long KORDER = 0xBA9432DC876510ull;
constexpr unsigned long long BSLOT = 0x76532107653210ull, PSLOT = 0xDCBA984DCBA984ull;
constexpr uint32_t HI128 = desc_hi(1024, 1), HI64 = desc_hi(512, 2);

struct Bars {
  uint64_t full1[32], empty1[32], full2[16], fullA[8], empty2[8], fullP[16], emptyP[8], hbar, tbar, hint[3], sig[2], sbar;
  uint32_t epoch, pad;
};

template <int NK, bool STORE, int J0 = 0, int J1 = NK>
__device__ __forceinline__ void make_p(const float (&acc)[NK * 16], float r0, float r1, uint4 (&p)[NK], uint4* pbase, int ks0, uint32_t tag) {
#pragma unroll
  for (int j = J0; j < J1; j++) {
    uint32_t w[4];
#pragma unroll
    for (int i = 0; i < 4; i++) {
      const int a = 8 * j + 2 * i, b = a + NK * 8;
      w[i] = pack2(swiglu(acc[a], acc[b], (i & 1) ? r1 : r0), swiglu(acc[a + 1], acc[b + 1], (i & 1) ? r1 : r0));
    }
    asm volatile("" : "+r"(w[0]), "+r"(w[1]), "+r"(w[2]), "+r"(w[3]));
    p[j] = make_uint4(w[0], w[1], w[2], w[3]);
    if (STORE) st_tag(pbase + ((ks0 + j) >> 2) * 1024 + ((ks0 + j) & 3) * 32, p[j], tag);
  }
}
__device__ __forceinline__ void spin_until(uint32_t t) {
  while ((int)(clock32() - t) < 0) {}
}

__global__ void __cluster_dims__(2, 1, 1) __launch_bounds__(NTHREADS, 1)
fused_kernel(const __nv_bfloat16* __restrict__ x, const Tables* __restrict__ tab, Scratch* __restrict__ scr,
             __nv_bfloat16* __restrict__ out, const char* __restrict__ wg_raw, const char* __restrict__ wu_raw,
             const char* __restrict__ wd_raw,
             const __grid_constant__ CUtensorMap tmWR, const __grid_constant__ CUtensorMap tmWI,
             const __grid_constant__ CUtensorMap tmGX, const __grid_constant__ CUtensorMap tmUX,
             const __grid_constant__ CUtensorMap tmGY, const __grid_constant__ CUtensorMap tmUY,
             const __grid_constant__ CUtensorMap tmD) {
  extern __shared__ __align__(1024) char smem_raw[];
  const uint32_t sbase = s2u(smem_raw);
  const uint32_t sbar = sbase + 14 * SLOT, sstat = sbar + 1280;
  const int tid = threadIdx.x, lane = tid & 31;
  const int c = blockIdx.x, rk = c & 1, f = (c >> 1) & 7, rb = 2 * (c >> 4) + rk;
  const int rb2 = 2 * (c >> 4) + (f >> 2), kh = (f >> 1) & 1, nq = 2 * (f & 1) + rk;
#define BAR(field, i) (sbar + (uint32_t)offsetof(Bars, field) + 8u * (i))
#define TOFF(field) (sbase + SM_T + (uint32_t)offsetof(Tables, field) + lane * 16)

  if (tid >= 256) {
    asm volatile("setmaxnreg.dec.sync.aligned.u32 56;");
    const int warp = __shfl_sync(0xffffffffu, tid >> 5, 0);
    if (lane == 0) {
      if (warp == 8) {
        if (sbase & 1023) die();
#pragma unroll
        for (int i = 0; i < 16; i++) mbar_init(BAR(emptyP, i), i < 7 ? 16 : i < 8 ? 8 : i < 13 ? 1 : i < 15 ? 8 : 32);
        mbar_expect(BAR(tbar, 0), T2_BYTES + 2 * 10240);
        mbar_expect(BAR(hbar, 0), 16384);
      } else if (warp == 9) {
#pragma unroll
        for (int i = 0; i < 32; i++) mbar_init(BAR(full1, i), 1);
#pragma unroll
        for (int i = 0; i < 32; i++) mbar_expect(BAR(full1, i), i < 16 ? 16384 : 12288);
      } else if (warp == 10) {
#pragma unroll
        for (int i = 0; i < 32; i++) mbar_init(BAR(empty1, i), 16);
#pragma unroll
        for (int i = 0; i < 14; i++) mbar_init(BAR(fullP, i), 1);
#pragma unroll
        for (int i = 0; i < 14; i++) mbar_expect(BAR(fullP, i), 16384);
      } else {
#pragma unroll
        for (int i = 0; i < 32; i++) mbar_init(BAR(full2, i), i < 24 ? 1 : 8);
#pragma unroll
        for (int i = 0; i < 24; i++) mbar_expect(BAR(full2, i), 16384);
      }
      asm volatile("fence.mbarrier_init.release.cluster;" ::: "memory");
    }
    if (tid == 256) {
      const int w0 = ((c >> 3) * 257 + 32 * (c & 7) + 1) & ~7;
      if (FILT_DELAY) {
        asm volatile("prefetch.tensormap [%0];" ::"l"(&tmWR) : "memory");
        asm volatile("prefetch.tensormap [%0];" ::"l"(&tmWI) : "memory");
        spin_until(clock32() + FILT_DELAY);
      }
      tma3(sbase + SM_W, &tmWR, BAR(tbar, 0), w0, 0, 0);
      tma3(sbase + SM_W + 10240, &tmWI, BAR(tbar, 0), w0, 0, 0);
      bulk_load(sbase + SM_T + T1_BYTES, reinterpret_cast<const char*>(tab) + T1_BYTES, T2_BYTES, BAR(tbar, 0));
    }
    if (tid == 288) {
      asm volatile("prefetch.tensormap [%0];" ::"l"(rk ? &tmUX : &tmGX) : "memory");
      asm volatile("prefetch.tensormap [%0];" ::"l"(rk ? &tmUY : &tmGY) : "memory");
      asm volatile("prefetch.tensormap [%0];" ::"l"(&tmD) : "memory");
    }
    if (tid == 320) {
      const unsigned e = ld_relaxed(&scr->cnt[(C_LN + rb) * 32]) >> 3;
      asm volatile("st.shared.u32 [%0], %1;" ::"r"(BAR(epoch, 0)), "r"(e) : "memory");
    }
    __syncwarp();
    asm volatile("barrier.cluster.arrive.relaxed.aligned;" ::: "memory");
    bar_arrive(NB_RDY, 384);
    asm volatile("barrier.cluster.wait.aligned;" ::: "memory");
    bar_sync(NB_INIT, 384);
    unsigned epoch;
    asm volatile("ld.shared.u32 %0, [%1];" : "=r"(epoch) : "r"(BAR(epoch, 0)) : "memory");
    if (warp == 8) {
      if (lane == 0) {
        const int ax = (7 * f + 3 * (f & 1)) >> 1;
        const int ay = 7 * f + ((f & 1) ? 0 : 4);
        const CUtensorMap* tx = rk ? &tmUX : &tmGX;
        const CUtensorMap* ty = rk ? &tmUY : &tmGY;
        if (RING_SIG >= 0) mbar_wait(BAR(sig, RING_SIG));
        uint32_t s = 2;
#pragma unroll 1
        for (int n = 0; n < 16; n++) {
          if (n >= 6) mbar_wait(BAR(empty1, n - 6));
          tma3_mc(sbase + (8 + s) * SLOT + rk * 8192, tx, BAR(full1, n), n * 32, ax);
          if (++s == 6) s = 0;
        }
#pragma unroll 1
        for (int k = 0; k < 16; k++) {
          mbar_wait(BAR(empty1, k < 8 ? 10 + ((12 * k + 11) >> 4) : 8 + k));
          tma3_mc(sbase + 8 * SLOT + (k & 7) * 12288 + rk * 6144, ty, BAR(full1, 16 + k), k * 32, ay);
        }
      }
    } else if (warp == 9) {
      if (lane == 0) {
        mbar_wait(BAR(fullA, 4));
        wait_counter(&scr->cnt[(C_LN + rb2) * 32], (epoch + 1) * 8);
        asm volatile("fence.proxy.async.global;" ::: "memory");
#pragma unroll 1
        for (int i = 0; i < 15; i++) {
          const int kblk = 14 * kh + (int)((KORDER >> (4 * i)) & 15);
          const int j = i < 7 ? i : i - 7, sl = j + (j >= 4);
          if (i == HPOS) {
            mbar_wait(BAR(emptyP, 7));
            bulk_load(sbase + 4 * SLOT, &scr->LN[(rb2 * 8 + 2 * nq) * 1024 + kh * 512], 8192, BAR(hbar, 0));
            bulk_load(sbase + 4 * SLOT + 8192, &scr->LN[(rb2 * 8 + 2 * nq + 1) * 1024 + kh * 512], 8192, BAR(hbar, 0));
          }
          if (i == 14) break;
          mbar_wait(i < 7 ? BAR(empty1, 17 + 2 * sl) : BAR(empty2, j));
          tma3(sbase + sl * SLOT, &tmD, BAR(full2, i), 0, 64 * kblk, 2 * nq);
        }
      }
    } else if (warp == 10) {
      bar_sync(NB_LN, 288);
      if (lane == 0) {
        PROFP(0);
        red_release(&scr->cnt[(C_LN + rb) * 32]);
        PROFP(1);
        wait_counter(&scr->cnt[(C_LN + rb) * 32], (epoch + 1) * 8);
        asm volatile("fence.proxy.async.global;" ::: "memory");
        PROFP(2);
#pragma unroll 1
        for (int kb = NLL; kb < 8; kb++) {
          if (2 * kb >= ALEAD) mbar_wait(BAR(empty1, 2 * kb - ALEAD));
          bulk_load(sbase + kb * SLOT, &scr->LN[(rb * 8 + kb) * 1024], 16384, BAR(fullA, kb));
        }
#pragma unroll 1
        for (int s = 0; s < 14; s++) {
          const int kblk = 14 * kh + (int)((KORDER >> (4 * s)) & 15);
          if (s == 0 || s == 8 || s == 11) {
            if (s != 11) PROFP(3 + (s >> 2));
            mbar_wait(BAR(hint, s == 0 ? 0 : s == 8 ? 1 : 2), 0);
            if (s != 11) PROFP(4 + (s >> 2));
          }
          const int j = s < 7 ? s : s - 7;
          mbar_wait(s < 7 ? BAR(empty1, 24 + s + (s == 0) + (s >= 4)) : BAR(emptyP, j));
          bulk_load_mc(sbase + (j ? 7 + j : 4) * SLOT + rk * 8192, &scr->P[(rb2 * 28 + kblk) * 1024 + rk * 512], 8192, BAR(fullP, s));
        }
        PROFP(7);
      }
    } else {
      if (lane == 0) {
        mbar_wait(BAR(tbar, 0));
        l2_prefetch(wg_raw + (size_t)c * 5376, 5376);
        l2_prefetch(wu_raw + (size_t)c * 5376, 5376);
        mbar_wait(BAR(sig, PF2_SIG), 0);
        l2_prefetch(wg_raw + 688128 + (size_t)c * 8960, 8960);
        l2_prefetch(wu_raw + 688128 + (size_t)c * 8960, 8960);
      }
      mbar_wait(BAR(fullA, 4), 0);
      if (lane == 0) l2_prefetch(wd_raw + (size_t)c * 14336, 14336);
      {
        const uint32_t tag = (epoch + 1) & 1;
        uint4 v0, v1, v2;
        int it = 0;
        while (true) {
          v0 = ld_b128(&scr->ST[rb * 64 + lane]);
          v1 = ld_b128(&scr->ST[rb * 64 + 32 + lane]);
          v2 = ld_b128(&scr->ST[rb2 * 64 + 32 * kh + lane]);
          if (!__any_sync(0xffffffffu, ((v0.x ^ tag) | (v1.x ^ tag) | (v2.x ^ tag)) & 1u)) break;
          if (++it > SPIN_LIMIT) { die(); break; }
        }
        sts4(sstat + lane * 16, v0.x & ~1u, v0.y, v0.z, v0.w);
        sts4(sstat + 512 + lane * 16, v1.x & ~1u, v1.y, v1.z, v1.w);
        sts4(sstat + 1024 + lane * 16, v2.x & ~1u, v2.y, v2.z, v2.w);
        mbar_arrive(BAR(sbar, 0));
      }
      if (lane == 0) {
        mbar_wait(BAR(empty1, XTRIG));
        int it = 0;
        while ((int)(ld_relaxed(&scr->cnt[(C_PX + rb2) * 32 + kh]) - (epoch + 1) * 32) < 0) {
          if (++it > SPIN_LIMIT) { die(); break; }
        }
        mbar_arrive(BAR(hint, 0));
        mbar_wait(BAR(emptyP, HTRIG));
        uint32_t done = 0;
        while (done != 3) {
          uint2 v;
          asm volatile("ld.relaxed.gpu.global.v2.u32 {%0,%1}, [%2];" : "=r"(v.x), "=r"(v.y) : "l"(&scr->cnt[(C_PY + rb2) * 32 + 2 * kh]) : "memory");
          if (!(done & 1) && (int)(v.x - (epoch + 1) * 16) >= 0) { done |= 1; mbar_arrive(BAR(hint, 1)); }
          if (!(done & 2) && (int)(v.y - (epoch + 1) * 16) >= 0) { done |= 2; mbar_arrive(BAR(hint, 2)); }
          if (++it > SPIN_LIMIT) { die(); break; }
        }
      }
    }
  } else {
    const int warp = __shfl_sync(0xffffffffu, tid >> 5, 0);
    const int g = lane >> 2, t = lane & 3;
    PROF(0);
    PROFG(14);
    uint4 fa[4], fb[4], tw[6];
#pragma unroll
    for (int i = 0; i < 4; i++) fa[i] = ldg_ca4(&tab->fa[i][lane][0]);
#pragma unroll
    for (int i = 0; i < 6; i++) tw[i] = ldg_ca4(&tab->tw1[i][lane][0]);
#pragma unroll
    for (int i = 0; i < 4; i++) fb[i] = ldg_ca4(&tab->fb[i][lane][0]);
#pragma unroll
    for (int i = 0; i < 4; i++) {
      const int r = i >> 1, ch = (i & 1) * 32 + lane;
      cp_async16(sbase + SM_X + (2 * warp + r) * 1024 + ((ch ^ ((ch >> 3) & 1)) * 16),
                 x + (size_t)(c + 128 * (2 * warp + r)) * 512 + ch * 8);
    }
    asm volatile("cp.async.commit_group;" ::: "memory");
    asm volatile("barrier.cluster.arrive.relaxed.aligned;" ::: "memory");
    uint32_t rbar;
    asm volatile("mapa.shared::cluster.u32 %0, %1, %2;" : "=r"(rbar) : "r"(sbar), "r"(rk ^ 1));
#define RBAR(field, i) (rbar + (uint32_t)offsetof(Bars, field) + 8u * (i))
    {
      const int ln = (tid >> 1) & 31, lg = ln >> 2, lt = ln & 3, i = 4 * (tid >> 6) + 2 * (tid & 1);
      const int kidx = lt + 8 * (i >> 3), nidx = 4 * ((i >> 1) & 3) + (lg >> 1);
      const uint32_t a0 = cfrag<2048>((c + 128 * kidx) * nidx, lg & 1), a1 = cfrag<2048>((c + 128 * (kidx + 4)) * nidx, lg & 1);
      const uint32_t b0 = cfrag<2048>(-(c + 128 * nidx) * kidx, lg & 1), b1 = cfrag<2048>(-(c + 128 * nidx) * (kidx + 4), lg & 1);
      asm volatile("st.shared.v2.u32 [%0], {%1,%2};" ::"r"(sbase + SM_FC + tid * 8), "r"(a0), "r"(a1) : "memory");
      asm volatile("st.shared.v2.u32 [%0], {%1,%2};" ::"r"(sbase + SM_FC + 2048 + tid * 8), "r"(b0), "r"(b1) : "memory");
    }
    bar_sync(NB_CONS, 256);
    uint4 fc[4];
#pragma unroll
    for (int i = 0; i < 4; i++) fc[i] = lds4(sbase + SM_FC + i * 512 + lane * 16);
    asm volatile("cp.async.wait_group 0;" ::: "memory");
    __syncwarp();
    bar_arrive(NB_INIT, 384);
    PROF(13);
    uint32_t tag, ones;
    uint4 q[4], o[4];
    {
      uint32_t v[2][8];
#pragma unroll
      for (int r = 0; r < 2; r++)
#pragma unroll
        for (int ks = 0; ks < 2; ks++) {
          const int ch = 32 * ks + 2 * (lane & 15) + (lane >> 4);
          asm volatile("ldmatrix.sync.aligned.m8n8.x4.trans.shared.b16 {%0,%1,%2,%3}, [%4];"
                       : "=r"(v[r][4 * ks]), "=r"(v[r][4 * ks + 1]), "=r"(v[r][4 * ks + 2]), "=r"(v[r][4 * ks + 3])
                       : "r"(sbase + SM_X + (2 * warp + r) * 1024 + ((ch ^ ((ch >> 3) & 1)) * 16)) : "memory");
        }
      float sq[2];
#pragma unroll
      for (int r = 0; r < 2; r++) {
        float s0 = 0.f, s1 = 0.f;
#pragma unroll
        for (int i = 0; i < 8; i++) {
          const float lo = bf_lo(v[r][i]), hi = u2f(v[r][i] & 0xffff0000u);
          s0 = fmaf(lo, lo, s0);
          s1 = fmaf(hi, hi, s1);
        }
        sq[r] = s0 + s1;
      }
      {
        float w = ((lane & 1) ? sq[1] : sq[0]) + __shfl_xor_sync(0xffffffffu, (lane & 1) ? sq[0] : sq[1], 1);
        w += __shfl_xor_sync(0xffffffffu, w, 2);
        w = sum_groups(w);
        const float o2 = __shfl_xor_sync(0xffffffffu, w, 1);
        sq[0] = (lane & 1) ? o2 : w;
        sq[1] = (lane & 1) ? w : o2;
      }
#pragma unroll
      for (int r = 0; r < 2; r++) {
        float dd[2][4], ee[2][4];
#pragma unroll
        for (int nt = 0; nt < 2; nt++) {
          mma_az(dd[nt], fa[0], v[r][2 * nt], v[r][2 * nt + 1]);
          mma_a(dd[nt], fa[1], v[r][4 + 2 * nt], v[r][5 + 2 * nt]);
          mma_az(ee[nt], fa[2], v[r][2 * nt], v[r][2 * nt + 1]);
          mma_a(ee[nt], fa[3], v[r][4 + 2 * nt], v[r][5 + 2 * nt]);
        }
        float mean = (dd[0][0] + dd[0][1]) + (dd[1][0] + dd[1][1]);
        mean += __shfl_xor_sync(0xffffffffu, mean, 1);
        mean += __shfl_xor_sync(0xffffffffu, mean, 2);
        mean = __shfl_sync(0xffffffffu, mean, 0) * (1.f / 512.f);
        const float rs = rsqrtf(fmaxf(fmaf(-mean, mean, sq[r] * (1.f / 512.f)), 0.f) + 1e-5f);
        float acc[4][4];
#pragma unroll
        for (int nt = 0; nt < 2; nt++) {
          const float (&d)[4] = dd[nt];
          const float (&e)[4] = ee[nt];
          const uint4 &ka = tw[2 * nt], &kb = tw[2 * nt + 1], &kc = tw[4 + nt];
          const uint32_t a0 = pack2(d[0] * u2f(ka.x) + d[2] * u2f(ka.y), d[1] * u2f(kb.x) + d[3] * u2f(kb.y));
          const uint32_t a2 = pack2(d[0] * u2f(ka.z) + d[2] * u2f(ka.w), d[1] * u2f(kb.z) + d[3] * u2f(kb.w));
          const uint32_t a1 = pack2(e[0] * u2f(kc.x) + e[2] * u2f(kc.y), e[1] * u2f(kc.z) + e[3] * u2f(kc.w));
          const uint32_t a3 = pack2(e[2] * u2f(kc.x) - e[0] * u2f(kc.y), e[3] * u2f(kc.z) - e[1] * u2f(kc.w));
          const uint32_t dc = pack2(fmaf(mean, -32.f, d[0]), fmaf(mean, -32.f, d[1]));
          const uint32_t h0 = g == 0 ? dc : a0, h2 = g == 0 ? 0u : a2;
          if (nt == 0) {
            mma16816_z(acc[0], a0, a1, a2, a3, fb[2 * nt].x, fb[2 * nt].y);
            mma16816_z(acc[1], a0, a1, a2, a3, fb[2 * nt].z, fb[2 * nt].w);
            mma16816_z(acc[2], h0, a1, h2, a3, fb[2 * nt + 1].x, fb[2 * nt + 1].y);
            mma16816_z(acc[3], h0, a1, h2, a3, fb[2 * nt + 1].z, fb[2 * nt + 1].w);
          } else {
            mma16816(acc[0], a0, a1, a2, a3, fb[2 * nt].x, fb[2 * nt].y);
            mma16816(acc[1], a0, a1, a2, a3, fb[2 * nt].z, fb[2 * nt].w);
            mma16816(acc[2], h0, a1, h2, a3, fb[2 * nt + 1].x, fb[2 * nt + 1].y);
            mma16816(acc[3], h0, a1, h2, a3, fb[2 * nt + 1].z, fb[2 * nt + 1].w);
          }
        }
#pragma unroll
        for (int h = 0; h < 2; h++) {
          const int j = 2 * warp + r, m = 2 * t + h;
          sts4(sbase + SM_E + ((j * 8 + m) * 8 + (g ^ (2 * t) ^ (2 * (j & 3)))) * 16,
               pack2(acc[h][0] * rs, acc[h][1] * rs), pack2(acc[h][2] * rs, acc[h][3] * rs),
               pack2(acc[2 + h][0] * rs, acc[2 + h][1] * rs), pack2(acc[2 + h][2] * rs, acc[2 + h][3] * rs));
        }
      }
      if (tid == 0) PROFP(12);
      bar_sync(NB_RDY, 384);
      if (tid == 0) PROFP(13);
      const uint32_t ea = sbase + SM_E + ((t * 8 + warp) * 8 + (g ^ (warp & 6) ^ (2 * t))) * 16;
      lds_frag(q[0], q[1], ea, ea + 4096);
      lds_frag(q[2], q[3], ea + 8192, ea + 12288);
      asm volatile("ld.shared.u32 %0, [%1];" : "=r"(tag) : "r"(BAR(epoch, 0)) : "memory");
      ones = ~(tag >> 31);
      tag = (tag + 1) & 1;
      cdft16(q, fc, o);
#pragma unroll
      for (int vv = 0; vv < 4; vv++) {
        o[vv].y &= ~1u;
        st_tag(&scr->Z1[(((4 * vv + t) * 8 + warp) * 128 + c) * 8 + g], o[vv], tag);
      }
    }
    PROF(1);
    asm volatile("setmaxnreg.inc.sync.aligned.u32 224;");
    {
      const uint4* const zp = &scr->Z1[(c * 128 + 8 * t + warp) * 8 + g];
      const uint32_t tst = clock32();
      mbar_wait(BAR(tbar, 0), 0);
      if (tid == 0) PROFP(14);
      uint4 f2[4], g2[4];
#pragma unroll
      for (int i = 0; i < 4; i++) {
        f2[i] = lds4(TOFF(f2) + warp * 2048 + i * 512);
        g2[i] = lds4(TOFF(g2) + warp * 2048 + i * 512);
      }
      const uint4 f8 = lds4(TOFF(f8)), g8 = lds4(TOFF(g8));
      float wfr[16], wfi[16];
      {
        const float nyq = ((c & 7) == 7 && g == 0) ? 0.5f : 1.f;
        const int gg = g == 0 ? 16 : g, wsh = (2 * (c >> 3) + 2) & 15;
#pragma unroll
        for (int i = 0; i < 16; i++) {
          const int ci = i >> 3, dd = (i >> 2) & 1, e = i & 3;
          const int kk = (e == 0 ? gg : e == 1 ? g + 8 : e == 2 ? 32 - g : 24 - g) - 1;
          const uint32_t a = sbase + SM_W + ((2 * warp + ci) * 8 + t + 4 * dd) * 80 + wsh + 2 * kk;
          wfr[i] = bf_lo(lds_u16(a)) * (e == 2 ? nyq : 1.f);
          wfi[i] = bf_lo(lds_u16(a + 10240)) * (e == 2 ? nyq : 1.f);
        }
      }
      asm volatile("barrier.cluster.wait.aligned;" ::: "memory");
      PROF(2);
      spin_until(tst + POLL_DELAY);
      ld_tag4_issue<256>(q, zp);
      ld_tag4_finish<256>(q, zp, tag);
      if (tid == 0) PROFP(30);
      if (lane == 0) mbar_arrive(BAR(sig, 0));
      reg_frag(q, ones);
      cdft16(q, f2, o);
      const uint32_t e2 = sbase + SM_E2;
#pragma unroll
      for (int vv = 0; vv < 4; vv++)
        sts4(e2 + ((warp * 16 + 4 * vv + t) * 8 + (g ^ (2 * t) ^ (2 * (warp & 3)))) * 16, o[vv].x, o[vv].y, o[vv].z, o[vv].w);
      bar_sync(NB_CONS, 256);
      uint32_t ad[2], res[2][2][4];
#pragma unroll
      for (int ci = 0; ci < 2; ci++) {
        const int cc = 2 * warp + ci;
        ad[ci] = e2 + ((t * 16 + cc) * 8 + (g ^ (2 * (cc & 3)) ^ (2 * t))) * 16;
        lds_frag(q[2 * ci], q[2 * ci + 1], ad[ci], ad[ci] + 8192);
      }
#pragma unroll
      for (int ci = 0; ci < 2; ci++)
#pragma unroll
        for (int p = 0; p < 2; p++) {
          uint32_t y[2][2];
#pragma unroll
          for (int vv = 0; vv < 2; vv++) {
            float d[4];
            mma_az(d, q[2 * ci + p], word(f8, 2 * vv), word(f8, 2 * vv + 1));
#pragma unroll
            for (int rr = 0; rr < 2; rr++) {
              const float fr = wfr[ci * 8 + vv * 4 + 2 * p + rr], fi = wfi[ci * 8 + vv * 4 + 2 * p + rr];
              y[vv][rr] = pack2(d[2 * rr] * fr - d[2 * rr + 1] * fi, d[2 * rr] * fi + d[2 * rr + 1] * fr);
            }
          }
#pragma unroll
          for (int vv = 0; vv < 2; vv++) {
            float d[4];
            mma16816_z(d, y[0][0], y[0][1], y[1][0], y[1][1], word(g8, 2 * vv), word(g8, 2 * vv + 1));
            res[ci][vv][2 * p] = pack2(d[0], d[1]);
            res[ci][vv][2 * p + 1] = pack2(d[2], d[3]);
          }
        }
#pragma unroll
      for (int i = 0; i < 4; i++)
        sts4(ad[i >> 1] + (i & 1) * 8192, res[i >> 1][i & 1][0], res[i >> 1][i & 1][1], res[i >> 1][i & 1][2], res[i >> 1][i & 1][3]);
      bar_sync(NB_CONS, 256);
      const uint32_t eb = e2 + ((warp * 16 + t) * 8 + (g ^ (2 * t) ^ (2 * (warp & 3)))) * 16;
      lds_frag(q[0], q[1], eb, eb + 512);
      lds_frag(q[2], q[3], eb + 1024, eb + 1536);
      cdft16(q, g2, o);
#pragma unroll
      for (int vv = 0; vv < 4; vv++) st_tag(&scr->Z2[((8 * (4 * vv + t) + warp) * 128 + c) * 8 + g], o[vv], tag);
    }
    PROF(3);
    {
      const uint4* const zp = &scr->Z2[((c * 16 + t) * 8 + warp) * 8 + g];
      const uint32_t tst = clock32();
      uint4 gb[4], ga[4], gc[4], tw[4];
      uint2 xr[2][4];
      uint2* lnp[2];
#pragma unroll
      for (int r = 0; r < 2; r++) {
        const int row = 16 * f + 2 * warp + r;
        lnp[r] = reinterpret_cast<uint2*>(&scr->LN[(rb * 8 + (g >> 2)) * 1024 + row * 8 + ((2 * (g & 3) + (t >> 1)) ^ (row & 7))]) + (t & 1);
        asm volatile("" : "+l"(lnp[r]));
      }
#pragma unroll
      for (int i = 0; i < 4; i++) {
        gc[i] = lds4(sbase + SM_FC + 2048 + i * 512 + lane * 16);
        gb[i] = lds4(TOFF(gb) + i * 512);
        ga[i] = lds4(TOFF(ga) + i * 512);
        tw[i] = lds4(TOFF(tw3) + i * 512);
        const int ch = 2 * (g + 8 * i) + (t >> 1);
#pragma unroll
        for (int r = 0; r < 2; r++) xr[r][i] = lds2(sbase + SM_X + (2 * warp + r) * 1024 + ((ch ^ ((ch >> 3) & 1)) * 16) + (t & 1) * 8);
      }
      PROF(4);
      spin_until(tst + POLL_DELAY2);
      ld_tag4_issue<256>(q, zp);
      ld_tag4_finish<256>(q, zp, tag);
      if (tid == 0) PROFP(31);
      if (lane == 0) mbar_arrive(BAR(sig, 1));
      reg_frag(q, ones);
      cdft16(q, gc, o);
#pragma unroll
      for (int vv = 0; vv < 4; vv++)
        sts4(sbase + SM_E + (((4 * vv + t) * 8 + warp) * 8 + (g ^ (warp & 6) ^ (2 * t))) * 16, o[vv].x, o[vv].y, o[vv].z, o[vv].w);
      if (tid == 0) PROFP(8);
      bar_sync(NB_CONS, 256);
      if (tid == 0) PROFP(9);
      uint32_t hv[2][8];
      const float mk = t == 0 ? 0.f : 1.f;
#pragma unroll
      for (int r = 0; r < 2; r++) {
        const int j = 2 * warp + r;
        uint4 u[2];
#pragma unroll
        for (int h = 0; h < 2; h++) u[h] = lds4(sbase + SM_E + ((j * 8 + 2 * t + h) * 8 + (g ^ (2 * t) ^ (2 * (j & 3)))) * 16);
        const uint32_t bp[4][2] = {{u[0].x, u[1].x & ones}, {u[0].y & ones, u[1].y}, {u[0].z, u[1].z & ones}, {u[0].w & ones, u[1].w}};
        float y[2][2][4];
#pragma unroll
        for (int i = 0; i < 2; i++) {
          float lo[4], hi[4], e[4];
          mma_az(lo, gb[2 * i], bp[0][0], bp[0][1]);
          mma_az(hi, gb[2 * i + 1], bp[2][0], bp[2][1]);
          mma_az(e, gb[2 * i], bp[1][0], bp[1][1]);
          mma_a(e, gb[2 * i + 1], bp[3][0], bp[3][1]);
          const uint4 &ka = tw[2 * i], &kb = tw[2 * i + 1];
          const float tr0 = fmaf(hi[0], mk, lo[0]), ti0 = fmaf(hi[2], mk, lo[2]);
          const float tr1 = lo[1] + hi[1], ti1 = lo[3] + hi[3];
          const float vr0 = tr0 * u2f(ka.x) - ti0 * u2f(ka.y), vi0 = tr0 * u2f(ka.y) + ti0 * u2f(ka.x);
          const float vr1 = tr1 * u2f(ka.z) - ti1 * u2f(ka.w), vi1 = tr1 * u2f(ka.w) + ti1 * u2f(ka.z);
          const uint32_t b0 = pack2(t == 0 ? hi[0] : vr0, vr1), b1 = pack2(t == 0 ? vr0 : vi0, vi1);
          const uint32_t b2 = pack2(e[0] * u2f(kb.x) - e[2] * u2f(kb.y), e[1] * u2f(kb.z) - e[3] * u2f(kb.w));
          const uint32_t b3 = pack2(e[0] * u2f(kb.y) + e[2] * u2f(kb.x), e[1] * u2f(kb.w) + e[3] * u2f(kb.z));
#pragma unroll
          for (int mt = 0; mt < 2; mt++) {
            mma_az(y[mt][i], ga[2 * mt], b0, b1);
            mma_a(y[mt][i], ga[2 * mt + 1], b2, b3);
          }
        }
#pragma unroll
        for (int i = 0; i < 4; i++) {
          hv[r][2 * i] = hadd2_bf16(xr[r][i].x, pack2(y[i >> 1][0][2 * (i & 1)], y[i >> 1][0][2 * (i & 1) + 1]));
          hv[r][2 * i + 1] = hadd2_bf16(xr[r][i].y, pack2(y[i >> 1][1][2 * (i & 1)], y[i >> 1][1][2 * (i & 1) + 1]));
        }
      }
      if (tid == 0 && hv[0][0] != 0x12345 && hv[1][7] != 0x12345) PROFP(10);
      float mean[2];
      uint32_t mb[2];
#pragma unroll
      for (int r = 0; r < 2; r++) {
        mean[r] = sum_groups(quad_sum(hv[r])) * (1.f / 512.f);
        mb[r] = pack2(mean[r], mean[r]);
      }
#pragma unroll
      for (int i = 0; i < 4; i++)
#pragma unroll
        for (int r = 0; r < 2; r++) {
          hv[r][2 * i] = hsub2_bf16(hv[r][2 * i], mb[r]);
          hv[r][2 * i + 1] = hsub2_bf16(hv[r][2 * i + 1], mb[r]);
          st_tag8(lnp[r] + i * 4096, hv[r][2 * i], hv[r][2 * i + 1], i == 0 ? tag : (hv[r][2 * i] & 1u));
        }
      if (tid == 0) PROFP(11);
      bar_arrive(NB_LN, 288);
      const uint32_t ones2 = ~(lds2(BAR(epoch, 0)).x >> 31);
      float rstd[2];
#pragma unroll
      for (int r = 0; r < 2; r++) {
        hv[r][0] &= ones2;
        rstd[r] = row_rstd(hv[r], mean[r] - bf_lo(mb[r]));
      }
      if (lane == 0)
        st_tag(&scr->ST[rb * 64 + 8 * f + warp], make_uint4(mb[0] << 16, __float_as_uint(rstd[0]), mb[1] << 16, __float_as_uint(rstd[1])), tag);
    }
    PROF(5);
    const int wgi = warp >> 2, wq = warp & 3;
    uint4* const pbase = &scr->P[rb * 28 * 1024 + warp * 128 + lane];
    const uint32_t a_lo0 = desc_lo(sbase + wgi * 8192, 16);
    const uint32_t ebar = lane == 0 ? BAR(empty1, 0) : RBAR(empty1, 0);
    float r0, r1;
    uint4 px[8], py[6];
    const int rh = wgi ^ kh ^ 1;
    const uint4* const psrc = &scr->P[(rb2 * 28 + 14 * kh) * 1024 + (4 * rh + wq) * 128 + lane];
    const uint32_t pa0 = sbase + (4 * rh + wq) * 2048;
    uint4 pf[3][4];
    uint32_t rdy = 0;
    {
      float acc[128];
#pragma unroll
      for (int i = 0; i < 128; i++) acc[i] = 0.f;
      const uint32_t b_lo0 = desc_lo(sbase + 8 * SLOT, 4096);
      const uint32_t t3 = clock32();
      if (WARM) {
        wg_fence();
#pragma unroll
        for (int i = 0; i < WARM; i++) wgmma_n256(acc, desc64(a_lo0 + 6 * 1024, HI128), desc64(b_lo0, HI128));
        wg_commit();
      }
      const uint4* const ap = &scr->LN[rb * 8 * 1024 + wgi * 512 + (tid & 127)];
      uint4 av[NLL][4];
      spin_until(t3 + POLL_DELAY3);
#pragma unroll
      for (int kb = 0; kb < NLL; kb++) ld_tag4_issue<128>(av[kb], ap + kb * 1024);
      bar_sync(NB_CONS, 256);
      uint32_t slot = 2;
      auto stage_x = [&](int kb, int hh) {
        if (LAGX && hh == ((16 - LAGX) & 1) && kb == ((16 - LAGX) >> 1) && wgi == 1) bar_sync(NB_LAG, 256);
        mbar_wait(BAR(full1, 2 * kb + hh));
        const uint32_t al = a_lo0 + kb * 1024 + hh * 4, bl = b_lo0 + slot * 1024;
        wg_fence();
        wgmma_n256(acc, desc64(al, HI128), desc64(bl, HI128), (kb | hh) != 0 ? 1 : ~ones);
        wgmma_n256(acc, desc64(al + 2, HI128), desc64(bl + 128, HI128));
        wg_commit();
        if (LAGX && hh == 1 && kb == 7 && wgi == 0) bar_arrive(NB_LAG, 256);
        wg_wait<1>();
        if ((kb | hh) != 0 && lane < 2) mbar_arrive_remote(ebar + 8 * (2 * kb + hh - 1));
        if (++slot == 6) slot = 0;
      };
#pragma unroll
      for (int kb = 0; kb < NLL; kb++) {
        ld_tag4_finish<128, true>(av[kb], ap + kb * 1024, tag);
#pragma unroll
        for (int i = 0; i < 4; i++)
          sts4(sbase + kb * SLOT + wgi * 8192 + ((tid & 127) + 128 * i) * 16, av[kb][i].x, av[kb][i].y, av[kb][i].z, av[kb][i].w);
        asm volatile("fence.proxy.async.shared::cta;" ::: "memory");
        bar_sync(NB_WG + wgi, 128);
        if (kb > 0) stage_x(kb - 1, 1);
        if (kb == 0) PROF(6);
        stage_x(kb, 0);
      }
      stage_x(NLL - 1, 1);
#pragma unroll 1
      for (int kb = NLL; kb < 8; kb++) {
        mbar_wait(BAR(fullA, kb));
        stage_x(kb, 0);
        stage_x(kb, 1);
      }
      mbar_wait(BAR(sbar, 0), 0);
      r0 = __uint_as_float(lds2(sstat + (16 * warp + g) * 8).y);
      r1 = __uint_as_float(lds2(sstat + (16 * warp + g + 8) * 8).y);
      wg_wait<0>();
      if (lane < 2) mbar_arrive_remote(ebar + 8 * 15);
      PROF(7);
      make_p<8, false>(acc, r0, r1, px, pbase, 0, tag);
    }
    PROF(8);
    {
      float acc[96];
#pragma unroll
      for (int i = 0; i < 96; i++) acc[i] = 0.f;
      const uint32_t b_lo0 = desc_lo(sbase + 8 * SLOT, 2048);
      uint4* const pdst = pbase + ((7 * f + 3 * (f & 1)) >> 1) * 1024;
      auto stage_y = [&](int k) {
        if (LAGY && k == 16 - LAGY && wgi == 1) bar_sync(NB_LAG, 256);
        mbar_wait(BAR(full1, 16 + k));
        const uint32_t al = a_lo0 + (k >> 1) * 1024 + (k & 1) * 4, bl = b_lo0 + (k & 7) * 768;
        wg_fence();
        wgmma_n192(acc, desc64(al, HI128), desc64(bl, HI64));
        wgmma_n192(acc, desc64(al + 2, HI128), desc64(bl + 64, HI64));
        wg_commit();
      };
#pragma unroll
      for (int k = 0; k < 4; k++) {
        stage_y(k);
        st_tag(pdst + (k >> 1) * 1024 + (k & 1) * 64, px[2 * k], tag);
        st_tag(pdst + (k >> 1) * 1024 + (k & 1) * 64 + 32, px[2 * k + 1], tag);
        if (k == 3 && lane == 0) red_relaxed(&scr->cnt[(C_PX + rb) * 32 + (f >> 2)]);
        wg_wait<1>();
        if (k != 0 && lane < 2) mbar_arrive_remote(ebar + 8 * (15 + k));
      }
#pragma unroll 1
      for (int k = 4; k < 16; k++) {
        stage_y(k);
        if (LAGY && k == 15 && wgi == 0) bar_arrive(NB_LAG, 256);
        wg_wait<1>();
        if (lane < 2) mbar_arrive_remote(ebar + 8 * (15 + k));
      }
      rdy = __all_sync(0xffffffffu, mbar_test(BAR(fullP, 0)) & mbar_test(BAR(full2, 0)) & mbar_test(BAR(fullP, 1)));
      if (rdy) {
#pragma unroll
        for (int kk = 0; kk < 4; kk++) pf[0][kk] = lds4(pa0 + 4 * SLOT + kk * 512 + lane * 16);
      }
      wg_wait<0>();
      if (lane < 2) mbar_arrive_remote(ebar + 8 * 31);
      PROF(9);
      make_p<6, true, 0, REDPOS>(acc, r0, r1, py, pbase, 14 * f + ((f & 1) ? 0 : 8), tag);
      if (lane == 0) red_relaxed(&scr->cnt[(C_PY + rb) * 32 + (f >> 1)]);
      make_p<6, true, REDPOS, 6>(acc, r0, r1, py, pbase, 14 * f + ((f & 1) ? 0 : 8), tag);
    }
    PROF(10);
    {
      float acc[64];
      const uint32_t b2_lo0 = desc_lo(sbase, 8192);
      const uint32_t pbar = ebar + (uint32_t)(offsetof(Bars, emptyP) - offsetof(Bars, empty1));
      if (!rdy) {
        mbar_wait(BAR(fullP, 0));
#pragma unroll
        for (int kk = 0; kk < 4; kk++) pf[0][kk] = lds4(pa0 + 4 * SLOT + kk * 512 + lane * 16);
      }
#pragma unroll
      for (int s = 0; s < 14; s++) {
        uint4 (&a)[4] = pf[s % 3];
        ld_tag4_finish<32>(a, psrc + (int)((KORDER >> (4 * s)) & 15) * 1024, tag);
        if (s < 8 && lane < (s < 7 ? 2 : 1)) mbar_arrive_remote(pbar + 8 * s);
        if (s >= 2) {
          wg_wait<1>();
          if (s <= 8 && lane == 0) mbar_arrive(BAR(empty2, s - 2));
        }
        if (!rdy) {
          if (s < 13) mbar_wait(BAR(fullP, s + 1));
          mbar_wait(BAR(full2, s));
        }
        if (tid == 0) PROFP(16 + s);
        if (s == 14 - LAG2 && wgi == 1) {
          const float m0 = __uint_as_float(lds2(sstat + 1024 + (16 * wq + g) * 8).x);
          const float m1 = __uint_as_float(lds2(sstat + 1024 + (16 * wq + g + 8) * 8).x);
          const uint32_t hb = sbase + 4 * SLOT + (16 * wq + (lane & 15)) * 128;
          wg_wait<0>();
          mbar_wait(BAR(hbar, 0));
#pragma unroll
          for (int i = 0; i < 8; i++) {
            uint32_t h[4];
            asm volatile("ldmatrix.sync.aligned.m8n8.x4.shared.b16 {%0,%1,%2,%3}, [%4];"
                         : "=r"(h[0]), "=r"(h[1]), "=r"(h[2]), "=r"(h[3])
                         : "r"(hb + (i >> 2) * 8192 + (((2 * (i & 3) + (lane >> 4)) ^ (lane & 7)) * 16)) : "memory");
            const uint32_t mk = ((t & 1) == 0 && nq == 0) ? ~1u : ~0u;
#pragma unroll
            for (int e = 0; e < 4; e++) {
              acc[8 * i + 2 * e] += bf_lo(h[e] & mk) + ((e & 1) ? m1 : m0);
              acc[8 * i + 2 * e + 1] += __uint_as_float(h[e] & 0xffff0000u) + ((e & 1) ? m1 : m0);
            }
          }
          bar_sync(NB_LAG, 256);
        }
        const uint32_t bl = b2_lo0 + (uint32_t)((BSLOT >> (4 * s)) & 15) * 1024;
        wg_fence();
        if (s < 13) {
#pragma unroll
          for (int kk = 0; kk < 4; kk++)
            pf[(s + 1) % 3][kk] = lds4(pa0 + (uint32_t)((PSLOT >> (4 * (s + 1))) & 15) * SLOT + kk * 512 + lane * 16);
          rdy = mbar_test(BAR(full2, s + 1));
          if (s < 12) rdy &= mbar_test(BAR(fullP, s + 2));
        }
        if (s == 0) wgmma_rs_n128<0>(acc, a[0].x, a[0].y, a[0].z, a[0].w, desc64(bl, HI128));
        else wgmma_rs_n128<1>(acc, a[0].x, a[0].y, a[0].z, a[0].w, desc64(bl, HI128));
#pragma unroll
        for (int kk = 1; kk < 4; kk++) wgmma_rs_n128<1>(acc, a[kk].x, a[kk].y, a[kk].z, a[kk].w, desc64(bl + kk * 128, HI128));
        wg_commit();
      }
      if (wgi == 0) {
        bar_arrive(NB_LAG, 256);
        uint4* const dst = &scr->Z1[(c ^ 4) * 1024 + tid];
        wg_wait<0>();
        PROF(11);
#pragma unroll
        for (int i = 0; i < 8; i++)
          st_tag(dst + i * 128, make_uint4(pack2(acc[8 * i], acc[8 * i + 1]), pack2(acc[8 * i + 2], acc[8 * i + 3]) | 1u,
                                           pack2(acc[8 * i + 4], acc[8 * i + 5]), pack2(acc[8 * i + 6], acc[8 * i + 7])), tag);
      } else {
        uint4 pv[2][4];
        const uint4* const xsrc = &scr->Z1[c * 1024 + (tid & 127)];
        ld_tag4_issue<128>(pv[0], xsrc);
        ld_tag4_issue<128>(pv[1], xsrc + 512);
        wg_wait<0>();
        PROF(11);
        uint32_t w[32];
#pragma unroll
        for (int i = 0; i < 32; i++) w[i] = pack2(acc[2 * i], acc[2 * i + 1]);
        int it = 0;
#pragma unroll 1
        while (!__all_sync(0xffffffffu, pv[0][0].y & pv[0][1].y & pv[0][2].y & pv[0][3].y & pv[1][0].y & pv[1][1].y & pv[1][2].y & pv[1][3].y & 1u)) {
          ld_tag4_issue<128>(pv[0], xsrc);
          ld_tag4_issue<128>(pv[1], xsrc + 512);
          if (++it > SPIN_LIMIT) { die(); break; }
        }
#pragma unroll
        for (int i = 0; i < 8; i++) {
          const uint4& p = pv[i >> 2][i & 3];
          asm volatile("stmatrix.sync.aligned.m8n8.x4.shared.b16 [%0], {%1,%2,%3,%4};"
                       ::"r"(pa0 + (9 + ((lane >> 3) & 1)) * SLOT + (lane & 7) * 256 + (((2 * i + (lane >> 4)) ^ (lane & 7)) * 16)),
                         "r"(hadd2_bf16(w[4 * i], p.x & ~1u)), "r"(hadd2_bf16(w[4 * i + 1], p.y)), "r"(hadd2_bf16(w[4 * i + 2], p.z)),
                         "r"(hadd2_bf16(w[4 * i + 3], p.w)) : "memory");
        }
        __syncwarp();
        uint4* const dst = reinterpret_cast<uint4*>(out) + (16 * (c >> 4) + 2 * (4 * rh + wq) + (rb2 & 1) + 128 * (lane >> 4)) * 64 + nq * 16 + (lane & 15);
#pragma unroll
        for (int i = 0; i < 8; i++) {
          const int r = 2 * (i & 3) + (lane >> 4);
          dst[i * 256 * 64] = lds4(pa0 + (9 + (i >> 2)) * SLOT + r * 256 + (((lane & 15) ^ r) * 16));
        }
      }
      PROF(12);
      PROFG(15);
    }
  }
#undef BAR
#undef TOFF
#undef RBAR
}

typedef CUresult (*EncodeFn)(CUtensorMap*, CUtensorMapDataType, cuuint32_t, void*, const cuuint64_t*, const cuuint64_t*,
                             const cuuint32_t*, const cuuint32_t*, CUtensorMapInterleave, CUtensorMapSwizzle,
                             CUtensorMapL2promotion, CUtensorMapFloatOOBfill);

}

extern "C" void kernel_launch(void* const* d_in, const int* in_sizes, int n_in, void* d_out, int out_size) {
  (void)in_sizes; (void)n_in; (void)out_size;
  static EncodeFn encode = nullptr;
  static void *tab = nullptr, *scr = nullptr;
  if (!encode) {
    void* fn = nullptr;
    cudaDriverEntryPointQueryResult qr;
    cudaGetDriverEntryPoint("cuTensorMapEncodeTiled", &fn, cudaEnableDefault, &qr);
    encode = (EncodeFn)fn;
    cudaGetSymbolAddress(&tab, g_tab);
    cudaGetSymbolAddress(&scr, g_scr);
    cudaFuncSetAttribute(fused_kernel, cudaFuncAttributeMaxDynamicSharedMemorySize, SMEM_BYTES);
  }
  CUtensorMap tmGX, tmUX, tmGY, tmUY, tmD, tmWR, tmWI;
  const cuuint32_t es[5] = {1, 1, 1, 1, 1};
  auto enc = [&](CUtensorMap* m, void* p, int rank, const cuuint64_t* gd, const cuuint64_t* gs, const cuuint32_t* bd,
                 CUtensorMapSwizzle sw, CUtensorMapL2promotion pr) {
    encode(m, CU_TENSOR_MAP_DATA_TYPE_BFLOAT16, rank, p, gd, gs, bd, es, CU_TENSOR_MAP_INTERLEAVE_NONE, sw, pr,
           CU_TENSOR_MAP_FLOAT_OOB_FILL_NONE);
  };
  {
    const cuuint64_t gd[3] = {64, 512, 28}, gs[2] = {3584, 128};
    const cuuint32_t bd[3] = {64, 32, 2};
    enc(&tmGX, d_in[4], 3, gd, gs, bd, CU_TENSOR_MAP_SWIZZLE_128B, CU_TENSOR_MAP_L2_PROMOTION_L2_256B);
    enc(&tmUX, d_in[5], 3, gd, gs, bd, CU_TENSOR_MAP_SWIZZLE_128B, CU_TENSOR_MAP_L2_PROMOTION_L2_256B);
  }
  {
    const cuuint64_t gd[3] = {32, 512, 56}, gs[2] = {3584, 64};
    const cuuint32_t bd[3] = {32, 32, 3};
    enc(&tmGY, d_in[4], 3, gd, gs, bd, CU_TENSOR_MAP_SWIZZLE_64B, CU_TENSOR_MAP_L2_PROMOTION_L2_128B);
    enc(&tmUY, d_in[5], 3, gd, gs, bd, CU_TENSOR_MAP_SWIZZLE_64B, CU_TENSOR_MAP_L2_PROMOTION_L2_128B);
  }
  {
    const cuuint64_t gd[3] = {64, 1792, 8}, gs[2] = {1024, 128};
    const cuuint32_t bd[3] = {64, 64, 2};
    enc(&tmD, d_in[6], 3, gd, gs, bd, CU_TENSOR_MAP_SWIZZLE_128B, CU_TENSOR_MAP_L2_PROMOTION_L2_256B);
  }
  {
    const cuuint64_t gd[3] = {4112, 8, 16}, gs[2] = {16 * 8224, 8224};
    const cuuint32_t bd[3] = {40, 8, 16};
    enc(&tmWR, d_in[1], 3, gd, gs, bd, CU_TENSOR_MAP_SWIZZLE_NONE, CU_TENSOR_MAP_L2_PROMOTION_NONE);
    enc(&tmWI, d_in[2], 3, gd, gs, bd, CU_TENSOR_MAP_SWIZZLE_NONE, CU_TENSOR_MAP_L2_PROMOTION_NONE);
  }
  fused_kernel<<<NCTA, NTHREADS, SMEM_BYTES>>>((const __nv_bfloat16*)d_in[0], (const Tables*)tab, (Scratch*)scr,
                                               (__nv_bfloat16*)d_out, (const char*)d_in[4], (const char*)d_in[5],
                                               (const char*)d_in[6], tmWR, tmWI, tmGX, tmUX, tmGY, tmUY, tmD);
}
```

```cpp
#include <cuda_runtime.h>
#include <cuda_bf16.h>
#include <cuda.h>
#include <stdint.h>

namespace {

constexpr int NCTA = 128;
constexpr int NTHREADS = 384;
constexpr int SLOT = 16384;
constexpr int SMEM_BYTES = 14 * SLOT + 3072;
constexpr int SPIN_LIMIT = 1 << 22;

struct Scratch {
  uint4 Z1[128 * 1024];
  uint4 LN[16 * 8 * 1024];
  uint4 P[16 * 28 * 1024];
  uint4 ST[1024];
  unsigned cnt[64 * 32];
};
__device__ __align__(1024) Scratch g_scr;
#define PROF(i)
#define PROFP(i)
#define PROFG(i)

constexpr double ccos(int i, int n) {
  i &= n - 1;
  if (i > n / 2) i = n - i;
  if (4 * i == n) return 0.0;
  const bool neg = 4 * i > n;
  if (neg) i = n / 2 - i;
  const double a = 6.283185307179586476925 * i / n, a2 = a * a;
  double term = 1.0, sum = 1.0;
  for (int k = 1; k < 14; k++) { term *= -a2 / ((2 * k - 1) * (2 * k)); sum += term; }
  return neg ? -sum : sum;
}
constexpr double csin(int i, int n) { return ccos(i - n / 4, n); }
constexpr unsigned fbits(double v, int mant) {
  if (v == 0.0) return 0;
  const unsigned sg = v < 0 ? 1u : 0u;
  if (v < 0) v = -v;
  int e = 127;
  while (v < 1.0) { v *= 2.0; e--; }
  const unsigned m = (unsigned)((v - 1.0) * (double)(1u << mant) + 0.5);
  return (sg << (8 + mant)) + ((unsigned)e << mant) + m;
}
constexpr unsigned pkb(double lo, double hi) { return fbits(lo, 7) | (fbits(hi, 7) << 16); }
constexpr double fa_elem(int mt, int r, int n1) {
  const int k1 = 8 * mt + (r & 7);
  return r < 8 ? ccos(k1 * n1, 32) : k1 == 0 ? ccos(16 * n1, 32) : -csin(k1 * n1, 32);
}
constexpr unsigned cfrag_c(int idx, int n, int ri, double s = 1.0) {
  return ri ? pkb(-s * csin(idx, n), s * ccos(idx, n)) : pkb(s * ccos(idx, n), s * csin(idx, n));
}
struct Tables {
  unsigned fa[4][32][4];
  unsigned fb[4][32][4];
  unsigned tw1[6][32][4];
  unsigned f2[8][4][32][4];
  unsigned g2[8][4][32][4];
  unsigned gb[4][32][4];
  unsigned ga[4][32][4];
  unsigned tw3[4][32][4];
  unsigned f8[32][4], g8[32][4];
};
constexpr int T1_BYTES = 7168, T2_BYTES = 39936;
static_assert(sizeof(Tables) == T1_BYTES + T2_BYTES, "table size");
constexpr Tables make_tables() {
  Tables T = {};
  for (int l = 0; l < 32; l++) {
    const int g = l >> 2, t = l & 3;
    for (int a = 0; a < 2; a++)
      for (int b = 0; b < 2; b++) {
        for (int r = 0; r < 4; r++) {
          const int row = g + 8 * (r & 1), col = 2 * t + 8 * (r >> 1);
          T.fa[2 * a + b][l][r] = pkb(fa_elem(a, row, 16 * b + col), fa_elem(a, row, 16 * b + col + 1));
          T.ga[2 * a + b][l][r] = pkb(fa_elem(b, col, 16 * a + row), fa_elem(b, col + 1, 16 * a + row));
        }
        const double sg = b ? -1.0 : 1.0;
        for (int h = 0; h < 2; h++) {
          const int ri = g & 1, m = 2 * (g >> 1) + h, k2 = b ? 15 - m : m;
          const int pa = (8 * a + 2 * t) * k2, pb = (8 * a + 2 * t + 1) * k2;
          T.fb[2 * a + b][l][2 * h] = ri == 0 ? pkb(ccos(pa, 16), ccos(pb, 16)) : pkb(-sg * csin(pa, 16), -sg * csin(pb, 16));
          T.fb[2 * a + b][l][2 * h + 1] = ri == 0 ? pkb(csin(pa, 16), csin(pb, 16)) : pkb(sg * ccos(pa, 16), sg * ccos(pb, 16));
        }
        const int n2 = 4 * (g >> 1) + 2 * a + (g & 1);
        for (int h = 0; h < 2; h++) {
          const int p = n2 * (b ? 15 - 2 * t - h : 2 * t + h);
          T.gb[2 * a + b][l][2 * h] = pkb(ccos(p, 16), -sg * csin(p, 16));
          T.gb[2 * a + b][l][2 * h + 1] = pkb(csin(p, 16), sg * ccos(p, 16));
          const int k1 = 8 * b + 2 * t + h, q = n2 * (k1 == 0 ? 16 : k1);
          T.tw3[2 * a + b][l][2 * h] = fbits(ccos(q, 512), 23);
          T.tw3[2 * a + b][l][2 * h + 1] = fbits(csin(q, 512), 23);
        }
        const int p = (8 * a + 2 * t + b) * (g == 0 ? 16 : g);
        T.tw1[2 * a + b][l][0] = fbits(g == 0 ? 0.0 : ccos(p, 512), 23);
        T.tw1[2 * a + b][l][1] = fbits(g == 0 ? ccos(p, 512) : csin(p, 512), 23);
        T.tw1[2 * a + b][l][2] = fbits(g == 0 ? 0.0 : -csin(p, 512), 23);
        T.tw1[2 * a + b][l][3] = fbits(g == 0 ? -csin(p, 512) : ccos(p, 512), 23);
        T.tw1[4 + a][l][2 * b] = fbits(ccos((8 * a + 2 * t + b) * (g + 8), 512), 23);
        T.tw1[4 + a][l][2 * b + 1] = fbits(csin((8 * a + 2 * t + b) * (g + 8), 512), 23);
      }
    for (int i = 0; i < 4; i++) {
      const int p8 = (t + 4 * (i & 1)) * (4 * (i >> 1) + (g >> 1));
      T.f8[l][i] = cfrag_c(p8, 8, g & 1);
      T.g8[l][i] = cfrag_c(-p8, 8, g & 1, 1.0 / (1 << 19));
    }
    for (int w = 0; w < 8; w++)
      for (int i = 0; i < 16; i++) {
        const int kidx = t + 4 * (i & 1) + 8 * (i >> 3), nidx = 4 * ((i >> 1) & 3) + (g >> 1);
        T.f2[w][i >> 2][l][i & 3] = cfrag_c((8 * kidx + w) * nidx, 128, g & 1);
        T.g2[w][i >> 2][l][i & 3] = cfrag_c(-(8 * nidx + w) * kidx, 128, g & 1);
      }
  }
  return T;
}
__device__ const __align__(128) Tables g_tab = make_tables();

__device__ __forceinline__ void die() { asm volatile("st.global.u32 [%0], %1;" ::"l"(0ull), "r"(0) : "memory"); }
__device__ __forceinline__ uint32_t s2u(const void* p) { return (uint32_t)__cvta_generic_to_shared(p); }
__device__ __forceinline__ void mbar_init(uint32_t b, int c) { asm volatile("mbarrier.init.shared::cta.b64 [%0], %1;" ::"r"(b), "r"(c)); }
__device__ __forceinline__ void mbar_expect(uint32_t b, int bytes) {
  asm volatile("mbarrier.arrive.expect_tx.shared::cta.b64 _, [%0], %1;" ::"r"(b), "r"(bytes) : "memory");
}
__device__ __forceinline__ void mbar_arrive(uint32_t b) { asm volatile("mbarrier.arrive.shared::cta.b64 _, [%0];" ::"r"(b) : "memory"); }
__device__ __forceinline__ uint32_t mbar_try(uint32_t b, uint32_t parity) {
  uint32_t ok;
  asm volatile("{.reg .pred p; mbarrier.try_wait.parity.shared::cta.b64 p, [%1], %2; selp.u32 %0,1,0,p;}"
               : "=r"(ok) : "r"(b), "r"(parity) : "memory");
  return ok;
}
__device__ __forceinline__ uint32_t mbar_test(uint32_t b) {
  uint32_t ok;
  asm volatile("{.reg .pred p; mbarrier.test_wait.parity.shared::cta.b64 p, [%1], 0; selp.u32 %0,1,0,p;}" : "=r"(ok) : "r"(b) : "memory");
  return ok;
}
__device__ __forceinline__ void mbar_wait(uint32_t b, uint32_t parity = 0) {
  int it = 0;
#pragma unroll 1
  while (!mbar_try(b, parity))
    if (++it > SPIN_LIMIT) { die(); break; }
}
__device__ __forceinline__ void bar_sync(int id, int n) { asm volatile("bar.sync %0, %1;" ::"r"(id), "r"(n) : "memory"); }
__device__ __forceinline__ void bar_arrive(int id, int n) { asm volatile("bar.arrive %0, %1;" ::"r"(id), "r"(n) : "memory"); }
__device__ __forceinline__ void red_release(unsigned* p) { asm volatile("red.release.gpu.global.add.u32 [%0], 1;" ::"l"(p) : "memory"); }
__device__ __forceinline__ void red_relaxed(unsigned* p) { asm volatile("red.relaxed.gpu.global.add.u32 [%0], 1;" ::"l"(p) : "memory"); }
__device__ __forceinline__ unsigned ld_acquire(const unsigned* p) {
  unsigned v;
  asm volatile("ld.acquire.gpu.global.u32 %0, [%1];" : "=r"(v) : "l"(p) : "memory");
  return v;
}
__device__ __forceinline__ unsigned ld_relaxed(const unsigned* p) {
  unsigned v;
  asm volatile("ld.relaxed.gpu.global.u32 %0, [%1];" : "=r"(v) : "l"(p) : "memory");
  return v;
}
__device__ __forceinline__ void wait_counter(const unsigned* p, unsigned target) {
  int it = 0;
  while ((int)(ld_acquire(p) - target) < 0)
    if (++it > SPIN_LIMIT) { die(); break; }
}
__device__ __forceinline__ void sts4(uint32_t a, uint32_t x, uint32_t y, uint32_t z, uint32_t w) {
  asm volatile("st.shared.v4.u32 [%0], {%1,%2,%3,%4};" ::"r"(a), "r"(x), "r"(y), "r"(z), "r"(w) : "memory");
}
__device__ __forceinline__ uint4 lds4(uint32_t a) {
  uint4 v;
  asm volatile("ld.shared.v4.u32 {%0,%1,%2,%3}, [%4];" : "=r"(v.x), "=r"(v.y), "=r"(v.z), "=r"(v.w) : "r"(a) : "memory");
  return v;
}
__device__ __forceinline__ uint32_t pack2(float lo, float hi) {
  uint32_t r;
  asm("cvt.rn.bf16x2.f32 %0, %1, %2;" : "=r"(r) : "f"(hi), "f"(lo));
  return r;
}
__device__ __forceinline__ float bf_lo(uint32_t v) { return __uint_as_float(v << 16); }
__device__ __forceinline__ uint32_t hadd2_bf16(uint32_t a, uint32_t b) {
  uint32_t r;
  asm("add.rn.bf16x2 %0, %1, %2;" : "=r"(r) : "r"(a), "r"(b));
  return r;
}
__device__ __forceinline__ void mma16816(float (&d)[4], uint32_t a0, uint32_t a1, uint32_t a2, uint32_t a3, uint32_t b0, uint32_t b1) {
  asm("mma.sync.aligned.m16n8k16.row.col.f32.bf16.bf16.f32 {%0,%1,%2,%3}, {%4,%5,%6,%7}, {%8,%9}, {%0,%1,%2,%3};"
      : "+f"(d[0]), "+f"(d[1]), "+f"(d[2]), "+f"(d[3])
      : "r"(a0), "r"(a1), "r"(a2), "r"(a3), "r"(b0), "r"(b1));
}
__device__ __forceinline__ void mma16816_z(float (&d)[4], uint32_t a0, uint32_t a1, uint32_t a2, uint32_t a3, uint32_t b0, uint32_t b1) {
  asm("{.reg .f32 z; mov.f32 z, 0f00000000;\n"
      "mma.sync.aligned.m16n8k16.row.col.f32.bf16.bf16.f32 {%0,%1,%2,%3}, {%4,%5,%6,%7}, {%8,%9}, {z,z,z,z};}"
      : "=f"(d[0]), "=f"(d[1]), "=f"(d[2]), "=f"(d[3])
      : "r"(a0), "r"(a1), "r"(a2), "r"(a3), "r"(b0), "r"(b1));
}
template <int N>
__device__ __forceinline__ void cs_frac(int idx, float& c, float& s) {
  int i = ((idx + N / 2) & (N - 1)) - N / 2;
  float a = (float)i * (6.283185307179586f / N);
  c = __cosf(a);
  s = __sinf(a);
}
template <int N>
__device__ __forceinline__ uint32_t cfrag(int idx, int ri) {
  float c, s;
  cs_frac<N>(idx, c, s);
  return ri ? pack2(-s, c) : pack2(c, s);
}
__device__ __forceinline__ uint32_t word(const uint4& v, int e) { return e == 0 ? v.x : e == 1 ? v.y : e == 2 ? v.z : v.w; }
__device__ __forceinline__ void cdft16(const uint4 (&A)[4], const uint4 (&F)[4], uint4 (&o)[4]) {
  float acc[2][4][4];
#pragma unroll
  for (int ks = 0; ks < 2; ks++)
#pragma unroll
    for (int p = 0; p < 2; p++)
#pragma unroll
      for (int v = 0; v < 4; v++) {
        const uint4& a = A[2 * ks + p];
        const uint32_t b0 = word(F[ks * 2 + (v >> 1)], (v & 1) * 2), b1 = word(F[ks * 2 + (v >> 1)], (v & 1) * 2 + 1);
        if (ks == 0) mma16816_z(acc[p][v], a.x, a.y, a.z, a.w, b0, b1);
        else mma16816(acc[p][v], a.x, a.y, a.z, a.w, b0, b1);
      }
#pragma unroll
  for (int v = 0; v < 4; v++)
    o[v] = make_uint4(pack2(acc[0][v][0], acc[0][v][1]), pack2(acc[0][v][2], acc[0][v][3]),
                      pack2(acc[1][v][0], acc[1][v][1]), pack2(acc[1][v][2], acc[1][v][3]));
}
__device__ __forceinline__ void lds_frag(uint4& f0, uint4& f1, uint32_t a0, uint32_t a1) {
  asm volatile("ld.volatile.shared.v2.u32 {%0,%1}, [%8]; ld.volatile.shared.v2.u32 {%2,%3}, [%9];\n"
               "ld.volatile.shared.v2.u32 {%4,%5}, [%8+8]; ld.volatile.shared.v2.u32 {%6,%7}, [%9+8];"
               : "=r"(f0.x), "=r"(f0.y), "=r"(f0.z), "=r"(f0.w), "=r"(f1.x), "=r"(f1.y), "=r"(f1.z), "=r"(f1.w) : "r"(a0), "r"(a1) : "memory");
}
__device__ __forceinline__ void reg_frag(uint4 (&q)[4], uint32_t ones) {
#pragma unroll
  for (int ks = 0; ks < 2; ks++) {
    const uint4 a = q[2 * ks], b = q[2 * ks + 1];
    q[2 * ks] = make_uint4(a.x, a.y, b.x & ones, b.y & ones);
    q[2 * ks + 1] = make_uint4(a.z & ones, a.w & ones, b.z, b.w);
  }
}
__device__ __forceinline__ void st_tag(uint4* p, const uint4& v, uint32_t tag) {
  asm volatile("st.relaxed.gpu.global.v4.b32 [%0], {%1,%2,%3,%4};"
               ::"l"(p), "r"((v.x & ~1u) | tag), "r"(v.y), "r"(v.z), "r"(v.w) : "memory");
}
__device__ __forceinline__ void st_tag8(void* p, uint32_t x, uint32_t y, uint32_t tag) {
  asm volatile("st.relaxed.gpu.global.v2.b32 [%0], {%1,%2};" ::"l"(p), "r"((x & ~1u) | tag), "r"(y) : "memory");
}
__device__ __forceinline__ uint4 ld_b128(const uint4* p) {
  uint4 v;
  asm volatile("ld.relaxed.gpu.global.v4.b32 {%0,%1,%2,%3}, [%4];"
               : "=r"(v.x), "=r"(v.y), "=r"(v.z), "=r"(v.w) : "l"(p) : "memory");
  return v;
}
template <int STRIDE>
__device__ __forceinline__ void ld_tag4_issue(uint4 (&q)[4], const uint4* p) {
#pragma unroll
  for (int i = 0; i < 4; i++) q[i] = ld_b128(p + i * STRIDE);
}
template <int STRIDE, bool HALVES = false>
__device__ __forceinline__ void ld_tag4_finish(uint4 (&q)[4], const uint4* p, uint32_t tag) {
  int it = 0;
#pragma unroll 1
  while (__any_sync(0xffffffffu, ((q[0].x ^ tag) | (q[1].x ^ tag) | (q[2].x ^ tag) | (q[3].x ^ tag) |
                                  (HALVES ? (q[0].z ^ tag) | (q[1].z ^ tag) | (q[2].z ^ tag) | (q[3].z ^ tag) : 0u)) & 1u)) {
    ld_tag4_issue<STRIDE>(q, p);
    if (++it > SPIN_LIMIT) { die(); break; }
  }
#pragma unroll
  for (int i = 0; i < 4; i++) {
    asm volatile("and.b32 %0, %0, 0xfffffffe;" : "+r"(q[i].x));
    if (HALVES) q[i].z &= ~1u;
  }
}
__device__ __forceinline__ float quad_sum(const uint32_t (&a)[8]) {
  float d[4];
  mma16816_z(d, a[0], a[1], a[2], a[3], 0x3f803f80u, 0x3f803f80u);
  mma16816(d, a[4], a[5], a[6], a[7], 0x3f803f80u, 0x3f803f80u);
  return d[0] + d[2];
}
__device__ __forceinline__ float sum_groups(float v) {
  v += __shfl_xor_sync(0xffffffffu, v, 4);
  v += __shfl_xor_sync(0xffffffffu, v, 8);
  v += __shfl_xor_sync(0xffffffffu, v, 16);
  return v;
}
__device__ __forceinline__ uint32_t hsub2_bf16(uint32_t a, uint32_t b) {
  uint32_t r;
  asm("sub.rn.bf16x2 %0, %1, %2;" : "=r"(r) : "r"(a), "r"(b));
  return r;
}
__device__ __forceinline__ float row_rstd(const uint32_t (&c)[8], float delta) {
  uint32_t s[8];
#pragma unroll
  for (int i = 0; i < 8; i++) asm("mul.rn.bf16x2 %0, %1, %1;" : "=r"(s[i]) : "r"(c[i]));
  return rsqrtf(fmaxf(fmaf(-delta, delta, sum_groups(quad_sum(s)) * (1.f / 512.f)), 0.f) + 1e-5f);
}
__device__ __forceinline__ uint64_t desc64(uint32_t lo, uint32_t hi) {
  uint64_t d;
  asm("mov.b64 %0, {%1, %2};" : "=l"(d) : "r"(lo), "r"(hi));
  return d;
}
constexpr uint32_t desc_hi(uint32_t sbo, uint32_t swz) { return (sbo >> 4) | (swz << 30); }
__device__ __forceinline__ uint32_t desc_lo(uint32_t addr, uint32_t lbo) { return ((addr & 0x3FFFF) >> 4) | ((lbo >> 4) << 16); }
__device__ __forceinline__ void cp_async16(uint32_t dst, const void* src) {
  asm volatile("cp.async.cg.shared.global [%0], [%1], 16;" ::"r"(dst), "l"(src) : "memory");
}
__device__ __forceinline__ uint2 lds2(uint32_t a) {
  uint2 v;
  asm volatile("ld.shared.v2.u32 {%0,%1}, [%2];" : "=r"(v.x), "=r"(v.y) : "r"(a) : "memory");
  return v;
}
__device__ __forceinline__ uint32_t lds_u16(uint32_t a) {
  uint16_t v;
  asm volatile("ld.shared.u16 %0, [%1];" : "=h"(v) : "r"(a) : "memory");
  return v;
}
__device__ __forceinline__ void wg_fence() { asm volatile("wgmma.fence.sync.aligned;" ::: "memory"); }
__device__ __forceinline__ void wg_commit() { asm volatile("wgmma.commit_group.sync.aligned;" ::: "memory"); }
template <int N>
__device__ __forceinline__ void wg_wait() { asm volatile("wgmma.wait_group.sync.aligned %0;" ::"n"(N) : "memory"); }
__device__ __forceinline__ void bulk_load(uint32_t dst, const void* src, int bytes, uint32_t bar) {
  asm volatile("cp.async.bulk.shared::cluster.global.mbarrier::complete_tx::bytes [%0], [%1], %2, [%3];"
               ::"r"(dst), "l"(src), "r"(bytes), "r"(bar) : "memory");
}
__device__ __forceinline__ void bulk_load_mc(uint32_t dst, const void* src, int bytes, uint32_t bar) {
  asm volatile("cp.async.bulk.shared::cluster.global.mbarrier::complete_tx::bytes.multicast::cluster [%0], [%1], %2, [%3], %4;"
               ::"r"(dst), "l"(src), "r"(bytes), "r"(bar), "h"((uint16_t)3) : "memory");
}
__device__ __forceinline__ void tma3(uint32_t dst, const CUtensorMap* tm, uint32_t bar, int c0, int c1, int c2) {
  asm volatile("cp.async.bulk.tensor.3d.shared::cluster.global.mbarrier::complete_tx::bytes [%0], [%1, {%3,%4,%5}], [%2];"
               ::"r"(dst), "l"(tm), "r"(bar), "r"(c0), "r"(c1), "r"(c2) : "memory");
}
__device__ __forceinline__ void tma3_mc(uint32_t dst, const CUtensorMap* tm, uint32_t bar, int c1, int c2) {
  asm volatile("cp.async.bulk.tensor.3d.shared::cluster.global.mbarrier::complete_tx::bytes.multicast::cluster [%0], [%1, {%3,%4,%5}], [%2], %6;"
               ::"r"(dst), "l"(tm), "r"(bar), "r"(0), "r"(c1), "r"(c2), "h"((uint16_t)3) : "memory");
}
__device__ __forceinline__ void mbar_arrive_remote(uint32_t rb) {
  asm volatile("mbarrier.arrive.shared::cluster.b64 _, [%0];" ::"r"(rb) : "memory");
}
__device__ __forceinline__ uint4 ldg_ca4(const void* p) {
  uint4 v;
  asm volatile("ld.global.ca.v4.u32 {%0,%1,%2,%3}, [%4];" : "=r"(v.x), "=r"(v.y), "=r"(v.z), "=r"(v.w) : "l"(p) : "memory");
  return v;
}
__device__ __forceinline__ float u2f(uint32_t v) { return __uint_as_float(v); }
__device__ __forceinline__ void mma_az(float (&d)[4], const uint4& a, uint32_t b0, uint32_t b1) { mma16816_z(d, a.x, a.y, a.z, a.w, b0, b1); }
__device__ __forceinline__ void mma_a(float (&d)[4], const uint4& a, uint32_t b0, uint32_t b1) { mma16816(d, a.x, a.y, a.z, a.w, b0, b1); }
__device__ __forceinline__ uint32_t clock32() {
  uint32_t v;
  asm volatile("mov.u32 %0, %%clock;" : "=r"(v) :: "memory");
  return v;
}
__device__ __forceinline__ float swiglu(float g, float u, float r) {
  float hg = (0.5f * r) * g, th;
  asm("tanh.approx.f32 %0, %1;" : "=f"(th) : "f"(hg));
  return fmaf(hg, th, hg) * (r * u);
}
__device__ __forceinline__ void l2_prefetch(const void* p, int bytes) {
  asm volatile("cp.async.bulk.prefetch.L2.global [%0], %1;" ::"l"(p), "r"(bytes) : "memory");
}

__device__ __forceinline__ void wgmma_n256(float (&d)[128], uint64_t da, uint64_t db, int sd = 1) {
  asm volatile("{.reg .pred p; setp.ne.b32 p, %130, 0;\n"
      "wgmma.mma_async.sync.aligned.m64n256k16.f32.bf16.bf16 {"
      "%0,%1,%2,%3,%4,%5,%6,%7,%8,%9,%10,%11,%12,%13,%14,%15,"
      "%16,%17,%18,%19,%20,%21,%22,%23,%24,%25,%26,%27,%28,%29,%30,%31,"
      "%32,%33,%34,%35,%36,%37,%38,%39,%40,%41,%42,%43,%44,%45,%46,%47,"
      "%48,%49,%50,%51,%52,%53,%54,%55,%56,%57,%58,%59,%60,%61,%62,%63,"
      "%64,%65,%66,%67,%68,%69,%70,%71,%72,%73,%74,%75,%76,%77,%78,%79,"
      "%80,%81,%82,%83,%84,%85,%86,%87,%88,%89,%90,%91,%92,%93,%94,%95,"
      "%96,%97,%98,%99,%100,%101,%102,%103,%104,%105,%106,%107,%108,%109,%110,%111,"
      "%112,%113,%114,%115,%116,%117,%118,%119,%120,%121,%122,%123,%124,%125,%126,%127"
      "}, %128, %129, p, 1, 1, 0, 1;}\n"
      : "+f"(d[0]),"+f"(d[1]),"+f"(d[2]),"+f"(d[3]),"+f"(d[4]),"+f"(d[5]),"+f"(d[6]),"+f"(d[7]),
        "+f"(d[8]),"+f"(d[9]),"+f"(d[10]),"+f"(d[11]),"+f"(d[12]),"+f"(d[13]),"+f"(d[14]),"+f"(d[15]),
        "+f"(d[16]),"+f"(d[17]),"+f"(d[18]),"+f"(d[19]),"+f"(d[20]),"+f"(d[21]),"+f"(d[22]),"+f"(d[23]),
        "+f"(d[24]),"+f"(d[25]),"+f"(d[26]),"+f"(d[27]),"+f"(d[28]),"+f"(d[29]),"+f"(d[30]),"+f"(d[31]),
        "+f"(d[32]),"+f"(d[33]),"+f"(d[34]),"+f"(d[35]),"+f"(d[36]),"+f"(d[37]),"+f"(d[38]),"+f"(d[39]),
        "+f"(d[40]),"+f"(d[41]),"+f"(d[42]),"+f"(d[43]),"+f"(d[44]),"+f"(d[45]),"+f"(d[46]),"+f"(d[47]),
        "+f"(d[48]),"+f"(d[49]),"+f"(d[50]),"+f"(d[51]),"+f"(d[52]),"+f"(d[53]),"+f"(d[54]),"+f"(d[55]),
        "+f"(d[56]),"+f"(d[57]),"+f"(d[58]),"+f"(d[59]),"+f"(d[60]),"+f"(d[61]),"+f"(d[62]),"+f"(d[63]),
        "+f"(d[64]),"+f"(d[65]),"+f"(d[66]),"+f"(d[67]),"+f"(d[68]),"+f"(d[69]),"+f"(d[70]),"+f"(d[71]),
        "+f"(d[72]),"+f"(d[73]),"+f"(d[74]),"+f"(d[75]),"+f"(d[76]),"+f"(d[77]),"+f"(d[78]),"+f"(d[79]),
        "+f"(d[80]),"+f"(d[81]),"+f"(d[82]),"+f"(d[83]),"+f"(d[84]),"+f"(d[85]),"+f"(d[86]),"+f"(d[87]),
        "+f"(d[88]),"+f"(d[89]),"+f"(d[90]),"+f"(d[91]),"+f"(d[92]),"+f"(d[93]),"+f"(d[94]),"+f"(d[95]),
        "+f"(d[96]),"+f"(d[97]),"+f"(d[98]),"+f"(d[99]),"+f"(d[100]),"+f"(d[101]),"+f"(d[102]),"+f"(d[103]),
        "+f"(d[104]),"+f"(d[105]),"+f"(d[106]),"+f"(d[107]),"+f"(d[108]),"+f"(d[109]),"+f"(d[110]),"+f"(d[111]),
        "+f"(d[112]),"+f"(d[113]),"+f"(d[114]),"+f"(d[115]),"+f"(d[116]),"+f"(d[117]),"+f"(d[118]),"+f"(d[119]),
        "+f"(d[120]),"+f"(d[121]),"+f"(d[122]),"+f"(d[123]),"+f"(d[124]),"+f"(d[125]),"+f"(d[126]),"+f"(d[127])
      : "l"(da), "l"(db), "r"(sd));
}
__device__ __forceinline__ void wgmma_n192(float (&d)[96], uint64_t da, uint64_t db) {
  asm volatile("wgmma.mma_async.sync.aligned.m64n192k16.f32.bf16.bf16 {"
      "%0,%1,%2,%3,%4,%5,%6,%7,%8,%9,%10,%11,%12,%13,%14,%15,"
      "%16,%17,%18,%19,%20,%21,%22,%23,%24,%25,%26,%27,%28,%29,%30,%31,"
      "%32,%33,%34,%35,%36,%37,%38,%39,%40,%41,%42,%43,%44,%45,%46,%47,"
      "%48,%49,%50,%51,%52,%53,%54,%55,%56,%57,%58,%59,%60,%61,%62,%63,"
      "%64,%65,%66,%67,%68,%69,%70,%71,%72,%73,%74,%75,%76,%77,%78,%79,"
      "%80,%81,%82,%83,%84,%85,%86,%87,%88,%89,%90,%91,%92,%93,%94,%95"
      "}, %96, %97, 1, 1, 1, 0, 1;\n"
      : "+f"(d[0]),"+f"(d[1]),"+f"(d[2]),"+f"(d[3]),"+f"(d[4]),"+f"(d[5]),"+f"(d[6]),"+f"(d[7]),
        "+f"(d[8]),"+f"(d[9]),"+f"(d[10]),"+f"(d[11]),"+f"(d[12]),"+f"(d[13]),"+f"(d[14]),"+f"(d[15]),
        "+f"(d[16]),"+f"(d[17]),"+f"(d[18]),"+f"(d[19]),"+f"(d[20]),"+f"(d[21]),"+f"(d[22]),"+f"(d[23]),
        "+f"(d[24]),"+f"(d[25]),"+f"(d[26]),"+f"(d[27]),"+f"(d[28]),"+f"(d[29]),"+f"(d[30]),"+f"(d[31]),
        "+f"(d[32]),"+f"(d[33]),"+f"(d[34]),"+f"(d[35]),"+f"(d[36]),"+f"(d[37]),"+f"(d[38]),"+f"(d[39]),
        "+f"(d[40]),"+f"(d[41]),"+f"(d[42]),"+f"(d[43]),"+f"(d[44]),"+f"(d[45]),"+f"(d[46]),"+f"(d[47]),
        "+f"(d[48]),"+f"(d[49]),"+f"(d[50]),"+f"(d[51]),"+f"(d[52]),"+f"(d[53]),"+f"(d[54]),"+f"(d[55]),
        "+f"(d[56]),"+f"(d[57]),"+f"(d[58]),"+f"(d[59]),"+f"(d[60]),"+f"(d[61]),"+f"(d[62]),"+f"(d[63]),
        "+f"(d[64]),"+f"(d[65]),"+f"(d[66]),"+f"(d[67]),"+f"(d[68]),"+f"(d[69]),"+f"(d[70]),"+f"(d[71]),
        "+f"(d[72]),"+f"(d[73]),"+f"(d[74]),"+f"(d[75]),"+f"(d[76]),"+f"(d[77]),"+f"(d[78]),"+f"(d[79]),
        "+f"(d[80]),"+f"(d[81]),"+f"(d[82]),"+f"(d[83]),"+f"(d[84]),"+f"(d[85]),"+f"(d[86]),"+f"(d[87]),
        "+f"(d[88]),"+f"(d[89]),"+f"(d[90]),"+f"(d[91]),"+f"(d[92]),"+f"(d[93]),"+f"(d[94]),"+f"(d[95])
      : "l"(da), "l"(db));
}
template <int SD>
__device__ __forceinline__ void wgmma_rs_n128(float (&d)[64], uint32_t a0, uint32_t a1, uint32_t a2, uint32_t a3, uint64_t db) {
  asm volatile("wgmma.mma_async.sync.aligned.m64n128k16.f32.bf16.bf16 {"
      "%0,%1,%2,%3,%4,%5,%6,%7,%8,%9,%10,%11,%12,%13,%14,%15,"
      "%16,%17,%18,%19,%20,%21,%22,%23,%24,%25,%26,%27,%28,%29,%30,%31,"
      "%32,%33,%34,%35,%36,%37,%38,%39,%40,%41,%42,%43,%44,%45,%46,%47,"
      "%48,%49,%50,%51,%52,%53,%54,%55,%56,%57,%58,%59,%60,%61,%62,%63"
      "}, {%64,%65,%66,%67}, %68, %69, 1, 1, 1;\n"
      : "+f"(d[0]),"+f"(d[1]),"+f"(d[2]),"+f"(d[3]),"+f"(d[4]),"+f"(d[5]),"+f"(d[6]),"+f"(d[7]),
        "+f"(d[8]),"+f"(d[9]),"+f"(d[10]),"+f"(d[11]),"+f"(d[12]),"+f"(d[13]),"+f"(d[14]),"+f"(d[15]),
        "+f"(d[16]),"+f"(d[17]),"+f"(d[18]),"+f"(d[19]),"+f"(d[20]),"+f"(d[21]),"+f"(d[22]),"+f"(d[23]),
        "+f"(d[24]),"+f"(d[25]),"+f"(d[26]),"+f"(d[27]),"+f"(d[28]),"+f"(d[29]),"+f"(d[30]),"+f"(d[31]),
        "+f"(d[32]),"+f"(d[33]),"+f"(d[34]),"+f"(d[35]),"+f"(d[36]),"+f"(d[37]),"+f"(d[38]),"+f"(d[39]),
        "+f"(d[40]),"+f"(d[41]),"+f"(d[42]),"+f"(d[43]),"+f"(d[44]),"+f"(d[45]),"+f"(d[46]),"+f"(d[47]),
        "+f"(d[48]),"+f"(d[49]),"+f"(d[50]),"+f"(d[51]),"+f"(d[52]),"+f"(d[53]),"+f"(d[54]),"+f"(d[55]),
        "+f"(d[56]),"+f"(d[57]),"+f"(d[58]),"+f"(d[59]),"+f"(d[60]),"+f"(d[61]),"+f"(d[62]),"+f"(d[63])
      : "r"(a0), "r"(a1), "r"(a2), "r"(a3), "l"(db), "n"(SD));
}

constexpr int C_LN = 0, C_PX = 16, C_PY = 32;
constexpr int NB_CONS = 1, NB_LN = 2, NB_LAG = 4, NB_INIT = 6, NB_RDY = 7, NB_WG = 8;
#define LAGX 3
#define LAGY 3
#define LAG2 5
constexpr int NLL = 2;
#define POLL_DELAY3 600
#define POLL_DELAY 1200
#define FILT_DELAY 600
#define WARM 4
#define ALEAD 6
#define POLL_DELAY2 1200
#define HPOS 14
#define REDPOS 1
#define XTRIG 21
#define HTRIG 0
#define RING_SIG 1
#define PF2_SIG 1
constexpr int SM_E = 0, SM_X = 16384, SM_E2 = 32768, SM_W = 49152, SM_FC = 69632, SM_T = 73728 - T1_BYTES;
constexpr unsigned long long KORDER = 0xBA9432DC876510ull;
constexpr unsigned long long BSLOT = 0x76532107653210ull, PSLOT = 0xDCBA984DCBA984ull;
constexpr uint32_t HI128 = desc_hi(1024, 1), HI64 = desc_hi(512, 2);

struct Bars {
  uint64_t full1[32], empty1[32], full2[16], fullA[8], empty2[8], fullP[16], emptyP[8], hbar, tbar, hint[3], sig[2], sbar;
  uint32_t epoch, pad;
};

template <int NK, bool STORE, int J0 = 0, int J1 = NK>
__device__ __forceinline__ void make_p(const float (&acc)[NK * 16], float r0, float r1, uint4 (&p)[NK], uint4* pbase, int ks0, uint32_t tag) {
#pragma unroll
  for (int j = J0; j < J1; j++) {
    uint32_t w[4];
#pragma unroll
    for (int i = 0; i < 4; i++) {
      const int a = 8 * j + 2 * i, b = a + NK * 8;
      w[i] = pack2(swiglu(acc[a], acc[b], (i & 1) ? r1 : r0), swiglu(acc[a + 1], acc[b + 1], (i & 1) ? r1 : r0));
    }
    asm volatile("" : "+r"(w[0]), "+r"(w[1]), "+r"(w[2]), "+r"(w[3]));
    p[j] = make_uint4(w[0], w[1], w[2], w[3]);
    if (STORE) st_tag(pbase + ((ks0 + j) >> 2) * 1024 + ((ks0 + j) & 3) * 32, p[j], tag);
  }
}
__device__ __forceinline__ void spin_until(uint32_t t) {
  while ((int)(clock32() - t) < 0) {}
}

__global__ void __cluster_dims__(2, 1, 1) __launch_bounds__(NTHREADS, 1)
fused_kernel(const __nv_bfloat16* __restrict__ x, const Tables* __restrict__ tab, Scratch* __restrict__ scr,
             __nv_bfloat16* __restrict__ out, const char* __restrict__ wg_raw, const char* __restrict__ wu_raw,
             const char* __restrict__ wd_raw,
             const __grid_constant__ CUtensorMap tmWR, const __grid_constant__ CUtensorMap tmWI,
             const __grid_constant__ CUtensorMap tmGX, const __grid_constant__ CUtensorMap tmUX,
             const __grid_constant__ CUtensorMap tmGY, const __grid_constant__ CUtensorMap tmUY,
             const __grid_constant__ CUtensorMap tmD) {
  extern __shared__ __align__(1024) char smem_raw[];
  const uint32_t sbase = s2u(smem_raw);
  const uint32_t sbar = sbase + 14 * SLOT, sstat = sbar + 1280;
  const int tid = threadIdx.x, lane = tid & 31;
  const int c = blockIdx.x, rk = c & 1, f = (c >> 1) & 7, rb = 2 * (c >> 4) + rk;
  const int rb2 = 2 * (c >> 4) + (f >> 2), kh = (f >> 1) & 1, nq = 2 * (f & 1) + rk;
#define BAR(field, i) (sbar + (uint32_t)offsetof(Bars, field) + 8u * (i))
#define TOFF(field) (sbase + SM_T + (uint32_t)offsetof(Tables, field) + lane * 16)

  if (tid >= 256) {
    asm volatile("setmaxnreg.dec.sync.aligned.u32 56;");
    const int warp = __shfl_sync(0xffffffffu, tid >> 5, 0);
    if (lane == 0) {
      if (warp == 8) {
        if (sbase & 1023) die();
#pragma unroll
        for (int i = 0; i < 16; i++) mbar_init(BAR(emptyP, i), i < 7 ? 16 : i < 8 ? 8 : i < 13 ? 1 : i < 15 ? 8 : 32);
        mbar_expect(BAR(tbar, 0), T2_BYTES + 2 * 10240);
        mbar_expect(BAR(hbar, 0), 16384);
      } else if (warp == 9) {
#pragma unroll
        for (int i = 0; i < 32; i++) mbar_init(BAR(full1, i), 1);
#pragma unroll
        for (int i = 0; i < 32; i++) mbar_expect(BAR(full1, i), i < 16 ? 16384 : 12288);
      } else if (warp == 10) {
#pragma unroll
        for (int i = 0; i < 32; i++) mbar_init(BAR(empty1, i), 16);
#pragma unroll
        for (int i = 0; i < 14; i++) mbar_init(BAR(fullP, i), 1);
#pragma unroll
        for (int i = 0; i < 14; i++) mbar_expect(BAR(fullP, i), 16384);
      } else {
#pragma unroll
        for (int i = 0; i < 32; i++) mbar_init(BAR(full2, i), i < 24 ? 1 : 8);
#pragma unroll
        for (int i = 0; i < 24; i++) mbar_expect(BAR(full2, i), 16384);
      }
      asm volatile("fence.mbarrier_init.release.cluster;" ::: "memory");
    }
    if (tid == 256) {
      const int w0 = ((c >> 3) * 257 + 32 * (c & 7) + 1) & ~7;
      if (FILT_DELAY) {
        asm volatile("prefetch.tensormap [%0];" ::"l"(&tmWR) : "memory");
        asm volatile("prefetch.tensormap [%0];" ::"l"(&tmWI) : "memory");
        spin_until(clock32() + FILT_DELAY);
      }
      tma3(sbase + SM_W, &tmWR, BAR(tbar, 0), w0, 0, 0);
      tma3(sbase + SM_W + 10240, &tmWI, BAR(tbar, 0), w0, 0, 0);
      bulk_load(sbase + SM_T + T1_BYTES, reinterpret_cast<const char*>(tab) + T1_BYTES, T2_BYTES, BAR(tbar, 0));
    }
    if (tid == 288) {
      asm volatile("prefetch.tensormap [%0];" ::"l"(rk ? &tmUX : &tmGX) : "memory");
      asm volatile("prefetch.tensormap [%0];" ::"l"(rk ? &tmUY : &tmGY) : "memory");
      asm volatile("prefetch.tensormap [%0];" ::"l"(&tmD) : "memory");
    }
    if (tid == 320) {
      const unsigned e = ld_relaxed(&scr->cnt[(C_LN + rb) * 32]) >> 3;
      asm volatile("st.shared.u32 [%0], %1;" ::"r"(BAR(epoch, 0)), "r"(e) : "memory");
    }
    __syncwarp();
    asm volatile("barrier.cluster.arrive.relaxed.aligned;" ::: "memory");
    bar_arrive(NB_RDY, 384);
    asm volatile("barrier.cluster.wait.aligned;" ::: "memory");
    bar_sync(NB_INIT, 384);
    unsigned epoch;
    asm volatile("ld.shared.u32 %0, [%1];" : "=r"(epoch) : "r"(BAR(epoch, 0)) : "memory");
    if (warp == 8) {
      if (lane == 0) {
        const int ax = (7 * f + 3 * (f & 1)) >> 1;
        const int ay = 7 * f + ((f & 1) ? 0 : 4);
        const CUtensorMap* tx = rk ? &tmUX : &tmGX;
        const CUtensorMap* ty = rk ? &tmUY : &tmGY;
        if (RING_SIG >= 0) mbar_wait(BAR(sig, RING_SIG));
        uint32_t s = 2;
#pragma unroll 1
        for (int n = 0; n < 16; n++) {
          if (n >= 6) mbar_wait(BAR(empty1, n - 6));
          tma3_mc(sbase + (8 + s) * SLOT + rk * 8192, tx, BAR(full1, n), n * 32, ax);
          if (++s == 6) s = 0;
        }
#pragma unroll 1
        for (int k = 0; k < 16; k++) {
          mbar_wait(BAR(empty1, k < 8 ? 10 + ((12 * k + 11) >> 4) : 8 + k));
          tma3_mc(sbase + 8 * SLOT + (k & 7) * 12288 + rk * 6144, ty, BAR(full1, 16 + k), k * 32, ay);
        }
      }
    } else if (warp == 9) {
      if (lane == 0) {
        mbar_wait(BAR(fullA, 4));
        wait_counter(&scr->cnt[(C_LN + rb2) * 32], (epoch + 1) * 8);
        asm volatile("fence.proxy.async.global;" ::: "memory");
#pragma unroll 1
        for (int i = 0; i < 15; i++) {
          const int kblk = 14 * kh + (int)((KORDER >> (4 * i)) & 15);
          const int j = i < 7 ? i : i - 7, sl = j + (j >= 4);
          if (i == HPOS) {
            mbar_wait(BAR(emptyP, 7));
            bulk_load(sbase + 4 * SLOT, &scr->LN[(rb2 * 8 + 2 * nq) * 1024 + kh * 512], 8192, BAR(hbar, 0));
            bulk_load(sbase + 4 * SLOT + 8192, &scr->LN[(rb2 * 8 + 2 * nq + 1) * 1024 + kh * 512], 8192, BAR(hbar, 0));
          }
          if (i == 14) break;
          mbar_wait(i < 7 ? BAR(empty1, 17 + 2 * sl) : BAR(empty2, j));
          tma3(sbase + sl * SLOT, &tmD, BAR(full2, i), 0, 64 * kblk, 2 * nq);
        }
      }
    } else if (warp == 10) {
      bar_sync(NB_LN, 288);
      if (lane == 0) {
        PROFP(0);
        red_release(&scr->cnt[(C_LN + rb) * 32]);
        PROFP(1);
        wait_counter(&scr->cnt[(C_LN + rb) * 32], (epoch + 1) * 8);
        asm volatile("fence.proxy.async.global;" ::: "memory");
        PROFP(2);
#pragma unroll 1
        for (int kb = NLL; kb < 8; kb++) {
          if (2 * kb >= ALEAD) mbar_wait(BAR(empty1, 2 * kb - ALEAD));
          bulk_load(sbase + kb * SLOT, &scr->LN[(rb * 8 + kb) * 1024], 16384, BAR(fullA, kb));
        }
#pragma unroll 1
        for (int s = 0; s < 14; s++) {
          const int kblk = 14 * kh + (int)((KORDER >> (4 * s)) & 15);
          if (s == 0 || s == 8 || s == 11) {
            if (s != 11) PROFP(3 + (s >> 2));
            mbar_wait(BAR(hint, s == 0 ? 0 : s == 8 ? 1 : 2), 0);
            if (s != 11) PROFP(4 + (s >> 2));
          }
          const int j = s < 7 ? s : s - 7;
          mbar_wait(s < 7 ? BAR(empty1, 24 + s + (s == 0) + (s >= 4)) : BAR(emptyP, j));
          bulk_load_mc(sbase + (j ? 7 + j : 4) * SLOT + rk * 8192, &scr->P[(rb2 * 28 + kblk) * 1024 + rk * 512], 8192, BAR(fullP, s));
        }
        PROFP(7);
      }
    } else {
      if (lane == 0) {
        mbar_wait(BAR(tbar, 0));
        l2_prefetch(wg_raw + (size_t)c * 5376, 5376);
        l2_prefetch(wu_raw + (size_t)c * 5376, 5376);
        mbar_wait(BAR(sig, PF2_SIG), 0);
        l2_prefetch(wg_raw + 688128 + (size_t)c * 8960, 8960);
        l2_prefetch(wu_raw + 688128 + (size_t)c * 8960, 8960);
      }
      mbar_wait(BAR(fullA, 4), 0);
      if (lane == 0) l2_prefetch(wd_raw + (size_t)c * 14336, 14336);
      {
        const uint32_t tag = (epoch + 1) & 1;
        uint4 v0, v1, v2;
        int it = 0;
        while (true) {
          v0 = ld_b128(&scr->ST[rb * 64 + lane]);
          v1 = ld_b128(&scr->ST[rb * 64 + 32 + lane]);
          v2 = ld_b128(&scr->ST[rb2 * 64 + 32 * kh + lane]);
          if (!__any_sync(0xffffffffu, ((v0.x ^ tag) | (v1.x ^ tag) | (v2.x ^ tag)) & 1u)) break;
          if (++it > SPIN_LIMIT) { die(); break; }
        }
        sts4(sstat + lane * 16, v0.x & ~1u, v0.y, v0.z, v0.w);
        sts4(sstat + 512 + lane * 16, v1.x & ~1u, v1.y, v1.z, v1.w);
        sts4(sstat + 1024 + lane * 16, v2.x & ~1u, v2.y, v2.z, v2.w);
        mbar_arrive(BAR(sbar, 0));
      }
      if (lane == 0) {
        mbar_wait(BAR(empty1, XTRIG));
        int it = 0;
        while ((int)(ld_relaxed(&scr->cnt[(C_PX + rb2) * 32 + kh]) - (epoch + 1) * 32) < 0) {
          if (++it > SPIN_LIMIT) { die(); break; }
        }
        mbar_arrive(BAR(hint, 0));
        mbar_wait(BAR(emptyP, HTRIG));
        uint32_t done = 0;
        while (done != 3) {
          uint2 v;
          asm volatile("ld.relaxed.gpu.global.v2.u32 {%0,%1}, [%2];" : "=r"(v.x), "=r"(v.y) : "l"(&scr->cnt[(C_PY + rb2) * 32 + 2 * kh]) : "memory");
          if (!(done & 1) && (int)(v.x - (epoch + 1) * 16) >= 0) { done |= 1; mbar_arrive(BAR(hint, 1)); }
          if (!(done & 2) && (int)(v.y - (epoch + 1) * 16) >= 0) { done |= 2; mbar_arrive(BAR(hint, 2)); }
          if (++it > SPIN_LIMIT) { die(); break; }
        }
      }
    }
  } else {
    const int warp = __shfl_sync(0xffffffffu, tid >> 5, 0);
    const int g = lane >> 2, t = lane & 3;
    PROF(0);
    PROFG(14);
    uint4 fa[4], fb[4], tw[6];
#pragma unroll
    for (int i = 0; i < 4; i++) fa[i] = ldg_ca4(&tab->fa[i][lane][0]);
#pragma unroll
    for (int i = 0; i < 6; i++) tw[i] = ldg_ca4(&tab->tw1[i][lane][0]);
#pragma unroll
    for (int i = 0; i < 4; i++) fb[i] = ldg_ca4(&tab->fb[i][lane][0]);
#pragma unroll
    for (int i = 0; i < 4; i++) {
      const int r = i >> 1, ch = (i & 1) * 32 + lane;
      cp_async16(sbase + SM_X + (2 * warp + r) * 1024 + ((ch ^ ((ch >> 3) & 1)) * 16),
                 x + (size_t)(c + 128 * (2 * warp + r)) * 512 + ch * 8);
    }
    asm volatile("cp.async.commit_group;" ::: "memory");
    asm volatile("barrier.cluster.arrive.relaxed.aligned;" ::: "memory");
    uint32_t rbar;
    asm volatile("mapa.shared::cluster.u32 %0, %1, %2;" : "=r"(rbar) : "r"(sbar), "r"(rk ^ 1));
#define RBAR(field, i) (rbar + (uint32_t)offsetof(Bars, field) + 8u * (i))
    {
      const int ln = (tid >> 1) & 31, lg = ln >> 2, lt = ln & 3, i = 4 * (tid >> 6) + 2 * (tid & 1);
      const int kidx = lt + 8 * (i >> 3), nidx = 4 * ((i >> 1) & 3) + (lg >> 1);
      const uint32_t a0 = cfrag<2048>((c + 128 * kidx) * nidx, lg & 1), a1 = cfrag<2048>((c + 128 * (kidx + 4)) * nidx, lg & 1);
      const uint32_t b0 = cfrag<2048>(-(c + 128 * nidx) * kidx, lg & 1), b1 = cfrag<2048>(-(c + 128 * nidx) * (kidx + 4), lg & 1);
      asm volatile("st.shared.v2.u32 [%0], {%1,%2};" ::"r"(sbase + SM_FC + tid * 8), "r"(a0), "r"(a1) : "memory");
      asm volatile("st.shared.v2.u32 [%0], {%1,%2};" ::"r"(sbase + SM_FC + 2048 + tid * 8), "r"(b0), "r"(b1) : "memory");
    }
    bar_sync(NB_CONS, 256);
    uint4 fc[4];
#pragma unroll
    for (int i = 0; i < 4; i++) fc[i] = lds4(sbase + SM_FC + i * 512 + lane * 16);
    asm volatile("cp.async.wait_group 0;" ::: "memory");
    __syncwarp();
    bar_arrive(NB_INIT, 384);
    PROF(13);
    uint32_t tag, ones;
    uint4 q[4], o[4];
    {
      uint32_t v[2][8];
#pragma unroll
      for (int r = 0; r < 2; r++)
#pragma unroll
        for (int ks = 0; ks < 2; ks++) {
          const int ch = 32 * ks + 2 * (lane & 15) + (lane >> 4);
          asm volatile("ldmatrix.sync.aligned.m8n8.x4.trans.shared.b16 {%0,%1,%2,%3}, [%4];"
                       : "=r"(v[r][4 * ks]), "=r"(v[r][4 * ks + 1]), "=r"(v[r][4 * ks + 2]), "=r"(v[r][4 * ks + 3])
                       : "r"(sbase + SM_X + (2 * warp + r) * 1024 + ((ch ^ ((ch >> 3) & 1)) * 16)) : "memory");
        }
      float sq[2];
#pragma unroll
      for (int r = 0; r < 2; r++) {
        float s0 = 0.f, s1 = 0.f;
#pragma unroll
        for (int i = 0; i < 8; i++) {
          const float lo = bf_lo(v[r][i]), hi = u2f(v[r][i] & 0xffff0000u);
          s0 = fmaf(lo, lo, s0);
          s1 = fmaf(hi, hi, s1);
        }
        sq[r] = s0 + s1;
      }
      {
        float w = ((lane & 1) ? sq[1] : sq[0]) + __shfl_xor_sync(0xffffffffu, (lane & 1) ? sq[0] : sq[1], 1);
        w += __shfl_xor_sync(0xffffffffu, w, 2);
        w = sum_groups(w);
        const float o2 = __shfl_xor_sync(0xffffffffu, w, 1);
        sq[0] = (lane & 1) ? o2 : w;
        sq[1] = (lane & 1) ? w : o2;
      }
#pragma unroll
      for (int r = 0; r < 2; r++) {
        float dd[2][4], ee[2][4];
#pragma unroll
        for (int nt = 0; nt < 2; nt++) {
          mma_az(dd[nt], fa[0], v[r][2 * nt], v[r][2 * nt + 1]);
          mma_a(dd[nt], fa[1], v[r][4 + 2 * nt], v[r][5 + 2 * nt]);
          mma_az(ee[nt], fa[2], v[r][2 * nt], v[r][2 * nt + 1]);
          mma_a(ee[nt], fa[3], v[r][4 + 2 * nt], v[r][5 + 2 * nt]);
        }
        float mean = (dd[0][0] + dd[0][1]) + (dd[1][0] + dd[1][1]);
        mean += __shfl_xor_sync(0xffffffffu, mean, 1);
        mean += __shfl_xor_sync(0xffffffffu, mean, 2);
        mean = __shfl_sync(0xffffffffu, mean, 0) * (1.f / 512.f);
        const float rs = rsqrtf(fmaxf(fmaf(-mean, mean, sq[r] * (1.f / 512.f)), 0.f) + 1e-5f);
        float acc[4][4];
#pragma unroll
        for (int nt = 0; nt < 2; nt++) {
          const float (&d)[4] = dd[nt];
          const float (&e)[4] = ee[nt];
          const uint4 &ka = tw[2 * nt], &kb = tw[2 * nt + 1], &kc = tw[4 + nt];
          const uint32_t a0 = pack2(d[0] * u2f(ka.x) + d[2] * u2f(ka.y), d[1] * u2f(kb.x) + d[3] * u2f(kb.y));
          const uint32_t a2 = pack2(d[0] * u2f(ka.z) + d[2] * u2f(ka.w), d[1] * u2f(kb.z) + d[3] * u2f(kb.w));
          const uint32_t a1 = pack2(e[0] * u2f(kc.x) + e[2] * u2f(kc.y), e[1] * u2f(kc.z) + e[3] * u2f(kc.w));
          const uint32_t a3 = pack2(e[2] * u2f(kc.x) - e[0] * u2f(kc.y), e[3] * u2f(kc.z) - e[1] * u2f(kc.w));
          const uint32_t dc = pack2(fmaf(mean, -32.f, d[0]), fmaf(mean, -32.f, d[1]));
          const uint32_t h0 = g == 0 ? dc : a0, h2 = g == 0 ? 0u : a2;
          if (nt == 0) {
            mma16816_z(acc[0], a0, a1, a2, a3, fb[2 * nt].x, fb[2 * nt].y);
            mma16816_z(acc[1], a0, a1, a2, a3, fb[2 * nt].z, fb[2 * nt].w);
            mma16816_z(acc[2], h0, a1, h2, a3, fb[2 * nt + 1].x, fb[2 * nt + 1].y);
            mma16816_z(acc[3], h0, a1, h2, a3, fb[2 * nt + 1].z, fb[2 * nt + 1].w);
          } else {
            mma16816(acc[0], a0, a1, a2, a3, fb[2 * nt].x, fb[2 * nt].y);
            mma16816(acc[1], a0, a1, a2, a3, fb[2 * nt].z, fb[2 * nt].w);
            mma16816(acc[2], h0, a1, h2, a3, fb[2 * nt + 1].x, fb[2 * nt + 1].y);
            mma16816(acc[3], h0, a1, h2, a3, fb[2 * nt + 1].z, fb[2 * nt + 1].w);
          }
        }
#pragma unroll
        for (int h = 0; h < 2; h++) {
          const int j = 2 * warp + r, m = 2 * t + h;
          sts4(sbase + SM_E + ((j * 8 + m) * 8 + (g ^ (2 * t) ^ (2 * (j & 3)))) * 16,
               pack2(acc[h][0] * rs, acc[h][1] * rs), pack2(acc[h][2] * rs, acc[h][3] * rs),
               pack2(acc[2 + h][0] * rs, acc[2 + h][1] * rs), pack2(acc[2 + h][2] * rs, acc[2 + h][3] * rs));
        }
      }
      if (tid == 0) PROFP(12);
      bar_sync(NB_RDY, 384);
      if (tid == 0) PROFP(13);
      const uint32_t ea = sbase + SM_E + ((t * 8 + warp) * 8 + (g ^ (warp & 6) ^ (2 * t))) * 16;
      lds_frag(q[0], q[1], ea, ea + 4096);
      lds_frag(q[2], q[3], ea + 8192, ea + 12288);
      asm volatile("ld.shared.u32 %0, [%1];" : "=r"(tag) : "r"(BAR(epoch, 0)) : "memory");
      ones = ~(tag >> 31);
      tag = (tag + 1) & 1;
      cdft16(q, fc, o);
#pragma unroll
      for (int vv = 0; vv < 4; vv++) {
        o[vv].y &= ~1u;
        o[vv].z = (o[vv].z & ~1u) | (tag ^ 1);
        st_tag(&scr->Z1[(((4 * vv + t) * 8 + warp) * 128 + c) * 8 + g], o[vv], tag);
      }
    }
    PROF(1);
    asm volatile("setmaxnreg.inc.sync.aligned.u32 224;");
    {
      uint4* const zp = &scr->Z1[(c * 128 + 8 * t + warp) * 8 + g];
      const uint32_t tst = clock32();
      mbar_wait(BAR(tbar, 0), 0);
      if (tid == 0) PROFP(14);
      uint4 f2[4], g2[4];
#pragma unroll
      for (int i = 0; i < 4; i++) {
        f2[i] = lds4(TOFF(f2) + warp * 2048 + i * 512);
        g2[i] = lds4(TOFF(g2) + warp * 2048 + i * 512);
      }
      const uint4 f8 = lds4(TOFF(f8)), g8 = lds4(TOFF(g8));
      float wfr[16], wfi[16];
      {
        const float nyq = ((c & 7) == 7 && g == 0) ? 0.5f : 1.f;
        const int gg = g == 0 ? 16 : g, wsh = (2 * (c >> 3) + 2) & 15;
#pragma unroll
        for (int i = 0; i < 16; i++) {
          const int ci = i >> 3, dd = (i >> 2) & 1, e = i & 3;
          const int kk = (e == 0 ? gg : e == 1 ? g + 8 : e == 2 ? 32 - g : 24 - g) - 1;
          const uint32_t a = sbase + SM_W + ((2 * warp + ci) * 8 + t + 4 * dd) * 80 + wsh + 2 * kk;
          wfr[i] = bf_lo(lds_u16(a)) * (e == 2 ? nyq : 1.f);
          wfi[i] = bf_lo(lds_u16(a + 10240)) * (e == 2 ? nyq : 1.f);
        }
      }
      asm volatile("barrier.cluster.wait.aligned;" ::: "memory");
      PROF(2);
      spin_until(tst + POLL_DELAY);
      ld_tag4_issue<256>(q, zp);
      ld_tag4_finish<256>(q, zp, tag);
      if (tid == 0) PROFP(30);
      if (lane == 0) mbar_arrive(BAR(sig, 0));
#pragma unroll
      for (int i = 0; i < 4; i++) q[i].z &= ~1u;
      reg_frag(q, ones);
      cdft16(q, f2, o);
      const uint32_t e2 = sbase + SM_E2;
#pragma unroll
      for (int vv = 0; vv < 4; vv++)
        sts4(e2 + ((warp * 16 + 4 * vv + t) * 8 + (g ^ (2 * t) ^ (2 * (warp & 3)))) * 16, o[vv].x, o[vv].y, o[vv].z, o[vv].w);
      bar_sync(NB_CONS, 256);
      uint32_t ad[2], res[2][2][4];
#pragma unroll
      for (int ci = 0; ci < 2; ci++) {
        const int cc = 2 * warp + ci;
        ad[ci] = e2 + ((t * 16 + cc) * 8 + (g ^ (2 * (cc & 3)) ^ (2 * t))) * 16;
        lds_frag(q[2 * ci], q[2 * ci + 1], ad[ci], ad[ci] + 8192);
      }
#pragma unroll
      for (int ci = 0; ci < 2; ci++)
#pragma unroll
        for (int p = 0; p < 2; p++) {
          uint32_t y[2][2];
#pragma unroll
          for (int vv = 0; vv < 2; vv++) {
            float d[4];
            mma_az(d, q[2 * ci + p], word(f8, 2 * vv), word(f8, 2 * vv + 1));
#pragma unroll
            for (int rr = 0; rr < 2; rr++) {
              const float fr = wfr[ci * 8 + vv * 4 + 2 * p + rr], fi = wfi[ci * 8 + vv * 4 + 2 * p + rr];
              y[vv][rr] = pack2(d[2 * rr] * fr - d[2 * rr + 1] * fi, d[2 * rr] * fi + d[2 * rr + 1] * fr);
            }
          }
#pragma unroll
          for (int vv = 0; vv < 2; vv++) {
            float d[4];
            mma16816_z(d, y[0][0], y[0][1], y[1][0], y[1][1], word(g8, 2 * vv), word(g8, 2 * vv + 1));
            res[ci][vv][2 * p] = pack2(d[0], d[1]);
            res[ci][vv][2 * p + 1] = pack2(d[2], d[3]);
          }
        }
#pragma unroll
      for (int i = 0; i < 4; i++)
        sts4(ad[i >> 1] + (i & 1) * 8192, res[i >> 1][i & 1][0], res[i >> 1][i & 1][1], res[i >> 1][i & 1][2], res[i >> 1][i & 1][3]);
      bar_sync(NB_CONS, 256);
      const uint32_t eb = e2 + ((warp * 16 + t) * 8 + (g ^ (2 * t) ^ (2 * (warp & 3)))) * 16;
      lds_frag(q[0], q[1], eb, eb + 512);
      lds_frag(q[2], q[3], eb + 1024, eb + 1536);
      cdft16(q, g2, o);
#pragma unroll
      for (int vv = 0; vv < 4; vv++) {
        o[vv].y &= ~1u;
        o[vv].z = (o[vv].z & ~1u) | tag;
        st_tag(zp + vv * 256, o[vv], tag);
      }
    }
    PROF(3);
    {
      const uint4* const zp = &scr->Z1[((t * 8 + warp) * 128 + c) * 8 + g];
      const uint32_t tst = clock32();
      uint4 gb[4], ga[4], gc[4], tw[4];
      uint2 xr[2][4];
      uint2* lnp[2];
#pragma unroll
      for (int r = 0; r < 2; r++) {
        const int row = 16 * f + 2 * warp + r;
        lnp[r] = reinterpret_cast<uint2*>(&scr->LN[(rb * 8 + (g >> 2)) * 1024 + row * 8 + ((2 * (g & 3) + (t >> 1)) ^ (row & 7))]) + (t & 1);
        asm volatile("" : "+l"(lnp[r]));
      }
#pragma unroll
      for (int i = 0; i < 4; i++) {
        gc[i] = lds4(sbase + SM_FC + 2048 + i * 512 + lane * 16);
        gb[i] = lds4(TOFF(gb) + i * 512);
        ga[i] = lds4(TOFF(ga) + i * 512);
        tw[i] = lds4(TOFF(tw3) + i * 512);
        const int ch = 2 * (g + 8 * i) + (t >> 1);
#pragma unroll
        for (int r = 0; r < 2; r++) xr[r][i] = lds2(sbase + SM_X + (2 * warp + r) * 1024 + ((ch ^ ((ch >> 3) & 1)) * 16) + (t & 1) * 8);
      }
      PROF(4);
      spin_until(tst + POLL_DELAY2);
      ld_tag4_issue<32768>(q, zp);
      ld_tag4_finish<32768, true>(q, zp, tag);
      if (tid == 0) PROFP(31);
      if (lane == 0) mbar_arrive(BAR(sig, 1));
      reg_frag(q, ones);
      cdft16(q, gc, o);
#pragma unroll
      for (int vv = 0; vv < 4; vv++)
        sts4(sbase + SM_E + (((4 * vv + t) * 8 + warp) * 8 + (g ^ (warp & 6) ^ (2 * t))) * 16, o[vv].x, o[vv].y, o[vv].z, o[vv].w);
      if (tid == 0) PROFP(8);
      bar_sync(NB_CONS, 256);
      if (tid == 0) PROFP(9);
      uint32_t hv[2][8];
      const float mk = t == 0 ? 0.f : 1.f;
#pragma unroll
      for (int r = 0; r < 2; r++) {
        const int j = 2 * warp + r;
        uint4 u[2];
#pragma unroll
        for (int h = 0; h < 2; h++) u[h] = lds4(sbase + SM_E + ((j * 8 + 2 * t + h) * 8 + (g ^ (2 * t) ^ (2 * (j & 3)))) * 16);
        const uint32_t bp[4][2] = {{u[0].x, u[1].x & ones}, {u[0].y & ones, u[1].y}, {u[0].z, u[1].z & ones}, {u[0].w & ones, u[1].w}};
        float y[2][2][4];
#pragma unroll
        for (int i = 0; i < 2; i++) {
          float lo[4], hi[4], e[4];
          mma_az(lo, gb[2 * i], bp[0][0], bp[0][1]);
          mma_az(hi, gb[2 * i + 1], bp[2][0], bp[2][1]);
          mma_az(e, gb[2 * i], bp[1][0], bp[1][1]);
          mma_a(e, gb[2 * i + 1], bp[3][0], bp[3][1]);
          const uint4 &ka = tw[2 * i], &kb = tw[2 * i + 1];
          const float tr0 = fmaf(hi[0], mk, lo[0]), ti0 = fmaf(hi[2], mk, lo[2]);
          const float tr1 = lo[1] + hi[1], ti1 = lo[3] + hi[3];
          const float vr0 = tr0 * u2f(ka.x) - ti0 * u2f(ka.y), vi0 = tr0 * u2f(ka.y) + ti0 * u2f(ka.x);
          const float vr1 = tr1 * u2f(ka.z) - ti1 * u2f(ka.w), vi1 = tr1 * u2f(ka.w) + ti1 * u2f(ka.z);
          const uint32_t b0 = pack2(t == 0 ? hi[0] : vr0, vr1), b1 = pack2(t == 0 ? vr0 : vi0, vi1);
          const uint32_t b2 = pack2(e[0] * u2f(kb.x) - e[2] * u2f(kb.y), e[1] * u2f(kb.z) - e[3] * u2f(kb.w));
          const uint32_t b3 = pack2(e[0] * u2f(kb.y) + e[2] * u2f(kb.x), e[1] * u2f(kb.w) + e[3] * u2f(kb.z));
#pragma unroll
          for (int mt = 0; mt < 2; mt++) {
            mma_az(y[mt][i], ga[2 * mt], b0, b1);
            mma_a(y[mt][i], ga[2 * mt + 1], b2, b3);
          }
        }
#pragma unroll
        for (int i = 0; i < 4; i++) {
          hv[r][2 * i] = hadd2_bf16(xr[r][i].x, pack2(y[i >> 1][0][2 * (i & 1)], y[i >> 1][0][2 * (i & 1) + 1]));
          hv[r][2 * i + 1] = hadd2_bf16(xr[r][i].y, pack2(y[i >> 1][1][2 * (i & 1)], y[i >> 1][1][2 * (i & 1) + 1]));
        }
      }
      if (tid == 0 && hv[0][0] != 0x12345 && hv[1][7] != 0x12345) PROFP(10);
      float mean[2];
      uint32_t mb[2];
#pragma unroll
      for (int r = 0; r < 2; r++) {
        mean[r] = sum_groups(quad_sum(hv[r])) * (1.f / 512.f);
        mb[r] = pack2(mean[r], mean[r]);
      }
#pragma unroll
      for (int i = 0; i < 4; i++)
#pragma unroll
        for (int r = 0; r < 2; r++) {
          hv[r][2 * i] = hsub2_bf16(hv[r][2 * i], mb[r]);
          hv[r][2 * i + 1] = hsub2_bf16(hv[r][2 * i + 1], mb[r]);
          st_tag8(lnp[r] + i * 4096, hv[r][2 * i], hv[r][2 * i + 1], i == 0 ? tag : (hv[r][2 * i] & 1u));
        }
      if (tid == 0) PROFP(11);
      bar_arrive(NB_LN, 288);
      const uint32_t ones2 = ~(lds2(BAR(epoch, 0)).x >> 31);
      float rstd[2];
#pragma unroll
      for (int r = 0; r < 2; r++) {
        hv[r][0] &= ones2;
        rstd[r] = row_rstd(hv[r], mean[r] - bf_lo(mb[r]));
      }
      if (lane == 0)
        st_tag(&scr->ST[rb * 64 + 8 * f + warp], make_uint4(mb[0] << 16, __float_as_uint(rstd[0]), mb[1] << 16, __float_as_uint(rstd[1])), tag);
    }
    PROF(5);
    const int wgi = warp >> 2, wq = warp & 3;
    uint4* const pbase = &scr->P[rb * 28 * 1024 + warp * 128 + lane];
    const uint32_t a_lo0 = desc_lo(sbase + wgi * 8192, 16);
    const uint32_t ebar = lane == 0 ? BAR(empty1, 0) : RBAR(empty1, 0);
    float r0, r1;
    uint4 px[8], py[6];
    const int rh = wgi ^ kh ^ 1;
    const uint4* const psrc = &scr->P[(rb2 * 28 + 14 * kh) * 1024 + (4 * rh + wq) * 128 + lane];
    const uint32_t pa0 = sbase + (4 * rh + wq) * 2048;
    uint4 pf[3][4];
    uint32_t rdy = 0;
    {
      float acc[128];
#pragma unroll
      for (int i = 0; i < 128; i++) acc[i] = 0.f;
      const uint32_t b_lo0 = desc_lo(sbase + 8 * SLOT, 4096);
      const uint32_t t3 = clock32();
      if (WARM) {
        wg_fence();
#pragma unroll
        for (int i = 0; i < WARM; i++) wgmma_n256(acc, desc64(a_lo0 + 6 * 1024, HI128), desc64(b_lo0, HI128));
        wg_commit();
      }
      const uint4* const ap = &scr->LN[rb * 8 * 1024 + wgi * 512 + (tid & 127)];
      uint4 av[NLL][4];
      spin_until(t3 + POLL_DELAY3);
#pragma unroll
      for (int kb = 0; kb < NLL; kb++) ld_tag4_issue<128>(av[kb], ap + kb * 1024);
      bar_sync(NB_CONS, 256);
      uint32_t slot = 2;
      auto stage_x = [&](int kb, int hh) {
        if (LAGX && hh == ((16 - LAGX) & 1) && kb == ((16 - LAGX) >> 1) && wgi == 1) bar_sync(NB_LAG, 256);
        mbar_wait(BAR(full1, 2 * kb + hh));
        const uint32_t al = a_lo0 + kb * 1024 + hh * 4, bl = b_lo0 + slot * 1024;
        wg_fence();
        wgmma_n256(acc, desc64(al, HI128), desc64(bl, HI128), (kb | hh) != 0 ? 1 : ~ones);
        wgmma_n256(acc, desc64(al + 2, HI128), desc64(bl + 128, HI128));
        wg_commit();
        if (LAGX && hh == 1 && kb == 7 && wgi == 0) bar_arrive(NB_LAG, 256);
        wg_wait<1>();
        if ((kb | hh) != 0 && lane < 2) mbar_arrive_remote(ebar + 8 * (2 * kb + hh - 1));
        if (++slot == 6) slot = 0;
      };
#pragma unroll
      for (int kb = 0; kb < NLL; kb++) {
        ld_tag4_finish<128, true>(av[kb], ap + kb * 1024, tag);
#pragma unroll
        for (int i = 0; i < 4; i++)
          sts4(sbase + kb * SLOT + wgi * 8192 + ((tid & 127) + 128 * i) * 16, av[kb][i].x, av[kb][i].y, av[kb][i].z, av[kb][i].w);
        asm volatile("fence.proxy.async.shared::cta;" ::: "memory");
        bar_sync(NB_WG + wgi, 128);
        if (kb > 0) stage_x(kb - 1, 1);
        if (kb == 0) PROF(6);
        stage_x(kb, 0);
      }
      stage_x(NLL - 1, 1);
#pragma unroll 1
      for (int kb = NLL; kb < 8; kb++) {
        mbar_wait(BAR(fullA, kb));
        stage_x(kb, 0);
        stage_x(kb, 1);
      }
      mbar_wait(BAR(sbar, 0), 0);
      r0 = __uint_as_float(lds2(sstat + (16 * warp + g) * 8).y);
      r1 = __uint_as_float(lds2(sstat + (16 * warp + g + 8) * 8).y);
      wg_wait<0>();
      if (lane < 2) mbar_arrive_remote(ebar + 8 * 15);
      PROF(7);
      make_p<8, false>(acc, r0, r1, px, pbase, 0, tag);
    }
    PROF(8);
    {
      float acc[96];
#pragma unroll
      for (int i = 0; i < 96; i++) acc[i] = 0.f;
      const uint32_t b_lo0 = desc_lo(sbase + 8 * SLOT, 2048);
      uint4* const pdst = pbase + ((7 * f + 3 * (f & 1)) >> 1) * 1024;
      auto stage_y = [&](int k) {
        if (LAGY && k == 16 - LAGY && wgi == 1) bar_sync(NB_LAG, 256);
        mbar_wait(BAR(full1, 16 + k));
        const uint32_t al = a_lo0 + (k >> 1) * 1024 + (k & 1) * 4, bl = b_lo0 + (k & 7) * 768;
        wg_fence();
        wgmma_n192(acc, desc64(al, HI128), desc64(bl, HI64));
        wgmma_n192(acc, desc64(al + 2, HI128), desc64(bl + 64, HI64));
        wg_commit();
      };
#pragma unroll
      for (int k = 0; k < 4; k++) {
        stage_y(k);
        st_tag(pdst + (k >> 1) * 1024 + (k & 1) * 64, px[2 * k], tag);
        st_tag(pdst + (k >> 1) * 1024 + (k & 1) * 64 + 32, px[2 * k + 1], tag);
        if (k == 3 && lane == 0) red_relaxed(&scr->cnt[(C_PX + rb) * 32 + (f >> 2)]);
        wg_wait<1>();
        if (k != 0 && lane < 2) mbar_arrive_remote(ebar + 8 * (15 + k));
      }
#pragma unroll 1
      for (int k = 4; k < 16; k++) {
        stage_y(k);
        if (LAGY && k == 15 && wgi == 0) bar_arrive(NB_LAG, 256);
        wg_wait<1>();
        if (lane < 2) mbar_arrive_remote(ebar + 8 * (15 + k));
      }
      rdy = __all_sync(0xffffffffu, mbar_test(BAR(fullP, 0)) & mbar_test(BAR(full2, 0)) & mbar_test(BAR(fullP, 1)));
      if (rdy) {
#pragma unroll
        for (int kk = 0; kk < 4; kk++) pf[0][kk] = lds4(pa0 + 4 * SLOT + kk * 512 + lane * 16);
      }
      wg_wait<0>();
      if (lane < 2) mbar_arrive_remote(ebar + 8 * 31);
      PROF(9);
      make_p<6, true, 0, REDPOS>(acc, r0, r1, py, pbase, 14 * f + ((f & 1) ? 0 : 8), tag);
      if (lane == 0) red_relaxed(&scr->cnt[(C_PY + rb) * 32 + (f >> 1)]);
      make_p<6, true, REDPOS, 6>(acc, r0, r1, py, pbase, 14 * f + ((f & 1) ? 0 : 8), tag);
    }
    PROF(10);
    {
      float acc[64];
      const uint32_t b2_lo0 = desc_lo(sbase, 8192);
      const uint32_t pbar = ebar + (uint32_t)(offsetof(Bars, emptyP) - offsetof(Bars, empty1));
      if (!rdy) {
        mbar_wait(BAR(fullP, 0));
#pragma unroll
        for (int kk = 0; kk < 4; kk++) pf[0][kk] = lds4(pa0 + 4 * SLOT + kk * 512 + lane * 16);
      }
#pragma unroll
      for (int s = 0; s < 14; s++) {
        uint4 (&a)[4] = pf[s % 3];
        ld_tag4_finish<32>(a, psrc + (int)((KORDER >> (4 * s)) & 15) * 1024, tag);
        if (s < 8 && lane < (s < 7 ? 2 : 1)) mbar_arrive_remote(pbar + 8 * s);
        if (s >= 2) {
          wg_wait<1>();
          if (s <= 8 && lane == 0) mbar_arrive(BAR(empty2, s - 2));
        }
        if (!rdy) {
          if (s < 13) mbar_wait(BAR(fullP, s + 1));
          mbar_wait(BAR(full2, s));
        }
        if (tid == 0) PROFP(16 + s);
        if (s == 14 - LAG2 && wgi == 1) {
          const float m0 = __uint_as_float(lds2(sstat + 1024 + (16 * wq + g) * 8).x);
          const float m1 = __uint_as_float(lds2(sstat + 1024 + (16 * wq + g + 8) * 8).x);
          const uint32_t hb = sbase + 4 * SLOT + (16 * wq + (lane & 15)) * 128;
          wg_wait<0>();
          mbar_wait(BAR(hbar, 0));
#pragma unroll
          for (int i = 0; i < 8; i++) {
            uint32_t h[4];
            asm volatile("ldmatrix.sync.aligned.m8n8.x4.shared.b16 {%0,%1,%2,%3}, [%4];"
                         : "=r"(h[0]), "=r"(h[1]), "=r"(h[2]), "=r"(h[3])
                         : "r"(hb + (i >> 2) * 8192 + (((2 * (i & 3) + (lane >> 4)) ^ (lane & 7)) * 16)) : "memory");
            const uint32_t mk = ((t & 1) == 0 && nq == 0) ? ~1u : ~0u;
#pragma unroll
            for (int e = 0; e < 4; e++) {
              acc[8 * i + 2 * e] += bf_lo(h[e] & mk) + ((e & 1) ? m1 : m0);
              acc[8 * i + 2 * e + 1] += __uint_as_float(h[e] & 0xffff0000u) + ((e & 1) ? m1 : m0);
            }
          }
          bar_sync(NB_LAG, 256);
        }
        const uint32_t bl = b2_lo0 + (uint32_t)((BSLOT >> (4 * s)) & 15) * 1024;
        wg_fence();
        if (s < 13) {
#pragma unroll
          for (int kk = 0; kk < 4; kk++)
            pf[(s + 1) % 3][kk] = lds4(pa0 + (uint32_t)((PSLOT >> (4 * (s + 1))) & 15) * SLOT + kk * 512 + lane * 16);
          rdy = mbar_test(BAR(full2, s + 1));
          if (s < 12) rdy &= mbar_test(BAR(fullP, s + 2));
        }
        if (s == 0) wgmma_rs_n128<0>(acc, a[0].x, a[0].y, a[0].z, a[0].w, desc64(bl, HI128));
        else wgmma_rs_n128<1>(acc, a[0].x, a[0].y, a[0].z, a[0].w, desc64(bl, HI128));
#pragma unroll
        for (int kk = 1; kk < 4; kk++) wgmma_rs_n128<1>(acc, a[kk].x, a[kk].y, a[kk].z, a[kk].w, desc64(bl + kk * 128, HI128));
        wg_commit();
      }
      if (wgi == 0) {
        bar_arrive(NB_LAG, 256);
        uint4* const dst = &scr->Z1[(tid >> 3) * 1024 + (c ^ 4) * 8 + (tid & 7)];
        wg_wait<0>();
        PROF(11);
#pragma unroll
        for (int i = 0; i < 8; i++)
          st_tag(dst + i * 16384, make_uint4(pack2(acc[8 * i], acc[8 * i + 1]), pack2(acc[8 * i + 2], acc[8 * i + 3]) | 1u,
                                           pack2(acc[8 * i + 4], acc[8 * i + 5]), pack2(acc[8 * i + 6], acc[8 * i + 7])), tag);
      } else {
        uint4 pv[2][4];
        const uint4* const xsrc = &scr->Z1[((tid & 127) >> 3) * 1024 + c * 8 + (tid & 7)];
        ld_tag4_issue<16384>(pv[0], xsrc);
        ld_tag4_issue<16384>(pv[1], xsrc + 65536);
        wg_wait<0>();
        PROF(11);
        uint32_t w[32];
#pragma unroll
        for (int i = 0; i < 32; i++) w[i] = pack2(acc[2 * i], acc[2 * i + 1]);
        int it = 0;
#pragma unroll 1
        while (!__all_sync(0xffffffffu, pv[0][0].y & pv[0][1].y & pv[0][2].y & pv[0][3].y & pv[1][0].y & pv[1][1].y & pv[1][2].y & pv[1][3].y & 1u)) {
          ld_tag4_issue<16384>(pv[0], xsrc);
          ld_tag4_issue<16384>(pv[1], xsrc + 65536);
          if (++it > SPIN_LIMIT) { die(); break; }
        }
#pragma unroll
        for (int i = 0; i < 8; i++) {
          const uint4& p = pv[i >> 2][i & 3];
          asm volatile("stmatrix.sync.aligned.m8n8.x4.shared.b16 [%0], {%1,%2,%3,%4};"
                       ::"r"(pa0 + (9 + ((lane >> 3) & 1)) * SLOT + (lane & 7) * 256 + (((2 * i + (lane >> 4)) ^ (lane & 7)) * 16)),
                         "r"(hadd2_bf16(w[4 * i], p.x & ~1u)), "r"(hadd2_bf16(w[4 * i + 1], p.y)), "r"(hadd2_bf16(w[4 * i + 2], p.z)),
                         "r"(hadd2_bf16(w[4 * i + 3], p.w)) : "memory");
        }
        __syncwarp();
        uint4* const dst = reinterpret_cast<uint4*>(out) + (16 * (c >> 4) + 2 * (4 * rh + wq) + (rb2 & 1) + 128 * (lane >> 4)) * 64 + nq * 16 + (lane & 15);
#pragma unroll
        for (int i = 0; i < 8; i++) {
          const int r = 2 * (i & 3) + (lane >> 4);
          dst[i * 256 * 64] = lds4(pa0 + (9 + (i >> 2)) * SLOT + r * 256 + (((lane & 15) ^ r) * 16));
        }
      }
      PROF(12);
      PROFG(15);
    }
  }
#undef BAR
#undef TOFF
#undef RBAR
}

typedef CUresult (*EncodeFn)(CUtensorMap*, CUtensorMapDataType, cuuint32_t, void*, const cuuint64_t*, const cuuint64_t*,
                             const cuuint32_t*, const cuuint32_t*, CUtensorMapInterleave, CUtensorMapSwizzle,
                             CUtensorMapL2promotion, CUtensorMapFloatOOBfill);

}

extern "C" void kernel_launch(void* const* d_in, const int* in_sizes, int n_in, void* d_out, int out_size) {
  (void)in_sizes; (void)n_in; (void)out_size;
  static EncodeFn encode = nullptr;
  static void *tab = nullptr, *scr = nullptr;
  if (!encode) {
    void* fn = nullptr;
    cudaDriverEntryPointQueryResult qr;
    cudaGetDriverEntryPoint("cuTensorMapEncodeTiled", &fn, cudaEnableDefault, &qr);
    encode = (EncodeFn)fn;
    cudaGetSymbolAddress(&tab, g_tab);
    cudaGetSymbolAddress(&scr, g_scr);
    cudaFuncSetAttribute(fused_kernel, cudaFuncAttributeMaxDynamicSharedMemorySize, SMEM_BYTES);
  }
  CUtensorMap tmGX, tmUX, tmGY, tmUY, tmD, tmWR, tmWI;
  const cuuint32_t es[5] = {1, 1, 1, 1, 1};
  auto enc = [&](CUtensorMap* m, void* p, int rank, const cuuint64_t* gd, const cuuint64_t* gs, const cuuint32_t* bd,
                 CUtensorMapSwizzle sw, CUtensorMapL2promotion pr) {
    encode(m, CU_TENSOR_MAP_DATA_TYPE_BFLOAT16, rank, p, gd, gs, bd, es, CU_TENSOR_MAP_INTERLEAVE_NONE, sw, pr,
           CU_TENSOR_MAP_FLOAT_OOB_FILL_NONE);
  };
  {
    const cuuint64_t gd[3] = {64, 512, 28}, gs[2] = {3584, 128};
    const cuuint32_t bd[3] = {64, 32, 2};
    enc(&tmGX, d_in[4], 3, gd, gs, bd, CU_TENSOR_MAP_SWIZZLE_128B, CU_TENSOR_MAP_L2_PROMOTION_L2_256B);
    enc(&tmUX, d_in[5], 3, gd, gs, bd, CU_TENSOR_MAP_SWIZZLE_128B, CU_TENSOR_MAP_L2_PROMOTION_L2_256B);
  }
  {
    const cuuint64_t gd[3] = {32, 512, 56}, gs[2] = {3584, 64};
    const cuuint32_t bd[3] = {32, 32, 3};
    enc(&tmGY, d_in[4], 3, gd, gs, bd, CU_TENSOR_MAP_SWIZZLE_64B, CU_TENSOR_MAP_L2_PROMOTION_L2_128B);
    enc(&tmUY, d_in[5], 3, gd, gs, bd, CU_TENSOR_MAP_SWIZZLE_64B, CU_TENSOR_MAP_L2_PROMOTION_L2_128B);
  }
  {
    const cuuint64_t gd[3] = {64, 1792, 8}, gs[2] = {1024, 128};
    const cuuint32_t bd[3] = {64, 64, 2};
    enc(&tmD, d_in[6], 3, gd, gs, bd, CU_TENSOR_MAP_SWIZZLE_128B, CU_TENSOR_MAP_L2_PROMOTION_L2_256B);
  }
  {
    const cuuint64_t gd[3] = {4112, 8, 16}, gs[2] = {16 * 8224, 8224};
    const cuuint32_t bd[3] = {40, 8, 16};
    enc(&tmWR, d_in[1], 3, gd, gs, bd, CU_TENSOR_MAP_SWIZZLE_NONE, CU_TENSOR_MAP_L2_PROMOTION_NONE);
    enc(&tmWI, d_in[2], 3, gd, gs, bd, CU_TENSOR_MAP_SWIZZLE_NONE, CU_TENSOR_MAP_L2_PROMOTION_NONE);
  }
  fused_kernel<<<NCTA, NTHREADS, SMEM_BYTES>>>((const __nv_bfloat16*)d_in[0], (const Tables*)tab, (Scratch*)scr,
                                               (__nv_bfloat16*)d_out, (const char*)d_in[4], (const char*)d_in[5],
                                               (const char*)d_in[6], tmWR, tmWI, tmGX, tmUX, tmGY, tmUY, tmD);
}
```

```cpp
#include <cuda_runtime.h>
#include <cuda_bf16.h>
#include <cuda.h>
#include <stdint.h>

namespace {

constexpr int NCTA = 128;
constexpr int NTHREADS = 384;
constexpr int SLOT = 16384;
constexpr int SMEM_BYTES = 14 * SLOT + 3072;
constexpr int SPIN_LIMIT = 1 << 22;

struct Scratch {
  uint4 Z1[128 * 1024];
  uint4 LN[16 * 8 * 1024];
  uint4 P[16 * 28 * 1024];
  uint4 ST[1024];
  unsigned cnt[64 * 32];
};
__device__ __align__(1024) Scratch g_scr;
#define PROF(i)
#define PROFP(i)
#define PROFG(i)

constexpr double ccos(int i, int n) {
  i &= n - 1;
  if (i > n / 2) i = n - i;
  if (4 * i == n) return 0.0;
  const bool neg = 4 * i > n;
  if (neg) i = n / 2 - i;
  const double a = 6.283185307179586476925 * i / n, a2 = a * a;
  double term = 1.0, sum = 1.0;
  for (int k = 1; k < 14; k++) { term *= -a2 / ((2 * k - 1) * (2 * k)); sum += term; }
  return neg ? -sum : sum;
}
constexpr double csin(int i, int n) { return ccos(i - n / 4, n); }
constexpr unsigned fbits(double v, int mant) {
  if (v == 0.0) return 0;
  const unsigned sg = v < 0 ? 1u : 0u;
  if (v < 0) v = -v;
  int e = 127;
  while (v < 1.0) { v *= 2.0; e--; }
  const unsigned m = (unsigned)((v - 1.0) * (double)(1u << mant) + 0.5);
  return (sg << (8 + mant)) + ((unsigned)e << mant) + m;
}
constexpr unsigned pkb(double lo, double hi) { return fbits(lo, 7) | (fbits(hi, 7) << 16); }
constexpr double fa_elem(int mt, int r, int n1) {
  const int k1 = 8 * mt + (r & 7);
  return r < 8 ? ccos(k1 * n1, 32) : k1 == 0 ? ccos(16 * n1, 32) : -csin(k1 * n1, 32);
}
constexpr unsigned cfrag_c(int idx, int n, int ri, double s = 1.0) {
  return ri ? pkb(-s * csin(idx, n), s * ccos(idx, n)) : pkb(s * ccos(idx, n), s * csin(idx, n));
}
struct Tables {
  unsigned fa[4][32][4];
  unsigned fb[4][32][4];
  unsigned tw1[6][32][4];
  unsigned f2[8][4][32][4];
  unsigned g2[8][4][32][4];
  unsigned gb[4][32][4];
  unsigned ga[4][32][4];
  unsigned tw3[4][32][4];
  unsigned f8[32][4], g8[32][4];
};
constexpr int T1_BYTES = 7168, T2_BYTES = 39936;
static_assert(sizeof(Tables) == T1_BYTES + T2_BYTES, "table size");
constexpr Tables make_tables() {
  Tables T = {};
  for (int l = 0; l < 32; l++) {
    const int g = l >> 2, t = l & 3;
    for (int a = 0; a < 2; a++)
      for (int b = 0; b < 2; b++) {
        for (int r = 0; r < 4; r++) {
          const int row = g + 8 * (r & 1), col = 2 * t + 8 * (r >> 1);
          T.fa[2 * a + b][l][r] = pkb(fa_elem(a, row, 16 * b + col), fa_elem(a, row, 16 * b + col + 1));
          T.ga[2 * a + b][l][r] = pkb(fa_elem(b, col, 16 * a + row), fa_elem(b, col + 1, 16 * a + row));
        }
        const double sg = b ? -1.0 : 1.0;
        for (int h = 0; h < 2; h++) {
          const int ri = g & 1, m = 2 * (g >> 1) + h, k2 = b ? 15 - m : m;
          const int pa = (8 * a + 2 * t) * k2, pb = (8 * a + 2 * t + 1) * k2;
          T.fb[2 * a + b][l][2 * h] = ri == 0 ? pkb(ccos(pa, 16), ccos(pb, 16)) : pkb(-sg * csin(pa, 16), -sg * csin(pb, 16));
          T.fb[2 * a + b][l][2 * h + 1] = ri == 0 ? pkb(csin(pa, 16), csin(pb, 16)) : pkb(sg * ccos(pa, 16), sg * ccos(pb, 16));
        }
        const int n2 = 4 * (g >> 1) + 2 * a + (g & 1);
        for (int h = 0; h < 2; h++) {
          const int p = n2 * (b ? 15 - 2 * t - h : 2 * t + h);
          T.gb[2 * a + b][l][2 * h] = pkb(ccos(p, 16), -sg * csin(p, 16));
          T.gb[2 * a + b][l][2 * h + 1] = pkb(csin(p, 16), sg * ccos(p, 16));
          const int k1 = 8 * b + 2 * t + h, q = n2 * (k1 == 0 ? 16 : k1);
          T.tw3[2 * a + b][l][2 * h] = fbits(ccos(q, 512), 23);
          T.tw3[2 * a + b][l][2 * h + 1] = fbits(csin(q, 512), 23);
        }
        const int p = (8 * a + 2 * t + b) * (g == 0 ? 16 : g);
        T.tw1[2 * a + b][l][0] = fbits(g == 0 ? 0.0 : ccos(p, 512), 23);
        T.tw1[2 * a + b][l][1] = fbits(g == 0 ? ccos(p, 512) : csin(p, 512), 23);
        T.tw1[2 * a + b][l][2] = fbits(g == 0 ? 0.0 : -csin(p, 512), 23);
        T.tw1[2 * a + b][l][3] = fbits(g == 0 ? -csin(p, 512) : ccos(p, 512), 23);
        T.tw1[4 + a][l][2 * b] = fbits(ccos((8 * a + 2 * t + b) * (g + 8), 512), 23);
        T.tw1[4 + a][l][2 * b + 1] = fbits(csin((8 * a + 2 * t + b) * (g + 8), 512), 23);
      }
    for (int i = 0; i < 4; i++) {
      const int p8 = (t + 4 * (i & 1)) * (4 * (i >> 1) + (g >> 1));
      T.f8[l][i] = cfrag_c(p8, 8, g & 1);
      T.g8[l][i] = cfrag_c(-p8, 8, g & 1, 1.0 / (1 << 19));
    }
    for (int w = 0; w < 8; w++)
      for (int i = 0; i < 16; i++) {
        const int kidx = t + 4 * (i & 1) + 8 * (i >> 3), nidx = 4 * ((i >> 1) & 3) + (g >> 1);
        T.f2[w][i >> 2][l][i & 3] = cfrag_c((8 * kidx + w) * nidx, 128, g & 1);
        T.g2[w][i >> 2][l][i & 3] = cfrag_c(-(8 * nidx + w) * kidx, 128, g & 1);
      }
  }
  return T;
}
__device__ const __align__(128) Tables g_tab = make_tables();

__device__ __forceinline__ void die() { asm volatile("st.global.u32 [%0], %1;" ::"l"(0ull), "r"(0) : "memory"); }
__device__ __forceinline__ uint32_t s2u(const void* p) { return (uint32_t)__cvta_generic_to_shared(p); }
__device__ __forceinline__ void mbar_init(uint32_t b, int c) { asm volatile("mbarrier.init.shared::cta.b64 [%0], %1;" ::"r"(b), "r"(c)); }
__device__ __forceinline__ void mbar_expect(uint32_t b, int bytes) {
  asm volatile("mbarrier.arrive.expect_tx.shared::cta.b64 _, [%0], %1;" ::"r"(b), "r"(bytes) : "memory");
}
__device__ __forceinline__ void mbar_arrive(uint32_t b) { asm volatile("mbarrier.arrive.shared::cta.b64 _, [%0];" ::"r"(b) : "memory"); }
__device__ __forceinline__ uint32_t mbar_try(uint32_t b, uint32_t parity) {
  uint32_t ok;
  asm volatile("{.reg .pred p; mbarrier.try_wait.parity.shared::cta.b64 p, [%1], %2; selp.u32 %0,1,0,p;}"
               : "=r"(ok) : "r"(b), "r"(parity) : "memory");
  return ok;
}
__device__ __forceinline__ uint32_t mbar_test(uint32_t b) {
  uint32_t ok;
  asm volatile("{.reg .pred p; mbarrier.test_wait.parity.shared::cta.b64 p, [%1], 0; selp.u32 %0,1,0,p;}" : "=r"(ok) : "r"(b) : "memory");
  return ok;
}
__device__ __forceinline__ void mbar_wait(uint32_t b, uint32_t parity = 0) {
  int it = 0;
#pragma unroll 1
  while (!mbar_try(b, parity))
    if (++it > SPIN_LIMIT) { die(); break; }
}
__device__ __forceinline__ void bar_sync(int id, int n) { asm volatile("bar.sync %0, %1;" ::"r"(id), "r"(n) : "memory"); }
__device__ __forceinline__ void bar_arrive(int id, int n) { asm volatile("bar.arrive %0, %1;" ::"r"(id), "r"(n) : "memory"); }
__device__ __forceinline__ void red_release(unsigned* p) { asm volatile("red.release.gpu.global.add.u32 [%0], 1;" ::"l"(p) : "memory"); }
__device__ __forceinline__ void red_relaxed(unsigned* p) { asm volatile("red.relaxed.gpu.global.add.u32 [%0], 1;" ::"l"(p) : "memory"); }
__device__ __forceinline__ unsigned ld_acquire(const unsigned* p) {
  unsigned v;
  asm volatile("ld.acquire.gpu.global.u32 %0, [%1];" : "=r"(v) : "l"(p) : "memory");
  return v;
}
__device__ __forceinline__ unsigned ld_relaxed(const unsigned* p) {
  unsigned v;
  asm volatile("ld.relaxed.gpu.global.u32 %0, [%1];" : "=r"(v) : "l"(p) : "memory");
  return v;
}
__device__ __forceinline__ void wait_counter(const unsigned* p, unsigned target) {
  int it = 0;
  while ((int)(ld_acquire(p) - target) < 0)
    if (++it > SPIN_LIMIT) { die(); break; }
}
__device__ __forceinline__ void sts4(uint32_t a, uint32_t x, uint32_t y, uint32_t z, uint32_t w) {
  asm volatile("st.shared.v4.u32 [%0], {%1,%2,%3,%4};" ::"r"(a), "r"(x), "r"(y), "r"(z), "r"(w) : "memory");
}
__device__ __forceinline__ uint4 lds4(uint32_t a) {
  uint4 v;
  asm volatile("ld.shared.v4.u32 {%0,%1,%2,%3}, [%4];" : "=r"(v.x), "=r"(v.y), "=r"(v.z), "=r"(v.w) : "r"(a) : "memory");
  return v;
}
__device__ __forceinline__ uint32_t pack2(float lo, float hi) {
  uint32_t r;
  asm("cvt.rn.bf16x2.f32 %0, %1, %2;" : "=r"(r) : "f"(hi), "f"(lo));
  return r;
}
__device__ __forceinline__ float bf_lo(uint32_t v) { return __uint_as_float(v << 16); }
__device__ __forceinline__ uint32_t hadd2_bf16(uint32_t a, uint32_t b) {
  uint32_t r;
  asm("add.rn.bf16x2 %0, %1, %2;" : "=r"(r) : "r"(a), "r"(b));
  return r;
}
__device__ __forceinline__ void mma16816(float (&d)[4], uint32_t a0, uint32_t a1, uint32_t a2, uint32_t a3, uint32_t b0, uint32_t b1) {
  asm("mma.sync.aligned.m16n8k16.row.col.f32.bf16.bf16.f32 {%0,%1,%2,%3}, {%4,%5,%6,%7}, {%8,%9}, {%0,%1,%2,%3};"
      : "+f"(d[0]), "+f"(d[1]), "+f"(d[2]), "+f"(d[3])
      : "r"(a0), "r"(a1), "r"(a2), "r"(a3), "r"(b0), "r"(b1));
}
__device__ __forceinline__ void mma16816_z(float (&d)[4], uint32_t a0, uint32_t a1, uint32_t a2, uint32_t a3, uint32_t b0, uint32_t b1) {
  asm("{.reg .f32 z; mov.f32 z, 0f00000000;\n"
      "mma.sync.aligned.m16n8k16.row.col.f32.bf16.bf16.f32 {%0,%1,%2,%3}, {%4,%5,%6,%7}, {%8,%9}, {z,z,z,z};}"
      : "=f"(d[0]), "=f"(d[1]), "=f"(d[2]), "=f"(d[3])
      : "r"(a0), "r"(a1), "r"(a2), "r"(a3), "r"(b0), "r"(b1));
}
template <int N>
__device__ __forceinline__ void cs_frac(int idx, float& c, float& s) {
  int i = ((idx + N / 2) & (N - 1)) - N / 2;
  float a = (float)i * (6.283185307179586f / N);
  c = __cosf(a);
  s = __sinf(a);
}
template <int N>
__device__ __forceinline__ uint32_t cfrag(int idx, int ri) {
  float c, s;
  cs_frac<N>(idx, c, s);
  return ri ? pack2(-s, c) : pack2(c, s);
}
__device__ __forceinline__ uint32_t word(const uint4& v, int e) { return e == 0 ? v.x : e == 1 ? v.y : e == 2 ? v.z : v.w; }
__device__ __forceinline__ void cdft16(const uint4 (&A)[4], const uint4 (&F)[4], uint4 (&o)[4]) {
  float acc[2][4][4];
#pragma unroll
  for (int ks = 0; ks < 2; ks++)
#pragma unroll
    for (int p = 0; p < 2; p++)
#pragma unroll
      for (int v = 0; v < 4; v++) {
        const uint4& a = A[2 * ks + p];
        const uint32_t b0 = word(F[ks * 2 + (v >> 1)], (v & 1) * 2), b1 = word(F[ks * 2 + (v >> 1)], (v & 1) * 2 + 1);
        if (ks == 0) mma16816_z(acc[p][v], a.x, a.y, a.z, a.w, b0, b1);
        else mma16816(acc[p][v], a.x, a.y, a.z, a.w, b0, b1);
      }
#pragma unroll
  for (int v = 0; v < 4; v++)
    o[v] = make_uint4(pack2(acc[0][v][0], acc[0][v][1]), pack2(acc[0][v][2], acc[0][v][3]),
                      pack2(acc[1][v][0], acc[1][v][1]), pack2(acc[1][v][2], acc[1][v][3]));
}
__device__ __forceinline__ void lds_frag(uint4& f0, uint4& f1, uint32_t a0, uint32_t a1) {
  asm volatile("ld.volatile.shared.v2.u32 {%0,%1}, [%8]; ld.volatile.shared.v2.u32 {%2,%3}, [%9];\n"
               "ld.volatile.shared.v2.u32 {%4,%5}, [%8+8]; ld.volatile.shared.v2.u32 {%6,%7}, [%9+8];"
               : "=r"(f0.x), "=r"(f0.y), "=r"(f0.z), "=r"(f0.w), "=r"(f1.x), "=r"(f1.y), "=r"(f1.z), "=r"(f1.w) : "r"(a0), "r"(a1) : "memory");
}
__device__ __forceinline__ void reg_frag(uint4 (&q)[4], uint32_t ones) {
#pragma unroll
  for (int ks = 0; ks < 2; ks++) {
    const uint4 a = q[2 * ks], b = q[2 * ks + 1];
    q[2 * ks] = make_uint4(a.x, a.y, b.x & ones, b.y & ones);
    q[2 * ks + 1] = make_uint4(a.z & ones, a.w & ones, b.z, b.w);
  }
}
__device__ __forceinline__ void st_tag(uint4* p, const uint4& v, uint32_t tag) {
  asm volatile("st.relaxed.gpu.global.v4.b32 [%0], {%1,%2,%3,%4};"
               ::"l"(p), "r"((v.x & ~1u) | tag), "r"(v.y), "r"(v.z), "r"(v.w) : "memory");
}
__device__ __forceinline__ void st_tag8(void* p, uint32_t x, uint32_t y, uint32_t tag) {
  asm volatile("st.relaxed.gpu.global.v2.b32 [%0], {%1,%2};" ::"l"(p), "r"((x & ~1u) | tag), "r"(y) : "memory");
}
__device__ __forceinline__ uint4 ld_b128(const uint4* p) {
  uint4 v;
  asm volatile("ld.relaxed.gpu.global.v4.b32 {%0,%1,%2,%3}, [%4];"
               : "=r"(v.x), "=r"(v.y), "=r"(v.z), "=r"(v.w) : "l"(p) : "memory");
  return v;
}
template <int STRIDE>
__device__ __forceinline__ void ld_tag4_issue(uint4 (&q)[4], const uint4* p) {
#pragma unroll
  for (int i = 0; i < 4; i++) q[i] = ld_b128(p + i * STRIDE);
}
template <int STRIDE, bool HALVES = false>
__device__ __forceinline__ void ld_tag4_finish(uint4 (&q)[4], const uint4* p, uint32_t tag) {
  int it = 0;
#pragma unroll 1
  while (__any_sync(0xffffffffu, ((q[0].x ^ tag) | (q[1].x ^ tag) | (q[2].x ^ tag) | (q[3].x ^ tag) |
                                  (HALVES ? (q[0].z ^ tag) | (q[1].z ^ tag) | (q[2].z ^ tag) | (q[3].z ^ tag) : 0u)) & 1u)) {
    ld_tag4_issue<STRIDE>(q, p);
    if (++it > SPIN_LIMIT) { die(); break; }
  }
#pragma unroll
  for (int i = 0; i < 4; i++) {
    asm volatile("and.b32 %0, %0, 0xfffffffe;" : "+r"(q[i].x));
    if (HALVES) q[i].z &= ~1u;
  }
}
__device__ __forceinline__ float quad_sum(const uint32_t (&a)[8]) {
  float d[4];
  mma16816_z(d, a[0], a[1], a[2], a[3], 0x3f803f80u, 0x3f803f80u);
  mma16816(d, a[4], a[5], a[6], a[7], 0x3f803f80u, 0x3f803f80u);
  return d[0] + d[2];
}
__device__ __forceinline__ float sum_groups(float v) {
  v += __shfl_xor_sync(0xffffffffu, v, 4);
  v += __shfl_xor_sync(0xffffffffu, v, 8);
  v += __shfl_xor_sync(0xffffffffu, v, 16);
  return v;
}
__device__ __forceinline__ uint32_t hsub2_bf16(uint32_t a, uint32_t b) {
  uint32_t r;
  asm("sub.rn.bf16x2 %0, %1, %2;" : "=r"(r) : "r"(a), "r"(b));
  return r;
}
__device__ __forceinline__ float row_rstd(const uint32_t (&c)[8], float delta) {
  uint32_t s[8];
#pragma unroll
  for (int i = 0; i < 8; i++) asm("mul.rn.bf16x2 %0, %1, %1;" : "=r"(s[i]) : "r"(c[i]));
  return rsqrtf(fmaxf(fmaf(-delta, delta, sum_groups(quad_sum(s)) * (1.f / 512.f)), 0.f) + 1e-5f);
}
__device__ __forceinline__ uint64_t desc64(uint32_t lo, uint32_t hi) {
  uint64_t d;
  asm("mov.b64 %0, {%1, %2};" : "=l"(d) : "r"(lo), "r"(hi));
  return d;
}
constexpr uint32_t desc_hi(uint32_t sbo, uint32_t swz) { return (sbo >> 4) | (swz << 30); }
__device__ __forceinline__ uint32_t desc_lo(uint32_t addr, uint32_t lbo) { return ((addr & 0x3FFFF) >> 4) | ((lbo >> 4) << 16); }
__device__ __forceinline__ void cp_async16(uint32_t dst, const void* src) {
  asm volatile("cp.async.cg.shared.global [%0], [%1], 16;" ::"r"(dst), "l"(src) : "memory");
}
__device__ __forceinline__ uint2 lds2(uint32_t a) {
  uint2 v;
  asm volatile("ld.shared.v2.u32 {%0,%1}, [%2];" : "=r"(v.x), "=r"(v.y) : "r"(a) : "memory");
  return v;
}
__device__ __forceinline__ uint32_t lds_u16(uint32_t a) {
  uint16_t v;
  asm volatile("ld.shared.u16 %0, [%1];" : "=h"(v) : "r"(a) : "memory");
  return v;
}
__device__ __forceinline__ void wg_fence() { asm volatile("wgmma.fence.sync.aligned;" ::: "memory"); }
__device__ __forceinline__ void wg_commit() { asm volatile("wgmma.commit_group.sync.aligned;" ::: "memory"); }
template <int N>
__device__ __forceinline__ void wg_wait() { asm volatile("wgmma.wait_group.sync.aligned %0;" ::"n"(N) : "memory"); }
__device__ __forceinline__ void bulk_load(uint32_t dst, const void* src, int bytes, uint32_t bar) {
  asm volatile("cp.async.bulk.shared::cluster.global.mbarrier::complete_tx::bytes [%0], [%1], %2, [%3];"
               ::"r"(dst), "l"(src), "r"(bytes), "r"(bar) : "memory");
}
__device__ __forceinline__ void bulk_load_mc(uint32_t dst, const void* src, int bytes, uint32_t bar) {
  asm volatile("cp.async.bulk.shared::cluster.global.mbarrier::complete_tx::bytes.multicast::cluster [%0], [%1], %2, [%3], %4;"
               ::"r"(dst), "l"(src), "r"(bytes), "r"(bar), "h"((uint16_t)3) : "memory");
}
__device__ __forceinline__ void tma3(uint32_t dst, const CUtensorMap* tm, uint32_t bar, int c0, int c1, int c2) {
  asm volatile("cp.async.bulk.tensor.3d.shared::cluster.global.mbarrier::complete_tx::bytes [%0], [%1, {%3,%4,%5}], [%2];"
               ::"r"(dst), "l"(tm), "r"(bar), "r"(c0), "r"(c1), "r"(c2) : "memory");
}
__device__ __forceinline__ void tma3_mc(uint32_t dst, const CUtensorMap* tm, uint32_t bar, int c1, int c2) {
  asm volatile("cp.async.bulk.tensor.3d.shared::cluster.global.mbarrier::complete_tx::bytes.multicast::cluster [%0], [%1, {%3,%4,%5}], [%2], %6;"
               ::"r"(dst), "l"(tm), "r"(bar), "r"(0), "r"(c1), "r"(c2), "h"((uint16_t)3) : "memory");
}
__device__ __forceinline__ void mbar_arrive_remote(uint32_t rb) {
  asm volatile("mbarrier.arrive.shared::cluster.b64 _, [%0];" ::"r"(rb) : "memory");
}
__device__ __forceinline__ uint4 ldg_ca4(const void* p) {
  uint4 v;
  asm volatile("ld.global.ca.v4.u32 {%0,%1,%2,%3}, [%4];" : "=r"(v.x), "=r"(v.y), "=r"(v.z), "=r"(v.w) : "l"(p) : "memory");
  return v;
}
__device__ __forceinline__ float u2f(uint32_t v) { return __uint_as_float(v); }
__device__ __forceinline__ void mma_az(float (&d)[4], const uint4& a, uint32_t b0, uint32_t b1) { mma16816_z(d, a.x, a.y, a.z, a.w, b0, b1); }
__device__ __forceinline__ void mma_a(float (&d)[4], const uint4& a, uint32_t b0, uint32_t b1) { mma16816(d, a.x, a.y, a.z, a.w, b0, b1); }
__device__ __forceinline__ uint32_t clock32() {
  uint32_t v;
  asm volatile("mov.u32 %0, %%clock;" : "=r"(v) :: "memory");
  return v;
}
__device__ __forceinline__ float swiglu(float g, float u, float r) {
  float hg = (0.5f * r) * g, th;
  asm("tanh.approx.f32 %0, %1;" : "=f"(th) : "f"(hg));
  return fmaf(hg, th, hg) * (r * u);
}
__device__ __forceinline__ void l2_prefetch(const void* p, int bytes) {
  asm volatile("cp.async.bulk.prefetch.L2.global [%0], %1;" ::"l"(p), "r"(bytes) : "memory");
}

__device__ __forceinline__ void wgmma_n256(float (&d)[128], uint64_t da, uint64_t db, int sd = 1) {
  asm volatile("{.reg .pred p; setp.ne.b32 p, %130, 0;\n"
      "wgmma.mma_async.sync.aligned.m64n256k16.f32.bf16.bf16 {"
      "%0,%1,%2,%3,%4,%5,%6,%7,%8,%9,%10,%11,%12,%13,%14,%15,"
      "%16,%17,%18,%19,%20,%21,%22,%23,%24,%25,%26,%27,%28,%29,%30,%31,"
      "%32,%33,%34,%35,%36,%37,%38,%39,%40,%41,%42,%43,%44,%45,%46,%47,"
      "%48,%49,%50,%51,%52,%53,%54,%55,%56,%57,%58,%59,%60,%61,%62,%63,"
      "%64,%65,%66,%67,%68,%69,%70,%71,%72,%73,%74,%75,%76,%77,%78,%79,"
      "%80,%81,%82,%83,%84,%85,%86,%87,%88,%89,%90,%91,%92,%93,%94,%95,"
      "%96,%97,%98,%99,%100,%101,%102,%103,%104,%105,%106,%107,%108,%109,%110,%111,"
      "%112,%113,%114,%115,%116,%117,%118,%119,%120,%121,%122,%123,%124,%125,%126,%127"
      "}, %128, %129, p, 1, 1, 0, 1;}\n"
      : "+f"(d[0]),"+f"(d[1]),"+f"(d[2]),"+f"(d[3]),"+f"(d[4]),"+f"(d[5]),"+f"(d[6]),"+f"(d[7]),
        "+f"(d[8]),"+f"(d[9]),"+f"(d[10]),"+f"(d[11]),"+f"(d[12]),"+f"(d[13]),"+f"(d[14]),"+f"(d[15]),
        "+f"(d[16]),"+f"(d[17]),"+f"(d[18]),"+f"(d[19]),"+f"(d[20]),"+f"(d[21]),"+f"(d[22]),"+f"(d[23]),
        "+f"(d[24]),"+f"(d[25]),"+f"(d[26]),"+f"(d[27]),"+f"(d[28]),"+f"(d[29]),"+f"(d[30]),"+f"(d[31]),
        "+f"(d[32]),"+f"(d[33]),"+f"(d[34]),"+f"(d[35]),"+f"(d[36]),"+f"(d[37]),"+f"(d[38]),"+f"(d[39]),
        "+f"(d[40]),"+f"(d[41]),"+f"(d[42]),"+f"(d[43]),"+f"(d[44]),"+f"(d[45]),"+f"(d[46]),"+f"(d[47]),
        "+f"(d[48]),"+f"(d[49]),"+f"(d[50]),"+f"(d[51]),"+f"(d[52]),"+f"(d[53]),"+f"(d[54]),"+f"(d[55]),
        "+f"(d[56]),"+f"(d[57]),"+f"(d[58]),"+f"(d[59]),"+f"(d[60]),"+f"(d[61]),"+f"(d[62]),"+f"(d[63]),
        "+f"(d[64]),"+f"(d[65]),"+f"(d[66]),"+f"(d[67]),"+f"(d[68]),"+f"(d[69]),"+f"(d[70]),"+f"(d[71]),
        "+f"(d[72]),"+f"(d[73]),"+f"(d[74]),"+f"(d[75]),"+f"(d[76]),"+f"(d[77]),"+f"(d[78]),"+f"(d[79]),
        "+f"(d[80]),"+f"(d[81]),"+f"(d[82]),"+f"(d[83]),"+f"(d[84]),"+f"(d[85]),"+f"(d[86]),"+f"(d[87]),
        "+f"(d[88]),"+f"(d[89]),"+f"(d[90]),"+f"(d[91]),"+f"(d[92]),"+f"(d[93]),"+f"(d[94]),"+f"(d[95]),
        "+f"(d[96]),"+f"(d[97]),"+f"(d[98]),"+f"(d[99]),"+f"(d[100]),"+f"(d[101]),"+f"(d[102]),"+f"(d[103]),
        "+f"(d[104]),"+f"(d[105]),"+f"(d[106]),"+f"(d[107]),"+f"(d[108]),"+f"(d[109]),"+f"(d[110]),"+f"(d[111]),
        "+f"(d[112]),"+f"(d[113]),"+f"(d[114]),"+f"(d[115]),"+f"(d[116]),"+f"(d[117]),"+f"(d[118]),"+f"(d[119]),
        "+f"(d[120]),"+f"(d[121]),"+f"(d[122]),"+f"(d[123]),"+f"(d[124]),"+f"(d[125]),"+f"(d[126]),"+f"(d[127])
      : "l"(da), "l"(db), "r"(sd));
}
__device__ __forceinline__ void wgmma_n192(float (&d)[96], uint64_t da, uint64_t db) {
  asm volatile("wgmma.mma_async.sync.aligned.m64n192k16.f32.bf16.bf16 {"
      "%0,%1,%2,%3,%4,%5,%6,%7,%8,%9,%10,%11,%12,%13,%14,%15,"
      "%16,%17,%18,%19,%20,%21,%22,%23,%24,%25,%26,%27,%28,%29,%30,%31,"
      "%32,%33,%34,%35,%36,%37,%38,%39,%40,%41,%42,%43,%44,%45,%46,%47,"
      "%48,%49,%50,%51,%52,%53,%54,%55,%56,%57,%58,%59,%60,%61,%62,%63,"
      "%64,%65,%66,%67,%68,%69,%70,%71,%72,%73,%74,%75,%76,%77,%78,%79,"
      "%80,%81,%82,%83,%84,%85,%86,%87,%88,%89,%90,%91,%92,%93,%94,%95"
      "}, %96, %97, 1, 1, 1, 0, 1;\n"
      : "+f"(d[0]),"+f"(d[1]),"+f"(d[2]),"+f"(d[3]),"+f"(d[4]),"+f"(d[5]),"+f"(d[6]),"+f"(d[7]),
        "+f"(d[8]),"+f"(d[9]),"+f"(d[10]),"+f"(d[11]),"+f"(d[12]),"+f"(d[13]),"+f"(d[14]),"+f"(d[15]),
        "+f"(d[16]),"+f"(d[17]),"+f"(d[18]),"+f"(d[19]),"+f"(d[20]),"+f"(d[21]),"+f"(d[22]),"+f"(d[23]),
        "+f"(d[24]),"+f"(d[25]),"+f"(d[26]),"+f"(d[27]),"+f"(d[28]),"+f"(d[29]),"+f"(d[30]),"+f"(d[31]),
        "+f"(d[32]),"+f"(d[33]),"+f"(d[34]),"+f"(d[35]),"+f"(d[36]),"+f"(d[37]),"+f"(d[38]),"+f"(d[39]),
        "+f"(d[40]),"+f"(d[41]),"+f"(d[42]),"+f"(d[43]),"+f"(d[44]),"+f"(d[45]),"+f"(d[46]),"+f"(d[47]),
        "+f"(d[48]),"+f"(d[49]),"+f"(d[50]),"+f"(d[51]),"+f"(d[52]),"+f"(d[53]),"+f"(d[54]),"+f"(d[55]),
        "+f"(d[56]),"+f"(d[57]),"+f"(d[58]),"+f"(d[59]),"+f"(d[60]),"+f"(d[61]),"+f"(d[62]),"+f"(d[63]),
        "+f"(d[64]),"+f"(d[65]),"+f"(d[66]),"+f"(d[67]),"+f"(d[68]),"+f"(d[69]),"+f"(d[70]),"+f"(d[71]),
        "+f"(d[72]),"+f"(d[73]),"+f"(d[74]),"+f"(d[75]),"+f"(d[76]),"+f"(d[77]),"+f"(d[78]),"+f"(d[79]),
        "+f"(d[80]),"+f"(d[81]),"+f"(d[82]),"+f"(d[83]),"+f"(d[84]),"+f"(d[85]),"+f"(d[86]),"+f"(d[87]),
        "+f"(d[88]),"+f"(d[89]),"+f"(d[90]),"+f"(d[91]),"+f"(d[92]),"+f"(d[93]),"+f"(d[94]),"+f"(d[95])
      : "l"(da), "l"(db));
}
template <int SD>
__device__ __forceinline__ void wgmma_rs_n128(float (&d)[64], uint32_t a0, uint32_t a1, uint32_t a2, uint32_t a3, uint64_t db) {
  asm volatile("wgmma.mma_async.sync.aligned.m64n128k16.f32.bf16.bf16 {"
      "%0,%1,%2,%3,%4,%5,%6,%7,%8,%9,%10,%11,%12,%13,%14,%15,"
      "%16,%17,%18,%19,%20,%21,%22,%23,%24,%25,%26,%27,%28,%29,%30,%31,"
      "%32,%33,%34,%35,%36,%37,%38,%39,%40,%41,%42,%43,%44,%45,%46,%47,"
      "%48,%49,%50,%51,%52,%53,%54,%55,%56,%57,%58,%59,%60,%61,%62,%63"
      "}, {%64,%65,%66,%67}, %68, %69, 1, 1, 1;\n"
      : "+f"(d[0]),"+f"(d[1]),"+f"(d[2]),"+f"(d[3]),"+f"(d[4]),"+f"(d[5]),"+f"(d[6]),"+f"(d[7]),
        "+f"(d[8]),"+f"(d[9]),"+f"(d[10]),"+f"(d[11]),"+f"(d[12]),"+f"(d[13]),"+f"(d[14]),"+f"(d[15]),
        "+f"(d[16]),"+f"(d[17]),"+f"(d[18]),"+f"(d[19]),"+f"(d[20]),"+f"(d[21]),"+f"(d[22]),"+f"(d[23]),
        "+f"(d[24]),"+f"(d[25]),"+f"(d[26]),"+f"(d[27]),"+f"(d[28]),"+f"(d[29]),"+f"(d[30]),"+f"(d[31]),
        "+f"(d[32]),"+f"(d[33]),"+f"(d[34]),"+f"(d[35]),"+f"(d[36]),"+f"(d[37]),"+f"(d[38]),"+f"(d[39]),
        "+f"(d[40]),"+f"(d[41]),"+f"(d[42]),"+f"(d[43]),"+f"(d[44]),"+f"(d[45]),"+f"(d[46]),"+f"(d[47]),
        "+f"(d[48]),"+f"(d[49]),"+f"(d[50]),"+f"(d[51]),"+f"(d[52]),"+f"(d[53]),"+f"(d[54]),"+f"(d[55]),
        "+f"(d[56]),"+f"(d[57]),"+f"(d[58]),"+f"(d[59]),"+f"(d[60]),"+f"(d[61]),"+f"(d[62]),"+f"(d[63])
      : "r"(a0), "r"(a1), "r"(a2), "r"(a3), "l"(db), "n"(SD));
}

constexpr int C_LN = 0, C_PX = 16, C_PY = 32;
constexpr int NB_CONS = 1, NB_LN = 2, NB_LAG = 4, NB_INIT = 6, NB_RDY = 7, NB_WG = 8;
#define LAGX 3
#define LAGY 3
#define LAG2 5
constexpr int NLL = 2;
#define POLL_DELAY3 600
#define POLL_DELAY 1200
#define FILT_DELAY 800
#define WARM 4
#define ALEAD 6
#define POLL_DELAY2 1000
#define HPOS 14
#define REDPOS 1
#define XTRIG 21
#define HTRIG 0
#define TABS1 0
#define RING_SIG 1
#define PF2_SIG 1
constexpr int SM_E = 0, SM_X = 16384, SM_E2 = 32768, SM_W = 49152, SM_FC = 69632, SM_T = 73728 - T1_BYTES;
constexpr unsigned long long KORDER = 0xBA9432DC876510ull;
constexpr unsigned long long BSLOT = 0x76532107653210ull, PSLOT = 0xDCBA984DCBA984ull;
constexpr uint32_t HI128 = desc_hi(1024, 1), HI64 = desc_hi(512, 2);

struct Bars {
  uint64_t full1[32], empty1[32], full2[16], fullA[8], empty2[8], fullP[16], emptyP[8], hbar, tbar, hint[3], sig[2], sbar;
  uint32_t epoch, pad;
};

template <int NK, bool STORE, int J0 = 0, int J1 = NK>
__device__ __forceinline__ void make_p(const float (&acc)[NK * 16], float r0, float r1, uint4 (&p)[NK], uint4* pbase, int ks0, uint32_t tag) {
#pragma unroll
  for (int j = J0; j < J1; j++) {
    uint32_t w[4];
#pragma unroll
    for (int i = 0; i < 4; i++) {
      const int a = 8 * j + 2 * i, b = a + NK * 8;
      w[i] = pack2(swiglu(acc[a], acc[b], (i & 1) ? r1 : r0), swiglu(acc[a + 1], acc[b + 1], (i & 1) ? r1 : r0));
    }
    asm volatile("" : "+r"(w[0]), "+r"(w[1]), "+r"(w[2]), "+r"(w[3]));
    p[j] = make_uint4(w[0], w[1], w[2], w[3]);
    if (STORE) st_tag(pbase + ((ks0 + j) >> 2) * 1024 + ((ks0 + j) & 3) * 32, p[j], tag);
  }
}
__device__ __forceinline__ void spin_until(uint32_t t) {
  while ((int)(clock32() - t) < 0) {}
}

__global__ void __cluster_dims__(2, 1, 1) __launch_bounds__(NTHREADS, 1)
fused_kernel(const __nv_bfloat16* __restrict__ x, const Tables* __restrict__ tab, Scratch* __restrict__ scr,
             __nv_bfloat16* __restrict__ out, const char* __restrict__ wg_raw, const char* __restrict__ wu_raw,
             const char* __restrict__ wd_raw,
             const __grid_constant__ CUtensorMap tmWR, const __grid_constant__ CUtensorMap tmWI,
             const __grid_constant__ CUtensorMap tmGX, const __grid_constant__ CUtensorMap tmUX,
             const __grid_constant__ CUtensorMap tmGY, const __grid_constant__ CUtensorMap tmUY,
             const __grid_constant__ CUtensorMap tmD) {
  extern __shared__ __align__(1024) char smem_raw[];
  const uint32_t sbase = s2u(smem_raw);
  const uint32_t sbar = sbase + 14 * SLOT, sstat = sbar + 1280;
  const int tid = threadIdx.x, lane = tid & 31;
  const int c = blockIdx.x, rk = c & 1, f = (c >> 1) & 7, rb = 2 * (c >> 4) + rk;
  const int rb2 = 2 * (c >> 4) + (f >> 2), kh = (f >> 1) & 1, nq = 2 * (f & 1) + rk;
#define BAR(field, i) (sbar + (uint32_t)offsetof(Bars, field) + 8u * (i))
#define TOFF(field) (sbase + SM_T + (uint32_t)offsetof(Tables, field) + lane * 16)

  if (tid >= 256) {
    asm volatile("setmaxnreg.dec.sync.aligned.u32 56;");
    const int warp = __shfl_sync(0xffffffffu, tid >> 5, 0);
    if (lane == 0) {
      if (warp == 8) {
        if (sbase & 1023) die();
#pragma unroll
        for (int i = 0; i < 16; i++) mbar_init(BAR(emptyP, i), i < 7 ? 16 : i < 8 ? 8 : i < 13 ? 1 : i < 15 ? 8 : 32);
        mbar_expect(BAR(tbar, 0), T2_BYTES + 2 * 10240);
        mbar_expect(BAR(hbar, 0), 16384);
      } else if (warp == 9) {
#pragma unroll
        for (int i = 0; i < 32; i++) mbar_init(BAR(full1, i), 1);
#pragma unroll
        for (int i = 0; i < 32; i++) mbar_expect(BAR(full1, i), i < 16 ? 16384 : 12288);
      } else if (warp == 10) {
#pragma unroll
        for (int i = 0; i < 32; i++) mbar_init(BAR(empty1, i), 16);
#pragma unroll
        for (int i = 0; i < 14; i++) mbar_init(BAR(fullP, i), 1);
#pragma unroll
        for (int i = 0; i < 14; i++) mbar_expect(BAR(fullP, i), 16384);
      } else {
#pragma unroll
        for (int i = 0; i < 32; i++) mbar_init(BAR(full2, i), i < 24 ? 1 : 8);
#pragma unroll
        for (int i = 0; i < 24; i++) mbar_expect(BAR(full2, i), 16384);
      }
      asm volatile("fence.mbarrier_init.release.cluster;" ::: "memory");
    }
    if (tid == 256) {
      const int w0 = ((c >> 3) * 257 + 32 * (c & 7) + 1) & ~7;
      if (FILT_DELAY) {
        asm volatile("prefetch.tensormap [%0];" ::"l"(&tmWR) : "memory");
        asm volatile("prefetch.tensormap [%0];" ::"l"(&tmWI) : "memory");
        spin_until(clock32() + FILT_DELAY);
      }
      tma3(sbase + SM_W, &tmWR, BAR(tbar, 0), w0, 0, 0);
      tma3(sbase + SM_W + 10240, &tmWI, BAR(tbar, 0), w0, 0, 0);
      bulk_load(sbase + SM_T + T1_BYTES, reinterpret_cast<const char*>(tab) + T1_BYTES, T2_BYTES, BAR(tbar, 0));
    }
    if (tid == 288) {
      asm volatile("prefetch.tensormap [%0];" ::"l"(rk ? &tmUX : &tmGX) : "memory");
      asm volatile("prefetch.tensormap [%0];" ::"l"(rk ? &tmUY : &tmGY) : "memory");
      asm volatile("prefetch.tensormap [%0];" ::"l"(&tmD) : "memory");
    }
    if (tid == 320) {
      const unsigned e = ld_relaxed(&scr->cnt[(C_LN + rb) * 32]) >> 3;
      asm volatile("st.shared.u32 [%0], %1;" ::"r"(BAR(epoch, 0)), "r"(e) : "memory");
    }
    __syncwarp();
    asm volatile("barrier.cluster.arrive.relaxed.aligned;" ::: "memory");
    bar_arrive(NB_RDY, 384);
    asm volatile("barrier.cluster.wait.aligned;" ::: "memory");
    bar_sync(NB_INIT, 384);
    unsigned epoch;
    asm volatile("ld.shared.u32 %0, [%1];" : "=r"(epoch) : "r"(BAR(epoch, 0)) : "memory");
    if (warp == 8) {
      if (lane == 0) {
        const int ax = (7 * f + 3 * (f & 1)) >> 1;
        const int ay = 7 * f + ((f & 1) ? 0 : 4);
        const CUtensorMap* tx = rk ? &tmUX : &tmGX;
        const CUtensorMap* ty = rk ? &tmUY : &tmGY;
        if (RING_SIG >= 0) mbar_wait(BAR(sig, RING_SIG));
        uint32_t s = 2;
#pragma unroll 1
        for (int n = 0; n < 16; n++) {
          if (n >= 6) mbar_wait(BAR(empty1, n - 6));
          tma3_mc(sbase + (8 + s) * SLOT + rk * 8192, tx, BAR(full1, n), n * 32, ax);
          if (++s == 6) s = 0;
        }
#pragma unroll 1
        for (int k = 0; k < 16; k++) {
          mbar_wait(BAR(empty1, k < 8 ? 10 + ((12 * k + 11) >> 4) : 8 + k));
          tma3_mc(sbase + 8 * SLOT + (k & 7) * 12288 + rk * 6144, ty, BAR(full1, 16 + k), k * 32, ay);
        }
      }
    } else if (warp == 9) {
      if (lane == 0) {
        mbar_wait(BAR(fullA, 4));
        wait_counter(&scr->cnt[(C_LN + rb2) * 32], (epoch + 1) * 8);
        asm volatile("fence.proxy.async.global;" ::: "memory");
#pragma unroll 1
        for (int i = 0; i < 15; i++) {
          const int kblk = 14 * kh + (int)((KORDER >> (4 * i)) & 15);
          const int j = i < 7 ? i : i - 7, sl = j + (j >= 4);
          if (i == HPOS) {
            mbar_wait(BAR(emptyP, 7));
            bulk_load(sbase + 4 * SLOT, &scr->LN[(rb2 * 8 + 2 * nq) * 1024 + kh * 512], 8192, BAR(hbar, 0));
            bulk_load(sbase + 4 * SLOT + 8192, &scr->LN[(rb2 * 8 + 2 * nq + 1) * 1024 + kh * 512], 8192, BAR(hbar, 0));
          }
          if (i == 14) break;
          mbar_wait(i < 7 ? BAR(empty1, 17 + 2 * sl) : BAR(empty2, j));
          tma3(sbase + sl * SLOT, &tmD, BAR(full2, i), 0, 64 * kblk, 2 * nq);
        }
      }
    } else if (warp == 10) {
      bar_sync(NB_LN, 288);
      if (lane == 0) {
        PROFP(0);
        red_release(&scr->cnt[(C_LN + rb) * 32]);
        PROFP(1);
        wait_counter(&scr->cnt[(C_LN + rb) * 32], (epoch + 1) * 8);
        asm volatile("fence.proxy.async.global;" ::: "memory");
        PROFP(2);
#pragma unroll 1
        for (int kb = NLL; kb < 8; kb++) {
          if (2 * kb >= ALEAD) mbar_wait(BAR(empty1, 2 * kb - ALEAD));
          bulk_load(sbase + kb * SLOT, &scr->LN[(rb * 8 + kb) * 1024], 16384, BAR(fullA, kb));
        }
#pragma unroll 1
        for (int s = 0; s < 14; s++) {
          const int kblk = 14 * kh + (int)((KORDER >> (4 * s)) & 15);
          if (s == 0 || s == 8 || s == 11) {
            if (s != 11) PROFP(3 + (s >> 2));
            mbar_wait(BAR(hint, s == 0 ? 0 : s == 8 ? 1 : 2), 0);
            if (s != 11) PROFP(4 + (s >> 2));
          }
          const int j = s < 7 ? s : s - 7;
          mbar_wait(s < 7 ? BAR(empty1, 24 + s + (s == 0) + (s >= 4)) : BAR(emptyP, j));
          bulk_load_mc(sbase + (j ? 7 + j : 4) * SLOT + rk * 8192, &scr->P[(rb2 * 28 + kblk) * 1024 + rk * 512], 8192, BAR(fullP, s));
        }
        PROFP(7);
      }
    } else {
      if (lane == 0) {
        mbar_wait(BAR(tbar, 0));
        l2_prefetch(wg_raw + (size_t)c * 5376, 5376);
        l2_prefetch(wu_raw + (size_t)c * 5376, 5376);
        mbar_wait(BAR(sig, PF2_SIG), 0);
        l2_prefetch(wg_raw + 688128 + (size_t)c * 8960, 8960);
        l2_prefetch(wu_raw + 688128 + (size_t)c * 8960, 8960);
      }
      mbar_wait(BAR(fullA, 4), 0);
      if (lane == 0) l2_prefetch(wd_raw + (size_t)c * 14336, 14336);
      {
        const uint32_t tag = (epoch + 1) & 1;
        uint4 v0, v1, v2;
        int it = 0;
        while (true) {
          v0 = ld_b128(&scr->ST[rb * 64 + lane]);
          v1 = ld_b128(&scr->ST[rb * 64 + 32 + lane]);
          v2 = ld_b128(&scr->ST[rb2 * 64 + 32 * kh + lane]);
          if (!__any_sync(0xffffffffu, ((v0.x ^ tag) | (v1.x ^ tag) | (v2.x ^ tag)) & 1u)) break;
          if (++it > SPIN_LIMIT) { die(); break; }
        }
        sts4(sstat + lane * 16, v0.x & ~1u, v0.y, v0.z, v0.w);
        sts4(sstat + 512 + lane * 16, v1.x & ~1u, v1.y, v1.z, v1.w);
        sts4(sstat + 1024 + lane * 16, v2.x & ~1u, v2.y, v2.z, v2.w);
        mbar_arrive(BAR(sbar, 0));
      }
      if (lane == 0) {
        mbar_wait(BAR(empty1, XTRIG));
        int it = 0;
        while ((int)(ld_relaxed(&scr->cnt[(C_PX + rb2) * 32 + kh]) - (epoch + 1) * 32) < 0) {
          if (++it > SPIN_LIMIT) { die(); break; }
        }
        mbar_arrive(BAR(hint, 0));
        mbar_wait(BAR(emptyP, HTRIG));
        uint32_t done = 0;
        while (done != 3) {
          uint2 v;
          asm volatile("ld.relaxed.gpu.global.v2.u32 {%0,%1}, [%2];" : "=r"(v.x), "=r"(v.y) : "l"(&scr->cnt[(C_PY + rb2) * 32 + 2 * kh]) : "memory");
          if (!(done & 1) && (int)(v.x - (epoch + 1) * 16) >= 0) { done |= 1; mbar_arrive(BAR(hint, 1)); }
          if (!(done & 2) && (int)(v.y - (epoch + 1) * 16) >= 0) { done |= 2; mbar_arrive(BAR(hint, 2)); }
          if (++it > SPIN_LIMIT) { die(); break; }
        }
      }
    }
  } else {
    const int warp = __shfl_sync(0xffffffffu, tid >> 5, 0);
    const int g = lane >> 2, t = lane & 3;
    const uint32_t tk = clock32();
    PROF(0);
    PROFG(14);
    uint4 fa[4], fb[4], tw[6];
#pragma unroll
    for (int i = 0; i < 4; i++) fa[i] = ldg_ca4(&tab->fa[i][lane][0]);
#pragma unroll
    for (int i = 0; i < 6; i++) tw[i] = ldg_ca4(&tab->tw1[i][lane][0]);
#pragma unroll
    for (int i = 0; i < 4; i++) fb[i] = ldg_ca4(&tab->fb[i][lane][0]);
#pragma unroll
    for (int i = 0; i < 4; i++) {
      const int r = i >> 1, ch = (i & 1) * 32 + lane;
      cp_async16(sbase + SM_X + (2 * warp + r) * 1024 + ((ch ^ ((ch >> 3) & 1)) * 16),
                 x + (size_t)(c + 128 * (2 * warp + r)) * 512 + ch * 8);
    }
    asm volatile("cp.async.commit_group;" ::: "memory");
    asm volatile("barrier.cluster.arrive.relaxed.aligned;" ::: "memory");
    uint32_t rbar;
    asm volatile("mapa.shared::cluster.u32 %0, %1, %2;" : "=r"(rbar) : "r"(sbar), "r"(rk ^ 1));
#define RBAR(field, i) (rbar + (uint32_t)offsetof(Bars, field) + 8u * (i))
    {
      const int ln = (tid >> 1) & 31, lg = ln >> 2, lt = ln & 3, i = 4 * (tid >> 6) + 2 * (tid & 1);
      const int kidx = lt + 8 * (i >> 3), nidx = 4 * ((i >> 1) & 3) + (lg >> 1);
      const uint32_t a0 = cfrag<2048>((c + 128 * kidx) * nidx, lg & 1), a1 = cfrag<2048>((c + 128 * (kidx + 4)) * nidx, lg & 1);
      const uint32_t b0 = cfrag<2048>(-(c + 128 * nidx) * kidx, lg & 1), b1 = cfrag<2048>(-(c + 128 * nidx) * (kidx + 4), lg & 1);
      asm volatile("st.shared.v2.u32 [%0], {%1,%2};" ::"r"(sbase + SM_FC + tid * 8), "r"(a0), "r"(a1) : "memory");
      asm volatile("st.shared.v2.u32 [%0], {%1,%2};" ::"r"(sbase + SM_FC + 2048 + tid * 8), "r"(b0), "r"(b1) : "memory");
    }
    bar_sync(NB_CONS, 256);
    uint4 fc[4];
#pragma unroll
    for (int i = 0; i < 4; i++) fc[i] = lds4(sbase + SM_FC + i * 512 + lane * 16);
    asm volatile("cp.async.wait_group 0;" ::: "memory");
    __syncwarp();
    bar_arrive(NB_INIT, 384);
    PROF(13);
    uint32_t tag, ones;
    uint4 q[4], o[4];
    {
      uint32_t v[2][8];
#pragma unroll
      for (int r = 0; r < 2; r++)
#pragma unroll
        for (int ks = 0; ks < 2; ks++) {
          const int ch = 32 * ks + 2 * (lane & 15) + (lane >> 4);
          asm volatile("ldmatrix.sync.aligned.m8n8.x4.trans.shared.b16 {%0,%1,%2,%3}, [%4];"
                       : "=r"(v[r][4 * ks]), "=r"(v[r][4 * ks + 1]), "=r"(v[r][4 * ks + 2]), "=r"(v[r][4 * ks + 3])
                       : "r"(sbase + SM_X + (2 * warp + r) * 1024 + ((ch ^ ((ch >> 3) & 1)) * 16)) : "memory");
        }
      float sq[2];
#pragma unroll
      for (int r = 0; r < 2; r++) {
        float s0 = 0.f, s1 = 0.f;
#pragma unroll
        for (int i = 0; i < 8; i++) {
          const float lo = bf_lo(v[r][i]), hi = u2f(v[r][i] & 0xffff0000u);
          s0 = fmaf(lo, lo, s0);
          s1 = fmaf(hi, hi, s1);
        }
        sq[r] = s0 + s1;
      }
      {
        float w = ((lane & 1) ? sq[1] : sq[0]) + __shfl_xor_sync(0xffffffffu, (lane & 1) ? sq[0] : sq[1], 1);
        w += __shfl_xor_sync(0xffffffffu, w, 2);
        w = sum_groups(w);
        const float o2 = __shfl_xor_sync(0xffffffffu, w, 1);
        sq[0] = (lane & 1) ? o2 : w;
        sq[1] = (lane & 1) ? w : o2;
      }
#pragma unroll
      for (int r = 0; r < 2; r++) {
        float dd[2][4], ee[2][4];
#pragma unroll
        for (int nt = 0; nt < 2; nt++) {
          mma_az(dd[nt], fa[0], v[r][2 * nt], v[r][2 * nt + 1]);
          mma_a(dd[nt], fa[1], v[r][4 + 2 * nt], v[r][5 + 2 * nt]);
          mma_az(ee[nt], fa[2], v[r][2 * nt], v[r][2 * nt + 1]);
          mma_a(ee[nt], fa[3], v[r][4 + 2 * nt], v[r][5 + 2 * nt]);
        }
        float mean = (dd[0][0] + dd[0][1]) + (dd[1][0] + dd[1][1]);
        mean += __shfl_xor_sync(0xffffffffu, mean, 1);
        mean += __shfl_xor_sync(0xffffffffu, mean, 2);
        mean = __shfl_sync(0xffffffffu, mean, 0) * (1.f / 512.f);
        const float rs = rsqrtf(fmaxf(fmaf(-mean, mean, sq[r] * (1.f / 512.f)), 0.f) + 1e-5f);
        float acc[4][4];
#pragma unroll
        for (int nt = 0; nt < 2; nt++) {
          const float (&d)[4] = dd[nt];
          const float (&e)[4] = ee[nt];
          const uint4 &ka = tw[2 * nt], &kb = tw[2 * nt + 1], &kc = tw[4 + nt];
          const uint32_t a0 = pack2(d[0] * u2f(ka.x) + d[2] * u2f(ka.y), d[1] * u2f(kb.x) + d[3] * u2f(kb.y));
          const uint32_t a2 = pack2(d[0] * u2f(ka.z) + d[2] * u2f(ka.w), d[1] * u2f(kb.z) + d[3] * u2f(kb.w));
          const uint32_t a1 = pack2(e[0] * u2f(kc.x) + e[2] * u2f(kc.y), e[1] * u2f(kc.z) + e[3] * u2f(kc.w));
          const uint32_t a3 = pack2(e[2] * u2f(kc.x) - e[0] * u2f(kc.y), e[3] * u2f(kc.z) - e[1] * u2f(kc.w));
          const uint32_t dc = pack2(fmaf(mean, -32.f, d[0]), fmaf(mean, -32.f, d[1]));
          const uint32_t h0 = g == 0 ? dc : a0, h2 = g == 0 ? 0u : a2;
          if (nt == 0) {
            mma16816_z(acc[0], a0, a1, a2, a3, fb[2 * nt].x, fb[2 * nt].y);
            mma16816_z(acc[1], a0, a1, a2, a3, fb[2 * nt].z, fb[2 * nt].w);
            mma16816_z(acc[2], h0, a1, h2, a3, fb[2 * nt + 1].x, fb[2 * nt + 1].y);
            mma16816_z(acc[3], h0, a1, h2, a3, fb[2 * nt + 1].z, fb[2 * nt + 1].w);
          } else {
            mma16816(acc[0], a0, a1, a2, a3, fb[2 * nt].x, fb[2 * nt].y);
            mma16816(acc[1], a0, a1, a2, a3, fb[2 * nt].z, fb[2 * nt].w);
            mma16816(acc[2], h0, a1, h2, a3, fb[2 * nt + 1].x, fb[2 * nt + 1].y);
            mma16816(acc[3], h0, a1, h2, a3, fb[2 * nt + 1].z, fb[2 * nt + 1].w);
          }
        }
#pragma unroll
        for (int h = 0; h < 2; h++) {
          const int j = 2 * warp + r, m = 2 * t + h;
          sts4(sbase + SM_E + ((j * 8 + m) * 8 + (g ^ (2 * t) ^ (2 * (j & 3)))) * 16,
               pack2(acc[h][0] * rs, acc[h][1] * rs), pack2(acc[h][2] * rs, acc[h][3] * rs),
               pack2(acc[2 + h][0] * rs, acc[2 + h][1] * rs), pack2(acc[2 + h][2] * rs, acc[2 + h][3] * rs));
        }
      }
      if (tid == 0) PROFP(12);
      bar_sync(NB_RDY, 384);
      if (tid == 0) PROFP(13);
      const uint32_t ea = sbase + SM_E + ((t * 8 + warp) * 8 + (g ^ (warp & 6) ^ (2 * t))) * 16;
      lds_frag(q[0], q[1], ea, ea + 4096);
      lds_frag(q[2], q[3], ea + 8192, ea + 12288);
      asm volatile("ld.shared.u32 %0, [%1];" : "=r"(tag) : "r"(BAR(epoch, 0)) : "memory");
      ones = ~(tag >> 31);
      tag = (tag + 1) & 1;
      cdft16(q, fc, o);
#pragma unroll
      for (int vv = 0; vv < 4; vv++) {
        o[vv].y &= ~1u;
        o[vv].z = (o[vv].z & ~1u) | (tag ^ 1);
        st_tag(&scr->Z1[(((4 * vv + t) * 8 + warp) * 128 + c) * 8 + g], o[vv], tag);
      }
    }
    PROF(1);
    asm volatile("setmaxnreg.inc.sync.aligned.u32 224;");
    {
      uint4* const zp = &scr->Z1[(c * 128 + 8 * t + warp) * 8 + g];
      const uint32_t tst = clock32();
      mbar_wait(BAR(tbar, 0), 0);
      if (tid == 0) PROFP(14);
      uint4 f2[4], g2[4];
#pragma unroll
      for (int i = 0; i < 4; i++) {
        f2[i] = lds4(TOFF(f2) + warp * 2048 + i * 512);
        g2[i] = lds4(TOFF(g2) + warp * 2048 + i * 512);
      }
      const uint4 f8 = lds4(TOFF(f8)), g8 = lds4(TOFF(g8));
      asm volatile("barrier.cluster.wait.aligned;" ::: "memory");
      spin_until(tst + POLL_DELAY);
      spin_until(tk + TABS1);
      ld_tag4_issue<256>(q, zp);
      float wfr[16], wfi[16];
      {
        const float nyq = ((c & 7) == 7 && g == 0) ? 0.5f : 1.f;
        uint32_t wa = sbase + SM_W + (16 * warp + t) * 80 + ((2 * (c >> 3) + 2) & 15) - 2;
        asm volatile("" : "+r"(wa));
        const uint32_t wb[3] = {wa + 2 * (g == 0 ? 16 : g), wa + 2 * g, wa - 2 * g};
#pragma unroll
        for (int i = 0; i < 16; i++) {
          const int ci = i >> 3, dd = (i >> 2) & 1, e = i & 3;
          const uint32_t a = wb[e < 2 ? e : 2] + (ci * 8 + 4 * dd) * 80 + (e == 0 ? 0 : e == 1 ? 16 : e == 2 ? 64 : 48);
          wfr[i] = bf_lo(lds_u16(a)) * (e == 2 ? nyq : 1.f);
          wfi[i] = bf_lo(lds_u16(a + 10240)) * (e == 2 ? nyq : 1.f);
        }
      }
      PROF(2);
      ld_tag4_finish<256>(q, zp, tag);
      if (tid == 0) PROFP(30);
      if (lane == 0) mbar_arrive(BAR(sig, 0));
#pragma unroll
      for (int i = 0; i < 4; i++) q[i].z &= ~1u;
      reg_frag(q, ones);
      cdft16(q, f2, o);
      const uint32_t e2 = sbase + SM_E2;
#pragma unroll
      for (int vv = 0; vv < 4; vv++)
        sts4(e2 + ((warp * 16 + 4 * vv + t) * 8 + (g ^ (2 * t) ^ (2 * (warp & 3)))) * 16, o[vv].x, o[vv].y, o[vv].z, o[vv].w);
      bar_sync(NB_CONS, 256);
      uint32_t ad[2], res[2][2][4];
#pragma unroll
      for (int ci = 0; ci < 2; ci++) {
        const int cc = 2 * warp + ci;
        ad[ci] = e2 + ((t * 16 + cc) * 8 + (g ^ (2 * (cc & 3)) ^ (2 * t))) * 16;
        lds_frag(q[2 * ci], q[2 * ci + 1], ad[ci], ad[ci] + 8192);
      }
#pragma unroll
      for (int ci = 0; ci < 2; ci++)
#pragma unroll
        for (int p = 0; p < 2; p++) {
          uint32_t y[2][2];
#pragma unroll
          for (int vv = 0; vv < 2; vv++) {
            float d[4];
            mma_az(d, q[2 * ci + p], word(f8, 2 * vv), word(f8, 2 * vv + 1));
#pragma unroll
            for (int rr = 0; rr < 2; rr++) {
              const float fr = wfr[ci * 8 + vv * 4 + 2 * p + rr], fi = wfi[ci * 8 + vv * 4 + 2 * p + rr];
              y[vv][rr] = pack2(d[2 * rr] * fr - d[2 * rr + 1] * fi, d[2 * rr] * fi + d[2 * rr + 1] * fr);
            }
          }
#pragma unroll
          for (int vv = 0; vv < 2; vv++) {
            float d[4];
            mma16816_z(d, y[0][0], y[0][1], y[1][0], y[1][1], word(g8, 2 * vv), word(g8, 2 * vv + 1));
            res[ci][vv][2 * p] = pack2(d[0], d[1]);
            res[ci][vv][2 * p + 1] = pack2(d[2], d[3]);
          }
        }
#pragma unroll
      for (int i = 0; i < 4; i++)
        sts4(ad[i >> 1] + (i & 1) * 8192, res[i >> 1][i & 1][0], res[i >> 1][i & 1][1], res[i >> 1][i & 1][2], res[i >> 1][i & 1][3]);
      bar_sync(NB_CONS, 256);
      const uint32_t eb = e2 + ((warp * 16 + t) * 8 + (g ^ (2 * t) ^ (2 * (warp & 3)))) * 16;
      lds_frag(q[0], q[1], eb, eb + 512);
      lds_frag(q[2], q[3], eb + 1024, eb + 1536);
      cdft16(q, g2, o);
#pragma unroll
      for (int vv = 0; vv < 4; vv++) {
        o[vv].y &= ~1u;
        o[vv].z = (o[vv].z & ~1u) | tag;
        st_tag(zp + vv * 256, o[vv], tag);
      }
    }
    PROF(3);
    {
      const uint4* const zp = &scr->Z1[((t * 8 + warp) * 128 + c) * 8 + g];
      const uint32_t tst = clock32();
      uint4 gb[4], ga[4], gc[4], tw[4];
      uint2 xr[2][4];
      uint2* lnp[2];
#pragma unroll
      for (int r = 0; r < 2; r++) {
        const int row = 16 * f + 2 * warp + r;
        lnp[r] = reinterpret_cast<uint2*>(&scr->LN[(rb * 8 + (g >> 2)) * 1024 + row * 8 + ((2 * (g & 3) + (t >> 1)) ^ (row & 7))]) + (t & 1);
        asm volatile("" : "+l"(lnp[r]));
      }
#pragma unroll
      for (int i = 0; i < 4; i++) {
        gc[i] = lds4(sbase + SM_FC + 2048 + i * 512 + lane * 16);
        gb[i] = lds4(TOFF(gb) + i * 512);
        ga[i] = lds4(TOFF(ga) + i * 512);
        tw[i] = lds4(TOFF(tw3) + i * 512);
        const int ch = 2 * (g + 8 * i) + (t >> 1);
#pragma unroll
        for (int r = 0; r < 2; r++) xr[r][i] = lds2(sbase + SM_X + (2 * warp + r) * 1024 + ((ch ^ ((ch >> 3) & 1)) * 16) + (t & 1) * 8);
      }
      PROF(4);
      spin_until(tst + POLL_DELAY2);
      ld_tag4_issue<32768>(q, zp);
      ld_tag4_finish<32768, true>(q, zp, tag);
      if (tid == 0) PROFP(31);
      if (lane == 0) mbar_arrive(BAR(sig, 1));
      reg_frag(q, ones);
      cdft16(q, gc, o);
#pragma unroll
      for (int vv = 0; vv < 4; vv++)
        sts4(sbase + SM_E + (((4 * vv + t) * 8 + warp) * 8 + (g ^ (warp & 6) ^ (2 * t))) * 16, o[vv].x, o[vv].y, o[vv].z, o[vv].w);
      if (tid == 0) PROFP(8);
      bar_sync(NB_CONS, 256);
      if (tid == 0) PROFP(9);
      uint32_t hv[2][8];
      const float mk = t == 0 ? 0.f : 1.f;
#pragma unroll
      for (int r = 0; r < 2; r++) {
        const int j = 2 * warp + r;
        uint4 u[2];
#pragma unroll
        for (int h = 0; h < 2; h++) u[h] = lds4(sbase + SM_E + ((j * 8 + 2 * t + h) * 8 + (g ^ (2 * t) ^ (2 * (j & 3)))) * 16);
        const uint32_t bp[4][2] = {{u[0].x, u[1].x & ones}, {u[0].y & ones, u[1].y}, {u[0].z, u[1].z & ones}, {u[0].w & ones, u[1].w}};
        float y[2][2][4];
#pragma unroll
        for (int i = 0; i < 2; i++) {
          float lo[4], hi[4], e[4];
          mma_az(lo, gb[2 * i], bp[0][0], bp[0][1]);
          mma_az(hi, gb[2 * i + 1], bp[2][0], bp[2][1]);
          mma_az(e, gb[2 * i], bp[1][0], bp[1][1]);
          mma_a(e, gb[2 * i + 1], bp[3][0], bp[3][1]);
          const uint4 &ka = tw[2 * i], &kb = tw[2 * i + 1];
          const float tr0 = fmaf(hi[0], mk, lo[0]), ti0 = fmaf(hi[2], mk, lo[2]);
          const float tr1 = lo[1] + hi[1], ti1 = lo[3] + hi[3];
          const float vr0 = tr0 * u2f(ka.x) - ti0 * u2f(ka.y), vi0 = tr0 * u2f(ka.y) + ti0 * u2f(ka.x);
          const float vr1 = tr1 * u2f(ka.z) - ti1 * u2f(ka.w), vi1 = tr1 * u2f(ka.w) + ti1 * u2f(ka.z);
          const uint32_t b0 = pack2(t == 0 ? hi[0] : vr0, vr1), b1 = pack2(t == 0 ? vr0 : vi0, vi1);
          const uint32_t b2 = pack2(e[0] * u2f(kb.x) - e[2] * u2f(kb.y), e[1] * u2f(kb.z) - e[3] * u2f(kb.w));
          const uint32_t b3 = pack2(e[0] * u2f(kb.y) + e[2] * u2f(kb.x), e[1] * u2f(kb.w) + e[3] * u2f(kb.z));
#pragma unroll
          for (int mt = 0; mt < 2; mt++) {
            mma_az(y[mt][i], ga[2 * mt], b0, b1);
            mma_a(y[mt][i], ga[2 * mt + 1], b2, b3);
          }
        }
#pragma unroll
        for (int i = 0; i < 4; i++) {
          hv[r][2 * i] = hadd2_bf16(xr[r][i].x, pack2(y[i >> 1][0][2 * (i & 1)], y[i >> 1][0][2 * (i & 1) + 1]));
          hv[r][2 * i + 1] = hadd2_bf16(xr[r][i].y, pack2(y[i >> 1][1][2 * (i & 1)], y[i >> 1][1][2 * (i & 1) + 1]));
        }
      }
      if (tid == 0 && hv[0][0] != 0x12345 && hv[1][7] != 0x12345) PROFP(10);
      float mean[2];
      uint32_t mb[2];
#pragma unroll
      for (int r = 0; r < 2; r++) {
        mean[r] = sum_groups(quad_sum(hv[r])) * (1.f / 512.f);
        mb[r] = pack2(mean[r], mean[r]);
      }
#pragma unroll
      for (int i = 0; i < 4; i++)
#pragma unroll
        for (int r = 0; r < 2; r++) {
          hv[r][2 * i] = hsub2_bf16(hv[r][2 * i], mb[r]);
          hv[r][2 * i + 1] = hsub2_bf16(hv[r][2 * i + 1], mb[r]);
          st_tag8(lnp[r] + i * 4096, hv[r][2 * i], hv[r][2 * i + 1], i == 0 ? tag : (hv[r][2 * i] & 1u));
        }
      if (tid == 0) PROFP(11);
      bar_arrive(NB_LN, 288);
      const uint32_t ones2 = ~(lds2(BAR(epoch, 0)).x >> 31);
      float rstd[2];
#pragma unroll
      for (int r = 0; r < 2; r++) {
        hv[r][0] &= ones2;
        rstd[r] = row_rstd(hv[r], mean[r] - bf_lo(mb[r]));
      }
      if (lane == 0)
        st_tag(&scr->ST[rb * 64 + 8 * f + warp], make_uint4(mb[0] << 16, __float_as_uint(rstd[0]), mb[1] << 16, __float_as_uint(rstd[1])), tag);
    }
    PROF(5);
    const int wgi = warp >> 2, wq = warp & 3;
    uint4* const pbase = &scr->P[rb * 28 * 1024 + warp * 128 + lane];
    const uint32_t a_lo0 = desc_lo(sbase + wgi * 8192, 16);
    const uint32_t ebar = lane == 0 ? BAR(empty1, 0) : RBAR(empty1, 0);
    float r0, r1;
    uint4 px[8], py[6];
    const int rh = wgi ^ kh ^ 1;
    const uint4* const psrc = &scr->P[(rb2 * 28 + 14 * kh) * 1024 + (4 * rh + wq) * 128 + lane];
    const uint32_t pa0 = sbase + (4 * rh + wq) * 2048;
    uint4 pf[3][4];
    uint32_t rdy = 0;
    {
      float acc[128];
#pragma unroll
      for (int i = 0; i < 128; i++) acc[i] = 0.f;
      const uint32_t b_lo0 = desc_lo(sbase + 8 * SLOT, 4096);
      const uint32_t t3 = clock32();
      if (WARM) {
        wg_fence();
#pragma unroll
        for (int i = 0; i < WARM; i++) wgmma_n256(acc, desc64(a_lo0 + 6 * 1024, HI128), desc64(b_lo0, HI128));
        wg_commit();
      }
      const uint4* const ap = &scr->LN[rb * 8 * 1024 + wgi * 512 + (tid & 127)];
      uint4 av[NLL][4];
      spin_until(t3 + POLL_DELAY3);
#pragma unroll
      for (int kb = 0; kb < NLL; kb++) ld_tag4_issue<128>(av[kb], ap + kb * 1024);
      bar_sync(NB_CONS, 256);
      uint32_t slot = 2;
      auto stage_x = [&](int kb, int hh) {
        if (LAGX && hh == ((16 - LAGX) & 1) && kb == ((16 - LAGX) >> 1) && wgi == 1) bar_sync(NB_LAG, 256);
        mbar_wait(BAR(full1, 2 * kb + hh));
        const uint32_t al = a_lo0 + kb * 1024 + hh * 4, bl = b_lo0 + slot * 1024;
        wg_fence();
        wgmma_n256(acc, desc64(al, HI128), desc64(bl, HI128), (kb | hh) != 0 ? 1 : ~ones);
        wgmma_n256(acc, desc64(al + 2, HI128), desc64(bl + 128, HI128));
        wg_commit();
        if (LAGX && hh == 1 && kb == 7 && wgi == 0) bar_arrive(NB_LAG, 256);
        wg_wait<1>();
        if ((kb | hh) != 0 && lane < 2) mbar_arrive_remote(ebar + 8 * (2 * kb + hh - 1));
        if (++slot == 6) slot = 0;
      };
#pragma unroll
      for (int kb = 0; kb < NLL; kb++) {
        ld_tag4_finish<128, true>(av[kb], ap + kb * 1024, tag);
#pragma unroll
        for (int i = 0; i < 4; i++)
          sts4(sbase + kb * SLOT + wgi * 8192 + ((tid & 127) + 128 * i) * 16, av[kb][i].x, av[kb][i].y, av[kb][i].z, av[kb][i].w);
        asm volatile("fence.proxy.async.shared::cta;" ::: "memory");
        bar_sync(NB_WG + wgi, 128);
        if (kb > 0) stage_x(kb - 1, 1);
        if (kb == 0) PROF(6);
        stage_x(kb, 0);
      }
      stage_x(NLL - 1, 1);
#pragma unroll 1
      for (int kb = NLL; kb < 8; kb++) {
        mbar_wait(BAR(fullA, kb));
        stage_x(kb, 0);
        stage_x(kb, 1);
      }
      mbar_wait(BAR(sbar, 0), 0);
      r0 = __uint_as_float(lds2(sstat + (16 * warp + g) * 8).y);
      r1 = __uint_as_float(lds2(sstat + (16 * warp + g + 8) * 8).y);
      wg_wait<0>();
      if (lane < 2) mbar_arrive_remote(ebar + 8 * 15);
      PROF(7);
      make_p<8, false>(acc, r0, r1, px, pbase, 0, tag);
    }
    PROF(8);
    {
      float acc[96];
#pragma unroll
      for (int i = 0; i < 96; i++) acc[i] = 0.f;
      const uint32_t b_lo0 = desc_lo(sbase + 8 * SLOT, 2048);
      uint4* const pdst = pbase + ((7 * f + 3 * (f & 1)) >> 1) * 1024;
      auto stage_y = [&](int k) {
        if (LAGY && k == 16 - LAGY && wgi == 1) bar_sync(NB_LAG, 256);
        mbar_wait(BAR(full1, 16 + k));
        const uint32_t al = a_lo0 + (k >> 1) * 1024 + (k & 1) * 4, bl = b_lo0 + (k & 7) * 768;
        wg_fence();
        wgmma_n192(acc, desc64(al, HI128), desc64(bl, HI64));
        wgmma_n192(acc, desc64(al + 2, HI128), desc64(bl + 64, HI64));
        wg_commit();
      };
#pragma unroll
      for (int k = 0; k < 4; k++) {
        stage_y(k);
        st_tag(pdst + (k >> 1) * 1024 + (k & 1) * 64, px[2 * k], tag);
        st_tag(pdst + (k >> 1) * 1024 + (k & 1) * 64 + 32, px[2 * k + 1], tag);
        if (k == 3 && lane == 0) red_relaxed(&scr->cnt[(C_PX + rb) * 32 + (f >> 2)]);
        wg_wait<1>();
        if (k != 0 && lane < 2) mbar_arrive_remote(ebar + 8 * (15 + k));
      }
#pragma unroll 1
      for (int k = 4; k < 16; k++) {
        stage_y(k);
        if (LAGY && k == 15 && wgi == 0) bar_arrive(NB_LAG, 256);
        wg_wait<1>();
        if (lane < 2) mbar_arrive_remote(ebar + 8 * (15 + k));
      }
      rdy = __all_sync(0xffffffffu, mbar_test(BAR(fullP, 0)) & mbar_test(BAR(full2, 0)) & mbar_test(BAR(fullP, 1)));
      if (rdy) {
#pragma unroll
        for (int kk = 0; kk < 4; kk++) pf[0][kk] = lds4(pa0 + 4 * SLOT + kk * 512 + lane * 16);
      }
      wg_wait<0>();
      if (lane < 2) mbar_arrive_remote(ebar + 8 * 31);
      PROF(9);
      make_p<6, true, 0, REDPOS>(acc, r0, r1, py, pbase, 14 * f + ((f & 1) ? 0 : 8), tag);
      if (lane == 0) red_relaxed(&scr->cnt[(C_PY + rb) * 32 + (f >> 1)]);
      make_p<6, true, REDPOS, 6>(acc, r0, r1, py, pbase, 14 * f + ((f & 1) ? 0 : 8), tag);
    }
    PROF(10);
    {
      float acc[64];
      const uint32_t b2_lo0 = desc_lo(sbase, 8192);
      const uint32_t pbar = ebar + (uint32_t)(offsetof(Bars, emptyP) - offsetof(Bars, empty1));
      if (!rdy) {
        mbar_wait(BAR(fullP, 0));
#pragma unroll
        for (int kk = 0; kk < 4; kk++) pf[0][kk] = lds4(pa0 + 4 * SLOT + kk * 512 + lane * 16);
      }
#pragma unroll
      for (int s = 0; s < 14; s++) {
        uint4 (&a)[4] = pf[s % 3];
        ld_tag4_finish<32>(a, psrc + (int)((KORDER >> (4 * s)) & 15) * 1024, tag);
        if (s < 8 && lane < (s < 7 ? 2 : 1)) mbar_arrive_remote(pbar + 8 * s);
        if (s >= 2) {
          wg_wait<1>();
          if (s <= 8 && lane == 0) mbar_arrive(BAR(empty2, s - 2));
        }
        if (!rdy) {
          if (s < 13) mbar_wait(BAR(fullP, s + 1));
          mbar_wait(BAR(full2, s));
        }
        if (tid == 0) PROFP(16 + s);
        if (s == 14 - LAG2 && wgi == 1) {
          const float m0 = __uint_as_float(lds2(sstat + 1024 + (16 * wq + g) * 8).x);
          const float m1 = __uint_as_float(lds2(sstat + 1024 + (16 * wq + g + 8) * 8).x);
          const uint32_t hb = sbase + 4 * SLOT + (16 * wq + (lane & 15)) * 128;
          wg_wait<0>();
          mbar_wait(BAR(hbar, 0));
#pragma unroll
          for (int i = 0; i < 8; i++) {
            uint32_t h[4];
            asm volatile("ldmatrix.sync.aligned.m8n8.x4.shared.b16 {%0,%1,%2,%3}, [%4];"
                         : "=r"(h[0]), "=r"(h[1]), "=r"(h[2]), "=r"(h[3])
                         : "r"(hb + (i >> 2) * 8192 + (((2 * (i & 3) + (lane >> 4)) ^ (lane & 7)) * 16)) : "memory");
            const uint32_t mk = ((t & 1) == 0 && nq == 0) ? ~1u : ~0u;
#pragma unroll
            for (int e = 0; e < 4; e++) {
              acc[8 * i + 2 * e] += bf_lo(h[e] & mk) + ((e & 1) ? m1 : m0);
              acc[8 * i + 2 * e + 1] += __uint_as_float(h[e] & 0xffff0000u) + ((e & 1) ? m1 : m0);
            }
          }
          bar_sync(NB_LAG, 256);
        }
        const uint32_t bl = b2_lo0 + (uint32_t)((BSLOT >> (4 * s)) & 15) * 1024;
        wg_fence();
        if (s < 13) {
#pragma unroll
          for (int kk = 0; kk < 4; kk++)
            pf[(s + 1) % 3][kk] = lds4(pa0 + (uint32_t)((PSLOT >> (4 * (s + 1))) & 15) * SLOT + kk * 512 + lane * 16);
          rdy = mbar_test(BAR(full2, s + 1));
          if (s < 12) rdy &= mbar_test(BAR(fullP, s + 2));
        }
        if (s == 0) wgmma_rs_n128<0>(acc, a[0].x, a[0].y, a[0].z, a[0].w, desc64(bl, HI128));
        else wgmma_rs_n128<1>(acc, a[0].x, a[0].y, a[0].z, a[0].w, desc64(bl, HI128));
#pragma unroll
        for (int kk = 1; kk < 4; kk++) wgmma_rs_n128<1>(acc, a[kk].x, a[kk].y, a[kk].z, a[kk].w, desc64(bl + kk * 128, HI128));
        wg_commit();
      }
      if (wgi == 0) {
        bar_arrive(NB_LAG, 256);
        uint4* const dst = &scr->Z1[(tid >> 3) * 1024 + (c ^ 4) * 8 + (tid & 7)];
        wg_wait<0>();
        PROF(11);
#pragma unroll
        for (int i = 0; i < 8; i++)
          st_tag(dst + i * 16384, make_uint4(pack2(acc[8 * i], acc[8 * i + 1]), pack2(acc[8 * i + 2], acc[8 * i + 3]) | 1u,
                                           pack2(acc[8 * i + 4], acc[8 * i + 5]), pack2(acc[8 * i + 6], acc[8 * i + 7])), tag);
      } else {
        uint4 pv[2][4];
        const uint4* const xsrc = &scr->Z1[((tid & 127) >> 3) * 1024 + c * 8 + (tid & 7)];
        ld_tag4_issue<16384>(pv[0], xsrc);
        ld_tag4_issue<16384>(pv[1], xsrc + 65536);
        wg_wait<0>();
        PROF(11);
        uint32_t w[32];
#pragma unroll
        for (int i = 0; i < 32; i++) w[i] = pack2(acc[2 * i], acc[2 * i + 1]);
        int it = 0;
#pragma unroll 1
        while (!__all_sync(0xffffffffu, pv[0][0].y & pv[0][1].y & pv[0][2].y & pv[0][3].y & pv[1][0].y & pv[1][1].y & pv[1][2].y & pv[1][3].y & 1u)) {
          ld_tag4_issue<16384>(pv[0], xsrc);
          ld_tag4_issue<16384>(pv[1], xsrc + 65536);
          if (++it > SPIN_LIMIT) { die(); break; }
        }
#pragma unroll
        for (int i = 0; i < 8; i++) {
          const uint4& p = pv[i >> 2][i & 3];
          asm volatile("stmatrix.sync.aligned.m8n8.x4.shared.b16 [%0], {%1,%2,%3,%4};"
                       ::"r"(pa0 + (9 + ((lane >> 3) & 1)) * SLOT + (lane & 7) * 256 + (((2 * i + (lane >> 4)) ^ (lane & 7)) * 16)),
                         "r"(hadd2_bf16(w[4 * i], p.x & ~1u)), "r"(hadd2_bf16(w[4 * i + 1], p.y)), "r"(hadd2_bf16(w[4 * i + 2], p.z)),
                         "r"(hadd2_bf16(w[4 * i + 3], p.w)) : "memory");
        }
        __syncwarp();
        uint4* const dst = reinterpret_cast<uint4*>(out) + (16 * (c >> 4) + 2 * (4 * rh + wq) + (rb2 & 1) + 128 * (lane >> 4)) * 64 + nq * 16 + (lane & 15);
#pragma unroll
        for (int i = 0; i < 8; i++) {
          const int r = 2 * (i & 3) + (lane >> 4);
          dst[i * 256 * 64] = lds4(pa0 + (9 + (i >> 2)) * SLOT + r * 256 + (((lane & 15) ^ r) * 16));
        }
      }
      PROF(12);
      PROFG(15);
    }
  }
#undef BAR
#undef TOFF
#undef RBAR
}

typedef CUresult (*EncodeFn)(CUtensorMap*, CUtensorMapDataType, cuuint32_t, void*, const cuuint64_t*, const cuuint64_t*,
                             const cuuint32_t*, const cuuint32_t*, CUtensorMapInterleave, CUtensorMapSwizzle,
                             CUtensorMapL2promotion, CUtensorMapFloatOOBfill);

}

extern "C" void kernel_launch(void* const* d_in, const int* in_sizes, int n_in, void* d_out, int out_size) {
  (void)in_sizes; (void)n_in; (void)out_size;
  static EncodeFn encode = nullptr;
  static void *tab = nullptr, *scr = nullptr;
  if (!encode) {
    void* fn = nullptr;
    cudaDriverEntryPointQueryResult qr;
    cudaGetDriverEntryPoint("cuTensorMapEncodeTiled", &fn, cudaEnableDefault, &qr);
    encode = (EncodeFn)fn;
    cudaGetSymbolAddress(&tab, g_tab);
    cudaGetSymbolAddress(&scr, g_scr);
    cudaFuncSetAttribute(fused_kernel, cudaFuncAttributeMaxDynamicSharedMemorySize, SMEM_BYTES);
  }
  CUtensorMap tmGX, tmUX, tmGY, tmUY, tmD, tmWR, tmWI;
  const cuuint32_t es[5] = {1, 1, 1, 1, 1};
  auto enc = [&](CUtensorMap* m, void* p, int rank, const cuuint64_t* gd, const cuuint64_t* gs, const cuuint32_t* bd,
                 CUtensorMapSwizzle sw, CUtensorMapL2promotion pr) {
    encode(m, CU_TENSOR_MAP_DATA_TYPE_BFLOAT16, rank, p, gd, gs, bd, es, CU_TENSOR_MAP_INTERLEAVE_NONE, sw, pr,
           CU_TENSOR_MAP_FLOAT_OOB_FILL_NONE);
  };
  {
    const cuuint64_t gd[3] = {64, 512, 28}, gs[2] = {3584, 128};
    const cuuint32_t bd[3] = {64, 32, 2};
    enc(&tmGX, d_in[4], 3, gd, gs, bd, CU_TENSOR_MAP_SWIZZLE_128B, CU_TENSOR_MAP_L2_PROMOTION_L2_256B);
    enc(&tmUX, d_in[5], 3, gd, gs, bd, CU_TENSOR_MAP_SWIZZLE_128B, CU_TENSOR_MAP_L2_PROMOTION_L2_256B);
  }
  {
    const cuuint64_t gd[3] = {32, 512, 56}, gs[2] = {3584, 64};
    const cuuint32_t bd[3] = {32, 32, 3};
    enc(&tmGY, d_in[4], 3, gd, gs, bd, CU_TENSOR_MAP_SWIZZLE_64B, CU_TENSOR_MAP_L2_PROMOTION_L2_128B);
    enc(&tmUY, d_in[5], 3, gd, gs, bd, CU_TENSOR_MAP_SWIZZLE_64B, CU_TENSOR_MAP_L2_PROMOTION_L2_128B);
  }
  {
    const cuuint64_t gd[3] = {64, 1792, 8}, gs[2] = {1024, 128};
    const cuuint32_t bd[3] = {64, 64, 2};
    enc(&tmD, d_in[6], 3, gd, gs, bd, CU_TENSOR_MAP_SWIZZLE_128B, CU_TENSOR_MAP_L2_PROMOTION_L2_256B);
  }
  {
    const cuuint64_t gd[3] = {4112, 8, 16}, gs[2] = {16 * 8224, 8224};
    const cuuint32_t bd[3] = {40, 8, 16};
    enc(&tmWR, d_in[1], 3, gd, gs, bd, CU_TENSOR_MAP_SWIZZLE_NONE, CU_TENSOR_MAP_L2_PROMOTION_NONE);
    enc(&tmWI, d_in[2], 3, gd, gs, bd, CU_TENSOR_MAP_SWIZZLE_NONE, CU_TENSOR_MAP_L2_PROMOTION_NONE);
  }
  fused_kernel<<<NCTA, NTHREADS, SMEM_BYTES>>>((const __nv_bfloat16*)d_in[0], (const Tables*)tab, (Scratch*)scr,
                                               (__nv_bfloat16*)d_out, (const char*)d_in[4], (const char*)d_in[5],
                                               (const char*)d_in[6], tmWR, tmWI, tmGX, tmUX, tmGY, tmUY, tmD);
}
```

```cpp
#include <cuda_runtime.h>
#include <cuda_bf16.h>
#include <cuda.h>
#include <stdint.h>

namespace {

constexpr int NCTA = 128;
constexpr int NTHREADS = 384;
constexpr int SLOT = 16384;
constexpr int SMEM_BYTES = 14 * SLOT + 3072;
constexpr int SPIN_LIMIT = 1 << 22;

struct Scratch {
  uint4 Z1[128 * 1024];
  uint4 LN[16 * 8 * 1024];
  uint4 P[16 * 28 * 1024];
  uint4 ST[1024];
  unsigned cnt[64 * 32];
};
__device__ __align__(1024) Scratch g_scr;

constexpr double ccos(int i, int n) {
  i &= n - 1;
  if (i > n / 2) i = n - i;
  if (4 * i == n) return 0.0;
  const bool neg = 4 * i > n;
  if (neg) i = n / 2 - i;
  const double a = 6.283185307179586476925 * i / n, a2 = a * a;
  double term = 1.0, sum = 1.0;
  for (int k = 1; k < 14; k++) { term *= -a2 / ((2 * k - 1) * (2 * k)); sum += term; }
  return neg ? -sum : sum;
}
constexpr double csin(int i, int n) { return ccos(i - n / 4, n); }
constexpr unsigned fbits(double v, int mant) {
  if (v == 0.0) return 0;
  const unsigned sg = v < 0 ? 1u : 0u;
  if (v < 0) v = -v;
  int e = 127;
  while (v < 1.0) { v *= 2.0; e--; }
  const unsigned m = (unsigned)((v - 1.0) * (double)(1u << mant) + 0.5);
  return (sg << (8 + mant)) + ((unsigned)e << mant) + m;
}
constexpr unsigned pkb(double lo, double hi) { return fbits(lo, 7) | (fbits(hi, 7) << 16); }
constexpr double fa_elem(int mt, int r, int n1) {
  const int k1 = 8 * mt + (r & 7);
  return r < 8 ? ccos(k1 * n1, 32) : k1 == 0 ? ccos(16 * n1, 32) : -csin(k1 * n1, 32);
}
constexpr unsigned cfrag_c(int idx, int n, int ri, double s = 1.0) {
  return ri ? pkb(-s * csin(idx, n), s * ccos(idx, n)) : pkb(s * ccos(idx, n), s * csin(idx, n));
}
struct Tables {
  unsigned fa[4][32][4];
  unsigned fb[4][32][4];
  unsigned tw1[6][32][4];
  unsigned f2[8][4][32][4];
  unsigned g2[8][4][32][4];
  unsigned gb[4][32][4];
  unsigned ga[4][32][4];
  unsigned tw3[4][32][4];
  unsigned f8[32][4], g8[32][4];
};
constexpr int T1_BYTES = 7168, T2_BYTES = 39936;
static_assert(sizeof(Tables) == T1_BYTES + T2_BYTES, "table size");
constexpr Tables make_tables() {
  Tables T = {};
  for (int l = 0; l < 32; l++) {
    const int g = l >> 2, t = l & 3;
    for (int a = 0; a < 2; a++)
      for (int b = 0; b < 2; b++) {
        for (int r = 0; r < 4; r++) {
          const int row = g + 8 * (r & 1), col = 2 * t + 8 * (r >> 1);
          T.fa[2 * a + b][l][r] = pkb(fa_elem(a, row, 16 * b + col), fa_elem(a, row, 16 * b + col + 1));
          T.ga[2 * a + b][l][r] = pkb(fa_elem(b, col, 16 * a + row), fa_elem(b, col + 1, 16 * a + row));
        }
        const double sg = b ? -1.0 : 1.0;
        for (int h = 0; h < 2; h++) {
          const int ri = g & 1, m = 2 * (g >> 1) + h, k2 = b ? 15 - m : m;
          const int pa = (8 * a + 2 * t) * k2, pb = (8 * a + 2 * t + 1) * k2;
          T.fb[2 * a + b][l][2 * h] = ri == 0 ? pkb(ccos(pa, 16), ccos(pb, 16)) : pkb(-sg * csin(pa, 16), -sg * csin(pb, 16));
          T.fb[2 * a + b][l][2 * h + 1] = ri == 0 ? pkb(csin(pa, 16), csin(pb, 16)) : pkb(sg * ccos(pa, 16), sg * ccos(pb, 16));
        }
        const int n2 = 4 * (g >> 1) + 2 * a + (g & 1);
        for (int h = 0; h < 2; h++) {
          const int p = n2 * (b ? 15 - 2 * t - h : 2 * t + h);
          T.gb[2 * a + b][l][2 * h] = pkb(ccos(p, 16), -sg * csin(p, 16));
          T.gb[2 * a + b][l][2 * h + 1] = pkb(csin(p, 16), sg * ccos(p, 16));
          const int k1 = 8 * b + 2 * t + h, q = n2 * (k1 == 0 ? 16 : k1);
          T.tw3[2 * a + b][l][2 * h] = fbits(ccos(q, 512), 23);
          T.tw3[2 * a + b][l][2 * h + 1] = fbits(csin(q, 512), 23);
        }
        const int p = (8 * a + 2 * t + b) * (g == 0 ? 16 : g);
        T.tw1[2 * a + b][l][0] = fbits(g == 0 ? 0.0 : ccos(p, 512), 23);
        T.tw1[2 * a + b][l][1] = fbits(g == 0 ? ccos(p, 512) : csin(p, 512), 23);
        T.tw1[2 * a + b][l][2] = fbits(g == 0 ? 0.0 : -csin(p, 512), 23);
        T.tw1[2 * a + b][l][3] = fbits(g == 0 ? -csin(p, 512) : ccos(p, 512), 23);
        T.tw1[4 + a][l][2 * b] = fbits(ccos((8 * a + 2 * t + b) * (g + 8), 512), 23);
        T.tw1[4 + a][l][2 * b + 1] = fbits(csin((8 * a + 2 * t + b) * (g + 8), 512), 23);
      }
    for (int i = 0; i < 4; i++) {
      const int p8 = (t + 4 * (i & 1)) * (4 * (i >> 1) + (g >> 1));
      T.f8[l][i] = cfrag_c(p8, 8, g & 1);
      T.g8[l][i] = cfrag_c(-p8, 8, g & 1, 1.0 / (1 << 19));
    }
    for (int w = 0; w < 8; w++)
      for (int i = 0; i < 16; i++) {
        const int kidx = t + 4 * (i & 1) + 8 * (i >> 3), nidx = 4 * ((i >> 1) & 3) + (g >> 1);
        T.f2[w][i >> 2][l][i & 3] = cfrag_c((8 * kidx + w) * nidx, 128, g & 1);
        T.g2[w][i >> 2][l][i & 3] = cfrag_c(-(8 * nidx + w) * kidx, 128, g & 1);
      }
  }
  return T;
}
__device__ const __align__(128) Tables g_tab = make_tables();

__device__ __forceinline__ void die() { asm volatile("st.global.u32 [%0], %1;" ::"l"(0ull), "r"(0) : "memory"); }
__device__ __forceinline__ uint32_t s2u(const void* p) { return (uint32_t)__cvta_generic_to_shared(p); }
__device__ __forceinline__ void mbar_init(uint32_t b, int c) { asm volatile("mbarrier.init.shared::cta.b64 [%0], %1;" ::"r"(b), "r"(c)); }
__device__ __forceinline__ void mbar_expect(uint32_t b, int bytes) {
  asm volatile("mbarrier.arrive.expect_tx.shared::cta.b64 _, [%0], %1;" ::"r"(b), "r"(bytes) : "memory");
}
__device__ __forceinline__ void mbar_arrive(uint32_t b) { asm volatile("mbarrier.arrive.shared::cta.b64 _, [%0];" ::"r"(b) : "memory"); }
__device__ __forceinline__ uint32_t mbar_try(uint32_t b, uint32_t parity) {
  uint32_t ok;
  asm volatile("{.reg .pred p; mbarrier.try_wait.parity.shared::cta.b64 p, [%1], %2; selp.u32 %0,1,0,p;}"
               : "=r"(ok) : "r"(b), "r"(parity) : "memory");
  return ok;
}
__device__ __forceinline__ uint32_t mbar_test(uint32_t b) {
  uint32_t ok;
  asm volatile("{.reg .pred p; mbarrier.test_wait.parity.shared::cta.b64 p, [%1], 0; selp.u32 %0,1,0,p;}" : "=r"(ok) : "r"(b) : "memory");
  return ok;
}
__device__ __forceinline__ void mbar_wait(uint32_t b, uint32_t parity = 0) {
  int it = 0;
#pragma unroll 1
  while (!mbar_try(b, parity))
    if (++it > SPIN_LIMIT) { die(); break; }
}
__device__ __forceinline__ void bar_sync(int id, int n) { asm volatile("bar.sync %0, %1;" ::"r"(id), "r"(n) : "memory"); }
__device__ __forceinline__ void bar_arrive(int id, int n) { asm volatile("bar.arrive %0, %1;" ::"r"(id), "r"(n) : "memory"); }
__device__ __forceinline__ void red_release(unsigned* p) { asm volatile("red.release.gpu.global.add.u32 [%0], 1;" ::"l"(p) : "memory"); }
__device__ __forceinline__ void red_relaxed(unsigned* p) { asm volatile("red.relaxed.gpu.global.add.u32 [%0], 1;" ::"l"(p) : "memory"); }
__device__ __forceinline__ unsigned ld_acquire(const unsigned* p) {
  unsigned v;
  asm volatile("ld.acquire.gpu.global.u32 %0, [%1];" : "=r"(v) : "l"(p) : "memory");
  return v;
}
__device__ __forceinline__ unsigned ld_relaxed(const unsigned* p) {
  unsigned v;
  asm volatile("ld.relaxed.gpu.global.u32 %0, [%1];" : "=r"(v) : "l"(p) : "memory");
  return v;
}
__device__ __forceinline__ void wait_counter(const unsigned* p, unsigned target) {
  int it = 0;
  while ((int)(ld_acquire(p) - target) < 0)
    if (++it > SPIN_LIMIT) { die(); break; }
}
__device__ __forceinline__ void sts4(uint32_t a, uint32_t x, uint32_t y, uint32_t z, uint32_t w) {
  asm volatile("st.shared.v4.u32 [%0], {%1,%2,%3,%4};" ::"r"(a), "r"(x), "r"(y), "r"(z), "r"(w) : "memory");
}
__device__ __forceinline__ uint4 lds4(uint32_t a) {
  uint4 v;
  asm volatile("ld.shared.v4.u32 {%0,%1,%2,%3}, [%4];" : "=r"(v.x), "=r"(v.y), "=r"(v.z), "=r"(v.w) : "r"(a) : "memory");
  return v;
}
__device__ __forceinline__ uint32_t pack2(float lo, float hi) {
  uint32_t r;
  asm("cvt.rn.bf16x2.f32 %0, %1, %2;" : "=r"(r) : "f"(hi), "f"(lo));
  return r;
}
__device__ __forceinline__ float bf_lo(uint32_t v) { return __uint_as_float(v << 16); }
__device__ __forceinline__ uint32_t hadd2_bf16(uint32_t a, uint32_t b) {
  uint32_t r;
  asm("add.rn.bf16x2 %0, %1, %2;" : "=r"(r) : "r"(a), "r"(b));
  return r;
}
__device__ __forceinline__ void mma16816(float (&d)[4], uint32_t a0, uint32_t a1, uint32_t a2, uint32_t a3, uint32_t b0, uint32_t b1) {
  asm("mma.sync.aligned.m16n8k16.row.col.f32.bf16.bf16.f32 {%0,%1,%2,%3}, {%4,%5,%6,%7}, {%8,%9}, {%0,%1,%2,%3};"
      : "+f"(d[0]), "+f"(d[1]), "+f"(d[2]), "+f"(d[3])
      : "r"(a0), "r"(a1), "r"(a2), "r"(a3), "r"(b0), "r"(b1));
}
__device__ __forceinline__ void mma16816_z(float (&d)[4], uint32_t a0, uint32_t a1, uint32_t a2, uint32_t a3, uint32_t b0, uint32_t b1) {
  asm("{.reg .f32 z; mov.f32 z, 0f00000000;\n"
      "mma.sync.aligned.m16n8k16.row.col.f32.bf16.bf16.f32 {%0,%1,%2,%3}, {%4,%5,%6,%7}, {%8,%9}, {z,z,z,z};}"
      : "=f"(d[0]), "=f"(d[1]), "=f"(d[2]), "=f"(d[3])
      : "r"(a0), "r"(a1), "r"(a2), "r"(a3), "r"(b0), "r"(b1));
}
template <int N>
__device__ __forceinline__ void cs_frac(int idx, float& c, float& s) {
  int i = ((idx + N / 2) & (N - 1)) - N / 2;
  float a = (float)i * (6.283185307179586f / N);
  c = __cosf(a);
  s = __sinf(a);
}
template <int N>
__device__ __forceinline__ uint32_t cfrag(int idx, int ri) {
  float c, s;
  cs_frac<N>(idx, c, s);
  return ri ? pack2(-s, c) : pack2(c, s);
}
__device__ __forceinline__ uint32_t word(const uint4& v, int e) { return e == 0 ? v.x : e == 1 ? v.y : e == 2 ? v.z : v.w; }
__device__ __forceinline__ void cdft16(const uint4 (&A)[4], const uint4 (&F)[4], uint4 (&o)[4]) {
  float acc[2][4][4];
#pragma unroll
  for (int ks = 0; ks < 2; ks++)
#pragma unroll
    for (int p = 0; p < 2; p++)
#pragma unroll
      for (int v = 0; v < 4; v++) {
        const uint4& a = A[2 * ks + p];
        const uint32_t b0 = word(F[ks * 2 + (v >> 1)], (v & 1) * 2), b1 = word(F[ks * 2 + (v >> 1)], (v & 1) * 2 + 1);
        if (ks == 0) mma16816_z(acc[p][v], a.x, a.y, a.z, a.w, b0, b1);
        else mma16816(acc[p][v], a.x, a.y, a.z, a.w, b0, b1);
      }
#pragma unroll
  for (int v = 0; v < 4; v++)
    o[v] = make_uint4(pack2(acc[0][v][0], acc[0][v][1]), pack2(acc[0][v][2], acc[0][v][3]),
                      pack2(acc[1][v][0], acc[1][v][1]), pack2(acc[1][v][2], acc[1][v][3]));
}
__device__ __forceinline__ void lds_frag(uint4& f0, uint4& f1, uint32_t a0, uint32_t a1) {
  asm volatile("ld.volatile.shared.v2.u32 {%0,%1}, [%8]; ld.volatile.shared.v2.u32 {%2,%3}, [%9];\n"
               "ld.volatile.shared.v2.u32 {%4,%5}, [%8+8]; ld.volatile.shared.v2.u32 {%6,%7}, [%9+8];"
               : "=r"(f0.x), "=r"(f0.y), "=r"(f0.z), "=r"(f0.w), "=r"(f1.x), "=r"(f1.y), "=r"(f1.z), "=r"(f1.w) : "r"(a0), "r"(a1) : "memory");
}
__device__ __forceinline__ void reg_frag(uint4 (&q)[4], uint32_t ones) {
#pragma unroll
  for (int ks = 0; ks < 2; ks++) {
    const uint4 a = q[2 * ks], b = q[2 * ks + 1];
    q[2 * ks] = make_uint4(a.x, a.y, b.x & ones, b.y & ones);
    q[2 * ks + 1] = make_uint4(a.z & ones, a.w & ones, b.z, b.w);
  }
}
__device__ __forceinline__ void st_tag(uint4* p, const uint4& v, uint32_t tag) {
  asm volatile("st.relaxed.gpu.global.v4.b32 [%0], {%1,%2,%3,%4};"
               ::"l"(p), "r"((v.x & ~1u) | tag), "r"(v.y), "r"(v.z), "r"(v.w) : "memory");
}
__device__ __forceinline__ void st_tag8(void* p, uint32_t x, uint32_t y, uint32_t tag) {
  asm volatile("st.relaxed.gpu.global.v2.b32 [%0], {%1,%2};" ::"l"(p), "r"((x & ~1u) | tag), "r"(y) : "memory");
}
__device__ __forceinline__ uint4 ld_b128(const uint4* p) {
  uint4 v;
  asm volatile("ld.relaxed.gpu.global.v4.b32 {%0,%1,%2,%3}, [%4];"
               : "=r"(v.x), "=r"(v.y), "=r"(v.z), "=r"(v.w) : "l"(p) : "memory");
  return v;
}
template <int STRIDE>
__device__ __forceinline__ void ld_tag4_issue(uint4 (&q)[4], const uint4* p) {
#pragma unroll
  for (int i = 0; i < 4; i++) q[i] = ld_b128(p + i * STRIDE);
}
template <int STRIDE, bool HALVES = false>
__device__ __forceinline__ void ld_tag4_finish(uint4 (&q)[4], const uint4* p, uint32_t tag) {
  int it = 0;
#pragma unroll 1
  while (__any_sync(0xffffffffu, ((q[0].x ^ tag) | (q[1].x ^ tag) | (q[2].x ^ tag) | (q[3].x ^ tag) |
                                  (HALVES ? (q[0].z ^ tag) | (q[1].z ^ tag) | (q[2].z ^ tag) | (q[3].z ^ tag) : 0u)) & 1u)) {
    ld_tag4_issue<STRIDE>(q, p);
    if (++it > SPIN_LIMIT) { die(); break; }
  }
#pragma unroll
  for (int i = 0; i < 4; i++) {
    asm volatile("and.b32 %0, %0, 0xfffffffe;" : "+r"(q[i].x));
    if (HALVES) q[i].z &= ~1u;
  }
}
__device__ __forceinline__ float quad_sum(const uint32_t (&a)[8]) {
  float d[4];
  mma16816_z(d, a[0], a[1], a[2], a[3], 0x3f803f80u, 0x3f803f80u);
  mma16816(d, a[4], a[5], a[6], a[7], 0x3f803f80u, 0x3f803f80u);
  return d[0] + d[2];
}
__device__ __forceinline__ float sum_groups(float v) {
  v += __shfl_xor_sync(0xffffffffu, v, 4);
  v += __shfl_xor_sync(0xffffffffu, v, 8);
  v += __shfl_xor_sync(0xffffffffu, v, 16);
  return v;
}
__device__ __forceinline__ uint32_t hsub2_bf16(uint32_t a, uint32_t b) {
  uint32_t r;
  asm("sub.rn.bf16x2 %0, %1, %2;" : "=r"(r) : "r"(a), "r"(b));
  return r;
}
__device__ __forceinline__ float row_rstd(const uint32_t (&c)[8], float delta) {
  uint32_t s[8];
#pragma unroll
  for (int i = 0; i < 8; i++) asm("mul.rn.bf16x2 %0, %1, %1;" : "=r"(s[i]) : "r"(c[i]));
  return rsqrtf(fmaxf(fmaf(-delta, delta, sum_groups(quad_sum(s)) * (1.f / 512.f)), 0.f) + 1e-5f);
}
__device__ __forceinline__ uint64_t desc64(uint32_t lo, uint32_t hi) {
  uint64_t d;
  asm("mov.b64 %0, {%1, %2};" : "=l"(d) : "r"(lo), "r"(hi));
  return d;
}
constexpr uint32_t desc_hi(uint32_t sbo, uint32_t swz) { return (sbo >> 4) | (swz << 30); }
__device__ __forceinline__ uint32_t desc_lo(uint32_t addr, uint32_t lbo) { return ((addr & 0x3FFFF) >> 4) | ((lbo >> 4) << 16); }
__device__ __forceinline__ void cp_async16(uint32_t dst, const void* src) {
  asm volatile("cp.async.cg.shared.global [%0], [%1], 16;" ::"r"(dst), "l"(src) : "memory");
}
__device__ __forceinline__ uint2 lds2(uint32_t a) {
  uint2 v;
  asm volatile("ld.shared.v2.u32 {%0,%1}, [%2];" : "=r"(v.x), "=r"(v.y) : "r"(a) : "memory");
  return v;
}
__device__ __forceinline__ uint32_t lds_u16(uint32_t a) {
  uint16_t v;
  asm volatile("ld.shared.u16 %0, [%1];" : "=h"(v) : "r"(a) : "memory");
  return v;
}
__device__ __forceinline__ void wg_fence() { asm volatile("wgmma.fence.sync.aligned;" ::: "memory"); }
__device__ __forceinline__ void wg_commit() { asm volatile("wgmma.commit_group.sync.aligned;" ::: "memory"); }
template <int N>
__device__ __forceinline__ void wg_wait() { asm volatile("wgmma.wait_group.sync.aligned %0;" ::"n"(N) : "memory"); }
__device__ __forceinline__ void bulk_load(uint32_t dst, const void* src, int bytes, uint32_t bar) {
  asm volatile("cp.async.bulk.shared::cluster.global.mbarrier::complete_tx::bytes [%0], [%1], %2, [%3];"
               ::"r"(dst), "l"(src), "r"(bytes), "r"(bar) : "memory");
}
__device__ __forceinline__ void bulk_load_mc(uint32_t dst, const void* src, int bytes, uint32_t bar) {
  asm volatile("cp.async.bulk.shared::cluster.global.mbarrier::complete_tx::bytes.multicast::cluster [%0], [%1], %2, [%3], %4;"
               ::"r"(dst), "l"(src), "r"(bytes), "r"(bar), "h"((uint16_t)3) : "memory");
}
__device__ __forceinline__ void tma3(uint32_t dst, const CUtensorMap* tm, uint32_t bar, int c0, int c1, int c2) {
  asm volatile("cp.async.bulk.tensor.3d.shared::cluster.global.mbarrier::complete_tx::bytes [%0], [%1, {%3,%4,%5}], [%2];"
               ::"r"(dst), "l"(tm), "r"(bar), "r"(c0), "r"(c1), "r"(c2) : "memory");
}
__device__ __forceinline__ void tma3_mc(uint32_t dst, const CUtensorMap* tm, uint32_t bar, int c1, int c2) {
  asm volatile("cp.async.bulk.tensor.3d.shared::cluster.global.mbarrier::complete_tx::bytes.multicast::cluster [%0], [%1, {%3,%4,%5}], [%2], %6;"
               ::"r"(dst), "l"(tm), "r"(bar), "r"(0), "r"(c1), "r"(c2), "h"((uint16_t)3) : "memory");
}
__device__ __forceinline__ void mbar_arrive_remote(uint32_t rb) {
  asm volatile("mbarrier.arrive.shared::cluster.b64 _, [%0];" ::"r"(rb) : "memory");
}
__device__ __forceinline__ uint4 ldg_ca4(const void* p) {
  uint4 v;
  asm volatile("ld.global.ca.v4.u32 {%0,%1,%2,%3}, [%4];" : "=r"(v.x), "=r"(v.y), "=r"(v.z), "=r"(v.w) : "l"(p) : "memory");
  return v;
}
__device__ __forceinline__ float u2f(uint32_t v) { return __uint_as_float(v); }
__device__ __forceinline__ void mma_az(float (&d)[4], const uint4& a, uint32_t b0, uint32_t b1) { mma16816_z(d, a.x, a.y, a.z, a.w, b0, b1); }
__device__ __forceinline__ void mma_a(float (&d)[4], const uint4& a, uint32_t b0, uint32_t b1) { mma16816(d, a.x, a.y, a.z, a.w, b0, b1); }
__device__ __forceinline__ uint32_t clock32() {
  uint32_t v;
  asm volatile("mov.u32 %0, %%clock;" : "=r"(v) :: "memory");
  return v;
}
__device__ __forceinline__ float swiglu(float g, float u, float r) {
  float hg = (0.5f * r) * g, th;
  asm("tanh.approx.f32 %0, %1;" : "=f"(th) : "f"(hg));
  return fmaf(hg, th, hg) * (r * u);
}
__device__ __forceinline__ void l2_prefetch(const void* p, int bytes) {
  asm volatile("cp.async.bulk.prefetch.L2.global [%0], %1;" ::"l"(p), "r"(bytes) : "memory");
}

__device__ __forceinline__ void wgmma_n256(float (&d)[128], uint64_t da, uint64_t db, int sd = 1) {
  asm volatile("{.reg .pred p; setp.ne.b32 p, %130, 0;\n"
      "wgmma.mma_async.sync.aligned.m64n256k16.f32.bf16.bf16 {"
      "%0,%1,%2,%3,%4,%5,%6,%7,%8,%9,%10,%11,%12,%13,%14,%15,"
      "%16,%17,%18,%19,%20,%21,%22,%23,%24,%25,%26,%27,%28,%29,%30,%31,"
      "%32,%33,%34,%35,%36,%37,%38,%39,%40,%41,%42,%43,%44,%45,%46,%47,"
      "%48,%49,%50,%51,%52,%53,%54,%55,%56,%57,%58,%59,%60,%61,%62,%63,"
      "%64,%65,%66,%67,%68,%69,%70,%71,%72,%73,%74,%75,%76,%77,%78,%79,"
      "%80,%81,%82,%83,%84,%85,%86,%87,%88,%89,%90,%91,%92,%93,%94,%95,"
      "%96,%97,%98,%99,%100,%101,%102,%103,%104,%105,%106,%107,%108,%109,%110,%111,"
      "%112,%113,%114,%115,%116,%117,%118,%119,%120,%121,%122,%123,%124,%125,%126,%127"
      "}, %128, %129, p, 1, 1, 0, 1;}\n"
      : "+f"(d[0]),"+f"(d[1]),"+f"(d[2]),"+f"(d[3]),"+f"(d[4]),"+f"(d[5]),"+f"(d[6]),"+f"(d[7]),
        "+f"(d[8]),"+f"(d[9]),"+f"(d[10]),"+f"(d[11]),"+f"(d[12]),"+f"(d[13]),"+f"(d[14]),"+f"(d[15]),
        "+f"(d[16]),"+f"(d[17]),"+f"(d[18]),"+f"(d[19]),"+f"(d[20]),"+f"(d[21]),"+f"(d[22]),"+f"(d[23]),
        "+f"(d[24]),"+f"(d[25]),"+f"(d[26]),"+f"(d[27]),"+f"(d[28]),"+f"(d[29]),"+f"(d[30]),"+f"(d[31]),
        "+f"(d[32]),"+f"(d[33]),"+f"(d[34]),"+f"(d[35]),"+f"(d[36]),"+f"(d[37]),"+f"(d[38]),"+f"(d[39]),
        "+f"(d[40]),"+f"(d[41]),"+f"(d[42]),"+f"(d[43]),"+f"(d[44]),"+f"(d[45]),"+f"(d[46]),"+f"(d[47]),
        "+f"(d[48]),"+f"(d[49]),"+f"(d[50]),"+f"(d[51]),"+f"(d[52]),"+f"(d[53]),"+f"(d[54]),"+f"(d[55]),
        "+f"(d[56]),"+f"(d[57]),"+f"(d[58]),"+f"(d[59]),"+f"(d[60]),"+f"(d[61]),"+f"(d[62]),"+f"(d[63]),
        "+f"(d[64]),"+f"(d[65]),"+f"(d[66]),"+f"(d[67]),"+f"(d[68]),"+f"(d[69]),"+f"(d[70]),"+f"(d[71]),
        "+f"(d[72]),"+f"(d[73]),"+f"(d[74]),"+f"(d[75]),"+f"(d[76]),"+f"(d[77]),"+f"(d[78]),"+f"(d[79]),
        "+f"(d[80]),"+f"(d[81]),"+f"(d[82]),"+f"(d[83]),"+f"(d[84]),"+f"(d[85]),"+f"(d[86]),"+f"(d[87]),
        "+f"(d[88]),"+f"(d[89]),"+f"(d[90]),"+f"(d[91]),"+f"(d[92]),"+f"(d[93]),"+f"(d[94]),"+f"(d[95]),
        "+f"(d[96]),"+f"(d[97]),"+f"(d[98]),"+f"(d[99]),"+f"(d[100]),"+f"(d[101]),"+f"(d[102]),"+f"(d[103]),
        "+f"(d[104]),"+f"(d[105]),"+f"(d[106]),"+f"(d[107]),"+f"(d[108]),"+f"(d[109]),"+f"(d[110]),"+f"(d[111]),
        "+f"(d[112]),"+f"(d[113]),"+f"(d[114]),"+f"(d[115]),"+f"(d[116]),"+f"(d[117]),"+f"(d[118]),"+f"(d[119]),
        "+f"(d[120]),"+f"(d[121]),"+f"(d[122]),"+f"(d[123]),"+f"(d[124]),"+f"(d[125]),"+f"(d[126]),"+f"(d[127])
      : "l"(da), "l"(db), "r"(sd));
}
__device__ __forceinline__ void wgmma_n192(float (&d)[96], uint64_t da, uint64_t db) {
  asm volatile("wgmma.mma_async.sync.aligned.m64n192k16.f32.bf16.bf16 {"
      "%0,%1,%2,%3,%4,%5,%6,%7,%8,%9,%10,%11,%12,%13,%14,%15,"
      "%16,%17,%18,%19,%20,%21,%22,%23,%24,%25,%26,%27,%28,%29,%30,%31,"
      "%32,%33,%34,%35,%36,%37,%38,%39,%40,%41,%42,%43,%44,%45,%46,%47,"
      "%48,%49,%50,%51,%52,%53,%54,%55,%56,%57,%58,%59,%60,%61,%62,%63,"
      "%64,%65,%66,%67,%68,%69,%70,%71,%72,%73,%74,%75,%76,%77,%78,%79,"
      "%80,%81,%82,%83,%84,%85,%86,%87,%88,%89,%90,%91,%92,%93,%94,%95"
      "}, %96, %97, 1, 1, 1, 0, 1;\n"
      : "+f"(d[0]),"+f"(d[1]),"+f"(d[2]),"+f"(d[3]),"+f"(d[4]),"+f"(d[5]),"+f"(d[6]),"+f"(d[7]),
        "+f"(d[8]),"+f"(d[9]),"+f"(d[10]),"+f"(d[11]),"+f"(d[12]),"+f"(d[13]),"+f"(d[14]),"+f"(d[15]),
        "+f"(d[16]),"+f"(d[17]),"+f"(d[18]),"+f"(d[19]),"+f"(d[20]),"+f"(d[21]),"+f"(d[22]),"+f"(d[23]),
        "+f"(d[24]),"+f"(d[25]),"+f"(d[26]),"+f"(d[27]),"+f"(d[28]),"+f"(d[29]),"+f"(d[30]),"+f"(d[31]),
        "+f"(d[32]),"+f"(d[33]),"+f"(d[34]),"+f"(d[35]),"+f"(d[36]),"+f"(d[37]),"+f"(d[38]),"+f"(d[39]),
        "+f"(d[40]),"+f"(d[41]),"+f"(d[42]),"+f"(d[43]),"+f"(d[44]),"+f"(d[45]),"+f"(d[46]),"+f"(d[47]),
        "+f"(d[48]),"+f"(d[49]),"+f"(d[50]),"+f"(d[51]),"+f"(d[52]),"+f"(d[53]),"+f"(d[54]),"+f"(d[55]),
        "+f"(d[56]),"+f"(d[57]),"+f"(d[58]),"+f"(d[59]),"+f"(d[60]),"+f"(d[61]),"+f"(d[62]),"+f"(d[63]),
        "+f"(d[64]),"+f"(d[65]),"+f"(d[66]),"+f"(d[67]),"+f"(d[68]),"+f"(d[69]),"+f"(d[70]),"+f"(d[71]),
        "+f"(d[72]),"+f"(d[73]),"+f"(d[74]),"+f"(d[75]),"+f"(d[76]),"+f"(d[77]),"+f"(d[78]),"+f"(d[79]),
        "+f"(d[80]),"+f"(d[81]),"+f"(d[82]),"+f"(d[83]),"+f"(d[84]),"+f"(d[85]),"+f"(d[86]),"+f"(d[87]),
        "+f"(d[88]),"+f"(d[89]),"+f"(d[90]),"+f"(d[91]),"+f"(d[92]),"+f"(d[93]),"+f"(d[94]),"+f"(d[95])
      : "l"(da), "l"(db));
}
template <int SD>
__device__ __forceinline__ void wgmma_rs_n128(float (&d)[64], uint32_t a0, uint32_t a1, uint32_t a2, uint32_t a3, uint64_t db) {
  asm volatile("wgmma.mma_async.sync.aligned.m64n128k16.f32.bf16.bf16 {"
      "%0,%1,%2,%3,%4,%5,%6,%7,%8,%9,%10,%11,%12,%13,%14,%15,"
      "%16,%17,%18,%19,%20,%21,%22,%23,%24,%25,%26,%27,%28,%29,%30,%31,"
      "%32,%33,%34,%35,%36,%37,%38,%39,%40,%41,%42,%43,%44,%45,%46,%47,"
      "%48,%49,%50,%51,%52,%53,%54,%55,%56,%57,%58,%59,%60,%61,%62,%63"
      "}, {%64,%65,%66,%67}, %68, %69, 1, 1, 1;\n"
      : "+f"(d[0]),"+f"(d[1]),"+f"(d[2]),"+f"(d[3]),"+f"(d[4]),"+f"(d[5]),"+f"(d[6]),"+f"(d[7]),
        "+f"(d[8]),"+f"(d[9]),"+f"(d[10]),"+f"(d[11]),"+f"(d[12]),"+f"(d[13]),"+f"(d[14]),"+f"(d[15]),
        "+f"(d[16]),"+f"(d[17]),"+f"(d[18]),"+f"(d[19]),"+f"(d[20]),"+f"(d[21]),"+f"(d[22]),"+f"(d[23]),
        "+f"(d[24]),"+f"(d[25]),"+f"(d[26]),"+f"(d[27]),"+f"(d[28]),"+f"(d[29]),"+f"(d[30]),"+f"(d[31]),
        "+f"(d[32]),"+f"(d[33]),"+f"(d[34]),"+f"(d[35]),"+f"(d[36]),"+f"(d[37]),"+f"(d[38]),"+f"(d[39]),
        "+f"(d[40]),"+f"(d[41]),"+f"(d[42]),"+f"(d[43]),"+f"(d[44]),"+f"(d[45]),"+f"(d[46]),"+f"(d[47]),
        "+f"(d[48]),"+f"(d[49]),"+f"(d[50]),"+f"(d[51]),"+f"(d[52]),"+f"(d[53]),"+f"(d[54]),"+f"(d[55]),
        "+f"(d[56]),"+f"(d[57]),"+f"(d[58]),"+f"(d[59]),"+f"(d[60]),"+f"(d[61]),"+f"(d[62]),"+f"(d[63])
      : "r"(a0), "r"(a1), "r"(a2), "r"(a3), "l"(db), "n"(SD));
}


constexpr int C_LN = 0, C_PX = 16, C_PY = 32;
constexpr int NB_CONS = 1, NB_LN = 2, NB_LAG = 4, NB_INIT = 6, NB_RDY = 7, NB_WG = 8;
constexpr int LAGX = 3;
constexpr int LAGY = 3;
constexpr int LAG2 = 5;
constexpr int NLL = 2;
constexpr int POLL_DELAY3 = 600;
constexpr int POLL_DELAY = 1200;
constexpr int FILT_DELAY = 800;
constexpr int WARM = 4;
constexpr int ALEAD = 6;
constexpr int POLL_DELAY2 = 1000;
constexpr int HPOS = 14;
constexpr int REDPOS = 1;
constexpr int XTRIG = 21;
constexpr int HTRIG = 0;
constexpr int RING_SIG = 1;
constexpr int PF2_SIG = 1;
constexpr int SM_E = 0, SM_X = 16384, SM_E2 = 32768, SM_W = 49152, SM_FC = 69632, SM_T = 73728 - T1_BYTES;
constexpr unsigned long long KORDER = 0xBA9432DC876510ull;
constexpr unsigned long long BSLOT = 0x76532107653210ull, PSLOT = 0xDCBA984DCBA984ull;
constexpr uint32_t HI128 = desc_hi(1024, 1), HI64 = desc_hi(512, 2);

struct Bars {
  uint64_t full1[32], empty1[32], full2[16], fullA[8], empty2[8], fullP[16], emptyP[8], hbar, tbar, hint[3], sig[2], sbar;
  uint32_t epoch, pad;
};

template <int NK, bool STORE, int J0 = 0, int J1 = NK>
__device__ __forceinline__ void make_p(const float (&acc)[NK * 16], float r0, float r1, uint4 (&p)[NK], uint4* pbase, int ks0, uint32_t tag) {
#pragma unroll
  for (int j = J0; j < J1; j++) {
    uint32_t w[4];
#pragma unroll
    for (int i = 0; i < 4; i++) {
      const int a = 8 * j + 2 * i, b = a + NK * 8;
      w[i] = pack2(swiglu(acc[a], acc[b], (i & 1) ? r1 : r0), swiglu(acc[a + 1], acc[b + 1], (i & 1) ? r1 : r0));
    }
    asm volatile("" : "+r"(w[0]), "+r"(w[1]), "+r"(w[2]), "+r"(w[3]));
    p[j] = make_uint4(w[0], w[1], w[2], w[3]);
    if (STORE) st_tag(pbase + ((ks0 + j) >> 2) * 1024 + ((ks0 + j) & 3) * 32, p[j], tag);
  }
}
__device__ __forceinline__ void spin_until(uint32_t t) {
  while ((int)(clock32() - t) < 0) {}
}

__global__ void __cluster_dims__(2, 1, 1) __launch_bounds__(NTHREADS, 1)
fused_kernel(const __nv_bfloat16* __restrict__ x, const Tables* __restrict__ tab, Scratch* __restrict__ scr,
             __nv_bfloat16* __restrict__ out, const char* __restrict__ wg_raw, const char* __restrict__ wu_raw,
             const char* __restrict__ wd_raw,
             const __grid_constant__ CUtensorMap tmWR, const __grid_constant__ CUtensorMap tmWI,
             const __grid_constant__ CUtensorMap tmGX, const __grid_constant__ CUtensorMap tmUX,
             const __grid_constant__ CUtensorMap tmGY, const __grid_constant__ CUtensorMap tmUY,
             const __grid_constant__ CUtensorMap tmD) {
  extern __shared__ __align__(1024) char smem_raw[];
  const uint32_t sbase = s2u(smem_raw);
  const uint32_t sbar = sbase + 14 * SLOT, sstat = sbar + 1280;
  const int tid = threadIdx.x, lane = tid & 31;
  const int c = blockIdx.x, rk = c & 1, f = (c >> 1) & 7, rb = 2 * (c >> 4) + rk;
  const int rb2 = 2 * (c >> 4) + (f >> 2), kh = (f >> 1) & 1, nq = 2 * (f & 1) + rk;
#define BAR(field, i) (sbar + (uint32_t)offsetof(Bars, field) + 8u * (i))
#define TOFF(field) (sbase + SM_T + (uint32_t)offsetof(Tables, field) + lane * 16)

  if (tid >= 256) {
    asm volatile("setmaxnreg.dec.sync.aligned.u32 56;");
    const int warp = __shfl_sync(0xffffffffu, tid >> 5, 0);
    if (lane == 0) {
      if (warp == 8) {
        if (sbase & 1023) die();
#pragma unroll
        for (int i = 0; i < 16; i++) mbar_init(BAR(emptyP, i), i < 7 ? 16 : i < 8 ? 8 : i < 13 ? 1 : i < 15 ? 8 : 32);
        mbar_expect(BAR(tbar, 0), T2_BYTES + 2 * 10240);
        mbar_expect(BAR(hbar, 0), 16384);
      } else if (warp == 9) {
#pragma unroll
        for (int i = 0; i < 32; i++) mbar_init(BAR(full1, i), 1);
#pragma unroll
        for (int i = 0; i < 32; i++) mbar_expect(BAR(full1, i), i < 16 ? 16384 : 12288);
      } else if (warp == 10) {
#pragma unroll
        for (int i = 0; i < 32; i++) mbar_init(BAR(empty1, i), 16);
#pragma unroll
        for (int i = 0; i < 14; i++) mbar_init(BAR(fullP, i), 1);
#pragma unroll
        for (int i = 0; i < 14; i++) mbar_expect(BAR(fullP, i), 16384);
      } else {
#pragma unroll
        for (int i = 0; i < 32; i++) mbar_init(BAR(full2, i), i < 24 ? 1 : 8);
#pragma unroll
        for (int i = 0; i < 24; i++) mbar_expect(BAR(full2, i), 16384);
      }
      asm volatile("fence.mbarrier_init.release.cluster;" ::: "memory");
    }
    if (tid == 256) {
      const int w0 = ((c >> 3) * 257 + 32 * (c & 7) + 1) & ~7;
      if (FILT_DELAY) {
        asm volatile("prefetch.tensormap [%0];" ::"l"(&tmWR) : "memory");
        asm volatile("prefetch.tensormap [%0];" ::"l"(&tmWI) : "memory");
        spin_until(clock32() + FILT_DELAY);
      }
      tma3(sbase + SM_W, &tmWR, BAR(tbar, 0), w0, 0, 0);
      tma3(sbase + SM_W + 10240, &tmWI, BAR(tbar, 0), w0, 0, 0);
      bulk_load(sbase + SM_T + T1_BYTES, reinterpret_cast<const char*>(tab) + T1_BYTES, T2_BYTES, BAR(tbar, 0));
    }
    if (tid == 288) {
      asm volatile("prefetch.tensormap [%0];" ::"l"(rk ? &tmUX : &tmGX) : "memory");
      asm volatile("prefetch.tensormap [%0];" ::"l"(rk ? &tmUY : &tmGY) : "memory");
      asm volatile("prefetch.tensormap [%0];" ::"l"(&tmD) : "memory");
    }
    if (tid == 320) {
      const unsigned e = ld_relaxed(&scr->cnt[(C_LN + rb) * 32]) >> 3;
      asm volatile("st.shared.u32 [%0], %1;" ::"r"(BAR(epoch, 0)), "r"(e) : "memory");
    }
    __syncwarp();
    asm volatile("barrier.cluster.arrive.relaxed.aligned;" ::: "memory");
    bar_arrive(NB_RDY, 384);
    asm volatile("barrier.cluster.wait.aligned;" ::: "memory");
    bar_sync(NB_INIT, 384);
    unsigned epoch;
    asm volatile("ld.shared.u32 %0, [%1];" : "=r"(epoch) : "r"(BAR(epoch, 0)) : "memory");
    if (warp == 8) {
      if (lane == 0) {
        const int ax = (7 * f + 3 * (f & 1)) >> 1;
        const int ay = 7 * f + ((f & 1) ? 0 : 4);
        const CUtensorMap* tx = rk ? &tmUX : &tmGX;
        const CUtensorMap* ty = rk ? &tmUY : &tmGY;
        if (RING_SIG >= 0) mbar_wait(BAR(sig, RING_SIG));
        uint32_t s = 2;
#pragma unroll 1
        for (int n = 0; n < 16; n++) {
          if (n >= 6) mbar_wait(BAR(empty1, n - 6));
          tma3_mc(sbase + (8 + s) * SLOT + rk * 8192, tx, BAR(full1, n), n * 32, ax);
          if (++s == 6) s = 0;
        }
#pragma unroll 1
        for (int k = 0; k < 16; k++) {
          mbar_wait(BAR(empty1, k < 8 ? 10 + ((12 * k + 11) >> 4) : 8 + k));
          tma3_mc(sbase + 8 * SLOT + (k & 7) * 12288 + rk * 6144, ty, BAR(full1, 16 + k), k * 32, ay);
        }
      }
    } else if (warp == 9) {
      if (lane == 0) {
        mbar_wait(BAR(fullA, 4));
        wait_counter(&scr->cnt[(C_LN + rb2) * 32], (epoch + 1) * 8);
        asm volatile("fence.proxy.async.global;" ::: "memory");
#pragma unroll 1
        for (int i = 0; i < 15; i++) {
          const int kblk = 14 * kh + (int)((KORDER >> (4 * i)) & 15);
          const int j = i < 7 ? i : i - 7, sl = j + (j >= 4);
          if (i == HPOS) {
            mbar_wait(BAR(emptyP, 7));
            bulk_load(sbase + 4 * SLOT, &scr->LN[(rb2 * 8 + 2 * nq) * 1024 + kh * 512], 8192, BAR(hbar, 0));
            bulk_load(sbase + 4 * SLOT + 8192, &scr->LN[(rb2 * 8 + 2 * nq + 1) * 1024 + kh * 512], 8192, BAR(hbar, 0));
          }
          if (i == 14) break;
          mbar_wait(i < 7 ? BAR(empty1, 17 + 2 * sl) : BAR(empty2, j));
          tma3(sbase + sl * SLOT, &tmD, BAR(full2, i), 0, 64 * kblk, 2 * nq);
        }
      }
    } else if (warp == 10) {
      bar_sync(NB_LN, 288);
      if (lane == 0) {
        red_release(&scr->cnt[(C_LN + rb) * 32]);
        wait_counter(&scr->cnt[(C_LN + rb) * 32], (epoch + 1) * 8);
        asm volatile("fence.proxy.async.global;" ::: "memory");
#pragma unroll 1
        for (int kb = NLL; kb < 8; kb++) {
          if (2 * kb >= ALEAD) mbar_wait(BAR(empty1, 2 * kb - ALEAD));
          bulk_load(sbase + kb * SLOT, &scr->LN[(rb * 8 + kb) * 1024], 16384, BAR(fullA, kb));
        }
#pragma unroll 1
        for (int s = 0; s < 14; s++) {
          const int kblk = 14 * kh + (int)((KORDER >> (4 * s)) & 15);
          if (s == 0 || s == 8 || s == 11) {
            mbar_wait(BAR(hint, s == 0 ? 0 : s == 8 ? 1 : 2), 0);
          }
          const int j = s < 7 ? s : s - 7;
          mbar_wait(s < 7 ? BAR(empty1, 24 + s + (s == 0) + (s >= 4)) : BAR(emptyP, j));
          bulk_load_mc(sbase + (j ? 7 + j : 4) * SLOT + rk * 8192, &scr->P[(rb2 * 28 + kblk) * 1024 + rk * 512], 8192, BAR(fullP, s));
        }
      }
    } else {
      if (lane == 0) {
        mbar_wait(BAR(tbar, 0));
        l2_prefetch(wg_raw + (size_t)c * 5376, 5376);
        l2_prefetch(wu_raw + (size_t)c * 5376, 5376);
        mbar_wait(BAR(sig, PF2_SIG), 0);
        l2_prefetch(wg_raw + 688128 + (size_t)c * 8960, 8960);
        l2_prefetch(wu_raw + 688128 + (size_t)c * 8960, 8960);
      }
      mbar_wait(BAR(fullA, 4), 0);
      if (lane == 0) l2_prefetch(wd_raw + (size_t)c * 14336, 14336);
      {
        const uint32_t tag = (epoch + 1) & 1;
        uint4 v0, v1, v2;
        int it = 0;
        while (true) {
          v0 = ld_b128(&scr->ST[rb * 64 + lane]);
          v1 = ld_b128(&scr->ST[rb * 64 + 32 + lane]);
          v2 = ld_b128(&scr->ST[rb2 * 64 + 32 * kh + lane]);
          if (!__any_sync(0xffffffffu, ((v0.x ^ tag) | (v1.x ^ tag) | (v2.x ^ tag)) & 1u)) break;
          if (++it > SPIN_LIMIT) { die(); break; }
        }
        sts4(sstat + lane * 16, v0.x & ~1u, v0.y, v0.z, v0.w);
        sts4(sstat + 512 + lane * 16, v1.x & ~1u, v1.y, v1.z, v1.w);
        sts4(sstat + 1024 + lane * 16, v2.x & ~1u, v2.y, v2.z, v2.w);
        mbar_arrive(BAR(sbar, 0));
      }
      if (lane == 0) {
        mbar_wait(BAR(empty1, XTRIG));
        int it = 0;
        while ((int)(ld_relaxed(&scr->cnt[(C_PX + rb2) * 32 + kh]) - (epoch + 1) * 32) < 0) {
          if (++it > SPIN_LIMIT) { die(); break; }
        }
        mbar_arrive(BAR(hint, 0));
        mbar_wait(BAR(emptyP, HTRIG));
        uint32_t done = 0;
        while (done != 3) {
          uint2 v;
          asm volatile("ld.relaxed.gpu.global.v2.u32 {%0,%1}, [%2];" : "=r"(v.x), "=r"(v.y) : "l"(&scr->cnt[(C_PY + rb2) * 32 + 2 * kh]) : "memory");
          if (!(done & 1) && (int)(v.x - (epoch + 1) * 16) >= 0) { done |= 1; mbar_arrive(BAR(hint, 1)); }
          if (!(done & 2) && (int)(v.y - (epoch + 1) * 16) >= 0) { done |= 2; mbar_arrive(BAR(hint, 2)); }
          if (++it > SPIN_LIMIT) { die(); break; }
        }
      }
    }
  } else {
    const int warp = __shfl_sync(0xffffffffu, tid >> 5, 0);
    const int g = lane >> 2, t = lane & 3;
    uint4 fa[4], fb[4], tw[6];
#pragma unroll
    for (int i = 0; i < 4; i++) fa[i] = ldg_ca4(&tab->fa[i][lane][0]);
#pragma unroll
    for (int i = 0; i < 6; i++) tw[i] = ldg_ca4(&tab->tw1[i][lane][0]);
#pragma unroll
    for (int i = 0; i < 4; i++) fb[i] = ldg_ca4(&tab->fb[i][lane][0]);
#pragma unroll
    for (int i = 0; i < 4; i++) {
      const int r = i >> 1, ch = (i & 1) * 32 + lane;
      cp_async16(sbase + SM_X + (2 * warp + r) * 1024 + ((ch ^ ((ch >> 3) & 1)) * 16),
                 x + (size_t)(c + 128 * (2 * warp + r)) * 512 + ch * 8);
    }
    asm volatile("cp.async.commit_group;" ::: "memory");
    asm volatile("barrier.cluster.arrive.relaxed.aligned;" ::: "memory");
    uint32_t rbar;
    asm volatile("mapa.shared::cluster.u32 %0, %1, %2;" : "=r"(rbar) : "r"(sbar), "r"(rk ^ 1));
#define RBAR(field, i) (rbar + (uint32_t)offsetof(Bars, field) + 8u * (i))
    {
      const int ln = (tid >> 1) & 31, lg = ln >> 2, lt = ln & 3, i = 4 * (tid >> 6) + 2 * (tid & 1);
      const int kidx = lt + 8 * (i >> 3), nidx = 4 * ((i >> 1) & 3) + (lg >> 1);
      const uint32_t a0 = cfrag<2048>((c + 128 * kidx) * nidx, lg & 1), a1 = cfrag<2048>((c + 128 * (kidx + 4)) * nidx, lg & 1);
      const uint32_t b0 = cfrag<2048>(-(c + 128 * nidx) * kidx, lg & 1), b1 = cfrag<2048>(-(c + 128 * nidx) * (kidx + 4), lg & 1);
      asm volatile("st.shared.v2.u32 [%0], {%1,%2};" ::"r"(sbase + SM_FC + tid * 8), "r"(a0), "r"(a1) : "memory");
      asm volatile("st.shared.v2.u32 [%0], {%1,%2};" ::"r"(sbase + SM_FC + 2048 + tid * 8), "r"(b0), "r"(b1) : "memory");
    }
    bar_sync(NB_CONS, 256);
    uint4 fc[4];
#pragma unroll
    for (int i = 0; i < 4; i++) fc[i] = lds4(sbase + SM_FC + i * 512 + lane * 16);
    asm volatile("cp.async.wait_group 0;" ::: "memory");
    __syncwarp();
    bar_arrive(NB_INIT, 384);
    uint32_t tag, ones;
    uint4 q[4], o[4];
    {
      uint32_t v[2][8];
#pragma unroll
      for (int r = 0; r < 2; r++)
#pragma unroll
        for (int ks = 0; ks < 2; ks++) {
          const int ch = 32 * ks + 2 * (lane & 15) + (lane >> 4);
          asm volatile("ldmatrix.sync.aligned.m8n8.x4.trans.shared.b16 {%0,%1,%2,%3}, [%4];"
                       : "=r"(v[r][4 * ks]), "=r"(v[r][4 * ks + 1]), "=r"(v[r][4 * ks + 2]), "=r"(v[r][4 * ks + 3])
                       : "r"(sbase + SM_X + (2 * warp + r) * 1024 + ((ch ^ ((ch >> 3) & 1)) * 16)) : "memory");
        }
      float sq[2];
#pragma unroll
      for (int r = 0; r < 2; r++) {
        float s0 = 0.f, s1 = 0.f;
#pragma unroll
        for (int i = 0; i < 8; i++) {
          const float lo = bf_lo(v[r][i]), hi = u2f(v[r][i] & 0xffff0000u);
          s0 = fmaf(lo, lo, s0);
          s1 = fmaf(hi, hi, s1);
        }
        sq[r] = s0 + s1;
      }
      {
        float w = ((lane & 1) ? sq[1] : sq[0]) + __shfl_xor_sync(0xffffffffu, (lane & 1) ? sq[0] : sq[1], 1);
        w += __shfl_xor_sync(0xffffffffu, w, 2);
        w = sum_groups(w);
        const float o2 = __shfl_xor_sync(0xffffffffu, w, 1);
        sq[0] = (lane & 1) ? o2 : w;
        sq[1] = (lane & 1) ? w : o2;
      }
#pragma unroll
      for (int r = 0; r < 2; r++) {
        float dd[2][4], ee[2][4];
#pragma unroll
        for (int nt = 0; nt < 2; nt++) {
          mma_az(dd[nt], fa[0], v[r][2 * nt], v[r][2 * nt + 1]);
          mma_a(dd[nt], fa[1], v[r][4 + 2 * nt], v[r][5 + 2 * nt]);
          mma_az(ee[nt], fa[2], v[r][2 * nt], v[r][2 * nt + 1]);
          mma_a(ee[nt], fa[3], v[r][4 + 2 * nt], v[r][5 + 2 * nt]);
        }
        float mean = (dd[0][0] + dd[0][1]) + (dd[1][0] + dd[1][1]);
        mean += __shfl_xor_sync(0xffffffffu, mean, 1);
        mean += __shfl_xor_sync(0xffffffffu, mean, 2);
        mean = __shfl_sync(0xffffffffu, mean, 0) * (1.f / 512.f);
        const float rs = rsqrtf(fmaxf(fmaf(-mean, mean, sq[r] * (1.f / 512.f)), 0.f) + 1e-5f);
        float acc[4][4];
#pragma unroll
        for (int nt = 0; nt < 2; nt++) {
          const float (&d)[4] = dd[nt];
          const float (&e)[4] = ee[nt];
          const uint4 &ka = tw[2 * nt], &kb = tw[2 * nt + 1], &kc = tw[4 + nt];
          const uint32_t a0 = pack2(d[0] * u2f(ka.x) + d[2] * u2f(ka.y), d[1] * u2f(kb.x) + d[3] * u2f(kb.y));
          const uint32_t a2 = pack2(d[0] * u2f(ka.z) + d[2] * u2f(ka.w), d[1] * u2f(kb.z) + d[3] * u2f(kb.w));
          const uint32_t a1 = pack2(e[0] * u2f(kc.x) + e[2] * u2f(kc.y), e[1] * u2f(kc.z) + e[3] * u2f(kc.w));
          const uint32_t a3 = pack2(e[2] * u2f(kc.x) - e[0] * u2f(kc.y), e[3] * u2f(kc.z) - e[1] * u2f(kc.w));
          const uint32_t dc = pack2(fmaf(mean, -32.f, d[0]), fmaf(mean, -32.f, d[1]));
          const uint32_t h0 = g == 0 ? dc : a0, h2 = g == 0 ? 0u : a2;
          if (nt == 0) {
            mma16816_z(acc[0], a0, a1, a2, a3, fb[2 * nt].x, fb[2 * nt].y);
            mma16816_z(acc[1], a0, a1, a2, a3, fb[2 * nt].z, fb[2 * nt].w);
            mma16816_z(acc[2], h0, a1, h2, a3, fb[2 * nt + 1].x, fb[2 * nt + 1].y);
            mma16816_z(acc[3], h0, a1, h2, a3, fb[2 * nt + 1].z, fb[2 * nt + 1].w);
          } else {
            mma16816(acc[0], a0, a1, a2, a3, fb[2 * nt].x, fb[2 * nt].y);
            mma16816(acc[1], a0, a1, a2, a3, fb[2 * nt].z, fb[2 * nt].w);
            mma16816(acc[2], h0, a1, h2, a3, fb[2 * nt + 1].x, fb[2 * nt + 1].y);
            mma16816(acc[3], h0, a1, h2, a3, fb[2 * nt + 1].z, fb[2 * nt + 1].w);
          }
        }
#pragma unroll
        for (int h = 0; h < 2; h++) {
          const int j = 2 * warp + r, m = 2 * t + h;
          sts4(sbase + SM_E + ((j * 8 + m) * 8 + (g ^ (2 * t) ^ (2 * (j & 3)))) * 16,
               pack2(acc[h][0] * rs, acc[h][1] * rs), pack2(acc[h][2] * rs, acc[h][3] * rs),
               pack2(acc[2 + h][0] * rs, acc[2 + h][1] * rs), pack2(acc[2 + h][2] * rs, acc[2 + h][3] * rs));
        }
      }
      bar_sync(NB_RDY, 384);
      const uint32_t ea = sbase + SM_E + ((t * 8 + warp) * 8 + (g ^ (warp & 6) ^ (2 * t))) * 16;
      lds_frag(q[0], q[1], ea, ea + 4096);
      lds_frag(q[2], q[3], ea + 8192, ea + 12288);
      asm volatile("ld.shared.u32 %0, [%1];" : "=r"(tag) : "r"(BAR(epoch, 0)) : "memory");
      ones = ~(tag >> 31);
      tag = (tag + 1) & 1;
      cdft16(q, fc, o);
#pragma unroll
      for (int vv = 0; vv < 4; vv++) {
        o[vv].y &= ~1u;
        o[vv].z = (o[vv].z & ~1u) | (tag ^ 1);
        st_tag(&scr->Z1[(((4 * vv + t) * 8 + warp) * 128 + c) * 8 + g], o[vv], tag);
      }
    }
    asm volatile("setmaxnreg.inc.sync.aligned.u32 224;");
    {
      uint4* const zp = &scr->Z1[(c * 128 + 8 * t + warp) * 8 + g];
      const uint32_t tst = clock32();
      mbar_wait(BAR(tbar, 0), 0);
      uint4 f2[4], g2[4];
#pragma unroll
      for (int i = 0; i < 4; i++) {
        f2[i] = lds4(TOFF(f2) + warp * 2048 + i * 512);
        g2[i] = lds4(TOFF(g2) + warp * 2048 + i * 512);
      }
      const uint4 f8 = lds4(TOFF(f8)), g8 = lds4(TOFF(g8));
      asm volatile("barrier.cluster.wait.aligned;" ::: "memory");
      spin_until(tst + POLL_DELAY);
      ld_tag4_issue<256>(q, zp);
      float wfr[16], wfi[16];
      {
        const float nyq = ((c & 7) == 7 && g == 0) ? 0.5f : 1.f;
        uint32_t wa = sbase + SM_W + (16 * warp + t) * 80 + ((2 * (c >> 3) + 2) & 15) - 2;
        asm volatile("" : "+r"(wa));
        const uint32_t wb[3] = {wa + 2 * (g == 0 ? 16 : g), wa + 2 * g, wa - 2 * g};
#pragma unroll
        for (int i = 0; i < 16; i++) {
          const int ci = i >> 3, dd = (i >> 2) & 1, e = i & 3;
          const uint32_t a = wb[e < 2 ? e : 2] + (ci * 8 + 4 * dd) * 80 + (e == 0 ? 0 : e == 1 ? 16 : e == 2 ? 64 : 48);
          wfr[i] = bf_lo(lds_u16(a)) * (e == 2 ? nyq : 1.f);
          wfi[i] = bf_lo(lds_u16(a + 10240)) * (e == 2 ? nyq : 1.f);
        }
      }
      ld_tag4_finish<256>(q, zp, tag);
      if (lane == 0) mbar_arrive(BAR(sig, 0));
#pragma unroll
      for (int i = 0; i < 4; i++) q[i].z &= ~1u;
      reg_frag(q, ones);
      cdft16(q, f2, o);
      const uint32_t e2 = sbase + SM_E2;
#pragma unroll
      for (int vv = 0; vv < 4; vv++)
        sts4(e2 + ((warp * 16 + 4 * vv + t) * 8 + (g ^ (2 * t) ^ (2 * (warp & 3)))) * 16, o[vv].x, o[vv].y, o[vv].z, o[vv].w);
      bar_sync(NB_CONS, 256);
      uint32_t ad[2], res[2][2][4];
#pragma unroll
      for (int ci = 0; ci < 2; ci++) {
        const int cc = 2 * warp + ci;
        ad[ci] = e2 + ((t * 16 + cc) * 8 + (g ^ (2 * (cc & 3)) ^ (2 * t))) * 16;
        lds_frag(q[2 * ci], q[2 * ci + 1], ad[ci], ad[ci] + 8192);
      }
#pragma unroll
      for (int ci = 0; ci < 2; ci++)
#pragma unroll
        for (int p = 0; p < 2; p++) {
          uint32_t y[2][2];
#pragma unroll
          for (int vv = 0; vv < 2; vv++) {
            float d[4];
            mma_az(d, q[2 * ci + p], word(f8, 2 * vv), word(f8, 2 * vv + 1));
#pragma unroll
            for (int rr = 0; rr < 2; rr++) {
              const float fr = wfr[ci * 8 + vv * 4 + 2 * p + rr], fi = wfi[ci * 8 + vv * 4 + 2 * p + rr];
              y[vv][rr] = pack2(d[2 * rr] * fr - d[2 * rr + 1] * fi, d[2 * rr] * fi + d[2 * rr + 1] * fr);
            }
          }
#pragma unroll
          for (int vv = 0; vv < 2; vv++) {
            float d[4];
            mma16816_z(d, y[0][0], y[0][1], y[1][0], y[1][1], word(g8, 2 * vv), word(g8, 2 * vv + 1));
            res[ci][vv][2 * p] = pack2(d[0], d[1]);
            res[ci][vv][2 * p + 1] = pack2(d[2], d[3]);
          }
        }
#pragma unroll
      for (int i = 0; i < 4; i++)
        sts4(ad[i >> 1] + (i & 1) * 8192, res[i >> 1][i & 1][0], res[i >> 1][i & 1][1], res[i >> 1][i & 1][2], res[i >> 1][i & 1][3]);
      bar_sync(NB_CONS, 256);
      const uint32_t eb = e2 + ((warp * 16 + t) * 8 + (g ^ (2 * t) ^ (2 * (warp & 3)))) * 16;
      lds_frag(q[0], q[1], eb, eb + 512);
      lds_frag(q[2], q[3], eb + 1024, eb + 1536);
      cdft16(q, g2, o);
#pragma unroll
      for (int vv = 0; vv < 4; vv++) {
        o[vv].y &= ~1u;
        o[vv].z = (o[vv].z & ~1u) | tag;
        st_tag(zp + vv * 256, o[vv], tag);
      }
    }
    {
      const uint4* const zp = &scr->Z1[((t * 8 + warp) * 128 + c) * 8 + g];
      const uint32_t tst = clock32();
      uint4 gb[4], ga[4], gc[4], tw[4];
      uint2 xr[2][4];
      uint2* lnp[2];
#pragma unroll
      for (int r = 0; r < 2; r++) {
        const int row = 16 * f + 2 * warp + r;
        lnp[r] = reinterpret_cast<uint2*>(&scr->LN[(rb * 8 + (g >> 2)) * 1024 + row * 8 + ((2 * (g & 3) + (t >> 1)) ^ (row & 7))]) + (t & 1);
        asm volatile("" : "+l"(lnp[r]));
      }
#pragma unroll
      for (int i = 0; i < 4; i++) {
        gc[i] = lds4(sbase + SM_FC + 2048 + i * 512 + lane * 16);
        gb[i] = lds4(TOFF(gb) + i * 512);
        ga[i] = lds4(TOFF(ga) + i * 512);
        tw[i] = lds4(TOFF(tw3) + i * 512);
        const int ch = 2 * (g + 8 * i) + (t >> 1);
#pragma unroll
        for (int r = 0; r < 2; r++) xr[r][i] = lds2(sbase + SM_X + (2 * warp + r) * 1024 + ((ch ^ ((ch >> 3) & 1)) * 16) + (t & 1) * 8);
      }
      spin_until(tst + POLL_DELAY2);
      ld_tag4_issue<32768>(q, zp);
      ld_tag4_finish<32768, true>(q, zp, tag);
      if (lane == 0) mbar_arrive(BAR(sig, 1));
      reg_frag(q, ones);
      cdft16(q, gc, o);
#pragma unroll
      for (int vv = 0; vv < 4; vv++)
        sts4(sbase + SM_E + (((4 * vv + t) * 8 + warp) * 8 + (g ^ (warp & 6) ^ (2 * t))) * 16, o[vv].x, o[vv].y, o[vv].z, o[vv].w);
      bar_sync(NB_CONS, 256);
      uint32_t hv[2][8];
      const float mk = t == 0 ? 0.f : 1.f;
#pragma unroll
      for (int r = 0; r < 2; r++) {
        const int j = 2 * warp + r;
        uint4 u[2];
#pragma unroll
        for (int h = 0; h < 2; h++) u[h] = lds4(sbase + SM_E + ((j * 8 + 2 * t + h) * 8 + (g ^ (2 * t) ^ (2 * (j & 3)))) * 16);
        const uint32_t bp[4][2] = {{u[0].x, u[1].x & ones}, {u[0].y & ones, u[1].y}, {u[0].z, u[1].z & ones}, {u[0].w & ones, u[1].w}};
        float y[2][2][4];
#pragma unroll
        for (int i = 0; i < 2; i++) {
          float lo[4], hi[4], e[4];
          mma_az(lo, gb[2 * i], bp[0][0], bp[0][1]);
          mma_az(hi, gb[2 * i + 1], bp[2][0], bp[2][1]);
          mma_az(e, gb[2 * i], bp[1][0], bp[1][1]);
          mma_a(e, gb[2 * i + 1], bp[3][0], bp[3][1]);
          const uint4 &ka = tw[2 * i], &kb = tw[2 * i + 1];
          const float tr0 = fmaf(hi[0], mk, lo[0]), ti0 = fmaf(hi[2], mk, lo[2]);
          const float tr1 = lo[1] + hi[1], ti1 = lo[3] + hi[3];
          const float vr0 = tr0 * u2f(ka.x) - ti0 * u2f(ka.y), vi0 = tr0 * u2f(ka.y) + ti0 * u2f(ka.x);
          const float vr1 = tr1 * u2f(ka.z) - ti1 * u2f(ka.w), vi1 = tr1 * u2f(ka.w) + ti1 * u2f(ka.z);
          const uint32_t b0 = pack2(t == 0 ? hi[0] : vr0, vr1), b1 = pack2(t == 0 ? vr0 : vi0, vi1);
          const uint32_t b2 = pack2(e[0] * u2f(kb.x) - e[2] * u2f(kb.y), e[1] * u2f(kb.z) - e[3] * u2f(kb.w));
          const uint32_t b3 = pack2(e[0] * u2f(kb.y) + e[2] * u2f(kb.x), e[1] * u2f(kb.w) + e[3] * u2f(kb.z));
#pragma unroll
          for (int mt = 0; mt < 2; mt++) {
            mma_az(y[mt][i], ga[2 * mt], b0, b1);
            mma_a(y[mt][i], ga[2 * mt + 1], b2, b3);
          }
        }
#pragma unroll
        for (int i = 0; i < 4; i++) {
          hv[r][2 * i] = hadd2_bf16(xr[r][i].x, pack2(y[i >> 1][0][2 * (i & 1)], y[i >> 1][0][2 * (i & 1) + 1]));
          hv[r][2 * i + 1] = hadd2_bf16(xr[r][i].y, pack2(y[i >> 1][1][2 * (i & 1)], y[i >> 1][1][2 * (i & 1) + 1]));
        }
      }
      float mean[2];
      uint32_t mb[2];
#pragma unroll
      for (int r = 0; r < 2; r++) {
        mean[r] = sum_groups(quad_sum(hv[r])) * (1.f / 512.f);
        mb[r] = pack2(mean[r], mean[r]);
      }
#pragma unroll
      for (int i = 0; i < 4; i++)
#pragma unroll
        for (int r = 0; r < 2; r++) {
          hv[r][2 * i] = hsub2_bf16(hv[r][2 * i], mb[r]);
          hv[r][2 * i + 1] = hsub2_bf16(hv[r][2 * i + 1], mb[r]);
          st_tag8(lnp[r] + i * 4096, hv[r][2 * i], hv[r][2 * i + 1], i == 0 ? tag : (hv[r][2 * i] & 1u));
        }
      bar_arrive(NB_LN, 288);
      const uint32_t ones2 = ~(lds2(BAR(epoch, 0)).x >> 31);
      float rstd[2];
#pragma unroll
      for (int r = 0; r < 2; r++) {
        hv[r][0] &= ones2;
        rstd[r] = row_rstd(hv[r], mean[r] - bf_lo(mb[r]));
      }
      if (lane == 0)
        st_tag(&scr->ST[rb * 64 + 8 * f + warp], make_uint4(mb[0] << 16, __float_as_uint(rstd[0]), mb[1] << 16, __float_as_uint(rstd[1])), tag);
    }
    const int wgi = warp >> 2, wq = warp & 3;
    uint4* const pbase = &scr->P[rb * 28 * 1024 + warp * 128 + lane];
    const uint32_t a_lo0 = desc_lo(sbase + wgi * 8192, 16);
    const uint32_t ebar = lane == 0 ? BAR(empty1, 0) : RBAR(empty1, 0);
    float r0, r1;
    uint4 px[8], py[6];
    const int rh = wgi ^ kh ^ 1;
    const uint4* const psrc = &scr->P[(rb2 * 28 + 14 * kh) * 1024 + (4 * rh + wq) * 128 + lane];
    const uint32_t pa0 = sbase + (4 * rh + wq) * 2048;
    uint4 pf[3][4];
    uint32_t rdy = 0;
    {
      float acc[128];
#pragma unroll
      for (int i = 0; i < 128; i++) acc[i] = 0.f;
      const uint32_t b_lo0 = desc_lo(sbase + 8 * SLOT, 4096);
      const uint32_t t3 = clock32();
      if (WARM) {
        wg_fence();
#pragma unroll
        for (int i = 0; i < WARM; i++) wgmma_n256(acc, desc64(a_lo0 + 6 * 1024, HI128), desc64(b_lo0, HI128));
        wg_commit();
      }
      const uint4* const ap = &scr->LN[rb * 8 * 1024 + wgi * 512 + (tid & 127)];
      uint4 av[NLL][4];
      spin_until(t3 + POLL_DELAY3);
#pragma unroll
      for (int kb = 0; kb < NLL; kb++) ld_tag4_issue<128>(av[kb], ap + kb * 1024);
      bar_sync(NB_CONS, 256);
      uint32_t slot = 2;
      auto stage_x = [&](int kb, int hh) {
        if (LAGX && hh == ((16 - LAGX) & 1) && kb == ((16 - LAGX) >> 1) && wgi == 1) bar_sync(NB_LAG, 256);
        mbar_wait(BAR(full1, 2 * kb + hh));
        const uint32_t al = a_lo0 + kb * 1024 + hh * 4, bl = b_lo0 + slot * 1024;
        wg_fence();
        wgmma_n256(acc, desc64(al, HI128), desc64(bl, HI128), (kb | hh) != 0 ? 1 : ~ones);
        wgmma_n256(acc, desc64(al + 2, HI128), desc64(bl + 128, HI128));
        wg_commit();
        if (LAGX && hh == 1 && kb == 7 && wgi == 0) bar_arrive(NB_LAG, 256);
        wg_wait<1>();
        if ((kb | hh) != 0 && lane < 2) mbar_arrive_remote(ebar + 8 * (2 * kb + hh - 1));
        if (++slot == 6) slot = 0;
      };
#pragma unroll
      for (int kb = 0; kb < NLL; kb++) {
        ld_tag4_finish<128, true>(av[kb], ap + kb * 1024, tag);
#pragma unroll
        for (int i = 0; i < 4; i++)
          sts4(sbase + kb * SLOT + wgi * 8192 + ((tid & 127) + 128 * i) * 16, av[kb][i].x, av[kb][i].y, av[kb][i].z, av[kb][i].w);
        asm volatile("fence.proxy.async.shared::cta;" ::: "memory");
        bar_sync(NB_WG + wgi, 128);
        if (kb > 0) stage_x(kb - 1, 1);
        stage_x(kb, 0);
      }
      stage_x(NLL - 1, 1);
#pragma unroll 1
      for (int kb = NLL; kb < 8; kb++) {
        mbar_wait(BAR(fullA, kb));
        stage_x(kb, 0);
        stage_x(kb, 1);
      }
      mbar_wait(BAR(sbar, 0), 0);
      r0 = __uint_as_float(lds2(sstat + (16 * warp + g) * 8).y);
      r1 = __uint_as_float(lds2(sstat + (16 * warp + g + 8) * 8).y);
      wg_wait<0>();
      if (lane < 2) mbar_arrive_remote(ebar + 8 * 15);
      make_p<8, false>(acc, r0, r1, px, pbase, 0, tag);
    }
    {
      float acc[96];
#pragma unroll
      for (int i = 0; i < 96; i++) acc[i] = 0.f;
      const uint32_t b_lo0 = desc_lo(sbase + 8 * SLOT, 2048);
      uint4* const pdst = pbase + ((7 * f + 3 * (f & 1)) >> 1) * 1024;
      auto stage_y = [&](int k) {
        if (LAGY && k == 16 - LAGY && wgi == 1) bar_sync(NB_LAG, 256);
        mbar_wait(BAR(full1, 16 + k));
        const uint32_t al = a_lo0 + (k >> 1) * 1024 + (k & 1) * 4, bl = b_lo0 + (k & 7) * 768;
        wg_fence();
        wgmma_n192(acc, desc64(al, HI128), desc64(bl, HI64));
        wgmma_n192(acc, desc64(al + 2, HI128), desc64(bl + 64, HI64));
        wg_commit();
      };
#pragma unroll
      for (int k = 0; k < 4; k++) {
        stage_y(k);
        st_tag(pdst + (k >> 1) * 1024 + (k & 1) * 64, px[2 * k], tag);
        st_tag(pdst + (k >> 1) * 1024 + (k & 1) * 64 + 32, px[2 * k + 1], tag);
        if (k == 3 && lane == 0) red_relaxed(&scr->cnt[(C_PX + rb) * 32 + (f >> 2)]);
        wg_wait<1>();
        if (k != 0 && lane < 2) mbar_arrive_remote(ebar + 8 * (15 + k));
      }
#pragma unroll 1
      for (int k = 4; k < 16; k++) {
        stage_y(k);
        if (LAGY && k == 15 && wgi == 0) bar_arrive(NB_LAG, 256);
        wg_wait<1>();
        if (lane < 2) mbar_arrive_remote(ebar + 8 * (15 + k));
      }
      rdy = __all_sync(0xffffffffu, mbar_test(BAR(fullP, 0)) & mbar_test(BAR(full2, 0)) & mbar_test(BAR(fullP, 1)));
      if (rdy) {
#pragma unroll
        for (int kk = 0; kk < 4; kk++) pf[0][kk] = lds4(pa0 + 4 * SLOT + kk * 512 + lane * 16);
      }
      wg_wait<0>();
      if (lane < 2) mbar_arrive_remote(ebar + 8 * 31);
      make_p<6, true, 0, REDPOS>(acc, r0, r1, py, pbase, 14 * f + ((f & 1) ? 0 : 8), tag);
      if (lane == 0) red_relaxed(&scr->cnt[(C_PY + rb) * 32 + (f >> 1)]);
      make_p<6, true, REDPOS, 6>(acc, r0, r1, py, pbase, 14 * f + ((f & 1) ? 0 : 8), tag);
    }
    {
      float acc[64];
      const uint32_t b2_lo0 = desc_lo(sbase, 8192);
      const uint32_t pbar = ebar + (uint32_t)(offsetof(Bars, emptyP) - offsetof(Bars, empty1));
      if (!rdy) {
        mbar_wait(BAR(fullP, 0));
#pragma unroll
        for (int kk = 0; kk < 4; kk++) pf[0][kk] = lds4(pa0 + 4 * SLOT + kk * 512 + lane * 16);
      }
#pragma unroll
      for (int s = 0; s < 14; s++) {
        uint4 (&a)[4] = pf[s % 3];
        ld_tag4_finish<32>(a, psrc + (int)((KORDER >> (4 * s)) & 15) * 1024, tag);
        if (s < 8 && lane < (s < 7 ? 2 : 1)) mbar_arrive_remote(pbar + 8 * s);
        if (s >= 2) {
          wg_wait<1>();
          if (s <= 8 && lane == 0) mbar_arrive(BAR(empty2, s - 2));
        }
        if (!rdy) {
          if (s < 13) mbar_wait(BAR(fullP, s + 1));
          mbar_wait(BAR(full2, s));
        }
        if (s == 14 - LAG2 && wgi == 1) {
          const float m0 = __uint_as_float(lds2(sstat + 1024 + (16 * wq + g) * 8).x);
          const float m1 = __uint_as_float(lds2(sstat + 1024 + (16 * wq + g + 8) * 8).x);
          const uint32_t hb = sbase + 4 * SLOT + (16 * wq + (lane & 15)) * 128;
          wg_wait<0>();
          mbar_wait(BAR(hbar, 0));
#pragma unroll
          for (int i = 0; i < 8; i++) {
            uint32_t h[4];
            asm volatile("ldmatrix.sync.aligned.m8n8.x4.shared.b16 {%0,%1,%2,%3}, [%4];"
                         : "=r"(h[0]), "=r"(h[1]), "=r"(h[2]), "=r"(h[3])
                         : "r"(hb + (i >> 2) * 8192 + (((2 * (i & 3) + (lane >> 4)) ^ (lane & 7)) * 16)) : "memory");
            const uint32_t mk = ((t & 1) == 0 && nq == 0) ? ~1u : ~0u;
#pragma unroll
            for (int e = 0; e < 4; e++) {
              acc[8 * i + 2 * e] += bf_lo(h[e] & mk) + ((e & 1) ? m1 : m0);
              acc[8 * i + 2 * e + 1] += __uint_as_float(h[e] & 0xffff0000u) + ((e & 1) ? m1 : m0);
            }
          }
          bar_sync(NB_LAG, 256);
        }
        const uint32_t bl = b2_lo0 + (uint32_t)((BSLOT >> (4 * s)) & 15) * 1024;
        wg_fence();
        if (s < 13) {
#pragma unroll
          for (int kk = 0; kk < 4; kk++)
            pf[(s + 1) % 3][kk] = lds4(pa0 + (uint32_t)((PSLOT >> (4 * (s + 1))) & 15) * SLOT + kk * 512 + lane * 16);
          rdy = mbar_test(BAR(full2, s + 1));
          if (s < 12) rdy &= mbar_test(BAR(fullP, s + 2));
        }
        if (s == 0) wgmma_rs_n128<0>(acc, a[0].x, a[0].y, a[0].z, a[0].w, desc64(bl, HI128));
        else wgmma_rs_n128<1>(acc, a[0].x, a[0].y, a[0].z, a[0].w, desc64(bl, HI128));
#pragma unroll
        for (int kk = 1; kk < 4; kk++) wgmma_rs_n128<1>(acc, a[kk].x, a[kk].y, a[kk].z, a[kk].w, desc64(bl + kk * 128, HI128));
        wg_commit();
      }
      if (wgi == 0) {
        bar_arrive(NB_LAG, 256);
        uint4* const dst = &scr->Z1[(tid >> 3) * 1024 + (c ^ 4) * 8 + (tid & 7)];
        wg_wait<0>();
#pragma unroll
        for (int i = 0; i < 8; i++)
          st_tag(dst + i * 16384, make_uint4(pack2(acc[8 * i], acc[8 * i + 1]), pack2(acc[8 * i + 2], acc[8 * i + 3]) | 1u,
                                           pack2(acc[8 * i + 4], acc[8 * i + 5]), pack2(acc[8 * i + 6], acc[8 * i + 7])), tag);
      } else {
        uint4 pv[2][4];
        const uint4* const xsrc = &scr->Z1[((tid & 127) >> 3) * 1024 + c * 8 + (tid & 7)];
        ld_tag4_issue<16384>(pv[0], xsrc);
        ld_tag4_issue<16384>(pv[1], xsrc + 65536);
        wg_wait<0>();
        uint32_t w[32];
#pragma unroll
        for (int i = 0; i < 32; i++) w[i] = pack2(acc[2 * i], acc[2 * i + 1]);
        int it = 0;
#pragma unroll 1
        while (!__all_sync(0xffffffffu, pv[0][0].y & pv[0][1].y & pv[0][2].y & pv[0][3].y & pv[1][0].y & pv[1][1].y & pv[1][2].y & pv[1][3].y & 1u)) {
          ld_tag4_issue<16384>(pv[0], xsrc);
          ld_tag4_issue<16384>(pv[1], xsrc + 65536);
          if (++it > SPIN_LIMIT) { die(); break; }
        }
#pragma unroll
        for (int i = 0; i < 8; i++) {
          const uint4& p = pv[i >> 2][i & 3];
          asm volatile("stmatrix.sync.aligned.m8n8.x4.shared.b16 [%0], {%1,%2,%3,%4};"
                       ::"r"(pa0 + (9 + ((lane >> 3) & 1)) * SLOT + (lane & 7) * 256 + (((2 * i + (lane >> 4)) ^ (lane & 7)) * 16)),
                         "r"(hadd2_bf16(w[4 * i], p.x & ~1u)), "r"(hadd2_bf16(w[4 * i + 1], p.y & ~1u)), "r"(hadd2_bf16(w[4 * i + 2], p.z)),
                         "r"(hadd2_bf16(w[4 * i + 3], p.w)) : "memory");
        }
        __syncwarp();
        uint4* const dst = reinterpret_cast<uint4*>(out) + (16 * (c >> 4) + 2 * (4 * rh + wq) + (rb2 & 1) + 128 * (lane >> 4)) * 64 + nq * 16 + (lane & 15);
#pragma unroll
        for (int i = 0; i < 8; i++) {
          const int r = 2 * (i & 3) + (lane >> 4);
          dst[i * 256 * 64] = lds4(pa0 + (9 + (i >> 2)) * SLOT + r * 256 + (((lane & 15) ^ r) * 16));
        }
      }
    }
  }
#undef BAR
#undef TOFF
#undef RBAR
}

typedef CUresult (*EncodeFn)(CUtensorMap*, CUtensorMapDataType, cuuint32_t, void*, const cuuint64_t*, const cuuint64_t*,
                             const cuuint32_t*, const cuuint32_t*, CUtensorMapInterleave, CUtensorMapSwizzle,
                             CUtensorMapL2promotion, CUtensorMapFloatOOBfill);

}

extern "C" void kernel_launch(void* const* d_in, const int* in_sizes, int n_in, void* d_out, int out_size) {
  (void)in_sizes; (void)n_in; (void)out_size;
  static EncodeFn encode = nullptr;
  static void *tab = nullptr, *scr = nullptr;
  if (!encode) {
    void* fn = nullptr;
    cudaDriverEntryPointQueryResult qr;
    cudaGetDriverEntryPoint("cuTensorMapEncodeTiled", &fn, cudaEnableDefault, &qr);
    encode = (EncodeFn)fn;
    cudaGetSymbolAddress(&tab, g_tab);
    cudaGetSymbolAddress(&scr, g_scr);
    cudaFuncSetAttribute(fused_kernel, cudaFuncAttributeMaxDynamicSharedMemorySize, SMEM_BYTES);
  }
  CUtensorMap tmGX, tmUX, tmGY, tmUY, tmD, tmWR, tmWI;
  const cuuint32_t es[5] = {1, 1, 1, 1, 1};
  auto enc = [&](CUtensorMap* m, void* p, int rank, const cuuint64_t* gd, const cuuint64_t* gs, const cuuint32_t* bd,
                 CUtensorMapSwizzle sw, CUtensorMapL2promotion pr) {
    encode(m, CU_TENSOR_MAP_DATA_TYPE_BFLOAT16, rank, p, gd, gs, bd, es, CU_TENSOR_MAP_INTERLEAVE_NONE, sw, pr,
           CU_TENSOR_MAP_FLOAT_OOB_FILL_NONE);
  };
  {
    const cuuint64_t gd[3] = {64, 512, 28}, gs[2] = {3584, 128};
    const cuuint32_t bd[3] = {64, 32, 2};
    enc(&tmGX, d_in[4], 3, gd, gs, bd, CU_TENSOR_MAP_SWIZZLE_128B, CU_TENSOR_MAP_L2_PROMOTION_L2_256B);
    enc(&tmUX, d_in[5], 3, gd, gs, bd, CU_TENSOR_MAP_SWIZZLE_128B, CU_TENSOR_MAP_L2_PROMOTION_L2_256B);
  }
  {
    const cuuint64_t gd[3] = {32, 512, 56}, gs[2] = {3584, 64};
    const cuuint32_t bd[3] = {32, 32, 3};
    enc(&tmGY, d_in[4], 3, gd, gs, bd, CU_TENSOR_MAP_SWIZZLE_64B, CU_TENSOR_MAP_L2_PROMOTION_L2_128B);
    enc(&tmUY, d_in[5], 3, gd, gs, bd, CU_TENSOR_MAP_SWIZZLE_64B, CU_TENSOR_MAP_L2_PROMOTION_L2_128B);
  }
  {
    const cuuint64_t gd[3] = {64, 1792, 8}, gs[2] = {1024, 128};
    const cuuint32_t bd[3] = {64, 64, 2};
    enc(&tmD, d_in[6], 3, gd, gs, bd, CU_TENSOR_MAP_SWIZZLE_128B, CU_TENSOR_MAP_L2_PROMOTION_L2_256B);
  }
  {
    const cuuint64_t gd[3] = {4112, 8, 16}, gs[2] = {16 * 8224, 8224};
    const cuuint32_t bd[3] = {40, 8, 16};
    enc(&tmWR, d_in[1], 3, gd, gs, bd, CU_TENSOR_MAP_SWIZZLE_NONE, CU_TENSOR_MAP_L2_PROMOTION_NONE);
    enc(&tmWI, d_in[2], 3, gd, gs, bd, CU_TENSOR_MAP_SWIZZLE_NONE, CU_TENSOR_MAP_L2_PROMOTION_NONE);
  }
  fused_kernel<<<NCTA, NTHREADS, SMEM_BYTES>>>((const __nv_bfloat16*)d_in[0], (const Tables*)tab, (Scratch*)scr,
                                               (__nv_bfloat16*)d_out, (const char*)d_in[4], (const char*)d_in[5],
                                               (const char*)d_in[6], tmWR, tmWI, tmGX, tmUX, tmGY, tmUY, tmD);
}
```

```cpp
#include <cuda_runtime.h>
#include <cuda_bf16.h>
#include <cuda.h>
#include <stdint.h>

namespace {

constexpr int NCTA = 128;
constexpr int NTHREADS = 384;
constexpr int SLOT = 16384;
constexpr int SMEM_BYTES = 14 * SLOT + 3072;
constexpr int SPIN_LIMIT = 1 << 22;

struct Scratch {
  uint4 Z1[128 * 1024];
  uint4 LN[16 * 8 * 1024];
  uint4 P[16 * 28 * 1024];
  uint4 ST[1024];
  unsigned cnt[64 * 32];
};
__device__ __align__(1024) Scratch g_scr;

constexpr double ccos(int i, int n) {
  i &= n - 1;
  if (i > n / 2) i = n - i;
  if (4 * i == n) return 0.0;
  const bool neg = 4 * i > n;
  if (neg) i = n / 2 - i;
  const double a = 6.283185307179586476925 * i / n, a2 = a * a;
  double term = 1.0, sum = 1.0;
  for (int k = 1; k < 14; k++) { term *= -a2 / ((2 * k - 1) * (2 * k)); sum += term; }
  return neg ? -sum : sum;
}
constexpr double csin(int i, int n) { return ccos(i - n / 4, n); }
constexpr unsigned fbits(double v, int mant) {
  if (v == 0.0) return 0;
  const unsigned sg = v < 0 ? 1u : 0u;
  if (v < 0) v = -v;
  int e = 127;
  while (v < 1.0) { v *= 2.0; e--; }
  const unsigned m = (unsigned)((v - 1.0) * (double)(1u << mant) + 0.5);
  return (sg << (8 + mant)) + ((unsigned)e << mant) + m;
}
constexpr unsigned pkb(double lo, double hi) { return fbits(lo, 7) | (fbits(hi, 7) << 16); }
constexpr double fa_elem(int mt, int r, int n1) {
  const int k1 = 8 * mt + (r & 7);
  return r < 8 ? ccos(k1 * n1, 32) : k1 == 0 ? ccos(16 * n1, 32) : -csin(k1 * n1, 32);
}
constexpr unsigned cfrag_c(int idx, int n, int ri, double s = 1.0) {
  return ri ? pkb(-s * csin(idx, n), s * ccos(idx, n)) : pkb(s * ccos(idx, n), s * csin(idx, n));
}
struct Tables {
  unsigned fa[4][32][4];
  unsigned fb[4][32][4];
  unsigned tw1[6][32][4];
  unsigned f2[8][4][32][4];
  unsigned g2[8][4][32][4];
  unsigned gb[4][32][4];
  unsigned ga[4][32][4];
  unsigned tw3[4][32][4];
  unsigned f8[32][4], g8[32][4];
};
constexpr int T1_BYTES = 7168, T2_BYTES = 39936;
static_assert(sizeof(Tables) == T1_BYTES + T2_BYTES, "table size");
constexpr Tables make_tables() {
  Tables T = {};
  for (int l = 0; l < 32; l++) {
    const int g = l >> 2, t = l & 3;
    for (int a = 0; a < 2; a++)
      for (int b = 0; b < 2; b++) {
        for (int r = 0; r < 4; r++) {
          const int row = g + 8 * (r & 1), col = 2 * t + 8 * (r >> 1);
          T.fa[2 * a + b][l][r] = pkb(fa_elem(a, row, 16 * b + col), fa_elem(a, row, 16 * b + col + 1));
          T.ga[2 * a + b][l][r] = pkb(fa_elem(b, col, 16 * a + row), fa_elem(b, col + 1, 16 * a + row));
        }
        const double sg = b ? -1.0 : 1.0;
        for (int h = 0; h < 2; h++) {
          const int ri = g & 1, m = 2 * (g >> 1) + h, k2 = b ? 15 - m : m;
          const int pa = (8 * a + 2 * t) * k2, pb = (8 * a + 2 * t + 1) * k2;
          T.fb[2 * a + b][l][2 * h] = ri == 0 ? pkb(ccos(pa, 16), ccos(pb, 16)) : pkb(-sg * csin(pa, 16), -sg * csin(pb, 16));
          T.fb[2 * a + b][l][2 * h + 1] = ri == 0 ? pkb(csin(pa, 16), csin(pb, 16)) : pkb(sg * ccos(pa, 16), sg * ccos(pb, 16));
        }
        const int n2 = 4 * (g >> 1) + 2 * a + (g & 1);
        for (int h = 0; h < 2; h++) {
          const int p = n2 * (b ? 15 - 2 * t - h : 2 * t + h);
          T.gb[2 * a + b][l][2 * h] = pkb(ccos(p, 16), -sg * csin(p, 16));
          T.gb[2 * a + b][l][2 * h + 1] = pkb(csin(p, 16), sg * ccos(p, 16));
          const int k1 = 8 * b + 2 * t + h, q = n2 * (k1 == 0 ? 16 : k1);
          T.tw3[2 * a + b][l][2 * h] = fbits(ccos(q, 512), 23);
          T.tw3[2 * a + b][l][2 * h + 1] = fbits(csin(q, 512), 23);
        }
        const int p = (8 * a + 2 * t + b) * (g == 0 ? 16 : g);
        T.tw1[2 * a + b][l][0] = fbits(g == 0 ? 0.0 : ccos(p, 512), 23);
        T.tw1[2 * a + b][l][1] = fbits(g == 0 ? ccos(p, 512) : csin(p, 512), 23);
        T.tw1[2 * a + b][l][2] = fbits(g == 0 ? 0.0 : -csin(p, 512), 23);
        T.tw1[2 * a + b][l][3] = fbits(g == 0 ? -csin(p, 512) : ccos(p, 512), 23);
        T.tw1[4 + a][l][2 * b] = fbits(ccos((8 * a + 2 * t + b) * (g + 8), 512), 23);
        T.tw1[4 + a][l][2 * b + 1] = fbits(csin((8 * a + 2 * t + b) * (g + 8), 512), 23);
      }
    for (int i = 0; i < 4; i++) {
      const int p8 = (t + 4 * (i & 1)) * (4 * (i >> 1) + (g >> 1));
      T.f8[l][i] = cfrag_c(p8, 8, g & 1);
      T.g8[l][i] = cfrag_c(-p8, 8, g & 1, 1.0 / (1 << 19));
    }
    for (int w = 0; w < 8; w++)
      for (int i = 0; i < 16; i++) {
        const int kidx = t + 4 * (i & 1) + 8 * (i >> 3), nidx = 4 * ((i >> 1) & 3) + (g >> 1);
        T.f2[w][i >> 2][l][i & 3] = cfrag_c((8 * kidx + w) * nidx, 128, g & 1);
        T.g2[w][i >> 2][l][i & 3] = cfrag_c(-(8 * nidx + w) * kidx, 128, g & 1);
      }
  }
  return T;
}
__device__ const __align__(128) Tables g_tab = make_tables();

__device__ __forceinline__ void die() { asm volatile("st.global.u32 [%0], %1;" ::"l"(0ull), "r"(0) : "memory"); }
__device__ __forceinline__ uint32_t s2u(const void* p) { return (uint32_t)__cvta_generic_to_shared(p); }
__device__ __forceinline__ void mbar_init(uint32_t b, int c) { asm volatile("mbarrier.init.shared::cta.b64 [%0], %1;" ::"r"(b), "r"(c)); }
__device__ __forceinline__ void mbar_expect(uint32_t b, int bytes) {
  asm volatile("mbarrier.arrive.expect_tx.shared::cta.b64 _, [%0], %1;" ::"r"(b), "r"(bytes) : "memory");
}
__device__ __forceinline__ void mbar_arrive(uint32_t b) { asm volatile("mbarrier.arrive.shared::cta.b64 _, [%0];" ::"r"(b) : "memory"); }
__device__ __forceinline__ uint32_t mbar_try(uint32_t b, uint32_t parity) {
  uint32_t ok;
  asm volatile("{.reg .pred p; mbarrier.try_wait.parity.shared::cta.b64 p, [%1], %2; selp.u32 %0,1,0,p;}"
               : "=r"(ok) : "r"(b), "r"(parity) : "memory");
  return ok;
}
__device__ __forceinline__ uint32_t mbar_test(uint32_t b) {
  uint32_t ok;
  asm volatile("{.reg .pred p; mbarrier.test_wait.parity.shared::cta.b64 p, [%1], 0; selp.u32 %0,1,0,p;}" : "=r"(ok) : "r"(b) : "memory");
  return ok;
}
__device__ __forceinline__ void mbar_wait(uint32_t b, uint32_t parity = 0) {
  int it = 0;
#pragma unroll 1
  while (!mbar_try(b, parity))
    if (++it > SPIN_LIMIT) { die(); break; }
}
__device__ __forceinline__ void bar_sync(int id, int n) { asm volatile("bar.sync %0, %1;" ::"r"(id), "r"(n) : "memory"); }
__device__ __forceinline__ void bar_arrive(int id, int n) { asm volatile("bar.arrive %0, %1;" ::"r"(id), "r"(n) : "memory"); }
__device__ __forceinline__ void red_release(unsigned* p) { asm volatile("red.release.gpu.global.add.u32 [%0], 1;" ::"l"(p) : "memory"); }
__device__ __forceinline__ void red_relaxed(unsigned* p) { asm volatile("red.relaxed.gpu.global.add.u32 [%0], 1;" ::"l"(p) : "memory"); }
__device__ __forceinline__ unsigned ld_acquire(const unsigned* p) {
  unsigned v;
  asm volatile("ld.acquire.gpu.global.u32 %0, [%1];" : "=r"(v) : "l"(p) : "memory");
  return v;
}
__device__ __forceinline__ unsigned ld_relaxed(const unsigned* p) {
  unsigned v;
  asm volatile("ld.relaxed.gpu.global.u32 %0, [%1];" : "=r"(v) : "l"(p) : "memory");
  return v;
}
__device__ __forceinline__ void wait_counter(const unsigned* p, unsigned target) {
  int it = 0;
  while ((int)(ld_acquire(p) - target) < 0)
    if (++it > SPIN_LIMIT) { die(); break; }
}
__device__ __forceinline__ void sts4(uint32_t a, uint32_t x, uint32_t y, uint32_t z, uint32_t w) {
  asm volatile("st.shared.v4.u32 [%0], {%1,%2,%3,%4};" ::"r"(a), "r"(x), "r"(y), "r"(z), "r"(w) : "memory");
}
__device__ __forceinline__ uint4 lds4(uint32_t a) {
  uint4 v;
  asm volatile("ld.shared.v4.u32 {%0,%1,%2,%3}, [%4];" : "=r"(v.x), "=r"(v.y), "=r"(v.z), "=r"(v.w) : "r"(a) : "memory");
  return v;
}
__device__ __forceinline__ uint32_t pack2(float lo, float hi) {
  uint32_t r;
  asm("cvt.rn.bf16x2.f32 %0, %1, %2;" : "=r"(r) : "f"(hi), "f"(lo));
  return r;
}
__device__ __forceinline__ float bf_lo(uint32_t v) { return __uint_as_float(v << 16); }
__device__ __forceinline__ uint32_t hadd2_bf16(uint32_t a, uint32_t b) {
  uint32_t r;
  asm("add.rn.bf16x2 %0, %1, %2;" : "=r"(r) : "r"(a), "r"(b));
  return r;
}
__device__ __forceinline__ void mma16816(float (&d)[4], uint32_t a0, uint32_t a1, uint32_t a2, uint32_t a3, uint32_t b0, uint32_t b1) {
  asm("mma.sync.aligned.m16n8k16.row.col.f32.bf16.bf16.f32 {%0,%1,%2,%3}, {%4,%5,%6,%7}, {%8,%9}, {%0,%1,%2,%3};"
      : "+f"(d[0]), "+f"(d[1]), "+f"(d[2]), "+f"(d[3])
      : "r"(a0), "r"(a1), "r"(a2), "r"(a3), "r"(b0), "r"(b1));
}
__device__ __forceinline__ void mma16816_z(float (&d)[4], uint32_t a0, uint32_t a1, uint32_t a2, uint32_t a3, uint32_t b0, uint32_t b1) {
  asm("{.reg .f32 z; mov.f32 z, 0f00000000;\n"
      "mma.sync.aligned.m16n8k16.row.col.f32.bf16.bf16.f32 {%0,%1,%2,%3}, {%4,%5,%6,%7}, {%8,%9}, {z,z,z,z};}"
      : "=f"(d[0]), "=f"(d[1]), "=f"(d[2]), "=f"(d[3])
      : "r"(a0), "r"(a1), "r"(a2), "r"(a3), "r"(b0), "r"(b1));
}
template <int N>
__device__ __forceinline__ void cs_frac(int idx, float& c, float& s) {
  int i = ((idx + N / 2) & (N - 1)) - N / 2;
  float a = (float)i * (6.283185307179586f / N);
  c = __cosf(a);
  s = __sinf(a);
}
template <int N>
__device__ __forceinline__ uint32_t cfrag(int idx, int ri) {
  float c, s;
  cs_frac<N>(idx, c, s);
  return ri ? pack2(-s, c) : pack2(c, s);
}
__device__ __forceinline__ uint32_t word(const uint4& v, int e) { return e == 0 ? v.x : e == 1 ? v.y : e == 2 ? v.z : v.w; }
__device__ __forceinline__ void cdft16(const uint4 (&A)[4], const uint4 (&F)[4], uint4 (&o)[4]) {
  float acc[2][4][4];
#pragma unroll
  for (int ks = 0; ks < 2; ks++)
#pragma unroll
    for (int p = 0; p < 2; p++)
#pragma unroll
      for (int v = 0; v < 4; v++) {
        const uint4& a = A[2 * ks + p];
        const uint32_t b0 = word(F[ks * 2 + (v >> 1)], (v & 1) * 2), b1 = word(F[ks * 2 + (v >> 1)], (v & 1) * 2 + 1);
        if (ks == 0) mma16816_z(acc[p][v], a.x, a.y, a.z, a.w, b0, b1);
        else mma16816(acc[p][v], a.x, a.y, a.z, a.w, b0, b1);
      }
#pragma unroll
  for (int v = 0; v < 4; v++)
    o[v] = make_uint4(pack2(acc[0][v][0], acc[0][v][1]), pack2(acc[0][v][2], acc[0][v][3]),
                      pack2(acc[1][v][0], acc[1][v][1]), pack2(acc[1][v][2], acc[1][v][3]));
}
__device__ __forceinline__ void lds_frag(uint4& f0, uint4& f1, uint32_t a0, uint32_t a1) {
  asm volatile("ld.volatile.shared.v2.u32 {%0,%1}, [%8]; ld.volatile.shared.v2.u32 {%2,%3}, [%9];\n"
               "ld.volatile.shared.v2.u32 {%4,%5}, [%8+8]; ld.volatile.shared.v2.u32 {%6,%7}, [%9+8];"
               : "=r"(f0.x), "=r"(f0.y), "=r"(f0.z), "=r"(f0.w), "=r"(f1.x), "=r"(f1.y), "=r"(f1.z), "=r"(f1.w) : "r"(a0), "r"(a1) : "memory");
}
__device__ __forceinline__ void reg_frag(uint4 (&q)[4], uint32_t ones) {
#pragma unroll
  for (int ks = 0; ks < 2; ks++) {
    const uint4 a = q[2 * ks], b = q[2 * ks + 1];
    q[2 * ks] = make_uint4(a.x, a.y, b.x & ones, b.y & ones);
    q[2 * ks + 1] = make_uint4(a.z & ones, a.w & ones, b.z, b.w);
  }
}
__device__ __forceinline__ void st_tag(uint4* p, const uint4& v, uint32_t tag) {
  asm volatile("st.relaxed.gpu.global.v4.b32 [%0], {%1,%2,%3,%4};"
               ::"l"(p), "r"((v.x & ~1u) | tag), "r"(v.y), "r"(v.z), "r"(v.w) : "memory");
}
__device__ __forceinline__ void st_tag8(void* p, uint32_t x, uint32_t y, uint32_t tag) {
  asm volatile("st.relaxed.gpu.global.v2.b32 [%0], {%1,%2};" ::"l"(p), "r"((x & ~1u) | tag), "r"(y) : "memory");
}
__device__ __forceinline__ uint4 ld_b128(const uint4* p) {
  uint4 v;
  asm volatile("ld.relaxed.gpu.global.v4.b32 {%0,%1,%2,%3}, [%4];"
               : "=r"(v.x), "=r"(v.y), "=r"(v.z), "=r"(v.w) : "l"(p) : "memory");
  return v;
}
template <int STRIDE>
__device__ __forceinline__ void ld_tag4_issue(uint4 (&q)[4], const uint4* p) {
#pragma unroll
  for (int i = 0; i < 4; i++) q[i] = ld_b128(p + i * STRIDE);
}
template <int STRIDE, bool HALVES = false>
__device__ __forceinline__ void ld_tag4_finish(uint4 (&q)[4], const uint4* p, uint32_t tag) {
  int it = 0;
#pragma unroll 1
  while (__any_sync(0xffffffffu, ((q[0].x ^ tag) | (q[1].x ^ tag) | (q[2].x ^ tag) | (q[3].x ^ tag) |
                                  (HALVES ? (q[0].z ^ tag) | (q[1].z ^ tag) | (q[2].z ^ tag) | (q[3].z ^ tag) : 0u)) & 1u)) {
    ld_tag4_issue<STRIDE>(q, p);
    if (++it > SPIN_LIMIT) { die(); break; }
  }
#pragma unroll
  for (int i = 0; i < 4; i++) {
    asm volatile("and.b32 %0, %0, 0xfffffffe;" : "+r"(q[i].x));
    if (HALVES) q[i].z &= ~1u;
  }
}
__device__ __forceinline__ float quad_sum(const uint32_t (&a)[8]) {
  float d[4];
  mma16816_z(d, a[0], a[1], a[2], a[3], 0x3f803f80u, 0x3f803f80u);
  mma16816(d, a[4], a[5], a[6], a[7], 0x3f803f80u, 0x3f803f80u);
  return d[0] + d[2];
}
__device__ __forceinline__ float sum_groups(float v) {
  v += __shfl_xor_sync(0xffffffffu, v, 4);
  v += __shfl_xor_sync(0xffffffffu, v, 8);
  v += __shfl_xor_sync(0xffffffffu, v, 16);
  return v;
}
__device__ __forceinline__ uint32_t hsub2_bf16(uint32_t a, uint32_t b) {
  uint32_t r;
  asm("sub.rn.bf16x2 %0, %1, %2;" : "=r"(r) : "r"(a), "r"(b));
  return r;
}
__device__ __forceinline__ float row_rstd(const uint32_t (&c)[8], float delta) {
  uint32_t s[8];
#pragma unroll
  for (int i = 0; i < 8; i++) asm("mul.rn.bf16x2 %0, %1, %1;" : "=r"(s[i]) : "r"(c[i]));
  return rsqrtf(fmaxf(fmaf(-delta, delta, sum_groups(quad_sum(s)) * (1.f / 512.f)), 0.f) + 1e-5f);
}
__device__ __forceinline__ uint64_t desc64(uint32_t lo, uint32_t hi) {
  uint64_t d;
  asm("mov.b64 %0, {%1, %2};" : "=l"(d) : "r"(lo), "r"(hi));
  return d;
}
constexpr uint32_t desc_hi(uint32_t sbo, uint32_t swz) { return (sbo >> 4) | (swz << 30); }
__device__ __forceinline__ uint32_t desc_lo(uint32_t addr, uint32_t lbo) { return ((addr & 0x3FFFF) >> 4) | ((lbo >> 4) << 16); }
__device__ __forceinline__ void cp_async16(uint32_t dst, const void* src) {
  asm volatile("cp.async.cg.shared.global [%0], [%1], 16;" ::"r"(dst), "l"(src) : "memory");
}
__device__ __forceinline__ uint2 lds2(uint32_t a) {
  uint2 v;
  asm volatile("ld.shared.v2.u32 {%0,%1}, [%2];" : "=r"(v.x), "=r"(v.y) : "r"(a) : "memory");
  return v;
}
__device__ __forceinline__ uint32_t lds_u16(uint32_t a) {
  uint16_t v;
  asm volatile("ld.shared.u16 %0, [%1];" : "=h"(v) : "r"(a) : "memory");
  return v;
}
__device__ __forceinline__ void wg_fence() { asm volatile("wgmma.fence.sync.aligned;" ::: "memory"); }
__device__ __forceinline__ void wg_commit() { asm volatile("wgmma.commit_group.sync.aligned;" ::: "memory"); }
template <int N>
__device__ __forceinline__ void wg_wait() { asm volatile("wgmma.wait_group.sync.aligned %0;" ::"n"(N) : "memory"); }
__device__ __forceinline__ void bulk_load(uint32_t dst, const void* src, int bytes, uint32_t bar) {
  asm volatile("cp.async.bulk.shared::cluster.global.mbarrier::complete_tx::bytes [%0], [%1], %2, [%3];"
               ::"r"(dst), "l"(src), "r"(bytes), "r"(bar) : "memory");
}
__device__ __forceinline__ void bulk_load_mc(uint32_t dst, const void* src, int bytes, uint32_t bar) {
  asm volatile("cp.async.bulk.shared::cluster.global.mbarrier::complete_tx::bytes.multicast::cluster [%0], [%1], %2, [%3], %4;"
               ::"r"(dst), "l"(src), "r"(bytes), "r"(bar), "h"((uint16_t)3) : "memory");
}
__device__ __forceinline__ void tma3(uint32_t dst, const CUtensorMap* tm, uint32_t bar, int c0, int c1, int c2) {
  asm volatile("cp.async.bulk.tensor.3d.shared::cluster.global.mbarrier::complete_tx::bytes [%0], [%1, {%3,%4,%5}], [%2];"
               ::"r"(dst), "l"(tm), "r"(bar), "r"(c0), "r"(c1), "r"(c2) : "memory");
}
__device__ __forceinline__ void tma3_mc(uint32_t dst, const CUtensorMap* tm, uint32_t bar, int c1, int c2) {
  asm volatile("cp.async.bulk.tensor.3d.shared::cluster.global.mbarrier::complete_tx::bytes.multicast::cluster [%0], [%1, {%3,%4,%5}], [%2], %6;"
               ::"r"(dst), "l"(tm), "r"(bar), "r"(0), "r"(c1), "r"(c2), "h"((uint16_t)3) : "memory");
}
__device__ __forceinline__ void mbar_arrive_remote(uint32_t rb) {
  asm volatile("mbarrier.arrive.shared::cluster.b64 _, [%0];" ::"r"(rb) : "memory");
}
__device__ __forceinline__ uint4 ldg_ca4(const void* p) {
  uint4 v;
  asm volatile("ld.global.ca.v4.u32 {%0,%1,%2,%3}, [%4];" : "=r"(v.x), "=r"(v.y), "=r"(v.z), "=r"(v.w) : "l"(p) : "memory");
  return v;
}
__device__ __forceinline__ float u2f(uint32_t v) { return __uint_as_float(v); }
__device__ __forceinline__ void mma_az(float (&d)[4], const uint4& a, uint32_t b0, uint32_t b1) { mma16816_z(d, a.x, a.y, a.z, a.w, b0, b1); }
__device__ __forceinline__ void mma_a(float (&d)[4], const uint4& a, uint32_t b0, uint32_t b1) { mma16816(d, a.x, a.y, a.z, a.w, b0, b1); }
__device__ __forceinline__ uint32_t clock32() {
  uint32_t v;
  asm volatile("mov.u32 %0, %%clock;" : "=r"(v) :: "memory");
  return v;
}
__device__ __forceinline__ float swiglu(float g, float u, float r) {
  float hg = (0.5f * r) * g, th;
  asm("tanh.approx.f32 %0, %1;" : "=f"(th) : "f"(hg));
  return fmaf(hg, th, hg) * (r * u);
}
__device__ __forceinline__ void l2_prefetch(const void* p, int bytes) {
  asm volatile("cp.async.bulk.prefetch.L2.global [%0], %1;" ::"l"(p), "r"(bytes) : "memory");
}

__device__ __forceinline__ void wgmma_n256(float (&d)[128], uint64_t da, uint64_t db, int sd = 1) {
  asm volatile("{.reg .pred p; setp.ne.b32 p, %130, 0;\n"
      "wgmma.mma_async.sync.aligned.m64n256k16.f32.bf16.bf16 {"
      "%0,%1,%2,%3,%4,%5,%6,%7,%8,%9,%10,%11,%12,%13,%14,%15,"
      "%16,%17,%18,%19,%20,%21,%22,%23,%24,%25,%26,%27,%28,%29,%30,%31,"
      "%32,%33,%34,%35,%36,%37,%38,%39,%40,%41,%42,%43,%44,%45,%46,%47,"
      "%48,%49,%50,%51,%52,%53,%54,%55,%56,%57,%58,%59,%60,%61,%62,%63,"
      "%64,%65,%66,%67,%68,%69,%70,%71,%72,%73,%74,%75,%76,%77,%78,%79,"
      "%80,%81,%82,%83,%84,%85,%86,%87,%88,%89,%90,%91,%92,%93,%94,%95,"
      "%96,%97,%98,%99,%100,%101,%102,%103,%104,%105,%106,%107,%108,%109,%110,%111,"
      "%112,%113,%114,%115,%116,%117,%118,%119,%120,%121,%122,%123,%124,%125,%126,%127"
      "}, %128, %129, p, 1, 1, 0, 1;}\n"
      : "+f"(d[0]),"+f"(d[1]),"+f"(d[2]),"+f"(d[3]),"+f"(d[4]),"+f"(d[5]),"+f"(d[6]),"+f"(d[7]),
        "+f"(d[8]),"+f"(d[9]),"+f"(d[10]),"+f"(d[11]),"+f"(d[12]),"+f"(d[13]),"+f"(d[14]),"+f"(d[15]),
        "+f"(d[16]),"+f"(d[17]),"+f"(d[18]),"+f"(d[19]),"+f"(d[20]),"+f"(d[21]),"+f"(d[22]),"+f"(d[23]),
        "+f"(d[24]),"+f"(d[25]),"+f"(d[26]),"+f"(d[27]),"+f"(d[28]),"+f"(d[29]),"+f"(d[30]),"+f"(d[31]),
        "+f"(d[32]),"+f"(d[33]),"+f"(d[34]),"+f"(d[35]),"+f"(d[36]),"+f"(d[37]),"+f"(d[38]),"+f"(d[39]),
        "+f"(d[40]),"+f"(d[41]),"+f"(d[42]),"+f"(d[43]),"+f"(d[44]),"+f"(d[45]),"+f"(d[46]),"+f"(d[47]),
        "+f"(d[48]),"+f"(d[49]),"+f"(d[50]),"+f"(d[51]),"+f"(d[52]),"+f"(d[53]),"+f"(d[54]),"+f"(d[55]),
        "+f"(d[56]),"+f"(d[57]),"+f"(d[58]),"+f"(d[59]),"+f"(d[60]),"+f"(d[61]),"+f"(d[62]),"+f"(d[63]),
        "+f"(d[64]),"+f"(d[65]),"+f"(d[66]),"+f"(d[67]),"+f"(d[68]),"+f"(d[69]),"+f"(d[70]),"+f"(d[71]),
        "+f"(d[72]),"+f"(d[73]),"+f"(d[74]),"+f"(d[75]),"+f"(d[76]),"+f"(d[77]),"+f"(d[78]),"+f"(d[79]),
        "+f"(d[80]),"+f"(d[81]),"+f"(d[82]),"+f"(d[83]),"+f"(d[84]),"+f"(d[85]),"+f"(d[86]),"+f"(d[87]),
        "+f"(d[88]),"+f"(d[89]),"+f"(d[90]),"+f"(d[91]),"+f"(d[92]),"+f"(d[93]),"+f"(d[94]),"+f"(d[95]),
        "+f"(d[96]),"+f"(d[97]),"+f"(d[98]),"+f"(d[99]),"+f"(d[100]),"+f"(d[101]),"+f"(d[102]),"+f"(d[103]),
        "+f"(d[104]),"+f"(d[105]),"+f"(d[106]),"+f"(d[107]),"+f"(d[108]),"+f"(d[109]),"+f"(d[110]),"+f"(d[111]),
        "+f"(d[112]),"+f"(d[113]),"+f"(d[114]),"+f"(d[115]),"+f"(d[116]),"+f"(d[117]),"+f"(d[118]),"+f"(d[119]),
        "+f"(d[120]),"+f"(d[121]),"+f"(d[122]),"+f"(d[123]),"+f"(d[124]),"+f"(d[125]),"+f"(d[126]),"+f"(d[127])
      : "l"(da), "l"(db), "r"(sd));
}
__device__ __forceinline__ void wgmma_n192(float (&d)[96], uint64_t da, uint64_t db) {
  asm volatile("wgmma.mma_async.sync.aligned.m64n192k16.f32.bf16.bf16 {"
      "%0,%1,%2,%3,%4,%5,%6,%7,%8,%9,%10,%11,%12,%13,%14,%15,"
      "%16,%17,%18,%19,%20,%21,%22,%23,%24,%25,%26,%27,%28,%29,%30,%31,"
      "%32,%33,%34,%35,%36,%37,%38,%39,%40,%41,%42,%43,%44,%45,%46,%47,"
      "%48,%49,%50,%51,%52,%53,%54,%55,%56,%57,%58,%59,%60,%61,%62,%63,"
      "%64,%65,%66,%67,%68,%69,%70,%71,%72,%73,%74,%75,%76,%77,%78,%79,"
      "%80,%81,%82,%83,%84,%85,%86,%87,%88,%89,%90,%91,%92,%93,%94,%95"
      "}, %96, %97, 1, 1, 1, 0, 1;\n"
      : "+f"(d[0]),"+f"(d[1]),"+f"(d[2]),"+f"(d[3]),"+f"(d[4]),"+f"(d[5]),"+f"(d[6]),"+f"(d[7]),
        "+f"(d[8]),"+f"(d[9]),"+f"(d[10]),"+f"(d[11]),"+f"(d[12]),"+f"(d[13]),"+f"(d[14]),"+f"(d[15]),
        "+f"(d[16]),"+f"(d[17]),"+f"(d[18]),"+f"(d[19]),"+f"(d[20]),"+f"(d[21]),"+f"(d[22]),"+f"(d[23]),
        "+f"(d[24]),"+f"(d[25]),"+f"(d[26]),"+f"(d[27]),"+f"(d[28]),"+f"(d[29]),"+f"(d[30]),"+f"(d[31]),
        "+f"(d[32]),"+f"(d[33]),"+f"(d[34]),"+f"(d[35]),"+f"(d[36]),"+f"(d[37]),"+f"(d[38]),"+f"(d[39]),
        "+f"(d[40]),"+f"(d[41]),"+f"(d[42]),"+f"(d[43]),"+f"(d[44]),"+f"(d[45]),"+f"(d[46]),"+f"(d[47]),
        "+f"(d[48]),"+f"(d[49]),"+f"(d[50]),"+f"(d[51]),"+f"(d[52]),"+f"(d[53]),"+f"(d[54]),"+f"(d[55]),
        "+f"(d[56]),"+f"(d[57]),"+f"(d[58]),"+f"(d[59]),"+f"(d[60]),"+f"(d[61]),"+f"(d[62]),"+f"(d[63]),
        "+f"(d[64]),"+f"(d[65]),"+f"(d[66]),"+f"(d[67]),"+f"(d[68]),"+f"(d[69]),"+f"(d[70]),"+f"(d[71]),
        "+f"(d[72]),"+f"(d[73]),"+f"(d[74]),"+f"(d[75]),"+f"(d[76]),"+f"(d[77]),"+f"(d[78]),"+f"(d[79]),
        "+f"(d[80]),"+f"(d[81]),"+f"(d[82]),"+f"(d[83]),"+f"(d[84]),"+f"(d[85]),"+f"(d[86]),"+f"(d[87]),
        "+f"(d[88]),"+f"(d[89]),"+f"(d[90]),"+f"(d[91]),"+f"(d[92]),"+f"(d[93]),"+f"(d[94]),"+f"(d[95])
      : "l"(da), "l"(db));
}
template <int SD>
__device__ __forceinline__ void wgmma_rs_n128(float (&d)[64], uint32_t a0, uint32_t a1, uint32_t a2, uint32_t a3, uint64_t db) {
  asm volatile("wgmma.mma_async.sync.aligned.m64n128k16.f32.bf16.bf16 {"
      "%0,%1,%2,%3,%4,%5,%6,%7,%8,%9,%10,%11,%12,%13,%14,%15,"
      "%16,%17,%18,%19,%20,%21,%22,%23,%24,%25,%26,%27,%28,%29,%30,%31,"
      "%32,%33,%34,%35,%36,%37,%38,%39,%40,%41,%42,%43,%44,%45,%46,%47,"
      "%48,%49,%50,%51,%52,%53,%54,%55,%56,%57,%58,%59,%60,%61,%62,%63"
      "}, {%64,%65,%66,%67}, %68, %69, 1, 1, 1;\n"
      : "+f"(d[0]),"+f"(d[1]),"+f"(d[2]),"+f"(d[3]),"+f"(d[4]),"+f"(d[5]),"+f"(d[6]),"+f"(d[7]),
        "+f"(d[8]),"+f"(d[9]),"+f"(d[10]),"+f"(d[11]),"+f"(d[12]),"+f"(d[13]),"+f"(d[14]),"+f"(d[15]),
        "+f"(d[16]),"+f"(d[17]),"+f"(d[18]),"+f"(d[19]),"+f"(d[20]),"+f"(d[21]),"+f"(d[22]),"+f"(d[23]),
        "+f"(d[24]),"+f"(d[25]),"+f"(d[26]),"+f"(d[27]),"+f"(d[28]),"+f"(d[29]),"+f"(d[30]),"+f"(d[31]),
        "+f"(d[32]),"+f"(d[33]),"+f"(d[34]),"+f"(d[35]),"+f"(d[36]),"+f"(d[37]),"+f"(d[38]),"+f"(d[39]),
        "+f"(d[40]),"+f"(d[41]),"+f"(d[42]),"+f"(d[43]),"+f"(d[44]),"+f"(d[45]),"+f"(d[46]),"+f"(d[47]),
        "+f"(d[48]),"+f"(d[49]),"+f"(d[50]),"+f"(d[51]),"+f"(d[52]),"+f"(d[53]),"+f"(d[54]),"+f"(d[55]),
        "+f"(d[56]),"+f"(d[57]),"+f"(d[58]),"+f"(d[59]),"+f"(d[60]),"+f"(d[61]),"+f"(d[62]),"+f"(d[63])
      : "r"(a0), "r"(a1), "r"(a2), "r"(a3), "l"(db), "n"(SD));
}


constexpr int C_LN = 0, C_PX = 16, C_PY = 32;
constexpr int NB_CONS = 1, NB_LN = 2, NB_LAG = 4, NB_INIT = 6, NB_RDY = 7, NB_WG = 8;
constexpr int LAGX = 3;
constexpr int LAGY = 3;
constexpr int LAG2 = 5;
constexpr int NLL = 2;
constexpr int POLL_DELAY3 = 600;
constexpr int POLL_DELAY = 1200;
constexpr int FILT_DELAY = 800;
constexpr int WARM = 4;
constexpr int ALEAD = 6;
constexpr int POLL_DELAY2 = 1000;
constexpr int HPOS = 14;
constexpr int REDPOS = 4;
constexpr int XTRIG = 20;
constexpr int HTRIG = 0;
constexpr int RING_SIG = 1;
constexpr int PF2_SIG = 1;
constexpr int SM_E = 0, SM_X = 16384, SM_E2 = 32768, SM_W = 49152, SM_FC = 69632, SM_T = 73728 - T1_BYTES;
constexpr unsigned long long KORDER = 0xBA9432DC876510ull;
constexpr unsigned long long BSLOT = 0x76542107654210ull, PSLOT = 0xDCBA983DCBA983ull;
constexpr uint32_t HI128 = desc_hi(1024, 1), HI64 = desc_hi(512, 2);

struct Bars {
  uint64_t full1[32], empty1[32], full2[16], fullA[8], empty2[8], fullP[16], emptyP[8], hbar, tbar, hint[3], sig[2], sbar;
  uint32_t epoch, pad;
};

template <int NK, bool STORE, int J0 = 0, int J1 = NK>
__device__ __forceinline__ void make_p(const float (&acc)[NK * 16], float r0, float r1, uint4 (&p)[NK], uint4* pbase, int ks0, uint32_t tag) {
#pragma unroll
  for (int j = J0; j < J1; j++) {
    uint32_t w[4];
#pragma unroll
    for (int i = 0; i < 4; i++) {
      const int a = 8 * j + 2 * i, b = a + NK * 8;
      w[i] = pack2(swiglu(acc[a], acc[b], (i & 1) ? r1 : r0), swiglu(acc[a + 1], acc[b + 1], (i & 1) ? r1 : r0));
    }
    asm volatile("" : "+r"(w[0]), "+r"(w[1]), "+r"(w[2]), "+r"(w[3]));
    p[j] = make_uint4(w[0], w[1], w[2], w[3]);
    if (STORE) st_tag(pbase + ((ks0 + j) >> 2) * 1024 + ((ks0 + j) & 3) * 32, p[j], tag);
  }
}
__device__ __forceinline__ void spin_until(uint32_t t) {
  while ((int)(clock32() - t) < 0) {}
}

__global__ void __cluster_dims__(2, 1, 1) __launch_bounds__(NTHREADS, 1)
fused_kernel(const __nv_bfloat16* __restrict__ x, const Tables* __restrict__ tab, Scratch* __restrict__ scr,
             __nv_bfloat16* __restrict__ out, const char* __restrict__ wg_raw, const char* __restrict__ wu_raw,
             const char* __restrict__ wd_raw,
             const __grid_constant__ CUtensorMap tmWR, const __grid_constant__ CUtensorMap tmWI,
             const __grid_constant__ CUtensorMap tmGX, const __grid_constant__ CUtensorMap tmUX,
             const __grid_constant__ CUtensorMap tmGY, const __grid_constant__ CUtensorMap tmUY,
             const __grid_constant__ CUtensorMap tmD) {
  extern __shared__ __align__(1024) char smem_raw[];
  const uint32_t sbase = s2u(smem_raw);
  const uint32_t sbar = sbase + 14 * SLOT, sstat = sbar + 1280;
  const int tid = threadIdx.x, lane = tid & 31;
  const int c = blockIdx.x, rk = c & 1, f = (c >> 1) & 7, rb = 2 * (c >> 4) + rk;
  const int rb2 = 2 * (c >> 4) + (f >> 2), kh = (f >> 1) & 1, nq = 2 * (f & 1) + rk;
#define BAR(field, i) (sbar + (uint32_t)offsetof(Bars, field) + 8u * (i))
#define TOFF(field) (sbase + SM_T + (uint32_t)offsetof(Tables, field) + lane * 16)

  if (tid >= 256) {
    asm volatile("setmaxnreg.dec.sync.aligned.u32 56;");
    const int warp = __shfl_sync(0xffffffffu, tid >> 5, 0);
    if (lane == 0) {
      if (warp == 8) {
        if (sbase & 1023) die();
#pragma unroll
        for (int i = 0; i < 16; i++) mbar_init(BAR(emptyP, i), i < 7 ? 16 : i < 8 ? 8 : i < 13 ? 1 : i < 15 ? 8 : 32);
        mbar_expect(BAR(tbar, 0), T2_BYTES + 2 * 10240);
        mbar_expect(BAR(hbar, 0), 16384);
      } else if (warp == 9) {
#pragma unroll
        for (int i = 0; i < 32; i++) mbar_init(BAR(full1, i), 1);
#pragma unroll
        for (int i = 0; i < 32; i++) mbar_expect(BAR(full1, i), i < 16 ? 16384 : 12288);
      } else if (warp == 10) {
#pragma unroll
        for (int i = 0; i < 32; i++) mbar_init(BAR(empty1, i), 16);
#pragma unroll
        for (int i = 0; i < 14; i++) mbar_init(BAR(fullP, i), 1);
#pragma unroll
        for (int i = 0; i < 14; i++) mbar_expect(BAR(fullP, i), 16384);
      } else {
#pragma unroll
        for (int i = 0; i < 32; i++) mbar_init(BAR(full2, i), i < 24 ? 1 : 8);
#pragma unroll
        for (int i = 0; i < 24; i++) mbar_expect(BAR(full2, i), 16384);
      }
      asm volatile("fence.mbarrier_init.release.cluster;" ::: "memory");
    }
    if (tid == 256) {
      const int w0 = ((c >> 3) * 257 + 32 * (c & 7) + 1) & ~7;
      if (FILT_DELAY) {
        asm volatile("prefetch.tensormap [%0];" ::"l"(&tmWR) : "memory");
        asm volatile("prefetch.tensormap [%0];" ::"l"(&tmWI) : "memory");
        spin_until(clock32() + FILT_DELAY);
      }
      tma3(sbase + SM_W, &tmWR, BAR(tbar, 0), w0, 0, 0);
      tma3(sbase + SM_W + 10240, &tmWI, BAR(tbar, 0), w0, 0, 0);
      bulk_load(sbase + SM_T + T1_BYTES, reinterpret_cast<const char*>(tab) + T1_BYTES, T2_BYTES, BAR(tbar, 0));
    }
    if (tid == 288) {
      asm volatile("prefetch.tensormap [%0];" ::"l"(rk ? &tmUX : &tmGX) : "memory");
      asm volatile("prefetch.tensormap [%0];" ::"l"(rk ? &tmUY : &tmGY) : "memory");
      asm volatile("prefetch.tensormap [%0];" ::"l"(&tmD) : "memory");
    }
    if (tid == 320) {
      const unsigned e = ld_relaxed(&scr->cnt[(C_LN + rb) * 32]) >> 3;
      asm volatile("st.shared.u32 [%0], %1;" ::"r"(BAR(epoch, 0)), "r"(e) : "memory");
    }
    __syncwarp();
    asm volatile("barrier.cluster.arrive.relaxed.aligned;" ::: "memory");
    bar_arrive(NB_RDY, 384);
    asm volatile("barrier.cluster.wait.aligned;" ::: "memory");
    bar_sync(NB_INIT, 384);
    unsigned epoch;
    asm volatile("ld.shared.u32 %0, [%1];" : "=r"(epoch) : "r"(BAR(epoch, 0)) : "memory");
    if (warp == 8) {
      if (lane == 0) {
        const int ax = (7 * f + 3 * (f & 1)) >> 1;
        const int ay = 7 * f + ((f & 1) ? 0 : 4);
        const CUtensorMap* tx = rk ? &tmUX : &tmGX;
        const CUtensorMap* ty = rk ? &tmUY : &tmGY;
        if (RING_SIG >= 0) mbar_wait(BAR(sig, RING_SIG));
        uint32_t s = 2;
#pragma unroll 1
        for (int n = 0; n < 16; n++) {
          if (n >= 6) mbar_wait(BAR(empty1, n - 6));
          tma3_mc(sbase + (8 + s) * SLOT + rk * 8192, tx, BAR(full1, n), n * 32, ax);
          if (++s == 6) s = 0;
        }
#pragma unroll 1
        for (int k = 0; k < 16; k++) {
          mbar_wait(BAR(empty1, k < 8 ? 10 + ((12 * k + 11) >> 4) : 8 + k));
          tma3_mc(sbase + 8 * SLOT + (k & 7) * 12288 + rk * 6144, ty, BAR(full1, 16 + k), k * 32, ay);
        }
      }
    } else if (warp == 9) {
      if (lane == 0) {
        mbar_wait(BAR(fullA, 4));
        wait_counter(&scr->cnt[(C_LN + rb2) * 32], (epoch + 1) * 8);
        asm volatile("fence.proxy.async.global;" ::: "memory");
#pragma unroll 1
        for (int i = 0; i < 15; i++) {
          const int kblk = 14 * kh + (int)((KORDER >> (4 * i)) & 15);
          const int j = i < 7 ? i : i - 7, sl = j + (j >= 3);
          if (i == HPOS) {
            mbar_wait(BAR(emptyP, 7));
            bulk_load(sbase + 3 * SLOT, &scr->LN[(rb2 * 8 + 2 * nq) * 1024 + kh * 512], 8192, BAR(hbar, 0));
            bulk_load(sbase + 3 * SLOT + 8192, &scr->LN[(rb2 * 8 + 2 * nq + 1) * 1024 + kh * 512], 8192, BAR(hbar, 0));
          }
          if (i == 14) break;
          mbar_wait(i < 7 ? BAR(empty1, 17 + 2 * sl) : BAR(empty2, j));
          tma3(sbase + sl * SLOT, &tmD, BAR(full2, i), 0, 64 * kblk, 2 * nq);
        }
      }
    } else if (warp == 10) {
      bar_sync(NB_LN, 288);
      if (lane == 0) {
        red_release(&scr->cnt[(C_LN + rb) * 32]);
        wait_counter(&scr->cnt[(C_LN + rb) * 32], (epoch + 1) * 8);
        asm volatile("fence.proxy.async.global;" ::: "memory");
#pragma unroll 1
        for (int kb = NLL; kb < 8; kb++) {
          if (2 * kb >= ALEAD) mbar_wait(BAR(empty1, 2 * kb - ALEAD));
          bulk_load(sbase + kb * SLOT, &scr->LN[(rb * 8 + kb) * 1024], 16384, BAR(fullA, kb));
        }
#pragma unroll 1
        for (int s = 0; s < 14; s++) {
          const int kblk = 14 * kh + (int)((KORDER >> (4 * s)) & 15);
          if (s == 0 || s == 8 || s == 11) {
            mbar_wait(BAR(hint, s == 0 ? 0 : s == 8 ? 1 : 2), 0);
          }
          const int j = s < 7 ? s : s - 7;
          mbar_wait(s < 7 ? BAR(empty1, 24 + s - (s == 0) + (s >= 4)) : BAR(emptyP, j));
          bulk_load_mc(sbase + (j ? 7 + j : 3) * SLOT + rk * 8192, &scr->P[(rb2 * 28 + kblk) * 1024 + rk * 512], 8192, BAR(fullP, s));
        }
      }
    } else {
      if (lane == 0) {
        mbar_wait(BAR(tbar, 0));
        l2_prefetch(wg_raw + (size_t)c * 5376, 5376);
        l2_prefetch(wu_raw + (size_t)c * 5376, 5376);
        mbar_wait(BAR(sig, PF2_SIG), 0);
        l2_prefetch(wg_raw + 688128 + (size_t)c * 8960, 8960);
        l2_prefetch(wu_raw + 688128 + (size_t)c * 8960, 8960);
      }
      mbar_wait(BAR(fullA, 4), 0);
      if (lane == 0) l2_prefetch(wd_raw + (size_t)c * 14336, 14336);
      {
        const uint32_t tag = (epoch + 1) & 1;
        uint4 v0, v1, v2;
        int it = 0;
        while (true) {
          v0 = ld_b128(&scr->ST[rb * 64 + lane]);
          v1 = ld_b128(&scr->ST[rb * 64 + 32 + lane]);
          v2 = ld_b128(&scr->ST[rb2 * 64 + 32 * kh + lane]);
          if (!__any_sync(0xffffffffu, ((v0.x ^ tag) | (v1.x ^ tag) | (v2.x ^ tag)) & 1u)) break;
          if (++it > SPIN_LIMIT) { die(); break; }
        }
        sts4(sstat + lane * 16, v0.x & ~1u, v0.y, v0.z, v0.w);
        sts4(sstat + 512 + lane * 16, v1.x & ~1u, v1.y, v1.z, v1.w);
        sts4(sstat + 1024 + lane * 16, v2.x & ~1u, v2.y, v2.z, v2.w);
        mbar_arrive(BAR(sbar, 0));
      }
      if (lane == 0) {
        mbar_wait(BAR(empty1, XTRIG));
        int it = 0;
        while ((int)(ld_relaxed(&scr->cnt[(C_PX + rb2) * 32 + kh]) - (epoch + 1) * 32) < 0) {
          if (++it > SPIN_LIMIT) { die(); break; }
        }
        mbar_arrive(BAR(hint, 0));
        mbar_wait(BAR(emptyP, HTRIG));
        uint32_t done = 0;
        while (done != 3) {
          uint2 v;
          asm volatile("ld.relaxed.gpu.global.v2.u32 {%0,%1}, [%2];" : "=r"(v.x), "=r"(v.y) : "l"(&scr->cnt[(C_PY + rb2) * 32 + 2 * kh]) : "memory");
          if (!(done & 1) && (int)(v.x - (epoch + 1) * 16) >= 0) { done |= 1; mbar_arrive(BAR(hint, 1)); }
          if (!(done & 2) && (int)(v.y - (epoch + 1) * 16) >= 0) { done |= 2; mbar_arrive(BAR(hint, 2)); }
          if (++it > SPIN_LIMIT) { die(); break; }
        }
      }
    }
  } else {
    const int warp = __shfl_sync(0xffffffffu, tid >> 5, 0);
    const int g = lane >> 2, t = lane & 3;
    uint4 fa[4], fb[4], tw[6];
#pragma unroll
    for (int i = 0; i < 4; i++) fa[i] = ldg_ca4(&tab->fa[i][lane][0]);
#pragma unroll
    for (int i = 0; i < 6; i++) tw[i] = ldg_ca4(&tab->tw1[i][lane][0]);
#pragma unroll
    for (int i = 0; i < 4; i++) fb[i] = ldg_ca4(&tab->fb[i][lane][0]);
#pragma unroll
    for (int i = 0; i < 4; i++) {
      const int r = i >> 1, ch = (i & 1) * 32 + lane;
      cp_async16(sbase + SM_X + (2 * warp + r) * 1024 + ((ch ^ ((ch >> 3) & 1)) * 16),
                 x + (size_t)(c + 128 * (2 * warp + r)) * 512 + ch * 8);
    }
    asm volatile("cp.async.commit_group;" ::: "memory");
    asm volatile("barrier.cluster.arrive.relaxed.aligned;" ::: "memory");
    uint32_t rbar;
    asm volatile("mapa.shared::cluster.u32 %0, %1, %2;" : "=r"(rbar) : "r"(sbar), "r"(rk ^ 1));
#define RBAR(field, i) (rbar + (uint32_t)offsetof(Bars, field) + 8u * (i))
    {
      const int ln = (tid >> 1) & 31, lg = ln >> 2, lt = ln & 3, i = 4 * (tid >> 6) + 2 * (tid & 1);
      const int kidx = lt + 8 * (i >> 3), nidx = 4 * ((i >> 1) & 3) + (lg >> 1);
      const uint32_t a0 = cfrag<2048>((c + 128 * kidx) * nidx, lg & 1), a1 = cfrag<2048>((c + 128 * (kidx + 4)) * nidx, lg & 1);
      const uint32_t b0 = cfrag<2048>(-(c + 128 * nidx) * kidx, lg & 1), b1 = cfrag<2048>(-(c + 128 * nidx) * (kidx + 4), lg & 1);
      asm volatile("st.shared.v2.u32 [%0], {%1,%2};" ::"r"(sbase + SM_FC + tid * 8), "r"(a0), "r"(a1) : "memory");
      asm volatile("st.shared.v2.u32 [%0], {%1,%2};" ::"r"(sbase + SM_FC + 2048 + tid * 8), "r"(b0), "r"(b1) : "memory");
    }
    bar_sync(NB_CONS, 256);
    uint4 fc[4];
#pragma unroll
    for (int i = 0; i < 4; i++) fc[i] = lds4(sbase + SM_FC + i * 512 + lane * 16);
    asm volatile("cp.async.wait_group 0;" ::: "memory");
    __syncwarp();
    bar_arrive(NB_INIT, 384);
    uint32_t tag, ones;
    uint4 q[4], o[4];
    {
      uint32_t v[2][8];
#pragma unroll
      for (int r = 0; r < 2; r++)
#pragma unroll
        for (int ks = 0; ks < 2; ks++) {
          const int ch = 32 * ks + 2 * (lane & 15) + (lane >> 4);
          asm volatile("ldmatrix.sync.aligned.m8n8.x4.trans.shared.b16 {%0,%1,%2,%3}, [%4];"
                       : "=r"(v[r][4 * ks]), "=r"(v[r][4 * ks + 1]), "=r"(v[r][4 * ks + 2]), "=r"(v[r][4 * ks + 3])
                       : "r"(sbase + SM_X + (2 * warp + r) * 1024 + ((ch ^ ((ch >> 3) & 1)) * 16)) : "memory");
        }
      float sq[2];
#pragma unroll
      for (int r = 0; r < 2; r++) {
        float s0 = 0.f, s1 = 0.f;
#pragma unroll
        for (int i = 0; i < 8; i++) {
          const float lo = bf_lo(v[r][i]), hi = u2f(v[r][i] & 0xffff0000u);
          s0 = fmaf(lo, lo, s0);
          s1 = fmaf(hi, hi, s1);
        }
        sq[r] = s0 + s1;
      }
      {
        float w = ((lane & 1) ? sq[1] : sq[0]) + __shfl_xor_sync(0xffffffffu, (lane & 1) ? sq[0] : sq[1], 1);
        w += __shfl_xor_sync(0xffffffffu, w, 2);
        w = sum_groups(w);
        const float o2 = __shfl_xor_sync(0xffffffffu, w, 1);
        sq[0] = (lane & 1) ? o2 : w;
        sq[1] = (lane & 1) ? w : o2;
      }
#pragma unroll
      for (int r = 0; r < 2; r++) {
        float dd[2][4], ee[2][4];
#pragma unroll
        for (int nt = 0; nt < 2; nt++) {
          mma_az(dd[nt], fa[0], v[r][2 * nt], v[r][2 * nt + 1]);
          mma_a(dd[nt], fa[1], v[r][4 + 2 * nt], v[r][5 + 2 * nt]);
          mma_az(ee[nt], fa[2], v[r][2 * nt], v[r][2 * nt + 1]);
          mma_a(ee[nt], fa[3], v[r][4 + 2 * nt], v[r][5 + 2 * nt]);
        }
        float mean = (dd[0][0] + dd[0][1]) + (dd[1][0] + dd[1][1]);
        mean += __shfl_xor_sync(0xffffffffu, mean, 1);
        mean += __shfl_xor_sync(0xffffffffu, mean, 2);
        mean = __shfl_sync(0xffffffffu, mean, 0) * (1.f / 512.f);
        const float rs = rsqrtf(fmaxf(fmaf(-mean, mean, sq[r] * (1.f / 512.f)), 0.f) + 1e-5f);
        float acc[4][4];
#pragma unroll
        for (int nt = 0; nt < 2; nt++) {
          const float (&d)[4] = dd[nt];
          const float (&e)[4] = ee[nt];
          const uint4 &ka = tw[2 * nt], &kb = tw[2 * nt + 1], &kc = tw[4 + nt];
          const uint32_t a0 = pack2(d[0] * u2f(ka.x) + d[2] * u2f(ka.y), d[1] * u2f(kb.x) + d[3] * u2f(kb.y));
          const uint32_t a2 = pack2(d[0] * u2f(ka.z) + d[2] * u2f(ka.w), d[1] * u2f(kb.z) + d[3] * u2f(kb.w));
          const uint32_t a1 = pack2(e[0] * u2f(kc.x) + e[2] * u2f(kc.y), e[1] * u2f(kc.z) + e[3] * u2f(kc.w));
          const uint32_t a3 = pack2(e[2] * u2f(kc.x) - e[0] * u2f(kc.y), e[3] * u2f(kc.z) - e[1] * u2f(kc.w));
          const uint32_t dc = pack2(fmaf(mean, -32.f, d[0]), fmaf(mean, -32.f, d[1]));
          const uint32_t h0 = g == 0 ? dc : a0, h2 = g == 0 ? 0u : a2;
          if (nt == 0) {
            mma16816_z(acc[0], a0, a1, a2, a3, fb[2 * nt].x, fb[2 * nt].y);
            mma16816_z(acc[1], a0, a1, a2, a3, fb[2 * nt].z, fb[2 * nt].w);
            mma16816_z(acc[2], h0, a1, h2, a3, fb[2 * nt + 1].x, fb[2 * nt + 1].y);
            mma16816_z(acc[3], h0, a1, h2, a3, fb[2 * nt + 1].z, fb[2 * nt + 1].w);
          } else {
            mma16816(acc[0], a0, a1, a2, a3, fb[2 * nt].x, fb[2 * nt].y);
            mma16816(acc[1], a0, a1, a2, a3, fb[2 * nt].z, fb[2 * nt].w);
            mma16816(acc[2], h0, a1, h2, a3, fb[2 * nt + 1].x, fb[2 * nt + 1].y);
            mma16816(acc[3], h0, a1, h2, a3, fb[2 * nt + 1].z, fb[2 * nt + 1].w);
          }
        }
#pragma unroll
        for (int h = 0; h < 2; h++) {
          const int j = 2 * warp + r, m = 2 * t + h;
          sts4(sbase + SM_E + ((j * 8 + m) * 8 + (g ^ (2 * t) ^ (2 * (j & 3)))) * 16,
               pack2(acc[h][0] * rs, acc[h][1] * rs), pack2(acc[h][2] * rs, acc[h][3] * rs),
               pack2(acc[2 + h][0] * rs, acc[2 + h][1] * rs), pack2(acc[2 + h][2] * rs, acc[2 + h][3] * rs));
        }
      }
      bar_sync(NB_RDY, 384);
      const uint32_t ea = sbase + SM_E + ((t * 8 + warp) * 8 + (g ^ (warp & 6) ^ (2 * t))) * 16;
      lds_frag(q[0], q[1], ea, ea + 4096);
      lds_frag(q[2], q[3], ea + 8192, ea + 12288);
      asm volatile("ld.shared.u32 %0, [%1];" : "=r"(tag) : "r"(BAR(epoch, 0)) : "memory");
      ones = ~(tag >> 31);
      tag = (tag + 1) & 1;
      cdft16(q, fc, o);
#pragma unroll
      for (int vv = 0; vv < 4; vv++) {
        o[vv].y &= ~1u;
        o[vv].z = (o[vv].z & ~1u) | (tag ^ 1);
        st_tag(&scr->Z1[(((4 * vv + t) * 8 + warp) * 128 + c) * 8 + g], o[vv], tag);
      }
    }
    asm volatile("setmaxnreg.inc.sync.aligned.u32 224;");
    {
      uint4* const zp = &scr->Z1[(c * 128 + 8 * t + warp) * 8 + g];
      const uint32_t tst = clock32();
      mbar_wait(BAR(tbar, 0), 0);
      uint4 f2[4], g2[4];
#pragma unroll
      for (int i = 0; i < 4; i++) {
        f2[i] = lds4(TOFF(f2) + warp * 2048 + i * 512);
        g2[i] = lds4(TOFF(g2) + warp * 2048 + i * 512);
      }
      const uint4 f8 = lds4(TOFF(f8)), g8 = lds4(TOFF(g8));
      asm volatile("barrier.cluster.wait.aligned;" ::: "memory");
      spin_until(tst + POLL_DELAY);
      ld_tag4_issue<256>(q, zp);
      float wfr[16], wfi[16];
      {
        const float nyq = ((c & 7) == 7 && g == 0) ? 0.5f : 1.f;
        uint32_t wa = sbase + SM_W + (16 * warp + t) * 80 + ((2 * (c >> 3) + 2) & 15) - 2;
        asm volatile("" : "+r"(wa));
        const uint32_t wb[3] = {wa + 2 * (g == 0 ? 16 : g), wa + 2 * g, wa - 2 * g};
#pragma unroll
        for (int i = 0; i < 16; i++) {
          const int ci = i >> 3, dd = (i >> 2) & 1, e = i & 3;
          const uint32_t a = wb[e < 2 ? e : 2] + (ci * 8 + 4 * dd) * 80 + (e == 0 ? 0 : e == 1 ? 16 : e == 2 ? 64 : 48);
          wfr[i] = bf_lo(lds_u16(a)) * (e == 2 ? nyq : 1.f);
          wfi[i] = bf_lo(lds_u16(a + 10240)) * (e == 2 ? nyq : 1.f);
        }
      }
      ld_tag4_finish<256>(q, zp, tag);
      if (lane == 0) mbar_arrive(BAR(sig, 0));
#pragma unroll
      for (int i = 0; i < 4; i++) q[i].z &= ~1u;
      reg_frag(q, ones);
      cdft16(q, f2, o);
      const uint32_t e2 = sbase + SM_E2;
#pragma unroll
      for (int vv = 0; vv < 4; vv++)
        sts4(e2 + ((warp * 16 + 4 * vv + t) * 8 + (g ^ (2 * t) ^ (2 * (warp & 3)))) * 16, o[vv].x, o[vv].y, o[vv].z, o[vv].w);
      bar_sync(NB_CONS, 256);
      uint32_t ad[2], res[2][2][4];
#pragma unroll
      for (int ci = 0; ci < 2; ci++) {
        const int cc = 2 * warp + ci;
        ad[ci] = e2 + ((t * 16 + cc) * 8 + (g ^ (2 * (cc & 3)) ^ (2 * t))) * 16;
        lds_frag(q[2 * ci], q[2 * ci + 1], ad[ci], ad[ci] + 8192);
      }
#pragma unroll
      for (int ci = 0; ci < 2; ci++)
#pragma unroll
        for (int p = 0; p < 2; p++) {
          uint32_t y[2][2];
#pragma unroll
          for (int vv = 0; vv < 2; vv++) {
            float d[4];
            mma_az(d, q[2 * ci + p], word(f8, 2 * vv), word(f8, 2 * vv + 1));
#pragma unroll
            for (int rr = 0; rr < 2; rr++) {
              const float fr = wfr[ci * 8 + vv * 4 + 2 * p + rr], fi = wfi[ci * 8 + vv * 4 + 2 * p + rr];
              y[vv][rr] = pack2(d[2 * rr] * fr - d[2 * rr + 1] * fi, d[2 * rr] * fi + d[2 * rr + 1] * fr);
            }
          }
#pragma unroll
          for (int vv = 0; vv < 2; vv++) {
            float d[4];
            mma16816_z(d, y[0][0], y[0][1], y[1][0], y[1][1], word(g8, 2 * vv), word(g8, 2 * vv + 1));
            res[ci][vv][2 * p] = pack2(d[0], d[1]);
            res[ci][vv][2 * p + 1] = pack2(d[2], d[3]);
          }
        }
#pragma unroll
      for (int i = 0; i < 4; i++)
        sts4(ad[i >> 1] + (i & 1) * 8192, res[i >> 1][i & 1][0], res[i >> 1][i & 1][1], res[i >> 1][i & 1][2], res[i >> 1][i & 1][3]);
      bar_sync(NB_CONS, 256);
      const uint32_t eb = e2 + ((warp * 16 + t) * 8 + (g ^ (2 * t) ^ (2 * (warp & 3)))) * 16;
      lds_frag(q[0], q[1], eb, eb + 512);
      lds_frag(q[2], q[3], eb + 1024, eb + 1536);
      cdft16(q, g2, o);
#pragma unroll
      for (int vv = 0; vv < 4; vv++) {
        o[vv].y &= ~1u;
        o[vv].z = (o[vv].z & ~1u) | tag;
        st_tag(zp + vv * 256, o[vv], tag);
      }
    }
    {
      const uint4* const zp = &scr->Z1[((t * 8 + warp) * 128 + c) * 8 + g];
      const uint32_t tst = clock32();
      uint4 gb[4], ga[4], gc[4], tw[4];
      uint2 xr[2][4];
      uint2* lnp[2];
#pragma unroll
      for (int r = 0; r < 2; r++) {
        const int row = 16 * f + 2 * warp + r;
        lnp[r] = reinterpret_cast<uint2*>(&scr->LN[(rb * 8 + (g >> 2)) * 1024 + row * 8 + ((2 * (g & 3) + (t >> 1)) ^ (row & 7))]) + (t & 1);
        asm volatile("" : "+l"(lnp[r]));
      }
#pragma unroll
      for (int i = 0; i < 4; i++) {
        gc[i] = lds4(sbase + SM_FC + 2048 + i * 512 + lane * 16);
        gb[i] = lds4(TOFF(gb) + i * 512);
        ga[i] = lds4(TOFF(ga) + i * 512);
        tw[i] = lds4(TOFF(tw3) + i * 512);
        const int ch = 2 * (g + 8 * i) + (t >> 1);
#pragma unroll
        for (int r = 0; r < 2; r++) xr[r][i] = lds2(sbase + SM_X + (2 * warp + r) * 1024 + ((ch ^ ((ch >> 3) & 1)) * 16) + (t & 1) * 8);
      }
      spin_until(tst + POLL_DELAY2);
      ld_tag4_issue<32768>(q, zp);
      ld_tag4_finish<32768, true>(q, zp, tag);
      if (lane == 0) mbar_arrive(BAR(sig, 1));
      reg_frag(q, ones);
      cdft16(q, gc, o);
#pragma unroll
      for (int vv = 0; vv < 4; vv++)
        sts4(sbase + SM_E + (((4 * vv + t) * 8 + warp) * 8 + (g ^ (warp & 6) ^ (2 * t))) * 16, o[vv].x, o[vv].y, o[vv].z, o[vv].w);
      bar_sync(NB_CONS, 256);
      uint32_t hv[2][8];
      const float mk = t == 0 ? 0.f : 1.f;
#pragma unroll
      for (int r = 0; r < 2; r++) {
        const int j = 2 * warp + r;
        uint4 u[2];
#pragma unroll
        for (int h = 0; h < 2; h++) u[h] = lds4(sbase + SM_E + ((j * 8 + 2 * t + h) * 8 + (g ^ (2 * t) ^ (2 * (j & 3)))) * 16);
        const uint32_t bp[4][2] = {{u[0].x, u[1].x & ones}, {u[0].y & ones, u[1].y}, {u[0].z, u[1].z & ones}, {u[0].w & ones, u[1].w}};
        float y[2][2][4];
#pragma unroll
        for (int i = 0; i < 2; i++) {
          float lo[4], hi[4], e[4];
          mma_az(lo, gb[2 * i], bp[0][0], bp[0][1]);
          mma_az(hi, gb[2 * i + 1], bp[2][0], bp[2][1]);
          mma_az(e, gb[2 * i], bp[1][0], bp[1][1]);
          mma_a(e, gb[2 * i + 1], bp[3][0], bp[3][1]);
          const uint4 &ka = tw[2 * i], &kb = tw[2 * i + 1];
          const float tr0 = fmaf(hi[0], mk, lo[0]), ti0 = fmaf(hi[2], mk, lo[2]);
          const float tr1 = lo[1] + hi[1], ti1 = lo[3] + hi[3];
          const float vr0 = tr0 * u2f(ka.x) - ti0 * u2f(ka.y), vi0 = tr0 * u2f(ka.y) + ti0 * u2f(ka.x);
          const float vr1 = tr1 * u2f(ka.z) - ti1 * u2f(ka.w), vi1 = tr1 * u2f(ka.w) + ti1 * u2f(ka.z);
          const uint32_t b0 = pack2(t == 0 ? hi[0] : vr0, vr1), b1 = pack2(t == 0 ? vr0 : vi0, vi1);
          const uint32_t b2 = pack2(e[0] * u2f(kb.x) - e[2] * u2f(kb.y), e[1] * u2f(kb.z) - e[3] * u2f(kb.w));
          const uint32_t b3 = pack2(e[0] * u2f(kb.y) + e[2] * u2f(kb.x), e[1] * u2f(kb.w) + e[3] * u2f(kb.z));
#pragma unroll
          for (int mt = 0; mt < 2; mt++) {
            mma_az(y[mt][i], ga[2 * mt], b0, b1);
            mma_a(y[mt][i], ga[2 * mt + 1], b2, b3);
          }
        }
#pragma unroll
        for (int i = 0; i < 4; i++) {
          hv[r][2 * i] = hadd2_bf16(xr[r][i].x, pack2(y[i >> 1][0][2 * (i & 1)], y[i >> 1][0][2 * (i & 1) + 1]));
          hv[r][2 * i + 1] = hadd2_bf16(xr[r][i].y, pack2(y[i >> 1][1][2 * (i & 1)], y[i >> 1][1][2 * (i & 1) + 1]));
        }
      }
      float mean[2];
      uint32_t mb[2];
#pragma unroll
      for (int r = 0; r < 2; r++) {
        mean[r] = sum_groups(quad_sum(hv[r])) * (1.f / 512.f);
        mb[r] = pack2(mean[r], mean[r]);
      }
#pragma unroll
      for (int i = 0; i < 4; i++)
#pragma unroll
        for (int r = 0; r < 2; r++) {
          hv[r][2 * i] = hsub2_bf16(hv[r][2 * i], mb[r]);
          hv[r][2 * i + 1] = hsub2_bf16(hv[r][2 * i + 1], mb[r]);
          st_tag8(lnp[r] + i * 4096, hv[r][2 * i], hv[r][2 * i + 1], i == 0 ? tag : (hv[r][2 * i] & 1u));
        }
      bar_arrive(NB_LN, 288);
      const uint32_t ones2 = ~(lds2(BAR(epoch, 0)).x >> 31);
      float rstd[2];
#pragma unroll
      for (int r = 0; r < 2; r++) {
        hv[r][0] &= ones2;
        rstd[r] = row_rstd(hv[r], mean[r] - bf_lo(mb[r]));
      }
      if (lane == 0)
        st_tag(&scr->ST[rb * 64 + 8 * f + warp], make_uint4(mb[0] << 16, __float_as_uint(rstd[0]), mb[1] << 16, __float_as_uint(rstd[1])), tag);
    }
    const int wgi = warp >> 2, wq = warp & 3;
    uint4* const pbase = &scr->P[rb * 28 * 1024 + warp * 128 + lane];
    const uint32_t a_lo0 = desc_lo(sbase + wgi * 8192, 16);
    const uint32_t ebar = lane == 0 ? BAR(empty1, 0) : RBAR(empty1, 0);
    float r0, r1;
    uint4 px[8], py[6];
    const int rh = wgi ^ kh ^ 1;
    const uint4* const psrc = &scr->P[(rb2 * 28 + 14 * kh) * 1024 + (4 * rh + wq) * 128 + lane];
    const uint32_t pa0 = sbase + (4 * rh + wq) * 2048;
    uint4 pf[3][4];
    uint32_t rdy = 0, got0;
    {
      float acc[128];
#pragma unroll
      for (int i = 0; i < 128; i++) acc[i] = 0.f;
      const uint32_t b_lo0 = desc_lo(sbase + 8 * SLOT, 4096);
      const uint32_t t3 = clock32();
      if (WARM) {
        wg_fence();
#pragma unroll
        for (int i = 0; i < WARM; i++) wgmma_n256(acc, desc64(a_lo0 + 6 * 1024, HI128), desc64(b_lo0, HI128));
        wg_commit();
      }
      const uint4* const ap = &scr->LN[rb * 8 * 1024 + wgi * 512 + (tid & 127)];
      uint4 av[NLL][4];
      spin_until(t3 + POLL_DELAY3);
#pragma unroll
      for (int kb = 0; kb < NLL; kb++) ld_tag4_issue<128>(av[kb], ap + kb * 1024);
      bar_sync(NB_CONS, 256);
      uint32_t slot = 2;
      auto stage_x = [&](int kb, int hh) {
        if (LAGX && hh == ((16 - LAGX) & 1) && kb == ((16 - LAGX) >> 1) && wgi == 1) bar_sync(NB_LAG, 256);
        mbar_wait(BAR(full1, 2 * kb + hh));
        const uint32_t al = a_lo0 + kb * 1024 + hh * 4, bl = b_lo0 + slot * 1024;
        wg_fence();
        wgmma_n256(acc, desc64(al, HI128), desc64(bl, HI128), (kb | hh) != 0 ? 1 : ~ones);
        wgmma_n256(acc, desc64(al + 2, HI128), desc64(bl + 128, HI128));
        wg_commit();
        if (LAGX && hh == 1 && kb == 7 && wgi == 0) bar_arrive(NB_LAG, 256);
        wg_wait<1>();
        if ((kb | hh) != 0 && lane < 2) mbar_arrive_remote(ebar + 8 * (2 * kb + hh - 1));
        if (++slot == 6) slot = 0;
      };
#pragma unroll
      for (int kb = 0; kb < NLL; kb++) {
        ld_tag4_finish<128, true>(av[kb], ap + kb * 1024, tag);
#pragma unroll
        for (int i = 0; i < 4; i++)
          sts4(sbase + kb * SLOT + wgi * 8192 + ((tid & 127) + 128 * i) * 16, av[kb][i].x, av[kb][i].y, av[kb][i].z, av[kb][i].w);
        asm volatile("fence.proxy.async.shared::cta;" ::: "memory");
        bar_sync(NB_WG + wgi, 128);
        if (kb > 0) stage_x(kb - 1, 1);
        stage_x(kb, 0);
      }
      stage_x(NLL - 1, 1);
#pragma unroll 1
      for (int kb = NLL; kb < 8; kb++) {
        mbar_wait(BAR(fullA, kb));
        stage_x(kb, 0);
        stage_x(kb, 1);
      }
      mbar_wait(BAR(sbar, 0), 0);
      r0 = __uint_as_float(lds2(sstat + (16 * warp + g) * 8).y);
      r1 = __uint_as_float(lds2(sstat + (16 * warp + g + 8) * 8).y);
      wg_wait<0>();
      if (lane < 2) mbar_arrive_remote(ebar + 8 * 15);
      make_p<8, false>(acc, r0, r1, px, pbase, 0, tag);
    }
    {
      float acc[96];
#pragma unroll
      for (int i = 0; i < 96; i++) acc[i] = 0.f;
      const uint32_t b_lo0 = desc_lo(sbase + 8 * SLOT, 2048);
      uint4* const pdst = pbase + ((7 * f + 3 * (f & 1)) >> 1) * 1024;
      auto stage_y = [&](int k) {
        if (LAGY && k == 16 - LAGY && wgi == 1) bar_sync(NB_LAG, 256);
        mbar_wait(BAR(full1, 16 + k));
        const uint32_t al = a_lo0 + (k >> 1) * 1024 + (k & 1) * 4, bl = b_lo0 + (k & 7) * 768;
        wg_fence();
        wgmma_n192(acc, desc64(al, HI128), desc64(bl, HI64));
        wgmma_n192(acc, desc64(al + 2, HI128), desc64(bl + 64, HI64));
        wg_commit();
      };
#pragma unroll
      for (int k = 0; k < 4; k++) {
        stage_y(k);
        st_tag(pdst + (k >> 1) * 1024 + (k & 1) * 64, px[2 * k], tag);
        st_tag(pdst + (k >> 1) * 1024 + (k & 1) * 64 + 32, px[2 * k + 1], tag);
        if (k == 3 && lane == 0) red_relaxed(&scr->cnt[(C_PX + rb) * 32 + (f >> 2)]);
        wg_wait<1>();
        if (k != 0 && lane < 2) mbar_arrive_remote(ebar + 8 * (15 + k));
      }
#pragma unroll 1
      for (int k = 4; k < 16; k++) {
        stage_y(k);
        if (LAGY && k == 15 && wgi == 0) bar_arrive(NB_LAG, 256);
        wg_wait<1>();
        if (lane < 2) mbar_arrive_remote(ebar + 8 * (15 + k));
      }
      got0 = __all_sync(0xffffffffu, mbar_test(BAR(fullP, 0)));
      if (got0) {
#pragma unroll
        for (int kk = 0; kk < 4; kk++) pf[0][kk] = lds4(pa0 + 3 * SLOT + kk * 512 + lane * 16);
      }
      wg_wait<0>();
      if (lane < 2) mbar_arrive_remote(ebar + 8 * 31);
      const int ks0 = 14 * f + ((f & 1) ? 0 : 8);
      auto reread = [&]() {
        asm volatile("ld.volatile.shared.f32 %0, [%2+4]; ld.volatile.shared.f32 %1, [%2+68];" : "=f"(r0), "=f"(r1) : "r"(sstat + (16 * warp + g) * 8) : "memory");
      };
      make_p<6, true, 0, 2>(acc, r0, r1, py, pbase, ks0, tag);
      if (REDPOS == 2 && lane == 0) red_relaxed(&scr->cnt[(C_PY + rb) * 32 + (f >> 1)]);
      reread();
      make_p<6, true, 2, 4>(acc, r0, r1, py, pbase, ks0, tag);
      if (REDPOS == 4 && lane == 0) red_relaxed(&scr->cnt[(C_PY + rb) * 32 + (f >> 1)]);
      reread();
      rdy = mbar_test(BAR(full2, 0)) & mbar_test(BAR(fullP, 1));
      make_p<6, true, 4, 6>(acc, r0, r1, py, pbase, ks0, tag);
      if (REDPOS == 6 && lane == 0) red_relaxed(&scr->cnt[(C_PY + rb) * 32 + (f >> 1)]);
    }
    {
      float acc[64];
      const uint32_t b2_lo0 = desc_lo(sbase, 8192);
      const uint32_t pbar = ebar + (uint32_t)(offsetof(Bars, emptyP) - offsetof(Bars, empty1));
      if (!got0) {
        mbar_wait(BAR(fullP, 0));
#pragma unroll
        for (int kk = 0; kk < 4; kk++) pf[0][kk] = lds4(pa0 + 3 * SLOT + kk * 512 + lane * 16);
      }
#pragma unroll
      for (int s = 0; s < 14; s++) {
        uint4 (&a)[4] = pf[s % 3];
        ld_tag4_finish<32>(a, psrc + (int)((KORDER >> (4 * s)) & 15) * 1024, tag);
        if (s < 8 && lane < (s < 7 ? 2 : 1)) mbar_arrive_remote(pbar + 8 * s);
        if (s >= 2) {
          wg_wait<1>();
          if (s <= 8 && lane == 0) mbar_arrive(BAR(empty2, s - 2));
        }
        if (!rdy) {
          if (s < 13) mbar_wait(BAR(fullP, s + 1));
          mbar_wait(BAR(full2, s));
        }
        if (s == 14 - LAG2 && wgi == 1) {
          const float m0 = __uint_as_float(lds2(sstat + 1024 + (16 * wq + g) * 8).x);
          const float m1 = __uint_as_float(lds2(sstat + 1024 + (16 * wq + g + 8) * 8).x);
          const uint32_t hb = sbase + 3 * SLOT + (16 * wq + (lane & 15)) * 128;
          wg_wait<0>();
          mbar_wait(BAR(hbar, 0));
#pragma unroll
          for (int i = 0; i < 8; i++) {
            uint32_t h[4];
            asm volatile("ldmatrix.sync.aligned.m8n8.x4.shared.b16 {%0,%1,%2,%3}, [%4];"
                         : "=r"(h[0]), "=r"(h[1]), "=r"(h[2]), "=r"(h[3])
                         : "r"(hb + (i >> 2) * 8192 + (((2 * (i & 3) + (lane >> 4)) ^ (lane & 7)) * 16)) : "memory");
            const uint32_t mk = ((t & 1) == 0 && nq == 0) ? ~1u : ~0u;
#pragma unroll
            for (int e = 0; e < 4; e++) {
              acc[8 * i + 2 * e] += bf_lo(h[e] & mk) + ((e & 1) ? m1 : m0);
              acc[8 * i + 2 * e + 1] += __uint_as_float(h[e] & 0xffff0000u) + ((e & 1) ? m1 : m0);
            }
          }
          bar_sync(NB_LAG, 256);
        }
        const uint32_t bl = b2_lo0 + (uint32_t)((BSLOT >> (4 * s)) & 15) * 1024;
        wg_fence();
        if (s < 13) {
#pragma unroll
          for (int kk = 0; kk < 4; kk++)
            pf[(s + 1) % 3][kk] = lds4(pa0 + (uint32_t)((PSLOT >> (4 * (s + 1))) & 15) * SLOT + kk * 512 + lane * 16);
          rdy = mbar_test(BAR(full2, s + 1));
          if (s < 12) rdy &= mbar_test(BAR(fullP, s + 2));
        }
        if (s == 0) wgmma_rs_n128<0>(acc, a[0].x, a[0].y, a[0].z, a[0].w, desc64(bl, HI128));
        else wgmma_rs_n128<1>(acc, a[0].x, a[0].y, a[0].z, a[0].w, desc64(bl, HI128));
#pragma unroll
        for (int kk = 1; kk < 4; kk++) wgmma_rs_n128<1>(acc, a[kk].x, a[kk].y, a[kk].z, a[kk].w, desc64(bl + kk * 128, HI128));
        wg_commit();
      }
      if (wgi == 0) {
        bar_arrive(NB_LAG, 256);
        uint4* const dst = &scr->Z1[(tid >> 3) * 1024 + (c ^ 4) * 8 + (tid & 7)];
        wg_wait<0>();
#pragma unroll
        for (int i = 0; i < 8; i++)
          st_tag(dst + i * 16384, make_uint4(pack2(acc[8 * i], acc[8 * i + 1]), pack2(acc[8 * i + 2], acc[8 * i + 3]) | 1u,
                                           pack2(acc[8 * i + 4], acc[8 * i + 5]), pack2(acc[8 * i + 6], acc[8 * i + 7])), tag);
      } else {
        uint4 pv[2][4];
        const uint4* const xsrc = &scr->Z1[((tid & 127) >> 3) * 1024 + c * 8 + (tid & 7)];
        ld_tag4_issue<16384>(pv[0], xsrc);
        ld_tag4_issue<16384>(pv[1], xsrc + 65536);
        wg_wait<0>();
        uint32_t w[32];
#pragma unroll
        for (int i = 0; i < 32; i++) w[i] = pack2(acc[2 * i], acc[2 * i + 1]);
        int it = 0;
#pragma unroll 1
        while (!__all_sync(0xffffffffu, pv[0][0].y & pv[0][1].y & pv[0][2].y & pv[0][3].y & pv[1][0].y & pv[1][1].y & pv[1][2].y & pv[1][3].y & 1u)) {
          ld_tag4_issue<16384>(pv[0], xsrc);
          ld_tag4_issue<16384>(pv[1], xsrc + 65536);
          if (++it > SPIN_LIMIT) { die(); break; }
        }
#pragma unroll
        for (int i = 0; i < 8; i++) {
          const uint4& p = pv[i >> 2][i & 3];
          asm volatile("stmatrix.sync.aligned.m8n8.x4.shared.b16 [%0], {%1,%2,%3,%4};"
                       ::"r"(pa0 + (9 + ((lane >> 3) & 1)) * SLOT + (lane & 7) * 256 + (((2 * i + (lane >> 4)) ^ (lane & 7)) * 16)),
                         "r"(hadd2_bf16(w[4 * i], p.x & ~1u)), "r"(hadd2_bf16(w[4 * i + 1], p.y & ~1u)), "r"(hadd2_bf16(w[4 * i + 2], p.z)),
                         "r"(hadd2_bf16(w[4 * i + 3], p.w)) : "memory");
        }
        __syncwarp();
        uint4* const dst = reinterpret_cast<uint4*>(out) + (16 * (c >> 4) + 2 * (4 * rh + wq) + (rb2 & 1) + 128 * (lane >> 4)) * 64 + nq * 16 + (lane & 15);
#pragma unroll
        for (int i = 0; i < 8; i++) {
          const int r = 2 * (i & 3) + (lane >> 4);
          dst[i * 256 * 64] = lds4(pa0 + (9 + (i >> 2)) * SLOT + r * 256 + (((lane & 15) ^ r) * 16));
        }
      }
    }
  }
#undef BAR
#undef TOFF
#undef RBAR
}

typedef CUresult (*EncodeFn)(CUtensorMap*, CUtensorMapDataType, cuuint32_t, void*, const cuuint64_t*, const cuuint64_t*,
                             const cuuint32_t*, const cuuint32_t*, CUtensorMapInterleave, CUtensorMapSwizzle,
                             CUtensorMapL2promotion, CUtensorMapFloatOOBfill);

}

extern "C" void kernel_launch(void* const* d_in, const int* in_sizes, int n_in, void* d_out, int out_size) {
  (void)in_sizes; (void)n_in; (void)out_size;
  static EncodeFn encode = nullptr;
  static void *tab = nullptr, *scr = nullptr;
  if (!encode) {
    void* fn = nullptr;
    cudaDriverEntryPointQueryResult qr;
    cudaGetDriverEntryPoint("cuTensorMapEncodeTiled", &fn, cudaEnableDefault, &qr);
    encode = (EncodeFn)fn;
    cudaGetSymbolAddress(&tab, g_tab);
    cudaGetSymbolAddress(&scr, g_scr);
    cudaFuncSetAttribute(fused_kernel, cudaFuncAttributeMaxDynamicSharedMemorySize, SMEM_BYTES);
  }
  CUtensorMap tmGX, tmUX, tmGY, tmUY, tmD, tmWR, tmWI;
  const cuuint32_t es[5] = {1, 1, 1, 1, 1};
  auto enc = [&](CUtensorMap* m, void* p, int rank, const cuuint64_t* gd, const cuuint64_t* gs, const cuuint32_t* bd,
                 CUtensorMapSwizzle sw, CUtensorMapL2promotion pr) {
    encode(m, CU_TENSOR_MAP_DATA_TYPE_BFLOAT16, rank, p, gd, gs, bd, es, CU_TENSOR_MAP_INTERLEAVE_NONE, sw, pr,
           CU_TENSOR_MAP_FLOAT_OOB_FILL_NONE);
  };
  {
    const cuuint64_t gd[3] = {64, 512, 28}, gs[2] = {3584, 128};
    const cuuint32_t bd[3] = {64, 32, 2};
    enc(&tmGX, d_in[4], 3, gd, gs, bd, CU_TENSOR_MAP_SWIZZLE_128B, CU_TENSOR_MAP_L2_PROMOTION_L2_256B);
    enc(&tmUX, d_in[5], 3, gd, gs, bd, CU_TENSOR_MAP_SWIZZLE_128B, CU_TENSOR_MAP_L2_PROMOTION_L2_256B);
  }
  {
    const cuuint64_t gd[3] = {32, 512, 56}, gs[2] = {3584, 64};
    const cuuint32_t bd[3] = {32, 32, 3};
    enc(&tmGY, d_in[4], 3, gd, gs, bd, CU_TENSOR_MAP_SWIZZLE_64B, CU_TENSOR_MAP_L2_PROMOTION_L2_128B);
    enc(&tmUY, d_in[5], 3, gd, gs, bd, CU_TENSOR_MAP_SWIZZLE_64B, CU_TENSOR_MAP_L2_PROMOTION_L2_128B);
  }
  {
    const cuuint64_t gd[3] = {64, 1792, 8}, gs[2] = {1024, 128};
    const cuuint32_t bd[3] = {64, 64, 2};
    enc(&tmD, d_in[6], 3, gd, gs, bd, CU_TENSOR_MAP_SWIZZLE_128B, CU_TENSOR_MAP_L2_PROMOTION_L2_256B);
  }
  {
    const cuuint64_t gd[3] = {4112, 8, 16}, gs[2] = {16 * 8224, 8224};
    const cuuint32_t bd[3] = {40, 8, 16};
    enc(&tmWR, d_in[1], 3, gd, gs, bd, CU_TENSOR_MAP_SWIZZLE_NONE, CU_TENSOR_MAP_L2_PROMOTION_NONE);
    enc(&tmWI, d_in[2], 3, gd, gs, bd, CU_TENSOR_MAP_SWIZZLE_NONE, CU_TENSOR_MAP_L2_PROMOTION_NONE);
  }
  fused_kernel<<<NCTA, NTHREADS, SMEM_BYTES>>>((const __nv_bfloat16*)d_in[0], (const Tables*)tab, (Scratch*)scr,
                                               (__nv_bfloat16*)d_out, (const char*)d_in[4], (const char*)d_in[5],
                                               (const char*)d_in[6], tmWR, tmWI, tmGX, tmUX, tmGY, tmUY, tmD);
}
```

```cpp
#include <cuda_runtime.h>
#include <cuda_bf16.h>
#include <cuda.h>
#include <stdint.h>

namespace {

constexpr int NCTA = 128;
constexpr int NTHREADS = 384;
constexpr int SLOT = 16384;
constexpr int SMEM_BYTES = 14 * SLOT + 3072;
constexpr int SPIN_LIMIT = 1 << 22;

struct Scratch {
  uint4 Z1[128 * 1024];
  uint4 LN[16 * 8 * 1024];
  uint4 P[16 * 28 * 1024];
  uint4 ST[1024];
  unsigned cnt[16 * 32];
  unsigned flag[64 * 32];
};
__device__ __align__(1024) Scratch g_scr;

constexpr double ccos(int i, int n) {
  i &= n - 1;
  if (i > n / 2) i = n - i;
  if (4 * i == n) return 0.0;
  const bool neg = 4 * i > n;
  if (neg) i = n / 2 - i;
  const double a = 6.283185307179586476925 * i / n, a2 = a * a;
  double term = 1.0, sum = 1.0;
  for (int k = 1; k < 14; k++) { term *= -a2 / ((2 * k - 1) * (2 * k)); sum += term; }
  return neg ? -sum : sum;
}
constexpr double csin(int i, int n) { return ccos(i - n / 4, n); }
constexpr unsigned fbits(double v, int mant) {
  if (v == 0.0) return 0;
  const unsigned sg = v < 0 ? 1u : 0u;
  if (v < 0) v = -v;
  int e = 127;
  while (v < 1.0) { v *= 2.0; e--; }
  const unsigned m = (unsigned)((v - 1.0) * (double)(1u << mant) + 0.5);
  return (sg << (8 + mant)) + ((unsigned)e << mant) + m;
}
constexpr unsigned pkb(double lo, double hi) { return fbits(lo, 7) | (fbits(hi, 7) << 16); }
constexpr double fa_elem(int mt, int r, int n1) {
  const int k1 = 8 * mt + (r & 7);
  return r < 8 ? ccos(k1 * n1, 32) : k1 == 0 ? ccos(16 * n1, 32) : -csin(k1 * n1, 32);
}
constexpr unsigned cfrag_c(int idx, int n, int ri, double s = 1.0) {
  return ri ? pkb(-s * csin(idx, n), s * ccos(idx, n)) : pkb(s * ccos(idx, n), s * csin(idx, n));
}
struct Tables {
  unsigned fa[4][32][4];
  unsigned fb[4][32][4];
  unsigned tw1[6][32][4];
  unsigned f2[8][4][32][4];
  unsigned g2[8][4][32][4];
  unsigned gb[4][32][4];
  unsigned ga[4][32][4];
  unsigned tw3[4][32][4];
  unsigned f8[32][4], g8[32][4];
};
constexpr int T1_BYTES = 7168, T2_BYTES = 39936;
static_assert(sizeof(Tables) == T1_BYTES + T2_BYTES, "table size");
constexpr Tables make_tables() {
  Tables T = {};
  for (int l = 0; l < 32; l++) {
    const int g = l >> 2, t = l & 3;
    for (int a = 0; a < 2; a++)
      for (int b = 0; b < 2; b++) {
        for (int r = 0; r < 4; r++) {
          const int row = g + 8 * (r & 1), col = 2 * t + 8 * (r >> 1);
          T.fa[2 * a + b][l][r] = pkb(fa_elem(a, row, 16 * b + col), fa_elem(a, row, 16 * b + col + 1));
          T.ga[2 * a + b][l][r] = pkb(fa_elem(b, col, 16 * a + row), fa_elem(b, col + 1, 16 * a + row));
        }
        const double sg = b ? -1.0 : 1.0;
        for (int h = 0; h < 2; h++) {
          const int ri = g & 1, m = 2 * (g >> 1) + h, k2 = b ? 15 - m : m;
          const int pa = (8 * a + 2 * t) * k2, pb = (8 * a + 2 * t + 1) * k2;
          T.fb[2 * a + b][l][2 * h] = ri == 0 ? pkb(ccos(pa, 16), ccos(pb, 16)) : pkb(-sg * csin(pa, 16), -sg * csin(pb, 16));
          T.fb[2 * a + b][l][2 * h + 1] = ri == 0 ? pkb(csin(pa, 16), csin(pb, 16)) : pkb(sg * ccos(pa, 16), sg * ccos(pb, 16));
        }
        const int n2 = 4 * (g >> 1) + 2 * a + (g & 1);
        for (int h = 0; h < 2; h++) {
          const int p = n2 * (b ? 15 - 2 * t - h : 2 * t + h);
          T.gb[2 * a + b][l][2 * h] = pkb(ccos(p, 16), -sg * csin(p, 16));
          T.gb[2 * a + b][l][2 * h + 1] = pkb(csin(p, 16), sg * ccos(p, 16));
          const int k1 = 8 * b + 2 * t + h, q = n2 * (k1 == 0 ? 16 : k1);
          T.tw3[2 * a + b][l][2 * h] = fbits(ccos(q, 512), 23);
          T.tw3[2 * a + b][l][2 * h + 1] = fbits(csin(q, 512), 23);
        }
        const int p = (8 * a + 2 * t + b) * (g == 0 ? 16 : g);
        T.tw1[2 * a + b][l][0] = fbits(g == 0 ? 0.0 : ccos(p, 512), 23);
        T.tw1[2 * a + b][l][1] = fbits(g == 0 ? ccos(p, 512) : csin(p, 512), 23);
        T.tw1[2 * a + b][l][2] = fbits(g == 0 ? 0.0 : -csin(p, 512), 23);
        T.tw1[2 * a + b][l][3] = fbits(g == 0 ? -csin(p, 512) : ccos(p, 512), 23);
        T.tw1[4 + a][l][2 * b] = fbits(ccos((8 * a + 2 * t + b) * (g + 8), 512), 23);
        T.tw1[4 + a][l][2 * b + 1] = fbits(csin((8 * a + 2 * t + b) * (g + 8), 512), 23);
      }
    for (int i = 0; i < 4; i++) {
      const int p8 = (t + 4 * (i & 1)) * (4 * (i >> 1) + (g >> 1));
      T.f8[l][i] = cfrag_c(p8, 8, g & 1);
      T.g8[l][i] = cfrag_c(-p8, 8, g & 1, 1.0 / (1 << 19));
    }
    for (int w = 0; w < 8; w++)
      for (int i = 0; i < 16; i++) {
        const int kidx = t + 4 * (i & 1) + 8 * (i >> 3), nidx = 4 * ((i >> 1) & 3) + (g >> 1);
        T.f2[w][i >> 2][l][i & 3] = cfrag_c((8 * kidx + w) * nidx, 128, g & 1);
        T.g2[w][i >> 2][l][i & 3] = cfrag_c(-(8 * nidx + w) * kidx, 128, g & 1);
      }
  }
  return T;
}
__device__ const __align__(128) Tables g_tab = make_tables();

__device__ __forceinline__ void die() { asm volatile("st.global.u32 [%0], %1;" ::"l"(0ull), "r"(0) : "memory"); }
__device__ __forceinline__ uint32_t s2u(const void* p) { return (uint32_t)__cvta_generic_to_shared(p); }
__device__ __forceinline__ void mbar_init(uint32_t b, int c) { asm volatile("mbarrier.init.shared::cta.b64 [%0], %1;" ::"r"(b), "r"(c)); }
__device__ __forceinline__ void mbar_expect(uint32_t b, int bytes) {
  asm volatile("mbarrier.arrive.expect_tx.shared::cta.b64 _, [%0], %1;" ::"r"(b), "r"(bytes) : "memory");
}
__device__ __forceinline__ void mbar_arrive(uint32_t b) { asm volatile("mbarrier.arrive.shared::cta.b64 _, [%0];" ::"r"(b) : "memory"); }
__device__ __forceinline__ uint32_t mbar_try(uint32_t b, uint32_t parity) {
  uint32_t ok;
  asm volatile("{.reg .pred p; mbarrier.try_wait.parity.shared::cta.b64 p, [%1], %2; selp.u32 %0,1,0,p;}"
               : "=r"(ok) : "r"(b), "r"(parity) : "memory");
  return ok;
}
__device__ __forceinline__ uint32_t mbar_test(uint32_t b) {
  uint32_t ok;
  asm volatile("{.reg .pred p; mbarrier.test_wait.parity.shared::cta.b64 p, [%1], 0; selp.u32 %0,1,0,p;}" : "=r"(ok) : "r"(b) : "memory");
  return ok;
}
__device__ __forceinline__ void mbar_wait(uint32_t b, uint32_t parity = 0) {
  int it = 0;
#pragma unroll 1
  while (!mbar_try(b, parity))
    if (++it > SPIN_LIMIT) { die(); break; }
}
__device__ __forceinline__ void bar_sync(int id, int n) { asm volatile("bar.sync %0, %1;" ::"r"(id), "r"(n) : "memory"); }
__device__ __forceinline__ void bar_arrive(int id, int n) { asm volatile("bar.arrive %0, %1;" ::"r"(id), "r"(n) : "memory"); }
__device__ __forceinline__ void red_release(unsigned* p) { asm volatile("red.release.gpu.global.add.u32 [%0], 1;" ::"l"(p) : "memory"); }
__device__ __forceinline__ void st_relaxed(unsigned* p, unsigned v) { asm volatile("st.relaxed.gpu.global.u32 [%0], %1;" ::"l"(p), "r"(v) : "memory"); }
__device__ __forceinline__ unsigned ld_acquire(const unsigned* p) {
  unsigned v;
  asm volatile("ld.acquire.gpu.global.u32 %0, [%1];" : "=r"(v) : "l"(p) : "memory");
  return v;
}
__device__ __forceinline__ unsigned ld_relaxed(const unsigned* p) {
  unsigned v;
  asm volatile("ld.relaxed.gpu.global.u32 %0, [%1];" : "=r"(v) : "l"(p) : "memory");
  return v;
}
__device__ __forceinline__ void wait_counter(const unsigned* p, unsigned target) {
  int it = 0;
  while ((int)(ld_acquire(p) - target) < 0)
    if (++it > SPIN_LIMIT) { die(); break; }
}
__device__ __forceinline__ void sts4(uint32_t a, uint32_t x, uint32_t y, uint32_t z, uint32_t w) {
  asm volatile("st.shared.v4.u32 [%0], {%1,%2,%3,%4};" ::"r"(a), "r"(x), "r"(y), "r"(z), "r"(w) : "memory");
}
__device__ __forceinline__ uint4 lds4(uint32_t a) {
  uint4 v;
  asm volatile("ld.shared.v4.u32 {%0,%1,%2,%3}, [%4];" : "=r"(v.x), "=r"(v.y), "=r"(v.z), "=r"(v.w) : "r"(a) : "memory");
  return v;
}
__device__ __forceinline__ uint32_t pack2(float lo, float hi) {
  uint32_t r;
  asm("cvt.rn.bf16x2.f32 %0, %1, %2;" : "=r"(r) : "f"(hi), "f"(lo));
  return r;
}
__device__ __forceinline__ float bf_lo(uint32_t v) { return __uint_as_float(v << 16); }
__device__ __forceinline__ uint32_t hadd2_bf16(uint32_t a, uint32_t b) {
  uint32_t r;
  asm("add.rn.bf16x2 %0, %1, %2;" : "=r"(r) : "r"(a), "r"(b));
  return r;
}
__device__ __forceinline__ void mma16816(float (&d)[4], uint32_t a0, uint32_t a1, uint32_t a2, uint32_t a3, uint32_t b0, uint32_t b1) {
  asm("mma.sync.aligned.m16n8k16.row.col.f32.bf16.bf16.f32 {%0,%1,%2,%3}, {%4,%5,%6,%7}, {%8,%9}, {%0,%1,%2,%3};"
      : "+f"(d[0]), "+f"(d[1]), "+f"(d[2]), "+f"(d[3])
      : "r"(a0), "r"(a1), "r"(a2), "r"(a3), "r"(b0), "r"(b1));
}
__device__ __forceinline__ void mma16816_z(float (&d)[4], uint32_t a0, uint32_t a1, uint32_t a2, uint32_t a3, uint32_t b0, uint32_t b1) {
  asm("{.reg .f32 z; mov.f32 z, 0f00000000;\n"
      "mma.sync.aligned.m16n8k16.row.col.f32.bf16.bf16.f32 {%0,%1,%2,%3}, {%4,%5,%6,%7}, {%8,%9}, {z,z,z,z};}"
      : "=f"(d[0]), "=f"(d[1]), "=f"(d[2]), "=f"(d[3])
      : "r"(a0), "r"(a1), "r"(a2), "r"(a3), "r"(b0), "r"(b1));
}
template <int N>
__device__ __forceinline__ void cs_frac(int idx, float& c, float& s) {
  int i = ((idx + N / 2) & (N - 1)) - N / 2;
  float a = (float)i * (6.283185307179586f / N);
  c = __cosf(a);
  s = __sinf(a);
}
template <int N>
__device__ __forceinline__ uint32_t cfrag(int idx, int ri) {
  float c, s;
  cs_frac<N>(idx, c, s);
  return ri ? pack2(-s, c) : pack2(c, s);
}
__device__ __forceinline__ uint32_t word(const uint4& v, int e) { return e == 0 ? v.x : e == 1 ? v.y : e == 2 ? v.z : v.w; }
__device__ __forceinline__ void cdft16(const uint4 (&A)[4], const uint4 (&F)[4], uint4 (&o)[4]) {
  float acc[2][4][4];
#pragma unroll
  for (int ks = 0; ks < 2; ks++)
#pragma unroll
    for (int p = 0; p < 2; p++)
#pragma unroll
      for (int v = 0; v < 4; v++) {
        const uint4& a = A[2 * ks + p];
        const uint32_t b0 = word(F[ks * 2 + (v >> 1)], (v & 1) * 2), b1 = word(F[ks * 2 + (v >> 1)], (v & 1) * 2 + 1);
        if (ks == 0) mma16816_z(acc[p][v], a.x, a.y, a.z, a.w, b0, b1);
        else mma16816(acc[p][v], a.x, a.y, a.z, a.w, b0, b1);
      }
#pragma unroll
  for (int v = 0; v < 4; v++)
    o[v] = make_uint4(pack2(acc[0][v][0], acc[0][v][1]), pack2(acc[0][v][2], acc[0][v][3]),
                      pack2(acc[1][v][0], acc[1][v][1]), pack2(acc[1][v][2], acc[1][v][3]));
}
__device__ __forceinline__ void lds_frag(uint4& f0, uint4& f1, uint32_t a0, uint32_t a1) {
  asm volatile("ld.volatile.shared.v2.u32 {%0,%1}, [%8]; ld.volatile.shared.v2.u32 {%2,%3}, [%9];\n"
               "ld.volatile.shared.v2.u32 {%4,%5}, [%8+8]; ld.volatile.shared.v2.u32 {%6,%7}, [%9+8];"
               : "=r"(f0.x), "=r"(f0.y), "=r"(f0.z), "=r"(f0.w), "=r"(f1.x), "=r"(f1.y), "=r"(f1.z), "=r"(f1.w) : "r"(a0), "r"(a1) : "memory");
}
__device__ __forceinline__ void reg_frag(uint4 (&q)[4], uint32_t ones) {
#pragma unroll
  for (int ks = 0; ks < 2; ks++) {
    const uint4 a = q[2 * ks], b = q[2 * ks + 1];
    q[2 * ks] = make_uint4(a.x, a.y, b.x & ones, b.y & ones);
    q[2 * ks + 1] = make_uint4(a.z & ones, a.w & ones, b.z, b.w);
  }
}
__device__ __forceinline__ void st_tag(uint4* p, const uint4& v, uint32_t tag) {
  asm volatile("st.relaxed.gpu.global.v4.b32 [%0], {%1,%2,%3,%4};"
               ::"l"(p), "r"((v.x & ~1u) | tag), "r"(v.y), "r"(v.z), "r"(v.w) : "memory");
}
__device__ __forceinline__ void st_tag8(void* p, uint32_t x, uint32_t y, uint32_t tag) {
  asm volatile("st.relaxed.gpu.global.v2.b32 [%0], {%1,%2};" ::"l"(p), "r"((x & ~1u) | tag), "r"(y) : "memory");
}
__device__ __forceinline__ uint4 ld_b128(const uint4* p) {
  uint4 v;
  asm volatile("ld.relaxed.gpu.global.v4.b32 {%0,%1,%2,%3}, [%4];"
               : "=r"(v.x), "=r"(v.y), "=r"(v.z), "=r"(v.w) : "l"(p) : "memory");
  return v;
}
template <int STRIDE>
__device__ __forceinline__ void ld_tag4_issue(uint4 (&q)[4], const uint4* p) {
#pragma unroll
  for (int i = 0; i < 4; i++) q[i] = ld_b128(p + i * STRIDE);
}
template <int STRIDE, bool HALVES = false>
__device__ __forceinline__ void ld_tag4_finish(uint4 (&q)[4], const uint4* p, uint32_t tag) {
  int it = 0;
#pragma unroll 1
  while (__any_sync(0xffffffffu, ((q[0].x ^ tag) | (q[1].x ^ tag) | (q[2].x ^ tag) | (q[3].x ^ tag) |
                                  (HALVES ? (q[0].z ^ tag) | (q[1].z ^ tag) | (q[2].z ^ tag) | (q[3].z ^ tag) : 0u)) & 1u)) {
    ld_tag4_issue<STRIDE>(q, p);
    if (++it > SPIN_LIMIT) { die(); break; }
  }
#pragma unroll
  for (int i = 0; i < 4; i++) {
    asm volatile("and.b32 %0, %0, 0xfffffffe;" : "+r"(q[i].x));
    if (HALVES) q[i].z &= ~1u;
  }
}
__device__ __forceinline__ float quad_sum(const uint32_t (&a)[8]) {
  float d[4];
  mma16816_z(d, a[0], a[1], a[2], a[3], 0x3f803f80u, 0x3f803f80u);
  mma16816(d, a[4], a[5], a[6], a[7], 0x3f803f80u, 0x3f803f80u);
  return d[0] + d[2];
}
__device__ __forceinline__ float sum_groups(float v) {
  v += __shfl_xor_sync(0xffffffffu, v, 4);
  v += __shfl_xor_sync(0xffffffffu, v, 8);
  v += __shfl_xor_sync(0xffffffffu, v, 16);
  return v;
}
__device__ __forceinline__ uint32_t hsub2_bf16(uint32_t a, uint32_t b) {
  uint32_t r;
  asm("sub.rn.bf16x2 %0, %1, %2;" : "=r"(r) : "r"(a), "r"(b));
  return r;
}
__device__ __forceinline__ float row_rstd(const uint32_t (&c)[8], float delta) {
  uint32_t s[8];
#pragma unroll
  for (int i = 0; i < 8; i++) asm("mul.rn.bf16x2 %0, %1, %1;" : "=r"(s[i]) : "r"(c[i]));
  return rsqrtf(fmaxf(fmaf(-delta, delta, sum_groups(quad_sum(s)) * (1.f / 512.f)), 0.f) + 1e-5f);
}
__device__ __forceinline__ uint64_t desc64(uint32_t lo, uint32_t hi) {
  uint64_t d;
  asm("mov.b64 %0, {%1, %2};" : "=l"(d) : "r"(lo), "r"(hi));
  return d;
}
constexpr uint32_t desc_hi(uint32_t sbo, uint32_t swz) { return (sbo >> 4) | (swz << 30); }
__device__ __forceinline__ uint32_t desc_lo(uint32_t addr, uint32_t lbo) { return ((addr & 0x3FFFF) >> 4) | ((lbo >> 4) << 16); }
__device__ __forceinline__ void cp_async16(uint32_t dst, const void* src) {
  asm volatile("cp.async.cg.shared.global [%0], [%1], 16;" ::"r"(dst), "l"(src) : "memory");
}
__device__ __forceinline__ uint2 lds2(uint32_t a) {
  uint2 v;
  asm volatile("ld.shared.v2.u32 {%0,%1}, [%2];" : "=r"(v.x), "=r"(v.y) : "r"(a) : "memory");
  return v;
}
__device__ __forceinline__ uint32_t lds_u16(uint32_t a) {
  uint16_t v;
  asm volatile("ld.shared.u16 %0, [%1];" : "=h"(v) : "r"(a) : "memory");
  return v;
}
__device__ __forceinline__ void wg_fence() { asm volatile("wgmma.fence.sync.aligned;" ::: "memory"); }
__device__ __forceinline__ void wg_commit() { asm volatile("wgmma.commit_group.sync.aligned;" ::: "memory"); }
template <int N>
__device__ __forceinline__ void wg_wait() { asm volatile("wgmma.wait_group.sync.aligned %0;" ::"n"(N) : "memory"); }
__device__ __forceinline__ void bulk_load(uint32_t dst, const void* src, int bytes, uint32_t bar) {
  asm volatile("cp.async.bulk.shared::cluster.global.mbarrier::complete_tx::bytes [%0], [%1], %2, [%3];"
               ::"r"(dst), "l"(src), "r"(bytes), "r"(bar) : "memory");
}
__device__ __forceinline__ void bulk_load_mc(uint32_t dst, const void* src, int bytes, uint32_t bar) {
  asm volatile("cp.async.bulk.shared::cluster.global.mbarrier::complete_tx::bytes.multicast::cluster [%0], [%1], %2, [%3], %4;"
               ::"r"(dst), "l"(src), "r"(bytes), "r"(bar), "h"((uint16_t)3) : "memory");
}
__device__ __forceinline__ void tma3(uint32_t dst, const CUtensorMap* tm, uint32_t bar, int c0, int c1, int c2) {
  asm volatile("cp.async.bulk.tensor.3d.shared::cluster.global.mbarrier::complete_tx::bytes [%0], [%1, {%3,%4,%5}], [%2];"
               ::"r"(dst), "l"(tm), "r"(bar), "r"(c0), "r"(c1), "r"(c2) : "memory");
}
__device__ __forceinline__ void tma3_mc(uint32_t dst, const CUtensorMap* tm, uint32_t bar, int c1, int c2) {
  asm volatile("cp.async.bulk.tensor.3d.shared::cluster.global.mbarrier::complete_tx::bytes.multicast::cluster [%0], [%1, {%3,%4,%5}], [%2], %6;"
               ::"r"(dst), "l"(tm), "r"(bar), "r"(0), "r"(c1), "r"(c2), "h"((uint16_t)3) : "memory");
}
__device__ __forceinline__ void mbar_arrive_remote(uint32_t rb) {
  asm volatile("mbarrier.arrive.shared::cluster.b64 _, [%0];" ::"r"(rb) : "memory");
}
__device__ __forceinline__ uint4 ldg_ca4(const void* p) {
  uint4 v;
  asm volatile("ld.global.ca.v4.u32 {%0,%1,%2,%3}, [%4];" : "=r"(v.x), "=r"(v.y), "=r"(v.z), "=r"(v.w) : "l"(p) : "memory");
  return v;
}
__device__ __forceinline__ float u2f(uint32_t v) { return __uint_as_float(v); }
__device__ __forceinline__ void mma_az(float (&d)[4], const uint4& a, uint32_t b0, uint32_t b1) { mma16816_z(d, a.x, a.y, a.z, a.w, b0, b1); }
__device__ __forceinline__ void mma_a(float (&d)[4], const uint4& a, uint32_t b0, uint32_t b1) { mma16816(d, a.x, a.y, a.z, a.w, b0, b1); }
__device__ __forceinline__ uint32_t clock32() {
  uint32_t v;
  asm volatile("mov.u32 %0, %%clock;" : "=r"(v) :: "memory");
  return v;
}
__device__ __forceinline__ float swiglu(float g, float u, float r) {
  float hg = (0.5f * r) * g, th;
  asm("tanh.approx.f32 %0, %1;" : "=f"(th) : "f"(hg));
  return fmaf(hg, th, hg) * (r * u);
}
__device__ __forceinline__ void l2_prefetch(const void* p, int bytes) {
  asm volatile("cp.async.bulk.prefetch.L2.global [%0], %1;" ::"l"(p), "r"(bytes) : "memory");
}

__device__ __forceinline__ void wgmma_n256(float (&d)[128], uint64_t da, uint64_t db, int sd = 1) {
  asm volatile("{.reg .pred p; setp.ne.b32 p, %130, 0;\n"
      "wgmma.mma_async.sync.aligned.m64n256k16.f32.bf16.bf16 {"
      "%0,%1,%2,%3,%4,%5,%6,%7,%8,%9,%10,%11,%12,%13,%14,%15,"
      "%16,%17,%18,%19,%20,%21,%22,%23,%24,%25,%26,%27,%28,%29,%30,%31,"
      "%32,%33,%34,%35,%36,%37,%38,%39,%40,%41,%42,%43,%44,%45,%46,%47,"
      "%48,%49,%50,%51,%52,%53,%54,%55,%56,%57,%58,%59,%60,%61,%62,%63,"
      "%64,%65,%66,%67,%68,%69,%70,%71,%72,%73,%74,%75,%76,%77,%78,%79,"
      "%80,%81,%82,%83,%84,%85,%86,%87,%88,%89,%90,%91,%92,%93,%94,%95,"
      "%96,%97,%98,%99,%100,%101,%102,%103,%104,%105,%106,%107,%108,%109,%110,%111,"
      "%112,%113,%114,%115,%116,%117,%118,%119,%120,%121,%122,%123,%124,%125,%126,%127"
      "}, %128, %129, p, 1, 1, 0, 1;}\n"
      : "+f"(d[0]),"+f"(d[1]),"+f"(d[2]),"+f"(d[3]),"+f"(d[4]),"+f"(d[5]),"+f"(d[6]),"+f"(d[7]),
        "+f"(d[8]),"+f"(d[9]),"+f"(d[10]),"+f"(d[11]),"+f"(d[12]),"+f"(d[13]),"+f"(d[14]),"+f"(d[15]),
        "+f"(d[16]),"+f"(d[17]),"+f"(d[18]),"+f"(d[19]),"+f"(d[20]),"+f"(d[21]),"+f"(d[22]),"+f"(d[23]),
        "+f"(d[24]),"+f"(d[25]),"+f"(d[26]),"+f"(d[27]),"+f"(d[28]),"+f"(d[29]),"+f"(d[30]),"+f"(d[31]),
        "+f"(d[32]),"+f"(d[33]),"+f"(d[34]),"+f"(d[35]),"+f"(d[36]),"+f"(d[37]),"+f"(d[38]),"+f"(d[39]),
        "+f"(d[40]),"+f"(d[41]),"+f"(d[42]),"+f"(d[43]),"+f"(d[44]),"+f"(d[45]),"+f"(d[46]),"+f"(d[47]),
        "+f"(d[48]),"+f"(d[49]),"+f"(d[50]),"+f"(d[51]),"+f"(d[52]),"+f"(d[53]),"+f"(d[54]),"+f"(d[55]),
        "+f"(d[56]),"+f"(d[57]),"+f"(d[58]),"+f"(d[59]),"+f"(d[60]),"+f"(d[61]),"+f"(d[62]),"+f"(d[63]),
        "+f"(d[64]),"+f"(d[65]),"+f"(d[66]),"+f"(d[67]),"+f"(d[68]),"+f"(d[69]),"+f"(d[70]),"+f"(d[71]),
        "+f"(d[72]),"+f"(d[73]),"+f"(d[74]),"+f"(d[75]),"+f"(d[76]),"+f"(d[77]),"+f"(d[78]),"+f"(d[79]),
        "+f"(d[80]),"+f"(d[81]),"+f"(d[82]),"+f"(d[83]),"+f"(d[84]),"+f"(d[85]),"+f"(d[86]),"+f"(d[87]),
        "+f"(d[88]),"+f"(d[89]),"+f"(d[90]),"+f"(d[91]),"+f"(d[92]),"+f"(d[93]),"+f"(d[94]),"+f"(d[95]),
        "+f"(d[96]),"+f"(d[97]),"+f"(d[98]),"+f"(d[99]),"+f"(d[100]),"+f"(d[101]),"+f"(d[102]),"+f"(d[103]),
        "+f"(d[104]),"+f"(d[105]),"+f"(d[106]),"+f"(d[107]),"+f"(d[108]),"+f"(d[109]),"+f"(d[110]),"+f"(d[111]),
        "+f"(d[112]),"+f"(d[113]),"+f"(d[114]),"+f"(d[115]),"+f"(d[116]),"+f"(d[117]),"+f"(d[118]),"+f"(d[119]),
        "+f"(d[120]),"+f"(d[121]),"+f"(d[122]),"+f"(d[123]),"+f"(d[124]),"+f"(d[125]),"+f"(d[126]),"+f"(d[127])
      : "l"(da), "l"(db), "r"(sd));
}
__device__ __forceinline__ void wgmma_n192(float (&d)[96], uint64_t da, uint64_t db) {
  asm volatile("wgmma.mma_async.sync.aligned.m64n192k16.f32.bf16.bf16 {"
      "%0,%1,%2,%3,%4,%5,%6,%7,%8,%9,%10,%11,%12,%13,%14,%15,"
      "%16,%17,%18,%19,%20,%21,%22,%23,%24,%25,%26,%27,%28,%29,%30,%31,"
      "%32,%33,%34,%35,%36,%37,%38,%39,%40,%41,%42,%43,%44,%45,%46,%47,"
      "%48,%49,%50,%51,%52,%53,%54,%55,%56,%57,%58,%59,%60,%61,%62,%63,"
      "%64,%65,%66,%67,%68,%69,%70,%71,%72,%73,%74,%75,%76,%77,%78,%79,"
      "%80,%81,%82,%83,%84,%85,%86,%87,%88,%89,%90,%91,%92,%93,%94,%95"
      "}, %96, %97, 1, 1, 1, 0, 1;\n"
      : "+f"(d[0]),"+f"(d[1]),"+f"(d[2]),"+f"(d[3]),"+f"(d[4]),"+f"(d[5]),"+f"(d[6]),"+f"(d[7]),
        "+f"(d[8]),"+f"(d[9]),"+f"(d[10]),"+f"(d[11]),"+f"(d[12]),"+f"(d[13]),"+f"(d[14]),"+f"(d[15]),
        "+f"(d[16]),"+f"(d[17]),"+f"(d[18]),"+f"(d[19]),"+f"(d[20]),"+f"(d[21]),"+f"(d[22]),"+f"(d[23]),
        "+f"(d[24]),"+f"(d[25]),"+f"(d[26]),"+f"(d[27]),"+f"(d[28]),"+f"(d[29]),"+f"(d[30]),"+f"(d[31]),
        "+f"(d[32]),"+f"(d[33]),"+f"(d[34]),"+f"(d[35]),"+f"(d[36]),"+f"(d[37]),"+f"(d[38]),"+f"(d[39]),
        "+f"(d[40]),"+f"(d[41]),"+f"(d[42]),"+f"(d[43]),"+f"(d[44]),"+f"(d[45]),"+f"(d[46]),"+f"(d[47]),
        "+f"(d[48]),"+f"(d[49]),"+f"(d[50]),"+f"(d[51]),"+f"(d[52]),"+f"(d[53]),"+f"(d[54]),"+f"(d[55]),
        "+f"(d[56]),"+f"(d[57]),"+f"(d[58]),"+f"(d[59]),"+f"(d[60]),"+f"(d[61]),"+f"(d[62]),"+f"(d[63]),
        "+f"(d[64]),"+f"(d[65]),"+f"(d[66]),"+f"(d[67]),"+f"(d[68]),"+f"(d[69]),"+f"(d[70]),"+f"(d[71]),
        "+f"(d[72]),"+f"(d[73]),"+f"(d[74]),"+f"(d[75]),"+f"(d[76]),"+f"(d[77]),"+f"(d[78]),"+f"(d[79]),
        "+f"(d[80]),"+f"(d[81]),"+f"(d[82]),"+f"(d[83]),"+f"(d[84]),"+f"(d[85]),"+f"(d[86]),"+f"(d[87]),
        "+f"(d[88]),"+f"(d[89]),"+f"(d[90]),"+f"(d[91]),"+f"(d[92]),"+f"(d[93]),"+f"(d[94]),"+f"(d[95])
      : "l"(da), "l"(db));
}
template <int SD>
__device__ __forceinline__ void wgmma_rs_n128(float (&d)[64], uint32_t a0, uint32_t a1, uint32_t a2, uint32_t a3, uint64_t db) {
  asm volatile("wgmma.mma_async.sync.aligned.m64n128k16.f32.bf16.bf16 {"
      "%0,%1,%2,%3,%4,%5,%6,%7,%8,%9,%10,%11,%12,%13,%14,%15,"
      "%16,%17,%18,%19,%20,%21,%22,%23,%24,%25,%26,%27,%28,%29,%30,%31,"
      "%32,%33,%34,%35,%36,%37,%38,%39,%40,%41,%42,%43,%44,%45,%46,%47,"
      "%48,%49,%50,%51,%52,%53,%54,%55,%56,%57,%58,%59,%60,%61,%62,%63"
      "}, {%64,%65,%66,%67}, %68, %69, 1, 1, 1;\n"
      : "+f"(d[0]),"+f"(d[1]),"+f"(d[2]),"+f"(d[3]),"+f"(d[4]),"+f"(d[5]),"+f"(d[6]),"+f"(d[7]),
        "+f"(d[8]),"+f"(d[9]),"+f"(d[10]),"+f"(d[11]),"+f"(d[12]),"+f"(d[13]),"+f"(d[14]),"+f"(d[15]),
        "+f"(d[16]),"+f"(d[17]),"+f"(d[18]),"+f"(d[19]),"+f"(d[20]),"+f"(d[21]),"+f"(d[22]),"+f"(d[23]),
        "+f"(d[24]),"+f"(d[25]),"+f"(d[26]),"+f"(d[27]),"+f"(d[28]),"+f"(d[29]),"+f"(d[30]),"+f"(d[31]),
        "+f"(d[32]),"+f"(d[33]),"+f"(d[34]),"+f"(d[35]),"+f"(d[36]),"+f"(d[37]),"+f"(d[38]),"+f"(d[39]),
        "+f"(d[40]),"+f"(d[41]),"+f"(d[42]),"+f"(d[43]),"+f"(d[44]),"+f"(d[45]),"+f"(d[46]),"+f"(d[47]),
        "+f"(d[48]),"+f"(d[49]),"+f"(d[50]),"+f"(d[51]),"+f"(d[52]),"+f"(d[53]),"+f"(d[54]),"+f"(d[55]),
        "+f"(d[56]),"+f"(d[57]),"+f"(d[58]),"+f"(d[59]),"+f"(d[60]),"+f"(d[61]),"+f"(d[62]),"+f"(d[63])
      : "r"(a0), "r"(a1), "r"(a2), "r"(a3), "l"(db), "n"(SD));
}


constexpr int NB_CONS = 1, NB_LN = 2, NB_LAG = 4, NB_INIT = 6, NB_RDY = 7, NB_WG = 8;
constexpr int LAGX = 3;
constexpr int LAG2 = 5;
constexpr int NLL = 2;
constexpr int POLL_DELAY3 = 600;
constexpr int POLL_DELAY = 1200;
constexpr int FILT_DELAY = 800;
constexpr int WARM = 4;
constexpr int ALEAD = 6;
constexpr int POLL_DELAY2 = 1000;
constexpr int HPOS = 14;
constexpr int REDPOS = 4;
constexpr int XTRIG = 20;
constexpr int HTRIG = 0;
constexpr int RING_SIG = 1;
constexpr int PF2_SIG = 1;
constexpr int SM_E = 0, SM_X = 16384, SM_E2 = 32768, SM_W = 49152, SM_FC = 69632, SM_T = 73728 - T1_BYTES;
constexpr unsigned long long KORDER = 0xBA9432DC876510ull;
constexpr unsigned long long BSLOT = 0x76542107654210ull, PSLOT = 0xDCBA983DCBA983ull;
constexpr uint32_t HI128 = desc_hi(1024, 1), HI64 = desc_hi(512, 2);

struct Bars {
  uint64_t full1[32], empty1[32], full2[16], fullA[8], empty2[8], fullP[16], emptyP[8], hbar, tbar, hint[3], sig[2], sbar;
  uint32_t epoch, pad;
};

template <int NK, bool STORE, int J0 = 0, int J1 = NK>
__device__ __forceinline__ void make_p(const float (&acc)[NK * 16], float r0, float r1, uint4 (&p)[NK], uint4* pbase, int ks0, uint32_t tag) {
#pragma unroll
  for (int j = J0; j < J1; j++) {
    uint32_t w[4];
#pragma unroll
    for (int i = 0; i < 4; i++) {
      const int a = 8 * j + 2 * i, b = a + NK * 8;
      w[i] = pack2(swiglu(acc[a], acc[b], (i & 1) ? r1 : r0), swiglu(acc[a + 1], acc[b + 1], (i & 1) ? r1 : r0));
    }
    asm volatile("" : "+r"(w[0]), "+r"(w[1]), "+r"(w[2]), "+r"(w[3]));
    p[j] = make_uint4(w[0], w[1], w[2], w[3]);
    if (STORE) st_tag(pbase + ((ks0 + j) >> 2) * 1024 + ((ks0 + j) & 3) * 32, p[j], tag);
  }
}
__device__ __forceinline__ void spin_until(uint32_t t) {
  while ((int)(clock32() - t) < 0) {}
}

__global__ void __cluster_dims__(2, 1, 1) __launch_bounds__(NTHREADS, 1)
fused_kernel(const __nv_bfloat16* __restrict__ x, const Tables* __restrict__ tab, Scratch* __restrict__ scr,
             __nv_bfloat16* __restrict__ out, const char* __restrict__ wg_raw, const char* __restrict__ wu_raw,
             const char* __restrict__ wd_raw,
             const __grid_constant__ CUtensorMap tmWR, const __grid_constant__ CUtensorMap tmWI,
             const __grid_constant__ CUtensorMap tmGX, const __grid_constant__ CUtensorMap tmUX,
             const __grid_constant__ CUtensorMap tmGY, const __grid_constant__ CUtensorMap tmUY,
             const __grid_constant__ CUtensorMap tmD) {
  extern __shared__ __align__(1024) char smem_raw[];
  const uint32_t sbase = s2u(smem_raw);
  const uint32_t sbar = sbase + 14 * SLOT, sstat = sbar + 1280;
  const int tid = threadIdx.x, lane = tid & 31;
  const int c = blockIdx.x, rk = c & 1, f = (c >> 1) & 7, rb = 2 * (c >> 4) + rk;
  const int rb2 = 2 * (c >> 4) + (f >> 2), kh = (f >> 1) & 1, nq = 2 * (f & 1) + rk;
#define BAR(field, i) (sbar + (uint32_t)offsetof(Bars, field) + 8u * (i))
#define TOFF(field) (sbase + SM_T + (uint32_t)offsetof(Tables, field) + lane * 16)

  if (tid >= 256) {
    asm volatile("setmaxnreg.dec.sync.aligned.u32 56;");
    const int warp = __shfl_sync(0xffffffffu, tid >> 5, 0);
    if (lane == 0) {
      if (warp == 8) {
        if (sbase & 1023) die();
#pragma unroll
        for (int i = 0; i < 16; i++) mbar_init(BAR(emptyP, i), i < 7 ? 16 : i < 8 ? 8 : i < 13 ? 1 : i < 15 ? 8 : 32);
        mbar_expect(BAR(tbar, 0), T2_BYTES + 2 * 10240);
        mbar_expect(BAR(hbar, 0), 16384);
      } else if (warp == 9) {
#pragma unroll
        for (int i = 0; i < 32; i++) mbar_init(BAR(full1, i), 1);
#pragma unroll
        for (int i = 0; i < 32; i++) mbar_expect(BAR(full1, i), i < 16 ? 16384 : 12288);
      } else if (warp == 10) {
#pragma unroll
        for (int i = 0; i < 32; i++) mbar_init(BAR(empty1, i), 16);
#pragma unroll
        for (int i = 0; i < 14; i++) mbar_init(BAR(fullP, i), 1);
#pragma unroll
        for (int i = 0; i < 14; i++) mbar_expect(BAR(fullP, i), 16384);
      } else {
#pragma unroll
        for (int i = 0; i < 32; i++) mbar_init(BAR(full2, i), i < 24 ? 1 : 8);
#pragma unroll
        for (int i = 0; i < 24; i++) mbar_expect(BAR(full2, i), 16384);
      }
      asm volatile("fence.mbarrier_init.release.cluster;" ::: "memory");
    }
    if (tid == 256) {
      const int w0 = ((c >> 3) * 257 + 32 * (c & 7) + 1) & ~7;
      if (FILT_DELAY) {
        asm volatile("prefetch.tensormap [%0];" ::"l"(&tmWR) : "memory");
        asm volatile("prefetch.tensormap [%0];" ::"l"(&tmWI) : "memory");
        spin_until(clock32() + FILT_DELAY);
      }
      tma3(sbase + SM_W, &tmWR, BAR(tbar, 0), w0, 0, 0);
      tma3(sbase + SM_W + 10240, &tmWI, BAR(tbar, 0), w0, 0, 0);
      bulk_load(sbase + SM_T + T1_BYTES, reinterpret_cast<const char*>(tab) + T1_BYTES, T2_BYTES, BAR(tbar, 0));
    }
    if (tid == 288) {
      asm volatile("prefetch.tensormap [%0];" ::"l"(rk ? &tmUX : &tmGX) : "memory");
      asm volatile("prefetch.tensormap [%0];" ::"l"(rk ? &tmUY : &tmGY) : "memory");
      asm volatile("prefetch.tensormap [%0];" ::"l"(&tmD) : "memory");
    }
    if (tid == 320) {
      const unsigned e = ld_relaxed(&scr->cnt[rb * 32]) >> 3;
      asm volatile("st.shared.u32 [%0], %1;" ::"r"(BAR(epoch, 0)), "r"(e) : "memory");
    }
    __syncwarp();
    asm volatile("barrier.cluster.arrive.relaxed.aligned;" ::: "memory");
    bar_arrive(NB_RDY, 384);
    asm volatile("barrier.cluster.wait.aligned;" ::: "memory");
    bar_sync(NB_INIT, 384);
    unsigned epoch;
    asm volatile("ld.shared.u32 %0, [%1];" : "=r"(epoch) : "r"(BAR(epoch, 0)) : "memory");
    if (warp == 8) {
      if (lane == 0) {
        const int ax = (7 * f + 3 * (f & 1)) >> 1;
        const int ay = 7 * f + ((f & 1) ? 0 : 4);
        const CUtensorMap* tx = rk ? &tmUX : &tmGX;
        const CUtensorMap* ty = rk ? &tmUY : &tmGY;
        if (RING_SIG >= 0) mbar_wait(BAR(sig, RING_SIG));
        uint32_t s = 2;
#pragma unroll 1
        for (int n = 0; n < 16; n++) {
          if (n >= 6) mbar_wait(BAR(empty1, n - 6));
          tma3_mc(sbase + (8 + s) * SLOT + rk * 8192, tx, BAR(full1, n), n * 32, ax);
          if (++s == 6) s = 0;
        }
#pragma unroll 1
        for (int k = 0; k < 16; k++) {
          mbar_wait(BAR(empty1, k < 8 ? 10 + ((12 * k + 11) >> 4) : 8 + k));
          tma3_mc(sbase + 8 * SLOT + (k & 7) * 12288 + rk * 6144, ty, BAR(full1, 16 + k), k * 32, ay);
        }
      }
    } else if (warp == 9) {
      if (lane == 0) {
        mbar_wait(BAR(fullA, 4));
        wait_counter(&scr->cnt[rb2 * 32], (epoch + 1) * 8);
        asm volatile("fence.proxy.async.global;" ::: "memory");
#pragma unroll 1
        for (int i = 0; i < 15; i++) {
          const int kblk = 14 * kh + (int)((KORDER >> (4 * i)) & 15);
          const int j = i < 7 ? i : i - 7, sl = j + (j >= 3);
          if (i == HPOS) {
            mbar_wait(BAR(emptyP, 7));
            bulk_load(sbase + 3 * SLOT, &scr->LN[(rb2 * 8 + 2 * nq) * 1024 + kh * 512], 8192, BAR(hbar, 0));
            bulk_load(sbase + 3 * SLOT + 8192, &scr->LN[(rb2 * 8 + 2 * nq + 1) * 1024 + kh * 512], 8192, BAR(hbar, 0));
          }
          if (i == 14) break;
          mbar_wait(i < 7 ? BAR(empty1, 17 + 2 * sl) : BAR(empty2, j));
          tma3(sbase + sl * SLOT, &tmD, BAR(full2, i), 0, 64 * kblk, 2 * nq);
        }
      }
    } else if (warp == 10) {
      bar_sync(NB_LN, 288);
      if (lane == 0) {
        red_release(&scr->cnt[rb * 32]);
        wait_counter(&scr->cnt[rb * 32], (epoch + 1) * 8);
        asm volatile("fence.proxy.async.global;" ::: "memory");
#pragma unroll 1
        for (int kb = NLL; kb < 8; kb++) {
          if (2 * kb >= ALEAD) mbar_wait(BAR(empty1, 2 * kb - ALEAD));
          bulk_load(sbase + kb * SLOT, &scr->LN[(rb * 8 + kb) * 1024], 16384, BAR(fullA, kb));
        }
#pragma unroll 1
        for (int s = 0; s < 14; s++) {
          const int kblk = 14 * kh + (int)((KORDER >> (4 * s)) & 15);
          if (s == 0 || s == 8 || s == 11) {
            mbar_wait(BAR(hint, s == 0 ? 0 : s == 8 ? 1 : 2), 0);
          }
          const int j = s < 7 ? s : s - 7;
          mbar_wait(s < 7 ? BAR(empty1, 24 + s - (s == 0) + (s >= 4)) : BAR(emptyP, j));
          bulk_load_mc(sbase + (j ? 7 + j : 3) * SLOT + rk * 8192, &scr->P[(rb2 * 28 + kblk) * 1024 + rk * 512], 8192, BAR(fullP, s));
        }
      }
    } else {
      if (lane == 0) {
        mbar_wait(BAR(tbar, 0));
        l2_prefetch(wg_raw + (size_t)c * 5376, 5376);
        l2_prefetch(wu_raw + (size_t)c * 5376, 5376);
        mbar_wait(BAR(sig, PF2_SIG), 0);
        l2_prefetch(wg_raw + 688128 + (size_t)c * 8960, 8960);
        l2_prefetch(wu_raw + 688128 + (size_t)c * 8960, 8960);
      }
      mbar_wait(BAR(fullA, 4), 0);
      if (lane == 0) l2_prefetch(wd_raw + (size_t)c * 14336, 14336);
      {
        const uint32_t tag = (epoch + 1) & 1;
        uint4 v0, v1, v2;
        int it = 0;
        while (true) {
          v0 = ld_b128(&scr->ST[rb * 64 + lane]);
          v1 = ld_b128(&scr->ST[rb * 64 + 32 + lane]);
          v2 = ld_b128(&scr->ST[rb2 * 64 + 32 * kh + lane]);
          if (!__any_sync(0xffffffffu, ((v0.x ^ tag) | (v1.x ^ tag) | (v2.x ^ tag)) & 1u)) break;
          if (++it > SPIN_LIMIT) { die(); break; }
        }
        sts4(sstat + lane * 16, v0.x & ~1u, v0.y, v0.z, v0.w);
        sts4(sstat + 512 + lane * 16, v1.x & ~1u, v1.y, v1.z, v1.w);
        sts4(sstat + 1024 + lane * 16, v2.x & ~1u, v2.y, v2.z, v2.w);
        mbar_arrive(BAR(sbar, 0));
      }
      {
        const unsigned* fp = &scr->flag[(rb2 * 2 + kh) * 32 + lane];
        const uint32_t tag = (epoch + 1) & 1;
        mbar_wait(BAR(empty1, XTRIG));
        int it = 0;
        while (!__all_sync(0xffffffffu, ld_relaxed(fp) == tag))
          if (++it > SPIN_LIMIT) { die(); break; }
        if (lane == 0) mbar_arrive(BAR(hint, 0));
        mbar_wait(BAR(emptyP, HTRIG));
        uint32_t done = 0;
        while (done != 3) {
          const uint32_t m = __ballot_sync(0xffffffffu, ld_relaxed(fp + 1024) == tag);
          const uint32_t now = ((m & 0xffffu) == 0xffffu ? 1u : 0u) | ((m >> 16) == 0xffffu ? 2u : 0u);
          if (lane < 2 && ((now & ~done) >> lane & 1)) mbar_arrive(BAR(hint, 1 + lane));
          done |= now;
          if (++it > SPIN_LIMIT) { die(); break; }
        }
      }
    }
  } else {
    const int warp = __shfl_sync(0xffffffffu, tid >> 5, 0);
    const int g = lane >> 2, t = lane & 3;
    uint4 fa[4], fb[4], tw[6];
#pragma unroll
    for (int i = 0; i < 4; i++) fa[i] = ldg_ca4(&tab->fa[i][lane][0]);
#pragma unroll
    for (int i = 0; i < 6; i++) tw[i] = ldg_ca4(&tab->tw1[i][lane][0]);
#pragma unroll
    for (int i = 0; i < 4; i++) fb[i] = ldg_ca4(&tab->fb[i][lane][0]);
#pragma unroll
    for (int i = 0; i < 4; i++) {
      const int r = i >> 1, ch = (i & 1) * 32 + lane;
      cp_async16(sbase + SM_X + (2 * warp + r) * 1024 + ((ch ^ ((ch >> 3) & 1)) * 16),
                 x + (size_t)(c + 128 * (2 * warp + r)) * 512 + ch * 8);
    }
    asm volatile("cp.async.commit_group;" ::: "memory");
    asm volatile("barrier.cluster.arrive.relaxed.aligned;" ::: "memory");
    uint32_t rbar;
    asm volatile("mapa.shared::cluster.u32 %0, %1, %2;" : "=r"(rbar) : "r"(sbar), "r"(rk ^ 1));
#define RBAR(field, i) (rbar + (uint32_t)offsetof(Bars, field) + 8u * (i))
    {
      const int ln = (tid >> 1) & 31, lg = ln >> 2, lt = ln & 3, i = 4 * (tid >> 6) + 2 * (tid & 1);
      const int kidx = lt + 8 * (i >> 3), nidx = 4 * ((i >> 1) & 3) + (lg >> 1);
      const uint32_t a0 = cfrag<2048>((c + 128 * kidx) * nidx, lg & 1), a1 = cfrag<2048>((c + 128 * (kidx + 4)) * nidx, lg & 1);
      const uint32_t b0 = cfrag<2048>(-(c + 128 * nidx) * kidx, lg & 1), b1 = cfrag<2048>(-(c + 128 * nidx) * (kidx + 4), lg & 1);
      asm volatile("st.shared.v2.u32 [%0], {%1,%2};" ::"r"(sbase + SM_FC + tid * 8), "r"(a0), "r"(a1) : "memory");
      asm volatile("st.shared.v2.u32 [%0], {%1,%2};" ::"r"(sbase + SM_FC + 2048 + tid * 8), "r"(b0), "r"(b1) : "memory");
    }
    bar_sync(NB_CONS, 256);
    uint4 fc[4];
#pragma unroll
    for (int i = 0; i < 4; i++) fc[i] = lds4(sbase + SM_FC + i * 512 + lane * 16);
    asm volatile("cp.async.wait_group 0;" ::: "memory");
    __syncwarp();
    bar_arrive(NB_INIT, 384);
    uint32_t tag, ones;
    uint4 q[4], o[4];
    {
      uint32_t v[2][8];
#pragma unroll
      for (int r = 0; r < 2; r++)
#pragma unroll
        for (int ks = 0; ks < 2; ks++) {
          const int ch = 32 * ks + 2 * (lane & 15) + (lane >> 4);
          asm volatile("ldmatrix.sync.aligned.m8n8.x4.trans.shared.b16 {%0,%1,%2,%3}, [%4];"
                       : "=r"(v[r][4 * ks]), "=r"(v[r][4 * ks + 1]), "=r"(v[r][4 * ks + 2]), "=r"(v[r][4 * ks + 3])
                       : "r"(sbase + SM_X + (2 * warp + r) * 1024 + ((ch ^ ((ch >> 3) & 1)) * 16)) : "memory");
        }
      float sq[2];
#pragma unroll
      for (int r = 0; r < 2; r++) {
        float s0 = 0.f, s1 = 0.f;
#pragma unroll
        for (int i = 0; i < 8; i++) {
          const float lo = bf_lo(v[r][i]), hi = u2f(v[r][i] & 0xffff0000u);
          s0 = fmaf(lo, lo, s0);
          s1 = fmaf(hi, hi, s1);
        }
        sq[r] = s0 + s1;
      }
      {
        float w = ((lane & 1) ? sq[1] : sq[0]) + __shfl_xor_sync(0xffffffffu, (lane & 1) ? sq[0] : sq[1], 1);
        w += __shfl_xor_sync(0xffffffffu, w, 2);
        w = sum_groups(w);
        const float o2 = __shfl_xor_sync(0xffffffffu, w, 1);
        sq[0] = (lane & 1) ? o2 : w;
        sq[1] = (lane & 1) ? w : o2;
      }
#pragma unroll
      for (int r = 0; r < 2; r++) {
        float dd[2][4], ee[2][4];
#pragma unroll
        for (int nt = 0; nt < 2; nt++) {
          mma_az(dd[nt], fa[0], v[r][2 * nt], v[r][2 * nt + 1]);
          mma_a(dd[nt], fa[1], v[r][4 + 2 * nt], v[r][5 + 2 * nt]);
          mma_az(ee[nt], fa[2], v[r][2 * nt], v[r][2 * nt + 1]);
          mma_a(ee[nt], fa[3], v[r][4 + 2 * nt], v[r][5 + 2 * nt]);
        }
        float mean = (dd[0][0] + dd[0][1]) + (dd[1][0] + dd[1][1]);
        mean += __shfl_xor_sync(0xffffffffu, mean, 1);
        mean += __shfl_xor_sync(0xffffffffu, mean, 2);
        mean = __shfl_sync(0xffffffffu, mean, 0) * (1.f / 512.f);
        const float rs = rsqrtf(fmaxf(fmaf(-mean, mean, sq[r] * (1.f / 512.f)), 0.f) + 1e-5f);
        float acc[4][4];
#pragma unroll
        for (int nt = 0; nt < 2; nt++) {
          const float (&d)[4] = dd[nt];
          const float (&e)[4] = ee[nt];
          const uint4 &ka = tw[2 * nt], &kb = tw[2 * nt + 1], &kc = tw[4 + nt];
          const uint32_t a0 = pack2(d[0] * u2f(ka.x) + d[2] * u2f(ka.y), d[1] * u2f(kb.x) + d[3] * u2f(kb.y));
          const uint32_t a2 = pack2(d[0] * u2f(ka.z) + d[2] * u2f(ka.w), d[1] * u2f(kb.z) + d[3] * u2f(kb.w));
          const uint32_t a1 = pack2(e[0] * u2f(kc.x) + e[2] * u2f(kc.y), e[1] * u2f(kc.z) + e[3] * u2f(kc.w));
          const uint32_t a3 = pack2(e[2] * u2f(kc.x) - e[0] * u2f(kc.y), e[3] * u2f(kc.z) - e[1] * u2f(kc.w));
          const uint32_t dc = pack2(fmaf(mean, -32.f, d[0]), fmaf(mean, -32.f, d[1]));
          const uint32_t h0 = g == 0 ? dc : a0, h2 = g == 0 ? 0u : a2;
          if (nt == 0) {
            mma16816_z(acc[0], a0, a1, a2, a3, fb[2 * nt].x, fb[2 * nt].y);
            mma16816_z(acc[1], a0, a1, a2, a3, fb[2 * nt].z, fb[2 * nt].w);
            mma16816_z(acc[2], h0, a1, h2, a3, fb[2 * nt + 1].x, fb[2 * nt + 1].y);
            mma16816_z(acc[3], h0, a1, h2, a3, fb[2 * nt + 1].z, fb[2 * nt + 1].w);
          } else {
            mma16816(acc[0], a0, a1, a2, a3, fb[2 * nt].x, fb[2 * nt].y);
            mma16816(acc[1], a0, a1, a2, a3, fb[2 * nt].z, fb[2 * nt].w);
            mma16816(acc[2], h0, a1, h2, a3, fb[2 * nt + 1].x, fb[2 * nt + 1].y);
            mma16816(acc[3], h0, a1, h2, a3, fb[2 * nt + 1].z, fb[2 * nt + 1].w);
          }
        }
#pragma unroll
        for (int h = 0; h < 2; h++) {
          const int j = 2 * warp + r, m = 2 * t + h;
          sts4(sbase + SM_E + ((j * 8 + m) * 8 + (g ^ (2 * t) ^ (2 * (j & 3)))) * 16,
               pack2(acc[h][0] * rs, acc[h][1] * rs), pack2(acc[h][2] * rs, acc[h][3] * rs),
               pack2(acc[2 + h][0] * rs, acc[2 + h][1] * rs), pack2(acc[2 + h][2] * rs, acc[2 + h][3] * rs));
        }
      }
      bar_sync(NB_RDY, 384);
      const uint32_t ea = sbase + SM_E + ((t * 8 + warp) * 8 + (g ^ (warp & 6) ^ (2 * t))) * 16;
      lds_frag(q[0], q[1], ea, ea + 4096);
      lds_frag(q[2], q[3], ea + 8192, ea + 12288);
      asm volatile("ld.shared.u32 %0, [%1];" : "=r"(tag) : "r"(BAR(epoch, 0)) : "memory");
      ones = ~(tag >> 31);
      tag = (tag + 1) & 1;
      cdft16(q, fc, o);
#pragma unroll
      for (int vv = 0; vv < 4; vv++) {
        o[vv].y &= ~1u;
        o[vv].z = (o[vv].z & ~1u) | (tag ^ 1);
        st_tag(&scr->Z1[(((4 * vv + t) * 8 + warp) * 128 + c) * 8 + g], o[vv], tag);
      }
    }
    asm volatile("setmaxnreg.inc.sync.aligned.u32 224;");
    {
      uint4* const zp = &scr->Z1[(c * 128 + 8 * t + warp) * 8 + g];
      const uint32_t tst = clock32();
      mbar_wait(BAR(tbar, 0), 0);
      uint4 f2[4], g2[4];
#pragma unroll
      for (int i = 0; i < 4; i++) {
        f2[i] = lds4(TOFF(f2) + warp * 2048 + i * 512);
        g2[i] = lds4(TOFF(g2) + warp * 2048 + i * 512);
      }
      const uint4 f8 = lds4(TOFF(f8)), g8 = lds4(TOFF(g8));
      asm volatile("barrier.cluster.wait.aligned;" ::: "memory");
      spin_until(tst + POLL_DELAY);
      ld_tag4_issue<256>(q, zp);
      float wfr[16], wfi[16];
      {
        const float nyq = ((c & 7) == 7 && g == 0) ? 0.5f : 1.f;
        uint32_t wa = sbase + SM_W + (16 * warp + t) * 80 + ((2 * (c >> 3) + 2) & 15) - 2;
        asm volatile("" : "+r"(wa));
        const uint32_t wb[3] = {wa + 2 * (g == 0 ? 16 : g), wa + 2 * g, wa - 2 * g};
#pragma unroll
        for (int i = 0; i < 16; i++) {
          const int ci = i >> 3, dd = (i >> 2) & 1, e = i & 3;
          const uint32_t a = wb[e < 2 ? e : 2] + (ci * 8 + 4 * dd) * 80 + (e == 0 ? 0 : e == 1 ? 16 : e == 2 ? 64 : 48);
          wfr[i] = bf_lo(lds_u16(a)) * (e == 2 ? nyq : 1.f);
          wfi[i] = bf_lo(lds_u16(a + 10240)) * (e == 2 ? nyq : 1.f);
        }
      }
      ld_tag4_finish<256>(q, zp, tag);
      if (lane == 0) mbar_arrive(BAR(sig, 0));
#pragma unroll
      for (int i = 0; i < 4; i++) q[i].z &= ~1u;
      reg_frag(q, ones);
      cdft16(q, f2, o);
      const uint32_t e2 = sbase + SM_E2;
#pragma unroll
      for (int vv = 0; vv < 4; vv++)
        sts4(e2 + ((warp * 16 + 4 * vv + t) * 8 + (g ^ (2 * t) ^ (2 * (warp & 3)))) * 16, o[vv].x, o[vv].y, o[vv].z, o[vv].w);
      bar_sync(NB_CONS, 256);
      uint32_t ad[2], res[2][2][4];
#pragma unroll
      for (int ci = 0; ci < 2; ci++) {
        const int cc = 2 * warp + ci;
        ad[ci] = e2 + ((t * 16 + cc) * 8 + (g ^ (2 * (cc & 3)) ^ (2 * t))) * 16;
        lds_frag(q[2 * ci], q[2 * ci + 1], ad[ci], ad[ci] + 8192);
      }
#pragma unroll
      for (int ci = 0; ci < 2; ci++)
#pragma unroll
        for (int p = 0; p < 2; p++) {
          uint32_t y[2][2];
#pragma unroll
          for (int vv = 0; vv < 2; vv++) {
            float d[4];
            mma_az(d, q[2 * ci + p], word(f8, 2 * vv), word(f8, 2 * vv + 1));
#pragma unroll
            for (int rr = 0; rr < 2; rr++) {
              const float fr = wfr[ci * 8 + vv * 4 + 2 * p + rr], fi = wfi[ci * 8 + vv * 4 + 2 * p + rr];
              y[vv][rr] = pack2(d[2 * rr] * fr - d[2 * rr + 1] * fi, d[2 * rr] * fi + d[2 * rr + 1] * fr);
            }
          }
#pragma unroll
          for (int vv = 0; vv < 2; vv++) {
            float d[4];
            mma16816_z(d, y[0][0], y[0][1], y[1][0], y[1][1], word(g8, 2 * vv), word(g8, 2 * vv + 1));
            res[ci][vv][2 * p] = pack2(d[0], d[1]);
            res[ci][vv][2 * p + 1] = pack2(d[2], d[3]);
          }
        }
#pragma unroll
      for (int i = 0; i < 4; i++)
        sts4(ad[i >> 1] + (i & 1) * 8192, res[i >> 1][i & 1][0], res[i >> 1][i & 1][1], res[i >> 1][i & 1][2], res[i >> 1][i & 1][3]);
      bar_sync(NB_CONS, 256);
      const uint32_t eb = e2 + ((warp * 16 + t) * 8 + (g ^ (2 * t) ^ (2 * (warp & 3)))) * 16;
      lds_frag(q[0], q[1], eb, eb + 512);
      lds_frag(q[2], q[3], eb + 1024, eb + 1536);
      cdft16(q, g2, o);
#pragma unroll
      for (int vv = 0; vv < 4; vv++) {
        o[vv].y &= ~1u;
        o[vv].z = (o[vv].z & ~1u) | tag;
        st_tag(zp + vv * 256, o[vv], tag);
      }
    }
    {
      const uint4* const zp = &scr->Z1[((t * 8 + warp) * 128 + c) * 8 + g];
      const uint32_t tst = clock32();
      uint4 gb[4], ga[4], gc[4], tw[4];
      uint2 xr[2][4];
      uint2* lnp[2];
#pragma unroll
      for (int r = 0; r < 2; r++) {
        const int row = 16 * f + 2 * warp + r;
        lnp[r] = reinterpret_cast<uint2*>(&scr->LN[(rb * 8 + (g >> 2)) * 1024 + row * 8 + ((2 * (g & 3) + (t >> 1)) ^ (row & 7))]) + (t & 1);
        asm volatile("" : "+l"(lnp[r]));
      }
#pragma unroll
      for (int i = 0; i < 4; i++) {
        gc[i] = lds4(sbase + SM_FC + 2048 + i * 512 + lane * 16);
        gb[i] = lds4(TOFF(gb) + i * 512);
        ga[i] = lds4(TOFF(ga) + i * 512);
        tw[i] = lds4(TOFF(tw3) + i * 512);
        const int ch = 2 * (g + 8 * i) + (t >> 1);
#pragma unroll
        for (int r = 0; r < 2; r++) xr[r][i] = lds2(sbase + SM_X + (2 * warp + r) * 1024 + ((ch ^ ((ch >> 3) & 1)) * 16) + (t & 1) * 8);
      }
      spin_until(tst + POLL_DELAY2);
      ld_tag4_issue<32768>(q, zp);
      ld_tag4_finish<32768, true>(q, zp, tag);
      if (lane == 0) mbar_arrive(BAR(sig, 1));
      reg_frag(q, ones);
      cdft16(q, gc, o);
#pragma unroll
      for (int vv = 0; vv < 4; vv++)
        sts4(sbase + SM_E + (((4 * vv + t) * 8 + warp) * 8 + (g ^ (warp & 6) ^ (2 * t))) * 16, o[vv].x, o[vv].y, o[vv].z, o[vv].w);
      bar_sync(NB_CONS, 256);
      uint32_t hv[2][8];
      const float mk = t == 0 ? 0.f : 1.f;
#pragma unroll
      for (int r = 0; r < 2; r++) {
        const int j = 2 * warp + r;
        uint4 u[2];
#pragma unroll
        for (int h = 0; h < 2; h++) u[h] = lds4(sbase + SM_E + ((j * 8 + 2 * t + h) * 8 + (g ^ (2 * t) ^ (2 * (j & 3)))) * 16);
        const uint32_t bp[4][2] = {{u[0].x, u[1].x & ones}, {u[0].y & ones, u[1].y}, {u[0].z, u[1].z & ones}, {u[0].w & ones, u[1].w}};
        float y[2][2][4];
#pragma unroll
        for (int i = 0; i < 2; i++) {
          float lo[4], hi[4], e[4];
          mma_az(lo, gb[2 * i], bp[0][0], bp[0][1]);
          mma_az(hi, gb[2 * i + 1], bp[2][0], bp[2][1]);
          mma_az(e, gb[2 * i], bp[1][0], bp[1][1]);
          mma_a(e, gb[2 * i + 1], bp[3][0], bp[3][1]);
          const uint4 &ka = tw[2 * i], &kb = tw[2 * i + 1];
          const float tr0 = fmaf(hi[0], mk, lo[0]), ti0 = fmaf(hi[2], mk, lo[2]);
          const float tr1 = lo[1] + hi[1], ti1 = lo[3] + hi[3];
          const float vr0 = tr0 * u2f(ka.x) - ti0 * u2f(ka.y), vi0 = tr0 * u2f(ka.y) + ti0 * u2f(ka.x);
          const float vr1 = tr1 * u2f(ka.z) - ti1 * u2f(ka.w), vi1 = tr1 * u2f(ka.w) + ti1 * u2f(ka.z);
          const uint32_t b0 = pack2(t == 0 ? hi[0] : vr0, vr1), b1 = pack2(t == 0 ? vr0 : vi0, vi1);
          const uint32_t b2 = pack2(e[0] * u2f(kb.x) - e[2] * u2f(kb.y), e[1] * u2f(kb.z) - e[3] * u2f(kb.w));
          const uint32_t b3 = pack2(e[0] * u2f(kb.y) + e[2] * u2f(kb.x), e[1] * u2f(kb.w) + e[3] * u2f(kb.z));
#pragma unroll
          for (int mt = 0; mt < 2; mt++) {
            mma_az(y[mt][i], ga[2 * mt], b0, b1);
            mma_a(y[mt][i], ga[2 * mt + 1], b2, b3);
          }
        }
#pragma unroll
        for (int i = 0; i < 4; i++) {
          hv[r][2 * i] = hadd2_bf16(xr[r][i].x, pack2(y[i >> 1][0][2 * (i & 1)], y[i >> 1][0][2 * (i & 1) + 1]));
          hv[r][2 * i + 1] = hadd2_bf16(xr[r][i].y, pack2(y[i >> 1][1][2 * (i & 1)], y[i >> 1][1][2 * (i & 1) + 1]));
        }
      }
      float mean[2];
      uint32_t mb[2];
#pragma unroll
      for (int r = 0; r < 2; r++) {
        mean[r] = sum_groups(quad_sum(hv[r])) * (1.f / 512.f);
        mb[r] = pack2(mean[r], mean[r]);
      }
#pragma unroll
      for (int i = 0; i < 4; i++)
#pragma unroll
        for (int r = 0; r < 2; r++) {
          hv[r][2 * i] = hsub2_bf16(hv[r][2 * i], mb[r]);
          hv[r][2 * i + 1] = hsub2_bf16(hv[r][2 * i + 1], mb[r]);
          st_tag8(lnp[r] + i * 4096, hv[r][2 * i], hv[r][2 * i + 1], i == 0 ? tag : (hv[r][2 * i] & 1u));
        }
      bar_arrive(NB_LN, 288);
      const uint32_t ones2 = ~(lds2(BAR(epoch, 0)).x >> 31);
      float rstd[2];
#pragma unroll
      for (int r = 0; r < 2; r++) {
        hv[r][0] &= ones2;
        rstd[r] = row_rstd(hv[r], mean[r] - bf_lo(mb[r]));
      }
      if (lane == 0)
        st_tag(&scr->ST[rb * 64 + 8 * f + warp], make_uint4(mb[0] << 16, __float_as_uint(rstd[0]), mb[1] << 16, __float_as_uint(rstd[1])), tag);
    }
    const int wgi = warp >> 2, wq = warp & 3;
    uint4* const pbase = &scr->P[rb * 28 * 1024 + warp * 128 + lane];
    const uint32_t a_lo0 = desc_lo(sbase + wgi * 8192, 16);
    const uint32_t ebar = lane == 0 ? BAR(empty1, 0) : RBAR(empty1, 0);
    unsigned* const pflag = &scr->flag[rb * 64 + f * 8 + warp];
    float r0, r1;
    uint4 px[8], py[6];
    const int rh = wgi ^ kh ^ 1;
    const uint4* const psrc = &scr->P[(rb2 * 28 + 14 * kh) * 1024 + (4 * rh + wq) * 128 + lane];
    const uint32_t pa0 = sbase + (4 * rh + wq) * 2048;
    uint4 pf[3][4];
    uint32_t rdy = 0, got0;
    {
      float acc[128];
#pragma unroll
      for (int i = 0; i < 128; i++) acc[i] = 0.f;
      const uint32_t b_lo0 = desc_lo(sbase + 8 * SLOT, 4096);
      const uint32_t t3 = clock32();
      if (WARM) {
        wg_fence();
#pragma unroll
        for (int i = 0; i < WARM; i++) wgmma_n256(acc, desc64(a_lo0 + 6 * 1024, HI128), desc64(b_lo0, HI128));
        wg_commit();
      }
      const uint4* const ap = &scr->LN[rb * 8 * 1024 + wgi * 512 + (tid & 127)];
      uint4 av[NLL][4];
      spin_until(t3 + POLL_DELAY3);
#pragma unroll
      for (int kb = 0; kb < NLL; kb++) ld_tag4_issue<128>(av[kb], ap + kb * 1024);
      bar_sync(NB_CONS, 256);
      uint32_t slot = 2;
      auto stage_x = [&](int kb, int hh) {
        if (LAGX && hh == ((16 - LAGX) & 1) && kb == ((16 - LAGX) >> 1) && wgi == 1) bar_sync(NB_LAG, 256);
        mbar_wait(BAR(full1, 2 * kb + hh));
        const uint32_t al = a_lo0 + kb * 1024 + hh * 4, bl = b_lo0 + slot * 1024;
        wg_fence();
        wgmma_n256(acc, desc64(al, HI128), desc64(bl, HI128), (kb | hh) != 0 ? 1 : ~ones);
        wgmma_n256(acc, desc64(al + 2, HI128), desc64(bl + 128, HI128));
        wg_commit();
        if (LAGX && hh == 1 && kb == 7 && wgi == 0) bar_arrive(NB_LAG, 256);
        wg_wait<1>();
        if ((kb | hh) != 0 && lane < 2) mbar_arrive_remote(ebar + 8 * (2 * kb + hh - 1));
        if (++slot == 6) slot = 0;
      };
#pragma unroll
      for (int kb = 0; kb < NLL; kb++) {
        ld_tag4_finish<128, true>(av[kb], ap + kb * 1024, tag);
#pragma unroll
        for (int i = 0; i < 4; i++)
          sts4(sbase + kb * SLOT + wgi * 8192 + ((tid & 127) + 128 * i) * 16, av[kb][i].x, av[kb][i].y, av[kb][i].z, av[kb][i].w);
        asm volatile("fence.proxy.async.shared::cta;" ::: "memory");
        bar_sync(NB_WG + wgi, 128);
        if (kb > 0) stage_x(kb - 1, 1);
        stage_x(kb, 0);
      }
      stage_x(NLL - 1, 1);
#pragma unroll 1
      for (int kb = NLL; kb < 8; kb++) {
        mbar_wait(BAR(fullA, kb));
        stage_x(kb, 0);
        stage_x(kb, 1);
      }
      mbar_wait(BAR(sbar, 0), 0);
      r0 = __uint_as_float(lds2(sstat + (16 * warp + g) * 8).y);
      r1 = __uint_as_float(lds2(sstat + (16 * warp + g + 8) * 8).y);
      wg_wait<0>();
      if (lane < 2) mbar_arrive_remote(ebar + 8 * 15);
      make_p<8, false>(acc, r0, r1, px, pbase, 0, tag);
    }
    {
      float acc[96];
#pragma unroll
      for (int i = 0; i < 96; i++) acc[i] = 0.f;
      const uint32_t b_lo0 = desc_lo(sbase + 8 * SLOT, 2048);
      uint4* const pdst = pbase + ((7 * f + 3 * (f & 1)) >> 1) * 1024;
      auto mma_y = [&](int k) {
        const uint32_t al = a_lo0 + (k >> 1) * 1024 + (k & 1) * 4, bl = b_lo0 + (k & 7) * 768;
        wg_fence();
        wgmma_n192(acc, desc64(al, HI128), desc64(bl, HI64));
        wgmma_n192(acc, desc64(al + 2, HI128), desc64(bl + 64, HI64));
        wg_commit();
      };
#pragma unroll
      for (int k = 0; k < 4; k++) {
        mbar_wait(BAR(full1, 16 + k));
        mma_y(k);
        st_tag(pdst + (k >> 1) * 1024 + (k & 1) * 64, px[2 * k], tag);
        st_tag(pdst + (k >> 1) * 1024 + (k & 1) * 64 + 32, px[2 * k + 1], tag);
        if (k == 3 && lane == 0) st_relaxed(pflag, tag);
        wg_wait<1>();
        if (k != 0 && lane < 2) mbar_arrive_remote(ebar + 8 * (15 + k));
      }
#pragma unroll 1
      for (int k = 4; k < 13; k++) {
        mbar_wait(BAR(full1, 16 + k));
        mma_y(k);
        wg_wait<1>();
        if (lane < 2) mbar_arrive_remote(ebar + 8 * (15 + k));
      }
      if (wgi == 1) {
        wg_wait<0>();
        if (lane < 2) mbar_arrive_remote(ebar + 8 * 28);
      }
#pragma unroll
      for (int k = 13; k < 16; k++) mbar_wait(BAR(full1, 16 + k));
      if (wgi == 1) bar_sync(NB_LAG, 256);
#pragma unroll
      for (int k = 13; k < 16; k++) mma_y(k);
      wg_wait<2>();
      if (lane < 2) {
        if (wgi == 0) mbar_arrive_remote(ebar + 8 * 28);
        mbar_arrive_remote(ebar + 8 * 29);
      }
      wg_wait<1>();
      if (wgi == 0) bar_arrive(NB_LAG, 256);
      if (lane < 2) mbar_arrive_remote(ebar + 8 * 30);
      got0 = __all_sync(0xffffffffu, mbar_test(BAR(fullP, 0)));
      if (got0) {
#pragma unroll
        for (int kk = 0; kk < 4; kk++) pf[0][kk] = lds4(pa0 + 3 * SLOT + kk * 512 + lane * 16);
      }
      wg_wait<0>();
      if (lane < 2) mbar_arrive_remote(ebar + 8 * 31);
      const int ks0 = 14 * f + ((f & 1) ? 0 : 8);
      auto reread = [&]() {
        asm volatile("ld.volatile.shared.f32 %0, [%2+4]; ld.volatile.shared.f32 %1, [%2+68];" : "=f"(r0), "=f"(r1) : "r"(sstat + (16 * warp + g) * 8) : "memory");
      };
      make_p<6, true, 0, 2>(acc, r0, r1, py, pbase, ks0, tag);
      if (REDPOS == 2 && lane == 0) st_relaxed(pflag + 1024, tag);
      reread();
      make_p<6, true, 2, 4>(acc, r0, r1, py, pbase, ks0, tag);
      if (REDPOS == 4 && lane == 0) st_relaxed(pflag + 1024, tag);
      reread();
      rdy = mbar_test(BAR(full2, 0)) & mbar_test(BAR(fullP, 1));
      make_p<6, true, 4, 6>(acc, r0, r1, py, pbase, ks0, tag);
      if (REDPOS == 6 && lane == 0) st_relaxed(pflag + 1024, tag);
    }
    {
      float acc[64];
      const uint32_t b2_lo0 = desc_lo(sbase, 8192);
      const uint32_t pbar = ebar + (uint32_t)(offsetof(Bars, emptyP) - offsetof(Bars, empty1));
      if (!got0) {
        mbar_wait(BAR(fullP, 0));
#pragma unroll
        for (int kk = 0; kk < 4; kk++) pf[0][kk] = lds4(pa0 + 3 * SLOT + kk * 512 + lane * 16);
      }
#pragma unroll
      for (int s = 0; s < 14; s++) {
        uint4 (&a)[4] = pf[s % 3];
        ld_tag4_finish<32>(a, psrc + (int)((KORDER >> (4 * s)) & 15) * 1024, tag);
        if (s < 8 && lane < (s < 7 ? 2 : 1)) mbar_arrive_remote(pbar + 8 * s);
        if (s >= 2) {
          wg_wait<1>();
          if (s <= 8 && lane == 0) mbar_arrive(BAR(empty2, s - 2));
        }
        if (!rdy) {
          if (s < 13) mbar_wait(BAR(fullP, s + 1));
          mbar_wait(BAR(full2, s));
        }
        if (s == 14 - LAG2 && wgi == 1) {
          const float m0 = __uint_as_float(lds2(sstat + 1024 + (16 * wq + g) * 8).x);
          const float m1 = __uint_as_float(lds2(sstat + 1024 + (16 * wq + g + 8) * 8).x);
          const uint32_t hb = sbase + 3 * SLOT + (16 * wq + (lane & 15)) * 128;
          wg_wait<0>();
          mbar_wait(BAR(hbar, 0));
#pragma unroll
          for (int i = 0; i < 8; i++) {
            uint32_t h[4];
            asm volatile("ldmatrix.sync.aligned.m8n8.x4.shared.b16 {%0,%1,%2,%3}, [%4];"
                         : "=r"(h[0]), "=r"(h[1]), "=r"(h[2]), "=r"(h[3])
                         : "r"(hb + (i >> 2) * 8192 + (((2 * (i & 3) + (lane >> 4)) ^ (lane & 7)) * 16)) : "memory");
            const uint32_t mk = ((t & 1) == 0 && nq == 0) ? ~1u : ~0u;
#pragma unroll
            for (int e = 0; e < 4; e++) {
              acc[8 * i + 2 * e] += bf_lo(h[e] & mk) + ((e & 1) ? m1 : m0);
              acc[8 * i + 2 * e + 1] += __uint_as_float(h[e] & 0xffff0000u) + ((e & 1) ? m1 : m0);
            }
          }
          bar_sync(NB_LAG, 256);
        }
        const uint32_t bl = b2_lo0 + (uint32_t)((BSLOT >> (4 * s)) & 15) * 1024;
        wg_fence();
        if (s < 13) {
#pragma unroll
          for (int kk = 0; kk < 4; kk++)
            pf[(s + 1) % 3][kk] = lds4(pa0 + (uint32_t)((PSLOT >> (4 * (s + 1))) & 15) * SLOT + kk * 512 + lane * 16);
          rdy = mbar_test(BAR(full2, s + 1));
          if (s < 12) rdy &= mbar_test(BAR(fullP, s + 2));
        }
        if (s == 0) wgmma_rs_n128<0>(acc, a[0].x, a[0].y, a[0].z, a[0].w, desc64(bl, HI128));
        else wgmma_rs_n128<1>(acc, a[0].x, a[0].y, a[0].z, a[0].w, desc64(bl, HI128));
#pragma unroll
        for (int kk = 1; kk < 4; kk++) wgmma_rs_n128<1>(acc, a[kk].x, a[kk].y, a[kk].z, a[kk].w, desc64(bl + kk * 128, HI128));
        wg_commit();
      }
      if (wgi == 0) {
        bar_arrive(NB_LAG, 256);
        uint4* const dst = &scr->Z1[(tid >> 3) * 1024 + (c ^ 4) * 8 + (tid & 7)];
        wg_wait<0>();
#pragma unroll
        for (int i = 0; i < 8; i++)
          st_tag(dst + i * 16384, make_uint4(pack2(acc[8 * i], acc[8 * i + 1]), pack2(acc[8 * i + 2], acc[8 * i + 3]) | 1u,
                                           pack2(acc[8 * i + 4], acc[8 * i + 5]), pack2(acc[8 * i + 6], acc[8 * i + 7])), tag);
      } else {
        uint4 pv[2][4];
        const uint4* const xsrc = &scr->Z1[((tid & 127) >> 3) * 1024 + c * 8 + (tid & 7)];
        ld_tag4_issue<16384>(pv[0], xsrc);
        ld_tag4_issue<16384>(pv[1], xsrc + 65536);
        wg_wait<0>();
        uint32_t w[32];
#pragma unroll
        for (int i = 0; i < 32; i++) w[i] = pack2(acc[2 * i], acc[2 * i + 1]);
        int it = 0;
#pragma unroll 1
        while (!__all_sync(0xffffffffu, pv[0][0].y & pv[0][1].y & pv[0][2].y & pv[0][3].y & pv[1][0].y & pv[1][1].y & pv[1][2].y & pv[1][3].y & 1u)) {
          ld_tag4_issue<16384>(pv[0], xsrc);
          ld_tag4_issue<16384>(pv[1], xsrc + 65536);
          if (++it > SPIN_LIMIT) { die(); break; }
        }
#pragma unroll
        for (int i = 0; i < 8; i++) {
          const uint4& p = pv[i >> 2][i & 3];
          asm volatile("stmatrix.sync.aligned.m8n8.x4.shared.b16 [%0], {%1,%2,%3,%4};"
                       ::"r"(pa0 + (9 + ((lane >> 3) & 1)) * SLOT + (lane & 7) * 256 + (((2 * i + (lane >> 4)) ^ (lane & 7)) * 16)),
                         "r"(hadd2_bf16(w[4 * i], p.x & ~1u)), "r"(hadd2_bf16(w[4 * i + 1], p.y & ~1u)), "r"(hadd2_bf16(w[4 * i + 2], p.z)),
                         "r"(hadd2_bf16(w[4 * i + 3], p.w)) : "memory");
        }
        __syncwarp();
        uint4* const dst = reinterpret_cast<uint4*>(out) + (16 * (c >> 4) + 2 * (4 * rh + wq) + (rb2 & 1) + 128 * (lane >> 4)) * 64 + nq * 16 + (lane & 15);
#pragma unroll
        for (int i = 0; i < 8; i++) {
          const int r = 2 * (i & 3) + (lane >> 4);
          dst[i * 256 * 64] = lds4(pa0 + (9 + (i >> 2)) * SLOT + r * 256 + (((lane & 15) ^ r) * 16));
        }
      }
    }
  }
#undef BAR
#undef TOFF
#undef RBAR
}

typedef CUresult (*EncodeFn)(CUtensorMap*, CUtensorMapDataType, cuuint32_t, void*, const cuuint64_t*, const cuuint64_t*,
                             const cuuint32_t*, const cuuint32_t*, CUtensorMapInterleave, CUtensorMapSwizzle,
                             CUtensorMapL2promotion, CUtensorMapFloatOOBfill);

}

extern "C" void kernel_launch(void* const* d_in, const int* in_sizes, int n_in, void* d_out, int out_size) {
  (void)in_sizes; (void)n_in; (void)out_size;
  static EncodeFn encode = nullptr;
  static void *tab = nullptr, *scr = nullptr;
  if (!encode) {
    void* fn = nullptr;
    cudaDriverEntryPointQueryResult qr;
    cudaGetDriverEntryPoint("cuTensorMapEncodeTiled", &fn, cudaEnableDefault, &qr);
    encode = (EncodeFn)fn;
    cudaGetSymbolAddress(&tab, g_tab);
    cudaGetSymbolAddress(&scr, g_scr);
    cudaFuncSetAttribute(fused_kernel, cudaFuncAttributeMaxDynamicSharedMemorySize, SMEM_BYTES);
  }
  CUtensorMap tmGX, tmUX, tmGY, tmUY, tmD, tmWR, tmWI;
  const cuuint32_t es[5] = {1, 1, 1, 1, 1};
  auto enc = [&](CUtensorMap* m, void* p, int rank, const cuuint64_t* gd, const cuuint64_t* gs, const cuuint32_t* bd,
                 CUtensorMapSwizzle sw, CUtensorMapL2promotion pr) {
    encode(m, CU_TENSOR_MAP_DATA_TYPE_BFLOAT16, rank, p, gd, gs, bd, es, CU_TENSOR_MAP_INTERLEAVE_NONE, sw, pr,
           CU_TENSOR_MAP_FLOAT_OOB_FILL_NONE);
  };
  {
    const cuuint64_t gd[3] = {64, 512, 28}, gs[2] = {3584, 128};
    const cuuint32_t bd[3] = {64, 32, 2};
    enc(&tmGX, d_in[4], 3, gd, gs, bd, CU_TENSOR_MAP_SWIZZLE_128B, CU_TENSOR_MAP_L2_PROMOTION_L2_256B);
    enc(&tmUX, d_in[5], 3, gd, gs, bd, CU_TENSOR_MAP_SWIZZLE_128B, CU_TENSOR_MAP_L2_PROMOTION_L2_256B);
  }
  {
    const cuuint64_t gd[3] = {32, 512, 56}, gs[2] = {3584, 64};
    const cuuint32_t bd[3] = {32, 32, 3};
    enc(&tmGY, d_in[4], 3, gd, gs, bd, CU_TENSOR_MAP_SWIZZLE_64B, CU_TENSOR_MAP_L2_PROMOTION_L2_128B);
    enc(&tmUY, d_in[5], 3, gd, gs, bd, CU_TENSOR_MAP_SWIZZLE_64B, CU_TENSOR_MAP_L2_PROMOTION_L2_128B);
  }
  {
    const cuuint64_t gd[3] = {64, 1792, 8}, gs[2] = {1024, 128};
    const cuuint32_t bd[3] = {64, 64, 2};
    enc(&tmD, d_in[6], 3, gd, gs, bd, CU_TENSOR_MAP_SWIZZLE_128B, CU_TENSOR_MAP_L2_PROMOTION_L2_256B);
  }
  {
    const cuuint64_t gd[3] = {4112, 8, 16}, gs[2] = {16 * 8224, 8224};
    const cuuint32_t bd[3] = {40, 8, 16};
    enc(&tmWR, d_in[1], 3, gd, gs, bd, CU_TENSOR_MAP_SWIZZLE_NONE, CU_TENSOR_MAP_L2_PROMOTION_NONE);
    enc(&tmWI, d_in[2], 3, gd, gs, bd, CU_TENSOR_MAP_SWIZZLE_NONE, CU_TENSOR_MAP_L2_PROMOTION_NONE);
  }
  fused_kernel<<<NCTA, NTHREADS, SMEM_BYTES>>>((const __nv_bfloat16*)d_in[0], (const Tables*)tab, (Scratch*)scr,
                                               (__nv_bfloat16*)d_out, (const char*)d_in[4], (const char*)d_in[5],
                                               (const char*)d_in[6], tmWR, tmWI, tmGX, tmUX, tmGY, tmUY, tmD);
}
```

```cpp
#include <cuda_runtime.h>
#include <cuda_bf16.h>
#include <cuda.h>
#include <stdint.h>

namespace {

constexpr int NCTA = 128;
constexpr int NTHREADS = 384;
constexpr int SLOT = 16384;
constexpr int SMEM_BYTES = 14 * SLOT + 3072;
constexpr int SPIN_LIMIT = 1 << 22;

struct Scratch {
  uint4 Z1[128 * 1024];
  uint4 LN[16 * 8 * 1024];
  uint4 P[16 * 28 * 1024];
  uint4 ST[1024];
  unsigned cnt[64 * 32];
};
__device__ __align__(1024) Scratch g_scr;

constexpr double ccos(int i, int n) {
  i &= n - 1;
  if (i > n / 2) i = n - i;
  if (4 * i == n) return 0.0;
  const bool neg = 4 * i > n;
  if (neg) i = n / 2 - i;
  const double a = 6.283185307179586476925 * i / n, a2 = a * a;
  double term = 1.0, sum = 1.0;
  for (int k = 1; k < 14; k++) { term *= -a2 / ((2 * k - 1) * (2 * k)); sum += term; }
  return neg ? -sum : sum;
}
constexpr double csin(int i, int n) { return ccos(i - n / 4, n); }
constexpr unsigned fbits(double v, int mant) {
  if (v == 0.0) return 0;
  const unsigned sg = v < 0 ? 1u : 0u;
  if (v < 0) v = -v;
  int e = 127;
  while (v < 1.0) { v *= 2.0; e--; }
  const unsigned m = (unsigned)((v - 1.0) * (double)(1u << mant) + 0.5);
  return (sg << (8 + mant)) + ((unsigned)e << mant) + m;
}
constexpr unsigned pkb(double lo, double hi) { return fbits(lo, 7) | (fbits(hi, 7) << 16); }
constexpr double fa_elem(int mt, int r, int n1) {
  const int k1 = 8 * mt + (r & 7);
  return r < 8 ? ccos(k1 * n1, 32) : k1 == 0 ? ccos(16 * n1, 32) : -csin(k1 * n1, 32);
}
constexpr unsigned cfrag_c(int idx, int n, int ri, double s = 1.0) {
  return ri ? pkb(-s * csin(idx, n), s * ccos(idx, n)) : pkb(s * ccos(idx, n), s * csin(idx, n));
}
struct Tables {
  unsigned fa[4][32][4];
  unsigned fb[4][32][4];
  unsigned tw1[6][32][4];
  unsigned f2[8][4][32][4];
  unsigned g2[8][4][32][4];
  unsigned gb[4][32][4];
  unsigned ga[4][32][4];
  unsigned tw3[4][32][4];
  unsigned f8[32][4], g8[32][4];
};
constexpr int T1_BYTES = 7168, T2_BYTES = 39936;
static_assert(sizeof(Tables) == T1_BYTES + T2_BYTES, "table size");
constexpr Tables make_tables() {
  Tables T = {};
  for (int l = 0; l < 32; l++) {
    const int g = l >> 2, t = l & 3;
    for (int a = 0; a < 2; a++)
      for (int b = 0; b < 2; b++) {
        for (int r = 0; r < 4; r++) {
          const int row = g + 8 * (r & 1), col = 2 * t + 8 * (r >> 1);
          T.fa[2 * a + b][l][r] = pkb(fa_elem(a, row, 16 * b + col), fa_elem(a, row, 16 * b + col + 1));
          T.ga[2 * a + b][l][r] = pkb(fa_elem(b, col, 16 * a + row), fa_elem(b, col + 1, 16 * a + row));
        }
        const double sg = b ? -1.0 : 1.0;
        for (int h = 0; h < 2; h++) {
          const int ri = g & 1, m = 2 * (g >> 1) + h, k2 = b ? 15 - m : m;
          const int pa = (8 * a + 2 * t) * k2, pb = (8 * a + 2 * t + 1) * k2;
          T.fb[2 * a + b][l][2 * h] = ri == 0 ? pkb(ccos(pa, 16), ccos(pb, 16)) : pkb(-sg * csin(pa, 16), -sg * csin(pb, 16));
          T.fb[2 * a + b][l][2 * h + 1] = ri == 0 ? pkb(csin(pa, 16), csin(pb, 16)) : pkb(sg * ccos(pa, 16), sg * ccos(pb, 16));
        }
        const int n2 = 4 * (g >> 1) + 2 * a + (g & 1);
        for (int h = 0; h < 2; h++) {
          const int p = n2 * (b ? 15 - 2 * t - h : 2 * t + h);
          T.gb[2 * a + b][l][2 * h] = pkb(ccos(p, 16), -sg * csin(p, 16));
          T.gb[2 * a + b][l][2 * h + 1] = pkb(csin(p, 16), sg * ccos(p, 16));
          const int k1 = 8 * b + 2 * t + h, q = n2 * (k1 == 0 ? 16 : k1);
          T.tw3[2 * a + b][l][2 * h] = fbits(ccos(q, 512), 23);
          T.tw3[2 * a + b][l][2 * h + 1] = fbits(csin(q, 512), 23);
        }
        const int p = (8 * a + 2 * t + b) * (g == 0 ? 16 : g);
        T.tw1[2 * a + b][l][0] = fbits(g == 0 ? 0.0 : ccos(p, 512), 23);
        T.tw1[2 * a + b][l][1] = fbits(g == 0 ? ccos(p, 512) : csin(p, 512), 23);
        T.tw1[2 * a + b][l][2] = fbits(g == 0 ? 0.0 : -csin(p, 512), 23);
        T.tw1[2 * a + b][l][3] = fbits(g == 0 ? -csin(p, 512) : ccos(p, 512), 23);
        T.tw1[4 + a][l][2 * b] = fbits(ccos((8 * a + 2 * t + b) * (g + 8), 512), 23);
        T.tw1[4 + a][l][2 * b + 1] = fbits(csin((8 * a + 2 * t + b) * (g + 8), 512), 23);
      }
    for (int i = 0; i < 4; i++) {
      const int p8 = (t + 4 * (i & 1)) * (4 * (i >> 1) + (g >> 1));
      T.f8[l][i] = cfrag_c(p8, 8, g & 1);
      T.g8[l][i] = cfrag_c(-p8, 8, g & 1, 1.0 / (1 << 19));
    }
    for (int w = 0; w < 8; w++)
      for (int i = 0; i < 16; i++) {
        const int kidx = t + 4 * (i & 1) + 8 * (i >> 3), nidx = 4 * ((i >> 1) & 3) + (g >> 1);
        T.f2[w][i >> 2][l][i & 3] = cfrag_c((8 * kidx + w) * nidx, 128, g & 1);
        T.g2[w][i >> 2][l][i & 3] = cfrag_c(-(8 * nidx + w) * kidx, 128, g & 1);
      }
  }
  return T;
}
__device__ const __align__(128) Tables g_tab = make_tables();

__device__ __forceinline__ void die() { asm volatile("st.global.u32 [%0], %1;" ::"l"(0ull), "r"(0) : "memory"); }
__device__ __forceinline__ uint32_t s2u(const void* p) { return (uint32_t)__cvta_generic_to_shared(p); }
__device__ __forceinline__ void mbar_init(uint32_t b, int c) { asm volatile("mbarrier.init.shared::cta.b64 [%0], %1;" ::"r"(b), "r"(c)); }
__device__ __forceinline__ void mbar_expect(uint32_t b, int bytes) {
  asm volatile("mbarrier.arrive.expect_tx.shared::cta.b64 _, [%0], %1;" ::"r"(b), "r"(bytes) : "memory");
}
__device__ __forceinline__ void mbar_arrive(uint32_t b) { asm volatile("mbarrier.arrive.shared::cta.b64 _, [%0];" ::"r"(b) : "memory"); }
__device__ __forceinline__ uint32_t mbar_try(uint32_t b, uint32_t parity) {
  uint32_t ok;
  asm volatile("{.reg .pred p; mbarrier.try_wait.parity.shared::cta.b64 p, [%1], %2; selp.u32 %0,1,0,p;}"
               : "=r"(ok) : "r"(b), "r"(parity) : "memory");
  return ok;
}
__device__ __forceinline__ uint32_t mbar_test(uint32_t b) {
  uint32_t ok;
  asm volatile("{.reg .pred p; mbarrier.test_wait.parity.shared::cta.b64 p, [%1], 0; selp.u32 %0,1,0,p;}" : "=r"(ok) : "r"(b) : "memory");
  return ok;
}
__device__ __forceinline__ void mbar_wait(uint32_t b, uint32_t parity = 0) {
  int it = 0;
#pragma unroll 1
  while (!mbar_try(b, parity))
    if (++it > SPIN_LIMIT) { die(); break; }
}
__device__ __forceinline__ void bar_sync(int id, int n) { asm volatile("bar.sync %0, %1;" ::"r"(id), "r"(n) : "memory"); }
__device__ __forceinline__ void bar_arrive(int id, int n) { asm volatile("bar.arrive %0, %1;" ::"r"(id), "r"(n) : "memory"); }
__device__ __forceinline__ void red_release(unsigned* p) { asm volatile("red.release.gpu.global.add.u32 [%0], 1;" ::"l"(p) : "memory"); }
__device__ __forceinline__ void red_relaxed(unsigned* p) { asm volatile("red.relaxed.gpu.global.add.u32 [%0], 1;" ::"l"(p) : "memory"); }
__device__ __forceinline__ unsigned ld_acquire(const unsigned* p) {
  unsigned v;
  asm volatile("ld.acquire.gpu.global.u32 %0, [%1];" : "=r"(v) : "l"(p) : "memory");
  return v;
}
__device__ __forceinline__ unsigned ld_relaxed(const unsigned* p) {
  unsigned v;
  asm volatile("ld.relaxed.gpu.global.u32 %0, [%1];" : "=r"(v) : "l"(p) : "memory");
  return v;
}
__device__ __forceinline__ void wait_counter(const unsigned* p, unsigned target) {
  int it = 0;
  while ((int)(ld_acquire(p) - target) < 0)
    if (++it > SPIN_LIMIT) { die(); break; }
}
__device__ __forceinline__ void sts4(uint32_t a, uint32_t x, uint32_t y, uint32_t z, uint32_t w) {
  asm volatile("st.shared.v4.u32 [%0], {%1,%2,%3,%4};" ::"r"(a), "r"(x), "r"(y), "r"(z), "r"(w) : "memory");
}
__device__ __forceinline__ uint4 lds4(uint32_t a) {
  uint4 v;
  asm volatile("ld.shared.v4.u32 {%0,%1,%2,%3}, [%4];" : "=r"(v.x), "=r"(v.y), "=r"(v.z), "=r"(v.w) : "r"(a) : "memory");
  return v;
}
__device__ __forceinline__ uint32_t pack2(float lo, float hi) {
  uint32_t r;
  asm("cvt.rn.bf16x2.f32 %0, %1, %2;" : "=r"(r) : "f"(hi), "f"(lo));
  return r;
}
__device__ __forceinline__ float bf_lo(uint32_t v) { return __uint_as_float(v << 16); }
__device__ __forceinline__ uint32_t hadd2_bf16(uint32_t a, uint32_t b) {
  uint32_t r;
  asm("add.rn.bf16x2 %0, %1, %2;" : "=r"(r) : "r"(a), "r"(b));
  return r;
}
__device__ __forceinline__ void mma16816(float (&d)[4], uint32_t a0, uint32_t a1, uint32_t a2, uint32_t a3, uint32_t b0, uint32_t b1) {
  asm("mma.sync.aligned.m16n8k16.row.col.f32.bf16.bf16.f32 {%0,%1,%2,%3}, {%4,%5,%6,%7}, {%8,%9}, {%0,%1,%2,%3};"
      : "+f"(d[0]), "+f"(d[1]), "+f"(d[2]), "+f"(d[3])
      : "r"(a0), "r"(a1), "r"(a2), "r"(a3), "r"(b0), "r"(b1));
}
__device__ __forceinline__ void mma16816_z(float (&d)[4], uint32_t a0, uint32_t a1, uint32_t a2, uint32_t a3, uint32_t b0, uint32_t b1) {
  asm("{.reg .f32 z; mov.f32 z, 0f00000000;\n"
      "mma.sync.aligned.m16n8k16.row.col.f32.bf16.bf16.f32 {%0,%1,%2,%3}, {%4,%5,%6,%7}, {%8,%9}, {z,z,z,z};}"
      : "=f"(d[0]), "=f"(d[1]), "=f"(d[2]), "=f"(d[3])
      : "r"(a0), "r"(a1), "r"(a2), "r"(a3), "r"(b0), "r"(b1));
}
template <int N>
__device__ __forceinline__ void cs_frac(int idx, float& c, float& s) {
  int i = ((idx + N / 2) & (N - 1)) - N / 2;
  float a = (float)i * (6.283185307179586f / N);
  c = __cosf(a);
  s = __sinf(a);
}
template <int N>
__device__ __forceinline__ uint32_t cfrag(int idx, int ri) {
  float c, s;
  cs_frac<N>(idx, c, s);
  return ri ? pack2(-s, c) : pack2(c, s);
}
__device__ __forceinline__ uint32_t word(const uint4& v, int e) { return e == 0 ? v.x : e == 1 ? v.y : e == 2 ? v.z : v.w; }
__device__ __forceinline__ void cdft16(const uint4 (&A)[4], const uint4 (&F)[4], uint4 (&o)[4]) {
  float acc[2][4][4];
#pragma unroll
  for (int ks = 0; ks < 2; ks++)
#pragma unroll
    for (int p = 0; p < 2; p++)
#pragma unroll
      for (int v = 0; v < 4; v++) {
        const uint4& a = A[2 * ks + p];
        const uint32_t b0 = word(F[ks * 2 + (v >> 1)], (v & 1) * 2), b1 = word(F[ks * 2 + (v >> 1)], (v & 1) * 2 + 1);
        if (ks == 0) mma16816_z(acc[p][v], a.x, a.y, a.z, a.w, b0, b1);
        else mma16816(acc[p][v], a.x, a.y, a.z, a.w, b0, b1);
      }
#pragma unroll
  for (int v = 0; v < 4; v++)
    o[v] = make_uint4(pack2(acc[0][v][0], acc[0][v][1]), pack2(acc[0][v][2], acc[0][v][3]),
                      pack2(acc[1][v][0], acc[1][v][1]), pack2(acc[1][v][2], acc[1][v][3]));
}
__device__ __forceinline__ void lds_frag(uint4& f0, uint4& f1, uint32_t a0, uint32_t a1) {
  asm volatile("ld.volatile.shared.v2.u32 {%0,%1}, [%8]; ld.volatile.shared.v2.u32 {%2,%3}, [%9];\n"
               "ld.volatile.shared.v2.u32 {%4,%5}, [%8+8]; ld.volatile.shared.v2.u32 {%6,%7}, [%9+8];"
               : "=r"(f0.x), "=r"(f0.y), "=r"(f0.z), "=r"(f0.w), "=r"(f1.x), "=r"(f1.y), "=r"(f1.z), "=r"(f1.w) : "r"(a0), "r"(a1) : "memory");
}
__device__ __forceinline__ void reg_frag(uint4 (&q)[4], uint32_t ones) {
#pragma unroll
  for (int ks = 0; ks < 2; ks++) {
    const uint4 a = q[2 * ks], b = q[2 * ks + 1];
    q[2 * ks] = make_uint4(a.x, a.y, b.x & ones, b.y & ones);
    q[2 * ks + 1] = make_uint4(a.z & ones, a.w & ones, b.z, b.w);
  }
}
__device__ __forceinline__ void st_tag(uint4* p, const uint4& v, uint32_t tag) {
  asm volatile("st.relaxed.gpu.global.v4.b32 [%0], {%1,%2,%3,%4};"
               ::"l"(p), "r"((v.x & ~1u) | tag), "r"(v.y), "r"(v.z), "r"(v.w) : "memory");
}
__device__ __forceinline__ void st_tag8(void* p, uint32_t x, uint32_t y, uint32_t tag) {
  asm volatile("st.relaxed.gpu.global.v2.b32 [%0], {%1,%2};" ::"l"(p), "r"((x & ~1u) | tag), "r"(y) : "memory");
}
__device__ __forceinline__ uint4 ld_b128(const uint4* p) {
  uint4 v;
  asm volatile("ld.relaxed.gpu.global.v4.b32 {%0,%1,%2,%3}, [%4];"
               : "=r"(v.x), "=r"(v.y), "=r"(v.z), "=r"(v.w) : "l"(p) : "memory");
  return v;
}
template <int STRIDE>
__device__ __forceinline__ void ld_tag4_issue(uint4 (&q)[4], const uint4* p) {
#pragma unroll
  for (int i = 0; i < 4; i++) q[i] = ld_b128(p + i * STRIDE);
}
template <int STRIDE, bool HALVES = false>
__device__ __forceinline__ void ld_tag4_finish(uint4 (&q)[4], const uint4* p, uint32_t tag) {
  int it = 0;
#pragma unroll 1
  while (__any_sync(0xffffffffu, ((q[0].x ^ tag) | (q[1].x ^ tag) | (q[2].x ^ tag) | (q[3].x ^ tag) |
                                  (HALVES ? (q[0].z ^ tag) | (q[1].z ^ tag) | (q[2].z ^ tag) | (q[3].z ^ tag) : 0u)) & 1u)) {
    ld_tag4_issue<STRIDE>(q, p);
    if (++it > SPIN_LIMIT) { die(); break; }
  }
#pragma unroll
  for (int i = 0; i < 4; i++) {
    asm volatile("and.b32 %0, %0, 0xfffffffe;" : "+r"(q[i].x));
    if (HALVES) q[i].z &= ~1u;
  }
}
__device__ __forceinline__ float quad_sum(const uint32_t (&a)[8]) {
  float d[4];
  mma16816_z(d, a[0], a[1], a[2], a[3], 0x3f803f80u, 0x3f803f80u);
  mma16816(d, a[4], a[5], a[6], a[7], 0x3f803f80u, 0x3f803f80u);
  return d[0] + d[2];
}
__device__ __forceinline__ float sum_groups(float v) {
  v += __shfl_xor_sync(0xffffffffu, v, 4);
  v += __shfl_xor_sync(0xffffffffu, v, 8);
  v += __shfl_xor_sync(0xffffffffu, v, 16);
  return v;
}
__device__ __forceinline__ uint32_t hsub2_bf16(uint32_t a, uint32_t b) {
  uint32_t r;
  asm("sub.rn.bf16x2 %0, %1, %2;" : "=r"(r) : "r"(a), "r"(b));
  return r;
}
__device__ __forceinline__ float row_rstd(const uint32_t (&c)[8], float delta) {
  uint32_t s[8];
#pragma unroll
  for (int i = 0; i < 8; i++) asm("mul.rn.bf16x2 %0, %1, %1;" : "=r"(s[i]) : "r"(c[i]));
  return rsqrtf(fmaxf(fmaf(-delta, delta, sum_groups(quad_sum(s)) * (1.f / 512.f)), 0.f) + 1e-5f);
}
__device__ __forceinline__ uint64_t desc64(uint32_t lo, uint32_t hi) {
  uint64_t d;
  asm("mov.b64 %0, {%1, %2};" : "=l"(d) : "r"(lo), "r"(hi));
  return d;
}
constexpr uint32_t desc_hi(uint32_t sbo, uint32_t swz) { return (sbo >> 4) | (swz << 30); }
__device__ __forceinline__ uint32_t desc_lo(uint32_t addr, uint32_t lbo) { return ((addr & 0x3FFFF) >> 4) | ((lbo >> 4) << 16); }
__device__ __forceinline__ void cp_async16(uint32_t dst, const void* src) {
  asm volatile("cp.async.cg.shared.global [%0], [%1], 16;" ::"r"(dst), "l"(src) : "memory");
}
__device__ __forceinline__ uint2 lds2(uint32_t a) {
  uint2 v;
  asm volatile("ld.shared.v2.u32 {%0,%1}, [%2];" : "=r"(v.x), "=r"(v.y) : "r"(a) : "memory");
  return v;
}
__device__ __forceinline__ uint32_t lds_u16(uint32_t a) {
  uint16_t v;
  asm volatile("ld.shared.u16 %0, [%1];" : "=h"(v) : "r"(a) : "memory");
  return v;
}
__device__ __forceinline__ void wg_fence() { asm volatile("wgmma.fence.sync.aligned;" ::: "memory"); }
__device__ __forceinline__ void wg_commit() { asm volatile("wgmma.commit_group.sync.aligned;" ::: "memory"); }
template <int N>
__device__ __forceinline__ void wg_wait() { asm volatile("wgmma.wait_group.sync.aligned %0;" ::"n"(N) : "memory"); }
__device__ __forceinline__ void bulk_load(uint32_t dst, const void* src, int bytes, uint32_t bar) {
  asm volatile("cp.async.bulk.shared::cluster.global.mbarrier::complete_tx::bytes [%0], [%1], %2, [%3];"
               ::"r"(dst), "l"(src), "r"(bytes), "r"(bar) : "memory");
}
__device__ __forceinline__ void bulk_load_mc(uint32_t dst, const void* src, int bytes, uint32_t bar) {
  asm volatile("cp.async.bulk.shared::cluster.global.mbarrier::complete_tx::bytes.multicast::cluster [%0], [%1], %2, [%3], %4;"
               ::"r"(dst), "l"(src), "r"(bytes), "r"(bar), "h"((uint16_t)3) : "memory");
}
__device__ __forceinline__ void tma3(uint32_t dst, const CUtensorMap* tm, uint32_t bar, int c0, int c1, int c2) {
  asm volatile("cp.async.bulk.tensor.3d.shared::cluster.global.mbarrier::complete_tx::bytes [%0], [%1, {%3,%4,%5}], [%2];"
               ::"r"(dst), "l"(tm), "r"(bar), "r"(c0), "r"(c1), "r"(c2) : "memory");
}
__device__ __forceinline__ void tma3_mc(uint32_t dst, const CUtensorMap* tm, uint32_t bar, int c1, int c2) {
  asm volatile("cp.async.bulk.tensor.3d.shared::cluster.global.mbarrier::complete_tx::bytes.multicast::cluster [%0], [%1, {%3,%4,%5}], [%2], %6;"
               ::"r"(dst), "l"(tm), "r"(bar), "r"(0), "r"(c1), "r"(c2), "h"((uint16_t)3) : "memory");
}
__device__ __forceinline__ void mbar_arrive_remote(uint32_t rb) {
  asm volatile("mbarrier.arrive.shared::cluster.b64 _, [%0];" ::"r"(rb) : "memory");
}
__device__ __forceinline__ uint4 ldg_ca4(const void* p) {
  uint4 v;
  asm volatile("ld.global.ca.v4.u32 {%0,%1,%2,%3}, [%4];" : "=r"(v.x), "=r"(v.y), "=r"(v.z), "=r"(v.w) : "l"(p) : "memory");
  return v;
}
__device__ __forceinline__ float u2f(uint32_t v) { return __uint_as_float(v); }
__device__ __forceinline__ void mma_az(float (&d)[4], const uint4& a, uint32_t b0, uint32_t b1) { mma16816_z(d, a.x, a.y, a.z, a.w, b0, b1); }
__device__ __forceinline__ void mma_a(float (&d)[4], const uint4& a, uint32_t b0, uint32_t b1) { mma16816(d, a.x, a.y, a.z, a.w, b0, b1); }
__device__ __forceinline__ uint32_t clock32() {
  uint32_t v;
  asm volatile("mov.u32 %0, %%clock;" : "=r"(v) :: "memory");
  return v;
}
__device__ __forceinline__ float swiglu(float g, float u, float r) {
  float hg = (0.5f * r) * g, th;
  asm("tanh.approx.f32 %0, %1;" : "=f"(th) : "f"(hg));
  return fmaf(hg, th, hg) * (r * u);
}
__device__ __forceinline__ void l2_prefetch(const void* p, int bytes) {
  asm volatile("cp.async.bulk.prefetch.L2.global [%0], %1;" ::"l"(p), "r"(bytes) : "memory");
}

__device__ __forceinline__ void wgmma_n256(float (&d)[128], uint64_t da, uint64_t db, int sd = 1) {
  asm volatile("{.reg .pred p; setp.ne.b32 p, %130, 0;\n"
      "wgmma.mma_async.sync.aligned.m64n256k16.f32.bf16.bf16 {"
      "%0,%1,%2,%3,%4,%5,%6,%7,%8,%9,%10,%11,%12,%13,%14,%15,"
      "%16,%17,%18,%19,%20,%21,%22,%23,%24,%25,%26,%27,%28,%29,%30,%31,"
      "%32,%33,%34,%35,%36,%37,%38,%39,%40,%41,%42,%43,%44,%45,%46,%47,"
      "%48,%49,%50,%51,%52,%53,%54,%55,%56,%57,%58,%59,%60,%61,%62,%63,"
      "%64,%65,%66,%67,%68,%69,%70,%71,%72,%73,%74,%75,%76,%77,%78,%79,"
      "%80,%81,%82,%83,%84,%85,%86,%87,%88,%89,%90,%91,%92,%93,%94,%95,"
      "%96,%97,%98,%99,%100,%101,%102,%103,%104,%105,%106,%107,%108,%109,%110,%111,"
      "%112,%113,%114,%115,%116,%117,%118,%119,%120,%121,%122,%123,%124,%125,%126,%127"
      "}, %128, %129, p, 1, 1, 0, 1;}\n"
      : "+f"(d[0]),"+f"(d[1]),"+f"(d[2]),"+f"(d[3]),"+f"(d[4]),"+f"(d[5]),"+f"(d[6]),"+f"(d[7]),
        "+f"(d[8]),"+f"(d[9]),"+f"(d[10]),"+f"(d[11]),"+f"(d[12]),"+f"(d[13]),"+f"(d[14]),"+f"(d[15]),
        "+f"(d[16]),"+f"(d[17]),"+f"(d[18]),"+f"(d[19]),"+f"(d[20]),"+f"(d[21]),"+f"(d[22]),"+f"(d[23]),
        "+f"(d[24]),"+f"(d[25]),"+f"(d[26]),"+f"(d[27]),"+f"(d[28]),"+f"(d[29]),"+f"(d[30]),"+f"(d[31]),
        "+f"(d[32]),"+f"(d[33]),"+f"(d[34]),"+f"(d[35]),"+f"(d[36]),"+f"(d[37]),"+f"(d[38]),"+f"(d[39]),
        "+f"(d[40]),"+f"(d[41]),"+f"(d[42]),"+f"(d[43]),"+f"(d[44]),"+f"(d[45]),"+f"(d[46]),"+f"(d[47]),
        "+f"(d[48]),"+f"(d[49]),"+f"(d[50]),"+f"(d[51]),"+f"(d[52]),"+f"(d[53]),"+f"(d[54]),"+f"(d[55]),
        "+f"(d[56]),"+f"(d[57]),"+f"(d[58]),"+f"(d[59]),"+f"(d[60]),"+f"(d[61]),"+f"(d[62]),"+f"(d[63]),
        "+f"(d[64]),"+f"(d[65]),"+f"(d[66]),"+f"(d[67]),"+f"(d[68]),"+f"(d[69]),"+f"(d[70]),"+f"(d[71]),
        "+f"(d[72]),"+f"(d[73]),"+f"(d[74]),"+f"(d[75]),"+f"(d[76]),"+f"(d[77]),"+f"(d[78]),"+f"(d[79]),
        "+f"(d[80]),"+f"(d[81]),"+f"(d[82]),"+f"(d[83]),"+f"(d[84]),"+f"(d[85]),"+f"(d[86]),"+f"(d[87]),
        "+f"(d[88]),"+f"(d[89]),"+f"(d[90]),"+f"(d[91]),"+f"(d[92]),"+f"(d[93]),"+f"(d[94]),"+f"(d[95]),
        "+f"(d[96]),"+f"(d[97]),"+f"(d[98]),"+f"(d[99]),"+f"(d[100]),"+f"(d[101]),"+f"(d[102]),"+f"(d[103]),
        "+f"(d[104]),"+f"(d[105]),"+f"(d[106]),"+f"(d[107]),"+f"(d[108]),"+f"(d[109]),"+f"(d[110]),"+f"(d[111]),
        "+f"(d[112]),"+f"(d[113]),"+f"(d[114]),"+f"(d[115]),"+f"(d[116]),"+f"(d[117]),"+f"(d[118]),"+f"(d[119]),
        "+f"(d[120]),"+f"(d[121]),"+f"(d[122]),"+f"(d[123]),"+f"(d[124]),"+f"(d[125]),"+f"(d[126]),"+f"(d[127])
      : "l"(da), "l"(db), "r"(sd));
}
__device__ __forceinline__ void wgmma_n192(float (&d)[96], uint64_t da, uint64_t db) {
  asm volatile("wgmma.mma_async.sync.aligned.m64n192k16.f32.bf16.bf16 {"
      "%0,%1,%2,%3,%4,%5,%6,%7,%8,%9,%10,%11,%12,%13,%14,%15,"
      "%16,%17,%18,%19,%20,%21,%22,%23,%24,%25,%26,%27,%28,%29,%30,%31,"
      "%32,%33,%34,%35,%36,%37,%38,%39,%40,%41,%42,%43,%44,%45,%46,%47,"
      "%48,%49,%50,%51,%52,%53,%54,%55,%56,%57,%58,%59,%60,%61,%62,%63,"
      "%64,%65,%66,%67,%68,%69,%70,%71,%72,%73,%74,%75,%76,%77,%78,%79,"
      "%80,%81,%82,%83,%84,%85,%86,%87,%88,%89,%90,%91,%92,%93,%94,%95"
      "}, %96, %97, 1, 1, 1, 0, 1;\n"
      : "+f"(d[0]),"+f"(d[1]),"+f"(d[2]),"+f"(d[3]),"+f"(d[4]),"+f"(d[5]),"+f"(d[6]),"+f"(d[7]),
        "+f"(d[8]),"+f"(d[9]),"+f"(d[10]),"+f"(d[11]),"+f"(d[12]),"+f"(d[13]),"+f"(d[14]),"+f"(d[15]),
        "+f"(d[16]),"+f"(d[17]),"+f"(d[18]),"+f"(d[19]),"+f"(d[20]),"+f"(d[21]),"+f"(d[22]),"+f"(d[23]),
        "+f"(d[24]),"+f"(d[25]),"+f"(d[26]),"+f"(d[27]),"+f"(d[28]),"+f"(d[29]),"+f"(d[30]),"+f"(d[31]),
        "+f"(d[32]),"+f"(d[33]),"+f"(d[34]),"+f"(d[35]),"+f"(d[36]),"+f"(d[37]),"+f"(d[38]),"+f"(d[39]),
        "+f"(d[40]),"+f"(d[41]),"+f"(d[42]),"+f"(d[43]),"+f"(d[44]),"+f"(d[45]),"+f"(d[46]),"+f"(d[47]),
        "+f"(d[48]),"+f"(d[49]),"+f"(d[50]),"+f"(d[51]),"+f"(d[52]),"+f"(d[53]),"+f"(d[54]),"+f"(d[55]),
        "+f"(d[56]),"+f"(d[57]),"+f"(d[58]),"+f"(d[59]),"+f"(d[60]),"+f"(d[61]),"+f"(d[62]),"+f"(d[63]),
        "+f"(d[64]),"+f"(d[65]),"+f"(d[66]),"+f"(d[67]),"+f"(d[68]),"+f"(d[69]),"+f"(d[70]),"+f"(d[71]),
        "+f"(d[72]),"+f"(d[73]),"+f"(d[74]),"+f"(d[75]),"+f"(d[76]),"+f"(d[77]),"+f"(d[78]),"+f"(d[79]),
        "+f"(d[80]),"+f"(d[81]),"+f"(d[82]),"+f"(d[83]),"+f"(d[84]),"+f"(d[85]),"+f"(d[86]),"+f"(d[87]),
        "+f"(d[88]),"+f"(d[89]),"+f"(d[90]),"+f"(d[91]),"+f"(d[92]),"+f"(d[93]),"+f"(d[94]),"+f"(d[95])
      : "l"(da), "l"(db));
}
template <int SD>
__device__ __forceinline__ void wgmma_rs_n128(float (&d)[64], uint32_t a0, uint32_t a1, uint32_t a2, uint32_t a3, uint64_t db) {
  asm volatile("wgmma.mma_async.sync.aligned.m64n128k16.f32.bf16.bf16 {"
      "%0,%1,%2,%3,%4,%5,%6,%7,%8,%9,%10,%11,%12,%13,%14,%15,"
      "%16,%17,%18,%19,%20,%21,%22,%23,%24,%25,%26,%27,%28,%29,%30,%31,"
      "%32,%33,%34,%35,%36,%37,%38,%39,%40,%41,%42,%43,%44,%45,%46,%47,"
      "%48,%49,%50,%51,%52,%53,%54,%55,%56,%57,%58,%59,%60,%61,%62,%63"
      "}, {%64,%65,%66,%67}, %68, %69, 1, 1, 1;\n"
      : "+f"(d[0]),"+f"(d[1]),"+f"(d[2]),"+f"(d[3]),"+f"(d[4]),"+f"(d[5]),"+f"(d[6]),"+f"(d[7]),
        "+f"(d[8]),"+f"(d[9]),"+f"(d[10]),"+f"(d[11]),"+f"(d[12]),"+f"(d[13]),"+f"(d[14]),"+f"(d[15]),
        "+f"(d[16]),"+f"(d[17]),"+f"(d[18]),"+f"(d[19]),"+f"(d[20]),"+f"(d[21]),"+f"(d[22]),"+f"(d[23]),
        "+f"(d[24]),"+f"(d[25]),"+f"(d[26]),"+f"(d[27]),"+f"(d[28]),"+f"(d[29]),"+f"(d[30]),"+f"(d[31]),
        "+f"(d[32]),"+f"(d[33]),"+f"(d[34]),"+f"(d[35]),"+f"(d[36]),"+f"(d[37]),"+f"(d[38]),"+f"(d[39]),
        "+f"(d[40]),"+f"(d[41]),"+f"(d[42]),"+f"(d[43]),"+f"(d[44]),"+f"(d[45]),"+f"(d[46]),"+f"(d[47]),
        "+f"(d[48]),"+f"(d[49]),"+f"(d[50]),"+f"(d[51]),"+f"(d[52]),"+f"(d[53]),"+f"(d[54]),"+f"(d[55]),
        "+f"(d[56]),"+f"(d[57]),"+f"(d[58]),"+f"(d[59]),"+f"(d[60]),"+f"(d[61]),"+f"(d[62]),"+f"(d[63])
      : "r"(a0), "r"(a1), "r"(a2), "r"(a3), "l"(db), "n"(SD));
}
__device__ __forceinline__ void wgmma_rs_n256(float (&d)[128], uint32_t a0, uint32_t a1, uint32_t a2, uint32_t a3, uint64_t db, int sd = 1) {
  asm volatile("{.reg .pred p; setp.ne.b32 p, %133, 0;\n"
      "wgmma.mma_async.sync.aligned.m64n256k16.f32.bf16.bf16 {"
      "%0,%1,%2,%3,%4,%5,%6,%7,%8,%9,%10,%11,%12,%13,%14,%15,"
      "%16,%17,%18,%19,%20,%21,%22,%23,%24,%25,%26,%27,%28,%29,%30,%31,"
      "%32,%33,%34,%35,%36,%37,%38,%39,%40,%41,%42,%43,%44,%45,%46,%47,"
      "%48,%49,%50,%51,%52,%53,%54,%55,%56,%57,%58,%59,%60,%61,%62,%63,"
      "%64,%65,%66,%67,%68,%69,%70,%71,%72,%73,%74,%75,%76,%77,%78,%79,"
      "%80,%81,%82,%83,%84,%85,%86,%87,%88,%89,%90,%91,%92,%93,%94,%95,"
      "%96,%97,%98,%99,%100,%101,%102,%103,%104,%105,%106,%107,%108,%109,%110,%111,"
      "%112,%113,%114,%115,%116,%117,%118,%119,%120,%121,%122,%123,%124,%125,%126,%127"
      "}, {%128,%129,%130,%131}, %132, p, 1, 1, 1;}\n"
      : "+f"(d[0]),"+f"(d[1]),"+f"(d[2]),"+f"(d[3]),"+f"(d[4]),"+f"(d[5]),"+f"(d[6]),"+f"(d[7]),
        "+f"(d[8]),"+f"(d[9]),"+f"(d[10]),"+f"(d[11]),"+f"(d[12]),"+f"(d[13]),"+f"(d[14]),"+f"(d[15]),
        "+f"(d[16]),"+f"(d[17]),"+f"(d[18]),"+f"(d[19]),"+f"(d[20]),"+f"(d[21]),"+f"(d[22]),"+f"(d[23]),
        "+f"(d[24]),"+f"(d[25]),"+f"(d[26]),"+f"(d[27]),"+f"(d[28]),"+f"(d[29]),"+f"(d[30]),"+f"(d[31]),
        "+f"(d[32]),"+f"(d[33]),"+f"(d[34]),"+f"(d[35]),"+f"(d[36]),"+f"(d[37]),"+f"(d[38]),"+f"(d[39]),
        "+f"(d[40]),"+f"(d[41]),"+f"(d[42]),"+f"(d[43]),"+f"(d[44]),"+f"(d[45]),"+f"(d[46]),"+f"(d[47]),
        "+f"(d[48]),"+f"(d[49]),"+f"(d[50]),"+f"(d[51]),"+f"(d[52]),"+f"(d[53]),"+f"(d[54]),"+f"(d[55]),
        "+f"(d[56]),"+f"(d[57]),"+f"(d[58]),"+f"(d[59]),"+f"(d[60]),"+f"(d[61]),"+f"(d[62]),"+f"(d[63]),
        "+f"(d[64]),"+f"(d[65]),"+f"(d[66]),"+f"(d[67]),"+f"(d[68]),"+f"(d[69]),"+f"(d[70]),"+f"(d[71]),
        "+f"(d[72]),"+f"(d[73]),"+f"(d[74]),"+f"(d[75]),"+f"(d[76]),"+f"(d[77]),"+f"(d[78]),"+f"(d[79]),
        "+f"(d[80]),"+f"(d[81]),"+f"(d[82]),"+f"(d[83]),"+f"(d[84]),"+f"(d[85]),"+f"(d[86]),"+f"(d[87]),
        "+f"(d[88]),"+f"(d[89]),"+f"(d[90]),"+f"(d[91]),"+f"(d[92]),"+f"(d[93]),"+f"(d[94]),"+f"(d[95]),
        "+f"(d[96]),"+f"(d[97]),"+f"(d[98]),"+f"(d[99]),"+f"(d[100]),"+f"(d[101]),"+f"(d[102]),"+f"(d[103]),
        "+f"(d[104]),"+f"(d[105]),"+f"(d[106]),"+f"(d[107]),"+f"(d[108]),"+f"(d[109]),"+f"(d[110]),"+f"(d[111]),
        "+f"(d[112]),"+f"(d[113]),"+f"(d[114]),"+f"(d[115]),"+f"(d[116]),"+f"(d[117]),"+f"(d[118]),"+f"(d[119]),
        "+f"(d[120]),"+f"(d[121]),"+f"(d[122]),"+f"(d[123]),"+f"(d[124]),"+f"(d[125]),"+f"(d[126]),"+f"(d[127])
      : "r"(a0), "r"(a1), "r"(a2), "r"(a3), "l"(db), "r"(sd));
}
__device__ __forceinline__ void wgmma_rs_n192(float (&d)[96], uint32_t a0, uint32_t a1, uint32_t a2, uint32_t a3, uint64_t db) {
  asm volatile("wgmma.mma_async.sync.aligned.m64n192k16.f32.bf16.bf16 {"
      "%0,%1,%2,%3,%4,%5,%6,%7,%8,%9,%10,%11,%12,%13,%14,%15,"
      "%16,%17,%18,%19,%20,%21,%22,%23,%24,%25,%26,%27,%28,%29,%30,%31,"
      "%32,%33,%34,%35,%36,%37,%38,%39,%40,%41,%42,%43,%44,%45,%46,%47,"
      "%48,%49,%50,%51,%52,%53,%54,%55,%56,%57,%58,%59,%60,%61,%62,%63,"
      "%64,%65,%66,%67,%68,%69,%70,%71,%72,%73,%74,%75,%76,%77,%78,%79,"
      "%80,%81,%82,%83,%84,%85,%86,%87,%88,%89,%90,%91,%92,%93,%94,%95"
      "}, {%96,%97,%98,%99}, %100, 1, 1, 1, 1;\n"
      : "+f"(d[0]),"+f"(d[1]),"+f"(d[2]),"+f"(d[3]),"+f"(d[4]),"+f"(d[5]),"+f"(d[6]),"+f"(d[7]),
        "+f"(d[8]),"+f"(d[9]),"+f"(d[10]),"+f"(d[11]),"+f"(d[12]),"+f"(d[13]),"+f"(d[14]),"+f"(d[15]),
        "+f"(d[16]),"+f"(d[17]),"+f"(d[18]),"+f"(d[19]),"+f"(d[20]),"+f"(d[21]),"+f"(d[22]),"+f"(d[23]),
        "+f"(d[24]),"+f"(d[25]),"+f"(d[26]),"+f"(d[27]),"+f"(d[28]),"+f"(d[29]),"+f"(d[30]),"+f"(d[31]),
        "+f"(d[32]),"+f"(d[33]),"+f"(d[34]),"+f"(d[35]),"+f"(d[36]),"+f"(d[37]),"+f"(d[38]),"+f"(d[39]),
        "+f"(d[40]),"+f"(d[41]),"+f"(d[42]),"+f"(d[43]),"+f"(d[44]),"+f"(d[45]),"+f"(d[46]),"+f"(d[47]),
        "+f"(d[48]),"+f"(d[49]),"+f"(d[50]),"+f"(d[51]),"+f"(d[52]),"+f"(d[53]),"+f"(d[54]),"+f"(d[55]),
        "+f"(d[56]),"+f"(d[57]),"+f"(d[58]),"+f"(d[59]),"+f"(d[60]),"+f"(d[61]),"+f"(d[62]),"+f"(d[63]),
        "+f"(d[64]),"+f"(d[65]),"+f"(d[66]),"+f"(d[67]),"+f"(d[68]),"+f"(d[69]),"+f"(d[70]),"+f"(d[71]),
        "+f"(d[72]),"+f"(d[73]),"+f"(d[74]),"+f"(d[75]),"+f"(d[76]),"+f"(d[77]),"+f"(d[78]),"+f"(d[79]),
        "+f"(d[80]),"+f"(d[81]),"+f"(d[82]),"+f"(d[83]),"+f"(d[84]),"+f"(d[85]),"+f"(d[86]),"+f"(d[87]),
        "+f"(d[88]),"+f"(d[89]),"+f"(d[90]),"+f"(d[91]),"+f"(d[92]),"+f"(d[93]),"+f"(d[94]),"+f"(d[95])
      : "r"(a0), "r"(a1), "r"(a2), "r"(a3), "l"(db));
}


constexpr int C_LN = 0, C_PX = 16, C_PY = 32;
constexpr int NB_CONS = 1, NB_LN = 2, NB_LAG = 4, NB_INIT = 6, NB_RDY = 7, NB_WG = 8;
constexpr int LAGX = 3;
constexpr int LAGY = 3;
constexpr int LAG2 = 5;
constexpr int NLL = 2;
constexpr int POLL_DELAY3 = 600;
constexpr int POLL_DELAY = 1200;
constexpr int FILT_DELAY = 800;
constexpr int WARM = 4;
constexpr int ALEAD = 6;
constexpr int POLL_DELAY2 = 1000;
constexpr int BGATE = 5;
constexpr int REDPOS = 4;
constexpr int XTRIG = 20;
constexpr int HTRIG = 0;
constexpr int RING_SIG = 1;
constexpr int PF2_SIG = 1;
constexpr int SM_E = 0, SM_X = 16384, SM_E2 = 32768, SM_W = 49152, SM_FC = 69632, SM_T = 73728 - T1_BYTES;
constexpr unsigned long long KORDER = 0xBA9432DC876510ull;
constexpr unsigned long long BSLOT = 0x65432106543210ull, PSLOT = 0xDCBA987DCBA987ull;
constexpr uint32_t HI128 = desc_hi(1024, 1), HI64 = desc_hi(512, 2);

struct Bars {
  uint64_t full1[32], empty1[32], full2[16], fullA[8], empty2[8], fullP[16], emptyP[8], hbar, tbar, hint[3], sig[2], sbar, freeA[4];
  uint32_t epoch, pad;
};

template <int NK, bool STORE, int J0 = 0, int J1 = NK>
__device__ __forceinline__ void make_p(const float (&acc)[NK * 16], float r0, float r1, uint4 (&p)[NK], uint4* pbase, int ks0, uint32_t tag) {
#pragma unroll
  for (int j = J0; j < J1; j++) {
    uint32_t w[4];
#pragma unroll
    for (int i = 0; i < 4; i++) {
      const int a = 8 * j + 2 * i, b = a + NK * 8;
      w[i] = pack2(swiglu(acc[a], acc[b], (i & 1) ? r1 : r0), swiglu(acc[a + 1], acc[b + 1], (i & 1) ? r1 : r0));
    }
    asm volatile("" : "+r"(w[0]), "+r"(w[1]), "+r"(w[2]), "+r"(w[3]));
    p[j] = make_uint4(w[0], w[1], w[2], w[3]);
    if (STORE) st_tag(pbase + ((ks0 + j) >> 2) * 1024 + ((ks0 + j) & 3) * 32, p[j], tag);
  }
}
__device__ __forceinline__ void spin_until(uint32_t t) {
  while ((int)(clock32() - t) < 0) {}
}

__global__ void __cluster_dims__(2, 1, 1) __launch_bounds__(NTHREADS, 1)
fused_kernel(const __nv_bfloat16* __restrict__ x, const Tables* __restrict__ tab, Scratch* __restrict__ scr,
             __nv_bfloat16* __restrict__ out, const char* __restrict__ wg_raw, const char* __restrict__ wu_raw,
             const char* __restrict__ wd_raw,
             const __grid_constant__ CUtensorMap tmWR, const __grid_constant__ CUtensorMap tmWI,
             const __grid_constant__ CUtensorMap tmGX, const __grid_constant__ CUtensorMap tmUX,
             const __grid_constant__ CUtensorMap tmGY, const __grid_constant__ CUtensorMap tmUY,
             const __grid_constant__ CUtensorMap tmD) {
  extern __shared__ __align__(1024) char smem_raw[];
  const uint32_t sbase = s2u(smem_raw);
  const uint32_t sbar = sbase + 14 * SLOT, sstat = sbar + 1280;
  const int tid = threadIdx.x, lane = tid & 31;
  const int c = blockIdx.x, rk = c & 1, f = (c >> 1) & 7, rb = 2 * (c >> 4) + rk;
  const int rb2 = 2 * (c >> 4) + (f >> 2), kh = (f >> 1) & 1, nq = 2 * (f & 1) + rk;
#define BAR(field, i) (sbar + (uint32_t)offsetof(Bars, field) + 8u * (i))
#define TOFF(field) (sbase + SM_T + (uint32_t)offsetof(Tables, field) + lane * 16)

  if (tid >= 256) {
    asm volatile("setmaxnreg.dec.sync.aligned.u32 40;");
    const int warp = __shfl_sync(0xffffffffu, tid >> 5, 0);
    if (lane == 0) {
      if (warp == 8) {
        if (sbase & 1023) die();
#pragma unroll
        for (int i = 0; i < 20; i++) mbar_init(BAR(emptyP, i), i < 7 ? 16 : i < 8 ? 8 : i < 13 ? 1 : i == 15 ? 32 : 8);
        mbar_expect(BAR(tbar, 0), T2_BYTES + 2 * 10240);
        mbar_expect(BAR(hbar, 0), 16384);
      } else if (warp == 9) {
#pragma unroll
        for (int i = 0; i < 32; i++) mbar_init(BAR(full1, i), 1);
#pragma unroll
        for (int i = 0; i < 32; i++) mbar_expect(BAR(full1, i), i < 16 ? 16384 : 12288);
      } else if (warp == 10) {
#pragma unroll
        for (int i = 0; i < 32; i++) mbar_init(BAR(empty1, i), 16);
#pragma unroll
        for (int i = 0; i < 14; i++) mbar_init(BAR(fullP, i), 1);
#pragma unroll
        for (int i = 0; i < 14; i++) mbar_expect(BAR(fullP, i), 16384);
      } else {
#pragma unroll
        for (int i = 0; i < 32; i++) mbar_init(BAR(full2, i), i < 24 ? 1 : 8);
#pragma unroll
        for (int i = 0; i < 24; i++) mbar_expect(BAR(full2, i), 16384);
      }
      asm volatile("fence.mbarrier_init.release.cluster;" ::: "memory");
    }
    if (tid == 256) {
      const int w0 = ((c >> 3) * 257 + 32 * (c & 7) + 1) & ~7;
      if (FILT_DELAY) {
        asm volatile("prefetch.tensormap [%0];" ::"l"(&tmWR) : "memory");
        asm volatile("prefetch.tensormap [%0];" ::"l"(&tmWI) : "memory");
        spin_until(clock32() + FILT_DELAY);
      }
      tma3(sbase + SM_W, &tmWR, BAR(tbar, 0), w0, 0, 0);
      tma3(sbase + SM_W + 10240, &tmWI, BAR(tbar, 0), w0, 0, 0);
      bulk_load(sbase + SM_T + T1_BYTES, reinterpret_cast<const char*>(tab) + T1_BYTES, T2_BYTES, BAR(tbar, 0));
    }
    if (tid == 288) {
      asm volatile("prefetch.tensormap [%0];" ::"l"(rk ? &tmUX : &tmGX) : "memory");
      asm volatile("prefetch.tensormap [%0];" ::"l"(rk ? &tmUY : &tmGY) : "memory");
      asm volatile("prefetch.tensormap [%0];" ::"l"(&tmD) : "memory");
    }
    if (tid == 320) {
      const unsigned e = ld_relaxed(&scr->cnt[(C_LN + rb) * 32]) >> 3;
      asm volatile("st.shared.u32 [%0], %1;" ::"r"(BAR(epoch, 0)), "r"(e) : "memory");
    }
    __syncwarp();
    asm volatile("barrier.cluster.arrive.relaxed.aligned;" ::: "memory");
    bar_arrive(NB_RDY, 384);
    asm volatile("barrier.cluster.wait.aligned;" ::: "memory");
    bar_sync(NB_INIT, 384);
    unsigned epoch;
    asm volatile("ld.shared.u32 %0, [%1];" : "=r"(epoch) : "r"(BAR(epoch, 0)) : "memory");
    if (warp == 8) {
      if (lane == 0) {
        const int ax = (7 * f + 3 * (f & 1)) >> 1;
        const int ay = 7 * f + ((f & 1) ? 0 : 4);
        const CUtensorMap* tx = rk ? &tmUX : &tmGX;
        const CUtensorMap* ty = rk ? &tmUY : &tmGY;
        if (RING_SIG >= 0) mbar_wait(BAR(sig, RING_SIG));
        uint32_t s = 2;
#pragma unroll 1
        for (int n = 0; n < 16; n++) {
          if (n >= 6) mbar_wait(BAR(empty1, n - 6));
          tma3_mc(sbase + (8 + s) * SLOT + rk * 8192, tx, BAR(full1, n), n * 32, ax);
          if (++s == 6) s = 0;
        }
#pragma unroll 1
        for (int k = 0; k < 16; k++) {
          mbar_wait(BAR(empty1, k < 8 ? 10 + ((12 * k + 11) >> 4) : 8 + k));
          tma3_mc(sbase + 8 * SLOT + (k & 7) * 12288 + rk * 6144, ty, BAR(full1, 16 + k), ((k + 8) & 15) * 32, ay);
        }
      }
    } else if (warp == 9) {
      if (lane == 0) {
#pragma unroll 1
        for (int i = 0; i < 14; i++) {
          const int kblk = 14 * kh + (int)((KORDER >> (4 * i)) & 15);
          const int j = i < 7 ? i : i - 7;
          if (i < 4) mbar_wait(BAR(freeA, i));
          mbar_wait(i < 4 ? BAR(empty1, BGATE + 2 * i) : i < 7 ? BAR(empty1, 9 + 2 * i) : BAR(empty2, j));
          tma3(sbase + j * SLOT, &tmD, BAR(full2, i), 0, 64 * kblk, 2 * nq);
          if (i == 3) {
            wait_counter(&scr->cnt[(C_LN + rb2) * 32], (epoch + 1) * 8);
            asm volatile("fence.proxy.async.global;" ::: "memory");
          }
        }
        mbar_wait(BAR(emptyP, 7));
        bulk_load(sbase + 7 * SLOT, &scr->LN[(rb2 * 8 + 2 * nq) * 1024 + kh * 512], 8192, BAR(hbar, 0));
        bulk_load(sbase + 7 * SLOT + 8192, &scr->LN[(rb2 * 8 + 2 * nq + 1) * 1024 + kh * 512], 8192, BAR(hbar, 0));
      }
    } else if (warp == 10) {
      bar_sync(NB_LN, 288);
      if (lane == 0) {
        red_release(&scr->cnt[(C_LN + rb) * 32]);
        wait_counter(&scr->cnt[(C_LN + rb) * 32], (epoch + 1) * 8);
        asm volatile("fence.proxy.async.global;" ::: "memory");
#pragma unroll 1
        for (int kb = NLL; kb < 8; kb++) {
          if (2 * kb >= ALEAD) mbar_wait(BAR(empty1, 2 * kb - ALEAD));
          bulk_load(sbase + kb * SLOT, &scr->LN[(rb * 8 + kb) * 1024], 16384, BAR(fullA, kb));
        }
#pragma unroll 1
        for (int s = 0; s < 14; s++) {
          const int kblk = 14 * kh + (int)((KORDER >> (4 * s)) & 15);
          if (s == 0 || s == 8 || s == 11) {
            mbar_wait(BAR(hint, s == 0 ? 0 : s == 8 ? 1 : 2), 0);
          }
          const int j = s < 7 ? s : s - 7;
          mbar_wait(s < 7 ? BAR(empty1, 24 + s - (s == 0) + (s >= 4)) : BAR(emptyP, j));
          bulk_load_mc(sbase + (7 + j) * SLOT + rk * 8192, &scr->P[(rb2 * 28 + kblk) * 1024 + rk * 512], 8192, BAR(fullP, s));
        }
      }
    } else {
      if (lane == 0) {
        mbar_wait(BAR(tbar, 0));
        l2_prefetch(wg_raw + (size_t)c * 5376, 5376);
        l2_prefetch(wu_raw + (size_t)c * 5376, 5376);
        mbar_wait(BAR(sig, PF2_SIG), 0);
        l2_prefetch(wg_raw + 688128 + (size_t)c * 8960, 8960);
        l2_prefetch(wu_raw + 688128 + (size_t)c * 8960, 8960);
      }
      mbar_wait(BAR(fullA, 2), 0);
      if (lane == 0) l2_prefetch(wd_raw + (size_t)c * 14336, 14336);
      {
        const uint32_t tag = (epoch + 1) & 1;
        uint4 v0, v1, v2;
        int it = 0;
        while (true) {
          v0 = ld_b128(&scr->ST[rb * 64 + lane]);
          v1 = ld_b128(&scr->ST[rb * 64 + 32 + lane]);
          v2 = ld_b128(&scr->ST[rb2 * 64 + 32 * kh + lane]);
          if (!__any_sync(0xffffffffu, ((v0.x ^ tag) | (v1.x ^ tag) | (v2.x ^ tag)) & 1u)) break;
          if (++it > SPIN_LIMIT) { die(); break; }
        }
        sts4(sstat + lane * 16, v0.x & ~1u, v0.y, v0.z, v0.w);
        sts4(sstat + 512 + lane * 16, v1.x & ~1u, v1.y, v1.z, v1.w);
        sts4(sstat + 1024 + lane * 16, v2.x & ~1u, v2.y, v2.z, v2.w);
        mbar_arrive(BAR(sbar, 0));
      }
      if (lane == 0) {
        mbar_wait(BAR(empty1, XTRIG));
        int it = 0;
        while ((int)(ld_relaxed(&scr->cnt[(C_PX + rb2) * 32 + kh]) - (epoch + 1) * 32) < 0) {
          if (++it > SPIN_LIMIT) { die(); break; }
        }
        mbar_arrive(BAR(hint, 0));
        mbar_wait(BAR(emptyP, HTRIG));
        uint32_t done = 0;
        while (done != 3) {
          uint2 v;
          asm volatile("ld.relaxed.gpu.global.v2.u32 {%0,%1}, [%2];" : "=r"(v.x), "=r"(v.y) : "l"(&scr->cnt[(C_PY + rb2) * 32 + 2 * kh]) : "memory");
          if (!(done & 1) && (int)(v.x - (epoch + 1) * 16) >= 0) { done |= 1; mbar_arrive(BAR(hint, 1)); }
          if (!(done & 2) && (int)(v.y - (epoch + 1) * 16) >= 0) { done |= 2; mbar_arrive(BAR(hint, 2)); }
          if (++it > SPIN_LIMIT) { die(); break; }
        }
      }
    }
  } else {
    const int warp = __shfl_sync(0xffffffffu, tid >> 5, 0);
    const int g = lane >> 2, t = lane & 3;
    uint4 fa[4], fb[4], tw[6];
#pragma unroll
    for (int i = 0; i < 4; i++) fa[i] = ldg_ca4(&tab->fa[i][lane][0]);
#pragma unroll
    for (int i = 0; i < 6; i++) tw[i] = ldg_ca4(&tab->tw1[i][lane][0]);
#pragma unroll
    for (int i = 0; i < 4; i++) fb[i] = ldg_ca4(&tab->fb[i][lane][0]);
#pragma unroll
    for (int i = 0; i < 4; i++) {
      const int r = i >> 1, ch = (i & 1) * 32 + lane;
      cp_async16(sbase + SM_X + (2 * warp + r) * 1024 + ((ch ^ ((ch >> 3) & 1)) * 16),
                 x + (size_t)(c + 128 * (2 * warp + r)) * 512 + ch * 8);
    }
    asm volatile("cp.async.commit_group;" ::: "memory");
    asm volatile("barrier.cluster.arrive.relaxed.aligned;" ::: "memory");
    uint32_t rbar;
    asm volatile("mapa.shared::cluster.u32 %0, %1, %2;" : "=r"(rbar) : "r"(sbar), "r"(rk ^ 1));
#define RBAR(field, i) (rbar + (uint32_t)offsetof(Bars, field) + 8u * (i))
    {
      const int ln = (tid >> 1) & 31, lg = ln >> 2, lt = ln & 3, i = 4 * (tid >> 6) + 2 * (tid & 1);
      const int kidx = lt + 8 * (i >> 3), nidx = 4 * ((i >> 1) & 3) + (lg >> 1);
      const uint32_t a0 = cfrag<2048>((c + 128 * kidx) * nidx, lg & 1), a1 = cfrag<2048>((c + 128 * (kidx + 4)) * nidx, lg & 1);
      const uint32_t b0 = cfrag<2048>(-(c + 128 * nidx) * kidx, lg & 1), b1 = cfrag<2048>(-(c + 128 * nidx) * (kidx + 4), lg & 1);
      asm volatile("st.shared.v2.u32 [%0], {%1,%2};" ::"r"(sbase + SM_FC + tid * 8), "r"(a0), "r"(a1) : "memory");
      asm volatile("st.shared.v2.u32 [%0], {%1,%2};" ::"r"(sbase + SM_FC + 2048 + tid * 8), "r"(b0), "r"(b1) : "memory");
    }
    bar_sync(NB_CONS, 256);
    uint4 fc[4];
#pragma unroll
    for (int i = 0; i < 4; i++) fc[i] = lds4(sbase + SM_FC + i * 512 + lane * 16);
    asm volatile("cp.async.wait_group 0;" ::: "memory");
    __syncwarp();
    bar_arrive(NB_INIT, 384);
    uint32_t tag, ones;
    uint4 q[4], o[4];
    {
      uint32_t v[2][8];
#pragma unroll
      for (int r = 0; r < 2; r++)
#pragma unroll
        for (int ks = 0; ks < 2; ks++) {
          const int ch = 32 * ks + 2 * (lane & 15) + (lane >> 4);
          asm volatile("ldmatrix.sync.aligned.m8n8.x4.trans.shared.b16 {%0,%1,%2,%3}, [%4];"
                       : "=r"(v[r][4 * ks]), "=r"(v[r][4 * ks + 1]), "=r"(v[r][4 * ks + 2]), "=r"(v[r][4 * ks + 3])
                       : "r"(sbase + SM_X + (2 * warp + r) * 1024 + ((ch ^ ((ch >> 3) & 1)) * 16)) : "memory");
        }
      float sq[2];
#pragma unroll
      for (int r = 0; r < 2; r++) {
        float s0 = 0.f, s1 = 0.f;
#pragma unroll
        for (int i = 0; i < 8; i++) {
          const float lo = bf_lo(v[r][i]), hi = u2f(v[r][i] & 0xffff0000u);
          s0 = fmaf(lo, lo, s0);
          s1 = fmaf(hi, hi, s1);
        }
        sq[r] = s0 + s1;
      }
      {
        float w = ((lane & 1) ? sq[1] : sq[0]) + __shfl_xor_sync(0xffffffffu, (lane & 1) ? sq[0] : sq[1], 1);
        w += __shfl_xor_sync(0xffffffffu, w, 2);
        w = sum_groups(w);
        const float o2 = __shfl_xor_sync(0xffffffffu, w, 1);
        sq[0] = (lane & 1) ? o2 : w;
        sq[1] = (lane & 1) ? w : o2;
      }
#pragma unroll
      for (int r = 0; r < 2; r++) {
        float dd[2][4], ee[2][4];
#pragma unroll
        for (int nt = 0; nt < 2; nt++) {
          mma_az(dd[nt], fa[0], v[r][2 * nt], v[r][2 * nt + 1]);
          mma_a(dd[nt], fa[1], v[r][4 + 2 * nt], v[r][5 + 2 * nt]);
          mma_az(ee[nt], fa[2], v[r][2 * nt], v[r][2 * nt + 1]);
          mma_a(ee[nt], fa[3], v[r][4 + 2 * nt], v[r][5 + 2 * nt]);
        }
        float mean = (dd[0][0] + dd[0][1]) + (dd[1][0] + dd[1][1]);
        mean += __shfl_xor_sync(0xffffffffu, mean, 1);
        mean += __shfl_xor_sync(0xffffffffu, mean, 2);
        mean = __shfl_sync(0xffffffffu, mean, 0) * (1.f / 512.f);
        const float rs = rsqrtf(fmaxf(fmaf(-mean, mean, sq[r] * (1.f / 512.f)), 0.f) + 1e-5f);
        float acc[4][4];
#pragma unroll
        for (int nt = 0; nt < 2; nt++) {
          const float (&d)[4] = dd[nt];
          const float (&e)[4] = ee[nt];
          const uint4 &ka = tw[2 * nt], &kb = tw[2 * nt + 1], &kc = tw[4 + nt];
          const uint32_t a0 = pack2(d[0] * u2f(ka.x) + d[2] * u2f(ka.y), d[1] * u2f(kb.x) + d[3] * u2f(kb.y));
          const uint32_t a2 = pack2(d[0] * u2f(ka.z) + d[2] * u2f(ka.w), d[1] * u2f(kb.z) + d[3] * u2f(kb.w));
          const uint32_t a1 = pack2(e[0] * u2f(kc.x) + e[2] * u2f(kc.y), e[1] * u2f(kc.z) + e[3] * u2f(kc.w));
          const uint32_t a3 = pack2(e[2] * u2f(kc.x) - e[0] * u2f(kc.y), e[3] * u2f(kc.z) - e[1] * u2f(kc.w));
          const uint32_t dc = pack2(fmaf(mean, -32.f, d[0]), fmaf(mean, -32.f, d[1]));
          const uint32_t h0 = g == 0 ? dc : a0, h2 = g == 0 ? 0u : a2;
          if (nt == 0) {
            mma16816_z(acc[0], a0, a1, a2, a3, fb[2 * nt].x, fb[2 * nt].y);
            mma16816_z(acc[1], a0, a1, a2, a3, fb[2 * nt].z, fb[2 * nt].w);
            mma16816_z(acc[2], h0, a1, h2, a3, fb[2 * nt + 1].x, fb[2 * nt + 1].y);
            mma16816_z(acc[3], h0, a1, h2, a3, fb[2 * nt + 1].z, fb[2 * nt + 1].w);
          } else {
            mma16816(acc[0], a0, a1, a2, a3, fb[2 * nt].x, fb[2 * nt].y);
            mma16816(acc[1], a0, a1, a2, a3, fb[2 * nt].z, fb[2 * nt].w);
            mma16816(acc[2], h0, a1, h2, a3, fb[2 * nt + 1].x, fb[2 * nt + 1].y);
            mma16816(acc[3], h0, a1, h2, a3, fb[2 * nt + 1].z, fb[2 * nt + 1].w);
          }
        }
#pragma unroll
        for (int h = 0; h < 2; h++) {
          const int j = 2 * warp + r, m = 2 * t + h;
          sts4(sbase + SM_E + ((j * 8 + m) * 8 + (g ^ (2 * t) ^ (2 * (j & 3)))) * 16,
               pack2(acc[h][0] * rs, acc[h][1] * rs), pack2(acc[h][2] * rs, acc[h][3] * rs),
               pack2(acc[2 + h][0] * rs, acc[2 + h][1] * rs), pack2(acc[2 + h][2] * rs, acc[2 + h][3] * rs));
        }
      }
      bar_sync(NB_RDY, 384);
      const uint32_t ea = sbase + SM_E + ((t * 8 + warp) * 8 + (g ^ (warp & 6) ^ (2 * t))) * 16;
      lds_frag(q[0], q[1], ea, ea + 4096);
      lds_frag(q[2], q[3], ea + 8192, ea + 12288);
      asm volatile("ld.shared.u32 %0, [%1];" : "=r"(tag) : "r"(BAR(epoch, 0)) : "memory");
      ones = ~(tag >> 31);
      tag = (tag + 1) & 1;
      cdft16(q, fc, o);
#pragma unroll
      for (int vv = 0; vv < 4; vv++) {
        o[vv].y &= ~1u;
        o[vv].z = (o[vv].z & ~1u) | (tag ^ 1);
        st_tag(&scr->Z1[(((4 * vv + t) * 8 + warp) * 128 + c) * 8 + g], o[vv], tag);
      }
    }
    asm volatile("setmaxnreg.inc.sync.aligned.u32 232;");
    {
      uint4* const zp = &scr->Z1[(c * 128 + 8 * t + warp) * 8 + g];
      const uint32_t tst = clock32();
      mbar_wait(BAR(tbar, 0), 0);
      uint4 f2[4], g2[4];
#pragma unroll
      for (int i = 0; i < 4; i++) {
        f2[i] = lds4(TOFF(f2) + warp * 2048 + i * 512);
        g2[i] = lds4(TOFF(g2) + warp * 2048 + i * 512);
      }
      const uint4 f8 = lds4(TOFF(f8)), g8 = lds4(TOFF(g8));
      asm volatile("barrier.cluster.wait.aligned;" ::: "memory");
      spin_until(tst + POLL_DELAY);
      ld_tag4_issue<256>(q, zp);
      float wfr[16], wfi[16];
      {
        const float nyq = ((c & 7) == 7 && g == 0) ? 0.5f : 1.f;
        uint32_t wa = sbase + SM_W + (16 * warp + t) * 80 + ((2 * (c >> 3) + 2) & 15) - 2;
        asm volatile("" : "+r"(wa));
        const uint32_t wb[3] = {wa + 2 * (g == 0 ? 16 : g), wa + 2 * g, wa - 2 * g};
#pragma unroll
        for (int i = 0; i < 16; i++) {
          const int ci = i >> 3, dd = (i >> 2) & 1, e = i & 3;
          const uint32_t a = wb[e < 2 ? e : 2] + (ci * 8 + 4 * dd) * 80 + (e == 0 ? 0 : e == 1 ? 16 : e == 2 ? 64 : 48);
          wfr[i] = bf_lo(lds_u16(a)) * (e == 2 ? nyq : 1.f);
          wfi[i] = bf_lo(lds_u16(a + 10240)) * (e == 2 ? nyq : 1.f);
        }
      }
      ld_tag4_finish<256>(q, zp, tag);
      if (lane == 0) mbar_arrive(BAR(sig, 0));
#pragma unroll
      for (int i = 0; i < 4; i++) q[i].z &= ~1u;
      reg_frag(q, ones);
      cdft16(q, f2, o);
      const uint32_t e2 = sbase + SM_E2;
#pragma unroll
      for (int vv = 0; vv < 4; vv++)
        sts4(e2 + ((warp * 16 + 4 * vv + t) * 8 + (g ^ (2 * t) ^ (2 * (warp & 3)))) * 16, o[vv].x, o[vv].y, o[vv].z, o[vv].w);
      bar_sync(NB_CONS, 256);
      uint32_t ad[2], res[2][2][4];
#pragma unroll
      for (int ci = 0; ci < 2; ci++) {
        const int cc = 2 * warp + ci;
        ad[ci] = e2 + ((t * 16 + cc) * 8 + (g ^ (2 * (cc & 3)) ^ (2 * t))) * 16;
        lds_frag(q[2 * ci], q[2 * ci + 1], ad[ci], ad[ci] + 8192);
      }
#pragma unroll
      for (int ci = 0; ci < 2; ci++)
#pragma unroll
        for (int p = 0; p < 2; p++) {
          uint32_t y[2][2];
#pragma unroll
          for (int vv = 0; vv < 2; vv++) {
            float d[4];
            mma_az(d, q[2 * ci + p], word(f8, 2 * vv), word(f8, 2 * vv + 1));
#pragma unroll
            for (int rr = 0; rr < 2; rr++) {
              const float fr = wfr[ci * 8 + vv * 4 + 2 * p + rr], fi = wfi[ci * 8 + vv * 4 + 2 * p + rr];
              y[vv][rr] = pack2(d[2 * rr] * fr - d[2 * rr + 1] * fi, d[2 * rr] * fi + d[2 * rr + 1] * fr);
            }
          }
#pragma unroll
          for (int vv = 0; vv < 2; vv++) {
            float d[4];
            mma16816_z(d, y[0][0], y[0][1], y[1][0], y[1][1], word(g8, 2 * vv), word(g8, 2 * vv + 1));
            res[ci][vv][2 * p] = pack2(d[0], d[1]);
            res[ci][vv][2 * p + 1] = pack2(d[2], d[3]);
          }
        }
#pragma unroll
      for (int i = 0; i < 4; i++)
        sts4(ad[i >> 1] + (i & 1) * 8192, res[i >> 1][i & 1][0], res[i >> 1][i & 1][1], res[i >> 1][i & 1][2], res[i >> 1][i & 1][3]);
      bar_sync(NB_CONS, 256);
      const uint32_t eb = e2 + ((warp * 16 + t) * 8 + (g ^ (2 * t) ^ (2 * (warp & 3)))) * 16;
      lds_frag(q[0], q[1], eb, eb + 512);
      lds_frag(q[2], q[3], eb + 1024, eb + 1536);
      cdft16(q, g2, o);
#pragma unroll
      for (int vv = 0; vv < 4; vv++) {
        o[vv].y &= ~1u;
        o[vv].z = (o[vv].z & ~1u) | tag;
        st_tag(zp + vv * 256, o[vv], tag);
      }
    }
    {
      const uint4* const zp = &scr->Z1[((t * 8 + warp) * 128 + c) * 8 + g];
      const uint32_t tst = clock32();
      uint4 gb[4], ga[4], gc[4], tw[4];
      uint2 xr[2][4];
      uint2* lnp[2];
#pragma unroll
      for (int r = 0; r < 2; r++) {
        const int row = 16 * f + 2 * warp + r;
        lnp[r] = reinterpret_cast<uint2*>(&scr->LN[(rb * 8 + (g >> 2)) * 1024 + row * 8 + ((2 * (g & 3) + (t >> 1)) ^ (row & 7))]) + (t & 1);
        asm volatile("" : "+l"(lnp[r]));
      }
#pragma unroll
      for (int i = 0; i < 4; i++) {
        gc[i] = lds4(sbase + SM_FC + 2048 + i * 512 + lane * 16);
        gb[i] = lds4(TOFF(gb) + i * 512);
        ga[i] = lds4(TOFF(ga) + i * 512);
        tw[i] = lds4(TOFF(tw3) + i * 512);
        const int ch = 2 * (g + 8 * i) + (t >> 1);
#pragma unroll
        for (int r = 0; r < 2; r++) xr[r][i] = lds2(sbase + SM_X + (2 * warp + r) * 1024 + ((ch ^ ((ch >> 3) & 1)) * 16) + (t & 1) * 8);
      }
      spin_until(tst + POLL_DELAY2);
      ld_tag4_issue<32768>(q, zp);
      ld_tag4_finish<32768, true>(q, zp, tag);
      if (lane == 0) mbar_arrive(BAR(sig, 1));
      reg_frag(q, ones);
      cdft16(q, gc, o);
#pragma unroll
      for (int vv = 0; vv < 4; vv++)
        sts4(sbase + SM_E + (((4 * vv + t) * 8 + warp) * 8 + (g ^ (warp & 6) ^ (2 * t))) * 16, o[vv].x, o[vv].y, o[vv].z, o[vv].w);
      bar_sync(NB_CONS, 256);
      uint32_t hv[2][8];
      const float mk = t == 0 ? 0.f : 1.f;
#pragma unroll
      for (int r = 0; r < 2; r++) {
        const int j = 2 * warp + r;
        uint4 u[2];
#pragma unroll
        for (int h = 0; h < 2; h++) u[h] = lds4(sbase + SM_E + ((j * 8 + 2 * t + h) * 8 + (g ^ (2 * t) ^ (2 * (j & 3)))) * 16);
        const uint32_t bp[4][2] = {{u[0].x, u[1].x & ones}, {u[0].y & ones, u[1].y}, {u[0].z, u[1].z & ones}, {u[0].w & ones, u[1].w}};
        float y[2][2][4];
#pragma unroll
        for (int i = 0; i < 2; i++) {
          float lo[4], hi[4], e[4];
          mma_az(lo, gb[2 * i], bp[0][0], bp[0][1]);
          mma_az(hi, gb[2 * i + 1], bp[2][0], bp[2][1]);
          mma_az(e, gb[2 * i], bp[1][0], bp[1][1]);
          mma_a(e, gb[2 * i + 1], bp[3][0], bp[3][1]);
          const uint4 &ka = tw[2 * i], &kb = tw[2 * i + 1];
          const float tr0 = fmaf(hi[0], mk, lo[0]), ti0 = fmaf(hi[2], mk, lo[2]);
          const float tr1 = lo[1] + hi[1], ti1 = lo[3] + hi[3];
          const float vr0 = tr0 * u2f(ka.x) - ti0 * u2f(ka.y), vi0 = tr0 * u2f(ka.y) + ti0 * u2f(ka.x);
          const float vr1 = tr1 * u2f(ka.z) - ti1 * u2f(ka.w), vi1 = tr1 * u2f(ka.w) + ti1 * u2f(ka.z);
          const uint32_t b0 = pack2(t == 0 ? hi[0] : vr0, vr1), b1 = pack2(t == 0 ? vr0 : vi0, vi1);
          const uint32_t b2 = pack2(e[0] * u2f(kb.x) - e[2] * u2f(kb.y), e[1] * u2f(kb.z) - e[3] * u2f(kb.w));
          const uint32_t b3 = pack2(e[0] * u2f(kb.y) + e[2] * u2f(kb.x), e[1] * u2f(kb.w) + e[3] * u2f(kb.z));
#pragma unroll
          for (int mt = 0; mt < 2; mt++) {
            mma_az(y[mt][i], ga[2 * mt], b0, b1);
            mma_a(y[mt][i], ga[2 * mt + 1], b2, b3);
          }
        }
#pragma unroll
        for (int i = 0; i < 4; i++) {
          hv[r][2 * i] = hadd2_bf16(xr[r][i].x, pack2(y[i >> 1][0][2 * (i & 1)], y[i >> 1][0][2 * (i & 1) + 1]));
          hv[r][2 * i + 1] = hadd2_bf16(xr[r][i].y, pack2(y[i >> 1][1][2 * (i & 1)], y[i >> 1][1][2 * (i & 1) + 1]));
        }
      }
      float mean[2];
      uint32_t mb[2];
#pragma unroll
      for (int r = 0; r < 2; r++) {
        mean[r] = sum_groups(quad_sum(hv[r])) * (1.f / 512.f);
        mb[r] = pack2(mean[r], mean[r]);
      }
#pragma unroll
      for (int i = 0; i < 4; i++)
#pragma unroll
        for (int r = 0; r < 2; r++) {
          hv[r][2 * i] = hsub2_bf16(hv[r][2 * i], mb[r]);
          hv[r][2 * i + 1] = hsub2_bf16(hv[r][2 * i + 1], mb[r]);
          st_tag8(lnp[r] + i * 4096, hv[r][2 * i], hv[r][2 * i + 1], i == 0 ? tag : (hv[r][2 * i] & 1u));
        }
      bar_arrive(NB_LN, 288);
      const uint32_t ones2 = ~(lds2(BAR(epoch, 0)).x >> 31);
      float rstd[2];
#pragma unroll
      for (int r = 0; r < 2; r++) {
        hv[r][0] &= ones2;
        rstd[r] = row_rstd(hv[r], mean[r] - bf_lo(mb[r]));
      }
      if (lane == 0)
        st_tag(&scr->ST[rb * 64 + 8 * f + warp], make_uint4(mb[0] << 16, __float_as_uint(rstd[0]), mb[1] << 16, __float_as_uint(rstd[1])), tag);
    }
    const int wgi = warp >> 2, wq = warp & 3;
    uint4* const pbase = &scr->P[rb * 28 * 1024 + warp * 128 + lane];
    const uint32_t a_lo0 = desc_lo(sbase + wgi * 8192, 16);
    const uint32_t ebar = lane == 0 ? BAR(empty1, 0) : RBAR(empty1, 0);
    float r0, r1;
    uint4 px[8], py[6];
    const int rh = wgi ^ kh ^ 1;
    const uint4* const psrc = &scr->P[(rb2 * 28 + 14 * kh) * 1024 + (4 * rh + wq) * 128 + lane];
    const uint32_t pa0 = sbase + (4 * rh + wq) * 2048;
    uint4 pf[3][4], ha[4][4];
    uint32_t rdy = 0, got0;
    {
      float acc[128];
#pragma unroll
      for (int i = 0; i < 128; i++) acc[i] = 0.f;
      const uint32_t b_lo0 = desc_lo(sbase + 8 * SLOT, 4096);
      const uint32_t t3 = clock32();
      if (WARM) {
        wg_fence();
#pragma unroll
        for (int i = 0; i < WARM; i++) wgmma_n256(acc, desc64(a_lo0 + 6 * 1024, HI128), desc64(b_lo0, HI128));
        wg_commit();
      }
      const uint4* const ap = &scr->LN[rb * 8 * 1024 + wgi * 512 + (tid & 127)];
      uint4 av[NLL][4];
      spin_until(t3 + POLL_DELAY3);
#pragma unroll
      for (int kb = 0; kb < NLL; kb++) ld_tag4_issue<128>(av[kb], ap + kb * 1024);
      bar_sync(NB_CONS, 256);
      const uint32_t lma = sbase + (16 * warp + (lane & 15)) * 128;
      auto load_a = [&](int kb) {
#pragma unroll
        for (int ks = 0; ks < 4; ks++)
          asm volatile("ldmatrix.sync.aligned.m8n8.x4.shared.b16 {%0,%1,%2,%3}, [%4];"
                       : "=r"(ha[kb][ks].x), "=r"(ha[kb][ks].y), "=r"(ha[kb][ks].z), "=r"(ha[kb][ks].w)
                       : "r"(lma + kb * SLOT + (((2 * ks + (lane >> 4)) ^ (lane & 7)) * 16)) : "memory");
      };
      auto stash_a = [&](int kb) {
        ld_tag4_finish<128, true>(av[kb], ap + kb * 1024, tag);
#pragma unroll
        for (int i = 0; i < 4; i++)
          sts4(sbase + kb * SLOT + wgi * 8192 + ((tid & 127) + 128 * i) * 16, av[kb][i].x, av[kb][i].y, av[kb][i].z, av[kb][i].w);
        bar_sync(NB_WG + wgi, 128);
      };
      stash_a(0);
      load_a(0);
#pragma unroll
      for (int n = 0; n < 8; n++) {
        const int kb = n >> 1, hh = n & 1;
        if (hh == 1 && kb < 3) {
          if (kb + 1 < NLL) stash_a(kb + 1); else mbar_wait(BAR(fullA, kb + 1));
        }
        mbar_wait(BAR(full1, n));
        const uint32_t bl = b_lo0 + ((n + 2) % 6) * 1024;
        wg_fence();
        if (hh == 1 && kb < 3) load_a(kb + 1);
        const uint4 &a0 = ha[kb][2 * hh], &a1 = ha[kb][2 * hh + 1];
        wgmma_rs_n256(acc, a0.x, a0.y, a0.z, a0.w, desc64(bl, HI128), n != 0 ? 1 : ~ones);
        wgmma_rs_n256(acc, a1.x, a1.y, a1.z, a1.w, desc64(bl + 128, HI128));
        wg_commit();
        if (hh == 1 && lane == 0) mbar_arrive(BAR(freeA, kb));
        wg_wait<1>();
        if (n != 0 && lane < 2) mbar_arrive_remote(ebar + 8 * (n - 1));
      }
      uint32_t slot = 4;
#pragma unroll 1
      for (int kb = 4; kb < 8; kb++) {
        mbar_wait(BAR(fullA, kb));
#pragma unroll
        for (int hh = 0; hh < 2; hh++) {
          if (LAGX && hh == ((16 - LAGX) & 1) && kb == ((16 - LAGX) >> 1) && wgi == 1) bar_sync(NB_LAG, 256);
          mbar_wait(BAR(full1, 2 * kb + hh));
          const uint32_t al = a_lo0 + kb * 1024 + hh * 4, bl = b_lo0 + slot * 1024;
          wg_fence();
          wgmma_n256(acc, desc64(al, HI128), desc64(bl, HI128));
          wgmma_n256(acc, desc64(al + 2, HI128), desc64(bl + 128, HI128));
          wg_commit();
          if (LAGX && hh == 1 && kb == 7 && wgi == 0) bar_arrive(NB_LAG, 256);
          wg_wait<1>();
          if (lane < 2) mbar_arrive_remote(ebar + 8 * (2 * kb + hh - 1));
          if (++slot == 6) slot = 0;
        }
      }
      mbar_wait(BAR(sbar, 0), 0);
      r0 = __uint_as_float(lds2(sstat + (16 * warp + g) * 8).y);
      r1 = __uint_as_float(lds2(sstat + (16 * warp + g + 8) * 8).y);
      wg_wait<0>();
      if (lane < 2) mbar_arrive_remote(ebar + 8 * 15);
      make_p<8, false>(acc, r0, r1, px, pbase, 0, tag);
    }
    {
      float acc[96];
#pragma unroll
      for (int i = 0; i < 96; i++) acc[i] = 0.f;
      const uint32_t b_lo0 = desc_lo(sbase + 8 * SLOT, 2048);
      uint4* const pdst = pbase + ((7 * f + 3 * (f & 1)) >> 1) * 1024;
      auto stage_y = [&](int k) {
        if (LAGY && k == 16 - LAGY && wgi == 1) bar_sync(NB_LAG, 256);
        mbar_wait(BAR(full1, 16 + k));
        const uint32_t al = a_lo0 + (4 + (k >> 1)) * 1024 + (k & 1) * 4, bl = b_lo0 + (k & 7) * 768;
        wg_fence();
        wgmma_n192(acc, desc64(al, HI128), desc64(bl, HI64));
        wgmma_n192(acc, desc64(al + 2, HI128), desc64(bl + 64, HI64));
        wg_commit();
      };
#pragma unroll
      for (int k = 0; k < 4; k++) {
        stage_y(k);
        st_tag(pdst + (k >> 1) * 1024 + (k & 1) * 64, px[2 * k], tag);
        st_tag(pdst + (k >> 1) * 1024 + (k & 1) * 64 + 32, px[2 * k + 1], tag);
        if (k == 3 && lane == 0) red_relaxed(&scr->cnt[(C_PX + rb) * 32 + (f >> 2)]);
        wg_wait<1>();
        if (k != 0 && lane < 2) mbar_arrive_remote(ebar + 8 * (15 + k));
      }
#pragma unroll 1
      for (int k = 4; k < 8; k++) {
        stage_y(k);
        wg_wait<1>();
        if (lane < 2) mbar_arrive_remote(ebar + 8 * (15 + k));
      }
      rdy = 0;
#pragma unroll
      for (int k = 8; k < 16; k++) {
        if (LAGY && k == 16 - LAGY && wgi == 1) bar_sync(NB_LAG, 256);
        if (!rdy) mbar_wait(BAR(full1, 16 + k));
        const uint32_t bl = b_lo0 + (k & 7) * 768;
        const uint4 &a0 = ha[(k - 8) >> 1][2 * (k & 1)], &a1 = ha[(k - 8) >> 1][2 * (k & 1) + 1];
        wg_fence();
        if (k < 15) rdy = mbar_test(BAR(full1, 17 + k));
        wgmma_rs_n192(acc, a0.x, a0.y, a0.z, a0.w, desc64(bl, HI64));
        wgmma_rs_n192(acc, a1.x, a1.y, a1.z, a1.w, desc64(bl + 64, HI64));
        wg_commit();
        if (LAGY && k == 15 && wgi == 0) bar_arrive(NB_LAG, 256);
        wg_wait<1>();
        if (lane < 2) mbar_arrive_remote(ebar + 8 * (15 + k));
      }
      got0 = __all_sync(0xffffffffu, mbar_test(BAR(fullP, 0)));
      if (got0) {
#pragma unroll
        for (int kk = 0; kk < 4; kk++) pf[0][kk] = lds4(pa0 + 7 * SLOT + kk * 512 + lane * 16);
      }
      wg_wait<0>();
      if (lane < 2) mbar_arrive_remote(ebar + 8 * 31);
      const int ks0 = 14 * f + ((f & 1) ? 0 : 8);
      auto reread = [&]() {
        asm volatile("ld.volatile.shared.f32 %0, [%2+4]; ld.volatile.shared.f32 %1, [%2+68];" : "=f"(r0), "=f"(r1) : "r"(sstat + (16 * warp + g) * 8) : "memory");
      };
      make_p<6, true, 0, 2>(acc, r0, r1, py, pbase, ks0, tag);
      if (REDPOS == 2 && lane == 0) red_relaxed(&scr->cnt[(C_PY + rb) * 32 + (f >> 1)]);
      reread();
      make_p<6, true, 2, 4>(acc, r0, r1, py, pbase, ks0, tag);
      if (REDPOS == 4 && lane == 0) red_relaxed(&scr->cnt[(C_PY + rb) * 32 + (f >> 1)]);
      reread();
      rdy = mbar_test(BAR(full2, 0)) & mbar_test(BAR(fullP, 1));
      make_p<6, true, 4, 6>(acc, r0, r1, py, pbase, ks0, tag);
      if (REDPOS == 6 && lane == 0) red_relaxed(&scr->cnt[(C_PY + rb) * 32 + (f >> 1)]);
    }
    {
      float acc[64];
      const uint32_t b2_lo0 = desc_lo(sbase, 8192);
      const uint32_t pbar = ebar + (uint32_t)(offsetof(Bars, emptyP) - offsetof(Bars, empty1));
      if (!got0) {
        mbar_wait(BAR(fullP, 0));
#pragma unroll
        for (int kk = 0; kk < 4; kk++) pf[0][kk] = lds4(pa0 + 7 * SLOT + kk * 512 + lane * 16);
      }
#pragma unroll
      for (int s = 0; s < 14; s++) {
        uint4 (&a)[4] = pf[s % 3];
        ld_tag4_finish<32>(a, psrc + (int)((KORDER >> (4 * s)) & 15) * 1024, tag);
        if (s < 8 && lane < (s < 7 ? 2 : 1)) mbar_arrive_remote(pbar + 8 * s);
        if (s >= 2) {
          wg_wait<1>();
          if (s <= 8 && lane == 0) mbar_arrive(BAR(empty2, s - 2));
        }
        if (!rdy) {
          if (s < 13) mbar_wait(BAR(fullP, s + 1));
          mbar_wait(BAR(full2, s));
        }
        if (s == 14 - LAG2 && wgi == 1) {
          const float m0 = __uint_as_float(lds2(sstat + 1024 + (16 * wq + g) * 8).x);
          const float m1 = __uint_as_float(lds2(sstat + 1024 + (16 * wq + g + 8) * 8).x);
          const uint32_t hb = sbase + 7 * SLOT + (16 * wq + (lane & 15)) * 128;
          wg_wait<0>();
          mbar_wait(BAR(hbar, 0));
#pragma unroll
          for (int i = 0; i < 8; i++) {
            uint32_t h[4];
            asm volatile("ldmatrix.sync.aligned.m8n8.x4.shared.b16 {%0,%1,%2,%3}, [%4];"
                         : "=r"(h[0]), "=r"(h[1]), "=r"(h[2]), "=r"(h[3])
                         : "r"(hb + (i >> 2) * 8192 + (((2 * (i & 3) + (lane >> 4)) ^ (lane & 7)) * 16)) : "memory");
            const uint32_t mk = ((t & 1) == 0 && nq == 0) ? ~1u : ~0u;
#pragma unroll
            for (int e = 0; e < 4; e++) {
              acc[8 * i + 2 * e] += bf_lo(h[e] & mk) + ((e & 1) ? m1 : m0);
              acc[8 * i + 2 * e + 1] += __uint_as_float(h[e] & 0xffff0000u) + ((e & 1) ? m1 : m0);
            }
          }
          bar_sync(NB_LAG, 256);
        }
        const uint32_t bl = b2_lo0 + (uint32_t)((BSLOT >> (4 * s)) & 15) * 1024;
        wg_fence();
        if (s < 13) {
#pragma unroll
          for (int kk = 0; kk < 4; kk++)
            pf[(s + 1) % 3][kk] = lds4(pa0 + (uint32_t)((PSLOT >> (4 * (s + 1))) & 15) * SLOT + kk * 512 + lane * 16);
          rdy = mbar_test(BAR(full2, s + 1));
          if (s < 12) rdy &= mbar_test(BAR(fullP, s + 2));
        }
        if (s == 0) wgmma_rs_n128<0>(acc, a[0].x, a[0].y, a[0].z, a[0].w, desc64(bl, HI128));
        else wgmma_rs_n128<1>(acc, a[0].x, a[0].y, a[0].z, a[0].w, desc64(bl, HI128));
#pragma unroll
        for (int kk = 1; kk < 4; kk++) wgmma_rs_n128<1>(acc, a[kk].x, a[kk].y, a[kk].z, a[kk].w, desc64(bl + kk * 128, HI128));
        wg_commit();
      }
      if (wgi == 0) {
        bar_arrive(NB_LAG, 256);
        uint4* const dst = &scr->Z1[(tid >> 3) * 1024 + (c ^ 4) * 8 + (tid & 7)];
        wg_wait<0>();
#pragma unroll
        for (int i = 0; i < 8; i++)
          st_tag(dst + i * 16384, make_uint4(pack2(acc[8 * i], acc[8 * i + 1]), pack2(acc[8 * i + 2], acc[8 * i + 3]) | 1u,
                                           pack2(acc[8 * i + 4], acc[8 * i + 5]), pack2(acc[8 * i + 6], acc[8 * i + 7])), tag);
      } else {
        uint4 pv[2][4];
        const uint4* const xsrc = &scr->Z1[((tid & 127) >> 3) * 1024 + c * 8 + (tid & 7)];
        ld_tag4_issue<16384>(pv[0], xsrc);
        ld_tag4_issue<16384>(pv[1], xsrc + 65536);
        wg_wait<0>();
        uint32_t w[32];
#pragma unroll
        for (int i = 0; i < 32; i++) w[i] = pack2(acc[2 * i], acc[2 * i + 1]);
        int it = 0;
#pragma unroll 1
        while (!__all_sync(0xffffffffu, pv[0][0].y & pv[0][1].y & pv[0][2].y & pv[0][3].y & pv[1][0].y & pv[1][1].y & pv[1][2].y & pv[1][3].y & 1u)) {
          ld_tag4_issue<16384>(pv[0], xsrc);
          ld_tag4_issue<16384>(pv[1], xsrc + 65536);
          if (++it > SPIN_LIMIT) { die(); break; }
        }
#pragma unroll
        for (int i = 0; i < 8; i++) {
          const uint4& p = pv[i >> 2][i & 3];
          asm volatile("stmatrix.sync.aligned.m8n8.x4.shared.b16 [%0], {%1,%2,%3,%4};"
                       ::"r"(pa0 + (9 + ((lane >> 3) & 1)) * SLOT + (lane & 7) * 256 + (((2 * i + (lane >> 4)) ^ (lane & 7)) * 16)),
                         "r"(hadd2_bf16(w[4 * i], p.x & ~1u)), "r"(hadd2_bf16(w[4 * i + 1], p.y & ~1u)), "r"(hadd2_bf16(w[4 * i + 2], p.z)),
                         "r"(hadd2_bf16(w[4 * i + 3], p.w)) : "memory");
        }
        __syncwarp();
        uint4* const dst = reinterpret_cast<uint4*>(out) + (16 * (c >> 4) + 2 * (4 * rh + wq) + (rb2 & 1) + 128 * (lane >> 4)) * 64 + nq * 16 + (lane & 15);
#pragma unroll
        for (int i = 0; i < 8; i++) {
          const int r = 2 * (i & 3) + (lane >> 4);
          dst[i * 256 * 64] = lds4(pa0 + (9 + (i >> 2)) * SLOT + r * 256 + (((lane & 15) ^ r) * 16));
        }
      }
    }
  }
#undef BAR
#undef TOFF
#undef RBAR
}

typedef CUresult (*EncodeFn)(CUtensorMap*, CUtensorMapDataType, cuuint32_t, void*, const cuuint64_t*, const cuuint64_t*,
                             const cuuint32_t*, const cuuint32_t*, CUtensorMapInterleave, CUtensorMapSwizzle,
                             CUtensorMapL2promotion, CUtensorMapFloatOOBfill);

}

extern "C" void kernel_launch(void* const* d_in, const int* in_sizes, int n_in, void* d_out, int out_size) {
  (void)in_sizes; (void)n_in; (void)out_size;
  static EncodeFn encode = nullptr;
  static void *tab = nullptr, *scr = nullptr;
  if (!encode) {
    void* fn = nullptr;
    cudaDriverEntryPointQueryResult qr;
    cudaGetDriverEntryPoint("cuTensorMapEncodeTiled", &fn, cudaEnableDefault, &qr);
    encode = (EncodeFn)fn;
    cudaGetSymbolAddress(&tab, g_tab);
    cudaGetSymbolAddress(&scr, g_scr);
    cudaFuncSetAttribute(fused_kernel, cudaFuncAttributeMaxDynamicSharedMemorySize, SMEM_BYTES);
  }
  CUtensorMap tmGX, tmUX, tmGY, tmUY, tmD, tmWR, tmWI;
  const cuuint32_t es[5] = {1, 1, 1, 1, 1};
  auto enc = [&](CUtensorMap* m, void* p, int rank, const cuuint64_t* gd, const cuuint64_t* gs, const cuuint32_t* bd,
                 CUtensorMapSwizzle sw, CUtensorMapL2promotion pr) {
    encode(m, CU_TENSOR_MAP_DATA_TYPE_BFLOAT16, rank, p, gd, gs, bd, es, CU_TENSOR_MAP_INTERLEAVE_NONE, sw, pr,
           CU_TENSOR_MAP_FLOAT_OOB_FILL_NONE);
  };
  {
    const cuuint64_t gd[3] = {64, 512, 28}, gs[2] = {3584, 128};
    const cuuint32_t bd[3] = {64, 32, 2};
    enc(&tmGX, d_in[4], 3, gd, gs, bd, CU_TENSOR_MAP_SWIZZLE_128B, CU_TENSOR_MAP_L2_PROMOTION_L2_256B);
    enc(&tmUX, d_in[5], 3, gd, gs, bd, CU_TENSOR_MAP_SWIZZLE_128B, CU_TENSOR_MAP_L2_PROMOTION_L2_256B);
  }
  {
    const cuuint64_t gd[3] = {32, 512, 56}, gs[2] = {3584, 64};
    const cuuint32_t bd[3] = {32, 32, 3};
    enc(&tmGY, d_in[4], 3, gd, gs, bd, CU_TENSOR_MAP_SWIZZLE_64B, CU_TENSOR_MAP_L2_PROMOTION_L2_128B);
    enc(&tmUY, d_in[5], 3, gd, gs, bd, CU_TENSOR_MAP_SWIZZLE_64B, CU_TENSOR_MAP_L2_PROMOTION_L2_128B);
  }
  {
    const cuuint64_t gd[3] = {64, 1792, 8}, gs[2] = {1024, 128};
    const cuuint32_t bd[3] = {64, 64, 2};
    enc(&tmD, d_in[6], 3, gd, gs, bd, CU_TENSOR_MAP_SWIZZLE_128B, CU_TENSOR_MAP_L2_PROMOTION_L2_256B);
  }
  {
    const cuuint64_t gd[3] = {4112, 8, 16}, gs[2] = {16 * 8224, 8224};
    const cuuint32_t bd[3] = {40, 8, 16};
    enc(&tmWR, d_in[1], 3, gd, gs, bd, CU_TENSOR_MAP_SWIZZLE_NONE, CU_TENSOR_MAP_L2_PROMOTION_NONE);
    enc(&tmWI, d_in[2], 3, gd, gs, bd, CU_TENSOR_MAP_SWIZZLE_NONE, CU_TENSOR_MAP_L2_PROMOTION_NONE);
  }
  fused_kernel<<<NCTA, NTHREADS, SMEM_BYTES>>>((const __nv_bfloat16*)d_in[0], (const Tables*)tab, (Scratch*)scr,
                                               (__nv_bfloat16*)d_out, (const char*)d_in[4], (const char*)d_in[5],
                                               (const char*)d_in[6], tmWR, tmWI, tmGX, tmUX, tmGY, tmUY, tmD);
}
```

```cpp
#include <cuda_runtime.h>
#include <cuda_bf16.h>
#include <cuda.h>
#include <stdint.h>

namespace {

constexpr int NCTA = 128;
constexpr int NTHREADS = 384;
constexpr int SLOT = 16384;
constexpr int SMEM_BYTES = 14 * SLOT + 3072;
constexpr int SPIN_LIMIT = 1 << 22;

struct Scratch {
  uint4 Z1[128 * 1024];
  uint4 LN[16 * 8 * 1024];
  uint4 P[16 * 28 * 1024];
  uint4 ST[1024];
  unsigned cnt[64 * 32];
};
__device__ __align__(1024) Scratch g_scr;

constexpr double ccos(int i, int n) {
  i &= n - 1;
  if (i > n / 2) i = n - i;
  if (4 * i == n) return 0.0;
  const bool neg = 4 * i > n;
  if (neg) i = n / 2 - i;
  const double a = 6.283185307179586476925 * i / n, a2 = a * a;
  double term = 1.0, sum = 1.0;
  for (int k = 1; k < 14; k++) { term *= -a2 / ((2 * k - 1) * (2 * k)); sum += term; }
  return neg ? -sum : sum;
}
constexpr double csin(int i, int n) { return ccos(i - n / 4, n); }
constexpr unsigned fbits(double v, int mant) {
  if (v == 0.0) return 0;
  const unsigned sg = v < 0 ? 1u : 0u;
  if (v < 0) v = -v;
  int e = 127;
  while (v < 1.0) { v *= 2.0; e--; }
  const unsigned m = (unsigned)((v - 1.0) * (double)(1u << mant) + 0.5);
  return (sg << (8 + mant)) + ((unsigned)e << mant) + m;
}
constexpr unsigned pkb(double lo, double hi) { return fbits(lo, 7) | (fbits(hi, 7) << 16); }
constexpr double fa_elem(int mt, int r, int n1) {
  const int k1 = 8 * mt + (r & 7);
  return r < 8 ? ccos(k1 * n1, 32) : k1 == 0 ? ccos(16 * n1, 32) : -csin(k1 * n1, 32);
}
constexpr unsigned cfrag_c(int idx, int n, int ri, double s = 1.0) {
  return ri ? pkb(-s * csin(idx, n), s * ccos(idx, n)) : pkb(s * ccos(idx, n), s * csin(idx, n));
}
struct Tables {
  unsigned fa[4][32][4];
  unsigned fb[4][32][4];
  unsigned tw1[6][32][4];
  unsigned f2[8][4][32][4];
  unsigned g2[8][4][32][4];
  unsigned gb[4][32][4];
  unsigned ga[4][32][4];
  unsigned tw3[4][32][4];
  unsigned f8[32][4], g8[32][4];
};
constexpr int T1_BYTES = 7168, T2_BYTES = 39936;
static_assert(sizeof(Tables) == T1_BYTES + T2_BYTES, "table size");
constexpr Tables make_tables() {
  Tables T = {};
  for (int l = 0; l < 32; l++) {
    const int g = l >> 2, t = l & 3;
    for (int a = 0; a < 2; a++)
      for (int b = 0; b < 2; b++) {
        for (int r = 0; r < 4; r++) {
          const int row = g + 8 * (r & 1), col = 2 * t + 8 * (r >> 1);
          T.fa[2 * a + b][l][r] = pkb(fa_elem(a, row, 16 * b + col), fa_elem(a, row, 16 * b + col + 1));
          T.ga[2 * a + b][l][r] = pkb(fa_elem(b, col, 16 * a + row), fa_elem(b, col + 1, 16 * a + row));
        }
        const double sg = b ? -1.0 : 1.0;
        for (int h = 0; h < 2; h++) {
          const int ri = g & 1, m = 2 * (g >> 1) + h, k2 = b ? 15 - m : m;
          const int pa = (8 * a + 2 * t) * k2, pb = (8 * a + 2 * t + 1) * k2;
          T.fb[2 * a + b][l][2 * h] = ri == 0 ? pkb(ccos(pa, 16), ccos(pb, 16)) : pkb(-sg * csin(pa, 16), -sg * csin(pb, 16));
          T.fb[2 * a + b][l][2 * h + 1] = ri == 0 ? pkb(csin(pa, 16), csin(pb, 16)) : pkb(sg * ccos(pa, 16), sg * ccos(pb, 16));
        }
        const int n2 = 4 * (g >> 1) + 2 * a + (g & 1);
        for (int h = 0; h < 2; h++) {
          const int p = n2 * (b ? 15 - 2 * t - h : 2 * t + h);
          T.gb[2 * a + b][l][2 * h] = pkb(ccos(p, 16), -sg * csin(p, 16));
          T.gb[2 * a + b][l][2 * h + 1] = pkb(csin(p, 16), sg * ccos(p, 16));
          const int k1 = 8 * b + 2 * t + h, q = n2 * (k1 == 0 ? 16 : k1);
          T.tw3[2 * a + b][l][2 * h] = fbits(ccos(q, 512), 23);
          T.tw3[2 * a + b][l][2 * h + 1] = fbits(csin(q, 512), 23);
        }
        const int p = (8 * a + 2 * t + b) * (g == 0 ? 16 : g);
        T.tw1[2 * a + b][l][0] = fbits(g == 0 ? 0.0 : ccos(p, 512), 23);
        T.tw1[2 * a + b][l][1] = fbits(g == 0 ? ccos(p, 512) : csin(p, 512), 23);
        T.tw1[2 * a + b][l][2] = fbits(g == 0 ? 0.0 : -csin(p, 512), 23);
        T.tw1[2 * a + b][l][3] = fbits(g == 0 ? -csin(p, 512) : ccos(p, 512), 23);
        T.tw1[4 + a][l][2 * b] = fbits(ccos((8 * a + 2 * t + b) * (g + 8), 512), 23);
        T.tw1[4 + a][l][2 * b + 1] = fbits(csin((8 * a + 2 * t + b) * (g + 8), 512), 23);
      }
    for (int i = 0; i < 4; i++) {
      const int p8 = (t + 4 * (i & 1)) * (4 * (i >> 1) + (g >> 1));
      T.f8[l][i] = cfrag_c(p8, 8, g & 1);
      T.g8[l][i] = cfrag_c(-p8, 8, g & 1, 1.0 / (1 << 19));
    }
    for (int w = 0; w < 8; w++)
      for (int i = 0; i < 16; i++) {
        const int kidx = t + 4 * (i & 1) + 8 * (i >> 3), nidx = 4 * ((i >> 1) & 3) + (g >> 1);
        T.f2[w][i >> 2][l][i & 3] = cfrag_c((8 * kidx + w) * nidx, 128, g & 1);
        T.g2[w][i >> 2][l][i & 3] = cfrag_c(-(8 * nidx + w) * kidx, 128, g & 1);
      }
  }
  return T;
}
__device__ const __align__(128) Tables g_tab = make_tables();

__device__ __forceinline__ void die() { asm volatile("st.global.u32 [%0], %1;" ::"l"(0ull), "r"(0) : "memory"); }
__device__ __forceinline__ uint32_t s2u(const void* p) { return (uint32_t)__cvta_generic_to_shared(p); }
__device__ __forceinline__ void mbar_init(uint32_t b, int c) { asm volatile("mbarrier.init.shared::cta.b64 [%0], %1;" ::"r"(b), "r"(c)); }
__device__ __forceinline__ void mbar_expect(uint32_t b, int bytes) {
  asm volatile("mbarrier.arrive.expect_tx.shared::cta.b64 _, [%0], %1;" ::"r"(b), "r"(bytes) : "memory");
}
__device__ __forceinline__ void mbar_arrive(uint32_t b) { asm volatile("mbarrier.arrive.shared::cta.b64 _, [%0];" ::"r"(b) : "memory"); }
__device__ __forceinline__ uint32_t mbar_try(uint32_t b, uint32_t parity) {
  uint32_t ok;
  asm volatile("{.reg .pred p; mbarrier.try_wait.parity.shared::cta.b64 p, [%1], %2; selp.u32 %0,1,0,p;}"
               : "=r"(ok) : "r"(b), "r"(parity) : "memory");
  return ok;
}
__device__ __forceinline__ uint32_t mbar_test(uint32_t b) {
  uint32_t ok;
  asm volatile("{.reg .pred p; mbarrier.test_wait.parity.shared::cta.b64 p, [%1], 0; selp.u32 %0,1,0,p;}" : "=r"(ok) : "r"(b) : "memory");
  return ok;
}
__device__ __forceinline__ void mbar_wait(uint32_t b, uint32_t parity = 0) {
  int it = 0;
#pragma unroll 1
  while (!mbar_try(b, parity))
    if (++it > SPIN_LIMIT) { die(); break; }
}
__device__ __forceinline__ void bar_sync(int id, int n) { asm volatile("bar.sync %0, %1;" ::"r"(id), "r"(n) : "memory"); }
__device__ __forceinline__ void bar_arrive(int id, int n) { asm volatile("bar.arrive %0, %1;" ::"r"(id), "r"(n) : "memory"); }
__device__ __forceinline__ void red_release(unsigned* p) { asm volatile("red.release.gpu.global.add.u32 [%0], 1;" ::"l"(p) : "memory"); }
__device__ __forceinline__ void red_relaxed(unsigned* p) { asm volatile("red.relaxed.gpu.global.add.u32 [%0], 1;" ::"l"(p) : "memory"); }
__device__ __forceinline__ unsigned ld_acquire(const unsigned* p) {
  unsigned v;
  asm volatile("ld.acquire.gpu.global.u32 %0, [%1];" : "=r"(v) : "l"(p) : "memory");
  return v;
}
__device__ __forceinline__ unsigned ld_relaxed(const unsigned* p) {
  unsigned v;
  asm volatile("ld.relaxed.gpu.global.u32 %0, [%1];" : "=r"(v) : "l"(p) : "memory");
  return v;
}
__device__ __forceinline__ void wait_counter(const unsigned* p, unsigned target) {
  int it = 0;
  while ((int)(ld_acquire(p) - target) < 0)
    if (++it > SPIN_LIMIT) { die(); break; }
}
__device__ __forceinline__ void sts4(uint32_t a, uint32_t x, uint32_t y, uint32_t z, uint32_t w) {
  asm volatile("st.shared.v4.u32 [%0], {%1,%2,%3,%4};" ::"r"(a), "r"(x), "r"(y), "r"(z), "r"(w) : "memory");
}
__device__ __forceinline__ uint4 lds4(uint32_t a) {
  uint4 v;
  asm volatile("ld.shared.v4.u32 {%0,%1,%2,%3}, [%4];" : "=r"(v.x), "=r"(v.y), "=r"(v.z), "=r"(v.w) : "r"(a) : "memory");
  return v;
}
__device__ __forceinline__ uint32_t pack2(float lo, float hi) {
  uint32_t r;
  asm("cvt.rn.bf16x2.f32 %0, %1, %2;" : "=r"(r) : "f"(hi), "f"(lo));
  return r;
}
__device__ __forceinline__ float bf_lo(uint32_t v) { return __uint_as_float(v << 16); }
__device__ __forceinline__ uint32_t hadd2_bf16(uint32_t a, uint32_t b) {
  uint32_t r;
  asm("add.rn.bf16x2 %0, %1, %2;" : "=r"(r) : "r"(a), "r"(b));
  return r;
}
__device__ __forceinline__ void mma16816(float (&d)[4], uint32_t a0, uint32_t a1, uint32_t a2, uint32_t a3, uint32_t b0, uint32_t b1) {
  asm("mma.sync.aligned.m16n8k16.row.col.f32.bf16.bf16.f32 {%0,%1,%2,%3}, {%4,%5,%6,%7}, {%8,%9}, {%0,%1,%2,%3};"
      : "+f"(d[0]), "+f"(d[1]), "+f"(d[2]), "+f"(d[3])
      : "r"(a0), "r"(a1), "r"(a2), "r"(a3), "r"(b0), "r"(b1));
}
__device__ __forceinline__ void mma16816_z(float (&d)[4], uint32_t a0, uint32_t a1, uint32_t a2, uint32_t a3, uint32_t b0, uint32_t b1) {
  asm("{.reg .f32 z; mov.f32 z, 0f00000000;\n"
      "mma.sync.aligned.m16n8k16.row.col.f32.bf16.bf16.f32 {%0,%1,%2,%3}, {%4,%5,%6,%7}, {%8,%9}, {z,z,z,z};}"
      : "=f"(d[0]), "=f"(d[1]), "=f"(d[2]), "=f"(d[3])
      : "r"(a0), "r"(a1), "r"(a2), "r"(a3), "r"(b0), "r"(b1));
}
template <int N>
__device__ __forceinline__ void cs_frac(int idx, float& c, float& s) {
  int i = ((idx + N / 2) & (N - 1)) - N / 2;
  float a = (float)i * (6.283185307179586f / N);
  c = __cosf(a);
  s = __sinf(a);
}
template <int N>
__device__ __forceinline__ uint32_t cfrag(int idx, int ri) {
  float c, s;
  cs_frac<N>(idx, c, s);
  return ri ? pack2(-s, c) : pack2(c, s);
}
__device__ __forceinline__ uint32_t word(const uint4& v, int e) { return e == 0 ? v.x : e == 1 ? v.y : e == 2 ? v.z : v.w; }
__device__ __forceinline__ void cdft16(const uint4 (&A)[4], const uint4 (&F)[4], uint4 (&o)[4]) {
  float acc[2][4][4];
#pragma unroll
  for (int ks = 0; ks < 2; ks++)
#pragma unroll
    for (int p = 0; p < 2; p++)
#pragma unroll
      for (int v = 0; v < 4; v++) {
        const uint4& a = A[2 * ks + p];
        const uint32_t b0 = word(F[ks * 2 + (v >> 1)], (v & 1) * 2), b1 = word(F[ks * 2 + (v >> 1)], (v & 1) * 2 + 1);
        if (ks == 0) mma16816_z(acc[p][v], a.x, a.y, a.z, a.w, b0, b1);
        else mma16816(acc[p][v], a.x, a.y, a.z, a.w, b0, b1);
      }
#pragma unroll
  for (int v = 0; v < 4; v++)
    o[v] = make_uint4(pack2(acc[0][v][0], acc[0][v][1]), pack2(acc[0][v][2], acc[0][v][3]),
                      pack2(acc[1][v][0], acc[1][v][1]), pack2(acc[1][v][2], acc[1][v][3]));
}
__device__ __forceinline__ void lds_frag(uint4& f0, uint4& f1, uint32_t a0, uint32_t a1) {
  asm volatile("ld.volatile.shared.v2.u32 {%0,%1}, [%8]; ld.volatile.shared.v2.u32 {%2,%3}, [%9];\n"
               "ld.volatile.shared.v2.u32 {%4,%5}, [%8+8]; ld.volatile.shared.v2.u32 {%6,%7}, [%9+8];"
               : "=r"(f0.x), "=r"(f0.y), "=r"(f0.z), "=r"(f0.w), "=r"(f1.x), "=r"(f1.y), "=r"(f1.z), "=r"(f1.w) : "r"(a0), "r"(a1) : "memory");
}
__device__ __forceinline__ void reg_frag(uint4 (&q)[4], uint32_t ones) {
#pragma unroll
  for (int ks = 0; ks < 2; ks++) {
    const uint4 a = q[2 * ks], b = q[2 * ks + 1];
    q[2 * ks] = make_uint4(a.x, a.y, b.x & ones, b.y & ones);
    q[2 * ks + 1] = make_uint4(a.z & ones, a.w & ones, b.z, b.w);
  }
}
__device__ __forceinline__ void st_tag(uint4* p, const uint4& v, uint32_t tag) {
  asm volatile("st.relaxed.gpu.global.v4.b32 [%0], {%1,%2,%3,%4};"
               ::"l"(p), "r"((v.x & ~1u) | tag), "r"(v.y), "r"(v.z), "r"(v.w) : "memory");
}
__device__ __forceinline__ void st_tag8(void* p, uint32_t x, uint32_t y, uint32_t tag) {
  asm volatile("st.relaxed.gpu.global.v2.b32 [%0], {%1,%2};" ::"l"(p), "r"((x & ~1u) | tag), "r"(y) : "memory");
}
__device__ __forceinline__ uint4 ld_b128(const uint4* p) {
  uint4 v;
  asm volatile("ld.relaxed.gpu.global.v4.b32 {%0,%1,%2,%3}, [%4];"
               : "=r"(v.x), "=r"(v.y), "=r"(v.z), "=r"(v.w) : "l"(p) : "memory");
  return v;
}
template <int STRIDE>
__device__ __forceinline__ void ld_tag4_issue(uint4 (&q)[4], const uint4* p) {
#pragma unroll
  for (int i = 0; i < 4; i++) q[i] = ld_b128(p + i * STRIDE);
}
template <int STRIDE, bool HALVES = false>
__device__ __forceinline__ void ld_tag4_finish(uint4 (&q)[4], const uint4* p, uint32_t tag) {
  int it = 0;
#pragma unroll 1
  while (__any_sync(0xffffffffu, ((q[0].x ^ tag) | (q[1].x ^ tag) | (q[2].x ^ tag) | (q[3].x ^ tag) |
                                  (HALVES ? (q[0].z ^ tag) | (q[1].z ^ tag) | (q[2].z ^ tag) | (q[3].z ^ tag) : 0u)) & 1u)) {
    ld_tag4_issue<STRIDE>(q, p);
    if (++it > SPIN_LIMIT) { die(); break; }
  }
#pragma unroll
  for (int i = 0; i < 4; i++) {
    asm volatile("and.b32 %0, %0, 0xfffffffe;" : "+r"(q[i].x));
    if (HALVES) q[i].z &= ~1u;
  }
}
__device__ __forceinline__ float quad_sum(const uint32_t (&a)[8]) {
  float d[4];
  mma16816_z(d, a[0], a[1], a[2], a[3], 0x3f803f80u, 0x3f803f80u);
  mma16816(d, a[4], a[5], a[6], a[7], 0x3f803f80u, 0x3f803f80u);
  return d[0] + d[2];
}
__device__ __forceinline__ float sum_groups(float v) {
  v += __shfl_xor_sync(0xffffffffu, v, 4);
  v += __shfl_xor_sync(0xffffffffu, v, 8);
  v += __shfl_xor_sync(0xffffffffu, v, 16);
  return v;
}
__device__ __forceinline__ uint32_t hsub2_bf16(uint32_t a, uint32_t b) {
  uint32_t r;
  asm("sub.rn.bf16x2 %0, %1, %2;" : "=r"(r) : "r"(a), "r"(b));
  return r;
}
__device__ __forceinline__ float row_rstd(const uint32_t (&c)[8], float delta) {
  uint32_t s[8];
#pragma unroll
  for (int i = 0; i < 8; i++) asm("mul.rn.bf16x2 %0, %1, %1;" : "=r"(s[i]) : "r"(c[i]));
  return rsqrtf(fmaxf(fmaf(-delta, delta, sum_groups(quad_sum(s)) * (1.f / 512.f)), 0.f) + 1e-5f);
}
__device__ __forceinline__ uint64_t desc64(uint32_t lo, uint32_t hi) {
  uint64_t d;
  asm("mov.b64 %0, {%1, %2};" : "=l"(d) : "r"(lo), "r"(hi));
  return d;
}
constexpr uint32_t desc_hi(uint32_t sbo, uint32_t swz) { return (sbo >> 4) | (swz << 30); }
__device__ __forceinline__ uint32_t desc_lo(uint32_t addr, uint32_t lbo) { return ((addr & 0x3FFFF) >> 4) | ((lbo >> 4) << 16); }
__device__ __forceinline__ void cp_async16(uint32_t dst, const void* src) {
  asm volatile("cp.async.cg.shared.global [%0], [%1], 16;" ::"r"(dst), "l"(src) : "memory");
}
__device__ __forceinline__ uint2 lds2(uint32_t a) {
  uint2 v;
  asm volatile("ld.shared.v2.u32 {%0,%1}, [%2];" : "=r"(v.x), "=r"(v.y) : "r"(a) : "memory");
  return v;
}
__device__ __forceinline__ uint32_t lds_u16(uint32_t a) {
  uint16_t v;
  asm volatile("ld.shared.u16 %0, [%1];" : "=h"(v) : "r"(a) : "memory");
  return v;
}
__device__ __forceinline__ void wg_fence() { asm volatile("wgmma.fence.sync.aligned;" ::: "memory"); }
__device__ __forceinline__ void wg_commit() { asm volatile("wgmma.commit_group.sync.aligned;" ::: "memory"); }
template <int N>
__device__ __forceinline__ void wg_wait() { asm volatile("wgmma.wait_group.sync.aligned %0;" ::"n"(N) : "memory"); }
__device__ __forceinline__ void bulk_load(uint32_t dst, const void* src, int bytes, uint32_t bar) {
  asm volatile("cp.async.bulk.shared::cluster.global.mbarrier::complete_tx::bytes [%0], [%1], %2, [%3];"
               ::"r"(dst), "l"(src), "r"(bytes), "r"(bar) : "memory");
}
__device__ __forceinline__ void bulk_load_mc(uint32_t dst, const void* src, int bytes, uint32_t bar) {
  asm volatile("cp.async.bulk.shared::cluster.global.mbarrier::complete_tx::bytes.multicast::cluster [%0], [%1], %2, [%3], %4;"
               ::"r"(dst), "l"(src), "r"(bytes), "r"(bar), "h"((uint16_t)3) : "memory");
}
__device__ __forceinline__ void tma3(uint32_t dst, const CUtensorMap* tm, uint32_t bar, int c0, int c1, int c2) {
  asm volatile("cp.async.bulk.tensor.3d.shared::cluster.global.mbarrier::complete_tx::bytes [%0], [%1, {%3,%4,%5}], [%2];"
               ::"r"(dst), "l"(tm), "r"(bar), "r"(c0), "r"(c1), "r"(c2) : "memory");
}
__device__ __forceinline__ void tma3_mc(uint32_t dst, const CUtensorMap* tm, uint32_t bar, int c1, int c2) {
  asm volatile("cp.async.bulk.tensor.3d.shared::cluster.global.mbarrier::complete_tx::bytes.multicast::cluster [%0], [%1, {%3,%4,%5}], [%2], %6;"
               ::"r"(dst), "l"(tm), "r"(bar), "r"(0), "r"(c1), "r"(c2), "h"((uint16_t)3) : "memory");
}
__device__ __forceinline__ void mbar_arrive_remote(uint32_t rb) {
  asm volatile("mbarrier.arrive.shared::cluster.b64 _, [%0];" ::"r"(rb) : "memory");
}
__device__ __forceinline__ uint4 ldg_ca4(const void* p) {
  uint4 v;
  asm volatile("ld.global.ca.v4.u32 {%0,%1,%2,%3}, [%4];" : "=r"(v.x), "=r"(v.y), "=r"(v.z), "=r"(v.w) : "l"(p) : "memory");
  return v;
}
__device__ __forceinline__ float u2f(uint32_t v) { return __uint_as_float(v); }
__device__ __forceinline__ void mma_az(float (&d)[4], const uint4& a, uint32_t b0, uint32_t b1) { mma16816_z(d, a.x, a.y, a.z, a.w, b0, b1); }
__device__ __forceinline__ void mma_a(float (&d)[4], const uint4& a, uint32_t b0, uint32_t b1) { mma16816(d, a.x, a.y, a.z, a.w, b0, b1); }
__device__ __forceinline__ uint32_t clock32() {
  uint32_t v;
  asm volatile("mov.u32 %0, %%clock;" : "=r"(v) :: "memory");
  return v;
}
__device__ __forceinline__ float swiglu(float g, float u, float r) {
  float hg = (0.5f * r) * g, th;
  asm("tanh.approx.f32 %0, %1;" : "=f"(th) : "f"(hg));
  return fmaf(hg, th, hg) * (r * u);
}
__device__ __forceinline__ void l2_prefetch(const void* p, int bytes) {
  asm volatile("cp.async.bulk.prefetch.L2.global [%0], %1;" ::"l"(p), "r"(bytes) : "memory");
}

__device__ __forceinline__ void wgmma_n256(float (&d)[128], uint64_t da, uint64_t db, int sd = 1) {
  asm volatile("{.reg .pred p; setp.ne.b32 p, %130, 0;\n"
      "wgmma.mma_async.sync.aligned.m64n256k16.f32.bf16.bf16 {"
      "%0,%1,%2,%3,%4,%5,%6,%7,%8,%9,%10,%11,%12,%13,%14,%15,"
      "%16,%17,%18,%19,%20,%21,%22,%23,%24,%25,%26,%27,%28,%29,%30,%31,"
      "%32,%33,%34,%35,%36,%37,%38,%39,%40,%41,%42,%43,%44,%45,%46,%47,"
      "%48,%49,%50,%51,%52,%53,%54,%55,%56,%57,%58,%59,%60,%61,%62,%63,"
      "%64,%65,%66,%67,%68,%69,%70,%71,%72,%73,%74,%75,%76,%77,%78,%79,"
      "%80,%81,%82,%83,%84,%85,%86,%87,%88,%89,%90,%91,%92,%93,%94,%95,"
      "%96,%97,%98,%99,%100,%101,%102,%103,%104,%105,%106,%107,%108,%109,%110,%111,"
      "%112,%113,%114,%115,%116,%117,%118,%119,%120,%121,%122,%123,%124,%125,%126,%127"
      "}, %128, %129, p, 1, 1, 0, 1;}\n"
      : "+f"(d[0]),"+f"(d[1]),"+f"(d[2]),"+f"(d[3]),"+f"(d[4]),"+f"(d[5]),"+f"(d[6]),"+f"(d[7]),
        "+f"(d[8]),"+f"(d[9]),"+f"(d[10]),"+f"(d[11]),"+f"(d[12]),"+f"(d[13]),"+f"(d[14]),"+f"(d[15]),
        "+f"(d[16]),"+f"(d[17]),"+f"(d[18]),"+f"(d[19]),"+f"(d[20]),"+f"(d[21]),"+f"(d[22]),"+f"(d[23]),
        "+f"(d[24]),"+f"(d[25]),"+f"(d[26]),"+f"(d[27]),"+f"(d[28]),"+f"(d[29]),"+f"(d[30]),"+f"(d[31]),
        "+f"(d[32]),"+f"(d[33]),"+f"(d[34]),"+f"(d[35]),"+f"(d[36]),"+f"(d[37]),"+f"(d[38]),"+f"(d[39]),
        "+f"(d[40]),"+f"(d[41]),"+f"(d[42]),"+f"(d[43]),"+f"(d[44]),"+f"(d[45]),"+f"(d[46]),"+f"(d[47]),
        "+f"(d[48]),"+f"(d[49]),"+f"(d[50]),"+f"(d[51]),"+f"(d[52]),"+f"(d[53]),"+f"(d[54]),"+f"(d[55]),
        "+f"(d[56]),"+f"(d[57]),"+f"(d[58]),"+f"(d[59]),"+f"(d[60]),"+f"(d[61]),"+f"(d[62]),"+f"(d[63]),
        "+f"(d[64]),"+f"(d[65]),"+f"(d[66]),"+f"(d[67]),"+f"(d[68]),"+f"(d[69]),"+f"(d[70]),"+f"(d[71]),
        "+f"(d[72]),"+f"(d[73]),"+f"(d[74]),"+f"(d[75]),"+f"(d[76]),"+f"(d[77]),"+f"(d[78]),"+f"(d[79]),
        "+f"(d[80]),"+f"(d[81]),"+f"(d[82]),"+f"(d[83]),"+f"(d[84]),"+f"(d[85]),"+f"(d[86]),"+f"(d[87]),
        "+f"(d[88]),"+f"(d[89]),"+f"(d[90]),"+f"(d[91]),"+f"(d[92]),"+f"(d[93]),"+f"(d[94]),"+f"(d[95]),
        "+f"(d[96]),"+f"(d[97]),"+f"(d[98]),"+f"(d[99]),"+f"(d[100]),"+f"(d[101]),"+f"(d[102]),"+f"(d[103]),
        "+f"(d[104]),"+f"(d[105]),"+f"(d[106]),"+f"(d[107]),"+f"(d[108]),"+f"(d[109]),"+f"(d[110]),"+f"(d[111]),
        "+f"(d[112]),"+f"(d[113]),"+f"(d[114]),"+f"(d[115]),"+f"(d[116]),"+f"(d[117]),"+f"(d[118]),"+f"(d[119]),
        "+f"(d[120]),"+f"(d[121]),"+f"(d[122]),"+f"(d[123]),"+f"(d[124]),"+f"(d[125]),"+f"(d[126]),"+f"(d[127])
      : "l"(da), "l"(db), "r"(sd));
}
__device__ __forceinline__ void wgmma_n192(float (&d)[96], uint64_t da, uint64_t db) {
  asm volatile("wgmma.mma_async.sync.aligned.m64n192k16.f32.bf16.bf16 {"
      "%0,%1,%2,%3,%4,%5,%6,%7,%8,%9,%10,%11,%12,%13,%14,%15,"
      "%16,%17,%18,%19,%20,%21,%22,%23,%24,%25,%26,%27,%28,%29,%30,%31,"
      "%32,%33,%34,%35,%36,%37,%38,%39,%40,%41,%42,%43,%44,%45,%46,%47,"
      "%48,%49,%50,%51,%52,%53,%54,%55,%56,%57,%58,%59,%60,%61,%62,%63,"
      "%64,%65,%66,%67,%68,%69,%70,%71,%72,%73,%74,%75,%76,%77,%78,%79,"
      "%80,%81,%82,%83,%84,%85,%86,%87,%88,%89,%90,%91,%92,%93,%94,%95"
      "}, %96, %97, 1, 1, 1, 0, 1;\n"
      : "+f"(d[0]),"+f"(d[1]),"+f"(d[2]),"+f"(d[3]),"+f"(d[4]),"+f"(d[5]),"+f"(d[6]),"+f"(d[7]),
        "+f"(d[8]),"+f"(d[9]),"+f"(d[10]),"+f"(d[11]),"+f"(d[12]),"+f"(d[13]),"+f"(d[14]),"+f"(d[15]),
        "+f"(d[16]),"+f"(d[17]),"+f"(d[18]),"+f"(d[19]),"+f"(d[20]),"+f"(d[21]),"+f"(d[22]),"+f"(d[23]),
        "+f"(d[24]),"+f"(d[25]),"+f"(d[26]),"+f"(d[27]),"+f"(d[28]),"+f"(d[29]),"+f"(d[30]),"+f"(d[31]),
        "+f"(d[32]),"+f"(d[33]),"+f"(d[34]),"+f"(d[35]),"+f"(d[36]),"+f"(d[37]),"+f"(d[38]),"+f"(d[39]),
        "+f"(d[40]),"+f"(d[41]),"+f"(d[42]),"+f"(d[43]),"+f"(d[44]),"+f"(d[45]),"+f"(d[46]),"+f"(d[47]),
        "+f"(d[48]),"+f"(d[49]),"+f"(d[50]),"+f"(d[51]),"+f"(d[52]),"+f"(d[53]),"+f"(d[54]),"+f"(d[55]),
        "+f"(d[56]),"+f"(d[57]),"+f"(d[58]),"+f"(d[59]),"+f"(d[60]),"+f"(d[61]),"+f"(d[62]),"+f"(d[63]),
        "+f"(d[64]),"+f"(d[65]),"+f"(d[66]),"+f"(d[67]),"+f"(d[68]),"+f"(d[69]),"+f"(d[70]),"+f"(d[71]),
        "+f"(d[72]),"+f"(d[73]),"+f"(d[74]),"+f"(d[75]),"+f"(d[76]),"+f"(d[77]),"+f"(d[78]),"+f"(d[79]),
        "+f"(d[80]),"+f"(d[81]),"+f"(d[82]),"+f"(d[83]),"+f"(d[84]),"+f"(d[85]),"+f"(d[86]),"+f"(d[87]),
        "+f"(d[88]),"+f"(d[89]),"+f"(d[90]),"+f"(d[91]),"+f"(d[92]),"+f"(d[93]),"+f"(d[94]),"+f"(d[95])
      : "l"(da), "l"(db));
}
template <int SD>
__device__ __forceinline__ void wgmma_rs_n128(float (&d)[64], uint32_t a0, uint32_t a1, uint32_t a2, uint32_t a3, uint64_t db) {
  asm volatile("wgmma.mma_async.sync.aligned.m64n128k16.f32.bf16.bf16 {"
      "%0,%1,%2,%3,%4,%5,%6,%7,%8,%9,%10,%11,%12,%13,%14,%15,"
      "%16,%17,%18,%19,%20,%21,%22,%23,%24,%25,%26,%27,%28,%29,%30,%31,"
      "%32,%33,%34,%35,%36,%37,%38,%39,%40,%41,%42,%43,%44,%45,%46,%47,"
      "%48,%49,%50,%51,%52,%53,%54,%55,%56,%57,%58,%59,%60,%61,%62,%63"
      "}, {%64,%65,%66,%67}, %68, %69, 1, 1, 1;\n"
      : "+f"(d[0]),"+f"(d[1]),"+f"(d[2]),"+f"(d[3]),"+f"(d[4]),"+f"(d[5]),"+f"(d[6]),"+f"(d[7]),
        "+f"(d[8]),"+f"(d[9]),"+f"(d[10]),"+f"(d[11]),"+f"(d[12]),"+f"(d[13]),"+f"(d[14]),"+f"(d[15]),
        "+f"(d[16]),"+f"(d[17]),"+f"(d[18]),"+f"(d[19]),"+f"(d[20]),"+f"(d[21]),"+f"(d[22]),"+f"(d[23]),
        "+f"(d[24]),"+f"(d[25]),"+f"(d[26]),"+f"(d[27]),"+f"(d[28]),"+f"(d[29]),"+f"(d[30]),"+f"(d[31]),
        "+f"(d[32]),"+f"(d[33]),"+f"(d[34]),"+f"(d[35]),"+f"(d[36]),"+f"(d[37]),"+f"(d[38]),"+f"(d[39]),
        "+f"(d[40]),"+f"(d[41]),"+f"(d[42]),"+f"(d[43]),"+f"(d[44]),"+f"(d[45]),"+f"(d[46]),"+f"(d[47]),
        "+f"(d[48]),"+f"(d[49]),"+f"(d[50]),"+f"(d[51]),"+f"(d[52]),"+f"(d[53]),"+f"(d[54]),"+f"(d[55]),
        "+f"(d[56]),"+f"(d[57]),"+f"(d[58]),"+f"(d[59]),"+f"(d[60]),"+f"(d[61]),"+f"(d[62]),"+f"(d[63])
      : "r"(a0), "r"(a1), "r"(a2), "r"(a3), "l"(db), "n"(SD));
}
__device__ __forceinline__ void wgmma_rs_n256(float (&d)[128], uint32_t a0, uint32_t a1, uint32_t a2, uint32_t a3, uint64_t db, int sd = 1) {
  asm volatile("{.reg .pred p; setp.ne.b32 p, %133, 0;\n"
      "wgmma.mma_async.sync.aligned.m64n256k16.f32.bf16.bf16 {"
      "%0,%1,%2,%3,%4,%5,%6,%7,%8,%9,%10,%11,%12,%13,%14,%15,"
      "%16,%17,%18,%19,%20,%21,%22,%23,%24,%25,%26,%27,%28,%29,%30,%31,"
      "%32,%33,%34,%35,%36,%37,%38,%39,%40,%41,%42,%43,%44,%45,%46,%47,"
      "%48,%49,%50,%51,%52,%53,%54,%55,%56,%57,%58,%59,%60,%61,%62,%63,"
      "%64,%65,%66,%67,%68,%69,%70,%71,%72,%73,%74,%75,%76,%77,%78,%79,"
      "%80,%81,%82,%83,%84,%85,%86,%87,%88,%89,%90,%91,%92,%93,%94,%95,"
      "%96,%97,%98,%99,%100,%101,%102,%103,%104,%105,%106,%107,%108,%109,%110,%111,"
      "%112,%113,%114,%115,%116,%117,%118,%119,%120,%121,%122,%123,%124,%125,%126,%127"
      "}, {%128,%129,%130,%131}, %132, p, 1, 1, 1;}\n"
      : "+f"(d[0]),"+f"(d[1]),"+f"(d[2]),"+f"(d[3]),"+f"(d[4]),"+f"(d[5]),"+f"(d[6]),"+f"(d[7]),
        "+f"(d[8]),"+f"(d[9]),"+f"(d[10]),"+f"(d[11]),"+f"(d[12]),"+f"(d[13]),"+f"(d[14]),"+f"(d[15]),
        "+f"(d[16]),"+f"(d[17]),"+f"(d[18]),"+f"(d[19]),"+f"(d[20]),"+f"(d[21]),"+f"(d[22]),"+f"(d[23]),
        "+f"(d[24]),"+f"(d[25]),"+f"(d[26]),"+f"(d[27]),"+f"(d[28]),"+f"(d[29]),"+f"(d[30]),"+f"(d[31]),
        "+f"(d[32]),"+f"(d[33]),"+f"(d[34]),"+f"(d[35]),"+f"(d[36]),"+f"(d[37]),"+f"(d[38]),"+f"(d[39]),
        "+f"(d[40]),"+f"(d[41]),"+f"(d[42]),"+f"(d[43]),"+f"(d[44]),"+f"(d[45]),"+f"(d[46]),"+f"(d[47]),
        "+f"(d[48]),"+f"(d[49]),"+f"(d[50]),"+f"(d[51]),"+f"(d[52]),"+f"(d[53]),"+f"(d[54]),"+f"(d[55]),
        "+f"(d[56]),"+f"(d[57]),"+f"(d[58]),"+f"(d[59]),"+f"(d[60]),"+f"(d[61]),"+f"(d[62]),"+f"(d[63]),
        "+f"(d[64]),"+f"(d[65]),"+f"(d[66]),"+f"(d[67]),"+f"(d[68]),"+f"(d[69]),"+f"(d[70]),"+f"(d[71]),
        "+f"(d[72]),"+f"(d[73]),"+f"(d[74]),"+f"(d[75]),"+f"(d[76]),"+f"(d[77]),"+f"(d[78]),"+f"(d[79]),
        "+f"(d[80]),"+f"(d[81]),"+f"(d[82]),"+f"(d[83]),"+f"(d[84]),"+f"(d[85]),"+f"(d[86]),"+f"(d[87]),
        "+f"(d[88]),"+f"(d[89]),"+f"(d[90]),"+f"(d[91]),"+f"(d[92]),"+f"(d[93]),"+f"(d[94]),"+f"(d[95]),
        "+f"(d[96]),"+f"(d[97]),"+f"(d[98]),"+f"(d[99]),"+f"(d[100]),"+f"(d[101]),"+f"(d[102]),"+f"(d[103]),
        "+f"(d[104]),"+f"(d[105]),"+f"(d[106]),"+f"(d[107]),"+f"(d[108]),"+f"(d[109]),"+f"(d[110]),"+f"(d[111]),
        "+f"(d[112]),"+f"(d[113]),"+f"(d[114]),"+f"(d[115]),"+f"(d[116]),"+f"(d[117]),"+f"(d[118]),"+f"(d[119]),
        "+f"(d[120]),"+f"(d[121]),"+f"(d[122]),"+f"(d[123]),"+f"(d[124]),"+f"(d[125]),"+f"(d[126]),"+f"(d[127])
      : "r"(a0), "r"(a1), "r"(a2), "r"(a3), "l"(db), "r"(sd));
}
__device__ __forceinline__ void wgmma_rs_n192(float (&d)[96], uint32_t a0, uint32_t a1, uint32_t a2, uint32_t a3, uint64_t db) {
  asm volatile("wgmma.mma_async.sync.aligned.m64n192k16.f32.bf16.bf16 {"
      "%0,%1,%2,%3,%4,%5,%6,%7,%8,%9,%10,%11,%12,%13,%14,%15,"
      "%16,%17,%18,%19,%20,%21,%22,%23,%24,%25,%26,%27,%28,%29,%30,%31,"
      "%32,%33,%34,%35,%36,%37,%38,%39,%40,%41,%42,%43,%44,%45,%46,%47,"
      "%48,%49,%50,%51,%52,%53,%54,%55,%56,%57,%58,%59,%60,%61,%62,%63,"
      "%64,%65,%66,%67,%68,%69,%70,%71,%72,%73,%74,%75,%76,%77,%78,%79,"
      "%80,%81,%82,%83,%84,%85,%86,%87,%88,%89,%90,%91,%92,%93,%94,%95"
      "}, {%96,%97,%98,%99}, %100, 1, 1, 1, 1;\n"
      : "+f"(d[0]),"+f"(d[1]),"+f"(d[2]),"+f"(d[3]),"+f"(d[4]),"+f"(d[5]),"+f"(d[6]),"+f"(d[7]),
        "+f"(d[8]),"+f"(d[9]),"+f"(d[10]),"+f"(d[11]),"+f"(d[12]),"+f"(d[13]),"+f"(d[14]),"+f"(d[15]),
        "+f"(d[16]),"+f"(d[17]),"+f"(d[18]),"+f"(d[19]),"+f"(d[20]),"+f"(d[21]),"+f"(d[22]),"+f"(d[23]),
        "+f"(d[24]),"+f"(d[25]),"+f"(d[26]),"+f"(d[27]),"+f"(d[28]),"+f"(d[29]),"+f"(d[30]),"+f"(d[31]),
        "+f"(d[32]),"+f"(d[33]),"+f"(d[34]),"+f"(d[35]),"+f"(d[36]),"+f"(d[37]),"+f"(d[38]),"+f"(d[39]),
        "+f"(d[40]),"+f"(d[41]),"+f"(d[42]),"+f"(d[43]),"+f"(d[44]),"+f"(d[45]),"+f"(d[46]),"+f"(d[47]),
        "+f"(d[48]),"+f"(d[49]),"+f"(d[50]),"+f"(d[51]),"+f"(d[52]),"+f"(d[53]),"+f"(d[54]),"+f"(d[55]),
        "+f"(d[56]),"+f"(d[57]),"+f"(d[58]),"+f"(d[59]),"+f"(d[60]),"+f"(d[61]),"+f"(d[62]),"+f"(d[63]),
        "+f"(d[64]),"+f"(d[65]),"+f"(d[66]),"+f"(d[67]),"+f"(d[68]),"+f"(d[69]),"+f"(d[70]),"+f"(d[71]),
        "+f"(d[72]),"+f"(d[73]),"+f"(d[74]),"+f"(d[75]),"+f"(d[76]),"+f"(d[77]),"+f"(d[78]),"+f"(d[79]),
        "+f"(d[80]),"+f"(d[81]),"+f"(d[82]),"+f"(d[83]),"+f"(d[84]),"+f"(d[85]),"+f"(d[86]),"+f"(d[87]),
        "+f"(d[88]),"+f"(d[89]),"+f"(d[90]),"+f"(d[91]),"+f"(d[92]),"+f"(d[93]),"+f"(d[94]),"+f"(d[95])
      : "r"(a0), "r"(a1), "r"(a2), "r"(a3), "l"(db));
}


constexpr int C_LN = 0, C_PX = 16, C_PY = 32;
constexpr int NB_CONS = 1, NB_LN = 2, NB_LAG = 4, NB_INIT = 6, NB_RDY = 7, NB_WG = 8;
constexpr int LAGX = 4;
constexpr int LAGY = 5;
constexpr int LAG2 = 5;
constexpr int NLL = 2;
constexpr int POLL_DELAY3 = 600;
constexpr int POLL_DELAY = 1200;
constexpr int FILT_DELAY = 800;
constexpr int WARM = 4;
constexpr int ALEAD = 6;
constexpr int POLL_DELAY2 = 1000;
constexpr int REDPOS = 4;
constexpr int XTRIG = 20;
constexpr int HTRIG = 0;
constexpr int RING_SIG = 1;
constexpr int PF2_SIG = 1;
constexpr int SM_E = 0, SM_X = 16384, SM_E2 = 32768, SM_W = 49152, SM_FC = 69632, SM_T = 73728 - T1_BYTES;
constexpr unsigned long long KORDER = 0xBA9432DC876510ull;
constexpr unsigned long long BSLOT = 0xA852140A852140ull, PSLOT = 0x9DCB7639DCB763ull;
constexpr uint32_t BDEP = 0xFE97531, PDEP = 0xFCBA754;
constexpr uint32_t HI128 = desc_hi(1024, 1), HI64 = desc_hi(512, 2);

struct Bars {
  uint64_t full1[32], empty1[32], full2[16], fullA[8], empty2[8], fullP[16], emptyP[8], hbar, tbar, hint[3], sig[2], sbar, freeA[4];
  uint32_t epoch, pad;
};

template <int NK, bool STORE, int J0 = 0, int J1 = NK>
__device__ __forceinline__ void make_p(const float (&acc)[NK * 16], float r0, float r1, uint4 (&p)[NK], uint4* pbase, int ks0, uint32_t tag) {
#pragma unroll
  for (int j = J0; j < J1; j++) {
    uint32_t w[4];
#pragma unroll
    for (int i = 0; i < 4; i++) {
      const int a = 8 * j + 2 * i, b = a + NK * 8;
      w[i] = pack2(swiglu(acc[a], acc[b], (i & 1) ? r1 : r0), swiglu(acc[a + 1], acc[b + 1], (i & 1) ? r1 : r0));
    }
    asm volatile("" : "+r"(w[0]), "+r"(w[1]), "+r"(w[2]), "+r"(w[3]));
    p[j] = make_uint4(w[0], w[1], w[2], w[3]);
    if (STORE) st_tag(pbase + ((ks0 + j) >> 2) * 1024 + ((ks0 + j) & 3) * 32, p[j], tag);
  }
}
__device__ __forceinline__ void spin_until(uint32_t t) {
  while ((int)(clock32() - t) < 0) {}
}

__global__ void __cluster_dims__(2, 1, 1) __launch_bounds__(NTHREADS, 1)
fused_kernel(const __nv_bfloat16* __restrict__ x, const Tables* __restrict__ tab, Scratch* __restrict__ scr,
             __nv_bfloat16* __restrict__ out, const char* __restrict__ wg_raw, const char* __restrict__ wu_raw,
             const char* __restrict__ wd_raw,
             const __grid_constant__ CUtensorMap tmWR, const __grid_constant__ CUtensorMap tmWI,
             const __grid_constant__ CUtensorMap tmGX, const __grid_constant__ CUtensorMap tmUX,
             const __grid_constant__ CUtensorMap tmGY, const __grid_constant__ CUtensorMap tmUY,
             const __grid_constant__ CUtensorMap tmD) {
  extern __shared__ __align__(1024) char smem_raw[];
  const uint32_t sbase = s2u(smem_raw);
  const uint32_t sbar = sbase + 14 * SLOT, sstat = sbar + 1280;
  const int tid = threadIdx.x, lane = tid & 31;
  const int c = blockIdx.x, rk = c & 1, f = (c >> 1) & 7, rb = 2 * (c >> 4) + rk;
  const int rb2 = 2 * (c >> 4) + (f >> 2), kh = (f >> 1) & 1, nq = 2 * (f & 1) + rk;
#define BAR(field, i) (sbar + (uint32_t)offsetof(Bars, field) + 8u * (i))
#define TOFF(field) (sbase + SM_T + (uint32_t)offsetof(Tables, field) + lane * 16)

  if (tid >= 256) {
    asm volatile("setmaxnreg.dec.sync.aligned.u32 40;");
    const int warp = __shfl_sync(0xffffffffu, tid >> 5, 0);
    if (lane == 0) {
      if (warp == 8) {
        if (sbase & 1023) die();
#pragma unroll
        for (int i = 0; i < 20; i++) mbar_init(BAR(emptyP, i), i < 7 ? 16 : i < 8 ? 8 : i < 13 ? 1 : i == 15 ? 32 : i < 15 ? 8 : 16);
        mbar_expect(BAR(tbar, 0), T2_BYTES + 2 * 10240);
        mbar_expect(BAR(hbar, 0), 16384);
      } else if (warp == 9) {
#pragma unroll
        for (int i = 0; i < 32; i++) mbar_init(BAR(full1, i), 1);
#pragma unroll
        for (int i = 0; i < 32; i++) mbar_expect(BAR(full1, i), i < 16 ? 16384 : 12288);
      } else if (warp == 10) {
#pragma unroll
        for (int i = 0; i < 32; i++) mbar_init(BAR(empty1, i), 16);
#pragma unroll
        for (int i = 0; i < 14; i++) mbar_init(BAR(fullP, i), 1);
#pragma unroll
        for (int i = 0; i < 14; i++) mbar_expect(BAR(fullP, i), 16384);
      } else {
#pragma unroll
        for (int i = 0; i < 32; i++) mbar_init(BAR(full2, i), i < 24 ? 1 : 8);
#pragma unroll
        for (int i = 0; i < 24; i++) mbar_expect(BAR(full2, i), 16384);
      }
      asm volatile("fence.mbarrier_init.release.cluster;" ::: "memory");
    }
    if (tid == 256) {
      const int w0 = ((c >> 3) * 257 + 32 * (c & 7) + 1) & ~7;
      if (FILT_DELAY) {
        asm volatile("prefetch.tensormap [%0];" ::"l"(&tmWR) : "memory");
        asm volatile("prefetch.tensormap [%0];" ::"l"(&tmWI) : "memory");
        spin_until(clock32() + FILT_DELAY);
      }
      tma3(sbase + SM_W, &tmWR, BAR(tbar, 0), w0, 0, 0);
      tma3(sbase + SM_W + 10240, &tmWI, BAR(tbar, 0), w0, 0, 0);
      bulk_load(sbase + SM_T + T1_BYTES, reinterpret_cast<const char*>(tab) + T1_BYTES, T2_BYTES, BAR(tbar, 0));
    }
    if (tid == 288) {
      asm volatile("prefetch.tensormap [%0];" ::"l"(rk ? &tmUX : &tmGX) : "memory");
      asm volatile("prefetch.tensormap [%0];" ::"l"(rk ? &tmUY : &tmGY) : "memory");
      asm volatile("prefetch.tensormap [%0];" ::"l"(&tmD) : "memory");
    }
    if (tid == 320) {
      const unsigned e = ld_relaxed(&scr->cnt[(C_LN + rb) * 32]) >> 3;
      asm volatile("st.shared.u32 [%0], %1;" ::"r"(BAR(epoch, 0)), "r"(e) : "memory");
    }
    __syncwarp();
    asm volatile("barrier.cluster.arrive.relaxed.aligned;" ::: "memory");
    bar_arrive(NB_RDY, 384);
    asm volatile("barrier.cluster.wait.aligned;" ::: "memory");
    bar_sync(NB_INIT, 384);
    unsigned epoch;
    asm volatile("ld.shared.u32 %0, [%1];" : "=r"(epoch) : "r"(BAR(epoch, 0)) : "memory");
    if (warp == 8) {
      if (lane == 0) {
        const int ax = (7 * f + 3 * (f & 1)) >> 1;
        const int ay = 7 * f + ((f & 1) ? 0 : 4);
        const CUtensorMap* tx = rk ? &tmUX : &tmGX;
        const CUtensorMap* ty = rk ? &tmUY : &tmGY;
        if (RING_SIG >= 0) mbar_wait(BAR(sig, RING_SIG));
        uint32_t s = 2;
#pragma unroll 1
        for (int n = 0; n < 16; n++) {
          if (n >= 6) mbar_wait(BAR(empty1, n - 6));
          tma3_mc(sbase + (8 + s) * SLOT + rk * 8192, tx, BAR(full1, n), n * 32, ax);
          if (++s == 6) s = 0;
          if (n >= 10 && n < 15) {
            const int k = n - 10;
            mbar_wait(BAR(freeA, (12 * k + 11) >> 4));
            tma3_mc(sbase + k * 12288 + rk * 6144, ty, BAR(full1, 16 + k), (k + 8) * 32, ay);
          }
        }
#pragma unroll 1
        for (int k = 5; k < 16; k++) {
          mbar_wait(BAR(empty1, k < 13 ? 10 + ((12 * (k - 5) + 11) >> 4) : 8 + k));
          tma3_mc(sbase + 8 * SLOT + ((k - 5) & 7) * 12288 + rk * 6144, ty, BAR(full1, 16 + k), ((k + 8) & 15) * 32, ay);
        }
      }
    } else if (warp == 9) {
      if (lane == 0) {
        mbar_wait(BAR(fullA, 4));
        wait_counter(&scr->cnt[(C_LN + rb2) * 32], (epoch + 1) * 8);
        asm volatile("fence.proxy.async.global;" ::: "memory");
#pragma unroll 1
        for (int i = 0; i < 14; i++) {
          const int kblk = 14 * kh + (int)((KORDER >> (4 * i)) & 15);
          mbar_wait(i < 7 ? BAR(empty1, 16 + ((BDEP >> (4 * i)) & 15)) : BAR(empty2, i - 7));
          tma3(sbase + (uint32_t)((BSLOT >> (4 * i)) & 15) * SLOT, &tmD, BAR(full2, i), 0, 64 * kblk, 2 * nq);
        }
        mbar_wait(BAR(emptyP, 7));
        bulk_load(sbase + 3 * SLOT, &scr->LN[(rb2 * 8 + 2 * nq) * 1024 + kh * 512], 8192, BAR(hbar, 0));
        bulk_load(sbase + 3 * SLOT + 8192, &scr->LN[(rb2 * 8 + 2 * nq + 1) * 1024 + kh * 512], 8192, BAR(hbar, 0));
      }
    } else if (warp == 10) {
      bar_sync(NB_LN, 288);
      if (lane == 0) {
        red_release(&scr->cnt[(C_LN + rb) * 32]);
        wait_counter(&scr->cnt[(C_LN + rb) * 32], (epoch + 1) * 8);
        asm volatile("fence.proxy.async.global;" ::: "memory");
#pragma unroll 1
        for (int kb = NLL; kb < 8; kb++) {
          if (2 * kb >= ALEAD) mbar_wait(BAR(empty1, 2 * kb - ALEAD));
          bulk_load(sbase + kb * SLOT, &scr->LN[(rb * 8 + kb) * 1024], 16384, BAR(fullA, kb));
        }
#pragma unroll 1
        for (int s = 0; s < 14; s++) {
          const int kblk = 14 * kh + (int)((KORDER >> (4 * s)) & 15);
          if (s == 0 || s == 8 || s == 11) {
            mbar_wait(BAR(hint, s == 0 ? 0 : s == 8 ? 1 : 2), 0);
          }
          mbar_wait(s < 7 ? BAR(empty1, 16 + ((PDEP >> (4 * s)) & 15)) : BAR(emptyP, s - 7));
          bulk_load_mc(sbase + (uint32_t)((PSLOT >> (4 * s)) & 15) * SLOT + rk * 8192, &scr->P[(rb2 * 28 + kblk) * 1024 + rk * 512], 8192, BAR(fullP, s));
        }
      }
    } else {
      if (lane == 0) {
        mbar_wait(BAR(tbar, 0));
        l2_prefetch(wg_raw + (size_t)c * 5376, 5376);
        l2_prefetch(wu_raw + (size_t)c * 5376, 5376);
        mbar_wait(BAR(sig, PF2_SIG), 0);
        l2_prefetch(wg_raw + 688128 + (size_t)c * 8960, 8960);
        l2_prefetch(wu_raw + 688128 + (size_t)c * 8960, 8960);
      }
      mbar_wait(BAR(fullA, 4), 0);
      if (lane == 0) l2_prefetch(wd_raw + (size_t)c * 14336, 14336);
      {
        const uint32_t tag = (epoch + 1) & 1;
        uint4 v0, v1, v2;
        int it = 0;
        while (true) {
          v0 = ld_b128(&scr->ST[rb * 64 + lane]);
          v1 = ld_b128(&scr->ST[rb * 64 + 32 + lane]);
          v2 = ld_b128(&scr->ST[rb2 * 64 + 32 * kh + lane]);
          if (!__any_sync(0xffffffffu, ((v0.x ^ tag) | (v1.x ^ tag) | (v2.x ^ tag)) & 1u)) break;
          if (++it > SPIN_LIMIT) { die(); break; }
        }
        sts4(sstat + lane * 16, v0.x & ~1u, v0.y, v0.z, v0.w);
        sts4(sstat + 512 + lane * 16, v1.x & ~1u, v1.y, v1.z, v1.w);
        sts4(sstat + 1024 + lane * 16, v2.x & ~1u, v2.y, v2.z, v2.w);
        mbar_arrive(BAR(sbar, 0));
      }
      if (lane == 0) {
        mbar_wait(BAR(empty1, XTRIG));
        int it = 0;
        while ((int)(ld_relaxed(&scr->cnt[(C_PX + rb2) * 32 + kh]) - (epoch + 1) * 32) < 0) {
          if (++it > SPIN_LIMIT) { die(); break; }
        }
        mbar_arrive(BAR(hint, 0));
        mbar_wait(BAR(emptyP, HTRIG));
        uint32_t done = 0;
        while (done != 3) {
          uint2 v;
          asm volatile("ld.relaxed.gpu.global.v2.u32 {%0,%1}, [%2];" : "=r"(v.x), "=r"(v.y) : "l"(&scr->cnt[(C_PY + rb2) * 32 + 2 * kh]) : "memory");
          if (!(done & 1) && (int)(v.x - (epoch + 1) * 16) >= 0) { done |= 1; mbar_arrive(BAR(hint, 1)); }
          if (!(done & 2) && (int)(v.y - (epoch + 1) * 16) >= 0) { done |= 2; mbar_arrive(BAR(hint, 2)); }
          if (++it > SPIN_LIMIT) { die(); break; }
        }
      }
    }
  } else {
    const int warp = __shfl_sync(0xffffffffu, tid >> 5, 0);
    const int g = lane >> 2, t = lane & 3;
    uint4 fa[4], fb[4], tw[6];
#pragma unroll
    for (int i = 0; i < 4; i++) fa[i] = ldg_ca4(&tab->fa[i][lane][0]);
#pragma unroll
    for (int i = 0; i < 6; i++) tw[i] = ldg_ca4(&tab->tw1[i][lane][0]);
#pragma unroll
    for (int i = 0; i < 4; i++) fb[i] = ldg_ca4(&tab->fb[i][lane][0]);
#pragma unroll
    for (int i = 0; i < 4; i++) {
      const int r = i >> 1, ch = (i & 1) * 32 + lane;
      cp_async16(sbase + SM_X + (2 * warp + r) * 1024 + ((ch ^ ((ch >> 3) & 1)) * 16),
                 x + (size_t)(c + 128 * (2 * warp + r)) * 512 + ch * 8);
    }
    asm volatile("cp.async.commit_group;" ::: "memory");
    asm volatile("barrier.cluster.arrive.relaxed.aligned;" ::: "memory");
    uint32_t rbar;
    asm volatile("mapa.shared::cluster.u32 %0, %1, %2;" : "=r"(rbar) : "r"(sbar), "r"(rk ^ 1));
#define RBAR(field, i) (rbar + (uint32_t)offsetof(Bars, field) + 8u * (i))
    {
      const int ln = (tid >> 1) & 31, lg = ln >> 2, lt = ln & 3, i = 4 * (tid >> 6) + 2 * (tid & 1);
      const int kidx = lt + 8 * (i >> 3), nidx = 4 * ((i >> 1) & 3) + (lg >> 1);
      const uint32_t a0 = cfrag<2048>((c + 128 * kidx) * nidx, lg & 1), a1 = cfrag<2048>((c + 128 * (kidx + 4)) * nidx, lg & 1);
      const uint32_t b0 = cfrag<2048>(-(c + 128 * nidx) * kidx, lg & 1), b1 = cfrag<2048>(-(c + 128 * nidx) * (kidx + 4), lg & 1);
      asm volatile("st.shared.v2.u32 [%0], {%1,%2};" ::"r"(sbase + SM_FC + tid * 8), "r"(a0), "r"(a1) : "memory");
      asm volatile("st.shared.v2.u32 [%0], {%1,%2};" ::"r"(sbase + SM_FC + 2048 + tid * 8), "r"(b0), "r"(b1) : "memory");
    }
    bar_sync(NB_CONS, 256);
    uint4 fc[4];
#pragma unroll
    for (int i = 0; i < 4; i++) fc[i] = lds4(sbase + SM_FC + i * 512 + lane * 16);
    asm volatile("cp.async.wait_group 0;" ::: "memory");
    __syncwarp();
    bar_arrive(NB_INIT, 384);
    uint32_t tag, ones;
    uint4 q[4], o[4];
    {
      uint32_t v[2][8];
#pragma unroll
      for (int r = 0; r < 2; r++)
#pragma unroll
        for (int ks = 0; ks < 2; ks++) {
          const int ch = 32 * ks + 2 * (lane & 15) + (lane >> 4);
          asm volatile("ldmatrix.sync.aligned.m8n8.x4.trans.shared.b16 {%0,%1,%2,%3}, [%4];"
                       : "=r"(v[r][4 * ks]), "=r"(v[r][4 * ks + 1]), "=r"(v[r][4 * ks + 2]), "=r"(v[r][4 * ks + 3])
                       : "r"(sbase + SM_X + (2 * warp + r) * 1024 + ((ch ^ ((ch >> 3) & 1)) * 16)) : "memory");
        }
      float sq[2];
#pragma unroll
      for (int r = 0; r < 2; r++) {
        float s0 = 0.f, s1 = 0.f;
#pragma unroll
        for (int i = 0; i < 8; i++) {
          const float lo = bf_lo(v[r][i]), hi = u2f(v[r][i] & 0xffff0000u);
          s0 = fmaf(lo, lo, s0);
          s1 = fmaf(hi, hi, s1);
        }
        sq[r] = s0 + s1;
      }
      {
        float w = ((lane & 1) ? sq[1] : sq[0]) + __shfl_xor_sync(0xffffffffu, (lane & 1) ? sq[0] : sq[1], 1);
        w += __shfl_xor_sync(0xffffffffu, w, 2);
        w = sum_groups(w);
        const float o2 = __shfl_xor_sync(0xffffffffu, w, 1);
        sq[0] = (lane & 1) ? o2 : w;
        sq[1] = (lane & 1) ? w : o2;
      }
#pragma unroll
      for (int r = 0; r < 2; r++) {
        float dd[2][4], ee[2][4];
#pragma unroll
        for (int nt = 0; nt < 2; nt++) {
          mma_az(dd[nt], fa[0], v[r][2 * nt], v[r][2 * nt + 1]);
          mma_a(dd[nt], fa[1], v[r][4 + 2 * nt], v[r][5 + 2 * nt]);
          mma_az(ee[nt], fa[2], v[r][2 * nt], v[r][2 * nt + 1]);
          mma_a(ee[nt], fa[3], v[r][4 + 2 * nt], v[r][5 + 2 * nt]);
        }
        float mean = (dd[0][0] + dd[0][1]) + (dd[1][0] + dd[1][1]);
        mean += __shfl_xor_sync(0xffffffffu, mean, 1);
        mean += __shfl_xor_sync(0xffffffffu, mean, 2);
        mean = __shfl_sync(0xffffffffu, mean, 0) * (1.f / 512.f);
        const float rs = rsqrtf(fmaxf(fmaf(-mean, mean, sq[r] * (1.f / 512.f)), 0.f) + 1e-5f);
        float acc[4][4];
#pragma unroll
        for (int nt = 0; nt < 2; nt++) {
          const float (&d)[4] = dd[nt];
          const float (&e)[4] = ee[nt];
          const uint4 &ka = tw[2 * nt], &kb = tw[2 * nt + 1], &kc = tw[4 + nt];
          const uint32_t a0 = pack2(d[0] * u2f(ka.x) + d[2] * u2f(ka.y), d[1] * u2f(kb.x) + d[3] * u2f(kb.y));
          const uint32_t a2 = pack2(d[0] * u2f(ka.z) + d[2] * u2f(ka.w), d[1] * u2f(kb.z) + d[3] * u2f(kb.w));
          const uint32_t a1 = pack2(e[0] * u2f(kc.x) + e[2] * u2f(kc.y), e[1] * u2f(kc.z) + e[3] * u2f(kc.w));
          const uint32_t a3 = pack2(e[2] * u2f(kc.x) - e[0] * u2f(kc.y), e[3] * u2f(kc.z) - e[1] * u2f(kc.w));
          const uint32_t dc = pack2(fmaf(mean, -32.f, d[0]), fmaf(mean, -32.f, d[1]));
          const uint32_t h0 = g == 0 ? dc : a0, h2 = g == 0 ? 0u : a2;
          if (nt == 0) {
            mma16816_z(acc[0], a0, a1, a2, a3, fb[2 * nt].x, fb[2 * nt].y);
            mma16816_z(acc[1], a0, a1, a2, a3, fb[2 * nt].z, fb[2 * nt].w);
            mma16816_z(acc[2], h0, a1, h2, a3, fb[2 * nt + 1].x, fb[2 * nt + 1].y);
            mma16816_z(acc[3], h0, a1, h2, a3, fb[2 * nt + 1].z, fb[2 * nt + 1].w);
          } else {
            mma16816(acc[0], a0, a1, a2, a3, fb[2 * nt].x, fb[2 * nt].y);
            mma16816(acc[1], a0, a1, a2, a3, fb[2 * nt].z, fb[2 * nt].w);
            mma16816(acc[2], h0, a1, h2, a3, fb[2 * nt + 1].x, fb[2 * nt + 1].y);
            mma16816(acc[3], h0, a1, h2, a3, fb[2 * nt + 1].z, fb[2 * nt + 1].w);
          }
        }
#pragma unroll
        for (int h = 0; h < 2; h++) {
          const int j = 2 * warp + r, m = 2 * t + h;
          sts4(sbase + SM_E + ((j * 8 + m) * 8 + (g ^ (2 * t) ^ (2 * (j & 3)))) * 16,
               pack2(acc[h][0] * rs, acc[h][1] * rs), pack2(acc[h][2] * rs, acc[h][3] * rs),
               pack2(acc[2 + h][0] * rs, acc[2 + h][1] * rs), pack2(acc[2 + h][2] * rs, acc[2 + h][3] * rs));
        }
      }
      bar_sync(NB_RDY, 384);
      const uint32_t ea = sbase + SM_E + ((t * 8 + warp) * 8 + (g ^ (warp & 6) ^ (2 * t))) * 16;
      lds_frag(q[0], q[1], ea, ea + 4096);
      lds_frag(q[2], q[3], ea + 8192, ea + 12288);
      asm volatile("ld.shared.u32 %0, [%1];" : "=r"(tag) : "r"(BAR(epoch, 0)) : "memory");
      ones = ~(tag >> 31);
      tag = (tag + 1) & 1;
      cdft16(q, fc, o);
#pragma unroll
      for (int vv = 0; vv < 4; vv++) {
        o[vv].y &= ~1u;
        o[vv].z = (o[vv].z & ~1u) | (tag ^ 1);
        st_tag(&scr->Z1[(((4 * vv + t) * 8 + warp) * 128 + c) * 8 + g], o[vv], tag);
      }
    }
    asm volatile("setmaxnreg.inc.sync.aligned.u32 232;");
    {
      uint4* const zp = &scr->Z1[(c * 128 + 8 * t + warp) * 8 + g];
      const uint32_t tst = clock32();
      mbar_wait(BAR(tbar, 0), 0);
      uint4 f2[4], g2[4];
#pragma unroll
      for (int i = 0; i < 4; i++) {
        f2[i] = lds4(TOFF(f2) + warp * 2048 + i * 512);
        g2[i] = lds4(TOFF(g2) + warp * 2048 + i * 512);
      }
      const uint4 f8 = lds4(TOFF(f8)), g8 = lds4(TOFF(g8));
      asm volatile("barrier.cluster.wait.aligned;" ::: "memory");
      spin_until(tst + POLL_DELAY);
      ld_tag4_issue<256>(q, zp);
      float wfr[16], wfi[16];
      {
        const float nyq = ((c & 7) == 7 && g == 0) ? 0.5f : 1.f;
        uint32_t wa = sbase + SM_W + (16 * warp + t) * 80 + ((2 * (c >> 3) + 2) & 15) - 2;
        asm volatile("" : "+r"(wa));
        const uint32_t wb[3] = {wa + 2 * (g == 0 ? 16 : g), wa + 2 * g, wa - 2 * g};
#pragma unroll
        for (int i = 0; i < 16; i++) {
          const int ci = i >> 3, dd = (i >> 2) & 1, e = i & 3;
          const uint32_t a = wb[e < 2 ? e : 2] + (ci * 8 + 4 * dd) * 80 + (e == 0 ? 0 : e == 1 ? 16 : e == 2 ? 64 : 48);
          wfr[i] = bf_lo(lds_u16(a)) * (e == 2 ? nyq : 1.f);
          wfi[i] = bf_lo(lds_u16(a + 10240)) * (e == 2 ? nyq : 1.f);
        }
      }
      ld_tag4_finish<256>(q, zp, tag);
      if (lane == 0) mbar_arrive(BAR(sig, 0));
#pragma unroll
      for (int i = 0; i < 4; i++) q[i].z &= ~1u;
      reg_frag(q, ones);
      cdft16(q, f2, o);
      const uint32_t e2 = sbase + SM_E2;
#pragma unroll
      for (int vv = 0; vv < 4; vv++)
        sts4(e2 + ((warp * 16 + 4 * vv + t) * 8 + (g ^ (2 * t) ^ (2 * (warp & 3)))) * 16, o[vv].x, o[vv].y, o[vv].z, o[vv].w);
      bar_sync(NB_CONS, 256);
      uint32_t ad[2], res[2][2][4];
#pragma unroll
      for (int ci = 0; ci < 2; ci++) {
        const int cc = 2 * warp + ci;
        ad[ci] = e2 + ((t * 16 + cc) * 8 + (g ^ (2 * (cc & 3)) ^ (2 * t))) * 16;
        lds_frag(q[2 * ci], q[2 * ci + 1], ad[ci], ad[ci] + 8192);
      }
#pragma unroll
      for (int ci = 0; ci < 2; ci++)
#pragma unroll
        for (int p = 0; p < 2; p++) {
          uint32_t y[2][2];
#pragma unroll
          for (int vv = 0; vv < 2; vv++) {
            float d[4];
            mma_az(d, q[2 * ci + p], word(f8, 2 * vv), word(f8, 2 * vv + 1));
#pragma unroll
            for (int rr = 0; rr < 2; rr++) {
              const float fr = wfr[ci * 8 + vv * 4 + 2 * p + rr], fi = wfi[ci * 8 + vv * 4 + 2 * p + rr];
              y[vv][rr] = pack2(d[2 * rr] * fr - d[2 * rr + 1] * fi, d[2 * rr] * fi + d[2 * rr + 1] * fr);
            }
          }
#pragma unroll
          for (int vv = 0; vv < 2; vv++) {
            float d[4];
            mma16816_z(d, y[0][0], y[0][1], y[1][0], y[1][1], word(g8, 2 * vv), word(g8, 2 * vv + 1));
            res[ci][vv][2 * p] = pack2(d[0], d[1]);
            res[ci][vv][2 * p + 1] = pack2(d[2], d[3]);
          }
        }
#pragma unroll
      for (int i = 0; i < 4; i++)
        sts4(ad[i >> 1] + (i & 1) * 8192, res[i >> 1][i & 1][0], res[i >> 1][i & 1][1], res[i >> 1][i & 1][2], res[i >> 1][i & 1][3]);
      bar_sync(NB_CONS, 256);
      const uint32_t eb = e2 + ((warp * 16 + t) * 8 + (g ^ (2 * t) ^ (2 * (warp & 3)))) * 16;
      lds_frag(q[0], q[1], eb, eb + 512);
      lds_frag(q[2], q[3], eb + 1024, eb + 1536);
      cdft16(q, g2, o);
#pragma unroll
      for (int vv = 0; vv < 4; vv++) {
        o[vv].y &= ~1u;
        o[vv].z = (o[vv].z & ~1u) | tag;
        st_tag(zp + vv * 256, o[vv], tag);
      }
    }
    {
      const uint4* const zp = &scr->Z1[((t * 8 + warp) * 128 + c) * 8 + g];
      const uint32_t tst = clock32();
      uint4 gb[4], ga[4], gc[4], tw[4];
      uint2 xr[2][4];
      uint2* lnp[2];
#pragma unroll
      for (int r = 0; r < 2; r++) {
        const int row = 16 * f + 2 * warp + r;
        lnp[r] = reinterpret_cast<uint2*>(&scr->LN[(rb * 8 + (g >> 2)) * 1024 + row * 8 + ((2 * (g & 3) + (t >> 1)) ^ (row & 7))]) + (t & 1);
        asm volatile("" : "+l"(lnp[r]));
      }
#pragma unroll
      for (int i = 0; i < 4; i++) {
        gc[i] = lds4(sbase + SM_FC + 2048 + i * 512 + lane * 16);
        gb[i] = lds4(TOFF(gb) + i * 512);
        ga[i] = lds4(TOFF(ga) + i * 512);
        tw[i] = lds4(TOFF(tw3) + i * 512);
        const int ch = 2 * (g + 8 * i) + (t >> 1);
#pragma unroll
        for (int r = 0; r < 2; r++) xr[r][i] = lds2(sbase + SM_X + (2 * warp + r) * 1024 + ((ch ^ ((ch >> 3) & 1)) * 16) + (t & 1) * 8);
      }
      spin_until(tst + POLL_DELAY2);
      ld_tag4_issue<32768>(q, zp);
      ld_tag4_finish<32768, true>(q, zp, tag);
      if (lane == 0) mbar_arrive(BAR(sig, 1));
      reg_frag(q, ones);
      cdft16(q, gc, o);
#pragma unroll
      for (int vv = 0; vv < 4; vv++)
        sts4(sbase + SM_E + (((4 * vv + t) * 8 + warp) * 8 + (g ^ (warp & 6) ^ (2 * t))) * 16, o[vv].x, o[vv].y, o[vv].z, o[vv].w);
      bar_sync(NB_CONS, 256);
      uint32_t hv[2][8];
      const float mk = t == 0 ? 0.f : 1.f;
#pragma unroll
      for (int r = 0; r < 2; r++) {
        const int j = 2 * warp + r;
        uint4 u[2];
#pragma unroll
        for (int h = 0; h < 2; h++) u[h] = lds4(sbase + SM_E + ((j * 8 + 2 * t + h) * 8 + (g ^ (2 * t) ^ (2 * (j & 3)))) * 16);
        const uint32_t bp[4][2] = {{u[0].x, u[1].x & ones}, {u[0].y & ones, u[1].y}, {u[0].z, u[1].z & ones}, {u[0].w & ones, u[1].w}};
        float y[2][2][4];
#pragma unroll
        for (int i = 0; i < 2; i++) {
          float lo[4], hi[4], e[4];
          mma_az(lo, gb[2 * i], bp[0][0], bp[0][1]);
          mma_az(hi, gb[2 * i + 1], bp[2][0], bp[2][1]);
          mma_az(e, gb[2 * i], bp[1][0], bp[1][1]);
          mma_a(e, gb[2 * i + 1], bp[3][0], bp[3][1]);
          const uint4 &ka = tw[2 * i], &kb = tw[2 * i + 1];
          const float tr0 = fmaf(hi[0], mk, lo[0]), ti0 = fmaf(hi[2], mk, lo[2]);
          const float tr1 = lo[1] + hi[1], ti1 = lo[3] + hi[3];
          const float vr0 = tr0 * u2f(ka.x) - ti0 * u2f(ka.y), vi0 = tr0 * u2f(ka.y) + ti0 * u2f(ka.x);
          const float vr1 = tr1 * u2f(ka.z) - ti1 * u2f(ka.w), vi1 = tr1 * u2f(ka.w) + ti1 * u2f(ka.z);
          const uint32_t b0 = pack2(t == 0 ? hi[0] : vr0, vr1), b1 = pack2(t == 0 ? vr0 : vi0, vi1);
          const uint32_t b2 = pack2(e[0] * u2f(kb.x) - e[2] * u2f(kb.y), e[1] * u2f(kb.z) - e[3] * u2f(kb.w));
          const uint32_t b3 = pack2(e[0] * u2f(kb.y) + e[2] * u2f(kb.x), e[1] * u2f(kb.w) + e[3] * u2f(kb.z));
#pragma unroll
          for (int mt = 0; mt < 2; mt++) {
            mma_az(y[mt][i], ga[2 * mt], b0, b1);
            mma_a(y[mt][i], ga[2 * mt + 1], b2, b3);
          }
        }
#pragma unroll
        for (int i = 0; i < 4; i++) {
          hv[r][2 * i] = hadd2_bf16(xr[r][i].x, pack2(y[i >> 1][0][2 * (i & 1)], y[i >> 1][0][2 * (i & 1) + 1]));
          hv[r][2 * i + 1] = hadd2_bf16(xr[r][i].y, pack2(y[i >> 1][1][2 * (i & 1)], y[i >> 1][1][2 * (i & 1) + 1]));
        }
      }
      float mean[2];
      uint32_t mb[2];
#pragma unroll
      for (int r = 0; r < 2; r++) {
        mean[r] = sum_groups(quad_sum(hv[r])) * (1.f / 512.f);
        mb[r] = pack2(mean[r], mean[r]);
      }
#pragma unroll
      for (int i = 0; i < 4; i++)
#pragma unroll
        for (int r = 0; r < 2; r++) {
          hv[r][2 * i] = hsub2_bf16(hv[r][2 * i], mb[r]);
          hv[r][2 * i + 1] = hsub2_bf16(hv[r][2 * i + 1], mb[r]);
          st_tag8(lnp[r] + i * 4096, hv[r][2 * i], hv[r][2 * i + 1], i == 0 ? tag : (hv[r][2 * i] & 1u));
        }
      bar_arrive(NB_LN, 288);
      const uint32_t ones2 = ~(lds2(BAR(epoch, 0)).x >> 31);
      float rstd[2];
#pragma unroll
      for (int r = 0; r < 2; r++) {
        hv[r][0] &= ones2;
        rstd[r] = row_rstd(hv[r], mean[r] - bf_lo(mb[r]));
      }
      if (lane == 0)
        st_tag(&scr->ST[rb * 64 + 8 * f + warp], make_uint4(mb[0] << 16, __float_as_uint(rstd[0]), mb[1] << 16, __float_as_uint(rstd[1])), tag);
    }
    const int wgi = warp >> 2, wq = warp & 3;
    uint4* const pbase = &scr->P[rb * 28 * 1024 + warp * 128 + lane];
    const uint32_t a_lo0 = desc_lo(sbase + wgi * 8192, 16);
    const uint32_t ebar = lane == 0 ? BAR(empty1, 0) : RBAR(empty1, 0);
    float r0, r1;
    uint4 px[8], py[6];
    const int rh = wgi ^ kh ^ 1;
    const uint4* const psrc = &scr->P[(rb2 * 28 + 14 * kh) * 1024 + (4 * rh + wq) * 128 + lane];
    const uint32_t pa0 = sbase + (4 * rh + wq) * 2048;
    uint4 pf[3][4], ha[4][4];
    uint32_t rdy = 0, got0;
    {
      float acc[128];
#pragma unroll
      for (int i = 0; i < 128; i++) acc[i] = 0.f;
      const uint32_t b_lo0 = desc_lo(sbase + 8 * SLOT, 4096);
      const uint32_t t3 = clock32();
      if (WARM) {
        wg_fence();
#pragma unroll
        for (int i = 0; i < WARM; i++) wgmma_n256(acc, desc64(a_lo0 + 6 * 1024, HI128), desc64(b_lo0, HI128));
        wg_commit();
      }
      const uint4* const ap = &scr->LN[rb * 8 * 1024 + wgi * 512 + (tid & 127)];
      uint4 av[NLL][4];
      spin_until(t3 + POLL_DELAY3);
#pragma unroll
      for (int kb = 0; kb < NLL; kb++) ld_tag4_issue<128>(av[kb], ap + kb * 1024);
      bar_sync(NB_CONS, 256);
      const uint32_t lma = sbase + (16 * warp + (lane & 15)) * 128;
      auto load_a = [&](int kb) {
#pragma unroll
        for (int ks = 0; ks < 4; ks++)
          asm volatile("ldmatrix.sync.aligned.m8n8.x4.shared.b16 {%0,%1,%2,%3}, [%4];"
                       : "=r"(ha[kb][ks].x), "=r"(ha[kb][ks].y), "=r"(ha[kb][ks].z), "=r"(ha[kb][ks].w)
                       : "r"(lma + kb * SLOT + (((2 * ks + (lane >> 4)) ^ (lane & 7)) * 16)) : "memory");
      };
      auto stash_a = [&](int kb) {
        ld_tag4_finish<128, true>(av[kb], ap + kb * 1024, tag);
#pragma unroll
        for (int i = 0; i < 4; i++)
          sts4(sbase + kb * SLOT + wgi * 8192 + ((tid & 127) + 128 * i) * 16, av[kb][i].x, av[kb][i].y, av[kb][i].z, av[kb][i].w);
        bar_sync(NB_WG + wgi, 128);
      };
      stash_a(0);
      load_a(0);
#pragma unroll
      for (int n = 0; n < 8; n++) {
        const int kb = n >> 1, hh = n & 1;
        if (hh == 1 && kb < 3) {
          if (kb + 1 < NLL) stash_a(kb + 1); else mbar_wait(BAR(fullA, kb + 1));
        }
        mbar_wait(BAR(full1, n));
        const uint32_t bl = b_lo0 + ((n + 2) % 6) * 1024;
        wg_fence();
        if (hh == 1 && kb < 3) load_a(kb + 1);
        const uint4 &a0 = ha[kb][2 * hh], &a1 = ha[kb][2 * hh + 1];
        wgmma_rs_n256(acc, a0.x, a0.y, a0.z, a0.w, desc64(bl, HI128), n != 0 ? 1 : ~ones);
        wgmma_rs_n256(acc, a1.x, a1.y, a1.z, a1.w, desc64(bl + 128, HI128));
        wg_commit();
        if (hh == 1 && lane < 2) mbar_arrive_remote(ebar + (uint32_t)(offsetof(Bars, freeA) - offsetof(Bars, empty1)) + 8 * kb);
        wg_wait<1>();
        if (n != 0 && lane < 2) mbar_arrive_remote(ebar + 8 * (n - 1));
      }
      uint32_t slot = 4;
#pragma unroll 1
      for (int kb = 4; kb < 8; kb++) {
        mbar_wait(BAR(fullA, kb));
#pragma unroll
        for (int hh = 0; hh < 2; hh++) {
          if (LAGX && hh == ((16 - LAGX) & 1) && kb == ((16 - LAGX) >> 1) && wgi == 1) bar_sync(NB_LAG, 256);
          mbar_wait(BAR(full1, 2 * kb + hh));
          const uint32_t al = a_lo0 + kb * 1024 + hh * 4, bl = b_lo0 + slot * 1024;
          wg_fence();
          wgmma_n256(acc, desc64(al, HI128), desc64(bl, HI128));
          wgmma_n256(acc, desc64(al + 2, HI128), desc64(bl + 128, HI128));
          wg_commit();
          if (LAGX && hh == 1 && kb == 7 && wgi == 0) bar_arrive(NB_LAG, 256);
          wg_wait<1>();
          if (lane < 2) mbar_arrive_remote(ebar + 8 * (2 * kb + hh - 1));
          if (++slot == 6) slot = 0;
        }
      }
      mbar_wait(BAR(sbar, 0), 0);
      r0 = __uint_as_float(lds2(sstat + (16 * warp + g) * 8).y);
      r1 = __uint_as_float(lds2(sstat + (16 * warp + g + 8) * 8).y);
      wg_wait<0>();
      if (lane < 2) mbar_arrive_remote(ebar + 8 * 15);
      make_p<8, false>(acc, r0, r1, px, pbase, 0, tag);
    }
    {
      float acc[96];
#pragma unroll
      for (int i = 0; i < 96; i++) acc[i] = 0.f;
      const uint32_t b_lo0 = desc_lo(sbase, 2048);
      uint4* const pdst = pbase + ((7 * f + 3 * (f & 1)) >> 1) * 1024;
      auto stage_y = [&](int k) {
        if (LAGY && k == 16 - LAGY && wgi == 1) bar_sync(NB_LAG, 256);
        mbar_wait(BAR(full1, 16 + k));
        const uint32_t al = a_lo0 + (4 + (k >> 1)) * 1024 + (k & 1) * 4, bl = b_lo0 + (k < 5 ? k * 768 : 8192 + (k - 5) * 768);
        wg_fence();
        wgmma_n192(acc, desc64(al, HI128), desc64(bl, HI64));
        wgmma_n192(acc, desc64(al + 2, HI128), desc64(bl + 64, HI64));
        wg_commit();
      };
#pragma unroll
      for (int k = 0; k < 4; k++) {
        stage_y(k);
        st_tag(pdst + (k >> 1) * 1024 + (k & 1) * 64, px[2 * k], tag);
        st_tag(pdst + (k >> 1) * 1024 + (k & 1) * 64 + 32, px[2 * k + 1], tag);
        if (k == 3 && lane == 0) red_relaxed(&scr->cnt[(C_PX + rb) * 32 + (f >> 2)]);
        wg_wait<1>();
        if (k != 0 && lane < 2) mbar_arrive_remote(ebar + 8 * (15 + k));
      }
#pragma unroll 1
      for (int k = 4; k < 8; k++) {
        stage_y(k);
        wg_wait<1>();
        if (lane < 2) mbar_arrive_remote(ebar + 8 * (15 + k));
      }
      rdy = 0;
#pragma unroll
      for (int k = 8; k < 16; k++) {
        if (LAGY && k == 16 - LAGY && wgi == 1) bar_sync(NB_LAG, 256);
        if (!rdy) mbar_wait(BAR(full1, 16 + k));
        const uint32_t bl = b_lo0 + 8192 + ((k - 5) & 7) * 768;
        const uint4 &a0 = ha[(k - 8) >> 1][2 * (k & 1)], &a1 = ha[(k - 8) >> 1][2 * (k & 1) + 1];
        wg_fence();
        if (k < 15) rdy = mbar_test(BAR(full1, 17 + k));
        wgmma_rs_n192(acc, a0.x, a0.y, a0.z, a0.w, desc64(bl, HI64));
        wgmma_rs_n192(acc, a1.x, a1.y, a1.z, a1.w, desc64(bl + 64, HI64));
        wg_commit();
        if (LAGY && k == 15 && wgi == 0) bar_arrive(NB_LAG, 256);
        wg_wait<1>();
        if (lane < 2) mbar_arrive_remote(ebar + 8 * (15 + k));
      }
      got0 = __all_sync(0xffffffffu, mbar_test(BAR(fullP, 0)));
      if (got0) {
#pragma unroll
        for (int kk = 0; kk < 4; kk++) pf[0][kk] = lds4(pa0 + 3 * SLOT + kk * 512 + lane * 16);
      }
      wg_wait<0>();
      if (lane < 2) mbar_arrive_remote(ebar + 8 * 31);
      const int ks0 = 14 * f + ((f & 1) ? 0 : 8);
      auto reread = [&]() {
        asm volatile("ld.volatile.shared.f32 %0, [%2+4]; ld.volatile.shared.f32 %1, [%2+68];" : "=f"(r0), "=f"(r1) : "r"(sstat + (16 * warp + g) * 8) : "memory");
      };
      make_p<6, true, 0, 2>(acc, r0, r1, py, pbase, ks0, tag);
      if (REDPOS == 2 && lane == 0) red_relaxed(&scr->cnt[(C_PY + rb) * 32 + (f >> 1)]);
      reread();
      make_p<6, true, 2, 4>(acc, r0, r1, py, pbase, ks0, tag);
      if (REDPOS == 4 && lane == 0) red_relaxed(&scr->cnt[(C_PY + rb) * 32 + (f >> 1)]);
      reread();
      rdy = mbar_test(BAR(full2, 0)) & mbar_test(BAR(fullP, 1));
      make_p<6, true, 4, 6>(acc, r0, r1, py, pbase, ks0, tag);
      if (REDPOS == 6 && lane == 0) red_relaxed(&scr->cnt[(C_PY + rb) * 32 + (f >> 1)]);
    }
    {
      float acc[64];
      const uint32_t b2_lo0 = desc_lo(sbase, 8192);
      const uint32_t pbar = ebar + (uint32_t)(offsetof(Bars, emptyP) - offsetof(Bars, empty1));
      if (!got0) {
        mbar_wait(BAR(fullP, 0));
#pragma unroll
        for (int kk = 0; kk < 4; kk++) pf[0][kk] = lds4(pa0 + 3 * SLOT + kk * 512 + lane * 16);
      }
#pragma unroll
      for (int s = 0; s < 14; s++) {
        uint4 (&a)[4] = pf[s % 3];
        ld_tag4_finish<32>(a, psrc + (int)((KORDER >> (4 * s)) & 15) * 1024, tag);
        if (s < 8 && lane < (s < 7 ? 2 : 1)) mbar_arrive_remote(pbar + 8 * s);
        if (s >= 2) {
          wg_wait<1>();
          if (s <= 8 && lane == 0) mbar_arrive(BAR(empty2, s - 2));
        }
        if (!rdy) {
          if (s < 13) mbar_wait(BAR(fullP, s + 1));
          mbar_wait(BAR(full2, s));
        }
        if (s == 14 - LAG2 && wgi == 1) {
          const float m0 = __uint_as_float(lds2(sstat + 1024 + (16 * wq + g) * 8).x);
          const float m1 = __uint_as_float(lds2(sstat + 1024 + (16 * wq + g + 8) * 8).x);
          const uint32_t hb = sbase + 3 * SLOT + (16 * wq + (lane & 15)) * 128;
          wg_wait<0>();
          mbar_wait(BAR(hbar, 0));
#pragma unroll
          for (int i = 0; i < 8; i++) {
            uint32_t h[4];
            asm volatile("ldmatrix.sync.aligned.m8n8.x4.shared.b16 {%0,%1,%2,%3}, [%4];"
                         : "=r"(h[0]), "=r"(h[1]), "=r"(h[2]), "=r"(h[3])
                         : "r"(hb + (i >> 2) * 8192 + (((2 * (i & 3) + (lane >> 4)) ^ (lane & 7)) * 16)) : "memory");
            const uint32_t mk = ((t & 1) == 0 && nq == 0) ? ~1u : ~0u;
#pragma unroll
            for (int e = 0; e < 4; e++) {
              acc[8 * i + 2 * e] += bf_lo(h[e] & mk) + ((e & 1) ? m1 : m0);
              acc[8 * i + 2 * e + 1] += __uint_as_float(h[e] & 0xffff0000u) + ((e & 1) ? m1 : m0);
            }
          }
          bar_sync(NB_LAG, 256);
        }
        const uint32_t bl = b2_lo0 + (uint32_t)((BSLOT >> (4 * s)) & 15) * 1024;
        wg_fence();
        if (s < 13) {
#pragma unroll
          for (int kk = 0; kk < 4; kk++)
            pf[(s + 1) % 3][kk] = lds4(pa0 + (uint32_t)((PSLOT >> (4 * (s + 1))) & 15) * SLOT + kk * 512 + lane * 16);
          rdy = mbar_test(BAR(full2, s + 1));
          if (s < 12) rdy &= mbar_test(BAR(fullP, s + 2));
        }
        if (s == 0) wgmma_rs_n128<0>(acc, a[0].x, a[0].y, a[0].z, a[0].w, desc64(bl, HI128));
        else wgmma_rs_n128<1>(acc, a[0].x, a[0].y, a[0].z, a[0].w, desc64(bl, HI128));
#pragma unroll
        for (int kk = 1; kk < 4; kk++) wgmma_rs_n128<1>(acc, a[kk].x, a[kk].y, a[kk].z, a[kk].w, desc64(bl + kk * 128, HI128));
        wg_commit();
      }
      if (wgi == 0) {
        bar_arrive(NB_LAG, 256);
        uint4* const dst = &scr->Z1[(tid >> 3) * 1024 + (c ^ 4) * 8 + (tid & 7)];
        wg_wait<0>();
#pragma unroll
        for (int i = 0; i < 8; i++)
          st_tag(dst + i * 16384, make_uint4(pack2(acc[8 * i], acc[8 * i + 1]), pack2(acc[8 * i + 2], acc[8 * i + 3]) | 1u,
                                           pack2(acc[8 * i + 4], acc[8 * i + 5]), pack2(acc[8 * i + 6], acc[8 * i + 7])), tag);
      } else {
        uint4 pv[2][4];
        const uint4* const xsrc = &scr->Z1[((tid & 127) >> 3) * 1024 + c * 8 + (tid & 7)];
        ld_tag4_issue<16384>(pv[0], xsrc);
        ld_tag4_issue<16384>(pv[1], xsrc + 65536);
        wg_wait<0>();
        uint32_t w[32];
#pragma unroll
        for (int i = 0; i < 32; i++) w[i] = pack2(acc[2 * i], acc[2 * i + 1]);
        int it = 0;
#pragma unroll 1
        while (!__all_sync(0xffffffffu, pv[0][0].y & pv[0][1].y & pv[0][2].y & pv[0][3].y & pv[1][0].y & pv[1][1].y & pv[1][2].y & pv[1][3].y & 1u)) {
          ld_tag4_issue<16384>(pv[0], xsrc);
          ld_tag4_issue<16384>(pv[1], xsrc + 65536);
          if (++it > SPIN_LIMIT) { die(); break; }
        }
#pragma unroll
        for (int i = 0; i < 8; i++) {
          const uint4& p = pv[i >> 2][i & 3];
          asm volatile("stmatrix.sync.aligned.m8n8.x4.shared.b16 [%0], {%1,%2,%3,%4};"
                       ::"r"(pa0 + (11 + ((lane >> 3) & 1)) * SLOT + (lane & 7) * 256 + (((2 * i + (lane >> 4)) ^ (lane & 7)) * 16)),
                         "r"(hadd2_bf16(w[4 * i], p.x & ~1u)), "r"(hadd2_bf16(w[4 * i + 1], p.y & ~1u)), "r"(hadd2_bf16(w[4 * i + 2], p.z)),
                         "r"(hadd2_bf16(w[4 * i + 3], p.w)) : "memory");
        }
        __syncwarp();
        uint4* const dst = reinterpret_cast<uint4*>(out) + (16 * (c >> 4) + 2 * (4 * rh + wq) + (rb2 & 1) + 128 * (lane >> 4)) * 64 + nq * 16 + (lane & 15);
#pragma unroll
        for (int i = 0; i < 8; i++) {
          const int r = 2 * (i & 3) + (lane >> 4);
          dst[i * 256 * 64] = lds4(pa0 + (11 + (i >> 2)) * SLOT + r * 256 + (((lane & 15) ^ r) * 16));
        }
      }
    }
  }
#undef BAR
#undef TOFF
#undef RBAR
}

typedef CUresult (*EncodeFn)(CUtensorMap*, CUtensorMapDataType, cuuint32_t, void*, const cuuint64_t*, const cuuint64_t*,
                             const cuuint32_t*, const cuuint32_t*, CUtensorMapInterleave, CUtensorMapSwizzle,
                             CUtensorMapL2promotion, CUtensorMapFloatOOBfill);

}

extern "C" void kernel_launch(void* const* d_in, const int* in_sizes, int n_in, void* d_out, int out_size) {
  (void)in_sizes; (void)n_in; (void)out_size;
  static EncodeFn encode = nullptr;
  static void *tab = nullptr, *scr = nullptr;
  if (!encode) {
    void* fn = nullptr;
    cudaDriverEntryPointQueryResult qr;
    cudaGetDriverEntryPoint("cuTensorMapEncodeTiled", &fn, cudaEnableDefault, &qr);
    encode = (EncodeFn)fn;
    cudaGetSymbolAddress(&tab, g_tab);
    cudaGetSymbolAddress(&scr, g_scr);
    cudaFuncSetAttribute(fused_kernel, cudaFuncAttributeMaxDynamicSharedMemorySize, SMEM_BYTES);
  }
  CUtensorMap tmGX, tmUX, tmGY, tmUY, tmD, tmWR, tmWI;
  const cuuint32_t es[5] = {1, 1, 1, 1, 1};
  auto enc = [&](CUtensorMap* m, void* p, int rank, const cuuint64_t* gd, const cuuint64_t* gs, const cuuint32_t* bd,
                 CUtensorMapSwizzle sw, CUtensorMapL2promotion pr) {
    encode(m, CU_TENSOR_MAP_DATA_TYPE_BFLOAT16, rank, p, gd, gs, bd, es, CU_TENSOR_MAP_INTERLEAVE_NONE, sw, pr,
           CU_TENSOR_MAP_FLOAT_OOB_FILL_NONE);
  };
  {
    const cuuint64_t gd[3] = {64, 512, 28}, gs[2] = {3584, 128};
    const cuuint32_t bd[3] = {64, 32, 2};
    enc(&tmGX, d_in[4], 3, gd, gs, bd, CU_TENSOR_MAP_SWIZZLE_128B, CU_TENSOR_MAP_L2_PROMOTION_L2_256B);
    enc(&tmUX, d_in[5], 3, gd, gs, bd, CU_TENSOR_MAP_SWIZZLE_128B, CU_TENSOR_MAP_L2_PROMOTION_L2_256B);
  }
  {
    const cuuint64_t gd[3] = {32, 512, 56}, gs[2] = {3584, 64};
    const cuuint32_t bd[3] = {32, 32, 3};
    enc(&tmGY, d_in[4], 3, gd, gs, bd, CU_TENSOR_MAP_SWIZZLE_64B, CU_TENSOR_MAP_L2_PROMOTION_L2_128B);
    enc(&tmUY, d_in[5], 3, gd, gs, bd, CU_TENSOR_MAP_SWIZZLE_64B, CU_TENSOR_MAP_L2_PROMOTION_L2_128B);
  }
  {
    const cuuint64_t gd[3] = {64, 1792, 8}, gs[2] = {1024, 128};
    const cuuint32_t bd[3] = {64, 64, 2};
    enc(&tmD, d_in[6], 3, gd, gs, bd, CU_TENSOR_MAP_SWIZZLE_128B, CU_TENSOR_MAP_L2_PROMOTION_L2_256B);
  }
  {
    const cuuint64_t gd[3] = {4112, 8, 16}, gs[2] = {16 * 8224, 8224};
    const cuuint32_t bd[3] = {40, 8, 16};
    enc(&tmWR, d_in[1], 3, gd, gs, bd, CU_TENSOR_MAP_SWIZZLE_NONE, CU_TENSOR_MAP_L2_PROMOTION_NONE);
    enc(&tmWI, d_in[2], 3, gd, gs, bd, CU_TENSOR_MAP_SWIZZLE_NONE, CU_TENSOR_MAP_L2_PROMOTION_NONE);
  }
  fused_kernel<<<NCTA, NTHREADS, SMEM_BYTES>>>((const __nv_bfloat16*)d_in[0], (const Tables*)tab, (Scratch*)scr,
                                               (__nv_bfloat16*)d_out, (const char*)d_in[4], (const char*)d_in[5],
                                               (const char*)d_in[6], tmWR, tmWI, tmGX, tmUX, tmGY, tmUY, tmD);
}
```

```cpp
#include <cuda_runtime.h>
#include <cuda_bf16.h>
#include <cuda.h>
#include <stdint.h>

namespace {

constexpr int NCTA = 128;
constexpr int NTHREADS = 384;
constexpr int SLOT = 16384;
constexpr int SMEM_BYTES = 14 * SLOT + 3072;
constexpr int SPIN_LIMIT = 1 << 22;

struct Scratch {
  uint4 Z1[128 * 1024];
  uint4 LN[16 * 8 * 1024];
  uint4 P[16 * 28 * 1024];
  uint4 ST[1024];
  unsigned cnt[64 * 32];
};
__device__ __align__(1024) Scratch g_scr;

constexpr double ccos(int i, int n) {
  i &= n - 1;
  if (i > n / 2) i = n - i;
  if (4 * i == n) return 0.0;
  const bool neg = 4 * i > n;
  if (neg) i = n / 2 - i;
  const double a = 6.283185307179586476925 * i / n, a2 = a * a;
  double term = 1.0, sum = 1.0;
  for (int k = 1; k < 14; k++) { term *= -a2 / ((2 * k - 1) * (2 * k)); sum += term; }
  return neg ? -sum : sum;
}
constexpr double csin(int i, int n) { return ccos(i - n / 4, n); }
constexpr unsigned fbits(double v, int mant) {
  if (v == 0.0) return 0;
  const unsigned sg = v < 0 ? 1u : 0u;
  if (v < 0) v = -v;
  int e = 127;
  while (v < 1.0) { v *= 2.0; e--; }
  const unsigned m = (unsigned)((v - 1.0) * (double)(1u << mant) + 0.5);
  return (sg << (8 + mant)) + ((unsigned)e << mant) + m;
}
constexpr unsigned pkb(double lo, double hi) { return fbits(lo, 7) | (fbits(hi, 7) << 16); }
constexpr double fa_elem(int mt, int r, int n1) {
  const int k1 = 8 * mt + (r & 7);
  return r < 8 ? ccos(k1 * n1, 32) : k1 == 0 ? ccos(16 * n1, 32) : -csin(k1 * n1, 32);
}
constexpr unsigned cfrag_c(int idx, int n, int ri, double s = 1.0) {
  return ri ? pkb(-s * csin(idx, n), s * ccos(idx, n)) : pkb(s * ccos(idx, n), s * csin(idx, n));
}
struct Tables {
  unsigned fa[4][32][4];
  unsigned fb[4][32][4];
  unsigned tw1[6][32][4];
  unsigned f2[8][4][32][4];
  unsigned g2[8][4][32][4];
  unsigned gb[4][32][4];
  unsigned ga[4][32][4];
  unsigned tw3[4][32][4];
  unsigned f8[32][4], g8[32][4];
};
constexpr int T1_BYTES = 7168, T2_BYTES = 39936;
static_assert(sizeof(Tables) == T1_BYTES + T2_BYTES, "table size");
constexpr Tables make_tables() {
  Tables T = {};
  for (int l = 0; l < 32; l++) {
    const int g = l >> 2, t = l & 3;
    for (int a = 0; a < 2; a++)
      for (int b = 0; b < 2; b++) {
        for (int r = 0; r < 4; r++) {
          const int row = g + 8 * (r & 1), col = 2 * t + 8 * (r >> 1);
          T.fa[2 * a + b][l][r] = pkb(fa_elem(a, row, 16 * b + col), fa_elem(a, row, 16 * b + col + 1));
          T.ga[2 * a + b][l][r] = pkb(fa_elem(b, col, 16 * a + row), fa_elem(b, col + 1, 16 * a + row));
        }
        const double sg = b ? -1.0 : 1.0;
        for (int h = 0; h < 2; h++) {
          const int ri = g & 1, m = 2 * (g >> 1) + h, k2 = b ? 15 - m : m;
          const int pa = (8 * a + 2 * t) * k2, pb = (8 * a + 2 * t + 1) * k2;
          T.fb[2 * a + b][l][2 * h] = ri == 0 ? pkb(ccos(pa, 16), ccos(pb, 16)) : pkb(-sg * csin(pa, 16), -sg * csin(pb, 16));
          T.fb[2 * a + b][l][2 * h + 1] = ri == 0 ? pkb(csin(pa, 16), csin(pb, 16)) : pkb(sg * ccos(pa, 16), sg * ccos(pb, 16));
        }
        const int n2 = 4 * (g >> 1) + 2 * a + (g & 1);
        for (int h = 0; h < 2; h++) {
          const int p = n2 * (b ? 15 - 2 * t - h : 2 * t + h);
          T.gb[2 * a + b][l][2 * h] = pkb(ccos(p, 16), -sg * csin(p, 16));
          T.gb[2 * a + b][l][2 * h + 1] = pkb(csin(p, 16), sg * ccos(p, 16));
          const int k1 = 8 * b + 2 * t + h, q = n2 * (k1 == 0 ? 16 : k1);
          T.tw3[2 * a + b][l][2 * h] = fbits(ccos(q, 512), 23);
          T.tw3[2 * a + b][l][2 * h + 1] = fbits(csin(q, 512), 23);
        }
        const int p = (8 * a + 2 * t + b) * (g == 0 ? 16 : g);
        T.tw1[2 * a + b][l][0] = fbits(g == 0 ? 0.0 : ccos(p, 512), 23);
        T.tw1[2 * a + b][l][1] = fbits(g == 0 ? ccos(p, 512) : csin(p, 512), 23);
        T.tw1[2 * a + b][l][2] = fbits(g == 0 ? 0.0 : -csin(p, 512), 23);
        T.tw1[2 * a + b][l][3] = fbits(g == 0 ? -csin(p, 512) : ccos(p, 512), 23);
        T.tw1[4 + a][l][2 * b] = fbits(ccos((8 * a + 2 * t + b) * (g + 8), 512), 23);
        T.tw1[4 + a][l][2 * b + 1] = fbits(csin((8 * a + 2 * t + b) * (g + 8), 512), 23);
      }
    for (int i = 0; i < 4; i++) {
      const int p8 = (t + 4 * (i & 1)) * (4 * (i >> 1) + (g >> 1));
      T.f8[l][i] = cfrag_c(p8, 8, g & 1);
      T.g8[l][i] = cfrag_c(-p8, 8, g & 1, 1.0 / (1 << 19));
    }
    for (int w = 0; w < 8; w++)
      for (int i = 0; i < 16; i++) {
        const int kidx = t + 4 * (i & 1) + 8 * (i >> 3), nidx = 4 * ((i >> 1) & 3) + (g >> 1);
        T.f2[w][i >> 2][l][i & 3] = cfrag_c((8 * kidx + w) * nidx, 128, g & 1);
        T.g2[w][i >> 2][l][i & 3] = cfrag_c(-(8 * nidx + w) * kidx, 128, g & 1);
      }
  }
  return T;
}
__device__ const __align__(128) Tables g_tab = make_tables();

__device__ __forceinline__ void die() { asm volatile("st.global.u32 [%0], %1;" ::"l"(0ull), "r"(0) : "memory"); }
__device__ __forceinline__ uint32_t s2u(const void* p) { return (uint32_t)__cvta_generic_to_shared(p); }
__device__ __forceinline__ void mbar_init(uint32_t b, int c) { asm volatile("mbarrier.init.shared::cta.b64 [%0], %1;" ::"r"(b), "r"(c)); }
__device__ __forceinline__ void mbar_expect(uint32_t b, int bytes) {
  asm volatile("mbarrier.arrive.expect_tx.shared::cta.b64 _, [%0], %1;" ::"r"(b), "r"(bytes) : "memory");
}
__device__ __forceinline__ void mbar_arrive(uint32_t b) { asm volatile("mbarrier.arrive.shared::cta.b64 _, [%0];" ::"r"(b) : "memory"); }
__device__ __forceinline__ uint32_t mbar_try(uint32_t b, uint32_t parity) {
  uint32_t ok;
  asm volatile("{.reg .pred p; mbarrier.try_wait.parity.shared::cta.b64 p, [%1], %2; selp.u32 %0,1,0,p;}"
               : "=r"(ok) : "r"(b), "r"(parity) : "memory");
  return ok;
}
__device__ __forceinline__ uint32_t mbar_test(uint32_t b) {
  uint32_t ok;
  asm volatile("{.reg .pred p; mbarrier.test_wait.parity.shared::cta.b64 p, [%1], 0; selp.u32 %0,1,0,p;}" : "=r"(ok) : "r"(b) : "memory");
  return ok;
}
__device__ __forceinline__ void mbar_wait(uint32_t b, uint32_t parity = 0) {
  int it = 0;
#pragma unroll 1
  while (!mbar_try(b, parity))
    if (++it > SPIN_LIMIT) { die(); break; }
}
__device__ __forceinline__ void bar_sync(int id, int n) { asm volatile("bar.sync %0, %1;" ::"r"(id), "r"(n) : "memory"); }
__device__ __forceinline__ void bar_arrive(int id, int n) { asm volatile("bar.arrive %0, %1;" ::"r"(id), "r"(n) : "memory"); }
__device__ __forceinline__ void red_release(unsigned* p) { asm volatile("red.release.gpu.global.add.u32 [%0], 1;" ::"l"(p) : "memory"); }
__device__ __forceinline__ void red_relaxed(unsigned* p) { asm volatile("red.relaxed.gpu.global.add.u32 [%0], 1;" ::"l"(p) : "memory"); }
__device__ __forceinline__ unsigned ld_acquire(const unsigned* p) {
  unsigned v;
  asm volatile("ld.acquire.gpu.global.u32 %0, [%1];" : "=r"(v) : "l"(p) : "memory");
  return v;
}
__device__ __forceinline__ unsigned ld_relaxed(const unsigned* p) {
  unsigned v;
  asm volatile("ld.relaxed.gpu.global.u32 %0, [%1];" : "=r"(v) : "l"(p) : "memory");
  return v;
}
__device__ __forceinline__ void wait_counter(const unsigned* p, unsigned target) {
  int it = 0;
  while ((int)(ld_acquire(p) - target) < 0)
    if (++it > SPIN_LIMIT) { die(); break; }
}
__device__ __forceinline__ void sts4(uint32_t a, uint32_t x, uint32_t y, uint32_t z, uint32_t w) {
  asm volatile("st.shared.v4.u32 [%0], {%1,%2,%3,%4};" ::"r"(a), "r"(x), "r"(y), "r"(z), "r"(w) : "memory");
}
__device__ __forceinline__ uint4 lds4(uint32_t a) {
  uint4 v;
  asm volatile("ld.shared.v4.u32 {%0,%1,%2,%3}, [%4];" : "=r"(v.x), "=r"(v.y), "=r"(v.z), "=r"(v.w) : "r"(a) : "memory");
  return v;
}
__device__ __forceinline__ uint32_t pack2(float lo, float hi) {
  uint32_t r;
  asm("cvt.rn.bf16x2.f32 %0, %1, %2;" : "=r"(r) : "f"(hi), "f"(lo));
  return r;
}
__device__ __forceinline__ float bf_lo(uint32_t v) { return __uint_as_float(v << 16); }
__device__ __forceinline__ uint32_t hadd2_bf16(uint32_t a, uint32_t b) {
  uint32_t r;
  asm("add.rn.bf16x2 %0, %1, %2;" : "=r"(r) : "r"(a), "r"(b));
  return r;
}
__device__ __forceinline__ void mma16816(float (&d)[4], uint32_t a0, uint32_t a1, uint32_t a2, uint32_t a3, uint32_t b0, uint32_t b1) {
  asm("mma.sync.aligned.m16n8k16.row.col.f32.bf16.bf16.f32 {%0,%1,%2,%3}, {%4,%5,%6,%7}, {%8,%9}, {%0,%1,%2,%3};"
      : "+f"(d[0]), "+f"(d[1]), "+f"(d[2]), "+f"(d[3])
      : "r"(a0), "r"(a1), "r"(a2), "r"(a3), "r"(b0), "r"(b1));
}
__device__ __forceinline__ void mma16816_z(float (&d)[4], uint32_t a0, uint32_t a1, uint32_t a2, uint32_t a3, uint32_t b0, uint32_t b1) {
  asm("{.reg .f32 z; mov.f32 z, 0f00000000;\n"
      "mma.sync.aligned.m16n8k16.row.col.f32.bf16.bf16.f32 {%0,%1,%2,%3}, {%4,%5,%6,%7}, {%8,%9}, {z,z,z,z};}"
      : "=f"(d[0]), "=f"(d[1]), "=f"(d[2]), "=f"(d[3])
      : "r"(a0), "r"(a1), "r"(a2), "r"(a3), "r"(b0), "r"(b1));
}
template <int N>
__device__ __forceinline__ void cs_frac(int idx, float& c, float& s) {
  int i = ((idx + N / 2) & (N - 1)) - N / 2;
  float a = (float)i * (6.283185307179586f / N);
  c = __cosf(a);
  s = __sinf(a);
}
template <int N>
__device__ __forceinline__ uint32_t cfrag(int idx, int ri) {
  float c, s;
  cs_frac<N>(idx, c, s);
  return ri ? pack2(-s, c) : pack2(c, s);
}
__device__ __forceinline__ uint32_t word(const uint4& v, int e) { return e == 0 ? v.x : e == 1 ? v.y : e == 2 ? v.z : v.w; }
__device__ __forceinline__ void cdft16(const uint4 (&A)[4], const uint4 (&F)[4], uint4 (&o)[4]) {
  float acc[2][4][4];
#pragma unroll
  for (int ks = 0; ks < 2; ks++)
#pragma unroll
    for (int p = 0; p < 2; p++)
#pragma unroll
      for (int v = 0; v < 4; v++) {
        const uint4& a = A[2 * ks + p];
        const uint32_t b0 = word(F[ks * 2 + (v >> 1)], (v & 1) * 2), b1 = word(F[ks * 2 + (v >> 1)], (v & 1) * 2 + 1);
        if (ks == 0) mma16816_z(acc[p][v], a.x, a.y, a.z, a.w, b0, b1);
        else mma16816(acc[p][v], a.x, a.y, a.z, a.w, b0, b1);
      }
#pragma unroll
  for (int v = 0; v < 4; v++)
    o[v] = make_uint4(pack2(acc[0][v][0], acc[0][v][1]), pack2(acc[0][v][2], acc[0][v][3]),
                      pack2(acc[1][v][0], acc[1][v][1]), pack2(acc[1][v][2], acc[1][v][3]));
}
__device__ __forceinline__ void lds_frag(uint4& f0, uint4& f1, uint32_t a0, uint32_t a1) {
  asm volatile("ld.volatile.shared.v2.u32 {%0,%1}, [%8]; ld.volatile.shared.v2.u32 {%2,%3}, [%9];\n"
               "ld.volatile.shared.v2.u32 {%4,%5}, [%8+8]; ld.volatile.shared.v2.u32 {%6,%7}, [%9+8];"
               : "=r"(f0.x), "=r"(f0.y), "=r"(f0.z), "=r"(f0.w), "=r"(f1.x), "=r"(f1.y), "=r"(f1.z), "=r"(f1.w) : "r"(a0), "r"(a1) : "memory");
}
__device__ __forceinline__ void reg_frag(uint4 (&q)[4], uint32_t ones) {
#pragma unroll
  for (int ks = 0; ks < 2; ks++) {
    const uint4 a = q[2 * ks], b = q[2 * ks + 1];
    q[2 * ks] = make_uint4(a.x, a.y, b.x & ones, b.y & ones);
    q[2 * ks + 1] = make_uint4(a.z & ones, a.w & ones, b.z, b.w);
  }
}
__device__ __forceinline__ void st_tag(uint4* p, const uint4& v, uint32_t tag) {
  asm volatile("st.relaxed.gpu.global.v4.b32 [%0], {%1,%2,%3,%4};"
               ::"l"(p), "r"((v.x & ~1u) | tag), "r"(v.y), "r"(v.z), "r"(v.w) : "memory");
}
__device__ __forceinline__ void st_tag8(void* p, uint32_t x, uint32_t y, uint32_t tag) {
  asm volatile("st.relaxed.gpu.global.v2.b32 [%0], {%1,%2};" ::"l"(p), "r"((x & ~1u) | tag), "r"(y) : "memory");
}
__device__ __forceinline__ uint4 ld_b128(const uint4* p) {
  uint4 v;
  asm volatile("ld.relaxed.gpu.global.v4.b32 {%0,%1,%2,%3}, [%4];"
               : "=r"(v.x), "=r"(v.y), "=r"(v.z), "=r"(v.w) : "l"(p) : "memory");
  return v;
}
template <int STRIDE>
__device__ __forceinline__ void ld_tag4_issue(uint4 (&q)[4], const uint4* p) {
#pragma unroll
  for (int i = 0; i < 4; i++) q[i] = ld_b128(p + i * STRIDE);
}
template <int STRIDE, bool HALVES = false>
__device__ __forceinline__ void ld_tag4_finish(uint4 (&q)[4], const uint4* p, uint32_t tag) {
  int it = 0;
#pragma unroll 1
  while (__any_sync(0xffffffffu, ((q[0].x ^ tag) | (q[1].x ^ tag) | (q[2].x ^ tag) | (q[3].x ^ tag) |
                                  (HALVES ? (q[0].z ^ tag) | (q[1].z ^ tag) | (q[2].z ^ tag) | (q[3].z ^ tag) : 0u)) & 1u)) {
    ld_tag4_issue<STRIDE>(q, p);
    if (++it > SPIN_LIMIT) { die(); break; }
  }
#pragma unroll
  for (int i = 0; i < 4; i++) {
    asm volatile("and.b32 %0, %0, 0xfffffffe;" : "+r"(q[i].x));
    if (HALVES) q[i].z &= ~1u;
  }
}
__device__ __forceinline__ float quad_sum(const uint32_t (&a)[8]) {
  float d[4];
  mma16816_z(d, a[0], a[1], a[2], a[3], 0x3f803f80u, 0x3f803f80u);
  mma16816(d, a[4], a[5], a[6], a[7], 0x3f803f80u, 0x3f803f80u);
  return d[0] + d[2];
}
__device__ __forceinline__ float sum_groups(float v) {
  v += __shfl_xor_sync(0xffffffffu, v, 4);
  v += __shfl_xor_sync(0xffffffffu, v, 8);
  v += __shfl_xor_sync(0xffffffffu, v, 16);
  return v;
}
__device__ __forceinline__ uint32_t hsub2_bf16(uint32_t a, uint32_t b) {
  uint32_t r;
  asm("sub.rn.bf16x2 %0, %1, %2;" : "=r"(r) : "r"(a), "r"(b));
  return r;
}
__device__ __forceinline__ float row_rstd(const uint32_t (&c)[8], float delta) {
  uint32_t s[8];
#pragma unroll
  for (int i = 0; i < 8; i++) asm("mul.rn.bf16x2 %0, %1, %1;" : "=r"(s[i]) : "r"(c[i]));
  return rsqrtf(fmaxf(fmaf(-delta, delta, sum_groups(quad_sum(s)) * (1.f / 512.f)), 0.f) + 1e-5f);
}
__device__ __forceinline__ uint64_t desc64(uint32_t lo, uint32_t hi) {
  uint64_t d;
  asm("mov.b64 %0, {%1, %2};" : "=l"(d) : "r"(lo), "r"(hi));
  return d;
}
constexpr uint32_t desc_hi(uint32_t sbo, uint32_t swz) { return (sbo >> 4) | (swz << 30); }
__device__ __forceinline__ uint32_t desc_lo(uint32_t addr, uint32_t lbo) { return ((addr & 0x3FFFF) >> 4) | ((lbo >> 4) << 16); }
__device__ __forceinline__ void cp_async16(uint32_t dst, const void* src) {
  asm volatile("cp.async.cg.shared.global [%0], [%1], 16;" ::"r"(dst), "l"(src) : "memory");
}
__device__ __forceinline__ uint2 lds2(uint32_t a) {
  uint2 v;
  asm volatile("ld.shared.v2.u32 {%0,%1}, [%2];" : "=r"(v.x), "=r"(v.y) : "r"(a) : "memory");
  return v;
}
__device__ __forceinline__ uint32_t lds_u16(uint32_t a) {
  uint16_t v;
  asm volatile("ld.shared.u16 %0, [%1];" : "=h"(v) : "r"(a) : "memory");
  return v;
}
__device__ __forceinline__ void wg_fence() { asm volatile("wgmma.fence.sync.aligned;" ::: "memory"); }
__device__ __forceinline__ void wg_commit() { asm volatile("wgmma.commit_group.sync.aligned;" ::: "memory"); }
template <int N>
__device__ __forceinline__ void wg_wait() { asm volatile("wgmma.wait_group.sync.aligned %0;" ::"n"(N) : "memory"); }
__device__ __forceinline__ void bulk_load(uint32_t dst, const void* src, int bytes, uint32_t bar) {
  asm volatile("cp.async.bulk.shared::cluster.global.mbarrier::complete_tx::bytes [%0], [%1], %2, [%3];"
               ::"r"(dst), "l"(src), "r"(bytes), "r"(bar) : "memory");
}
__device__ __forceinline__ void bulk_load_mc(uint32_t dst, const void* src, int bytes, uint32_t bar) {
  asm volatile("cp.async.bulk.shared::cluster.global.mbarrier::complete_tx::bytes.multicast::cluster [%0], [%1], %2, [%3], %4;"
               ::"r"(dst), "l"(src), "r"(bytes), "r"(bar), "h"((uint16_t)3) : "memory");
}
__device__ __forceinline__ void tma3(uint32_t dst, const CUtensorMap* tm, uint32_t bar, int c0, int c1, int c2) {
  asm volatile("cp.async.bulk.tensor.3d.shared::cluster.global.mbarrier::complete_tx::bytes [%0], [%1, {%3,%4,%5}], [%2];"
               ::"r"(dst), "l"(tm), "r"(bar), "r"(c0), "r"(c1), "r"(c2) : "memory");
}
__device__ __forceinline__ void tma3_mc(uint32_t dst, const CUtensorMap* tm, uint32_t bar, int c1, int c2) {
  asm volatile("cp.async.bulk.tensor.3d.shared::cluster.global.mbarrier::complete_tx::bytes.multicast::cluster [%0], [%1, {%3,%4,%5}], [%2], %6;"
               ::"r"(dst), "l"(tm), "r"(bar), "r"(0), "r"(c1), "r"(c2), "h"((uint16_t)3) : "memory");
}
__device__ __forceinline__ void mbar_arrive_remote(uint32_t rb) {
  asm volatile("mbarrier.arrive.shared::cluster.b64 _, [%0];" ::"r"(rb) : "memory");
}
__device__ __forceinline__ uint4 ldg_ca4(const void* p) {
  uint4 v;
  asm volatile("ld.global.ca.v4.u32 {%0,%1,%2,%3}, [%4];" : "=r"(v.x), "=r"(v.y), "=r"(v.z), "=r"(v.w) : "l"(p) : "memory");
  return v;
}
__device__ __forceinline__ float u2f(uint32_t v) { return __uint_as_float(v); }
__device__ __forceinline__ void mma_az(float (&d)[4], const uint4& a, uint32_t b0, uint32_t b1) { mma16816_z(d, a.x, a.y, a.z, a.w, b0, b1); }
__device__ __forceinline__ void mma_a(float (&d)[4], const uint4& a, uint32_t b0, uint32_t b1) { mma16816(d, a.x, a.y, a.z, a.w, b0, b1); }
__device__ __forceinline__ uint32_t clock32() {
  uint32_t v;
  asm volatile("mov.u32 %0, %%clock;" : "=r"(v) :: "memory");
  return v;
}
__device__ __forceinline__ float swiglu(float g, float u, float r) {
  float hg = (0.5f * r) * g, th;
  asm("tanh.approx.f32 %0, %1;" : "=f"(th) : "f"(hg));
  return fmaf(hg, th, hg) * (r * u);
}
__device__ __forceinline__ void l2_prefetch(const void* p, int bytes) {
  asm volatile("cp.async.bulk.prefetch.L2.global [%0], %1;" ::"l"(p), "r"(bytes) : "memory");
}

__device__ __forceinline__ void wgmma_n256(float (&d)[128], uint64_t da, uint64_t db, int sd = 1) {
  asm volatile("{.reg .pred p; setp.ne.b32 p, %130, 0;\n"
      "wgmma.mma_async.sync.aligned.m64n256k16.f32.bf16.bf16 {"
      "%0,%1,%2,%3,%4,%5,%6,%7,%8,%9,%10,%11,%12,%13,%14,%15,"
      "%16,%17,%18,%19,%20,%21,%22,%23,%24,%25,%26,%27,%28,%29,%30,%31,"
      "%32,%33,%34,%35,%36,%37,%38,%39,%40,%41,%42,%43,%44,%45,%46,%47,"
      "%48,%49,%50,%51,%52,%53,%54,%55,%56,%57,%58,%59,%60,%61,%62,%63,"
      "%64,%65,%66,%67,%68,%69,%70,%71,%72,%73,%74,%75,%76,%77,%78,%79,"
      "%80,%81,%82,%83,%84,%85,%86,%87,%88,%89,%90,%91,%92,%93,%94,%95,"
      "%96,%97,%98,%99,%100,%101,%102,%103,%104,%105,%106,%107,%108,%109,%110,%111,"
      "%112,%113,%114,%115,%116,%117,%118,%119,%120,%121,%122,%123,%124,%125,%126,%127"
      "}, %128, %129, p, 1, 1, 0, 1;}\n"
      : "+f"(d[0]),"+f"(d[1]),"+f"(d[2]),"+f"(d[3]),"+f"(d[4]),"+f"(d[5]),"+f"(d[6]),"+f"(d[7]),
        "+f"(d[8]),"+f"(d[9]),"+f"(d[10]),"+f"(d[11]),"+f"(d[12]),"+f"(d[13]),"+f"(d[14]),"+f"(d[15]),
        "+f"(d[16]),"+f"(d[17]),"+f"(d[18]),"+f"(d[19]),"+f"(d[20]),"+f"(d[21]),"+f"(d[22]),"+f"(d[23]),
        "+f"(d[24]),"+f"(d[25]),"+f"(d[26]),"+f"(d[27]),"+f"(d[28]),"+f"(d[29]),"+f"(d[30]),"+f"(d[31]),
        "+f"(d[32]),"+f"(d[33]),"+f"(d[34]),"+f"(d[35]),"+f"(d[36]),"+f"(d[37]),"+f"(d[38]),"+f"(d[39]),
        "+f"(d[40]),"+f"(d[41]),"+f"(d[42]),"+f"(d[43]),"+f"(d[44]),"+f"(d[45]),"+f"(d[46]),"+f"(d[47]),
        "+f"(d[48]),"+f"(d[49]),"+f"(d[50]),"+f"(d[51]),"+f"(d[52]),"+f"(d[53]),"+f"(d[54]),"+f"(d[55]),
        "+f"(d[56]),"+f"(d[57]),"+f"(d[58]),"+f"(d[59]),"+f"(d[60]),"+f"(d[61]),"+f"(d[62]),"+f"(d[63]),
        "+f"(d[64]),"+f"(d[65]),"+f"(d[66]),"+f"(d[67]),"+f"(d[68]),"+f"(d[69]),"+f"(d[70]),"+f"(d[71]),
        "+f"(d[72]),"+f"(d[73]),"+f"(d[74]),"+f"(d[75]),"+f"(d[76]),"+f"(d[77]),"+f"(d[78]),"+f"(d[79]),
        "+f"(d[80]),"+f"(d[81]),"+f"(d[82]),"+f"(d[83]),"+f"(d[84]),"+f"(d[85]),"+f"(d[86]),"+f"(d[87]),
        "+f"(d[88]),"+f"(d[89]),"+f"(d[90]),"+f"(d[91]),"+f"(d[92]),"+f"(d[93]),"+f"(d[94]),"+f"(d[95]),
        "+f"(d[96]),"+f"(d[97]),"+f"(d[98]),"+f"(d[99]),"+f"(d[100]),"+f"(d[101]),"+f"(d[102]),"+f"(d[103]),
        "+f"(d[104]),"+f"(d[105]),"+f"(d[106]),"+f"(d[107]),"+f"(d[108]),"+f"(d[109]),"+f"(d[110]),"+f"(d[111]),
        "+f"(d[112]),"+f"(d[113]),"+f"(d[114]),"+f"(d[115]),"+f"(d[116]),"+f"(d[117]),"+f"(d[118]),"+f"(d[119]),
        "+f"(d[120]),"+f"(d[121]),"+f"(d[122]),"+f"(d[123]),"+f"(d[124]),"+f"(d[125]),"+f"(d[126]),"+f"(d[127])
      : "l"(da), "l"(db), "r"(sd));
}
__device__ __forceinline__ void wgmma_n192(float (&d)[96], uint64_t da, uint64_t db) {
  asm volatile("wgmma.mma_async.sync.aligned.m64n192k16.f32.bf16.bf16 {"
      "%0,%1,%2,%3,%4,%5,%6,%7,%8,%9,%10,%11,%12,%13,%14,%15,"
      "%16,%17,%18,%19,%20,%21,%22,%23,%24,%25,%26,%27,%28,%29,%30,%31,"
      "%32,%33,%34,%35,%36,%37,%38,%39,%40,%41,%42,%43,%44,%45,%46,%47,"
      "%48,%49,%50,%51,%52,%53,%54,%55,%56,%57,%58,%59,%60,%61,%62,%63,"
      "%64,%65,%66,%67,%68,%69,%70,%71,%72,%73,%74,%75,%76,%77,%78,%79,"
      "%80,%81,%82,%83,%84,%85,%86,%87,%88,%89,%90,%91,%92,%93,%94,%95"
      "}, %96, %97, 1, 1, 1, 0, 1;\n"
      : "+f"(d[0]),"+f"(d[1]),"+f"(d[2]),"+f"(d[3]),"+f"(d[4]),"+f"(d[5]),"+f"(d[6]),"+f"(d[7]),
        "+f"(d[8]),"+f"(d[9]),"+f"(d[10]),"+f"(d[11]),"+f"(d[12]),"+f"(d[13]),"+f"(d[14]),"+f"(d[15]),
        "+f"(d[16]),"+f"(d[17]),"+f"(d[18]),"+f"(d[19]),"+f"(d[20]),"+f"(d[21]),"+f"(d[22]),"+f"(d[23]),
        "+f"(d[24]),"+f"(d[25]),"+f"(d[26]),"+f"(d[27]),"+f"(d[28]),"+f"(d[29]),"+f"(d[30]),"+f"(d[31]),
        "+f"(d[32]),"+f"(d[33]),"+f"(d[34]),"+f"(d[35]),"+f"(d[36]),"+f"(d[37]),"+f"(d[38]),"+f"(d[39]),
        "+f"(d[40]),"+f"(d[41]),"+f"(d[42]),"+f"(d[43]),"+f"(d[44]),"+f"(d[45]),"+f"(d[46]),"+f"(d[47]),
        "+f"(d[48]),"+f"(d[49]),"+f"(d[50]),"+f"(d[51]),"+f"(d[52]),"+f"(d[53]),"+f"(d[54]),"+f"(d[55]),
        "+f"(d[56]),"+f"(d[57]),"+f"(d[58]),"+f"(d[59]),"+f"(d[60]),"+f"(d[61]),"+f"(d[62]),"+f"(d[63]),
        "+f"(d[64]),"+f"(d[65]),"+f"(d[66]),"+f"(d[67]),"+f"(d[68]),"+f"(d[69]),"+f"(d[70]),"+f"(d[71]),
        "+f"(d[72]),"+f"(d[73]),"+f"(d[74]),"+f"(d[75]),"+f"(d[76]),"+f"(d[77]),"+f"(d[78]),"+f"(d[79]),
        "+f"(d[80]),"+f"(d[81]),"+f"(d[82]),"+f"(d[83]),"+f"(d[84]),"+f"(d[85]),"+f"(d[86]),"+f"(d[87]),
        "+f"(d[88]),"+f"(d[89]),"+f"(d[90]),"+f"(d[91]),"+f"(d[92]),"+f"(d[93]),"+f"(d[94]),"+f"(d[95])
      : "l"(da), "l"(db));
}
template <int SD>
__device__ __forceinline__ void wgmma_rs_n128(float (&d)[64], uint32_t a0, uint32_t a1, uint32_t a2, uint32_t a3, uint64_t db) {
  asm volatile("wgmma.mma_async.sync.aligned.m64n128k16.f32.bf16.bf16 {"
      "%0,%1,%2,%3,%4,%5,%6,%7,%8,%9,%10,%11,%12,%13,%14,%15,"
      "%16,%17,%18,%19,%20,%21,%22,%23,%24,%25,%26,%27,%28,%29,%30,%31,"
      "%32,%33,%34,%35,%36,%37,%38,%39,%40,%41,%42,%43,%44,%45,%46,%47,"
      "%48,%49,%50,%51,%52,%53,%54,%55,%56,%57,%58,%59,%60,%61,%62,%63"
      "}, {%64,%65,%66,%67}, %68, %69, 1, 1, 1;\n"
      : "+f"(d[0]),"+f"(d[1]),"+f"(d[2]),"+f"(d[3]),"+f"(d[4]),"+f"(d[5]),"+f"(d[6]),"+f"(d[7]),
        "+f"(d[8]),"+f"(d[9]),"+f"(d[10]),"+f"(d[11]),"+f"(d[12]),"+f"(d[13]),"+f"(d[14]),"+f"(d[15]),
        "+f"(d[16]),"+f"(d[17]),"+f"(d[18]),"+f"(d[19]),"+f"(d[20]),"+f"(d[21]),"+f"(d[22]),"+f"(d[23]),
        "+f"(d[24]),"+f"(d[25]),"+f"(d[26]),"+f"(d[27]),"+f"(d[28]),"+f"(d[29]),"+f"(d[30]),"+f"(d[31]),
        "+f"(d[32]),"+f"(d[33]),"+f"(d[34]),"+f"(d[35]),"+f"(d[36]),"+f"(d[37]),"+f"(d[38]),"+f"(d[39]),
        "+f"(d[40]),"+f"(d[41]),"+f"(d[42]),"+f"(d[43]),"+f"(d[44]),"+f"(d[45]),"+f"(d[46]),"+f"(d[47]),
        "+f"(d[48]),"+f"(d[49]),"+f"(d[50]),"+f"(d[51]),"+f"(d[52]),"+f"(d[53]),"+f"(d[54]),"+f"(d[55]),
        "+f"(d[56]),"+f"(d[57]),"+f"(d[58]),"+f"(d[59]),"+f"(d[60]),"+f"(d[61]),"+f"(d[62]),"+f"(d[63])
      : "r"(a0), "r"(a1), "r"(a2), "r"(a3), "l"(db), "n"(SD));
}
__device__ __forceinline__ void wgmma_rs_n256(float (&d)[128], uint32_t a0, uint32_t a1, uint32_t a2, uint32_t a3, uint64_t db, int sd = 1) {
  asm volatile("{.reg .pred p; setp.ne.b32 p, %133, 0;\n"
      "wgmma.mma_async.sync.aligned.m64n256k16.f32.bf16.bf16 {"
      "%0,%1,%2,%3,%4,%5,%6,%7,%8,%9,%10,%11,%12,%13,%14,%15,"
      "%16,%17,%18,%19,%20,%21,%22,%23,%24,%25,%26,%27,%28,%29,%30,%31,"
      "%32,%33,%34,%35,%36,%37,%38,%39,%40,%41,%42,%43,%44,%45,%46,%47,"
      "%48,%49,%50,%51,%52,%53,%54,%55,%56,%57,%58,%59,%60,%61,%62,%63,"
      "%64,%65,%66,%67,%68,%69,%70,%71,%72,%73,%74,%75,%76,%77,%78,%79,"
      "%80,%81,%82,%83,%84,%85,%86,%87,%88,%89,%90,%91,%92,%93,%94,%95,"
      "%96,%97,%98,%99,%100,%101,%102,%103,%104,%105,%106,%107,%108,%109,%110,%111,"
      "%112,%113,%114,%115,%116,%117,%118,%119,%120,%121,%122,%123,%124,%125,%126,%127"
      "}, {%128,%129,%130,%131}, %132, p, 1, 1, 1;}\n"
      : "+f"(d[0]),"+f"(d[1]),"+f"(d[2]),"+f"(d[3]),"+f"(d[4]),"+f"(d[5]),"+f"(d[6]),"+f"(d[7]),
        "+f"(d[8]),"+f"(d[9]),"+f"(d[10]),"+f"(d[11]),"+f"(d[12]),"+f"(d[13]),"+f"(d[14]),"+f"(d[15]),
        "+f"(d[16]),"+f"(d[17]),"+f"(d[18]),"+f"(d[19]),"+f"(d[20]),"+f"(d[21]),"+f"(d[22]),"+f"(d[23]),
        "+f"(d[24]),"+f"(d[25]),"+f"(d[26]),"+f"(d[27]),"+f"(d[28]),"+f"(d[29]),"+f"(d[30]),"+f"(d[31]),
        "+f"(d[32]),"+f"(d[33]),"+f"(d[34]),"+f"(d[35]),"+f"(d[36]),"+f"(d[37]),"+f"(d[38]),"+f"(d[39]),
        "+f"(d[40]),"+f"(d[41]),"+f"(d[42]),"+f"(d[43]),"+f"(d[44]),"+f"(d[45]),"+f"(d[46]),"+f"(d[47]),
        "+f"(d[48]),"+f"(d[49]),"+f"(d[50]),"+f"(d[51]),"+f"(d[52]),"+f"(d[53]),"+f"(d[54]),"+f"(d[55]),
        "+f"(d[56]),"+f"(d[57]),"+f"(d[58]),"+f"(d[59]),"+f"(d[60]),"+f"(d[61]),"+f"(d[62]),"+f"(d[63]),
        "+f"(d[64]),"+f"(d[65]),"+f"(d[66]),"+f"(d[67]),"+f"(d[68]),"+f"(d[69]),"+f"(d[70]),"+f"(d[71]),
        "+f"(d[72]),"+f"(d[73]),"+f"(d[74]),"+f"(d[75]),"+f"(d[76]),"+f"(d[77]),"+f"(d[78]),"+f"(d[79]),
        "+f"(d[80]),"+f"(d[81]),"+f"(d[82]),"+f"(d[83]),"+f"(d[84]),"+f"(d[85]),"+f"(d[86]),"+f"(d[87]),
        "+f"(d[88]),"+f"(d[89]),"+f"(d[90]),"+f"(d[91]),"+f"(d[92]),"+f"(d[93]),"+f"(d[94]),"+f"(d[95]),
        "+f"(d[96]),"+f"(d[97]),"+f"(d[98]),"+f"(d[99]),"+f"(d[100]),"+f"(d[101]),"+f"(d[102]),"+f"(d[103]),
        "+f"(d[104]),"+f"(d[105]),"+f"(d[106]),"+f"(d[107]),"+f"(d[108]),"+f"(d[109]),"+f"(d[110]),"+f"(d[111]),
        "+f"(d[112]),"+f"(d[113]),"+f"(d[114]),"+f"(d[115]),"+f"(d[116]),"+f"(d[117]),"+f"(d[118]),"+f"(d[119]),
        "+f"(d[120]),"+f"(d[121]),"+f"(d[122]),"+f"(d[123]),"+f"(d[124]),"+f"(d[125]),"+f"(d[126]),"+f"(d[127])
      : "r"(a0), "r"(a1), "r"(a2), "r"(a3), "l"(db), "r"(sd));
}
__device__ __forceinline__ void wgmma_rs_n192(float (&d)[96], uint32_t a0, uint32_t a1, uint32_t a2, uint32_t a3, uint64_t db) {
  asm volatile("wgmma.mma_async.sync.aligned.m64n192k16.f32.bf16.bf16 {"
      "%0,%1,%2,%3,%4,%5,%6,%7,%8,%9,%10,%11,%12,%13,%14,%15,"
      "%16,%17,%18,%19,%20,%21,%22,%23,%24,%25,%26,%27,%28,%29,%30,%31,"
      "%32,%33,%34,%35,%36,%37,%38,%39,%40,%41,%42,%43,%44,%45,%46,%47,"
      "%48,%49,%50,%51,%52,%53,%54,%55,%56,%57,%58,%59,%60,%61,%62,%63,"
      "%64,%65,%66,%67,%68,%69,%70,%71,%72,%73,%74,%75,%76,%77,%78,%79,"
      "%80,%81,%82,%83,%84,%85,%86,%87,%88,%89,%90,%91,%92,%93,%94,%95"
      "}, {%96,%97,%98,%99}, %100, 1, 1, 1, 1;\n"
      : "+f"(d[0]),"+f"(d[1]),"+f"(d[2]),"+f"(d[3]),"+f"(d[4]),"+f"(d[5]),"+f"(d[6]),"+f"(d[7]),
        "+f"(d[8]),"+f"(d[9]),"+f"(d[10]),"+f"(d[11]),"+f"(d[12]),"+f"(d[13]),"+f"(d[14]),"+f"(d[15]),
        "+f"(d[16]),"+f"(d[17]),"+f"(d[18]),"+f"(d[19]),"+f"(d[20]),"+f"(d[21]),"+f"(d[22]),"+f"(d[23]),
        "+f"(d[24]),"+f"(d[25]),"+f"(d[26]),"+f"(d[27]),"+f"(d[28]),"+f"(d[29]),"+f"(d[30]),"+f"(d[31]),
        "+f"(d[32]),"+f"(d[33]),"+f"(d[34]),"+f"(d[35]),"+f"(d[36]),"+f"(d[37]),"+f"(d[38]),"+f"(d[39]),
        "+f"(d[40]),"+f"(d[41]),"+f"(d[42]),"+f"(d[43]),"+f"(d[44]),"+f"(d[45]),"+f"(d[46]),"+f"(d[47]),
        "+f"(d[48]),"+f"(d[49]),"+f"(d[50]),"+f"(d[51]),"+f"(d[52]),"+f"(d[53]),"+f"(d[54]),"+f"(d[55]),
        "+f"(d[56]),"+f"(d[57]),"+f"(d[58]),"+f"(d[59]),"+f"(d[60]),"+f"(d[61]),"+f"(d[62]),"+f"(d[63]),
        "+f"(d[64]),"+f"(d[65]),"+f"(d[66]),"+f"(d[67]),"+f"(d[68]),"+f"(d[69]),"+f"(d[70]),"+f"(d[71]),
        "+f"(d[72]),"+f"(d[73]),"+f"(d[74]),"+f"(d[75]),"+f"(d[76]),"+f"(d[77]),"+f"(d[78]),"+f"(d[79]),
        "+f"(d[80]),"+f"(d[81]),"+f"(d[82]),"+f"(d[83]),"+f"(d[84]),"+f"(d[85]),"+f"(d[86]),"+f"(d[87]),
        "+f"(d[88]),"+f"(d[89]),"+f"(d[90]),"+f"(d[91]),"+f"(d[92]),"+f"(d[93]),"+f"(d[94]),"+f"(d[95])
      : "r"(a0), "r"(a1), "r"(a2), "r"(a3), "l"(db));
}


constexpr int C_LN = 0, C_PX = 16, C_PY = 32;
constexpr int NB_CONS = 1, NB_LN = 2, NB_LAG = 4, NB_INIT = 6, NB_RDY = 7, NB_WG = 8;
constexpr int LAGX = 3;
constexpr int LAGY = 3;
constexpr int LAG2 = 5;
constexpr int NLL = 2;
constexpr int POLL_DELAY3 = 600;
constexpr int POLL_DELAY = 1200;
constexpr int FILT_DELAY = 800;
constexpr int WARM = 4;
constexpr int ALEAD = 6;
constexpr int POLL_DELAY2 = 1000;
constexpr int REDPOS = 4;
constexpr int XTRIG = 20;
constexpr int HTRIG = 0;
constexpr int RING_SIG = 1;
constexpr int PF2_SIG = 1;
constexpr int SM_E = 0, SM_X = 16384, SM_E2 = 32768, SM_W = 49152, SM_FC = 69632, SM_T = 73728 - T1_BYTES;
constexpr unsigned long long KORDER = 0xBA9432DC876510ull;
constexpr unsigned long long BSLOT = 0xA852140A852140ull, PSLOT = 0x9DCB7639DCB763ull;
constexpr uint32_t BDEP = 0xFE97531, PDEP = 0xFCBA754;
constexpr uint32_t HI128 = desc_hi(1024, 1), HI64 = desc_hi(512, 2);

struct Bars {
  uint64_t full1[32], empty1[32], full2[16], fullA[8], empty2[8], fullP[32], emptyP[8], hbar, tbar, hint[3], sig[2], sbar, freeA[4];
  uint32_t epoch, pad;
};

template <int NK, bool STORE, int J0 = 0, int J1 = NK>
__device__ __forceinline__ void make_p(const float (&acc)[NK * 16], float r0, float r1, uint4 (&p)[NK], uint4* pbase, int ks0, uint32_t tag) {
#pragma unroll
  for (int j = J0; j < J1; j++) {
    uint32_t w[4];
#pragma unroll
    for (int i = 0; i < 4; i++) {
      const int a = 8 * j + 2 * i, b = a + NK * 8;
      w[i] = pack2(swiglu(acc[a], acc[b], (i & 1) ? r1 : r0), swiglu(acc[a + 1], acc[b + 1], (i & 1) ? r1 : r0));
    }
    asm volatile("" : "+r"(w[0]), "+r"(w[1]), "+r"(w[2]), "+r"(w[3]));
    p[j] = make_uint4(w[0], w[1], w[2], w[3]);
    if (STORE) st_tag(pbase + ((ks0 + j) >> 2) * 1024 + ((ks0 + j) & 3) * 32, p[j], tag);
  }
}
__device__ __forceinline__ void spin_until(uint32_t t) {
  while ((int)(clock32() - t) < 0) {}
}

__global__ void __cluster_dims__(2, 1, 1) __launch_bounds__(NTHREADS, 1)
fused_kernel(const __nv_bfloat16* __restrict__ x, const Tables* __restrict__ tab, Scratch* __restrict__ scr,
             __nv_bfloat16* __restrict__ out, const char* __restrict__ wg_raw, const char* __restrict__ wu_raw,
             const char* __restrict__ wd_raw,
             const __grid_constant__ CUtensorMap tmWR, const __grid_constant__ CUtensorMap tmWI,
             const __grid_constant__ CUtensorMap tmGX, const __grid_constant__ CUtensorMap tmUX,
             const __grid_constant__ CUtensorMap tmGY, const __grid_constant__ CUtensorMap tmUY,
             const __grid_constant__ CUtensorMap tmD) {
  extern __shared__ __align__(1024) char smem_raw[];
  const uint32_t sbase = s2u(smem_raw);
  const uint32_t sbar = sbase + 14 * SLOT, sstat = sbar + 1408;
  const int tid = threadIdx.x, lane = tid & 31;
  const int c = blockIdx.x, rk = c & 1, f = (c >> 1) & 7, rb = 2 * (c >> 4) + rk;
  const int rb2 = 2 * (c >> 4) + (f >> 2), kh = (f >> 1) & 1, nq = 2 * (f & 1) + rk;
#define BAR(field, i) (sbar + (uint32_t)offsetof(Bars, field) + 8u * (i))
#define TOFF(field) (sbase + SM_T + (uint32_t)offsetof(Tables, field) + lane * 16)

  if (tid >= 256) {
    asm volatile("setmaxnreg.dec.sync.aligned.u32 40;");
    const int warp = __shfl_sync(0xffffffffu, tid >> 5, 0);
    if (lane == 0) {
      if (warp == 8) {
        if (sbase & 1023) die();
#pragma unroll
        for (int i = 0; i < 20; i++) mbar_init(BAR(emptyP, i), i < 8 ? 8 : i < 13 ? 1 : i == 15 ? 32 : i < 15 ? 8 : 16);
        mbar_expect(BAR(tbar, 0), T2_BYTES + 2 * 10240);
        mbar_expect(BAR(hbar, 0), 16384);
      } else if (warp == 9) {
#pragma unroll
        for (int i = 0; i < 32; i++) mbar_init(BAR(full1, i), 1);
#pragma unroll
        for (int i = 0; i < 32; i++) mbar_expect(BAR(full1, i), i < 16 ? 16384 : 12288);
      } else if (warp == 10) {
#pragma unroll
        for (int i = 0; i < 32; i++) mbar_init(BAR(empty1, i), 16);
#pragma unroll
        for (int i = 0; i < 30; i++) mbar_init(BAR(fullP, i), 1);
#pragma unroll
        for (int i = 0; i < 30; i++) mbar_expect(BAR(fullP, i), 8192);
      } else {
#pragma unroll
        for (int i = 0; i < 32; i++) mbar_init(BAR(full2, i), i < 24 ? 1 : 8);
#pragma unroll
        for (int i = 0; i < 24; i++) mbar_expect(BAR(full2, i), 16384);
      }
      asm volatile("fence.mbarrier_init.release.cluster;" ::: "memory");
    }
    if (tid == 256) {
      const int w0 = ((c >> 3) * 257 + 32 * (c & 7) + 1) & ~7;
      if (FILT_DELAY) {
        asm volatile("prefetch.tensormap [%0];" ::"l"(&tmWR) : "memory");
        asm volatile("prefetch.tensormap [%0];" ::"l"(&tmWI) : "memory");
        spin_until(clock32() + FILT_DELAY);
      }
      tma3(sbase + SM_W, &tmWR, BAR(tbar, 0), w0, 0, 0);
      tma3(sbase + SM_W + 10240, &tmWI, BAR(tbar, 0), w0, 0, 0);
      bulk_load(sbase + SM_T + T1_BYTES, reinterpret_cast<const char*>(tab) + T1_BYTES, T2_BYTES, BAR(tbar, 0));
    }
    if (tid == 288) {
      asm volatile("prefetch.tensormap [%0];" ::"l"(rk ? &tmUX : &tmGX) : "memory");
      asm volatile("prefetch.tensormap [%0];" ::"l"(rk ? &tmUY : &tmGY) : "memory");
      asm volatile("prefetch.tensormap [%0];" ::"l"(&tmD) : "memory");
    }
    if (tid == 320) {
      const unsigned e = ld_relaxed(&scr->cnt[(C_LN + rb) * 32]) >> 3;
      asm volatile("st.shared.u32 [%0], %1;" ::"r"(BAR(epoch, 0)), "r"(e) : "memory");
    }
    __syncwarp();
    asm volatile("barrier.cluster.arrive.relaxed.aligned;" ::: "memory");
    bar_arrive(NB_RDY, 384);
    asm volatile("barrier.cluster.wait.aligned;" ::: "memory");
    bar_sync(NB_INIT, 384);
    unsigned epoch;
    asm volatile("ld.shared.u32 %0, [%1];" : "=r"(epoch) : "r"(BAR(epoch, 0)) : "memory");
    if (warp == 8) {
      if (lane == 0) {
        const int ax = (7 * f + 3 * (f & 1)) >> 1;
        const int ay = 7 * f + ((f & 1) ? 0 : 4);
        const CUtensorMap* tx = rk ? &tmUX : &tmGX;
        const CUtensorMap* ty = rk ? &tmUY : &tmGY;
        if (RING_SIG >= 0) mbar_wait(BAR(sig, RING_SIG));
        uint32_t s = 2;
#pragma unroll 1
        for (int n = 0; n < 16; n++) {
          if (n >= 6) mbar_wait(BAR(empty1, n - 6));
          tma3_mc(sbase + (8 + s) * SLOT + rk * 8192, tx, BAR(full1, n), n * 32, ax);
          if (++s == 6) s = 0;
          if (n >= 10 && n < 15) {
            const int k = n - 10;
            mbar_wait(BAR(freeA, (12 * k + 11) >> 4));
            tma3_mc(sbase + k * 12288 + rk * 6144, ty, BAR(full1, 16 + k), (k + 8) * 32, ay);
          }
        }
#pragma unroll 1
        for (int k = 5; k < 16; k++) {
          mbar_wait(BAR(empty1, k < 13 ? 10 + ((12 * (k - 5) + 11) >> 4) : 8 + k));
          tma3_mc(sbase + 8 * SLOT + ((k - 5) & 7) * 12288 + rk * 6144, ty, BAR(full1, 16 + k), ((k + 8) & 15) * 32, ay);
        }
      }
    } else if (warp == 9) {
      if (lane == 0) {
        mbar_wait(BAR(fullA, 4));
        wait_counter(&scr->cnt[(C_LN + rb2) * 32], (epoch + 1) * 8);
        asm volatile("fence.proxy.async.global;" ::: "memory");
#pragma unroll 1
        for (int i = 0; i < 14; i++) {
          const int kblk = 14 * kh + (int)((KORDER >> (4 * i)) & 15);
          mbar_wait(i < 7 ? BAR(empty1, 16 + ((BDEP >> (4 * i)) & 15)) : BAR(empty2, i - 7));
          tma3(sbase + (uint32_t)((BSLOT >> (4 * i)) & 15) * SLOT, &tmD, BAR(full2, i), 0, 64 * kblk, 2 * nq);
        }
        mbar_wait(BAR(emptyP, 7));
        bulk_load(sbase + 3 * SLOT, &scr->LN[(rb2 * 8 + 2 * nq) * 1024 + kh * 512], 8192, BAR(hbar, 0));
        bulk_load(sbase + 3 * SLOT + 8192, &scr->LN[(rb2 * 8 + 2 * nq + 1) * 1024 + kh * 512], 8192, BAR(hbar, 0));
      }
    } else if (warp == 10) {
      bar_sync(NB_LN, 288);
      if (lane == 0) {
        red_release(&scr->cnt[(C_LN + rb) * 32]);
        wait_counter(&scr->cnt[(C_LN + rb) * 32], (epoch + 1) * 8);
        asm volatile("fence.proxy.async.global;" ::: "memory");
#pragma unroll 1
        for (int kb = NLL; kb < 8; kb++) {
          if (2 * kb >= ALEAD) mbar_wait(BAR(empty1, 2 * kb - ALEAD));
          bulk_load(sbase + kb * SLOT, &scr->LN[(rb * 8 + kb) * 1024], 16384, BAR(fullA, kb));
        }
#pragma unroll 1
        for (int s = 0; s < 14; s++) {
          const int kblk = 14 * kh + (int)((KORDER >> (4 * s)) & 15);
          if (s == 0 || s == 8 || s == 11) {
            mbar_wait(BAR(hint, s == 0 ? 0 : s == 8 ? 1 : 2), 0);
          }
          mbar_wait(s < 7 ? BAR(empty1, 16 + ((PDEP >> (4 * s)) & 15)) : BAR(emptyP, s - 7));
          bulk_load_mc(sbase + (uint32_t)((PSLOT >> (4 * s)) & 15) * SLOT + rk * 8192, &scr->P[(rb2 * 28 + kblk) * 1024 + rk * 512], 8192, BAR(fullP, 16 * rk + s));
        }
      }
    } else {
      if (lane == 0) {
        mbar_wait(BAR(tbar, 0));
        l2_prefetch(wg_raw + (size_t)c * 5376, 5376);
        l2_prefetch(wu_raw + (size_t)c * 5376, 5376);
        mbar_wait(BAR(sig, PF2_SIG), 0);
        l2_prefetch(wg_raw + 688128 + (size_t)c * 8960, 8960);
        l2_prefetch(wu_raw + 688128 + (size_t)c * 8960, 8960);
      }
      mbar_wait(BAR(fullA, 4), 0);
      if (lane == 0) l2_prefetch(wd_raw + (size_t)c * 14336, 14336);
      {
        const uint32_t tag = (epoch + 1) & 1;
        uint4 v0, v1, v2;
        int it = 0;
        while (true) {
          v0 = ld_b128(&scr->ST[rb * 64 + lane]);
          v1 = ld_b128(&scr->ST[rb * 64 + 32 + lane]);
          v2 = ld_b128(&scr->ST[rb2 * 64 + 32 * kh + lane]);
          if (!__any_sync(0xffffffffu, ((v0.x ^ tag) | (v1.x ^ tag) | (v2.x ^ tag)) & 1u)) break;
          if (++it > SPIN_LIMIT) { die(); break; }
        }
        sts4(sstat + lane * 16, v0.x & ~1u, v0.y, v0.z, v0.w);
        sts4(sstat + 512 + lane * 16, v1.x & ~1u, v1.y, v1.z, v1.w);
        sts4(sstat + 1024 + lane * 16, v2.x & ~1u, v2.y, v2.z, v2.w);
        mbar_arrive(BAR(sbar, 0));
      }
      if (lane == 0) {
        mbar_wait(BAR(empty1, XTRIG));
        int it = 0;
        while ((int)(ld_relaxed(&scr->cnt[(C_PX + rb2) * 32 + kh]) - (epoch + 1) * 32) < 0) {
          if (++it > SPIN_LIMIT) { die(); break; }
        }
        mbar_arrive(BAR(hint, 0));
        mbar_wait(BAR(emptyP, HTRIG));
        uint32_t done = 0;
        while (done != 3) {
          uint2 v;
          asm volatile("ld.relaxed.gpu.global.v2.u32 {%0,%1}, [%2];" : "=r"(v.x), "=r"(v.y) : "l"(&scr->cnt[(C_PY + rb2) * 32 + 4 * (rk ^ kh ^ 1) + 2 * kh]) : "memory");
          if (!(done & 1) && (int)(v.x - (epoch + 1) * 8) >= 0) { done |= 1; mbar_arrive(BAR(hint, 1)); }
          if (!(done & 2) && (int)(v.y - (epoch + 1) * 8) >= 0) { done |= 2; mbar_arrive(BAR(hint, 2)); }
          if (++it > SPIN_LIMIT) { die(); break; }
        }
      }
    }
  } else {
    const int warp = __shfl_sync(0xffffffffu, tid >> 5, 0);
    const int g = lane >> 2, t = lane & 3;
    uint4 fa[4], fb[4], tw[6];
#pragma unroll
    for (int i = 0; i < 4; i++) fa[i] = ldg_ca4(&tab->fa[i][lane][0]);
#pragma unroll
    for (int i = 0; i < 6; i++) tw[i] = ldg_ca4(&tab->tw1[i][lane][0]);
#pragma unroll
    for (int i = 0; i < 4; i++) fb[i] = ldg_ca4(&tab->fb[i][lane][0]);
#pragma unroll
    for (int i = 0; i < 4; i++) {
      const int r = i >> 1, ch = (i & 1) * 32 + lane;
      cp_async16(sbase + SM_X + (2 * warp + r) * 1024 + ((ch ^ ((ch >> 3) & 1)) * 16),
                 x + (size_t)(c + 128 * (2 * warp + r)) * 512 + ch * 8);
    }
    asm volatile("cp.async.commit_group;" ::: "memory");
    asm volatile("barrier.cluster.arrive.relaxed.aligned;" ::: "memory");
    uint32_t rbar;
    asm volatile("mapa.shared::cluster.u32 %0, %1, %2;" : "=r"(rbar) : "r"(sbar), "r"(rk ^ 1));
#define RBAR(field, i) (rbar + (uint32_t)offsetof(Bars, field) + 8u * (i))
    {
      const int ln = (tid >> 1) & 31, lg = ln >> 2, lt = ln & 3, i = 4 * (tid >> 6) + 2 * (tid & 1);
      const int kidx = lt + 8 * (i >> 3), nidx = 4 * ((i >> 1) & 3) + (lg >> 1);
      const uint32_t a0 = cfrag<2048>((c + 128 * kidx) * nidx, lg & 1), a1 = cfrag<2048>((c + 128 * (kidx + 4)) * nidx, lg & 1);
      const uint32_t b0 = cfrag<2048>(-(c + 128 * nidx) * kidx, lg & 1), b1 = cfrag<2048>(-(c + 128 * nidx) * (kidx + 4), lg & 1);
      asm volatile("st.shared.v2.u32 [%0], {%1,%2};" ::"r"(sbase + SM_FC + tid * 8), "r"(a0), "r"(a1) : "memory");
      asm volatile("st.shared.v2.u32 [%0], {%1,%2};" ::"r"(sbase + SM_FC + 2048 + tid * 8), "r"(b0), "r"(b1) : "memory");
    }
    bar_sync(NB_CONS, 256);
    uint4 fc[4];
#pragma unroll
    for (int i = 0; i < 4; i++) fc[i] = lds4(sbase + SM_FC + i * 512 + lane * 16);
    asm volatile("cp.async.wait_group 0;" ::: "memory");
    __syncwarp();
    bar_arrive(NB_INIT, 384);
    uint32_t tag, ones;
    uint4 q[4], o[4];
    {
      uint32_t v[2][8];
#pragma unroll
      for (int r = 0; r < 2; r++)
#pragma unroll
        for (int ks = 0; ks < 2; ks++) {
          const int ch = 32 * ks + 2 * (lane & 15) + (lane >> 4);
          asm volatile("ldmatrix.sync.aligned.m8n8.x4.trans.shared.b16 {%0,%1,%2,%3}, [%4];"
                       : "=r"(v[r][4 * ks]), "=r"(v[r][4 * ks + 1]), "=r"(v[r][4 * ks + 2]), "=r"(v[r][4 * ks + 3])
                       : "r"(sbase + SM_X + (2 * warp + r) * 1024 + ((ch ^ ((ch >> 3) & 1)) * 16)) : "memory");
        }
      float sq[2];
#pragma unroll
      for (int r = 0; r < 2; r++) {
        float s0 = 0.f, s1 = 0.f;
#pragma unroll
        for (int i = 0; i < 8; i++) {
          const float lo = bf_lo(v[r][i]), hi = u2f(v[r][i] & 0xffff0000u);
          s0 = fmaf(lo, lo, s0);
          s1 = fmaf(hi, hi, s1);
        }
        sq[r] = s0 + s1;
      }
      {
        float w = ((lane & 1) ? sq[1] : sq[0]) + __shfl_xor_sync(0xffffffffu, (lane & 1) ? sq[0] : sq[1], 1);
        w += __shfl_xor_sync(0xffffffffu, w, 2);
        w = sum_groups(w);
        const float o2 = __shfl_xor_sync(0xffffffffu, w, 1);
        sq[0] = (lane & 1) ? o2 : w;
        sq[1] = (lane & 1) ? w : o2;
      }
#pragma unroll
      for (int r = 0; r < 2; r++) {
        float dd[2][4], ee[2][4];
#pragma unroll
        for (int nt = 0; nt < 2; nt++) {
          mma_az(dd[nt], fa[0], v[r][2 * nt], v[r][2 * nt + 1]);
          mma_a(dd[nt], fa[1], v[r][4 + 2 * nt], v[r][5 + 2 * nt]);
          mma_az(ee[nt], fa[2], v[r][2 * nt], v[r][2 * nt + 1]);
          mma_a(ee[nt], fa[3], v[r][4 + 2 * nt], v[r][5 + 2 * nt]);
        }
        float mean = (dd[0][0] + dd[0][1]) + (dd[1][0] + dd[1][1]);
        mean += __shfl_xor_sync(0xffffffffu, mean, 1);
        mean += __shfl_xor_sync(0xffffffffu, mean, 2);
        mean = __shfl_sync(0xffffffffu, mean, 0) * (1.f / 512.f);
        const float rs = rsqrtf(fmaxf(fmaf(-mean, mean, sq[r] * (1.f / 512.f)), 0.f) + 1e-5f);
        float acc[4][4];
#pragma unroll
        for (int nt = 0; nt < 2; nt++) {
          const float (&d)[4] = dd[nt];
          const float (&e)[4] = ee[nt];
          const uint4 &ka = tw[2 * nt], &kb = tw[2 * nt + 1], &kc = tw[4 + nt];
          const uint32_t a0 = pack2(d[0] * u2f(ka.x) + d[2] * u2f(ka.y), d[1] * u2f(kb.x) + d[3] * u2f(kb.y));
          const uint32_t a2 = pack2(d[0] * u2f(ka.z) + d[2] * u2f(ka.w), d[1] * u2f(kb.z) + d[3] * u2f(kb.w));
          const uint32_t a1 = pack2(e[0] * u2f(kc.x) + e[2] * u2f(kc.y), e[1] * u2f(kc.z) + e[3] * u2f(kc.w));
          const uint32_t a3 = pack2(e[2] * u2f(kc.x) - e[0] * u2f(kc.y), e[3] * u2f(kc.z) - e[1] * u2f(kc.w));
          const uint32_t dc = pack2(fmaf(mean, -32.f, d[0]), fmaf(mean, -32.f, d[1]));
          const uint32_t h0 = g == 0 ? dc : a0, h2 = g == 0 ? 0u : a2;
          if (nt == 0) {
            mma16816_z(acc[0], a0, a1, a2, a3, fb[2 * nt].x, fb[2 * nt].y);
            mma16816_z(acc[1], a0, a1, a2, a3, fb[2 * nt].z, fb[2 * nt].w);
            mma16816_z(acc[2], h0, a1, h2, a3, fb[2 * nt + 1].x, fb[2 * nt + 1].y);
            mma16816_z(acc[3], h0, a1, h2, a3, fb[2 * nt + 1].z, fb[2 * nt + 1].w);
          } else {
            mma16816(acc[0], a0, a1, a2, a3, fb[2 * nt].x, fb[2 * nt].y);
            mma16816(acc[1], a0, a1, a2, a3, fb[2 * nt].z, fb[2 * nt].w);
            mma16816(acc[2], h0, a1, h2, a3, fb[2 * nt + 1].x, fb[2 * nt + 1].y);
            mma16816(acc[3], h0, a1, h2, a3, fb[2 * nt + 1].z, fb[2 * nt + 1].w);
          }
        }
#pragma unroll
        for (int h = 0; h < 2; h++) {
          const int j = 2 * warp + r, m = 2 * t + h;
          sts4(sbase + SM_E + ((j * 8 + m) * 8 + (g ^ (2 * t) ^ (2 * (j & 3)))) * 16,
               pack2(acc[h][0] * rs, acc[h][1] * rs), pack2(acc[h][2] * rs, acc[h][3] * rs),
               pack2(acc[2 + h][0] * rs, acc[2 + h][1] * rs), pack2(acc[2 + h][2] * rs, acc[2 + h][3] * rs));
        }
      }
      bar_sync(NB_RDY, 384);
      const uint32_t ea = sbase + SM_E + ((t * 8 + warp) * 8 + (g ^ (warp & 6) ^ (2 * t))) * 16;
      lds_frag(q[0], q[1], ea, ea + 4096);
      lds_frag(q[2], q[3], ea + 8192, ea + 12288);
      asm volatile("ld.shared.u32 %0, [%1];" : "=r"(tag) : "r"(BAR(epoch, 0)) : "memory");
      ones = ~(tag >> 31);
      tag = (tag + 1) & 1;
      cdft16(q, fc, o);
#pragma unroll
      for (int vv = 0; vv < 4; vv++) {
        o[vv].y &= ~1u;
        o[vv].z = (o[vv].z & ~1u) | (tag ^ 1);
        st_tag(&scr->Z1[(((4 * vv + t) * 8 + warp) * 128 + c) * 8 + g], o[vv], tag);
      }
    }
    asm volatile("setmaxnreg.inc.sync.aligned.u32 232;");
    {
      uint4* const zp = &scr->Z1[(c * 128 + 8 * t + warp) * 8 + g];
      const uint32_t tst = clock32();
      mbar_wait(BAR(tbar, 0), 0);
      uint4 f2[4], g2[4];
#pragma unroll
      for (int i = 0; i < 4; i++) {
        f2[i] = lds4(TOFF(f2) + warp * 2048 + i * 512);
        g2[i] = lds4(TOFF(g2) + warp * 2048 + i * 512);
      }
      const uint4 f8 = lds4(TOFF(f8)), g8 = lds4(TOFF(g8));
      asm volatile("barrier.cluster.wait.aligned;" ::: "memory");
      spin_until(tst + POLL_DELAY);
      ld_tag4_issue<256>(q, zp);
      float wfr[16], wfi[16];
      {
        const float nyq = ((c & 7) == 7 && g == 0) ? 0.5f : 1.f;
        uint32_t wa = sbase + SM_W + (16 * warp + t) * 80 + ((2 * (c >> 3) + 2) & 15) - 2;
        asm volatile("" : "+r"(wa));
        const uint32_t wb[3] = {wa + 2 * (g == 0 ? 16 : g), wa + 2 * g, wa - 2 * g};
#pragma unroll
        for (int i = 0; i < 16; i++) {
          const int ci = i >> 3, dd = (i >> 2) & 1, e = i & 3;
          const uint32_t a = wb[e < 2 ? e : 2] + (ci * 8 + 4 * dd) * 80 + (e == 0 ? 0 : e == 1 ? 16 : e == 2 ? 64 : 48);
          wfr[i] = bf_lo(lds_u16(a)) * (e == 2 ? nyq : 1.f);
          wfi[i] = bf_lo(lds_u16(a + 10240)) * (e == 2 ? nyq : 1.f);
        }
      }
      ld_tag4_finish<256>(q, zp, tag);
      if (lane == 0) mbar_arrive(BAR(sig, 0));
#pragma unroll
      for (int i = 0; i < 4; i++) q[i].z &= ~1u;
      reg_frag(q, ones);
      cdft16(q, f2, o);
      const uint32_t e2 = sbase + SM_E2;
#pragma unroll
      for (int vv = 0; vv < 4; vv++)
        sts4(e2 + ((warp * 16 + 4 * vv + t) * 8 + (g ^ (2 * t) ^ (2 * (warp & 3)))) * 16, o[vv].x, o[vv].y, o[vv].z, o[vv].w);
      bar_sync(NB_CONS, 256);
      uint32_t ad[2], res[2][2][4];
#pragma unroll
      for (int ci = 0; ci < 2; ci++) {
        const int cc = 2 * warp + ci;
        ad[ci] = e2 + ((t * 16 + cc) * 8 + (g ^ (2 * (cc & 3)) ^ (2 * t))) * 16;
        lds_frag(q[2 * ci], q[2 * ci + 1], ad[ci], ad[ci] + 8192);
      }
#pragma unroll
      for (int ci = 0; ci < 2; ci++)
#pragma unroll
        for (int p = 0; p < 2; p++) {
          uint32_t y[2][2];
#pragma unroll
          for (int vv = 0; vv < 2; vv++) {
            float d[4];
            mma_az(d, q[2 * ci + p], word(f8, 2 * vv), word(f8, 2 * vv + 1));
#pragma unroll
            for (int rr = 0; rr < 2; rr++) {
              const float fr = wfr[ci * 8 + vv * 4 + 2 * p + rr], fi = wfi[ci * 8 + vv * 4 + 2 * p + rr];
              y[vv][rr] = pack2(d[2 * rr] * fr - d[2 * rr + 1] * fi, d[2 * rr] * fi + d[2 * rr + 1] * fr);
            }
          }
#pragma unroll
          for (int vv = 0; vv < 2; vv++) {
            float d[4];
            mma16816_z(d, y[0][0], y[0][1], y[1][0], y[1][1], word(g8, 2 * vv), word(g8, 2 * vv + 1));
            res[ci][vv][2 * p] = pack2(d[0], d[1]);
            res[ci][vv][2 * p + 1] = pack2(d[2], d[3]);
          }
        }
#pragma unroll
      for (int i = 0; i < 4; i++)
        sts4(ad[i >> 1] + (i & 1) * 8192, res[i >> 1][i & 1][0], res[i >> 1][i & 1][1], res[i >> 1][i & 1][2], res[i >> 1][i & 1][3]);
      bar_sync(NB_CONS, 256);
      const uint32_t eb = e2 + ((warp * 16 + t) * 8 + (g ^ (2 * t) ^ (2 * (warp & 3)))) * 16;
      lds_frag(q[0], q[1], eb, eb + 512);
      lds_frag(q[2], q[3], eb + 1024, eb + 1536);
      cdft16(q, g2, o);
#pragma unroll
      for (int vv = 0; vv < 4; vv++) {
        o[vv].y &= ~1u;
        o[vv].z = (o[vv].z & ~1u) | tag;
        st_tag(zp + vv * 256, o[vv], tag);
      }
    }
    {
      const uint4* const zp = &scr->Z1[((t * 8 + warp) * 128 + c) * 8 + g];
      const uint32_t tst = clock32();
      uint4 gb[4], ga[4], gc[4], tw[4];
      uint2 xr[2][4];
      uint2* lnp[2];
#pragma unroll
      for (int r = 0; r < 2; r++) {
        const int row = 16 * f + 2 * warp + r;
        lnp[r] = reinterpret_cast<uint2*>(&scr->LN[(rb * 8 + (g >> 2)) * 1024 + row * 8 + ((2 * (g & 3) + (t >> 1)) ^ (row & 7))]) + (t & 1);
        asm volatile("" : "+l"(lnp[r]));
      }
#pragma unroll
      for (int i = 0; i < 4; i++) {
        gc[i] = lds4(sbase + SM_FC + 2048 + i * 512 + lane * 16);
        gb[i] = lds4(TOFF(gb) + i * 512);
        ga[i] = lds4(TOFF(ga) + i * 512);
        tw[i] = lds4(TOFF(tw3) + i * 512);
        const int ch = 2 * (g + 8 * i) + (t >> 1);
#pragma unroll
        for (int r = 0; r < 2; r++) xr[r][i] = lds2(sbase + SM_X + (2 * warp + r) * 1024 + ((ch ^ ((ch >> 3) & 1)) * 16) + (t & 1) * 8);
      }
      spin_until(tst + POLL_DELAY2);
      ld_tag4_issue<32768>(q, zp);
      ld_tag4_finish<32768, true>(q, zp, tag);
      if (lane == 0) mbar_arrive(BAR(sig, 1));
      reg_frag(q, ones);
      cdft16(q, gc, o);
#pragma unroll
      for (int vv = 0; vv < 4; vv++)
        sts4(sbase + SM_E + (((4 * vv + t) * 8 + warp) * 8 + (g ^ (warp & 6) ^ (2 * t))) * 16, o[vv].x, o[vv].y, o[vv].z, o[vv].w);
      bar_sync(NB_CONS, 256);
      uint32_t hv[2][8];
      const float mk = t == 0 ? 0.f : 1.f;
#pragma unroll
      for (int r = 0; r < 2; r++) {
        const int j = 2 * warp + r;
        uint4 u[2];
#pragma unroll
        for (int h = 0; h < 2; h++) u[h] = lds4(sbase + SM_E + ((j * 8 + 2 * t + h) * 8 + (g ^ (2 * t) ^ (2 * (j & 3)))) * 16);
        const uint32_t bp[4][2] = {{u[0].x, u[1].x & ones}, {u[0].y & ones, u[1].y}, {u[0].z, u[1].z & ones}, {u[0].w & ones, u[1].w}};
        float y[2][2][4];
#pragma unroll
        for (int i = 0; i < 2; i++) {
          float lo[4], hi[4], e[4];
          mma_az(lo, gb[2 * i], bp[0][0], bp[0][1]);
          mma_az(hi, gb[2 * i + 1], bp[2][0], bp[2][1]);
          mma_az(e, gb[2 * i], bp[1][0], bp[1][1]);
          mma_a(e, gb[2 * i + 1], bp[3][0], bp[3][1]);
          const uint4 &ka = tw[2 * i], &kb = tw[2 * i + 1];
          const float tr0 = fmaf(hi[0], mk, lo[0]), ti0 = fmaf(hi[2], mk, lo[2]);
          const float tr1 = lo[1] + hi[1], ti1 = lo[3] + hi[3];
          const float vr0 = tr0 * u2f(ka.x) - ti0 * u2f(ka.y), vi0 = tr0 * u2f(ka.y) + ti0 * u2f(ka.x);
          const float vr1 = tr1 * u2f(ka.z) - ti1 * u2f(ka.w), vi1 = tr1 * u2f(ka.w) + ti1 * u2f(ka.z);
          const uint32_t b0 = pack2(t == 0 ? hi[0] : vr0, vr1), b1 = pack2(t == 0 ? vr0 : vi0, vi1);
          const uint32_t b2 = pack2(e[0] * u2f(kb.x) - e[2] * u2f(kb.y), e[1] * u2f(kb.z) - e[3] * u2f(kb.w));
          const uint32_t b3 = pack2(e[0] * u2f(kb.y) + e[2] * u2f(kb.x), e[1] * u2f(kb.w) + e[3] * u2f(kb.z));
#pragma unroll
          for (int mt = 0; mt < 2; mt++) {
            mma_az(y[mt][i], ga[2 * mt], b0, b1);
            mma_a(y[mt][i], ga[2 * mt + 1], b2, b3);
          }
        }
#pragma unroll
        for (int i = 0; i < 4; i++) {
          hv[r][2 * i] = hadd2_bf16(xr[r][i].x, pack2(y[i >> 1][0][2 * (i & 1)], y[i >> 1][0][2 * (i & 1) + 1]));
          hv[r][2 * i + 1] = hadd2_bf16(xr[r][i].y, pack2(y[i >> 1][1][2 * (i & 1)], y[i >> 1][1][2 * (i & 1) + 1]));
        }
      }
      float mean[2];
      uint32_t mb[2];
#pragma unroll
      for (int r = 0; r < 2; r++) {
        mean[r] = sum_groups(quad_sum(hv[r])) * (1.f / 512.f);
        mb[r] = pack2(mean[r], mean[r]);
      }
#pragma unroll
      for (int i = 0; i < 4; i++)
#pragma unroll
        for (int r = 0; r < 2; r++) {
          hv[r][2 * i] = hsub2_bf16(hv[r][2 * i], mb[r]);
          hv[r][2 * i + 1] = hsub2_bf16(hv[r][2 * i + 1], mb[r]);
          st_tag8(lnp[r] + i * 4096, hv[r][2 * i], hv[r][2 * i + 1], i == 0 ? tag : (hv[r][2 * i] & 1u));
        }
      bar_arrive(NB_LN, 288);
      const uint32_t ones2 = ~(lds2(BAR(epoch, 0)).x >> 31);
      float rstd[2];
#pragma unroll
      for (int r = 0; r < 2; r++) {
        hv[r][0] &= ones2;
        rstd[r] = row_rstd(hv[r], mean[r] - bf_lo(mb[r]));
      }
      if (lane == 0)
        st_tag(&scr->ST[rb * 64 + 8 * f + warp], make_uint4(mb[0] << 16, __float_as_uint(rstd[0]), mb[1] << 16, __float_as_uint(rstd[1])), tag);
    }
    const int wgi = warp >> 2, wq = warp & 3;
    const int wr = wgi ^ (f >> 2) ^ 1, rt = 4 * wr + wq;
    uint4* const pbase = &scr->P[rb * 28 * 1024 + rt * 128 + lane];
    const uint32_t a_lo0 = desc_lo(sbase + wr * 8192, 16);
    const uint32_t ebar = lane == 0 ? BAR(empty1, 0) : RBAR(empty1, 0);
    float r0, r1;
    uint4 px[8], py[6];
    const int rh = wgi ^ kh ^ 1;
    const uint32_t fpb = BAR(fullP, 16 * rh);
    const uint4* const psrc = &scr->P[(rb2 * 28 + 14 * kh) * 1024 + (4 * rh + wq) * 128 + lane];
    const uint32_t pa0 = sbase + (4 * rh + wq) * 2048;
    uint4 pf[3][4], ha[4][4];
    uint32_t rdy = 0, got0;
    {
      float acc[128];
#pragma unroll
      for (int i = 0; i < 128; i++) acc[i] = 0.f;
      const uint32_t b_lo0 = desc_lo(sbase + 8 * SLOT, 4096);
      const uint32_t t3 = clock32();
      if (WARM) {
        wg_fence();
#pragma unroll
        for (int i = 0; i < WARM; i++) wgmma_n256(acc, desc64(a_lo0 + 6 * 1024, HI128), desc64(b_lo0, HI128));
        wg_commit();
      }
      const uint4* const ap = &scr->LN[rb * 8 * 1024 + wr * 512 + (tid & 127)];
      uint4 av[NLL][4];
      spin_until(t3 + POLL_DELAY3);
#pragma unroll
      for (int kb = 0; kb < NLL; kb++) ld_tag4_issue<128>(av[kb], ap + kb * 1024);
      bar_sync(NB_CONS, 256);
      const uint32_t lma = sbase + (16 * rt + (lane & 15)) * 128;
      auto load_a = [&](int kb) {
#pragma unroll
        for (int ks = 0; ks < 4; ks++)
          asm volatile("ldmatrix.sync.aligned.m8n8.x4.shared.b16 {%0,%1,%2,%3}, [%4];"
                       : "=r"(ha[kb][ks].x), "=r"(ha[kb][ks].y), "=r"(ha[kb][ks].z), "=r"(ha[kb][ks].w)
                       : "r"(lma + kb * SLOT + (((2 * ks + (lane >> 4)) ^ (lane & 7)) * 16)) : "memory");
      };
      auto stash_a = [&](int kb) {
        ld_tag4_finish<128, true>(av[kb], ap + kb * 1024, tag);
#pragma unroll
        for (int i = 0; i < 4; i++)
          sts4(sbase + kb * SLOT + wr * 8192 + ((tid & 127) + 128 * i) * 16, av[kb][i].x, av[kb][i].y, av[kb][i].z, av[kb][i].w);
        bar_sync(NB_WG + wgi, 128);
      };
      stash_a(0);
      load_a(0);
#pragma unroll
      for (int n = 0; n < 8; n++) {
        const int kb = n >> 1, hh = n & 1;
        if (hh == 1 && kb < 3) {
          if (kb + 1 < NLL) stash_a(kb + 1); else mbar_wait(BAR(fullA, kb + 1));
        }
        mbar_wait(BAR(full1, n));
        const uint32_t bl = b_lo0 + ((n + 2) % 6) * 1024;
        wg_fence();
        if (hh == 1 && kb < 3) load_a(kb + 1);
        const uint4 &a0 = ha[kb][2 * hh], &a1 = ha[kb][2 * hh + 1];
        wgmma_rs_n256(acc, a0.x, a0.y, a0.z, a0.w, desc64(bl, HI128), n != 0 ? 1 : ~ones);
        wgmma_rs_n256(acc, a1.x, a1.y, a1.z, a1.w, desc64(bl + 128, HI128));
        wg_commit();
        if (hh == 1 && lane < 2) mbar_arrive_remote(ebar + (uint32_t)(offsetof(Bars, freeA) - offsetof(Bars, empty1)) + 8 * kb);
        wg_wait<1>();
        if (n != 0 && lane < 2) mbar_arrive_remote(ebar + 8 * (n - 1));
      }
      uint32_t slot = 4;
#pragma unroll 1
      for (int kb = 4; kb < 8; kb++) {
        mbar_wait(BAR(fullA, kb));
#pragma unroll
        for (int hh = 0; hh < 2; hh++) {
          if (LAGX && hh == ((16 - LAGX) & 1) && kb == ((16 - LAGX) >> 1) && wgi == 1) bar_sync(NB_LAG, 256);
          mbar_wait(BAR(full1, 2 * kb + hh));
          const uint32_t al = a_lo0 + kb * 1024 + hh * 4, bl = b_lo0 + slot * 1024;
          wg_fence();
          wgmma_n256(acc, desc64(al, HI128), desc64(bl, HI128));
          wgmma_n256(acc, desc64(al + 2, HI128), desc64(bl + 128, HI128));
          wg_commit();
          if (LAGX && hh == 1 && kb == 7 && wgi == 0) bar_arrive(NB_LAG, 256);
          wg_wait<1>();
          if (lane < 2) mbar_arrive_remote(ebar + 8 * (2 * kb + hh - 1));
          if (++slot == 6) slot = 0;
        }
      }
      mbar_wait(BAR(sbar, 0), 0);
      r0 = __uint_as_float(lds2(sstat + (16 * rt + g) * 8).y);
      r1 = __uint_as_float(lds2(sstat + (16 * rt + g + 8) * 8).y);
      wg_wait<0>();
      if (lane < 2) mbar_arrive_remote(ebar + 8 * 15);
      make_p<8, false>(acc, r0, r1, px, pbase, 0, tag);
    }
    {
      float acc[96];
#pragma unroll
      for (int i = 0; i < 96; i++) acc[i] = 0.f;
      const uint32_t b_lo0 = desc_lo(sbase, 2048);
      uint4* const pdst = pbase + ((7 * f + 3 * (f & 1)) >> 1) * 1024;
      auto stage_y = [&](int k) {
        if (LAGY && k == 16 - LAGY && wgi == 1) bar_sync(NB_LAG, 256);
        mbar_wait(BAR(full1, 16 + k));
        const uint32_t al = a_lo0 + (4 + (k >> 1)) * 1024 + (k & 1) * 4, bl = b_lo0 + (k < 5 ? k * 768 : 8192 + (k - 5) * 768);
        wg_fence();
        wgmma_n192(acc, desc64(al, HI128), desc64(bl, HI64));
        wgmma_n192(acc, desc64(al + 2, HI128), desc64(bl + 64, HI64));
        wg_commit();
      };
#pragma unroll
      for (int k = 0; k < 4; k++) {
        stage_y(k);
        st_tag(pdst + (k >> 1) * 1024 + (k & 1) * 64, px[2 * k], tag);
        st_tag(pdst + (k >> 1) * 1024 + (k & 1) * 64 + 32, px[2 * k + 1], tag);
        if (k == 3 && lane == 0) red_relaxed(&scr->cnt[(C_PX + rb) * 32 + (f >> 2)]);
        wg_wait<1>();
        if (k != 0 && lane < 2) mbar_arrive_remote(ebar + 8 * (15 + k));
      }
#pragma unroll 1
      for (int k = 4; k < 8; k++) {
        stage_y(k);
        wg_wait<1>();
        if (lane < 2) mbar_arrive_remote(ebar + 8 * (15 + k));
      }
      rdy = 0;
#pragma unroll
      for (int k = 8; k < 16; k++) {
        if (LAGY && k == 16 - LAGY && wgi == 1) bar_sync(NB_LAG, 256);
        if (!rdy) mbar_wait(BAR(full1, 16 + k));
        const uint32_t bl = b_lo0 + 8192 + ((k - 5) & 7) * 768;
        const uint4 &a0 = ha[(k - 8) >> 1][2 * (k & 1)], &a1 = ha[(k - 8) >> 1][2 * (k & 1) + 1];
        wg_fence();
        if (k < 15) rdy = mbar_test(BAR(full1, 17 + k));
        wgmma_rs_n192(acc, a0.x, a0.y, a0.z, a0.w, desc64(bl, HI64));
        wgmma_rs_n192(acc, a1.x, a1.y, a1.z, a1.w, desc64(bl + 64, HI64));
        wg_commit();
        if (LAGY && k == 15 && wgi == 0) bar_arrive(NB_LAG, 256);
        wg_wait<1>();
        if (lane < 2) mbar_arrive_remote(ebar + 8 * (15 + k));
      }
      got0 = __all_sync(0xffffffffu, mbar_test((fpb + 8 * (0))));
      if (got0) {
#pragma unroll
        for (int kk = 0; kk < 4; kk++) pf[0][kk] = lds4(pa0 + 3 * SLOT + kk * 512 + lane * 16);
      }
      wg_wait<0>();
      if (lane < 2) mbar_arrive_remote(ebar + 8 * 31);
      const int ks0 = 14 * f + ((f & 1) ? 0 : 8);
      auto reread = [&]() {
        asm volatile("ld.volatile.shared.f32 %0, [%2+4]; ld.volatile.shared.f32 %1, [%2+68];" : "=f"(r0), "=f"(r1) : "r"(sstat + (16 * rt + g) * 8) : "memory");
      };
      make_p<6, true, 0, 2>(acc, r0, r1, py, pbase, ks0, tag);
      if (REDPOS == 2 && lane == 0) red_relaxed(&scr->cnt[(C_PY + rb) * 32 + 4 * wgi + (f >> 1)]);
      reread();
      make_p<6, true, 2, 4>(acc, r0, r1, py, pbase, ks0, tag);
      if (REDPOS == 4 && lane == 0) red_relaxed(&scr->cnt[(C_PY + rb) * 32 + 4 * wgi + (f >> 1)]);
      reread();
      rdy = mbar_test(BAR(full2, 0)) & mbar_test((fpb + 8 * (1)));
      make_p<6, true, 4, 6>(acc, r0, r1, py, pbase, ks0, tag);
      if (REDPOS == 6 && lane == 0) red_relaxed(&scr->cnt[(C_PY + rb) * 32 + 4 * wgi + (f >> 1)]);
    }
    {
      float acc[64];
      const uint32_t b2_lo0 = desc_lo(sbase, 8192);
      const uint32_t pbar = rh == rk ? BAR(emptyP, 0) : RBAR(emptyP, 0);
      if (!got0) {
        mbar_wait((fpb + 8 * (0)));
#pragma unroll
        for (int kk = 0; kk < 4; kk++) pf[0][kk] = lds4(pa0 + 3 * SLOT + kk * 512 + lane * 16);
      }
#pragma unroll
      for (int s = 0; s < 14; s++) {
        uint4 (&a)[4] = pf[s % 3];
        ld_tag4_finish<32>(a, psrc + (int)((KORDER >> (4 * s)) & 15) * 1024, tag);
        if (s < 8 && lane == 0) mbar_arrive_remote(s < 7 ? pbar + 8 * s : BAR(emptyP, 7));
        if (s >= 2) {
          wg_wait<1>();
          if (s <= 8 && lane == 0) mbar_arrive(BAR(empty2, s - 2));
        }
        if (!rdy) {
          if (s < 13) mbar_wait((fpb + 8 * (s + 1)));
          mbar_wait(BAR(full2, s));
        }
        if (s == 14 - LAG2 && wgi == 1) {
          const float m0 = __uint_as_float(lds2(sstat + 1024 + (16 * wq + g) * 8).x);
          const float m1 = __uint_as_float(lds2(sstat + 1024 + (16 * wq + g + 8) * 8).x);
          const uint32_t hb = sbase + 3 * SLOT + (16 * wq + (lane & 15)) * 128;
          wg_wait<0>();
          mbar_wait(BAR(hbar, 0));
#pragma unroll
          for (int i = 0; i < 8; i++) {
            uint32_t h[4];
            asm volatile("ldmatrix.sync.aligned.m8n8.x4.shared.b16 {%0,%1,%2,%3}, [%4];"
                         : "=r"(h[0]), "=r"(h[1]), "=r"(h[2]), "=r"(h[3])
                         : "r"(hb + (i >> 2) * 8192 + (((2 * (i & 3) + (lane >> 4)) ^ (lane & 7)) * 16)) : "memory");
            const uint32_t mk = ((t & 1) == 0 && nq == 0) ? ~1u : ~0u;
#pragma unroll
            for (int e = 0; e < 4; e++) {
              acc[8 * i + 2 * e] += bf_lo(h[e] & mk) + ((e & 1) ? m1 : m0);
              acc[8 * i + 2 * e + 1] += __uint_as_float(h[e] & 0xffff0000u) + ((e & 1) ? m1 : m0);
            }
          }
          bar_sync(NB_LAG, 256);
        }
        const uint32_t bl = b2_lo0 + (uint32_t)((BSLOT >> (4 * s)) & 15) * 1024;
        wg_fence();
        if (s < 13) {
#pragma unroll
          for (int kk = 0; kk < 4; kk++)
            pf[(s + 1) % 3][kk] = lds4(pa0 + (uint32_t)((PSLOT >> (4 * (s + 1))) & 15) * SLOT + kk * 512 + lane * 16);
          rdy = mbar_test(BAR(full2, s + 1));
          if (s < 12) rdy &= mbar_test((fpb + 8 * (s + 2)));
        }
        if (s == 0) wgmma_rs_n128<0>(acc, a[0].x, a[0].y, a[0].z, a[0].w, desc64(bl, HI128));
        else wgmma_rs_n128<1>(acc, a[0].x, a[0].y, a[0].z, a[0].w, desc64(bl, HI128));
#pragma unroll
        for (int kk = 1; kk < 4; kk++) wgmma_rs_n128<1>(acc, a[kk].x, a[kk].y, a[kk].z, a[kk].w, desc64(bl + kk * 128, HI128));
        wg_commit();
      }
      if (wgi == 0) {
        bar_arrive(NB_LAG, 256);
        uint4* const dst = &scr->Z1[(tid >> 3) * 1024 + (c ^ 4) * 8 + (tid & 7)];
        wg_wait<0>();
#pragma unroll
        for (int i = 0; i < 8; i++)
          st_tag(dst + i * 16384, make_uint4(pack2(acc[8 * i], acc[8 * i + 1]), pack2(acc[8 * i + 2], acc[8 * i + 3]) | 1u,
                                           pack2(acc[8 * i + 4], acc[8 * i + 5]), pack2(acc[8 * i + 6], acc[8 * i + 7])), tag);
      } else {
        uint4 pv[2][4];
        const uint4* const xsrc = &scr->Z1[((tid & 127) >> 3) * 1024 + c * 8 + (tid & 7)];
        ld_tag4_issue<16384>(pv[0], xsrc);
        ld_tag4_issue<16384>(pv[1], xsrc + 65536);
        wg_wait<0>();
        uint32_t w[32];
#pragma unroll
        for (int i = 0; i < 32; i++) w[i] = pack2(acc[2 * i], acc[2 * i + 1]);
        int it = 0;
#pragma unroll 1
        while (!__all_sync(0xffffffffu, pv[0][0].y & pv[0][1].y & pv[0][2].y & pv[0][3].y & pv[1][0].y & pv[1][1].y & pv[1][2].y & pv[1][3].y & 1u)) {
          ld_tag4_issue<16384>(pv[0], xsrc);
          ld_tag4_issue<16384>(pv[1], xsrc + 65536);
          if (++it > SPIN_LIMIT) { die(); break; }
        }
#pragma unroll
        for (int i = 0; i < 8; i++) {
          const uint4& p = pv[i >> 2][i & 3];
          asm volatile("stmatrix.sync.aligned.m8n8.x4.shared.b16 [%0], {%1,%2,%3,%4};"
                       ::"r"(pa0 + (11 + ((lane >> 3) & 1)) * SLOT + (lane & 7) * 256 + (((2 * i + (lane >> 4)) ^ (lane & 7)) * 16)),
                         "r"(hadd2_bf16(w[4 * i], p.x & ~1u)), "r"(hadd2_bf16(w[4 * i + 1], p.y & ~1u)), "r"(hadd2_bf16(w[4 * i + 2], p.z)),
                         "r"(hadd2_bf16(w[4 * i + 3], p.w)) : "memory");
        }
        __syncwarp();
        uint4* const dst = reinterpret_cast<uint4*>(out) + (16 * (c >> 4) + 2 * (4 * rh + wq) + (rb2 & 1) + 128 * (lane >> 4)) * 64 + nq * 16 + (lane & 15);
#pragma unroll
        for (int i = 0; i < 8; i++) {
          const int r = 2 * (i & 3) + (lane >> 4);
          dst[i * 256 * 64] = lds4(pa0 + (11 + (i >> 2)) * SLOT + r * 256 + (((lane & 15) ^ r) * 16));
        }
      }
    }
  }
#undef BAR
#undef TOFF
#undef RBAR
}

typedef CUresult (*EncodeFn)(CUtensorMap*, CUtensorMapDataType, cuuint32_t, void*, const cuuint64_t*, const cuuint64_t*,
                             const cuuint32_t*, const cuuint32_t*, CUtensorMapInterleave, CUtensorMapSwizzle,
                             CUtensorMapL2promotion, CUtensorMapFloatOOBfill);

}

extern "C" void kernel_launch(void* const* d_in, const int* in_sizes, int n_in, void* d_out, int out_size) {
  (void)in_sizes; (void)n_in; (void)out_size;
  static EncodeFn encode = nullptr;
  static void *tab = nullptr, *scr = nullptr;
  if (!encode) {
    void* fn = nullptr;
    cudaDriverEntryPointQueryResult qr;
    cudaGetDriverEntryPoint("cuTensorMapEncodeTiled", &fn, cudaEnableDefault, &qr);
    encode = (EncodeFn)fn;
    cudaGetSymbolAddress(&tab, g_tab);
    cudaGetSymbolAddress(&scr, g_scr);
    cudaFuncSetAttribute(fused_kernel, cudaFuncAttributeMaxDynamicSharedMemorySize, SMEM_BYTES);
  }
  CUtensorMap tmGX, tmUX, tmGY, tmUY, tmD, tmWR, tmWI;
  const cuuint32_t es[5] = {1, 1, 1, 1, 1};
  auto enc = [&](CUtensorMap* m, void* p, int rank, const cuuint64_t* gd, const cuuint64_t* gs, const cuuint32_t* bd,
                 CUtensorMapSwizzle sw, CUtensorMapL2promotion pr) {
    encode(m, CU_TENSOR_MAP_DATA_TYPE_BFLOAT16, rank, p, gd, gs, bd, es, CU_TENSOR_MAP_INTERLEAVE_NONE, sw, pr,
           CU_TENSOR_MAP_FLOAT_OOB_FILL_NONE);
  };
  {
    const cuuint64_t gd[3] = {64, 512, 28}, gs[2] = {3584, 128};
    const cuuint32_t bd[3] = {64, 32, 2};
    enc(&tmGX, d_in[4], 3, gd, gs, bd, CU_TENSOR_MAP_SWIZZLE_128B, CU_TENSOR_MAP_L2_PROMOTION_L2_256B);
    enc(&tmUX, d_in[5], 3, gd, gs, bd, CU_TENSOR_MAP_SWIZZLE_128B, CU_TENSOR_MAP_L2_PROMOTION_L2_256B);
  }
  {
    const cuuint64_t gd[3] = {32, 512, 56}, gs[2] = {3584, 64};
    const cuuint32_t bd[3] = {32, 32, 3};
    enc(&tmGY, d_in[4], 3, gd, gs, bd, CU_TENSOR_MAP_SWIZZLE_64B, CU_TENSOR_MAP_L2_PROMOTION_L2_128B);
    enc(&tmUY, d_in[5], 3, gd, gs, bd, CU_TENSOR_MAP_SWIZZLE_64B, CU_TENSOR_MAP_L2_PROMOTION_L2_128B);
  }
  {
    const cuuint64_t gd[3] = {64, 1792, 8}, gs[2] = {1024, 128};
    const cuuint32_t bd[3] = {64, 64, 2};
    enc(&tmD, d_in[6], 3, gd, gs, bd, CU_TENSOR_MAP_SWIZZLE_128B, CU_TENSOR_MAP_L2_PROMOTION_L2_256B);
  }
  {
    const cuuint64_t gd[3] = {4112, 8, 16}, gs[2] = {16 * 8224, 8224};
    const cuuint32_t bd[3] = {40, 8, 16};
    enc(&tmWR, d_in[1], 3, gd, gs, bd, CU_TENSOR_MAP_SWIZZLE_NONE, CU_TENSOR_MAP_L2_PROMOTION_NONE);
    enc(&tmWI, d_in[2], 3, gd, gs, bd, CU_TENSOR_MAP_SWIZZLE_NONE, CU_TENSOR_MAP_L2_PROMOTION_NONE);
  }
  fused_kernel<<<NCTA, NTHREADS, SMEM_BYTES>>>((const __nv_bfloat16*)d_in[0], (const Tables*)tab, (Scratch*)scr,
                                               (__nv_bfloat16*)d_out, (const char*)d_in[4], (const char*)d_in[5],
                                               (const char*)d_in[6], tmWR, tmWI, tmGX, tmUX, tmGY, tmUY, tmD);
}
```

```cpp
#include <cuda_runtime.h>
#include <cuda_bf16.h>
#include <cuda.h>
#include <stdint.h>

namespace {

constexpr int NCTA = 128;
constexpr int NTHREADS = 384;
constexpr int SLOT = 16384;
constexpr int SMEM_BYTES = 14 * SLOT + 3072;
constexpr int SPIN_LIMIT = 1 << 22;

struct Scratch {
  uint4 Z1[128 * 1024];
  uint4 LN[16 * 8 * 1024];
  uint4 P[16 * 28 * 1024];
  uint4 ST[1024];
  unsigned cnt[64 * 32];
};
__device__ __align__(1024) Scratch g_scr;

constexpr double ccos(int i, int n) {
  i &= n - 1;
  if (i > n / 2) i = n - i;
  if (4 * i == n) return 0.0;
  const bool neg = 4 * i > n;
  if (neg) i = n / 2 - i;
  const double a = 6.283185307179586476925 * i / n, a2 = a * a;
  double term = 1.0, sum = 1.0;
  for (int k = 1; k < 14; k++) { term *= -a2 / ((2 * k - 1) * (2 * k)); sum += term; }
  return neg ? -sum : sum;
}
constexpr double csin(int i, int n) { return ccos(i - n / 4, n); }
constexpr unsigned fbits(double v, int mant) {
  if (v == 0.0) return 0;
  const unsigned sg = v < 0 ? 1u : 0u;
  if (v < 0) v = -v;
  int e = 127;
  while (v < 1.0) { v *= 2.0; e--; }
  const unsigned m = (unsigned)((v - 1.0) * (double)(1u << mant) + 0.5);
  return (sg << (8 + mant)) + ((unsigned)e << mant) + m;
}
constexpr unsigned pkb(double lo, double hi) { return fbits(lo, 7) | (fbits(hi, 7) << 16); }
constexpr double fa_elem(int mt, int r, int n1) {
  const int k1 = 8 * mt + (r & 7);
  return r < 8 ? ccos(k1 * n1, 32) : k1 == 0 ? ccos(16 * n1, 32) : -csin(k1 * n1, 32);
}
constexpr unsigned cfrag_c(int idx, int n, int ri, double s = 1.0) {
  return ri ? pkb(-s * csin(idx, n), s * ccos(idx, n)) : pkb(s * ccos(idx, n), s * csin(idx, n));
}
struct Tables {
  unsigned fa[4][32][4];
  unsigned fb[4][32][4];
  unsigned tw1[6][32][4];
  unsigned f2[8][4][32][4];
  unsigned g2[8][4][32][4];
  unsigned gb[4][32][4];
  unsigned ga[4][32][4];
  unsigned tw3[4][32][4];
  unsigned f8[32][4], g8[32][4];
};
constexpr int T1_BYTES = 7168, T2_BYTES = 39936;
static_assert(sizeof(Tables) == T1_BYTES + T2_BYTES, "table size");
constexpr Tables make_tables() {
  Tables T = {};
  for (int l = 0; l < 32; l++) {
    const int g = l >> 2, t = l & 3;
    for (int a = 0; a < 2; a++)
      for (int b = 0; b < 2; b++) {
        for (int r = 0; r < 4; r++) {
          const int row = g + 8 * (r & 1), col = 2 * t + 8 * (r >> 1);
          T.fa[2 * a + b][l][r] = pkb(fa_elem(a, row, 16 * b + col), fa_elem(a, row, 16 * b + col + 1));
          T.ga[2 * a + b][l][r] = pkb(fa_elem(b, col, 16 * a + row), fa_elem(b, col + 1, 16 * a + row));
        }
        const double sg = b ? -1.0 : 1.0;
        for (int h = 0; h < 2; h++) {
          const int ri = g & 1, m = 2 * (g >> 1) + h, k2 = b ? 15 - m : m;
          const int pa = (8 * a + 2 * t) * k2, pb = (8 * a + 2 * t + 1) * k2;
          T.fb[2 * a + b][l][2 * h] = ri == 0 ? pkb(ccos(pa, 16), ccos(pb, 16)) : pkb(-sg * csin(pa, 16), -sg * csin(pb, 16));
          T.fb[2 * a + b][l][2 * h + 1] = ri == 0 ? pkb(csin(pa, 16), csin(pb, 16)) : pkb(sg * ccos(pa, 16), sg * ccos(pb, 16));
        }
        const int n2 = 4 * (g >> 1) + 2 * a + (g & 1);
        for (int h = 0; h < 2; h++) {
          const int p = n2 * (b ? 15 - 2 * t - h : 2 * t + h);
          T.gb[2 * a + b][l][2 * h] = pkb(ccos(p, 16), -sg * csin(p, 16));
          T.gb[2 * a + b][l][2 * h + 1] = pkb(csin(p, 16), sg * ccos(p, 16));
          const int k1 = 8 * b + 2 * t + h, q = n2 * (k1 == 0 ? 16 : k1);
          T.tw3[2 * a + b][l][2 * h] = fbits(ccos(q, 512), 23);
          T.tw3[2 * a + b][l][2 * h + 1] = fbits(csin(q, 512), 23);
        }
        const int p = (8 * a + 2 * t + b) * (g == 0 ? 16 : g);
        T.tw1[2 * a + b][l][0] = fbits(g == 0 ? 0.0 : ccos(p, 512), 23);
        T.tw1[2 * a + b][l][1] = fbits(g == 0 ? ccos(p, 512) : csin(p, 512), 23);
        T.tw1[2 * a + b][l][2] = fbits(g == 0 ? 0.0 : -csin(p, 512), 23);
        T.tw1[2 * a + b][l][3] = fbits(g == 0 ? -csin(p, 512) : ccos(p, 512), 23);
        T.tw1[4 + a][l][2 * b] = fbits(ccos((8 * a + 2 * t + b) * (g + 8), 512), 23);
        T.tw1[4 + a][l][2 * b + 1] = fbits(csin((8 * a + 2 * t + b) * (g + 8), 512), 23);
      }
    for (int i = 0; i < 4; i++) {
      const int p8 = (t + 4 * (i & 1)) * (4 * (i >> 1) + (g >> 1));
      T.f8[l][i] = cfrag_c(p8, 8, g & 1);
      T.g8[l][i] = cfrag_c(-p8, 8, g & 1, 1.0 / (1 << 19));
    }
    for (int w = 0; w < 8; w++)
      for (int i = 0; i < 16; i++) {
        const int kidx = t + 4 * (i & 1) + 8 * (i >> 3), nidx = 4 * ((i >> 1) & 3) + (g >> 1);
        T.f2[w][i >> 2][l][i & 3] = cfrag_c((8 * kidx + w) * nidx, 128, g & 1);
        T.g2[w][i >> 2][l][i & 3] = cfrag_c(-(8 * nidx + w) * kidx, 128, g & 1);
      }
  }
  return T;
}
__device__ const __align__(128) Tables g_tab = make_tables();

__device__ __forceinline__ void die() { asm volatile("st.global.u32 [%0], %1;" ::"l"(0ull), "r"(0) : "memory"); }
__device__ __forceinline__ uint32_t s2u(const void* p) { return (uint32_t)__cvta_generic_to_shared(p); }
__device__ __forceinline__ void mbar_init(uint32_t b, int c) { asm volatile("mbarrier.init.shared::cta.b64 [%0], %1;" ::"r"(b), "r"(c)); }
__device__ __forceinline__ void mbar_expect(uint32_t b, int bytes) {
  asm volatile("mbarrier.arrive.expect_tx.shared::cta.b64 _, [%0], %1;" ::"r"(b), "r"(bytes) : "memory");
}
__device__ __forceinline__ void mbar_arrive(uint32_t b) { asm volatile("mbarrier.arrive.shared::cta.b64 _, [%0];" ::"r"(b) : "memory"); }
__device__ __forceinline__ uint32_t mbar_try(uint32_t b, uint32_t parity) {
  uint32_t ok;
  asm volatile("{.reg .pred p; mbarrier.try_wait.parity.shared::cta.b64 p, [%1], %2; selp.u32 %0,1,0,p;}"
               : "=r"(ok) : "r"(b), "r"(parity) : "memory");
  return ok;
}
__device__ __forceinline__ uint32_t mbar_test(uint32_t b) {
  uint32_t ok;
  asm volatile("{.reg .pred p; mbarrier.test_wait.parity.shared::cta.b64 p, [%1], 0; selp.u32 %0,1,0,p;}" : "=r"(ok) : "r"(b) : "memory");
  return ok;
}
__device__ __forceinline__ void mbar_wait(uint32_t b, uint32_t parity = 0) {
  int it = 0;
#pragma unroll 1
  while (!mbar_try(b, parity))
    if (++it > SPIN_LIMIT) { die(); break; }
}
__device__ __forceinline__ void bar_sync(int id, int n) { asm volatile("bar.sync %0, %1;" ::"r"(id), "r"(n) : "memory"); }
__device__ __forceinline__ void bar_arrive(int id, int n) { asm volatile("bar.arrive %0, %1;" ::"r"(id), "r"(n) : "memory"); }
__device__ __forceinline__ void red_release(unsigned* p) { asm volatile("red.release.gpu.global.add.u32 [%0], 1;" ::"l"(p) : "memory"); }
__device__ __forceinline__ void red_relaxed(unsigned* p) { asm volatile("red.relaxed.gpu.global.add.u32 [%0], 1;" ::"l"(p) : "memory"); }
__device__ __forceinline__ unsigned ld_acquire(const unsigned* p) {
  unsigned v;
  asm volatile("ld.acquire.gpu.global.u32 %0, [%1];" : "=r"(v) : "l"(p) : "memory");
  return v;
}
__device__ __forceinline__ unsigned ld_relaxed(const unsigned* p) {
  unsigned v;
  asm volatile("ld.relaxed.gpu.global.u32 %0, [%1];" : "=r"(v) : "l"(p) : "memory");
  return v;
}
__device__ __forceinline__ void wait_counter(const unsigned* p, unsigned target) {
  int it = 0;
  while ((int)(ld_acquire(p) - target) < 0)
    if (++it > SPIN_LIMIT) { die(); break; }
}
__device__ __forceinline__ void sts4(uint32_t a, uint32_t x, uint32_t y, uint32_t z, uint32_t w) {
  asm volatile("st.shared.v4.u32 [%0], {%1,%2,%3,%4};" ::"r"(a), "r"(x), "r"(y), "r"(z), "r"(w) : "memory");
}
__device__ __forceinline__ uint4 lds4(uint32_t a) {
  uint4 v;
  asm volatile("ld.shared.v4.u32 {%0,%1,%2,%3}, [%4];" : "=r"(v.x), "=r"(v.y), "=r"(v.z), "=r"(v.w) : "r"(a) : "memory");
  return v;
}
__device__ __forceinline__ uint32_t pack2(float lo, float hi) {
  uint32_t r;
  asm("cvt.rn.bf16x2.f32 %0, %1, %2;" : "=r"(r) : "f"(hi), "f"(lo));
  return r;
}
__device__ __forceinline__ float bf_lo(uint32_t v) { return __uint_as_float(v << 16); }
__device__ __forceinline__ uint32_t hadd2_bf16(uint32_t a, uint32_t b) {
  uint32_t r;
  asm("add.rn.bf16x2 %0, %1, %2;" : "=r"(r) : "r"(a), "r"(b));
  return r;
}
__device__ __forceinline__ void mma16816(float (&d)[4], uint32_t a0, uint32_t a1, uint32_t a2, uint32_t a3, uint32_t b0, uint32_t b1) {
  asm("mma.sync.aligned.m16n8k16.row.col.f32.bf16.bf16.f32 {%0,%1,%2,%3}, {%4,%5,%6,%7}, {%8,%9}, {%0,%1,%2,%3};"
      : "+f"(d[0]), "+f"(d[1]), "+f"(d[2]), "+f"(d[3])
      : "r"(a0), "r"(a1), "r"(a2), "r"(a3), "r"(b0), "r"(b1));
}
__device__ __forceinline__ void mma16816_z(float (&d)[4], uint32_t a0, uint32_t a1, uint32_t a2, uint32_t a3, uint32_t b0, uint32_t b1) {
  asm("{.reg .f32 z; mov.f32 z, 0f00000000;\n"
      "mma.sync.aligned.m16n8k16.row.col.f32.bf16.bf16.f32 {%0,%1,%2,%3}, {%4,%5,%6,%7}, {%8,%9}, {z,z,z,z};}"
      : "=f"(d[0]), "=f"(d[1]), "=f"(d[2]), "=f"(d[3])
      : "r"(a0), "r"(a1), "r"(a2), "r"(a3), "r"(b0), "r"(b1));
}
template <int N>
__device__ __forceinline__ void cs_frac(int idx, float& c, float& s) {
  int i = ((idx + N / 2) & (N - 1)) - N / 2;
  float a = (float)i * (6.283185307179586f / N);
  c = __cosf(a);
  s = __sinf(a);
}
template <int N>
__device__ __forceinline__ uint32_t cfrag(int idx, int ri) {
  float c, s;
  cs_frac<N>(idx, c, s);
  return ri ? pack2(-s, c) : pack2(c, s);
}
__device__ __forceinline__ uint32_t word(const uint4& v, int e) { return e == 0 ? v.x : e == 1 ? v.y : e == 2 ? v.z : v.w; }
__device__ __forceinline__ void cdft16(const uint4 (&A)[4], const uint4 (&F)[4], uint4 (&o)[4]) {
  float acc[2][4][4];
#pragma unroll
  for (int ks = 0; ks < 2; ks++)
#pragma unroll
    for (int p = 0; p < 2; p++)
#pragma unroll
      for (int v = 0; v < 4; v++) {
        const uint4& a = A[2 * ks + p];
        const uint32_t b0 = word(F[ks * 2 + (v >> 1)], (v & 1) * 2), b1 = word(F[ks * 2 + (v >> 1)], (v & 1) * 2 + 1);
        if (ks == 0) mma16816_z(acc[p][v], a.x, a.y, a.z, a.w, b0, b1);
        else mma16816(acc[p][v], a.x, a.y, a.z, a.w, b0, b1);
      }
#pragma unroll
  for (int v = 0; v < 4; v++)
    o[v] = make_uint4(pack2(acc[0][v][0], acc[0][v][1]), pack2(acc[0][v][2], acc[0][v][3]),
                      pack2(acc[1][v][0], acc[1][v][1]), pack2(acc[1][v][2], acc[1][v][3]));
}
__device__ __forceinline__ void lds_frag(uint4& f0, uint4& f1, uint32_t a0, uint32_t a1) {
  asm volatile("ld.volatile.shared.v2.u32 {%0,%1}, [%8]; ld.volatile.shared.v2.u32 {%2,%3}, [%9];\n"
               "ld.volatile.shared.v2.u32 {%4,%5}, [%8+8]; ld.volatile.shared.v2.u32 {%6,%7}, [%9+8];"
               : "=r"(f0.x), "=r"(f0.y), "=r"(f0.z), "=r"(f0.w), "=r"(f1.x), "=r"(f1.y), "=r"(f1.z), "=r"(f1.w) : "r"(a0), "r"(a1) : "memory");
}
__device__ __forceinline__ void reg_frag(uint4 (&q)[4], uint32_t ones) {
#pragma unroll
  for (int ks = 0; ks < 2; ks++) {
    const uint4 a = q[2 * ks], b = q[2 * ks + 1];
    q[2 * ks] = make_uint4(a.x, a.y, b.x & ones, b.y & ones);
    q[2 * ks + 1] = make_uint4(a.z & ones, a.w & ones, b.z, b.w);
  }
}
__device__ __forceinline__ void st_tag(uint4* p, const uint4& v, uint32_t tag) {
  asm volatile("st.relaxed.gpu.global.v4.b32 [%0], {%1,%2,%3,%4};"
               ::"l"(p), "r"((v.x & ~1u) | tag), "r"(v.y), "r"(v.z), "r"(v.w) : "memory");
}
__device__ __forceinline__ void st_tag8(void* p, uint32_t x, uint32_t y, uint32_t tag) {
  asm volatile("st.relaxed.gpu.global.v2.b32 [%0], {%1,%2};" ::"l"(p), "r"((x & ~1u) | tag), "r"(y) : "memory");
}
__device__ __forceinline__ uint4 ld_b128(const uint4* p) {
  uint4 v;
  asm volatile("ld.relaxed.gpu.global.v4.b32 {%0,%1,%2,%3}, [%4];"
               : "=r"(v.x), "=r"(v.y), "=r"(v.z), "=r"(v.w) : "l"(p) : "memory");
  return v;
}
template <int STRIDE>
__device__ __forceinline__ void ld_tag4_issue(uint4 (&q)[4], const uint4* p) {
#pragma unroll
  for (int i = 0; i < 4; i++) q[i] = ld_b128(p + i * STRIDE);
}
template <int STRIDE, bool HALVES = false>
__device__ __forceinline__ void ld_tag4_finish(uint4 (&q)[4], const uint4* p, uint32_t tag) {
  int it = 0;
#pragma unroll 1
  while (__any_sync(0xffffffffu, ((q[0].x ^ tag) | (q[1].x ^ tag) | (q[2].x ^ tag) | (q[3].x ^ tag) |
                                  (HALVES ? (q[0].z ^ tag) | (q[1].z ^ tag) | (q[2].z ^ tag) | (q[3].z ^ tag) : 0u)) & 1u)) {
    ld_tag4_issue<STRIDE>(q, p);
    if (++it > SPIN_LIMIT) { die(); break; }
  }
#pragma unroll
  for (int i = 0; i < 4; i++) {
    asm volatile("and.b32 %0, %0, 0xfffffffe;" : "+r"(q[i].x));
    if (HALVES) q[i].z &= ~1u;
  }
}
__device__ __forceinline__ float quad_sum(const uint32_t (&a)[8]) {
  float d[4];
  mma16816_z(d, a[0], a[1], a[2], a[3], 0x3f803f80u, 0x3f803f80u);
  mma16816(d, a[4], a[5], a[6], a[7], 0x3f803f80u, 0x3f803f80u);
  return d[0] + d[2];
}
__device__ __forceinline__ float sum_groups(float v) {
  v += __shfl_xor_sync(0xffffffffu, v, 4);
  v += __shfl_xor_sync(0xffffffffu, v, 8);
  v += __shfl_xor_sync(0xffffffffu, v, 16);
  return v;
}
__device__ __forceinline__ uint32_t hsub2_bf16(uint32_t a, uint32_t b) {
  uint32_t r;
  asm("sub.rn.bf16x2 %0, %1, %2;" : "=r"(r) : "r"(a), "r"(b));
  return r;
}
__device__ __forceinline__ float row_rstd(const uint32_t (&c)[8], float delta) {
  uint32_t s[8];
#pragma unroll
  for (int i = 0; i < 8; i++) asm("mul.rn.bf16x2 %0, %1, %1;" : "=r"(s[i]) : "r"(c[i]));
  return rsqrtf(fmaxf(fmaf(-delta, delta, sum_groups(quad_sum(s)) * (1.f / 512.f)), 0.f) + 1e-5f);
}
__device__ __forceinline__ uint64_t desc64(uint32_t lo, uint32_t hi) {
  uint64_t d;
  asm("mov.b64 %0, {%1, %2};" : "=l"(d) : "r"(lo), "r"(hi));
  return d;
}
constexpr uint32_t desc_hi(uint32_t sbo, uint32_t swz) { return (sbo >> 4) | (swz << 30); }
__device__ __forceinline__ uint32_t desc_lo(uint32_t addr, uint32_t lbo) { return ((addr & 0x3FFFF) >> 4) | ((lbo >> 4) << 16); }
__device__ __forceinline__ void cp_async16(uint32_t dst, const void* src) {
  asm volatile("cp.async.cg.shared.global [%0], [%1], 16;" ::"r"(dst), "l"(src) : "memory");
}
__device__ __forceinline__ uint2 lds2(uint32_t a) {
  uint2 v;
  asm volatile("ld.shared.v2.u32 {%0,%1}, [%2];" : "=r"(v.x), "=r"(v.y) : "r"(a) : "memory");
  return v;
}
__device__ __forceinline__ uint32_t lds_u16(uint32_t a) {
  uint16_t v;
  asm volatile("ld.shared.u16 %0, [%1];" : "=h"(v) : "r"(a) : "memory");
  return v;
}
__device__ __forceinline__ void wg_fence() { asm volatile("wgmma.fence.sync.aligned;" ::: "memory"); }
__device__ __forceinline__ void wg_commit() { asm volatile("wgmma.commit_group.sync.aligned;" ::: "memory"); }
template <int N>
__device__ __forceinline__ void wg_wait() { asm volatile("wgmma.wait_group.sync.aligned %0;" ::"n"(N) : "memory"); }
__device__ __forceinline__ void bulk_load(uint32_t dst, const void* src, int bytes, uint32_t bar) {
  asm volatile("cp.async.bulk.shared::cluster.global.mbarrier::complete_tx::bytes [%0], [%1], %2, [%3];"
               ::"r"(dst), "l"(src), "r"(bytes), "r"(bar) : "memory");
}
__device__ __forceinline__ void bulk_load_mc(uint32_t dst, const void* src, int bytes, uint32_t bar) {
  asm volatile("cp.async.bulk.shared::cluster.global.mbarrier::complete_tx::bytes.multicast::cluster [%0], [%1], %2, [%3], %4;"
               ::"r"(dst), "l"(src), "r"(bytes), "r"(bar), "h"((uint16_t)3) : "memory");
}
__device__ __forceinline__ void tma3(uint32_t dst, const CUtensorMap* tm, uint32_t bar, int c0, int c1, int c2) {
  asm volatile("cp.async.bulk.tensor.3d.shared::cluster.global.mbarrier::complete_tx::bytes [%0], [%1, {%3,%4,%5}], [%2];"
               ::"r"(dst), "l"(tm), "r"(bar), "r"(c0), "r"(c1), "r"(c2) : "memory");
}
__device__ __forceinline__ void tma3_mc(uint32_t dst, const CUtensorMap* tm, uint32_t bar, int c1, int c2) {
  asm volatile("cp.async.bulk.tensor.3d.shared::cluster.global.mbarrier::complete_tx::bytes.multicast::cluster [%0], [%1, {%3,%4,%5}], [%2], %6;"
               ::"r"(dst), "l"(tm), "r"(bar), "r"(0), "r"(c1), "r"(c2), "h"((uint16_t)3) : "memory");
}
__device__ __forceinline__ void mbar_arrive_remote(uint32_t rb) {
  asm volatile("mbarrier.arrive.shared::cluster.b64 _, [%0];" ::"r"(rb) : "memory");
}
__device__ __forceinline__ uint4 ldg_ca4(const void* p) {
  uint4 v;
  asm volatile("ld.global.ca.v4.u32 {%0,%1,%2,%3}, [%4];" : "=r"(v.x), "=r"(v.y), "=r"(v.z), "=r"(v.w) : "l"(p) : "memory");
  return v;
}
__device__ __forceinline__ float u2f(uint32_t v) { return __uint_as_float(v); }
__device__ __forceinline__ void mma_az(float (&d)[4], const uint4& a, uint32_t b0, uint32_t b1) { mma16816_z(d, a.x, a.y, a.z, a.w, b0, b1); }
__device__ __forceinline__ void mma_a(float (&d)[4], const uint4& a, uint32_t b0, uint32_t b1) { mma16816(d, a.x, a.y, a.z, a.w, b0, b1); }
__device__ __forceinline__ uint32_t clock32() {
  uint32_t v;
  asm volatile("mov.u32 %0, %%clock;" : "=r"(v) :: "memory");
  return v;
}
__device__ __forceinline__ float swiglu(float g, float u, float r) {
  float hg = (0.5f * r) * g, th;
  asm("tanh.approx.f32 %0, %1;" : "=f"(th) : "f"(hg));
  return fmaf(hg, th, hg) * (r * u);
}
__device__ __forceinline__ void l2_prefetch(const void* p, int bytes) {
  asm volatile("cp.async.bulk.prefetch.L2.global [%0], %1;" ::"l"(p), "r"(bytes) : "memory");
}

__device__ __forceinline__ void wgmma_n256(float (&d)[128], uint64_t da, uint64_t db, int sd = 1) {
  asm volatile("{.reg .pred p; setp.ne.b32 p, %130, 0;\n"
      "wgmma.mma_async.sync.aligned.m64n256k16.f32.bf16.bf16 {"
      "%0,%1,%2,%3,%4,%5,%6,%7,%8,%9,%10,%11,%12,%13,%14,%15,"
      "%16,%17,%18,%19,%20,%21,%22,%23,%24,%25,%26,%27,%28,%29,%30,%31,"
      "%32,%33,%34,%35,%36,%37,%38,%39,%40,%41,%42,%43,%44,%45,%46,%47,"
      "%48,%49,%50,%51,%52,%53,%54,%55,%56,%57,%58,%59,%60,%61,%62,%63,"
      "%64,%65,%66,%67,%68,%69,%70,%71,%72,%73,%74,%75,%76,%77,%78,%79,"
      "%80,%81,%82,%83,%84,%85,%86,%87,%88,%89,%90,%91,%92,%93,%94,%95,"
      "%96,%97,%98,%99,%100,%101,%102,%103,%104,%105,%106,%107,%108,%109,%110,%111,"
      "%112,%113,%114,%115,%116,%117,%118,%119,%120,%121,%122,%123,%124,%125,%126,%127"
      "}, %128, %129, p, 1, 1, 0, 1;}\n"
      : "+f"(d[0]),"+f"(d[1]),"+f"(d[2]),"+f"(d[3]),"+f"(d[4]),"+f"(d[5]),"+f"(d[6]),"+f"(d[7]),
        "+f"(d[8]),"+f"(d[9]),"+f"(d[10]),"+f"(d[11]),"+f"(d[12]),"+f"(d[13]),"+f"(d[14]),"+f"(d[15]),
        "+f"(d[16]),"+f"(d[17]),"+f"(d[18]),"+f"(d[19]),"+f"(d[20]),"+f"(d[21]),"+f"(d[22]),"+f"(d[23]),
        "+f"(d[24]),"+f"(d[25]),"+f"(d[26]),"+f"(d[27]),"+f"(d[28]),"+f"(d[29]),"+f"(d[30]),"+f"(d[31]),
        "+f"(d[32]),"+f"(d[33]),"+f"(d[34]),"+f"(d[35]),"+f"(d[36]),"+f"(d[37]),"+f"(d[38]),"+f"(d[39]),
        "+f"(d[40]),"+f"(d[41]),"+f"(d[42]),"+f"(d[43]),"+f"(d[44]),"+f"(d[45]),"+f"(d[46]),"+f"(d[47]),
        "+f"(d[48]),"+f"(d[49]),"+f"(d[50]),"+f"(d[51]),"+f"(d[52]),"+f"(d[53]),"+f"(d[54]),"+f"(d[55]),
        "+f"(d[56]),"+f"(d[57]),"+f"(d[58]),"+f"(d[59]),"+f"(d[60]),"+f"(d[61]),"+f"(d[62]),"+f"(d[63]),
        "+f"(d[64]),"+f"(d[65]),"+f"(d[66]),"+f"(d[67]),"+f"(d[68]),"+f"(d[69]),"+f"(d[70]),"+f"(d[71]),
        "+f"(d[72]),"+f"(d[73]),"+f"(d[74]),"+f"(d[75]),"+f"(d[76]),"+f"(d[77]),"+f"(d[78]),"+f"(d[79]),
        "+f"(d[80]),"+f"(d[81]),"+f"(d[82]),"+f"(d[83]),"+f"(d[84]),"+f"(d[85]),"+f"(d[86]),"+f"(d[87]),
        "+f"(d[88]),"+f"(d[89]),"+f"(d[90]),"+f"(d[91]),"+f"(d[92]),"+f"(d[93]),"+f"(d[94]),"+f"(d[95]),
        "+f"(d[96]),"+f"(d[97]),"+f"(d[98]),"+f"(d[99]),"+f"(d[100]),"+f"(d[101]),"+f"(d[102]),"+f"(d[103]),
        "+f"(d[104]),"+f"(d[105]),"+f"(d[106]),"+f"(d[107]),"+f"(d[108]),"+f"(d[109]),"+f"(d[110]),"+f"(d[111]),
        "+f"(d[112]),"+f"(d[113]),"+f"(d[114]),"+f"(d[115]),"+f"(d[116]),"+f"(d[117]),"+f"(d[118]),"+f"(d[119]),
        "+f"(d[120]),"+f"(d[121]),"+f"(d[122]),"+f"(d[123]),"+f"(d[124]),"+f"(d[125]),"+f"(d[126]),"+f"(d[127])
      : "l"(da), "l"(db), "r"(sd));
}
__device__ __forceinline__ void wgmma_n192(float (&d)[96], uint64_t da, uint64_t db) {
  asm volatile("wgmma.mma_async.sync.aligned.m64n192k16.f32.bf16.bf16 {"
      "%0,%1,%2,%3,%4,%5,%6,%7,%8,%9,%10,%11,%12,%13,%14,%15,"
      "%16,%17,%18,%19,%20,%21,%22,%23,%24,%25,%26,%27,%28,%29,%30,%31,"
      "%32,%33,%34,%35,%36,%37,%38,%39,%40,%41,%42,%43,%44,%45,%46,%47,"
      "%48,%49,%50,%51,%52,%53,%54,%55,%56,%57,%58,%59,%60,%61,%62,%63,"
      "%64,%65,%66,%67,%68,%69,%70,%71,%72,%73,%74,%75,%76,%77,%78,%79,"
      "%80,%81,%82,%83,%84,%85,%86,%87,%88,%89,%90,%91,%92,%93,%94,%95"
      "}, %96, %97, 1, 1, 1, 0, 1;\n"
      : "+f"(d[0]),"+f"(d[1]),"+f"(d[2]),"+f"(d[3]),"+f"(d[4]),"+f"(d[5]),"+f"(d[6]),"+f"(d[7]),
        "+f"(d[8]),"+f"(d[9]),"+f"(d[10]),"+f"(d[11]),"+f"(d[12]),"+f"(d[13]),"+f"(d[14]),"+f"(d[15]),
        "+f"(d[16]),"+f"(d[17]),"+f"(d[18]),"+f"(d[19]),"+f"(d[20]),"+f"(d[21]),"+f"(d[22]),"+f"(d[23]),
        "+f"(d[24]),"+f"(d[25]),"+f"(d[26]),"+f"(d[27]),"+f"(d[28]),"+f"(d[29]),"+f"(d[30]),"+f"(d[31]),
        "+f"(d[32]),"+f"(d[33]),"+f"(d[34]),"+f"(d[35]),"+f"(d[36]),"+f"(d[37]),"+f"(d[38]),"+f"(d[39]),
        "+f"(d[40]),"+f"(d[41]),"+f"(d[42]),"+f"(d[43]),"+f"(d[44]),"+f"(d[45]),"+f"(d[46]),"+f"(d[47]),
        "+f"(d[48]),"+f"(d[49]),"+f"(d[50]),"+f"(d[51]),"+f"(d[52]),"+f"(d[53]),"+f"(d[54]),"+f"(d[55]),
        "+f"(d[56]),"+f"(d[57]),"+f"(d[58]),"+f"(d[59]),"+f"(d[60]),"+f"(d[61]),"+f"(d[62]),"+f"(d[63]),
        "+f"(d[64]),"+f"(d[65]),"+f"(d[66]),"+f"(d[67]),"+f"(d[68]),"+f"(d[69]),"+f"(d[70]),"+f"(d[71]),
        "+f"(d[72]),"+f"(d[73]),"+f"(d[74]),"+f"(d[75]),"+f"(d[76]),"+f"(d[77]),"+f"(d[78]),"+f"(d[79]),
        "+f"(d[80]),"+f"(d[81]),"+f"(d[82]),"+f"(d[83]),"+f"(d[84]),"+f"(d[85]),"+f"(d[86]),"+f"(d[87]),
        "+f"(d[88]),"+f"(d[89]),"+f"(d[90]),"+f"(d[91]),"+f"(d[92]),"+f"(d[93]),"+f"(d[94]),"+f"(d[95])
      : "l"(da), "l"(db));
}
template <int SD>
__device__ __forceinline__ void wgmma_rs_n128(float (&d)[64], uint32_t a0, uint32_t a1, uint32_t a2, uint32_t a3, uint64_t db) {
  asm volatile("wgmma.mma_async.sync.aligned.m64n128k16.f32.bf16.bf16 {"
      "%0,%1,%2,%3,%4,%5,%6,%7,%8,%9,%10,%11,%12,%13,%14,%15,"
      "%16,%17,%18,%19,%20,%21,%22,%23,%24,%25,%26,%27,%28,%29,%30,%31,"
      "%32,%33,%34,%35,%36,%37,%38,%39,%40,%41,%42,%43,%44,%45,%46,%47,"
      "%48,%49,%50,%51,%52,%53,%54,%55,%56,%57,%58,%59,%60,%61,%62,%63"
      "}, {%64,%65,%66,%67}, %68, %69, 1, 1, 1;\n"
      : "+f"(d[0]),"+f"(d[1]),"+f"(d[2]),"+f"(d[3]),"+f"(d[4]),"+f"(d[5]),"+f"(d[6]),"+f"(d[7]),
        "+f"(d[8]),"+f"(d[9]),"+f"(d[10]),"+f"(d[11]),"+f"(d[12]),"+f"(d[13]),"+f"(d[14]),"+f"(d[15]),
        "+f"(d[16]),"+f"(d[17]),"+f"(d[18]),"+f"(d[19]),"+f"(d[20]),"+f"(d[21]),"+f"(d[22]),"+f"(d[23]),
        "+f"(d[24]),"+f"(d[25]),"+f"(d[26]),"+f"(d[27]),"+f"(d[28]),"+f"(d[29]),"+f"(d[30]),"+f"(d[31]),
        "+f"(d[32]),"+f"(d[33]),"+f"(d[34]),"+f"(d[35]),"+f"(d[36]),"+f"(d[37]),"+f"(d[38]),"+f"(d[39]),
        "+f"(d[40]),"+f"(d[41]),"+f"(d[42]),"+f"(d[43]),"+f"(d[44]),"+f"(d[45]),"+f"(d[46]),"+f"(d[47]),
        "+f"(d[48]),"+f"(d[49]),"+f"(d[50]),"+f"(d[51]),"+f"(d[52]),"+f"(d[53]),"+f"(d[54]),"+f"(d[55]),
        "+f"(d[56]),"+f"(d[57]),"+f"(d[58]),"+f"(d[59]),"+f"(d[60]),"+f"(d[61]),"+f"(d[62]),"+f"(d[63])
      : "r"(a0), "r"(a1), "r"(a2), "r"(a3), "l"(db), "n"(SD));
}
__device__ __forceinline__ void wgmma_rs_n256(float (&d)[128], uint32_t a0, uint32_t a1, uint32_t a2, uint32_t a3, uint64_t db, int sd = 1) {
  asm volatile("{.reg .pred p; setp.ne.b32 p, %133, 0;\n"
      "wgmma.mma_async.sync.aligned.m64n256k16.f32.bf16.bf16 {"
      "%0,%1,%2,%3,%4,%5,%6,%7,%8,%9,%10,%11,%12,%13,%14,%15,"
      "%16,%17,%18,%19,%20,%21,%22,%23,%24,%25,%26,%27,%28,%29,%30,%31,"
      "%32,%33,%34,%35,%36,%37,%38,%39,%40,%41,%42,%43,%44,%45,%46,%47,"
      "%48,%49,%50,%51,%52,%53,%54,%55,%56,%57,%58,%59,%60,%61,%62,%63,"
      "%64,%65,%66,%67,%68,%69,%70,%71,%72,%73,%74,%75,%76,%77,%78,%79,"
      "%80,%81,%82,%83,%84,%85,%86,%87,%88,%89,%90,%91,%92,%93,%94,%95,"
      "%96,%97,%98,%99,%100,%101,%102,%103,%104,%105,%106,%107,%108,%109,%110,%111,"
      "%112,%113,%114,%115,%116,%117,%118,%119,%120,%121,%122,%123,%124,%125,%126,%127"
      "}, {%128,%129,%130,%131}, %132, p, 1, 1, 1;}\n"
      : "+f"(d[0]),"+f"(d[1]),"+f"(d[2]),"+f"(d[3]),"+f"(d[4]),"+f"(d[5]),"+f"(d[6]),"+f"(d[7]),
        "+f"(d[8]),"+f"(d[9]),"+f"(d[10]),"+f"(d[11]),"+f"(d[12]),"+f"(d[13]),"+f"(d[14]),"+f"(d[15]),
        "+f"(d[16]),"+f"(d[17]),"+f"(d[18]),"+f"(d[19]),"+f"(d[20]),"+f"(d[21]),"+f"(d[22]),"+f"(d[23]),
        "+f"(d[24]),"+f"(d[25]),"+f"(d[26]),"+f"(d[27]),"+f"(d[28]),"+f"(d[29]),"+f"(d[30]),"+f"(d[31]),
        "+f"(d[32]),"+f"(d[33]),"+f"(d[34]),"+f"(d[35]),"+f"(d[36]),"+f"(d[37]),"+f"(d[38]),"+f"(d[39]),
        "+f"(d[40]),"+f"(d[41]),"+f"(d[42]),"+f"(d[43]),"+f"(d[44]),"+f"(d[45]),"+f"(d[46]),"+f"(d[47]),
        "+f"(d[48]),"+f"(d[49]),"+f"(d[50]),"+f"(d[51]),"+f"(d[52]),"+f"(d[53]),"+f"(d[54]),"+f"(d[55]),
        "+f"(d[56]),"+f"(d[57]),"+f"(d[58]),"+f"(d[59]),"+f"(d[60]),"+f"(d[61]),"+f"(d[62]),"+f"(d[63]),
        "+f"(d[64]),"+f"(d[65]),"+f"(d[66]),"+f"(d[67]),"+f"(d[68]),"+f"(d[69]),"+f"(d[70]),"+f"(d[71]),
        "+f"(d[72]),"+f"(d[73]),"+f"(d[74]),"+f"(d[75]),"+f"(d[76]),"+f"(d[77]),"+f"(d[78]),"+f"(d[79]),
        "+f"(d[80]),"+f"(d[81]),"+f"(d[82]),"+f"(d[83]),"+f"(d[84]),"+f"(d[85]),"+f"(d[86]),"+f"(d[87]),
        "+f"(d[88]),"+f"(d[89]),"+f"(d[90]),"+f"(d[91]),"+f"(d[92]),"+f"(d[93]),"+f"(d[94]),"+f"(d[95]),
        "+f"(d[96]),"+f"(d[97]),"+f"(d[98]),"+f"(d[99]),"+f"(d[100]),"+f"(d[101]),"+f"(d[102]),"+f"(d[103]),
        "+f"(d[104]),"+f"(d[105]),"+f"(d[106]),"+f"(d[107]),"+f"(d[108]),"+f"(d[109]),"+f"(d[110]),"+f"(d[111]),
        "+f"(d[112]),"+f"(d[113]),"+f"(d[114]),"+f"(d[115]),"+f"(d[116]),"+f"(d[117]),"+f"(d[118]),"+f"(d[119]),
        "+f"(d[120]),"+f"(d[121]),"+f"(d[122]),"+f"(d[123]),"+f"(d[124]),"+f"(d[125]),"+f"(d[126]),"+f"(d[127])
      : "r"(a0), "r"(a1), "r"(a2), "r"(a3), "l"(db), "r"(sd));
}
__device__ __forceinline__ void wgmma_rs_n192(float (&d)[96], uint32_t a0, uint32_t a1, uint32_t a2, uint32_t a3, uint64_t db) {
  asm volatile("wgmma.mma_async.sync.aligned.m64n192k16.f32.bf16.bf16 {"
      "%0,%1,%2,%3,%4,%5,%6,%7,%8,%9,%10,%11,%12,%13,%14,%15,"
      "%16,%17,%18,%19,%20,%21,%22,%23,%24,%25,%26,%27,%28,%29,%30,%31,"
      "%32,%33,%34,%35,%36,%37,%38,%39,%40,%41,%42,%43,%44,%45,%46,%47,"
      "%48,%49,%50,%51,%52,%53,%54,%55,%56,%57,%58,%59,%60,%61,%62,%63,"
      "%64,%65,%66,%67,%68,%69,%70,%71,%72,%73,%74,%75,%76,%77,%78,%79,"
      "%80,%81,%82,%83,%84,%85,%86,%87,%88,%89,%90,%91,%92,%93,%94,%95"
      "}, {%96,%97,%98,%99}, %100, 1, 1, 1, 1;\n"
      : "+f"(d[0]),"+f"(d[1]),"+f"(d[2]),"+f"(d[3]),"+f"(d[4]),"+f"(d[5]),"+f"(d[6]),"+f"(d[7]),
        "+f"(d[8]),"+f"(d[9]),"+f"(d[10]),"+f"(d[11]),"+f"(d[12]),"+f"(d[13]),"+f"(d[14]),"+f"(d[15]),
        "+f"(d[16]),"+f"(d[17]),"+f"(d[18]),"+f"(d[19]),"+f"(d[20]),"+f"(d[21]),"+f"(d[22]),"+f"(d[23]),
        "+f"(d[24]),"+f"(d[25]),"+f"(d[26]),"+f"(d[27]),"+f"(d[28]),"+f"(d[29]),"+f"(d[30]),"+f"(d[31]),
        "+f"(d[32]),"+f"(d[33]),"+f"(d[34]),"+f"(d[35]),"+f"(d[36]),"+f"(d[37]),"+f"(d[38]),"+f"(d[39]),
        "+f"(d[40]),"+f"(d[41]),"+f"(d[42]),"+f"(d[43]),"+f"(d[44]),"+f"(d[45]),"+f"(d[46]),"+f"(d[47]),
        "+f"(d[48]),"+f"(d[49]),"+f"(d[50]),"+f"(d[51]),"+f"(d[52]),"+f"(d[53]),"+f"(d[54]),"+f"(d[55]),
        "+f"(d[56]),"+f"(d[57]),"+f"(d[58]),"+f"(d[59]),"+f"(d[60]),"+f"(d[61]),"+f"(d[62]),"+f"(d[63]),
        "+f"(d[64]),"+f"(d[65]),"+f"(d[66]),"+f"(d[67]),"+f"(d[68]),"+f"(d[69]),"+f"(d[70]),"+f"(d[71]),
        "+f"(d[72]),"+f"(d[73]),"+f"(d[74]),"+f"(d[75]),"+f"(d[76]),"+f"(d[77]),"+f"(d[78]),"+f"(d[79]),
        "+f"(d[80]),"+f"(d[81]),"+f"(d[82]),"+f"(d[83]),"+f"(d[84]),"+f"(d[85]),"+f"(d[86]),"+f"(d[87]),
        "+f"(d[88]),"+f"(d[89]),"+f"(d[90]),"+f"(d[91]),"+f"(d[92]),"+f"(d[93]),"+f"(d[94]),"+f"(d[95])
      : "r"(a0), "r"(a1), "r"(a2), "r"(a3), "l"(db));
}


constexpr int C_LN = 0, C_PX = 16, C_PY = 32;
constexpr int NB_CONS = 1, NB_LN = 2, NB_LAG = 4, NB_INIT = 6, NB_RDY = 7, NB_WG = 8;
constexpr int LAGX = 3;
constexpr int LAGY = 6;
constexpr int LAG2 = 5;
constexpr int NLL = 2;
constexpr int POLL_DELAY3 = 600;
constexpr int POLL_DELAY = 1200;
constexpr int FILT_DELAY = 800;
constexpr int WARM = 4;
constexpr int ALEAD = 6;
constexpr int POLL_DELAY2 = 1000;
constexpr int REDPOS = 4;
constexpr int XTRIG = 20;
constexpr int HTRIG = 0;
constexpr int RING_SIG = 1;
constexpr int PF2_SIG = 1;
constexpr int SM_E = 0, SM_X = 16384, SM_E2 = 32768, SM_W = 49152, SM_FC = 69632, SM_T = 73728 - T1_BYTES;
constexpr unsigned long long KORDER = 0xBA9432DC876510ull;
constexpr unsigned long long BSLOT = 0x52140A98D52140ull, PSLOT = 0xB763CB763CB763ull;
constexpr unsigned long long BDEP = 0xFFEC97531ull, PDEP = 0xBA754ull;
constexpr uint32_t HI128 = desc_hi(1024, 1), HI64 = desc_hi(512, 2);

struct Bars {
  uint64_t full1[32], empty1[32], full2[16], fullA[8], empty2[8], fullP[32], emptyP[9], hbar, tbar, hint[3], sig[2], sbar, freeA[4];
  uint32_t epoch, pad;
};

template <int NK, bool STORE, int J0 = 0, int J1 = NK>
__device__ __forceinline__ void make_p(const float (&acc)[NK * 16], float r0, float r1, uint4 (&p)[NK], uint4* pbase, int ks0, uint32_t tag) {
#pragma unroll
  for (int j = J0; j < J1; j++) {
    uint32_t w[4];
#pragma unroll
    for (int i = 0; i < 4; i++) {
      const int a = 8 * j + 2 * i, b = a + NK * 8;
      w[i] = pack2(swiglu(acc[a], acc[b], (i & 1) ? r1 : r0), swiglu(acc[a + 1], acc[b + 1], (i & 1) ? r1 : r0));
    }
    asm volatile("" : "+r"(w[0]), "+r"(w[1]), "+r"(w[2]), "+r"(w[3]));
    p[j] = make_uint4(w[0], w[1], w[2], w[3]);
    if (STORE) st_tag(pbase + ((ks0 + j) >> 2) * 1024 + ((ks0 + j) & 3) * 32, p[j], tag);
  }
}
__device__ __forceinline__ void spin_until(uint32_t t) {
  while ((int)(clock32() - t) < 0) {}
}

__global__ void __cluster_dims__(2, 1, 1) __launch_bounds__(NTHREADS, 1)
fused_kernel(const __nv_bfloat16* __restrict__ x, const Tables* __restrict__ tab, Scratch* __restrict__ scr,
             __nv_bfloat16* __restrict__ out, const char* __restrict__ wg_raw, const char* __restrict__ wu_raw,
             const char* __restrict__ wd_raw,
             const __grid_constant__ CUtensorMap tmWR, const __grid_constant__ CUtensorMap tmWI,
             const __grid_constant__ CUtensorMap tmGX, const __grid_constant__ CUtensorMap tmUX,
             const __grid_constant__ CUtensorMap tmGY, const __grid_constant__ CUtensorMap tmUY,
             const __grid_constant__ CUtensorMap tmD) {
  extern __shared__ __align__(1024) char smem_raw[];
  const uint32_t sbase = s2u(smem_raw);
  const uint32_t sbar = sbase + 14 * SLOT, sstat = sbar + 1408;
  const int tid = threadIdx.x, lane = tid & 31;
  const int c = blockIdx.x, rk = c & 1, f = (c >> 1) & 7, rb = 2 * (c >> 4) + rk;
  const int rb2 = 2 * (c >> 4) + (f >> 2), kh = (f >> 1) & 1, nq = 2 * (f & 1) + rk;
#define BAR(field, i) (sbar + (uint32_t)offsetof(Bars, field) + 8u * (i))
#define TOFF(field) (sbase + SM_T + (uint32_t)offsetof(Tables, field) + lane * 16)

  if (tid >= 256) {
    asm volatile("setmaxnreg.dec.sync.aligned.u32 40;");
    const int warp = __shfl_sync(0xffffffffu, tid >> 5, 0);
    if (lane == 0) {
      if (warp == 8) {
        if (sbase & 1023) die();
#pragma unroll
        for (int i = 0; i < 21; i++) mbar_init(BAR(emptyP, i), i < 9 ? 8 : i < 14 ? 1 : i < 16 ? 8 : i == 16 ? 32 : 16);
        mbar_expect(BAR(tbar, 0), T2_BYTES + 2 * 10240);
        mbar_expect(BAR(hbar, 0), 16384);
      } else if (warp == 9) {
#pragma unroll
        for (int i = 0; i < 32; i++) mbar_init(BAR(full1, i), 1);
#pragma unroll
        for (int i = 0; i < 32; i++) mbar_expect(BAR(full1, i), i < 16 ? 16384 : 12288);
      } else if (warp == 10) {
#pragma unroll
        for (int i = 0; i < 32; i++) mbar_init(BAR(empty1, i), 16);
#pragma unroll
        for (int i = 0; i < 30; i++) mbar_init(BAR(fullP, i), 1);
#pragma unroll
        for (int i = 0; i < 30; i++) mbar_expect(BAR(fullP, i), 8192);
      } else {
#pragma unroll
        for (int i = 0; i < 32; i++) mbar_init(BAR(full2, i), i < 24 ? 1 : 8);
#pragma unroll
        for (int i = 0; i < 24; i++) mbar_expect(BAR(full2, i), 16384);
      }
      asm volatile("fence.mbarrier_init.release.cluster;" ::: "memory");
    }
    if (tid == 256) {
      const int w0 = ((c >> 3) * 257 + 32 * (c & 7) + 1) & ~7;
      if (FILT_DELAY) {
        asm volatile("prefetch.tensormap [%0];" ::"l"(&tmWR) : "memory");
        asm volatile("prefetch.tensormap [%0];" ::"l"(&tmWI) : "memory");
        spin_until(clock32() + FILT_DELAY);
      }
      tma3(sbase + SM_W, &tmWR, BAR(tbar, 0), w0, 0, 0);
      tma3(sbase + SM_W + 10240, &tmWI, BAR(tbar, 0), w0, 0, 0);
      bulk_load(sbase + SM_T + T1_BYTES, reinterpret_cast<const char*>(tab) + T1_BYTES, T2_BYTES, BAR(tbar, 0));
    }
    if (tid == 288) {
      asm volatile("prefetch.tensormap [%0];" ::"l"(rk ? &tmUX : &tmGX) : "memory");
      asm volatile("prefetch.tensormap [%0];" ::"l"(rk ? &tmUY : &tmGY) : "memory");
      asm volatile("prefetch.tensormap [%0];" ::"l"(&tmD) : "memory");
    }
    if (tid == 320) {
      const unsigned e = ld_relaxed(&scr->cnt[(C_LN + rb) * 32]) >> 3;
      asm volatile("st.shared.u32 [%0], %1;" ::"r"(BAR(epoch, 0)), "r"(e) : "memory");
    }
    __syncwarp();
    asm volatile("barrier.cluster.arrive.relaxed.aligned;" ::: "memory");
    bar_arrive(NB_RDY, 384);
    asm volatile("barrier.cluster.wait.aligned;" ::: "memory");
    bar_sync(NB_INIT, 384);
    unsigned epoch;
    asm volatile("ld.shared.u32 %0, [%1];" : "=r"(epoch) : "r"(BAR(epoch, 0)) : "memory");
    if (warp == 8) {
      if (lane == 0) {
        const int ax = (7 * f + 3 * (f & 1)) >> 1;
        const int ay = 7 * f + ((f & 1) ? 0 : 4);
        const CUtensorMap* tx = rk ? &tmUX : &tmGX;
        const CUtensorMap* ty = rk ? &tmUY : &tmGY;
        if (RING_SIG >= 0) mbar_wait(BAR(sig, RING_SIG));
        uint32_t s = 2;
#pragma unroll 1
        for (int n = 0; n < 16; n++) {
          if (n >= 6) mbar_wait(BAR(empty1, n - 6));
          tma3_mc(sbase + (8 + s) * SLOT + rk * 8192, tx, BAR(full1, n), n * 32, ax);
          if (++s == 6) s = 0;
          if (n >= 10 && n < 15) {
            const int k = n - 10;
            mbar_wait(BAR(freeA, (12 * k + 11) >> 4));
            tma3_mc(sbase + k * 12288 + rk * 6144, ty, BAR(full1, 16 + k), (k + 8) * 32, ay);
          }
        }
#pragma unroll 1
        for (int k = 5; k < 16; k++) {
          mbar_wait(BAR(empty1, k < 13 ? 10 + ((12 * (k - 5) + 11) >> 4) : 8 + k));
          tma3_mc(sbase + 8 * SLOT + ((k - 5) & 7) * 12288 + rk * 6144, ty, BAR(full1, 16 + k), ((k + 8) & 15) * 32, ay);
        }
      }
    } else if (warp == 9) {
      if (lane == 0) {
        mbar_wait(BAR(fullA, 4));
        wait_counter(&scr->cnt[(C_LN + rb2) * 32], (epoch + 1) * 8);
        asm volatile("fence.proxy.async.global;" ::: "memory");
#pragma unroll 1
        for (int i = 0; i < 14; i++) {
          const int kblk = 14 * kh + (int)((KORDER >> (4 * i)) & 15);
          mbar_wait(i < 9 ? BAR(empty1, 16 + (uint32_t)((BDEP >> (4 * i)) & 15)) : BAR(empty2, i - 9));
          tma3(sbase + (uint32_t)((BSLOT >> (4 * i)) & 15) * SLOT, &tmD, BAR(full2, i), 0, 64 * kblk, 2 * nq);
        }
        mbar_wait(BAR(empty2, 5));
        bulk_load(sbase + 13 * SLOT, &scr->LN[(rb2 * 8 + 2 * nq) * 1024 + kh * 512], 8192, BAR(hbar, 0));
        bulk_load(sbase + 13 * SLOT + 8192, &scr->LN[(rb2 * 8 + 2 * nq + 1) * 1024 + kh * 512], 8192, BAR(hbar, 0));
      }
    } else if (warp == 10) {
      bar_sync(NB_LN, 288);
      if (lane == 0) {
        red_release(&scr->cnt[(C_LN + rb) * 32]);
        wait_counter(&scr->cnt[(C_LN + rb) * 32], (epoch + 1) * 8);
        asm volatile("fence.proxy.async.global;" ::: "memory");
#pragma unroll 1
        for (int kb = NLL; kb < 8; kb++) {
          if (2 * kb >= ALEAD) mbar_wait(BAR(empty1, 2 * kb - ALEAD));
          bulk_load(sbase + kb * SLOT, &scr->LN[(rb * 8 + kb) * 1024], 16384, BAR(fullA, kb));
        }
#pragma unroll 1
        for (int s = 0; s < 14; s++) {
          const int kblk = 14 * kh + (int)((KORDER >> (4 * s)) & 15);
          if (s == 0 || s == 8 || s == 11) {
            mbar_wait(BAR(hint, s == 0 ? 0 : s == 8 ? 1 : 2), 0);
          }
          mbar_wait(s < 5 ? BAR(empty1, 16 + (uint32_t)((PDEP >> (4 * s)) & 15)) : BAR(emptyP, s - 5));
          bulk_load_mc(sbase + (uint32_t)((PSLOT >> (4 * s)) & 15) * SLOT + rk * 8192, &scr->P[(rb2 * 28 + kblk) * 1024 + rk * 512], 8192, BAR(fullP, 16 * rk + s));
        }
      }
    } else {
      if (lane == 0) {
        mbar_wait(BAR(tbar, 0));
        l2_prefetch(wg_raw + (size_t)c * 5376, 5376);
        l2_prefetch(wu_raw + (size_t)c * 5376, 5376);
        mbar_wait(BAR(sig, PF2_SIG), 0);
        l2_prefetch(wg_raw + 688128 + (size_t)c * 8960, 8960);
        l2_prefetch(wu_raw + 688128 + (size_t)c * 8960, 8960);
      }
      mbar_wait(BAR(fullA, 4), 0);
      if (lane == 0) l2_prefetch(wd_raw + (size_t)c * 14336, 14336);
      {
        const uint32_t tag = (epoch + 1) & 1;
        uint4 v0, v1, v2;
        int it = 0;
        while (true) {
          v0 = ld_b128(&scr->ST[rb * 64 + lane]);
          v1 = ld_b128(&scr->ST[rb * 64 + 32 + lane]);
          v2 = ld_b128(&scr->ST[rb2 * 64 + 32 * kh + lane]);
          if (!__any_sync(0xffffffffu, ((v0.x ^ tag) | (v1.x ^ tag) | (v2.x ^ tag)) & 1u)) break;
          if (++it > SPIN_LIMIT) { die(); break; }
        }
        sts4(sstat + lane * 16, v0.x & ~1u, v0.y, v0.z, v0.w);
        sts4(sstat + 512 + lane * 16, v1.x & ~1u, v1.y, v1.z, v1.w);
        sts4(sstat + 1024 + lane * 16, v2.x & ~1u, v2.y, v2.z, v2.w);
        mbar_arrive(BAR(sbar, 0));
      }
      if (lane == 0) {
        mbar_wait(BAR(empty1, XTRIG));
        int it = 0;
        while ((int)(ld_relaxed(&scr->cnt[(C_PX + rb2) * 32 + kh]) - (epoch + 1) * 32) < 0) {
          if (++it > SPIN_LIMIT) { die(); break; }
        }
        mbar_arrive(BAR(hint, 0));
        mbar_wait(BAR(emptyP, HTRIG));
        uint32_t done = 0;
        while (done != 3) {
          uint2 v;
          asm volatile("ld.relaxed.gpu.global.v2.u32 {%0,%1}, [%2];" : "=r"(v.x), "=r"(v.y) : "l"(&scr->cnt[(C_PY + rb2) * 32 + 4 * (rk ^ kh ^ 1) + 2 * kh]) : "memory");
          if (!(done & 1) && (int)(v.x - (epoch + 1) * 8) >= 0) { done |= 1; mbar_arrive(BAR(hint, 1)); }
          if (!(done & 2) && (int)(v.y - (epoch + 1) * 8) >= 0) { done |= 2; mbar_arrive(BAR(hint, 2)); }
          if (++it > SPIN_LIMIT) { die(); break; }
        }
      }
    }
  } else {
    const int warp = __shfl_sync(0xffffffffu, tid >> 5, 0);
    const int g = lane >> 2, t = lane & 3;
    uint4 fa[4], fb[4], tw[6];
#pragma unroll
    for (int i = 0; i < 4; i++) fa[i] = ldg_ca4(&tab->fa[i][lane][0]);
#pragma unroll
    for (int i = 0; i < 6; i++) tw[i] = ldg_ca4(&tab->tw1[i][lane][0]);
#pragma unroll
    for (int i = 0; i < 4; i++) fb[i] = ldg_ca4(&tab->fb[i][lane][0]);
#pragma unroll
    for (int i = 0; i < 4; i++) {
      const int r = i >> 1, ch = (i & 1) * 32 + lane;
      cp_async16(sbase + SM_X + (2 * warp + r) * 1024 + ((ch ^ ((ch >> 3) & 1)) * 16),
                 x + (size_t)(c + 128 * (2 * warp + r)) * 512 + ch * 8);
    }
    asm volatile("cp.async.commit_group;" ::: "memory");
    asm volatile("barrier.cluster.arrive.relaxed.aligned;" ::: "memory");
    uint32_t rbar;
    asm volatile("mapa.shared::cluster.u32 %0, %1, %2;" : "=r"(rbar) : "r"(sbar), "r"(rk ^ 1));
#define RBAR(field, i) (rbar + (uint32_t)offsetof(Bars, field) + 8u * (i))
    {
      const int ln = (tid >> 1) & 31, lg = ln >> 2, lt = ln & 3, i = 4 * (tid >> 6) + 2 * (tid & 1);
      const int kidx = lt + 8 * (i >> 3), nidx = 4 * ((i >> 1) & 3) + (lg >> 1);
      const uint32_t a0 = cfrag<2048>((c + 128 * kidx) * nidx, lg & 1), a1 = cfrag<2048>((c + 128 * (kidx + 4)) * nidx, lg & 1);
      const uint32_t b0 = cfrag<2048>(-(c + 128 * nidx) * kidx, lg & 1), b1 = cfrag<2048>(-(c + 128 * nidx) * (kidx + 4), lg & 1);
      asm volatile("st.shared.v2.u32 [%0], {%1,%2};" ::"r"(sbase + SM_FC + tid * 8), "r"(a0), "r"(a1) : "memory");
      asm volatile("st.shared.v2.u32 [%0], {%1,%2};" ::"r"(sbase + SM_FC + 2048 + tid * 8), "r"(b0), "r"(b1) : "memory");
    }
    bar_sync(NB_CONS, 256);
    uint4 fc[4];
#pragma unroll
    for (int i = 0; i < 4; i++) fc[i] = lds4(sbase + SM_FC + i * 512 + lane * 16);
    asm volatile("cp.async.wait_group 0;" ::: "memory");
    __syncwarp();
    bar_arrive(NB_INIT, 384);
    uint32_t tag, ones;
    uint4 q[4], o[4];
    {
      uint32_t v[2][8];
#pragma unroll
      for (int r = 0; r < 2; r++)
#pragma unroll
        for (int ks = 0; ks < 2; ks++) {
          const int ch = 32 * ks + 2 * (lane & 15) + (lane >> 4);
          asm volatile("ldmatrix.sync.aligned.m8n8.x4.trans.shared.b16 {%0,%1,%2,%3}, [%4];"
                       : "=r"(v[r][4 * ks]), "=r"(v[r][4 * ks + 1]), "=r"(v[r][4 * ks + 2]), "=r"(v[r][4 * ks + 3])
                       : "r"(sbase + SM_X + (2 * warp + r) * 1024 + ((ch ^ ((ch >> 3) & 1)) * 16)) : "memory");
        }
      float sq[2];
#pragma unroll
      for (int r = 0; r < 2; r++) {
        float s0 = 0.f, s1 = 0.f;
#pragma unroll
        for (int i = 0; i < 8; i++) {
          const float lo = bf_lo(v[r][i]), hi = u2f(v[r][i] & 0xffff0000u);
          s0 = fmaf(lo, lo, s0);
          s1 = fmaf(hi, hi, s1);
        }
        sq[r] = s0 + s1;
      }
      {
        float w = ((lane & 1) ? sq[1] : sq[0]) + __shfl_xor_sync(0xffffffffu, (lane & 1) ? sq[0] : sq[1], 1);
        w += __shfl_xor_sync(0xffffffffu, w, 2);
        w = sum_groups(w);
        const float o2 = __shfl_xor_sync(0xffffffffu, w, 1);
        sq[0] = (lane & 1) ? o2 : w;
        sq[1] = (lane & 1) ? w : o2;
      }
#pragma unroll
      for (int r = 0; r < 2; r++) {
        float dd[2][4], ee[2][4];
#pragma unroll
        for (int nt = 0; nt < 2; nt++) {
          mma_az(dd[nt], fa[0], v[r][2 * nt], v[r][2 * nt + 1]);
          mma_a(dd[nt], fa[1], v[r][4 + 2 * nt], v[r][5 + 2 * nt]);
          mma_az(ee[nt], fa[2], v[r][2 * nt], v[r][2 * nt + 1]);
          mma_a(ee[nt], fa[3], v[r][4 + 2 * nt], v[r][5 + 2 * nt]);
        }
        float mean = (dd[0][0] + dd[0][1]) + (dd[1][0] + dd[1][1]);
        mean += __shfl_xor_sync(0xffffffffu, mean, 1);
        mean += __shfl_xor_sync(0xffffffffu, mean, 2);
        mean = __shfl_sync(0xffffffffu, mean, 0) * (1.f / 512.f);
        const float rs = rsqrtf(fmaxf(fmaf(-mean, mean, sq[r] * (1.f / 512.f)), 0.f) + 1e-5f);
        float acc[4][4];
#pragma unroll
        for (int nt = 0; nt < 2; nt++) {
          const float (&d)[4] = dd[nt];
          const float (&e)[4] = ee[nt];
          const uint4 &ka = tw[2 * nt], &kb = tw[2 * nt + 1], &kc = tw[4 + nt];
          const uint32_t a0 = pack2(d[0] * u2f(ka.x) + d[2] * u2f(ka.y), d[1] * u2f(kb.x) + d[3] * u2f(kb.y));
          const uint32_t a2 = pack2(d[0] * u2f(ka.z) + d[2] * u2f(ka.w), d[1] * u2f(kb.z) + d[3] * u2f(kb.w));
          const uint32_t a1 = pack2(e[0] * u2f(kc.x) + e[2] * u2f(kc.y), e[1] * u2f(kc.z) + e[3] * u2f(kc.w));
          const uint32_t a3 = pack2(e[2] * u2f(kc.x) - e[0] * u2f(kc.y), e[3] * u2f(kc.z) - e[1] * u2f(kc.w));
          const uint32_t dc = pack2(fmaf(mean, -32.f, d[0]), fmaf(mean, -32.f, d[1]));
          const uint32_t h0 = g == 0 ? dc : a0, h2 = g == 0 ? 0u : a2;
          if (nt == 0) {
            mma16816_z(acc[0], a0, a1, a2, a3, fb[2 * nt].x, fb[2 * nt].y);
            mma16816_z(acc[1], a0, a1, a2, a3, fb[2 * nt].z, fb[2 * nt].w);
            mma16816_z(acc[2], h0, a1, h2, a3, fb[2 * nt + 1].x, fb[2 * nt + 1].y);
            mma16816_z(acc[3], h0, a1, h2, a3, fb[2 * nt + 1].z, fb[2 * nt + 1].w);
          } else {
            mma16816(acc[0], a0, a1, a2, a3, fb[2 * nt].x, fb[2 * nt].y);
            mma16816(acc[1], a0, a1, a2, a3, fb[2 * nt].z, fb[2 * nt].w);
            mma16816(acc[2], h0, a1, h2, a3, fb[2 * nt + 1].x, fb[2 * nt + 1].y);
            mma16816(acc[3], h0, a1, h2, a3, fb[2 * nt + 1].z, fb[2 * nt + 1].w);
          }
        }
#pragma unroll
        for (int h = 0; h < 2; h++) {
          const int j = 2 * warp + r, m = 2 * t + h;
          sts4(sbase + SM_E + ((j * 8 + m) * 8 + (g ^ (2 * t) ^ (2 * (j & 3)))) * 16,
               pack2(acc[h][0] * rs, acc[h][1] * rs), pack2(acc[h][2] * rs, acc[h][3] * rs),
               pack2(acc[2 + h][0] * rs, acc[2 + h][1] * rs), pack2(acc[2 + h][2] * rs, acc[2 + h][3] * rs));
        }
      }
      bar_sync(NB_RDY, 384);
      const uint32_t ea = sbase + SM_E + ((t * 8 + warp) * 8 + (g ^ (warp & 6) ^ (2 * t))) * 16;
      lds_frag(q[0], q[1], ea, ea + 4096);
      lds_frag(q[2], q[3], ea + 8192, ea + 12288);
      asm volatile("ld.shared.u32 %0, [%1];" : "=r"(tag) : "r"(BAR(epoch, 0)) : "memory");
      ones = ~(tag >> 31);
      tag = (tag + 1) & 1;
      cdft16(q, fc, o);
#pragma unroll
      for (int vv = 0; vv < 4; vv++) {
        o[vv].y &= ~1u;
        o[vv].z = (o[vv].z & ~1u) | (tag ^ 1);
        st_tag(&scr->Z1[(((4 * vv + t) * 8 + warp) * 128 + c) * 8 + g], o[vv], tag);
      }
    }
    asm volatile("setmaxnreg.inc.sync.aligned.u32 232;");
    {
      uint4* const zp = &scr->Z1[(c * 128 + 8 * t + warp) * 8 + g];
      const uint32_t tst = clock32();
      mbar_wait(BAR(tbar, 0), 0);
      uint4 f2[4], g2[4];
#pragma unroll
      for (int i = 0; i < 4; i++) {
        f2[i] = lds4(TOFF(f2) + warp * 2048 + i * 512);
        g2[i] = lds4(TOFF(g2) + warp * 2048 + i * 512);
      }
      const uint4 f8 = lds4(TOFF(f8)), g8 = lds4(TOFF(g8));
      asm volatile("barrier.cluster.wait.aligned;" ::: "memory");
      spin_until(tst + POLL_DELAY);
      ld_tag4_issue<256>(q, zp);
      float wfr[16], wfi[16];
      {
        const float nyq = ((c & 7) == 7 && g == 0) ? 0.5f : 1.f;
        uint32_t wa = sbase + SM_W + (16 * warp + t) * 80 + ((2 * (c >> 3) + 2) & 15) - 2;
        asm volatile("" : "+r"(wa));
        const uint32_t wb[3] = {wa + 2 * (g == 0 ? 16 : g), wa + 2 * g, wa - 2 * g};
#pragma unroll
        for (int i = 0; i < 16; i++) {
          const int ci = i >> 3, dd = (i >> 2) & 1, e = i & 3;
          const uint32_t a = wb[e < 2 ? e : 2] + (ci * 8 + 4 * dd) * 80 + (e == 0 ? 0 : e == 1 ? 16 : e == 2 ? 64 : 48);
          wfr[i] = bf_lo(lds_u16(a)) * (e == 2 ? nyq : 1.f);
          wfi[i] = bf_lo(lds_u16(a + 10240)) * (e == 2 ? nyq : 1.f);
        }
      }
      ld_tag4_finish<256>(q, zp, tag);
      if (lane == 0) mbar_arrive(BAR(sig, 0));
#pragma unroll
      for (int i = 0; i < 4; i++) q[i].z &= ~1u;
      reg_frag(q, ones);
      cdft16(q, f2, o);
      const uint32_t e2 = sbase + SM_E2;
#pragma unroll
      for (int vv = 0; vv < 4; vv++)
        sts4(e2 + ((warp * 16 + 4 * vv + t) * 8 + (g ^ (2 * t) ^ (2 * (warp & 3)))) * 16, o[vv].x, o[vv].y, o[vv].z, o[vv].w);
      bar_sync(NB_CONS, 256);
      uint32_t ad[2], res[2][2][4];
#pragma unroll
      for (int ci = 0; ci < 2; ci++) {
        const int cc = 2 * warp + ci;
        ad[ci] = e2 + ((t * 16 + cc) * 8 + (g ^ (2 * (cc & 3)) ^ (2 * t))) * 16;
        lds_frag(q[2 * ci], q[2 * ci + 1], ad[ci], ad[ci] + 8192);
      }
#pragma unroll
      for (int ci = 0; ci < 2; ci++)
#pragma unroll
        for (int p = 0; p < 2; p++) {
          uint32_t y[2][2];
#pragma unroll
          for (int vv = 0; vv < 2; vv++) {
            float d[4];
            mma_az(d, q[2 * ci + p], word(f8, 2 * vv), word(f8, 2 * vv + 1));
#pragma unroll
            for (int rr = 0; rr < 2; rr++) {
              const float fr = wfr[ci * 8 + vv * 4 + 2 * p + rr], fi = wfi[ci * 8 + vv * 4 + 2 * p + rr];
              y[vv][rr] = pack2(d[2 * rr] * fr - d[2 * rr + 1] * fi, d[2 * rr] * fi + d[2 * rr + 1] * fr);
            }
          }
#pragma unroll
          for (int vv = 0; vv < 2; vv++) {
            float d[4];
            mma16816_z(d, y[0][0], y[0][1], y[1][0], y[1][1], word(g8, 2 * vv), word(g8, 2 * vv + 1));
            res[ci][vv][2 * p] = pack2(d[0], d[1]);
            res[ci][vv][2 * p + 1] = pack2(d[2], d[3]);
          }
        }
#pragma unroll
      for (int i = 0; i < 4; i++)
        sts4(ad[i >> 1] + (i & 1) * 8192, res[i >> 1][i & 1][0], res[i >> 1][i & 1][1], res[i >> 1][i & 1][2], res[i >> 1][i & 1][3]);
      bar_sync(NB_CONS, 256);
      const uint32_t eb = e2 + ((warp * 16 + t) * 8 + (g ^ (2 * t) ^ (2 * (warp & 3)))) * 16;
      lds_frag(q[0], q[1], eb, eb + 512);
      lds_frag(q[2], q[3], eb + 1024, eb + 1536);
      cdft16(q, g2, o);
#pragma unroll
      for (int vv = 0; vv < 4; vv++) {
        o[vv].y &= ~1u;
        o[vv].z = (o[vv].z & ~1u) | tag;
        st_tag(zp + vv * 256, o[vv], tag);
      }
    }
    {
      const uint4* const zp = &scr->Z1[((t * 8 + warp) * 128 + c) * 8 + g];
      const uint32_t tst = clock32();
      uint4 gb[4], ga[4], gc[4], tw[4];
      uint2 xr[2][4];
      uint2* lnp[2];
#pragma unroll
      for (int r = 0; r < 2; r++) {
        const int row = 16 * f + 2 * warp + r;
        lnp[r] = reinterpret_cast<uint2*>(&scr->LN[(rb * 8 + (g >> 2)) * 1024 + row * 8 + ((2 * (g & 3) + (t >> 1)) ^ (row & 7))]) + (t & 1);
        asm volatile("" : "+l"(lnp[r]));
      }
#pragma unroll
      for (int i = 0; i < 4; i++) {
        gc[i] = lds4(sbase + SM_FC + 2048 + i * 512 + lane * 16);
        gb[i] = lds4(TOFF(gb) + i * 512);
        ga[i] = lds4(TOFF(ga) + i * 512);
        tw[i] = lds4(TOFF(tw3) + i * 512);
        const int ch = 2 * (g + 8 * i) + (t >> 1);
#pragma unroll
        for (int r = 0; r < 2; r++) xr[r][i] = lds2(sbase + SM_X + (2 * warp + r) * 1024 + ((ch ^ ((ch >> 3) & 1)) * 16) + (t & 1) * 8);
      }
      spin_until(tst + POLL_DELAY2);
      ld_tag4_issue<32768>(q, zp);
      ld_tag4_finish<32768, true>(q, zp, tag);
      if (lane == 0) mbar_arrive(BAR(sig, 1));
      reg_frag(q, ones);
      cdft16(q, gc, o);
#pragma unroll
      for (int vv = 0; vv < 4; vv++)
        sts4(sbase + SM_E + (((4 * vv + t) * 8 + warp) * 8 + (g ^ (warp & 6) ^ (2 * t))) * 16, o[vv].x, o[vv].y, o[vv].z, o[vv].w);
      bar_sync(NB_CONS, 256);
      uint32_t hv[2][8];
      const float mk = t == 0 ? 0.f : 1.f;
#pragma unroll
      for (int r = 0; r < 2; r++) {
        const int j = 2 * warp + r;
        uint4 u[2];
#pragma unroll
        for (int h = 0; h < 2; h++) u[h] = lds4(sbase + SM_E + ((j * 8 + 2 * t + h) * 8 + (g ^ (2 * t) ^ (2 * (j & 3)))) * 16);
        const uint32_t bp[4][2] = {{u[0].x, u[1].x & ones}, {u[0].y & ones, u[1].y}, {u[0].z, u[1].z & ones}, {u[0].w & ones, u[1].w}};
        float y[2][2][4];
#pragma unroll
        for (int i = 0; i < 2; i++) {
          float lo[4], hi[4], e[4];
          mma_az(lo, gb[2 * i], bp[0][0], bp[0][1]);
          mma_az(hi, gb[2 * i + 1], bp[2][0], bp[2][1]);
          mma_az(e, gb[2 * i], bp[1][0], bp[1][1]);
          mma_a(e, gb[2 * i + 1], bp[3][0], bp[3][1]);
          const uint4 &ka = tw[2 * i], &kb = tw[2 * i + 1];
          const float tr0 = fmaf(hi[0], mk, lo[0]), ti0 = fmaf(hi[2], mk, lo[2]);
          const float tr1 = lo[1] + hi[1], ti1 = lo[3] + hi[3];
          const float vr0 = tr0 * u2f(ka.x) - ti0 * u2f(ka.y), vi0 = tr0 * u2f(ka.y) + ti0 * u2f(ka.x);
          const float vr1 = tr1 * u2f(ka.z) - ti1 * u2f(ka.w), vi1 = tr1 * u2f(ka.w) + ti1 * u2f(ka.z);
          const uint32_t b0 = pack2(t == 0 ? hi[0] : vr0, vr1), b1 = pack2(t == 0 ? vr0 : vi0, vi1);
          const uint32_t b2 = pack2(e[0] * u2f(kb.x) - e[2] * u2f(kb.y), e[1] * u2f(kb.z) - e[3] * u2f(kb.w));
          const uint32_t b3 = pack2(e[0] * u2f(kb.y) + e[2] * u2f(kb.x), e[1] * u2f(kb.w) + e[3] * u2f(kb.z));
#pragma unroll
          for (int mt = 0; mt < 2; mt++) {
            mma_az(y[mt][i], ga[2 * mt], b0, b1);
            mma_a(y[mt][i], ga[2 * mt + 1], b2, b3);
          }
        }
#pragma unroll
        for (int i = 0; i < 4; i++) {
          hv[r][2 * i] = hadd2_bf16(xr[r][i].x, pack2(y[i >> 1][0][2 * (i & 1)], y[i >> 1][0][2 * (i & 1) + 1]));
          hv[r][2 * i + 1] = hadd2_bf16(xr[r][i].y, pack2(y[i >> 1][1][2 * (i & 1)], y[i >> 1][1][2 * (i & 1) + 1]));
        }
      }
      float mean[2];
      uint32_t mb[2];
#pragma unroll
      for (int r = 0; r < 2; r++) {
        mean[r] = sum_groups(quad_sum(hv[r])) * (1.f / 512.f);
        mb[r] = pack2(mean[r], mean[r]);
      }
#pragma unroll
      for (int i = 0; i < 4; i++)
#pragma unroll
        for (int r = 0; r < 2; r++) {
          hv[r][2 * i] = hsub2_bf16(hv[r][2 * i], mb[r]);
          hv[r][2 * i + 1] = hsub2_bf16(hv[r][2 * i + 1], mb[r]);
          st_tag8(lnp[r] + i * 4096, hv[r][2 * i], hv[r][2 * i + 1], i == 0 ? tag : (hv[r][2 * i] & 1u));
        }
      bar_arrive(NB_LN, 288);
      const uint32_t ones2 = ~(lds2(BAR(epoch, 0)).x >> 31);
      float rstd[2];
#pragma unroll
      for (int r = 0; r < 2; r++) {
        hv[r][0] &= ones2;
        rstd[r] = row_rstd(hv[r], mean[r] - bf_lo(mb[r]));
      }
      if (lane == 0)
        st_tag(&scr->ST[rb * 64 + 8 * f + warp], make_uint4(mb[0] << 16, __float_as_uint(rstd[0]), mb[1] << 16, __float_as_uint(rstd[1])), tag);
    }
    const int wgi = warp >> 2, wq = warp & 3;
    const int wr = wgi ^ (f >> 2) ^ 1, rt = 4 * wr + wq;
    uint4* const pbase = &scr->P[rb * 28 * 1024 + rt * 128 + lane];
    const uint32_t a_lo0 = desc_lo(sbase + wr * 8192, 16);
    const uint32_t ebar = lane == 0 ? BAR(empty1, 0) : RBAR(empty1, 0);
    float r0, r1;
    uint4 px[8], py[6];
    const int rh = wgi ^ kh ^ 1;
    const uint32_t fpb = BAR(fullP, 16 * rh);
    const uint4* const psrc = &scr->P[(rb2 * 28 + 14 * kh) * 1024 + (4 * rh + wq) * 128 + lane];
    const uint32_t pa0 = sbase + (4 * rh + wq) * 2048;
    uint4 pf[3][4], ha[4][4];
    uint32_t rdy = 0, got0;
    {
      float acc[128];
#pragma unroll
      for (int i = 0; i < 128; i++) acc[i] = 0.f;
      const uint32_t b_lo0 = desc_lo(sbase + 8 * SLOT, 4096);
      const uint32_t t3 = clock32();
      if (WARM) {
        wg_fence();
#pragma unroll
        for (int i = 0; i < WARM; i++) wgmma_n256(acc, desc64(a_lo0 + 6 * 1024, HI128), desc64(b_lo0, HI128));
        wg_commit();
      }
      const uint4* const ap = &scr->LN[rb * 8 * 1024 + wr * 512 + (tid & 127)];
      uint4 av[NLL][4];
      spin_until(t3 + POLL_DELAY3);
#pragma unroll
      for (int kb = 0; kb < NLL; kb++) ld_tag4_issue<128>(av[kb], ap + kb * 1024);
      bar_sync(NB_CONS, 256);
      const uint32_t lma = sbase + (16 * rt + (lane & 15)) * 128;
      auto load_a = [&](int kb) {
#pragma unroll
        for (int ks = 0; ks < 4; ks++)
          asm volatile("ldmatrix.sync.aligned.m8n8.x4.shared.b16 {%0,%1,%2,%3}, [%4];"
                       : "=r"(ha[kb][ks].x), "=r"(ha[kb][ks].y), "=r"(ha[kb][ks].z), "=r"(ha[kb][ks].w)
                       : "r"(lma + kb * SLOT + (((2 * ks + (lane >> 4)) ^ (lane & 7)) * 16)) : "memory");
      };
      auto stash_a = [&](int kb) {
        ld_tag4_finish<128, true>(av[kb], ap + kb * 1024, tag);
#pragma unroll
        for (int i = 0; i < 4; i++)
          sts4(sbase + kb * SLOT + wr * 8192 + ((tid & 127) + 128 * i) * 16, av[kb][i].x, av[kb][i].y, av[kb][i].z, av[kb][i].w);
        bar_sync(NB_WG + wgi, 128);
      };
      stash_a(0);
      load_a(0);
#pragma unroll
      for (int n = 0; n < 8; n++) {
        const int kb = n >> 1, hh = n & 1;
        if (hh == 1 && kb < 3) {
          if (kb + 1 < NLL) stash_a(kb + 1); else mbar_wait(BAR(fullA, kb + 1));
        }
        mbar_wait(BAR(full1, n));
        const uint32_t bl = b_lo0 + ((n + 2) % 6) * 1024;
        wg_fence();
        if (hh == 1 && kb < 3) load_a(kb + 1);
        const uint4 &a0 = ha[kb][2 * hh], &a1 = ha[kb][2 * hh + 1];
        wgmma_rs_n256(acc, a0.x, a0.y, a0.z, a0.w, desc64(bl, HI128), n != 0 ? 1 : ~ones);
        wgmma_rs_n256(acc, a1.x, a1.y, a1.z, a1.w, desc64(bl + 128, HI128));
        wg_commit();
        if (hh == 1 && lane < 2) mbar_arrive_remote(ebar + (uint32_t)(offsetof(Bars, freeA) - offsetof(Bars, empty1)) + 8 * kb);
        wg_wait<1>();
        if (n != 0 && lane < 2) mbar_arrive_remote(ebar + 8 * (n - 1));
      }
      uint32_t slot = 4;
#pragma unroll 1
      for (int kb = 4; kb < 8; kb++) {
        mbar_wait(BAR(fullA, kb));
#pragma unroll
        for (int hh = 0; hh < 2; hh++) {
          if (LAGX && hh == ((16 - LAGX) & 1) && kb == ((16 - LAGX) >> 1) && wgi == 1) bar_sync(NB_LAG, 256);
          mbar_wait(BAR(full1, 2 * kb + hh));
          const uint32_t al = a_lo0 + kb * 1024 + hh * 4, bl = b_lo0 + slot * 1024;
          wg_fence();
          wgmma_n256(acc, desc64(al, HI128), desc64(bl, HI128));
          wgmma_n256(acc, desc64(al + 2, HI128), desc64(bl + 128, HI128));
          wg_commit();
          if (LAGX && hh == 1 && kb == 7 && wgi == 0) bar_arrive(NB_LAG, 256);
          wg_wait<1>();
          if (lane < 2) mbar_arrive_remote(ebar + 8 * (2 * kb + hh - 1));
          if (++slot == 6) slot = 0;
        }
      }
      mbar_wait(BAR(sbar, 0), 0);
      r0 = __uint_as_float(lds2(sstat + (16 * rt + g) * 8).y);
      r1 = __uint_as_float(lds2(sstat + (16 * rt + g + 8) * 8).y);
      wg_wait<0>();
      if (lane < 2) mbar_arrive_remote(ebar + 8 * 15);
      make_p<8, false>(acc, r0, r1, px, pbase, 0, tag);
    }
    {
      float acc[96];
#pragma unroll
      for (int i = 0; i < 96; i++) acc[i] = 0.f;
      const uint32_t b_lo0 = desc_lo(sbase, 2048);
      uint4* const pdst = pbase + ((7 * f + 3 * (f & 1)) >> 1) * 1024;
      auto stage_y = [&](int k) {
        if (LAGY && k == 16 - LAGY && wgi == 1) bar_sync(NB_LAG, 256);
        mbar_wait(BAR(full1, 16 + k));
        const uint32_t al = a_lo0 + (4 + (k >> 1)) * 1024 + (k & 1) * 4, bl = b_lo0 + (k < 5 ? k * 768 : 8192 + (k - 5) * 768);
        wg_fence();
        wgmma_n192(acc, desc64(al, HI128), desc64(bl, HI64));
        wgmma_n192(acc, desc64(al + 2, HI128), desc64(bl + 64, HI64));
        wg_commit();
      };
#pragma unroll
      for (int k = 0; k < 4; k++) {
        stage_y(k);
        st_tag(pdst + (k >> 1) * 1024 + (k & 1) * 64, px[2 * k], tag);
        st_tag(pdst + (k >> 1) * 1024 + (k & 1) * 64 + 32, px[2 * k + 1], tag);
        if (k == 3 && lane == 0) red_relaxed(&scr->cnt[(C_PX + rb) * 32 + (f >> 2)]);
        wg_wait<1>();
        if (k != 0 && lane < 2) mbar_arrive_remote(ebar + 8 * (15 + k));
      }
#pragma unroll 1
      for (int k = 4; k < 8; k++) {
        stage_y(k);
        wg_wait<1>();
        if (lane < 2) mbar_arrive_remote(ebar + 8 * (15 + k));
      }
      rdy = 0;
#pragma unroll
      for (int k = 8; k < 16; k++) {
        if (LAGY && k == 16 - LAGY && wgi == 1) bar_sync(NB_LAG, 256);
        if (!rdy) mbar_wait(BAR(full1, 16 + k));
        const uint32_t bl = b_lo0 + 8192 + ((k - 5) & 7) * 768;
        const uint4 &a0 = ha[(k - 8) >> 1][2 * (k & 1)], &a1 = ha[(k - 8) >> 1][2 * (k & 1) + 1];
        wg_fence();
        if (k < 15) rdy = mbar_test(BAR(full1, 17 + k));
        wgmma_rs_n192(acc, a0.x, a0.y, a0.z, a0.w, desc64(bl, HI64));
        wgmma_rs_n192(acc, a1.x, a1.y, a1.z, a1.w, desc64(bl + 64, HI64));
        wg_commit();
        if (LAGY && k == 15 && wgi == 0) bar_arrive(NB_LAG, 256);
        wg_wait<1>();
        if (lane < 2) mbar_arrive_remote(ebar + 8 * (15 + k));
      }
      got0 = __all_sync(0xffffffffu, mbar_test((fpb + 8 * (0))));
      if (got0) {
#pragma unroll
        for (int kk = 0; kk < 4; kk++) pf[0][kk] = lds4(pa0 + 3 * SLOT + kk * 512 + lane * 16);
      }
      wg_wait<0>();
      if (lane < 2) mbar_arrive_remote(ebar + 8 * 31);
      const int ks0 = 14 * f + ((f & 1) ? 0 : 8);
      auto reread = [&]() {
        asm volatile("ld.volatile.shared.f32 %0, [%2+4]; ld.volatile.shared.f32 %1, [%2+68];" : "=f"(r0), "=f"(r1) : "r"(sstat + (16 * rt + g) * 8) : "memory");
      };
      make_p<6, true, 0, 2>(acc, r0, r1, py, pbase, ks0, tag);
      if (REDPOS == 2 && lane == 0) red_relaxed(&scr->cnt[(C_PY + rb) * 32 + 4 * wgi + (f >> 1)]);
      reread();
      make_p<6, true, 2, 4>(acc, r0, r1, py, pbase, ks0, tag);
      if (REDPOS == 4 && lane == 0) red_relaxed(&scr->cnt[(C_PY + rb) * 32 + 4 * wgi + (f >> 1)]);
      reread();
      rdy = mbar_test(BAR(full2, 0)) & mbar_test((fpb + 8 * (1)));
      make_p<6, true, 4, 6>(acc, r0, r1, py, pbase, ks0, tag);
      if (REDPOS == 6 && lane == 0) red_relaxed(&scr->cnt[(C_PY + rb) * 32 + 4 * wgi + (f >> 1)]);
    }
    {
      float acc[64];
      const uint32_t b2_lo0 = desc_lo(sbase, 8192);
      const uint32_t pbar = rh == rk ? BAR(emptyP, 0) : RBAR(emptyP, 0);
      if (!got0) {
        mbar_wait((fpb + 8 * (0)));
#pragma unroll
        for (int kk = 0; kk < 4; kk++) pf[0][kk] = lds4(pa0 + 3 * SLOT + kk * 512 + lane * 16);
      }
#pragma unroll
      for (int s = 0; s < 14; s++) {
        uint4 (&a)[4] = pf[s % 3];
        ld_tag4_finish<32>(a, psrc + (int)((KORDER >> (4 * s)) & 15) * 1024, tag);
        if (s < 9 && lane == 0) mbar_arrive_remote(pbar + 8 * s);
        if (s >= 2) {
          wg_wait<1>();
          if (s <= 7 && lane == 0) mbar_arrive(BAR(empty2, s - 2));
        }
        if (!rdy) {
          if (s < 13) mbar_wait((fpb + 8 * (s + 1)));
          mbar_wait(BAR(full2, s));
        }
        if (s == 14 - LAG2 && wgi == 1) {
          const float m0 = __uint_as_float(lds2(sstat + 1024 + (16 * wq + g) * 8).x);
          const float m1 = __uint_as_float(lds2(sstat + 1024 + (16 * wq + g + 8) * 8).x);
          const uint32_t hb = sbase + 13 * SLOT + (16 * wq + (lane & 15)) * 128;
          wg_wait<0>();
          mbar_wait(BAR(hbar, 0));
#pragma unroll
          for (int i = 0; i < 8; i++) {
            uint32_t h[4];
            asm volatile("ldmatrix.sync.aligned.m8n8.x4.shared.b16 {%0,%1,%2,%3}, [%4];"
                         : "=r"(h[0]), "=r"(h[1]), "=r"(h[2]), "=r"(h[3])
                         : "r"(hb + (i >> 2) * 8192 + (((2 * (i & 3) + (lane >> 4)) ^ (lane & 7)) * 16)) : "memory");
            const uint32_t mk = ((t & 1) == 0 && nq == 0) ? ~1u : ~0u;
#pragma unroll
            for (int e = 0; e < 4; e++) {
              acc[8 * i + 2 * e] += bf_lo(h[e] & mk) + ((e & 1) ? m1 : m0);
              acc[8 * i + 2 * e + 1] += __uint_as_float(h[e] & 0xffff0000u) + ((e & 1) ? m1 : m0);
            }
          }
          bar_sync(NB_LAG, 256);
        }
        const uint32_t bl = b2_lo0 + (uint32_t)((BSLOT >> (4 * s)) & 15) * 1024;
        wg_fence();
        if (s < 13) {
#pragma unroll
          for (int kk = 0; kk < 4; kk++)
            pf[(s + 1) % 3][kk] = lds4(pa0 + (uint32_t)((PSLOT >> (4 * (s + 1))) & 15) * SLOT + kk * 512 + lane * 16);
          rdy = mbar_test(BAR(full2, s + 1));
          if (s < 12) rdy &= mbar_test((fpb + 8 * (s + 2)));
        }
        if (s == 0) wgmma_rs_n128<0>(acc, a[0].x, a[0].y, a[0].z, a[0].w, desc64(bl, HI128));
        else wgmma_rs_n128<1>(acc, a[0].x, a[0].y, a[0].z, a[0].w, desc64(bl, HI128));
#pragma unroll
        for (int kk = 1; kk < 4; kk++) wgmma_rs_n128<1>(acc, a[kk].x, a[kk].y, a[kk].z, a[kk].w, desc64(bl + kk * 128, HI128));
        wg_commit();
      }
      if (wgi == 0) {
        bar_arrive(NB_LAG, 256);
        uint4* const dst = &scr->Z1[(tid >> 3) * 1024 + (c ^ 4) * 8 + (tid & 7)];
        wg_wait<0>();
#pragma unroll
        for (int i = 0; i < 8; i++)
          st_tag(dst + i * 16384, make_uint4(pack2(acc[8 * i], acc[8 * i + 1]), pack2(acc[8 * i + 2], acc[8 * i + 3]) | 1u,
                                           pack2(acc[8 * i + 4], acc[8 * i + 5]), pack2(acc[8 * i + 6], acc[8 * i + 7])), tag);
      } else {
        uint4 pv[2][4];
        const uint4* const xsrc = &scr->Z1[((tid & 127) >> 3) * 1024 + c * 8 + (tid & 7)];
        ld_tag4_issue<16384>(pv[0], xsrc);
        ld_tag4_issue<16384>(pv[1], xsrc + 65536);
        wg_wait<0>();
        uint32_t w[32];
#pragma unroll
        for (int i = 0; i < 32; i++) w[i] = pack2(acc[2 * i], acc[2 * i + 1]);
        int it = 0;
#pragma unroll 1
        while (!__all_sync(0xffffffffu, pv[0][0].y & pv[0][1].y & pv[0][2].y & pv[0][3].y & pv[1][0].y & pv[1][1].y & pv[1][2].y & pv[1][3].y & 1u)) {
          ld_tag4_issue<16384>(pv[0], xsrc);
          ld_tag4_issue<16384>(pv[1], xsrc + 65536);
          if (++it > SPIN_LIMIT) { die(); break; }
        }
#pragma unroll
        for (int i = 0; i < 8; i++) {
          const uint4& p = pv[i >> 2][i & 3];
          asm volatile("stmatrix.sync.aligned.m8n8.x4.shared.b16 [%0], {%1,%2,%3,%4};"
                       ::"r"(pa0 + (11 + ((lane >> 3) & 1)) * SLOT + (lane & 7) * 256 + (((2 * i + (lane >> 4)) ^ (lane & 7)) * 16)),
                         "r"(hadd2_bf16(w[4 * i], p.x & ~1u)), "r"(hadd2_bf16(w[4 * i + 1], p.y & ~1u)), "r"(hadd2_bf16(w[4 * i + 2], p.z)),
                         "r"(hadd2_bf16(w[4 * i + 3], p.w)) : "memory");
        }
        __syncwarp();
        uint4* const dst = reinterpret_cast<uint4*>(out) + (16 * (c >> 4) + 2 * (4 * rh + wq) + (rb2 & 1) + 128 * (lane >> 4)) * 64 + nq * 16 + (lane & 15);
#pragma unroll
        for (int i = 0; i < 8; i++) {
          const int r = 2 * (i & 3) + (lane >> 4);
          dst[i * 256 * 64] = lds4(pa0 + (11 + (i >> 2)) * SLOT + r * 256 + (((lane & 15) ^ r) * 16));
        }
      }
    }
  }
#undef BAR
#undef TOFF
#undef RBAR
}

typedef CUresult (*EncodeFn)(CUtensorMap*, CUtensorMapDataType, cuuint32_t, void*, const cuuint64_t*, const cuuint64_t*,
                             const cuuint32_t*, const cuuint32_t*, CUtensorMapInterleave, CUtensorMapSwizzle,
                             CUtensorMapL2promotion, CUtensorMapFloatOOBfill);

}

extern "C" void kernel_launch(void* const* d_in, const int* in_sizes, int n_in, void* d_out, int out_size) {
  (void)in_sizes; (void)n_in; (void)out_size;
  static EncodeFn encode = nullptr;
  static void *tab = nullptr, *scr = nullptr;
  if (!encode) {
    void* fn = nullptr;
    cudaDriverEntryPointQueryResult qr;
    cudaGetDriverEntryPoint("cuTensorMapEncodeTiled", &fn, cudaEnableDefault, &qr);
    encode = (EncodeFn)fn;
    cudaGetSymbolAddress(&tab, g_tab);
    cudaGetSymbolAddress(&scr, g_scr);
    cudaFuncSetAttribute(fused_kernel, cudaFuncAttributeMaxDynamicSharedMemorySize, SMEM_BYTES);
  }
  CUtensorMap tmGX, tmUX, tmGY, tmUY, tmD, tmWR, tmWI;
  const cuuint32_t es[5] = {1, 1, 1, 1, 1};
  auto enc = [&](CUtensorMap* m, void* p, int rank, const cuuint64_t* gd, const cuuint64_t* gs, const cuuint32_t* bd,
                 CUtensorMapSwizzle sw, CUtensorMapL2promotion pr) {
    encode(m, CU_TENSOR_MAP_DATA_TYPE_BFLOAT16, rank, p, gd, gs, bd, es, CU_TENSOR_MAP_INTERLEAVE_NONE, sw, pr,
           CU_TENSOR_MAP_FLOAT_OOB_FILL_NONE);
  };
  {
    const cuuint64_t gd[3] = {64, 512, 28}, gs[2] = {3584, 128};
    const cuuint32_t bd[3] = {64, 32, 2};
    enc(&tmGX, d_in[4], 3, gd, gs, bd, CU_TENSOR_MAP_SWIZZLE_128B, CU_TENSOR_MAP_L2_PROMOTION_L2_256B);
    enc(&tmUX, d_in[5], 3, gd, gs, bd, CU_TENSOR_MAP_SWIZZLE_128B, CU_TENSOR_MAP_L2_PROMOTION_L2_256B);
  }
  {
    const cuuint64_t gd[3] = {32, 512, 56}, gs[2] = {3584, 64};
    const cuuint32_t bd[3] = {32, 32, 3};
    enc(&tmGY, d_in[4], 3, gd, gs, bd, CU_TENSOR_MAP_SWIZZLE_64B, CU_TENSOR_MAP_L2_PROMOTION_L2_128B);
    enc(&tmUY, d_in[5], 3, gd, gs, bd, CU_TENSOR_MAP_SWIZZLE_64B, CU_TENSOR_MAP_L2_PROMOTION_L2_128B);
  }
  {
    const cuuint64_t gd[3] = {64, 1792, 8}, gs[2] = {1024, 128};
    const cuuint32_t bd[3] = {64, 64, 2};
    enc(&tmD, d_in[6], 3, gd, gs, bd, CU_TENSOR_MAP_SWIZZLE_128B, CU_TENSOR_MAP_L2_PROMOTION_L2_256B);
  }
  {
    const cuuint64_t gd[3] = {4112, 8, 16}, gs[2] = {16 * 8224, 8224};
    const cuuint32_t bd[3] = {40, 8, 16};
    enc(&tmWR, d_in[1], 3, gd, gs, bd, CU_TENSOR_MAP_SWIZZLE_NONE, CU_TENSOR_MAP_L2_PROMOTION_NONE);
    enc(&tmWI, d_in[2], 3, gd, gs, bd, CU_TENSOR_MAP_SWIZZLE_NONE, CU_TENSOR_MAP_L2_PROMOTION_NONE);
  }
  fused_kernel<<<NCTA, NTHREADS, SMEM_BYTES>>>((const __nv_bfloat16*)d_in[0], (const Tables*)tab, (Scratch*)scr,
                                               (__nv_bfloat16*)d_out, (const char*)d_in[4], (const char*)d_in[5],
                                               (const char*)d_in[6], tmWR, tmWI, tmGX, tmUX, tmGY, tmUY, tmD);
}
```

```cpp
#include <cuda_runtime.h>
#include <cuda_bf16.h>
#include <cuda.h>
#include <stdint.h>

namespace {

constexpr int NCTA = 128;
constexpr int NTHREADS = 384;
constexpr int SLOT = 16384;
constexpr int SMEM_BYTES = 14 * SLOT + 3072;
constexpr int SPIN_LIMIT = 1 << 22;

struct Scratch {
  uint4 Z1[128 * 1024];
  uint4 LN[16 * 8 * 1024];
  uint4 P[16 * 28 * 1024];
  uint4 ST[1024];
  unsigned cnt[64 * 32];
};
__device__ __align__(1024) Scratch g_scr;

constexpr double ccos(int i, int n) {
  i &= n - 1;
  if (i > n / 2) i = n - i;
  if (4 * i == n) return 0.0;
  const bool neg = 4 * i > n;
  if (neg) i = n / 2 - i;
  const double a = 6.283185307179586476925 * i / n, a2 = a * a;
  double term = 1.0, sum = 1.0;
  for (int k = 1; k < 14; k++) { term *= -a2 / ((2 * k - 1) * (2 * k)); sum += term; }
  return neg ? -sum : sum;
}
constexpr double csin(int i, int n) { return ccos(i - n / 4, n); }
constexpr unsigned fbits(double v, int mant) {
  if (v == 0.0) return 0;
  const unsigned sg = v < 0 ? 1u : 0u;
  if (v < 0) v = -v;
  int e = 127;
  while (v < 1.0) { v *= 2.0; e--; }
  const unsigned m = (unsigned)((v - 1.0) * (double)(1u << mant) + 0.5);
  return (sg << (8 + mant)) + ((unsigned)e << mant) + m;
}
constexpr unsigned pkb(double lo, double hi) { return fbits(lo, 7) | (fbits(hi, 7) << 16); }
constexpr double fa_elem(int mt, int r, int n1) {
  const int k1 = 8 * mt + (r & 7);
  return r < 8 ? ccos(k1 * n1, 32) : k1 == 0 ? ccos(16 * n1, 32) : -csin(k1 * n1, 32);
}
constexpr unsigned cfrag_c(int idx, int n, int ri, double s = 1.0) {
  return ri ? pkb(-s * csin(idx, n), s * ccos(idx, n)) : pkb(s * ccos(idx, n), s * csin(idx, n));
}
struct Tables {
  unsigned fa[4][32][4];
  unsigned fb[4][32][4];
  unsigned tw1[6][32][4];
  unsigned f2[8][4][32][4];
  unsigned g2[8][4][32][4];
  unsigned gb[4][32][4];
  unsigned ga[4][32][4];
  unsigned tw3[4][32][4];
  unsigned f8[32][4], g8[32][4];
};
constexpr int T1_BYTES = 7168, T2_BYTES = 39936;
static_assert(sizeof(Tables) == T1_BYTES + T2_BYTES, "table size");
constexpr Tables make_tables() {
  Tables T = {};
  for (int l = 0; l < 32; l++) {
    const int g = l >> 2, t = l & 3;
    for (int a = 0; a < 2; a++)
      for (int b = 0; b < 2; b++) {
        for (int r = 0; r < 4; r++) {
          const int row = g + 8 * (r & 1), col = 2 * t + 8 * (r >> 1);
          T.fa[2 * a + b][l][r] = pkb(fa_elem(a, row, 16 * b + col), fa_elem(a, row, 16 * b + col + 1));
          T.ga[2 * a + b][l][r] = pkb(fa_elem(b, col, 16 * a + row), fa_elem(b, col + 1, 16 * a + row));
        }
        const double sg = b ? -1.0 : 1.0;
        for (int h = 0; h < 2; h++) {
          const int ri = g & 1, m = 2 * (g >> 1) + h, k2 = b ? 15 - m : m;
          const int pa = (8 * a + 2 * t) * k2, pb = (8 * a + 2 * t + 1) * k2;
          T.fb[2 * a + b][l][2 * h] = ri == 0 ? pkb(ccos(pa, 16), ccos(pb, 16)) : pkb(-sg * csin(pa, 16), -sg * csin(pb, 16));
          T.fb[2 * a + b][l][2 * h + 1] = ri == 0 ? pkb(csin(pa, 16), csin(pb, 16)) : pkb(sg * ccos(pa, 16), sg * ccos(pb, 16));
        }
        const int n2 = 4 * (g >> 1) + 2 * a + (g & 1);
        for (int h = 0; h < 2; h++) {
          const int p = n2 * (b ? 15 - 2 * t - h : 2 * t + h);
          T.gb[2 * a + b][l][2 * h] = pkb(ccos(p, 16), -sg * csin(p, 16));
          T.gb[2 * a + b][l][2 * h + 1] = pkb(csin(p, 16), sg * ccos(p, 16));
          const int k1 = 8 * b + 2 * t + h, q = n2 * (k1 == 0 ? 16 : k1);
          T.tw3[2 * a + b][l][2 * h] = fbits(ccos(q, 512), 23);
          T.tw3[2 * a + b][l][2 * h + 1] = fbits(csin(q, 512), 23);
        }
        const int p = (8 * a + 2 * t + b) * (g == 0 ? 16 : g);
        T.tw1[2 * a + b][l][0] = fbits(g == 0 ? 0.0 : ccos(p, 512), 23);
        T.tw1[2 * a + b][l][1] = fbits(g == 0 ? ccos(p, 512) : csin(p, 512), 23);
        T.tw1[2 * a + b][l][2] = fbits(g == 0 ? 0.0 : -csin(p, 512), 23);
        T.tw1[2 * a + b][l][3] = fbits(g == 0 ? -csin(p, 512) : ccos(p, 512), 23);
        T.tw1[4 + a][l][2 * b] = fbits(ccos((8 * a + 2 * t + b) * (g + 8), 512), 23);
        T.tw1[4 + a][l][2 * b + 1] = fbits(csin((8 * a + 2 * t + b) * (g + 8), 512), 23);
      }
    for (int i = 0; i < 4; i++) {
      const int p8 = (t + 4 * (i & 1)) * (4 * (i >> 1) + (g >> 1));
      T.f8[l][i] = cfrag_c(p8, 8, g & 1);
      T.g8[l][i] = cfrag_c(-p8, 8, g & 1, 1.0 / (1 << 19));
    }
    for (int w = 0; w < 8; w++)
      for (int i = 0; i < 16; i++) {
        const int kidx = t + 4 * (i & 1) + 8 * (i >> 3), nidx = 4 * ((i >> 1) & 3) + (g >> 1);
        T.f2[w][i >> 2][l][i & 3] = cfrag_c((8 * kidx + w) * nidx, 128, g & 1);
        T.g2[w][i >> 2][l][i & 3] = cfrag_c(-(8 * nidx + w) * kidx, 128, g & 1);
      }
  }
  return T;
}
__device__ const __align__(128) Tables g_tab = make_tables();

__device__ __forceinline__ void die() { asm volatile("st.global.u32 [%0], %1;" ::"l"(0ull), "r"(0) : "memory"); }
__device__ __forceinline__ uint32_t s2u(const void* p) { return (uint32_t)__cvta_generic_to_shared(p); }
__device__ __forceinline__ void mbar_init(uint32_t b, int c) { asm volatile("mbarrier.init.shared::cta.b64 [%0], %1;" ::"r"(b), "r"(c)); }
__device__ __forceinline__ void mbar_expect(uint32_t b, int bytes) {
  asm volatile("mbarrier.arrive.expect_tx.shared::cta.b64 _, [%0], %1;" ::"r"(b), "r"(bytes) : "memory");
}
__device__ __forceinline__ void mbar_arrive(uint32_t b) { asm volatile("mbarrier.arrive.shared::cta.b64 _, [%0];" ::"r"(b) : "memory"); }
__device__ __forceinline__ uint32_t mbar_try(uint32_t b, uint32_t parity) {
  uint32_t ok;
  asm volatile("{.reg .pred p; mbarrier.try_wait.parity.shared::cta.b64 p, [%1], %2; selp.u32 %0,1,0,p;}"
               : "=r"(ok) : "r"(b), "r"(parity) : "memory");
  return ok;
}
__device__ __forceinline__ uint32_t mbar_test(uint32_t b) {
  uint32_t ok;
  asm volatile("{.reg .pred p; mbarrier.test_wait.parity.shared::cta.b64 p, [%1], 0; selp.u32 %0,1,0,p;}" : "=r"(ok) : "r"(b) : "memory");
  return ok;
}
__device__ __forceinline__ void mbar_wait(uint32_t b, uint32_t parity = 0) {
  int it = 0;
#pragma unroll 1
  while (!mbar_try(b, parity))
    if (++it > SPIN_LIMIT) { die(); break; }
}
__device__ __forceinline__ void bar_sync(int id, int n) { asm volatile("bar.sync %0, %1;" ::"r"(id), "r"(n) : "memory"); }
__device__ __forceinline__ void bar_arrive(int id, int n) { asm volatile("bar.arrive %0, %1;" ::"r"(id), "r"(n) : "memory"); }
__device__ __forceinline__ void red_release(unsigned* p) { asm volatile("red.release.gpu.global.add.u32 [%0], 1;" ::"l"(p) : "memory"); }
__device__ __forceinline__ void red_relaxed(unsigned* p) { asm volatile("red.relaxed.gpu.global.add.u32 [%0], 1;" ::"l"(p) : "memory"); }
__device__ __forceinline__ unsigned ld_acquire(const unsigned* p) {
  unsigned v;
  asm volatile("ld.acquire.gpu.global.u32 %0, [%1];" : "=r"(v) : "l"(p) : "memory");
  return v;
}
__device__ __forceinline__ unsigned ld_relaxed(const unsigned* p) {
  unsigned v;
  asm volatile("ld.relaxed.gpu.global.u32 %0, [%1];" : "=r"(v) : "l"(p) : "memory");
  return v;
}
__device__ __forceinline__ void wait_counter(const unsigned* p, unsigned target) {
  int it = 0;
  while ((int)(ld_acquire(p) - target) < 0)
    if (++it > SPIN_LIMIT) { die(); break; }
}
__device__ __forceinline__ void sts4(uint32_t a, uint32_t x, uint32_t y, uint32_t z, uint32_t w) {
  asm volatile("st.shared.v4.u32 [%0], {%1,%2,%3,%4};" ::"r"(a), "r"(x), "r"(y), "r"(z), "r"(w) : "memory");
}
__device__ __forceinline__ uint4 lds4(uint32_t a) {
  uint4 v;
  asm volatile("ld.shared.v4.u32 {%0,%1,%2,%3}, [%4];" : "=r"(v.x), "=r"(v.y), "=r"(v.z), "=r"(v.w) : "r"(a) : "memory");
  return v;
}
__device__ __forceinline__ uint32_t pack2(float lo, float hi) {
  uint32_t r;
  asm("cvt.rn.bf16x2.f32 %0, %1, %2;" : "=r"(r) : "f"(hi), "f"(lo));
  return r;
}
__device__ __forceinline__ float bf_lo(uint32_t v) { return __uint_as_float(v << 16); }
__device__ __forceinline__ uint32_t hadd2_bf16(uint32_t a, uint32_t b) {
  uint32_t r;
  asm("add.rn.bf16x2 %0, %1, %2;" : "=r"(r) : "r"(a), "r"(b));
  return r;
}
__device__ __forceinline__ void mma16816(float (&d)[4], uint32_t a0, uint32_t a1, uint32_t a2, uint32_t a3, uint32_t b0, uint32_t b1) {
  asm("mma.sync.aligned.m16n8k16.row.col.f32.bf16.bf16.f32 {%0,%1,%2,%3}, {%4,%5,%6,%7}, {%8,%9}, {%0,%1,%2,%3};"
      : "+f"(d[0]), "+f"(d[1]), "+f"(d[2]), "+f"(d[3])
      : "r"(a0), "r"(a1), "r"(a2), "r"(a3), "r"(b0), "r"(b1));
}
__device__ __forceinline__ void mma16816_z(float (&d)[4], uint32_t a0, uint32_t a1, uint32_t a2, uint32_t a3, uint32_t b0, uint32_t b1) {
  asm("{.reg .f32 z; mov.f32 z, 0f00000000;\n"
      "mma.sync.aligned.m16n8k16.row.col.f32.bf16.bf16.f32 {%0,%1,%2,%3}, {%4,%5,%6,%7}, {%8,%9}, {z,z,z,z};}"
      : "=f"(d[0]), "=f"(d[1]), "=f"(d[2]), "=f"(d[3])
      : "r"(a0), "r"(a1), "r"(a2), "r"(a3), "r"(b0), "r"(b1));
}
template <int N>
__device__ __forceinline__ void cs_frac(int idx, float& c, float& s) {
  int i = ((idx + N / 2) & (N - 1)) - N / 2;
  float a = (float)i * (6.283185307179586f / N);
  c = __cosf(a);
  s = __sinf(a);
}
template <int N>
__device__ __forceinline__ uint32_t cfrag(int idx, int ri) {
  float c, s;
  cs_frac<N>(idx, c, s);
  return ri ? pack2(-s, c) : pack2(c, s);
}
__device__ __forceinline__ uint32_t word(const uint4& v, int e) { return e == 0 ? v.x : e == 1 ? v.y : e == 2 ? v.z : v.w; }
__device__ __forceinline__ void cdft16(const uint4 (&A)[4], const uint4 (&F)[4], uint4 (&o)[4]) {
  float acc[2][4][4];
#pragma unroll
  for (int ks = 0; ks < 2; ks++)
#pragma unroll
    for (int p = 0; p < 2; p++)
#pragma unroll
      for (int v = 0; v < 4; v++) {
        const uint4& a = A[2 * ks + p];
        const uint32_t b0 = word(F[ks * 2 + (v >> 1)], (v & 1) * 2), b1 = word(F[ks * 2 + (v >> 1)], (v & 1) * 2 + 1);
        if (ks == 0) mma16816_z(acc[p][v], a.x, a.y, a.z, a.w, b0, b1);
        else mma16816(acc[p][v], a.x, a.y, a.z, a.w, b0, b1);
      }
#pragma unroll
  for (int v = 0; v < 4; v++)
    o[v] = make_uint4(pack2(acc[0][v][0], acc[0][v][1]), pack2(acc[0][v][2], acc[0][v][3]),
                      pack2(acc[1][v][0], acc[1][v][1]), pack2(acc[1][v][2], acc[1][v][3]));
}
__device__ __forceinline__ void lds_frag(uint4& f0, uint4& f1, uint32_t a0, uint32_t a1) {
  asm volatile("ld.volatile.shared.v2.u32 {%0,%1}, [%8]; ld.volatile.shared.v2.u32 {%2,%3}, [%9];\n"
               "ld.volatile.shared.v2.u32 {%4,%5}, [%8+8]; ld.volatile.shared.v2.u32 {%6,%7}, [%9+8];"
               : "=r"(f0.x), "=r"(f0.y), "=r"(f0.z), "=r"(f0.w), "=r"(f1.x), "=r"(f1.y), "=r"(f1.z), "=r"(f1.w) : "r"(a0), "r"(a1) : "memory");
}
__device__ __forceinline__ void reg_frag(uint4 (&q)[4], uint32_t ones) {
#pragma unroll
  for (int ks = 0; ks < 2; ks++) {
    const uint4 a = q[2 * ks], b = q[2 * ks + 1];
    q[2 * ks] = make_uint4(a.x, a.y, b.x & ones, b.y & ones);
    q[2 * ks + 1] = make_uint4(a.z & ones, a.w & ones, b.z, b.w);
  }
}
__device__ __forceinline__ void st_tag(uint4* p, const uint4& v, uint32_t tag) {
  asm volatile("st.relaxed.gpu.global.v4.b32 [%0], {%1,%2,%3,%4};"
               ::"l"(p), "r"((v.x & ~1u) | tag), "r"(v.y), "r"(v.z), "r"(v.w) : "memory");
}
__device__ __forceinline__ void st_tag8(void* p, uint32_t x, uint32_t y, uint32_t tag) {
  asm volatile("st.relaxed.gpu.global.v2.b32 [%0], {%1,%2};" ::"l"(p), "r"((x & ~1u) | tag), "r"(y) : "memory");
}
__device__ __forceinline__ uint4 ld_b128(const uint4* p) {
  uint4 v;
  asm volatile("ld.relaxed.gpu.global.v4.b32 {%0,%1,%2,%3}, [%4];"
               : "=r"(v.x), "=r"(v.y), "=r"(v.z), "=r"(v.w) : "l"(p) : "memory");
  return v;
}
template <int STRIDE>
__device__ __forceinline__ void ld_tag4_issue(uint4 (&q)[4], const uint4* p) {
#pragma unroll
  for (int i = 0; i < 4; i++) q[i] = ld_b128(p + i * STRIDE);
}
template <int STRIDE, bool HALVES = false>
__device__ __forceinline__ void ld_tag4_finish(uint4 (&q)[4], const uint4* p, uint32_t tag) {
  int it = 0;
#pragma unroll 1
  while (__any_sync(0xffffffffu, ((q[0].x ^ tag) | (q[1].x ^ tag) | (q[2].x ^ tag) | (q[3].x ^ tag) |
                                  (HALVES ? (q[0].z ^ tag) | (q[1].z ^ tag) | (q[2].z ^ tag) | (q[3].z ^ tag) : 0u)) & 1u)) {
    ld_tag4_issue<STRIDE>(q, p);
    if (++it > SPIN_LIMIT) { die(); break; }
  }
#pragma unroll
  for (int i = 0; i < 4; i++) {
    asm volatile("and.b32 %0, %0, 0xfffffffe;" : "+r"(q[i].x));
    if (HALVES) q[i].z &= ~1u;
  }
}
__device__ __forceinline__ float quad_sum(const uint32_t (&a)[8]) {
  float d[4];
  mma16816_z(d, a[0], a[1], a[2], a[3], 0x3f803f80u, 0x3f803f80u);
  mma16816(d, a[4], a[5], a[6], a[7], 0x3f803f80u, 0x3f803f80u);
  return d[0] + d[2];
}
__device__ __forceinline__ float sum_groups(float v) {
  v += __shfl_xor_sync(0xffffffffu, v, 4);
  v += __shfl_xor_sync(0xffffffffu, v, 8);
  v += __shfl_xor_sync(0xffffffffu, v, 16);
  return v;
}
__device__ __forceinline__ uint32_t hsub2_bf16(uint32_t a, uint32_t b) {
  uint32_t r;
  asm("sub.rn.bf16x2 %0, %1, %2;" : "=r"(r) : "r"(a), "r"(b));
  return r;
}
__device__ __forceinline__ float row_rstd(const uint32_t (&c)[8], float delta) {
  uint32_t s[8];
#pragma unroll
  for (int i = 0; i < 8; i++) asm("mul.rn.bf16x2 %0, %1, %1;" : "=r"(s[i]) : "r"(c[i]));
  return rsqrtf(fmaxf(fmaf(-delta, delta, sum_groups(quad_sum(s)) * (1.f / 512.f)), 0.f) + 1e-5f);
}
__device__ __forceinline__ uint64_t desc64(uint32_t lo, uint32_t hi) {
  uint64_t d;
  asm("mov.b64 %0, {%1, %2};" : "=l"(d) : "r"(lo), "r"(hi));
  return d;
}
constexpr uint32_t desc_hi(uint32_t sbo, uint32_t swz) { return (sbo >> 4) | (swz << 30); }
__device__ __forceinline__ uint32_t desc_lo(uint32_t addr, uint32_t lbo) { return ((addr & 0x3FFFF) >> 4) | ((lbo >> 4) << 16); }
__device__ __forceinline__ void cp_async16(uint32_t dst, const void* src) {
  asm volatile("cp.async.cg.shared.global [%0], [%1], 16;" ::"r"(dst), "l"(src) : "memory");
}
__device__ __forceinline__ uint2 lds2(uint32_t a) {
  uint2 v;
  asm volatile("ld.shared.v2.u32 {%0,%1}, [%2];" : "=r"(v.x), "=r"(v.y) : "r"(a) : "memory");
  return v;
}
__device__ __forceinline__ uint32_t lds_u16(uint32_t a) {
  uint16_t v;
  asm volatile("ld.shared.u16 %0, [%1];" : "=h"(v) : "r"(a) : "memory");
  return v;
}
__device__ __forceinline__ void wg_fence() { asm volatile("wgmma.fence.sync.aligned;" ::: "memory"); }
__device__ __forceinline__ void wg_commit() { asm volatile("wgmma.commit_group.sync.aligned;" ::: "memory"); }
template <int N>
__device__ __forceinline__ void wg_wait() { asm volatile("wgmma.wait_group.sync.aligned %0;" ::"n"(N) : "memory"); }
__device__ __forceinline__ void bulk_load(uint32_t dst, const void* src, int bytes, uint32_t bar) {
  asm volatile("cp.async.bulk.shared::cluster.global.mbarrier::complete_tx::bytes [%0], [%1], %2, [%3];"
               ::"r"(dst), "l"(src), "r"(bytes), "r"(bar) : "memory");
}
__device__ __forceinline__ void bulk_load_mc(uint32_t dst, const void* src, int bytes, uint32_t bar) {
  asm volatile("cp.async.bulk.shared::cluster.global.mbarrier::complete_tx::bytes.multicast::cluster [%0], [%1], %2, [%3], %4;"
               ::"r"(dst), "l"(src), "r"(bytes), "r"(bar), "h"((uint16_t)3) : "memory");
}
__device__ __forceinline__ void tma3(uint32_t dst, const CUtensorMap* tm, uint32_t bar, int c0, int c1, int c2) {
  asm volatile("cp.async.bulk.tensor.3d.shared::cluster.global.mbarrier::complete_tx::bytes [%0], [%1, {%3,%4,%5}], [%2];"
               ::"r"(dst), "l"(tm), "r"(bar), "r"(c0), "r"(c1), "r"(c2) : "memory");
}
__device__ __forceinline__ void tma3_mc(uint32_t dst, const CUtensorMap* tm, uint32_t bar, int c1, int c2) {
  asm volatile("cp.async.bulk.tensor.3d.shared::cluster.global.mbarrier::complete_tx::bytes.multicast::cluster [%0], [%1, {%3,%4,%5}], [%2], %6;"
               ::"r"(dst), "l"(tm), "r"(bar), "r"(0), "r"(c1), "r"(c2), "h"((uint16_t)3) : "memory");
}
__device__ __forceinline__ void mbar_arrive_remote(uint32_t rb) {
  asm volatile("mbarrier.arrive.shared::cluster.b64 _, [%0];" ::"r"(rb) : "memory");
}
__device__ __forceinline__ uint4 ldg_ca4(const void* p) {
  uint4 v;
  asm volatile("ld.global.ca.v4.u32 {%0,%1,%2,%3}, [%4];" : "=r"(v.x), "=r"(v.y), "=r"(v.z), "=r"(v.w) : "l"(p) : "memory");
  return v;
}
__device__ __forceinline__ float u2f(uint32_t v) { return __uint_as_float(v); }
__device__ __forceinline__ void mma_az(float (&d)[4], const uint4& a, uint32_t b0, uint32_t b1) { mma16816_z(d, a.x, a.y, a.z, a.w, b0, b1); }
__device__ __forceinline__ void mma_a(float (&d)[4], const uint4& a, uint32_t b0, uint32_t b1) { mma16816(d, a.x, a.y, a.z, a.w, b0, b1); }
__device__ __forceinline__ uint32_t clock32() {
  uint32_t v;
  asm volatile("mov.u32 %0, %%clock;" : "=r"(v) :: "memory");
  return v;
}
__device__ __forceinline__ float swiglu(float g, float u, float r) {
  float hg = (0.5f * r) * g, th;
  asm("tanh.approx.f32 %0, %1;" : "=f"(th) : "f"(hg));
  return fmaf(hg, th, hg) * (r * u);
}
__device__ __forceinline__ void l2_prefetch(const void* p, int bytes) {
  asm volatile("cp.async.bulk.prefetch.L2.global [%0], %1;" ::"l"(p), "r"(bytes) : "memory");
}

__device__ __forceinline__ void wgmma_n256(float (&d)[128], uint64_t da, uint64_t db, int sd = 1) {
  asm volatile("{.reg .pred p; setp.ne.b32 p, %130, 0;\n"
      "wgmma.mma_async.sync.aligned.m64n256k16.f32.bf16.bf16 {"
      "%0,%1,%2,%3,%4,%5,%6,%7,%8,%9,%10,%11,%12,%13,%14,%15,"
      "%16,%17,%18,%19,%20,%21,%22,%23,%24,%25,%26,%27,%28,%29,%30,%31,"
      "%32,%33,%34,%35,%36,%37,%38,%39,%40,%41,%42,%43,%44,%45,%46,%47,"
      "%48,%49,%50,%51,%52,%53,%54,%55,%56,%57,%58,%59,%60,%61,%62,%63,"
      "%64,%65,%66,%67,%68,%69,%70,%71,%72,%73,%74,%75,%76,%77,%78,%79,"
      "%80,%81,%82,%83,%84,%85,%86,%87,%88,%89,%90,%91,%92,%93,%94,%95,"
      "%96,%97,%98,%99,%100,%101,%102,%103,%104,%105,%106,%107,%108,%109,%110,%111,"
      "%112,%113,%114,%115,%116,%117,%118,%119,%120,%121,%122,%123,%124,%125,%126,%127"
      "}, %128, %129, p, 1, 1, 0, 1;}\n"
      : "+f"(d[0]),"+f"(d[1]),"+f"(d[2]),"+f"(d[3]),"+f"(d[4]),"+f"(d[5]),"+f"(d[6]),"+f"(d[7]),
        "+f"(d[8]),"+f"(d[9]),"+f"(d[10]),"+f"(d[11]),"+f"(d[12]),"+f"(d[13]),"+f"(d[14]),"+f"(d[15]),
        "+f"(d[16]),"+f"(d[17]),"+f"(d[18]),"+f"(d[19]),"+f"(d[20]),"+f"(d[21]),"+f"(d[22]),"+f"(d[23]),
        "+f"(d[24]),"+f"(d[25]),"+f"(d[26]),"+f"(d[27]),"+f"(d[28]),"+f"(d[29]),"+f"(d[30]),"+f"(d[31]),
        "+f"(d[32]),"+f"(d[33]),"+f"(d[34]),"+f"(d[35]),"+f"(d[36]),"+f"(d[37]),"+f"(d[38]),"+f"(d[39]),
        "+f"(d[40]),"+f"(d[41]),"+f"(d[42]),"+f"(d[43]),"+f"(d[44]),"+f"(d[45]),"+f"(d[46]),"+f"(d[47]),
        "+f"(d[48]),"+f"(d[49]),"+f"(d[50]),"+f"(d[51]),"+f"(d[52]),"+f"(d[53]),"+f"(d[54]),"+f"(d[55]),
        "+f"(d[56]),"+f"(d[57]),"+f"(d[58]),"+f"(d[59]),"+f"(d[60]),"+f"(d[61]),"+f"(d[62]),"+f"(d[63]),
        "+f"(d[64]),"+f"(d[65]),"+f"(d[66]),"+f"(d[67]),"+f"(d[68]),"+f"(d[69]),"+f"(d[70]),"+f"(d[71]),
        "+f"(d[72]),"+f"(d[73]),"+f"(d[74]),"+f"(d[75]),"+f"(d[76]),"+f"(d[77]),"+f"(d[78]),"+f"(d[79]),
        "+f"(d[80]),"+f"(d[81]),"+f"(d[82]),"+f"(d[83]),"+f"(d[84]),"+f"(d[85]),"+f"(d[86]),"+f"(d[87]),
        "+f"(d[88]),"+f"(d[89]),"+f"(d[90]),"+f"(d[91]),"+f"(d[92]),"+f"(d[93]),"+f"(d[94]),"+f"(d[95]),
        "+f"(d[96]),"+f"(d[97]),"+f"(d[98]),"+f"(d[99]),"+f"(d[100]),"+f"(d[101]),"+f"(d[102]),"+f"(d[103]),
        "+f"(d[104]),"+f"(d[105]),"+f"(d[106]),"+f"(d[107]),"+f"(d[108]),"+f"(d[109]),"+f"(d[110]),"+f"(d[111]),
        "+f"(d[112]),"+f"(d[113]),"+f"(d[114]),"+f"(d[115]),"+f"(d[116]),"+f"(d[117]),"+f"(d[118]),"+f"(d[119]),
        "+f"(d[120]),"+f"(d[121]),"+f"(d[122]),"+f"(d[123]),"+f"(d[124]),"+f"(d[125]),"+f"(d[126]),"+f"(d[127])
      : "l"(da), "l"(db), "r"(sd));
}
__device__ __forceinline__ void wgmma_n192(float (&d)[96], uint64_t da, uint64_t db) {
  asm volatile("wgmma.mma_async.sync.aligned.m64n192k16.f32.bf16.bf16 {"
      "%0,%1,%2,%3,%4,%5,%6,%7,%8,%9,%10,%11,%12,%13,%14,%15,"
      "%16,%17,%18,%19,%20,%21,%22,%23,%24,%25,%26,%27,%28,%29,%30,%31,"
      "%32,%33,%34,%35,%36,%37,%38,%39,%40,%41,%42,%43,%44,%45,%46,%47,"
      "%48,%49,%50,%51,%52,%53,%54,%55,%56,%57,%58,%59,%60,%61,%62,%63,"
      "%64,%65,%66,%67,%68,%69,%70,%71,%72,%73,%74,%75,%76,%77,%78,%79,"
      "%80,%81,%82,%83,%84,%85,%86,%87,%88,%89,%90,%91,%92,%93,%94,%95"
      "}, %96, %97, 1, 1, 1, 0, 1;\n"
      : "+f"(d[0]),"+f"(d[1]),"+f"(d[2]),"+f"(d[3]),"+f"(d[4]),"+f"(d[5]),"+f"(d[6]),"+f"(d[7]),
        "+f"(d[8]),"+f"(d[9]),"+f"(d[10]),"+f"(d[11]),"+f"(d[12]),"+f"(d[13]),"+f"(d[14]),"+f"(d[15]),
        "+f"(d[16]),"+f"(d[17]),"+f"(d[18]),"+f"(d[19]),"+f"(d[20]),"+f"(d[21]),"+f"(d[22]),"+f"(d[23]),
        "+f"(d[24]),"+f"(d[25]),"+f"(d[26]),"+f"(d[27]),"+f"(d[28]),"+f"(d[29]),"+f"(d[30]),"+f"(d[31]),
        "+f"(d[32]),"+f"(d[33]),"+f"(d[34]),"+f"(d[35]),"+f"(d[36]),"+f"(d[37]),"+f"(d[38]),"+f"(d[39]),
        "+f"(d[40]),"+f"(d[41]),"+f"(d[42]),"+f"(d[43]),"+f"(d[44]),"+f"(d[45]),"+f"(d[46]),"+f"(d[47]),
        "+f"(d[48]),"+f"(d[49]),"+f"(d[50]),"+f"(d[51]),"+f"(d[52]),"+f"(d[53]),"+f"(d[54]),"+f"(d[55]),
        "+f"(d[56]),"+f"(d[57]),"+f"(d[58]),"+f"(d[59]),"+f"(d[60]),"+f"(d[61]),"+f"(d[62]),"+f"(d[63]),
        "+f"(d[64]),"+f"(d[65]),"+f"(d[66]),"+f"(d[67]),"+f"(d[68]),"+f"(d[69]),"+f"(d[70]),"+f"(d[71]),
        "+f"(d[72]),"+f"(d[73]),"+f"(d[74]),"+f"(d[75]),"+f"(d[76]),"+f"(d[77]),"+f"(d[78]),"+f"(d[79]),
        "+f"(d[80]),"+f"(d[81]),"+f"(d[82]),"+f"(d[83]),"+f"(d[84]),"+f"(d[85]),"+f"(d[86]),"+f"(d[87]),
        "+f"(d[88]),"+f"(d[89]),"+f"(d[90]),"+f"(d[91]),"+f"(d[92]),"+f"(d[93]),"+f"(d[94]),"+f"(d[95])
      : "l"(da), "l"(db));
}
template <int SD>
__device__ __forceinline__ void wgmma_rs_n128(float (&d)[64], uint32_t a0, uint32_t a1, uint32_t a2, uint32_t a3, uint64_t db) {
  asm volatile("wgmma.mma_async.sync.aligned.m64n128k16.f32.bf16.bf16 {"
      "%0,%1,%2,%3,%4,%5,%6,%7,%8,%9,%10,%11,%12,%13,%14,%15,"
      "%16,%17,%18,%19,%20,%21,%22,%23,%24,%25,%26,%27,%28,%29,%30,%31,"
      "%32,%33,%34,%35,%36,%37,%38,%39,%40,%41,%42,%43,%44,%45,%46,%47,"
      "%48,%49,%50,%51,%52,%53,%54,%55,%56,%57,%58,%59,%60,%61,%62,%63"
      "}, {%64,%65,%66,%67}, %68, %69, 1, 1, 1;\n"
      : "+f"(d[0]),"+f"(d[1]),"+f"(d[2]),"+f"(d[3]),"+f"(d[4]),"+f"(d[5]),"+f"(d[6]),"+f"(d[7]),
        "+f"(d[8]),"+f"(d[9]),"+f"(d[10]),"+f"(d[11]),"+f"(d[12]),"+f"(d[13]),"+f"(d[14]),"+f"(d[15]),
        "+f"(d[16]),"+f"(d[17]),"+f"(d[18]),"+f"(d[19]),"+f"(d[20]),"+f"(d[21]),"+f"(d[22]),"+f"(d[23]),
        "+f"(d[24]),"+f"(d[25]),"+f"(d[26]),"+f"(d[27]),"+f"(d[28]),"+f"(d[29]),"+f"(d[30]),"+f"(d[31]),
        "+f"(d[32]),"+f"(d[33]),"+f"(d[34]),"+f"(d[35]),"+f"(d[36]),"+f"(d[37]),"+f"(d[38]),"+f"(d[39]),
        "+f"(d[40]),"+f"(d[41]),"+f"(d[42]),"+f"(d[43]),"+f"(d[44]),"+f"(d[45]),"+f"(d[46]),"+f"(d[47]),
        "+f"(d[48]),"+f"(d[49]),"+f"(d[50]),"+f"(d[51]),"+f"(d[52]),"+f"(d[53]),"+f"(d[54]),"+f"(d[55]),
        "+f"(d[56]),"+f"(d[57]),"+f"(d[58]),"+f"(d[59]),"+f"(d[60]),"+f"(d[61]),"+f"(d[62]),"+f"(d[63])
      : "r"(a0), "r"(a1), "r"(a2), "r"(a3), "l"(db), "n"(SD));
}
__device__ __forceinline__ void wgmma_rs_n256(float (&d)[128], uint32_t a0, uint32_t a1, uint32_t a2, uint32_t a3, uint64_t db, int sd = 1) {
  asm volatile("{.reg .pred p; setp.ne.b32 p, %133, 0;\n"
      "wgmma.mma_async.sync.aligned.m64n256k16.f32.bf16.bf16 {"
      "%0,%1,%2,%3,%4,%5,%6,%7,%8,%9,%10,%11,%12,%13,%14,%15,"
      "%16,%17,%18,%19,%20,%21,%22,%23,%24,%25,%26,%27,%28,%29,%30,%31,"
      "%32,%33,%34,%35,%36,%37,%38,%39,%40,%41,%42,%43,%44,%45,%46,%47,"
      "%48,%49,%50,%51,%52,%53,%54,%55,%56,%57,%58,%59,%60,%61,%62,%63,"
      "%64,%65,%66,%67,%68,%69,%70,%71,%72,%73,%74,%75,%76,%77,%78,%79,"
      "%80,%81,%82,%83,%84,%85,%86,%87,%88,%89,%90,%91,%92,%93,%94,%95,"
      "%96,%97,%98,%99,%100,%101,%102,%103,%104,%105,%106,%107,%108,%109,%110,%111,"
      "%112,%113,%114,%115,%116,%117,%118,%119,%120,%121,%122,%123,%124,%125,%126,%127"
      "}, {%128,%129,%130,%131}, %132, p, 1, 1, 1;}\n"
      : "+f"(d[0]),"+f"(d[1]),"+f"(d[2]),"+f"(d[3]),"+f"(d[4]),"+f"(d[5]),"+f"(d[6]),"+f"(d[7]),
        "+f"(d[8]),"+f"(d[9]),"+f"(d[10]),"+f"(d[11]),"+f"(d[12]),"+f"(d[13]),"+f"(d[14]),"+f"(d[15]),
        "+f"(d[16]),"+f"(d[17]),"+f"(d[18]),"+f"(d[19]),"+f"(d[20]),"+f"(d[21]),"+f"(d[22]),"+f"(d[23]),
        "+f"(d[24]),"+f"(d[25]),"+f"(d[26]),"+f"(d[27]),"+f"(d[28]),"+f"(d[29]),"+f"(d[30]),"+f"(d[31]),
        "+f"(d[32]),"+f"(d[33]),"+f"(d[34]),"+f"(d[35]),"+f"(d[36]),"+f"(d[37]),"+f"(d[38]),"+f"(d[39]),
        "+f"(d[40]),"+f"(d[41]),"+f"(d[42]),"+f"(d[43]),"+f"(d[44]),"+f"(d[45]),"+f"(d[46]),"+f"(d[47]),
        "+f"(d[48]),"+f"(d[49]),"+f"(d[50]),"+f"(d[51]),"+f"(d[52]),"+f"(d[53]),"+f"(d[54]),"+f"(d[55]),
        "+f"(d[56]),"+f"(d[57]),"+f"(d[58]),"+f"(d[59]),"+f"(d[60]),"+f"(d[61]),"+f"(d[62]),"+f"(d[63]),
        "+f"(d[64]),"+f"(d[65]),"+f"(d[66]),"+f"(d[67]),"+f"(d[68]),"+f"(d[69]),"+f"(d[70]),"+f"(d[71]),
        "+f"(d[72]),"+f"(d[73]),"+f"(d[74]),"+f"(d[75]),"+f"(d[76]),"+f"(d[77]),"+f"(d[78]),"+f"(d[79]),
        "+f"(d[80]),"+f"(d[81]),"+f"(d[82]),"+f"(d[83]),"+f"(d[84]),"+f"(d[85]),"+f"(d[86]),"+f"(d[87]),
        "+f"(d[88]),"+f"(d[89]),"+f"(d[90]),"+f"(d[91]),"+f"(d[92]),"+f"(d[93]),"+f"(d[94]),"+f"(d[95]),
        "+f"(d[96]),"+f"(d[97]),"+f"(d[98]),"+f"(d[99]),"+f"(d[100]),"+f"(d[101]),"+f"(d[102]),"+f"(d[103]),
        "+f"(d[104]),"+f"(d[105]),"+f"(d[106]),"+f"(d[107]),"+f"(d[108]),"+f"(d[109]),"+f"(d[110]),"+f"(d[111]),
        "+f"(d[112]),"+f"(d[113]),"+f"(d[114]),"+f"(d[115]),"+f"(d[116]),"+f"(d[117]),"+f"(d[118]),"+f"(d[119]),
        "+f"(d[120]),"+f"(d[121]),"+f"(d[122]),"+f"(d[123]),"+f"(d[124]),"+f"(d[125]),"+f"(d[126]),"+f"(d[127])
      : "r"(a0), "r"(a1), "r"(a2), "r"(a3), "l"(db), "r"(sd));
}
__device__ __forceinline__ void wgmma_rs_n192(float (&d)[96], uint32_t a0, uint32_t a1, uint32_t a2, uint32_t a3, uint64_t db) {
  asm volatile("wgmma.mma_async.sync.aligned.m64n192k16.f32.bf16.bf16 {"
      "%0,%1,%2,%3,%4,%5,%6,%7,%8,%9,%10,%11,%12,%13,%14,%15,"
      "%16,%17,%18,%19,%20,%21,%22,%23,%24,%25,%26,%27,%28,%29,%30,%31,"
      "%32,%33,%34,%35,%36,%37,%38,%39,%40,%41,%42,%43,%44,%45,%46,%47,"
      "%48,%49,%50,%51,%52,%53,%54,%55,%56,%57,%58,%59,%60,%61,%62,%63,"
      "%64,%65,%66,%67,%68,%69,%70,%71,%72,%73,%74,%75,%76,%77,%78,%79,"
      "%80,%81,%82,%83,%84,%85,%86,%87,%88,%89,%90,%91,%92,%93,%94,%95"
      "}, {%96,%97,%98,%99}, %100, 1, 1, 1, 1;\n"
      : "+f"(d[0]),"+f"(d[1]),"+f"(d[2]),"+f"(d[3]),"+f"(d[4]),"+f"(d[5]),"+f"(d[6]),"+f"(d[7]),
        "+f"(d[8]),"+f"(d[9]),"+f"(d[10]),"+f"(d[11]),"+f"(d[12]),"+f"(d[13]),"+f"(d[14]),"+f"(d[15]),
        "+f"(d[16]),"+f"(d[17]),"+f"(d[18]),"+f"(d[19]),"+f"(d[20]),"+f"(d[21]),"+f"(d[22]),"+f"(d[23]),
        "+f"(d[24]),"+f"(d[25]),"+f"(d[26]),"+f"(d[27]),"+f"(d[28]),"+f"(d[29]),"+f"(d[30]),"+f"(d[31]),
        "+f"(d[32]),"+f"(d[33]),"+f"(d[34]),"+f"(d[35]),"+f"(d[36]),"+f"(d[37]),"+f"(d[38]),"+f"(d[39]),
        "+f"(d[40]),"+f"(d[41]),"+f"(d[42]),"+f"(d[43]),"+f"(d[44]),"+f"(d[45]),"+f"(d[46]),"+f"(d[47]),
        "+f"(d[48]),"+f"(d[49]),"+f"(d[50]),"+f"(d[51]),"+f"(d[52]),"+f"(d[53]),"+f"(d[54]),"+f"(d[55]),
        "+f"(d[56]),"+f"(d[57]),"+f"(d[58]),"+f"(d[59]),"+f"(d[60]),"+f"(d[61]),"+f"(d[62]),"+f"(d[63]),
        "+f"(d[64]),"+f"(d[65]),"+f"(d[66]),"+f"(d[67]),"+f"(d[68]),"+f"(d[69]),"+f"(d[70]),"+f"(d[71]),
        "+f"(d[72]),"+f"(d[73]),"+f"(d[74]),"+f"(d[75]),"+f"(d[76]),"+f"(d[77]),"+f"(d[78]),"+f"(d[79]),
        "+f"(d[80]),"+f"(d[81]),"+f"(d[82]),"+f"(d[83]),"+f"(d[84]),"+f"(d[85]),"+f"(d[86]),"+f"(d[87]),
        "+f"(d[88]),"+f"(d[89]),"+f"(d[90]),"+f"(d[91]),"+f"(d[92]),"+f"(d[93]),"+f"(d[94]),"+f"(d[95])
      : "r"(a0), "r"(a1), "r"(a2), "r"(a3), "l"(db));
}


constexpr int C_LN = 0, C_PX = 16, C_PY = 32;
constexpr int NB_CONS = 1, NB_LN = 2, NB_LAG = 4, NB_INIT = 6, NB_RDY = 7, NB_WG = 8;
constexpr int LAGX = 3;
constexpr int LAGY = 6;
constexpr int LAG2 = 5;
constexpr int NLL = 2;
constexpr int POLL_DELAY3 = 600;
constexpr int POLL_DELAY = 1200;
constexpr int FILT_DELAY = 800;
constexpr int WARM = 4;
constexpr int ALEAD = 6;
constexpr int POLL_DELAY2 = 1000;
constexpr int REDPOS = 4;
constexpr int XTRIG = 20;
constexpr int HTRIG = 0;
constexpr int RING_SIG = 1;
constexpr int PF2_SIG = 1;
constexpr int SM_E = 0, SM_X = 16384, SM_E2 = 32768, SM_W = 49152, SM_FC = 69632, SM_T = 73728 - T1_BYTES;
constexpr unsigned long long KORDER = 0xBA9432DC876510ull;
constexpr unsigned long long BSLOT = 0x852140A9852140ull, PSLOT = 0x63DCB763DCB763ull;
constexpr unsigned long long BDEP = 0xFFE97531ull, PDEP = 0xCBA754ull;
constexpr uint32_t HI128 = desc_hi(1024, 1), HI64 = desc_hi(512, 2);

struct Bars {
  uint64_t full1[32], empty1[32], full2[16], fullA[8], empty2[8], fullP[32], emptyP[9], hbar, tbar, hint[3], sig[2], sbar, freeA[4];
  uint32_t epoch, pad;
};

template <int NK, bool STORE, int J0 = 0, int J1 = NK>
__device__ __forceinline__ void make_p(const float (&acc)[NK * 16], float r0, float r1, uint4 (&p)[NK], uint4* pbase, int ks0, uint32_t tag) {
#pragma unroll
  for (int j = J0; j < J1; j++) {
    uint32_t w[4];
#pragma unroll
    for (int i = 0; i < 4; i++) {
      const int a = 8 * j + 2 * i, b = a + NK * 8;
      w[i] = pack2(swiglu(acc[a], acc[b], (i & 1) ? r1 : r0), swiglu(acc[a + 1], acc[b + 1], (i & 1) ? r1 : r0));
    }
    asm volatile("" : "+r"(w[0]), "+r"(w[1]), "+r"(w[2]), "+r"(w[3]));
    p[j] = make_uint4(w[0], w[1], w[2], w[3]);
    if (STORE) st_tag(pbase + ((ks0 + j) >> 2) * 1024 + ((ks0 + j) & 3) * 32, p[j], tag);
  }
}
__device__ __forceinline__ void spin_until(uint32_t t) {
  while ((int)(clock32() - t) < 0) {}
}

__global__ void __cluster_dims__(2, 1, 1) __launch_bounds__(NTHREADS, 1)
fused_kernel(const __nv_bfloat16* __restrict__ x, const Tables* __restrict__ tab, Scratch* __restrict__ scr,
             __nv_bfloat16* __restrict__ out, const char* __restrict__ wg_raw, const char* __restrict__ wu_raw,
             const char* __restrict__ wd_raw,
             const __grid_constant__ CUtensorMap tmWR, const __grid_constant__ CUtensorMap tmWI,
             const __grid_constant__ CUtensorMap tmGX, const __grid_constant__ CUtensorMap tmUX,
             const __grid_constant__ CUtensorMap tmGY, const __grid_constant__ CUtensorMap tmUY,
             const __grid_constant__ CUtensorMap tmD) {
  extern __shared__ __align__(1024) char smem_raw[];
  const uint32_t sbase = s2u(smem_raw);
  const uint32_t sbar = sbase + 14 * SLOT, sstat = sbar + 1408;
  const int tid = threadIdx.x, lane = tid & 31;
  const int c = blockIdx.x, rk = c & 1, f = (c >> 1) & 7, rb = 2 * (c >> 4) + rk;
  const int rb2 = 2 * (c >> 4) + (f >> 2), kh = (f >> 1) & 1, nq = 2 * (f & 1) + rk;
#define BAR(field, i) (sbar + (uint32_t)offsetof(Bars, field) + 8u * (i))
#define TOFF(field) (sbase + SM_T + (uint32_t)offsetof(Tables, field) + lane * 16)

  if (tid >= 256) {
    asm volatile("setmaxnreg.dec.sync.aligned.u32 40;");
    const int warp = __shfl_sync(0xffffffffu, tid >> 5, 0);
    if (lane == 0) {
      if (warp == 8) {
        if (sbase & 1023) die();
#pragma unroll
        for (int i = 0; i < 21; i++) mbar_init(BAR(emptyP, i), i < 9 ? 8 : i < 14 ? 1 : i < 16 ? 8 : i == 16 ? 32 : 16);
        mbar_expect(BAR(tbar, 0), T2_BYTES + 2 * 10240);
        mbar_expect(BAR(hbar, 0), 16384);
      } else if (warp == 9) {
#pragma unroll
        for (int i = 0; i < 32; i++) mbar_init(BAR(full1, i), 1);
#pragma unroll
        for (int i = 0; i < 32; i++) mbar_expect(BAR(full1, i), i < 16 ? 16384 : 12288);
      } else if (warp == 10) {
#pragma unroll
        for (int i = 0; i < 32; i++) mbar_init(BAR(empty1, i), 16);
#pragma unroll
        for (int i = 0; i < 30; i++) mbar_init(BAR(fullP, i), 1);
#pragma unroll
        for (int i = 0; i < 30; i++) mbar_expect(BAR(fullP, i), 8192);
      } else {
#pragma unroll
        for (int i = 0; i < 32; i++) mbar_init(BAR(full2, i), i < 24 ? 1 : 8);
#pragma unroll
        for (int i = 0; i < 24; i++) mbar_expect(BAR(full2, i), 16384);
      }
      asm volatile("fence.mbarrier_init.release.cluster;" ::: "memory");
    }
    if (tid == 256) {
      const int w0 = ((c >> 3) * 257 + 32 * (c & 7) + 1) & ~7;
      if (FILT_DELAY) {
        asm volatile("prefetch.tensormap [%0];" ::"l"(&tmWR) : "memory");
        asm volatile("prefetch.tensormap [%0];" ::"l"(&tmWI) : "memory");
        spin_until(clock32() + FILT_DELAY);
      }
      tma3(sbase + SM_W, &tmWR, BAR(tbar, 0), w0, 0, 0);
      tma3(sbase + SM_W + 10240, &tmWI, BAR(tbar, 0), w0, 0, 0);
      bulk_load(sbase + SM_T + T1_BYTES, reinterpret_cast<const char*>(tab) + T1_BYTES, T2_BYTES, BAR(tbar, 0));
    }
    if (tid == 288) {
      asm volatile("prefetch.tensormap [%0];" ::"l"(rk ? &tmUX : &tmGX) : "memory");
      asm volatile("prefetch.tensormap [%0];" ::"l"(rk ? &tmUY : &tmGY) : "memory");
      asm volatile("prefetch.tensormap [%0];" ::"l"(&tmD) : "memory");
    }
    if (tid == 320) {
      const unsigned e = ld_relaxed(&scr->cnt[(C_LN + rb) * 32]) >> 3;
      asm volatile("st.shared.u32 [%0], %1;" ::"r"(BAR(epoch, 0)), "r"(e) : "memory");
    }
    __syncwarp();
    asm volatile("barrier.cluster.arrive.relaxed.aligned;" ::: "memory");
    bar_arrive(NB_RDY, 384);
    asm volatile("barrier.cluster.wait.aligned;" ::: "memory");
    bar_sync(NB_INIT, 384);
    unsigned epoch;
    asm volatile("ld.shared.u32 %0, [%1];" : "=r"(epoch) : "r"(BAR(epoch, 0)) : "memory");
    if (warp == 8) {
      if (lane == 0) {
        const int ax = (7 * f + 3 * (f & 1)) >> 1;
        const int ay = 7 * f + ((f & 1) ? 0 : 4);
        const CUtensorMap* tx = rk ? &tmUX : &tmGX;
        const CUtensorMap* ty = rk ? &tmUY : &tmGY;
        if (RING_SIG >= 0) mbar_wait(BAR(sig, RING_SIG));
        uint32_t s = 2;
#pragma unroll 1
        for (int n = 0; n < 16; n++) {
          if (n >= 6) mbar_wait(BAR(empty1, n - 6));
          tma3_mc(sbase + (8 + s) * SLOT + rk * 8192, tx, BAR(full1, n), n * 32, ax);
          if (++s == 6) s = 0;
          if (n >= 10 && n < 15) {
            const int k = n - 10;
            mbar_wait(BAR(freeA, (12 * k + 11) >> 4));
            tma3_mc(sbase + k * 12288 + rk * 6144, ty, BAR(full1, 16 + k), (k + 8) * 32, ay);
          }
        }
#pragma unroll 1
        for (int k = 5; k < 16; k++) {
          mbar_wait(BAR(empty1, k < 13 ? 10 + ((12 * (k - 5) + 11) >> 4) : 8 + k));
          tma3_mc(sbase + 8 * SLOT + ((k - 5) & 7) * 12288 + rk * 6144, ty, BAR(full1, 16 + k), ((k + 8) & 15) * 32, ay);
        }
      }
    } else if (warp == 9) {
      if (lane == 0) {
        mbar_wait(BAR(fullA, 4));
        wait_counter(&scr->cnt[(C_LN + rb2) * 32], (epoch + 1) * 8);
        asm volatile("fence.proxy.async.global;" ::: "memory");
#pragma unroll 1
        for (int i = 0; i < 14; i++) {
          const int kblk = 14 * kh + (int)((KORDER >> (4 * i)) & 15);
          mbar_wait(i < 8 ? BAR(empty1, 16 + (uint32_t)((BDEP >> (4 * i)) & 15)) : BAR(empty2, i - 8));
          tma3(sbase + (uint32_t)((BSLOT >> (4 * i)) & 15) * SLOT, &tmD, BAR(full2, i), 0, 64 * kblk, 2 * nq);
        }
        mbar_wait(BAR(empty2, 6));
        bulk_load(sbase + 9 * SLOT, &scr->LN[(rb2 * 8 + 2 * nq) * 1024 + kh * 512], 8192, BAR(hbar, 0));
        bulk_load(sbase + 9 * SLOT + 8192, &scr->LN[(rb2 * 8 + 2 * nq + 1) * 1024 + kh * 512], 8192, BAR(hbar, 0));
      }
    } else if (warp == 10) {
      bar_sync(NB_LN, 288);
      if (lane == 0) {
        red_release(&scr->cnt[(C_LN + rb) * 32]);
        wait_counter(&scr->cnt[(C_LN + rb) * 32], (epoch + 1) * 8);
        asm volatile("fence.proxy.async.global;" ::: "memory");
#pragma unroll 1
        for (int kb = NLL; kb < 8; kb++) {
          if (2 * kb >= ALEAD) mbar_wait(BAR(empty1, 2 * kb - ALEAD));
          bulk_load(sbase + kb * SLOT, &scr->LN[(rb * 8 + kb) * 1024], 16384, BAR(fullA, kb));
        }
#pragma unroll 1
        for (int s = 0; s < 14; s++) {
          const int kblk = 14 * kh + (int)((KORDER >> (4 * s)) & 15);
          if (s == 0 || s == 8 || s == 11) {
            mbar_wait(BAR(hint, s == 0 ? 0 : s == 8 ? 1 : 2), 0);
          }
          mbar_wait(s < 6 ? BAR(empty1, 16 + (uint32_t)((PDEP >> (4 * s)) & 15)) : BAR(emptyP, s - 6));
          bulk_load_mc(sbase + (uint32_t)((PSLOT >> (4 * s)) & 15) * SLOT + rk * 8192, &scr->P[(rb2 * 28 + kblk) * 1024 + rk * 512], 8192, BAR(fullP, 16 * rk + s));
        }
      }
    } else {
      if (lane == 0) {
        mbar_wait(BAR(tbar, 0));
        l2_prefetch(wg_raw + (size_t)c * 5376, 5376);
        l2_prefetch(wu_raw + (size_t)c * 5376, 5376);
        mbar_wait(BAR(sig, PF2_SIG), 0);
        l2_prefetch(wg_raw + 688128 + (size_t)c * 8960, 8960);
        l2_prefetch(wu_raw + 688128 + (size_t)c * 8960, 8960);
      }
      mbar_wait(BAR(fullA, 4), 0);
      if (lane == 0) l2_prefetch(wd_raw + (size_t)c * 14336, 14336);
      {
        const uint32_t tag = (epoch + 1) & 1;
        uint4 v0, v1, v2;
        int it = 0;
        while (true) {
          v0 = ld_b128(&scr->ST[rb * 64 + lane]);
          v1 = ld_b128(&scr->ST[rb * 64 + 32 + lane]);
          v2 = ld_b128(&scr->ST[rb2 * 64 + 32 * kh + lane]);
          if (!__any_sync(0xffffffffu, ((v0.x ^ tag) | (v1.x ^ tag) | (v2.x ^ tag)) & 1u)) break;
          if (++it > SPIN_LIMIT) { die(); break; }
        }
        sts4(sstat + lane * 16, v0.x & ~1u, v0.y, v0.z, v0.w);
        sts4(sstat + 512 + lane * 16, v1.x & ~1u, v1.y, v1.z, v1.w);
        sts4(sstat + 1024 + lane * 16, v2.x & ~1u, v2.y, v2.z, v2.w);
        mbar_arrive(BAR(sbar, 0));
      }
      if (lane == 0) {
        mbar_wait(BAR(empty1, XTRIG));
        int it = 0;
        while ((int)(ld_relaxed(&scr->cnt[(C_PX + rb2) * 32 + kh]) - (epoch + 1) * 32) < 0) {
          if (++it > SPIN_LIMIT) { die(); break; }
        }
        mbar_arrive(BAR(hint, 0));
        mbar_wait(BAR(emptyP, HTRIG));
        uint32_t done = 0;
        while (done != 3) {
          uint2 v;
          asm volatile("ld.relaxed.gpu.global.v2.u32 {%0,%1}, [%2];" : "=r"(v.x), "=r"(v.y) : "l"(&scr->cnt[(C_PY + rb2) * 32 + 4 * (rk ^ kh ^ 1) + 2 * kh]) : "memory");
          if (!(done & 1) && (int)(v.x - (epoch + 1) * 8) >= 0) { done |= 1; mbar_arrive(BAR(hint, 1)); }
          if (!(done & 2) && (int)(v.y - (epoch + 1) * 8) >= 0) { done |= 2; mbar_arrive(BAR(hint, 2)); }
          if (++it > SPIN_LIMIT) { die(); break; }
        }
      }
    }
  } else {
    const int warp = __shfl_sync(0xffffffffu, tid >> 5, 0);
    const int g = lane >> 2, t = lane & 3;
    uint4 fa[4], fb[4], tw[6];
#pragma unroll
    for (int i = 0; i < 4; i++) fa[i] = ldg_ca4(&tab->fa[i][lane][0]);
#pragma unroll
    for (int i = 0; i < 6; i++) tw[i] = ldg_ca4(&tab->tw1[i][lane][0]);
#pragma unroll
    for (int i = 0; i < 4; i++) fb[i] = ldg_ca4(&tab->fb[i][lane][0]);
#pragma unroll
    for (int i = 0; i < 4; i++) {
      const int r = i >> 1, ch = (i & 1) * 32 + lane;
      cp_async16(sbase + SM_X + (2 * warp + r) * 1024 + ((ch ^ ((ch >> 3) & 1)) * 16),
                 x + (size_t)(c + 128 * (2 * warp + r)) * 512 + ch * 8);
    }
    asm volatile("cp.async.commit_group;" ::: "memory");
    asm volatile("barrier.cluster.arrive.relaxed.aligned;" ::: "memory");
    uint32_t rbar;
    asm volatile("mapa.shared::cluster.u32 %0, %1, %2;" : "=r"(rbar) : "r"(sbar), "r"(rk ^ 1));
#define RBAR(field, i) (rbar + (uint32_t)offsetof(Bars, field) + 8u * (i))
    {
      const int ln = (tid >> 1) & 31, lg = ln >> 2, lt = ln & 3, i = 4 * (tid >> 6) + 2 * (tid & 1);
      const int kidx = lt + 8 * (i >> 3), nidx = 4 * ((i >> 1) & 3) + (lg >> 1);
      const uint32_t a0 = cfrag<2048>((c + 128 * kidx) * nidx, lg & 1), a1 = cfrag<2048>((c + 128 * (kidx + 4)) * nidx, lg & 1);
      const uint32_t b0 = cfrag<2048>(-(c + 128 * nidx) * kidx, lg & 1), b1 = cfrag<2048>(-(c + 128 * nidx) * (kidx + 4), lg & 1);
      asm volatile("st.shared.v2.u32 [%0], {%1,%2};" ::"r"(sbase + SM_FC + tid * 8), "r"(a0), "r"(a1) : "memory");
      asm volatile("st.shared.v2.u32 [%0], {%1,%2};" ::"r"(sbase + SM_FC + 2048 + tid * 8), "r"(b0), "r"(b1) : "memory");
    }
    bar_sync(NB_CONS, 256);
    uint4 fc[4];
#pragma unroll
    for (int i = 0; i < 4; i++) fc[i] = lds4(sbase + SM_FC + i * 512 + lane * 16);
    asm volatile("cp.async.wait_group 0;" ::: "memory");
    __syncwarp();
    bar_arrive(NB_INIT, 384);
    uint32_t tag, ones;
    uint4 q[4], o[4];
    {
      uint32_t v[2][8];
#pragma unroll
      for (int r = 0; r < 2; r++)
#pragma unroll
        for (int ks = 0; ks < 2; ks++) {
          const int ch = 32 * ks + 2 * (lane & 15) + (lane >> 4);
          asm volatile("ldmatrix.sync.aligned.m8n8.x4.trans.shared.b16 {%0,%1,%2,%3}, [%4];"
                       : "=r"(v[r][4 * ks]), "=r"(v[r][4 * ks + 1]), "=r"(v[r][4 * ks + 2]), "=r"(v[r][4 * ks + 3])
                       : "r"(sbase + SM_X + (2 * warp + r) * 1024 + ((ch ^ ((ch >> 3) & 1)) * 16)) : "memory");
        }
      float sq[2];
#pragma unroll
      for (int r = 0; r < 2; r++) {
        float s0 = 0.f, s1 = 0.f;
#pragma unroll
        for (int i = 0; i < 8; i++) {
          const float lo = bf_lo(v[r][i]), hi = u2f(v[r][i] & 0xffff0000u);
          s0 = fmaf(lo, lo, s0);
          s1 = fmaf(hi, hi, s1);
        }
        sq[r] = s0 + s1;
      }
      {
        float w = ((lane & 1) ? sq[1] : sq[0]) + __shfl_xor_sync(0xffffffffu, (lane & 1) ? sq[0] : sq[1], 1);
        w += __shfl_xor_sync(0xffffffffu, w, 2);
        w = sum_groups(w);
        const float o2 = __shfl_xor_sync(0xffffffffu, w, 1);
        sq[0] = (lane & 1) ? o2 : w;
        sq[1] = (lane & 1) ? w : o2;
      }
#pragma unroll
      for (int r = 0; r < 2; r++) {
        float dd[2][4], ee[2][4];
#pragma unroll
        for (int nt = 0; nt < 2; nt++) {
          mma_az(dd[nt], fa[0], v[r][2 * nt], v[r][2 * nt + 1]);
          mma_a(dd[nt], fa[1], v[r][4 + 2 * nt], v[r][5 + 2 * nt]);
          mma_az(ee[nt], fa[2], v[r][2 * nt], v[r][2 * nt + 1]);
          mma_a(ee[nt], fa[3], v[r][4 + 2 * nt], v[r][5 + 2 * nt]);
        }
        float mean = (dd[0][0] + dd[0][1]) + (dd[1][0] + dd[1][1]);
        mean += __shfl_xor_sync(0xffffffffu, mean, 1);
        mean += __shfl_xor_sync(0xffffffffu, mean, 2);
        mean = __shfl_sync(0xffffffffu, mean, 0) * (1.f / 512.f);
        const float rs = rsqrtf(fmaxf(fmaf(-mean, mean, sq[r] * (1.f / 512.f)), 0.f) + 1e-5f);
        float acc[4][4];
#pragma unroll
        for (int nt = 0; nt < 2; nt++) {
          const float (&d)[4] = dd[nt];
          const float (&e)[4] = ee[nt];
          const uint4 &ka = tw[2 * nt], &kb = tw[2 * nt + 1], &kc = tw[4 + nt];
          const uint32_t a0 = pack2(d[0] * u2f(ka.x) + d[2] * u2f(ka.y), d[1] * u2f(kb.x) + d[3] * u2f(kb.y));
          const uint32_t a2 = pack2(d[0] * u2f(ka.z) + d[2] * u2f(ka.w), d[1] * u2f(kb.z) + d[3] * u2f(kb.w));
          const uint32_t a1 = pack2(e[0] * u2f(kc.x) + e[2] * u2f(kc.y), e[1] * u2f(kc.z) + e[3] * u2f(kc.w));
          const uint32_t a3 = pack2(e[2] * u2f(kc.x) - e[0] * u2f(kc.y), e[3] * u2f(kc.z) - e[1] * u2f(kc.w));
          const uint32_t dc = pack2(fmaf(mean, -32.f, d[0]), fmaf(mean, -32.f, d[1]));
          const uint32_t h0 = g == 0 ? dc : a0, h2 = g == 0 ? 0u : a2;
          if (nt == 0) {
            mma16816_z(acc[0], a0, a1, a2, a3, fb[2 * nt].x, fb[2 * nt].y);
            mma16816_z(acc[1], a0, a1, a2, a3, fb[2 * nt].z, fb[2 * nt].w);
            mma16816_z(acc[2], h0, a1, h2, a3, fb[2 * nt + 1].x, fb[2 * nt + 1].y);
            mma16816_z(acc[3], h0, a1, h2, a3, fb[2 * nt + 1].z, fb[2 * nt + 1].w);
          } else {
            mma16816(acc[0], a0, a1, a2, a3, fb[2 * nt].x, fb[2 * nt].y);
            mma16816(acc[1], a0, a1, a2, a3, fb[2 * nt].z, fb[2 * nt].w);
            mma16816(acc[2], h0, a1, h2, a3, fb[2 * nt + 1].x, fb[2 * nt + 1].y);
            mma16816(acc[3], h0, a1, h2, a3, fb[2 * nt + 1].z, fb[2 * nt + 1].w);
          }
        }
#pragma unroll
        for (int h = 0; h < 2; h++) {
          const int j = 2 * warp + r, m = 2 * t + h;
          sts4(sbase + SM_E + ((j * 8 + m) * 8 + (g ^ (2 * t) ^ (2 * (j & 3)))) * 16,
               pack2(acc[h][0] * rs, acc[h][1] * rs), pack2(acc[h][2] * rs, acc[h][3] * rs),
               pack2(acc[2 + h][0] * rs, acc[2 + h][1] * rs), pack2(acc[2 + h][2] * rs, acc[2 + h][3] * rs));
        }
      }
      bar_sync(NB_RDY, 384);
      const uint32_t ea = sbase + SM_E + ((t * 8 + warp) * 8 + (g ^ (warp & 6) ^ (2 * t))) * 16;
      lds_frag(q[0], q[1], ea, ea + 4096);
      lds_frag(q[2], q[3], ea + 8192, ea + 12288);
      asm volatile("ld.shared.u32 %0, [%1];" : "=r"(tag) : "r"(BAR(epoch, 0)) : "memory");
      ones = ~(tag >> 31);
      tag = (tag + 1) & 1;
      cdft16(q, fc, o);
#pragma unroll
      for (int vv = 0; vv < 4; vv++) {
        o[vv].y &= ~1u;
        o[vv].z = (o[vv].z & ~1u) | (tag ^ 1);
        st_tag(&scr->Z1[(((4 * vv + t) * 8 + warp) * 128 + c) * 8 + g], o[vv], tag);
      }
    }
    asm volatile("setmaxnreg.inc.sync.aligned.u32 232;");
    {
      uint4* const zp = &scr->Z1[(c * 128 + 8 * t + warp) * 8 + g];
      const uint32_t tst = clock32();
      mbar_wait(BAR(tbar, 0), 0);
      uint4 f2[4], g2[4];
#pragma unroll
      for (int i = 0; i < 4; i++) {
        f2[i] = lds4(TOFF(f2) + warp * 2048 + i * 512);
        g2[i] = lds4(TOFF(g2) + warp * 2048 + i * 512);
      }
      const uint4 f8 = lds4(TOFF(f8)), g8 = lds4(TOFF(g8));
      asm volatile("barrier.cluster.wait.aligned;" ::: "memory");
      spin_until(tst + POLL_DELAY);
      ld_tag4_issue<256>(q, zp);
      float wfr[16], wfi[16];
      {
        const float nyq = ((c & 7) == 7 && g == 0) ? 0.5f : 1.f;
        uint32_t wa = sbase + SM_W + (16 * warp + t) * 80 + ((2 * (c >> 3) + 2) & 15) - 2;
        asm volatile("" : "+r"(wa));
        const uint32_t wb[3] = {wa + 2 * (g == 0 ? 16 : g), wa + 2 * g, wa - 2 * g};
#pragma unroll
        for (int i = 0; i < 16; i++) {
          const int ci = i >> 3, dd = (i >> 2) & 1, e = i & 3;
          const uint32_t a = wb[e < 2 ? e : 2] + (ci * 8 + 4 * dd) * 80 + (e == 0 ? 0 : e == 1 ? 16 : e == 2 ? 64 : 48);
          wfr[i] = bf_lo(lds_u16(a)) * (e == 2 ? nyq : 1.f);
          wfi[i] = bf_lo(lds_u16(a + 10240)) * (e == 2 ? nyq : 1.f);
        }
      }
      ld_tag4_finish<256>(q, zp, tag);
      if (lane == 0) mbar_arrive(BAR(sig, 0));
#pragma unroll
      for (int i = 0; i < 4; i++) q[i].z &= ~1u;
      reg_frag(q, ones);
      cdft16(q, f2, o);
      const uint32_t e2 = sbase + SM_E2;
#pragma unroll
      for (int vv = 0; vv < 4; vv++)
        sts4(e2 + ((warp * 16 + 4 * vv + t) * 8 + (g ^ (2 * t) ^ (2 * (warp & 3)))) * 16, o[vv].x, o[vv].y, o[vv].z, o[vv].w);
      bar_sync(NB_CONS, 256);
      uint32_t ad[2], res[2][2][4];
#pragma unroll
      for (int ci = 0; ci < 2; ci++) {
        const int cc = 2 * warp + ci;
        ad[ci] = e2 + ((t * 16 + cc) * 8 + (g ^ (2 * (cc & 3)) ^ (2 * t))) * 16;
        lds_frag(q[2 * ci], q[2 * ci + 1], ad[ci], ad[ci] + 8192);
      }
#pragma unroll
      for (int ci = 0; ci < 2; ci++)
#pragma unroll
        for (int p = 0; p < 2; p++) {
          uint32_t y[2][2];
#pragma unroll
          for (int vv = 0; vv < 2; vv++) {
            float d[4];
            mma_az(d, q[2 * ci + p], word(f8, 2 * vv), word(f8, 2 * vv + 1));
#pragma unroll
            for (int rr = 0; rr < 2; rr++) {
              const float fr = wfr[ci * 8 + vv * 4 + 2 * p + rr], fi = wfi[ci * 8 + vv * 4 + 2 * p + rr];
              y[vv][rr] = pack2(d[2 * rr] * fr - d[2 * rr + 1] * fi, d[2 * rr] * fi + d[2 * rr + 1] * fr);
            }
          }
#pragma unroll
          for (int vv = 0; vv < 2; vv++) {
            float d[4];
            mma16816_z(d, y[0][0], y[0][1], y[1][0], y[1][1], word(g8, 2 * vv), word(g8, 2 * vv + 1));
            res[ci][vv][2 * p] = pack2(d[0], d[1]);
            res[ci][vv][2 * p + 1] = pack2(d[2], d[3]);
          }
        }
#pragma unroll
      for (int i = 0; i < 4; i++)
        sts4(ad[i >> 1] + (i & 1) * 8192, res[i >> 1][i & 1][0], res[i >> 1][i & 1][1], res[i >> 1][i & 1][2], res[i >> 1][i & 1][3]);
      bar_sync(NB_CONS, 256);
      const uint32_t eb = e2 + ((warp * 16 + t) * 8 + (g ^ (2 * t) ^ (2 * (warp & 3)))) * 16;
      lds_frag(q[0], q[1], eb, eb + 512);
      lds_frag(q[2], q[3], eb + 1024, eb + 1536);
      cdft16(q, g2, o);
#pragma unroll
      for (int vv = 0; vv < 4; vv++) {
        o[vv].y &= ~1u;
        o[vv].z = (o[vv].z & ~1u) | tag;
        st_tag(zp + vv * 256, o[vv], tag);
      }
    }
    {
      const uint4* const zp = &scr->Z1[((t * 8 + warp) * 128 + c) * 8 + g];
      const uint32_t tst = clock32();
      uint4 gb[4], ga[4], gc[4], tw[4];
      uint2 xr[2][4];
      uint2* lnp[2];
#pragma unroll
      for (int r = 0; r < 2; r++) {
        const int row = 16 * f + 2 * warp + r;
        lnp[r] = reinterpret_cast<uint2*>(&scr->LN[(rb * 8 + (g >> 2)) * 1024 + row * 8 + ((2 * (g & 3) + (t >> 1)) ^ (row & 7))]) + (t & 1);
        asm volatile("" : "+l"(lnp[r]));
      }
#pragma unroll
      for (int i = 0; i < 4; i++) {
        gc[i] = lds4(sbase + SM_FC + 2048 + i * 512 + lane * 16);
        gb[i] = lds4(TOFF(gb) + i * 512);
        ga[i] = lds4(TOFF(ga) + i * 512);
        tw[i] = lds4(TOFF(tw3) + i * 512);
        const int ch = 2 * (g + 8 * i) + (t >> 1);
#pragma unroll
        for (int r = 0; r < 2; r++) xr[r][i] = lds2(sbase + SM_X + (2 * warp + r) * 1024 + ((ch ^ ((ch >> 3) & 1)) * 16) + (t & 1) * 8);
      }
      spin_until(tst + POLL_DELAY2);
      ld_tag4_issue<32768>(q, zp);
      ld_tag4_finish<32768, true>(q, zp, tag);
      if (lane == 0) mbar_arrive(BAR(sig, 1));
      reg_frag(q, ones);
      cdft16(q, gc, o);
#pragma unroll
      for (int vv = 0; vv < 4; vv++)
        sts4(sbase + SM_E + (((4 * vv + t) * 8 + warp) * 8 + (g ^ (warp & 6) ^ (2 * t))) * 16, o[vv].x, o[vv].y, o[vv].z, o[vv].w);
      bar_sync(NB_CONS, 256);
      uint32_t hv[2][8];
      const float mk = t == 0 ? 0.f : 1.f;
#pragma unroll
      for (int r = 0; r < 2; r++) {
        const int j = 2 * warp + r;
        uint4 u[2];
#pragma unroll
        for (int h = 0; h < 2; h++) u[h] = lds4(sbase + SM_E + ((j * 8 + 2 * t + h) * 8 + (g ^ (2 * t) ^ (2 * (j & 3)))) * 16);
        const uint32_t bp[4][2] = {{u[0].x, u[1].x & ones}, {u[0].y & ones, u[1].y}, {u[0].z, u[1].z & ones}, {u[0].w & ones, u[1].w}};
        float y[2][2][4];
#pragma unroll
        for (int i = 0; i < 2; i++) {
          float lo[4], hi[4], e[4];
          mma_az(lo, gb[2 * i], bp[0][0], bp[0][1]);
          mma_az(hi, gb[2 * i + 1], bp[2][0], bp[2][1]);
          mma_az(e, gb[2 * i], bp[1][0], bp[1][1]);
          mma_a(e, gb[2 * i + 1], bp[3][0], bp[3][1]);
          const uint4 &ka = tw[2 * i], &kb = tw[2 * i + 1];
          const float tr0 = fmaf(hi[0], mk, lo[0]), ti0 = fmaf(hi[2], mk, lo[2]);
          const float tr1 = lo[1] + hi[1], ti1 = lo[3] + hi[3];
          const float vr0 = tr0 * u2f(ka.x) - ti0 * u2f(ka.y), vi0 = tr0 * u2f(ka.y) + ti0 * u2f(ka.x);
          const float vr1 = tr1 * u2f(ka.z) - ti1 * u2f(ka.w), vi1 = tr1 * u2f(ka.w) + ti1 * u2f(ka.z);
          const uint32_t b0 = pack2(t == 0 ? hi[0] : vr0, vr1), b1 = pack2(t == 0 ? vr0 : vi0, vi1);
          const uint32_t b2 = pack2(e[0] * u2f(kb.x) - e[2] * u2f(kb.y), e[1] * u2f(kb.z) - e[3] * u2f(kb.w));
          const uint32_t b3 = pack2(e[0] * u2f(kb.y) + e[2] * u2f(kb.x), e[1] * u2f(kb.w) + e[3] * u2f(kb.z));
#pragma unroll
          for (int mt = 0; mt < 2; mt++) {
            mma_az(y[mt][i], ga[2 * mt], b0, b1);
            mma_a(y[mt][i], ga[2 * mt + 1], b2, b3);
          }
        }
#pragma unroll
        for (int i = 0; i < 4; i++) {
          hv[r][2 * i] = hadd2_bf16(xr[r][i].x, pack2(y[i >> 1][0][2 * (i & 1)], y[i >> 1][0][2 * (i & 1) + 1]));
          hv[r][2 * i + 1] = hadd2_bf16(xr[r][i].y, pack2(y[i >> 1][1][2 * (i & 1)], y[i >> 1][1][2 * (i & 1) + 1]));
        }
      }
      float mean[2];
      uint32_t mb[2];
#pragma unroll
      for (int r = 0; r < 2; r++) {
        mean[r] = sum_groups(quad_sum(hv[r])) * (1.f / 512.f);
        mb[r] = pack2(mean[r], mean[r]);
      }
#pragma unroll
      for (int i = 0; i < 4; i++)
#pragma unroll
        for (int r = 0; r < 2; r++) {
          hv[r][2 * i] = hsub2_bf16(hv[r][2 * i], mb[r]);
          hv[r][2 * i + 1] = hsub2_bf16(hv[r][2 * i + 1], mb[r]);
          st_tag8(lnp[r] + i * 4096, hv[r][2 * i], hv[r][2 * i + 1], i == 0 ? tag : (hv[r][2 * i] & 1u));
        }
      bar_arrive(NB_LN, 288);
      const uint32_t ones2 = ~(lds2(BAR(epoch, 0)).x >> 31);
      float rstd[2];
#pragma unroll
      for (int r = 0; r < 2; r++) {
        hv[r][0] &= ones2;
        rstd[r] = row_rstd(hv[r], mean[r] - bf_lo(mb[r]));
      }
      if (lane == 0)
        st_tag(&scr->ST[rb * 64 + 8 * f + warp], make_uint4(mb[0] << 16, __float_as_uint(rstd[0]), mb[1] << 16, __float_as_uint(rstd[1])), tag);
    }
    const int wgi = warp >> 2, wq = warp & 3;
    const int wr = wgi ^ (f >> 2) ^ 1, rt = 4 * wr + wq;
    uint4* const pbase = &scr->P[rb * 28 * 1024 + rt * 128 + lane];
    const uint32_t a_lo0 = desc_lo(sbase + wr * 8192, 16);
    const uint32_t ebar = lane == 0 ? BAR(empty1, 0) : RBAR(empty1, 0);
    float r0, r1;
    uint4 px[8], py[6];
    const int rh = wgi ^ kh ^ 1;
    const uint32_t fpb = BAR(fullP, 16 * rh);
    const uint4* const psrc = &scr->P[(rb2 * 28 + 14 * kh) * 1024 + (4 * rh + wq) * 128 + lane];
    const uint32_t pa0 = sbase + (4 * rh + wq) * 2048;
    uint4 pf[3][4], ha[4][4];
    uint32_t rdy = 0, got0;
    {
      float acc[128];
#pragma unroll
      for (int i = 0; i < 128; i++) acc[i] = 0.f;
      const uint32_t b_lo0 = desc_lo(sbase + 8 * SLOT, 4096);
      const uint32_t t3 = clock32();
      if (WARM) {
        wg_fence();
#pragma unroll
        for (int i = 0; i < WARM; i++) wgmma_n256(acc, desc64(a_lo0 + 6 * 1024, HI128), desc64(b_lo0, HI128));
        wg_commit();
      }
      const uint4* const ap = &scr->LN[rb * 8 * 1024 + wr * 512 + (tid & 127)];
      uint4 av[NLL][4];
      spin_until(t3 + POLL_DELAY3);
#pragma unroll
      for (int kb = 0; kb < NLL; kb++) ld_tag4_issue<128>(av[kb], ap + kb * 1024);
      bar_sync(NB_CONS, 256);
      const uint32_t lma = sbase + (16 * rt + (lane & 15)) * 128;
      auto load_a = [&](int kb) {
#pragma unroll
        for (int ks = 0; ks < 4; ks++)
          asm volatile("ldmatrix.sync.aligned.m8n8.x4.shared.b16 {%0,%1,%2,%3}, [%4];"
                       : "=r"(ha[kb][ks].x), "=r"(ha[kb][ks].y), "=r"(ha[kb][ks].z), "=r"(ha[kb][ks].w)
                       : "r"(lma + kb * SLOT + (((2 * ks + (lane >> 4)) ^ (lane & 7)) * 16)) : "memory");
      };
      auto stash_a = [&](int kb) {
        ld_tag4_finish<128, true>(av[kb], ap + kb * 1024, tag);
#pragma unroll
        for (int i = 0; i < 4; i++)
          sts4(sbase + kb * SLOT + wr * 8192 + ((tid & 127) + 128 * i) * 16, av[kb][i].x, av[kb][i].y, av[kb][i].z, av[kb][i].w);
        bar_sync(NB_WG + wgi, 128);
      };
      stash_a(0);
      load_a(0);
#pragma unroll
      for (int n = 0; n < 8; n++) {
        const int kb = n >> 1, hh = n & 1;
        if (hh == 1 && kb < 3) {
          if (kb + 1 < NLL) stash_a(kb + 1); else mbar_wait(BAR(fullA, kb + 1));
        }
        mbar_wait(BAR(full1, n));
        const uint32_t bl = b_lo0 + ((n + 2) % 6) * 1024;
        wg_fence();
        if (hh == 1 && kb < 3) load_a(kb + 1);
        const uint4 &a0 = ha[kb][2 * hh], &a1 = ha[kb][2 * hh + 1];
        wgmma_rs_n256(acc, a0.x, a0.y, a0.z, a0.w, desc64(bl, HI128), n != 0 ? 1 : ~ones);
        wgmma_rs_n256(acc, a1.x, a1.y, a1.z, a1.w, desc64(bl + 128, HI128));
        wg_commit();
        if (hh == 1 && lane < 2) mbar_arrive_remote(ebar + (uint32_t)(offsetof(Bars, freeA) - offsetof(Bars, empty1)) + 8 * kb);
        wg_wait<1>();
        if (n != 0 && lane < 2) mbar_arrive_remote(ebar + 8 * (n - 1));
      }
      uint32_t slot = 4;
#pragma unroll 1
      for (int kb = 4; kb < 8; kb++) {
        mbar_wait(BAR(fullA, kb));
#pragma unroll
        for (int hh = 0; hh < 2; hh++) {
          if (LAGX && hh == ((16 - LAGX) & 1) && kb == ((16 - LAGX) >> 1) && wgi == 1) bar_sync(NB_LAG, 256);
          mbar_wait(BAR(full1, 2 * kb + hh));
          const uint32_t al = a_lo0 + kb * 1024 + hh * 4, bl = b_lo0 + slot * 1024;
          wg_fence();
          wgmma_n256(acc, desc64(al, HI128), desc64(bl, HI128));
          wgmma_n256(acc, desc64(al + 2, HI128), desc64(bl + 128, HI128));
          wg_commit();
          if (LAGX && hh == 1 && kb == 7 && wgi == 0) bar_arrive(NB_LAG, 256);
          wg_wait<1>();
          if (lane < 2) mbar_arrive_remote(ebar + 8 * (2 * kb + hh - 1));
          if (++slot == 6) slot = 0;
        }
      }
      mbar_wait(BAR(sbar, 0), 0);
      r0 = __uint_as_float(lds2(sstat + (16 * rt + g) * 8).y);
      r1 = __uint_as_float(lds2(sstat + (16 * rt + g + 8) * 8).y);
      wg_wait<0>();
      if (lane < 2) mbar_arrive_remote(ebar + 8 * 15);
      make_p<8, false>(acc, r0, r1, px, pbase, 0, tag);
    }
    {
      float acc[96];
#pragma unroll
      for (int i = 0; i < 96; i++) acc[i] = 0.f;
      const uint32_t b_lo0 = desc_lo(sbase, 2048);
      uint4* const pdst = pbase + ((7 * f + 3 * (f & 1)) >> 1) * 1024;
      auto stage_y = [&](int k) {
        if (LAGY && k == 16 - LAGY && wgi == 1) bar_sync(NB_LAG, 256);
        mbar_wait(BAR(full1, 16 + k));
        const uint32_t al = a_lo0 + (4 + (k >> 1)) * 1024 + (k & 1) * 4, bl = b_lo0 + (k < 5 ? k * 768 : 8192 + (k - 5) * 768);
        wg_fence();
        wgmma_n192(acc, desc64(al, HI128), desc64(bl, HI64));
        wgmma_n192(acc, desc64(al + 2, HI128), desc64(bl + 64, HI64));
        wg_commit();
      };
#pragma unroll
      for (int k = 0; k < 4; k++) {
        stage_y(k);
        st_tag(pdst + (k >> 1) * 1024 + (k & 1) * 64, px[2 * k], tag);
        st_tag(pdst + (k >> 1) * 1024 + (k & 1) * 64 + 32, px[2 * k + 1], tag);
        if (k == 3 && lane == 0) red_relaxed(&scr->cnt[(C_PX + rb) * 32 + (f >> 2)]);
        wg_wait<1>();
        if (k != 0 && lane < 2) mbar_arrive_remote(ebar + 8 * (15 + k));
      }
#pragma unroll 1
      for (int k = 4; k < 8; k++) {
        stage_y(k);
        wg_wait<1>();
        if (lane < 2) mbar_arrive_remote(ebar + 8 * (15 + k));
      }
      rdy = 0;
#pragma unroll
      for (int k = 8; k < 16; k++) {
        if (LAGY && k == 16 - LAGY && wgi == 1) bar_sync(NB_LAG, 256);
        if (!rdy) mbar_wait(BAR(full1, 16 + k));
        const uint32_t bl = b_lo0 + 8192 + ((k - 5) & 7) * 768;
        const uint4 &a0 = ha[(k - 8) >> 1][2 * (k & 1)], &a1 = ha[(k - 8) >> 1][2 * (k & 1) + 1];
        wg_fence();
        if (k < 15) rdy = mbar_test(BAR(full1, 17 + k));
        wgmma_rs_n192(acc, a0.x, a0.y, a0.z, a0.w, desc64(bl, HI64));
        wgmma_rs_n192(acc, a1.x, a1.y, a1.z, a1.w, desc64(bl + 64, HI64));
        wg_commit();
        if (LAGY && k == 15 && wgi == 0) bar_arrive(NB_LAG, 256);
        wg_wait<1>();
        if (lane < 2) mbar_arrive_remote(ebar + 8 * (15 + k));
      }
      got0 = __all_sync(0xffffffffu, mbar_test((fpb + 8 * (0))));
      if (got0) {
#pragma unroll
        for (int kk = 0; kk < 4; kk++) pf[0][kk] = lds4(pa0 + 3 * SLOT + kk * 512 + lane * 16);
      }
      wg_wait<0>();
      if (lane < 2) mbar_arrive_remote(ebar + 8 * 31);
      const int ks0 = 14 * f + ((f & 1) ? 0 : 8);
      auto reread = [&]() {
        asm volatile("ld.volatile.shared.f32 %0, [%2+4]; ld.volatile.shared.f32 %1, [%2+68];" : "=f"(r0), "=f"(r1) : "r"(sstat + (16 * rt + g) * 8) : "memory");
      };
      make_p<6, true, 0, 2>(acc, r0, r1, py, pbase, ks0, tag);
      if (REDPOS == 2 && lane == 0) red_relaxed(&scr->cnt[(C_PY + rb) * 32 + 4 * wgi + (f >> 1)]);
      reread();
      make_p<6, true, 2, 4>(acc, r0, r1, py, pbase, ks0, tag);
      if (REDPOS == 4 && lane == 0) red_relaxed(&scr->cnt[(C_PY + rb) * 32 + 4 * wgi + (f >> 1)]);
      reread();
      rdy = mbar_test(BAR(full2, 0)) & mbar_test((fpb + 8 * (1)));
      make_p<6, true, 4, 6>(acc, r0, r1, py, pbase, ks0, tag);
      if (REDPOS == 6 && lane == 0) red_relaxed(&scr->cnt[(C_PY + rb) * 32 + 4 * wgi + (f >> 1)]);
    }
    {
      float acc[64];
      const uint32_t b2_lo0 = desc_lo(sbase, 8192);
      const uint32_t pbar = rh == rk ? BAR(emptyP, 0) : RBAR(emptyP, 0);
      if (!got0) {
        mbar_wait((fpb + 8 * (0)));
#pragma unroll
        for (int kk = 0; kk < 4; kk++) pf[0][kk] = lds4(pa0 + 3 * SLOT + kk * 512 + lane * 16);
      }
#pragma unroll
      for (int s = 0; s < 14; s++) {
        uint4 (&a)[4] = pf[s % 3];
        ld_tag4_finish<32>(a, psrc + (int)((KORDER >> (4 * s)) & 15) * 1024, tag);
        if (s < 8 && lane == 0) mbar_arrive_remote(pbar + 8 * s);
        if (s >= 2) {
          wg_wait<1>();
          if (s <= 8 && lane == 0) mbar_arrive(BAR(empty2, s - 2));
        }
        if (!rdy) {
          if (s < 13) mbar_wait((fpb + 8 * (s + 1)));
          mbar_wait(BAR(full2, s));
        }
        if (s == 14 - LAG2 && wgi == 1) {
          const float m0 = __uint_as_float(lds2(sstat + 1024 + (16 * wq + g) * 8).x);
          const float m1 = __uint_as_float(lds2(sstat + 1024 + (16 * wq + g + 8) * 8).x);
          const uint32_t hb = sbase + 9 * SLOT + (16 * wq + (lane & 15)) * 128;
          wg_wait<0>();
          mbar_wait(BAR(hbar, 0));
#pragma unroll
          for (int i = 0; i < 8; i++) {
            uint32_t h[4];
            asm volatile("ldmatrix.sync.aligned.m8n8.x4.shared.b16 {%0,%1,%2,%3}, [%4];"
                         : "=r"(h[0]), "=r"(h[1]), "=r"(h[2]), "=r"(h[3])
                         : "r"(hb + (i >> 2) * 8192 + (((2 * (i & 3) + (lane >> 4)) ^ (lane & 7)) * 16)) : "memory");
            const uint32_t mk = ((t & 1) == 0 && nq == 0) ? ~1u : ~0u;
#pragma unroll
            for (int e = 0; e < 4; e++) {
              acc[8 * i + 2 * e] += bf_lo(h[e] & mk) + ((e & 1) ? m1 : m0);
              acc[8 * i + 2 * e + 1] += __uint_as_float(h[e] & 0xffff0000u) + ((e & 1) ? m1 : m0);
            }
          }
          bar_sync(NB_LAG, 256);
        }
        const uint32_t bl = b2_lo0 + (uint32_t)((BSLOT >> (4 * s)) & 15) * 1024;
        wg_fence();
        if (s < 13) {
#pragma unroll
          for (int kk = 0; kk < 4; kk++)
            pf[(s + 1) % 3][kk] = lds4(pa0 + (uint32_t)((PSLOT >> (4 * (s + 1))) & 15) * SLOT + kk * 512 + lane * 16);
          rdy = mbar_test(BAR(full2, s + 1));
          if (s < 12) rdy &= mbar_test((fpb + 8 * (s + 2)));
        }
        if (s == 0) wgmma_rs_n128<0>(acc, a[0].x, a[0].y, a[0].z, a[0].w, desc64(bl, HI128));
        else wgmma_rs_n128<1>(acc, a[0].x, a[0].y, a[0].z, a[0].w, desc64(bl, HI128));
#pragma unroll
        for (int kk = 1; kk < 4; kk++) wgmma_rs_n128<1>(acc, a[kk].x, a[kk].y, a[kk].z, a[kk].w, desc64(bl + kk * 128, HI128));
        wg_commit();
      }
      if (wgi == 0) {
        bar_arrive(NB_LAG, 256);
        uint4* const dst = &scr->Z1[(tid >> 3) * 1024 + (c ^ 4) * 8 + (tid & 7)];
        wg_wait<0>();
#pragma unroll
        for (int i = 0; i < 8; i++)
          st_tag(dst + i * 16384, make_uint4(pack2(acc[8 * i], acc[8 * i + 1]), pack2(acc[8 * i + 2], acc[8 * i + 3]) | 1u,
                                           pack2(acc[8 * i + 4], acc[8 * i + 5]), pack2(acc[8 * i + 6], acc[8 * i + 7])), tag);
      } else {
        uint4 pv[2][4];
        const uint4* const xsrc = &scr->Z1[((tid & 127) >> 3) * 1024 + c * 8 + (tid & 7)];
        ld_tag4_issue<16384>(pv[0], xsrc);
        ld_tag4_issue<16384>(pv[1], xsrc + 65536);
        wg_wait<0>();
        uint32_t w[32];
#pragma unroll
        for (int i = 0; i < 32; i++) w[i] = pack2(acc[2 * i], acc[2 * i + 1]);
        int it = 0;
#pragma unroll 1
        while (!__all_sync(0xffffffffu, pv[0][0].y & pv[0][1].y & pv[0][2].y & pv[0][3].y & pv[1][0].y & pv[1][1].y & pv[1][2].y & pv[1][3].y & 1u)) {
          ld_tag4_issue<16384>(pv[0], xsrc);
          ld_tag4_issue<16384>(pv[1], xsrc + 65536);
          if (++it > SPIN_LIMIT) { die(); break; }
        }
#pragma unroll
        for (int i = 0; i < 8; i++) {
          const uint4& p = pv[i >> 2][i & 3];
          asm volatile("stmatrix.sync.aligned.m8n8.x4.shared.b16 [%0], {%1,%2,%3,%4};"
                       ::"r"(pa0 + (11 + ((lane >> 3) & 1)) * SLOT + (lane & 7) * 256 + (((2 * i + (lane >> 4)) ^ (lane & 7)) * 16)),
                         "r"(hadd2_bf16(w[4 * i], p.x & ~1u)), "r"(hadd2_bf16(w[4 * i + 1], p.y & ~1u)), "r"(hadd2_bf16(w[4 * i + 2], p.z)),
                         "r"(hadd2_bf16(w[4 * i + 3], p.w)) : "memory");
        }
        __syncwarp();
        uint4* const dst = reinterpret_cast<uint4*>(out) + (16 * (c >> 4) + 2 * (4 * rh + wq) + (rb2 & 1) + 128 * (lane >> 4)) * 64 + nq * 16 + (lane & 15);
#pragma unroll
        for (int i = 0; i < 8; i++) {
          const int r = 2 * (i & 3) + (lane >> 4);
          dst[i * 256 * 64] = lds4(pa0 + (11 + (i >> 2)) * SLOT + r * 256 + (((lane & 15) ^ r) * 16));
        }
      }
    }
  }
#undef BAR
#undef TOFF
#undef RBAR
}

typedef CUresult (*EncodeFn)(CUtensorMap*, CUtensorMapDataType, cuuint32_t, void*, const cuuint64_t*, const cuuint64_t*,
                             const cuuint32_t*, const cuuint32_t*, CUtensorMapInterleave, CUtensorMapSwizzle,
                             CUtensorMapL2promotion, CUtensorMapFloatOOBfill);

}

extern "C" void kernel_launch(void* const* d_in, const int* in_sizes, int n_in, void* d_out, int out_size) {
  (void)in_sizes; (void)n_in; (void)out_size;
  static EncodeFn encode = nullptr;
  static void *tab = nullptr, *scr = nullptr;
  if (!encode) {
    void* fn = nullptr;
    cudaDriverEntryPointQueryResult qr;
    cudaGetDriverEntryPoint("cuTensorMapEncodeTiled", &fn, cudaEnableDefault, &qr);
    encode = (EncodeFn)fn;
    cudaGetSymbolAddress(&tab, g_tab);
    cudaGetSymbolAddress(&scr, g_scr);
    cudaFuncSetAttribute(fused_kernel, cudaFuncAttributeMaxDynamicSharedMemorySize, SMEM_BYTES);
  }
  CUtensorMap tmGX, tmUX, tmGY, tmUY, tmD, tmWR, tmWI;
  const cuuint32_t es[5] = {1, 1, 1, 1, 1};
  auto enc = [&](CUtensorMap* m, void* p, int rank, const cuuint64_t* gd, const cuuint64_t* gs, const cuuint32_t* bd,
                 CUtensorMapSwizzle sw, CUtensorMapL2promotion pr) {
    encode(m, CU_TENSOR_MAP_DATA_TYPE_BFLOAT16, rank, p, gd, gs, bd, es, CU_TENSOR_MAP_INTERLEAVE_NONE, sw, pr,
           CU_TENSOR_MAP_FLOAT_OOB_FILL_NONE);
  };
  {
    const cuuint64_t gd[3] = {64, 512, 28}, gs[2] = {3584, 128};
    const cuuint32_t bd[3] = {64, 32, 2};
    enc(&tmGX, d_in[4], 3, gd, gs, bd, CU_TENSOR_MAP_SWIZZLE_128B, CU_TENSOR_MAP_L2_PROMOTION_L2_256B);
    enc(&tmUX, d_in[5], 3, gd, gs, bd, CU_TENSOR_MAP_SWIZZLE_128B, CU_TENSOR_MAP_L2_PROMOTION_L2_256B);
  }
  {
    const cuuint64_t gd[3] = {32, 512, 56}, gs[2] = {3584, 64};
    const cuuint32_t bd[3] = {32, 32, 3};
    enc(&tmGY, d_in[4], 3, gd, gs, bd, CU_TENSOR_MAP_SWIZZLE_64B, CU_TENSOR_MAP_L2_PROMOTION_L2_128B);
    enc(&tmUY, d_in[5], 3, gd, gs, bd, CU_TENSOR_MAP_SWIZZLE_64B, CU_TENSOR_MAP_L2_PROMOTION_L2_128B);
  }
  {
    const cuuint64_t gd[3] = {64, 1792, 8}, gs[2] = {1024, 128};
    const cuuint32_t bd[3] = {64, 64, 2};
    enc(&tmD, d_in[6], 3, gd, gs, bd, CU_TENSOR_MAP_SWIZZLE_128B, CU_TENSOR_MAP_L2_PROMOTION_L2_256B);
  }
  {
    const cuuint64_t gd[3] = {4112, 8, 16}, gs[2] = {16 * 8224, 8224};
    const cuuint32_t bd[3] = {40, 8, 16};
    enc(&tmWR, d_in[1], 3, gd, gs, bd, CU_TENSOR_MAP_SWIZZLE_NONE, CU_TENSOR_MAP_L2_PROMOTION_NONE);
    enc(&tmWI, d_in[2], 3, gd, gs, bd, CU_TENSOR_MAP_SWIZZLE_NONE, CU_TENSOR_MAP_L2_PROMOTION_NONE);
  }
  fused_kernel<<<NCTA, NTHREADS, SMEM_BYTES>>>((const __nv_bfloat16*)d_in[0], (const Tables*)tab, (Scratch*)scr,
                                               (__nv_bfloat16*)d_out, (const char*)d_in[4], (const char*)d_in[5],
                                               (const char*)d_in[6], tmWR, tmWI, tmGX, tmUX, tmGY, tmUY, tmD);
}
```

```cpp
#include <cuda_runtime.h>
#include <cuda_bf16.h>
#include <cuda.h>
#include <stdint.h>

namespace {

constexpr int NCTA = 128;
constexpr int NTHREADS = 384;
constexpr int SLOT = 16384;
constexpr int SMEM_BYTES = 14 * SLOT + 3072;
constexpr int SPIN_LIMIT = 1 << 22;

struct Scratch {
  uint4 Z1[128 * 1024];
  uint4 LN[16 * 8 * 1024];
  uint4 P[16 * 28 * 1024];
  uint4 ST[1024];
  unsigned cnt[64 * 32];
};
__device__ __align__(1024) Scratch g_scr;

constexpr double ccos(int i, int n) {
  i &= n - 1;
  if (i > n / 2) i = n - i;
  if (4 * i == n) return 0.0;
  const bool neg = 4 * i > n;
  if (neg) i = n / 2 - i;
  const double a = 6.283185307179586476925 * i / n, a2 = a * a;
  double term = 1.0, sum = 1.0;
  for (int k = 1; k < 14; k++) { term *= -a2 / ((2 * k - 1) * (2 * k)); sum += term; }
  return neg ? -sum : sum;
}
constexpr double csin(int i, int n) { return ccos(i - n / 4, n); }
constexpr unsigned fbits(double v, int mant) {
  if (v == 0.0) return 0;
  const unsigned sg = v < 0 ? 1u : 0u;
  if (v < 0) v = -v;
  int e = 127;
  while (v < 1.0) { v *= 2.0; e--; }
  const unsigned m = (unsigned)((v - 1.0) * (double)(1u << mant) + 0.5);
  return (sg << (8 + mant)) + ((unsigned)e << mant) + m;
}
constexpr unsigned pkb(double lo, double hi) { return fbits(lo, 7) | (fbits(hi, 7) << 16); }
constexpr double fa_elem(int mt, int r, int n1) {
  const int k1 = 8 * mt + (r & 7);
  return r < 8 ? ccos(k1 * n1, 32) : k1 == 0 ? ccos(16 * n1, 32) : -csin(k1 * n1, 32);
}
constexpr unsigned cfrag_c(int idx, int n, int ri, double s = 1.0) {
  return ri ? pkb(-s * csin(idx, n), s * ccos(idx, n)) : pkb(s * ccos(idx, n), s * csin(idx, n));
}
struct Tables {
  unsigned fa[4][32][4];
  unsigned fb[4][32][4];
  unsigned tw1[6][32][4];
  unsigned f2[8][4][32][4];
  unsigned g2[8][4][32][4];
  unsigned gb[4][32][4];
  unsigned ga[4][32][4];
  unsigned tw3[4][32][4];
  unsigned f8[32][4], g8[32][4];
};
constexpr int T1_BYTES = 7168, T2_BYTES = 39936;
static_assert(sizeof(Tables) == T1_BYTES + T2_BYTES, "table size");
constexpr Tables make_tables() {
  Tables T = {};
  for (int l = 0; l < 32; l++) {
    const int g = l >> 2, t = l & 3;
    for (int a = 0; a < 2; a++)
      for (int b = 0; b < 2; b++) {
        for (int r = 0; r < 4; r++) {
          const int row = g + 8 * (r & 1), col = 2 * t + 8 * (r >> 1);
          T.fa[2 * a + b][l][r] = pkb(fa_elem(a, row, 16 * b + col), fa_elem(a, row, 16 * b + col + 1));
          T.ga[2 * a + b][l][r] = pkb(fa_elem(b, col, 16 * a + row), fa_elem(b, col + 1, 16 * a + row));
        }
        const double sg = b ? -1.0 : 1.0;
        for (int h = 0; h < 2; h++) {
          const int ri = g & 1, m = 2 * (g >> 1) + h, k2 = b ? 15 - m : m;
          const int pa = (8 * a + 2 * t) * k2, pb = (8 * a + 2 * t + 1) * k2;
          T.fb[2 * a + b][l][2 * h] = ri == 0 ? pkb(ccos(pa, 16), ccos(pb, 16)) : pkb(-sg * csin(pa, 16), -sg * csin(pb, 16));
          T.fb[2 * a + b][l][2 * h + 1] = ri == 0 ? pkb(csin(pa, 16), csin(pb, 16)) : pkb(sg * ccos(pa, 16), sg * ccos(pb, 16));
        }
        const int n2 = 4 * (g >> 1) + 2 * a + (g & 1);
        for (int h = 0; h < 2; h++) {
          const int p = n2 * (b ? 15 - 2 * t - h : 2 * t + h);
          T.gb[2 * a + b][l][2 * h] = pkb(ccos(p, 16), -sg * csin(p, 16));
          T.gb[2 * a + b][l][2 * h + 1] = pkb(csin(p, 16), sg * ccos(p, 16));
          const int k1 = 8 * b + 2 * t + h, q = n2 * (k1 == 0 ? 16 : k1);
          T.tw3[2 * a + b][l][2 * h] = fbits(ccos(q, 512), 23);
          T.tw3[2 * a + b][l][2 * h + 1] = fbits(csin(q, 512), 23);
        }
        const int p = (8 * a + 2 * t + b) * (g == 0 ? 16 : g);
        T.tw1[2 * a + b][l][0] = fbits(g == 0 ? 0.0 : ccos(p, 512), 23);
        T.tw1[2 * a + b][l][1] = fbits(g == 0 ? ccos(p, 512) : csin(p, 512), 23);
        T.tw1[2 * a + b][l][2] = fbits(g == 0 ? 0.0 : -csin(p, 512), 23);
        T.tw1[2 * a + b][l][3] = fbits(g == 0 ? -csin(p, 512) : ccos(p, 512), 23);
        T.tw1[4 + a][l][2 * b] = fbits(ccos((8 * a + 2 * t + b) * (g + 8), 512), 23);
        T.tw1[4 + a][l][2 * b + 1] = fbits(csin((8 * a + 2 * t + b) * (g + 8), 512), 23);
      }
    for (int i = 0; i < 4; i++) {
      const int p8 = (t + 4 * (i & 1)) * (4 * (i >> 1) + (g >> 1));
      T.f8[l][i] = cfrag_c(p8, 8, g & 1);
      T.g8[l][i] = cfrag_c(-p8, 8, g & 1, 1.0 / (1 << 19));
    }
    for (int w = 0; w < 8; w++)
      for (int i = 0; i < 16; i++) {
        const int kidx = t + 4 * (i & 1) + 8 * (i >> 3), nidx = 4 * ((i >> 1) & 3) + (g >> 1);
        T.f2[w][i >> 2][l][i & 3] = cfrag_c((8 * kidx + w) * nidx, 128, g & 1);
        T.g2[w][i >> 2][l][i & 3] = cfrag_c(-(8 * nidx + w) * kidx, 128, g & 1);
      }
  }
  return T;
}
__device__ const __align__(128) Tables g_tab = make_tables();

__device__ __forceinline__ void die() { asm volatile("st.global.u32 [%0], %1;" ::"l"(0ull), "r"(0) : "memory"); }
__device__ __forceinline__ uint32_t s2u(const void* p) { return (uint32_t)__cvta_generic_to_shared(p); }
__device__ __forceinline__ void mbar_init(uint32_t b, int c) { asm volatile("mbarrier.init.shared::cta.b64 [%0], %1;" ::"r"(b), "r"(c)); }
__device__ __forceinline__ void mbar_expect(uint32_t b, int bytes) {
  asm volatile("mbarrier.arrive.expect_tx.shared::cta.b64 _, [%0], %1;" ::"r"(b), "r"(bytes) : "memory");
}
__device__ __forceinline__ void mbar_arrive(uint32_t b) { asm volatile("mbarrier.arrive.shared::cta.b64 _, [%0];" ::"r"(b) : "memory"); }
__device__ __forceinline__ uint32_t mbar_try(uint32_t b, uint32_t parity) {
  uint32_t ok;
  asm volatile("{.reg .pred p; mbarrier.try_wait.parity.shared::cta.b64 p, [%1], %2; selp.u32 %0,1,0,p;}"
               : "=r"(ok) : "r"(b), "r"(parity) : "memory");
  return ok;
}
__device__ __forceinline__ uint32_t mbar_test(uint32_t b) {
  uint32_t ok;
  asm volatile("{.reg .pred p; mbarrier.test_wait.parity.shared::cta.b64 p, [%1], 0; selp.u32 %0,1,0,p;}" : "=r"(ok) : "r"(b) : "memory");
  return ok;
}
__device__ __forceinline__ void mbar_wait(uint32_t b, uint32_t parity = 0) {
  int it = 0;
#pragma unroll 1
  while (!mbar_try(b, parity))
    if (++it > SPIN_LIMIT) { die(); break; }
}
__device__ __forceinline__ void bar_sync(int id, int n) { asm volatile("bar.sync %0, %1;" ::"r"(id), "r"(n) : "memory"); }
__device__ __forceinline__ void bar_arrive(int id, int n) { asm volatile("bar.arrive %0, %1;" ::"r"(id), "r"(n) : "memory"); }
__device__ __forceinline__ void red_release(unsigned* p) { asm volatile("red.release.gpu.global.add.u32 [%0], 1;" ::"l"(p) : "memory"); }
__device__ __forceinline__ void red_relaxed(unsigned* p) { asm volatile("red.relaxed.gpu.global.add.u32 [%0], 1;" ::"l"(p) : "memory"); }
__device__ __forceinline__ unsigned ld_acquire(const unsigned* p) {
  unsigned v;
  asm volatile("ld.acquire.gpu.global.u32 %0, [%1];" : "=r"(v) : "l"(p) : "memory");
  return v;
}
__device__ __forceinline__ unsigned ld_relaxed(const unsigned* p) {
  unsigned v;
  asm volatile("ld.relaxed.gpu.global.u32 %0, [%1];" : "=r"(v) : "l"(p) : "memory");
  return v;
}
__device__ __forceinline__ void wait_counter(const unsigned* p, unsigned target) {
  int it = 0;
  while ((int)(ld_acquire(p) - target) < 0)
    if (++it > SPIN_LIMIT) { die(); break; }
}
__device__ __forceinline__ void sts4(uint32_t a, uint32_t x, uint32_t y, uint32_t z, uint32_t w) {
  asm volatile("st.shared.v4.u32 [%0], {%1,%2,%3,%4};" ::"r"(a), "r"(x), "r"(y), "r"(z), "r"(w) : "memory");
}
__device__ __forceinline__ uint4 lds4(uint32_t a) {
  uint4 v;
  asm volatile("ld.shared.v4.u32 {%0,%1,%2,%3}, [%4];" : "=r"(v.x), "=r"(v.y), "=r"(v.z), "=r"(v.w) : "r"(a) : "memory");
  return v;
}
__device__ __forceinline__ uint32_t pack2(float lo, float hi) {
  uint32_t r;
  asm("cvt.rn.bf16x2.f32 %0, %1, %2;" : "=r"(r) : "f"(hi), "f"(lo));
  return r;
}
__device__ __forceinline__ float bf_lo(uint32_t v) { return __uint_as_float(v << 16); }
__device__ __forceinline__ uint32_t hadd2_bf16(uint32_t a, uint32_t b) {
  uint32_t r;
  asm("add.rn.bf16x2 %0, %1, %2;" : "=r"(r) : "r"(a), "r"(b));
  return r;
}
__device__ __forceinline__ void mma16816(float (&d)[4], uint32_t a0, uint32_t a1, uint32_t a2, uint32_t a3, uint32_t b0, uint32_t b1) {
  asm("mma.sync.aligned.m16n8k16.row.col.f32.bf16.bf16.f32 {%0,%1,%2,%3}, {%4,%5,%6,%7}, {%8,%9}, {%0,%1,%2,%3};"
      : "+f"(d[0]), "+f"(d[1]), "+f"(d[2]), "+f"(d[3])
      : "r"(a0), "r"(a1), "r"(a2), "r"(a3), "r"(b0), "r"(b1));
}
__device__ __forceinline__ void mma16816_z(float (&d)[4], uint32_t a0, uint32_t a1, uint32_t a2, uint32_t a3, uint32_t b0, uint32_t b1) {
  asm("{.reg .f32 z; mov.f32 z, 0f00000000;\n"
      "mma.sync.aligned.m16n8k16.row.col.f32.bf16.bf16.f32 {%0,%1,%2,%3}, {%4,%5,%6,%7}, {%8,%9}, {z,z,z,z};}"
      : "=f"(d[0]), "=f"(d[1]), "=f"(d[2]), "=f"(d[3])
      : "r"(a0), "r"(a1), "r"(a2), "r"(a3), "r"(b0), "r"(b1));
}
template <int N>
__device__ __forceinline__ void cs_frac(int idx, float& c, float& s) {
  int i = ((idx + N / 2) & (N - 1)) - N / 2;
  float a = (float)i * (6.283185307179586f / N);
  c = __cosf(a);
  s = __sinf(a);
}
template <int N>
__device__ __forceinline__ uint32_t cfrag(int idx, int ri) {
  float c, s;
  cs_frac<N>(idx, c, s);
  return ri ? pack2(-s, c) : pack2(c, s);
}
__device__ __forceinline__ uint32_t word(const uint4& v, int e) { return e == 0 ? v.x : e == 1 ? v.y : e == 2 ? v.z : v.w; }
__device__ __forceinline__ void cdft16(const uint4 (&A)[4], const uint4 (&F)[4], uint4 (&o)[4]) {
  float acc[2][4][4];
#pragma unroll
  for (int ks = 0; ks < 2; ks++)
#pragma unroll
    for (int p = 0; p < 2; p++)
#pragma unroll
      for (int v = 0; v < 4; v++) {
        const uint4& a = A[2 * ks + p];
        const uint32_t b0 = word(F[ks * 2 + (v >> 1)], (v & 1) * 2), b1 = word(F[ks * 2 + (v >> 1)], (v & 1) * 2 + 1);
        if (ks == 0) mma16816_z(acc[p][v], a.x, a.y, a.z, a.w, b0, b1);
        else mma16816(acc[p][v], a.x, a.y, a.z, a.w, b0, b1);
      }
#pragma unroll
  for (int v = 0; v < 4; v++)
    o[v] = make_uint4(pack2(acc[0][v][0], acc[0][v][1]), pack2(acc[0][v][2], acc[0][v][3]),
                      pack2(acc[1][v][0], acc[1][v][1]), pack2(acc[1][v][2], acc[1][v][3]));
}
__device__ __forceinline__ void lds_frag(uint4& f0, uint4& f1, uint32_t a0, uint32_t a1) {
  asm volatile("ld.volatile.shared.v2.u32 {%0,%1}, [%8]; ld.volatile.shared.v2.u32 {%2,%3}, [%9];\n"
               "ld.volatile.shared.v2.u32 {%4,%5}, [%8+8]; ld.volatile.shared.v2.u32 {%6,%7}, [%9+8];"
               : "=r"(f0.x), "=r"(f0.y), "=r"(f0.z), "=r"(f0.w), "=r"(f1.x), "=r"(f1.y), "=r"(f1.z), "=r"(f1.w) : "r"(a0), "r"(a1) : "memory");
}
__device__ __forceinline__ void reg_frag(uint4 (&q)[4], uint32_t ones) {
#pragma unroll
  for (int ks = 0; ks < 2; ks++) {
    const uint4 a = q[2 * ks], b = q[2 * ks + 1];
    q[2 * ks] = make_uint4(a.x, a.y, b.x & ones, b.y & ones);
    q[2 * ks + 1] = make_uint4(a.z & ones, a.w & ones, b.z, b.w);
  }
}
__device__ __forceinline__ void st_tag(uint4* p, const uint4& v, uint32_t tag) {
  asm volatile("st.relaxed.gpu.global.v4.b32 [%0], {%1,%2,%3,%4};"
               ::"l"(p), "r"((v.x & ~1u) | tag), "r"(v.y), "r"(v.z), "r"(v.w) : "memory");
}
__device__ __forceinline__ void st_tag8(void* p, uint32_t x, uint32_t y, uint32_t tag) {
  asm volatile("st.relaxed.gpu.global.v2.b32 [%0], {%1,%2};" ::"l"(p), "r"((x & ~1u) | tag), "r"(y) : "memory");
}
__device__ __forceinline__ uint4 ld_b128(const uint4* p) {
  uint4 v;
  asm volatile("ld.relaxed.gpu.global.v4.b32 {%0,%1,%2,%3}, [%4];"
               : "=r"(v.x), "=r"(v.y), "=r"(v.z), "=r"(v.w) : "l"(p) : "memory");
  return v;
}
template <int STRIDE>
__device__ __forceinline__ void ld_tag4_issue(uint4 (&q)[4], const uint4* p) {
#pragma unroll
  for (int i = 0; i < 4; i++) q[i] = ld_b128(p + i * STRIDE);
}
template <int STRIDE, bool HALVES = false>
__device__ __forceinline__ void ld_tag4_finish(uint4 (&q)[4], const uint4* p, uint32_t tag) {
  int it = 0;
#pragma unroll 1
  while (__any_sync(0xffffffffu, ((q[0].x ^ tag) | (q[1].x ^ tag) | (q[2].x ^ tag) | (q[3].x ^ tag) |
                                  (HALVES ? (q[0].z ^ tag) | (q[1].z ^ tag) | (q[2].z ^ tag) | (q[3].z ^ tag) : 0u)) & 1u)) {
    ld_tag4_issue<STRIDE>(q, p);
    if (++it > SPIN_LIMIT) { die(); break; }
  }
#pragma unroll
  for (int i = 0; i < 4; i++) {
    asm volatile("and.b32 %0, %0, 0xfffffffe;" : "+r"(q[i].x));
    if (HALVES) q[i].z &= ~1u;
  }
}
__device__ __forceinline__ float quad_sum(const uint32_t (&a)[8]) {
  float d[4];
  mma16816_z(d, a[0], a[1], a[2], a[3], 0x3f803f80u, 0x3f803f80u);
  mma16816(d, a[4], a[5], a[6], a[7], 0x3f803f80u, 0x3f803f80u);
  return d[0] + d[2];
}
__device__ __forceinline__ float sum_groups(float v) {
  v += __shfl_xor_sync(0xffffffffu, v, 4);
  v += __shfl_xor_sync(0xffffffffu, v, 8);
  v += __shfl_xor_sync(0xffffffffu, v, 16);
  return v;
}
__device__ __forceinline__ uint32_t hsub2_bf16(uint32_t a, uint32_t b) {
  uint32_t r;
  asm("sub.rn.bf16x2 %0, %1, %2;" : "=r"(r) : "r"(a), "r"(b));
  return r;
}
__device__ __forceinline__ float row_rstd(const uint32_t (&c)[8], float delta) {
  uint32_t s[8];
#pragma unroll
  for (int i = 0; i < 8; i++) asm("mul.rn.bf16x2 %0, %1, %1;" : "=r"(s[i]) : "r"(c[i]));
  return rsqrtf(fmaxf(fmaf(-delta, delta, sum_groups(quad_sum(s)) * (1.f / 512.f)), 0.f) + 1e-5f);
}
__device__ __forceinline__ uint64_t desc64(uint32_t lo, uint32_t hi) {
  uint64_t d;
  asm("mov.b64 %0, {%1, %2};" : "=l"(d) : "r"(lo), "r"(hi));
  return d;
}
constexpr uint32_t desc_hi(uint32_t sbo, uint32_t swz) { return (sbo >> 4) | (swz << 30); }
__device__ __forceinline__ uint32_t desc_lo(uint32_t addr, uint32_t lbo) { return ((addr & 0x3FFFF) >> 4) | ((lbo >> 4) << 16); }
__device__ __forceinline__ void cp_async16(uint32_t dst, const void* src) {
  asm volatile("cp.async.cg.shared.global [%0], [%1], 16;" ::"r"(dst), "l"(src) : "memory");
}
__device__ __forceinline__ uint2 lds2(uint32_t a) {
  uint2 v;
  asm volatile("ld.shared.v2.u32 {%0,%1}, [%2];" : "=r"(v.x), "=r"(v.y) : "r"(a) : "memory");
  return v;
}
__device__ __forceinline__ uint32_t lds_u16(uint32_t a) {
  uint16_t v;
  asm volatile("ld.shared.u16 %0, [%1];" : "=h"(v) : "r"(a) : "memory");
  return v;
}
__device__ __forceinline__ void wg_fence() { asm volatile("wgmma.fence.sync.aligned;" ::: "memory"); }
__device__ __forceinline__ void wg_commit() { asm volatile("wgmma.commit_group.sync.aligned;" ::: "memory"); }
template <int N>
__device__ __forceinline__ void wg_wait() { asm volatile("wgmma.wait_group.sync.aligned %0;" ::"n"(N) : "memory"); }
__device__ __forceinline__ void bulk_load(uint32_t dst, const void* src, int bytes, uint32_t bar) {
  asm volatile("cp.async.bulk.shared::cluster.global.mbarrier::complete_tx::bytes [%0], [%1], %2, [%3];"
               ::"r"(dst), "l"(src), "r"(bytes), "r"(bar) : "memory");
}
__device__ __forceinline__ void bulk_load_mc(uint32_t dst, const void* src, int bytes, uint32_t bar) {
  asm volatile("cp.async.bulk.shared::cluster.global.mbarrier::complete_tx::bytes.multicast::cluster [%0], [%1], %2, [%3], %4;"
               ::"r"(dst), "l"(src), "r"(bytes), "r"(bar), "h"((uint16_t)3) : "memory");
}
__device__ __forceinline__ void tma3(uint32_t dst, const CUtensorMap* tm, uint32_t bar, int c0, int c1, int c2) {
  asm volatile("cp.async.bulk.tensor.3d.shared::cluster.global.mbarrier::complete_tx::bytes [%0], [%1, {%3,%4,%5}], [%2];"
               ::"r"(dst), "l"(tm), "r"(bar), "r"(c0), "r"(c1), "r"(c2) : "memory");
}
__device__ __forceinline__ void tma3_mc(uint32_t dst, const CUtensorMap* tm, uint32_t bar, int c1, int c2) {
  asm volatile("cp.async.bulk.tensor.3d.shared::cluster.global.mbarrier::complete_tx::bytes.multicast::cluster [%0], [%1, {%3,%4,%5}], [%2], %6;"
               ::"r"(dst), "l"(tm), "r"(bar), "r"(0), "r"(c1), "r"(c2), "h"((uint16_t)3) : "memory");
}
__device__ __forceinline__ void mbar_arrive_remote(uint32_t rb) {
  asm volatile("mbarrier.arrive.shared::cluster.b64 _, [%0];" ::"r"(rb) : "memory");
}
__device__ __forceinline__ uint4 ldg_ca4(const void* p) {
  uint4 v;
  asm volatile("ld.global.ca.v4.u32 {%0,%1,%2,%3}, [%4];" : "=r"(v.x), "=r"(v.y), "=r"(v.z), "=r"(v.w) : "l"(p) : "memory");
  return v;
}
__device__ __forceinline__ float u2f(uint32_t v) { return __uint_as_float(v); }
__device__ __forceinline__ void mma_az(float (&d)[4], const uint4& a, uint32_t b0, uint32_t b1) { mma16816_z(d, a.x, a.y, a.z, a.w, b0, b1); }
__device__ __forceinline__ void mma_a(float (&d)[4], const uint4& a, uint32_t b0, uint32_t b1) { mma16816(d, a.x, a.y, a.z, a.w, b0, b1); }
__device__ __forceinline__ uint32_t clock32() {
  uint32_t v;
  asm volatile("mov.u32 %0, %%clock;" : "=r"(v) :: "memory");
  return v;
}
__device__ __forceinline__ float swiglu(float g, float u, float r) {
  float hg = (0.5f * r) * g, th;
  asm("tanh.approx.f32 %0, %1;" : "=f"(th) : "f"(hg));
  return fmaf(hg, th, hg) * (r * u);
}
__device__ __forceinline__ void l2_prefetch(const void* p, int bytes) {
  asm volatile("cp.async.bulk.prefetch.L2.global [%0], %1;" ::"l"(p), "r"(bytes) : "memory");
}

__device__ __forceinline__ void wgmma_n256(float (&d)[128], uint64_t da, uint64_t db, int sd = 1) {
  asm volatile("{.reg .pred p; setp.ne.b32 p, %130, 0;\n"
      "wgmma.mma_async.sync.aligned.m64n256k16.f32.bf16.bf16 {"
      "%0,%1,%2,%3,%4,%5,%6,%7,%8,%9,%10,%11,%12,%13,%14,%15,"
      "%16,%17,%18,%19,%20,%21,%22,%23,%24,%25,%26,%27,%28,%29,%30,%31,"
      "%32,%33,%34,%35,%36,%37,%38,%39,%40,%41,%42,%43,%44,%45,%46,%47,"
      "%48,%49,%50,%51,%52,%53,%54,%55,%56,%57,%58,%59,%60,%61,%62,%63,"
      "%64,%65,%66,%67,%68,%69,%70,%71,%72,%73,%74,%75,%76,%77,%78,%79,"
      "%80,%81,%82,%83,%84,%85,%86,%87,%88,%89,%90,%91,%92,%93,%94,%95,"
      "%96,%97,%98,%99,%100,%101,%102,%103,%104,%105,%106,%107,%108,%109,%110,%111,"
      "%112,%113,%114,%115,%116,%117,%118,%119,%120,%121,%122,%123,%124,%125,%126,%127"
      "}, %128, %129, p, 1, 1, 0, 1;}\n"
      : "+f"(d[0]),"+f"(d[1]),"+f"(d[2]),"+f"(d[3]),"+f"(d[4]),"+f"(d[5]),"+f"(d[6]),"+f"(d[7]),
        "+f"(d[8]),"+f"(d[9]),"+f"(d[10]),"+f"(d[11]),"+f"(d[12]),"+f"(d[13]),"+f"(d[14]),"+f"(d[15]),
        "+f"(d[16]),"+f"(d[17]),"+f"(d[18]),"+f"(d[19]),"+f"(d[20]),"+f"(d[21]),"+f"(d[22]),"+f"(d[23]),
        "+f"(d[24]),"+f"(d[25]),"+f"(d[26]),"+f"(d[27]),"+f"(d[28]),"+f"(d[29]),"+f"(d[30]),"+f"(d[31]),
        "+f"(d[32]),"+f"(d[33]),"+f"(d[34]),"+f"(d[35]),"+f"(d[36]),"+f"(d[37]),"+f"(d[38]),"+f"(d[39]),
        "+f"(d[40]),"+f"(d[41]),"+f"(d[42]),"+f"(d[43]),"+f"(d[44]),"+f"(d[45]),"+f"(d[46]),"+f"(d[47]),
        "+f"(d[48]),"+f"(d[49]),"+f"(d[50]),"+f"(d[51]),"+f"(d[52]),"+f"(d[53]),"+f"(d[54]),"+f"(d[55]),
        "+f"(d[56]),"+f"(d[57]),"+f"(d[58]),"+f"(d[59]),"+f"(d[60]),"+f"(d[61]),"+f"(d[62]),"+f"(d[63]),
        "+f"(d[64]),"+f"(d[65]),"+f"(d[66]),"+f"(d[67]),"+f"(d[68]),"+f"(d[69]),"+f"(d[70]),"+f"(d[71]),
        "+f"(d[72]),"+f"(d[73]),"+f"(d[74]),"+f"(d[75]),"+f"(d[76]),"+f"(d[77]),"+f"(d[78]),"+f"(d[79]),
        "+f"(d[80]),"+f"(d[81]),"+f"(d[82]),"+f"(d[83]),"+f"(d[84]),"+f"(d[85]),"+f"(d[86]),"+f"(d[87]),
        "+f"(d[88]),"+f"(d[89]),"+f"(d[90]),"+f"(d[91]),"+f"(d[92]),"+f"(d[93]),"+f"(d[94]),"+f"(d[95]),
        "+f"(d[96]),"+f"(d[97]),"+f"(d[98]),"+f"(d[99]),"+f"(d[100]),"+f"(d[101]),"+f"(d[102]),"+f"(d[103]),
        "+f"(d[104]),"+f"(d[105]),"+f"(d[106]),"+f"(d[107]),"+f"(d[108]),"+f"(d[109]),"+f"(d[110]),"+f"(d[111]),
        "+f"(d[112]),"+f"(d[113]),"+f"(d[114]),"+f"(d[115]),"+f"(d[116]),"+f"(d[117]),"+f"(d[118]),"+f"(d[119]),
        "+f"(d[120]),"+f"(d[121]),"+f"(d[122]),"+f"(d[123]),"+f"(d[124]),"+f"(d[125]),"+f"(d[126]),"+f"(d[127])
      : "l"(da), "l"(db), "r"(sd));
}
__device__ __forceinline__ void wgmma_n192(float (&d)[96], uint64_t da, uint64_t db) {
  asm volatile("wgmma.mma_async.sync.aligned.m64n192k16.f32.bf16.bf16 {"
      "%0,%1,%2,%3,%4,%5,%6,%7,%8,%9,%10,%11,%12,%13,%14,%15,"
      "%16,%17,%18,%19,%20,%21,%22,%23,%24,%25,%26,%27,%28,%29,%30,%31,"
      "%32,%33,%34,%35,%36,%37,%38,%39,%40,%41,%42,%43,%44,%45,%46,%47,"
      "%48,%49,%50,%51,%52,%53,%54,%55,%56,%57,%58,%59,%60,%61,%62,%63,"
      "%64,%65,%66,%67,%68,%69,%70,%71,%72,%73,%74,%75,%76,%77,%78,%79,"
      "%80,%81,%82,%83,%84,%85,%86,%87,%88,%89,%90,%91,%92,%93,%94,%95"
      "}, %96, %97, 1, 1, 1, 0, 1;\n"
      : "+f"(d[0]),"+f"(d[1]),"+f"(d[2]),"+f"(d[3]),"+f"(d[4]),"+f"(d[5]),"+f"(d[6]),"+f"(d[7]),
        "+f"(d[8]),"+f"(d[9]),"+f"(d[10]),"+f"(d[11]),"+f"(d[12]),"+f"(d[13]),"+f"(d[14]),"+f"(d[15]),
        "+f"(d[16]),"+f"(d[17]),"+f"(d[18]),"+f"(d[19]),"+f"(d[20]),"+f"(d[21]),"+f"(d[22]),"+f"(d[23]),
        "+f"(d[24]),"+f"(d[25]),"+f"(d[26]),"+f"(d[27]),"+f"(d[28]),"+f"(d[29]),"+f"(d[30]),"+f"(d[31]),
        "+f"(d[32]),"+f"(d[33]),"+f"(d[34]),"+f"(d[35]),"+f"(d[36]),"+f"(d[37]),"+f"(d[38]),"+f"(d[39]),
        "+f"(d[40]),"+f"(d[41]),"+f"(d[42]),"+f"(d[43]),"+f"(d[44]),"+f"(d[45]),"+f"(d[46]),"+f"(d[47]),
        "+f"(d[48]),"+f"(d[49]),"+f"(d[50]),"+f"(d[51]),"+f"(d[52]),"+f"(d[53]),"+f"(d[54]),"+f"(d[55]),
        "+f"(d[56]),"+f"(d[57]),"+f"(d[58]),"+f"(d[59]),"+f"(d[60]),"+f"(d[61]),"+f"(d[62]),"+f"(d[63]),
        "+f"(d[64]),"+f"(d[65]),"+f"(d[66]),"+f"(d[67]),"+f"(d[68]),"+f"(d[69]),"+f"(d[70]),"+f"(d[71]),
        "+f"(d[72]),"+f"(d[73]),"+f"(d[74]),"+f"(d[75]),"+f"(d[76]),"+f"(d[77]),"+f"(d[78]),"+f"(d[79]),
        "+f"(d[80]),"+f"(d[81]),"+f"(d[82]),"+f"(d[83]),"+f"(d[84]),"+f"(d[85]),"+f"(d[86]),"+f"(d[87]),
        "+f"(d[88]),"+f"(d[89]),"+f"(d[90]),"+f"(d[91]),"+f"(d[92]),"+f"(d[93]),"+f"(d[94]),"+f"(d[95])
      : "l"(da), "l"(db));
}
__device__ __forceinline__ void wgmma_rs_n128(float (&d)[64], uint32_t a0, uint32_t a1, uint32_t a2, uint32_t a3, uint64_t db, int sd = 1) {
  asm volatile("{.reg .pred p; setp.ne.b32 p, %69, 0;\n"
      "wgmma.mma_async.sync.aligned.m64n128k16.f32.bf16.bf16 {"
      "%0,%1,%2,%3,%4,%5,%6,%7,%8,%9,%10,%11,%12,%13,%14,%15,"
      "%16,%17,%18,%19,%20,%21,%22,%23,%24,%25,%26,%27,%28,%29,%30,%31,"
      "%32,%33,%34,%35,%36,%37,%38,%39,%40,%41,%42,%43,%44,%45,%46,%47,"
      "%48,%49,%50,%51,%52,%53,%54,%55,%56,%57,%58,%59,%60,%61,%62,%63"
      "}, {%64,%65,%66,%67}, %68, p, 1, 1, 1;}\n"
      : "+f"(d[0]),"+f"(d[1]),"+f"(d[2]),"+f"(d[3]),"+f"(d[4]),"+f"(d[5]),"+f"(d[6]),"+f"(d[7]),
        "+f"(d[8]),"+f"(d[9]),"+f"(d[10]),"+f"(d[11]),"+f"(d[12]),"+f"(d[13]),"+f"(d[14]),"+f"(d[15]),
        "+f"(d[16]),"+f"(d[17]),"+f"(d[18]),"+f"(d[19]),"+f"(d[20]),"+f"(d[21]),"+f"(d[22]),"+f"(d[23]),
        "+f"(d[24]),"+f"(d[25]),"+f"(d[26]),"+f"(d[27]),"+f"(d[28]),"+f"(d[29]),"+f"(d[30]),"+f"(d[31]),
        "+f"(d[32]),"+f"(d[33]),"+f"(d[34]),"+f"(d[35]),"+f"(d[36]),"+f"(d[37]),"+f"(d[38]),"+f"(d[39]),
        "+f"(d[40]),"+f"(d[41]),"+f"(d[42]),"+f"(d[43]),"+f"(d[44]),"+f"(d[45]),"+f"(d[46]),"+f"(d[47]),
        "+f"(d[48]),"+f"(d[49]),"+f"(d[50]),"+f"(d[51]),"+f"(d[52]),"+f"(d[53]),"+f"(d[54]),"+f"(d[55]),
        "+f"(d[56]),"+f"(d[57]),"+f"(d[58]),"+f"(d[59]),"+f"(d[60]),"+f"(d[61]),"+f"(d[62]),"+f"(d[63])
      : "r"(a0), "r"(a1), "r"(a2), "r"(a3), "l"(db), "r"(sd));
}
__device__ __forceinline__ void wgmma_rs_n256(float (&d)[128], uint32_t a0, uint32_t a1, uint32_t a2, uint32_t a3, uint64_t db, int sd = 1) {
  asm volatile("{.reg .pred p; setp.ne.b32 p, %133, 0;\n"
      "wgmma.mma_async.sync.aligned.m64n256k16.f32.bf16.bf16 {"
      "%0,%1,%2,%3,%4,%5,%6,%7,%8,%9,%10,%11,%12,%13,%14,%15,"
      "%16,%17,%18,%19,%20,%21,%22,%23,%24,%25,%26,%27,%28,%29,%30,%31,"
      "%32,%33,%34,%35,%36,%37,%38,%39,%40,%41,%42,%43,%44,%45,%46,%47,"
      "%48,%49,%50,%51,%52,%53,%54,%55,%56,%57,%58,%59,%60,%61,%62,%63,"
      "%64,%65,%66,%67,%68,%69,%70,%71,%72,%73,%74,%75,%76,%77,%78,%79,"
      "%80,%81,%82,%83,%84,%85,%86,%87,%88,%89,%90,%91,%92,%93,%94,%95,"
      "%96,%97,%98,%99,%100,%101,%102,%103,%104,%105,%106,%107,%108,%109,%110,%111,"
      "%112,%113,%114,%115,%116,%117,%118,%119,%120,%121,%122,%123,%124,%125,%126,%127"
      "}, {%128,%129,%130,%131}, %132, p, 1, 1, 1;}\n"
      : "+f"(d[0]),"+f"(d[1]),"+f"(d[2]),"+f"(d[3]),"+f"(d[4]),"+f"(d[5]),"+f"(d[6]),"+f"(d[7]),
        "+f"(d[8]),"+f"(d[9]),"+f"(d[10]),"+f"(d[11]),"+f"(d[12]),"+f"(d[13]),"+f"(d[14]),"+f"(d[15]),
        "+f"(d[16]),"+f"(d[17]),"+f"(d[18]),"+f"(d[19]),"+f"(d[20]),"+f"(d[21]),"+f"(d[22]),"+f"(d[23]),
        "+f"(d[24]),"+f"(d[25]),"+f"(d[26]),"+f"(d[27]),"+f"(d[28]),"+f"(d[29]),"+f"(d[30]),"+f"(d[31]),
        "+f"(d[32]),"+f"(d[33]),"+f"(d[34]),"+f"(d[35]),"+f"(d[36]),"+f"(d[37]),"+f"(d[38]),"+f"(d[39]),
        "+f"(d[40]),"+f"(d[41]),"+f"(d[42]),"+f"(d[43]),"+f"(d[44]),"+f"(d[45]),"+f"(d[46]),"+f"(d[47]),
        "+f"(d[48]),"+f"(d[49]),"+f"(d[50]),"+f"(d[51]),"+f"(d[52]),"+f"(d[53]),"+f"(d[54]),"+f"(d[55]),
        "+f"(d[56]),"+f"(d[57]),"+f"(d[58]),"+f"(d[59]),"+f"(d[60]),"+f"(d[61]),"+f"(d[62]),"+f"(d[63]),
        "+f"(d[64]),"+f"(d[65]),"+f"(d[66]),"+f"(d[67]),"+f"(d[68]),"+f"(d[69]),"+f"(d[70]),"+f"(d[71]),
        "+f"(d[72]),"+f"(d[73]),"+f"(d[74]),"+f"(d[75]),"+f"(d[76]),"+f"(d[77]),"+f"(d[78]),"+f"(d[79]),
        "+f"(d[80]),"+f"(d[81]),"+f"(d[82]),"+f"(d[83]),"+f"(d[84]),"+f"(d[85]),"+f"(d[86]),"+f"(d[87]),
        "+f"(d[88]),"+f"(d[89]),"+f"(d[90]),"+f"(d[91]),"+f"(d[92]),"+f"(d[93]),"+f"(d[94]),"+f"(d[95]),
        "+f"(d[96]),"+f"(d[97]),"+f"(d[98]),"+f"(d[99]),"+f"(d[100]),"+f"(d[101]),"+f"(d[102]),"+f"(d[103]),
        "+f"(d[104]),"+f"(d[105]),"+f"(d[106]),"+f"(d[107]),"+f"(d[108]),"+f"(d[109]),"+f"(d[110]),"+f"(d[111]),
        "+f"(d[112]),"+f"(d[113]),"+f"(d[114]),"+f"(d[115]),"+f"(d[116]),"+f"(d[117]),"+f"(d[118]),"+f"(d[119]),
        "+f"(d[120]),"+f"(d[121]),"+f"(d[122]),"+f"(d[123]),"+f"(d[124]),"+f"(d[125]),"+f"(d[126]),"+f"(d[127])
      : "r"(a0), "r"(a1), "r"(a2), "r"(a3), "l"(db), "r"(sd));
}
__device__ __forceinline__ void wgmma_rs_n192(float (&d)[96], uint32_t a0, uint32_t a1, uint32_t a2, uint32_t a3, uint64_t db) {
  asm volatile("wgmma.mma_async.sync.aligned.m64n192k16.f32.bf16.bf16 {"
      "%0,%1,%2,%3,%4,%5,%6,%7,%8,%9,%10,%11,%12,%13,%14,%15,"
      "%16,%17,%18,%19,%20,%21,%22,%23,%24,%25,%26,%27,%28,%29,%30,%31,"
      "%32,%33,%34,%35,%36,%37,%38,%39,%40,%41,%42,%43,%44,%45,%46,%47,"
      "%48,%49,%50,%51,%52,%53,%54,%55,%56,%57,%58,%59,%60,%61,%62,%63,"
      "%64,%65,%66,%67,%68,%69,%70,%71,%72,%73,%74,%75,%76,%77,%78,%79,"
      "%80,%81,%82,%83,%84,%85,%86,%87,%88,%89,%90,%91,%92,%93,%94,%95"
      "}, {%96,%97,%98,%99}, %100, 1, 1, 1, 1;\n"
      : "+f"(d[0]),"+f"(d[1]),"+f"(d[2]),"+f"(d[3]),"+f"(d[4]),"+f"(d[5]),"+f"(d[6]),"+f"(d[7]),
        "+f"(d[8]),"+f"(d[9]),"+f"(d[10]),"+f"(d[11]),"+f"(d[12]),"+f"(d[13]),"+f"(d[14]),"+f"(d[15]),
        "+f"(d[16]),"+f"(d[17]),"+f"(d[18]),"+f"(d[19]),"+f"(d[20]),"+f"(d[21]),"+f"(d[22]),"+f"(d[23]),
        "+f"(d[24]),"+f"(d[25]),"+f"(d[26]),"+f"(d[27]),"+f"(d[28]),"+f"(d[29]),"+f"(d[30]),"+f"(d[31]),
        "+f"(d[32]),"+f"(d[33]),"+f"(d[34]),"+f"(d[35]),"+f"(d[36]),"+f"(d[37]),"+f"(d[38]),"+f"(d[39]),
        "+f"(d[40]),"+f"(d[41]),"+f"(d[42]),"+f"(d[43]),"+f"(d[44]),"+f"(d[45]),"+f"(d[46]),"+f"(d[47]),
        "+f"(d[48]),"+f"(d[49]),"+f"(d[50]),"+f"(d[51]),"+f"(d[52]),"+f"(d[53]),"+f"(d[54]),"+f"(d[55]),
        "+f"(d[56]),"+f"(d[57]),"+f"(d[58]),"+f"(d[59]),"+f"(d[60]),"+f"(d[61]),"+f"(d[62]),"+f"(d[63]),
        "+f"(d[64]),"+f"(d[65]),"+f"(d[66]),"+f"(d[67]),"+f"(d[68]),"+f"(d[69]),"+f"(d[70]),"+f"(d[71]),
        "+f"(d[72]),"+f"(d[73]),"+f"(d[74]),"+f"(d[75]),"+f"(d[76]),"+f"(d[77]),"+f"(d[78]),"+f"(d[79]),
        "+f"(d[80]),"+f"(d[81]),"+f"(d[82]),"+f"(d[83]),"+f"(d[84]),"+f"(d[85]),"+f"(d[86]),"+f"(d[87]),
        "+f"(d[88]),"+f"(d[89]),"+f"(d[90]),"+f"(d[91]),"+f"(d[92]),"+f"(d[93]),"+f"(d[94]),"+f"(d[95])
      : "r"(a0), "r"(a1), "r"(a2), "r"(a3), "l"(db));
}


constexpr int C_LN = 0, C_PX = 16, C_PY = 32;
constexpr int NB_CONS = 1, NB_LN = 2, NB_LAG = 4, NB_INIT = 6, NB_RDY = 7, NB_WG = 8;
constexpr int LAGX = 3;
constexpr int LAGY = 6;
constexpr int NLL = 2;
constexpr int POLL_DELAY3 = 600;
constexpr int POLL_DELAY = 1200;
constexpr int FILT_DELAY = 800;
constexpr int WARM = 4;
constexpr int ALEAD = 6;
constexpr int POLL_DELAY2 = 1000;
constexpr int REDPOS = 4;
constexpr int XTRIG = 20;
constexpr int HTRIG = 0;
constexpr int RING_SIG = 1;
constexpr int PF2_SIG = 1;
constexpr int SM_E = 0, SM_X = 16384, SM_E2 = 32768, SM_W = 49152, SM_FC = 69632, SM_T = 73728 - T1_BYTES;
constexpr unsigned long long KORDER = 0xBA9432DC876510ull;
constexpr unsigned long long BSLOT = 0x52140A98D52140ull, PSLOT = 0xB763CB763CB763ull;
constexpr unsigned long long BDEP = 0xFFEC97531ull, PDEP = 0xBA754ull;
constexpr uint32_t HI128 = desc_hi(1024, 1), HI64 = desc_hi(512, 2);

struct Bars {
  uint64_t full1[32], empty1[32], full2[16], fullA[8], empty2[8], fullP[32], emptyP[9], hbar, tbar, hint[3], sig[2], sbar, freeA[4];
  uint32_t epoch, pad;
};

template <int NK, bool STORE, int J0 = 0, int J1 = NK>
__device__ __forceinline__ void make_p(const float (&acc)[NK * 16], float r0, float r1, uint4 (&p)[NK], uint4* pbase, int ks0, uint32_t tag) {
#pragma unroll
  for (int j = J0; j < J1; j++) {
    uint32_t w[4];
#pragma unroll
    for (int i = 0; i < 4; i++) {
      const int a = 8 * j + 2 * i, b = a + NK * 8;
      w[i] = pack2(swiglu(acc[a], acc[b], (i & 1) ? r1 : r0), swiglu(acc[a + 1], acc[b + 1], (i & 1) ? r1 : r0));
    }
    asm volatile("" : "+r"(w[0]), "+r"(w[1]), "+r"(w[2]), "+r"(w[3]));
    p[j] = make_uint4(w[0], w[1], w[2], w[3]);
    if (STORE) st_tag(pbase + ((ks0 + j) >> 2) * 1024 + ((ks0 + j) & 3) * 32, p[j], tag);
  }
}
__device__ __forceinline__ void spin_until(uint32_t t) {
  while ((int)(clock32() - t) < 0) {}
}

__global__ void __cluster_dims__(2, 1, 1) __launch_bounds__(NTHREADS, 1)
fused_kernel(const __nv_bfloat16* __restrict__ x, const Tables* __restrict__ tab, Scratch* __restrict__ scr,
             __nv_bfloat16* __restrict__ out, const char* __restrict__ wg_raw, const char* __restrict__ wu_raw,
             const char* __restrict__ wd_raw,
             const __grid_constant__ CUtensorMap tmWR, const __grid_constant__ CUtensorMap tmWI,
             const __grid_constant__ CUtensorMap tmGX, const __grid_constant__ CUtensorMap tmUX,
             const __grid_constant__ CUtensorMap tmGY, const __grid_constant__ CUtensorMap tmUY,
             const __grid_constant__ CUtensorMap tmD) {
  extern __shared__ __align__(1024) char smem_raw[];
  const uint32_t sbase = s2u(smem_raw);
  const uint32_t sbar = sbase + 14 * SLOT, sstat = sbar + 1408;
  const int tid = threadIdx.x, lane = tid & 31;
  const int c = blockIdx.x, rk = c & 1, f = (c >> 1) & 7, rb = 2 * (c >> 4) + rk;
  const int rb2 = 2 * (c >> 4) + (f >> 2), kh = (f >> 1) & 1, nq = 2 * (f & 1) + rk;
#define BAR(field, i) (sbar + (uint32_t)offsetof(Bars, field) + 8u * (i))
#define TOFF(field) (sbase + SM_T + (uint32_t)offsetof(Tables, field) + lane * 16)

  if (tid >= 256) {
    asm volatile("setmaxnreg.dec.sync.aligned.u32 40;");
    const int warp = __shfl_sync(0xffffffffu, tid >> 5, 0);
    if (lane == 0) {
      if (warp == 8) {
        if (sbase & 1023) die();
#pragma unroll
        for (int i = 0; i < 21; i++) mbar_init(BAR(emptyP, i), i < 9 ? 8 : i < 14 ? 1 : i < 16 ? 8 : i == 16 ? 32 : 16);
        mbar_expect(BAR(tbar, 0), T2_BYTES + 2 * 10240);
        mbar_expect(BAR(hbar, 0), 16384);
      } else if (warp == 9) {
#pragma unroll
        for (int i = 0; i < 32; i++) mbar_init(BAR(full1, i), 1);
#pragma unroll
        for (int i = 0; i < 32; i++) mbar_expect(BAR(full1, i), i < 16 ? 16384 : 12288);
      } else if (warp == 10) {
#pragma unroll
        for (int i = 0; i < 32; i++) mbar_init(BAR(empty1, i), 16);
#pragma unroll
        for (int i = 0; i < 30; i++) mbar_init(BAR(fullP, i), 1);
#pragma unroll
        for (int i = 0; i < 30; i++) mbar_expect(BAR(fullP, i), 8192);
      } else {
#pragma unroll
        for (int i = 0; i < 32; i++) mbar_init(BAR(full2, i), i < 24 ? 1 : 8);
#pragma unroll
        for (int i = 0; i < 24; i++) mbar_expect(BAR(full2, i), 16384);
      }
      asm volatile("fence.mbarrier_init.release.cluster;" ::: "memory");
    }
    if (tid == 256) {
      const int w0 = ((c >> 3) * 257 + 32 * (c & 7) + 1) & ~7;
      if (FILT_DELAY) {
        asm volatile("prefetch.tensormap [%0];" ::"l"(&tmWR) : "memory");
        asm volatile("prefetch.tensormap [%0];" ::"l"(&tmWI) : "memory");
        spin_until(clock32() + FILT_DELAY);
      }
      tma3(sbase + SM_W, &tmWR, BAR(tbar, 0), w0, 0, 0);
      tma3(sbase + SM_W + 10240, &tmWI, BAR(tbar, 0), w0, 0, 0);
      bulk_load(sbase + SM_T + T1_BYTES, reinterpret_cast<const char*>(tab) + T1_BYTES, T2_BYTES, BAR(tbar, 0));
    }
    if (tid == 288) {
      asm volatile("prefetch.tensormap [%0];" ::"l"(rk ? &tmUX : &tmGX) : "memory");
      asm volatile("prefetch.tensormap [%0];" ::"l"(rk ? &tmUY : &tmGY) : "memory");
      asm volatile("prefetch.tensormap [%0];" ::"l"(&tmD) : "memory");
    }
    if (tid == 320) {
      const unsigned e = ld_relaxed(&scr->cnt[(C_LN + rb) * 32]) >> 3;
      asm volatile("st.shared.u32 [%0], %1;" ::"r"(BAR(epoch, 0)), "r"(e) : "memory");
    }
    __syncwarp();
    asm volatile("barrier.cluster.arrive.relaxed.aligned;" ::: "memory");
    bar_arrive(NB_RDY, 384);
    asm volatile("barrier.cluster.wait.aligned;" ::: "memory");
    bar_sync(NB_INIT, 384);
    unsigned epoch;
    asm volatile("ld.shared.u32 %0, [%1];" : "=r"(epoch) : "r"(BAR(epoch, 0)) : "memory");
    if (warp == 8) {
      if (lane == 0) {
        const int ax = (7 * f + 3 * (f & 1)) >> 1;
        const int ay = 7 * f + ((f & 1) ? 0 : 4);
        const CUtensorMap* tx = rk ? &tmUX : &tmGX;
        const CUtensorMap* ty = rk ? &tmUY : &tmGY;
        if (RING_SIG >= 0) mbar_wait(BAR(sig, RING_SIG));
        uint32_t s = 2;
#pragma unroll 1
        for (int n = 0; n < 16; n++) {
          if (n >= 6) mbar_wait(BAR(empty1, n - 6));
          tma3_mc(sbase + (8 + s) * SLOT + rk * 8192, tx, BAR(full1, n), n * 32, ax);
          if (++s == 6) s = 0;
          if (n >= 10 && n < 15) {
            const int k = n - 10;
            mbar_wait(BAR(freeA, (12 * k + 11) >> 4));
            tma3_mc(sbase + k * 12288 + rk * 6144, ty, BAR(full1, 16 + k), (k + 8) * 32, ay);
          }
        }
#pragma unroll 1
        for (int k = 5; k < 16; k++) {
          mbar_wait(BAR(empty1, k < 13 ? 10 + ((12 * (k - 5) + 11) >> 4) : 8 + k));
          tma3_mc(sbase + 8 * SLOT + ((k - 5) & 7) * 12288 + rk * 6144, ty, BAR(full1, 16 + k), ((k + 8) & 15) * 32, ay);
        }
      }
    } else if (warp == 9) {
      if (lane == 0) {
        mbar_wait(BAR(fullA, 4));
        wait_counter(&scr->cnt[(C_LN + rb2) * 32], (epoch + 1) * 8);
        asm volatile("fence.proxy.async.global;" ::: "memory");
#pragma unroll 1
        for (int i = 0; i < 14; i++) {
          const int kblk = 14 * kh + (int)((KORDER >> (4 * i)) & 15);
          mbar_wait(i < 9 ? BAR(empty1, 16 + (uint32_t)((BDEP >> (4 * i)) & 15)) : BAR(empty2, i - 9));
          tma3(sbase + (uint32_t)((BSLOT >> (4 * i)) & 15) * SLOT, &tmD, BAR(full2, i), 0, 64 * kblk, 2 * nq);
        }
        mbar_wait(BAR(empty2, 5));
        bulk_load(sbase + 13 * SLOT, &scr->LN[(rb2 * 8 + 2 * nq) * 1024 + kh * 512], 8192, BAR(hbar, 0));
        bulk_load(sbase + 13 * SLOT + 8192, &scr->LN[(rb2 * 8 + 2 * nq + 1) * 1024 + kh * 512], 8192, BAR(hbar, 0));
      }
    } else if (warp == 10) {
      bar_sync(NB_LN, 288);
      if (lane == 0) {
        red_release(&scr->cnt[(C_LN + rb) * 32]);
        wait_counter(&scr->cnt[(C_LN + rb) * 32], (epoch + 1) * 8);
        asm volatile("fence.proxy.async.global;" ::: "memory");
#pragma unroll 1
        for (int kb = NLL; kb < 8; kb++) {
          if (2 * kb >= ALEAD) mbar_wait(BAR(empty1, 2 * kb - ALEAD));
          bulk_load(sbase + kb * SLOT, &scr->LN[(rb * 8 + kb) * 1024], 16384, BAR(fullA, kb));
        }
#pragma unroll 1
        for (int s = 0; s < 14; s++) {
          const int kblk = 14 * kh + (int)((KORDER >> (4 * s)) & 15);
          if (s == 0 || s == 8 || s == 11) {
            mbar_wait(BAR(hint, s == 0 ? 0 : s == 8 ? 1 : 2), 0);
          }
          mbar_wait(s < 5 ? BAR(empty1, 16 + (uint32_t)((PDEP >> (4 * s)) & 15)) : BAR(emptyP, s - 5));
          bulk_load_mc(sbase + (uint32_t)((PSLOT >> (4 * s)) & 15) * SLOT + rk * 8192, &scr->P[(rb2 * 28 + kblk) * 1024 + rk * 512], 8192, BAR(fullP, 16 * rk + s));
        }
      }
    } else {
      if (lane == 0) {
        mbar_wait(BAR(tbar, 0));
        l2_prefetch(wg_raw + (size_t)c * 5376, 5376);
        l2_prefetch(wu_raw + (size_t)c * 5376, 5376);
        mbar_wait(BAR(sig, PF2_SIG), 0);
        l2_prefetch(wg_raw + 688128 + (size_t)c * 8960, 8960);
        l2_prefetch(wu_raw + 688128 + (size_t)c * 8960, 8960);
      }
      mbar_wait(BAR(fullA, 4), 0);
      if (lane == 0) l2_prefetch(wd_raw + (size_t)c * 14336, 14336);
      {
        const uint32_t tag = (epoch + 1) & 1;
        uint4 v0, v1, v2;
        int it = 0;
        while (true) {
          v0 = ld_b128(&scr->ST[rb * 64 + lane]);
          v1 = ld_b128(&scr->ST[rb * 64 + 32 + lane]);
          v2 = ld_b128(&scr->ST[rb2 * 64 + 32 * kh + lane]);
          if (!__any_sync(0xffffffffu, ((v0.x ^ tag) | (v1.x ^ tag) | (v2.x ^ tag)) & 1u)) break;
          if (++it > SPIN_LIMIT) { die(); break; }
        }
        sts4(sstat + lane * 16, v0.x & ~1u, v0.y, v0.z, v0.w);
        sts4(sstat + 512 + lane * 16, v1.x & ~1u, v1.y, v1.z, v1.w);
        sts4(sstat + 1024 + lane * 16, v2.x & ~1u, v2.y, v2.z, v2.w);
        mbar_arrive(BAR(sbar, 0));
      }
      if (lane == 0) {
        mbar_wait(BAR(empty1, XTRIG));
        int it = 0;
        while ((int)(ld_relaxed(&scr->cnt[(C_PX + rb2) * 32 + kh]) - (epoch + 1) * 32) < 0) {
          if (++it > SPIN_LIMIT) { die(); break; }
        }
        mbar_arrive(BAR(hint, 0));
        mbar_wait(BAR(emptyP, HTRIG));
        uint32_t done = 0;
        while (done != 3) {
          uint2 v;
          asm volatile("ld.relaxed.gpu.global.v2.u32 {%0,%1}, [%2];" : "=r"(v.x), "=r"(v.y) : "l"(&scr->cnt[(C_PY + rb2) * 32 + 4 * (rk ^ kh ^ 1) + 2 * kh]) : "memory");
          if (!(done & 1) && (int)(v.x - (epoch + 1) * 8) >= 0) { done |= 1; mbar_arrive(BAR(hint, 1)); }
          if (!(done & 2) && (int)(v.y - (epoch + 1) * 8) >= 0) { done |= 2; mbar_arrive(BAR(hint, 2)); }
          if (++it > SPIN_LIMIT) { die(); break; }
        }
      }
    }
  } else {
    const int warp = __shfl_sync(0xffffffffu, tid >> 5, 0);
    const int g = lane >> 2, t = lane & 3;
    uint4 fa[4], fb[4], tw[6];
#pragma unroll
    for (int i = 0; i < 4; i++) fa[i] = ldg_ca4(&tab->fa[i][lane][0]);
#pragma unroll
    for (int i = 0; i < 6; i++) tw[i] = ldg_ca4(&tab->tw1[i][lane][0]);
#pragma unroll
    for (int i = 0; i < 4; i++) fb[i] = ldg_ca4(&tab->fb[i][lane][0]);
#pragma unroll
    for (int i = 0; i < 4; i++) {
      const int r = i >> 1, ch = (i & 1) * 32 + lane;
      cp_async16(sbase + SM_X + (2 * warp + r) * 1024 + ((ch ^ ((ch >> 3) & 1)) * 16),
                 x + (size_t)(c + 128 * (2 * warp + r)) * 512 + ch * 8);
    }
    asm volatile("cp.async.commit_group;" ::: "memory");
    asm volatile("barrier.cluster.arrive.relaxed.aligned;" ::: "memory");
    uint32_t rbar;
    asm volatile("mapa.shared::cluster.u32 %0, %1, %2;" : "=r"(rbar) : "r"(sbar), "r"(rk ^ 1));
#define RBAR(field, i) (rbar + (uint32_t)offsetof(Bars, field) + 8u * (i))
    {
      const int ln = (tid >> 1) & 31, lg = ln >> 2, lt = ln & 3, i = 4 * (tid >> 6) + 2 * (tid & 1);
      const int kidx = lt + 8 * (i >> 3), nidx = 4 * ((i >> 1) & 3) + (lg >> 1);
      const uint32_t a0 = cfrag<2048>((c + 128 * kidx) * nidx, lg & 1), a1 = cfrag<2048>((c + 128 * (kidx + 4)) * nidx, lg & 1);
      const uint32_t b0 = cfrag<2048>(-(c + 128 * nidx) * kidx, lg & 1), b1 = cfrag<2048>(-(c + 128 * nidx) * (kidx + 4), lg & 1);
      asm volatile("st.shared.v2.u32 [%0], {%1,%2};" ::"r"(sbase + SM_FC + tid * 8), "r"(a0), "r"(a1) : "memory");
      asm volatile("st.shared.v2.u32 [%0], {%1,%2};" ::"r"(sbase + SM_FC + 2048 + tid * 8), "r"(b0), "r"(b1) : "memory");
    }
    bar_sync(NB_CONS, 256);
    uint4 fc[4];
#pragma unroll
    for (int i = 0; i < 4; i++) fc[i] = lds4(sbase + SM_FC + i * 512 + lane * 16);
    asm volatile("cp.async.wait_group 0;" ::: "memory");
    __syncwarp();
    bar_arrive(NB_INIT, 384);
    uint32_t tag, ones;
    uint4 q[4], o[4];
    {
      uint32_t v[2][8];
#pragma unroll
      for (int r = 0; r < 2; r++)
#pragma unroll
        for (int ks = 0; ks < 2; ks++) {
          const int ch = 32 * ks + 2 * (lane & 15) + (lane >> 4);
          asm volatile("ldmatrix.sync.aligned.m8n8.x4.trans.shared.b16 {%0,%1,%2,%3}, [%4];"
                       : "=r"(v[r][4 * ks]), "=r"(v[r][4 * ks + 1]), "=r"(v[r][4 * ks + 2]), "=r"(v[r][4 * ks + 3])
                       : "r"(sbase + SM_X + (2 * warp + r) * 1024 + ((ch ^ ((ch >> 3) & 1)) * 16)) : "memory");
        }
      float sq[2];
#pragma unroll
      for (int r = 0; r < 2; r++) {
        float s0 = 0.f, s1 = 0.f;
#pragma unroll
        for (int i = 0; i < 8; i++) {
          const float lo = bf_lo(v[r][i]), hi = u2f(v[r][i] & 0xffff0000u);
          s0 = fmaf(lo, lo, s0);
          s1 = fmaf(hi, hi, s1);
        }
        sq[r] = s0 + s1;
      }
      {
        float w = ((lane & 1) ? sq[1] : sq[0]) + __shfl_xor_sync(0xffffffffu, (lane & 1) ? sq[0] : sq[1], 1);
        w += __shfl_xor_sync(0xffffffffu, w, 2);
        w = sum_groups(w);
        const float o2 = __shfl_xor_sync(0xffffffffu, w, 1);
        sq[0] = (lane & 1) ? o2 : w;
        sq[1] = (lane & 1) ? w : o2;
      }
#pragma unroll
      for (int r = 0; r < 2; r++) {
        float dd[2][4], ee[2][4];
#pragma unroll
        for (int nt = 0; nt < 2; nt++) {
          mma_az(dd[nt], fa[0], v[r][2 * nt], v[r][2 * nt + 1]);
          mma_a(dd[nt], fa[1], v[r][4 + 2 * nt], v[r][5 + 2 * nt]);
          mma_az(ee[nt], fa[2], v[r][2 * nt], v[r][2 * nt + 1]);
          mma_a(ee[nt], fa[3], v[r][4 + 2 * nt], v[r][5 + 2 * nt]);
        }
        float mean = (dd[0][0] + dd[0][1]) + (dd[1][0] + dd[1][1]);
        mean += __shfl_xor_sync(0xffffffffu, mean, 1);
        mean += __shfl_xor_sync(0xffffffffu, mean, 2);
        mean = __shfl_sync(0xffffffffu, mean, 0) * (1.f / 512.f);
        const float rs = rsqrtf(fmaxf(fmaf(-mean, mean, sq[r] * (1.f / 512.f)), 0.f) + 1e-5f);
        float acc[4][4];
#pragma unroll
        for (int nt = 0; nt < 2; nt++) {
          const float (&d)[4] = dd[nt];
          const float (&e)[4] = ee[nt];
          const uint4 &ka = tw[2 * nt], &kb = tw[2 * nt + 1], &kc = tw[4 + nt];
          const uint32_t a0 = pack2(d[0] * u2f(ka.x) + d[2] * u2f(ka.y), d[1] * u2f(kb.x) + d[3] * u2f(kb.y));
          const uint32_t a2 = pack2(d[0] * u2f(ka.z) + d[2] * u2f(ka.w), d[1] * u2f(kb.z) + d[3] * u2f(kb.w));
          const uint32_t a1 = pack2(e[0] * u2f(kc.x) + e[2] * u2f(kc.y), e[1] * u2f(kc.z) + e[3] * u2f(kc.w));
          const uint32_t a3 = pack2(e[2] * u2f(kc.x) - e[0] * u2f(kc.y), e[3] * u2f(kc.z) - e[1] * u2f(kc.w));
          const uint32_t dc = pack2(fmaf(mean, -32.f, d[0]), fmaf(mean, -32.f, d[1]));
          const uint32_t h0 = g == 0 ? dc : a0, h2 = g == 0 ? 0u : a2;
          if (nt == 0) {
            mma16816_z(acc[0], a0, a1, a2, a3, fb[2 * nt].x, fb[2 * nt].y);
            mma16816_z(acc[1], a0, a1, a2, a3, fb[2 * nt].z, fb[2 * nt].w);
            mma16816_z(acc[2], h0, a1, h2, a3, fb[2 * nt + 1].x, fb[2 * nt + 1].y);
            mma16816_z(acc[3], h0, a1, h2, a3, fb[2 * nt + 1].z, fb[2 * nt + 1].w);
          } else {
            mma16816(acc[0], a0, a1, a2, a3, fb[2 * nt].x, fb[2 * nt].y);
            mma16816(acc[1], a0, a1, a2, a3, fb[2 * nt].z, fb[2 * nt].w);
            mma16816(acc[2], h0, a1, h2, a3, fb[2 * nt + 1].x, fb[2 * nt + 1].y);
            mma16816(acc[3], h0, a1, h2, a3, fb[2 * nt + 1].z, fb[2 * nt + 1].w);
          }
        }
#pragma unroll
        for (int h = 0; h < 2; h++) {
          const int j = 2 * warp + r, m = 2 * t + h;
          sts4(sbase + SM_E + ((j * 8 + m) * 8 + (g ^ (2 * t) ^ (2 * (j & 3)))) * 16,
               pack2(acc[h][0] * rs, acc[h][1] * rs), pack2(acc[h][2] * rs, acc[h][3] * rs),
               pack2(acc[2 + h][0] * rs, acc[2 + h][1] * rs), pack2(acc[2 + h][2] * rs, acc[2 + h][3] * rs));
        }
      }
      bar_sync(NB_RDY, 384);
      const uint32_t ea = sbase + SM_E + ((t * 8 + warp) * 8 + (g ^ (warp & 6) ^ (2 * t))) * 16;
      lds_frag(q[0], q[1], ea, ea + 4096);
      lds_frag(q[2], q[3], ea + 8192, ea + 12288);
      asm volatile("ld.shared.u32 %0, [%1];" : "=r"(tag) : "r"(BAR(epoch, 0)) : "memory");
      ones = ~(tag >> 31);
      tag = (tag + 1) & 1;
      cdft16(q, fc, o);
#pragma unroll
      for (int vv = 0; vv < 4; vv++) {
        o[vv].y &= ~1u;
        o[vv].z = (o[vv].z & ~1u) | (tag ^ 1);
        st_tag(&scr->Z1[(((4 * vv + t) * 8 + warp) * 128 + c) * 8 + g], o[vv], tag);
      }
    }
    asm volatile("setmaxnreg.inc.sync.aligned.u32 232;");
    {
      uint4* const zp = &scr->Z1[(c * 128 + 8 * t + warp) * 8 + g];
      const uint32_t tst = clock32();
      mbar_wait(BAR(tbar, 0), 0);
      uint4 f2[4], g2[4];
#pragma unroll
      for (int i = 0; i < 4; i++) {
        f2[i] = lds4(TOFF(f2) + warp * 2048 + i * 512);
        g2[i] = lds4(TOFF(g2) + warp * 2048 + i * 512);
      }
      const uint4 f8 = lds4(TOFF(f8)), g8 = lds4(TOFF(g8));
      asm volatile("barrier.cluster.wait.aligned;" ::: "memory");
      spin_until(tst + POLL_DELAY);
      ld_tag4_issue<256>(q, zp);
      float wfr[16], wfi[16];
      {
        const float nyq = ((c & 7) == 7 && g == 0) ? 0.5f : 1.f;
        uint32_t wa = sbase + SM_W + (16 * warp + t) * 80 + ((2 * (c >> 3) + 2) & 15) - 2;
        asm volatile("" : "+r"(wa));
        const uint32_t wb[3] = {wa + 2 * (g == 0 ? 16 : g), wa + 2 * g, wa - 2 * g};
#pragma unroll
        for (int i = 0; i < 16; i++) {
          const int ci = i >> 3, dd = (i >> 2) & 1, e = i & 3;
          const uint32_t a = wb[e < 2 ? e : 2] + (ci * 8 + 4 * dd) * 80 + (e == 0 ? 0 : e == 1 ? 16 : e == 2 ? 64 : 48);
          wfr[i] = bf_lo(lds_u16(a)) * (e == 2 ? nyq : 1.f);
          wfi[i] = bf_lo(lds_u16(a + 10240)) * (e == 2 ? nyq : 1.f);
        }
      }
      ld_tag4_finish<256>(q, zp, tag);
      if (lane == 0) mbar_arrive(BAR(sig, 0));
#pragma unroll
      for (int i = 0; i < 4; i++) q[i].z &= ~1u;
      reg_frag(q, ones);
      cdft16(q, f2, o);
      const uint32_t e2 = sbase + SM_E2;
#pragma unroll
      for (int vv = 0; vv < 4; vv++)
        sts4(e2 + ((warp * 16 + 4 * vv + t) * 8 + (g ^ (2 * t) ^ (2 * (warp & 3)))) * 16, o[vv].x, o[vv].y, o[vv].z, o[vv].w);
      bar_sync(NB_CONS, 256);
      uint32_t ad[2], res[2][2][4];
#pragma unroll
      for (int ci = 0; ci < 2; ci++) {
        const int cc = 2 * warp + ci;
        ad[ci] = e2 + ((t * 16 + cc) * 8 + (g ^ (2 * (cc & 3)) ^ (2 * t))) * 16;
        lds_frag(q[2 * ci], q[2 * ci + 1], ad[ci], ad[ci] + 8192);
      }
#pragma unroll
      for (int ci = 0; ci < 2; ci++)
#pragma unroll
        for (int p = 0; p < 2; p++) {
          uint32_t y[2][2];
#pragma unroll
          for (int vv = 0; vv < 2; vv++) {
            float d[4];
            mma_az(d, q[2 * ci + p], word(f8, 2 * vv), word(f8, 2 * vv + 1));
#pragma unroll
            for (int rr = 0; rr < 2; rr++) {
              const float fr = wfr[ci * 8 + vv * 4 + 2 * p + rr], fi = wfi[ci * 8 + vv * 4 + 2 * p + rr];
              y[vv][rr] = pack2(d[2 * rr] * fr - d[2 * rr + 1] * fi, d[2 * rr] * fi + d[2 * rr + 1] * fr);
            }
          }
#pragma unroll
          for (int vv = 0; vv < 2; vv++) {
            float d[4];
            mma16816_z(d, y[0][0], y[0][1], y[1][0], y[1][1], word(g8, 2 * vv), word(g8, 2 * vv + 1));
            res[ci][vv][2 * p] = pack2(d[0], d[1]);
            res[ci][vv][2 * p + 1] = pack2(d[2], d[3]);
          }
        }
#pragma unroll
      for (int i = 0; i < 4; i++)
        sts4(ad[i >> 1] + (i & 1) * 8192, res[i >> 1][i & 1][0], res[i >> 1][i & 1][1], res[i >> 1][i & 1][2], res[i >> 1][i & 1][3]);
      bar_sync(NB_CONS, 256);
      const uint32_t eb = e2 + ((warp * 16 + t) * 8 + (g ^ (2 * t) ^ (2 * (warp & 3)))) * 16;
      lds_frag(q[0], q[1], eb, eb + 512);
      lds_frag(q[2], q[3], eb + 1024, eb + 1536);
      cdft16(q, g2, o);
#pragma unroll
      for (int vv = 0; vv < 4; vv++) {
        o[vv].y &= ~1u;
        o[vv].z = (o[vv].z & ~1u) | tag;
        st_tag(zp + vv * 256, o[vv], tag);
      }
    }
    {
      const uint4* const zp = &scr->Z1[((t * 8 + warp) * 128 + c) * 8 + g];
      const uint32_t tst = clock32();
      uint4 gb[4], ga[4], gc[4], tw[4];
      uint2 xr[2][4];
      uint2* lnp[2];
#pragma unroll
      for (int r = 0; r < 2; r++) {
        const int row = 16 * f + 2 * warp + r;
        lnp[r] = reinterpret_cast<uint2*>(&scr->LN[(rb * 8 + (g >> 2)) * 1024 + row * 8 + ((2 * (g & 3) + (t >> 1)) ^ (row & 7))]) + (t & 1);
        asm volatile("" : "+l"(lnp[r]));
      }
#pragma unroll
      for (int i = 0; i < 4; i++) {
        gc[i] = lds4(sbase + SM_FC + 2048 + i * 512 + lane * 16);
        gb[i] = lds4(TOFF(gb) + i * 512);
        ga[i] = lds4(TOFF(ga) + i * 512);
        tw[i] = lds4(TOFF(tw3) + i * 512);
        const int ch = 2 * (g + 8 * i) + (t >> 1);
#pragma unroll
        for (int r = 0; r < 2; r++) xr[r][i] = lds2(sbase + SM_X + (2 * warp + r) * 1024 + ((ch ^ ((ch >> 3) & 1)) * 16) + (t & 1) * 8);
      }
      spin_until(tst + POLL_DELAY2);
      ld_tag4_issue<32768>(q, zp);
      ld_tag4_finish<32768, true>(q, zp, tag);
      if (lane == 0) mbar_arrive(BAR(sig, 1));
      reg_frag(q, ones);
      cdft16(q, gc, o);
#pragma unroll
      for (int vv = 0; vv < 4; vv++)
        sts4(sbase + SM_E + (((4 * vv + t) * 8 + warp) * 8 + (g ^ (warp & 6) ^ (2 * t))) * 16, o[vv].x, o[vv].y, o[vv].z, o[vv].w);
      bar_sync(NB_CONS, 256);
      uint32_t hv[2][8];
      const float mk = t == 0 ? 0.f : 1.f;
#pragma unroll
      for (int r = 0; r < 2; r++) {
        const int j = 2 * warp + r;
        uint4 u[2];
#pragma unroll
        for (int h = 0; h < 2; h++) u[h] = lds4(sbase + SM_E + ((j * 8 + 2 * t + h) * 8 + (g ^ (2 * t) ^ (2 * (j & 3)))) * 16);
        const uint32_t bp[4][2] = {{u[0].x, u[1].x & ones}, {u[0].y & ones, u[1].y}, {u[0].z, u[1].z & ones}, {u[0].w & ones, u[1].w}};
        float y[2][2][4];
#pragma unroll
        for (int i = 0; i < 2; i++) {
          float lo[4], hi[4], e[4];
          mma_az(lo, gb[2 * i], bp[0][0], bp[0][1]);
          mma_az(hi, gb[2 * i + 1], bp[2][0], bp[2][1]);
          mma_az(e, gb[2 * i], bp[1][0], bp[1][1]);
          mma_a(e, gb[2 * i + 1], bp[3][0], bp[3][1]);
          const uint4 &ka = tw[2 * i], &kb = tw[2 * i + 1];
          const float tr0 = fmaf(hi[0], mk, lo[0]), ti0 = fmaf(hi[2], mk, lo[2]);
          const float tr1 = lo[1] + hi[1], ti1 = lo[3] + hi[3];
          const float vr0 = tr0 * u2f(ka.x) - ti0 * u2f(ka.y), vi0 = tr0 * u2f(ka.y) + ti0 * u2f(ka.x);
          const float vr1 = tr1 * u2f(ka.z) - ti1 * u2f(ka.w), vi1 = tr1 * u2f(ka.w) + ti1 * u2f(ka.z);
          const uint32_t b0 = pack2(t == 0 ? hi[0] : vr0, vr1), b1 = pack2(t == 0 ? vr0 : vi0, vi1);
          const uint32_t b2 = pack2(e[0] * u2f(kb.x) - e[2] * u2f(kb.y), e[1] * u2f(kb.z) - e[3] * u2f(kb.w));
          const uint32_t b3 = pack2(e[0] * u2f(kb.y) + e[2] * u2f(kb.x), e[1] * u2f(kb.w) + e[3] * u2f(kb.z));
#pragma unroll
          for (int mt = 0; mt < 2; mt++) {
            mma_az(y[mt][i], ga[2 * mt], b0, b1);
            mma_a(y[mt][i], ga[2 * mt + 1], b2, b3);
          }
        }
#pragma unroll
        for (int i = 0; i < 4; i++) {
          hv[r][2 * i] = hadd2_bf16(xr[r][i].x, pack2(y[i >> 1][0][2 * (i & 1)], y[i >> 1][0][2 * (i & 1) + 1]));
          hv[r][2 * i + 1] = hadd2_bf16(xr[r][i].y, pack2(y[i >> 1][1][2 * (i & 1)], y[i >> 1][1][2 * (i & 1) + 1]));
        }
      }
      float mean[2];
      uint32_t mb[2];
#pragma unroll
      for (int r = 0; r < 2; r++) {
        mean[r] = sum_groups(quad_sum(hv[r])) * (1.f / 512.f);
        mb[r] = pack2(mean[r], mean[r]);
      }
#pragma unroll
      for (int i = 0; i < 4; i++)
#pragma unroll
        for (int r = 0; r < 2; r++) {
          hv[r][2 * i] = hsub2_bf16(hv[r][2 * i], mb[r]);
          hv[r][2 * i + 1] = hsub2_bf16(hv[r][2 * i + 1], mb[r]);
          st_tag8(lnp[r] + i * 4096, hv[r][2 * i], hv[r][2 * i + 1], i == 0 ? tag : (hv[r][2 * i] & 1u));
        }
      bar_arrive(NB_LN, 288);
      const uint32_t ones2 = ~(lds2(BAR(epoch, 0)).x >> 31);
      float rstd[2];
#pragma unroll
      for (int r = 0; r < 2; r++) {
        hv[r][0] &= ones2;
        rstd[r] = row_rstd(hv[r], mean[r] - bf_lo(mb[r]));
      }
      if (lane == 0)
        st_tag(&scr->ST[rb * 64 + 8 * f + warp], make_uint4(mb[0] << 16, __float_as_uint(rstd[0]), mb[1] << 16, __float_as_uint(rstd[1])), tag);
    }
    const int wgi = warp >> 2, wq = warp & 3;
    const int wr = wgi ^ (f >> 2) ^ 1, rt = 4 * wr + wq;
    uint4* const pbase = &scr->P[rb * 28 * 1024 + rt * 128 + lane];
    const uint32_t a_lo0 = desc_lo(sbase + wr * 8192, 16);
    const uint32_t ebar = lane == 0 ? BAR(empty1, 0) : RBAR(empty1, 0);
    float r0, r1;
    uint4 px[8], py[6];
    const int rh = wgi ^ kh ^ 1;
    const uint32_t fpb = BAR(fullP, 16 * rh);
    const uint4* const psrc = &scr->P[(rb2 * 28 + 14 * kh) * 1024 + (4 * rh + wq) * 128 + lane];
    const uint32_t pa0 = sbase + (4 * rh + wq) * 2048;
    uint4 pf[3][4], ha[4][4];
    uint32_t rdy = 0, got0;
    {
      float acc[128];
#pragma unroll
      for (int i = 0; i < 128; i++) acc[i] = 0.f;
      const uint32_t b_lo0 = desc_lo(sbase + 8 * SLOT, 4096);
      const uint32_t t3 = clock32();
      if (WARM) {
        wg_fence();
#pragma unroll
        for (int i = 0; i < WARM; i++) wgmma_n256(acc, desc64(a_lo0 + 6 * 1024, HI128), desc64(b_lo0, HI128));
        wg_commit();
      }
      const uint4* const ap = &scr->LN[rb * 8 * 1024 + wr * 512 + (tid & 127)];
      uint4 av[NLL][4];
      spin_until(t3 + POLL_DELAY3);
#pragma unroll
      for (int kb = 0; kb < NLL; kb++) ld_tag4_issue<128>(av[kb], ap + kb * 1024);
      bar_sync(NB_CONS, 256);
      const uint32_t lma = sbase + (16 * rt + (lane & 15)) * 128;
      auto load_a = [&](int kb) {
#pragma unroll
        for (int ks = 0; ks < 4; ks++)
          asm volatile("ldmatrix.sync.aligned.m8n8.x4.shared.b16 {%0,%1,%2,%3}, [%4];"
                       : "=r"(ha[kb][ks].x), "=r"(ha[kb][ks].y), "=r"(ha[kb][ks].z), "=r"(ha[kb][ks].w)
                       : "r"(lma + kb * SLOT + (((2 * ks + (lane >> 4)) ^ (lane & 7)) * 16)) : "memory");
      };
      auto stash_a = [&](int kb) {
        ld_tag4_finish<128, true>(av[kb], ap + kb * 1024, tag);
#pragma unroll
        for (int i = 0; i < 4; i++)
          sts4(sbase + kb * SLOT + wr * 8192 + ((tid & 127) + 128 * i) * 16, av[kb][i].x, av[kb][i].y, av[kb][i].z, av[kb][i].w);
        bar_sync(NB_WG + wgi, 128);
      };
      stash_a(0);
      load_a(0);
#pragma unroll
      for (int n = 0; n < 8; n++) {
        const int kb = n >> 1, hh = n & 1;
        if (hh == 1 && kb < 3) {
          if (kb + 1 < NLL) stash_a(kb + 1); else mbar_wait(BAR(fullA, kb + 1));
        }
        mbar_wait(BAR(full1, n));
        const uint32_t bl = b_lo0 + ((n + 2) % 6) * 1024;
        wg_fence();
        if (hh == 1 && kb < 3) load_a(kb + 1);
        const uint4 &a0 = ha[kb][2 * hh], &a1 = ha[kb][2 * hh + 1];
        wgmma_rs_n256(acc, a0.x, a0.y, a0.z, a0.w, desc64(bl, HI128), n != 0 ? 1 : ~ones);
        wgmma_rs_n256(acc, a1.x, a1.y, a1.z, a1.w, desc64(bl + 128, HI128));
        wg_commit();
        if (hh == 1 && lane < 2) mbar_arrive_remote(ebar + (uint32_t)(offsetof(Bars, freeA) - offsetof(Bars, empty1)) + 8 * kb);
        wg_wait<1>();
        if (n != 0 && lane < 2) mbar_arrive_remote(ebar + 8 * (n - 1));
      }
      uint32_t slot = 4;
#pragma unroll 1
      for (int kb = 4; kb < 8; kb++) {
        mbar_wait(BAR(fullA, kb));
#pragma unroll
        for (int hh = 0; hh < 2; hh++) {
          if (LAGX && hh == ((16 - LAGX) & 1) && kb == ((16 - LAGX) >> 1) && wgi == 1) bar_sync(NB_LAG, 256);
          mbar_wait(BAR(full1, 2 * kb + hh));
          const uint32_t al = a_lo0 + kb * 1024 + hh * 4, bl = b_lo0 + slot * 1024;
          wg_fence();
          wgmma_n256(acc, desc64(al, HI128), desc64(bl, HI128));
          wgmma_n256(acc, desc64(al + 2, HI128), desc64(bl + 128, HI128));
          wg_commit();
          if (LAGX && hh == 1 && kb == 7 && wgi == 0) bar_arrive(NB_LAG, 256);
          wg_wait<1>();
          if (lane < 2) mbar_arrive_remote(ebar + 8 * (2 * kb + hh - 1));
          if (++slot == 6) slot = 0;
        }
      }
      mbar_wait(BAR(sbar, 0), 0);
      r0 = __uint_as_float(lds2(sstat + (16 * rt + g) * 8).y);
      r1 = __uint_as_float(lds2(sstat + (16 * rt + g + 8) * 8).y);
      wg_wait<0>();
      if (lane < 2) mbar_arrive_remote(ebar + 8 * 15);
      make_p<8, false>(acc, r0, r1, px, pbase, 0, tag);
    }
    {
      float acc[96];
#pragma unroll
      for (int i = 0; i < 96; i++) acc[i] = 0.f;
      const uint32_t b_lo0 = desc_lo(sbase, 2048);
      uint4* const pdst = pbase + ((7 * f + 3 * (f & 1)) >> 1) * 1024;
      auto stage_y = [&](int k) {
        if (LAGY && k == 16 - LAGY && wgi == 1) bar_sync(NB_LAG, 256);
        mbar_wait(BAR(full1, 16 + k));
        const uint32_t al = a_lo0 + (4 + (k >> 1)) * 1024 + (k & 1) * 4, bl = b_lo0 + (k < 5 ? k * 768 : 8192 + (k - 5) * 768);
        wg_fence();
        wgmma_n192(acc, desc64(al, HI128), desc64(bl, HI64));
        wgmma_n192(acc, desc64(al + 2, HI128), desc64(bl + 64, HI64));
        wg_commit();
      };
#pragma unroll
      for (int k = 0; k < 4; k++) {
        stage_y(k);
        st_tag(pdst + (k >> 1) * 1024 + (k & 1) * 64, px[2 * k], tag);
        st_tag(pdst + (k >> 1) * 1024 + (k & 1) * 64 + 32, px[2 * k + 1], tag);
        if (k == 3 && lane == 0) red_relaxed(&scr->cnt[(C_PX + rb) * 32 + (f >> 2)]);
        wg_wait<1>();
        if (k != 0 && lane < 2) mbar_arrive_remote(ebar + 8 * (15 + k));
      }
#pragma unroll 1
      for (int k = 4; k < 8; k++) {
        stage_y(k);
        wg_wait<1>();
        if (lane < 2) mbar_arrive_remote(ebar + 8 * (15 + k));
      }
      rdy = 0;
#pragma unroll
      for (int k = 8; k < 16; k++) {
        if (LAGY && k == 16 - LAGY && wgi == 1) bar_sync(NB_LAG, 256);
        if (!rdy) mbar_wait(BAR(full1, 16 + k));
        const uint32_t bl = b_lo0 + 8192 + ((k - 5) & 7) * 768;
        const uint4 &a0 = ha[(k - 8) >> 1][2 * (k & 1)], &a1 = ha[(k - 8) >> 1][2 * (k & 1) + 1];
        wg_fence();
        if (k < 15) rdy = mbar_test(BAR(full1, 17 + k));
        wgmma_rs_n192(acc, a0.x, a0.y, a0.z, a0.w, desc64(bl, HI64));
        wgmma_rs_n192(acc, a1.x, a1.y, a1.z, a1.w, desc64(bl + 64, HI64));
        wg_commit();
        if (LAGY && k == 15 && wgi == 0) bar_arrive(NB_LAG, 256);
        wg_wait<1>();
        if (lane < 2) mbar_arrive_remote(ebar + 8 * (15 + k));
      }
      got0 = __all_sync(0xffffffffu, mbar_test((fpb + 8 * (0))));
      if (got0) {
#pragma unroll
        for (int kk = 0; kk < 4; kk++) pf[0][kk] = lds4(pa0 + 3 * SLOT + kk * 512 + lane * 16);
      }
      wg_wait<0>();
      if (lane < 2) mbar_arrive_remote(ebar + 8 * 31);
      const int ks0 = 14 * f + ((f & 1) ? 0 : 8);
      auto reread = [&]() {
        asm volatile("ld.volatile.shared.f32 %0, [%2+4]; ld.volatile.shared.f32 %1, [%2+68];" : "=f"(r0), "=f"(r1) : "r"(sstat + (16 * rt + g) * 8) : "memory");
      };
      make_p<6, true, 0, 2>(acc, r0, r1, py, pbase, ks0, tag);
      if (REDPOS == 2 && lane == 0) red_relaxed(&scr->cnt[(C_PY + rb) * 32 + 4 * wgi + (f >> 1)]);
      reread();
      make_p<6, true, 2, 4>(acc, r0, r1, py, pbase, ks0, tag);
      if (REDPOS == 4 && lane == 0) red_relaxed(&scr->cnt[(C_PY + rb) * 32 + 4 * wgi + (f >> 1)]);
      reread();
      rdy = mbar_test(BAR(full2, 0)) & mbar_test((fpb + 8 * (1)));
      make_p<6, true, 4, 6>(acc, r0, r1, py, pbase, ks0, tag);
      if (REDPOS == 6 && lane == 0) red_relaxed(&scr->cnt[(C_PY + rb) * 32 + 4 * wgi + (f >> 1)]);
    }
    {
      float acc[64];
#pragma unroll
      for (int i = 0; i < 64; i++) acc[i] = 0.f;
      const uint32_t b2_lo0 = desc_lo(sbase, 8192);
      const uint32_t pbar = rh == rk ? BAR(emptyP, 0) : RBAR(emptyP, 0);
      if (!got0) {
        mbar_wait((fpb + 8 * (0)));
#pragma unroll
        for (int kk = 0; kk < 4; kk++) pf[0][kk] = lds4(pa0 + 3 * SLOT + kk * 512 + lane * 16);
      }
      auto check2 = [&](int s, uint4 (&a)[4]) {
        ld_tag4_finish<32>(a, psrc + (int)((KORDER >> (4 * s)) & 15) * 1024, tag);
        if (s < 9 && lane == 0) mbar_arrive_remote(pbar + 8 * s);
      };
      auto stage2 = [&](int s, uint4 (&a)[4], uint4 (&nx)[4], bool last) {
        if (!rdy) {
          if (!last) mbar_wait(fpb + 8 * (s + 1));
          mbar_wait(BAR(full2, s));
        }
        const uint32_t bl = b2_lo0 + (uint32_t)((BSLOT >> (4 * s)) & 15) * 1024;
        const uint32_t pn = pa0 + (uint32_t)((PSLOT >> (4 * s + 4)) & 15) * SLOT + lane * 16;
        wg_fence();
        if (!last) {
#pragma unroll
          for (int kk = 0; kk < 4; kk++) nx[kk] = lds4(pn + kk * 512);
          rdy = mbar_test(BAR(full2, s + 1)) & mbar_test(fpb + 8 * (s < 12 ? s + 2 : 13));
        }
#pragma unroll
        for (int kk = 0; kk < 4; kk++) wgmma_rs_n128(acc, a[kk].x, a[kk].y, a[kk].z, a[kk].w, desc64(bl + kk * 128, HI128));
        wg_commit();
        if (!last) {
          check2(s + 1, nx);
          wg_wait<1>();
          if (s >= 1 && s <= 6 && lane == 0) mbar_arrive(BAR(empty2, s - 1));
        }
      };
      check2(0, pf[0]);
#pragma unroll 1
      for (int s0 = 0; s0 < 12; s0 += 3) {
        if (s0 == 9 && wgi == 1) {
          int ln = lane;
          asm volatile("" : "+r"(ln));
          const float m0 = __uint_as_float(lds2(sstat + 1024 + (16 * wq + (ln >> 2)) * 8).x);
          const float m1 = __uint_as_float(lds2(sstat + 1024 + (16 * wq + (ln >> 2) + 8) * 8).x);
          const uint32_t hb = sbase + 13 * SLOT + (16 * wq + (ln & 15)) * 128;
          wg_wait<0>();
          mbar_wait(BAR(hbar, 0));
#pragma unroll
          for (int i = 0; i < 8; i++) {
            uint32_t h[4];
            asm volatile("ldmatrix.sync.aligned.m8n8.x4.shared.b16 {%0,%1,%2,%3}, [%4];"
                         : "=r"(h[0]), "=r"(h[1]), "=r"(h[2]), "=r"(h[3])
                         : "r"(hb + (i >> 2) * 8192 + (((2 * (i & 3) + (ln >> 4)) ^ (ln & 7)) * 16)) : "memory");
            const uint32_t mk = ((ln & 1) == 0 && nq == 0) ? ~1u : ~0u;
#pragma unroll
            for (int e = 0; e < 4; e++) {
              acc[8 * i + 2 * e] += bf_lo(h[e] & mk) + ((e & 1) ? m1 : m0);
              acc[8 * i + 2 * e + 1] += __uint_as_float(h[e] & 0xffff0000u) + ((e & 1) ? m1 : m0);
            }
          }
          bar_sync(NB_LAG, 256);
        }
        stage2(s0, pf[0], pf[1], false);
        stage2(s0 + 1, pf[1], pf[2], false);
        stage2(s0 + 2, pf[2], pf[0], false);
      }
      stage2(12, pf[0], pf[1], false);
      stage2(13, pf[1], pf[2], true);
      if (wgi == 0) {
        bar_arrive(NB_LAG, 256);
        uint4* const dst = &scr->Z1[(tid >> 3) * 1024 + (c ^ 4) * 8 + (tid & 7)];
        wg_wait<0>();
#pragma unroll
        for (int i = 0; i < 8; i++)
          st_tag(dst + i * 16384, make_uint4(pack2(acc[8 * i], acc[8 * i + 1]), pack2(acc[8 * i + 2], acc[8 * i + 3]) | 1u,
                                           pack2(acc[8 * i + 4], acc[8 * i + 5]), pack2(acc[8 * i + 6], acc[8 * i + 7])), tag);
      } else {
        uint4 pv[2][4];
        const uint4* const xsrc = &scr->Z1[((tid & 127) >> 3) * 1024 + c * 8 + (tid & 7)];
        ld_tag4_issue<16384>(pv[0], xsrc);
        ld_tag4_issue<16384>(pv[1], xsrc + 65536);
        wg_wait<0>();
        uint32_t w[32];
#pragma unroll
        for (int i = 0; i < 32; i++) w[i] = pack2(acc[2 * i], acc[2 * i + 1]);
        int it = 0;
#pragma unroll 1
        while (!__all_sync(0xffffffffu, pv[0][0].y & pv[0][1].y & pv[0][2].y & pv[0][3].y & pv[1][0].y & pv[1][1].y & pv[1][2].y & pv[1][3].y & 1u)) {
          ld_tag4_issue<16384>(pv[0], xsrc);
          ld_tag4_issue<16384>(pv[1], xsrc + 65536);
          if (++it > SPIN_LIMIT) { die(); break; }
        }
#pragma unroll
        for (int i = 0; i < 8; i++) {
          const uint4& p = pv[i >> 2][i & 3];
          asm volatile("stmatrix.sync.aligned.m8n8.x4.shared.b16 [%0], {%1,%2,%3,%4};"
                       ::"r"(pa0 + (11 + ((lane >> 3) & 1)) * SLOT + (lane & 7) * 256 + (((2 * i + (lane >> 4)) ^ (lane & 7)) * 16)),
                         "r"(hadd2_bf16(w[4 * i], p.x & ~1u)), "r"(hadd2_bf16(w[4 * i + 1], p.y & ~1u)), "r"(hadd2_bf16(w[4 * i + 2], p.z)),
                         "r"(hadd2_bf16(w[4 * i + 3], p.w)) : "memory");
        }
        __syncwarp();
        uint4* const dst = reinterpret_cast<uint4*>(out) + (16 * (c >> 4) + 2 * (4 * rh + wq) + (rb2 & 1) + 128 * (lane >> 4)) * 64 + nq * 16 + (lane & 15);
#pragma unroll
        for (int i = 0; i < 8; i++) {
          const int r = 2 * (i & 3) + (lane >> 4);
          dst[i * 256 * 64] = lds4(pa0 + (11 + (i >> 2)) * SLOT + r * 256 + (((lane & 15) ^ r) * 16));
        }
      }
    }
  }
#undef BAR
#undef TOFF
#undef RBAR
}

typedef CUresult (*EncodeFn)(CUtensorMap*, CUtensorMapDataType, cuuint32_t, void*, const cuuint64_t*, const cuuint64_t*,
                             const cuuint32_t*, const cuuint32_t*, CUtensorMapInterleave, CUtensorMapSwizzle,
                             CUtensorMapL2promotion, CUtensorMapFloatOOBfill);

}

extern "C" void kernel_launch(void* const* d_in, const int* in_sizes, int n_in, void* d_out, int out_size) {
  (void)in_sizes; (void)n_in; (void)out_size;
  static EncodeFn encode = nullptr;
  static void *tab = nullptr, *scr = nullptr;
  if (!encode) {
    void* fn = nullptr;
    cudaDriverEntryPointQueryResult qr;
    cudaGetDriverEntryPoint("cuTensorMapEncodeTiled", &fn, cudaEnableDefault, &qr);
    encode = (EncodeFn)fn;
    cudaGetSymbolAddress(&tab, g_tab);
    cudaGetSymbolAddress(&scr, g_scr);
    cudaFuncSetAttribute(fused_kernel, cudaFuncAttributeMaxDynamicSharedMemorySize, SMEM_BYTES);
  }
  CUtensorMap tmGX, tmUX, tmGY, tmUY, tmD, tmWR, tmWI;
  const cuuint32_t es[5] = {1, 1, 1, 1, 1};
  auto enc = [&](CUtensorMap* m, void* p, int rank, const cuuint64_t* gd, const cuuint64_t* gs, const cuuint32_t* bd,
                 CUtensorMapSwizzle sw, CUtensorMapL2promotion pr) {
    encode(m, CU_TENSOR_MAP_DATA_TYPE_BFLOAT16, rank, p, gd, gs, bd, es, CU_TENSOR_MAP_INTERLEAVE_NONE, sw, pr,
           CU_TENSOR_MAP_FLOAT_OOB_FILL_NONE);
  };
  {
    const cuuint64_t gd[3] = {64, 512, 28}, gs[2] = {3584, 128};
    const cuuint32_t bd[3] = {64, 32, 2};
    enc(&tmGX, d_in[4], 3, gd, gs, bd, CU_TENSOR_MAP_SWIZZLE_128B, CU_TENSOR_MAP_L2_PROMOTION_L2_256B);
    enc(&tmUX, d_in[5], 3, gd, gs, bd, CU_TENSOR_MAP_SWIZZLE_128B, CU_TENSOR_MAP_L2_PROMOTION_L2_256B);
  }
  {
    const cuuint64_t gd[3] = {32, 512, 56}, gs[2] = {3584, 64};
    const cuuint32_t bd[3] = {32, 32, 3};
    enc(&tmGY, d_in[4], 3, gd, gs, bd, CU_TENSOR_MAP_SWIZZLE_64B, CU_TENSOR_MAP_L2_PROMOTION_L2_128B);
    enc(&tmUY, d_in[5], 3, gd, gs, bd, CU_TENSOR_MAP_SWIZZLE_64B, CU_TENSOR_MAP_L2_PROMOTION_L2_128B);
  }
  {
    const cuuint64_t gd[3] = {64, 1792, 8}, gs[2] = {1024, 128};
    const cuuint32_t bd[3] = {64, 64, 2};
    enc(&tmD, d_in[6], 3, gd, gs, bd, CU_TENSOR_MAP_SWIZZLE_128B, CU_TENSOR_MAP_L2_PROMOTION_L2_256B);
  }
  {
    const cuuint64_t gd[3] = {4112, 8, 16}, gs[2] = {16 * 8224, 8224};
    const cuuint32_t bd[3] = {40, 8, 16};
    enc(&tmWR, d_in[1], 3, gd, gs, bd, CU_TENSOR_MAP_SWIZZLE_NONE, CU_TENSOR_MAP_L2_PROMOTION_NONE);
    enc(&tmWI, d_in[2], 3, gd, gs, bd, CU_TENSOR_MAP_SWIZZLE_NONE, CU_TENSOR_MAP_L2_PROMOTION_NONE);
  }
  fused_kernel<<<NCTA, NTHREADS, SMEM_BYTES>>>((const __nv_bfloat16*)d_in[0], (const Tables*)tab, (Scratch*)scr,
                                               (__nv_bfloat16*)d_out, (const char*)d_in[4], (const char*)d_in[5],
                                               (const char*)d_in[6], tmWR, tmWI, tmGX, tmUX, tmGY, tmUY, tmD);
}
```

```cpp
#include <cuda_runtime.h>
#include <cuda_bf16.h>
#include <cuda.h>
#include <stdint.h>

namespace {

constexpr int NCTA = 128;
constexpr int NTHREADS = 384;
constexpr int SLOT = 16384;
constexpr int SMEM_BYTES = 14 * SLOT + 3072;
constexpr int SPIN_LIMIT = 1 << 22;

struct Scratch {
  uint4 Z1[128 * 1024];
  uint4 LN[16 * 8 * 1024];
  uint4 P[16 * 28 * 1024];
  uint4 ST[1024];
  unsigned cnt[64 * 32];
};
__device__ __align__(1024) Scratch g_scr;

constexpr double ccos(int i, int n) {
  i &= n - 1;
  if (i > n / 2) i = n - i;
  if (4 * i == n) return 0.0;
  const bool neg = 4 * i > n;
  if (neg) i = n / 2 - i;
  const double a = 6.283185307179586476925 * i / n, a2 = a * a;
  double term = 1.0, sum = 1.0;
  for (int k = 1; k < 14; k++) { term *= -a2 / ((2 * k - 1) * (2 * k)); sum += term; }
  return neg ? -sum : sum;
}
constexpr double csin(int i, int n) { return ccos(i - n / 4, n); }
constexpr unsigned fbits(double v, int mant) {
  if (v == 0.0) return 0;
  const unsigned sg = v < 0 ? 1u : 0u;
  if (v < 0) v = -v;
  int e = 127;
  while (v < 1.0) { v *= 2.0; e--; }
  const unsigned m = (unsigned)((v - 1.0) * (double)(1u << mant) + 0.5);
  return (sg << (8 + mant)) + ((unsigned)e << mant) + m;
}
constexpr unsigned pkb(double lo, double hi) { return fbits(lo, 7) | (fbits(hi, 7) << 16); }
constexpr double fa_elem(int mt, int r, int n1) {
  const int k1 = 8 * mt + (r & 7);
  return r < 8 ? ccos(k1 * n1, 32) : k1 == 0 ? ccos(16 * n1, 32) : -csin(k1 * n1, 32);
}
constexpr unsigned cfrag_c(int idx, int n, int ri, double s = 1.0) {
  return ri ? pkb(-s * csin(idx, n), s * ccos(idx, n)) : pkb(s * ccos(idx, n), s * csin(idx, n));
}
struct Tables {
  unsigned fa[4][32][4];
  unsigned fb[4][32][4];
  unsigned tw1[6][32][4];
  unsigned f2[8][4][32][4];
  unsigned g2[8][4][32][4];
  unsigned gb[4][32][4];
  unsigned ga[4][32][4];
  unsigned tw3[4][32][4];
  unsigned f8[32][4], g8[32][4];
};
constexpr int T1_BYTES = 7168, T2_BYTES = 39936;
static_assert(sizeof(Tables) == T1_BYTES + T2_BYTES, "table size");
constexpr Tables make_tables() {
  Tables T = {};
  for (int l = 0; l < 32; l++) {
    const int g = l >> 2, t = l & 3;
    for (int a = 0; a < 2; a++)
      for (int b = 0; b < 2; b++) {
        for (int r = 0; r < 4; r++) {
          const int row = g + 8 * (r & 1), col = 2 * t + 8 * (r >> 1);
          T.fa[2 * a + b][l][r] = pkb(fa_elem(a, row, 16 * b + col), fa_elem(a, row, 16 * b + col + 1));
          T.ga[2 * a + b][l][r] = pkb(fa_elem(b, col, 16 * a + row), fa_elem(b, col + 1, 16 * a + row));
        }
        const double sg = b ? -1.0 : 1.0;
        for (int h = 0; h < 2; h++) {
          const int ri = g & 1, m = 2 * (g >> 1) + h, k2 = b ? 15 - m : m;
          const int pa = (8 * a + 2 * t) * k2, pb = (8 * a + 2 * t + 1) * k2;
          T.fb[2 * a + b][l][2 * h] = ri == 0 ? pkb(ccos(pa, 16), ccos(pb, 16)) : pkb(-sg * csin(pa, 16), -sg * csin(pb, 16));
          T.fb[2 * a + b][l][2 * h + 1] = ri == 0 ? pkb(csin(pa, 16), csin(pb, 16)) : pkb(sg * ccos(pa, 16), sg * ccos(pb, 16));
        }
        const int n2 = 4 * (g >> 1) + 2 * a + (g & 1);
        for (int h = 0; h < 2; h++) {
          const int p = n2 * (b ? 15 - 2 * t - h : 2 * t + h);
          T.gb[2 * a + b][l][2 * h] = pkb(ccos(p, 16), -sg * csin(p, 16));
          T.gb[2 * a + b][l][2 * h + 1] = pkb(csin(p, 16), sg * ccos(p, 16));
          const int k1 = 8 * b + 2 * t + h, q = n2 * (k1 == 0 ? 16 : k1);
          T.tw3[2 * a + b][l][2 * h] = fbits(ccos(q, 512), 23);
          T.tw3[2 * a + b][l][2 * h + 1] = fbits(csin(q, 512), 23);
        }
        const int p = (8 * a + 2 * t + b) * (g == 0 ? 16 : g);
        T.tw1[2 * a + b][l][0] = fbits(g == 0 ? 0.0 : ccos(p, 512), 23);
        T.tw1[2 * a + b][l][1] = fbits(g == 0 ? ccos(p, 512) : csin(p, 512), 23);
        T.tw1[2 * a + b][l][2] = fbits(g == 0 ? 0.0 : -csin(p, 512), 23);
        T.tw1[2 * a + b][l][3] = fbits(g == 0 ? -csin(p, 512) : ccos(p, 512), 23);
        T.tw1[4 + a][l][2 * b] = fbits(ccos((8 * a + 2 * t + b) * (g + 8), 512), 23);
        T.tw1[4 + a][l][2 * b + 1] = fbits(csin((8 * a + 2 * t + b) * (g + 8), 512), 23);
      }
    for (int i = 0; i < 4; i++) {
      const int p8 = (t + 4 * (i & 1)) * (4 * (i >> 1) + (g >> 1));
      T.f8[l][i] = cfrag_c(p8, 8, g & 1);
      T.g8[l][i] = cfrag_c(-p8, 8, g & 1, 1.0 / (1 << 19));
    }
    for (int w = 0; w < 8; w++)
      for (int i = 0; i < 16; i++) {
        const int kidx = t + 4 * (i & 1) + 8 * (i >> 3), nidx = 4 * ((i >> 1) & 3) + (g >> 1);
        T.f2[w][i >> 2][l][i & 3] = cfrag_c((8 * kidx + w) * nidx, 128, g & 1);
        T.g2[w][i >> 2][l][i & 3] = cfrag_c(-(8 * nidx + w) * kidx, 128, g & 1);
      }
  }
  return T;
}
__device__ const __align__(128) Tables g_tab = make_tables();

__device__ __forceinline__ void die() { asm volatile("st.global.u32 [%0], %1;" ::"l"(0ull), "r"(0) : "memory"); }
__device__ __forceinline__ uint32_t s2u(const void* p) { return (uint32_t)__cvta_generic_to_shared(p); }
__device__ __forceinline__ void mbar_init(uint32_t b, int c) { asm volatile("mbarrier.init.shared::cta.b64 [%0], %1;" ::"r"(b), "r"(c)); }
__device__ __forceinline__ void mbar_expect(uint32_t b, int bytes) {
  asm volatile("mbarrier.arrive.expect_tx.shared::cta.b64 _, [%0], %1;" ::"r"(b), "r"(bytes) : "memory");
}
__device__ __forceinline__ void mbar_arrive(uint32_t b) { asm volatile("mbarrier.arrive.shared::cta.b64 _, [%0];" ::"r"(b) : "memory"); }
__device__ __forceinline__ uint32_t mbar_try(uint32_t b, uint32_t parity) {
  uint32_t ok;
  asm volatile("{.reg .pred p; mbarrier.try_wait.parity.shared::cta.b64 p, [%1], %2; selp.u32 %0,1,0,p;}"
               : "=r"(ok) : "r"(b), "r"(parity) : "memory");
  return ok;
}
__device__ __forceinline__ uint32_t mbar_test(uint32_t b) {
  uint32_t ok;
  asm volatile("{.reg .pred p; mbarrier.test_wait.parity.shared::cta.b64 p, [%1], 0; selp.u32 %0,1,0,p;}" : "=r"(ok) : "r"(b) : "memory");
  return ok;
}
__device__ __forceinline__ void mbar_wait(uint32_t b, uint32_t parity = 0) {
  int it = 0;
#pragma unroll 1
  while (!mbar_try(b, parity))
    if (++it > SPIN_LIMIT) { die(); break; }
}
__device__ __forceinline__ void bar_sync(int id, int n) { asm volatile("bar.sync %0, %1;" ::"r"(id), "r"(n) : "memory"); }
__device__ __forceinline__ void bar_arrive(int id, int n) { asm volatile("bar.arrive %0, %1;" ::"r"(id), "r"(n) : "memory"); }
__device__ __forceinline__ void red_release(unsigned* p) { asm volatile("red.release.gpu.global.add.u32 [%0], 1;" ::"l"(p) : "memory"); }
__device__ __forceinline__ void red_relaxed(unsigned* p) { asm volatile("red.relaxed.gpu.global.add.u32 [%0], 1;" ::"l"(p) : "memory"); }
__device__ __forceinline__ unsigned ld_acquire(const unsigned* p) {
  unsigned v;
  asm volatile("ld.acquire.gpu.global.u32 %0, [%1];" : "=r"(v) : "l"(p) : "memory");
  return v;
}
__device__ __forceinline__ unsigned ld_relaxed(const unsigned* p) {
  unsigned v;
  asm volatile("ld.relaxed.gpu.global.u32 %0, [%1];" : "=r"(v) : "l"(p) : "memory");
  return v;
}
__device__ __forceinline__ void wait_counter(const unsigned* p, unsigned target) {
  int it = 0;
  while ((int)(ld_acquire(p) - target) < 0)
    if (++it > SPIN_LIMIT) { die(); break; }
}
__device__ __forceinline__ void sts4(uint32_t a, uint32_t x, uint32_t y, uint32_t z, uint32_t w) {
  asm volatile("st.shared.v4.u32 [%0], {%1,%2,%3,%4};" ::"r"(a), "r"(x), "r"(y), "r"(z), "r"(w) : "memory");
}
__device__ __forceinline__ uint4 lds4(uint32_t a) {
  uint4 v;
  asm volatile("ld.shared.v4.u32 {%0,%1,%2,%3}, [%4];" : "=r"(v.x), "=r"(v.y), "=r"(v.z), "=r"(v.w) : "r"(a) : "memory");
  return v;
}
__device__ __forceinline__ uint32_t pack2(float lo, float hi) {
  uint32_t r;
  asm("cvt.rn.bf16x2.f32 %0, %1, %2;" : "=r"(r) : "f"(hi), "f"(lo));
  return r;
}
__device__ __forceinline__ float bf_lo(uint32_t v) { return __uint_as_float(v << 16); }
__device__ __forceinline__ uint32_t hadd2_bf16(uint32_t a, uint32_t b) {
  uint32_t r;
  asm("add.rn.bf16x2 %0, %1, %2;" : "=r"(r) : "r"(a), "r"(b));
  return r;
}
__device__ __forceinline__ void mma16816(float (&d)[4], uint32_t a0, uint32_t a1, uint32_t a2, uint32_t a3, uint32_t b0, uint32_t b1) {
  asm("mma.sync.aligned.m16n8k16.row.col.f32.bf16.bf16.f32 {%0,%1,%2,%3}, {%4,%5,%6,%7}, {%8,%9}, {%0,%1,%2,%3};"
      : "+f"(d[0]), "+f"(d[1]), "+f"(d[2]), "+f"(d[3])
      : "r"(a0), "r"(a1), "r"(a2), "r"(a3), "r"(b0), "r"(b1));
}
__device__ __forceinline__ void mma16816_z(float (&d)[4], uint32_t a0, uint32_t a1, uint32_t a2, uint32_t a3, uint32_t b0, uint32_t b1) {
  asm("{.reg .f32 z; mov.f32 z, 0f00000000;\n"
      "mma.sync.aligned.m16n8k16.row.col.f32.bf16.bf16.f32 {%0,%1,%2,%3}, {%4,%5,%6,%7}, {%8,%9}, {z,z,z,z};}"
      : "=f"(d[0]), "=f"(d[1]), "=f"(d[2]), "=f"(d[3])
      : "r"(a0), "r"(a1), "r"(a2), "r"(a3), "r"(b0), "r"(b1));
}
template <int N>
__device__ __forceinline__ void cs_frac(int idx, float& c, float& s) {
  int i = ((idx + N / 2) & (N - 1)) - N / 2;
  float a = (float)i * (6.283185307179586f / N);
  c = __cosf(a);
  s = __sinf(a);
}
template <int N>
__device__ __forceinline__ uint32_t cfrag(int idx, int ri) {
  float c, s;
  cs_frac<N>(idx, c, s);
  return ri ? pack2(-s, c) : pack2(c, s);
}
__device__ __forceinline__ uint32_t word(const uint4& v, int e) { return e == 0 ? v.x : e == 1 ? v.y : e == 2 ? v.z : v.w; }
__device__ __forceinline__ void cdft16(const uint4 (&A)[4], const uint4 (&F)[4], uint4 (&o)[4]) {
  float acc[2][4][4];
#pragma unroll
  for (int ks = 0; ks < 2; ks++)
#pragma unroll
    for (int p = 0; p < 2; p++)
#pragma unroll
      for (int v = 0; v < 4; v++) {
        const uint4& a = A[2 * ks + p];
        const uint32_t b0 = word(F[ks * 2 + (v >> 1)], (v & 1) * 2), b1 = word(F[ks * 2 + (v >> 1)], (v & 1) * 2 + 1);
        if (ks == 0) mma16816_z(acc[p][v], a.x, a.y, a.z, a.w, b0, b1);
        else mma16816(acc[p][v], a.x, a.y, a.z, a.w, b0, b1);
      }
#pragma unroll
  for (int v = 0; v < 4; v++)
    o[v] = make_uint4(pack2(acc[0][v][0], acc[0][v][1]), pack2(acc[0][v][2], acc[0][v][3]),
                      pack2(acc[1][v][0], acc[1][v][1]), pack2(acc[1][v][2], acc[1][v][3]));
}
__device__ __forceinline__ void lds_frag(uint4& f0, uint4& f1, uint32_t a0, uint32_t a1) {
  asm volatile("ld.volatile.shared.v2.u32 {%0,%1}, [%8]; ld.volatile.shared.v2.u32 {%2,%3}, [%9];\n"
               "ld.volatile.shared.v2.u32 {%4,%5}, [%8+8]; ld.volatile.shared.v2.u32 {%6,%7}, [%9+8];"
               : "=r"(f0.x), "=r"(f0.y), "=r"(f0.z), "=r"(f0.w), "=r"(f1.x), "=r"(f1.y), "=r"(f1.z), "=r"(f1.w) : "r"(a0), "r"(a1) : "memory");
}
__device__ __forceinline__ void reg_frag(uint4 (&q)[4], uint32_t ones) {
#pragma unroll
  for (int ks = 0; ks < 2; ks++) {
    const uint4 a = q[2 * ks], b = q[2 * ks + 1];
    q[2 * ks] = make_uint4(a.x, a.y, b.x & ones, b.y & ones);
    q[2 * ks + 1] = make_uint4(a.z & ones, a.w & ones, b.z, b.w);
  }
}
__device__ __forceinline__ void st_tag(uint4* p, const uint4& v, uint32_t tag) {
  asm volatile("st.relaxed.gpu.global.v4.b32 [%0], {%1,%2,%3,%4};"
               ::"l"(p), "r"((v.x & ~1u) | tag), "r"(v.y), "r"(v.z), "r"(v.w) : "memory");
}
__device__ __forceinline__ void st_tag8(void* p, uint32_t x, uint32_t y, uint32_t tag) {
  asm volatile("st.relaxed.gpu.global.v2.b32 [%0], {%1,%2};" ::"l"(p), "r"((x & ~1u) | tag), "r"(y) : "memory");
}
__device__ __forceinline__ uint4 ld_b128(const uint4* p) {
  uint4 v;
  asm volatile("ld.relaxed.gpu.global.v4.b32 {%0,%1,%2,%3}, [%4];"
               : "=r"(v.x), "=r"(v.y), "=r"(v.z), "=r"(v.w) : "l"(p) : "memory");
  return v;
}
template <int STRIDE>
__device__ __forceinline__ void ld_tag4_issue(uint4 (&q)[4], const uint4* p) {
#pragma unroll
  for (int i = 0; i < 4; i++) q[i] = ld_b128(p + i * STRIDE);
}
template <int STRIDE, bool HALVES = false>
__device__ __forceinline__ void ld_tag4_finish(uint4 (&q)[4], const uint4* p, uint32_t tag) {
  int it = 0;
#pragma unroll 1
  while (__any_sync(0xffffffffu, ((q[0].x ^ tag) | (q[1].x ^ tag) | (q[2].x ^ tag) | (q[3].x ^ tag) |
                                  (HALVES ? (q[0].z ^ tag) | (q[1].z ^ tag) | (q[2].z ^ tag) | (q[3].z ^ tag) : 0u)) & 1u)) {
    ld_tag4_issue<STRIDE>(q, p);
    if (++it > SPIN_LIMIT) { die(); break; }
  }
#pragma unroll
  for (int i = 0; i < 4; i++) {
    asm volatile("and.b32 %0, %0, 0xfffffffe;" : "+r"(q[i].x));
    if (HALVES) q[i].z &= ~1u;
  }
}
__device__ __forceinline__ float quad_sum(const uint32_t (&a)[8]) {
  float d[4];
  mma16816_z(d, a[0], a[1], a[2], a[3], 0x3f803f80u, 0x3f803f80u);
  mma16816(d, a[4], a[5], a[6], a[7], 0x3f803f80u, 0x3f803f80u);
  return d[0] + d[2];
}
__device__ __forceinline__ float sum_groups(float v) {
  v += __shfl_xor_sync(0xffffffffu, v, 4);
  v += __shfl_xor_sync(0xffffffffu, v, 8);
  v += __shfl_xor_sync(0xffffffffu, v, 16);
  return v;
}
__device__ __forceinline__ uint32_t hsub2_bf16(uint32_t a, uint32_t b) {
  uint32_t r;
  asm("sub.rn.bf16x2 %0, %1, %2;" : "=r"(r) : "r"(a), "r"(b));
  return r;
}
__device__ __forceinline__ float row_rstd(const uint32_t (&c)[8], float delta) {
  uint32_t s[8];
#pragma unroll
  for (int i = 0; i < 8; i++) asm("mul.rn.bf16x2 %0, %1, %1;" : "=r"(s[i]) : "r"(c[i]));
  return rsqrtf(fmaxf(fmaf(-delta, delta, sum_groups(quad_sum(s)) * (1.f / 512.f)), 0.f) + 1e-5f);
}
__device__ __forceinline__ uint64_t desc64(uint32_t lo, uint32_t hi) {
  uint64_t d;
  asm("mov.b64 %0, {%1, %2};" : "=l"(d) : "r"(lo), "r"(hi));
  return d;
}
constexpr uint32_t desc_hi(uint32_t sbo, uint32_t swz) { return (sbo >> 4) | (swz << 30); }
__device__ __forceinline__ uint32_t desc_lo(uint32_t addr, uint32_t lbo) { return ((addr & 0x3FFFF) >> 4) | ((lbo >> 4) << 16); }
__device__ __forceinline__ void cp_async16(uint32_t dst, const void* src) {
  asm volatile("cp.async.cg.shared.global [%0], [%1], 16;" ::"r"(dst), "l"(src) : "memory");
}
__device__ __forceinline__ uint2 lds2(uint32_t a) {
  uint2 v;
  asm volatile("ld.shared.v2.u32 {%0,%1}, [%2];" : "=r"(v.x), "=r"(v.y) : "r"(a) : "memory");
  return v;
}
__device__ __forceinline__ uint32_t lds_u16(uint32_t a) {
  uint16_t v;
  asm volatile("ld.shared.u16 %0, [%1];" : "=h"(v) : "r"(a) : "memory");
  return v;
}
__device__ __forceinline__ void wg_fence() { asm volatile("wgmma.fence.sync.aligned;" ::: "memory"); }
__device__ __forceinline__ void wg_commit() { asm volatile("wgmma.commit_group.sync.aligned;" ::: "memory"); }
template <int N>
__device__ __forceinline__ void wg_wait() { asm volatile("wgmma.wait_group.sync.aligned %0;" ::"n"(N) : "memory"); }
__device__ __forceinline__ void bulk_load(uint32_t dst, const void* src, int bytes, uint32_t bar) {
  asm volatile("cp.async.bulk.shared::cluster.global.mbarrier::complete_tx::bytes [%0], [%1], %2, [%3];"
               ::"r"(dst), "l"(src), "r"(bytes), "r"(bar) : "memory");
}
__device__ __forceinline__ void bulk_load_mc(uint32_t dst, const void* src, int bytes, uint32_t bar) {
  asm volatile("cp.async.bulk.shared::cluster.global.mbarrier::complete_tx::bytes.multicast::cluster [%0], [%1], %2, [%3], %4;"
               ::"r"(dst), "l"(src), "r"(bytes), "r"(bar), "h"((uint16_t)3) : "memory");
}
__device__ __forceinline__ void tma3(uint32_t dst, const CUtensorMap* tm, uint32_t bar, int c0, int c1, int c2) {
  asm volatile("cp.async.bulk.tensor.3d.shared::cluster.global.mbarrier::complete_tx::bytes [%0], [%1, {%3,%4,%5}], [%2];"
               ::"r"(dst), "l"(tm), "r"(bar), "r"(c0), "r"(c1), "r"(c2) : "memory");
}
__device__ __forceinline__ void tma3_mc(uint32_t dst, const CUtensorMap* tm, uint32_t bar, int c1, int c2) {
  asm volatile("cp.async.bulk.tensor.3d.shared::cluster.global.mbarrier::complete_tx::bytes.multicast::cluster [%0], [%1, {%3,%4,%5}], [%2], %6;"
               ::"r"(dst), "l"(tm), "r"(bar), "r"(0), "r"(c1), "r"(c2), "h"((uint16_t)3) : "memory");
}
__device__ __forceinline__ void mbar_arrive_remote(uint32_t rb) {
  asm volatile("mbarrier.arrive.shared::cluster.b64 _, [%0];" ::"r"(rb) : "memory");
}
__device__ __forceinline__ uint4 ldg_ca4(const void* p) {
  uint4 v;
  asm volatile("ld.global.ca.v4.u32 {%0,%1,%2,%3}, [%4];" : "=r"(v.x), "=r"(v.y), "=r"(v.z), "=r"(v.w) : "l"(p) : "memory");
  return v;
}
__device__ __forceinline__ float u2f(uint32_t v) { return __uint_as_float(v); }
__device__ __forceinline__ void mma_az(float (&d)[4], const uint4& a, uint32_t b0, uint32_t b1) { mma16816_z(d, a.x, a.y, a.z, a.w, b0, b1); }
__device__ __forceinline__ void mma_a(float (&d)[4], const uint4& a, uint32_t b0, uint32_t b1) { mma16816(d, a.x, a.y, a.z, a.w, b0, b1); }
__device__ __forceinline__ uint32_t clock32() {
  uint32_t v;
  asm volatile("mov.u32 %0, %%clock;" : "=r"(v) :: "memory");
  return v;
}
__device__ __forceinline__ float swiglu(float g, float u, float r) {
  float hg = (0.5f * r) * g, th;
  asm("tanh.approx.f32 %0, %1;" : "=f"(th) : "f"(hg));
  return fmaf(hg, th, hg) * (r * u);
}
__device__ __forceinline__ void l2_prefetch(const void* p, int bytes) {
  asm volatile("cp.async.bulk.prefetch.L2.global [%0], %1;" ::"l"(p), "r"(bytes) : "memory");
}

__device__ __forceinline__ void wgmma_n256(float (&d)[128], uint64_t da, uint64_t db, int sd = 1) {
  asm volatile("{.reg .pred p; setp.ne.b32 p, %130, 0;\n"
      "wgmma.mma_async.sync.aligned.m64n256k16.f32.bf16.bf16 {"
      "%0,%1,%2,%3,%4,%5,%6,%7,%8,%9,%10,%11,%12,%13,%14,%15,"
      "%16,%17,%18,%19,%20,%21,%22,%23,%24,%25,%26,%27,%28,%29,%30,%31,"
      "%32,%33,%34,%35,%36,%37,%38,%39,%40,%41,%42,%43,%44,%45,%46,%47,"
      "%48,%49,%50,%51,%52,%53,%54,%55,%56,%57,%58,%59,%60,%61,%62,%63,"
      "%64,%65,%66,%67,%68,%69,%70,%71,%72,%73,%74,%75,%76,%77,%78,%79,"
      "%80,%81,%82,%83,%84,%85,%86,%87,%88,%89,%90,%91,%92,%93,%94,%95,"
      "%96,%97,%98,%99,%100,%101,%102,%103,%104,%105,%106,%107,%108,%109,%110,%111,"
      "%112,%113,%114,%115,%116,%117,%118,%119,%120,%121,%122,%123,%124,%125,%126,%127"
      "}, %128, %129, p, 1, 1, 0, 1;}\n"
      : "+f"(d[0]),"+f"(d[1]),"+f"(d[2]),"+f"(d[3]),"+f"(d[4]),"+f"(d[5]),"+f"(d[6]),"+f"(d[7]),
        "+f"(d[8]),"+f"(d[9]),"+f"(d[10]),"+f"(d[11]),"+f"(d[12]),"+f"(d[13]),"+f"(d[14]),"+f"(d[15]),
        "+f"(d[16]),"+f"(d[17]),"+f"(d[18]),"+f"(d[19]),"+f"(d[20]),"+f"(d[21]),"+f"(d[22]),"+f"(d[23]),
        "+f"(d[24]),"+f"(d[25]),"+f"(d[26]),"+f"(d[27]),"+f"(d[28]),"+f"(d[29]),"+f"(d[30]),"+f"(d[31]),
        "+f"(d[32]),"+f"(d[33]),"+f"(d[34]),"+f"(d[35]),"+f"(d[36]),"+f"(d[37]),"+f"(d[38]),"+f"(d[39]),
        "+f"(d[40]),"+f"(d[41]),"+f"(d[42]),"+f"(d[43]),"+f"(d[44]),"+f"(d[45]),"+f"(d[46]),"+f"(d[47]),
        "+f"(d[48]),"+f"(d[49]),"+f"(d[50]),"+f"(d[51]),"+f"(d[52]),"+f"(d[53]),"+f"(d[54]),"+f"(d[55]),
        "+f"(d[56]),"+f"(d[57]),"+f"(d[58]),"+f"(d[59]),"+f"(d[60]),"+f"(d[61]),"+f"(d[62]),"+f"(d[63]),
        "+f"(d[64]),"+f"(d[65]),"+f"(d[66]),"+f"(d[67]),"+f"(d[68]),"+f"(d[69]),"+f"(d[70]),"+f"(d[71]),
        "+f"(d[72]),"+f"(d[73]),"+f"(d[74]),"+f"(d[75]),"+f"(d[76]),"+f"(d[77]),"+f"(d[78]),"+f"(d[79]),
        "+f"(d[80]),"+f"(d[81]),"+f"(d[82]),"+f"(d[83]),"+f"(d[84]),"+f"(d[85]),"+f"(d[86]),"+f"(d[87]),
        "+f"(d[88]),"+f"(d[89]),"+f"(d[90]),"+f"(d[91]),"+f"(d[92]),"+f"(d[93]),"+f"(d[94]),"+f"(d[95]),
        "+f"(d[96]),"+f"(d[97]),"+f"(d[98]),"+f"(d[99]),"+f"(d[100]),"+f"(d[101]),"+f"(d[102]),"+f"(d[103]),
        "+f"(d[104]),"+f"(d[105]),"+f"(d[106]),"+f"(d[107]),"+f"(d[108]),"+f"(d[109]),"+f"(d[110]),"+f"(d[111]),
        "+f"(d[112]),"+f"(d[113]),"+f"(d[114]),"+f"(d[115]),"+f"(d[116]),"+f"(d[117]),"+f"(d[118]),"+f"(d[119]),
        "+f"(d[120]),"+f"(d[121]),"+f"(d[122]),"+f"(d[123]),"+f"(d[124]),"+f"(d[125]),"+f"(d[126]),"+f"(d[127])
      : "l"(da), "l"(db), "r"(sd));
}
__device__ __forceinline__ void wgmma_n192(float (&d)[96], uint64_t da, uint64_t db) {
  asm volatile("wgmma.mma_async.sync.aligned.m64n192k16.f32.bf16.bf16 {"
      "%0,%1,%2,%3,%4,%5,%6,%7,%8,%9,%10,%11,%12,%13,%14,%15,"
      "%16,%17,%18,%19,%20,%21,%22,%23,%24,%25,%26,%27,%28,%29,%30,%31,"
      "%32,%33,%34,%35,%36,%37,%38,%39,%40,%41,%42,%43,%44,%45,%46,%47,"
      "%48,%49,%50,%51,%52,%53,%54,%55,%56,%57,%58,%59,%60,%61,%62,%63,"
      "%64,%65,%66,%67,%68,%69,%70,%71,%72,%73,%74,%75,%76,%77,%78,%79,"
      "%80,%81,%82,%83,%84,%85,%86,%87,%88,%89,%90,%91,%92,%93,%94,%95"
      "}, %96, %97, 1, 1, 1, 0, 1;\n"
      : "+f"(d[0]),"+f"(d[1]),"+f"(d[2]),"+f"(d[3]),"+f"(d[4]),"+f"(d[5]),"+f"(d[6]),"+f"(d[7]),
        "+f"(d[8]),"+f"(d[9]),"+f"(d[10]),"+f"(d[11]),"+f"(d[12]),"+f"(d[13]),"+f"(d[14]),"+f"(d[15]),
        "+f"(d[16]),"+f"(d[17]),"+f"(d[18]),"+f"(d[19]),"+f"(d[20]),"+f"(d[21]),"+f"(d[22]),"+f"(d[23]),
        "+f"(d[24]),"+f"(d[25]),"+f"(d[26]),"+f"(d[27]),"+f"(d[28]),"+f"(d[29]),"+f"(d[30]),"+f"(d[31]),
        "+f"(d[32]),"+f"(d[33]),"+f"(d[34]),"+f"(d[35]),"+f"(d[36]),"+f"(d[37]),"+f"(d[38]),"+f"(d[39]),
        "+f"(d[40]),"+f"(d[41]),"+f"(d[42]),"+f"(d[43]),"+f"(d[44]),"+f"(d[45]),"+f"(d[46]),"+f"(d[47]),
        "+f"(d[48]),"+f"(d[49]),"+f"(d[50]),"+f"(d[51]),"+f"(d[52]),"+f"(d[53]),"+f"(d[54]),"+f"(d[55]),
        "+f"(d[56]),"+f"(d[57]),"+f"(d[58]),"+f"(d[59]),"+f"(d[60]),"+f"(d[61]),"+f"(d[62]),"+f"(d[63]),
        "+f"(d[64]),"+f"(d[65]),"+f"(d[66]),"+f"(d[67]),"+f"(d[68]),"+f"(d[69]),"+f"(d[70]),"+f"(d[71]),
        "+f"(d[72]),"+f"(d[73]),"+f"(d[74]),"+f"(d[75]),"+f"(d[76]),"+f"(d[77]),"+f"(d[78]),"+f"(d[79]),
        "+f"(d[80]),"+f"(d[81]),"+f"(d[82]),"+f"(d[83]),"+f"(d[84]),"+f"(d[85]),"+f"(d[86]),"+f"(d[87]),
        "+f"(d[88]),"+f"(d[89]),"+f"(d[90]),"+f"(d[91]),"+f"(d[92]),"+f"(d[93]),"+f"(d[94]),"+f"(d[95])
      : "l"(da), "l"(db));
}
__device__ __forceinline__ void wgmma_rs_n128(float (&d)[64], uint32_t a0, uint32_t a1, uint32_t a2, uint32_t a3, uint64_t db, int sd = 1) {
  asm volatile("{.reg .pred p; setp.ne.b32 p, %69, 0;\n"
      "wgmma.mma_async.sync.aligned.m64n128k16.f32.bf16.bf16 {"
      "%0,%1,%2,%3,%4,%5,%6,%7,%8,%9,%10,%11,%12,%13,%14,%15,"
      "%16,%17,%18,%19,%20,%21,%22,%23,%24,%25,%26,%27,%28,%29,%30,%31,"
      "%32,%33,%34,%35,%36,%37,%38,%39,%40,%41,%42,%43,%44,%45,%46,%47,"
      "%48,%49,%50,%51,%52,%53,%54,%55,%56,%57,%58,%59,%60,%61,%62,%63"
      "}, {%64,%65,%66,%67}, %68, p, 1, 1, 1;}\n"
      : "+f"(d[0]),"+f"(d[1]),"+f"(d[2]),"+f"(d[3]),"+f"(d[4]),"+f"(d[5]),"+f"(d[6]),"+f"(d[7]),
        "+f"(d[8]),"+f"(d[9]),"+f"(d[10]),"+f"(d[11]),"+f"(d[12]),"+f"(d[13]),"+f"(d[14]),"+f"(d[15]),
        "+f"(d[16]),"+f"(d[17]),"+f"(d[18]),"+f"(d[19]),"+f"(d[20]),"+f"(d[21]),"+f"(d[22]),"+f"(d[23]),
        "+f"(d[24]),"+f"(d[25]),"+f"(d[26]),"+f"(d[27]),"+f"(d[28]),"+f"(d[29]),"+f"(d[30]),"+f"(d[31]),
        "+f"(d[32]),"+f"(d[33]),"+f"(d[34]),"+f"(d[35]),"+f"(d[36]),"+f"(d[37]),"+f"(d[38]),"+f"(d[39]),
        "+f"(d[40]),"+f"(d[41]),"+f"(d[42]),"+f"(d[43]),"+f"(d[44]),"+f"(d[45]),"+f"(d[46]),"+f"(d[47]),
        "+f"(d[48]),"+f"(d[49]),"+f"(d[50]),"+f"(d[51]),"+f"(d[52]),"+f"(d[53]),"+f"(d[54]),"+f"(d[55]),
        "+f"(d[56]),"+f"(d[57]),"+f"(d[58]),"+f"(d[59]),"+f"(d[60]),"+f"(d[61]),"+f"(d[62]),"+f"(d[63])
      : "r"(a0), "r"(a1), "r"(a2), "r"(a3), "l"(db), "r"(sd));
}
__device__ __forceinline__ void wgmma_rs_n256(float (&d)[128], uint32_t a0, uint32_t a1, uint32_t a2, uint32_t a3, uint64_t db, int sd = 1) {
  asm volatile("{.reg .pred p; setp.ne.b32 p, %133, 0;\n"
      "wgmma.mma_async.sync.aligned.m64n256k16.f32.bf16.bf16 {"
      "%0,%1,%2,%3,%4,%5,%6,%7,%8,%9,%10,%11,%12,%13,%14,%15,"
      "%16,%17,%18,%19,%20,%21,%22,%23,%24,%25,%26,%27,%28,%29,%30,%31,"
      "%32,%33,%34,%35,%36,%37,%38,%39,%40,%41,%42,%43,%44,%45,%46,%47,"
      "%48,%49,%50,%51,%52,%53,%54,%55,%56,%57,%58,%59,%60,%61,%62,%63,"
      "%64,%65,%66,%67,%68,%69,%70,%71,%72,%73,%74,%75,%76,%77,%78,%79,"
      "%80,%81,%82,%83,%84,%85,%86,%87,%88,%89,%90,%91,%92,%93,%94,%95,"
      "%96,%97,%98,%99,%100,%101,%102,%103,%104,%105,%106,%107,%108,%109,%110,%111,"
      "%112,%113,%114,%115,%116,%117,%118,%119,%120,%121,%122,%123,%124,%125,%126,%127"
      "}, {%128,%129,%130,%131}, %132, p, 1, 1, 1;}\n"
      : "+f"(d[0]),"+f"(d[1]),"+f"(d[2]),"+f"(d[3]),"+f"(d[4]),"+f"(d[5]),"+f"(d[6]),"+f"(d[7]),
        "+f"(d[8]),"+f"(d[9]),"+f"(d[10]),"+f"(d[11]),"+f"(d[12]),"+f"(d[13]),"+f"(d[14]),"+f"(d[15]),
        "+f"(d[16]),"+f"(d[17]),"+f"(d[18]),"+f"(d[19]),"+f"(d[20]),"+f"(d[21]),"+f"(d[22]),"+f"(d[23]),
        "+f"(d[24]),"+f"(d[25]),"+f"(d[26]),"+f"(d[27]),"+f"(d[28]),"+f"(d[29]),"+f"(d[30]),"+f"(d[31]),
        "+f"(d[32]),"+f"(d[33]),"+f"(d[34]),"+f"(d[35]),"+f"(d[36]),"+f"(d[37]),"+f"(d[38]),"+f"(d[39]),
        "+f"(d[40]),"+f"(d[41]),"+f"(d[42]),"+f"(d[43]),"+f"(d[44]),"+f"(d[45]),"+f"(d[46]),"+f"(d[47]),
        "+f"(d[48]),"+f"(d[49]),"+f"(d[50]),"+f"(d[51]),"+f"(d[52]),"+f"(d[53]),"+f"(d[54]),"+f"(d[55]),
        "+f"(d[56]),"+f"(d[57]),"+f"(d[58]),"+f"(d[59]),"+f"(d[60]),"+f"(d[61]),"+f"(d[62]),"+f"(d[63]),
        "+f"(d[64]),"+f"(d[65]),"+f"(d[66]),"+f"(d[67]),"+f"(d[68]),"+f"(d[69]),"+f"(d[70]),"+f"(d[71]),
        "+f"(d[72]),"+f"(d[73]),"+f"(d[74]),"+f"(d[75]),"+f"(d[76]),"+f"(d[77]),"+f"(d[78]),"+f"(d[79]),
        "+f"(d[80]),"+f"(d[81]),"+f"(d[82]),"+f"(d[83]),"+f"(d[84]),"+f"(d[85]),"+f"(d[86]),"+f"(d[87]),
        "+f"(d[88]),"+f"(d[89]),"+f"(d[90]),"+f"(d[91]),"+f"(d[92]),"+f"(d[93]),"+f"(d[94]),"+f"(d[95]),
        "+f"(d[96]),"+f"(d[97]),"+f"(d[98]),"+f"(d[99]),"+f"(d[100]),"+f"(d[101]),"+f"(d[102]),"+f"(d[103]),
        "+f"(d[104]),"+f"(d[105]),"+f"(d[106]),"+f"(d[107]),"+f"(d[108]),"+f"(d[109]),"+f"(d[110]),"+f"(d[111]),
        "+f"(d[112]),"+f"(d[113]),"+f"(d[114]),"+f"(d[115]),"+f"(d[116]),"+f"(d[117]),"+f"(d[118]),"+f"(d[119]),
        "+f"(d[120]),"+f"(d[121]),"+f"(d[122]),"+f"(d[123]),"+f"(d[124]),"+f"(d[125]),"+f"(d[126]),"+f"(d[127])
      : "r"(a0), "r"(a1), "r"(a2), "r"(a3), "l"(db), "r"(sd));
}
__device__ __forceinline__ void wgmma_rs_n192(float (&d)[96], uint32_t a0, uint32_t a1, uint32_t a2, uint32_t a3, uint64_t db) {
  asm volatile("wgmma.mma_async.sync.aligned.m64n192k16.f32.bf16.bf16 {"
      "%0,%1,%2,%3,%4,%5,%6,%7,%8,%9,%10,%11,%12,%13,%14,%15,"
      "%16,%17,%18,%19,%20,%21,%22,%23,%24,%25,%26,%27,%28,%29,%30,%31,"
      "%32,%33,%34,%35,%36,%37,%38,%39,%40,%41,%42,%43,%44,%45,%46,%47,"
      "%48,%49,%50,%51,%52,%53,%54,%55,%56,%57,%58,%59,%60,%61,%62,%63,"
      "%64,%65,%66,%67,%68,%69,%70,%71,%72,%73,%74,%75,%76,%77,%78,%79,"
      "%80,%81,%82,%83,%84,%85,%86,%87,%88,%89,%90,%91,%92,%93,%94,%95"
      "}, {%96,%97,%98,%99}, %100, 1, 1, 1, 1;\n"
      : "+f"(d[0]),"+f"(d[1]),"+f"(d[2]),"+f"(d[3]),"+f"(d[4]),"+f"(d[5]),"+f"(d[6]),"+f"(d[7]),
        "+f"(d[8]),"+f"(d[9]),"+f"(d[10]),"+f"(d[11]),"+f"(d[12]),"+f"(d[13]),"+f"(d[14]),"+f"(d[15]),
        "+f"(d[16]),"+f"(d[17]),"+f"(d[18]),"+f"(d[19]),"+f"(d[20]),"+f"(d[21]),"+f"(d[22]),"+f"(d[23]),
        "+f"(d[24]),"+f"(d[25]),"+f"(d[26]),"+f"(d[27]),"+f"(d[28]),"+f"(d[29]),"+f"(d[30]),"+f"(d[31]),
        "+f"(d[32]),"+f"(d[33]),"+f"(d[34]),"+f"(d[35]),"+f"(d[36]),"+f"(d[37]),"+f"(d[38]),"+f"(d[39]),
        "+f"(d[40]),"+f"(d[41]),"+f"(d[42]),"+f"(d[43]),"+f"(d[44]),"+f"(d[45]),"+f"(d[46]),"+f"(d[47]),
        "+f"(d[48]),"+f"(d[49]),"+f"(d[50]),"+f"(d[51]),"+f"(d[52]),"+f"(d[53]),"+f"(d[54]),"+f"(d[55]),
        "+f"(d[56]),"+f"(d[57]),"+f"(d[58]),"+f"(d[59]),"+f"(d[60]),"+f"(d[61]),"+f"(d[62]),"+f"(d[63]),
        "+f"(d[64]),"+f"(d[65]),"+f"(d[66]),"+f"(d[67]),"+f"(d[68]),"+f"(d[69]),"+f"(d[70]),"+f"(d[71]),
        "+f"(d[72]),"+f"(d[73]),"+f"(d[74]),"+f"(d[75]),"+f"(d[76]),"+f"(d[77]),"+f"(d[78]),"+f"(d[79]),
        "+f"(d[80]),"+f"(d[81]),"+f"(d[82]),"+f"(d[83]),"+f"(d[84]),"+f"(d[85]),"+f"(d[86]),"+f"(d[87]),
        "+f"(d[88]),"+f"(d[89]),"+f"(d[90]),"+f"(d[91]),"+f"(d[92]),"+f"(d[93]),"+f"(d[94]),"+f"(d[95])
      : "r"(a0), "r"(a1), "r"(a2), "r"(a3), "l"(db));
}


constexpr int C_LN = 0, C_PX = 16, C_PY = 32;
constexpr int NB_CONS = 1, NB_LN = 2, NB_LAG = 4, NB_INIT = 6, NB_RDY = 7, NB_WG = 8;
constexpr int LAGX = 3;
constexpr int LAGY = 6;
constexpr int LAG2 = 5;
constexpr int NLL = 2;
constexpr int POLL_DELAY3 = 600;
constexpr int POLL_DELAY = 1200;
constexpr int FILT_DELAY = 800;
constexpr int WARM = 4;
constexpr int ALEAD = 6;
constexpr int POLL_DELAY2 = 1000;
constexpr int REDPOS = 4;
constexpr int XTRIG = 20;
constexpr int HTRIG = 0;
constexpr int RING_SIG = 1;
constexpr int PF2_SIG = 1;
constexpr int SM_E = 0, SM_X = 16384, SM_E2 = 32768, SM_W = 49152, SM_FC = 69632, SM_T = 73728 - T1_BYTES;
constexpr unsigned long long KORDER = 0xBA9432DC876510ull;
constexpr unsigned long long BSLOT = 0x52140A98D52140ull, PSLOT = 0xB763CB763CB763ull;
constexpr unsigned long long BDEP = 0xFFEC97531ull, PDEP = 0xBA754ull;
constexpr uint32_t HI128 = desc_hi(1024, 1), HI64 = desc_hi(512, 2);

struct Bars {
  uint64_t full1[32], empty1[32], full2[16], fullA[8], empty2[8], fullP[32], emptyP[9], hbar, tbar, hint[3], sig[2], sbar, freeA[4];
  uint32_t epoch, pad;
};

template <int NK, bool STORE, int J0 = 0, int J1 = NK>
__device__ __forceinline__ void make_p(const float (&acc)[NK * 16], float r0, float r1, uint4 (&p)[NK], uint4* pbase, int ks0, uint32_t tag) {
#pragma unroll
  for (int j = J0; j < J1; j++) {
    uint32_t w[4];
#pragma unroll
    for (int i = 0; i < 4; i++) {
      const int a = 8 * j + 2 * i, b = a + NK * 8;
      w[i] = pack2(swiglu(acc[a], acc[b], (i & 1) ? r1 : r0), swiglu(acc[a + 1], acc[b + 1], (i & 1) ? r1 : r0));
    }
    asm volatile("" : "+r"(w[0]), "+r"(w[1]), "+r"(w[2]), "+r"(w[3]));
    p[j] = make_uint4(w[0], w[1], w[2], w[3]);
    if (STORE) st_tag(pbase + ((ks0 + j) >> 2) * 1024 + ((ks0 + j) & 3) * 32, p[j], tag);
  }
}
__device__ __forceinline__ void spin_until(uint32_t t) {
  while ((int)(clock32() - t) < 0) {}
}

__global__ void __cluster_dims__(2, 1, 1) __launch_bounds__(NTHREADS, 1)
fused_kernel(const __nv_bfloat16* __restrict__ x, const Tables* __restrict__ tab, Scratch* __restrict__ scr,
             __nv_bfloat16* __restrict__ out, const char* __restrict__ wg_raw, const char* __restrict__ wu_raw,
             const char* __restrict__ wd_raw,
             const __grid_constant__ CUtensorMap tmWR, const __grid_constant__ CUtensorMap tmWI,
             const __grid_constant__ CUtensorMap tmGX, const __grid_constant__ CUtensorMap tmUX,
             const __grid_constant__ CUtensorMap tmGY, const __grid_constant__ CUtensorMap tmUY,
             const __grid_constant__ CUtensorMap tmD) {
  extern __shared__ __align__(1024) char smem_raw[];
  const uint32_t sbase = s2u(smem_raw);
  const uint32_t sbar = sbase + 14 * SLOT, sstat = sbar + 1408;
  const int tid = threadIdx.x, lane = tid & 31;
  const int c = blockIdx.x, rk = c & 1, f = (c >> 1) & 7, rb = 2 * (c >> 4) + rk;
  const int rb2 = 2 * (c >> 4) + (f >> 2), kh = (f >> 1) & 1, nq = 2 * (f & 1) + rk;
#define BAR(field, i) (sbar + (uint32_t)offsetof(Bars, field) + 8u * (i))
#define TOFF(field) (sbase + SM_T + (uint32_t)offsetof(Tables, field) + lane * 16)

  if (tid >= 256) {
    asm volatile("setmaxnreg.dec.sync.aligned.u32 40;");
    const int warp = __shfl_sync(0xffffffffu, tid >> 5, 0);
    if (lane == 0) {
      if (warp == 8) {
        if (sbase & 1023) die();
#pragma unroll
        for (int i = 0; i < 21; i++) mbar_init(BAR(emptyP, i), i < 9 ? 8 : i < 14 ? 1 : i < 16 ? 8 : i == 16 ? 32 : 16);
        mbar_expect(BAR(tbar, 0), T2_BYTES + 2 * 10240);
        mbar_expect(BAR(hbar, 0), 16384);
      } else if (warp == 9) {
#pragma unroll
        for (int i = 0; i < 32; i++) mbar_init(BAR(full1, i), 1);
#pragma unroll
        for (int i = 0; i < 32; i++) mbar_expect(BAR(full1, i), i < 16 ? 16384 : 12288);
      } else if (warp == 10) {
#pragma unroll
        for (int i = 0; i < 32; i++) mbar_init(BAR(empty1, i), 16);
#pragma unroll
        for (int i = 0; i < 30; i++) mbar_init(BAR(fullP, i), 1);
#pragma unroll
        for (int i = 0; i < 30; i++) mbar_expect(BAR(fullP, i), 8192);
      } else {
#pragma unroll
        for (int i = 0; i < 32; i++) mbar_init(BAR(full2, i), i < 24 ? 1 : 8);
#pragma unroll
        for (int i = 0; i < 24; i++) mbar_expect(BAR(full2, i), 16384);
      }
      asm volatile("fence.mbarrier_init.release.cluster;" ::: "memory");
    }
    if (tid == 256) {
      const int w0 = ((c >> 3) * 257 + 32 * (c & 7) + 1) & ~7;
      if (FILT_DELAY) {
        asm volatile("prefetch.tensormap [%0];" ::"l"(&tmWR) : "memory");
        asm volatile("prefetch.tensormap [%0];" ::"l"(&tmWI) : "memory");
        spin_until(clock32() + FILT_DELAY);
      }
      tma3(sbase + SM_W, &tmWR, BAR(tbar, 0), w0, 0, 0);
      tma3(sbase + SM_W + 10240, &tmWI, BAR(tbar, 0), w0, 0, 0);
      bulk_load(sbase + SM_T + T1_BYTES, reinterpret_cast<const char*>(tab) + T1_BYTES, T2_BYTES, BAR(tbar, 0));
    }
    if (tid == 288) {
      asm volatile("prefetch.tensormap [%0];" ::"l"(rk ? &tmUX : &tmGX) : "memory");
      asm volatile("prefetch.tensormap [%0];" ::"l"(rk ? &tmUY : &tmGY) : "memory");
      asm volatile("prefetch.tensormap [%0];" ::"l"(&tmD) : "memory");
    }
    if (tid == 320) {
      const unsigned e = ld_relaxed(&scr->cnt[(C_LN + rb) * 32]) >> 3;
      asm volatile("st.shared.u32 [%0], %1;" ::"r"(BAR(epoch, 0)), "r"(e) : "memory");
    }
    __syncwarp();
    asm volatile("barrier.cluster.arrive.relaxed.aligned;" ::: "memory");
    bar_arrive(NB_RDY, 384);
    asm volatile("barrier.cluster.wait.aligned;" ::: "memory");
    bar_sync(NB_INIT, 384);
    unsigned epoch;
    asm volatile("ld.shared.u32 %0, [%1];" : "=r"(epoch) : "r"(BAR(epoch, 0)) : "memory");
    if (warp == 8) {
      if (lane == 0) {
        const int ax = (7 * f + 3 * (f & 1)) >> 1;
        const int ay = 7 * f + ((f & 1) ? 0 : 4);
        const CUtensorMap* tx = rk ? &tmUX : &tmGX;
        const CUtensorMap* ty = rk ? &tmUY : &tmGY;
        if (RING_SIG >= 0) mbar_wait(BAR(sig, RING_SIG));
        uint32_t s = 2;
#pragma unroll 1
        for (int n = 0; n < 16; n++) {
          if (n >= 6) mbar_wait(BAR(empty1, n - 6));
          tma3_mc(sbase + (8 + s) * SLOT + rk * 8192, tx, BAR(full1, n), n * 32, ax);
          if (++s == 6) s = 0;
          if (n >= 10 && n < 15) {
            const int k = n - 10;
            mbar_wait(BAR(freeA, (12 * k + 11) >> 4));
            tma3_mc(sbase + k * 12288 + rk * 6144, ty, BAR(full1, 16 + k), (k + 8) * 32, ay);
          }
        }
#pragma unroll 1
        for (int k = 5; k < 16; k++) {
          mbar_wait(BAR(empty1, k < 13 ? 10 + ((12 * (k - 5) + 11) >> 4) : 8 + k));
          tma3_mc(sbase + 8 * SLOT + ((k - 5) & 7) * 12288 + rk * 6144, ty, BAR(full1, 16 + k), ((k + 8) & 15) * 32, ay);
        }
      }
    } else if (warp == 9) {
      if (lane == 0) {
        mbar_wait(BAR(fullA, 4));
        wait_counter(&scr->cnt[(C_LN + rb2) * 32], (epoch + 1) * 8);
        asm volatile("fence.proxy.async.global;" ::: "memory");
#pragma unroll 1
        for (int i = 0; i < 14; i++) {
          const int kblk = 14 * kh + (int)((KORDER >> (4 * i)) & 15);
          mbar_wait(i < 9 ? BAR(empty1, 16 + (uint32_t)((BDEP >> (4 * i)) & 15)) : BAR(empty2, i - 9));
          tma3(sbase + (uint32_t)((BSLOT >> (4 * i)) & 15) * SLOT, &tmD, BAR(full2, i), 0, 64 * kblk, 2 * nq);
        }
        mbar_wait(BAR(empty2, 5));
        bulk_load(sbase + 13 * SLOT, &scr->LN[(rb2 * 8 + 2 * nq) * 1024 + kh * 512], 8192, BAR(hbar, 0));
        bulk_load(sbase + 13 * SLOT + 8192, &scr->LN[(rb2 * 8 + 2 * nq + 1) * 1024 + kh * 512], 8192, BAR(hbar, 0));
      }
    } else if (warp == 10) {
      bar_sync(NB_LN, 288);
      if (lane == 0) {
        red_release(&scr->cnt[(C_LN + rb) * 32]);
        wait_counter(&scr->cnt[(C_LN + rb) * 32], (epoch + 1) * 8);
        asm volatile("fence.proxy.async.global;" ::: "memory");
#pragma unroll 1
        for (int kb = NLL; kb < 8; kb++) {
          if (2 * kb >= ALEAD) mbar_wait(BAR(empty1, 2 * kb - ALEAD));
          bulk_load(sbase + kb * SLOT, &scr->LN[(rb * 8 + kb) * 1024], 16384, BAR(fullA, kb));
        }
#pragma unroll 1
        for (int s = 0; s < 14; s++) {
          const int kblk = 14 * kh + (int)((KORDER >> (4 * s)) & 15);
          if (s == 0 || s == 8 || s == 11) {
            mbar_wait(BAR(hint, s == 0 ? 0 : s == 8 ? 1 : 2), 0);
          }
          mbar_wait(s < 5 ? BAR(empty1, 16 + (uint32_t)((PDEP >> (4 * s)) & 15)) : BAR(emptyP, s - 5));
          bulk_load_mc(sbase + (uint32_t)((PSLOT >> (4 * s)) & 15) * SLOT + rk * 8192, &scr->P[(rb2 * 28 + kblk) * 1024 + rk * 512], 8192, BAR(fullP, 16 * rk + s));
        }
      }
    } else {
      if (lane == 0) {
        mbar_wait(BAR(tbar, 0));
        l2_prefetch(wg_raw + (size_t)c * 5376, 5376);
        l2_prefetch(wu_raw + (size_t)c * 5376, 5376);
        mbar_wait(BAR(sig, PF2_SIG), 0);
        l2_prefetch(wg_raw + 688128 + (size_t)c * 8960, 8960);
        l2_prefetch(wu_raw + 688128 + (size_t)c * 8960, 8960);
      }
      mbar_wait(BAR(fullA, 4), 0);
      if (lane == 0) l2_prefetch(wd_raw + (size_t)c * 14336, 14336);
      {
        const uint32_t tag = (epoch + 1) & 1;
        uint4 v0, v1, v2;
        int it = 0;
        while (true) {
          v0 = ld_b128(&scr->ST[rb * 64 + lane]);
          v1 = ld_b128(&scr->ST[rb * 64 + 32 + lane]);
          v2 = ld_b128(&scr->ST[rb2 * 64 + 32 * kh + lane]);
          if (!__any_sync(0xffffffffu, ((v0.x ^ tag) | (v1.x ^ tag) | (v2.x ^ tag)) & 1u)) break;
          if (++it > SPIN_LIMIT) { die(); break; }
        }
        sts4(sstat + lane * 16, v0.x & ~1u, v0.y, v0.z, v0.w);
        sts4(sstat + 512 + lane * 16, v1.x & ~1u, v1.y, v1.z, v1.w);
        sts4(sstat + 1024 + lane * 16, v2.x & ~1u, v2.y, v2.z, v2.w);
        mbar_arrive(BAR(sbar, 0));
      }
      if (lane == 0) {
        mbar_wait(BAR(empty1, XTRIG));
        int it = 0;
        while ((int)(ld_relaxed(&scr->cnt[(C_PX + rb2) * 32 + kh]) - (epoch + 1) * 32) < 0) {
          if (++it > SPIN_LIMIT) { die(); break; }
        }
        mbar_arrive(BAR(hint, 0));
        mbar_wait(BAR(emptyP, HTRIG));
        uint32_t done = 0;
        while (done != 3) {
          uint2 v;
          asm volatile("ld.relaxed.gpu.global.v2.u32 {%0,%1}, [%2];" : "=r"(v.x), "=r"(v.y) : "l"(&scr->cnt[(C_PY + rb2) * 32 + 4 * (rk ^ kh ^ 1) + 2 * kh]) : "memory");
          if (!(done & 1) && (int)(v.x - (epoch + 1) * 8) >= 0) { done |= 1; mbar_arrive(BAR(hint, 1)); }
          if (!(done & 2) && (int)(v.y - (epoch + 1) * 8) >= 0) { done |= 2; mbar_arrive(BAR(hint, 2)); }
          if (++it > SPIN_LIMIT) { die(); break; }
        }
      }
    }
  } else {
    const int warp = __shfl_sync(0xffffffffu, tid >> 5, 0);
    const int g = lane >> 2, t = lane & 3;
    uint4 fa[4], fb[4], tw[6];
#pragma unroll
    for (int i = 0; i < 4; i++) fa[i] = ldg_ca4(&tab->fa[i][lane][0]);
#pragma unroll
    for (int i = 0; i < 6; i++) tw[i] = ldg_ca4(&tab->tw1[i][lane][0]);
#pragma unroll
    for (int i = 0; i < 4; i++) fb[i] = ldg_ca4(&tab->fb[i][lane][0]);
#pragma unroll
    for (int i = 0; i < 4; i++) {
      const int r = i >> 1, ch = (i & 1) * 32 + lane;
      cp_async16(sbase + SM_X + (2 * warp + r) * 1024 + ((ch ^ ((ch >> 3) & 1)) * 16),
                 x + (size_t)(c + 128 * (2 * warp + r)) * 512 + ch * 8);
    }
    asm volatile("cp.async.commit_group;" ::: "memory");
    asm volatile("barrier.cluster.arrive.relaxed.aligned;" ::: "memory");
    uint32_t rbar;
    asm volatile("mapa.shared::cluster.u32 %0, %1, %2;" : "=r"(rbar) : "r"(sbar), "r"(rk ^ 1));
#define RBAR(field, i) (rbar + (uint32_t)offsetof(Bars, field) + 8u * (i))
    {
      const int ln = (tid >> 1) & 31, lg = ln >> 2, lt = ln & 3, i = 4 * (tid >> 6) + 2 * (tid & 1);
      const int kidx = lt + 8 * (i >> 3), nidx = 4 * ((i >> 1) & 3) + (lg >> 1);
      const uint32_t a0 = cfrag<2048>((c + 128 * kidx) * nidx, lg & 1), a1 = cfrag<2048>((c + 128 * (kidx + 4)) * nidx, lg & 1);
      const uint32_t b0 = cfrag<2048>(-(c + 128 * nidx) * kidx, lg & 1), b1 = cfrag<2048>(-(c + 128 * nidx) * (kidx + 4), lg & 1);
      asm volatile("st.shared.v2.u32 [%0], {%1,%2};" ::"r"(sbase + SM_FC + tid * 8), "r"(a0), "r"(a1) : "memory");
      asm volatile("st.shared.v2.u32 [%0], {%1,%2};" ::"r"(sbase + SM_FC + 2048 + tid * 8), "r"(b0), "r"(b1) : "memory");
    }
    bar_sync(NB_CONS, 256);
    uint4 fc[4];
#pragma unroll
    for (int i = 0; i < 4; i++) fc[i] = lds4(sbase + SM_FC + i * 512 + lane * 16);
    asm volatile("cp.async.wait_group 0;" ::: "memory");
    __syncwarp();
    bar_arrive(NB_INIT, 384);
    uint32_t tag, ones;
    uint4 q[4], o[4];
    {
      uint32_t v[2][8];
#pragma unroll
      for (int r = 0; r < 2; r++)
#pragma unroll
        for (int ks = 0; ks < 2; ks++) {
          const int ch = 32 * ks + 2 * (lane & 15) + (lane >> 4);
          asm volatile("ldmatrix.sync.aligned.m8n8.x4.trans.shared.b16 {%0,%1,%2,%3}, [%4];"
                       : "=r"(v[r][4 * ks]), "=r"(v[r][4 * ks + 1]), "=r"(v[r][4 * ks + 2]), "=r"(v[r][4 * ks + 3])
                       : "r"(sbase + SM_X + (2 * warp + r) * 1024 + ((ch ^ ((ch >> 3) & 1)) * 16)) : "memory");
        }
      float sq[2];
#pragma unroll
      for (int r = 0; r < 2; r++) {
        float s0 = 0.f, s1 = 0.f;
#pragma unroll
        for (int i = 0; i < 8; i++) {
          const float lo = bf_lo(v[r][i]), hi = u2f(v[r][i] & 0xffff0000u);
          s0 = fmaf(lo, lo, s0);
          s1 = fmaf(hi, hi, s1);
        }
        sq[r] = s0 + s1;
      }
      {
        float w = ((lane & 1) ? sq[1] : sq[0]) + __shfl_xor_sync(0xffffffffu, (lane & 1) ? sq[0] : sq[1], 1);
        w += __shfl_xor_sync(0xffffffffu, w, 2);
        w = sum_groups(w);
        const float o2 = __shfl_xor_sync(0xffffffffu, w, 1);
        sq[0] = (lane & 1) ? o2 : w;
        sq[1] = (lane & 1) ? w : o2;
      }
#pragma unroll
      for (int r = 0; r < 2; r++) {
        float dd[2][4], ee[2][4];
#pragma unroll
        for (int nt = 0; nt < 2; nt++) {
          mma_az(dd[nt], fa[0], v[r][2 * nt], v[r][2 * nt + 1]);
          mma_a(dd[nt], fa[1], v[r][4 + 2 * nt], v[r][5 + 2 * nt]);
          mma_az(ee[nt], fa[2], v[r][2 * nt], v[r][2 * nt + 1]);
          mma_a(ee[nt], fa[3], v[r][4 + 2 * nt], v[r][5 + 2 * nt]);
        }
        float mean = (dd[0][0] + dd[0][1]) + (dd[1][0] + dd[1][1]);
        mean += __shfl_xor_sync(0xffffffffu, mean, 1);
        mean += __shfl_xor_sync(0xffffffffu, mean, 2);
        mean = __shfl_sync(0xffffffffu, mean, 0) * (1.f / 512.f);
        const float rs = rsqrtf(fmaxf(fmaf(-mean, mean, sq[r] * (1.f / 512.f)), 0.f) + 1e-5f);
        float acc[4][4];
#pragma unroll
        for (int nt = 0; nt < 2; nt++) {
          const float (&d)[4] = dd[nt];
          const float (&e)[4] = ee[nt];
          const uint4 &ka = tw[2 * nt], &kb = tw[2 * nt + 1], &kc = tw[4 + nt];
          const uint32_t a0 = pack2(d[0] * u2f(ka.x) + d[2] * u2f(ka.y), d[1] * u2f(kb.x) + d[3] * u2f(kb.y));
          const uint32_t a2 = pack2(d[0] * u2f(ka.z) + d[2] * u2f(ka.w), d[1] * u2f(kb.z) + d[3] * u2f(kb.w));
          const uint32_t a1 = pack2(e[0] * u2f(kc.x) + e[2] * u2f(kc.y), e[1] * u2f(kc.z) + e[3] * u2f(kc.w));
          const uint32_t a3 = pack2(e[2] * u2f(kc.x) - e[0] * u2f(kc.y), e[3] * u2f(kc.z) - e[1] * u2f(kc.w));
          const uint32_t dc = pack2(fmaf(mean, -32.f, d[0]), fmaf(mean, -32.f, d[1]));
          const uint32_t h0 = g == 0 ? dc : a0, h2 = g == 0 ? 0u : a2;
          if (nt == 0) {
            mma16816_z(acc[0], a0, a1, a2, a3, fb[2 * nt].x, fb[2 * nt].y);
            mma16816_z(acc[1], a0, a1, a2, a3, fb[2 * nt].z, fb[2 * nt].w);
            mma16816_z(acc[2], h0, a1, h2, a3, fb[2 * nt + 1].x, fb[2 * nt + 1].y);
            mma16816_z(acc[3], h0, a1, h2, a3, fb[2 * nt + 1].z, fb[2 * nt + 1].w);
          } else {
            mma16816(acc[0], a0, a1, a2, a3, fb[2 * nt].x, fb[2 * nt].y);
            mma16816(acc[1], a0, a1, a2, a3, fb[2 * nt].z, fb[2 * nt].w);
            mma16816(acc[2], h0, a1, h2, a3, fb[2 * nt + 1].x, fb[2 * nt + 1].y);
            mma16816(acc[3], h0, a1, h2, a3, fb[2 * nt + 1].z, fb[2 * nt + 1].w);
          }
        }
#pragma unroll
        for (int h = 0; h < 2; h++) {
          const int j = 2 * warp + r, m = 2 * t + h;
          sts4(sbase + SM_E + ((j * 8 + m) * 8 + (g ^ (2 * t) ^ (2 * (j & 3)))) * 16,
               pack2(acc[h][0] * rs, acc[h][1] * rs), pack2(acc[h][2] * rs, acc[h][3] * rs),
               pack2(acc[2 + h][0] * rs, acc[2 + h][1] * rs), pack2(acc[2 + h][2] * rs, acc[2 + h][3] * rs));
        }
      }
      bar_sync(NB_RDY, 384);
      const uint32_t ea = sbase + SM_E + ((t * 8 + warp) * 8 + (g ^ (warp & 6) ^ (2 * t))) * 16;
      lds_frag(q[0], q[1], ea, ea + 4096);
      lds_frag(q[2], q[3], ea + 8192, ea + 12288);
      asm volatile("ld.shared.u32 %0, [%1];" : "=r"(tag) : "r"(BAR(epoch, 0)) : "memory");
      ones = ~(tag >> 31);
      tag = (tag + 1) & 1;
      cdft16(q, fc, o);
#pragma unroll
      for (int vv = 0; vv < 4; vv++) {
        o[vv].y &= ~1u;
        o[vv].z = (o[vv].z & ~1u) | (tag ^ 1);
        st_tag(&scr->Z1[(((4 * vv + t) * 8 + warp) * 128 + c) * 8 + g], o[vv], tag);
      }
    }
    asm volatile("setmaxnreg.inc.sync.aligned.u32 232;");
    {
      uint4* const zp = &scr->Z1[(c * 128 + 8 * t + warp) * 8 + g];
      const uint32_t tst = clock32();
      mbar_wait(BAR(tbar, 0), 0);
      uint4 f2[4], g2[4];
#pragma unroll
      for (int i = 0; i < 4; i++) {
        f2[i] = lds4(TOFF(f2) + warp * 2048 + i * 512);
        g2[i] = lds4(TOFF(g2) + warp * 2048 + i * 512);
      }
      const uint4 f8 = lds4(TOFF(f8)), g8 = lds4(TOFF(g8));
      asm volatile("barrier.cluster.wait.aligned;" ::: "memory");
      spin_until(tst + POLL_DELAY);
      ld_tag4_issue<256>(q, zp);
      float wfr[16], wfi[16];
      {
        const float nyq = ((c & 7) == 7 && g == 0) ? 0.5f : 1.f;
        uint32_t wa = sbase + SM_W + (16 * warp + t) * 80 + ((2 * (c >> 3) + 2) & 15) - 2;
        asm volatile("" : "+r"(wa));
        const uint32_t wb[3] = {wa + 2 * (g == 0 ? 16 : g), wa + 2 * g, wa - 2 * g};
#pragma unroll
        for (int i = 0; i < 16; i++) {
          const int ci = i >> 3, dd = (i >> 2) & 1, e = i & 3;
          const uint32_t a = wb[e < 2 ? e : 2] + (ci * 8 + 4 * dd) * 80 + (e == 0 ? 0 : e == 1 ? 16 : e == 2 ? 64 : 48);
          wfr[i] = bf_lo(lds_u16(a)) * (e == 2 ? nyq : 1.f);
          wfi[i] = bf_lo(lds_u16(a + 10240)) * (e == 2 ? nyq : 1.f);
        }
      }
      ld_tag4_finish<256>(q, zp, tag);
      if (lane == 0) mbar_arrive(BAR(sig, 0));
#pragma unroll
      for (int i = 0; i < 4; i++) q[i].z &= ~1u;
      reg_frag(q, ones);
      cdft16(q, f2, o);
      const uint32_t e2 = sbase + SM_E2;
#pragma unroll
      for (int vv = 0; vv < 4; vv++)
        sts4(e2 + ((warp * 16 + 4 * vv + t) * 8 + (g ^ (2 * t) ^ (2 * (warp & 3)))) * 16, o[vv].x, o[vv].y, o[vv].z, o[vv].w);
      bar_sync(NB_CONS, 256);
      uint32_t ad[2], res[2][2][4];
#pragma unroll
      for (int ci = 0; ci < 2; ci++) {
        const int cc = 2 * warp + ci;
        ad[ci] = e2 + ((t * 16 + cc) * 8 + (g ^ (2 * (cc & 3)) ^ (2 * t))) * 16;
        lds_frag(q[2 * ci], q[2 * ci + 1], ad[ci], ad[ci] + 8192);
      }
#pragma unroll
      for (int ci = 0; ci < 2; ci++)
#pragma unroll
        for (int p = 0; p < 2; p++) {
          uint32_t y[2][2];
#pragma unroll
          for (int vv = 0; vv < 2; vv++) {
            float d[4];
            mma_az(d, q[2 * ci + p], word(f8, 2 * vv), word(f8, 2 * vv + 1));
#pragma unroll
            for (int rr = 0; rr < 2; rr++) {
              const float fr = wfr[ci * 8 + vv * 4 + 2 * p + rr], fi = wfi[ci * 8 + vv * 4 + 2 * p + rr];
              y[vv][rr] = pack2(d[2 * rr] * fr - d[2 * rr + 1] * fi, d[2 * rr] * fi + d[2 * rr + 1] * fr);
            }
          }
#pragma unroll
          for (int vv = 0; vv < 2; vv++) {
            float d[4];
            mma16816_z(d, y[0][0], y[0][1], y[1][0], y[1][1], word(g8, 2 * vv), word(g8, 2 * vv + 1));
            res[ci][vv][2 * p] = pack2(d[0], d[1]);
            res[ci][vv][2 * p + 1] = pack2(d[2], d[3]);
          }
        }
#pragma unroll
      for (int i = 0; i < 4; i++)
        sts4(ad[i >> 1] + (i & 1) * 8192, res[i >> 1][i & 1][0], res[i >> 1][i & 1][1], res[i >> 1][i & 1][2], res[i >> 1][i & 1][3]);
      bar_sync(NB_CONS, 256);
      const uint32_t eb = e2 + ((warp * 16 + t) * 8 + (g ^ (2 * t) ^ (2 * (warp & 3)))) * 16;
      lds_frag(q[0], q[1], eb, eb + 512);
      lds_frag(q[2], q[3], eb + 1024, eb + 1536);
      cdft16(q, g2, o);
#pragma unroll
      for (int vv = 0; vv < 4; vv++) {
        o[vv].y &= ~1u;
        o[vv].z = (o[vv].z & ~1u) | tag;
        st_tag(zp + vv * 256, o[vv], tag);
      }
    }
    {
      const uint4* const zp = &scr->Z1[((t * 8 + warp) * 128 + c) * 8 + g];
      const uint32_t tst = clock32();
      uint4 gb[4], ga[4], gc[4], tw[4];
      uint2 xr[2][4];
      uint2* lnp[2];
#pragma unroll
      for (int r = 0; r < 2; r++) {
        const int row = 16 * f + 2 * warp + r;
        lnp[r] = reinterpret_cast<uint2*>(&scr->LN[(rb * 8 + (g >> 2)) * 1024 + row * 8 + ((2 * (g & 3) + (t >> 1)) ^ (row & 7))]) + (t & 1);
        asm volatile("" : "+l"(lnp[r]));
      }
#pragma unroll
      for (int i = 0; i < 4; i++) {
        gc[i] = lds4(sbase + SM_FC + 2048 + i * 512 + lane * 16);
        gb[i] = lds4(TOFF(gb) + i * 512);
        ga[i] = lds4(TOFF(ga) + i * 512);
        tw[i] = lds4(TOFF(tw3) + i * 512);
        const int ch = 2 * (g + 8 * i) + (t >> 1);
#pragma unroll
        for (int r = 0; r < 2; r++) xr[r][i] = lds2(sbase + SM_X + (2 * warp + r) * 1024 + ((ch ^ ((ch >> 3) & 1)) * 16) + (t & 1) * 8);
      }
      spin_until(tst + POLL_DELAY2);
      ld_tag4_issue<32768>(q, zp);
      ld_tag4_finish<32768, true>(q, zp, tag);
      if (lane == 0) mbar_arrive(BAR(sig, 1));
      reg_frag(q, ones);
      cdft16(q, gc, o);
#pragma unroll
      for (int vv = 0; vv < 4; vv++)
        sts4(sbase + SM_E + (((4 * vv + t) * 8 + warp) * 8 + (g ^ (warp & 6) ^ (2 * t))) * 16, o[vv].x, o[vv].y, o[vv].z, o[vv].w);
      bar_sync(NB_CONS, 256);
      uint32_t hv[2][8];
      const float mk = t == 0 ? 0.f : 1.f;
#pragma unroll
      for (int r = 0; r < 2; r++) {
        const int j = 2 * warp + r;
        uint4 u[2];
#pragma unroll
        for (int h = 0; h < 2; h++) u[h] = lds4(sbase + SM_E + ((j * 8 + 2 * t + h) * 8 + (g ^ (2 * t) ^ (2 * (j & 3)))) * 16);
        const uint32_t bp[4][2] = {{u[0].x, u[1].x & ones}, {u[0].y & ones, u[1].y}, {u[0].z, u[1].z & ones}, {u[0].w & ones, u[1].w}};
        float y[2][2][4];
#pragma unroll
        for (int i = 0; i < 2; i++) {
          float lo[4], hi[4], e[4];
          mma_az(lo, gb[2 * i], bp[0][0], bp[0][1]);
          mma_az(hi, gb[2 * i + 1], bp[2][0], bp[2][1]);
          mma_az(e, gb[2 * i], bp[1][0], bp[1][1]);
          mma_a(e, gb[2 * i + 1], bp[3][0], bp[3][1]);
          const uint4 &ka = tw[2 * i], &kb = tw[2 * i + 1];
          const float tr0 = fmaf(hi[0], mk, lo[0]), ti0 = fmaf(hi[2], mk, lo[2]);
          const float tr1 = lo[1] + hi[1], ti1 = lo[3] + hi[3];
          const float vr0 = tr0 * u2f(ka.x) - ti0 * u2f(ka.y), vi0 = tr0 * u2f(ka.y) + ti0 * u2f(ka.x);
          const float vr1 = tr1 * u2f(ka.z) - ti1 * u2f(ka.w), vi1 = tr1 * u2f(ka.w) + ti1 * u2f(ka.z);
          const uint32_t b0 = pack2(t == 0 ? hi[0] : vr0, vr1), b1 = pack2(t == 0 ? vr0 : vi0, vi1);
          const uint32_t b2 = pack2(e[0] * u2f(kb.x) - e[2] * u2f(kb.y), e[1] * u2f(kb.z) - e[3] * u2f(kb.w));
          const uint32_t b3 = pack2(e[0] * u2f(kb.y) + e[2] * u2f(kb.x), e[1] * u2f(kb.w) + e[3] * u2f(kb.z));
#pragma unroll
          for (int mt = 0; mt < 2; mt++) {
            mma_az(y[mt][i], ga[2 * mt], b0, b1);
            mma_a(y[mt][i], ga[2 * mt + 1], b2, b3);
          }
        }
#pragma unroll
        for (int i = 0; i < 4; i++) {
          hv[r][2 * i] = hadd2_bf16(xr[r][i].x, pack2(y[i >> 1][0][2 * (i & 1)], y[i >> 1][0][2 * (i & 1) + 1]));
          hv[r][2 * i + 1] = hadd2_bf16(xr[r][i].y, pack2(y[i >> 1][1][2 * (i & 1)], y[i >> 1][1][2 * (i & 1) + 1]));
        }
      }
      float mean[2];
      uint32_t mb[2];
#pragma unroll
      for (int r = 0; r < 2; r++) {
        mean[r] = sum_groups(quad_sum(hv[r])) * (1.f / 512.f);
        mb[r] = pack2(mean[r], mean[r]);
      }
#pragma unroll
      for (int i = 0; i < 4; i++)
#pragma unroll
        for (int r = 0; r < 2; r++) {
          hv[r][2 * i] = hsub2_bf16(hv[r][2 * i], mb[r]);
          hv[r][2 * i + 1] = hsub2_bf16(hv[r][2 * i + 1], mb[r]);
          st_tag8(lnp[r] + i * 4096, hv[r][2 * i], hv[r][2 * i + 1], i == 0 ? tag : (hv[r][2 * i] & 1u));
        }
      bar_arrive(NB_LN, 288);
      const uint32_t ones2 = ~(lds2(BAR(epoch, 0)).x >> 31);
      float rstd[2];
#pragma unroll
      for (int r = 0; r < 2; r++) {
        hv[r][0] &= ones2;
        rstd[r] = row_rstd(hv[r], mean[r] - bf_lo(mb[r]));
      }
      if (lane == 0)
        st_tag(&scr->ST[rb * 64 + 8 * f + warp], make_uint4(mb[0] << 16, __float_as_uint(rstd[0]), mb[1] << 16, __float_as_uint(rstd[1])), tag);
    }
    const int wgi = warp >> 2, wq = warp & 3;
    const int wr = wgi ^ (f >> 2) ^ 1, rt = 4 * wr + wq;
    uint4* const pbase = &scr->P[rb * 28 * 1024 + rt * 128 + lane];
    const uint32_t a_lo0 = desc_lo(sbase + wr * 8192, 16);
    const uint32_t ebar = lane == 0 ? BAR(empty1, 0) : RBAR(empty1, 0);
    float r0, r1;
    uint4 px[8], py[6];
    const int rh = wgi ^ kh ^ 1;
    const uint32_t fpb = BAR(fullP, 16 * rh);
    const uint4* const psrc = &scr->P[(rb2 * 28 + 14 * kh) * 1024 + (4 * rh + wq) * 128 + lane];
    const uint32_t pa0 = sbase + (4 * rh + wq) * 2048;
    uint4 pf[3][4], ha[4][4];
    uint32_t rdy = 0, got0;
    {
      float acc[128];
#pragma unroll
      for (int i = 0; i < 128; i++) acc[i] = 0.f;
      const uint32_t b_lo0 = desc_lo(sbase + 8 * SLOT, 4096);
      const uint32_t t3 = clock32();
      if (WARM) {
        wg_fence();
#pragma unroll
        for (int i = 0; i < WARM; i++) wgmma_n256(acc, desc64(a_lo0 + 6 * 1024, HI128), desc64(b_lo0, HI128));
        wg_commit();
      }
      const uint4* const ap = &scr->LN[rb * 8 * 1024 + wr * 512 + (tid & 127)];
      uint4 av[NLL][4];
      spin_until(t3 + POLL_DELAY3);
#pragma unroll
      for (int kb = 0; kb < NLL; kb++) ld_tag4_issue<128>(av[kb], ap + kb * 1024);
      bar_sync(NB_CONS, 256);
      const uint32_t lma = sbase + (16 * rt + (lane & 15)) * 128;
      auto load_a = [&](int kb) {
#pragma unroll
        for (int ks = 0; ks < 4; ks++)
          asm volatile("ldmatrix.sync.aligned.m8n8.x4.shared.b16 {%0,%1,%2,%3}, [%4];"
                       : "=r"(ha[kb][ks].x), "=r"(ha[kb][ks].y), "=r"(ha[kb][ks].z), "=r"(ha[kb][ks].w)
                       : "r"(lma + kb * SLOT + (((2 * ks + (lane >> 4)) ^ (lane & 7)) * 16)) : "memory");
      };
      auto stash_a = [&](int kb) {
        ld_tag4_finish<128, true>(av[kb], ap + kb * 1024, tag);
#pragma unroll
        for (int i = 0; i < 4; i++)
          sts4(sbase + kb * SLOT + wr * 8192 + ((tid & 127) + 128 * i) * 16, av[kb][i].x, av[kb][i].y, av[kb][i].z, av[kb][i].w);
        bar_sync(NB_WG + wgi, 128);
      };
      stash_a(0);
      load_a(0);
#pragma unroll
      for (int n = 0; n < 8; n++) {
        const int kb = n >> 1, hh = n & 1;
        if (hh == 1 && kb < 3) {
          if (kb + 1 < NLL) stash_a(kb + 1); else mbar_wait(BAR(fullA, kb + 1));
        }
        mbar_wait(BAR(full1, n));
        const uint32_t bl = b_lo0 + ((n + 2) % 6) * 1024;
        wg_fence();
        if (hh == 1 && kb < 3) load_a(kb + 1);
        const uint4 &a0 = ha[kb][2 * hh], &a1 = ha[kb][2 * hh + 1];
        wgmma_rs_n256(acc, a0.x, a0.y, a0.z, a0.w, desc64(bl, HI128), n != 0 ? 1 : ~ones);
        wgmma_rs_n256(acc, a1.x, a1.y, a1.z, a1.w, desc64(bl + 128, HI128));
        wg_commit();
        if (hh == 1 && lane < 2) mbar_arrive_remote(ebar + (uint32_t)(offsetof(Bars, freeA) - offsetof(Bars, empty1)) + 8 * kb);
        wg_wait<1>();
        if (n != 0 && lane < 2) mbar_arrive_remote(ebar + 8 * (n - 1));
      }
      uint32_t slot = 4;
#pragma unroll 1
      for (int kb = 4; kb < 8; kb++) {
        mbar_wait(BAR(fullA, kb));
#pragma unroll
        for (int hh = 0; hh < 2; hh++) {
          if (LAGX && hh == ((16 - LAGX) & 1) && kb == ((16 - LAGX) >> 1) && wgi == 1) bar_sync(NB_LAG, 256);
          mbar_wait(BAR(full1, 2 * kb + hh));
          const uint32_t al = a_lo0 + kb * 1024 + hh * 4, bl = b_lo0 + slot * 1024;
          wg_fence();
          wgmma_n256(acc, desc64(al, HI128), desc64(bl, HI128));
          wgmma_n256(acc, desc64(al + 2, HI128), desc64(bl + 128, HI128));
          wg_commit();
          if (LAGX && hh == 1 && kb == 7 && wgi == 0) bar_arrive(NB_LAG, 256);
          wg_wait<1>();
          if (lane < 2) mbar_arrive_remote(ebar + 8 * (2 * kb + hh - 1));
          if (++slot == 6) slot = 0;
        }
      }
      mbar_wait(BAR(sbar, 0), 0);
      r0 = __uint_as_float(lds2(sstat + (16 * rt + g) * 8).y);
      r1 = __uint_as_float(lds2(sstat + (16 * rt + g + 8) * 8).y);
      wg_wait<0>();
      if (lane < 2) mbar_arrive_remote(ebar + 8 * 15);
      make_p<8, false>(acc, r0, r1, px, pbase, 0, tag);
    }
    {
      float acc[96];
#pragma unroll
      for (int i = 0; i < 96; i++) acc[i] = 0.f;
      const uint32_t b_lo0 = desc_lo(sbase, 2048);
      uint4* const pdst = pbase + ((7 * f + 3 * (f & 1)) >> 1) * 1024;
      auto stage_y = [&](int k) {
        if (LAGY && k == 16 - LAGY && wgi == 1) bar_sync(NB_LAG, 256);
        mbar_wait(BAR(full1, 16 + k));
        const uint32_t al = a_lo0 + (4 + (k >> 1)) * 1024 + (k & 1) * 4, bl = b_lo0 + (k < 5 ? k * 768 : 8192 + (k - 5) * 768);
        wg_fence();
        wgmma_n192(acc, desc64(al, HI128), desc64(bl, HI64));
        wgmma_n192(acc, desc64(al + 2, HI128), desc64(bl + 64, HI64));
        wg_commit();
      };
#pragma unroll
      for (int k = 0; k < 4; k++) {
        stage_y(k);
        st_tag(pdst + (k >> 1) * 1024 + (k & 1) * 64, px[2 * k], tag);
        st_tag(pdst + (k >> 1) * 1024 + (k & 1) * 64 + 32, px[2 * k + 1], tag);
        if (k == 3 && lane == 0) red_relaxed(&scr->cnt[(C_PX + rb) * 32 + (f >> 2)]);
        wg_wait<1>();
        if (k != 0 && lane < 2) mbar_arrive_remote(ebar + 8 * (15 + k));
      }
#pragma unroll 1
      for (int k = 4; k < 8; k++) {
        stage_y(k);
        wg_wait<1>();
        if (lane < 2) mbar_arrive_remote(ebar + 8 * (15 + k));
      }
      rdy = 0;
#pragma unroll
      for (int k = 8; k < 16; k++) {
        if (LAGY && k == 16 - LAGY && wgi == 1) bar_sync(NB_LAG, 256);
        if (!rdy) mbar_wait(BAR(full1, 16 + k));
        const uint32_t bl = b_lo0 + 8192 + ((k - 5) & 7) * 768;
        const uint4 &a0 = ha[(k - 8) >> 1][2 * (k & 1)], &a1 = ha[(k - 8) >> 1][2 * (k & 1) + 1];
        wg_fence();
        if (k < 15) rdy = mbar_test(BAR(full1, 17 + k));
        wgmma_rs_n192(acc, a0.x, a0.y, a0.z, a0.w, desc64(bl, HI64));
        wgmma_rs_n192(acc, a1.x, a1.y, a1.z, a1.w, desc64(bl + 64, HI64));
        wg_commit();
        if (LAGY && k == 15 && wgi == 0) bar_arrive(NB_LAG, 256);
        wg_wait<1>();
        if (lane < 2) mbar_arrive_remote(ebar + 8 * (15 + k));
      }
      got0 = __all_sync(0xffffffffu, mbar_test((fpb + 8 * (0))));
      if (got0) {
#pragma unroll
        for (int kk = 0; kk < 4; kk++) pf[0][kk] = lds4(pa0 + 3 * SLOT + kk * 512 + lane * 16);
      }
      wg_wait<0>();
      if (lane < 2) mbar_arrive_remote(ebar + 8 * 31);
      const int ks0 = 14 * f + ((f & 1) ? 0 : 8);
      auto reread = [&]() {
        asm volatile("ld.volatile.shared.f32 %0, [%2+4]; ld.volatile.shared.f32 %1, [%2+68];" : "=f"(r0), "=f"(r1) : "r"(sstat + (16 * rt + g) * 8) : "memory");
      };
      make_p<6, true, 0, 2>(acc, r0, r1, py, pbase, ks0, tag);
      if (REDPOS == 2 && lane == 0) red_relaxed(&scr->cnt[(C_PY + rb) * 32 + 4 * wgi + (f >> 1)]);
      reread();
      make_p<6, true, 2, 4>(acc, r0, r1, py, pbase, ks0, tag);
      if (REDPOS == 4 && lane == 0) red_relaxed(&scr->cnt[(C_PY + rb) * 32 + 4 * wgi + (f >> 1)]);
      reread();
      rdy = mbar_test(BAR(full2, 0)) & mbar_test((fpb + 8 * (1)));
      make_p<6, true, 4, 6>(acc, r0, r1, py, pbase, ks0, tag);
      if (REDPOS == 6 && lane == 0) red_relaxed(&scr->cnt[(C_PY + rb) * 32 + 4 * wgi + (f >> 1)]);
    }
    {
      float acc[64];
      const uint32_t b2_lo0 = desc_lo(sbase, 8192);
      const uint32_t pbar = rh == rk ? BAR(emptyP, 0) : RBAR(emptyP, 0);
      if (!got0) {
        mbar_wait((fpb + 8 * (0)));
#pragma unroll
        for (int kk = 0; kk < 4; kk++) pf[0][kk] = lds4(pa0 + 3 * SLOT + kk * 512 + lane * 16);
      }
#pragma unroll
      for (int s = 0; s < 14; s++) {
        uint4 (&a)[4] = pf[s % 3];
        ld_tag4_finish<32>(a, psrc + (int)((KORDER >> (4 * s)) & 15) * 1024, tag);
        if (s < 9 && lane == 0) mbar_arrive_remote(pbar + 8 * s);
        if (s >= 2) {
          wg_wait<1>();
          if (s <= 7 && lane == 0) mbar_arrive(BAR(empty2, s - 2));
        }
        if (!rdy) {
          if (s < 13) mbar_wait((fpb + 8 * (s + 1)));
          mbar_wait(BAR(full2, s));
        }
        if (s == 14 - LAG2 && wgi == 1) bar_sync(NB_LAG, 256);
        const uint32_t bl = b2_lo0 + (uint32_t)((BSLOT >> (4 * s)) & 15) * 1024;
        wg_fence();
        if (s < 13) {
#pragma unroll
          for (int kk = 0; kk < 4; kk++)
            pf[(s + 1) % 3][kk] = lds4(pa0 + (uint32_t)((PSLOT >> (4 * (s + 1))) & 15) * SLOT + kk * 512 + lane * 16);
          rdy = mbar_test(BAR(full2, s + 1));
          if (s < 12) rdy &= mbar_test((fpb + 8 * (s + 2)));
        }
        if (s == 0) wgmma_rs_n128(acc, a[0].x, a[0].y, a[0].z, a[0].w, desc64(bl, HI128), 0);
        else wgmma_rs_n128(acc, a[0].x, a[0].y, a[0].z, a[0].w, desc64(bl, HI128));
#pragma unroll
        for (int kk = 1; kk < 4; kk++) wgmma_rs_n128(acc, a[kk].x, a[kk].y, a[kk].z, a[kk].w, desc64(bl + kk * 128, HI128));
        wg_commit();
      }
      if (wgi == 0) {
        bar_arrive(NB_LAG, 256);
        uint4* const dst = &scr->Z1[(tid >> 3) * 1024 + (c ^ 4) * 8 + (tid & 7)];
        wg_wait<0>();
#pragma unroll
        for (int i = 0; i < 8; i++)
          st_tag(dst + i * 16384, make_uint4(pack2(acc[8 * i], acc[8 * i + 1]), pack2(acc[8 * i + 2], acc[8 * i + 3]) | 1u,
                                           pack2(acc[8 * i + 4], acc[8 * i + 5]), pack2(acc[8 * i + 6], acc[8 * i + 7])), tag);
      } else {
        uint4 pv[2][4];
        const uint4* const xsrc = &scr->Z1[((tid & 127) >> 3) * 1024 + c * 8 + (tid & 7)];
        ld_tag4_issue<16384>(pv[0], xsrc);
        ld_tag4_issue<16384>(pv[1], xsrc + 65536);
        uint32_t w[32];
        {
          const uint32_t m0 = __byte_perm(lds2(sstat + 1024 + (16 * wq + g) * 8).x, 0, 0x3232);
          const uint32_t m1 = __byte_perm(lds2(sstat + 1024 + (16 * wq + g + 8) * 8).x, 0, 0x3232);
          const uint32_t hb = sbase + 13 * SLOT + (16 * wq + (lane & 15)) * 128;
          const uint32_t mk = ((t & 1) == 0 && nq == 0) ? ~1u : ~0u;
          mbar_wait(BAR(hbar, 0));
#pragma unroll
          for (int i = 0; i < 8; i++) {
            asm volatile("ldmatrix.sync.aligned.m8n8.x4.shared.b16 {%0,%1,%2,%3}, [%4];"
                         : "=r"(w[4 * i]), "=r"(w[4 * i + 1]), "=r"(w[4 * i + 2]), "=r"(w[4 * i + 3])
                         : "r"(hb + (i >> 2) * 8192 + (((2 * (i & 3) + (lane >> 4)) ^ (lane & 7)) * 16)) : "memory");
#pragma unroll
            for (int e = 0; e < 4; e++) w[4 * i + e] = hadd2_bf16(w[4 * i + e] & mk, (e & 1) ? m1 : m0);
          }
        }
        wg_wait<0>();
#pragma unroll
        for (int i = 0; i < 32; i++) w[i] = hadd2_bf16(w[i], pack2(acc[2 * i], acc[2 * i + 1]));
        int it = 0;
#pragma unroll 1
        while (!__all_sync(0xffffffffu, pv[0][0].y & pv[0][1].y & pv[0][2].y & pv[0][3].y & pv[1][0].y & pv[1][1].y & pv[1][2].y & pv[1][3].y & 1u)) {
          ld_tag4_issue<16384>(pv[0], xsrc);
          ld_tag4_issue<16384>(pv[1], xsrc + 65536);
          if (++it > SPIN_LIMIT) { die(); break; }
        }
#pragma unroll
        for (int i = 0; i < 8; i++) {
          const uint4& p = pv[i >> 2][i & 3];
          asm volatile("stmatrix.sync.aligned.m8n8.x4.shared.b16 [%0], {%1,%2,%3,%4};"
                       ::"r"(pa0 + (11 + ((lane >> 3) & 1)) * SLOT + (lane & 7) * 256 + (((2 * i + (lane >> 4)) ^ (lane & 7)) * 16)),
                         "r"(hadd2_bf16(w[4 * i], p.x & ~1u)), "r"(hadd2_bf16(w[4 * i + 1], p.y & ~1u)), "r"(hadd2_bf16(w[4 * i + 2], p.z)),
                         "r"(hadd2_bf16(w[4 * i + 3], p.w)) : "memory");
        }
        __syncwarp();
        uint4* const dst = reinterpret_cast<uint4*>(out) + (16 * (c >> 4) + 2 * (4 * rh + wq) + (rb2 & 1) + 128 * (lane >> 4)) * 64 + nq * 16 + (lane & 15);
#pragma unroll
        for (int i = 0; i < 8; i++) {
          const int r = 2 * (i & 3) + (lane >> 4);
          dst[i * 256 * 64] = lds4(pa0 + (11 + (i >> 2)) * SLOT + r * 256 + (((lane & 15) ^ r) * 16));
        }
      }
    }
  }
#undef BAR
#undef TOFF
#undef RBAR
}

typedef CUresult (*EncodeFn)(CUtensorMap*, CUtensorMapDataType, cuuint32_t, void*, const cuuint64_t*, const cuuint64_t*,
                             const cuuint32_t*, const cuuint32_t*, CUtensorMapInterleave, CUtensorMapSwizzle,
                             CUtensorMapL2promotion, CUtensorMapFloatOOBfill);

}

extern "C" void kernel_launch(void* const* d_in, const int* in_sizes, int n_in, void* d_out, int out_size) {
  (void)in_sizes; (void)n_in; (void)out_size;
  static EncodeFn encode = nullptr;
  static void *tab = nullptr, *scr = nullptr;
  if (!encode) {
    void* fn = nullptr;
    cudaDriverEntryPointQueryResult qr;
    cudaGetDriverEntryPoint("cuTensorMapEncodeTiled", &fn, cudaEnableDefault, &qr);
    encode = (EncodeFn)fn;
    cudaGetSymbolAddress(&tab, g_tab);
    cudaGetSymbolAddress(&scr, g_scr);
    cudaFuncSetAttribute(fused_kernel, cudaFuncAttributeMaxDynamicSharedMemorySize, SMEM_BYTES);
  }
  CUtensorMap tmGX, tmUX, tmGY, tmUY, tmD, tmWR, tmWI;
  const cuuint32_t es[5] = {1, 1, 1, 1, 1};
  auto enc = [&](CUtensorMap* m, void* p, int rank, const cuuint64_t* gd, const cuuint64_t* gs, const cuuint32_t* bd,
                 CUtensorMapSwizzle sw, CUtensorMapL2promotion pr) {
    encode(m, CU_TENSOR_MAP_DATA_TYPE_BFLOAT16, rank, p, gd, gs, bd, es, CU_TENSOR_MAP_INTERLEAVE_NONE, sw, pr,
           CU_TENSOR_MAP_FLOAT_OOB_FILL_NONE);
  };
  {
    const cuuint64_t gd[3] = {64, 512, 28}, gs[2] = {3584, 128};
    const cuuint32_t bd[3] = {64, 32, 2};
    enc(&tmGX, d_in[4], 3, gd, gs, bd, CU_TENSOR_MAP_SWIZZLE_128B, CU_TENSOR_MAP_L2_PROMOTION_L2_256B);
    enc(&tmUX, d_in[5], 3, gd, gs, bd, CU_TENSOR_MAP_SWIZZLE_128B, CU_TENSOR_MAP_L2_PROMOTION_L2_256B);
  }
  {
    const cuuint64_t gd[3] = {32, 512, 56}, gs[2] = {3584, 64};
    const cuuint32_t bd[3] = {32, 32, 3};
    enc(&tmGY, d_in[4], 3, gd, gs, bd, CU_TENSOR_MAP_SWIZZLE_64B, CU_TENSOR_MAP_L2_PROMOTION_L2_128B);
    enc(&tmUY, d_in[5], 3, gd, gs, bd, CU_TENSOR_MAP_SWIZZLE_64B, CU_TENSOR_MAP_L2_PROMOTION_L2_128B);
  }
  {
    const cuuint64_t gd[3] = {64, 1792, 8}, gs[2] = {1024, 128};
    const cuuint32_t bd[3] = {64, 64, 2};
    enc(&tmD, d_in[6], 3, gd, gs, bd, CU_TENSOR_MAP_SWIZZLE_128B, CU_TENSOR_MAP_L2_PROMOTION_L2_256B);
  }
  {
    const cuuint64_t gd[3] = {4112, 8, 16}, gs[2] = {16 * 8224, 8224};
    const cuuint32_t bd[3] = {40, 8, 16};
    enc(&tmWR, d_in[1], 3, gd, gs, bd, CU_TENSOR_MAP_SWIZZLE_NONE, CU_TENSOR_MAP_L2_PROMOTION_NONE);
    enc(&tmWI, d_in[2], 3, gd, gs, bd, CU_TENSOR_MAP_SWIZZLE_NONE, CU_TENSOR_MAP_L2_PROMOTION_NONE);
  }
  fused_kernel<<<NCTA, NTHREADS, SMEM_BYTES>>>((const __nv_bfloat16*)d_in[0], (const Tables*)tab, (Scratch*)scr,
                                               (__nv_bfloat16*)d_out, (const char*)d_in[4], (const char*)d_in[5],
                                               (const char*)d_in[6], tmWR, tmWI, tmGX, tmUX, tmGY, tmUY, tmD);
}
```

```cpp
#include <cuda_runtime.h>
#include <cuda_bf16.h>
#include <cuda.h>
#include <stdint.h>

namespace {

constexpr int NCTA = 128;
constexpr int NTHREADS = 384;
constexpr int SLOT = 16384;
constexpr int SMEM_BYTES = 14 * SLOT + 3072;
constexpr int SPIN_LIMIT = 1 << 22;

struct Scratch {
  uint4 Z1[128 * 1024];
  uint4 LN[16 * 8 * 1024];
  uint4 P[16 * 28 * 1024];
  uint4 ST[1024];
  unsigned cnt[64 * 32];
};
__device__ __align__(1024) Scratch g_scr;

constexpr double ccos(int i, int n) {
  i &= n - 1;
  if (i > n / 2) i = n - i;
  if (4 * i == n) return 0.0;
  const bool neg = 4 * i > n;
  if (neg) i = n / 2 - i;
  const double a = 6.283185307179586476925 * i / n, a2 = a * a;
  double term = 1.0, sum = 1.0;
  for (int k = 1; k < 14; k++) { term *= -a2 / ((2 * k - 1) * (2 * k)); sum += term; }
  return neg ? -sum : sum;
}
constexpr double csin(int i, int n) { return ccos(i - n / 4, n); }
constexpr unsigned fbits(double v, int mant) {
  if (v == 0.0) return 0;
  const unsigned sg = v < 0 ? 1u : 0u;
  if (v < 0) v = -v;
  int e = 127;
  while (v < 1.0) { v *= 2.0; e--; }
  const unsigned m = (unsigned)((v - 1.0) * (double)(1u << mant) + 0.5);
  return (sg << (8 + mant)) + ((unsigned)e << mant) + m;
}
constexpr unsigned pkb(double lo, double hi) { return fbits(lo, 7) | (fbits(hi, 7) << 16); }
constexpr double fa_elem(int mt, int r, int n1) {
  const int k1 = 8 * mt + (r & 7);
  return r < 8 ? ccos(k1 * n1, 32) : k1 == 0 ? ccos(16 * n1, 32) : -csin(k1 * n1, 32);
}
constexpr unsigned cfrag_c(int idx, int n, int ri, double s = 1.0) {
  return ri ? pkb(-s * csin(idx, n), s * ccos(idx, n)) : pkb(s * ccos(idx, n), s * csin(idx, n));
}
struct Tables {
  unsigned fa[4][32][4];
  unsigned fb[4][32][4];
  unsigned tw1[6][32][4];
  unsigned f2[8][4][32][4];
  unsigned g2[8][4][32][4];
  unsigned gb[4][32][4];
  unsigned ga[4][32][4];
  unsigned tw3[4][32][4];
  unsigned f8[32][4], g8[32][4];
};
constexpr int T1_BYTES = 7168, T2_BYTES = 39936;
static_assert(sizeof(Tables) == T1_BYTES + T2_BYTES, "table size");
constexpr Tables make_tables() {
  Tables T = {};
  for (int l = 0; l < 32; l++) {
    const int g = l >> 2, t = l & 3;
    for (int a = 0; a < 2; a++)
      for (int b = 0; b < 2; b++) {
        for (int r = 0; r < 4; r++) {
          const int row = g + 8 * (r & 1), col = 2 * t + 8 * (r >> 1);
          T.fa[2 * a + b][l][r] = pkb(fa_elem(a, row, 16 * b + col), fa_elem(a, row, 16 * b + col + 1));
          T.ga[2 * a + b][l][r] = pkb(fa_elem(b, col, 16 * a + row), fa_elem(b, col + 1, 16 * a + row));
        }
        const double sg = b ? -1.0 : 1.0;
        for (int h = 0; h < 2; h++) {
          const int ri = g & 1, m = 2 * (g >> 1) + h, k2 = b ? 15 - m : m;
          const int pa = (8 * a + 2 * t) * k2, pb = (8 * a + 2 * t + 1) * k2;
          T.fb[2 * a + b][l][2 * h] = ri == 0 ? pkb(ccos(pa, 16), ccos(pb, 16)) : pkb(-sg * csin(pa, 16), -sg * csin(pb, 16));
          T.fb[2 * a + b][l][2 * h + 1] = ri == 0 ? pkb(csin(pa, 16), csin(pb, 16)) : pkb(sg * ccos(pa, 16), sg * ccos(pb, 16));
        }
        const int n2 = 4 * (g >> 1) + 2 * a + (g & 1);
        for (int h = 0; h < 2; h++) {
          const int p = n2 * (b ? 15 - 2 * t - h : 2 * t + h);
          T.gb[2 * a + b][l][2 * h] = pkb(ccos(p, 16), -sg * csin(p, 16));
          T.gb[2 * a + b][l][2 * h + 1] = pkb(csin(p, 16), sg * ccos(p, 16));
          const int k1 = 8 * b + 2 * t + h, q = n2 * (k1 == 0 ? 16 : k1);
          T.tw3[2 * a + b][l][2 * h] = fbits(ccos(q, 512), 23);
          T.tw3[2 * a + b][l][2 * h + 1] = fbits(csin(q, 512), 23);
        }
        const int p = (8 * a + 2 * t + b) * (g == 0 ? 16 : g);
        T.tw1[2 * a + b][l][0] = fbits(g == 0 ? 0.0 : ccos(p, 512), 23);
        T.tw1[2 * a + b][l][1] = fbits(g == 0 ? ccos(p, 512) : csin(p, 512), 23);
        T.tw1[2 * a + b][l][2] = fbits(g == 0 ? 0.0 : -csin(p, 512), 23);
        T.tw1[2 * a + b][l][3] = fbits(g == 0 ? -csin(p, 512) : ccos(p, 512), 23);
        T.tw1[4 + a][l][2 * b] = fbits(ccos((8 * a + 2 * t + b) * (g + 8), 512), 23);
        T.tw1[4 + a][l][2 * b + 1] = fbits(csin((8 * a + 2 * t + b) * (g + 8), 512), 23);
      }
    for (int i = 0; i < 4; i++) {
      const int p8 = (t + 4 * (i & 1)) * (4 * (i >> 1) + (g >> 1));
      T.f8[l][i] = cfrag_c(p8, 8, g & 1);
      T.g8[l][i] = cfrag_c(-p8, 8, g & 1, 1.0 / (1 << 19));
    }
    for (int w = 0; w < 8; w++)
      for (int i = 0; i < 16; i++) {
        const int kidx = t + 4 * (i & 1) + 8 * (i >> 3), nidx = 4 * ((i >> 1) & 3) + (g >> 1);
        T.f2[w][i >> 2][l][i & 3] = cfrag_c((8 * kidx + w) * nidx, 128, g & 1);
        T.g2[w][i >> 2][l][i & 3] = cfrag_c(-(8 * nidx + w) * kidx, 128, g & 1);
      }
  }
  return T;
}
__device__ const __align__(128) Tables g_tab = make_tables();

__device__ __forceinline__ void die() { asm volatile("st.global.u32 [%0], %1;" ::"l"(0ull), "r"(0) : "memory"); }
__device__ __forceinline__ uint32_t s2u(const void* p) { return (uint32_t)__cvta_generic_to_shared(p); }
__device__ __forceinline__ void mbar_init(uint32_t b, int c) { asm volatile("mbarrier.init.shared::cta.b64 [%0], %1;" ::"r"(b), "r"(c)); }
__device__ __forceinline__ void mbar_expect(uint32_t b, int bytes) {
  asm volatile("mbarrier.arrive.expect_tx.shared::cta.b64 _, [%0], %1;" ::"r"(b), "r"(bytes) : "memory");
}
__device__ __forceinline__ void mbar_arrive(uint32_t b) { asm volatile("mbarrier.arrive.shared::cta.b64 _, [%0];" ::"r"(b) : "memory"); }
__device__ __forceinline__ uint32_t mbar_try(uint32_t b, uint32_t parity) {
  uint32_t ok;
  asm volatile("{.reg .pred p; mbarrier.try_wait.parity.shared::cta.b64 p, [%1], %2; selp.u32 %0,1,0,p;}"
               : "=r"(ok) : "r"(b), "r"(parity) : "memory");
  return ok;
}
__device__ __forceinline__ uint32_t mbar_test(uint32_t b) {
  uint32_t ok;
  asm volatile("{.reg .pred p; mbarrier.test_wait.parity.shared::cta.b64 p, [%1], 0; selp.u32 %0,1,0,p;}" : "=r"(ok) : "r"(b) : "memory");
  return ok;
}
__device__ __forceinline__ void mbar_wait_bounded(uint32_t b) {
  int it = 0;
#pragma unroll 1
  while (!mbar_try(b, 0))
    if (++it > SPIN_LIMIT) { die(); break; }
}
__device__ __forceinline__ void mbar_wait(uint32_t b) {
  asm volatile("{.reg .pred p;\nW_%=: mbarrier.try_wait.parity.shared::cta.b64 p, [%0], 0;\n@!p bra W_%=;}" ::"r"(b) : "memory");
}
__device__ __forceinline__ void bar_sync(int id, int n) { asm volatile("bar.sync %0, %1;" ::"r"(id), "r"(n) : "memory"); }
__device__ __forceinline__ void bar_arrive(int id, int n) { asm volatile("bar.arrive %0, %1;" ::"r"(id), "r"(n) : "memory"); }
__device__ __forceinline__ void red_release(unsigned* p) { asm volatile("red.release.gpu.global.add.u32 [%0], 1;" ::"l"(p) : "memory"); }
__device__ __forceinline__ void red_relaxed(unsigned* p) { asm volatile("red.relaxed.gpu.global.add.u32 [%0], 1;" ::"l"(p) : "memory"); }
__device__ __forceinline__ unsigned ld_acquire(const unsigned* p) {
  unsigned v;
  asm volatile("ld.acquire.gpu.global.u32 %0, [%1];" : "=r"(v) : "l"(p) : "memory");
  return v;
}
__device__ __forceinline__ unsigned ld_relaxed(const unsigned* p) {
  unsigned v;
  asm volatile("ld.relaxed.gpu.global.u32 %0, [%1];" : "=r"(v) : "l"(p) : "memory");
  return v;
}
__device__ __forceinline__ void wait_counter(const unsigned* p, unsigned target) {
#pragma unroll 1
  while ((int)(ld_acquire(p) - target) < 0) {}
}
__device__ __forceinline__ void sts4(uint32_t a, uint32_t x, uint32_t y, uint32_t z, uint32_t w) {
  asm volatile("st.shared.v4.u32 [%0], {%1,%2,%3,%4};" ::"r"(a), "r"(x), "r"(y), "r"(z), "r"(w) : "memory");
}
__device__ __forceinline__ uint4 lds4(uint32_t a) {
  uint4 v;
  asm volatile("ld.shared.v4.u32 {%0,%1,%2,%3}, [%4];" : "=r"(v.x), "=r"(v.y), "=r"(v.z), "=r"(v.w) : "r"(a) : "memory");
  return v;
}
__device__ __forceinline__ uint32_t pack2(float lo, float hi) {
  uint32_t r;
  asm("cvt.rn.bf16x2.f32 %0, %1, %2;" : "=r"(r) : "f"(hi), "f"(lo));
  return r;
}
__device__ __forceinline__ float bf_lo(uint32_t v) { return __uint_as_float(v << 16); }
__device__ __forceinline__ uint32_t hadd2_bf16(uint32_t a, uint32_t b) {
  uint32_t r;
  asm("add.rn.bf16x2 %0, %1, %2;" : "=r"(r) : "r"(a), "r"(b));
  return r;
}
__device__ __forceinline__ void mma16816(float (&d)[4], uint32_t a0, uint32_t a1, uint32_t a2, uint32_t a3, uint32_t b0, uint32_t b1) {
  asm("mma.sync.aligned.m16n8k16.row.col.f32.bf16.bf16.f32 {%0,%1,%2,%3}, {%4,%5,%6,%7}, {%8,%9}, {%0,%1,%2,%3};"
      : "+f"(d[0]), "+f"(d[1]), "+f"(d[2]), "+f"(d[3])
      : "r"(a0), "r"(a1), "r"(a2), "r"(a3), "r"(b0), "r"(b1));
}
__device__ __forceinline__ void mma16816_z(float (&d)[4], uint32_t a0, uint32_t a1, uint32_t a2, uint32_t a3, uint32_t b0, uint32_t b1) {
  asm("{.reg .f32 z; mov.f32 z, 0f00000000;\n"
      "mma.sync.aligned.m16n8k16.row.col.f32.bf16.bf16.f32 {%0,%1,%2,%3}, {%4,%5,%6,%7}, {%8,%9}, {z,z,z,z};}"
      : "=f"(d[0]), "=f"(d[1]), "=f"(d[2]), "=f"(d[3])
      : "r"(a0), "r"(a1), "r"(a2), "r"(a3), "r"(b0), "r"(b1));
}
template <int N>
__device__ __forceinline__ void cs_frac(int idx, float& c, float& s) {
  int i = ((idx + N / 2) & (N - 1)) - N / 2;
  float a = (float)i * (6.283185307179586f / N);
  c = __cosf(a);
  s = __sinf(a);
}
template <int N>
__device__ __forceinline__ uint32_t cfrag(int idx, int ri) {
  float c, s;
  cs_frac<N>(idx, c, s);
  return ri ? pack2(-s, c) : pack2(c, s);
}
__device__ __forceinline__ uint32_t word(const uint4& v, int e) { return e == 0 ? v.x : e == 1 ? v.y : e == 2 ? v.z : v.w; }
__device__ __forceinline__ void cdft16(const uint4 (&A)[4], const uint4 (&F)[4], uint4 (&o)[4]) {
  float acc[2][4][4];
#pragma unroll
  for (int ks = 0; ks < 2; ks++)
#pragma unroll
    for (int p = 0; p < 2; p++)
#pragma unroll
      for (int v = 0; v < 4; v++) {
        const uint4& a = A[2 * ks + p];
        const uint32_t b0 = word(F[ks * 2 + (v >> 1)], (v & 1) * 2), b1 = word(F[ks * 2 + (v >> 1)], (v & 1) * 2 + 1);
        if (ks == 0) mma16816_z(acc[p][v], a.x, a.y, a.z, a.w, b0, b1);
        else mma16816(acc[p][v], a.x, a.y, a.z, a.w, b0, b1);
      }
#pragma unroll
  for (int v = 0; v < 4; v++)
    o[v] = make_uint4(pack2(acc[0][v][0], acc[0][v][1]), pack2(acc[0][v][2], acc[0][v][3]),
                      pack2(acc[1][v][0], acc[1][v][1]), pack2(acc[1][v][2], acc[1][v][3]));
}
__device__ __forceinline__ void lds_frag(uint4& f0, uint4& f1, uint32_t a0, uint32_t a1) {
  asm volatile("ld.volatile.shared.v2.u32 {%0,%1}, [%8]; ld.volatile.shared.v2.u32 {%2,%3}, [%9];\n"
               "ld.volatile.shared.v2.u32 {%4,%5}, [%8+8]; ld.volatile.shared.v2.u32 {%6,%7}, [%9+8];"
               : "=r"(f0.x), "=r"(f0.y), "=r"(f0.z), "=r"(f0.w), "=r"(f1.x), "=r"(f1.y), "=r"(f1.z), "=r"(f1.w) : "r"(a0), "r"(a1) : "memory");
}
__device__ __forceinline__ void reg_frag(uint4 (&q)[4], uint32_t ones) {
#pragma unroll
  for (int ks = 0; ks < 2; ks++) {
    const uint4 a = q[2 * ks], b = q[2 * ks + 1];
    q[2 * ks] = make_uint4(a.x, a.y, b.x & ones, b.y & ones);
    q[2 * ks + 1] = make_uint4(a.z & ones, a.w & ones, b.z, b.w);
  }
}
__device__ __forceinline__ void st_tag(uint4* p, const uint4& v, uint32_t tag) {
  asm volatile("st.relaxed.gpu.global.v4.b32 [%0], {%1,%2,%3,%4};"
               ::"l"(p), "r"((v.x & ~1u) | tag), "r"(v.y), "r"(v.z), "r"(v.w) : "memory");
}
__device__ __forceinline__ void st_tag8(void* p, uint32_t x, uint32_t y, uint32_t tag) {
  asm volatile("st.relaxed.gpu.global.v2.b32 [%0], {%1,%2};" ::"l"(p), "r"((x & ~1u) | tag), "r"(y) : "memory");
}
__device__ __forceinline__ uint4 ld_b128(const uint4* p) {
  uint4 v;
  asm volatile("ld.relaxed.gpu.global.v4.b32 {%0,%1,%2,%3}, [%4];"
               : "=r"(v.x), "=r"(v.y), "=r"(v.z), "=r"(v.w) : "l"(p) : "memory");
  return v;
}
template <int STRIDE>
__device__ __forceinline__ void ld_tag4_issue(uint4 (&q)[4], const uint4* p) {
#pragma unroll
  for (int i = 0; i < 4; i++) q[i] = ld_b128(p + i * STRIDE);
}
__device__ __forceinline__ uint32_t tag_miss(uint32_t a, uint32_t b, uint32_t c, uint32_t d, uint32_t tag) {
  uint32_t r;
  asm("{.reg .b32 u, v; lop3.b32 u, %1, %2, %5, 0x7e; lop3.b32 v, %3, %4, %5, 0x7e; lop3.b32 %0, u, v, 1, 0xa8;}"
      : "=r"(r) : "r"(a), "r"(b), "r"(c), "r"(d), "r"(tag));
  return r;
}
template <int STRIDE, bool HALVES = false>
__device__ __forceinline__ void ld_tag4_finish(uint4 (&q)[4], const uint4* p, uint32_t tag) {
#pragma unroll 1
  while (__any_sync(0xffffffffu, tag_miss(q[0].x, q[1].x, q[2].x, q[3].x, tag) | (HALVES ? tag_miss(q[0].z, q[1].z, q[2].z, q[3].z, tag) : 0u)))
    ld_tag4_issue<STRIDE>(q, p);
#pragma unroll
  for (int i = 0; i < 4; i++) {
    asm volatile("and.b32 %0, %0, 0xfffffffe;" : "+r"(q[i].x));
    if (HALVES) q[i].z &= ~1u;
  }
}
__device__ __forceinline__ float quad_sum(const uint32_t (&a)[8]) {
  float d[4];
  mma16816_z(d, a[0], a[1], a[2], a[3], 0x3f803f80u, 0x3f803f80u);
  mma16816(d, a[4], a[5], a[6], a[7], 0x3f803f80u, 0x3f803f80u);
  return d[0] + d[2];
}
__device__ __forceinline__ float sum_groups(float v) {
  v += __shfl_xor_sync(0xffffffffu, v, 4);
  v += __shfl_xor_sync(0xffffffffu, v, 8);
  v += __shfl_xor_sync(0xffffffffu, v, 16);
  return v;
}
__device__ __forceinline__ uint32_t hsub2_bf16(uint32_t a, uint32_t b) {
  uint32_t r;
  asm("sub.rn.bf16x2 %0, %1, %2;" : "=r"(r) : "r"(a), "r"(b));
  return r;
}
__device__ __forceinline__ float row_rstd(const uint32_t (&c)[8], float delta) {
  uint32_t s[8];
#pragma unroll
  for (int i = 0; i < 8; i++) asm("mul.rn.bf16x2 %0, %1, %1;" : "=r"(s[i]) : "r"(c[i]));
  return rsqrtf(fmaxf(fmaf(-delta, delta, sum_groups(quad_sum(s)) * (1.f / 512.f)), 0.f) + 1e-5f);
}
__device__ __forceinline__ uint64_t desc64(uint32_t lo, uint32_t hi) {
  uint64_t d;
  asm("mov.b64 %0, {%1, %2};" : "=l"(d) : "r"(lo), "r"(hi));
  return d;
}
constexpr uint32_t desc_hi(uint32_t sbo, uint32_t swz) { return (sbo >> 4) | (swz << 30); }
__device__ __forceinline__ uint32_t desc_lo(uint32_t addr, uint32_t lbo) { return ((addr & 0x3FFFF) >> 4) | ((lbo >> 4) << 16); }
__device__ __forceinline__ void cp_async16(uint32_t dst, const void* src) {
  asm volatile("cp.async.cg.shared.global [%0], [%1], 16;" ::"r"(dst), "l"(src) : "memory");
}
__device__ __forceinline__ uint2 lds2(uint32_t a) {
  uint2 v;
  asm volatile("ld.shared.v2.u32 {%0,%1}, [%2];" : "=r"(v.x), "=r"(v.y) : "r"(a) : "memory");
  return v;
}
__device__ __forceinline__ uint32_t lds_u16(uint32_t a) {
  uint16_t v;
  asm volatile("ld.shared.u16 %0, [%1];" : "=h"(v) : "r"(a) : "memory");
  return v;
}
__device__ __forceinline__ void wg_fence() { asm volatile("wgmma.fence.sync.aligned;" ::: "memory"); }
__device__ __forceinline__ void wg_commit() { asm volatile("wgmma.commit_group.sync.aligned;" ::: "memory"); }
template <int N>
__device__ __forceinline__ void wg_wait() { asm volatile("wgmma.wait_group.sync.aligned %0;" ::"n"(N) : "memory"); }
__device__ __forceinline__ void bulk_load(uint32_t dst, const void* src, int bytes, uint32_t bar) {
  asm volatile("cp.async.bulk.shared::cluster.global.mbarrier::complete_tx::bytes [%0], [%1], %2, [%3];"
               ::"r"(dst), "l"(src), "r"(bytes), "r"(bar) : "memory");
}
__device__ __forceinline__ void bulk_load_mc(uint32_t dst, const void* src, int bytes, uint32_t bar) {
  asm volatile("cp.async.bulk.shared::cluster.global.mbarrier::complete_tx::bytes.multicast::cluster [%0], [%1], %2, [%3], %4;"
               ::"r"(dst), "l"(src), "r"(bytes), "r"(bar), "h"((uint16_t)3) : "memory");
}
__device__ __forceinline__ void tma3(uint32_t dst, const CUtensorMap* tm, uint32_t bar, int c0, int c1, int c2) {
  asm volatile("cp.async.bulk.tensor.3d.shared::cluster.global.mbarrier::complete_tx::bytes [%0], [%1, {%3,%4,%5}], [%2];"
               ::"r"(dst), "l"(tm), "r"(bar), "r"(c0), "r"(c1), "r"(c2) : "memory");
}
__device__ __forceinline__ void tma3_mc(uint32_t dst, const CUtensorMap* tm, uint32_t bar, int c1, int c2) {
  asm volatile("cp.async.bulk.tensor.3d.shared::cluster.global.mbarrier::complete_tx::bytes.multicast::cluster [%0], [%1, {%3,%4,%5}], [%2], %6;"
               ::"r"(dst), "l"(tm), "r"(bar), "r"(0), "r"(c1), "r"(c2), "h"((uint16_t)3) : "memory");
}
__device__ __forceinline__ void mbar_arrive_remote(uint32_t rb) {
  asm volatile("mbarrier.arrive.shared::cluster.b64 _, [%0];" ::"r"(rb) : "memory");
}
__device__ __forceinline__ uint4 ldg_ca4(const void* p) {
  uint4 v;
  asm volatile("ld.global.ca.v4.u32 {%0,%1,%2,%3}, [%4];" : "=r"(v.x), "=r"(v.y), "=r"(v.z), "=r"(v.w) : "l"(p) : "memory");
  return v;
}
__device__ __forceinline__ float u2f(uint32_t v) { return __uint_as_float(v); }
__device__ __forceinline__ void mma_az(float (&d)[4], const uint4& a, uint32_t b0, uint32_t b1) { mma16816_z(d, a.x, a.y, a.z, a.w, b0, b1); }
__device__ __forceinline__ void mma_a(float (&d)[4], const uint4& a, uint32_t b0, uint32_t b1) { mma16816(d, a.x, a.y, a.z, a.w, b0, b1); }
__device__ __forceinline__ uint32_t clock32() {
  uint32_t v;
  asm volatile("mov.u32 %0, %%clock;" : "=r"(v) :: "memory");
  return v;
}
__device__ __forceinline__ float swiglu(float g, float u, float r) {
  float hg = (0.5f * r) * g, th;
  asm("tanh.approx.f32 %0, %1;" : "=f"(th) : "f"(hg));
  return fmaf(hg, th, hg) * (r * u);
}
__device__ __forceinline__ void l2_prefetch(const void* p, int bytes) {
  asm volatile("cp.async.bulk.prefetch.L2.global [%0], %1;" ::"l"(p), "r"(bytes) : "memory");
}

__device__ __forceinline__ void wgmma_n256(float (&d)[128], uint64_t da, uint64_t db, int sd = 1) {
  asm volatile("{.reg .pred p; setp.ne.b32 p, %130, 0;\n"
      "wgmma.mma_async.sync.aligned.m64n256k16.f32.bf16.bf16 {"
      "%0,%1,%2,%3,%4,%5,%6,%7,%8,%9,%10,%11,%12,%13,%14,%15,"
      "%16,%17,%18,%19,%20,%21,%22,%23,%24,%25,%26,%27,%28,%29,%30,%31,"
      "%32,%33,%34,%35,%36,%37,%38,%39,%40,%41,%42,%43,%44,%45,%46,%47,"
      "%48,%49,%50,%51,%52,%53,%54,%55,%56,%57,%58,%59,%60,%61,%62,%63,"
      "%64,%65,%66,%67,%68,%69,%70,%71,%72,%73,%74,%75,%76,%77,%78,%79,"
      "%80,%81,%82,%83,%84,%85,%86,%87,%88,%89,%90,%91,%92,%93,%94,%95,"
      "%96,%97,%98,%99,%100,%101,%102,%103,%104,%105,%106,%107,%108,%109,%110,%111,"
      "%112,%113,%114,%115,%116,%117,%118,%119,%120,%121,%122,%123,%124,%125,%126,%127"
      "}, %128, %129, p, 1, 1, 0, 1;}\n"
      : "+f"(d[0]),"+f"(d[1]),"+f"(d[2]),"+f"(d[3]),"+f"(d[4]),"+f"(d[5]),"+f"(d[6]),"+f"(d[7]),
        "+f"(d[8]),"+f"(d[9]),"+f"(d[10]),"+f"(d[11]),"+f"(d[12]),"+f"(d[13]),"+f"(d[14]),"+f"(d[15]),
        "+f"(d[16]),"+f"(d[17]),"+f"(d[18]),"+f"(d[19]),"+f"(d[20]),"+f"(d[21]),"+f"(d[22]),"+f"(d[23]),
        "+f"(d[24]),"+f"(d[25]),"+f"(d[26]),"+f"(d[27]),"+f"(d[28]),"+f"(d[29]),"+f"(d[30]),"+f"(d[31]),
        "+f"(d[32]),"+f"(d[33]),"+f"(d[34]),"+f"(d[35]),"+f"(d[36]),"+f"(d[37]),"+f"(d[38]),"+f"(d[39]),
        "+f"(d[40]),"+f"(d[41]),"+f"(d[42]),"+f"(d[43]),"+f"(d[44]),"+f"(d[45]),"+f"(d[46]),"+f"(d[47]),
        "+f"(d[48]),"+f"(d[49]),"+f"(d[50]),"+f"(d[51]),"+f"(d[52]),"+f"(d[53]),"+f"(d[54]),"+f"(d[55]),
        "+f"(d[56]),"+f"(d[57]),"+f"(d[58]),"+f"(d[59]),"+f"(d[60]),"+f"(d[61]),"+f"(d[62]),"+f"(d[63]),
        "+f"(d[64]),"+f"(d[65]),"+f"(d[66]),"+f"(d[67]),"+f"(d[68]),"+f"(d[69]),"+f"(d[70]),"+f"(d[71]),
        "+f"(d[72]),"+f"(d[73]),"+f"(d[74]),"+f"(d[75]),"+f"(d[76]),"+f"(d[77]),"+f"(d[78]),"+f"(d[79]),
        "+f"(d[80]),"+f"(d[81]),"+f"(d[82]),"+f"(d[83]),"+f"(d[84]),"+f"(d[85]),"+f"(d[86]),"+f"(d[87]),
        "+f"(d[88]),"+f"(d[89]),"+f"(d[90]),"+f"(d[91]),"+f"(d[92]),"+f"(d[93]),"+f"(d[94]),"+f"(d[95]),
        "+f"(d[96]),"+f"(d[97]),"+f"(d[98]),"+f"(d[99]),"+f"(d[100]),"+f"(d[101]),"+f"(d[102]),"+f"(d[103]),
        "+f"(d[104]),"+f"(d[105]),"+f"(d[106]),"+f"(d[107]),"+f"(d[108]),"+f"(d[109]),"+f"(d[110]),"+f"(d[111]),
        "+f"(d[112]),"+f"(d[113]),"+f"(d[114]),"+f"(d[115]),"+f"(d[116]),"+f"(d[117]),"+f"(d[118]),"+f"(d[119]),
        "+f"(d[120]),"+f"(d[121]),"+f"(d[122]),"+f"(d[123]),"+f"(d[124]),"+f"(d[125]),"+f"(d[126]),"+f"(d[127])
      : "l"(da), "l"(db), "r"(sd));
}
__device__ __forceinline__ void wgmma_n192(float (&d)[96], uint64_t da, uint64_t db) {
  asm volatile("wgmma.mma_async.sync.aligned.m64n192k16.f32.bf16.bf16 {"
      "%0,%1,%2,%3,%4,%5,%6,%7,%8,%9,%10,%11,%12,%13,%14,%15,"
      "%16,%17,%18,%19,%20,%21,%22,%23,%24,%25,%26,%27,%28,%29,%30,%31,"
      "%32,%33,%34,%35,%36,%37,%38,%39,%40,%41,%42,%43,%44,%45,%46,%47,"
      "%48,%49,%50,%51,%52,%53,%54,%55,%56,%57,%58,%59,%60,%61,%62,%63,"
      "%64,%65,%66,%67,%68,%69,%70,%71,%72,%73,%74,%75,%76,%77,%78,%79,"
      "%80,%81,%82,%83,%84,%85,%86,%87,%88,%89,%90,%91,%92,%93,%94,%95"
      "}, %96, %97, 1, 1, 1, 0, 1;\n"
      : "+f"(d[0]),"+f"(d[1]),"+f"(d[2]),"+f"(d[3]),"+f"(d[4]),"+f"(d[5]),"+f"(d[6]),"+f"(d[7]),
        "+f"(d[8]),"+f"(d[9]),"+f"(d[10]),"+f"(d[11]),"+f"(d[12]),"+f"(d[13]),"+f"(d[14]),"+f"(d[15]),
        "+f"(d[16]),"+f"(d[17]),"+f"(d[18]),"+f"(d[19]),"+f"(d[20]),"+f"(d[21]),"+f"(d[22]),"+f"(d[23]),
        "+f"(d[24]),"+f"(d[25]),"+f"(d[26]),"+f"(d[27]),"+f"(d[28]),"+f"(d[29]),"+f"(d[30]),"+f"(d[31]),
        "+f"(d[32]),"+f"(d[33]),"+f"(d[34]),"+f"(d[35]),"+f"(d[36]),"+f"(d[37]),"+f"(d[38]),"+f"(d[39]),
        "+f"(d[40]),"+f"(d[41]),"+f"(d[42]),"+f"(d[43]),"+f"(d[44]),"+f"(d[45]),"+f"(d[46]),"+f"(d[47]),
        "+f"(d[48]),"+f"(d[49]),"+f"(d[50]),"+f"(d[51]),"+f"(d[52]),"+f"(d[53]),"+f"(d[54]),"+f"(d[55]),
        "+f"(d[56]),"+f"(d[57]),"+f"(d[58]),"+f"(d[59]),"+f"(d[60]),"+f"(d[61]),"+f"(d[62]),"+f"(d[63]),
        "+f"(d[64]),"+f"(d[65]),"+f"(d[66]),"+f"(d[67]),"+f"(d[68]),"+f"(d[69]),"+f"(d[70]),"+f"(d[71]),
        "+f"(d[72]),"+f"(d[73]),"+f"(d[74]),"+f"(d[75]),"+f"(d[76]),"+f"(d[77]),"+f"(d[78]),"+f"(d[79]),
        "+f"(d[80]),"+f"(d[81]),"+f"(d[82]),"+f"(d[83]),"+f"(d[84]),"+f"(d[85]),"+f"(d[86]),"+f"(d[87]),
        "+f"(d[88]),"+f"(d[89]),"+f"(d[90]),"+f"(d[91]),"+f"(d[92]),"+f"(d[93]),"+f"(d[94]),"+f"(d[95])
      : "l"(da), "l"(db));
}
__device__ __forceinline__ void wgmma_rs_n128(float (&d)[64], uint32_t a0, uint32_t a1, uint32_t a2, uint32_t a3, uint64_t db, int sd = 1) {
  asm volatile("{.reg .pred p; setp.ne.b32 p, %69, 0;\n"
      "wgmma.mma_async.sync.aligned.m64n128k16.f32.bf16.bf16 {"
      "%0,%1,%2,%3,%4,%5,%6,%7,%8,%9,%10,%11,%12,%13,%14,%15,"
      "%16,%17,%18,%19,%20,%21,%22,%23,%24,%25,%26,%27,%28,%29,%30,%31,"
      "%32,%33,%34,%35,%36,%37,%38,%39,%40,%41,%42,%43,%44,%45,%46,%47,"
      "%48,%49,%50,%51,%52,%53,%54,%55,%56,%57,%58,%59,%60,%61,%62,%63"
      "}, {%64,%65,%66,%67}, %68, p, 1, 1, 1;}\n"
      : "+f"(d[0]),"+f"(d[1]),"+f"(d[2]),"+f"(d[3]),"+f"(d[4]),"+f"(d[5]),"+f"(d[6]),"+f"(d[7]),
        "+f"(d[8]),"+f"(d[9]),"+f"(d[10]),"+f"(d[11]),"+f"(d[12]),"+f"(d[13]),"+f"(d[14]),"+f"(d[15]),
        "+f"(d[16]),"+f"(d[17]),"+f"(d[18]),"+f"(d[19]),"+f"(d[20]),"+f"(d[21]),"+f"(d[22]),"+f"(d[23]),
        "+f"(d[24]),"+f"(d[25]),"+f"(d[26]),"+f"(d[27]),"+f"(d[28]),"+f"(d[29]),"+f"(d[30]),"+f"(d[31]),
        "+f"(d[32]),"+f"(d[33]),"+f"(d[34]),"+f"(d[35]),"+f"(d[36]),"+f"(d[37]),"+f"(d[38]),"+f"(d[39]),
        "+f"(d[40]),"+f"(d[41]),"+f"(d[42]),"+f"(d[43]),"+f"(d[44]),"+f"(d[45]),"+f"(d[46]),"+f"(d[47]),
        "+f"(d[48]),"+f"(d[49]),"+f"(d[50]),"+f"(d[51]),"+f"(d[52]),"+f"(d[53]),"+f"(d[54]),"+f"(d[55]),
        "+f"(d[56]),"+f"(d[57]),"+f"(d[58]),"+f"(d[59]),"+f"(d[60]),"+f"(d[61]),"+f"(d[62]),"+f"(d[63])
      : "r"(a0), "r"(a1), "r"(a2), "r"(a3), "l"(db), "r"(sd));
}
__device__ __forceinline__ void wgmma_rs_n256(float (&d)[128], uint32_t a0, uint32_t a1, uint32_t a2, uint32_t a3, uint64_t db, int sd = 1) {
  asm volatile("{.reg .pred p; setp.ne.b32 p, %133, 0;\n"
      "wgmma.mma_async.sync.aligned.m64n256k16.f32.bf16.bf16 {"
      "%0,%1,%2,%3,%4,%5,%6,%7,%8,%9,%10,%11,%12,%13,%14,%15,"
      "%16,%17,%18,%19,%20,%21,%22,%23,%24,%25,%26,%27,%28,%29,%30,%31,"
      "%32,%33,%34,%35,%36,%37,%38,%39,%40,%41,%42,%43,%44,%45,%46,%47,"
      "%48,%49,%50,%51,%52,%53,%54,%55,%56,%57,%58,%59,%60,%61,%62,%63,"
      "%64,%65,%66,%67,%68,%69,%70,%71,%72,%73,%74,%75,%76,%77,%78,%79,"
      "%80,%81,%82,%83,%84,%85,%86,%87,%88,%89,%90,%91,%92,%93,%94,%95,"
      "%96,%97,%98,%99,%100,%101,%102,%103,%104,%105,%106,%107,%108,%109,%110,%111,"
      "%112,%113,%114,%115,%116,%117,%118,%119,%120,%121,%122,%123,%124,%125,%126,%127"
      "}, {%128,%129,%130,%131}, %132, p, 1, 1, 1;}\n"
      : "+f"(d[0]),"+f"(d[1]),"+f"(d[2]),"+f"(d[3]),"+f"(d[4]),"+f"(d[5]),"+f"(d[6]),"+f"(d[7]),
        "+f"(d[8]),"+f"(d[9]),"+f"(d[10]),"+f"(d[11]),"+f"(d[12]),"+f"(d[13]),"+f"(d[14]),"+f"(d[15]),
        "+f"(d[16]),"+f"(d[17]),"+f"(d[18]),"+f"(d[19]),"+f"(d[20]),"+f"(d[21]),"+f"(d[22]),"+f"(d[23]),
        "+f"(d[24]),"+f"(d[25]),"+f"(d[26]),"+f"(d[27]),"+f"(d[28]),"+f"(d[29]),"+f"(d[30]),"+f"(d[31]),
        "+f"(d[32]),"+f"(d[33]),"+f"(d[34]),"+f"(d[35]),"+f"(d[36]),"+f"(d[37]),"+f"(d[38]),"+f"(d[39]),
        "+f"(d[40]),"+f"(d[41]),"+f"(d[42]),"+f"(d[43]),"+f"(d[44]),"+f"(d[45]),"+f"(d[46]),"+f"(d[47]),
        "+f"(d[48]),"+f"(d[49]),"+f"(d[50]),"+f"(d[51]),"+f"(d[52]),"+f"(d[53]),"+f"(d[54]),"+f"(d[55]),
        "+f"(d[56]),"+f"(d[57]),"+f"(d[58]),"+f"(d[59]),"+f"(d[60]),"+f"(d[61]),"+f"(d[62]),"+f"(d[63]),
        "+f"(d[64]),"+f"(d[65]),"+f"(d[66]),"+f"(d[67]),"+f"(d[68]),"+f"(d[69]),"+f"(d[70]),"+f"(d[71]),
        "+f"(d[72]),"+f"(d[73]),"+f"(d[74]),"+f"(d[75]),"+f"(d[76]),"+f"(d[77]),"+f"(d[78]),"+f"(d[79]),
        "+f"(d[80]),"+f"(d[81]),"+f"(d[82]),"+f"(d[83]),"+f"(d[84]),"+f"(d[85]),"+f"(d[86]),"+f"(d[87]),
        "+f"(d[88]),"+f"(d[89]),"+f"(d[90]),"+f"(d[91]),"+f"(d[92]),"+f"(d[93]),"+f"(d[94]),"+f"(d[95]),
        "+f"(d[96]),"+f"(d[97]),"+f"(d[98]),"+f"(d[99]),"+f"(d[100]),"+f"(d[101]),"+f"(d[102]),"+f"(d[103]),
        "+f"(d[104]),"+f"(d[105]),"+f"(d[106]),"+f"(d[107]),"+f"(d[108]),"+f"(d[109]),"+f"(d[110]),"+f"(d[111]),
        "+f"(d[112]),"+f"(d[113]),"+f"(d[114]),"+f"(d[115]),"+f"(d[116]),"+f"(d[117]),"+f"(d[118]),"+f"(d[119]),
        "+f"(d[120]),"+f"(d[121]),"+f"(d[122]),"+f"(d[123]),"+f"(d[124]),"+f"(d[125]),"+f"(d[126]),"+f"(d[127])
      : "r"(a0), "r"(a1), "r"(a2), "r"(a3), "l"(db), "r"(sd));
}
__device__ __forceinline__ void wgmma_rs_n192(float (&d)[96], uint32_t a0, uint32_t a1, uint32_t a2, uint32_t a3, uint64_t db) {
  asm volatile("wgmma.mma_async.sync.aligned.m64n192k16.f32.bf16.bf16 {"
      "%0,%1,%2,%3,%4,%5,%6,%7,%8,%9,%10,%11,%12,%13,%14,%15,"
      "%16,%17,%18,%19,%20,%21,%22,%23,%24,%25,%26,%27,%28,%29,%30,%31,"
      "%32,%33,%34,%35,%36,%37,%38,%39,%40,%41,%42,%43,%44,%45,%46,%47,"
      "%48,%49,%50,%51,%52,%53,%54,%55,%56,%57,%58,%59,%60,%61,%62,%63,"
      "%64,%65,%66,%67,%68,%69,%70,%71,%72,%73,%74,%75,%76,%77,%78,%79,"
      "%80,%81,%82,%83,%84,%85,%86,%87,%88,%89,%90,%91,%92,%93,%94,%95"
      "}, {%96,%97,%98,%99}, %100, 1, 1, 1, 1;\n"
      : "+f"(d[0]),"+f"(d[1]),"+f"(d[2]),"+f"(d[3]),"+f"(d[4]),"+f"(d[5]),"+f"(d[6]),"+f"(d[7]),
        "+f"(d[8]),"+f"(d[9]),"+f"(d[10]),"+f"(d[11]),"+f"(d[12]),"+f"(d[13]),"+f"(d[14]),"+f"(d[15]),
        "+f"(d[16]),"+f"(d[17]),"+f"(d[18]),"+f"(d[19]),"+f"(d[20]),"+f"(d[21]),"+f"(d[22]),"+f"(d[23]),
        "+f"(d[24]),"+f"(d[25]),"+f"(d[26]),"+f"(d[27]),"+f"(d[28]),"+f"(d[29]),"+f"(d[30]),"+f"(d[31]),
        "+f"(d[32]),"+f"(d[33]),"+f"(d[34]),"+f"(d[35]),"+f"(d[36]),"+f"(d[37]),"+f"(d[38]),"+f"(d[39]),
        "+f"(d[40]),"+f"(d[41]),"+f"(d[42]),"+f"(d[43]),"+f"(d[44]),"+f"(d[45]),"+f"(d[46]),"+f"(d[47]),
        "+f"(d[48]),"+f"(d[49]),"+f"(d[50]),"+f"(d[51]),"+f"(d[52]),"+f"(d[53]),"+f"(d[54]),"+f"(d[55]),
        "+f"(d[56]),"+f"(d[57]),"+f"(d[58]),"+f"(d[59]),"+f"(d[60]),"+f"(d[61]),"+f"(d[62]),"+f"(d[63]),
        "+f"(d[64]),"+f"(d[65]),"+f"(d[66]),"+f"(d[67]),"+f"(d[68]),"+f"(d[69]),"+f"(d[70]),"+f"(d[71]),
        "+f"(d[72]),"+f"(d[73]),"+f"(d[74]),"+f"(d[75]),"+f"(d[76]),"+f"(d[77]),"+f"(d[78]),"+f"(d[79]),
        "+f"(d[80]),"+f"(d[81]),"+f"(d[82]),"+f"(d[83]),"+f"(d[84]),"+f"(d[85]),"+f"(d[86]),"+f"(d[87]),
        "+f"(d[88]),"+f"(d[89]),"+f"(d[90]),"+f"(d[91]),"+f"(d[92]),"+f"(d[93]),"+f"(d[94]),"+f"(d[95])
      : "r"(a0), "r"(a1), "r"(a2), "r"(a3), "l"(db));
}


constexpr int C_LN = 0, C_PX = 16, C_PY = 32;
constexpr int NB_CONS = 1, NB_LN = 2, NB_LAG = 4, NB_INIT = 6, NB_RDY = 7, NB_WG = 8;
constexpr int LAGX = 3;
constexpr int LAGY = 6;
constexpr int LAG2 = 5;
constexpr int NLL = 2;
constexpr int POLL_DELAY3 = 600;
constexpr int POLL_DELAY = 1200;
constexpr int FILT_DELAY = 800;
constexpr int WARM = 4;
constexpr int ALEAD = 6;
constexpr int POLL_DELAY2 = 1000;
constexpr int REDPOS = 4;
constexpr int XTRIG = 20;
constexpr int HTRIG = 0;
constexpr int PACED = 1;
constexpr int RING_SIG = 1;
constexpr int PF2_SIG = 1;
constexpr int SM_E = 0, SM_X = 16384, SM_E2 = 32768, SM_W = 49152, SM_FC = 69632, SM_T = 73728 - T1_BYTES;
constexpr unsigned long long KORDER = 0xBA9432DC876510ull;
constexpr unsigned long long BSLOT = 0x52140A98D52140ull, PSLOT = 0xB763CB763CB763ull;
constexpr unsigned long long BDEP = 0xFFEC97531ull, PDEP = 0xBA754ull;
constexpr uint32_t HI128 = desc_hi(1024, 1), HI64 = desc_hi(512, 2);

struct Bars {
  uint64_t full1[32], empty1[32], freeA[4], full2[16], fullA[8], empty2[8], emptyP[9], sig[2], done, fullP[32], hbar, tbar, hint[3], sbar;
  uint32_t epoch, pad;
};

template <int NK, bool STORE, int J0 = 0, int J1 = NK>
__device__ __forceinline__ void make_p(const float (&acc)[NK * 16], float r0, float r1, uint4 (&p)[NK], uint4* pbase, int ks0, uint32_t tag) {
#pragma unroll
  for (int j = J0; j < J1; j++) {
    uint32_t w[4];
#pragma unroll
    for (int i = 0; i < 4; i++) {
      const int a = 8 * j + 2 * i, b = a + NK * 8;
      w[i] = pack2(swiglu(acc[a], acc[b], (i & 1) ? r1 : r0), swiglu(acc[a + 1], acc[b + 1], (i & 1) ? r1 : r0));
    }
    asm volatile("" : "+r"(w[0]), "+r"(w[1]), "+r"(w[2]), "+r"(w[3]));
    p[j] = make_uint4(w[0], w[1], w[2], w[3]);
    if (STORE) st_tag(pbase + ((ks0 + j) >> 2) * 1024 + ((ks0 + j) & 3) * 32, p[j], tag);
  }
}
__device__ __forceinline__ void spin_until(uint32_t t) {
  while ((int)(clock32() - t) < 0) {}
}

__global__ void __cluster_dims__(2, 1, 1) __launch_bounds__(NTHREADS, 1)
fused_kernel(const __nv_bfloat16* __restrict__ x, const Tables* __restrict__ tab, Scratch* __restrict__ scr,
             __nv_bfloat16* __restrict__ out, const char* __restrict__ wg_raw, const char* __restrict__ wu_raw,
             const char* __restrict__ wd_raw,
             const __grid_constant__ CUtensorMap tmWR, const __grid_constant__ CUtensorMap tmWI,
             const __grid_constant__ CUtensorMap tmGX, const __grid_constant__ CUtensorMap tmUX,
             const __grid_constant__ CUtensorMap tmGY, const __grid_constant__ CUtensorMap tmUY,
             const __grid_constant__ CUtensorMap tmD) {
  extern __shared__ __align__(1024) char smem_raw[];
  const uint32_t sbase = s2u(smem_raw);
  const uint32_t sbar = sbase + 14 * SLOT, sstat = sbar + 1408;
  const int tid = threadIdx.x, lane = tid & 31;
  const int c = blockIdx.x, rk = c & 1, f = (c >> 1) & 7, rb = 2 * (c >> 4) + rk;
  const int rb2 = 2 * (c >> 4) + (f >> 2), kh = (f >> 1) & 1, nq = 2 * (f & 1) + rk;
#define BAR(field, i) (sbar + (uint32_t)offsetof(Bars, field) + 8u * (i))
#define TOFF(field) (sbase + SM_T + (uint32_t)offsetof(Tables, field) + lane * 16)

  if (tid >= 256) {
    asm volatile("setmaxnreg.dec.sync.aligned.u32 40;");
    const int warp = __shfl_sync(0xffffffffu, tid >> 5, 0);
    if (lane == 0) {
      auto init = [&](uint32_t b, int n, int count, int bytes) {
#pragma unroll 1
        for (int i = 0; i < n; i++) {
          mbar_init(b + 8 * i, count);
          if (bytes) mbar_expect(b + 8 * i, bytes);
        }
      };
      if (warp == 8) {
        if (sbase & 1023) die();
        init(BAR(tbar, 0), 1, 1, T2_BYTES + 2 * 10240);
        init(BAR(hbar, 0), 1, 1, 16384);
        init(BAR(hint, 0), 3, 1, 0);
        init(BAR(sbar, 0), 1, 32, 0);
        init(BAR(empty2, 0), 20, 8, 0);
      } else if (warp == 9) {
        init(BAR(full1, 0), 16, 1, 16384);
        init(BAR(full1, 16), 16, 1, 12288);
      } else if (warp == 10) {
        init(BAR(fullP, 0), 30, 1, 8192);
      } else {
        init(BAR(full2, 0), 24, 1, 16384);
        init(BAR(empty1, 0), 36, 16, 0);
      }
      asm volatile("fence.mbarrier_init.release.cluster;" ::: "memory");
    }
    if (tid == 256) {
      const int w0 = ((c >> 3) * 257 + 32 * (c & 7) + 1) & ~7;
      if (FILT_DELAY) {
        asm volatile("prefetch.tensormap [%0];" ::"l"(&tmWR) : "memory");
        asm volatile("prefetch.tensormap [%0];" ::"l"(&tmWI) : "memory");
        spin_until(clock32() + FILT_DELAY);
      }
      tma3(sbase + SM_W, &tmWR, BAR(tbar, 0), w0, 0, 0);
      tma3(sbase + SM_W + 10240, &tmWI, BAR(tbar, 0), w0, 0, 0);
      bulk_load(sbase + SM_T + T1_BYTES, reinterpret_cast<const char*>(tab) + T1_BYTES, T2_BYTES, BAR(tbar, 0));
    }
    if (tid == 288) {
      asm volatile("prefetch.tensormap [%0];" ::"l"(rk ? &tmUX : &tmGX) : "memory");
      asm volatile("prefetch.tensormap [%0];" ::"l"(rk ? &tmUY : &tmGY) : "memory");
      asm volatile("prefetch.tensormap [%0];" ::"l"(&tmD) : "memory");
    }
    if (tid == 320) {
      const unsigned e = ld_relaxed(&scr->cnt[(C_LN + rb) * 32]) >> 3;
      asm volatile("st.shared.u32 [%0], %1;" ::"r"(BAR(epoch, 0)), "r"(e) : "memory");
    }
    __syncwarp();
    asm volatile("barrier.cluster.arrive.relaxed.aligned;" ::: "memory");
    bar_arrive(NB_RDY, 384);
    asm volatile("barrier.cluster.wait.aligned;" ::: "memory");
    bar_sync(NB_INIT, 384);
    unsigned epoch;
    asm volatile("ld.shared.u32 %0, [%1];" : "=r"(epoch) : "r"(BAR(epoch, 0)) : "memory");
    if (warp == 8) {
      if (lane == 0) {
        const int ax = (7 * f + 3 * (f & 1)) >> 1;
        const int ay = 7 * f + ((f & 1) ? 0 : 4);
        const CUtensorMap* tx = rk ? &tmUX : &tmGX;
        const CUtensorMap* ty = rk ? &tmUY : &tmGY;
        if (RING_SIG >= 0) mbar_wait_bounded(BAR(sig, RING_SIG));
        uint32_t s = 2;
#pragma unroll 1
        for (int n = 0; n < 16; n++) {
          if (n >= 6) mbar_wait_bounded(BAR(empty1, n - 6));
          tma3_mc(sbase + (8 + s) * SLOT + rk * 8192, tx, BAR(full1, n), n * 32, ax);
          if (++s == 6) s = 0;
          if (n >= 10 && n < 15) {
            const int k = n - 10;
            mbar_wait_bounded(BAR(freeA, (12 * k + 11) >> 4));
            tma3_mc(sbase + k * 12288 + rk * 6144, ty, BAR(full1, 16 + k), (k + 8) * 32, ay);
          }
        }
#pragma unroll 1
        for (int k = 5; k < 16; k++) {
          mbar_wait_bounded(BAR(empty1, k < 13 ? 10 + ((12 * (k - 5) + 11) >> 4) : 8 + k));
          tma3_mc(sbase + 8 * SLOT + ((k - 5) & 7) * 12288 + rk * 6144, ty, BAR(full1, 16 + k), ((k + 8) & 15) * 32, ay);
        }
        mbar_wait_bounded(BAR(done, 0));
      }
    } else if (warp == 9) {
      if (lane == 0) {
        mbar_wait(BAR(fullA, 4));
        wait_counter(&scr->cnt[(C_LN + rb2) * 32], (epoch + 1) * 8);
        asm volatile("fence.proxy.async.global;" ::: "memory");
#pragma unroll 1
        for (int i = 0; i < 14; i++) {
          const int kblk = 14 * kh + (int)((KORDER >> (4 * i)) & 15);
          mbar_wait(i < 9 ? BAR(empty1, 16 + (uint32_t)((BDEP >> (4 * i)) & 15)) : BAR(empty2, i - 9));
          tma3(sbase + (uint32_t)((BSLOT >> (4 * i)) & 15) * SLOT, &tmD, BAR(full2, i), 0, 64 * kblk, 2 * nq);
        }
        mbar_wait(BAR(empty2, 5));
        bulk_load(sbase + 13 * SLOT, &scr->LN[(rb2 * 8 + 2 * nq) * 1024 + kh * 512], 8192, BAR(hbar, 0));
        bulk_load(sbase + 13 * SLOT + 8192, &scr->LN[(rb2 * 8 + 2 * nq + 1) * 1024 + kh * 512], 8192, BAR(hbar, 0));
      }
    } else if (warp == 10) {
      bar_sync(NB_LN, 288);
      if (lane == 0) {
        red_release(&scr->cnt[(C_LN + rb) * 32]);
        wait_counter(&scr->cnt[(C_LN + rb) * 32], (epoch + 1) * 8);
        asm volatile("fence.proxy.async.global;" ::: "memory");
#pragma unroll 1
        for (int kb = NLL; kb < 8; kb++) {
          if (2 * kb >= ALEAD) mbar_wait(BAR(empty1, 2 * kb - ALEAD));
          bulk_load(sbase + kb * SLOT, &scr->LN[(rb * 8 + kb) * 1024], 16384, BAR(fullA, kb));
        }
#pragma unroll 1
        for (int s = 0; s < 14; s++) {
          const int kblk = 14 * kh + (int)((KORDER >> (4 * s)) & 15);
          if (s == 0 || s == 8 || s == 11) {
            mbar_wait(BAR(hint, s == 0 ? 0 : s == 8 ? 1 : 2));
          }
          mbar_wait(s < 5 ? BAR(empty1, 16 + (uint32_t)((PDEP >> (4 * s)) & 15)) : BAR(emptyP, s - 5));
          bulk_load_mc(sbase + (uint32_t)((PSLOT >> (4 * s)) & 15) * SLOT + rk * 8192, &scr->P[(rb2 * 28 + kblk) * 1024 + rk * 512], 8192, BAR(fullP, 16 * rk + s));
        }
      }
    } else {
      if (lane == 0) {
        mbar_wait(BAR(tbar, 0));
        l2_prefetch(wg_raw + (size_t)c * 5376, 5376);
        l2_prefetch(wu_raw + (size_t)c * 5376, 5376);
        mbar_wait(BAR(sig, PF2_SIG));
        l2_prefetch(wg_raw + 688128 + (size_t)c * 8960, 8960);
        l2_prefetch(wu_raw + 688128 + (size_t)c * 8960, 8960);
      }
      mbar_wait(BAR(fullA, 4));
      if (lane == 0) l2_prefetch(wd_raw + (size_t)c * 14336, 14336);
      {
        const uint32_t tag = (epoch + 1) & 1;
        uint4 v0, v1, v2;
        while (true) {
          v0 = ld_b128(&scr->ST[rb * 64 + lane]);
          v1 = ld_b128(&scr->ST[rb * 64 + 32 + lane]);
          v2 = ld_b128(&scr->ST[rb2 * 64 + 32 * kh + lane]);
          if (!__any_sync(0xffffffffu, ((v0.x ^ tag) | (v1.x ^ tag) | (v2.x ^ tag)) & 1u)) break;
        }
        sts4(sstat + lane * 16, v0.x & ~1u, v0.y, v0.z, v0.w);
        sts4(sstat + 512 + lane * 16, v1.x & ~1u, v1.y, v1.z, v1.w);
        sts4(sstat + 1024 + lane * 16, v2.x & ~1u, v2.y, v2.z, v2.w);
        mbar_arrive(BAR(sbar, 0));
      }
      if (lane == 0) {
        mbar_wait(BAR(empty1, XTRIG));
        while ((int)(ld_relaxed(&scr->cnt[(C_PX + rb2) * 32 + kh]) - (epoch + 1) * 32) < 0) {
        }
        mbar_arrive(BAR(hint, 0));
        mbar_wait(BAR(emptyP, HTRIG));
        uint32_t done = 0;
        while (done != 3) {
          uint2 v;
          asm volatile("ld.relaxed.gpu.global.v2.u32 {%0,%1}, [%2];" : "=r"(v.x), "=r"(v.y) : "l"(&scr->cnt[(C_PY + rb2) * 32 + 4 * (rk ^ kh ^ 1) + 2 * kh]) : "memory");
          if (!(done & 1) && (int)(v.x - (epoch + 1) * 8) >= 0) { done |= 1; mbar_arrive(BAR(hint, 1)); }
          if (!(done & 2) && (int)(v.y - (epoch + 1) * 8) >= 0) { done |= 2; mbar_arrive(BAR(hint, 2)); }
        }
      }
    }
  } else {
    const int warp = __shfl_sync(0xffffffffu, tid >> 5, 0);
    const int g = lane >> 2, t = lane & 3;
    uint4 fa[4], fb[4], tw[6];
#pragma unroll
    for (int i = 0; i < 4; i++) fa[i] = ldg_ca4(&tab->fa[i][lane][0]);
#pragma unroll
    for (int i = 0; i < 6; i++) tw[i] = ldg_ca4(&tab->tw1[i][lane][0]);
#pragma unroll
    for (int i = 0; i < 4; i++) fb[i] = ldg_ca4(&tab->fb[i][lane][0]);
#pragma unroll
    for (int i = 0; i < 4; i++) {
      const int r = i >> 1, ch = (i & 1) * 32 + lane;
      cp_async16(sbase + SM_X + (2 * warp + r) * 1024 + ((ch ^ ((ch >> 3) & 1)) * 16),
                 x + (size_t)(c + 128 * (2 * warp + r)) * 512 + ch * 8);
    }
    asm volatile("cp.async.commit_group;" ::: "memory");
    asm volatile("barrier.cluster.arrive.relaxed.aligned;" ::: "memory");
    uint32_t rbar;
    asm volatile("mapa.shared::cluster.u32 %0, %1, %2;" : "=r"(rbar) : "r"(sbar), "r"(rk ^ 1));
#define RBAR(field, i) (rbar + (uint32_t)offsetof(Bars, field) + 8u * (i))
    {
      const int ln = (tid >> 1) & 31, lg = ln >> 2, lt = ln & 3, i = 4 * (tid >> 6) + 2 * (tid & 1);
      const int kidx = lt + 8 * (i >> 3), nidx = 4 * ((i >> 1) & 3) + (lg >> 1);
      const uint32_t a0 = cfrag<2048>((c + 128 * kidx) * nidx, lg & 1), a1 = cfrag<2048>((c + 128 * (kidx + 4)) * nidx, lg & 1);
      const uint32_t b0 = cfrag<2048>(-(c + 128 * nidx) * kidx, lg & 1), b1 = cfrag<2048>(-(c + 128 * nidx) * (kidx + 4), lg & 1);
      asm volatile("st.shared.v2.u32 [%0], {%1,%2};" ::"r"(sbase + SM_FC + tid * 8), "r"(a0), "r"(a1) : "memory");
      asm volatile("st.shared.v2.u32 [%0], {%1,%2};" ::"r"(sbase + SM_FC + 2048 + tid * 8), "r"(b0), "r"(b1) : "memory");
    }
    bar_sync(NB_CONS, 256);
    uint4 fc[4];
#pragma unroll
    for (int i = 0; i < 4; i++) fc[i] = lds4(sbase + SM_FC + i * 512 + lane * 16);
    asm volatile("cp.async.wait_group 0;" ::: "memory");
    __syncwarp();
    bar_arrive(NB_INIT, 384);
    uint32_t tag, ones;
    uint4 q[4], o[4];
    {
      uint32_t v[2][8];
#pragma unroll
      for (int r = 0; r < 2; r++)
#pragma unroll
        for (int ks = 0; ks < 2; ks++) {
          const int ch = 32 * ks + 2 * (lane & 15) + (lane >> 4);
          asm volatile("ldmatrix.sync.aligned.m8n8.x4.trans.shared.b16 {%0,%1,%2,%3}, [%4];"
                       : "=r"(v[r][4 * ks]), "=r"(v[r][4 * ks + 1]), "=r"(v[r][4 * ks + 2]), "=r"(v[r][4 * ks + 3])
                       : "r"(sbase + SM_X + (2 * warp + r) * 1024 + ((ch ^ ((ch >> 3) & 1)) * 16)) : "memory");
        }
      float sq[2];
#pragma unroll
      for (int r = 0; r < 2; r++) {
        float s0 = 0.f, s1 = 0.f;
#pragma unroll
        for (int i = 0; i < 8; i++) {
          const float lo = bf_lo(v[r][i]), hi = u2f(v[r][i] & 0xffff0000u);
          s0 = fmaf(lo, lo, s0);
          s1 = fmaf(hi, hi, s1);
        }
        sq[r] = s0 + s1;
      }
      {
        float w = ((lane & 1) ? sq[1] : sq[0]) + __shfl_xor_sync(0xffffffffu, (lane & 1) ? sq[0] : sq[1], 1);
        w += __shfl_xor_sync(0xffffffffu, w, 2);
        w = sum_groups(w);
        const float o2 = __shfl_xor_sync(0xffffffffu, w, 1);
        sq[0] = (lane & 1) ? o2 : w;
        sq[1] = (lane & 1) ? w : o2;
      }
#pragma unroll
      for (int r = 0; r < 2; r++) {
        float dd[2][4], ee[2][4];
#pragma unroll
        for (int nt = 0; nt < 2; nt++) {
          mma_az(dd[nt], fa[0], v[r][2 * nt], v[r][2 * nt + 1]);
          mma_a(dd[nt], fa[1], v[r][4 + 2 * nt], v[r][5 + 2 * nt]);
          mma_az(ee[nt], fa[2], v[r][2 * nt], v[r][2 * nt + 1]);
          mma_a(ee[nt], fa[3], v[r][4 + 2 * nt], v[r][5 + 2 * nt]);
        }
        float mean = (dd[0][0] + dd[0][1]) + (dd[1][0] + dd[1][1]);
        mean += __shfl_xor_sync(0xffffffffu, mean, 1);
        mean += __shfl_xor_sync(0xffffffffu, mean, 2);
        mean = __shfl_sync(0xffffffffu, mean, 0) * (1.f / 512.f);
        const float rs = rsqrtf(fmaxf(fmaf(-mean, mean, sq[r] * (1.f / 512.f)), 0.f) + 1e-5f);
        float acc[4][4];
#pragma unroll
        for (int nt = 0; nt < 2; nt++) {
          const float (&d)[4] = dd[nt];
          const float (&e)[4] = ee[nt];
          const uint4 &ka = tw[2 * nt], &kb = tw[2 * nt + 1], &kc = tw[4 + nt];
          const uint32_t a0 = pack2(d[0] * u2f(ka.x) + d[2] * u2f(ka.y), d[1] * u2f(kb.x) + d[3] * u2f(kb.y));
          const uint32_t a2 = pack2(d[0] * u2f(ka.z) + d[2] * u2f(ka.w), d[1] * u2f(kb.z) + d[3] * u2f(kb.w));
          const uint32_t a1 = pack2(e[0] * u2f(kc.x) + e[2] * u2f(kc.y), e[1] * u2f(kc.z) + e[3] * u2f(kc.w));
          const uint32_t a3 = pack2(e[2] * u2f(kc.x) - e[0] * u2f(kc.y), e[3] * u2f(kc.z) - e[1] * u2f(kc.w));
          const uint32_t dc = pack2(fmaf(mean, -32.f, d[0]), fmaf(mean, -32.f, d[1]));
          const uint32_t h0 = g == 0 ? dc : a0, h2 = g == 0 ? 0u : a2;
          if (nt == 0) {
            mma16816_z(acc[0], a0, a1, a2, a3, fb[2 * nt].x, fb[2 * nt].y);
            mma16816_z(acc[1], a0, a1, a2, a3, fb[2 * nt].z, fb[2 * nt].w);
            mma16816_z(acc[2], h0, a1, h2, a3, fb[2 * nt + 1].x, fb[2 * nt + 1].y);
            mma16816_z(acc[3], h0, a1, h2, a3, fb[2 * nt + 1].z, fb[2 * nt + 1].w);
          } else {
            mma16816(acc[0], a0, a1, a2, a3, fb[2 * nt].x, fb[2 * nt].y);
            mma16816(acc[1], a0, a1, a2, a3, fb[2 * nt].z, fb[2 * nt].w);
            mma16816(acc[2], h0, a1, h2, a3, fb[2 * nt + 1].x, fb[2 * nt + 1].y);
            mma16816(acc[3], h0, a1, h2, a3, fb[2 * nt + 1].z, fb[2 * nt + 1].w);
          }
        }
#pragma unroll
        for (int h = 0; h < 2; h++) {
          const int j = 2 * warp + r, m = 2 * t + h;
          sts4(sbase + SM_E + ((j * 8 + m) * 8 + (g ^ (2 * t) ^ (2 * (j & 3)))) * 16,
               pack2(acc[h][0] * rs, acc[h][1] * rs), pack2(acc[h][2] * rs, acc[h][3] * rs),
               pack2(acc[2 + h][0] * rs, acc[2 + h][1] * rs), pack2(acc[2 + h][2] * rs, acc[2 + h][3] * rs));
        }
      }
      bar_sync(NB_RDY, 384);
      const uint32_t ea = sbase + SM_E + ((t * 8 + warp) * 8 + (g ^ (warp & 6) ^ (2 * t))) * 16;
      lds_frag(q[0], q[1], ea, ea + 4096);
      lds_frag(q[2], q[3], ea + 8192, ea + 12288);
      asm volatile("ld.shared.u32 %0, [%1];" : "=r"(tag) : "r"(BAR(epoch, 0)) : "memory");
      ones = ~(tag >> 31);
      tag = (tag + 1) & 1;
      cdft16(q, fc, o);
#pragma unroll
      for (int vv = 0; vv < 4; vv++) {
        o[vv].y &= ~1u;
        o[vv].z = (o[vv].z & ~1u) | (tag ^ 1);
        st_tag(&scr->Z1[(((4 * vv + t) * 8 + warp) * 128 + c) * 8 + g], o[vv], tag);
      }
    }
    asm volatile("setmaxnreg.inc.sync.aligned.u32 232;");
    {
      uint4* const zp = &scr->Z1[(c * 128 + 8 * t + warp) * 8 + g];
      const uint32_t tst = clock32();
      mbar_wait(BAR(tbar, 0));
      uint4 f2[4], g2[4];
#pragma unroll
      for (int i = 0; i < 4; i++) {
        f2[i] = lds4(TOFF(f2) + warp * 2048 + i * 512);
        g2[i] = lds4(TOFF(g2) + warp * 2048 + i * 512);
      }
      const uint4 f8 = lds4(TOFF(f8)), g8 = lds4(TOFF(g8));
      asm volatile("barrier.cluster.wait.aligned;" ::: "memory");
      spin_until(tst + POLL_DELAY);
      ld_tag4_issue<256>(q, zp);
      float wfr[16], wfi[16];
      {
        const float nyq = ((c & 7) == 7 && g == 0) ? 0.5f : 1.f;
        uint32_t wa = sbase + SM_W + (16 * warp + t) * 80 + ((2 * (c >> 3) + 2) & 15) - 2;
        asm volatile("" : "+r"(wa));
        const uint32_t wb[3] = {wa + 2 * (g == 0 ? 16 : g), wa + 2 * g, wa - 2 * g};
#pragma unroll
        for (int i = 0; i < 16; i++) {
          const int ci = i >> 3, dd = (i >> 2) & 1, e = i & 3;
          const uint32_t a = wb[e < 2 ? e : 2] + (ci * 8 + 4 * dd) * 80 + (e == 0 ? 0 : e == 1 ? 16 : e == 2 ? 64 : 48);
          wfr[i] = bf_lo(lds_u16(a)) * (e == 2 ? nyq : 1.f);
          wfi[i] = bf_lo(lds_u16(a + 10240)) * (e == 2 ? nyq : 1.f);
        }
      }
      ld_tag4_finish<256>(q, zp, tag);
      if (lane == 0) mbar_arrive(BAR(sig, 0));
#pragma unroll
      for (int i = 0; i < 4; i++) q[i].z &= ~1u;
      reg_frag(q, ones);
      cdft16(q, f2, o);
      const uint32_t e2 = sbase + SM_E2;
#pragma unroll
      for (int vv = 0; vv < 4; vv++)
        sts4(e2 + ((warp * 16 + 4 * vv + t) * 8 + (g ^ (2 * t) ^ (2 * (warp & 3)))) * 16, o[vv].x, o[vv].y, o[vv].z, o[vv].w);
      bar_sync(NB_CONS, 256);
      uint32_t ad[2], res[2][2][4];
#pragma unroll
      for (int ci = 0; ci < 2; ci++) {
        const int cc = 2 * warp + ci;
        ad[ci] = e2 + ((t * 16 + cc) * 8 + (g ^ (2 * (cc & 3)) ^ (2 * t))) * 16;
        lds_frag(q[2 * ci], q[2 * ci + 1], ad[ci], ad[ci] + 8192);
      }
#pragma unroll
      for (int ci = 0; ci < 2; ci++)
#pragma unroll
        for (int p = 0; p < 2; p++) {
          uint32_t y[2][2];
#pragma unroll
          for (int vv = 0; vv < 2; vv++) {
            float d[4];
            mma_az(d, q[2 * ci + p], word(f8, 2 * vv), word(f8, 2 * vv + 1));
#pragma unroll
            for (int rr = 0; rr < 2; rr++) {
              const float fr = wfr[ci * 8 + vv * 4 + 2 * p + rr], fi = wfi[ci * 8 + vv * 4 + 2 * p + rr];
              y[vv][rr] = pack2(d[2 * rr] * fr - d[2 * rr + 1] * fi, d[2 * rr] * fi + d[2 * rr + 1] * fr);
            }
          }
#pragma unroll
          for (int vv = 0; vv < 2; vv++) {
            float d[4];
            mma16816_z(d, y[0][0], y[0][1], y[1][0], y[1][1], word(g8, 2 * vv), word(g8, 2 * vv + 1));
            res[ci][vv][2 * p] = pack2(d[0], d[1]);
            res[ci][vv][2 * p + 1] = pack2(d[2], d[3]);
          }
        }
#pragma unroll
      for (int i = 0; i < 4; i++)
        sts4(ad[i >> 1] + (i & 1) * 8192, res[i >> 1][i & 1][0], res[i >> 1][i & 1][1], res[i >> 1][i & 1][2], res[i >> 1][i & 1][3]);
      bar_sync(NB_CONS, 256);
      const uint32_t eb = e2 + ((warp * 16 + t) * 8 + (g ^ (2 * t) ^ (2 * (warp & 3)))) * 16;
      lds_frag(q[0], q[1], eb, eb + 512);
      lds_frag(q[2], q[3], eb + 1024, eb + 1536);
      cdft16(q, g2, o);
#pragma unroll
      for (int vv = 0; vv < 4; vv++) {
        o[vv].y &= ~1u;
        o[vv].z = (o[vv].z & ~1u) | tag;
        st_tag(zp + vv * 256, o[vv], tag);
      }
    }
    {
      const uint4* const zp = &scr->Z1[((t * 8 + warp) * 128 + c) * 8 + g];
      const uint32_t tst = clock32();
      uint4 gb[4], ga[4], gc[4], tw[4];
      uint2 xr[2][4];
      uint2* lnp[2];
#pragma unroll
      for (int r = 0; r < 2; r++) {
        const int row = 16 * f + 2 * warp + r;
        lnp[r] = reinterpret_cast<uint2*>(&scr->LN[(rb * 8 + (g >> 2)) * 1024 + row * 8 + ((2 * (g & 3) + (t >> 1)) ^ (row & 7))]) + (t & 1);
        asm volatile("" : "+l"(lnp[r]));
      }
#pragma unroll
      for (int i = 0; i < 4; i++) {
        gc[i] = lds4(sbase + SM_FC + 2048 + i * 512 + lane * 16);
        gb[i] = lds4(TOFF(gb) + i * 512);
        ga[i] = lds4(TOFF(ga) + i * 512);
        tw[i] = lds4(TOFF(tw3) + i * 512);
        const int ch = 2 * (g + 8 * i) + (t >> 1);
#pragma unroll
        for (int r = 0; r < 2; r++) xr[r][i] = lds2(sbase + SM_X + (2 * warp + r) * 1024 + ((ch ^ ((ch >> 3) & 1)) * 16) + (t & 1) * 8);
      }
      spin_until(tst + POLL_DELAY2);
      ld_tag4_issue<32768>(q, zp);
      ld_tag4_finish<32768, true>(q, zp, tag);
      if (lane == 0) mbar_arrive(BAR(sig, 1));
      reg_frag(q, ones);
      cdft16(q, gc, o);
#pragma unroll
      for (int vv = 0; vv < 4; vv++)
        sts4(sbase + SM_E + (((4 * vv + t) * 8 + warp) * 8 + (g ^ (warp & 6) ^ (2 * t))) * 16, o[vv].x, o[vv].y, o[vv].z, o[vv].w);
      bar_sync(NB_CONS, 256);
      uint32_t hv[2][8];
      const float mk = t == 0 ? 0.f : 1.f;
#pragma unroll
      for (int r = 0; r < 2; r++) {
        const int j = 2 * warp + r;
        uint4 u[2];
#pragma unroll
        for (int h = 0; h < 2; h++) u[h] = lds4(sbase + SM_E + ((j * 8 + 2 * t + h) * 8 + (g ^ (2 * t) ^ (2 * (j & 3)))) * 16);
        const uint32_t bp[4][2] = {{u[0].x, u[1].x & ones}, {u[0].y & ones, u[1].y}, {u[0].z, u[1].z & ones}, {u[0].w & ones, u[1].w}};
        float y[2][2][4];
#pragma unroll
        for (int i = 0; i < 2; i++) {
          float lo[4], hi[4], e[4];
          mma_az(lo, gb[2 * i], bp[0][0], bp[0][1]);
          mma_az(hi, gb[2 * i + 1], bp[2][0], bp[2][1]);
          mma_az(e, gb[2 * i], bp[1][0], bp[1][1]);
          mma_a(e, gb[2 * i + 1], bp[3][0], bp[3][1]);
          const uint4 &ka = tw[2 * i], &kb = tw[2 * i + 1];
          const float tr0 = fmaf(hi[0], mk, lo[0]), ti0 = fmaf(hi[2], mk, lo[2]);
          const float tr1 = lo[1] + hi[1], ti1 = lo[3] + hi[3];
          const float vr0 = tr0 * u2f(ka.x) - ti0 * u2f(ka.y), vi0 = tr0 * u2f(ka.y) + ti0 * u2f(ka.x);
          const float vr1 = tr1 * u2f(ka.z) - ti1 * u2f(ka.w), vi1 = tr1 * u2f(ka.w) + ti1 * u2f(ka.z);
          const uint32_t b0 = pack2(t == 0 ? hi[0] : vr0, vr1), b1 = pack2(t == 0 ? vr0 : vi0, vi1);
          const uint32_t b2 = pack2(e[0] * u2f(kb.x) - e[2] * u2f(kb.y), e[1] * u2f(kb.z) - e[3] * u2f(kb.w));
          const uint32_t b3 = pack2(e[0] * u2f(kb.y) + e[2] * u2f(kb.x), e[1] * u2f(kb.w) + e[3] * u2f(kb.z));
#pragma unroll
          for (int mt = 0; mt < 2; mt++) {
            mma_az(y[mt][i], ga[2 * mt], b0, b1);
            mma_a(y[mt][i], ga[2 * mt + 1], b2, b3);
          }
        }
#pragma unroll
        for (int i = 0; i < 4; i++) {
          hv[r][2 * i] = hadd2_bf16(xr[r][i].x, pack2(y[i >> 1][0][2 * (i & 1)], y[i >> 1][0][2 * (i & 1) + 1]));
          hv[r][2 * i + 1] = hadd2_bf16(xr[r][i].y, pack2(y[i >> 1][1][2 * (i & 1)], y[i >> 1][1][2 * (i & 1) + 1]));
        }
      }
      float mean[2];
      uint32_t mb[2];
#pragma unroll
      for (int r = 0; r < 2; r++) {
        mean[r] = sum_groups(quad_sum(hv[r])) * (1.f / 512.f);
        mb[r] = pack2(mean[r], mean[r]);
      }
#pragma unroll
      for (int i = 0; i < 4; i++)
#pragma unroll
        for (int r = 0; r < 2; r++) {
          hv[r][2 * i] = hsub2_bf16(hv[r][2 * i], mb[r]);
          hv[r][2 * i + 1] = hsub2_bf16(hv[r][2 * i + 1], mb[r]);
          st_tag8(lnp[r] + i * 4096, hv[r][2 * i], hv[r][2 * i + 1], i == 0 ? tag : (hv[r][2 * i] & 1u));
        }
      bar_arrive(NB_LN, 288);
      const uint32_t ones2 = ~(lds2(BAR(epoch, 0)).x >> 31);
      float rstd[2];
#pragma unroll
      for (int r = 0; r < 2; r++) {
        hv[r][0] &= ones2;
        rstd[r] = row_rstd(hv[r], mean[r] - bf_lo(mb[r]));
      }
      if (lane == 0)
        st_tag(&scr->ST[rb * 64 + 8 * f + warp], make_uint4(mb[0] << 16, __float_as_uint(rstd[0]), mb[1] << 16, __float_as_uint(rstd[1])), tag);
    }
    const int wgi = warp >> 2, wq = warp & 3;
    const int wr = wgi ^ (f >> 2) ^ 1, rt = 4 * wr + wq;
    uint4* const pbase = &scr->P[rb * 28 * 1024 + rt * 128 + lane];
    const uint32_t a_lo0 = desc_lo(sbase + wr * 8192, 16);
    const uint32_t ebar = lane == 0 ? BAR(empty1, 0) : RBAR(empty1, 0);
    float r0, r1;
    uint4 px[8], py[6];
    const int rh = wgi ^ kh ^ 1;
    const uint32_t fpb = BAR(fullP, 16 * rh);
    const uint4* const psrc = &scr->P[(rb2 * 28 + 14 * kh) * 1024 + (4 * rh + wq) * 128 + lane];
    const uint32_t pa0 = sbase + (4 * rh + wq) * 2048;
    uint4 pf[3][4], ha[4][4];
    uint32_t rdy = 0, got0;
    {
      float acc[128];
#pragma unroll
      for (int i = 0; i < 128; i++) acc[i] = 0.f;
      const uint32_t b_lo0 = desc_lo(sbase + 8 * SLOT, 4096);
      const uint32_t t3 = clock32();
      if (WARM) {
        wg_fence();
#pragma unroll
        for (int i = 0; i < WARM; i++) wgmma_n256(acc, desc64(a_lo0 + 6 * 1024, HI128), desc64(b_lo0, HI128));
        wg_commit();
      }
      const uint4* const ap = &scr->LN[rb * 8 * 1024 + wr * 512 + (tid & 127)];
      uint4 av[NLL][4];
      spin_until(t3 + POLL_DELAY3);
#pragma unroll
      for (int kb = 0; kb < NLL; kb++) ld_tag4_issue<128>(av[kb], ap + kb * 1024);
      bar_sync(NB_CONS, 256);
      const uint32_t lma = sbase + (16 * rt + (lane & 15)) * 128;
      auto load_a = [&](int kb) {
#pragma unroll
        for (int ks = 0; ks < 4; ks++)
          asm volatile("ldmatrix.sync.aligned.m8n8.x4.shared.b16 {%0,%1,%2,%3}, [%4];"
                       : "=r"(ha[kb][ks].x), "=r"(ha[kb][ks].y), "=r"(ha[kb][ks].z), "=r"(ha[kb][ks].w)
                       : "r"(lma + kb * SLOT + (((2 * ks + (lane >> 4)) ^ (lane & 7)) * 16)) : "memory");
      };
      auto stash_a = [&](int kb) {
        ld_tag4_finish<128, true>(av[kb], ap + kb * 1024, tag);
#pragma unroll
        for (int i = 0; i < 4; i++)
          sts4(sbase + kb * SLOT + wr * 8192 + ((tid & 127) + 128 * i) * 16, av[kb][i].x, av[kb][i].y, av[kb][i].z, av[kb][i].w);
        bar_sync(NB_WG + wgi, 128);
      };
      stash_a(0);
      load_a(0);
#pragma unroll
      for (int n = 0; n < 8; n++) {
        const int kb = n >> 1, hh = n & 1;
        if (hh == 1 && kb < 3) {
          if (kb + 1 < NLL) stash_a(kb + 1); else mbar_wait(BAR(fullA, kb + 1));
        }
        mbar_wait(BAR(full1, n));
        const uint32_t bl = b_lo0 + ((n + 2) % 6) * 1024;
        wg_fence();
        if (hh == 1 && kb < 3) load_a(kb + 1);
        const uint4 &a0 = ha[kb][2 * hh], &a1 = ha[kb][2 * hh + 1];
        wgmma_rs_n256(acc, a0.x, a0.y, a0.z, a0.w, desc64(bl, HI128), n != 0 ? 1 : ~ones);
        wgmma_rs_n256(acc, a1.x, a1.y, a1.z, a1.w, desc64(bl + 128, HI128));
        wg_commit();
        if (hh == 1 && lane < 2) mbar_arrive_remote(ebar + (uint32_t)(offsetof(Bars, freeA) - offsetof(Bars, empty1)) + 8 * kb);
        wg_wait<1>();
        if (n != 0 && lane < 2) mbar_arrive_remote(ebar + 8 * (n - 1));
      }
      uint32_t slot = 4;
#pragma unroll 1
      for (int kb = 4; kb < 8; kb++) {
        mbar_wait(BAR(fullA, kb));
#pragma unroll
        for (int hh = 0; hh < 2; hh++) {
          if (LAGX && hh == ((16 - LAGX) & 1) && kb == ((16 - LAGX) >> 1) && wgi == 1) bar_sync(NB_LAG, 256);
          mbar_wait(BAR(full1, 2 * kb + hh));
          const uint32_t al = a_lo0 + kb * 1024 + hh * 4, bl = b_lo0 + slot * 1024;
          wg_fence();
          wgmma_n256(acc, desc64(al, HI128), desc64(bl, HI128));
          wgmma_n256(acc, desc64(al + 2, HI128), desc64(bl + 128, HI128));
          wg_commit();
          if (LAGX && hh == 1 && kb == 7 && wgi == 0) bar_arrive(NB_LAG, 256);
          wg_wait<1>();
          if (lane < 2) mbar_arrive_remote(ebar + 8 * (2 * kb + hh - 1));
          if (++slot == 6) slot = 0;
        }
      }
      mbar_wait(BAR(sbar, 0));
      r0 = __uint_as_float(lds2(sstat + (16 * rt + g) * 8).y);
      r1 = __uint_as_float(lds2(sstat + (16 * rt + g + 8) * 8).y);
      wg_wait<0>();
      if (lane < 2) mbar_arrive_remote(ebar + 8 * 15);
      make_p<8, !PACED>(acc, r0, r1, px, pbase, 14 * f + 6 * (f & 1), tag);
      if (!PACED && lane == 0) red_relaxed(&scr->cnt[(C_PX + rb) * 32 + (f >> 2)]);
    }
    {
      float acc[96];
#pragma unroll
      for (int i = 0; i < 96; i++) acc[i] = 0.f;
      const uint32_t b_lo0 = desc_lo(sbase, 2048);
      uint4* const pdst = pbase + ((7 * f + 3 * (f & 1)) >> 1) * 1024;
      auto stage_y = [&](int k) {
        if (LAGY && k == 16 - LAGY && wgi == 1) bar_sync(NB_LAG, 256);
        if (PACED && k < 4) mbar_wait_bounded(BAR(full1, 16 + k)); else mbar_wait(BAR(full1, 16 + k));
        const uint32_t al = a_lo0 + (4 + (k >> 1)) * 1024 + (k & 1) * 4, bl = b_lo0 + (k < 5 ? k * 768 : 8192 + (k - 5) * 768);
        wg_fence();
        wgmma_n192(acc, desc64(al, HI128), desc64(bl, HI64));
        wgmma_n192(acc, desc64(al + 2, HI128), desc64(bl + 64, HI64));
        wg_commit();
      };
#pragma unroll
      for (int k = 0; k < 4 * PACED; k++) {
        stage_y(k);
        st_tag(pdst + (k >> 1) * 1024 + (k & 1) * 64, px[2 * k], tag);
        st_tag(pdst + (k >> 1) * 1024 + (k & 1) * 64 + 32, px[2 * k + 1], tag);
        if (k == 3 && lane == 0) red_relaxed(&scr->cnt[(C_PX + rb) * 32 + (f >> 2)]);
        wg_wait<1>();
        if (k != 0 && lane < 2) mbar_arrive_remote(ebar + 8 * (15 + k));
      }
#pragma unroll 1
      for (int k = 4 * PACED; k < 8; k++) {
        stage_y(k);
        wg_wait<1>();
        if (k != 0 && lane < 2) mbar_arrive_remote(ebar + 8 * (15 + k));
      }
      rdy = 0;
#pragma unroll
      for (int k = 8; k < 16; k++) {
        if (LAGY && k == 16 - LAGY && wgi == 1) bar_sync(NB_LAG, 256);
        if (!rdy) mbar_wait(BAR(full1, 16 + k));
        const uint32_t bl = b_lo0 + 8192 + ((k - 5) & 7) * 768;
        const uint4 &a0 = ha[(k - 8) >> 1][2 * (k & 1)], &a1 = ha[(k - 8) >> 1][2 * (k & 1) + 1];
        wg_fence();
        if (k < 15) rdy = mbar_test(BAR(full1, 17 + k));
        wgmma_rs_n192(acc, a0.x, a0.y, a0.z, a0.w, desc64(bl, HI64));
        wgmma_rs_n192(acc, a1.x, a1.y, a1.z, a1.w, desc64(bl + 64, HI64));
        wg_commit();
        if (LAGY && k == 15 && wgi == 0) bar_arrive(NB_LAG, 256);
        wg_wait<1>();
        if (lane < 2) mbar_arrive_remote(ebar + 8 * (15 + k));
      }
      got0 = __all_sync(0xffffffffu, mbar_test((fpb + 8 * (0))));
      if (got0) {
#pragma unroll
        for (int kk = 0; kk < 4; kk++) pf[0][kk] = lds4(pa0 + 3 * SLOT + kk * 512 + lane * 16);
      }
      wg_wait<0>();
      if (lane < 2) mbar_arrive_remote(ebar + 8 * 31);
      const int ks0 = 14 * f + ((f & 1) ? 0 : 8);
      auto reread = [&]() {
        asm volatile("ld.volatile.shared.f32 %0, [%2+4]; ld.volatile.shared.f32 %1, [%2+68];" : "=f"(r0), "=f"(r1) : "r"(sstat + (16 * rt + g) * 8) : "memory");
      };
      make_p<6, true, 0, 2>(acc, r0, r1, py, pbase, ks0, tag);
      if (REDPOS == 2 && lane == 0) red_relaxed(&scr->cnt[(C_PY + rb) * 32 + 4 * wgi + (f >> 1)]);
      reread();
      make_p<6, true, 2, 4>(acc, r0, r1, py, pbase, ks0, tag);
      if (REDPOS == 4 && lane == 0) red_relaxed(&scr->cnt[(C_PY + rb) * 32 + 4 * wgi + (f >> 1)]);
      reread();
      rdy = mbar_test(BAR(full2, 0)) & mbar_test((fpb + 8 * (1)));
      make_p<6, true, 4, 6>(acc, r0, r1, py, pbase, ks0, tag);
      if (REDPOS == 6 && lane == 0) red_relaxed(&scr->cnt[(C_PY + rb) * 32 + 4 * wgi + (f >> 1)]);
    }
    {
      float acc[64];
      const uint32_t b2_lo0 = desc_lo(sbase, 8192);
      const uint32_t pbar = rh == rk ? BAR(emptyP, 0) : RBAR(emptyP, 0);
      if (!got0) {
        mbar_wait((fpb + 8 * (0)));
#pragma unroll
        for (int kk = 0; kk < 4; kk++) pf[0][kk] = lds4(pa0 + 3 * SLOT + kk * 512 + lane * 16);
      }
#pragma unroll
      for (int s = 0; s < 14; s++) {
        uint4 (&a)[4] = pf[s % 3];
        ld_tag4_finish<32>(a, psrc + (int)((KORDER >> (4 * s)) & 15) * 1024, tag);
        if (s < 9 && lane == 0) mbar_arrive_remote(pbar + 8 * s);
        if (s >= 2) {
          wg_wait<1>();
          if (s <= 7 && lane == 0) mbar_arrive(BAR(empty2, s - 2));
        }
        if (!rdy) {
          if (s < 13) mbar_wait((fpb + 8 * (s + 1)));
          mbar_wait(BAR(full2, s));
        }
        if (s == 14 - LAG2 && wgi == 1) bar_sync(NB_LAG, 256);
        const uint32_t bl = b2_lo0 + (uint32_t)((BSLOT >> (4 * s)) & 15) * 1024;
        wg_fence();
        if (s < 13) {
#pragma unroll
          for (int kk = 0; kk < 4; kk++)
            pf[(s + 1) % 3][kk] = lds4(pa0 + (uint32_t)((PSLOT >> (4 * (s + 1))) & 15) * SLOT + kk * 512 + lane * 16);
          rdy = mbar_test(BAR(full2, s + 1));
          if (s < 12) rdy &= mbar_test((fpb + 8 * (s + 2)));
        }
        if (s == 0) wgmma_rs_n128(acc, a[0].x, a[0].y, a[0].z, a[0].w, desc64(bl, HI128), 0);
        else wgmma_rs_n128(acc, a[0].x, a[0].y, a[0].z, a[0].w, desc64(bl, HI128));
#pragma unroll
        for (int kk = 1; kk < 4; kk++) wgmma_rs_n128(acc, a[kk].x, a[kk].y, a[kk].z, a[kk].w, desc64(bl + kk * 128, HI128));
        wg_commit();
      }
      if (wgi == 0) {
        bar_arrive(NB_LAG, 256);
        uint4* const dst = &scr->Z1[(tid >> 3) * 1024 + (c ^ 4) * 8 + (tid & 7)];
        wg_wait<0>();
#pragma unroll
        for (int i = 0; i < 8; i++)
          st_tag(dst + i * 16384, make_uint4(pack2(acc[8 * i], acc[8 * i + 1]), pack2(acc[8 * i + 2], acc[8 * i + 3]) | 1u,
                                           pack2(acc[8 * i + 4], acc[8 * i + 5]), pack2(acc[8 * i + 6], acc[8 * i + 7])), tag);
      } else {
        uint4 pv[2][4];
        const uint4* const xsrc = &scr->Z1[((tid & 127) >> 3) * 1024 + c * 8 + (tid & 7)];
        ld_tag4_issue<16384>(pv[0], xsrc);
        ld_tag4_issue<16384>(pv[1], xsrc + 65536);
        uint32_t w[32];
        {
          const uint32_t m0 = __byte_perm(lds2(sstat + 1024 + (16 * wq + g) * 8).x, 0, 0x3232);
          const uint32_t m1 = __byte_perm(lds2(sstat + 1024 + (16 * wq + g + 8) * 8).x, 0, 0x3232);
          const uint32_t hb = sbase + 13 * SLOT + (16 * wq + (lane & 15)) * 128;
          const uint32_t mk = ((t & 1) == 0 && nq == 0) ? ~1u : ~0u;
          mbar_wait(BAR(hbar, 0));
#pragma unroll
          for (int i = 0; i < 8; i++) {
            asm volatile("ldmatrix.sync.aligned.m8n8.x4.shared.b16 {%0,%1,%2,%3}, [%4];"
                         : "=r"(w[4 * i]), "=r"(w[4 * i + 1]), "=r"(w[4 * i + 2]), "=r"(w[4 * i + 3])
                         : "r"(hb + (i >> 2) * 8192 + (((2 * (i & 3) + (lane >> 4)) ^ (lane & 7)) * 16)) : "memory");
#pragma unroll
            for (int e = 0; e < 4; e++) w[4 * i + e] = hadd2_bf16(w[4 * i + e] & mk, (e & 1) ? m1 : m0);
          }
        }
        wg_wait<0>();
#pragma unroll
        for (int i = 0; i < 32; i++) w[i] = hadd2_bf16(w[i], pack2(acc[2 * i], acc[2 * i + 1]));
#pragma unroll 1
        while (!__all_sync(0xffffffffu, pv[0][0].y & pv[0][1].y & pv[0][2].y & pv[0][3].y & pv[1][0].y & pv[1][1].y & pv[1][2].y & pv[1][3].y & 1u)) {
          ld_tag4_issue<16384>(pv[0], xsrc);
          ld_tag4_issue<16384>(pv[1], xsrc + 65536);
        }
#pragma unroll
        for (int i = 0; i < 8; i++) {
          const uint4& p = pv[i >> 2][i & 3];
          asm volatile("stmatrix.sync.aligned.m8n8.x4.shared.b16 [%0], {%1,%2,%3,%4};"
                       ::"r"(pa0 + (11 + ((lane >> 3) & 1)) * SLOT + (lane & 7) * 256 + (((2 * i + (lane >> 4)) ^ (lane & 7)) * 16)),
                         "r"(hadd2_bf16(w[4 * i], p.x & ~1u)), "r"(hadd2_bf16(w[4 * i + 1], p.y & ~1u)), "r"(hadd2_bf16(w[4 * i + 2], p.z)),
                         "r"(hadd2_bf16(w[4 * i + 3], p.w)) : "memory");
        }
        __syncwarp();
        uint4* const dst = reinterpret_cast<uint4*>(out) + (16 * (c >> 4) + 2 * (4 * rh + wq) + (rb2 & 1) + 128 * (lane >> 4)) * 64 + nq * 16 + (lane & 15);
#pragma unroll
        for (int i = 0; i < 8; i++) {
          const int r = 2 * (i & 3) + (lane >> 4);
          dst[i * 256 * 64] = lds4(pa0 + (11 + (i >> 2)) * SLOT + r * 256 + (((lane & 15) ^ r) * 16));
        }
      }
      if (lane == 0) mbar_arrive(BAR(done, 0));
    }
  }
#undef BAR
#undef TOFF
#undef RBAR
}

typedef CUresult (*EncodeFn)(CUtensorMap*, CUtensorMapDataType, cuuint32_t, void*, const cuuint64_t*, const cuuint64_t*,
                             const cuuint32_t*, const cuuint32_t*, CUtensorMapInterleave, CUtensorMapSwizzle,
                             CUtensorMapL2promotion, CUtensorMapFloatOOBfill);

}

extern "C" void kernel_launch(void* const* d_in, const int* in_sizes, int n_in, void* d_out, int out_size) {
  (void)in_sizes; (void)n_in; (void)out_size;
  static EncodeFn encode = nullptr;
  static void *tab = nullptr, *scr = nullptr;
  if (!encode) {
    void* fn = nullptr;
    cudaDriverEntryPointQueryResult qr;
    cudaGetDriverEntryPoint("cuTensorMapEncodeTiled", &fn, cudaEnableDefault, &qr);
    encode = (EncodeFn)fn;
    cudaGetSymbolAddress(&tab, g_tab);
    cudaGetSymbolAddress(&scr, g_scr);
    cudaFuncSetAttribute(fused_kernel, cudaFuncAttributeMaxDynamicSharedMemorySize, SMEM_BYTES);
  }
  CUtensorMap tmGX, tmUX, tmGY, tmUY, tmD, tmWR, tmWI;
  const cuuint32_t es[5] = {1, 1, 1, 1, 1};
  auto enc = [&](CUtensorMap* m, void* p, int rank, const cuuint64_t* gd, const cuuint64_t* gs, const cuuint32_t* bd,
                 CUtensorMapSwizzle sw, CUtensorMapL2promotion pr) {
    encode(m, CU_TENSOR_MAP_DATA_TYPE_BFLOAT16, rank, p, gd, gs, bd, es, CU_TENSOR_MAP_INTERLEAVE_NONE, sw, pr,
           CU_TENSOR_MAP_FLOAT_OOB_FILL_NONE);
  };
  {
    const cuuint64_t gd[3] = {64, 512, 28}, gs[2] = {3584, 128};
    const cuuint32_t bd[3] = {64, 32, 2};
    enc(&tmGX, d_in[4], 3, gd, gs, bd, CU_TENSOR_MAP_SWIZZLE_128B, CU_TENSOR_MAP_L2_PROMOTION_L2_256B);
    enc(&tmUX, d_in[5], 3, gd, gs, bd, CU_TENSOR_MAP_SWIZZLE_128B, CU_TENSOR_MAP_L2_PROMOTION_L2_256B);
  }
  {
    const cuuint64_t gd[3] = {32, 512, 56}, gs[2] = {3584, 64};
    const cuuint32_t bd[3] = {32, 32, 3};
    enc(&tmGY, d_in[4], 3, gd, gs, bd, CU_TENSOR_MAP_SWIZZLE_64B, CU_TENSOR_MAP_L2_PROMOTION_L2_128B);
    enc(&tmUY, d_in[5], 3, gd, gs, bd, CU_TENSOR_MAP_SWIZZLE_64B, CU_TENSOR_MAP_L2_PROMOTION_L2_128B);
  }
  {
    const cuuint64_t gd[3] = {64, 1792, 8}, gs[2] = {1024, 128};
    const cuuint32_t bd[3] = {64, 64, 2};
    enc(&tmD, d_in[6], 3, gd, gs, bd, CU_TENSOR_MAP_SWIZZLE_128B, CU_TENSOR_MAP_L2_PROMOTION_L2_256B);
  }
  {
    const cuuint64_t gd[3] = {4112, 8, 16}, gs[2] = {16 * 8224, 8224};
    const cuuint32_t bd[3] = {40, 8, 16};
    enc(&tmWR, d_in[1], 3, gd, gs, bd, CU_TENSOR_MAP_SWIZZLE_NONE, CU_TENSOR_MAP_L2_PROMOTION_NONE);
    enc(&tmWI, d_in[2], 3, gd, gs, bd, CU_TENSOR_MAP_SWIZZLE_NONE, CU_TENSOR_MAP_L2_PROMOTION_NONE);
  }
  fused_kernel<<<NCTA, NTHREADS, SMEM_BYTES>>>((const __nv_bfloat16*)d_in[0], (const Tables*)tab, (Scratch*)scr,
                                               (__nv_bfloat16*)d_out, (const char*)d_in[4], (const char*)d_in[5],
                                               (const char*)d_in[6], tmWR, tmWI, tmGX, tmUX, tmGY, tmUY, tmD);
}
```

```cpp
#include <cuda_runtime.h>
#include <cuda_bf16.h>
#include <cuda.h>
#include <stdint.h>

namespace {

constexpr int NCTA = 128;
constexpr int NTHREADS = 384;
constexpr int SLOT = 16384;
constexpr int SMEM_BYTES = 14 * SLOT + 3072;
constexpr int SPIN_LIMIT = 1 << 22;

struct Scratch {
  uint4 Z1[128 * 1024];
  uint4 LN[16 * 8 * 1024];
  uint4 P[16 * 28 * 1024];
  uint4 ST[1024];
  unsigned cnt[64 * 32];
};
__device__ __align__(1024) Scratch g_scr;

constexpr double ccos(int i, int n) {
  i &= n - 1;
  if (i > n / 2) i = n - i;
  if (4 * i == n) return 0.0;
  const bool neg = 4 * i > n;
  if (neg) i = n / 2 - i;
  const double a = 6.283185307179586476925 * i / n, a2 = a * a;
  double term = 1.0, sum = 1.0;
  for (int k = 1; k < 14; k++) { term *= -a2 / ((2 * k - 1) * (2 * k)); sum += term; }
  return neg ? -sum : sum;
}
constexpr double csin(int i, int n) { return ccos(i - n / 4, n); }
constexpr unsigned fbits(double v, int mant) {
  if (v == 0.0) return 0;
  const unsigned sg = v < 0 ? 1u : 0u;
  if (v < 0) v = -v;
  int e = 127;
  while (v < 1.0) { v *= 2.0; e--; }
  const unsigned m = (unsigned)((v - 1.0) * (double)(1u << mant) + 0.5);
  return (sg << (8 + mant)) + ((unsigned)e << mant) + m;
}
constexpr unsigned pkb(double lo, double hi) { return fbits(lo, 7) | (fbits(hi, 7) << 16); }
constexpr double fa_elem(int mt, int r, int n1) {
  const int k1 = 8 * mt + (r & 7);
  return r < 8 ? ccos(k1 * n1, 32) : k1 == 0 ? ccos(16 * n1, 32) : -csin(k1 * n1, 32);
}
constexpr unsigned cfrag_c(int idx, int n, int ri, double s = 1.0) {
  return ri ? pkb(-s * csin(idx, n), s * ccos(idx, n)) : pkb(s * ccos(idx, n), s * csin(idx, n));
}
struct Tables {
  unsigned fa[4][32][4];
  unsigned fb[4][32][4];
  unsigned tw1[6][32][4];
  unsigned f2[8][4][32][4];
  unsigned g2[8][4][32][4];
  unsigned gb[4][32][4];
  unsigned ga[4][32][4];
  unsigned tw3[4][32][4];
  unsigned f8[32][4], g8[32][4];
};
constexpr int T1_BYTES = 7168, T2_BYTES = 39936;
static_assert(sizeof(Tables) == T1_BYTES + T2_BYTES, "table size");
constexpr Tables make_tables() {
  Tables T = {};
  for (int l = 0; l < 32; l++) {
    const int g = l >> 2, t = l & 3;
    for (int a = 0; a < 2; a++)
      for (int b = 0; b < 2; b++) {
        for (int r = 0; r < 4; r++) {
          const int row = g + 8 * (r & 1), col = 2 * t + 8 * (r >> 1);
          T.fa[2 * a + b][l][r] = pkb(fa_elem(a, row, 16 * b + col), fa_elem(a, row, 16 * b + col + 1));
          T.ga[2 * a + b][l][r] = pkb(fa_elem(b, col, 16 * a + row), fa_elem(b, col + 1, 16 * a + row));
        }
        const double sg = b ? -1.0 : 1.0;
        for (int h = 0; h < 2; h++) {
          const int ri = g & 1, m = 2 * (g >> 1) + h, k2 = b ? 15 - m : m;
          const int pa = (8 * a + 2 * t) * k2, pb = (8 * a + 2 * t + 1) * k2;
          T.fb[2 * a + b][l][2 * h] = ri == 0 ? pkb(ccos(pa, 16), ccos(pb, 16)) : pkb(-sg * csin(pa, 16), -sg * csin(pb, 16));
          T.fb[2 * a + b][l][2 * h + 1] = ri == 0 ? pkb(csin(pa, 16), csin(pb, 16)) : pkb(sg * ccos(pa, 16), sg * ccos(pb, 16));
        }
        const int n2 = 4 * (g >> 1) + 2 * a + (g & 1);
        for (int h = 0; h < 2; h++) {
          const int p = n2 * (b ? 15 - 2 * t - h : 2 * t + h);
          T.gb[2 * a + b][l][2 * h] = pkb(ccos(p, 16), -sg * csin(p, 16));
          T.gb[2 * a + b][l][2 * h + 1] = pkb(csin(p, 16), sg * ccos(p, 16));
          const int k1 = 8 * b + 2 * t + h, q = n2 * (k1 == 0 ? 16 : k1);
          T.tw3[2 * a + b][l][2 * h] = fbits(ccos(q, 512), 23);
          T.tw3[2 * a + b][l][2 * h + 1] = fbits(csin(q, 512), 23);
        }
        const int p = (8 * a + 2 * t + b) * (g == 0 ? 16 : g);
        T.tw1[2 * a + b][l][0] = fbits(g == 0 ? 0.0 : ccos(p, 512), 23);
        T.tw1[2 * a + b][l][1] = fbits(g == 0 ? ccos(p, 512) : csin(p, 512), 23);
        T.tw1[2 * a + b][l][2] = fbits(g == 0 ? 0.0 : -csin(p, 512), 23);
        T.tw1[2 * a + b][l][3] = fbits(g == 0 ? -csin(p, 512) : ccos(p, 512), 23);
        T.tw1[4 + a][l][2 * b] = fbits(ccos((8 * a + 2 * t + b) * (g + 8), 512), 23);
        T.tw1[4 + a][l][2 * b + 1] = fbits(csin((8 * a + 2 * t + b) * (g + 8), 512), 23);
      }
    for (int i = 0; i < 4; i++) {
      const int p8 = (t + 4 * (i & 1)) * (4 * (i >> 1) + (g >> 1));
      T.f8[l][i] = cfrag_c(p8, 8, g & 1);
      T.g8[l][i] = cfrag_c(-p8, 8, g & 1, 1.0 / (1 << 19));
    }
    for (int w = 0; w < 8; w++)
      for (int i = 0; i < 16; i++) {
        const int kidx = t + 4 * (i & 1) + 8 * (i >> 3), nidx = 4 * ((i >> 1) & 3) + (g >> 1);
        T.f2[w][i >> 2][l][i & 3] = cfrag_c((8 * kidx + w) * nidx, 128, g & 1);
        T.g2[w][i >> 2][l][i & 3] = cfrag_c(-(8 * nidx + w) * kidx, 128, g & 1);
      }
  }
  return T;
}
__device__ const __align__(128) Tables g_tab = make_tables();

__device__ __forceinline__ void die() { asm volatile("st.global.u32 [%0], %1;" ::"l"(0ull), "r"(0) : "memory"); }
__device__ __forceinline__ uint32_t s2u(const void* p) { return (uint32_t)__cvta_generic_to_shared(p); }
__device__ __forceinline__ void mbar_init(uint32_t b, int c) { asm volatile("mbarrier.init.shared::cta.b64 [%0], %1;" ::"r"(b), "r"(c)); }
__device__ __forceinline__ void mbar_expect(uint32_t b, int bytes) {
  asm volatile("mbarrier.arrive.expect_tx.shared::cta.b64 _, [%0], %1;" ::"r"(b), "r"(bytes) : "memory");
}
__device__ __forceinline__ void mbar_arrive(uint32_t b) { asm volatile("mbarrier.arrive.shared::cta.b64 _, [%0];" ::"r"(b) : "memory"); }
__device__ __forceinline__ uint32_t mbar_try(uint32_t b, uint32_t parity) {
  uint32_t ok;
  asm volatile("{.reg .pred p; mbarrier.try_wait.parity.shared::cta.b64 p, [%1], %2; selp.u32 %0,1,0,p;}"
               : "=r"(ok) : "r"(b), "r"(parity) : "memory");
  return ok;
}
__device__ __forceinline__ uint32_t mbar_test(uint32_t b) {
  uint32_t ok;
  asm volatile("{.reg .pred p; mbarrier.test_wait.parity.shared::cta.b64 p, [%1], 0; selp.u32 %0,1,0,p;}" : "=r"(ok) : "r"(b) : "memory");
  return ok;
}
__device__ __forceinline__ void mbar_wait_bounded(uint32_t b) {
  int it = 0;
#pragma unroll 1
  while (!mbar_try(b, 0))
    if (++it > SPIN_LIMIT) { die(); break; }
}
__device__ __forceinline__ void mbar_wait(uint32_t b) {
  asm volatile("{.reg .pred p;\nW_%=: mbarrier.try_wait.parity.shared::cta.b64 p, [%0], 0;\n@!p bra W_%=;}" ::"r"(b) : "memory");
}
__device__ __forceinline__ void bar_sync(int id, int n) { asm volatile("bar.sync %0, %1;" ::"r"(id), "r"(n) : "memory"); }
__device__ __forceinline__ void bar_arrive(int id, int n) { asm volatile("bar.arrive %0, %1;" ::"r"(id), "r"(n) : "memory"); }
__device__ __forceinline__ void red_release(unsigned* p) { asm volatile("red.release.gpu.global.add.u32 [%0], 1;" ::"l"(p) : "memory"); }
__device__ __forceinline__ void red_relaxed(unsigned* p) { asm volatile("red.relaxed.gpu.global.add.u32 [%0], 1;" ::"l"(p) : "memory"); }
__device__ __forceinline__ unsigned ld_acquire(const unsigned* p) {
  unsigned v;
  asm volatile("ld.acquire.gpu.global.u32 %0, [%1];" : "=r"(v) : "l"(p) : "memory");
  return v;
}
__device__ __forceinline__ unsigned ld_relaxed(const unsigned* p) {
  unsigned v;
  asm volatile("ld.relaxed.gpu.global.u32 %0, [%1];" : "=r"(v) : "l"(p) : "memory");
  return v;
}
__device__ __forceinline__ void wait_counter(const unsigned* p, unsigned target) {
#pragma unroll 1
  while ((int)(ld_acquire(p) - target) < 0) {}
}
__device__ __forceinline__ void sts4(uint32_t a, uint32_t x, uint32_t y, uint32_t z, uint32_t w) {
  asm volatile("st.shared.v4.u32 [%0], {%1,%2,%3,%4};" ::"r"(a), "r"(x), "r"(y), "r"(z), "r"(w) : "memory");
}
__device__ __forceinline__ uint4 lds4(uint32_t a) {
  uint4 v;
  asm volatile("ld.shared.v4.u32 {%0,%1,%2,%3}, [%4];" : "=r"(v.x), "=r"(v.y), "=r"(v.z), "=r"(v.w) : "r"(a) : "memory");
  return v;
}
__device__ __forceinline__ uint32_t pack2(float lo, float hi) {
  uint32_t r;
  asm("cvt.rn.bf16x2.f32 %0, %1, %2;" : "=r"(r) : "f"(hi), "f"(lo));
  return r;
}
__device__ __forceinline__ float bf_lo(uint32_t v) { return __uint_as_float(v << 16); }
__device__ __forceinline__ uint32_t hadd2_bf16(uint32_t a, uint32_t b) {
  uint32_t r;
  asm("add.rn.bf16x2 %0, %1, %2;" : "=r"(r) : "r"(a), "r"(b));
  return r;
}
__device__ __forceinline__ void mma16816(float (&d)[4], uint32_t a0, uint32_t a1, uint32_t a2, uint32_t a3, uint32_t b0, uint32_t b1) {
  asm("mma.sync.aligned.m16n8k16.row.col.f32.bf16.bf16.f32 {%0,%1,%2,%3}, {%4,%5,%6,%7}, {%8,%9}, {%0,%1,%2,%3};"
      : "+f"(d[0]), "+f"(d[1]), "+f"(d[2]), "+f"(d[3])
      : "r"(a0), "r"(a1), "r"(a2), "r"(a3), "r"(b0), "r"(b1));
}
__device__ __forceinline__ void mma16816_z(float (&d)[4], uint32_t a0, uint32_t a1, uint32_t a2, uint32_t a3, uint32_t b0, uint32_t b1) {
  asm("{.reg .f32 z; mov.f32 z, 0f00000000;\n"
      "mma.sync.aligned.m16n8k16.row.col.f32.bf16.bf16.f32 {%0,%1,%2,%3}, {%4,%5,%6,%7}, {%8,%9}, {z,z,z,z};}"
      : "=f"(d[0]), "=f"(d[1]), "=f"(d[2]), "=f"(d[3])
      : "r"(a0), "r"(a1), "r"(a2), "r"(a3), "r"(b0), "r"(b1));
}
template <int N>
__device__ __forceinline__ void cs_frac(int idx, float& c, float& s) {
  int i = ((idx + N / 2) & (N - 1)) - N / 2;
  float a = (float)i * (6.283185307179586f / N);
  c = __cosf(a);
  s = __sinf(a);
}
template <int N>
__device__ __forceinline__ uint32_t cfrag(int idx, int ri) {
  float c, s;
  cs_frac<N>(idx, c, s);
  return ri ? pack2(-s, c) : pack2(c, s);
}
__device__ __forceinline__ uint32_t word(const uint4& v, int e) { return e == 0 ? v.x : e == 1 ? v.y : e == 2 ? v.z : v.w; }
__device__ __forceinline__ void cdft16(const uint4 (&A)[4], const uint4 (&F)[4], uint4 (&o)[4]) {
  float acc[2][4][4];
#pragma unroll
  for (int ks = 0; ks < 2; ks++)
#pragma unroll
    for (int p = 0; p < 2; p++)
#pragma unroll
      for (int v = 0; v < 4; v++) {
        const uint4& a = A[2 * ks + p];
        const uint32_t b0 = word(F[ks * 2 + (v >> 1)], (v & 1) * 2), b1 = word(F[ks * 2 + (v >> 1)], (v & 1) * 2 + 1);
        if (ks == 0) mma16816_z(acc[p][v], a.x, a.y, a.z, a.w, b0, b1);
        else mma16816(acc[p][v], a.x, a.y, a.z, a.w, b0, b1);
      }
#pragma unroll
  for (int v = 0; v < 4; v++)
    o[v] = make_uint4(pack2(acc[0][v][0], acc[0][v][1]), pack2(acc[0][v][2], acc[0][v][3]),
                      pack2(acc[1][v][0], acc[1][v][1]), pack2(acc[1][v][2], acc[1][v][3]));
}
__device__ __forceinline__ void lds_frag(uint4& f0, uint4& f1, uint32_t a0, uint32_t a1) {
  asm volatile("ld.volatile.shared.v2.u32 {%0,%1}, [%8]; ld.volatile.shared.v2.u32 {%2,%3}, [%9];\n"
               "ld.volatile.shared.v2.u32 {%4,%5}, [%8+8]; ld.volatile.shared.v2.u32 {%6,%7}, [%9+8];"
               : "=r"(f0.x), "=r"(f0.y), "=r"(f0.z), "=r"(f0.w), "=r"(f1.x), "=r"(f1.y), "=r"(f1.z), "=r"(f1.w) : "r"(a0), "r"(a1) : "memory");
}
__device__ __forceinline__ void reg_frag(uint4 (&q)[4], uint32_t ones) {
#pragma unroll
  for (int ks = 0; ks < 2; ks++) {
    const uint4 a = q[2 * ks], b = q[2 * ks + 1];
    q[2 * ks] = make_uint4(a.x, a.y, b.x & ones, b.y & ones);
    q[2 * ks + 1] = make_uint4(a.z & ones, a.w & ones, b.z, b.w);
  }
}
__device__ __forceinline__ void st_tag(uint4* p, const uint4& v, uint32_t tag) {
  asm volatile("st.relaxed.gpu.global.v4.b32 [%0], {%1,%2,%3,%4};"
               ::"l"(p), "r"((v.x & ~1u) | tag), "r"(v.y), "r"(v.z), "r"(v.w) : "memory");
}
__device__ __forceinline__ void st_tag8(void* p, uint32_t x, uint32_t y, uint32_t tag) {
  asm volatile("st.relaxed.gpu.global.v2.b32 [%0], {%1,%2};" ::"l"(p), "r"((x & ~1u) | tag), "r"(y) : "memory");
}
__device__ __forceinline__ uint4 ld_b128(const uint4* p) {
  uint4 v;
  asm volatile("ld.relaxed.gpu.global.v4.b32 {%0,%1,%2,%3}, [%4];"
               : "=r"(v.x), "=r"(v.y), "=r"(v.z), "=r"(v.w) : "l"(p) : "memory");
  return v;
}
template <int STRIDE>
__device__ __forceinline__ void ld_tag4_issue(uint4 (&q)[4], const uint4* p) {
#pragma unroll
  for (int i = 0; i < 4; i++) q[i] = ld_b128(p + i * STRIDE);
}
__device__ __forceinline__ uint32_t tag_miss(uint32_t a, uint32_t b, uint32_t c, uint32_t d, uint32_t tag) {
  uint32_t r;
  asm("{.reg .b32 u, v; lop3.b32 u, %1, %2, %5, 0x7e; lop3.b32 v, %3, %4, %5, 0x7e; lop3.b32 %0, u, v, 1, 0xa8;}"
      : "=r"(r) : "r"(a), "r"(b), "r"(c), "r"(d), "r"(tag));
  return r;
}
template <int STRIDE, bool HALVES = false>
__device__ __forceinline__ void ld_tag4_finish(uint4 (&q)[4], const uint4* p, uint32_t tag) {
  int it = 0;
#pragma unroll 1
  while (__any_sync(0xffffffffu, tag_miss(q[0].x, q[1].x, q[2].x, q[3].x, tag) | (HALVES ? tag_miss(q[0].z, q[1].z, q[2].z, q[3].z, tag) : 0u))) {
    ld_tag4_issue<STRIDE>(q, p);
    if (++it > SPIN_LIMIT) { die(); break; }
  }
#pragma unroll
  for (int i = 0; i < 4; i++) {
    asm volatile("and.b32 %0, %0, 0xfffffffe;" : "+r"(q[i].x));
    if (HALVES) q[i].z &= ~1u;
  }
}
__device__ __forceinline__ float quad_sum(const uint32_t (&a)[8]) {
  float d[4];
  mma16816_z(d, a[0], a[1], a[2], a[3], 0x3f803f80u, 0x3f803f80u);
  mma16816(d, a[4], a[5], a[6], a[7], 0x3f803f80u, 0x3f803f80u);
  return d[0] + d[2];
}
__device__ __forceinline__ float sum_groups(float v) {
  v += __shfl_xor_sync(0xffffffffu, v, 4);
  v += __shfl_xor_sync(0xffffffffu, v, 8);
  v += __shfl_xor_sync(0xffffffffu, v, 16);
  return v;
}
__device__ __forceinline__ uint32_t hsub2_bf16(uint32_t a, uint32_t b) {
  uint32_t r;
  asm("sub.rn.bf16x2 %0, %1, %2;" : "=r"(r) : "r"(a), "r"(b));
  return r;
}
__device__ __forceinline__ float row_rstd(const uint32_t (&c)[8], float delta) {
  uint32_t s[8];
#pragma unroll
  for (int i = 0; i < 8; i++) asm("mul.rn.bf16x2 %0, %1, %1;" : "=r"(s[i]) : "r"(c[i]));
  return rsqrtf(fmaxf(fmaf(-delta, delta, sum_groups(quad_sum(s)) * (1.f / 512.f)), 0.f) + 1e-5f);
}
__device__ __forceinline__ uint64_t desc64(uint32_t lo, uint32_t hi) {
  uint64_t d;
  asm("mov.b64 %0, {%1, %2};" : "=l"(d) : "r"(lo), "r"(hi));
  return d;
}
constexpr uint32_t desc_hi(uint32_t sbo, uint32_t swz) { return (sbo >> 4) | (swz << 30); }
__device__ __forceinline__ uint32_t desc_lo(uint32_t addr, uint32_t lbo) { return ((addr & 0x3FFFF) >> 4) | ((lbo >> 4) << 16); }
__device__ __forceinline__ void cp_async16(uint32_t dst, const void* src) {
  asm volatile("cp.async.cg.shared.global [%0], [%1], 16;" ::"r"(dst), "l"(src) : "memory");
}
__device__ __forceinline__ uint2 lds2(uint32_t a) {
  uint2 v;
  asm volatile("ld.shared.v2.u32 {%0,%1}, [%2];" : "=r"(v.x), "=r"(v.y) : "r"(a) : "memory");
  return v;
}
__device__ __forceinline__ uint32_t lds_u16(uint32_t a) {
  uint16_t v;
  asm volatile("ld.shared.u16 %0, [%1];" : "=h"(v) : "r"(a) : "memory");
  return v;
}
__device__ __forceinline__ void wg_fence() { asm volatile("wgmma.fence.sync.aligned;" ::: "memory"); }
__device__ __forceinline__ void wg_commit() { asm volatile("wgmma.commit_group.sync.aligned;" ::: "memory"); }
template <int N>
__device__ __forceinline__ void wg_wait() { asm volatile("wgmma.wait_group.sync.aligned %0;" ::"n"(N) : "memory"); }
__device__ __forceinline__ void bulk_load(uint32_t dst, const void* src, int bytes, uint32_t bar) {
  asm volatile("cp.async.bulk.shared::cluster.global.mbarrier::complete_tx::bytes [%0], [%1], %2, [%3];"
               ::"r"(dst), "l"(src), "r"(bytes), "r"(bar) : "memory");
}
__device__ __forceinline__ void bulk_load_mc(uint32_t dst, const void* src, int bytes, uint32_t bar) {
  asm volatile("cp.async.bulk.shared::cluster.global.mbarrier::complete_tx::bytes.multicast::cluster [%0], [%1], %2, [%3], %4;"
               ::"r"(dst), "l"(src), "r"(bytes), "r"(bar), "h"((uint16_t)3) : "memory");
}
__device__ __forceinline__ void tma3(uint32_t dst, const CUtensorMap* tm, uint32_t bar, int c0, int c1, int c2) {
  asm volatile("cp.async.bulk.tensor.3d.shared::cluster.global.mbarrier::complete_tx::bytes [%0], [%1, {%3,%4,%5}], [%2];"
               ::"r"(dst), "l"(tm), "r"(bar), "r"(c0), "r"(c1), "r"(c2) : "memory");
}
__device__ __forceinline__ void tma3_mc(uint32_t dst, const CUtensorMap* tm, uint32_t bar, int c1, int c2) {
  asm volatile("cp.async.bulk.tensor.3d.shared::cluster.global.mbarrier::complete_tx::bytes.multicast::cluster [%0], [%1, {%3,%4,%5}], [%2], %6;"
               ::"r"(dst), "l"(tm), "r"(bar), "r"(0), "r"(c1), "r"(c2), "h"((uint16_t)3) : "memory");
}
__device__ __forceinline__ void mbar_arrive_remote(uint32_t rb) {
  asm volatile("mbarrier.arrive.shared::cluster.b64 _, [%0];" ::"r"(rb) : "memory");
}
__device__ __forceinline__ uint4 ldg_ca4(const void* p) {
  uint4 v;
  asm volatile("ld.global.ca.v4.u32 {%0,%1,%2,%3}, [%4];" : "=r"(v.x), "=r"(v.y), "=r"(v.z), "=r"(v.w) : "l"(p) : "memory");
  return v;
}
__device__ __forceinline__ float u2f(uint32_t v) { return __uint_as_float(v); }
__device__ __forceinline__ void mma_az(float (&d)[4], const uint4& a, uint32_t b0, uint32_t b1) { mma16816_z(d, a.x, a.y, a.z, a.w, b0, b1); }
__device__ __forceinline__ void mma_a(float (&d)[4], const uint4& a, uint32_t b0, uint32_t b1) { mma16816(d, a.x, a.y, a.z, a.w, b0, b1); }
__device__ __forceinline__ uint32_t clock32() {
  uint32_t v;
  asm volatile("mov.u32 %0, %%clock;" : "=r"(v) :: "memory");
  return v;
}
__device__ __forceinline__ float swiglu(float g, float u, float r) {
  float hg = (0.5f * r) * g, th;
  asm("tanh.approx.f32 %0, %1;" : "=f"(th) : "f"(hg));
  return fmaf(hg, th, hg) * (r * u);
}
__device__ __forceinline__ void l2_prefetch(const void* p, int bytes) {
  asm volatile("cp.async.bulk.prefetch.L2.global [%0], %1;" ::"l"(p), "r"(bytes) : "memory");
}

__device__ __forceinline__ void wgmma_n256(float (&d)[128], uint64_t da, uint64_t db, int sd = 1) {
  asm volatile("{.reg .pred p; setp.ne.b32 p, %130, 0;\n"
      "wgmma.mma_async.sync.aligned.m64n256k16.f32.bf16.bf16 {"
      "%0,%1,%2,%3,%4,%5,%6,%7,%8,%9,%10,%11,%12,%13,%14,%15,"
      "%16,%17,%18,%19,%20,%21,%22,%23,%24,%25,%26,%27,%28,%29,%30,%31,"
      "%32,%33,%34,%35,%36,%37,%38,%39,%40,%41,%42,%43,%44,%45,%46,%47,"
      "%48,%49,%50,%51,%52,%53,%54,%55,%56,%57,%58,%59,%60,%61,%62,%63,"
      "%64,%65,%66,%67,%68,%69,%70,%71,%72,%73,%74,%75,%76,%77,%78,%79,"
      "%80,%81,%82,%83,%84,%85,%86,%87,%88,%89,%90,%91,%92,%93,%94,%95,"
      "%96,%97,%98,%99,%100,%101,%102,%103,%104,%105,%106,%107,%108,%109,%110,%111,"
      "%112,%113,%114,%115,%116,%117,%118,%119,%120,%121,%122,%123,%124,%125,%126,%127"
      "}, %128, %129, p, 1, 1, 0, 1;}\n"
      : "+f"(d[0]),"+f"(d[1]),"+f"(d[2]),"+f"(d[3]),"+f"(d[4]),"+f"(d[5]),"+f"(d[6]),"+f"(d[7]),
        "+f"(d[8]),"+f"(d[9]),"+f"(d[10]),"+f"(d[11]),"+f"(d[12]),"+f"(d[13]),"+f"(d[14]),"+f"(d[15]),
        "+f"(d[16]),"+f"(d[17]),"+f"(d[18]),"+f"(d[19]),"+f"(d[20]),"+f"(d[21]),"+f"(d[22]),"+f"(d[23]),
        "+f"(d[24]),"+f"(d[25]),"+f"(d[26]),"+f"(d[27]),"+f"(d[28]),"+f"(d[29]),"+f"(d[30]),"+f"(d[31]),
        "+f"(d[32]),"+f"(d[33]),"+f"(d[34]),"+f"(d[35]),"+f"(d[36]),"+f"(d[37]),"+f"(d[38]),"+f"(d[39]),
        "+f"(d[40]),"+f"(d[41]),"+f"(d[42]),"+f"(d[43]),"+f"(d[44]),"+f"(d[45]),"+f"(d[46]),"+f"(d[47]),
        "+f"(d[48]),"+f"(d[49]),"+f"(d[50]),"+f"(d[51]),"+f"(d[52]),"+f"(d[53]),"+f"(d[54]),"+f"(d[55]),
        "+f"(d[56]),"+f"(d[57]),"+f"(d[58]),"+f"(d[59]),"+f"(d[60]),"+f"(d[61]),"+f"(d[62]),"+f"(d[63]),
        "+f"(d[64]),"+f"(d[65]),"+f"(d[66]),"+f"(d[67]),"+f"(d[68]),"+f"(d[69]),"+f"(d[70]),"+f"(d[71]),
        "+f"(d[72]),"+f"(d[73]),"+f"(d[74]),"+f"(d[75]),"+f"(d[76]),"+f"(d[77]),"+f"(d[78]),"+f"(d[79]),
        "+f"(d[80]),"+f"(d[81]),"+f"(d[82]),"+f"(d[83]),"+f"(d[84]),"+f"(d[85]),"+f"(d[86]),"+f"(d[87]),
        "+f"(d[88]),"+f"(d[89]),"+f"(d[90]),"+f"(d[91]),"+f"(d[92]),"+f"(d[93]),"+f"(d[94]),"+f"(d[95]),
        "+f"(d[96]),"+f"(d[97]),"+f"(d[98]),"+f"(d[99]),"+f"(d[100]),"+f"(d[101]),"+f"(d[102]),"+f"(d[103]),
        "+f"(d[104]),"+f"(d[105]),"+f"(d[106]),"+f"(d[107]),"+f"(d[108]),"+f"(d[109]),"+f"(d[110]),"+f"(d[111]),
        "+f"(d[112]),"+f"(d[113]),"+f"(d[114]),"+f"(d[115]),"+f"(d[116]),"+f"(d[117]),"+f"(d[118]),"+f"(d[119]),
        "+f"(d[120]),"+f"(d[121]),"+f"(d[122]),"+f"(d[123]),"+f"(d[124]),"+f"(d[125]),"+f"(d[126]),"+f"(d[127])
      : "l"(da), "l"(db), "r"(sd));
}
__device__ __forceinline__ void wgmma_n192(float (&d)[96], uint64_t da, uint64_t db) {
  asm volatile("wgmma.mma_async.sync.aligned.m64n192k16.f32.bf16.bf16 {"
      "%0,%1,%2,%3,%4,%5,%6,%7,%8,%9,%10,%11,%12,%13,%14,%15,"
      "%16,%17,%18,%19,%20,%21,%22,%23,%24,%25,%26,%27,%28,%29,%30,%31,"
      "%32,%33,%34,%35,%36,%37,%38,%39,%40,%41,%42,%43,%44,%45,%46,%47,"
      "%48,%49,%50,%51,%52,%53,%54,%55,%56,%57,%58,%59,%60,%61,%62,%63,"
      "%64,%65,%66,%67,%68,%69,%70,%71,%72,%73,%74,%75,%76,%77,%78,%79,"
      "%80,%81,%82,%83,%84,%85,%86,%87,%88,%89,%90,%91,%92,%93,%94,%95"
      "}, %96, %97, 1, 1, 1, 0, 1;\n"
      : "+f"(d[0]),"+f"(d[1]),"+f"(d[2]),"+f"(d[3]),"+f"(d[4]),"+f"(d[5]),"+f"(d[6]),"+f"(d[7]),
        "+f"(d[8]),"+f"(d[9]),"+f"(d[10]),"+f"(d[11]),"+f"(d[12]),"+f"(d[13]),"+f"(d[14]),"+f"(d[15]),
        "+f"(d[16]),"+f"(d[17]),"+f"(d[18]),"+f"(d[19]),"+f"(d[20]),"+f"(d[21]),"+f"(d[22]),"+f"(d[23]),
        "+f"(d[24]),"+f"(d[25]),"+f"(d[26]),"+f"(d[27]),"+f"(d[28]),"+f"(d[29]),"+f"(d[30]),"+f"(d[31]),
        "+f"(d[32]),"+f"(d[33]),"+f"(d[34]),"+f"(d[35]),"+f"(d[36]),"+f"(d[37]),"+f"(d[38]),"+f"(d[39]),
        "+f"(d[40]),"+f"(d[41]),"+f"(d[42]),"+f"(d[43]),"+f"(d[44]),"+f"(d[45]),"+f"(d[46]),"+f"(d[47]),
        "+f"(d[48]),"+f"(d[49]),"+f"(d[50]),"+f"(d[51]),"+f"(d[52]),"+f"(d[53]),"+f"(d[54]),"+f"(d[55]),
        "+f"(d[56]),"+f"(d[57]),"+f"(d[58]),"+f"(d[59]),"+f"(d[60]),"+f"(d[61]),"+f"(d[62]),"+f"(d[63]),
        "+f"(d[64]),"+f"(d[65]),"+f"(d[66]),"+f"(d[67]),"+f"(d[68]),"+f"(d[69]),"+f"(d[70]),"+f"(d[71]),
        "+f"(d[72]),"+f"(d[73]),"+f"(d[74]),"+f"(d[75]),"+f"(d[76]),"+f"(d[77]),"+f"(d[78]),"+f"(d[79]),
        "+f"(d[80]),"+f"(d[81]),"+f"(d[82]),"+f"(d[83]),"+f"(d[84]),"+f"(d[85]),"+f"(d[86]),"+f"(d[87]),
        "+f"(d[88]),"+f"(d[89]),"+f"(d[90]),"+f"(d[91]),"+f"(d[92]),"+f"(d[93]),"+f"(d[94]),"+f"(d[95])
      : "l"(da), "l"(db));
}
__device__ __forceinline__ void wgmma_rs_n128(float (&d)[64], uint32_t a0, uint32_t a1, uint32_t a2, uint32_t a3, uint64_t db, int sd = 1) {
  asm volatile("{.reg .pred p; setp.ne.b32 p, %69, 0;\n"
      "wgmma.mma_async.sync.aligned.m64n128k16.f32.bf16.bf16 {"
      "%0,%1,%2,%3,%4,%5,%6,%7,%8,%9,%10,%11,%12,%13,%14,%15,"
      "%16,%17,%18,%19,%20,%21,%22,%23,%24,%25,%26,%27,%28,%29,%30,%31,"
      "%32,%33,%34,%35,%36,%37,%38,%39,%40,%41,%42,%43,%44,%45,%46,%47,"
      "%48,%49,%50,%51,%52,%53,%54,%55,%56,%57,%58,%59,%60,%61,%62,%63"
      "}, {%64,%65,%66,%67}, %68, p, 1, 1, 1;}\n"
      : "+f"(d[0]),"+f"(d[1]),"+f"(d[2]),"+f"(d[3]),"+f"(d[4]),"+f"(d[5]),"+f"(d[6]),"+f"(d[7]),
        "+f"(d[8]),"+f"(d[9]),"+f"(d[10]),"+f"(d[11]),"+f"(d[12]),"+f"(d[13]),"+f"(d[14]),"+f"(d[15]),
        "+f"(d[16]),"+f"(d[17]),"+f"(d[18]),"+f"(d[19]),"+f"(d[20]),"+f"(d[21]),"+f"(d[22]),"+f"(d[23]),
        "+f"(d[24]),"+f"(d[25]),"+f"(d[26]),"+f"(d[27]),"+f"(d[28]),"+f"(d[29]),"+f"(d[30]),"+f"(d[31]),
        "+f"(d[32]),"+f"(d[33]),"+f"(d[34]),"+f"(d[35]),"+f"(d[36]),"+f"(d[37]),"+f"(d[38]),"+f"(d[39]),
        "+f"(d[40]),"+f"(d[41]),"+f"(d[42]),"+f"(d[43]),"+f"(d[44]),"+f"(d[45]),"+f"(d[46]),"+f"(d[47]),
        "+f"(d[48]),"+f"(d[49]),"+f"(d[50]),"+f"(d[51]),"+f"(d[52]),"+f"(d[53]),"+f"(d[54]),"+f"(d[55]),
        "+f"(d[56]),"+f"(d[57]),"+f"(d[58]),"+f"(d[59]),"+f"(d[60]),"+f"(d[61]),"+f"(d[62]),"+f"(d[63])
      : "r"(a0), "r"(a1), "r"(a2), "r"(a3), "l"(db), "r"(sd));
}
__device__ __forceinline__ void wgmma_rs_n256(float (&d)[128], uint32_t a0, uint32_t a1, uint32_t a2, uint32_t a3, uint64_t db, int sd = 1) {
  asm volatile("{.reg .pred p; setp.ne.b32 p, %133, 0;\n"
      "wgmma.mma_async.sync.aligned.m64n256k16.f32.bf16.bf16 {"
      "%0,%1,%2,%3,%4,%5,%6,%7,%8,%9,%10,%11,%12,%13,%14,%15,"
      "%16,%17,%18,%19,%20,%21,%22,%23,%24,%25,%26,%27,%28,%29,%30,%31,"
      "%32,%33,%34,%35,%36,%37,%38,%39,%40,%41,%42,%43,%44,%45,%46,%47,"
      "%48,%49,%50,%51,%52,%53,%54,%55,%56,%57,%58,%59,%60,%61,%62,%63,"
      "%64,%65,%66,%67,%68,%69,%70,%71,%72,%73,%74,%75,%76,%77,%78,%79,"
      "%80,%81,%82,%83,%84,%85,%86,%87,%88,%89,%90,%91,%92,%93,%94,%95,"
      "%96,%97,%98,%99,%100,%101,%102,%103,%104,%105,%106,%107,%108,%109,%110,%111,"
      "%112,%113,%114,%115,%116,%117,%118,%119,%120,%121,%122,%123,%124,%125,%126,%127"
      "}, {%128,%129,%130,%131}, %132, p, 1, 1, 1;}\n"
      : "+f"(d[0]),"+f"(d[1]),"+f"(d[2]),"+f"(d[3]),"+f"(d[4]),"+f"(d[5]),"+f"(d[6]),"+f"(d[7]),
        "+f"(d[8]),"+f"(d[9]),"+f"(d[10]),"+f"(d[11]),"+f"(d[12]),"+f"(d[13]),"+f"(d[14]),"+f"(d[15]),
        "+f"(d[16]),"+f"(d[17]),"+f"(d[18]),"+f"(d[19]),"+f"(d[20]),"+f"(d[21]),"+f"(d[22]),"+f"(d[23]),
        "+f"(d[24]),"+f"(d[25]),"+f"(d[26]),"+f"(d[27]),"+f"(d[28]),"+f"(d[29]),"+f"(d[30]),"+f"(d[31]),
        "+f"(d[32]),"+f"(d[33]),"+f"(d[34]),"+f"(d[35]),"+f"(d[36]),"+f"(d[37]),"+f"(d[38]),"+f"(d[39]),
        "+f"(d[40]),"+f"(d[41]),"+f"(d[42]),"+f"(d[43]),"+f"(d[44]),"+f"(d[45]),"+f"(d[46]),"+f"(d[47]),
        "+f"(d[48]),"+f"(d[49]),"+f"(d[50]),"+f"(d[51]),"+f"(d[52]),"+f"(d[53]),"+f"(d[54]),"+f"(d[55]),
        "+f"(d[56]),"+f"(d[57]),"+f"(d[58]),"+f"(d[59]),"+f"(d[60]),"+f"(d[61]),"+f"(d[62]),"+f"(d[63]),
        "+f"(d[64]),"+f"(d[65]),"+f"(d[66]),"+f"(d[67]),"+f"(d[68]),"+f"(d[69]),"+f"(d[70]),"+f"(d[71]),
        "+f"(d[72]),"+f"(d[73]),"+f"(d[74]),"+f"(d[75]),"+f"(d[76]),"+f"(d[77]),"+f"(d[78]),"+f"(d[79]),
        "+f"(d[80]),"+f"(d[81]),"+f"(d[82]),"+f"(d[83]),"+f"(d[84]),"+f"(d[85]),"+f"(d[86]),"+f"(d[87]),
        "+f"(d[88]),"+f"(d[89]),"+f"(d[90]),"+f"(d[91]),"+f"(d[92]),"+f"(d[93]),"+f"(d[94]),"+f"(d[95]),
        "+f"(d[96]),"+f"(d[97]),"+f"(d[98]),"+f"(d[99]),"+f"(d[100]),"+f"(d[101]),"+f"(d[102]),"+f"(d[103]),
        "+f"(d[104]),"+f"(d[105]),"+f"(d[106]),"+f"(d[107]),"+f"(d[108]),"+f"(d[109]),"+f"(d[110]),"+f"(d[111]),
        "+f"(d[112]),"+f"(d[113]),"+f"(d[114]),"+f"(d[115]),"+f"(d[116]),"+f"(d[117]),"+f"(d[118]),"+f"(d[119]),
        "+f"(d[120]),"+f"(d[121]),"+f"(d[122]),"+f"(d[123]),"+f"(d[124]),"+f"(d[125]),"+f"(d[126]),"+f"(d[127])
      : "r"(a0), "r"(a1), "r"(a2), "r"(a3), "l"(db), "r"(sd));
}
__device__ __forceinline__ void wgmma_rs_n192(float (&d)[96], uint32_t a0, uint32_t a1, uint32_t a2, uint32_t a3, uint64_t db) {
  asm volatile("wgmma.mma_async.sync.aligned.m64n192k16.f32.bf16.bf16 {"
      "%0,%1,%2,%3,%4,%5,%6,%7,%8,%9,%10,%11,%12,%13,%14,%15,"
      "%16,%17,%18,%19,%20,%21,%22,%23,%24,%25,%26,%27,%28,%29,%30,%31,"
      "%32,%33,%34,%35,%36,%37,%38,%39,%40,%41,%42,%43,%44,%45,%46,%47,"
      "%48,%49,%50,%51,%52,%53,%54,%55,%56,%57,%58,%59,%60,%61,%62,%63,"
      "%64,%65,%66,%67,%68,%69,%70,%71,%72,%73,%74,%75,%76,%77,%78,%79,"
      "%80,%81,%82,%83,%84,%85,%86,%87,%88,%89,%90,%91,%92,%93,%94,%95"
      "}, {%96,%97,%98,%99}, %100, 1, 1, 1, 1;\n"
      : "+f"(d[0]),"+f"(d[1]),"+f"(d[2]),"+f"(d[3]),"+f"(d[4]),"+f"(d[5]),"+f"(d[6]),"+f"(d[7]),
        "+f"(d[8]),"+f"(d[9]),"+f"(d[10]),"+f"(d[11]),"+f"(d[12]),"+f"(d[13]),"+f"(d[14]),"+f"(d[15]),
        "+f"(d[16]),"+f"(d[17]),"+f"(d[18]),"+f"(d[19]),"+f"(d[20]),"+f"(d[21]),"+f"(d[22]),"+f"(d[23]),
        "+f"(d[24]),"+f"(d[25]),"+f"(d[26]),"+f"(d[27]),"+f"(d[28]),"+f"(d[29]),"+f"(d[30]),"+f"(d[31]),
        "+f"(d[32]),"+f"(d[33]),"+f"(d[34]),"+f"(d[35]),"+f"(d[36]),"+f"(d[37]),"+f"(d[38]),"+f"(d[39]),
        "+f"(d[40]),"+f"(d[41]),"+f"(d[42]),"+f"(d[43]),"+f"(d[44]),"+f"(d[45]),"+f"(d[46]),"+f"(d[47]),
        "+f"(d[48]),"+f"(d[49]),"+f"(d[50]),"+f"(d[51]),"+f"(d[52]),"+f"(d[53]),"+f"(d[54]),"+f"(d[55]),
        "+f"(d[56]),"+f"(d[57]),"+f"(d[58]),"+f"(d[59]),"+f"(d[60]),"+f"(d[61]),"+f"(d[62]),"+f"(d[63]),
        "+f"(d[64]),"+f"(d[65]),"+f"(d[66]),"+f"(d[67]),"+f"(d[68]),"+f"(d[69]),"+f"(d[70]),"+f"(d[71]),
        "+f"(d[72]),"+f"(d[73]),"+f"(d[74]),"+f"(d[75]),"+f"(d[76]),"+f"(d[77]),"+f"(d[78]),"+f"(d[79]),
        "+f"(d[80]),"+f"(d[81]),"+f"(d[82]),"+f"(d[83]),"+f"(d[84]),"+f"(d[85]),"+f"(d[86]),"+f"(d[87]),
        "+f"(d[88]),"+f"(d[89]),"+f"(d[90]),"+f"(d[91]),"+f"(d[92]),"+f"(d[93]),"+f"(d[94]),"+f"(d[95])
      : "r"(a0), "r"(a1), "r"(a2), "r"(a3), "l"(db));
}


constexpr int C_LN = 0, C_PX = 16, C_PY = 32;
constexpr int NB_CONS = 1, NB_LN = 2, NB_LAG = 4, NB_INIT = 6, NB_RDY = 7, NB_WG = 8;
constexpr int LAGX = 3;
constexpr int LAGY = 6;
constexpr int LAG2 = 5;
constexpr int NLL = 2;
constexpr int POLL_DELAY3 = 600;
constexpr int POLL_DELAY = 1200;
constexpr int FILT_DELAY = 800;
constexpr int WARM = 4;
constexpr int ALEAD = 6;
constexpr int POLL_DELAY2 = 1000;
constexpr int REDPOS = 4;
constexpr int XTRIG = 20;
constexpr int HTRIG = 0;
constexpr int PACED = 1;
constexpr int RING_SIG = 1;
constexpr int PF2_SIG = 1;
constexpr int SM_E = 0, SM_X = 16384, SM_E2 = 32768, SM_W = 49152, SM_FC = 69632, SM_T = 73728 - T1_BYTES;
constexpr unsigned long long KORDER = 0xBA9432DC876510ull;
constexpr unsigned long long BSLOT = 0x52140A98D52140ull, PSLOT = 0xB763CB763CB763ull;
constexpr unsigned long long BDEP = 0xFFEC97531ull, PDEP = 0xBA754ull;
constexpr uint32_t HI128 = desc_hi(1024, 1), HI64 = desc_hi(512, 2);

struct Bars {
  uint64_t full1[32], empty1[32], freeA[4], full2[16], fullA[8], empty2[8], emptyP[9], sig[2], done, fullP[32], hbar, tbar, hint[3], sbar;
  uint32_t epoch, pad;
};

template <int NK, bool STORE, int J0 = 0, int J1 = NK>
__device__ __forceinline__ void make_p(const float (&acc)[NK * 16], float r0, float r1, uint4 (&p)[NK], uint4* pbase, int ks0, uint32_t tag) {
#pragma unroll
  for (int j = J0; j < J1; j++) {
    uint32_t w[4];
#pragma unroll
    for (int i = 0; i < 4; i++) {
      const int a = 8 * j + 2 * i, b = a + NK * 8;
      w[i] = pack2(swiglu(acc[a], acc[b], (i & 1) ? r1 : r0), swiglu(acc[a + 1], acc[b + 1], (i & 1) ? r1 : r0));
    }
    asm volatile("" : "+r"(w[0]), "+r"(w[1]), "+r"(w[2]), "+r"(w[3]));
    p[j] = make_uint4(w[0], w[1], w[2], w[3]);
    if (STORE) st_tag(pbase + ((ks0 + j) >> 2) * 1024 + ((ks0 + j) & 3) * 32, p[j], tag);
  }
}
__device__ __forceinline__ void spin_until(uint32_t t) {
  while ((int)(clock32() - t) < 0) {}
}

__global__ void __cluster_dims__(2, 1, 1) __launch_bounds__(NTHREADS, 1)
fused_kernel(const __nv_bfloat16* __restrict__ x, const Tables* __restrict__ tab, Scratch* __restrict__ scr,
             __nv_bfloat16* __restrict__ out, const char* __restrict__ wg_raw, const char* __restrict__ wu_raw,
             const char* __restrict__ wd_raw,
             const __grid_constant__ CUtensorMap tmWR, const __grid_constant__ CUtensorMap tmWI,
             const __grid_constant__ CUtensorMap tmGX, const __grid_constant__ CUtensorMap tmUX,
             const __grid_constant__ CUtensorMap tmGY, const __grid_constant__ CUtensorMap tmUY,
             const __grid_constant__ CUtensorMap tmD) {
  extern __shared__ __align__(1024) char smem_raw[];
  const uint32_t sbase = s2u(smem_raw);
  const uint32_t sbar = sbase + 14 * SLOT, sstat = sbar + 1408;
  const int tid = threadIdx.x, lane = tid & 31;
  const int c = blockIdx.x, rk = c & 1, f = (c >> 1) & 7, rb = 2 * (c >> 4) + rk;
  const int rb2 = 2 * (c >> 4) + (f >> 2), kh = (f >> 1) & 1, nq = 2 * (f & 1) + rk;
#define BAR(field, i) (sbar + (uint32_t)offsetof(Bars, field) + 8u * (i))
#define TOFF(field) (sbase + SM_T + (uint32_t)offsetof(Tables, field) + lane * 16)

  if (tid >= 256) {
    asm volatile("setmaxnreg.dec.sync.aligned.u32 40;");
    const int warp = __shfl_sync(0xffffffffu, tid >> 5, 0);
    if (lane == 0) {
      auto init = [&](uint32_t b, int n, int count, int bytes) {
#pragma unroll
        for (int i = 0; i < n; i++) mbar_init(b + 8 * i, count);
#pragma unroll
        for (int i = 0; i < (bytes ? n : 0); i++) mbar_expect(b + 8 * i, bytes);
      };
      if (warp == 8) {
        if (sbase & 1023) die();
        init(BAR(tbar, 0), 1, 1, T2_BYTES + 2 * 10240);
        init(BAR(hbar, 0), 1, 1, 16384);
        init(BAR(hint, 0), 3, 1, 0);
        init(BAR(sbar, 0), 1, 32, 0);
        init(BAR(empty2, 0), 20, 8, 0);
      } else if (warp == 9) {
        init(BAR(full1, 0), 16, 1, 16384);
        init(BAR(full1, 16), 16, 1, 12288);
      } else if (warp == 10) {
        init(BAR(fullP, 0), 30, 1, 8192);
      } else {
        init(BAR(full2, 0), 24, 1, 16384);
        init(BAR(empty1, 0), 36, 16, 0);
      }
      asm volatile("fence.mbarrier_init.release.cluster;" ::: "memory");
    }
    if (tid == 256) {
      const int w0 = ((c >> 3) * 257 + 32 * (c & 7) + 1) & ~7;
      if (FILT_DELAY) {
        asm volatile("prefetch.tensormap [%0];" ::"l"(&tmWR) : "memory");
        asm volatile("prefetch.tensormap [%0];" ::"l"(&tmWI) : "memory");
        spin_until(clock32() + FILT_DELAY);
      }
      tma3(sbase + SM_W, &tmWR, BAR(tbar, 0), w0, 0, 0);
      tma3(sbase + SM_W + 10240, &tmWI, BAR(tbar, 0), w0, 0, 0);
      bulk_load(sbase + SM_T + T1_BYTES, reinterpret_cast<const char*>(tab) + T1_BYTES, T2_BYTES, BAR(tbar, 0));
    }
    if (tid == 288) {
      asm volatile("prefetch.tensormap [%0];" ::"l"(rk ? &tmUX : &tmGX) : "memory");
      asm volatile("prefetch.tensormap [%0];" ::"l"(rk ? &tmUY : &tmGY) : "memory");
      asm volatile("prefetch.tensormap [%0];" ::"l"(&tmD) : "memory");
    }
    if (tid == 320) {
      const unsigned e = ld_relaxed(&scr->cnt[(C_LN + rb) * 32]) >> 3;
      asm volatile("st.shared.u32 [%0], %1;" ::"r"(BAR(epoch, 0)), "r"(e) : "memory");
    }
    __syncwarp();
    asm volatile("barrier.cluster.arrive.relaxed.aligned;" ::: "memory");
    bar_arrive(NB_RDY, 384);
    asm volatile("barrier.cluster.wait.aligned;" ::: "memory");
    bar_sync(NB_INIT, 384);
    unsigned epoch;
    asm volatile("ld.shared.u32 %0, [%1];" : "=r"(epoch) : "r"(BAR(epoch, 0)) : "memory");
    if (warp == 8) {
      if (lane == 0) {
        const int ax = (7 * f + 3 * (f & 1)) >> 1;
        const int ay = 7 * f + ((f & 1) ? 0 : 4);
        const CUtensorMap* tx = rk ? &tmUX : &tmGX;
        const CUtensorMap* ty = rk ? &tmUY : &tmGY;
        if (RING_SIG >= 0) mbar_wait_bounded(BAR(sig, RING_SIG));
        uint32_t s = 2;
#pragma unroll 1
        for (int n = 0; n < 16; n++) {
          if (n >= 6) mbar_wait_bounded(BAR(empty1, n - 6));
          tma3_mc(sbase + (8 + s) * SLOT + rk * 8192, tx, BAR(full1, n), n * 32, ax);
          if (++s == 6) s = 0;
          if (n >= 10 && n < 15) {
            const int k = n - 10;
            mbar_wait_bounded(BAR(freeA, (12 * k + 11) >> 4));
            tma3_mc(sbase + k * 12288 + rk * 6144, ty, BAR(full1, 16 + k), (k + 8) * 32, ay);
          }
        }
#pragma unroll 1
        for (int k = 5; k < 16; k++) {
          mbar_wait_bounded(BAR(empty1, k < 13 ? 10 + ((12 * (k - 5) + 11) >> 4) : 8 + k));
          tma3_mc(sbase + 8 * SLOT + ((k - 5) & 7) * 12288 + rk * 6144, ty, BAR(full1, 16 + k), ((k + 8) & 15) * 32, ay);
        }
        mbar_wait_bounded(BAR(done, 0));
      }
    } else if (warp == 9) {
      if (lane == 0) {
        mbar_wait(BAR(fullA, 4));
        wait_counter(&scr->cnt[(C_LN + rb2) * 32], (epoch + 1) * 8);
        asm volatile("fence.proxy.async.global;" ::: "memory");
#pragma unroll 1
        for (int i = 0; i < 14; i++) {
          const int kblk = 14 * kh + (int)((KORDER >> (4 * i)) & 15);
          mbar_wait(i < 9 ? BAR(empty1, 16 + (uint32_t)((BDEP >> (4 * i)) & 15)) : BAR(empty2, i - 9));
          tma3(sbase + (uint32_t)((BSLOT >> (4 * i)) & 15) * SLOT, &tmD, BAR(full2, i), 0, 64 * kblk, 2 * nq);
        }
        mbar_wait(BAR(empty2, 5));
        bulk_load(sbase + 13 * SLOT, &scr->LN[(rb2 * 8 + 2 * nq) * 1024 + kh * 512], 8192, BAR(hbar, 0));
        bulk_load(sbase + 13 * SLOT + 8192, &scr->LN[(rb2 * 8 + 2 * nq + 1) * 1024 + kh * 512], 8192, BAR(hbar, 0));
      }
    } else if (warp == 10) {
      bar_sync(NB_LN, 288);
      if (lane == 0) {
        red_release(&scr->cnt[(C_LN + rb) * 32]);
        wait_counter(&scr->cnt[(C_LN + rb) * 32], (epoch + 1) * 8);
        asm volatile("fence.proxy.async.global;" ::: "memory");
#pragma unroll 1
        for (int kb = NLL; kb < 8; kb++) {
          if (2 * kb >= ALEAD) mbar_wait(BAR(empty1, 2 * kb - ALEAD));
          bulk_load(sbase + kb * SLOT, &scr->LN[(rb * 8 + kb) * 1024], 16384, BAR(fullA, kb));
        }
#pragma unroll 1
        for (int s = 0; s < 14; s++) {
          const int kblk = 14 * kh + (int)((KORDER >> (4 * s)) & 15);
          if (s == 0 || s == 8 || s == 11) {
            mbar_wait(BAR(hint, s == 0 ? 0 : s == 8 ? 1 : 2));
          }
          mbar_wait(s < 5 ? BAR(empty1, 16 + (uint32_t)((PDEP >> (4 * s)) & 15)) : BAR(emptyP, s - 5));
          bulk_load_mc(sbase + (uint32_t)((PSLOT >> (4 * s)) & 15) * SLOT + rk * 8192, &scr->P[(rb2 * 28 + kblk) * 1024 + rk * 512], 8192, BAR(fullP, 16 * rk + s));
        }
      }
    } else {
      if (lane == 0) {
        mbar_wait(BAR(tbar, 0));
        l2_prefetch(wg_raw + (size_t)c * 5376, 5376);
        l2_prefetch(wu_raw + (size_t)c * 5376, 5376);
        mbar_wait(BAR(sig, PF2_SIG));
        l2_prefetch(wg_raw + 688128 + (size_t)c * 8960, 8960);
        l2_prefetch(wu_raw + 688128 + (size_t)c * 8960, 8960);
      }
      mbar_wait(BAR(fullA, 4));
      if (lane == 0) l2_prefetch(wd_raw + (size_t)c * 14336, 14336);
      {
        const uint32_t tag = (epoch + 1) & 1;
        uint4 v0, v1, v2;
        while (true) {
          v0 = ld_b128(&scr->ST[rb * 64 + lane]);
          v1 = ld_b128(&scr->ST[rb * 64 + 32 + lane]);
          v2 = ld_b128(&scr->ST[rb2 * 64 + 32 * kh + lane]);
          if (!__any_sync(0xffffffffu, ((v0.x ^ tag) | (v1.x ^ tag) | (v2.x ^ tag)) & 1u)) break;
        }
        sts4(sstat + lane * 16, v0.x & ~1u, v0.y, v0.z, v0.w);
        sts4(sstat + 512 + lane * 16, v1.x & ~1u, v1.y, v1.z, v1.w);
        sts4(sstat + 1024 + lane * 16, v2.x & ~1u, v2.y, v2.z, v2.w);
        mbar_arrive(BAR(sbar, 0));
      }
      if (lane == 0) {
        mbar_wait(BAR(empty1, XTRIG));
        while ((int)(ld_relaxed(&scr->cnt[(C_PX + rb2) * 32 + kh]) - (epoch + 1) * 32) < 0) {
        }
        mbar_arrive(BAR(hint, 0));
        mbar_wait(BAR(emptyP, HTRIG));
        uint32_t done = 0;
        while (done != 3) {
          uint2 v;
          asm volatile("ld.relaxed.gpu.global.v2.u32 {%0,%1}, [%2];" : "=r"(v.x), "=r"(v.y) : "l"(&scr->cnt[(C_PY + rb2) * 32 + 4 * (rk ^ kh ^ 1) + 2 * kh]) : "memory");
          if (!(done & 1) && (int)(v.x - (epoch + 1) * 8) >= 0) { done |= 1; mbar_arrive(BAR(hint, 1)); }
          if (!(done & 2) && (int)(v.y - (epoch + 1) * 8) >= 0) { done |= 2; mbar_arrive(BAR(hint, 2)); }
        }
      }
    }
  } else {
    const int warp = __shfl_sync(0xffffffffu, tid >> 5, 0);
    const int g = lane >> 2, t = lane & 3;
    uint4 fa[4], fb[4], tw[6];
#pragma unroll
    for (int i = 0; i < 4; i++) fa[i] = ldg_ca4(&tab->fa[i][lane][0]);
#pragma unroll
    for (int i = 0; i < 6; i++) tw[i] = ldg_ca4(&tab->tw1[i][lane][0]);
#pragma unroll
    for (int i = 0; i < 4; i++) fb[i] = ldg_ca4(&tab->fb[i][lane][0]);
#pragma unroll
    for (int i = 0; i < 4; i++) {
      const int r = i >> 1, ch = (i & 1) * 32 + lane;
      cp_async16(sbase + SM_X + (2 * warp + r) * 1024 + ((ch ^ ((ch >> 3) & 1)) * 16),
                 x + (size_t)(c + 128 * (2 * warp + r)) * 512 + ch * 8);
    }
    asm volatile("cp.async.commit_group;" ::: "memory");
    asm volatile("barrier.cluster.arrive.relaxed.aligned;" ::: "memory");
    uint32_t rbar;
    asm volatile("mapa.shared::cluster.u32 %0, %1, %2;" : "=r"(rbar) : "r"(sbar), "r"(rk ^ 1));
#define RBAR(field, i) (rbar + (uint32_t)offsetof(Bars, field) + 8u * (i))
    {
      const int ln = (tid >> 1) & 31, lg = ln >> 2, lt = ln & 3, i = 4 * (tid >> 6) + 2 * (tid & 1);
      const int kidx = lt + 8 * (i >> 3), nidx = 4 * ((i >> 1) & 3) + (lg >> 1);
      const uint32_t a0 = cfrag<2048>((c + 128 * kidx) * nidx, lg & 1), a1 = cfrag<2048>((c + 128 * (kidx + 4)) * nidx, lg & 1);
      const uint32_t b0 = cfrag<2048>(-(c + 128 * nidx) * kidx, lg & 1), b1 = cfrag<2048>(-(c + 128 * nidx) * (kidx + 4), lg & 1);
      asm volatile("st.shared.v2.u32 [%0], {%1,%2};" ::"r"(sbase + SM_FC + tid * 8), "r"(a0), "r"(a1) : "memory");
      asm volatile("st.shared.v2.u32 [%0], {%1,%2};" ::"r"(sbase + SM_FC + 2048 + tid * 8), "r"(b0), "r"(b1) : "memory");
    }
    bar_sync(NB_CONS, 256);
    uint4 fc[4];
#pragma unroll
    for (int i = 0; i < 4; i++) fc[i] = lds4(sbase + SM_FC + i * 512 + lane * 16);
    asm volatile("cp.async.wait_group 0;" ::: "memory");
    __syncwarp();
    bar_arrive(NB_INIT, 384);
    uint32_t tag, ones;
    uint4 q[4], o[4];
    {
      uint32_t v[2][8];
#pragma unroll
      for (int r = 0; r < 2; r++)
#pragma unroll
        for (int ks = 0; ks < 2; ks++) {
          const int ch = 32 * ks + 2 * (lane & 15) + (lane >> 4);
          asm volatile("ldmatrix.sync.aligned.m8n8.x4.trans.shared.b16 {%0,%1,%2,%3}, [%4];"
                       : "=r"(v[r][4 * ks]), "=r"(v[r][4 * ks + 1]), "=r"(v[r][4 * ks + 2]), "=r"(v[r][4 * ks + 3])
                       : "r"(sbase + SM_X + (2 * warp + r) * 1024 + ((ch ^ ((ch >> 3) & 1)) * 16)) : "memory");
        }
      float sq[2];
#pragma unroll
      for (int r = 0; r < 2; r++) {
        float s0 = 0.f, s1 = 0.f;
#pragma unroll
        for (int i = 0; i < 8; i++) {
          const float lo = bf_lo(v[r][i]), hi = u2f(v[r][i] & 0xffff0000u);
          s0 = fmaf(lo, lo, s0);
          s1 = fmaf(hi, hi, s1);
        }
        sq[r] = s0 + s1;
      }
      {
        float w = ((lane & 1) ? sq[1] : sq[0]) + __shfl_xor_sync(0xffffffffu, (lane & 1) ? sq[0] : sq[1], 1);
        w += __shfl_xor_sync(0xffffffffu, w, 2);
        w = sum_groups(w);
        const float o2 = __shfl_xor_sync(0xffffffffu, w, 1);
        sq[0] = (lane & 1) ? o2 : w;
        sq[1] = (lane & 1) ? w : o2;
      }
#pragma unroll
      for (int r = 0; r < 2; r++) {
        float dd[2][4], ee[2][4];
#pragma unroll
        for (int nt = 0; nt < 2; nt++) {
          mma_az(dd[nt], fa[0], v[r][2 * nt], v[r][2 * nt + 1]);
          mma_a(dd[nt], fa[1], v[r][4 + 2 * nt], v[r][5 + 2 * nt]);
          mma_az(ee[nt], fa[2], v[r][2 * nt], v[r][2 * nt + 1]);
          mma_a(ee[nt], fa[3], v[r][4 + 2 * nt], v[r][5 + 2 * nt]);
        }
        float mean = (dd[0][0] + dd[0][1]) + (dd[1][0] + dd[1][1]);
        mean += __shfl_xor_sync(0xffffffffu, mean, 1);
        mean += __shfl_xor_sync(0xffffffffu, mean, 2);
        mean = __shfl_sync(0xffffffffu, mean, 0) * (1.f / 512.f);
        const float rs = rsqrtf(fmaxf(fmaf(-mean, mean, sq[r] * (1.f / 512.f)), 0.f) + 1e-5f);
        float acc[4][4];
#pragma unroll
        for (int nt = 0; nt < 2; nt++) {
          const float (&d)[4] = dd[nt];
          const float (&e)[4] = ee[nt];
          const uint4 &ka = tw[2 * nt], &kb = tw[2 * nt + 1], &kc = tw[4 + nt];
          const uint32_t a0 = pack2(d[0] * u2f(ka.x) + d[2] * u2f(ka.y), d[1] * u2f(kb.x) + d[3] * u2f(kb.y));
          const uint32_t a2 = pack2(d[0] * u2f(ka.z) + d[2] * u2f(ka.w), d[1] * u2f(kb.z) + d[3] * u2f(kb.w));
          const uint32_t a1 = pack2(e[0] * u2f(kc.x) + e[2] * u2f(kc.y), e[1] * u2f(kc.z) + e[3] * u2f(kc.w));
          const uint32_t a3 = pack2(e[2] * u2f(kc.x) - e[0] * u2f(kc.y), e[3] * u2f(kc.z) - e[1] * u2f(kc.w));
          const uint32_t dc = pack2(fmaf(mean, -32.f, d[0]), fmaf(mean, -32.f, d[1]));
          const uint32_t h0 = g == 0 ? dc : a0, h2 = g == 0 ? 0u : a2;
          if (nt == 0) {
            mma16816_z(acc[0], a0, a1, a2, a3, fb[2 * nt].x, fb[2 * nt].y);
            mma16816_z(acc[1], a0, a1, a2, a3, fb[2 * nt].z, fb[2 * nt].w);
            mma16816_z(acc[2], h0, a1, h2, a3, fb[2 * nt + 1].x, fb[2 * nt + 1].y);
            mma16816_z(acc[3], h0, a1, h2, a3, fb[2 * nt + 1].z, fb[2 * nt + 1].w);
          } else {
            mma16816(acc[0], a0, a1, a2, a3, fb[2 * nt].x, fb[2 * nt].y);
            mma16816(acc[1], a0, a1, a2, a3, fb[2 * nt].z, fb[2 * nt].w);
            mma16816(acc[2], h0, a1, h2, a3, fb[2 * nt + 1].x, fb[2 * nt + 1].y);
            mma16816(acc[3], h0, a1, h2, a3, fb[2 * nt + 1].z, fb[2 * nt + 1].w);
          }
        }
#pragma unroll
        for (int h = 0; h < 2; h++) {
          const int j = 2 * warp + r, m = 2 * t + h;
          sts4(sbase + SM_E + ((j * 8 + m) * 8 + (g ^ (2 * t) ^ (2 * (j & 3)))) * 16,
               pack2(acc[h][0] * rs, acc[h][1] * rs), pack2(acc[h][2] * rs, acc[h][3] * rs),
               pack2(acc[2 + h][0] * rs, acc[2 + h][1] * rs), pack2(acc[2 + h][2] * rs, acc[2 + h][3] * rs));
        }
      }
      bar_sync(NB_RDY, 384);
      const uint32_t ea = sbase + SM_E + ((t * 8 + warp) * 8 + (g ^ (warp & 6) ^ (2 * t))) * 16;
      lds_frag(q[0], q[1], ea, ea + 4096);
      lds_frag(q[2], q[3], ea + 8192, ea + 12288);
      asm volatile("ld.shared.u32 %0, [%1];" : "=r"(tag) : "r"(BAR(epoch, 0)) : "memory");
      ones = ~(tag >> 31);
      tag = (tag + 1) & 1;
      cdft16(q, fc, o);
#pragma unroll
      for (int vv = 0; vv < 4; vv++) {
        o[vv].y &= ~1u;
        o[vv].z = (o[vv].z & ~1u) | (tag ^ 1);
        st_tag(&scr->Z1[(((4 * vv + t) * 8 + warp) * 128 + c) * 8 + g], o[vv], tag);
      }
    }
    asm volatile("setmaxnreg.inc.sync.aligned.u32 232;");
    {
      uint4* const zp = &scr->Z1[(c * 128 + 8 * t + warp) * 8 + g];
      const uint32_t tst = clock32();
      mbar_wait(BAR(tbar, 0));
      uint4 f2[4], g2[4];
#pragma unroll
      for (int i = 0; i < 4; i++) {
        f2[i] = lds4(TOFF(f2) + warp * 2048 + i * 512);
        g2[i] = lds4(TOFF(g2) + warp * 2048 + i * 512);
      }
      const uint4 f8 = lds4(TOFF(f8)), g8 = lds4(TOFF(g8));
      asm volatile("barrier.cluster.wait.aligned;" ::: "memory");
      spin_until(tst + POLL_DELAY);
      ld_tag4_issue<256>(q, zp);
      float wfr[16], wfi[16];
      {
        const float nyq = ((c & 7) == 7 && g == 0) ? 0.5f : 1.f;
        uint32_t wa = sbase + SM_W + (16 * warp + t) * 80 + ((2 * (c >> 3) + 2) & 15) - 2;
        asm volatile("" : "+r"(wa));
        const uint32_t wb[3] = {wa + 2 * (g == 0 ? 16 : g), wa + 2 * g, wa - 2 * g};
#pragma unroll
        for (int i = 0; i < 16; i++) {
          const int ci = i >> 3, dd = (i >> 2) & 1, e = i & 3;
          const uint32_t a = wb[e < 2 ? e : 2] + (ci * 8 + 4 * dd) * 80 + (e == 0 ? 0 : e == 1 ? 16 : e == 2 ? 64 : 48);
          wfr[i] = bf_lo(lds_u16(a)) * (e == 2 ? nyq : 1.f);
          wfi[i] = bf_lo(lds_u16(a + 10240)) * (e == 2 ? nyq : 1.f);
        }
      }
      ld_tag4_finish<256>(q, zp, tag);
      if (lane == 0) mbar_arrive(BAR(sig, 0));
#pragma unroll
      for (int i = 0; i < 4; i++) q[i].z &= ~1u;
      reg_frag(q, ones);
      cdft16(q, f2, o);
      const uint32_t e2 = sbase + SM_E2;
#pragma unroll
      for (int vv = 0; vv < 4; vv++)
        sts4(e2 + ((warp * 16 + 4 * vv + t) * 8 + (g ^ (2 * t) ^ (2 * (warp & 3)))) * 16, o[vv].x, o[vv].y, o[vv].z, o[vv].w);
      bar_sync(NB_CONS, 256);
      uint32_t ad[2], res[2][2][4];
#pragma unroll
      for (int ci = 0; ci < 2; ci++) {
        const int cc = 2 * warp + ci;
        ad[ci] = e2 + ((t * 16 + cc) * 8 + (g ^ (2 * (cc & 3)) ^ (2 * t))) * 16;
        lds_frag(q[2 * ci], q[2 * ci + 1], ad[ci], ad[ci] + 8192);
      }
#pragma unroll
      for (int ci = 0; ci < 2; ci++)
#pragma unroll
        for (int p = 0; p < 2; p++) {
          uint32_t y[2][2];
#pragma unroll
          for (int vv = 0; vv < 2; vv++) {
            float d[4];
            mma_az(d, q[2 * ci + p], word(f8, 2 * vv), word(f8, 2 * vv + 1));
#pragma unroll
            for (int rr = 0; rr < 2; rr++) {
              const float fr = wfr[ci * 8 + vv * 4 + 2 * p + rr], fi = wfi[ci * 8 + vv * 4 + 2 * p + rr];
              y[vv][rr] = pack2(d[2 * rr] * fr - d[2 * rr + 1] * fi, d[2 * rr] * fi + d[2 * rr + 1] * fr);
            }
          }
#pragma unroll
          for (int vv = 0; vv < 2; vv++) {
            float d[4];
            mma16816_z(d, y[0][0], y[0][1], y[1][0], y[1][1], word(g8, 2 * vv), word(g8, 2 * vv + 1));
            res[ci][vv][2 * p] = pack2(d[0], d[1]);
            res[ci][vv][2 * p + 1] = pack2(d[2], d[3]);
          }
        }
#pragma unroll
      for (int i = 0; i < 4; i++)
        sts4(ad[i >> 1] + (i & 1) * 8192, res[i >> 1][i & 1][0], res[i >> 1][i & 1][1], res[i >> 1][i & 1][2], res[i >> 1][i & 1][3]);
      bar_sync(NB_CONS, 256);
      const uint32_t eb = e2 + ((warp * 16 + t) * 8 + (g ^ (2 * t) ^ (2 * (warp & 3)))) * 16;
      lds_frag(q[0], q[1], eb, eb + 512);
      lds_frag(q[2], q[3], eb + 1024, eb + 1536);
      cdft16(q, g2, o);
#pragma unroll
      for (int vv = 0; vv < 4; vv++) {
        o[vv].y &= ~1u;
        o[vv].z = (o[vv].z & ~1u) | tag;
        st_tag(zp + vv * 256, o[vv], tag);
      }
    }
    {
      const uint4* const zp = &scr->Z1[((t * 8 + warp) * 128 + c) * 8 + g];
      const uint32_t tst = clock32();
      uint4 gb[4], ga[4], gc[4], tw[4];
      uint2 xr[2][4];
      uint2* lnp[2];
#pragma unroll
      for (int r = 0; r < 2; r++) {
        const int row = 16 * f + 2 * warp + r;
        lnp[r] = reinterpret_cast<uint2*>(&scr->LN[(rb * 8 + (g >> 2)) * 1024 + row * 8 + ((2 * (g & 3) + (t >> 1)) ^ (row & 7))]) + (t & 1);
        asm volatile("" : "+l"(lnp[r]));
      }
#pragma unroll
      for (int i = 0; i < 4; i++) {
        gc[i] = lds4(sbase + SM_FC + 2048 + i * 512 + lane * 16);
        gb[i] = lds4(TOFF(gb) + i * 512);
        ga[i] = lds4(TOFF(ga) + i * 512);
        tw[i] = lds4(TOFF(tw3) + i * 512);
        const int ch = 2 * (g + 8 * i) + (t >> 1);
#pragma unroll
        for (int r = 0; r < 2; r++) xr[r][i] = lds2(sbase + SM_X + (2 * warp + r) * 1024 + ((ch ^ ((ch >> 3) & 1)) * 16) + (t & 1) * 8);
      }
      spin_until(tst + POLL_DELAY2);
      ld_tag4_issue<32768>(q, zp);
      ld_tag4_finish<32768, true>(q, zp, tag);
      if (lane == 0) mbar_arrive(BAR(sig, 1));
      reg_frag(q, ones);
      cdft16(q, gc, o);
#pragma unroll
      for (int vv = 0; vv < 4; vv++)
        sts4(sbase + SM_E + (((4 * vv + t) * 8 + warp) * 8 + (g ^ (warp & 6) ^ (2 * t))) * 16, o[vv].x, o[vv].y, o[vv].z, o[vv].w);
      bar_sync(NB_CONS, 256);
      uint32_t hv[2][8];
      const float mk = t == 0 ? 0.f : 1.f;
#pragma unroll
      for (int r = 0; r < 2; r++) {
        const int j = 2 * warp + r;
        uint4 u[2];
#pragma unroll
        for (int h = 0; h < 2; h++) u[h] = lds4(sbase + SM_E + ((j * 8 + 2 * t + h) * 8 + (g ^ (2 * t) ^ (2 * (j & 3)))) * 16);
        const uint32_t bp[4][2] = {{u[0].x, u[1].x & ones}, {u[0].y & ones, u[1].y}, {u[0].z, u[1].z & ones}, {u[0].w & ones, u[1].w}};
        float y[2][2][4];
#pragma unroll
        for (int i = 0; i < 2; i++) {
          float lo[4], hi[4], e[4];
          mma_az(lo, gb[2 * i], bp[0][0], bp[0][1]);
          mma_az(hi, gb[2 * i + 1], bp[2][0], bp[2][1]);
          mma_az(e, gb[2 * i], bp[1][0], bp[1][1]);
          mma_a(e, gb[2 * i + 1], bp[3][0], bp[3][1]);
          const uint4 &ka = tw[2 * i], &kb = tw[2 * i + 1];
          const float tr0 = fmaf(hi[0], mk, lo[0]), ti0 = fmaf(hi[2], mk, lo[2]);
          const float tr1 = lo[1] + hi[1], ti1 = lo[3] + hi[3];
          const float vr0 = tr0 * u2f(ka.x) - ti0 * u2f(ka.y), vi0 = tr0 * u2f(ka.y) + ti0 * u2f(ka.x);
          const float vr1 = tr1 * u2f(ka.z) - ti1 * u2f(ka.w), vi1 = tr1 * u2f(ka.w) + ti1 * u2f(ka.z);
          const uint32_t b0 = pack2(t == 0 ? hi[0] : vr0, vr1), b1 = pack2(t == 0 ? vr0 : vi0, vi1);
          const uint32_t b2 = pack2(e[0] * u2f(kb.x) - e[2] * u2f(kb.y), e[1] * u2f(kb.z) - e[3] * u2f(kb.w));
          const uint32_t b3 = pack2(e[0] * u2f(kb.y) + e[2] * u2f(kb.x), e[1] * u2f(kb.w) + e[3] * u2f(kb.z));
#pragma unroll
          for (int mt = 0; mt < 2; mt++) {
            mma_az(y[mt][i], ga[2 * mt], b0, b1);
            mma_a(y[mt][i], ga[2 * mt + 1], b2, b3);
          }
        }
#pragma unroll
        for (int i = 0; i < 4; i++) {
          hv[r][2 * i] = hadd2_bf16(xr[r][i].x, pack2(y[i >> 1][0][2 * (i & 1)], y[i >> 1][0][2 * (i & 1) + 1]));
          hv[r][2 * i + 1] = hadd2_bf16(xr[r][i].y, pack2(y[i >> 1][1][2 * (i & 1)], y[i >> 1][1][2 * (i & 1) + 1]));
        }
      }
      float mean[2];
      uint32_t mb[2];
#pragma unroll
      for (int r = 0; r < 2; r++) {
        mean[r] = sum_groups(quad_sum(hv[r])) * (1.f / 512.f);
        mb[r] = pack2(mean[r], mean[r]);
      }
#pragma unroll
      for (int i = 0; i < 4; i++)
#pragma unroll
        for (int r = 0; r < 2; r++) {
          hv[r][2 * i] = hsub2_bf16(hv[r][2 * i], mb[r]);
          hv[r][2 * i + 1] = hsub2_bf16(hv[r][2 * i + 1], mb[r]);
          st_tag8(lnp[r] + i * 4096, hv[r][2 * i], hv[r][2 * i + 1], i == 0 ? tag : (hv[r][2 * i] & 1u));
        }
      bar_arrive(NB_LN, 288);
      const uint32_t ones2 = ~(lds2(BAR(epoch, 0)).x >> 31);
      float rstd[2];
#pragma unroll
      for (int r = 0; r < 2; r++) {
        hv[r][0] &= ones2;
        rstd[r] = row_rstd(hv[r], mean[r] - bf_lo(mb[r]));
      }
      if (lane == 0)
        st_tag(&scr->ST[rb * 64 + 8 * f + warp], make_uint4(mb[0] << 16, __float_as_uint(rstd[0]), mb[1] << 16, __float_as_uint(rstd[1])), tag);
    }
    const int wgi = warp >> 2, wq = warp & 3;
    const int wr = wgi ^ (f >> 2) ^ 1, rt = 4 * wr + wq;
    uint4* const pbase = &scr->P[rb * 28 * 1024 + rt * 128 + lane];
    const uint32_t a_lo0 = desc_lo(sbase + wr * 8192, 16);
    const uint32_t ebar = lane == 0 ? BAR(empty1, 0) : RBAR(empty1, 0);
    float r0, r1;
    uint4 px[8], py[6];
    const int rh = wgi ^ kh ^ 1;
    const uint32_t fpb = BAR(fullP, 16 * rh);
    const uint4* const psrc = &scr->P[(rb2 * 28 + 14 * kh) * 1024 + (4 * rh + wq) * 128 + lane];
    const uint32_t pa0 = sbase + (4 * rh + wq) * 2048;
    uint4 pf[3][4], ha[4][4];
    uint32_t rdy = 0, got0;
    {
      float acc[128];
#pragma unroll
      for (int i = 0; i < 128; i++) acc[i] = 0.f;
      const uint32_t b_lo0 = desc_lo(sbase + 8 * SLOT, 4096);
      const uint32_t t3 = clock32();
      if (WARM) {
        wg_fence();
#pragma unroll
        for (int i = 0; i < WARM; i++) wgmma_n256(acc, desc64(a_lo0 + 6 * 1024, HI128), desc64(b_lo0, HI128));
        wg_commit();
      }
      const uint4* const ap = &scr->LN[rb * 8 * 1024 + wr * 512 + (tid & 127)];
      uint4 av[NLL][4];
      spin_until(t3 + POLL_DELAY3);
#pragma unroll
      for (int kb = 0; kb < NLL; kb++) ld_tag4_issue<128>(av[kb], ap + kb * 1024);
      bar_sync(NB_CONS, 256);
      const uint32_t lma = sbase + (16 * rt + (lane & 15)) * 128;
      auto load_a = [&](int kb) {
#pragma unroll
        for (int ks = 0; ks < 4; ks++)
          asm volatile("ldmatrix.sync.aligned.m8n8.x4.shared.b16 {%0,%1,%2,%3}, [%4];"
                       : "=r"(ha[kb][ks].x), "=r"(ha[kb][ks].y), "=r"(ha[kb][ks].z), "=r"(ha[kb][ks].w)
                       : "r"(lma + kb * SLOT + (((2 * ks + (lane >> 4)) ^ (lane & 7)) * 16)) : "memory");
      };
      auto stash_a = [&](int kb) {
        ld_tag4_finish<128, true>(av[kb], ap + kb * 1024, tag);
#pragma unroll
        for (int i = 0; i < 4; i++)
          sts4(sbase + kb * SLOT + wr * 8192 + ((tid & 127) + 128 * i) * 16, av[kb][i].x, av[kb][i].y, av[kb][i].z, av[kb][i].w);
        bar_sync(NB_WG + wgi, 128);
      };
      stash_a(0);
      load_a(0);
#pragma unroll
      for (int n = 0; n < 8; n++) {
        const int kb = n >> 1, hh = n & 1;
        if (hh == 1 && kb < 3) {
          if (kb + 1 < NLL) stash_a(kb + 1); else mbar_wait(BAR(fullA, kb + 1));
        }
        mbar_wait(BAR(full1, n));
        const uint32_t bl = b_lo0 + ((n + 2) % 6) * 1024;
        wg_fence();
        if (hh == 1 && kb < 3) load_a(kb + 1);
        const uint4 &a0 = ha[kb][2 * hh], &a1 = ha[kb][2 * hh + 1];
        wgmma_rs_n256(acc, a0.x, a0.y, a0.z, a0.w, desc64(bl, HI128), n != 0 ? 1 : ~ones);
        wgmma_rs_n256(acc, a1.x, a1.y, a1.z, a1.w, desc64(bl + 128, HI128));
        wg_commit();
        if (hh == 1 && lane < 2) mbar_arrive_remote(ebar + (uint32_t)(offsetof(Bars, freeA) - offsetof(Bars, empty1)) + 8 * kb);
        wg_wait<1>();
        if (n != 0 && lane < 2) mbar_arrive_remote(ebar + 8 * (n - 1));
      }
      uint32_t slot = 4;
#pragma unroll 1
      for (int kb = 4; kb < 8; kb++) {
        mbar_wait(BAR(fullA, kb));
#pragma unroll
        for (int hh = 0; hh < 2; hh++) {
          if (LAGX && hh == ((16 - LAGX) & 1) && kb == ((16 - LAGX) >> 1) && wgi == 1) bar_sync(NB_LAG, 256);
          mbar_wait(BAR(full1, 2 * kb + hh));
          const uint32_t al = a_lo0 + kb * 1024 + hh * 4, bl = b_lo0 + slot * 1024;
          wg_fence();
          wgmma_n256(acc, desc64(al, HI128), desc64(bl, HI128));
          wgmma_n256(acc, desc64(al + 2, HI128), desc64(bl + 128, HI128));
          wg_commit();
          if (LAGX && hh == 1 && kb == 7 && wgi == 0) bar_arrive(NB_LAG, 256);
          wg_wait<1>();
          if (lane < 2) mbar_arrive_remote(ebar + 8 * (2 * kb + hh - 1));
          if (++slot == 6) slot = 0;
        }
      }
      mbar_wait(BAR(sbar, 0));
      r0 = __uint_as_float(lds2(sstat + (16 * rt + g) * 8).y);
      r1 = __uint_as_float(lds2(sstat + (16 * rt + g + 8) * 8).y);
      wg_wait<0>();
      if (lane < 2) mbar_arrive_remote(ebar + 8 * 15);
      make_p<8, !PACED>(acc, r0, r1, px, pbase, 14 * f + 6 * (f & 1), tag);
      if (!PACED && lane == 0) red_relaxed(&scr->cnt[(C_PX + rb) * 32 + (f >> 2)]);
    }
    {
      float acc[96];
#pragma unroll
      for (int i = 0; i < 96; i++) acc[i] = 0.f;
      const uint32_t b_lo0 = desc_lo(sbase, 2048);
      uint4* const pdst = pbase + ((7 * f + 3 * (f & 1)) >> 1) * 1024;
      auto stage_y = [&](int k) {
        if (LAGY && k == 16 - LAGY && wgi == 1) bar_sync(NB_LAG, 256);
        if (PACED && k < 4) mbar_wait_bounded(BAR(full1, 16 + k)); else mbar_wait(BAR(full1, 16 + k));
        const uint32_t al = a_lo0 + (4 + (k >> 1)) * 1024 + (k & 1) * 4, bl = b_lo0 + (k < 5 ? k * 768 : 8192 + (k - 5) * 768);
        wg_fence();
        wgmma_n192(acc, desc64(al, HI128), desc64(bl, HI64));
        wgmma_n192(acc, desc64(al + 2, HI128), desc64(bl + 64, HI64));
        wg_commit();
      };
#pragma unroll
      for (int k = 0; k < 4 * PACED; k++) {
        stage_y(k);
        st_tag(pdst + (k >> 1) * 1024 + (k & 1) * 64, px[2 * k], tag);
        st_tag(pdst + (k >> 1) * 1024 + (k & 1) * 64 + 32, px[2 * k + 1], tag);
        if (k == 3 && lane == 0) red_relaxed(&scr->cnt[(C_PX + rb) * 32 + (f >> 2)]);
        wg_wait<1>();
        if (k != 0 && lane < 2) mbar_arrive_remote(ebar + 8 * (15 + k));
      }
#pragma unroll 1
      for (int k = 4 * PACED; k < 8; k++) {
        stage_y(k);
        wg_wait<1>();
        if (k != 0 && lane < 2) mbar_arrive_remote(ebar + 8 * (15 + k));
      }
      rdy = 0;
#pragma unroll
      for (int k = 8; k < 16; k++) {
        if (LAGY && k == 16 - LAGY && wgi == 1) bar_sync(NB_LAG, 256);
        if (!rdy) mbar_wait(BAR(full1, 16 + k));
        const uint32_t bl = b_lo0 + 8192 + ((k - 5) & 7) * 768;
        const uint4 &a0 = ha[(k - 8) >> 1][2 * (k & 1)], &a1 = ha[(k - 8) >> 1][2 * (k & 1) + 1];
        wg_fence();
        if (k < 15) rdy = mbar_test(BAR(full1, 17 + k));
        wgmma_rs_n192(acc, a0.x, a0.y, a0.z, a0.w, desc64(bl, HI64));
        wgmma_rs_n192(acc, a1.x, a1.y, a1.z, a1.w, desc64(bl + 64, HI64));
        wg_commit();
        if (LAGY && k == 15 && wgi == 0) bar_arrive(NB_LAG, 256);
        wg_wait<1>();
        if (lane < 2) mbar_arrive_remote(ebar + 8 * (15 + k));
      }
      got0 = __all_sync(0xffffffffu, mbar_test((fpb + 8 * (0))));
      if (got0) {
#pragma unroll
        for (int kk = 0; kk < 4; kk++) pf[0][kk] = lds4(pa0 + 3 * SLOT + kk * 512 + lane * 16);
      }
      wg_wait<0>();
      if (lane < 2) mbar_arrive_remote(ebar + 8 * 31);
      const int ks0 = 14 * f + ((f & 1) ? 0 : 8);
      auto reread = [&]() {
        asm volatile("ld.volatile.shared.f32 %0, [%2+4]; ld.volatile.shared.f32 %1, [%2+68];" : "=f"(r0), "=f"(r1) : "r"(sstat + (16 * rt + g) * 8) : "memory");
      };
      make_p<6, true, 0, 2>(acc, r0, r1, py, pbase, ks0, tag);
      if (REDPOS == 2 && lane == 0) red_relaxed(&scr->cnt[(C_PY + rb) * 32 + 4 * wgi + (f >> 1)]);
      reread();
      make_p<6, true, 2, 4>(acc, r0, r1, py, pbase, ks0, tag);
      if (REDPOS == 4 && lane == 0) red_relaxed(&scr->cnt[(C_PY + rb) * 32 + 4 * wgi + (f >> 1)]);
      reread();
      rdy = mbar_test(BAR(full2, 0)) & mbar_test((fpb + 8 * (1)));
      make_p<6, true, 4, 6>(acc, r0, r1, py, pbase, ks0, tag);
      if (REDPOS == 6 && lane == 0) red_relaxed(&scr->cnt[(C_PY + rb) * 32 + 4 * wgi + (f >> 1)]);
    }
    {
      float acc[64];
      const uint32_t b2_lo0 = desc_lo(sbase, 8192);
      const uint32_t pbar = rh == rk ? BAR(emptyP, 0) : RBAR(emptyP, 0);
      if (!got0) {
        mbar_wait((fpb + 8 * (0)));
#pragma unroll
        for (int kk = 0; kk < 4; kk++) pf[0][kk] = lds4(pa0 + 3 * SLOT + kk * 512 + lane * 16);
      }
#pragma unroll
      for (int s = 0; s < 14; s++) {
        uint4 (&a)[4] = pf[s % 3];
        ld_tag4_finish<32>(a, psrc + (int)((KORDER >> (4 * s)) & 15) * 1024, tag);
        if (s < 9 && lane == 0) mbar_arrive_remote(pbar + 8 * s);
        if (s >= 2) {
          wg_wait<1>();
          if (s <= 7 && lane == 0) mbar_arrive(BAR(empty2, s - 2));
        }
        if (!rdy) {
          if (s < 13) mbar_wait((fpb + 8 * (s + 1)));
          mbar_wait(BAR(full2, s));
        }
        if (s == 14 - LAG2 && wgi == 1) bar_sync(NB_LAG, 256);
        const uint32_t bl = b2_lo0 + (uint32_t)((BSLOT >> (4 * s)) & 15) * 1024;
        wg_fence();
        if (s < 13) {
#pragma unroll
          for (int kk = 0; kk < 4; kk++)
            pf[(s + 1) % 3][kk] = lds4(pa0 + (uint32_t)((PSLOT >> (4 * (s + 1))) & 15) * SLOT + kk * 512 + lane * 16);
          rdy = mbar_test(BAR(full2, s + 1));
          if (s < 12) rdy &= mbar_test((fpb + 8 * (s + 2)));
        }
        if (s == 0) wgmma_rs_n128(acc, a[0].x, a[0].y, a[0].z, a[0].w, desc64(bl, HI128), 0);
        else wgmma_rs_n128(acc, a[0].x, a[0].y, a[0].z, a[0].w, desc64(bl, HI128));
#pragma unroll
        for (int kk = 1; kk < 4; kk++) wgmma_rs_n128(acc, a[kk].x, a[kk].y, a[kk].z, a[kk].w, desc64(bl + kk * 128, HI128));
        wg_commit();
      }
      if (wgi == 0) {
        bar_arrive(NB_LAG, 256);
        uint4* const dst = &scr->Z1[(tid >> 3) * 1024 + (c ^ 4) * 8 + (tid & 7)];
        wg_wait<0>();
#pragma unroll
        for (int i = 0; i < 8; i++)
          st_tag(dst + i * 16384, make_uint4(pack2(acc[8 * i], acc[8 * i + 1]), pack2(acc[8 * i + 2], acc[8 * i + 3]) | 1u,
                                           pack2(acc[8 * i + 4], acc[8 * i + 5]), pack2(acc[8 * i + 6], acc[8 * i + 7])), tag);
      } else {
        uint4 pv[2][4];
        const uint4* const xsrc = &scr->Z1[((tid & 127) >> 3) * 1024 + c * 8 + (tid & 7)];
        ld_tag4_issue<16384>(pv[0], xsrc);
        ld_tag4_issue<16384>(pv[1], xsrc + 65536);
        uint32_t w[32];
        {
          const uint32_t m0 = __byte_perm(lds2(sstat + 1024 + (16 * wq + g) * 8).x, 0, 0x3232);
          const uint32_t m1 = __byte_perm(lds2(sstat + 1024 + (16 * wq + g + 8) * 8).x, 0, 0x3232);
          const uint32_t hb = sbase + 13 * SLOT + (16 * wq + (lane & 15)) * 128;
          const uint32_t mk = ((t & 1) == 0 && nq == 0) ? ~1u : ~0u;
          mbar_wait(BAR(hbar, 0));
#pragma unroll
          for (int i = 0; i < 8; i++) {
            asm volatile("ldmatrix.sync.aligned.m8n8.x4.shared.b16 {%0,%1,%2,%3}, [%4];"
                         : "=r"(w[4 * i]), "=r"(w[4 * i + 1]), "=r"(w[4 * i + 2]), "=r"(w[4 * i + 3])
                         : "r"(hb + (i >> 2) * 8192 + (((2 * (i & 3) + (lane >> 4)) ^ (lane & 7)) * 16)) : "memory");
#pragma unroll
            for (int e = 0; e < 4; e++) w[4 * i + e] = hadd2_bf16(w[4 * i + e] & mk, (e & 1) ? m1 : m0);
          }
        }
        wg_wait<0>();
#pragma unroll
        for (int i = 0; i < 32; i++) w[i] = hadd2_bf16(w[i], pack2(acc[2 * i], acc[2 * i + 1]));
#pragma unroll 1
        while (!__all_sync(0xffffffffu, pv[0][0].y & pv[0][1].y & pv[0][2].y & pv[0][3].y & pv[1][0].y & pv[1][1].y & pv[1][2].y & pv[1][3].y & 1u)) {
          ld_tag4_issue<16384>(pv[0], xsrc);
          ld_tag4_issue<16384>(pv[1], xsrc + 65536);
        }
#pragma unroll
        for (int i = 0; i < 8; i++) {
          const uint4& p = pv[i >> 2][i & 3];
          asm volatile("stmatrix.sync.aligned.m8n8.x4.shared.b16 [%0], {%1,%2,%3,%4};"
                       ::"r"(pa0 + (11 + ((lane >> 3) & 1)) * SLOT + (lane & 7) * 256 + (((2 * i + (lane >> 4)) ^ (lane & 7)) * 16)),
                         "r"(hadd2_bf16(w[4 * i], p.x & ~1u)), "r"(hadd2_bf16(w[4 * i + 1], p.y & ~1u)), "r"(hadd2_bf16(w[4 * i + 2], p.z)),
                         "r"(hadd2_bf16(w[4 * i + 3], p.w)) : "memory");
        }
        __syncwarp();
        uint4* const dst = reinterpret_cast<uint4*>(out) + (16 * (c >> 4) + 2 * (4 * rh + wq) + (rb2 & 1) + 128 * (lane >> 4)) * 64 + nq * 16 + (lane & 15);
#pragma unroll
        for (int i = 0; i < 8; i++) {
          const int r = 2 * (i & 3) + (lane >> 4);
          dst[i * 256 * 64] = lds4(pa0 + (11 + (i >> 2)) * SLOT + r * 256 + (((lane & 15) ^ r) * 16));
        }
      }
      if (lane == 0) mbar_arrive(BAR(done, 0));
    }
  }
#undef BAR
#undef TOFF
#undef RBAR
}

typedef CUresult (*EncodeFn)(CUtensorMap*, CUtensorMapDataType, cuuint32_t, void*, const cuuint64_t*, const cuuint64_t*,
                             const cuuint32_t*, const cuuint32_t*, CUtensorMapInterleave, CUtensorMapSwizzle,
                             CUtensorMapL2promotion, CUtensorMapFloatOOBfill);

}

extern "C" void kernel_launch(void* const* d_in, const int* in_sizes, int n_in, void* d_out, int out_size) {
  (void)in_sizes; (void)n_in; (void)out_size;
  static EncodeFn encode = nullptr;
  static void *tab = nullptr, *scr = nullptr;
  if (!encode) {
    void* fn = nullptr;
    cudaDriverEntryPointQueryResult qr;
    cudaGetDriverEntryPoint("cuTensorMapEncodeTiled", &fn, cudaEnableDefault, &qr);
    encode = (EncodeFn)fn;
    cudaGetSymbolAddress(&tab, g_tab);
    cudaGetSymbolAddress(&scr, g_scr);
    cudaFuncSetAttribute(fused_kernel, cudaFuncAttributeMaxDynamicSharedMemorySize, SMEM_BYTES);
  }
  CUtensorMap tmGX, tmUX, tmGY, tmUY, tmD, tmWR, tmWI;
  const cuuint32_t es[5] = {1, 1, 1, 1, 1};
  auto enc = [&](CUtensorMap* m, void* p, int rank, const cuuint64_t* gd, const cuuint64_t* gs, const cuuint32_t* bd,
                 CUtensorMapSwizzle sw, CUtensorMapL2promotion pr) {
    encode(m, CU_TENSOR_MAP_DATA_TYPE_BFLOAT16, rank, p, gd, gs, bd, es, CU_TENSOR_MAP_INTERLEAVE_NONE, sw, pr,
           CU_TENSOR_MAP_FLOAT_OOB_FILL_NONE);
  };
  {
    const cuuint64_t gd[3] = {64, 512, 28}, gs[2] = {3584, 128};
    const cuuint32_t bd[3] = {64, 32, 2};
    enc(&tmGX, d_in[4], 3, gd, gs, bd, CU_TENSOR_MAP_SWIZZLE_128B, CU_TENSOR_MAP_L2_PROMOTION_L2_256B);
    enc(&tmUX, d_in[5], 3, gd, gs, bd, CU_TENSOR_MAP_SWIZZLE_128B, CU_TENSOR_MAP_L2_PROMOTION_L2_256B);
  }
  {
    const cuuint64_t gd[3] = {32, 512, 56}, gs[2] = {3584, 64};
    const cuuint32_t bd[3] = {32, 32, 3};
    enc(&tmGY, d_in[4], 3, gd, gs, bd, CU_TENSOR_MAP_SWIZZLE_64B, CU_TENSOR_MAP_L2_PROMOTION_L2_128B);
    enc(&tmUY, d_in[5], 3, gd, gs, bd, CU_TENSOR_MAP_SWIZZLE_64B, CU_TENSOR_MAP_L2_PROMOTION_L2_128B);
  }
  {
    const cuuint64_t gd[3] = {64, 1792, 8}, gs[2] = {1024, 128};
    const cuuint32_t bd[3] = {64, 64, 2};
    enc(&tmD, d_in[6], 3, gd, gs, bd, CU_TENSOR_MAP_SWIZZLE_128B, CU_TENSOR_MAP_L2_PROMOTION_L2_256B);
  }
  {
    const cuuint64_t gd[3] = {4112, 8, 16}, gs[2] = {16 * 8224, 8224};
    const cuuint32_t bd[3] = {40, 8, 16};
    enc(&tmWR, d_in[1], 3, gd, gs, bd, CU_TENSOR_MAP_SWIZZLE_NONE, CU_TENSOR_MAP_L2_PROMOTION_NONE);
    enc(&tmWI, d_in[2], 3, gd, gs, bd, CU_TENSOR_MAP_SWIZZLE_NONE, CU_TENSOR_MAP_L2_PROMOTION_NONE);
  }
  fused_kernel<<<NCTA, NTHREADS, SMEM_BYTES>>>((const __nv_bfloat16*)d_in[0], (const Tables*)tab, (Scratch*)scr,
                                               (__nv_bfloat16*)d_out, (const char*)d_in[4], (const char*)d_in[5],
                                               (const char*)d_in[6], tmWR, tmWI, tmGX, tmUX, tmGY, tmUY, tmD);
}
```

```cpp
#include <cuda_runtime.h>
#include <cuda_bf16.h>
#include <cuda.h>
#include <stdint.h>

namespace {

constexpr int NCTA = 128;
constexpr int NTHREADS = 384;
constexpr int SLOT = 16384;
constexpr int SMEM_BYTES = 14 * SLOT + 3072;
constexpr int SPIN_LIMIT = 1 << 22;

struct Scratch {
  uint4 Z1[128 * 1024];
  uint4 LN[16 * 8 * 1024];
  uint4 P[16 * 28 * 1024];
  uint4 ST[1024];
  unsigned cnt[64 * 32];
};
__device__ __align__(1024) Scratch g_scr;

constexpr double ccos(int i, int n) {
  i &= n - 1;
  if (i > n / 2) i = n - i;
  if (4 * i == n) return 0.0;
  const bool neg = 4 * i > n;
  if (neg) i = n / 2 - i;
  const double a = 6.283185307179586476925 * i / n, a2 = a * a;
  double term = 1.0, sum = 1.0;
  for (int k = 1; k < 14; k++) { term *= -a2 / ((2 * k - 1) * (2 * k)); sum += term; }
  return neg ? -sum : sum;
}
constexpr double csin(int i, int n) { return ccos(i - n / 4, n); }
constexpr unsigned fbits(double v, int mant) {
  if (v == 0.0) return 0;
  const unsigned sg = v < 0 ? 1u : 0u;
  if (v < 0) v = -v;
  int e = 127;
  while (v < 1.0) { v *= 2.0; e--; }
  const unsigned m = (unsigned)((v - 1.0) * (double)(1u << mant) + 0.5);
  return (sg << (8 + mant)) + ((unsigned)e << mant) + m;
}
constexpr unsigned pkb(double lo, double hi) { return fbits(lo, 7) | (fbits(hi, 7) << 16); }
constexpr double fa_elem(int mt, int r, int n1) {
  const int k1 = 8 * mt + (r & 7);
  return r < 8 ? ccos(k1 * n1, 32) : k1 == 0 ? ccos(16 * n1, 32) : -csin(k1 * n1, 32);
}
constexpr unsigned cfrag_c(int idx, int n, int ri, double s = 1.0) {
  return ri ? pkb(-s * csin(idx, n), s * ccos(idx, n)) : pkb(s * ccos(idx, n), s * csin(idx, n));
}
struct Tables {
  unsigned fa[4][32][4];
  unsigned fb[4][32][4];
  unsigned tw1[6][32][4];
  unsigned f2[8][4][32][4];
  unsigned g2[8][4][32][4];
  unsigned gb[4][32][4];
  unsigned ga[4][32][4];
  unsigned tw3[4][32][4];
  unsigned f8[32][4], g8[32][4];
};
constexpr int T1_BYTES = 7168, T2_BYTES = 39936;
static_assert(sizeof(Tables) == T1_BYTES + T2_BYTES, "table size");
constexpr Tables make_tables() {
  Tables T = {};
  for (int l = 0; l < 32; l++) {
    const int g = l >> 2, t = l & 3;
    for (int a = 0; a < 2; a++)
      for (int b = 0; b < 2; b++) {
        for (int r = 0; r < 4; r++) {
          const int row = g + 8 * (r & 1), col = 2 * t + 8 * (r >> 1);
          T.fa[2 * a + b][l][r] = pkb(fa_elem(a, row, 16 * b + col), fa_elem(a, row, 16 * b + col + 1));
          T.ga[2 * a + b][l][r] = pkb(fa_elem(b, col, 16 * a + row), fa_elem(b, col + 1, 16 * a + row));
        }
        const double sg = b ? -1.0 : 1.0;
        for (int h = 0; h < 2; h++) {
          const int ri = g & 1, m = 2 * (g >> 1) + h, k2 = b ? 15 - m : m;
          const int pa = (8 * a + 2 * t) * k2, pb = (8 * a + 2 * t + 1) * k2;
          T.fb[2 * a + b][l][2 * h] = ri == 0 ? pkb(ccos(pa, 16), ccos(pb, 16)) : pkb(-sg * csin(pa, 16), -sg * csin(pb, 16));
          T.fb[2 * a + b][l][2 * h + 1] = ri == 0 ? pkb(csin(pa, 16), csin(pb, 16)) : pkb(sg * ccos(pa, 16), sg * ccos(pb, 16));
        }
        const int n2 = 4 * (g >> 1) + 2 * a + (g & 1);
        for (int h = 0; h < 2; h++) {
          const int p = n2 * (b ? 15 - 2 * t - h : 2 * t + h);
          T.gb[2 * a + b][l][2 * h] = pkb(ccos(p, 16), -sg * csin(p, 16));
          T.gb[2 * a + b][l][2 * h + 1] = pkb(csin(p, 16), sg * ccos(p, 16));
          const int k1 = 8 * b + 2 * t + h, q = n2 * (k1 == 0 ? 16 : k1);
          T.tw3[2 * a + b][l][2 * h] = fbits(ccos(q, 512), 23);
          T.tw3[2 * a + b][l][2 * h + 1] = fbits(csin(q, 512), 23);
        }
        const int p = (8 * a + 2 * t + b) * (g == 0 ? 16 : g);
        T.tw1[2 * a + b][l][0] = fbits(g == 0 ? 0.0 : ccos(p, 512), 23);
        T.tw1[2 * a + b][l][1] = fbits(g == 0 ? ccos(p, 512) : csin(p, 512), 23);
        T.tw1[2 * a + b][l][2] = fbits(g == 0 ? 0.0 : -csin(p, 512), 23);
        T.tw1[2 * a + b][l][3] = fbits(g == 0 ? -csin(p, 512) : ccos(p, 512), 23);
        T.tw1[4 + a][l][2 * b] = fbits(ccos((8 * a + 2 * t + b) * (g + 8), 512), 23);
        T.tw1[4 + a][l][2 * b + 1] = fbits(csin((8 * a + 2 * t + b) * (g + 8), 512), 23);
      }
    for (int i = 0; i < 4; i++) {
      const int p8 = (t + 4 * (i & 1)) * (4 * (i >> 1) + (g >> 1));
      T.f8[l][i] = cfrag_c(p8, 8, g & 1);
      T.g8[l][i] = cfrag_c(-p8, 8, g & 1, 1.0 / (1 << 19));
    }
    for (int w = 0; w < 8; w++)
      for (int i = 0; i < 16; i++) {
        const int kidx = t + 4 * (i & 1) + 8 * (i >> 3), nidx = 4 * ((i >> 1) & 3) + (g >> 1);
        T.f2[w][i >> 2][l][i & 3] = cfrag_c((8 * kidx + w) * nidx, 128, g & 1);
        T.g2[w][i >> 2][l][i & 3] = cfrag_c(-(8 * nidx + w) * kidx, 128, g & 1);
      }
  }
  return T;
}
__device__ const __align__(128) Tables g_tab = make_tables();

__device__ __forceinline__ void die() { asm volatile("st.global.u32 [%0], %1;" ::"l"(0ull), "r"(0) : "memory"); }
__device__ __forceinline__ uint32_t s2u(const void* p) { return (uint32_t)__cvta_generic_to_shared(p); }
__device__ __forceinline__ void mbar_init(uint32_t b, int c) { asm volatile("mbarrier.init.shared::cta.b64 [%0], %1;" ::"r"(b), "r"(c)); }
__device__ __forceinline__ void mbar_expect(uint32_t b, int bytes) {
  asm volatile("mbarrier.arrive.expect_tx.shared::cta.b64 _, [%0], %1;" ::"r"(b), "r"(bytes) : "memory");
}
__device__ __forceinline__ void mbar_arrive(uint32_t b) { asm volatile("mbarrier.arrive.shared::cta.b64 _, [%0];" ::"r"(b) : "memory"); }
__device__ __forceinline__ uint32_t mbar_try(uint32_t b, uint32_t parity) {
  uint32_t ok;
  asm volatile("{.reg .pred p; mbarrier.try_wait.parity.shared::cta.b64 p, [%1], %2; selp.u32 %0,1,0,p;}"
               : "=r"(ok) : "r"(b), "r"(parity) : "memory");
  return ok;
}
__device__ __forceinline__ uint32_t mbar_test(uint32_t b) {
  uint32_t ok;
  asm volatile("{.reg .pred p; mbarrier.test_wait.parity.shared::cta.b64 p, [%1], 0; selp.u32 %0,1,0,p;}" : "=r"(ok) : "r"(b) : "memory");
  return ok;
}
__device__ __forceinline__ void mbar_wait_bounded(uint32_t b) {
  int it = 0;
#pragma unroll 1
  while (!mbar_try(b, 0))
    if (++it > SPIN_LIMIT) { die(); break; }
}
__device__ __forceinline__ void mbar_wait(uint32_t b) {
  asm volatile("{.reg .pred p;\nW_%=: mbarrier.try_wait.parity.shared::cta.b64 p, [%0], 0;\n@!p bra W_%=;}" ::"r"(b) : "memory");
}
__device__ __forceinline__ void bar_sync(int id, int n) { asm volatile("bar.sync %0, %1;" ::"r"(id), "r"(n) : "memory"); }
__device__ __forceinline__ void bar_arrive(int id, int n) { asm volatile("bar.arrive %0, %1;" ::"r"(id), "r"(n) : "memory"); }
__device__ __forceinline__ void red_release(unsigned* p) { asm volatile("red.release.gpu.global.add.u32 [%0], 1;" ::"l"(p) : "memory"); }
__device__ __forceinline__ void red_relaxed(unsigned* p) { asm volatile("red.relaxed.gpu.global.add.u32 [%0], 1;" ::"l"(p) : "memory"); }
__device__ __forceinline__ unsigned ld_acquire(const unsigned* p) {
  unsigned v;
  asm volatile("ld.acquire.gpu.global.u32 %0, [%1];" : "=r"(v) : "l"(p) : "memory");
  return v;
}
__device__ __forceinline__ unsigned ld_relaxed(const unsigned* p) {
  unsigned v;
  asm volatile("ld.relaxed.gpu.global.u32 %0, [%1];" : "=r"(v) : "l"(p) : "memory");
  return v;
}
__device__ __forceinline__ void wait_counter(const unsigned* p, unsigned target) {
#pragma unroll 1
  while ((int)(ld_acquire(p) - target) < 0) {}
}
__device__ __forceinline__ void sts4(uint32_t a, uint32_t x, uint32_t y, uint32_t z, uint32_t w) {
  asm volatile("st.shared.v4.u32 [%0], {%1,%2,%3,%4};" ::"r"(a), "r"(x), "r"(y), "r"(z), "r"(w) : "memory");
}
__device__ __forceinline__ uint4 lds4(uint32_t a) {
  uint4 v;
  asm volatile("ld.shared.v4.u32 {%0,%1,%2,%3}, [%4];" : "=r"(v.x), "=r"(v.y), "=r"(v.z), "=r"(v.w) : "r"(a) : "memory");
  return v;
}
__device__ __forceinline__ uint32_t pack2(float lo, float hi) {
  uint32_t r;
  asm("cvt.rn.bf16x2.f32 %0, %1, %2;" : "=r"(r) : "f"(hi), "f"(lo));
  return r;
}
__device__ __forceinline__ float bf_lo(uint32_t v) { return __uint_as_float(v << 16); }
__device__ __forceinline__ uint32_t hadd2_bf16(uint32_t a, uint32_t b) {
  uint32_t r;
  asm("add.rn.bf16x2 %0, %1, %2;" : "=r"(r) : "r"(a), "r"(b));
  return r;
}
__device__ __forceinline__ void mma16816(float (&d)[4], uint32_t a0, uint32_t a1, uint32_t a2, uint32_t a3, uint32_t b0, uint32_t b1) {
  asm("mma.sync.aligned.m16n8k16.row.col.f32.bf16.bf16.f32 {%0,%1,%2,%3}, {%4,%5,%6,%7}, {%8,%9}, {%0,%1,%2,%3};"
      : "+f"(d[0]), "+f"(d[1]), "+f"(d[2]), "+f"(d[3])
      : "r"(a0), "r"(a1), "r"(a2), "r"(a3), "r"(b0), "r"(b1));
}
__device__ __forceinline__ void mma16816_z(float (&d)[4], uint32_t a0, uint32_t a1, uint32_t a2, uint32_t a3, uint32_t b0, uint32_t b1) {
  asm("{.reg .f32 z; mov.f32 z, 0f00000000;\n"
      "mma.sync.aligned.m16n8k16.row.col.f32.bf16.bf16.f32 {%0,%1,%2,%3}, {%4,%5,%6,%7}, {%8,%9}, {z,z,z,z};}"
      : "=f"(d[0]), "=f"(d[1]), "=f"(d[2]), "=f"(d[3])
      : "r"(a0), "r"(a1), "r"(a2), "r"(a3), "r"(b0), "r"(b1));
}
template <int N>
__device__ __forceinline__ void cs_frac(int idx, float& c, float& s) {
  int i = ((idx + N / 2) & (N - 1)) - N / 2;
  float a = (float)i * (6.283185307179586f / N);
  c = __cosf(a);
  s = __sinf(a);
}
template <int N>
__device__ __forceinline__ uint32_t cfrag(int idx, int ri) {
  float c, s;
  cs_frac<N>(idx, c, s);
  return ri ? pack2(-s, c) : pack2(c, s);
}
__device__ __forceinline__ uint32_t word(const uint4& v, int e) { return e == 0 ? v.x : e == 1 ? v.y : e == 2 ? v.z : v.w; }
__device__ __forceinline__ void cdft16(const uint4 (&A)[4], const uint4 (&F)[4], uint4 (&o)[4]) {
  float acc[2][4][4];
#pragma unroll
  for (int ks = 0; ks < 2; ks++)
#pragma unroll
    for (int p = 0; p < 2; p++)
#pragma unroll
      for (int v = 0; v < 4; v++) {
        const uint4& a = A[2 * ks + p];
        const uint32_t b0 = word(F[ks * 2 + (v >> 1)], (v & 1) * 2), b1 = word(F[ks * 2 + (v >> 1)], (v & 1) * 2 + 1);
        if (ks == 0) mma16816_z(acc[p][v], a.x, a.y, a.z, a.w, b0, b1);
        else mma16816(acc[p][v], a.x, a.y, a.z, a.w, b0, b1);
      }
#pragma unroll
  for (int v = 0; v < 4; v++)
    o[v] = make_uint4(pack2(acc[0][v][0], acc[0][v][1]), pack2(acc[0][v][2], acc[0][v][3]),
                      pack2(acc[1][v][0], acc[1][v][1]), pack2(acc[1][v][2], acc[1][v][3]));
}
__device__ __forceinline__ void lds_frag(uint4& f0, uint4& f1, uint32_t a0, uint32_t a1) {
  asm volatile("ld.volatile.shared.v2.u32 {%0,%1}, [%8]; ld.volatile.shared.v2.u32 {%2,%3}, [%9];\n"
               "ld.volatile.shared.v2.u32 {%4,%5}, [%8+8]; ld.volatile.shared.v2.u32 {%6,%7}, [%9+8];"
               : "=r"(f0.x), "=r"(f0.y), "=r"(f0.z), "=r"(f0.w), "=r"(f1.x), "=r"(f1.y), "=r"(f1.z), "=r"(f1.w) : "r"(a0), "r"(a1) : "memory");
}
__device__ __forceinline__ void reg_frag(uint4 (&q)[4], uint32_t ones) {
#pragma unroll
  for (int ks = 0; ks < 2; ks++) {
    const uint4 a = q[2 * ks], b = q[2 * ks + 1];
    q[2 * ks] = make_uint4(a.x, a.y, b.x & ones, b.y & ones);
    q[2 * ks + 1] = make_uint4(a.z & ones, a.w & ones, b.z, b.w);
  }
}
__device__ __forceinline__ void st_tag(uint4* p, const uint4& v, uint32_t tag) {
  asm volatile("st.relaxed.gpu.global.v4.b32 [%0], {%1,%2,%3,%4};"
               ::"l"(p), "r"((v.x & ~1u) | tag), "r"(v.y), "r"(v.z), "r"(v.w) : "memory");
}
__device__ __forceinline__ void st_tag8(void* p, uint32_t x, uint32_t y, uint32_t tag) {
  asm volatile("st.relaxed.gpu.global.v2.b32 [%0], {%1,%2};" ::"l"(p), "r"((x & ~1u) | tag), "r"(y) : "memory");
}
__device__ __forceinline__ uint4 ld_b128(const uint4* p) {
  uint4 v;
  asm volatile("ld.relaxed.gpu.global.v4.b32 {%0,%1,%2,%3}, [%4];"
               : "=r"(v.x), "=r"(v.y), "=r"(v.z), "=r"(v.w) : "l"(p) : "memory");
  return v;
}
template <int STRIDE>
__device__ __forceinline__ void ld_tag4_issue(uint4 (&q)[4], const uint4* p) {
#pragma unroll
  for (int i = 0; i < 4; i++) q[i] = ld_b128(p + i * STRIDE);
}
__device__ __forceinline__ uint32_t tag_miss(uint32_t a, uint32_t b, uint32_t c, uint32_t d, uint32_t tag) {
  uint32_t r;
  asm("{.reg .b32 u, v; lop3.b32 u, %1, %2, %5, 0x7e; lop3.b32 v, %3, %4, %5, 0x7e; lop3.b32 %0, u, v, 1, 0xa8;}"
      : "=r"(r) : "r"(a), "r"(b), "r"(c), "r"(d), "r"(tag));
  return r;
}
template <int STRIDE, bool HALVES = false>
__device__ __forceinline__ void ld_tag4_finish(uint4 (&q)[4], const uint4* p, uint32_t tag) {
  int it = 0;
#pragma unroll 1
  while (__any_sync(0xffffffffu, tag_miss(q[0].x, q[1].x, q[2].x, q[3].x, tag) | (HALVES ? tag_miss(q[0].z, q[1].z, q[2].z, q[3].z, tag) : 0u))) {
    ld_tag4_issue<STRIDE>(q, p);
    if (++it > SPIN_LIMIT) { die(); break; }
  }
#pragma unroll
  for (int i = 0; i < 4; i++) {
    asm volatile("and.b32 %0, %0, 0xfffffffe;" : "+r"(q[i].x));
    if (HALVES) q[i].z &= ~1u;
  }
}
__device__ __forceinline__ float quad_sum(const uint32_t (&a)[8]) {
  float d[4];
  mma16816_z(d, a[0], a[1], a[2], a[3], 0x3f803f80u, 0x3f803f80u);
  mma16816(d, a[4], a[5], a[6], a[7], 0x3f803f80u, 0x3f803f80u);
  return d[0] + d[2];
}
__device__ __forceinline__ float sum_groups(float v) {
  v += __shfl_xor_sync(0xffffffffu, v, 4);
  v += __shfl_xor_sync(0xffffffffu, v, 8);
  v += __shfl_xor_sync(0xffffffffu, v, 16);
  return v;
}
__device__ __forceinline__ uint32_t hsub2_bf16(uint32_t a, uint32_t b) {
  uint32_t r;
  asm("sub.rn.bf16x2 %0, %1, %2;" : "=r"(r) : "r"(a), "r"(b));
  return r;
}
__device__ __forceinline__ float row_rstd(const uint32_t (&c)[8], float delta) {
  uint32_t s[8];
#pragma unroll
  for (int i = 0; i < 8; i++) asm("mul.rn.bf16x2 %0, %1, %1;" : "=r"(s[i]) : "r"(c[i]));
  return rsqrtf(fmaxf(fmaf(-delta, delta, sum_groups(quad_sum(s)) * (1.f / 512.f)), 0.f) + 1e-5f);
}
__device__ __forceinline__ uint64_t desc64(uint32_t lo, uint32_t hi) {
  uint64_t d;
  asm("mov.b64 %0, {%1, %2};" : "=l"(d) : "r"(lo), "r"(hi));
  return d;
}
constexpr uint32_t desc_hi(uint32_t sbo, uint32_t swz) { return (sbo >> 4) | (swz << 30); }
__device__ __forceinline__ uint32_t desc_lo(uint32_t addr, uint32_t lbo) { return ((addr & 0x3FFFF) >> 4) | ((lbo >> 4) << 16); }
__device__ __forceinline__ void cp_async16(uint32_t dst, const void* src) {
  asm volatile("cp.async.cg.shared.global [%0], [%1], 16;" ::"r"(dst), "l"(src) : "memory");
}
__device__ __forceinline__ uint2 lds2(uint32_t a) {
  uint2 v;
  asm volatile("ld.shared.v2.u32 {%0,%1}, [%2];" : "=r"(v.x), "=r"(v.y) : "r"(a) : "memory");
  return v;
}
__device__ __forceinline__ uint32_t lds_u16(uint32_t a) {
  uint16_t v;
  asm volatile("ld.shared.u16 %0, [%1];" : "=h"(v) : "r"(a) : "memory");
  return v;
}
__device__ __forceinline__ void wg_fence() { asm volatile("wgmma.fence.sync.aligned;" ::: "memory"); }
__device__ __forceinline__ void wg_commit() { asm volatile("wgmma.commit_group.sync.aligned;" ::: "memory"); }
template <int N>
__device__ __forceinline__ void wg_wait() { asm volatile("wgmma.wait_group.sync.aligned %0;" ::"n"(N) : "memory"); }
__device__ __forceinline__ void bulk_load(uint32_t dst, const void* src, int bytes, uint32_t bar) {
  asm volatile("cp.async.bulk.shared::cluster.global.mbarrier::complete_tx::bytes [%0], [%1], %2, [%3];"
               ::"r"(dst), "l"(src), "r"(bytes), "r"(bar) : "memory");
}
__device__ __forceinline__ void bulk_load_mc(uint32_t dst, const void* src, int bytes, uint32_t bar) {
  asm volatile("cp.async.bulk.shared::cluster.global.mbarrier::complete_tx::bytes.multicast::cluster [%0], [%1], %2, [%3], %4;"
               ::"r"(dst), "l"(src), "r"(bytes), "r"(bar), "h"((uint16_t)3) : "memory");
}
__device__ __forceinline__ void tma3(uint32_t dst, const CUtensorMap* tm, uint32_t bar, int c0, int c1, int c2) {
  asm volatile("cp.async.bulk.tensor.3d.shared::cluster.global.mbarrier::complete_tx::bytes [%0], [%1, {%3,%4,%5}], [%2];"
               ::"r"(dst), "l"(tm), "r"(bar), "r"(c0), "r"(c1), "r"(c2) : "memory");
}
__device__ __forceinline__ void tma3_mc(uint32_t dst, const CUtensorMap* tm, uint32_t bar, int c1, int c2) {
  asm volatile("cp.async.bulk.tensor.3d.shared::cluster.global.mbarrier::complete_tx::bytes.multicast::cluster [%0], [%1, {%3,%4,%5}], [%2], %6;"
               ::"r"(dst), "l"(tm), "r"(bar), "r"(0), "r"(c1), "r"(c2), "h"((uint16_t)3) : "memory");
}
__device__ __forceinline__ void mbar_arrive_remote(uint32_t rb) {
  asm volatile("mbarrier.arrive.shared::cluster.b64 _, [%0];" ::"r"(rb) : "memory");
}
__device__ __forceinline__ uint4 ldg_ca4(const void* p) {
  uint4 v;
  asm volatile("ld.global.ca.v4.u32 {%0,%1,%2,%3}, [%4];" : "=r"(v.x), "=r"(v.y), "=r"(v.z), "=r"(v.w) : "l"(p) : "memory");
  return v;
}
__device__ __forceinline__ float u2f(uint32_t v) { return __uint_as_float(v); }
__device__ __forceinline__ void mma_az(float (&d)[4], const uint4& a, uint32_t b0, uint32_t b1) { mma16816_z(d, a.x, a.y, a.z, a.w, b0, b1); }
__device__ __forceinline__ void mma_a(float (&d)[4], const uint4& a, uint32_t b0, uint32_t b1) { mma16816(d, a.x, a.y, a.z, a.w, b0, b1); }
__device__ __forceinline__ uint32_t clock32() {
  uint32_t v;
  asm volatile("mov.u32 %0, %%clock;" : "=r"(v) :: "memory");
  return v;
}
__device__ __forceinline__ float swiglu(float g, float u, float r) {
  float hg = (0.5f * r) * g, th;
  asm("tanh.approx.f32 %0, %1;" : "=f"(th) : "f"(hg));
  return fmaf(hg, th, hg) * (r * u);
}
__device__ __forceinline__ void l2_prefetch(const void* p, int bytes) {
  asm volatile("cp.async.bulk.prefetch.L2.global [%0], %1;" ::"l"(p), "r"(bytes) : "memory");
}

__device__ __forceinline__ void wgmma_n256(float (&d)[128], uint64_t da, uint64_t db, int sd = 1) {
  asm volatile("{.reg .pred p; setp.ne.b32 p, %130, 0;\n"
      "wgmma.mma_async.sync.aligned.m64n256k16.f32.bf16.bf16 {"
      "%0,%1,%2,%3,%4,%5,%6,%7,%8,%9,%10,%11,%12,%13,%14,%15,"
      "%16,%17,%18,%19,%20,%21,%22,%23,%24,%25,%26,%27,%28,%29,%30,%31,"
      "%32,%33,%34,%35,%36,%37,%38,%39,%40,%41,%42,%43,%44,%45,%46,%47,"
      "%48,%49,%50,%51,%52,%53,%54,%55,%56,%57,%58,%59,%60,%61,%62,%63,"
      "%64,%65,%66,%67,%68,%69,%70,%71,%72,%73,%74,%75,%76,%77,%78,%79,"
      "%80,%81,%82,%83,%84,%85,%86,%87,%88,%89,%90,%91,%92,%93,%94,%95,"
      "%96,%97,%98,%99,%100,%101,%102,%103,%104,%105,%106,%107,%108,%109,%110,%111,"
      "%112,%113,%114,%115,%116,%117,%118,%119,%120,%121,%122,%123,%124,%125,%126,%127"
      "}, %128, %129, p, 1, 1, 0, 1;}\n"
      : "+f"(d[0]),"+f"(d[1]),"+f"(d[2]),"+f"(d[3]),"+f"(d[4]),"+f"(d[5]),"+f"(d[6]),"+f"(d[7]),
        "+f"(d[8]),"+f"(d[9]),"+f"(d[10]),"+f"(d[11]),"+f"(d[12]),"+f"(d[13]),"+f"(d[14]),"+f"(d[15]),
        "+f"(d[16]),"+f"(d[17]),"+f"(d[18]),"+f"(d[19]),"+f"(d[20]),"+f"(d[21]),"+f"(d[22]),"+f"(d[23]),
        "+f"(d[24]),"+f"(d[25]),"+f"(d[26]),"+f"(d[27]),"+f"(d[28]),"+f"(d[29]),"+f"(d[30]),"+f"(d[31]),
        "+f"(d[32]),"+f"(d[33]),"+f"(d[34]),"+f"(d[35]),"+f"(d[36]),"+f"(d[37]),"+f"(d[38]),"+f"(d[39]),
        "+f"(d[40]),"+f"(d[41]),"+f"(d[42]),"+f"(d[43]),"+f"(d[44]),"+f"(d[45]),"+f"(d[46]),"+f"(d[47]),
        "+f"(d[48]),"+f"(d[49]),"+f"(d[50]),"+f"(d[51]),"+f"(d[52]),"+f"(d[53]),"+f"(d[54]),"+f"(d[55]),
        "+f"(d[56]),"+f"(d[57]),"+f"(d[58]),"+f"(d[59]),"+f"(d[60]),"+f"(d[61]),"+f"(d[62]),"+f"(d[63]),
        "+f"(d[64]),"+f"(d[65]),"+f"(d[66]),"+f"(d[67]),"+f"(d[68]),"+f"(d[69]),"+f"(d[70]),"+f"(d[71]),
        "+f"(d[72]),"+f"(d[73]),"+f"(d[74]),"+f"(d[75]),"+f"(d[76]),"+f"(d[77]),"+f"(d[78]),"+f"(d[79]),
        "+f"(d[80]),"+f"(d[81]),"+f"(d[82]),"+f"(d[83]),"+f"(d[84]),"+f"(d[85]),"+f"(d[86]),"+f"(d[87]),
        "+f"(d[88]),"+f"(d[89]),"+f"(d[90]),"+f"(d[91]),"+f"(d[92]),"+f"(d[93]),"+f"(d[94]),"+f"(d[95]),
        "+f"(d[96]),"+f"(d[97]),"+f"(d[98]),"+f"(d[99]),"+f"(d[100]),"+f"(d[101]),"+f"(d[102]),"+f"(d[103]),
        "+f"(d[104]),"+f"(d[105]),"+f"(d[106]),"+f"(d[107]),"+f"(d[108]),"+f"(d[109]),"+f"(d[110]),"+f"(d[111]),
        "+f"(d[112]),"+f"(d[113]),"+f"(d[114]),"+f"(d[115]),"+f"(d[116]),"+f"(d[117]),"+f"(d[118]),"+f"(d[119]),
        "+f"(d[120]),"+f"(d[121]),"+f"(d[122]),"+f"(d[123]),"+f"(d[124]),"+f"(d[125]),"+f"(d[126]),"+f"(d[127])
      : "l"(da), "l"(db), "r"(sd));
}
__device__ __forceinline__ void wgmma_n192(float (&d)[96], uint64_t da, uint64_t db) {
  asm volatile("wgmma.mma_async.sync.aligned.m64n192k16.f32.bf16.bf16 {"
      "%0,%1,%2,%3,%4,%5,%6,%7,%8,%9,%10,%11,%12,%13,%14,%15,"
      "%16,%17,%18,%19,%20,%21,%22,%23,%24,%25,%26,%27,%28,%29,%30,%31,"
      "%32,%33,%34,%35,%36,%37,%38,%39,%40,%41,%42,%43,%44,%45,%46,%47,"
      "%48,%49,%50,%51,%52,%53,%54,%55,%56,%57,%58,%59,%60,%61,%62,%63,"
      "%64,%65,%66,%67,%68,%69,%70,%71,%72,%73,%74,%75,%76,%77,%78,%79,"
      "%80,%81,%82,%83,%84,%85,%86,%87,%88,%89,%90,%91,%92,%93,%94,%95"
      "}, %96, %97, 1, 1, 1, 0, 1;\n"
      : "+f"(d[0]),"+f"(d[1]),"+f"(d[2]),"+f"(d[3]),"+f"(d[4]),"+f"(d[5]),"+f"(d[6]),"+f"(d[7]),
        "+f"(d[8]),"+f"(d[9]),"+f"(d[10]),"+f"(d[11]),"+f"(d[12]),"+f"(d[13]),"+f"(d[14]),"+f"(d[15]),
        "+f"(d[16]),"+f"(d[17]),"+f"(d[18]),"+f"(d[19]),"+f"(d[20]),"+f"(d[21]),"+f"(d[22]),"+f"(d[23]),
        "+f"(d[24]),"+f"(d[25]),"+f"(d[26]),"+f"(d[27]),"+f"(d[28]),"+f"(d[29]),"+f"(d[30]),"+f"(d[31]),
        "+f"(d[32]),"+f"(d[33]),"+f"(d[34]),"+f"(d[35]),"+f"(d[36]),"+f"(d[37]),"+f"(d[38]),"+f"(d[39]),
        "+f"(d[40]),"+f"(d[41]),"+f"(d[42]),"+f"(d[43]),"+f"(d[44]),"+f"(d[45]),"+f"(d[46]),"+f"(d[47]),
        "+f"(d[48]),"+f"(d[49]),"+f"(d[50]),"+f"(d[51]),"+f"(d[52]),"+f"(d[53]),"+f"(d[54]),"+f"(d[55]),
        "+f"(d[56]),"+f"(d[57]),"+f"(d[58]),"+f"(d[59]),"+f"(d[60]),"+f"(d[61]),"+f"(d[62]),"+f"(d[63]),
        "+f"(d[64]),"+f"(d[65]),"+f"(d[66]),"+f"(d[67]),"+f"(d[68]),"+f"(d[69]),"+f"(d[70]),"+f"(d[71]),
        "+f"(d[72]),"+f"(d[73]),"+f"(d[74]),"+f"(d[75]),"+f"(d[76]),"+f"(d[77]),"+f"(d[78]),"+f"(d[79]),
        "+f"(d[80]),"+f"(d[81]),"+f"(d[82]),"+f"(d[83]),"+f"(d[84]),"+f"(d[85]),"+f"(d[86]),"+f"(d[87]),
        "+f"(d[88]),"+f"(d[89]),"+f"(d[90]),"+f"(d[91]),"+f"(d[92]),"+f"(d[93]),"+f"(d[94]),"+f"(d[95])
      : "l"(da), "l"(db));
}
__device__ __forceinline__ void wgmma_rs_n128(float (&d)[64], uint32_t a0, uint32_t a1, uint32_t a2, uint32_t a3, uint64_t db, int sd = 1) {
  asm volatile("{.reg .pred p; setp.ne.b32 p, %69, 0;\n"
      "wgmma.mma_async.sync.aligned.m64n128k16.f32.bf16.bf16 {"
      "%0,%1,%2,%3,%4,%5,%6,%7,%8,%9,%10,%11,%12,%13,%14,%15,"
      "%16,%17,%18,%19,%20,%21,%22,%23,%24,%25,%26,%27,%28,%29,%30,%31,"
      "%32,%33,%34,%35,%36,%37,%38,%39,%40,%41,%42,%43,%44,%45,%46,%47,"
      "%48,%49,%50,%51,%52,%53,%54,%55,%56,%57,%58,%59,%60,%61,%62,%63"
      "}, {%64,%65,%66,%67}, %68, p, 1, 1, 1;}\n"
      : "+f"(d[0]),"+f"(d[1]),"+f"(d[2]),"+f"(d[3]),"+f"(d[4]),"+f"(d[5]),"+f"(d[6]),"+f"(d[7]),
        "+f"(d[8]),"+f"(d[9]),"+f"(d[10]),"+f"(d[11]),"+f"(d[12]),"+f"(d[13]),"+f"(d[14]),"+f"(d[15]),
        "+f"(d[16]),"+f"(d[17]),"+f"(d[18]),"+f"(d[19]),"+f"(d[20]),"+f"(d[21]),"+f"(d[22]),"+f"(d[23]),
        "+f"(d[24]),"+f"(d[25]),"+f"(d[26]),"+f"(d[27]),"+f"(d[28]),"+f"(d[29]),"+f"(d[30]),"+f"(d[31]),
        "+f"(d[32]),"+f"(d[33]),"+f"(d[34]),"+f"(d[35]),"+f"(d[36]),"+f"(d[37]),"+f"(d[38]),"+f"(d[39]),
        "+f"(d[40]),"+f"(d[41]),"+f"(d[42]),"+f"(d[43]),"+f"(d[44]),"+f"(d[45]),"+f"(d[46]),"+f"(d[47]),
        "+f"(d[48]),"+f"(d[49]),"+f"(d[50]),"+f"(d[51]),"+f"(d[52]),"+f"(d[53]),"+f"(d[54]),"+f"(d[55]),
        "+f"(d[56]),"+f"(d[57]),"+f"(d[58]),"+f"(d[59]),"+f"(d[60]),"+f"(d[61]),"+f"(d[62]),"+f"(d[63])
      : "r"(a0), "r"(a1), "r"(a2), "r"(a3), "l"(db), "r"(sd));
}
__device__ __forceinline__ void wgmma_rs_n256(float (&d)[128], uint32_t a0, uint32_t a1, uint32_t a2, uint32_t a3, uint64_t db, int sd = 1) {
  asm volatile("{.reg .pred p; setp.ne.b32 p, %133, 0;\n"
      "wgmma.mma_async.sync.aligned.m64n256k16.f32.bf16.bf16 {"
      "%0,%1,%2,%3,%4,%5,%6,%7,%8,%9,%10,%11,%12,%13,%14,%15,"
      "%16,%17,%18,%19,%20,%21,%22,%23,%24,%25,%26,%27,%28,%29,%30,%31,"
      "%32,%33,%34,%35,%36,%37,%38,%39,%40,%41,%42,%43,%44,%45,%46,%47,"
      "%48,%49,%50,%51,%52,%53,%54,%55,%56,%57,%58,%59,%60,%61,%62,%63,"
      "%64,%65,%66,%67,%68,%69,%70,%71,%72,%73,%74,%75,%76,%77,%78,%79,"
      "%80,%81,%82,%83,%84,%85,%86,%87,%88,%89,%90,%91,%92,%93,%94,%95,"
      "%96,%97,%98,%99,%100,%101,%102,%103,%104,%105,%106,%107,%108,%109,%110,%111,"
      "%112,%113,%114,%115,%116,%117,%118,%119,%120,%121,%122,%123,%124,%125,%126,%127"
      "}, {%128,%129,%130,%131}, %132, p, 1, 1, 1;}\n"
      : "+f"(d[0]),"+f"(d[1]),"+f"(d[2]),"+f"(d[3]),"+f"(d[4]),"+f"(d[5]),"+f"(d[6]),"+f"(d[7]),
        "+f"(d[8]),"+f"(d[9]),"+f"(d[10]),"+f"(d[11]),"+f"(d[12]),"+f"(d[13]),"+f"(d[14]),"+f"(d[15]),
        "+f"(d[16]),"+f"(d[17]),"+f"(d[18]),"+f"(d[19]),"+f"(d[20]),"+f"(d[21]),"+f"(d[22]),"+f"(d[23]),
        "+f"(d[24]),"+f"(d[25]),"+f"(d[26]),"+f"(d[27]),"+f"(d[28]),"+f"(d[29]),"+f"(d[30]),"+f"(d[31]),
        "+f"(d[32]),"+f"(d[33]),"+f"(d[34]),"+f"(d[35]),"+f"(d[36]),"+f"(d[37]),"+f"(d[38]),"+f"(d[39]),
        "+f"(d[40]),"+f"(d[41]),"+f"(d[42]),"+f"(d[43]),"+f"(d[44]),"+f"(d[45]),"+f"(d[46]),"+f"(d[47]),
        "+f"(d[48]),"+f"(d[49]),"+f"(d[50]),"+f"(d[51]),"+f"(d[52]),"+f"(d[53]),"+f"(d[54]),"+f"(d[55]),
        "+f"(d[56]),"+f"(d[57]),"+f"(d[58]),"+f"(d[59]),"+f"(d[60]),"+f"(d[61]),"+f"(d[62]),"+f"(d[63]),
        "+f"(d[64]),"+f"(d[65]),"+f"(d[66]),"+f"(d[67]),"+f"(d[68]),"+f"(d[69]),"+f"(d[70]),"+f"(d[71]),
        "+f"(d[72]),"+f"(d[73]),"+f"(d[74]),"+f"(d[75]),"+f"(d[76]),"+f"(d[77]),"+f"(d[78]),"+f"(d[79]),
        "+f"(d[80]),"+f"(d[81]),"+f"(d[82]),"+f"(d[83]),"+f"(d[84]),"+f"(d[85]),"+f"(d[86]),"+f"(d[87]),
        "+f"(d[88]),"+f"(d[89]),"+f"(d[90]),"+f"(d[91]),"+f"(d[92]),"+f"(d[93]),"+f"(d[94]),"+f"(d[95]),
        "+f"(d[96]),"+f"(d[97]),"+f"(d[98]),"+f"(d[99]),"+f"(d[100]),"+f"(d[101]),"+f"(d[102]),"+f"(d[103]),
        "+f"(d[104]),"+f"(d[105]),"+f"(d[106]),"+f"(d[107]),"+f"(d[108]),"+f"(d[109]),"+f"(d[110]),"+f"(d[111]),
        "+f"(d[112]),"+f"(d[113]),"+f"(d[114]),"+f"(d[115]),"+f"(d[116]),"+f"(d[117]),"+f"(d[118]),"+f"(d[119]),
        "+f"(d[120]),"+f"(d[121]),"+f"(d[122]),"+f"(d[123]),"+f"(d[124]),"+f"(d[125]),"+f"(d[126]),"+f"(d[127])
      : "r"(a0), "r"(a1), "r"(a2), "r"(a3), "l"(db), "r"(sd));
}
__device__ __forceinline__ void wgmma_rs_n192(float (&d)[96], uint32_t a0, uint32_t a1, uint32_t a2, uint32_t a3, uint64_t db) {
  asm volatile("wgmma.mma_async.sync.aligned.m64n192k16.f32.bf16.bf16 {"
      "%0,%1,%2,%3,%4,%5,%6,%7,%8,%9,%10,%11,%12,%13,%14,%15,"
      "%16,%17,%18,%19,%20,%21,%22,%23,%24,%25,%26,%27,%28,%29,%30,%31,"
      "%32,%33,%34,%35,%36,%37,%38,%39,%40,%41,%42,%43,%44,%45,%46,%47,"
      "%48,%49,%50,%51,%52,%53,%54,%55,%56,%57,%58,%59,%60,%61,%62,%63,"
      "%64,%65,%66,%67,%68,%69,%70,%71,%72,%73,%74,%75,%76,%77,%78,%79,"
      "%80,%81,%82,%83,%84,%85,%86,%87,%88,%89,%90,%91,%92,%93,%94,%95"
      "}, {%96,%97,%98,%99}, %100, 1, 1, 1, 1;\n"
      : "+f"(d[0]),"+f"(d[1]),"+f"(d[2]),"+f"(d[3]),"+f"(d[4]),"+f"(d[5]),"+f"(d[6]),"+f"(d[7]),
        "+f"(d[8]),"+f"(d[9]),"+f"(d[10]),"+f"(d[11]),"+f"(d[12]),"+f"(d[13]),"+f"(d[14]),"+f"(d[15]),
        "+f"(d[16]),"+f"(d[17]),"+f"(d[18]),"+f"(d[19]),"+f"(d[20]),"+f"(d[21]),"+f"(d[22]),"+f"(d[23]),
        "+f"(d[24]),"+f"(d[25]),"+f"(d[26]),"+f"(d[27]),"+f"(d[28]),"+f"(d[29]),"+f"(d[30]),"+f"(d[31]),
        "+f"(d[32]),"+f"(d[33]),"+f"(d[34]),"+f"(d[35]),"+f"(d[36]),"+f"(d[37]),"+f"(d[38]),"+f"(d[39]),
        "+f"(d[40]),"+f"(d[41]),"+f"(d[42]),"+f"(d[43]),"+f"(d[44]),"+f"(d[45]),"+f"(d[46]),"+f"(d[47]),
        "+f"(d[48]),"+f"(d[49]),"+f"(d[50]),"+f"(d[51]),"+f"(d[52]),"+f"(d[53]),"+f"(d[54]),"+f"(d[55]),
        "+f"(d[56]),"+f"(d[57]),"+f"(d[58]),"+f"(d[59]),"+f"(d[60]),"+f"(d[61]),"+f"(d[62]),"+f"(d[63]),
        "+f"(d[64]),"+f"(d[65]),"+f"(d[66]),"+f"(d[67]),"+f"(d[68]),"+f"(d[69]),"+f"(d[70]),"+f"(d[71]),
        "+f"(d[72]),"+f"(d[73]),"+f"(d[74]),"+f"(d[75]),"+f"(d[76]),"+f"(d[77]),"+f"(d[78]),"+f"(d[79]),
        "+f"(d[80]),"+f"(d[81]),"+f"(d[82]),"+f"(d[83]),"+f"(d[84]),"+f"(d[85]),"+f"(d[86]),"+f"(d[87]),
        "+f"(d[88]),"+f"(d[89]),"+f"(d[90]),"+f"(d[91]),"+f"(d[92]),"+f"(d[93]),"+f"(d[94]),"+f"(d[95])
      : "r"(a0), "r"(a1), "r"(a2), "r"(a3), "l"(db));
}


constexpr int C_LN = 0, C_PX = 16, C_PY = 32;
constexpr int NB_CONS = 1, NB_LN = 2, NB_LAG = 4, NB_INIT = 6, NB_RDY = 7;
constexpr int LAGX = 3;
constexpr int LAGY = 6;
constexpr int LAG2 = 5;
constexpr int NLL = 2;
constexpr int POLL_DELAY = 1200;
constexpr int POLL_DELAY2 = 1000;
constexpr int POLL_DELAY3 = 600;
constexpr int FILT_DELAY = 800;
constexpr int WARM = 4;
constexpr int ALEAD = 6;
constexpr int XTRIG = 20;
constexpr int HTRIG = 0;
constexpr int SM_E = 0, SM_X = 16384, SM_E2 = 32768, SM_W = 49152, SM_FC = 69632, SM_T = 73728 - T1_BYTES;
constexpr unsigned long long KORDER = 0xBA9432DC876510ull;
constexpr unsigned long long BSLOT = 0x52140A98D52140ull, PSLOT = 0xB763CB763CB763ull;
constexpr unsigned long long BDEP = 0xFFEC97531ull, PDEP = 0xBA754ull;
constexpr uint32_t HI128 = desc_hi(1024, 1), HI64 = desc_hi(512, 2);

struct Bars {
  uint64_t full1[32], empty1[32], freeA[4], full2[16], fullA[8], empty2[8], emptyP[9], sig, done, fullP[32], hbar, tbar, hint[3], sbar;
  uint32_t epoch, pad;
};

template <int NK, bool STORE, int J0 = 0, int J1 = NK>
__device__ __forceinline__ void make_p(const float (&acc)[NK * 16], float r0, float r1, uint4 (&p)[NK], uint4* pbase, int ks0, uint32_t tag) {
#pragma unroll
  for (int j = J0; j < J1; j++) {
    uint32_t w[4];
#pragma unroll
    for (int i = 0; i < 4; i++) {
      const int a = 8 * j + 2 * i, b = a + NK * 8;
      w[i] = pack2(swiglu(acc[a], acc[b], (i & 1) ? r1 : r0), swiglu(acc[a + 1], acc[b + 1], (i & 1) ? r1 : r0));
    }
    asm volatile("" : "+r"(w[0]), "+r"(w[1]), "+r"(w[2]), "+r"(w[3]));
    p[j] = make_uint4(w[0], w[1], w[2], w[3]);
    if (STORE) st_tag(pbase + ((ks0 + j) >> 2) * 1024 + ((ks0 + j) & 3) * 32, p[j], tag);
  }
}
__device__ __forceinline__ void spin_until(uint32_t t) {
  while ((int)(clock32() - t) < 0) {}
}

__global__ void __cluster_dims__(2, 1, 1) __launch_bounds__(NTHREADS, 1)
fused_kernel(const __nv_bfloat16* __restrict__ x, const Tables* __restrict__ tab, Scratch* __restrict__ scr,
             __nv_bfloat16* __restrict__ out, const char* __restrict__ wg_raw, const char* __restrict__ wu_raw,
             const char* __restrict__ wd_raw,
             const __grid_constant__ CUtensorMap tmWR, const __grid_constant__ CUtensorMap tmWI,
             const __grid_constant__ CUtensorMap tmGX, const __grid_constant__ CUtensorMap tmUX,
             const __grid_constant__ CUtensorMap tmGY, const __grid_constant__ CUtensorMap tmUY,
             const __grid_constant__ CUtensorMap tmD) {
  extern __shared__ __align__(1024) char smem_raw[];
  const uint32_t sbase = s2u(smem_raw);
  const uint32_t sbar = sbase + 14 * SLOT, sstat = sbar + 1408;
  const int tid = threadIdx.x, lane = tid & 31;
  const int c = blockIdx.x, rk = c & 1, f = (c >> 1) & 7, rb = 2 * (c >> 4) + rk;
  const int rb2 = 2 * (c >> 4) + (f >> 2), kh = (f >> 1) & 1, nq = 2 * (f & 1) + rk;
#define BAR(field, i) (sbar + (uint32_t)offsetof(Bars, field) + 8u * (i))
#define TOFF(field) (sbase + SM_T + (uint32_t)offsetof(Tables, field) + lane * 16)

  if (tid >= 256) {
    asm volatile("setmaxnreg.dec.sync.aligned.u32 40;");
    const int warp = __shfl_sync(0xffffffffu, tid >> 5, 0);
    if (lane == 0) {
      auto init = [&](uint32_t b, int n, int count, int bytes) {
#pragma unroll
        for (int i = 0; i < n; i++) mbar_init(b + 8 * i, count);
#pragma unroll
        for (int i = 0; i < (bytes ? n : 0); i++) mbar_expect(b + 8 * i, bytes);
      };
      if (warp == 8) {
        if (sbase & 1023) die();
        init(BAR(tbar, 0), 1, 1, T2_BYTES + 2 * 10240);
        init(BAR(hbar, 0), 1, 1, 16384);
        init(BAR(hint, 0), 3, 1, 0);
        init(BAR(sbar, 0), 1, 32, 0);
        init(BAR(empty2, 0), 19, 8, 0);
      } else if (warp == 9) {
        init(BAR(full1, 0), 16, 1, 16384);
        init(BAR(full1, 16), 16, 1, 12288);
      } else if (warp == 10) {
        init(BAR(fullP, 0), 30, 1, 8192);
      } else {
        init(BAR(full2, 0), 24, 1, 16384);
        init(BAR(empty1, 0), 36, 16, 0);
      }
      asm volatile("fence.mbarrier_init.release.cluster;" ::: "memory");
    }
    if (tid == 256) {
      const int w0 = ((c >> 3) * 257 + 32 * (c & 7) + 1) & ~7;
      asm volatile("prefetch.tensormap [%0];" ::"l"(&tmWR) : "memory");
      asm volatile("prefetch.tensormap [%0];" ::"l"(&tmWI) : "memory");
      spin_until(clock32() + FILT_DELAY);
      tma3(sbase + SM_W, &tmWR, BAR(tbar, 0), w0, 0, 0);
      tma3(sbase + SM_W + 10240, &tmWI, BAR(tbar, 0), w0, 0, 0);
      bulk_load(sbase + SM_T + T1_BYTES, reinterpret_cast<const char*>(tab) + T1_BYTES, T2_BYTES, BAR(tbar, 0));
    }
    if (tid == 288) {
      asm volatile("prefetch.tensormap [%0];" ::"l"(rk ? &tmUX : &tmGX) : "memory");
      asm volatile("prefetch.tensormap [%0];" ::"l"(rk ? &tmUY : &tmGY) : "memory");
      asm volatile("prefetch.tensormap [%0];" ::"l"(&tmD) : "memory");
    }
    if (tid == 320) {
      const unsigned e = ld_relaxed(&scr->cnt[(C_LN + rb) * 32]) >> 3;
      asm volatile("st.shared.u32 [%0], %1;" ::"r"(BAR(epoch, 0)), "r"(e) : "memory");
    }
    __syncwarp();
    asm volatile("barrier.cluster.arrive.relaxed.aligned;" ::: "memory");
    bar_arrive(NB_RDY, 384);
    asm volatile("barrier.cluster.wait.aligned;" ::: "memory");
    bar_sync(NB_INIT, 384);
    unsigned epoch;
    asm volatile("ld.shared.u32 %0, [%1];" : "=r"(epoch) : "r"(BAR(epoch, 0)) : "memory");
    if (warp == 8) {
      if (lane == 0) {
        const int ax = (7 * f + 3 * (f & 1)) >> 1;
        const int ay = 7 * f + ((f & 1) ? 0 : 4);
        const CUtensorMap* tx = rk ? &tmUX : &tmGX;
        const CUtensorMap* ty = rk ? &tmUY : &tmGY;
        mbar_wait_bounded(BAR(sig, 0));
        uint32_t s = 2;
#pragma unroll 1
        for (int n = 0; n < 16; n++) {
          if (n >= 6) mbar_wait_bounded(BAR(empty1, n - 6));
          tma3_mc(sbase + (8 + s) * SLOT + rk * 8192, tx, BAR(full1, n), n * 32, ax);
          if (++s == 6) s = 0;
          if (n >= 10 && n < 15) {
            const int k = n - 10;
            mbar_wait_bounded(BAR(freeA, (12 * k + 11) >> 4));
            tma3_mc(sbase + k * 12288 + rk * 6144, ty, BAR(full1, 16 + k), (k + 8) * 32, ay);
          }
        }
#pragma unroll 1
        for (int k = 5; k < 16; k++) {
          mbar_wait_bounded(BAR(empty1, k < 13 ? 10 + ((12 * (k - 5) + 11) >> 4) : 8 + k));
          tma3_mc(sbase + 8 * SLOT + ((k - 5) & 7) * 12288 + rk * 6144, ty, BAR(full1, 16 + k), ((k + 8) & 15) * 32, ay);
        }
        mbar_wait_bounded(BAR(done, 0));
      }
    } else if (warp == 9) {
      if (lane == 0) {
        mbar_wait(BAR(fullA, 4));
        wait_counter(&scr->cnt[(C_LN + rb2) * 32], (epoch + 1) * 8);
        asm volatile("fence.proxy.async.global;" ::: "memory");
#pragma unroll 1
        for (int i = 0; i < 14; i++) {
          const int kblk = 14 * kh + (int)((KORDER >> (4 * i)) & 15);
          mbar_wait(i < 9 ? BAR(empty1, 16 + (uint32_t)((BDEP >> (4 * i)) & 15)) : BAR(empty2, i - 9));
          tma3(sbase + (uint32_t)((BSLOT >> (4 * i)) & 15) * SLOT, &tmD, BAR(full2, i), 0, 64 * kblk, 2 * nq);
        }
        mbar_wait(BAR(empty2, 5));
        bulk_load(sbase + 13 * SLOT, &scr->LN[(rb2 * 8 + 2 * nq) * 1024 + kh * 512], 8192, BAR(hbar, 0));
        bulk_load(sbase + 13 * SLOT + 8192, &scr->LN[(rb2 * 8 + 2 * nq + 1) * 1024 + kh * 512], 8192, BAR(hbar, 0));
      }
    } else if (warp == 10) {
      bar_sync(NB_LN, 288);
      if (lane == 0) {
        red_release(&scr->cnt[(C_LN + rb) * 32]);
        wait_counter(&scr->cnt[(C_LN + rb) * 32], (epoch + 1) * 8);
        asm volatile("fence.proxy.async.global;" ::: "memory");
#pragma unroll 1
        for (int kb = NLL; kb < 8; kb++) {
          if (2 * kb >= ALEAD) mbar_wait(BAR(empty1, 2 * kb - ALEAD));
          bulk_load(sbase + kb * SLOT, &scr->LN[(rb * 8 + kb) * 1024], 16384, BAR(fullA, kb));
        }
#pragma unroll 1
        for (int s = 0; s < 14; s++) {
          const int kblk = 14 * kh + (int)((KORDER >> (4 * s)) & 15);
          if (s == 0 || s == 8 || s == 11) {
            mbar_wait(BAR(hint, s == 0 ? 0 : s == 8 ? 1 : 2));
          }
          mbar_wait(s < 5 ? BAR(empty1, 16 + (uint32_t)((PDEP >> (4 * s)) & 15)) : BAR(emptyP, s - 5));
          bulk_load_mc(sbase + (uint32_t)((PSLOT >> (4 * s)) & 15) * SLOT + rk * 8192, &scr->P[(rb2 * 28 + kblk) * 1024 + rk * 512], 8192, BAR(fullP, 16 * rk + s));
        }
      }
    } else {
      if (lane == 0) {
        mbar_wait(BAR(tbar, 0));
        l2_prefetch(wg_raw + (size_t)c * 5376, 5376);
        l2_prefetch(wu_raw + (size_t)c * 5376, 5376);
        mbar_wait(BAR(sig, 0));
        l2_prefetch(wg_raw + 688128 + (size_t)c * 8960, 8960);
        l2_prefetch(wu_raw + 688128 + (size_t)c * 8960, 8960);
      }
      mbar_wait(BAR(fullA, 4));
      if (lane == 0) l2_prefetch(wd_raw + (size_t)c * 14336, 14336);
      {
        const uint32_t tag = (epoch + 1) & 1;
        uint4 v0, v1, v2;
        while (true) {
          v0 = ld_b128(&scr->ST[rb * 64 + lane]);
          v1 = ld_b128(&scr->ST[rb * 64 + 32 + lane]);
          v2 = ld_b128(&scr->ST[rb2 * 64 + 32 * kh + lane]);
          if (!__any_sync(0xffffffffu, ((v0.x ^ tag) | (v1.x ^ tag) | (v2.x ^ tag)) & 1u)) break;
        }
        sts4(sstat + lane * 16, v0.x & ~1u, v0.y, v0.z, v0.w);
        sts4(sstat + 512 + lane * 16, v1.x & ~1u, v1.y, v1.z, v1.w);
        sts4(sstat + 1024 + lane * 16, v2.x & ~1u, v2.y, v2.z, v2.w);
        mbar_arrive(BAR(sbar, 0));
      }
      if (lane == 0) {
        mbar_wait(BAR(empty1, XTRIG));
        while ((int)(ld_relaxed(&scr->cnt[(C_PX + rb2) * 32 + kh]) - (epoch + 1) * 32) < 0) {
        }
        mbar_arrive(BAR(hint, 0));
        mbar_wait(BAR(emptyP, HTRIG));
        uint32_t done = 0;
        while (done != 3) {
          uint2 v;
          asm volatile("ld.relaxed.gpu.global.v2.u32 {%0,%1}, [%2];" : "=r"(v.x), "=r"(v.y) : "l"(&scr->cnt[(C_PY + rb2) * 32 + 4 * (rk ^ kh ^ 1) + 2 * kh]) : "memory");
          if (!(done & 1) && (int)(v.x - (epoch + 1) * 8) >= 0) { done |= 1; mbar_arrive(BAR(hint, 1)); }
          if (!(done & 2) && (int)(v.y - (epoch + 1) * 8) >= 0) { done |= 2; mbar_arrive(BAR(hint, 2)); }
        }
      }
    }
  } else {
    const int warp = __shfl_sync(0xffffffffu, tid >> 5, 0);
    const int g = lane >> 2, t = lane & 3;
    uint4 fa[4], fb[4], tw[6];
#pragma unroll
    for (int i = 0; i < 4; i++) fa[i] = ldg_ca4(&tab->fa[i][lane][0]);
#pragma unroll
    for (int i = 0; i < 6; i++) tw[i] = ldg_ca4(&tab->tw1[i][lane][0]);
#pragma unroll
    for (int i = 0; i < 4; i++) fb[i] = ldg_ca4(&tab->fb[i][lane][0]);
#pragma unroll
    for (int i = 0; i < 4; i++) {
      const int r = i >> 1, ch = (i & 1) * 32 + lane;
      cp_async16(sbase + SM_X + (2 * warp + r) * 1024 + ((ch ^ ((ch >> 3) & 1)) * 16),
                 x + (size_t)(c + 128 * (2 * warp + r)) * 512 + ch * 8);
    }
    asm volatile("cp.async.commit_group;" ::: "memory");
    asm volatile("barrier.cluster.arrive.relaxed.aligned;" ::: "memory");
    uint32_t rbar;
    asm volatile("mapa.shared::cluster.u32 %0, %1, %2;" : "=r"(rbar) : "r"(sbar), "r"(rk ^ 1));
#define RBAR(field, i) (rbar + (uint32_t)offsetof(Bars, field) + 8u * (i))
    {
      const int ln = (tid >> 1) & 31, lg = ln >> 2, lt = ln & 3, i = 4 * (tid >> 6) + 2 * (tid & 1);
      const int kidx = lt + 8 * (i >> 3), nidx = 4 * ((i >> 1) & 3) + (lg >> 1);
      const uint32_t a0 = cfrag<2048>((c + 128 * kidx) * nidx, lg & 1), a1 = cfrag<2048>((c + 128 * (kidx + 4)) * nidx, lg & 1);
      const uint32_t b0 = cfrag<2048>(-(c + 128 * nidx) * kidx, lg & 1), b1 = cfrag<2048>(-(c + 128 * nidx) * (kidx + 4), lg & 1);
      asm volatile("st.shared.v2.u32 [%0], {%1,%2};" ::"r"(sbase + SM_FC + tid * 8), "r"(a0), "r"(a1) : "memory");
      asm volatile("st.shared.v2.u32 [%0], {%1,%2};" ::"r"(sbase + SM_FC + 2048 + tid * 8), "r"(b0), "r"(b1) : "memory");
    }
    bar_sync(NB_CONS, 256);
    uint4 fc[4];
#pragma unroll
    for (int i = 0; i < 4; i++) fc[i] = lds4(sbase + SM_FC + i * 512 + lane * 16);
    asm volatile("cp.async.wait_group 0;" ::: "memory");
    __syncwarp();
    bar_arrive(NB_INIT, 384);
    uint32_t tag, ones;
    uint4 q[4], o[4];
    {
      uint32_t v[2][8];
#pragma unroll
      for (int r = 0; r < 2; r++)
#pragma unroll
        for (int ks = 0; ks < 2; ks++) {
          const int ch = 32 * ks + 2 * (lane & 15) + (lane >> 4);
          asm volatile("ldmatrix.sync.aligned.m8n8.x4.trans.shared.b16 {%0,%1,%2,%3}, [%4];"
                       : "=r"(v[r][4 * ks]), "=r"(v[r][4 * ks + 1]), "=r"(v[r][4 * ks + 2]), "=r"(v[r][4 * ks + 3])
                       : "r"(sbase + SM_X + (2 * warp + r) * 1024 + ((ch ^ ((ch >> 3) & 1)) * 16)) : "memory");
        }
      float sq[2];
#pragma unroll
      for (int r = 0; r < 2; r++) {
        float s0 = 0.f, s1 = 0.f;
#pragma unroll
        for (int i = 0; i < 8; i++) {
          const float lo = bf_lo(v[r][i]), hi = u2f(v[r][i] & 0xffff0000u);
          s0 = fmaf(lo, lo, s0);
          s1 = fmaf(hi, hi, s1);
        }
        sq[r] = s0 + s1;
      }
      {
        float w = ((lane & 1) ? sq[1] : sq[0]) + __shfl_xor_sync(0xffffffffu, (lane & 1) ? sq[0] : sq[1], 1);
        w += __shfl_xor_sync(0xffffffffu, w, 2);
        w = sum_groups(w);
        const float o2 = __shfl_xor_sync(0xffffffffu, w, 1);
        sq[0] = (lane & 1) ? o2 : w;
        sq[1] = (lane & 1) ? w : o2;
      }
#pragma unroll
      for (int r = 0; r < 2; r++) {
        float dd[2][4], ee[2][4];
#pragma unroll
        for (int nt = 0; nt < 2; nt++) {
          mma_az(dd[nt], fa[0], v[r][2 * nt], v[r][2 * nt + 1]);
          mma_a(dd[nt], fa[1], v[r][4 + 2 * nt], v[r][5 + 2 * nt]);
          mma_az(ee[nt], fa[2], v[r][2 * nt], v[r][2 * nt + 1]);
          mma_a(ee[nt], fa[3], v[r][4 + 2 * nt], v[r][5 + 2 * nt]);
        }
        float mean = (dd[0][0] + dd[0][1]) + (dd[1][0] + dd[1][1]);
        mean += __shfl_xor_sync(0xffffffffu, mean, 1);
        mean += __shfl_xor_sync(0xffffffffu, mean, 2);
        mean = __shfl_sync(0xffffffffu, mean, 0) * (1.f / 512.f);
        const float rs = rsqrtf(fmaxf(fmaf(-mean, mean, sq[r] * (1.f / 512.f)), 0.f) + 1e-5f);
        float acc[4][4];
#pragma unroll
        for (int nt = 0; nt < 2; nt++) {
          const float (&d)[4] = dd[nt];
          const float (&e)[4] = ee[nt];
          const uint4 &ka = tw[2 * nt], &kb = tw[2 * nt + 1], &kc = tw[4 + nt];
          const uint32_t a0 = pack2(d[0] * u2f(ka.x) + d[2] * u2f(ka.y), d[1] * u2f(kb.x) + d[3] * u2f(kb.y));
          const uint32_t a2 = pack2(d[0] * u2f(ka.z) + d[2] * u2f(ka.w), d[1] * u2f(kb.z) + d[3] * u2f(kb.w));
          const uint32_t a1 = pack2(e[0] * u2f(kc.x) + e[2] * u2f(kc.y), e[1] * u2f(kc.z) + e[3] * u2f(kc.w));
          const uint32_t a3 = pack2(e[2] * u2f(kc.x) - e[0] * u2f(kc.y), e[3] * u2f(kc.z) - e[1] * u2f(kc.w));
          const uint32_t dc = pack2(fmaf(mean, -32.f, d[0]), fmaf(mean, -32.f, d[1]));
          const uint32_t h0 = g == 0 ? dc : a0, h2 = g == 0 ? 0u : a2;
          if (nt == 0) {
            mma16816_z(acc[0], a0, a1, a2, a3, fb[2 * nt].x, fb[2 * nt].y);
            mma16816_z(acc[1], a0, a1, a2, a3, fb[2 * nt].z, fb[2 * nt].w);
            mma16816_z(acc[2], h0, a1, h2, a3, fb[2 * nt + 1].x, fb[2 * nt + 1].y);
            mma16816_z(acc[3], h0, a1, h2, a3, fb[2 * nt + 1].z, fb[2 * nt + 1].w);
          } else {
            mma16816(acc[0], a0, a1, a2, a3, fb[2 * nt].x, fb[2 * nt].y);
            mma16816(acc[1], a0, a1, a2, a3, fb[2 * nt].z, fb[2 * nt].w);
            mma16816(acc[2], h0, a1, h2, a3, fb[2 * nt + 1].x, fb[2 * nt + 1].y);
            mma16816(acc[3], h0, a1, h2, a3, fb[2 * nt + 1].z, fb[2 * nt + 1].w);
          }
        }
#pragma unroll
        for (int h = 0; h < 2; h++) {
          const int j = 2 * warp + r, m = 2 * t + h;
          sts4(sbase + SM_E + ((j * 8 + m) * 8 + (g ^ (2 * t) ^ (2 * (j & 3)))) * 16,
               pack2(acc[h][0] * rs, acc[h][1] * rs), pack2(acc[h][2] * rs, acc[h][3] * rs),
               pack2(acc[2 + h][0] * rs, acc[2 + h][1] * rs), pack2(acc[2 + h][2] * rs, acc[2 + h][3] * rs));
        }
      }
      bar_sync(NB_RDY, 384);
      const uint32_t ea = sbase + SM_E + ((t * 8 + warp) * 8 + (g ^ (warp & 6) ^ (2 * t))) * 16;
      lds_frag(q[0], q[1], ea, ea + 4096);
      lds_frag(q[2], q[3], ea + 8192, ea + 12288);
      asm volatile("ld.shared.u32 %0, [%1];" : "=r"(tag) : "r"(BAR(epoch, 0)) : "memory");
      ones = ~(tag >> 31);
      tag = (tag + 1) & 1;
      cdft16(q, fc, o);
#pragma unroll
      for (int vv = 0; vv < 4; vv++) {
        o[vv].y &= ~1u;
        o[vv].z = (o[vv].z & ~1u) | (tag ^ 1);
        st_tag(&scr->Z1[(((4 * vv + t) * 8 + warp) * 128 + c) * 8 + g], o[vv], tag);
      }
    }
    asm volatile("setmaxnreg.inc.sync.aligned.u32 232;");
    {
      uint4* const zp = &scr->Z1[(c * 128 + 8 * t + warp) * 8 + g];
      const uint32_t tst = clock32();
      mbar_wait(BAR(tbar, 0));
      uint4 f2[4], g2[4];
#pragma unroll
      for (int i = 0; i < 4; i++) {
        f2[i] = lds4(TOFF(f2) + warp * 2048 + i * 512);
        g2[i] = lds4(TOFF(g2) + warp * 2048 + i * 512);
      }
      const uint4 f8 = lds4(TOFF(f8)), g8 = lds4(TOFF(g8));
      asm volatile("barrier.cluster.wait.aligned;" ::: "memory");
      spin_until(tst + POLL_DELAY);
      ld_tag4_issue<256>(q, zp);
      float wfr[16], wfi[16];
      {
        const float nyq = ((c & 7) == 7 && g == 0) ? 0.5f : 1.f;
        uint32_t wa = sbase + SM_W + (16 * warp + t) * 80 + ((2 * (c >> 3) + 2) & 15) - 2;
        asm volatile("" : "+r"(wa));
        const uint32_t wb[3] = {wa + 2 * (g == 0 ? 16 : g), wa + 2 * g, wa - 2 * g};
#pragma unroll
        for (int i = 0; i < 16; i++) {
          const int ci = i >> 3, dd = (i >> 2) & 1, e = i & 3;
          const uint32_t a = wb[e < 2 ? e : 2] + (ci * 8 + 4 * dd) * 80 + (e == 0 ? 0 : e == 1 ? 16 : e == 2 ? 64 : 48);
          wfr[i] = bf_lo(lds_u16(a)) * (e == 2 ? nyq : 1.f);
          wfi[i] = bf_lo(lds_u16(a + 10240)) * (e == 2 ? nyq : 1.f);
        }
      }
      ld_tag4_finish<256>(q, zp, tag);
#pragma unroll
      for (int i = 0; i < 4; i++) q[i].z &= ~1u;
      reg_frag(q, ones);
      cdft16(q, f2, o);
      const uint32_t e2 = sbase + SM_E2;
#pragma unroll
      for (int vv = 0; vv < 4; vv++)
        sts4(e2 + ((warp * 16 + 4 * vv + t) * 8 + (g ^ (2 * t) ^ (2 * (warp & 3)))) * 16, o[vv].x, o[vv].y, o[vv].z, o[vv].w);
      bar_sync(NB_CONS, 256);
      uint32_t ad[2], res[2][2][4];
#pragma unroll
      for (int ci = 0; ci < 2; ci++) {
        const int cc = 2 * warp + ci;
        ad[ci] = e2 + ((t * 16 + cc) * 8 + (g ^ (2 * (cc & 3)) ^ (2 * t))) * 16;
        lds_frag(q[2 * ci], q[2 * ci + 1], ad[ci], ad[ci] + 8192);
      }
#pragma unroll
      for (int ci = 0; ci < 2; ci++)
#pragma unroll
        for (int p = 0; p < 2; p++) {
          uint32_t y[2][2];
#pragma unroll
          for (int vv = 0; vv < 2; vv++) {
            float d[4];
            mma_az(d, q[2 * ci + p], word(f8, 2 * vv), word(f8, 2 * vv + 1));
#pragma unroll
            for (int rr = 0; rr < 2; rr++) {
              const float fr = wfr[ci * 8 + vv * 4 + 2 * p + rr], fi = wfi[ci * 8 + vv * 4 + 2 * p + rr];
              y[vv][rr] = pack2(d[2 * rr] * fr - d[2 * rr + 1] * fi, d[2 * rr] * fi + d[2 * rr + 1] * fr);
            }
          }
#pragma unroll
          for (int vv = 0; vv < 2; vv++) {
            float d[4];
            mma16816_z(d, y[0][0], y[0][1], y[1][0], y[1][1], word(g8, 2 * vv), word(g8, 2 * vv + 1));
            res[ci][vv][2 * p] = pack2(d[0], d[1]);
            res[ci][vv][2 * p + 1] = pack2(d[2], d[3]);
          }
        }
#pragma unroll
      for (int i = 0; i < 4; i++)
        sts4(ad[i >> 1] + (i & 1) * 8192, res[i >> 1][i & 1][0], res[i >> 1][i & 1][1], res[i >> 1][i & 1][2], res[i >> 1][i & 1][3]);
      bar_sync(NB_CONS, 256);
      const uint32_t eb = e2 + ((warp * 16 + t) * 8 + (g ^ (2 * t) ^ (2 * (warp & 3)))) * 16;
      lds_frag(q[0], q[1], eb, eb + 512);
      lds_frag(q[2], q[3], eb + 1024, eb + 1536);
      cdft16(q, g2, o);
#pragma unroll
      for (int vv = 0; vv < 4; vv++) {
        o[vv].y &= ~1u;
        o[vv].z = (o[vv].z & ~1u) | tag;
        st_tag(zp + vv * 256, o[vv], tag);
      }
    }
    {
      const uint4* const zp = &scr->Z1[((t * 8 + warp) * 128 + c) * 8 + g];
      const uint32_t tst = clock32();
      uint4 gb[4], ga[4], gc[4], tw[4];
      uint2 xr[2][4];
      uint2* lnp[2];
#pragma unroll
      for (int r = 0; r < 2; r++) {
        const int row = 16 * f + 2 * warp + r;
        lnp[r] = reinterpret_cast<uint2*>(&scr->LN[(rb * 8 + (g >> 2)) * 1024 + row * 8 + ((2 * (g & 3) + (t >> 1)) ^ (row & 7))]) + (t & 1);
        asm volatile("" : "+l"(lnp[r]));
      }
#pragma unroll
      for (int i = 0; i < 4; i++) {
        gc[i] = lds4(sbase + SM_FC + 2048 + i * 512 + lane * 16);
        gb[i] = lds4(TOFF(gb) + i * 512);
        ga[i] = lds4(TOFF(ga) + i * 512);
        tw[i] = lds4(TOFF(tw3) + i * 512);
        const int ch = 2 * (g + 8 * i) + (t >> 1);
#pragma unroll
        for (int r = 0; r < 2; r++) xr[r][i] = lds2(sbase + SM_X + (2 * warp + r) * 1024 + ((ch ^ ((ch >> 3) & 1)) * 16) + (t & 1) * 8);
      }
      spin_until(tst + POLL_DELAY2);
      ld_tag4_issue<32768>(q, zp);
      ld_tag4_finish<32768, true>(q, zp, tag);
      if (lane == 0) mbar_arrive(BAR(sig, 0));
      reg_frag(q, ones);
      cdft16(q, gc, o);
#pragma unroll
      for (int vv = 0; vv < 4; vv++)
        sts4(sbase + SM_E + (((4 * vv + t) * 8 + warp) * 8 + (g ^ (warp & 6) ^ (2 * t))) * 16, o[vv].x, o[vv].y, o[vv].z, o[vv].w);
      bar_sync(NB_CONS, 256);
      uint32_t hv[2][8];
      const float mk = t == 0 ? 0.f : 1.f;
#pragma unroll
      for (int r = 0; r < 2; r++) {
        const int j = 2 * warp + r;
        uint4 u[2];
#pragma unroll
        for (int h = 0; h < 2; h++) u[h] = lds4(sbase + SM_E + ((j * 8 + 2 * t + h) * 8 + (g ^ (2 * t) ^ (2 * (j & 3)))) * 16);
        const uint32_t bp[4][2] = {{u[0].x, u[1].x & ones}, {u[0].y & ones, u[1].y}, {u[0].z, u[1].z & ones}, {u[0].w & ones, u[1].w}};
        float y[2][2][4];
#pragma unroll
        for (int i = 0; i < 2; i++) {
          float lo[4], hi[4], e[4];
          mma_az(lo, gb[2 * i], bp[0][0], bp[0][1]);
          mma_az(hi, gb[2 * i + 1], bp[2][0], bp[2][1]);
          mma_az(e, gb[2 * i], bp[1][0], bp[1][1]);
          mma_a(e, gb[2 * i + 1], bp[3][0], bp[3][1]);
          const uint4 &ka = tw[2 * i], &kb = tw[2 * i + 1];
          const float tr0 = fmaf(hi[0], mk, lo[0]), ti0 = fmaf(hi[2], mk, lo[2]);
          const float tr1 = lo[1] + hi[1], ti1 = lo[3] + hi[3];
          const float vr0 = tr0 * u2f(ka.x) - ti0 * u2f(ka.y), vi0 = tr0 * u2f(ka.y) + ti0 * u2f(ka.x);
          const float vr1 = tr1 * u2f(ka.z) - ti1 * u2f(ka.w), vi1 = tr1 * u2f(ka.w) + ti1 * u2f(ka.z);
          const uint32_t b0 = pack2(t == 0 ? hi[0] : vr0, vr1), b1 = pack2(t == 0 ? vr0 : vi0, vi1);
          const uint32_t b2 = pack2(e[0] * u2f(kb.x) - e[2] * u2f(kb.y), e[1] * u2f(kb.z) - e[3] * u2f(kb.w));
          const uint32_t b3 = pack2(e[0] * u2f(kb.y) + e[2] * u2f(kb.x), e[1] * u2f(kb.w) + e[3] * u2f(kb.z));
#pragma unroll
          for (int mt = 0; mt < 2; mt++) {
            mma_az(y[mt][i], ga[2 * mt], b0, b1);
            mma_a(y[mt][i], ga[2 * mt + 1], b2, b3);
          }
        }
#pragma unroll
        for (int i = 0; i < 4; i++) {
          hv[r][2 * i] = hadd2_bf16(xr[r][i].x, pack2(y[i >> 1][0][2 * (i & 1)], y[i >> 1][0][2 * (i & 1) + 1]));
          hv[r][2 * i + 1] = hadd2_bf16(xr[r][i].y, pack2(y[i >> 1][1][2 * (i & 1)], y[i >> 1][1][2 * (i & 1) + 1]));
        }
      }
      float mean[2];
      uint32_t mb[2];
#pragma unroll
      for (int r = 0; r < 2; r++) {
        mean[r] = sum_groups(quad_sum(hv[r])) * (1.f / 512.f);
        mb[r] = pack2(mean[r], mean[r]);
      }
#pragma unroll
      for (int i = 0; i < 4; i++)
#pragma unroll
        for (int r = 0; r < 2; r++) {
          hv[r][2 * i] = hsub2_bf16(hv[r][2 * i], mb[r]);
          hv[r][2 * i + 1] = hsub2_bf16(hv[r][2 * i + 1], mb[r]);
          st_tag8(lnp[r] + i * 4096, hv[r][2 * i], hv[r][2 * i + 1], i == 0 ? tag : (hv[r][2 * i] & 1u));
        }
      bar_arrive(NB_LN, 288);
      const uint32_t ones2 = ~(lds2(BAR(epoch, 0)).x >> 31);
      float rstd[2];
#pragma unroll
      for (int r = 0; r < 2; r++) {
        hv[r][0] &= ones2;
        rstd[r] = row_rstd(hv[r], mean[r] - bf_lo(mb[r]));
      }
      if (lane == 0)
        st_tag(&scr->ST[rb * 64 + 8 * f + warp], make_uint4(mb[0] << 16, __float_as_uint(rstd[0]), mb[1] << 16, __float_as_uint(rstd[1])), tag);
    }
    const int wgi = warp >> 2, wq = warp & 3;
    const int wr = wgi ^ (f >> 2) ^ 1, rt = 4 * wr + wq;
    uint4* const pbase = &scr->P[rb * 28 * 1024 + rt * 128 + lane];
    const uint32_t a_lo0 = desc_lo(sbase + wr * 8192, 16);
    const uint32_t ebar = lane == 0 ? BAR(empty1, 0) : RBAR(empty1, 0);
    float r0, r1;
    uint4 px[8], py[6];
    const int rh = wgi ^ kh ^ 1;
    const uint32_t fpb = BAR(fullP, 16 * rh);
    const uint4* const psrc = &scr->P[(rb2 * 28 + 14 * kh) * 1024 + (4 * rh + wq) * 128 + lane];
    const uint32_t pa0 = sbase + (4 * rh + wq) * 2048;
    uint4 pf[3][4], ha[4][4];
    uint32_t rdy = 0, got0;
    {
      float acc[128];
#pragma unroll
      for (int i = 0; i < 128; i++) acc[i] = 0.f;
      const uint32_t b_lo0 = desc_lo(sbase + 8 * SLOT, 4096);
      const uint32_t t3 = clock32();
      if (WARM) {
        wg_fence();
#pragma unroll
        for (int i = 0; i < WARM; i++) wgmma_n256(acc, desc64(a_lo0 + 6 * 1024, HI128), desc64(b_lo0, HI128));
        wg_commit();
      }
      const uint4* const ap = &scr->LN[rb * 8 * 1024 + rt * 128 + lane];
      uint4 av[NLL][4];
      spin_until(t3 + POLL_DELAY3);
#pragma unroll
      for (int kb = 0; kb < NLL; kb++) ld_tag4_issue<32>(av[kb], ap + kb * 1024);
      const uint32_t lma = sbase + (16 * rt + (lane & 15)) * 128, stg = sbase + SM_X + warp * 2048;
      auto load_a = [&](int kb) {
#pragma unroll
        for (int ks = 0; ks < 4; ks++)
          asm volatile("ldmatrix.sync.aligned.m8n8.x4.shared.b16 {%0,%1,%2,%3}, [%4];"
                       : "=r"(ha[kb][ks].x), "=r"(ha[kb][ks].y), "=r"(ha[kb][ks].z), "=r"(ha[kb][ks].w)
                       : "r"((kb < NLL ? stg + (lane & 15) * 128 : lma + kb * SLOT) + (((2 * ks + (lane >> 4)) ^ (lane & 7)) * 16)) : "memory");
      };
      auto stash_a = [&](int kb) {
        ld_tag4_finish<32, true>(av[kb], ap + kb * 1024, tag);
#pragma unroll
        for (int i = 0; i < 4; i++) sts4(stg + (lane + 32 * i) * 16, av[kb][i].x, av[kb][i].y, av[kb][i].z, av[kb][i].w);
        __syncwarp();
      };
      stash_a(0);
      load_a(0);
#pragma unroll
      for (int n = 0; n < 8; n++) {
        const int kb = n >> 1, hh = n & 1;
        if (hh == 1 && kb + 1 < NLL) stash_a(kb + 1);
        if (!rdy) {
          if (hh == 1 && kb + 1 >= NLL && kb < 3) mbar_wait(BAR(fullA, kb + 1));
          mbar_wait(BAR(full1, n));
        }
        const uint32_t bl = b_lo0 + ((n + 2) % 6) * 1024;
        wg_fence();
        if (hh == 1 && kb < 3) load_a(kb + 1);
        rdy = mbar_test(BAR(full1, n + 1));
        if (hh == 0 && kb + 1 >= NLL && kb < 3) rdy &= mbar_test(BAR(fullA, kb + 1));
        const uint4 &a0 = ha[kb][2 * hh], &a1 = ha[kb][2 * hh + 1];
        wgmma_rs_n256(acc, a0.x, a0.y, a0.z, a0.w, desc64(bl, HI128), n != 0 ? 1 : ~ones);
        wgmma_rs_n256(acc, a1.x, a1.y, a1.z, a1.w, desc64(bl + 128, HI128));
        wg_commit();
        if (hh == 1 && lane < 2) mbar_arrive_remote(ebar + (uint32_t)(offsetof(Bars, freeA) - offsetof(Bars, empty1)) + 8 * kb);
        wg_wait<1>();
        if (n != 0 && lane < 2) mbar_arrive_remote(ebar + 8 * (n - 1));
      }
      uint32_t slot = 4;
#pragma unroll 1
      for (int kb = 4; kb < 8; kb++) {
        mbar_wait(BAR(fullA, kb));
#pragma unroll
        for (int hh = 0; hh < 2; hh++) {
          if (hh == ((16 - LAGX) & 1) && kb == ((16 - LAGX) >> 1) && wgi == 1) bar_sync(NB_LAG, 256);
          mbar_wait(BAR(full1, 2 * kb + hh));
          const uint32_t al = a_lo0 + kb * 1024 + hh * 4, bl = b_lo0 + slot * 1024;
          wg_fence();
          wgmma_n256(acc, desc64(al, HI128), desc64(bl, HI128));
          wgmma_n256(acc, desc64(al + 2, HI128), desc64(bl + 128, HI128));
          wg_commit();
          if (hh == 1 && kb == 7 && wgi == 0) bar_arrive(NB_LAG, 256);
          wg_wait<1>();
          if (lane < 2) mbar_arrive_remote(ebar + 8 * (2 * kb + hh - 1));
          if (++slot == 6) slot = 0;
        }
      }
      mbar_wait(BAR(sbar, 0));
      r0 = __uint_as_float(lds2(sstat + (16 * rt + g) * 8).y);
      r1 = __uint_as_float(lds2(sstat + (16 * rt + g + 8) * 8).y);
      wg_wait<0>();
      if (lane < 2) mbar_arrive_remote(ebar + 8 * 15);
      make_p<8, false>(acc, r0, r1, px, pbase, 0, tag);
    }
    {
      float acc[96];
#pragma unroll
      for (int i = 0; i < 96; i++) acc[i] = 0.f;
      const uint32_t b_lo0 = desc_lo(sbase, 2048);
      uint4* const pdst = pbase + ((7 * f + 3 * (f & 1)) >> 1) * 1024;
      auto stage_y = [&](int k) {
        if (k < 4) mbar_wait_bounded(BAR(full1, 16 + k));
        else mbar_wait(BAR(full1, 16 + k));
        const uint32_t al = a_lo0 + (4 + (k >> 1)) * 1024 + (k & 1) * 4, bl = b_lo0 + (k < 5 ? k * 768 : 8192 + (k - 5) * 768);
        wg_fence();
        wgmma_n192(acc, desc64(al, HI128), desc64(bl, HI64));
        wgmma_n192(acc, desc64(al + 2, HI128), desc64(bl + 64, HI64));
        wg_commit();
      };
#pragma unroll
      for (int k = 0; k < 4; k++) {
        stage_y(k);
        st_tag(pdst + (k >> 1) * 1024 + (k & 1) * 64, px[2 * k], tag);
        st_tag(pdst + (k >> 1) * 1024 + (k & 1) * 64 + 32, px[2 * k + 1], tag);
        if (k == 3 && lane == 0) red_relaxed(&scr->cnt[(C_PX + rb) * 32 + (f >> 2)]);
        wg_wait<1>();
        if (k != 0 && lane < 2) mbar_arrive_remote(ebar + 8 * (15 + k));
      }
#pragma unroll 1
      for (int k = 4; k < 8; k++) {
        stage_y(k);
        wg_wait<1>();
        if (k != 0 && lane < 2) mbar_arrive_remote(ebar + 8 * (15 + k));
      }
      rdy = 0;
#pragma unroll
      for (int k = 8; k < 16; k++) {
        if (k == 16 - LAGY && wgi == 1) bar_sync(NB_LAG, 256);
        if (!rdy) mbar_wait(BAR(full1, 16 + k));
        const uint32_t bl = b_lo0 + 8192 + ((k - 5) & 7) * 768;
        const uint4 &a0 = ha[(k - 8) >> 1][2 * (k & 1)], &a1 = ha[(k - 8) >> 1][2 * (k & 1) + 1];
        wg_fence();
        if (k < 15) rdy = mbar_test(BAR(full1, 17 + k));
        wgmma_rs_n192(acc, a0.x, a0.y, a0.z, a0.w, desc64(bl, HI64));
        wgmma_rs_n192(acc, a1.x, a1.y, a1.z, a1.w, desc64(bl + 64, HI64));
        wg_commit();
        if (k == 15 && wgi == 0) bar_arrive(NB_LAG, 256);
        wg_wait<1>();
        if (lane < 2) mbar_arrive_remote(ebar + 8 * (15 + k));
      }
      got0 = __all_sync(0xffffffffu, mbar_test(fpb));
      if (got0) {
#pragma unroll
        for (int kk = 0; kk < 4; kk++) pf[0][kk] = lds4(pa0 + 3 * SLOT + kk * 512 + lane * 16);
      }
      wg_wait<0>();
      if (lane < 2) mbar_arrive_remote(ebar + 8 * 31);
      const int ks0 = 14 * f + ((f & 1) ? 0 : 8);
      auto reread = [&]() {
        asm volatile("ld.volatile.shared.f32 %0, [%2+4]; ld.volatile.shared.f32 %1, [%2+68];" : "=f"(r0), "=f"(r1) : "r"(sstat + (16 * rt + g) * 8) : "memory");
      };
      make_p<6, true, 0, 2>(acc, r0, r1, py, pbase, ks0, tag);
      reread();
      make_p<6, true, 2, 4>(acc, r0, r1, py, pbase, ks0, tag);
      if (lane == 0) red_relaxed(&scr->cnt[(C_PY + rb) * 32 + 4 * wgi + (f >> 1)]);
      reread();
      rdy = mbar_test(BAR(full2, 0)) & mbar_test(fpb + 8);
      make_p<6, true, 4, 6>(acc, r0, r1, py, pbase, ks0, tag);
    }
    {
      float acc[64];
      const uint32_t b2_lo0 = desc_lo(sbase, 8192);
      const uint32_t pbar = rh == rk ? BAR(emptyP, 0) : RBAR(emptyP, 0);
      if (!got0) {
        mbar_wait(fpb);
#pragma unroll
        for (int kk = 0; kk < 4; kk++) pf[0][kk] = lds4(pa0 + 3 * SLOT + kk * 512 + lane * 16);
      }
#pragma unroll
      for (int s = 0; s < 14; s++) {
        uint4 (&a)[4] = pf[s % 3];
        ld_tag4_finish<32>(a, psrc + (int)((KORDER >> (4 * s)) & 15) * 1024, tag);
        if (s < 9 && lane == 0) mbar_arrive_remote(pbar + 8 * s);
        if (s >= 2) {
          wg_wait<1>();
          if (s <= 7 && lane == 0) mbar_arrive(BAR(empty2, s - 2));
        }
        if (!rdy) {
          if (s < 13) mbar_wait(fpb + 8 * (s + 1));
          mbar_wait(BAR(full2, s));
        }
        if (s == 14 - LAG2 && wgi == 1) bar_sync(NB_LAG, 256);
        const uint32_t bl = b2_lo0 + (uint32_t)((BSLOT >> (4 * s)) & 15) * 1024;
        wg_fence();
        if (s < 13) {
#pragma unroll
          for (int kk = 0; kk < 4; kk++)
            pf[(s + 1) % 3][kk] = lds4(pa0 + (uint32_t)((PSLOT >> (4 * (s + 1))) & 15) * SLOT + kk * 512 + lane * 16);
          rdy = mbar_test(BAR(full2, s + 1));
          if (s < 12) rdy &= mbar_test(fpb + 8 * (s + 2));
        }
        if (s == 0) wgmma_rs_n128(acc, a[0].x, a[0].y, a[0].z, a[0].w, desc64(bl, HI128), 0);
        else wgmma_rs_n128(acc, a[0].x, a[0].y, a[0].z, a[0].w, desc64(bl, HI128));
#pragma unroll
        for (int kk = 1; kk < 4; kk++) wgmma_rs_n128(acc, a[kk].x, a[kk].y, a[kk].z, a[kk].w, desc64(bl + kk * 128, HI128));
        wg_commit();
      }
      if (wgi == 0) {
        bar_arrive(NB_LAG, 256);
        uint4* const dst = &scr->Z1[(tid >> 3) * 1024 + (c ^ 4) * 8 + (tid & 7)];
        wg_wait<0>();
#pragma unroll
        for (int i = 0; i < 8; i++)
          st_tag(dst + i * 16384, make_uint4(pack2(acc[8 * i], acc[8 * i + 1]), pack2(acc[8 * i + 2], acc[8 * i + 3]) | 1u,
                                           pack2(acc[8 * i + 4], acc[8 * i + 5]), pack2(acc[8 * i + 6], acc[8 * i + 7])), tag);
      } else {
        uint4 pv[2][4];
        const uint4* const xsrc = &scr->Z1[((tid & 127) >> 3) * 1024 + c * 8 + (tid & 7)];
        ld_tag4_issue<16384>(pv[0], xsrc);
        ld_tag4_issue<16384>(pv[1], xsrc + 65536);
        uint32_t w[32];
        {
          const uint32_t m0 = __byte_perm(lds2(sstat + 1024 + (16 * wq + g) * 8).x, 0, 0x3232);
          const uint32_t m1 = __byte_perm(lds2(sstat + 1024 + (16 * wq + g + 8) * 8).x, 0, 0x3232);
          const uint32_t hb = sbase + 13 * SLOT + (16 * wq + (lane & 15)) * 128;
          const uint32_t mk = ((t & 1) == 0 && nq == 0) ? ~1u : ~0u;
          mbar_wait(BAR(hbar, 0));
#pragma unroll
          for (int i = 0; i < 8; i++) {
            asm volatile("ldmatrix.sync.aligned.m8n8.x4.shared.b16 {%0,%1,%2,%3}, [%4];"
                         : "=r"(w[4 * i]), "=r"(w[4 * i + 1]), "=r"(w[4 * i + 2]), "=r"(w[4 * i + 3])
                         : "r"(hb + (i >> 2) * 8192 + (((2 * (i & 3) + (lane >> 4)) ^ (lane & 7)) * 16)) : "memory");
#pragma unroll
            for (int e = 0; e < 4; e++) w[4 * i + e] = hadd2_bf16(w[4 * i + e] & mk, (e & 1) ? m1 : m0);
          }
        }
        wg_wait<0>();
#pragma unroll
        for (int i = 0; i < 32; i++) w[i] = hadd2_bf16(w[i], pack2(acc[2 * i], acc[2 * i + 1]));
#pragma unroll 1
        while (!__all_sync(0xffffffffu, pv[0][0].y & pv[0][1].y & pv[0][2].y & pv[0][3].y & pv[1][0].y & pv[1][1].y & pv[1][2].y & pv[1][3].y & 1u)) {
          ld_tag4_issue<16384>(pv[0], xsrc);
          ld_tag4_issue<16384>(pv[1], xsrc + 65536);
        }
#pragma unroll
        for (int i = 0; i < 8; i++) {
          const uint4& p = pv[i >> 2][i & 3];
          asm volatile("stmatrix.sync.aligned.m8n8.x4.shared.b16 [%0], {%1,%2,%3,%4};"
                       ::"r"(pa0 + (11 + ((lane >> 3) & 1)) * SLOT + (lane & 7) * 256 + (((2 * i + (lane >> 4)) ^ (lane & 7)) * 16)),
                         "r"(hadd2_bf16(w[4 * i], p.x & ~1u)), "r"(hadd2_bf16(w[4 * i + 1], p.y & ~1u)), "r"(hadd2_bf16(w[4 * i + 2], p.z)),
                         "r"(hadd2_bf16(w[4 * i + 3], p.w)) : "memory");
        }
        __syncwarp();
        uint4* const dst = reinterpret_cast<uint4*>(out) + (16 * (c >> 4) + 2 * (4 * rh + wq) + (rb2 & 1) + 128 * (lane >> 4)) * 64 + nq * 16 + (lane & 15);
#pragma unroll
        for (int i = 0; i < 8; i++) {
          const int r = 2 * (i & 3) + (lane >> 4);
          dst[i * 256 * 64] = lds4(pa0 + (11 + (i >> 2)) * SLOT + r * 256 + (((lane & 15) ^ r) * 16));
        }
      }
      if (lane == 0) mbar_arrive(BAR(done, 0));
    }
  }
#undef BAR
#undef TOFF
#undef RBAR
}

typedef CUresult (*EncodeFn)(CUtensorMap*, CUtensorMapDataType, cuuint32_t, void*, const cuuint64_t*, const cuuint64_t*,
                             const cuuint32_t*, const cuuint32_t*, CUtensorMapInterleave, CUtensorMapSwizzle,
                             CUtensorMapL2promotion, CUtensorMapFloatOOBfill);

}

extern "C" void kernel_launch(void* const* d_in, const int* in_sizes, int n_in, void* d_out, int out_size) {
  (void)in_sizes; (void)n_in; (void)out_size;
  static EncodeFn encode = nullptr;
  static void *tab = nullptr, *scr = nullptr;
  if (!encode) {
    void* fn = nullptr;
    cudaDriverEntryPointQueryResult qr;
    cudaGetDriverEntryPoint("cuTensorMapEncodeTiled", &fn, cudaEnableDefault, &qr);
    encode = (EncodeFn)fn;
    cudaGetSymbolAddress(&tab, g_tab);
    cudaGetSymbolAddress(&scr, g_scr);
    cudaFuncSetAttribute(fused_kernel, cudaFuncAttributeMaxDynamicSharedMemorySize, SMEM_BYTES);
  }
  CUtensorMap tmGX, tmUX, tmGY, tmUY, tmD, tmWR, tmWI;
  const cuuint32_t es[5] = {1, 1, 1, 1, 1};
  auto enc = [&](CUtensorMap* m, void* p, int rank, const cuuint64_t* gd, const cuuint64_t* gs, const cuuint32_t* bd,
                 CUtensorMapSwizzle sw, CUtensorMapL2promotion pr) {
    encode(m, CU_TENSOR_MAP_DATA_TYPE_BFLOAT16, rank, p, gd, gs, bd, es, CU_TENSOR_MAP_INTERLEAVE_NONE, sw, pr,
           CU_TENSOR_MAP_FLOAT_OOB_FILL_NONE);
  };
  {
    const cuuint64_t gd[3] = {64, 512, 28}, gs[2] = {3584, 128};
    const cuuint32_t bd[3] = {64, 32, 2};
    enc(&tmGX, d_in[4], 3, gd, gs, bd, CU_TENSOR_MAP_SWIZZLE_128B, CU_TENSOR_MAP_L2_PROMOTION_L2_256B);
    enc(&tmUX, d_in[5], 3, gd, gs, bd, CU_TENSOR_MAP_SWIZZLE_128B, CU_TENSOR_MAP_L2_PROMOTION_L2_256B);
  }
  {
    const cuuint64_t gd[3] = {32, 512, 56}, gs[2] = {3584, 64};
    const cuuint32_t bd[3] = {32, 32, 3};
    enc(&tmGY, d_in[4], 3, gd, gs, bd, CU_TENSOR_MAP_SWIZZLE_64B, CU_TENSOR_MAP_L2_PROMOTION_L2_128B);
    enc(&tmUY, d_in[5], 3, gd, gs, bd, CU_TENSOR_MAP_SWIZZLE_64B, CU_TENSOR_MAP_L2_PROMOTION_L2_128B);
  }
  {
    const cuuint64_t gd[3] = {64, 1792, 8}, gs[2] = {1024, 128};
    const cuuint32_t bd[3] = {64, 64, 2};
    enc(&tmD, d_in[6], 3, gd, gs, bd, CU_TENSOR_MAP_SWIZZLE_128B, CU_TENSOR_MAP_L2_PROMOTION_L2_256B);
  }
  {
    const cuuint64_t gd[3] = {4112, 8, 16}, gs[2] = {16 * 8224, 8224};
    const cuuint32_t bd[3] = {40, 8, 16};
    enc(&tmWR, d_in[1], 3, gd, gs, bd, CU_TENSOR_MAP_SWIZZLE_NONE, CU_TENSOR_MAP_L2_PROMOTION_NONE);
    enc(&tmWI, d_in[2], 3, gd, gs, bd, CU_TENSOR_MAP_SWIZZLE_NONE, CU_TENSOR_MAP_L2_PROMOTION_NONE);
  }
  fused_kernel<<<NCTA, NTHREADS, SMEM_BYTES>>>((const __nv_bfloat16*)d_in[0], (const Tables*)tab, (Scratch*)scr,
                                               (__nv_bfloat16*)d_out, (const char*)d_in[4], (const char*)d_in[5],
                                               (const char*)d_in[6], tmWR, tmWI, tmGX, tmUX, tmGY, tmUY, tmD);
}
```

```cpp
#include <cuda_runtime.h>
#include <cuda_bf16.h>
#include <cuda.h>
#include <stdint.h>

namespace {

constexpr int NCTA = 128;
constexpr int NTHREADS = 384;
constexpr int SLOT = 16384;
constexpr int SMEM_BYTES = 14 * SLOT + 3072;
constexpr int SPIN_LIMIT = 1 << 22;

struct Scratch {
  uint4 Z1[128 * 1024];
  uint4 LN[16 * 8 * 1024];
  uint4 P[16 * 28 * 1024];
  uint4 ST[1024];
  unsigned cnt[64 * 32];
};
__device__ __align__(1024) Scratch g_scr;

constexpr double ccos(int i, int n) {
  i &= n - 1;
  if (i > n / 2) i = n - i;
  if (4 * i == n) return 0.0;
  const bool neg = 4 * i > n;
  if (neg) i = n / 2 - i;
  const double a = 6.283185307179586476925 * i / n, a2 = a * a;
  double term = 1.0, sum = 1.0;
  for (int k = 1; k < 14; k++) { term *= -a2 / ((2 * k - 1) * (2 * k)); sum += term; }
  return neg ? -sum : sum;
}
constexpr double csin(int i, int n) { return ccos(i - n / 4, n); }
constexpr unsigned fbits(double v, int mant) {
  if (v == 0.0) return 0;
  const unsigned sg = v < 0 ? 1u : 0u;
  if (v < 0) v = -v;
  int e = 127;
  while (v < 1.0) { v *= 2.0; e--; }
  const unsigned m = (unsigned)((v - 1.0) * (double)(1u << mant) + 0.5);
  return (sg << (8 + mant)) + ((unsigned)e << mant) + m;
}
constexpr unsigned pkb(double lo, double hi) { return fbits(lo, 7) | (fbits(hi, 7) << 16); }
constexpr double fa_elem(int mt, int r, int n1) {
  const int k1 = 8 * mt + (r & 7);
  return r < 8 ? ccos(k1 * n1, 32) : k1 == 0 ? ccos(16 * n1, 32) : -csin(k1 * n1, 32);
}
constexpr unsigned cfrag_c(int idx, int n, int ri, double s = 1.0) {
  return ri ? pkb(-s * csin(idx, n), s * ccos(idx, n)) : pkb(s * ccos(idx, n), s * csin(idx, n));
}
struct Tables {
  unsigned fa[4][32][4];
  unsigned fb[4][32][4];
  unsigned tw1[6][32][4];
  unsigned f2[8][4][32][4];
  unsigned g2[8][4][32][4];
  unsigned gb[4][32][4];
  unsigned ga[4][32][4];
  unsigned tw3[4][32][4];
  unsigned f8[32][4], g8[32][4];
};
constexpr int T1_BYTES = 7168, T2_BYTES = 39936;
static_assert(sizeof(Tables) == T1_BYTES + T2_BYTES, "table size");
constexpr Tables make_tables() {
  Tables T = {};
  for (int l = 0; l < 32; l++) {
    const int g = l >> 2, t = l & 3;
    for (int a = 0; a < 2; a++)
      for (int b = 0; b < 2; b++) {
        for (int r = 0; r < 4; r++) {
          const int row = g + 8 * (r & 1), col = 2 * t + 8 * (r >> 1);
          T.fa[2 * a + b][l][r] = pkb(fa_elem(a, row, 16 * b + col), fa_elem(a, row, 16 * b + col + 1));
          T.ga[2 * a + b][l][r] = pkb(fa_elem(b, col, 16 * a + row), fa_elem(b, col + 1, 16 * a + row));
        }
        const double sg = b ? -1.0 : 1.0;
        for (int h = 0; h < 2; h++) {
          const int ri = g & 1, m = 2 * (g >> 1) + h, k2 = b ? 15 - m : m;
          const int pa = (8 * a + 2 * t) * k2, pb = (8 * a + 2 * t + 1) * k2;
          T.fb[2 * a + b][l][2 * h] = ri == 0 ? pkb(ccos(pa, 16), ccos(pb, 16)) : pkb(-sg * csin(pa, 16), -sg * csin(pb, 16));
          T.fb[2 * a + b][l][2 * h + 1] = ri == 0 ? pkb(csin(pa, 16), csin(pb, 16)) : pkb(sg * ccos(pa, 16), sg * ccos(pb, 16));
        }
        const int n2 = 4 * (g >> 1) + 2 * a + (g & 1);
        for (int h = 0; h < 2; h++) {
          const int p = n2 * (b ? 15 - 2 * t - h : 2 * t + h);
          T.gb[2 * a + b][l][2 * h] = pkb(ccos(p, 16), -sg * csin(p, 16));
          T.gb[2 * a + b][l][2 * h + 1] = pkb(csin(p, 16), sg * ccos(p, 16));
          const int k1 = 8 * b + 2 * t + h, q = n2 * (k1 == 0 ? 16 : k1);
          T.tw3[2 * a + b][l][2 * h] = fbits(ccos(q, 512), 23);
          T.tw3[2 * a + b][l][2 * h + 1] = fbits(csin(q, 512), 23);
        }
        const int p = (8 * a + 2 * t + b) * (g == 0 ? 16 : g);
        T.tw1[2 * a + b][l][0] = fbits(g == 0 ? 0.0 : ccos(p, 512), 23);
        T.tw1[2 * a + b][l][1] = fbits(g == 0 ? ccos(p, 512) : csin(p, 512), 23);
        T.tw1[2 * a + b][l][2] = fbits(g == 0 ? 0.0 : -csin(p, 512), 23);
        T.tw1[2 * a + b][l][3] = fbits(g == 0 ? -csin(p, 512) : ccos(p, 512), 23);
        T.tw1[4 + a][l][2 * b] = fbits(ccos((8 * a + 2 * t + b) * (g + 8), 512), 23);
        T.tw1[4 + a][l][2 * b + 1] = fbits(csin((8 * a + 2 * t + b) * (g + 8), 512), 23);
      }
    for (int i = 0; i < 4; i++) {
      const int p8 = (t + 4 * (i & 1)) * (4 * (i >> 1) + (g >> 1));
      T.f8[l][i] = cfrag_c(p8, 8, g & 1);
      T.g8[l][i] = cfrag_c(-p8, 8, g & 1, 1.0 / (1 << 19));
    }
    for (int w = 0; w < 8; w++)
      for (int i = 0; i < 16; i++) {
        const int kidx = t + 4 * (i & 1) + 8 * (i >> 3), nidx = 4 * ((i >> 1) & 3) + (g >> 1);
        T.f2[w][i >> 2][l][i & 3] = cfrag_c((8 * kidx + w) * nidx, 128, g & 1);
        T.g2[w][i >> 2][l][i & 3] = cfrag_c(-(8 * nidx + w) * kidx, 128, g & 1);
      }
  }
  return T;
}
__device__ const __align__(128) Tables g_tab = make_tables();

__device__ __forceinline__ void die() { asm volatile("st.global.u32 [%0], %1;" ::"l"(0ull), "r"(0) : "memory"); }
__device__ __forceinline__ uint32_t s2u(const void* p) { return (uint32_t)__cvta_generic_to_shared(p); }
__device__ __forceinline__ void mbar_init(uint32_t b, int c) { asm volatile("mbarrier.init.shared::cta.b64 [%0], %1;" ::"r"(b), "r"(c)); }
__device__ __forceinline__ void mbar_expect(uint32_t b, int bytes) {
  asm volatile("mbarrier.arrive.expect_tx.shared::cta.b64 _, [%0], %1;" ::"r"(b), "r"(bytes) : "memory");
}
__device__ __forceinline__ void mbar_arrive(uint32_t b) { asm volatile("mbarrier.arrive.shared::cta.b64 _, [%0];" ::"r"(b) : "memory"); }
__device__ __forceinline__ uint32_t mbar_try(uint32_t b, uint32_t parity) {
  uint32_t ok;
  asm volatile("{.reg .pred p; mbarrier.try_wait.parity.shared::cta.b64 p, [%1], %2; selp.u32 %0,1,0,p;}"
               : "=r"(ok) : "r"(b), "r"(parity) : "memory");
  return ok;
}
__device__ __forceinline__ uint32_t mbar_test(uint32_t b) {
  uint32_t ok;
  asm volatile("{.reg .pred p; mbarrier.test_wait.parity.shared::cta.b64 p, [%1], 0; selp.u32 %0,1,0,p;}" : "=r"(ok) : "r"(b) : "memory");
  return ok;
}
__device__ __forceinline__ void mbar_wait_bounded(uint32_t b) {
  int it = 0;
#pragma unroll 1
  while (!mbar_try(b, 0))
    if (++it > SPIN_LIMIT) { die(); break; }
}
__device__ __forceinline__ void mbar_wait(uint32_t b) {
  asm volatile("{.reg .pred p;\nW_%=: mbarrier.try_wait.parity.shared::cta.b64 p, [%0], 0;\n@!p bra W_%=;}" ::"r"(b) : "memory");
}
__device__ __forceinline__ void bar_sync(int id, int n) { asm volatile("bar.sync %0, %1;" ::"r"(id), "r"(n) : "memory"); }
__device__ __forceinline__ void bar_arrive(int id, int n) { asm volatile("bar.arrive %0, %1;" ::"r"(id), "r"(n) : "memory"); }
__device__ __forceinline__ void red_release(unsigned* p) { asm volatile("red.release.gpu.global.add.u32 [%0], 1;" ::"l"(p) : "memory"); }
__device__ __forceinline__ void red_relaxed(unsigned* p) { asm volatile("red.relaxed.gpu.global.add.u32 [%0], 1;" ::"l"(p) : "memory"); }
__device__ __forceinline__ unsigned ld_acquire(const unsigned* p) {
  unsigned v;
  asm volatile("ld.acquire.gpu.global.u32 %0, [%1];" : "=r"(v) : "l"(p) : "memory");
  return v;
}
__device__ __forceinline__ unsigned ld_relaxed(const unsigned* p) {
  unsigned v;
  asm volatile("ld.relaxed.gpu.global.u32 %0, [%1];" : "=r"(v) : "l"(p) : "memory");
  return v;
}
__device__ __forceinline__ void wait_counter(const unsigned* p, unsigned target) {
#pragma unroll 1
  while ((int)(ld_acquire(p) - target) < 0) {}
}
__device__ __forceinline__ void sts4(uint32_t a, uint32_t x, uint32_t y, uint32_t z, uint32_t w) {
  asm volatile("st.shared.v4.u32 [%0], {%1,%2,%3,%4};" ::"r"(a), "r"(x), "r"(y), "r"(z), "r"(w) : "memory");
}
__device__ __forceinline__ uint4 lds4(uint32_t a) {
  uint4 v;
  asm volatile("ld.shared.v4.u32 {%0,%1,%2,%3}, [%4];" : "=r"(v.x), "=r"(v.y), "=r"(v.z), "=r"(v.w) : "r"(a) : "memory");
  return v;
}
__device__ __forceinline__ uint32_t pack2(float lo, float hi) {
  uint32_t r;
  asm("cvt.rn.bf16x2.f32 %0, %1, %2;" : "=r"(r) : "f"(hi), "f"(lo));
  return r;
}
__device__ __forceinline__ float bf_lo(uint32_t v) { return __uint_as_float(v << 16); }
__device__ __forceinline__ uint32_t hadd2_bf16(uint32_t a, uint32_t b) {
  uint32_t r;
  asm("add.rn.bf16x2 %0, %1, %2;" : "=r"(r) : "r"(a), "r"(b));
  return r;
}
__device__ __forceinline__ void mma16816(float (&d)[4], uint32_t a0, uint32_t a1, uint32_t a2, uint32_t a3, uint32_t b0, uint32_t b1) {
  asm("mma.sync.aligned.m16n8k16.row.col.f32.bf16.bf16.f32 {%0,%1,%2,%3}, {%4,%5,%6,%7}, {%8,%9}, {%0,%1,%2,%3};"
      : "+f"(d[0]), "+f"(d[1]), "+f"(d[2]), "+f"(d[3])
      : "r"(a0), "r"(a1), "r"(a2), "r"(a3), "r"(b0), "r"(b1));
}
__device__ __forceinline__ void mma16816_z(float (&d)[4], uint32_t a0, uint32_t a1, uint32_t a2, uint32_t a3, uint32_t b0, uint32_t b1) {
  asm("{.reg .f32 z; mov.f32 z, 0f00000000;\n"
      "mma.sync.aligned.m16n8k16.row.col.f32.bf16.bf16.f32 {%0,%1,%2,%3}, {%4,%5,%6,%7}, {%8,%9}, {z,z,z,z};}"
      : "=f"(d[0]), "=f"(d[1]), "=f"(d[2]), "=f"(d[3])
      : "r"(a0), "r"(a1), "r"(a2), "r"(a3), "r"(b0), "r"(b1));
}
template <int N>
__device__ __forceinline__ void cs_frac(int idx, float& c, float& s) {
  int i = ((idx + N / 2) & (N - 1)) - N / 2;
  float a = (float)i * (6.283185307179586f / N);
  c = __cosf(a);
  s = __sinf(a);
}
template <int N>
__device__ __forceinline__ uint32_t cfrag(int idx, int ri) {
  float c, s;
  cs_frac<N>(idx, c, s);
  return ri ? pack2(-s, c) : pack2(c, s);
}
__device__ __forceinline__ uint32_t word(const uint4& v, int e) { return e == 0 ? v.x : e == 1 ? v.y : e == 2 ? v.z : v.w; }
__device__ __forceinline__ void cdft16(const uint4 (&A)[4], const uint4 (&F)[4], uint4 (&o)[4]) {
  float acc[2][4][4];
#pragma unroll
  for (int ks = 0; ks < 2; ks++)
#pragma unroll
    for (int p = 0; p < 2; p++)
#pragma unroll
      for (int v = 0; v < 4; v++) {
        const uint4& a = A[2 * ks + p];
        const uint32_t b0 = word(F[ks * 2 + (v >> 1)], (v & 1) * 2), b1 = word(F[ks * 2 + (v >> 1)], (v & 1) * 2 + 1);
        if (ks == 0) mma16816_z(acc[p][v], a.x, a.y, a.z, a.w, b0, b1);
        else mma16816(acc[p][v], a.x, a.y, a.z, a.w, b0, b1);
      }
#pragma unroll
  for (int v = 0; v < 4; v++)
    o[v] = make_uint4(pack2(acc[0][v][0], acc[0][v][1]), pack2(acc[0][v][2], acc[0][v][3]),
                      pack2(acc[1][v][0], acc[1][v][1]), pack2(acc[1][v][2], acc[1][v][3]));
}
__device__ __forceinline__ void lds_frag(uint4& f0, uint4& f1, uint32_t a0, uint32_t a1) {
  asm volatile("ld.volatile.shared.v2.u32 {%0,%1}, [%8]; ld.volatile.shared.v2.u32 {%2,%3}, [%9];\n"
               "ld.volatile.shared.v2.u32 {%4,%5}, [%8+8]; ld.volatile.shared.v2.u32 {%6,%7}, [%9+8];"
               : "=r"(f0.x), "=r"(f0.y), "=r"(f0.z), "=r"(f0.w), "=r"(f1.x), "=r"(f1.y), "=r"(f1.z), "=r"(f1.w) : "r"(a0), "r"(a1) : "memory");
}
__device__ __forceinline__ void reg_frag(uint4 (&q)[4], uint32_t ones) {
#pragma unroll
  for (int ks = 0; ks < 2; ks++) {
    const uint4 a = q[2 * ks], b = q[2 * ks + 1];
    q[2 * ks] = make_uint4(a.x, a.y, b.x & ones, b.y & ones);
    q[2 * ks + 1] = make_uint4(a.z & ones, a.w & ones, b.z, b.w);
  }
}
__device__ __forceinline__ void st_tag(uint4* p, const uint4& v, uint32_t tag) {
  asm volatile("st.relaxed.gpu.global.v4.b32 [%0], {%1,%2,%3,%4};"
               ::"l"(p), "r"((v.x & ~1u) | tag), "r"(v.y), "r"(v.z), "r"(v.w) : "memory");
}
__device__ __forceinline__ void st_tag8(void* p, uint32_t x, uint32_t y, uint32_t tag) {
  asm volatile("st.relaxed.gpu.global.v2.b32 [%0], {%1,%2};" ::"l"(p), "r"((x & ~1u) | tag), "r"(y) : "memory");
}
__device__ __forceinline__ uint4 ld_b128(const uint4* p) {
  uint4 v;
  asm volatile("ld.relaxed.gpu.global.v4.b32 {%0,%1,%2,%3}, [%4];"
               : "=r"(v.x), "=r"(v.y), "=r"(v.z), "=r"(v.w) : "l"(p) : "memory");
  return v;
}
template <int STRIDE>
__device__ __forceinline__ void ld_tag4_issue(uint4 (&q)[4], const uint4* p) {
#pragma unroll
  for (int i = 0; i < 4; i++) q[i] = ld_b128(p + i * STRIDE);
}
__device__ __forceinline__ uint32_t tag_miss(uint32_t a, uint32_t b, uint32_t c, uint32_t d, uint32_t tag) {
  uint32_t r;
  asm("{.reg .b32 u, v; lop3.b32 u, %1, %2, %5, 0x7e; lop3.b32 v, %3, %4, %5, 0x7e; lop3.b32 %0, u, v, 1, 0xa8;}"
      : "=r"(r) : "r"(a), "r"(b), "r"(c), "r"(d), "r"(tag));
  return r;
}
template <int STRIDE, bool HALVES = false>
__device__ __forceinline__ void ld_tag4_finish(uint4 (&q)[4], const uint4* p, uint32_t tag) {
  int it = 0;
#pragma unroll 1
  while (__any_sync(0xffffffffu, tag_miss(q[0].x, q[1].x, q[2].x, q[3].x, tag) | (HALVES ? tag_miss(q[0].z, q[1].z, q[2].z, q[3].z, tag) : 0u))) {
    ld_tag4_issue<STRIDE>(q, p);
    if (++it > SPIN_LIMIT) { die(); break; }
  }
#pragma unroll
  for (int i = 0; i < 4; i++) {
    asm volatile("and.b32 %0, %0, 0xfffffffe;" : "+r"(q[i].x));
    if (HALVES) q[i].z &= ~1u;
  }
}
__device__ __forceinline__ float quad_sum(const uint32_t (&a)[8]) {
  float d[4];
  mma16816_z(d, a[0], a[1], a[2], a[3], 0x3f803f80u, 0x3f803f80u);
  mma16816(d, a[4], a[5], a[6], a[7], 0x3f803f80u, 0x3f803f80u);
  return d[0] + d[2];
}
__device__ __forceinline__ float sum_groups(float v) {
  v += __shfl_xor_sync(0xffffffffu, v, 4);
  v += __shfl_xor_sync(0xffffffffu, v, 8);
  v += __shfl_xor_sync(0xffffffffu, v, 16);
  return v;
}
__device__ __forceinline__ uint32_t hsub2_bf16(uint32_t a, uint32_t b) {
  uint32_t r;
  asm("sub.rn.bf16x2 %0, %1, %2;" : "=r"(r) : "r"(a), "r"(b));
  return r;
}
__device__ __forceinline__ float row_rstd(const uint32_t (&c)[8], float delta) {
  uint32_t s[8];
#pragma unroll
  for (int i = 0; i < 8; i++) asm("mul.rn.bf16x2 %0, %1, %1;" : "=r"(s[i]) : "r"(c[i]));
  return rsqrtf(fmaxf(fmaf(-delta, delta, sum_groups(quad_sum(s)) * (1.f / 512.f)), 0.f) + 1e-5f);
}
__device__ __forceinline__ uint64_t desc64(uint32_t lo, uint32_t hi) {
  uint64_t d;
  asm("mov.b64 %0, {%1, %2};" : "=l"(d) : "r"(lo), "r"(hi));
  return d;
}
constexpr uint32_t desc_hi(uint32_t sbo, uint32_t swz) { return (sbo >> 4) | (swz << 30); }
__device__ __forceinline__ uint32_t desc_lo(uint32_t addr, uint32_t lbo) { return ((addr & 0x3FFFF) >> 4) | ((lbo >> 4) << 16); }
__device__ __forceinline__ void cp_async16(uint32_t dst, const void* src) {
  asm volatile("cp.async.cg.shared.global [%0], [%1], 16;" ::"r"(dst), "l"(src) : "memory");
}
__device__ __forceinline__ uint2 lds2(uint32_t a) {
  uint2 v;
  asm volatile("ld.shared.v2.u32 {%0,%1}, [%2];" : "=r"(v.x), "=r"(v.y) : "r"(a) : "memory");
  return v;
}
__device__ __forceinline__ uint32_t lds_u16(uint32_t a) {
  uint16_t v;
  asm volatile("ld.shared.u16 %0, [%1];" : "=h"(v) : "r"(a) : "memory");
  return v;
}
__device__ __forceinline__ void wg_fence() { asm volatile("wgmma.fence.sync.aligned;" ::: "memory"); }
__device__ __forceinline__ void wg_commit() { asm volatile("wgmma.commit_group.sync.aligned;" ::: "memory"); }
template <int N>
__device__ __forceinline__ void wg_wait() { asm volatile("wgmma.wait_group.sync.aligned %0;" ::"n"(N) : "memory"); }
__device__ __forceinline__ void bulk_load(uint32_t dst, const void* src, int bytes, uint32_t bar) {
  asm volatile("cp.async.bulk.shared::cluster.global.mbarrier::complete_tx::bytes [%0], [%1], %2, [%3];"
               ::"r"(dst), "l"(src), "r"(bytes), "r"(bar) : "memory");
}
__device__ __forceinline__ void bulk_load_mc(uint32_t dst, const void* src, int bytes, uint32_t bar) {
  asm volatile("cp.async.bulk.shared::cluster.global.mbarrier::complete_tx::bytes.multicast::cluster [%0], [%1], %2, [%3], %4;"
               ::"r"(dst), "l"(src), "r"(bytes), "r"(bar), "h"((uint16_t)3) : "memory");
}
__device__ __forceinline__ void tma3(uint32_t dst, const CUtensorMap* tm, uint32_t bar, int c0, int c1, int c2) {
  asm volatile("cp.async.bulk.tensor.3d.shared::cluster.global.mbarrier::complete_tx::bytes [%0], [%1, {%3,%4,%5}], [%2];"
               ::"r"(dst), "l"(tm), "r"(bar), "r"(c0), "r"(c1), "r"(c2) : "memory");
}
__device__ __forceinline__ void tma3_mc(uint32_t dst, const CUtensorMap* tm, uint32_t bar, int c1, int c2) {
  asm volatile("cp.async.bulk.tensor.3d.shared::cluster.global.mbarrier::complete_tx::bytes.multicast::cluster [%0], [%1, {%3,%4,%5}], [%2], %6;"
               ::"r"(dst), "l"(tm), "r"(bar), "r"(0), "r"(c1), "r"(c2), "h"((uint16_t)3) : "memory");
}
__device__ __forceinline__ void mbar_arrive_remote(uint32_t rb) {
  asm volatile("mbarrier.arrive.shared::cluster.b64 _, [%0];" ::"r"(rb) : "memory");
}
__device__ __forceinline__ uint4 ldg_ca4(const void* p) {
  uint4 v;
  asm volatile("ld.global.ca.v4.u32 {%0,%1,%2,%3}, [%4];" : "=r"(v.x), "=r"(v.y), "=r"(v.z), "=r"(v.w) : "l"(p) : "memory");
  return v;
}
__device__ __forceinline__ float u2f(uint32_t v) { return __uint_as_float(v); }
__device__ __forceinline__ void mma_az(float (&d)[4], const uint4& a, uint32_t b0, uint32_t b1) { mma16816_z(d, a.x, a.y, a.z, a.w, b0, b1); }
__device__ __forceinline__ void mma_a(float (&d)[4], const uint4& a, uint32_t b0, uint32_t b1) { mma16816(d, a.x, a.y, a.z, a.w, b0, b1); }
__device__ __forceinline__ uint32_t clock32() {
  uint32_t v;
  asm volatile("mov.u32 %0, %%clock;" : "=r"(v) :: "memory");
  return v;
}
__device__ __forceinline__ float swiglu(float g, float u, float r) {
  float hg = (0.5f * r) * g, th;
  asm("tanh.approx.f32 %0, %1;" : "=f"(th) : "f"(hg));
  return fmaf(hg, th, hg) * (r * u);
}
__device__ __forceinline__ void l2_prefetch(const void* p, int bytes) {
  asm volatile("cp.async.bulk.prefetch.L2.global [%0], %1;" ::"l"(p), "r"(bytes) : "memory");
}

__device__ __forceinline__ void wgmma_n256(float (&d)[128], uint64_t da, uint64_t db, int sd = 1) {
  asm volatile("{.reg .pred p; setp.ne.b32 p, %130, 0;\n"
      "wgmma.mma_async.sync.aligned.m64n256k16.f32.bf16.bf16 {"
      "%0,%1,%2,%3,%4,%5,%6,%7,%8,%9,%10,%11,%12,%13,%14,%15,"
      "%16,%17,%18,%19,%20,%21,%22,%23,%24,%25,%26,%27,%28,%29,%30,%31,"
      "%32,%33,%34,%35,%36,%37,%38,%39,%40,%41,%42,%43,%44,%45,%46,%47,"
      "%48,%49,%50,%51,%52,%53,%54,%55,%56,%57,%58,%59,%60,%61,%62,%63,"
      "%64,%65,%66,%67,%68,%69,%70,%71,%72,%73,%74,%75,%76,%77,%78,%79,"
      "%80,%81,%82,%83,%84,%85,%86,%87,%88,%89,%90,%91,%92,%93,%94,%95,"
      "%96,%97,%98,%99,%100,%101,%102,%103,%104,%105,%106,%107,%108,%109,%110,%111,"
      "%112,%113,%114,%115,%116,%117,%118,%119,%120,%121,%122,%123,%124,%125,%126,%127"
      "}, %128, %129, p, 1, 1, 0, 1;}\n"
      : "+f"(d[0]),"+f"(d[1]),"+f"(d[2]),"+f"(d[3]),"+f"(d[4]),"+f"(d[5]),"+f"(d[6]),"+f"(d[7]),
        "+f"(d[8]),"+f"(d[9]),"+f"(d[10]),"+f"(d[11]),"+f"(d[12]),"+f"(d[13]),"+f"(d[14]),"+f"(d[15]),
        "+f"(d[16]),"+f"(d[17]),"+f"(d[18]),"+f"(d[19]),"+f"(d[20]),"+f"(d[21]),"+f"(d[22]),"+f"(d[23]),
        "+f"(d[24]),"+f"(d[25]),"+f"(d[26]),"+f"(d[27]),"+f"(d[28]),"+f"(d[29]),"+f"(d[30]),"+f"(d[31]),
        "+f"(d[32]),"+f"(d[33]),"+f"(d[34]),"+f"(d[35]),"+f"(d[36]),"+f"(d[37]),"+f"(d[38]),"+f"(d[39]),
        "+f"(d[40]),"+f"(d[41]),"+f"(d[42]),"+f"(d[43]),"+f"(d[44]),"+f"(d[45]),"+f"(d[46]),"+f"(d[47]),
        "+f"(d[48]),"+f"(d[49]),"+f"(d[50]),"+f"(d[51]),"+f"(d[52]),"+f"(d[53]),"+f"(d[54]),"+f"(d[55]),
        "+f"(d[56]),"+f"(d[57]),"+f"(d[58]),"+f"(d[59]),"+f"(d[60]),"+f"(d[61]),"+f"(d[62]),"+f"(d[63]),
        "+f"(d[64]),"+f"(d[65]),"+f"(d[66]),"+f"(d[67]),"+f"(d[68]),"+f"(d[69]),"+f"(d[70]),"+f"(d[71]),
        "+f"(d[72]),"+f"(d[73]),"+f"(d[74]),"+f"(d[75]),"+f"(d[76]),"+f"(d[77]),"+f"(d[78]),"+f"(d[79]),
        "+f"(d[80]),"+f"(d[81]),"+f"(d[82]),"+f"(d[83]),"+f"(d[84]),"+f"(d[85]),"+f"(d[86]),"+f"(d[87]),
        "+f"(d[88]),"+f"(d[89]),"+f"(d[90]),"+f"(d[91]),"+f"(d[92]),"+f"(d[93]),"+f"(d[94]),"+f"(d[95]),
        "+f"(d[96]),"+f"(d[97]),"+f"(d[98]),"+f"(d[99]),"+f"(d[100]),"+f"(d[101]),"+f"(d[102]),"+f"(d[103]),
        "+f"(d[104]),"+f"(d[105]),"+f"(d[106]),"+f"(d[107]),"+f"(d[108]),"+f"(d[109]),"+f"(d[110]),"+f"(d[111]),
        "+f"(d[112]),"+f"(d[113]),"+f"(d[114]),"+f"(d[115]),"+f"(d[116]),"+f"(d[117]),"+f"(d[118]),"+f"(d[119]),
        "+f"(d[120]),"+f"(d[121]),"+f"(d[122]),"+f"(d[123]),"+f"(d[124]),"+f"(d[125]),"+f"(d[126]),"+f"(d[127])
      : "l"(da), "l"(db), "r"(sd));
}
__device__ __forceinline__ void wgmma_n192(float (&d)[96], uint64_t da, uint64_t db) {
  asm volatile("wgmma.mma_async.sync.aligned.m64n192k16.f32.bf16.bf16 {"
      "%0,%1,%2,%3,%4,%5,%6,%7,%8,%9,%10,%11,%12,%13,%14,%15,"
      "%16,%17,%18,%19,%20,%21,%22,%23,%24,%25,%26,%27,%28,%29,%30,%31,"
      "%32,%33,%34,%35,%36,%37,%38,%39,%40,%41,%42,%43,%44,%45,%46,%47,"
      "%48,%49,%50,%51,%52,%53,%54,%55,%56,%57,%58,%59,%60,%61,%62,%63,"
      "%64,%65,%66,%67,%68,%69,%70,%71,%72,%73,%74,%75,%76,%77,%78,%79,"
      "%80,%81,%82,%83,%84,%85,%86,%87,%88,%89,%90,%91,%92,%93,%94,%95"
      "}, %96, %97, 1, 1, 1, 0, 1;\n"
      : "+f"(d[0]),"+f"(d[1]),"+f"(d[2]),"+f"(d[3]),"+f"(d[4]),"+f"(d[5]),"+f"(d[6]),"+f"(d[7]),
        "+f"(d[8]),"+f"(d[9]),"+f"(d[10]),"+f"(d[11]),"+f"(d[12]),"+f"(d[13]),"+f"(d[14]),"+f"(d[15]),
        "+f"(d[16]),"+f"(d[17]),"+f"(d[18]),"+f"(d[19]),"+f"(d[20]),"+f"(d[21]),"+f"(d[22]),"+f"(d[23]),
        "+f"(d[24]),"+f"(d[25]),"+f"(d[26]),"+f"(d[27]),"+f"(d[28]),"+f"(d[29]),"+f"(d[30]),"+f"(d[31]),
        "+f"(d[32]),"+f"(d[33]),"+f"(d[34]),"+f"(d[35]),"+f"(d[36]),"+f"(d[37]),"+f"(d[38]),"+f"(d[39]),
        "+f"(d[40]),"+f"(d[41]),"+f"(d[42]),"+f"(d[43]),"+f"(d[44]),"+f"(d[45]),"+f"(d[46]),"+f"(d[47]),
        "+f"(d[48]),"+f"(d[49]),"+f"(d[50]),"+f"(d[51]),"+f"(d[52]),"+f"(d[53]),"+f"(d[54]),"+f"(d[55]),
        "+f"(d[56]),"+f"(d[57]),"+f"(d[58]),"+f"(d[59]),"+f"(d[60]),"+f"(d[61]),"+f"(d[62]),"+f"(d[63]),
        "+f"(d[64]),"+f"(d[65]),"+f"(d[66]),"+f"(d[67]),"+f"(d[68]),"+f"(d[69]),"+f"(d[70]),"+f"(d[71]),
        "+f"(d[72]),"+f"(d[73]),"+f"(d[74]),"+f"(d[75]),"+f"(d[76]),"+f"(d[77]),"+f"(d[78]),"+f"(d[79]),
        "+f"(d[80]),"+f"(d[81]),"+f"(d[82]),"+f"(d[83]),"+f"(d[84]),"+f"(d[85]),"+f"(d[86]),"+f"(d[87]),
        "+f"(d[88]),"+f"(d[89]),"+f"(d[90]),"+f"(d[91]),"+f"(d[92]),"+f"(d[93]),"+f"(d[94]),"+f"(d[95])
      : "l"(da), "l"(db));
}
__device__ __forceinline__ void wgmma_rs_n128(float (&d)[64], uint32_t a0, uint32_t a1, uint32_t a2, uint32_t a3, uint64_t db, int sd = 1) {
  asm volatile("{.reg .pred p; setp.ne.b32 p, %69, 0;\n"
      "wgmma.mma_async.sync.aligned.m64n128k16.f32.bf16.bf16 {"
      "%0,%1,%2,%3,%4,%5,%6,%7,%8,%9,%10,%11,%12,%13,%14,%15,"
      "%16,%17,%18,%19,%20,%21,%22,%23,%24,%25,%26,%27,%28,%29,%30,%31,"
      "%32,%33,%34,%35,%36,%37,%38,%39,%40,%41,%42,%43,%44,%45,%46,%47,"
      "%48,%49,%50,%51,%52,%53,%54,%55,%56,%57,%58,%59,%60,%61,%62,%63"
      "}, {%64,%65,%66,%67}, %68, p, 1, 1, 1;}\n"
      : "+f"(d[0]),"+f"(d[1]),"+f"(d[2]),"+f"(d[3]),"+f"(d[4]),"+f"(d[5]),"+f"(d[6]),"+f"(d[7]),
        "+f"(d[8]),"+f"(d[9]),"+f"(d[10]),"+f"(d[11]),"+f"(d[12]),"+f"(d[13]),"+f"(d[14]),"+f"(d[15]),
        "+f"(d[16]),"+f"(d[17]),"+f"(d[18]),"+f"(d[19]),"+f"(d[20]),"+f"(d[21]),"+f"(d[22]),"+f"(d[23]),
        "+f"(d[24]),"+f"(d[25]),"+f"(d[26]),"+f"(d[27]),"+f"(d[28]),"+f"(d[29]),"+f"(d[30]),"+f"(d[31]),
        "+f"(d[32]),"+f"(d[33]),"+f"(d[34]),"+f"(d[35]),"+f"(d[36]),"+f"(d[37]),"+f"(d[38]),"+f"(d[39]),
        "+f"(d[40]),"+f"(d[41]),"+f"(d[42]),"+f"(d[43]),"+f"(d[44]),"+f"(d[45]),"+f"(d[46]),"+f"(d[47]),
        "+f"(d[48]),"+f"(d[49]),"+f"(d[50]),"+f"(d[51]),"+f"(d[52]),"+f"(d[53]),"+f"(d[54]),"+f"(d[55]),
        "+f"(d[56]),"+f"(d[57]),"+f"(d[58]),"+f"(d[59]),"+f"(d[60]),"+f"(d[61]),"+f"(d[62]),"+f"(d[63])
      : "r"(a0), "r"(a1), "r"(a2), "r"(a3), "l"(db), "r"(sd));
}
__device__ __forceinline__ void wgmma_rs_n256(float (&d)[128], uint32_t a0, uint32_t a1, uint32_t a2, uint32_t a3, uint64_t db, int sd = 1) {
  asm volatile("{.reg .pred p; setp.ne.b32 p, %133, 0;\n"
      "wgmma.mma_async.sync.aligned.m64n256k16.f32.bf16.bf16 {"
      "%0,%1,%2,%3,%4,%5,%6,%7,%8,%9,%10,%11,%12,%13,%14,%15,"
      "%16,%17,%18,%19,%20,%21,%22,%23,%24,%25,%26,%27,%28,%29,%30,%31,"
      "%32,%33,%34,%35,%36,%37,%38,%39,%40,%41,%42,%43,%44,%45,%46,%47,"
      "%48,%49,%50,%51,%52,%53,%54,%55,%56,%57,%58,%59,%60,%61,%62,%63,"
      "%64,%65,%66,%67,%68,%69,%70,%71,%72,%73,%74,%75,%76,%77,%78,%79,"
      "%80,%81,%82,%83,%84,%85,%86,%87,%88,%89,%90,%91,%92,%93,%94,%95,"
      "%96,%97,%98,%99,%100,%101,%102,%103,%104,%105,%106,%107,%108,%109,%110,%111,"
      "%112,%113,%114,%115,%116,%117,%118,%119,%120,%121,%122,%123,%124,%125,%126,%127"
      "}, {%128,%129,%130,%131}, %132, p, 1, 1, 1;}\n"
      : "+f"(d[0]),"+f"(d[1]),"+f"(d[2]),"+f"(d[3]),"+f"(d[4]),"+f"(d[5]),"+f"(d[6]),"+f"(d[7]),
        "+f"(d[8]),"+f"(d[9]),"+f"(d[10]),"+f"(d[11]),"+f"(d[12]),"+f"(d[13]),"+f"(d[14]),"+f"(d[15]),
        "+f"(d[16]),"+f"(d[17]),"+f"(d[18]),"+f"(d[19]),"+f"(d[20]),"+f"(d[21]),"+f"(d[22]),"+f"(d[23]),
        "+f"(d[24]),"+f"(d[25]),"+f"(d[26]),"+f"(d[27]),"+f"(d[28]),"+f"(d[29]),"+f"(d[30]),"+f"(d[31]),
        "+f"(d[32]),"+f"(d[33]),"+f"(d[34]),"+f"(d[35]),"+f"(d[36]),"+f"(d[37]),"+f"(d[38]),"+f"(d[39]),
        "+f"(d[40]),"+f"(d[41]),"+f"(d[42]),"+f"(d[43]),"+f"(d[44]),"+f"(d[45]),"+f"(d[46]),"+f"(d[47]),
        "+f"(d[48]),"+f"(d[49]),"+f"(d[50]),"+f"(d[51]),"+f"(d[52]),"+f"(d[53]),"+f"(d[54]),"+f"(d[55]),
        "+f"(d[56]),"+f"(d[57]),"+f"(d[58]),"+f"(d[59]),"+f"(d[60]),"+f"(d[61]),"+f"(d[62]),"+f"(d[63]),
        "+f"(d[64]),"+f"(d[65]),"+f"(d[66]),"+f"(d[67]),"+f"(d[68]),"+f"(d[69]),"+f"(d[70]),"+f"(d[71]),
        "+f"(d[72]),"+f"(d[73]),"+f"(d[74]),"+f"(d[75]),"+f"(d[76]),"+f"(d[77]),"+f"(d[78]),"+f"(d[79]),
        "+f"(d[80]),"+f"(d[81]),"+f"(d[82]),"+f"(d[83]),"+f"(d[84]),"+f"(d[85]),"+f"(d[86]),"+f"(d[87]),
        "+f"(d[88]),"+f"(d[89]),"+f"(d[90]),"+f"(d[91]),"+f"(d[92]),"+f"(d[93]),"+f"(d[94]),"+f"(d[95]),
        "+f"(d[96]),"+f"(d[97]),"+f"(d[98]),"+f"(d[99]),"+f"(d[100]),"+f"(d[101]),"+f"(d[102]),"+f"(d[103]),
        "+f"(d[104]),"+f"(d[105]),"+f"(d[106]),"+f"(d[107]),"+f"(d[108]),"+f"(d[109]),"+f"(d[110]),"+f"(d[111]),
        "+f"(d[112]),"+f"(d[113]),"+f"(d[114]),"+f"(d[115]),"+f"(d[116]),"+f"(d[117]),"+f"(d[118]),"+f"(d[119]),
        "+f"(d[120]),"+f"(d[121]),"+f"(d[122]),"+f"(d[123]),"+f"(d[124]),"+f"(d[125]),"+f"(d[126]),"+f"(d[127])
      : "r"(a0), "r"(a1), "r"(a2), "r"(a3), "l"(db), "r"(sd));
}
__device__ __forceinline__ void wgmma_rs_n192(float (&d)[96], uint32_t a0, uint32_t a1, uint32_t a2, uint32_t a3, uint64_t db) {
  asm volatile("wgmma.mma_async.sync.aligned.m64n192k16.f32.bf16.bf16 {"
      "%0,%1,%2,%3,%4,%5,%6,%7,%8,%9,%10,%11,%12,%13,%14,%15,"
      "%16,%17,%18,%19,%20,%21,%22,%23,%24,%25,%26,%27,%28,%29,%30,%31,"
      "%32,%33,%34,%35,%36,%37,%38,%39,%40,%41,%42,%43,%44,%45,%46,%47,"
      "%48,%49,%50,%51,%52,%53,%54,%55,%56,%57,%58,%59,%60,%61,%62,%63,"
      "%64,%65,%66,%67,%68,%69,%70,%71,%72,%73,%74,%75,%76,%77,%78,%79,"
      "%80,%81,%82,%83,%84,%85,%86,%87,%88,%89,%90,%91,%92,%93,%94,%95"
      "}, {%96,%97,%98,%99}, %100, 1, 1, 1, 1;\n"
      : "+f"(d[0]),"+f"(d[1]),"+f"(d[2]),"+f"(d[3]),"+f"(d[4]),"+f"(d[5]),"+f"(d[6]),"+f"(d[7]),
        "+f"(d[8]),"+f"(d[9]),"+f"(d[10]),"+f"(d[11]),"+f"(d[12]),"+f"(d[13]),"+f"(d[14]),"+f"(d[15]),
        "+f"(d[16]),"+f"(d[17]),"+f"(d[18]),"+f"(d[19]),"+f"(d[20]),"+f"(d[21]),"+f"(d[22]),"+f"(d[23]),
        "+f"(d[24]),"+f"(d[25]),"+f"(d[26]),"+f"(d[27]),"+f"(d[28]),"+f"(d[29]),"+f"(d[30]),"+f"(d[31]),
        "+f"(d[32]),"+f"(d[33]),"+f"(d[34]),"+f"(d[35]),"+f"(d[36]),"+f"(d[37]),"+f"(d[38]),"+f"(d[39]),
        "+f"(d[40]),"+f"(d[41]),"+f"(d[42]),"+f"(d[43]),"+f"(d[44]),"+f"(d[45]),"+f"(d[46]),"+f"(d[47]),
        "+f"(d[48]),"+f"(d[49]),"+f"(d[50]),"+f"(d[51]),"+f"(d[52]),"+f"(d[53]),"+f"(d[54]),"+f"(d[55]),
        "+f"(d[56]),"+f"(d[57]),"+f"(d[58]),"+f"(d[59]),"+f"(d[60]),"+f"(d[61]),"+f"(d[62]),"+f"(d[63]),
        "+f"(d[64]),"+f"(d[65]),"+f"(d[66]),"+f"(d[67]),"+f"(d[68]),"+f"(d[69]),"+f"(d[70]),"+f"(d[71]),
        "+f"(d[72]),"+f"(d[73]),"+f"(d[74]),"+f"(d[75]),"+f"(d[76]),"+f"(d[77]),"+f"(d[78]),"+f"(d[79]),
        "+f"(d[80]),"+f"(d[81]),"+f"(d[82]),"+f"(d[83]),"+f"(d[84]),"+f"(d[85]),"+f"(d[86]),"+f"(d[87]),
        "+f"(d[88]),"+f"(d[89]),"+f"(d[90]),"+f"(d[91]),"+f"(d[92]),"+f"(d[93]),"+f"(d[94]),"+f"(d[95])
      : "r"(a0), "r"(a1), "r"(a2), "r"(a3), "l"(db));
}


constexpr int C_LN = 0, C_PX = 16, C_PY = 32;
constexpr int NB_CONS = 1, NB_LN = 2, NB_LAG = 4, NB_INIT = 6, NB_RDY = 7;
constexpr int LAGX = 3;
constexpr int LAGY = 6;
constexpr int LAG2 = 6;
constexpr int NLL = 2;
constexpr int POLL_DELAY = 1200;
constexpr int POLL_DELAY2 = 1000;
constexpr int POLL_DELAY3 = 600;
constexpr int POLL_DELAY4 = 1300;
constexpr int FILT_DELAY = 800;
constexpr int WARM = 4;
constexpr int ALEAD = 6;
constexpr int XTRIG = 20;
constexpr int HTRIG = 0;
constexpr int SM_E = 0, SM_X = 16384, SM_E2 = 32768, SM_W = 49152, SM_FC = 69632, SM_T = 73728 - T1_BYTES;
constexpr unsigned long long KORDER = 0xBA9432DC876510ull;
constexpr unsigned long long BSLOT = 0x52140A98D52140ull, PSLOT = 0xB763CB763CB763ull;
constexpr unsigned long long BDEP = 0xFFEC97531ull, PDEP = 0xBA754ull;
constexpr uint32_t HI128 = desc_hi(1024, 1), HI64 = desc_hi(512, 2);

struct Bars {
  uint64_t full1[32], empty1[32], freeA[4], full2[16], fullA[8], empty2[8], emptyP[9], sig, done, fullP[32], hbar, tbar, hint[3], sbar;
  uint32_t epoch, pad;
};

template <int NK, bool STORE, int J0 = 0, int J1 = NK>
__device__ __forceinline__ void make_p(const float (&acc)[NK * 16], float r0, float r1, uint4 (&p)[NK], uint4* pbase, int ks0, uint32_t tag) {
#pragma unroll
  for (int j = J0; j < J1; j++) {
    uint32_t w[4];
#pragma unroll
    for (int i = 0; i < 4; i++) {
      const int a = 8 * j + 2 * i, b = a + NK * 8;
      w[i] = pack2(swiglu(acc[a], acc[b], (i & 1) ? r1 : r0), swiglu(acc[a + 1], acc[b + 1], (i & 1) ? r1 : r0));
    }
    asm volatile("" : "+r"(w[0]), "+r"(w[1]), "+r"(w[2]), "+r"(w[3]));
    p[j] = make_uint4(w[0], w[1], w[2], w[3]);
    if (STORE) st_tag(pbase + ((ks0 + j) >> 2) * 1024 + ((ks0 + j) & 3) * 32, p[j], tag);
  }
}
__device__ __forceinline__ void spin_until(uint32_t t) {
  while ((int)(clock32() - t) < 0) {}
}

__global__ void __cluster_dims__(2, 1, 1) __launch_bounds__(NTHREADS, 1)
fused_kernel(const __nv_bfloat16* __restrict__ x, const Tables* __restrict__ tab, Scratch* __restrict__ scr,
             __nv_bfloat16* __restrict__ out, const char* __restrict__ wg_raw, const char* __restrict__ wu_raw,
             const char* __restrict__ wd_raw,
             const __grid_constant__ CUtensorMap tmWR, const __grid_constant__ CUtensorMap tmWI,
             const __grid_constant__ CUtensorMap tmGX, const __grid_constant__ CUtensorMap tmUX,
             const __grid_constant__ CUtensorMap tmGY, const __grid_constant__ CUtensorMap tmUY,
             const __grid_constant__ CUtensorMap tmD) {
  extern __shared__ __align__(1024) char smem_raw[];
  const uint32_t sbase = s2u(smem_raw);
  const uint32_t sbar = sbase + 14 * SLOT, sstat = sbar + 1408;
  const int tid = threadIdx.x, lane = tid & 31;
  const int c = blockIdx.x, rk = c & 1, f = (c >> 1) & 7, rb = 2 * (c >> 4) + rk;
  const int rb2 = 2 * (c >> 4) + (f >> 2), kh = (f >> 1) & 1, nq = 2 * (f & 1) + rk;
#define BAR(field, i) (sbar + (uint32_t)offsetof(Bars, field) + 8u * (i))
#define TOFF(field) (sbase + SM_T + (uint32_t)offsetof(Tables, field) + lane * 16)

  if (tid >= 256) {
    asm volatile("setmaxnreg.dec.sync.aligned.u32 40;");
    const int warp = __shfl_sync(0xffffffffu, tid >> 5, 0);
    if (lane == 0) {
      auto init = [&](uint32_t b, int n, int count, int bytes) {
#pragma unroll
        for (int i = 0; i < n; i++) mbar_init(b + 8 * i, count);
#pragma unroll
        for (int i = 0; i < (bytes ? n : 0); i++) mbar_expect(b + 8 * i, bytes);
      };
      if (warp == 8) {
        if (sbase & 1023) die();
        init(BAR(tbar, 0), 1, 1, T2_BYTES + 2 * 10240);
        init(BAR(hbar, 0), 1, 1, 16384);
        init(BAR(hint, 0), 3, 1, 0);
        init(BAR(sbar, 0), 1, 32, 0);
        init(BAR(empty2, 0), 19, 8, 0);
      } else if (warp == 9) {
        init(BAR(full1, 0), 16, 1, 16384);
        init(BAR(full1, 16), 16, 1, 12288);
      } else if (warp == 10) {
        init(BAR(fullP, 0), 30, 1, 8192);
      } else {
        init(BAR(full2, 0), 24, 1, 16384);
        init(BAR(empty1, 0), 36, 16, 0);
      }
      asm volatile("fence.mbarrier_init.release.cluster;" ::: "memory");
    }
    if (tid == 256) {
      const int w0 = ((c >> 3) * 257 + 32 * (c & 7) + 1) & ~7;
      asm volatile("prefetch.tensormap [%0];" ::"l"(&tmWR) : "memory");
      asm volatile("prefetch.tensormap [%0];" ::"l"(&tmWI) : "memory");
      spin_until(clock32() + FILT_DELAY);
      tma3(sbase + SM_W, &tmWR, BAR(tbar, 0), w0, 0, 0);
      tma3(sbase + SM_W + 10240, &tmWI, BAR(tbar, 0), w0, 0, 0);
      bulk_load(sbase + SM_T + T1_BYTES, reinterpret_cast<const char*>(tab) + T1_BYTES, T2_BYTES, BAR(tbar, 0));
    }
    if (tid == 288) {
      asm volatile("prefetch.tensormap [%0];" ::"l"(rk ? &tmUX : &tmGX) : "memory");
      asm volatile("prefetch.tensormap [%0];" ::"l"(rk ? &tmUY : &tmGY) : "memory");
      asm volatile("prefetch.tensormap [%0];" ::"l"(&tmD) : "memory");
    }
    if (tid == 320) {
      const unsigned e = ld_relaxed(&scr->cnt[(C_LN + rb) * 32]) >> 3;
      asm volatile("st.shared.u32 [%0], %1;" ::"r"(BAR(epoch, 0)), "r"(e) : "memory");
    }
    __syncwarp();
    asm volatile("barrier.cluster.arrive.relaxed.aligned;" ::: "memory");
    bar_arrive(NB_RDY, 384);
    asm volatile("barrier.cluster.wait.aligned;" ::: "memory");
    bar_sync(NB_INIT, 384);
    unsigned epoch;
    asm volatile("ld.shared.u32 %0, [%1];" : "=r"(epoch) : "r"(BAR(epoch, 0)) : "memory");
    if (warp == 8) {
      if (lane == 0) {
        const int ax = (7 * f + 3 * (f & 1)) >> 1;
        const int ay = 7 * f + ((f & 1) ? 0 : 4);
        const CUtensorMap* tx = rk ? &tmUX : &tmGX;
        const CUtensorMap* ty = rk ? &tmUY : &tmGY;
        mbar_wait_bounded(BAR(sig, 0));
        uint32_t s = 2;
#pragma unroll 1
        for (int n = 0; n < 16; n++) {
          if (n >= 6) mbar_wait_bounded(BAR(empty1, n - 6));
          tma3_mc(sbase + (8 + s) * SLOT + rk * 8192, tx, BAR(full1, n), n * 32, ax);
          if (++s == 6) s = 0;
          if (n >= 10 && n < 15) {
            const int k = n - 10;
            mbar_wait_bounded(BAR(freeA, (12 * k + 11) >> 4));
            tma3_mc(sbase + k * 12288 + rk * 6144, ty, BAR(full1, 16 + k), (k + 8) * 32, ay);
          }
        }
#pragma unroll 1
        for (int k = 5; k < 16; k++) {
          mbar_wait_bounded(BAR(empty1, k < 13 ? 10 + ((12 * (k - 5) + 11) >> 4) : 8 + k));
          tma3_mc(sbase + 8 * SLOT + ((k - 5) & 7) * 12288 + rk * 6144, ty, BAR(full1, 16 + k), ((k + 8) & 15) * 32, ay);
        }
        mbar_wait_bounded(BAR(done, 0));
      }
    } else if (warp == 9) {
      if (lane == 0) {
        mbar_wait(BAR(fullA, 4));
        wait_counter(&scr->cnt[(C_LN + rb2) * 32], (epoch + 1) * 8);
        asm volatile("fence.proxy.async.global;" ::: "memory");
#pragma unroll 1
        for (int i = 0; i < 14; i++) {
          const int kblk = 14 * kh + (int)((KORDER >> (4 * i)) & 15);
          mbar_wait(i < 9 ? BAR(empty1, 16 + (uint32_t)((BDEP >> (4 * i)) & 15)) : BAR(empty2, i - 9));
          tma3(sbase + (uint32_t)((BSLOT >> (4 * i)) & 15) * SLOT, &tmD, BAR(full2, i), 0, 64 * kblk, 2 * nq);
        }
        mbar_wait(BAR(empty2, 5));
        bulk_load(sbase + 13 * SLOT, &scr->LN[(rb2 * 8 + 2 * nq) * 1024 + kh * 512], 8192, BAR(hbar, 0));
        bulk_load(sbase + 13 * SLOT + 8192, &scr->LN[(rb2 * 8 + 2 * nq + 1) * 1024 + kh * 512], 8192, BAR(hbar, 0));
      }
    } else if (warp == 10) {
      bar_sync(NB_LN, 288);
      if (lane == 0) {
        red_release(&scr->cnt[(C_LN + rb) * 32]);
        wait_counter(&scr->cnt[(C_LN + rb) * 32], (epoch + 1) * 8);
        asm volatile("fence.proxy.async.global;" ::: "memory");
#pragma unroll 1
        for (int kb = NLL; kb < 8; kb++) {
          if (2 * kb >= ALEAD) mbar_wait(BAR(empty1, 2 * kb - ALEAD));
          bulk_load(sbase + kb * SLOT, &scr->LN[(rb * 8 + kb) * 1024], 16384, BAR(fullA, kb));
        }
#pragma unroll 1
        for (int s = 0; s < 14; s++) {
          const int kblk = 14 * kh + (int)((KORDER >> (4 * s)) & 15);
          if (s == 0 || s == 8 || s == 11) {
            mbar_wait(BAR(hint, s == 0 ? 0 : s == 8 ? 1 : 2));
          }
          mbar_wait(s < 5 ? BAR(empty1, 16 + (uint32_t)((PDEP >> (4 * s)) & 15)) : BAR(emptyP, s - 5));
          bulk_load_mc(sbase + (uint32_t)((PSLOT >> (4 * s)) & 15) * SLOT + rk * 8192, &scr->P[(rb2 * 28 + kblk) * 1024 + rk * 512], 8192, BAR(fullP, 16 * rk + s));
        }
      }
    } else {
      if (lane == 0) {
        mbar_wait(BAR(tbar, 0));
        l2_prefetch(wg_raw + (size_t)c * 5376, 5376);
        l2_prefetch(wu_raw + (size_t)c * 5376, 5376);
        mbar_wait(BAR(sig, 0));
        l2_prefetch(wg_raw + 688128 + (size_t)c * 8960, 8960);
        l2_prefetch(wu_raw + 688128 + (size_t)c * 8960, 8960);
      }
      mbar_wait(BAR(fullA, 4));
      if (lane == 0) l2_prefetch(wd_raw + (size_t)c * 14336, 14336);
      {
        const uint32_t tag = (epoch + 1) & 1;
        uint4 v0, v1, v2;
        while (true) {
          v0 = ld_b128(&scr->ST[rb * 64 + lane]);
          v1 = ld_b128(&scr->ST[rb * 64 + 32 + lane]);
          v2 = ld_b128(&scr->ST[rb2 * 64 + 32 * kh + lane]);
          if (!__any_sync(0xffffffffu, ((v0.x ^ tag) | (v1.x ^ tag) | (v2.x ^ tag)) & 1u)) break;
        }
        sts4(sstat + lane * 16, v0.x & ~1u, v0.y, v0.z, v0.w);
        sts4(sstat + 512 + lane * 16, v1.x & ~1u, v1.y, v1.z, v1.w);
        sts4(sstat + 1024 + lane * 16, v2.x & ~1u, v2.y, v2.z, v2.w);
        mbar_arrive(BAR(sbar, 0));
      }
      if (lane == 0) {
        mbar_wait(BAR(empty1, XTRIG));
        while ((int)(ld_relaxed(&scr->cnt[(C_PX + rb2) * 32 + kh]) - (epoch + 1) * 32) < 0) {
        }
        mbar_arrive(BAR(hint, 0));
        mbar_wait(BAR(emptyP, HTRIG));
        uint32_t done = 0;
        while (done != 3) {
          uint2 v;
          asm volatile("ld.relaxed.gpu.global.v2.u32 {%0,%1}, [%2];" : "=r"(v.x), "=r"(v.y) : "l"(&scr->cnt[(C_PY + rb2) * 32 + 4 * (rk ^ kh ^ 1) + 2 * kh]) : "memory");
          if (!(done & 1) && (int)(v.x - (epoch + 1) * 8) >= 0) { done |= 1; mbar_arrive(BAR(hint, 1)); }
          if (!(done & 2) && (int)(v.y - (epoch + 1) * 8) >= 0) { done |= 2; mbar_arrive(BAR(hint, 2)); }
        }
      }
    }
  } else {
    const int warp = __shfl_sync(0xffffffffu, tid >> 5, 0);
    const int g = lane >> 2, t = lane & 3;
    uint4 fa[4], fb[4], tw[6];
#pragma unroll
    for (int i = 0; i < 4; i++) fa[i] = ldg_ca4(&tab->fa[i][lane][0]);
#pragma unroll
    for (int i = 0; i < 6; i++) tw[i] = ldg_ca4(&tab->tw1[i][lane][0]);
#pragma unroll
    for (int i = 0; i < 4; i++) fb[i] = ldg_ca4(&tab->fb[i][lane][0]);
#pragma unroll
    for (int i = 0; i < 4; i++) {
      const int r = i >> 1, ch = (i & 1) * 32 + lane;
      cp_async16(sbase + SM_X + (2 * warp + r) * 1024 + ((ch ^ ((ch >> 3) & 1)) * 16),
                 x + (size_t)(c + 128 * (2 * warp + r)) * 512 + ch * 8);
    }
    asm volatile("cp.async.commit_group;" ::: "memory");
    asm volatile("barrier.cluster.arrive.relaxed.aligned;" ::: "memory");
    uint32_t rbar;
    asm volatile("mapa.shared::cluster.u32 %0, %1, %2;" : "=r"(rbar) : "r"(sbar), "r"(rk ^ 1));
#define RBAR(field, i) (rbar + (uint32_t)offsetof(Bars, field) + 8u * (i))
    {
      const int ln = (tid >> 1) & 31, lg = ln >> 2, lt = ln & 3, i = 4 * (tid >> 6) + 2 * (tid & 1);
      const int kidx = lt + 8 * (i >> 3), nidx = 4 * ((i >> 1) & 3) + (lg >> 1);
      const uint32_t a0 = cfrag<2048>((c + 128 * kidx) * nidx, lg & 1), a1 = cfrag<2048>((c + 128 * (kidx + 4)) * nidx, lg & 1);
      const uint32_t b0 = cfrag<2048>(-(c + 128 * nidx) * kidx, lg & 1), b1 = cfrag<2048>(-(c + 128 * nidx) * (kidx + 4), lg & 1);
      asm volatile("st.shared.v2.u32 [%0], {%1,%2};" ::"r"(sbase + SM_FC + tid * 8), "r"(a0), "r"(a1) : "memory");
      asm volatile("st.shared.v2.u32 [%0], {%1,%2};" ::"r"(sbase + SM_FC + 2048 + tid * 8), "r"(b0), "r"(b1) : "memory");
    }
    bar_sync(NB_CONS, 256);
    uint4 fc[4];
#pragma unroll
    for (int i = 0; i < 4; i++) fc[i] = lds4(sbase + SM_FC + i * 512 + lane * 16);
    asm volatile("cp.async.wait_group 0;" ::: "memory");
    __syncwarp();
    bar_arrive(NB_INIT, 384);
    uint32_t tag, ones;
    uint4 q[4], o[4];
    {
      uint32_t v[2][8];
#pragma unroll
      for (int r = 0; r < 2; r++)
#pragma unroll
        for (int ks = 0; ks < 2; ks++) {
          const int ch = 32 * ks + 2 * (lane & 15) + (lane >> 4);
          asm volatile("ldmatrix.sync.aligned.m8n8.x4.trans.shared.b16 {%0,%1,%2,%3}, [%4];"
                       : "=r"(v[r][4 * ks]), "=r"(v[r][4 * ks + 1]), "=r"(v[r][4 * ks + 2]), "=r"(v[r][4 * ks + 3])
                       : "r"(sbase + SM_X + (2 * warp + r) * 1024 + ((ch ^ ((ch >> 3) & 1)) * 16)) : "memory");
        }
      float sq[2];
#pragma unroll
      for (int r = 0; r < 2; r++) {
        float s0 = 0.f, s1 = 0.f;
#pragma unroll
        for (int i = 0; i < 8; i++) {
          const float lo = bf_lo(v[r][i]), hi = u2f(v[r][i] & 0xffff0000u);
          s0 = fmaf(lo, lo, s0);
          s1 = fmaf(hi, hi, s1);
        }
        sq[r] = s0 + s1;
      }
      {
        float w = ((lane & 1) ? sq[1] : sq[0]) + __shfl_xor_sync(0xffffffffu, (lane & 1) ? sq[0] : sq[1], 1);
        w += __shfl_xor_sync(0xffffffffu, w, 2);
        w = sum_groups(w);
        const float o2 = __shfl_xor_sync(0xffffffffu, w, 1);
        sq[0] = (lane & 1) ? o2 : w;
        sq[1] = (lane & 1) ? w : o2;
      }
#pragma unroll
      for (int r = 0; r < 2; r++) {
        float dd[2][4], ee[2][4];
#pragma unroll
        for (int nt = 0; nt < 2; nt++) {
          mma_az(dd[nt], fa[0], v[r][2 * nt], v[r][2 * nt + 1]);
          mma_a(dd[nt], fa[1], v[r][4 + 2 * nt], v[r][5 + 2 * nt]);
          mma_az(ee[nt], fa[2], v[r][2 * nt], v[r][2 * nt + 1]);
          mma_a(ee[nt], fa[3], v[r][4 + 2 * nt], v[r][5 + 2 * nt]);
        }
        float mean = (dd[0][0] + dd[0][1]) + (dd[1][0] + dd[1][1]);
        mean += __shfl_xor_sync(0xffffffffu, mean, 1);
        mean += __shfl_xor_sync(0xffffffffu, mean, 2);
        mean = __shfl_sync(0xffffffffu, mean, 0) * (1.f / 512.f);
        const float rs = rsqrtf(fmaxf(fmaf(-mean, mean, sq[r] * (1.f / 512.f)), 0.f) + 1e-5f);
        float acc[4][4];
#pragma unroll
        for (int nt = 0; nt < 2; nt++) {
          const float (&d)[4] = dd[nt];
          const float (&e)[4] = ee[nt];
          const uint4 &ka = tw[2 * nt], &kb = tw[2 * nt + 1], &kc = tw[4 + nt];
          const uint32_t a0 = pack2(d[0] * u2f(ka.x) + d[2] * u2f(ka.y), d[1] * u2f(kb.x) + d[3] * u2f(kb.y));
          const uint32_t a2 = pack2(d[0] * u2f(ka.z) + d[2] * u2f(ka.w), d[1] * u2f(kb.z) + d[3] * u2f(kb.w));
          const uint32_t a1 = pack2(e[0] * u2f(kc.x) + e[2] * u2f(kc.y), e[1] * u2f(kc.z) + e[3] * u2f(kc.w));
          const uint32_t a3 = pack2(e[2] * u2f(kc.x) - e[0] * u2f(kc.y), e[3] * u2f(kc.z) - e[1] * u2f(kc.w));
          const uint32_t dc = pack2(fmaf(mean, -32.f, d[0]), fmaf(mean, -32.f, d[1]));
          const uint32_t h0 = g == 0 ? dc : a0, h2 = g == 0 ? 0u : a2;
          if (nt == 0) {
            mma16816_z(acc[0], a0, a1, a2, a3, fb[2 * nt].x, fb[2 * nt].y);
            mma16816_z(acc[1], a0, a1, a2, a3, fb[2 * nt].z, fb[2 * nt].w);
            mma16816_z(acc[2], h0, a1, h2, a3, fb[2 * nt + 1].x, fb[2 * nt + 1].y);
            mma16816_z(acc[3], h0, a1, h2, a3, fb[2 * nt + 1].z, fb[2 * nt + 1].w);
          } else {
            mma16816(acc[0], a0, a1, a2, a3, fb[2 * nt].x, fb[2 * nt].y);
            mma16816(acc[1], a0, a1, a2, a3, fb[2 * nt].z, fb[2 * nt].w);
            mma16816(acc[2], h0, a1, h2, a3, fb[2 * nt + 1].x, fb[2 * nt + 1].y);
            mma16816(acc[3], h0, a1, h2, a3, fb[2 * nt + 1].z, fb[2 * nt + 1].w);
          }
        }
#pragma unroll
        for (int h = 0; h < 2; h++) {
          const int j = 2 * warp + r, m = 2 * t + h;
          sts4(sbase + SM_E + ((j * 8 + m) * 8 + (g ^ (2 * t) ^ (2 * (j & 3)))) * 16,
               pack2(acc[h][0] * rs, acc[h][1] * rs), pack2(acc[h][2] * rs, acc[h][3] * rs),
               pack2(acc[2 + h][0] * rs, acc[2 + h][1] * rs), pack2(acc[2 + h][2] * rs, acc[2 + h][3] * rs));
        }
      }
      bar_sync(NB_RDY, 384);
      const uint32_t ea = sbase + SM_E + ((t * 8 + warp) * 8 + (g ^ (warp & 6) ^ (2 * t))) * 16;
      lds_frag(q[0], q[1], ea, ea + 4096);
      lds_frag(q[2], q[3], ea + 8192, ea + 12288);
      asm volatile("ld.shared.u32 %0, [%1];" : "=r"(tag) : "r"(BAR(epoch, 0)) : "memory");
      ones = ~(tag >> 31);
      tag = (tag + 1) & 1;
      cdft16(q, fc, o);
#pragma unroll
      for (int vv = 0; vv < 4; vv++) {
        o[vv].y &= ~1u;
        o[vv].z = (o[vv].z & ~1u) | (tag ^ 1);
        st_tag(&scr->Z1[(((4 * vv + t) * 8 + warp) * 128 + c) * 8 + g], o[vv], tag);
      }
    }
    asm volatile("setmaxnreg.inc.sync.aligned.u32 232;");
    {
      uint4* const zp = &scr->Z1[(c * 128 + 8 * t + warp) * 8 + g];
      const uint32_t tst = clock32();
      mbar_wait(BAR(tbar, 0));
      uint4 f2[4], g2[4];
#pragma unroll
      for (int i = 0; i < 4; i++) {
        f2[i] = lds4(TOFF(f2) + warp * 2048 + i * 512);
        g2[i] = lds4(TOFF(g2) + warp * 2048 + i * 512);
      }
      const uint4 f8 = lds4(TOFF(f8)), g8 = lds4(TOFF(g8));
      asm volatile("barrier.cluster.wait.aligned;" ::: "memory");
      spin_until(tst + POLL_DELAY);
      ld_tag4_issue<256>(q, zp);
      float wfr[16], wfi[16];
      {
        const float nyq = ((c & 7) == 7 && g == 0) ? 0.5f : 1.f;
        uint32_t wa = sbase + SM_W + (16 * warp + t) * 80 + ((2 * (c >> 3) + 2) & 15) - 2;
        asm volatile("" : "+r"(wa));
        const uint32_t wb[3] = {wa + 2 * (g == 0 ? 16 : g), wa + 2 * g, wa - 2 * g};
#pragma unroll
        for (int i = 0; i < 16; i++) {
          const int ci = i >> 3, dd = (i >> 2) & 1, e = i & 3;
          const uint32_t a = wb[e < 2 ? e : 2] + (ci * 8 + 4 * dd) * 80 + (e == 0 ? 0 : e == 1 ? 16 : e == 2 ? 64 : 48);
          wfr[i] = bf_lo(lds_u16(a)) * (e == 2 ? nyq : 1.f);
          wfi[i] = bf_lo(lds_u16(a + 10240)) * (e == 2 ? nyq : 1.f);
        }
      }
      ld_tag4_finish<256>(q, zp, tag);
#pragma unroll
      for (int i = 0; i < 4; i++) q[i].z &= ~1u;
      reg_frag(q, ones);
      cdft16(q, f2, o);
      const uint32_t e2 = sbase + SM_E2;
#pragma unroll
      for (int vv = 0; vv < 4; vv++)
        sts4(e2 + ((warp * 16 + 4 * vv + t) * 8 + (g ^ (2 * t) ^ (2 * (warp & 3)))) * 16, o[vv].x, o[vv].y, o[vv].z, o[vv].w);
      bar_sync(NB_CONS, 256);
      uint32_t ad[2], res[2][2][4];
#pragma unroll
      for (int ci = 0; ci < 2; ci++) {
        const int cc = 2 * warp + ci;
        ad[ci] = e2 + ((t * 16 + cc) * 8 + (g ^ (2 * (cc & 3)) ^ (2 * t))) * 16;
        lds_frag(q[2 * ci], q[2 * ci + 1], ad[ci], ad[ci] + 8192);
      }
#pragma unroll
      for (int ci = 0; ci < 2; ci++)
#pragma unroll
        for (int p = 0; p < 2; p++) {
          uint32_t y[2][2];
#pragma unroll
          for (int vv = 0; vv < 2; vv++) {
            float d[4];
            mma_az(d, q[2 * ci + p], word(f8, 2 * vv), word(f8, 2 * vv + 1));
#pragma unroll
            for (int rr = 0; rr < 2; rr++) {
              const float fr = wfr[ci * 8 + vv * 4 + 2 * p + rr], fi = wfi[ci * 8 + vv * 4 + 2 * p + rr];
              y[vv][rr] = pack2(d[2 * rr] * fr - d[2 * rr + 1] * fi, d[2 * rr] * fi + d[2 * rr + 1] * fr);
            }
          }
#pragma unroll
          for (int vv = 0; vv < 2; vv++) {
            float d[4];
            mma16816_z(d, y[0][0], y[0][1], y[1][0], y[1][1], word(g8, 2 * vv), word(g8, 2 * vv + 1));
            res[ci][vv][2 * p] = pack2(d[0], d[1]);
            res[ci][vv][2 * p + 1] = pack2(d[2], d[3]);
          }
        }
#pragma unroll
      for (int i = 0; i < 4; i++)
        sts4(ad[i >> 1] + (i & 1) * 8192, res[i >> 1][i & 1][0], res[i >> 1][i & 1][1], res[i >> 1][i & 1][2], res[i >> 1][i & 1][3]);
      bar_sync(NB_CONS, 256);
      const uint32_t eb = e2 + ((warp * 16 + t) * 8 + (g ^ (2 * t) ^ (2 * (warp & 3)))) * 16;
      lds_frag(q[0], q[1], eb, eb + 512);
      lds_frag(q[2], q[3], eb + 1024, eb + 1536);
      cdft16(q, g2, o);
#pragma unroll
      for (int vv = 0; vv < 4; vv++) {
        o[vv].y &= ~1u;
        o[vv].z = (o[vv].z & ~1u) | tag;
        st_tag(zp + vv * 256, o[vv], tag);
      }
    }
    {
      const uint4* const zp = &scr->Z1[((t * 8 + warp) * 128 + c) * 8 + g];
      const uint32_t tst = clock32();
      uint4 gb[4], ga[4], gc[4], tw[4];
      uint2 xr[2][4];
      uint2* lnp[2];
#pragma unroll
      for (int r = 0; r < 2; r++) {
        const int row = 16 * f + 2 * warp + r;
        lnp[r] = reinterpret_cast<uint2*>(&scr->LN[(rb * 8 + (g >> 2)) * 1024 + row * 8 + ((2 * (g & 3) + (t >> 1)) ^ (row & 7))]) + (t & 1);
        asm volatile("" : "+l"(lnp[r]));
      }
#pragma unroll
      for (int i = 0; i < 4; i++) {
        gc[i] = lds4(sbase + SM_FC + 2048 + i * 512 + lane * 16);
        gb[i] = lds4(TOFF(gb) + i * 512);
        ga[i] = lds4(TOFF(ga) + i * 512);
        tw[i] = lds4(TOFF(tw3) + i * 512);
        const int ch = 2 * (g + 8 * i) + (t >> 1);
#pragma unroll
        for (int r = 0; r < 2; r++) xr[r][i] = lds2(sbase + SM_X + (2 * warp + r) * 1024 + ((ch ^ ((ch >> 3) & 1)) * 16) + (t & 1) * 8);
      }
      spin_until(tst + POLL_DELAY2);
      ld_tag4_issue<32768>(q, zp);
      ld_tag4_finish<32768, true>(q, zp, tag);
      if (lane == 0) mbar_arrive(BAR(sig, 0));
      reg_frag(q, ones);
      cdft16(q, gc, o);
#pragma unroll
      for (int vv = 0; vv < 4; vv++)
        sts4(sbase + SM_E + (((4 * vv + t) * 8 + warp) * 8 + (g ^ (warp & 6) ^ (2 * t))) * 16, o[vv].x, o[vv].y, o[vv].z, o[vv].w);
      bar_sync(NB_CONS, 256);
      uint32_t hv[2][8];
      const float mk = t == 0 ? 0.f : 1.f;
#pragma unroll
      for (int r = 0; r < 2; r++) {
        const int j = 2 * warp + r;
        uint4 u[2];
#pragma unroll
        for (int h = 0; h < 2; h++) u[h] = lds4(sbase + SM_E + ((j * 8 + 2 * t + h) * 8 + (g ^ (2 * t) ^ (2 * (j & 3)))) * 16);
        const uint32_t bp[4][2] = {{u[0].x, u[1].x & ones}, {u[0].y & ones, u[1].y}, {u[0].z, u[1].z & ones}, {u[0].w & ones, u[1].w}};
        float y[2][2][4];
#pragma unroll
        for (int i = 0; i < 2; i++) {
          float lo[4], hi[4], e[4];
          mma_az(lo, gb[2 * i], bp[0][0], bp[0][1]);
          mma_az(hi, gb[2 * i + 1], bp[2][0], bp[2][1]);
          mma_az(e, gb[2 * i], bp[1][0], bp[1][1]);
          mma_a(e, gb[2 * i + 1], bp[3][0], bp[3][1]);
          const uint4 &ka = tw[2 * i], &kb = tw[2 * i + 1];
          const float tr0 = fmaf(hi[0], mk, lo[0]), ti0 = fmaf(hi[2], mk, lo[2]);
          const float tr1 = lo[1] + hi[1], ti1 = lo[3] + hi[3];
          const float vr0 = tr0 * u2f(ka.x) - ti0 * u2f(ka.y), vi0 = tr0 * u2f(ka.y) + ti0 * u2f(ka.x);
          const float vr1 = tr1 * u2f(ka.z) - ti1 * u2f(ka.w), vi1 = tr1 * u2f(ka.w) + ti1 * u2f(ka.z);
          const uint32_t b0 = pack2(t == 0 ? hi[0] : vr0, vr1), b1 = pack2(t == 0 ? vr0 : vi0, vi1);
          const uint32_t b2 = pack2(e[0] * u2f(kb.x) - e[2] * u2f(kb.y), e[1] * u2f(kb.z) - e[3] * u2f(kb.w));
          const uint32_t b3 = pack2(e[0] * u2f(kb.y) + e[2] * u2f(kb.x), e[1] * u2f(kb.w) + e[3] * u2f(kb.z));
#pragma unroll
          for (int mt = 0; mt < 2; mt++) {
            mma_az(y[mt][i], ga[2 * mt], b0, b1);
            mma_a(y[mt][i], ga[2 * mt + 1], b2, b3);
          }
        }
#pragma unroll
        for (int i = 0; i < 4; i++) {
          hv[r][2 * i] = hadd2_bf16(xr[r][i].x, pack2(y[i >> 1][0][2 * (i & 1)], y[i >> 1][0][2 * (i & 1) + 1]));
          hv[r][2 * i + 1] = hadd2_bf16(xr[r][i].y, pack2(y[i >> 1][1][2 * (i & 1)], y[i >> 1][1][2 * (i & 1) + 1]));
        }
      }
      float mean[2];
      uint32_t mb[2];
#pragma unroll
      for (int r = 0; r < 2; r++) {
        mean[r] = sum_groups(quad_sum(hv[r])) * (1.f / 512.f);
        mb[r] = pack2(mean[r], mean[r]);
      }
#pragma unroll
      for (int i = 0; i < 4; i++)
#pragma unroll
        for (int r = 0; r < 2; r++) {
          hv[r][2 * i] = hsub2_bf16(hv[r][2 * i], mb[r]);
          hv[r][2 * i + 1] = hsub2_bf16(hv[r][2 * i + 1], mb[r]);
          st_tag8(lnp[r] + i * 4096, hv[r][2 * i], hv[r][2 * i + 1], i == 0 ? tag : (hv[r][2 * i] & 1u));
        }
      bar_arrive(NB_LN, 288);
      const uint32_t ones2 = ~(lds2(BAR(epoch, 0)).x >> 31);
      float rstd[2];
#pragma unroll
      for (int r = 0; r < 2; r++) {
        hv[r][0] &= ones2;
        rstd[r] = row_rstd(hv[r], mean[r] - bf_lo(mb[r]));
      }
      if (lane == 0)
        st_tag(&scr->ST[rb * 64 + 8 * f + warp], make_uint4(mb[0] << 16, __float_as_uint(rstd[0]), mb[1] << 16, __float_as_uint(rstd[1])), tag);
    }
    const int wgi = warp >> 2, wq = warp & 3;
    const int wr = wgi ^ (f >> 2) ^ 1, rt = 4 * wr + wq;
    uint4* const pbase = &scr->P[rb * 28 * 1024 + rt * 128 + lane];
    const uint32_t a_lo0 = desc_lo(sbase + wr * 8192, 16);
    const uint32_t ebar = lane == 0 ? BAR(empty1, 0) : RBAR(empty1, 0);
    float r0, r1;
    uint4 px[8], py[6];
    const int rh = wgi ^ kh ^ 1;
    const uint32_t fpb = BAR(fullP, 16 * rh);
    const uint4* const psrc = &scr->P[(rb2 * 28 + 14 * kh) * 1024 + (4 * rh + wq) * 128 + lane];
    const uint32_t pa0 = sbase + (4 * rh + wq) * 2048;
    uint4 pf[LAG2][4], ha[4][4];
    uint32_t rdy = 0, got0;
    {
      float acc[128];
#pragma unroll
      for (int i = 0; i < 128; i++) acc[i] = 0.f;
      const uint32_t b_lo0 = desc_lo(sbase + 8 * SLOT, 4096);
      const uint32_t t3 = clock32();
      if (WARM) {
        wg_fence();
#pragma unroll
        for (int i = 0; i < WARM; i++) wgmma_n256(acc, desc64(a_lo0 + 6 * 1024, HI128), desc64(b_lo0, HI128));
        wg_commit();
      }
      const uint4* const ap = &scr->LN[rb * 8 * 1024 + rt * 128 + lane];
      uint4 av[NLL][4];
      spin_until(t3 + POLL_DELAY3);
#pragma unroll
      for (int kb = 0; kb < NLL; kb++) ld_tag4_issue<32>(av[kb], ap + kb * 1024);
      const uint32_t lma = sbase + (16 * rt + (lane & 15)) * 128, stg = sbase + SM_X + warp * 2048;
      auto load_a = [&](int kb) {
#pragma unroll
        for (int ks = 0; ks < 4; ks++)
          asm volatile("ldmatrix.sync.aligned.m8n8.x4.shared.b16 {%0,%1,%2,%3}, [%4];"
                       : "=r"(ha[kb][ks].x), "=r"(ha[kb][ks].y), "=r"(ha[kb][ks].z), "=r"(ha[kb][ks].w)
                       : "r"((kb < NLL ? stg + (lane & 15) * 128 : lma + kb * SLOT) + (((2 * ks + (lane >> 4)) ^ (lane & 7)) * 16)) : "memory");
      };
      auto stash_a = [&](int kb) {
        ld_tag4_finish<32, true>(av[kb], ap + kb * 1024, tag);
#pragma unroll
        for (int i = 0; i < 4; i++) sts4(stg + (lane + 32 * i) * 16, av[kb][i].x, av[kb][i].y, av[kb][i].z, av[kb][i].w);
        __syncwarp();
      };
      stash_a(0);
      load_a(0);
#pragma unroll
      for (int n = 0; n < 8; n++) {
        const int kb = n >> 1, hh = n & 1;
        if (hh == 1 && kb + 1 < NLL) stash_a(kb + 1);
        if (!rdy) {
          if (hh == 1 && kb + 1 >= NLL && kb < 3) mbar_wait(BAR(fullA, kb + 1));
          mbar_wait(BAR(full1, n));
        }
        const uint32_t bl = b_lo0 + ((n + 2) % 6) * 1024;
        wg_fence();
        if (hh == 1 && kb < 3) load_a(kb + 1);
        rdy = mbar_test(BAR(full1, n + 1));
        if (hh == 0 && kb + 1 >= NLL && kb < 3) rdy &= mbar_test(BAR(fullA, kb + 1));
        const uint4 &a0 = ha[kb][2 * hh], &a1 = ha[kb][2 * hh + 1];
        wgmma_rs_n256(acc, a0.x, a0.y, a0.z, a0.w, desc64(bl, HI128), n != 0 ? 1 : ~ones);
        wgmma_rs_n256(acc, a1.x, a1.y, a1.z, a1.w, desc64(bl + 128, HI128));
        wg_commit();
        if (hh == 1 && lane < 2) mbar_arrive_remote(ebar + (uint32_t)(offsetof(Bars, freeA) - offsetof(Bars, empty1)) + 8 * kb);
        wg_wait<1>();
        if (n != 0 && lane < 2) mbar_arrive_remote(ebar + 8 * (n - 1));
      }
      uint32_t slot = 4;
#pragma unroll 1
      for (int kb = 4; kb < 8; kb++) {
        mbar_wait(BAR(fullA, kb));
#pragma unroll
        for (int hh = 0; hh < 2; hh++) {
          if (hh == ((16 - LAGX) & 1) && kb == ((16 - LAGX) >> 1) && wgi == 1) bar_sync(NB_LAG, 256);
          mbar_wait(BAR(full1, 2 * kb + hh));
          const uint32_t al = a_lo0 + kb * 1024 + hh * 4, bl = b_lo0 + slot * 1024;
          wg_fence();
          wgmma_n256(acc, desc64(al, HI128), desc64(bl, HI128));
          wgmma_n256(acc, desc64(al + 2, HI128), desc64(bl + 128, HI128));
          wg_commit();
          if (hh == 1 && kb == 7 && wgi == 0) bar_arrive(NB_LAG, 256);
          wg_wait<1>();
          if (lane < 2) mbar_arrive_remote(ebar + 8 * (2 * kb + hh - 1));
          if (++slot == 6) slot = 0;
        }
      }
      mbar_wait(BAR(sbar, 0));
      r0 = __uint_as_float(lds2(sstat + (16 * rt + g) * 8).y);
      r1 = __uint_as_float(lds2(sstat + (16 * rt + g + 8) * 8).y);
      wg_wait<0>();
      if (lane < 2) mbar_arrive_remote(ebar + 8 * 15);
      make_p<8, false>(acc, r0, r1, px, pbase, 0, tag);
    }
    {
      float acc[96];
#pragma unroll
      for (int i = 0; i < 96; i++) acc[i] = 0.f;
      const uint32_t b_lo0 = desc_lo(sbase, 2048);
      uint4* const pdst = pbase + ((7 * f + 3 * (f & 1)) >> 1) * 1024;
      auto stage_y = [&](int k) {
        if (k < 4) mbar_wait_bounded(BAR(full1, 16 + k));
        else mbar_wait(BAR(full1, 16 + k));
        const uint32_t al = a_lo0 + (4 + (k >> 1)) * 1024 + (k & 1) * 4, bl = b_lo0 + (k < 5 ? k * 768 : 8192 + (k - 5) * 768);
        wg_fence();
        wgmma_n192(acc, desc64(al, HI128), desc64(bl, HI64));
        wgmma_n192(acc, desc64(al + 2, HI128), desc64(bl + 64, HI64));
        wg_commit();
      };
#pragma unroll
      for (int k = 0; k < 4; k++) {
        stage_y(k);
        st_tag(pdst + (k >> 1) * 1024 + (k & 1) * 64, px[2 * k], tag);
        st_tag(pdst + (k >> 1) * 1024 + (k & 1) * 64 + 32, px[2 * k + 1], tag);
        if (k == 3 && lane == 0) red_relaxed(&scr->cnt[(C_PX + rb) * 32 + (f >> 2)]);
        wg_wait<1>();
        if (k != 0 && lane < 2) mbar_arrive_remote(ebar + 8 * (15 + k));
      }
#pragma unroll 1
      for (int k = 4; k < 8; k++) {
        stage_y(k);
        wg_wait<1>();
        if (k != 0 && lane < 2) mbar_arrive_remote(ebar + 8 * (15 + k));
      }
      rdy = 0;
#pragma unroll
      for (int k = 8; k < 16; k++) {
        if (k == 16 - LAGY && wgi == 1) bar_sync(NB_LAG, 256);
        if (!rdy) mbar_wait(BAR(full1, 16 + k));
        const uint32_t bl = b_lo0 + 8192 + ((k - 5) & 7) * 768;
        const uint4 &a0 = ha[(k - 8) >> 1][2 * (k & 1)], &a1 = ha[(k - 8) >> 1][2 * (k & 1) + 1];
        wg_fence();
        if (k < 15) rdy = mbar_test(BAR(full1, 17 + k));
        wgmma_rs_n192(acc, a0.x, a0.y, a0.z, a0.w, desc64(bl, HI64));
        wgmma_rs_n192(acc, a1.x, a1.y, a1.z, a1.w, desc64(bl + 64, HI64));
        wg_commit();
        if (k == 15 && wgi == 0) bar_arrive(NB_LAG, 256);
        wg_wait<1>();
        if (lane < 2) mbar_arrive_remote(ebar + 8 * (15 + k));
      }
      got0 = __all_sync(0xffffffffu, mbar_test(fpb));
      if (got0) {
#pragma unroll
        for (int kk = 0; kk < 4; kk++) pf[0][kk] = lds4(pa0 + 3 * SLOT + kk * 512 + lane * 16);
      }
      wg_wait<0>();
      if (lane < 2) mbar_arrive_remote(ebar + 8 * 31);
      const int ks0 = 14 * f + ((f & 1) ? 0 : 8);
      auto reread = [&]() {
        asm volatile("ld.volatile.shared.f32 %0, [%2+4]; ld.volatile.shared.f32 %1, [%2+68];" : "=f"(r0), "=f"(r1) : "r"(sstat + (16 * rt + g) * 8) : "memory");
      };
      make_p<6, true, 0, 2>(acc, r0, r1, py, pbase, ks0, tag);
      reread();
      make_p<6, true, 2, 4>(acc, r0, r1, py, pbase, ks0, tag);
      if (lane == 0) red_relaxed(&scr->cnt[(C_PY + rb) * 32 + 4 * wgi + (f >> 1)]);
      reread();
      rdy = mbar_test(BAR(full2, 0)) & mbar_test(fpb + 8);
      make_p<6, true, 4, 6>(acc, r0, r1, py, pbase, ks0, tag);
    }
    {
      float acc[64];
      const uint32_t b2_lo0 = desc_lo(sbase, 8192);
      const uint32_t pbar = rh == rk ? BAR(emptyP, 0) : RBAR(emptyP, 0);
      if (!got0) {
        mbar_wait(fpb);
#pragma unroll
        for (int kk = 0; kk < 4; kk++) pf[0][kk] = lds4(pa0 + 3 * SLOT + kk * 512 + lane * 16);
      }
      constexpr int S1 = 14 - LAG2;
      auto fetch2 = [&](int s) {
#pragma unroll
        for (int kk = 0; kk < 4; kk++) pf[s % LAG2][kk] = lds4(pa0 + (uint32_t)((PSLOT >> (4 * s)) & 15) * SLOT + kk * 512 + lane * 16);
      };
      auto check2 = [&](int s) {
        ld_tag4_finish<32>(pf[s % LAG2], psrc + (int)((KORDER >> (4 * s)) & 15) * 1024, tag);
        if (s < 9 && lane == 0) mbar_arrive_remote(pbar + 8 * s);
      };
      auto mma2 = [&](int s) {
        const uint4 (&a)[4] = pf[s % LAG2];
        const uint32_t bl = b2_lo0 + (uint32_t)((BSLOT >> (4 * s)) & 15) * 1024;
#pragma unroll
        for (int kk = 0; kk < 4; kk++) wgmma_rs_n128(acc, a[kk].x, a[kk].y, a[kk].z, a[kk].w, desc64(bl + kk * 128, HI128), s + kk != 0);
      };
      auto stage2 = [&](int s) {
        check2(s);
        if (s >= 2) {
          wg_wait<1>();
          if (s <= 7 && lane == 0) mbar_arrive(BAR(empty2, s - 2));
        }
        if (!rdy) {
          if (s < 13) mbar_wait(fpb + 8 * (s + 1));
          mbar_wait(BAR(full2, s));
        }
        wg_fence();
        if (s < 13) {
          fetch2(s + 1);
          rdy = mbar_test(BAR(full2, s + 1));
          if (s < 12) rdy &= mbar_test(fpb + 8 * (s + 2));
        }
        mma2(s);
        wg_commit();
      };
#pragma unroll
      for (int s = 0; s < S1; s++) stage2(s);
      if (wgi == 0) {
#pragma unroll
        for (int s = S1; s < 14; s++) stage2(s);
        bar_arrive(NB_LAG, 256);
        uint4* const dst = &scr->Z1[(tid >> 3) * 1024 + (c ^ 4) * 8 + (tid & 7)];
        wg_wait<0>();
#pragma unroll
        for (int i = 0; i < 8; i++)
          st_tag(dst + i * 16384, make_uint4(pack2(acc[8 * i], acc[8 * i + 1]), pack2(acc[8 * i + 2], acc[8 * i + 3]) | 1u,
                                           pack2(acc[8 * i + 4], acc[8 * i + 5]), pack2(acc[8 * i + 6], acc[8 * i + 7])), tag);
      } else {
        check2(S1);
        wg_wait<0>();
        if (S1 - 2 <= 5 && lane == 0) mbar_arrive(BAR(empty2, S1 - 2));
#pragma unroll
        for (int s = S1 + 1; s < 14; s++) {
          mbar_wait(fpb + 8 * s);
          fetch2(s);
          check2(s);
        }
        bar_sync(NB_LAG, 256);
        const uint32_t t4 = clock32();
        wg_fence();
#pragma unroll
        for (int s = S1; s < 14; s++) mma2(s);
        wg_commit();
        spin_until(t4 + POLL_DELAY4);
        uint4 pv[2][4];
        const uint4* const xsrc = &scr->Z1[((tid & 127) >> 3) * 1024 + c * 8 + (tid & 7)];
        ld_tag4_issue<16384>(pv[0], xsrc);
        ld_tag4_issue<16384>(pv[1], xsrc + 65536);
        uint32_t w[32];
        {
          const uint32_t m0 = __byte_perm(lds2(sstat + 1024 + (16 * wq + g) * 8).x, 0, 0x3232);
          const uint32_t m1 = __byte_perm(lds2(sstat + 1024 + (16 * wq + g + 8) * 8).x, 0, 0x3232);
          const uint32_t hb = sbase + 13 * SLOT + (16 * wq + (lane & 15)) * 128;
          const uint32_t mk = ((t & 1) == 0 && nq == 0) ? ~1u : ~0u;
          mbar_wait(BAR(hbar, 0));
#pragma unroll
          for (int i = 0; i < 8; i++) {
            asm volatile("ldmatrix.sync.aligned.m8n8.x4.shared.b16 {%0,%1,%2,%3}, [%4];"
                         : "=r"(w[4 * i]), "=r"(w[4 * i + 1]), "=r"(w[4 * i + 2]), "=r"(w[4 * i + 3])
                         : "r"(hb + (i >> 2) * 8192 + (((2 * (i & 3) + (lane >> 4)) ^ (lane & 7)) * 16)) : "memory");
#pragma unroll
            for (int e = 0; e < 4; e++) w[4 * i + e] = hadd2_bf16(w[4 * i + e] & mk, (e & 1) ? m1 : m0);
          }
        }
        wg_wait<0>();
#pragma unroll
        for (int i = 0; i < 32; i++) w[i] = hadd2_bf16(w[i], pack2(acc[2 * i], acc[2 * i + 1]));
#pragma unroll 1
        while (!__all_sync(0xffffffffu, pv[0][0].y & pv[0][1].y & pv[0][2].y & pv[0][3].y & pv[1][0].y & pv[1][1].y & pv[1][2].y & pv[1][3].y & 1u)) {
          ld_tag4_issue<16384>(pv[0], xsrc);
          ld_tag4_issue<16384>(pv[1], xsrc + 65536);
        }
#pragma unroll
        for (int i = 0; i < 8; i++) {
          const uint4& p = pv[i >> 2][i & 3];
          asm volatile("stmatrix.sync.aligned.m8n8.x4.shared.b16 [%0], {%1,%2,%3,%4};"
                       ::"r"(pa0 + (11 + ((lane >> 3) & 1)) * SLOT + (lane & 7) * 256 + (((2 * i + (lane >> 4)) ^ (lane & 7)) * 16)),
                         "r"(hadd2_bf16(w[4 * i], p.x & ~1u)), "r"(hadd2_bf16(w[4 * i + 1], p.y & ~1u)), "r"(hadd2_bf16(w[4 * i + 2], p.z)),
                         "r"(hadd2_bf16(w[4 * i + 3], p.w)) : "memory");
        }
        __syncwarp();
        uint4* const dst = reinterpret_cast<uint4*>(out) + (16 * (c >> 4) + 2 * (4 * rh + wq) + (rb2 & 1) + 128 * (lane >> 4)) * 64 + nq * 16 + (lane & 15);
#pragma unroll
        for (int i = 0; i < 8; i++) {
          const int r = 2 * (i & 3) + (lane >> 4);
          dst[i * 256 * 64] = lds4(pa0 + (11 + (i >> 2)) * SLOT + r * 256 + (((lane & 15) ^ r) * 16));
        }
      }
      if (lane == 0) mbar_arrive(BAR(done, 0));
    }
  }
#undef BAR
#undef TOFF
#undef RBAR
}

typedef CUresult (*EncodeFn)(CUtensorMap*, CUtensorMapDataType, cuuint32_t, void*, const cuuint64_t*, const cuuint64_t*,
                             const cuuint32_t*, const cuuint32_t*, CUtensorMapInterleave, CUtensorMapSwizzle,
                             CUtensorMapL2promotion, CUtensorMapFloatOOBfill);

}

extern "C" void kernel_launch(void* const* d_in, const int* in_sizes, int n_in, void* d_out, int out_size) {
  (void)in_sizes; (void)n_in; (void)out_size;
  static EncodeFn encode = nullptr;
  static void *tab = nullptr, *scr = nullptr;
  if (!encode) {
    void* fn = nullptr;
    cudaDriverEntryPointQueryResult qr;
    cudaGetDriverEntryPoint("cuTensorMapEncodeTiled", &fn, cudaEnableDefault, &qr);
    encode = (EncodeFn)fn;
    cudaGetSymbolAddress(&tab, g_tab);
    cudaGetSymbolAddress(&scr, g_scr);
    cudaFuncSetAttribute(fused_kernel, cudaFuncAttributeMaxDynamicSharedMemorySize, SMEM_BYTES);
  }
  CUtensorMap tmGX, tmUX, tmGY, tmUY, tmD, tmWR, tmWI;
  const cuuint32_t es[5] = {1, 1, 1, 1, 1};
  auto enc = [&](CUtensorMap* m, void* p, int rank, const cuuint64_t* gd, const cuuint64_t* gs, const cuuint32_t* bd,
                 CUtensorMapSwizzle sw, CUtensorMapL2promotion pr) {
    encode(m, CU_TENSOR_MAP_DATA_TYPE_BFLOAT16, rank, p, gd, gs, bd, es, CU_TENSOR_MAP_INTERLEAVE_NONE, sw, pr,
           CU_TENSOR_MAP_FLOAT_OOB_FILL_NONE);
  };
  {
    const cuuint64_t gd[3] = {64, 512, 28}, gs[2] = {3584, 128};
    const cuuint32_t bd[3] = {64, 32, 2};
    enc(&tmGX, d_in[4], 3, gd, gs, bd, CU_TENSOR_MAP_SWIZZLE_128B, CU_TENSOR_MAP_L2_PROMOTION_L2_256B);
    enc(&tmUX, d_in[5], 3, gd, gs, bd, CU_TENSOR_MAP_SWIZZLE_128B, CU_TENSOR_MAP_L2_PROMOTION_L2_256B);
  }
  {
    const cuuint64_t gd[3] = {32, 512, 56}, gs[2] = {3584, 64};
    const cuuint32_t bd[3] = {32, 32, 3};
    enc(&tmGY, d_in[4], 3, gd, gs, bd, CU_TENSOR_MAP_SWIZZLE_64B, CU_TENSOR_MAP_L2_PROMOTION_L2_128B);
    enc(&tmUY, d_in[5], 3, gd, gs, bd, CU_TENSOR_MAP_SWIZZLE_64B, CU_TENSOR_MAP_L2_PROMOTION_L2_128B);
  }
  {
    const cuuint64_t gd[3] = {64, 1792, 8}, gs[2] = {1024, 128};
    const cuuint32_t bd[3] = {64, 64, 2};
    enc(&tmD, d_in[6], 3, gd, gs, bd, CU_TENSOR_MAP_SWIZZLE_128B, CU_TENSOR_MAP_L2_PROMOTION_L2_256B);
  }
  {
    const cuuint64_t gd[3] = {4112, 8, 16}, gs[2] = {16 * 8224, 8224};
    const cuuint32_t bd[3] = {40, 8, 16};
    enc(&tmWR, d_in[1], 3, gd, gs, bd, CU_TENSOR_MAP_SWIZZLE_NONE, CU_TENSOR_MAP_L2_PROMOTION_NONE);
    enc(&tmWI, d_in[2], 3, gd, gs, bd, CU_TENSOR_MAP_SWIZZLE_NONE, CU_TENSOR_MAP_L2_PROMOTION_NONE);
  }
  fused_kernel<<<NCTA, NTHREADS, SMEM_BYTES>>>((const __nv_bfloat16*)d_in[0], (const Tables*)tab, (Scratch*)scr,
                                               (__nv_bfloat16*)d_out, (const char*)d_in[4], (const char*)d_in[5],
                                               (const char*)d_in[6], tmWR, tmWI, tmGX, tmUX, tmGY, tmUY, tmD);
}
```

```cpp
#include <cuda_runtime.h>
#include <cuda_bf16.h>
#include <cuda.h>
#include <stdint.h>

namespace {

constexpr int NCTA = 128;
constexpr int NTHREADS = 384;
constexpr int SLOT = 16384;
constexpr int SMEM_BYTES = 14 * SLOT + 3072;
constexpr int SPIN_LIMIT = 1 << 22;

struct Scratch {
  uint4 Z1[128 * 1024];
  uint4 LN[16 * 8 * 1024];
  uint4 P[16 * 28 * 1024];
  uint4 ST[1024];
  unsigned cnt[64 * 32];
};
__device__ __align__(1024) Scratch g_scr;

constexpr double ccos(int i, int n) {
  i &= n - 1;
  if (i > n / 2) i = n - i;
  if (4 * i == n) return 0.0;
  const bool neg = 4 * i > n;
  if (neg) i = n / 2 - i;
  const double a = 6.283185307179586476925 * i / n, a2 = a * a;
  double term = 1.0, sum = 1.0;
  for (int k = 1; k < 14; k++) { term *= -a2 / ((2 * k - 1) * (2 * k)); sum += term; }
  return neg ? -sum : sum;
}
constexpr double csin(int i, int n) { return ccos(i - n / 4, n); }
constexpr unsigned fbits(double v, int mant) {
  if (v == 0.0) return 0;
  const unsigned sg = v < 0 ? 1u : 0u;
  if (v < 0) v = -v;
  int e = 127;
  while (v < 1.0) { v *= 2.0; e--; }
  const unsigned m = (unsigned)((v - 1.0) * (double)(1u << mant) + 0.5);
  return (sg << (8 + mant)) + ((unsigned)e << mant) + m;
}
constexpr unsigned pkb(double lo, double hi) { return fbits(lo, 7) | (fbits(hi, 7) << 16); }
constexpr double fa_elem(int mt, int r, int n1) {
  const int k1 = 8 * mt + (r & 7);
  return r < 8 ? ccos(k1 * n1, 32) : k1 == 0 ? ccos(16 * n1, 32) : -csin(k1 * n1, 32);
}
constexpr unsigned cfrag_c(int idx, int n, int ri, double s = 1.0) {
  return ri ? pkb(-s * csin(idx, n), s * ccos(idx, n)) : pkb(s * ccos(idx, n), s * csin(idx, n));
}
struct Tables {
  unsigned fa[4][32][4];
  unsigned fb[4][32][4];
  unsigned tw1[6][32][4];
  unsigned f2[8][4][32][4];
  unsigned g2[8][4][32][4];
  unsigned gb[4][32][4];
  unsigned ga[4][32][4];
  unsigned tw3[4][32][4];
  unsigned f8[32][4], g8[32][4];
};
constexpr int T1_BYTES = 7168, T2_BYTES = 39936;
static_assert(sizeof(Tables) == T1_BYTES + T2_BYTES, "table size");
constexpr Tables make_tables() {
  Tables T = {};
  for (int l = 0; l < 32; l++) {
    const int g = l >> 2, t = l & 3;
    for (int a = 0; a < 2; a++)
      for (int b = 0; b < 2; b++) {
        for (int r = 0; r < 4; r++) {
          const int row = g + 8 * (r & 1), col = 2 * t + 8 * (r >> 1);
          T.fa[2 * a + b][l][r] = pkb(fa_elem(a, row, 16 * b + col), fa_elem(a, row, 16 * b + col + 1));
          T.ga[2 * a + b][l][r] = pkb(fa_elem(b, col, 16 * a + row), fa_elem(b, col + 1, 16 * a + row));
        }
        const double sg = b ? -1.0 : 1.0;
        for (int h = 0; h < 2; h++) {
          const int ri = g & 1, m = 2 * (g >> 1) + h, k2 = b ? 15 - m : m;
          const int pa = (8 * a + 2 * t) * k2, pb = (8 * a + 2 * t + 1) * k2;
          T.fb[2 * a + b][l][2 * h] = ri == 0 ? pkb(ccos(pa, 16), ccos(pb, 16)) : pkb(-sg * csin(pa, 16), -sg * csin(pb, 16));
          T.fb[2 * a + b][l][2 * h + 1] = ri == 0 ? pkb(csin(pa, 16), csin(pb, 16)) : pkb(sg * ccos(pa, 16), sg * ccos(pb, 16));
        }
        const int n2 = 4 * (g >> 1) + 2 * a + (g & 1);
        for (int h = 0; h < 2; h++) {
          const int p = n2 * (b ? 15 - 2 * t - h : 2 * t + h);
          T.gb[2 * a + b][l][2 * h] = pkb(ccos(p, 16), -sg * csin(p, 16));
          T.gb[2 * a + b][l][2 * h + 1] = pkb(csin(p, 16), sg * ccos(p, 16));
          const int k1 = 8 * b + 2 * t + h, q = n2 * (k1 == 0 ? 16 : k1);
          T.tw3[2 * a + b][l][2 * h] = fbits(ccos(q, 512), 23);
          T.tw3[2 * a + b][l][2 * h + 1] = fbits(csin(q, 512), 23);
        }
        const int p = (8 * a + 2 * t + b) * (g == 0 ? 16 : g);
        T.tw1[2 * a + b][l][0] = fbits(g == 0 ? 0.0 : ccos(p, 512), 23);
        T.tw1[2 * a + b][l][1] = fbits(g == 0 ? ccos(p, 512) : csin(p, 512), 23);
        T.tw1[2 * a + b][l][2] = fbits(g == 0 ? 0.0 : -csin(p, 512), 23);
        T.tw1[2 * a + b][l][3] = fbits(g == 0 ? -csin(p, 512) : ccos(p, 512), 23);
        T.tw1[4 + a][l][2 * b] = fbits(ccos((8 * a + 2 * t + b) * (g + 8), 512), 23);
        T.tw1[4 + a][l][2 * b + 1] = fbits(csin((8 * a + 2 * t + b) * (g + 8), 512), 23);
      }
    for (int i = 0; i < 4; i++) {
      const int p8 = (t + 4 * (i & 1)) * (4 * (i >> 1) + (g >> 1));
      T.f8[l][i] = cfrag_c(p8, 8, g & 1);
      T.g8[l][i] = cfrag_c(-p8, 8, g & 1, 1.0 / (1 << 19));
    }
    for (int w = 0; w < 8; w++)
      for (int i = 0; i < 16; i++) {
        const int kidx = t + 4 * (i & 1) + 8 * (i >> 3), nidx = 4 * ((i >> 1) & 3) + (g >> 1);
        T.f2[w][i >> 2][l][i & 3] = cfrag_c((8 * kidx + w) * nidx, 128, g & 1);
        T.g2[w][i >> 2][l][i & 3] = cfrag_c(-(8 * nidx + w) * kidx, 128, g & 1);
      }
  }
  return T;
}
__device__ const __align__(128) Tables g_tab = make_tables();

__device__ __forceinline__ void die() { asm volatile("st.global.u32 [%0], %1;" ::"l"(0ull), "r"(0) : "memory"); }
__device__ __forceinline__ uint32_t s2u(const void* p) { return (uint32_t)__cvta_generic_to_shared(p); }
__device__ __forceinline__ void mbar_init(uint32_t b, int c) { asm volatile("mbarrier.init.shared::cta.b64 [%0], %1;" ::"r"(b), "r"(c)); }
__device__ __forceinline__ void mbar_expect(uint32_t b, int bytes) {
  asm volatile("mbarrier.arrive.expect_tx.shared::cta.b64 _, [%0], %1;" ::"r"(b), "r"(bytes) : "memory");
}
__device__ __forceinline__ void mbar_arrive(uint32_t b) { asm volatile("mbarrier.arrive.shared::cta.b64 _, [%0];" ::"r"(b) : "memory"); }
__device__ __forceinline__ uint32_t mbar_try(uint32_t b, uint32_t parity) {
  uint32_t ok;
  asm volatile("{.reg .pred p; mbarrier.try_wait.parity.shared::cta.b64 p, [%1], %2; selp.u32 %0,1,0,p;}"
               : "=r"(ok) : "r"(b), "r"(parity) : "memory");
  return ok;
}
__device__ __forceinline__ uint32_t mbar_test(uint32_t b) {
  uint32_t ok;
  asm volatile("{.reg .pred p; mbarrier.test_wait.parity.shared::cta.b64 p, [%1], 0; selp.u32 %0,1,0,p;}" : "=r"(ok) : "r"(b) : "memory");
  return ok;
}
__device__ __forceinline__ void mbar_wait_bounded(uint32_t b) {
  int it = 0;
#pragma unroll 1
  while (!mbar_try(b, 0))
    if (++it > SPIN_LIMIT) { die(); break; }
}
__device__ __forceinline__ void mbar_wait(uint32_t b) {
  asm volatile("{.reg .pred p;\nW_%=: mbarrier.try_wait.parity.shared::cta.b64 p, [%0], 0;\n@!p bra W_%=;}" ::"r"(b) : "memory");
}
__device__ __forceinline__ void bar_sync(int id, int n) { asm volatile("bar.sync %0, %1;" ::"r"(id), "r"(n) : "memory"); }
__device__ __forceinline__ void bar_arrive(int id, int n) { asm volatile("bar.arrive %0, %1;" ::"r"(id), "r"(n) : "memory"); }
__device__ __forceinline__ void red_release(unsigned* p) { asm volatile("red.release.gpu.global.add.u32 [%0], 1;" ::"l"(p) : "memory"); }
__device__ __forceinline__ void red_relaxed(unsigned* p) { asm volatile("red.relaxed.gpu.global.add.u32 [%0], 1;" ::"l"(p) : "memory"); }
__device__ __forceinline__ unsigned ld_acquire(const unsigned* p) {
  unsigned v;
  asm volatile("ld.acquire.gpu.global.u32 %0, [%1];" : "=r"(v) : "l"(p) : "memory");
  return v;
}
__device__ __forceinline__ unsigned ld_relaxed(const unsigned* p) {
  unsigned v;
  asm volatile("ld.relaxed.gpu.global.u32 %0, [%1];" : "=r"(v) : "l"(p) : "memory");
  return v;
}
__device__ __forceinline__ void wait_counter(const unsigned* p, unsigned target) {
#pragma unroll 1
  while ((int)(ld_acquire(p) - target) < 0) {}
}
__device__ __forceinline__ void sts4(uint32_t a, uint32_t x, uint32_t y, uint32_t z, uint32_t w) {
  asm volatile("st.shared.v4.u32 [%0], {%1,%2,%3,%4};" ::"r"(a), "r"(x), "r"(y), "r"(z), "r"(w) : "memory");
}
__device__ __forceinline__ uint4 lds4(uint32_t a) {
  uint4 v;
  asm volatile("ld.shared.v4.u32 {%0,%1,%2,%3}, [%4];" : "=r"(v.x), "=r"(v.y), "=r"(v.z), "=r"(v.w) : "r"(a) : "memory");
  return v;
}
__device__ __forceinline__ uint32_t pack2(float lo, float hi) {
  uint32_t r;
  asm("cvt.rn.bf16x2.f32 %0, %1, %2;" : "=r"(r) : "f"(hi), "f"(lo));
  return r;
}
__device__ __forceinline__ float bf_lo(uint32_t v) { return __uint_as_float(v << 16); }
__device__ __forceinline__ uint32_t hadd2_bf16(uint32_t a, uint32_t b) {
  uint32_t r;
  asm("add.rn.bf16x2 %0, %1, %2;" : "=r"(r) : "r"(a), "r"(b));
  return r;
}
__device__ __forceinline__ void mma16816(float (&d)[4], uint32_t a0, uint32_t a1, uint32_t a2, uint32_t a3, uint32_t b0, uint32_t b1) {
  asm("mma.sync.aligned.m16n8k16.row.col.f32.bf16.bf16.f32 {%0,%1,%2,%3}, {%4,%5,%6,%7}, {%8,%9}, {%0,%1,%2,%3};"
      : "+f"(d[0]), "+f"(d[1]), "+f"(d[2]), "+f"(d[3])
      : "r"(a0), "r"(a1), "r"(a2), "r"(a3), "r"(b0), "r"(b1));
}
__device__ __forceinline__ void mma16816_z(float (&d)[4], uint32_t a0, uint32_t a1, uint32_t a2, uint32_t a3, uint32_t b0, uint32_t b1) {
  asm("{.reg .f32 z; mov.f32 z, 0f00000000;\n"
      "mma.sync.aligned.m16n8k16.row.col.f32.bf16.bf16.f32 {%0,%1,%2,%3}, {%4,%5,%6,%7}, {%8,%9}, {z,z,z,z};}"
      : "=f"(d[0]), "=f"(d[1]), "=f"(d[2]), "=f"(d[3])
      : "r"(a0), "r"(a1), "r"(a2), "r"(a3), "r"(b0), "r"(b1));
}
template <int N>
__device__ __forceinline__ void cs_frac(int idx, float& c, float& s) {
  int i = ((idx + N / 2) & (N - 1)) - N / 2;
  float a = (float)i * (6.283185307179586f / N);
  c = __cosf(a);
  s = __sinf(a);
}
template <int N>
__device__ __forceinline__ uint32_t cfrag(int idx, int ri) {
  float c, s;
  cs_frac<N>(idx, c, s);
  return ri ? pack2(-s, c) : pack2(c, s);
}
__device__ __forceinline__ uint32_t word(const uint4& v, int e) { return e == 0 ? v.x : e == 1 ? v.y : e == 2 ? v.z : v.w; }
__device__ __forceinline__ void cdft16(const uint4 (&A)[4], const uint4 (&F)[4], uint4 (&o)[4]) {
  float acc[2][4][4];
#pragma unroll
  for (int ks = 0; ks < 2; ks++)
#pragma unroll
    for (int p = 0; p < 2; p++)
#pragma unroll
      for (int v = 0; v < 4; v++) {
        const uint4& a = A[2 * ks + p];
        const uint32_t b0 = word(F[ks * 2 + (v >> 1)], (v & 1) * 2), b1 = word(F[ks * 2 + (v >> 1)], (v & 1) * 2 + 1);
        if (ks == 0) mma16816_z(acc[p][v], a.x, a.y, a.z, a.w, b0, b1);
        else mma16816(acc[p][v], a.x, a.y, a.z, a.w, b0, b1);
      }
#pragma unroll
  for (int v = 0; v < 4; v++)
    o[v] = make_uint4(pack2(acc[0][v][0], acc[0][v][1]), pack2(acc[0][v][2], acc[0][v][3]),
                      pack2(acc[1][v][0], acc[1][v][1]), pack2(acc[1][v][2], acc[1][v][3]));
}
__device__ __forceinline__ void lds_frag(uint4& f0, uint4& f1, uint32_t a0, uint32_t a1) {
  asm volatile("ld.volatile.shared.v2.u32 {%0,%1}, [%8]; ld.volatile.shared.v2.u32 {%2,%3}, [%9];\n"
               "ld.volatile.shared.v2.u32 {%4,%5}, [%8+8]; ld.volatile.shared.v2.u32 {%6,%7}, [%9+8];"
               : "=r"(f0.x), "=r"(f0.y), "=r"(f0.z), "=r"(f0.w), "=r"(f1.x), "=r"(f1.y), "=r"(f1.z), "=r"(f1.w) : "r"(a0), "r"(a1) : "memory");
}
__device__ __forceinline__ void reg_frag(uint4 (&q)[4], uint32_t ones) {
#pragma unroll
  for (int ks = 0; ks < 2; ks++) {
    const uint4 a = q[2 * ks], b = q[2 * ks + 1];
    q[2 * ks] = make_uint4(a.x, a.y, b.x & ones, b.y & ones);
    q[2 * ks + 1] = make_uint4(a.z & ones, a.w & ones, b.z, b.w);
  }
}
__device__ __forceinline__ void st_tag(uint4* p, const uint4& v, uint32_t tag) {
  asm volatile("st.relaxed.gpu.global.v4.b32 [%0], {%1,%2,%3,%4};"
               ::"l"(p), "r"((v.x & ~1u) | tag), "r"(v.y), "r"(v.z), "r"(v.w) : "memory");
}
__device__ __forceinline__ void st_tag8(void* p, uint32_t x, uint32_t y, uint32_t tag) {
  asm volatile("st.relaxed.gpu.global.v2.b32 [%0], {%1,%2};" ::"l"(p), "r"((x & ~1u) | tag), "r"(y) : "memory");
}
__device__ __forceinline__ uint4 ld_b128(const uint4* p) {
  uint4 v;
  asm volatile("ld.relaxed.gpu.global.v4.b32 {%0,%1,%2,%3}, [%4];"
               : "=r"(v.x), "=r"(v.y), "=r"(v.z), "=r"(v.w) : "l"(p) : "memory");
  return v;
}
template <int STRIDE>
__device__ __forceinline__ void ld_tag4_issue(uint4 (&q)[4], const uint4* p) {
#pragma unroll
  for (int i = 0; i < 4; i++) q[i] = ld_b128(p + i * STRIDE);
}
__device__ __forceinline__ uint32_t tag_miss(uint32_t a, uint32_t b, uint32_t c, uint32_t d, uint32_t tag) {
  uint32_t r;
  asm("{.reg .b32 u, v; lop3.b32 u, %1, %2, %5, 0x7e; lop3.b32 v, %3, %4, %5, 0x7e; lop3.b32 %0, u, v, 1, 0xa8;}"
      : "=r"(r) : "r"(a), "r"(b), "r"(c), "r"(d), "r"(tag));
  return r;
}
template <int STRIDE, bool HALVES = false>
__device__ __forceinline__ void ld_tag4_finish(uint4 (&q)[4], const uint4* p, uint32_t tag) {
  int it = 0;
#pragma unroll 1
  while (__any_sync(0xffffffffu, tag_miss(q[0].x, q[1].x, q[2].x, q[3].x, tag) | (HALVES ? tag_miss(q[0].z, q[1].z, q[2].z, q[3].z, tag) : 0u))) {
    ld_tag4_issue<STRIDE>(q, p);
    if (++it > SPIN_LIMIT) { die(); break; }
  }
#pragma unroll
  for (int i = 0; i < 4; i++) {
    asm volatile("and.b32 %0, %0, 0xfffffffe;" : "+r"(q[i].x));
    if (HALVES) q[i].z &= ~1u;
  }
}
__device__ __forceinline__ float quad_sum(const uint32_t (&a)[8]) {
  float d[4];
  mma16816_z(d, a[0], a[1], a[2], a[3], 0x3f803f80u, 0x3f803f80u);
  mma16816(d, a[4], a[5], a[6], a[7], 0x3f803f80u, 0x3f803f80u);
  return d[0] + d[2];
}
__device__ __forceinline__ float sum_groups(float v) {
  v += __shfl_xor_sync(0xffffffffu, v, 4);
  v += __shfl_xor_sync(0xffffffffu, v, 8);
  v += __shfl_xor_sync(0xffffffffu, v, 16);
  return v;
}
__device__ __forceinline__ uint32_t hsub2_bf16(uint32_t a, uint32_t b) {
  uint32_t r;
  asm("sub.rn.bf16x2 %0, %1, %2;" : "=r"(r) : "r"(a), "r"(b));
  return r;
}
__device__ __forceinline__ float row_rstd(const uint32_t (&c)[8], float delta) {
  uint32_t s[8];
#pragma unroll
  for (int i = 0; i < 8; i++) asm("mul.rn.bf16x2 %0, %1, %1;" : "=r"(s[i]) : "r"(c[i]));
  return rsqrtf(fmaxf(fmaf(-delta, delta, sum_groups(quad_sum(s)) * (1.f / 512.f)), 0.f) + 1e-5f);
}
__device__ __forceinline__ uint64_t desc64(uint32_t lo, uint32_t hi) {
  uint64_t d;
  asm("mov.b64 %0, {%1, %2};" : "=l"(d) : "r"(lo), "r"(hi));
  return d;
}
constexpr uint32_t desc_hi(uint32_t sbo, uint32_t swz) { return (sbo >> 4) | (swz << 30); }
__device__ __forceinline__ uint32_t desc_lo(uint32_t addr, uint32_t lbo) { return ((addr & 0x3FFFF) >> 4) | ((lbo >> 4) << 16); }
__device__ __forceinline__ void cp_async16(uint32_t dst, const void* src) {
  asm volatile("cp.async.cg.shared.global [%0], [%1], 16;" ::"r"(dst), "l"(src) : "memory");
}
__device__ __forceinline__ uint2 lds2(uint32_t a) {
  uint2 v;
  asm volatile("ld.shared.v2.u32 {%0,%1}, [%2];" : "=r"(v.x), "=r"(v.y) : "r"(a) : "memory");
  return v;
}
__device__ __forceinline__ uint32_t lds_u16(uint32_t a) {
  uint16_t v;
  asm volatile("ld.shared.u16 %0, [%1];" : "=h"(v) : "r"(a) : "memory");
  return v;
}
__device__ __forceinline__ void wg_fence() { asm volatile("wgmma.fence.sync.aligned;" ::: "memory"); }
__device__ __forceinline__ void wg_commit() { asm volatile("wgmma.commit_group.sync.aligned;" ::: "memory"); }
template <int N>
__device__ __forceinline__ void wg_wait() { asm volatile("wgmma.wait_group.sync.aligned %0;" ::"n"(N) : "memory"); }
__device__ __forceinline__ void bulk_load(uint32_t dst, const void* src, int bytes, uint32_t bar) {
  asm volatile("cp.async.bulk.shared::cluster.global.mbarrier::complete_tx::bytes [%0], [%1], %2, [%3];"
               ::"r"(dst), "l"(src), "r"(bytes), "r"(bar) : "memory");
}
__device__ __forceinline__ void bulk_load_mc(uint32_t dst, const void* src, int bytes, uint32_t bar) {
  asm volatile("cp.async.bulk.shared::cluster.global.mbarrier::complete_tx::bytes.multicast::cluster [%0], [%1], %2, [%3], %4;"
               ::"r"(dst), "l"(src), "r"(bytes), "r"(bar), "h"((uint16_t)3) : "memory");
}
__device__ __forceinline__ void tma3(uint32_t dst, const CUtensorMap* tm, uint32_t bar, int c0, int c1, int c2) {
  asm volatile("cp.async.bulk.tensor.3d.shared::cluster.global.mbarrier::complete_tx::bytes [%0], [%1, {%3,%4,%5}], [%2];"
               ::"r"(dst), "l"(tm), "r"(bar), "r"(c0), "r"(c1), "r"(c2) : "memory");
}
__device__ __forceinline__ void tma3_mc(uint32_t dst, const CUtensorMap* tm, uint32_t bar, int c1, int c2) {
  asm volatile("cp.async.bulk.tensor.3d.shared::cluster.global.mbarrier::complete_tx::bytes.multicast::cluster [%0], [%1, {%3,%4,%5}], [%2], %6;"
               ::"r"(dst), "l"(tm), "r"(bar), "r"(0), "r"(c1), "r"(c2), "h"((uint16_t)3) : "memory");
}
__device__ __forceinline__ void mbar_arrive_remote(uint32_t rb) {
  asm volatile("mbarrier.arrive.shared::cluster.b64 _, [%0];" ::"r"(rb) : "memory");
}
__device__ __forceinline__ uint4 ldg_ca4(const void* p) {
  uint4 v;
  asm volatile("ld.global.ca.v4.u32 {%0,%1,%2,%3}, [%4];" : "=r"(v.x), "=r"(v.y), "=r"(v.z), "=r"(v.w) : "l"(p) : "memory");
  return v;
}
__device__ __forceinline__ float u2f(uint32_t v) { return __uint_as_float(v); }
__device__ __forceinline__ void mma_az(float (&d)[4], const uint4& a, uint32_t b0, uint32_t b1) { mma16816_z(d, a.x, a.y, a.z, a.w, b0, b1); }
__device__ __forceinline__ void mma_a(float (&d)[4], const uint4& a, uint32_t b0, uint32_t b1) { mma16816(d, a.x, a.y, a.z, a.w, b0, b1); }
__device__ __forceinline__ uint32_t clock32() {
  uint32_t v;
  asm volatile("mov.u32 %0, %%clock;" : "=r"(v) :: "memory");
  return v;
}
__device__ __forceinline__ float swiglu(float g, float u, float r) {
  float hg = (0.5f * r) * g, th;
  asm("tanh.approx.f32 %0, %1;" : "=f"(th) : "f"(hg));
  return fmaf(hg, th, hg) * (r * u);
}
__device__ __forceinline__ void l2_prefetch(const void* p, int bytes) {
  asm volatile("cp.async.bulk.prefetch.L2.global [%0], %1;" ::"l"(p), "r"(bytes) : "memory");
}

__device__ __forceinline__ void wgmma_n256(float (&d)[128], uint64_t da, uint64_t db, int sd = 1) {
  asm volatile("{.reg .pred p; setp.ne.b32 p, %130, 0;\n"
      "wgmma.mma_async.sync.aligned.m64n256k16.f32.bf16.bf16 {"
      "%0,%1,%2,%3,%4,%5,%6,%7,%8,%9,%10,%11,%12,%13,%14,%15,"
      "%16,%17,%18,%19,%20,%21,%22,%23,%24,%25,%26,%27,%28,%29,%30,%31,"
      "%32,%33,%34,%35,%36,%37,%38,%39,%40,%41,%42,%43,%44,%45,%46,%47,"
      "%48,%49,%50,%51,%52,%53,%54,%55,%56,%57,%58,%59,%60,%61,%62,%63,"
      "%64,%65,%66,%67,%68,%69,%70,%71,%72,%73,%74,%75,%76,%77,%78,%79,"
      "%80,%81,%82,%83,%84,%85,%86,%87,%88,%89,%90,%91,%92,%93,%94,%95,"
      "%96,%97,%98,%99,%100,%101,%102,%103,%104,%105,%106,%107,%108,%109,%110,%111,"
      "%112,%113,%114,%115,%116,%117,%118,%119,%120,%121,%122,%123,%124,%125,%126,%127"
      "}, %128, %129, p, 1, 1, 0, 1;}\n"
      : "+f"(d[0]),"+f"(d[1]),"+f"(d[2]),"+f"(d[3]),"+f"(d[4]),"+f"(d[5]),"+f"(d[6]),"+f"(d[7]),
        "+f"(d[8]),"+f"(d[9]),"+f"(d[10]),"+f"(d[11]),"+f"(d[12]),"+f"(d[13]),"+f"(d[14]),"+f"(d[15]),
        "+f"(d[16]),"+f"(d[17]),"+f"(d[18]),"+f"(d[19]),"+f"(d[20]),"+f"(d[21]),"+f"(d[22]),"+f"(d[23]),
        "+f"(d[24]),"+f"(d[25]),"+f"(d[26]),"+f"(d[27]),"+f"(d[28]),"+f"(d[29]),"+f"(d[30]),"+f"(d[31]),
        "+f"(d[32]),"+f"(d[33]),"+f"(d[34]),"+f"(d[35]),"+f"(d[36]),"+f"(d[37]),"+f"(d[38]),"+f"(d[39]),
        "+f"(d[40]),"+f"(d[41]),"+f"(d[42]),"+f"(d[43]),"+f"(d[44]),"+f"(d[45]),"+f"(d[46]),"+f"(d[47]),
        "+f"(d[48]),"+f"(d[49]),"+f"(d[50]),"+f"(d[51]),"+f"(d[52]),"+f"(d[53]),"+f"(d[54]),"+f"(d[55]),
        "+f"(d[56]),"+f"(d[57]),"+f"(d[58]),"+f"(d[59]),"+f"(d[60]),"+f"(d[61]),"+f"(d[62]),"+f"(d[63]),
        "+f"(d[64]),"+f"(d[65]),"+f"(d[66]),"+f"(d[67]),"+f"(d[68]),"+f"(d[69]),"+f"(d[70]),"+f"(d[71]),
        "+f"(d[72]),"+f"(d[73]),"+f"(d[74]),"+f"(d[75]),"+f"(d[76]),"+f"(d[77]),"+f"(d[78]),"+f"(d[79]),
        "+f"(d[80]),"+f"(d[81]),"+f"(d[82]),"+f"(d[83]),"+f"(d[84]),"+f"(d[85]),"+f"(d[86]),"+f"(d[87]),
        "+f"(d[88]),"+f"(d[89]),"+f"(d[90]),"+f"(d[91]),"+f"(d[92]),"+f"(d[93]),"+f"(d[94]),"+f"(d[95]),
        "+f"(d[96]),"+f"(d[97]),"+f"(d[98]),"+f"(d[99]),"+f"(d[100]),"+f"(d[101]),"+f"(d[102]),"+f"(d[103]),
        "+f"(d[104]),"+f"(d[105]),"+f"(d[106]),"+f"(d[107]),"+f"(d[108]),"+f"(d[109]),"+f"(d[110]),"+f"(d[111]),
        "+f"(d[112]),"+f"(d[113]),"+f"(d[114]),"+f"(d[115]),"+f"(d[116]),"+f"(d[117]),"+f"(d[118]),"+f"(d[119]),
        "+f"(d[120]),"+f"(d[121]),"+f"(d[122]),"+f"(d[123]),"+f"(d[124]),"+f"(d[125]),"+f"(d[126]),"+f"(d[127])
      : "l"(da), "l"(db), "r"(sd));
}
__device__ __forceinline__ void wgmma_n192(float (&d)[96], uint64_t da, uint64_t db) {
  asm volatile("wgmma.mma_async.sync.aligned.m64n192k16.f32.bf16.bf16 {"
      "%0,%1,%2,%3,%4,%5,%6,%7,%8,%9,%10,%11,%12,%13,%14,%15,"
      "%16,%17,%18,%19,%20,%21,%22,%23,%24,%25,%26,%27,%28,%29,%30,%31,"
      "%32,%33,%34,%35,%36,%37,%38,%39,%40,%41,%42,%43,%44,%45,%46,%47,"
      "%48,%49,%50,%51,%52,%53,%54,%55,%56,%57,%58,%59,%60,%61,%62,%63,"
      "%64,%65,%66,%67,%68,%69,%70,%71,%72,%73,%74,%75,%76,%77,%78,%79,"
      "%80,%81,%82,%83,%84,%85,%86,%87,%88,%89,%90,%91,%92,%93,%94,%95"
      "}, %96, %97, 1, 1, 1, 0, 1;\n"
      : "+f"(d[0]),"+f"(d[1]),"+f"(d[2]),"+f"(d[3]),"+f"(d[4]),"+f"(d[5]),"+f"(d[6]),"+f"(d[7]),
        "+f"(d[8]),"+f"(d[9]),"+f"(d[10]),"+f"(d[11]),"+f"(d[12]),"+f"(d[13]),"+f"(d[14]),"+f"(d[15]),
        "+f"(d[16]),"+f"(d[17]),"+f"(d[18]),"+f"(d[19]),"+f"(d[20]),"+f"(d[21]),"+f"(d[22]),"+f"(d[23]),
        "+f"(d[24]),"+f"(d[25]),"+f"(d[26]),"+f"(d[27]),"+f"(d[28]),"+f"(d[29]),"+f"(d[30]),"+f"(d[31]),
        "+f"(d[32]),"+f"(d[33]),"+f"(d[34]),"+f"(d[35]),"+f"(d[36]),"+f"(d[37]),"+f"(d[38]),"+f"(d[39]),
        "+f"(d[40]),"+f"(d[41]),"+f"(d[42]),"+f"(d[43]),"+f"(d[44]),"+f"(d[45]),"+f"(d[46]),"+f"(d[47]),
        "+f"(d[48]),"+f"(d[49]),"+f"(d[50]),"+f"(d[51]),"+f"(d[52]),"+f"(d[53]),"+f"(d[54]),"+f"(d[55]),
        "+f"(d[56]),"+f"(d[57]),"+f"(d[58]),"+f"(d[59]),"+f"(d[60]),"+f"(d[61]),"+f"(d[62]),"+f"(d[63]),
        "+f"(d[64]),"+f"(d[65]),"+f"(d[66]),"+f"(d[67]),"+f"(d[68]),"+f"(d[69]),"+f"(d[70]),"+f"(d[71]),
        "+f"(d[72]),"+f"(d[73]),"+f"(d[74]),"+f"(d[75]),"+f"(d[76]),"+f"(d[77]),"+f"(d[78]),"+f"(d[79]),
        "+f"(d[80]),"+f"(d[81]),"+f"(d[82]),"+f"(d[83]),"+f"(d[84]),"+f"(d[85]),"+f"(d[86]),"+f"(d[87]),
        "+f"(d[88]),"+f"(d[89]),"+f"(d[90]),"+f"(d[91]),"+f"(d[92]),"+f"(d[93]),"+f"(d[94]),"+f"(d[95])
      : "l"(da), "l"(db));
}
__device__ __forceinline__ void wgmma_rs_n128(float (&d)[64], uint32_t a0, uint32_t a1, uint32_t a2, uint32_t a3, uint64_t db, int sd = 1) {
  asm volatile("{.reg .pred p; setp.ne.b32 p, %69, 0;\n"
      "wgmma.mma_async.sync.aligned.m64n128k16.f32.bf16.bf16 {"
      "%0,%1,%2,%3,%4,%5,%6,%7,%8,%9,%10,%11,%12,%13,%14,%15,"
      "%16,%17,%18,%19,%20,%21,%22,%23,%24,%25,%26,%27,%28,%29,%30,%31,"
      "%32,%33,%34,%35,%36,%37,%38,%39,%40,%41,%42,%43,%44,%45,%46,%47,"
      "%48,%49,%50,%51,%52,%53,%54,%55,%56,%57,%58,%59,%60,%61,%62,%63"
      "}, {%64,%65,%66,%67}, %68, p, 1, 1, 1;}\n"
      : "+f"(d[0]),"+f"(d[1]),"+f"(d[2]),"+f"(d[3]),"+f"(d[4]),"+f"(d[5]),"+f"(d[6]),"+f"(d[7]),
        "+f"(d[8]),"+f"(d[9]),"+f"(d[10]),"+f"(d[11]),"+f"(d[12]),"+f"(d[13]),"+f"(d[14]),"+f"(d[15]),
        "+f"(d[16]),"+f"(d[17]),"+f"(d[18]),"+f"(d[19]),"+f"(d[20]),"+f"(d[21]),"+f"(d[22]),"+f"(d[23]),
        "+f"(d[24]),"+f"(d[25]),"+f"(d[26]),"+f"(d[27]),"+f"(d[28]),"+f"(d[29]),"+f"(d[30]),"+f"(d[31]),
        "+f"(d[32]),"+f"(d[33]),"+f"(d[34]),"+f"(d[35]),"+f"(d[36]),"+f"(d[37]),"+f"(d[38]),"+f"(d[39]),
        "+f"(d[40]),"+f"(d[41]),"+f"(d[42]),"+f"(d[43]),"+f"(d[44]),"+f"(d[45]),"+f"(d[46]),"+f"(d[47]),
        "+f"(d[48]),"+f"(d[49]),"+f"(d[50]),"+f"(d[51]),"+f"(d[52]),"+f"(d[53]),"+f"(d[54]),"+f"(d[55]),
        "+f"(d[56]),"+f"(d[57]),"+f"(d[58]),"+f"(d[59]),"+f"(d[60]),"+f"(d[61]),"+f"(d[62]),"+f"(d[63])
      : "r"(a0), "r"(a1), "r"(a2), "r"(a3), "l"(db), "r"(sd));
}
__device__ __forceinline__ void wgmma_rs_n256(float (&d)[128], uint32_t a0, uint32_t a1, uint32_t a2, uint32_t a3, uint64_t db, int sd = 1) {
  asm volatile("{.reg .pred p; setp.ne.b32 p, %133, 0;\n"
      "wgmma.mma_async.sync.aligned.m64n256k16.f32.bf16.bf16 {"
      "%0,%1,%2,%3,%4,%5,%6,%7,%8,%9,%10,%11,%12,%13,%14,%15,"
      "%16,%17,%18,%19,%20,%21,%22,%23,%24,%25,%26,%27,%28,%29,%30,%31,"
      "%32,%33,%34,%35,%36,%37,%38,%39,%40,%41,%42,%43,%44,%45,%46,%47,"
      "%48,%49,%50,%51,%52,%53,%54,%55,%56,%57,%58,%59,%60,%61,%62,%63,"
      "%64,%65,%66,%67,%68,%69,%70,%71,%72,%73,%74,%75,%76,%77,%78,%79,"
      "%80,%81,%82,%83,%84,%85,%86,%87,%88,%89,%90,%91,%92,%93,%94,%95,"
      "%96,%97,%98,%99,%100,%101,%102,%103,%104,%105,%106,%107,%108,%109,%110,%111,"
      "%112,%113,%114,%115,%116,%117,%118,%119,%120,%121,%122,%123,%124,%125,%126,%127"
      "}, {%128,%129,%130,%131}, %132, p, 1, 1, 1;}\n"
      : "+f"(d[0]),"+f"(d[1]),"+f"(d[2]),"+f"(d[3]),"+f"(d[4]),"+f"(d[5]),"+f"(d[6]),"+f"(d[7]),
        "+f"(d[8]),"+f"(d[9]),"+f"(d[10]),"+f"(d[11]),"+f"(d[12]),"+f"(d[13]),"+f"(d[14]),"+f"(d[15]),
        "+f"(d[16]),"+f"(d[17]),"+f"(d[18]),"+f"(d[19]),"+f"(d[20]),"+f"(d[21]),"+f"(d[22]),"+f"(d[23]),
        "+f"(d[24]),"+f"(d[25]),"+f"(d[26]),"+f"(d[27]),"+f"(d[28]),"+f"(d[29]),"+f"(d[30]),"+f"(d[31]),
        "+f"(d[32]),"+f"(d[33]),"+f"(d[34]),"+f"(d[35]),"+f"(d[36]),"+f"(d[37]),"+f"(d[38]),"+f"(d[39]),
        "+f"(d[40]),"+f"(d[41]),"+f"(d[42]),"+f"(d[43]),"+f"(d[44]),"+f"(d[45]),"+f"(d[46]),"+f"(d[47]),
        "+f"(d[48]),"+f"(d[49]),"+f"(d[50]),"+f"(d[51]),"+f"(d[52]),"+f"(d[53]),"+f"(d[54]),"+f"(d[55]),
        "+f"(d[56]),"+f"(d[57]),"+f"(d[58]),"+f"(d[59]),"+f"(d[60]),"+f"(d[61]),"+f"(d[62]),"+f"(d[63]),
        "+f"(d[64]),"+f"(d[65]),"+f"(d[66]),"+f"(d[67]),"+f"(d[68]),"+f"(d[69]),"+f"(d[70]),"+f"(d[71]),
        "+f"(d[72]),"+f"(d[73]),"+f"(d[74]),"+f"(d[75]),"+f"(d[76]),"+f"(d[77]),"+f"(d[78]),"+f"(d[79]),
        "+f"(d[80]),"+f"(d[81]),"+f"(d[82]),"+f"(d[83]),"+f"(d[84]),"+f"(d[85]),"+f"(d[86]),"+f"(d[87]),
        "+f"(d[88]),"+f"(d[89]),"+f"(d[90]),"+f"(d[91]),"+f"(d[92]),"+f"(d[93]),"+f"(d[94]),"+f"(d[95]),
        "+f"(d[96]),"+f"(d[97]),"+f"(d[98]),"+f"(d[99]),"+f"(d[100]),"+f"(d[101]),"+f"(d[102]),"+f"(d[103]),
        "+f"(d[104]),"+f"(d[105]),"+f"(d[106]),"+f"(d[107]),"+f"(d[108]),"+f"(d[109]),"+f"(d[110]),"+f"(d[111]),
        "+f"(d[112]),"+f"(d[113]),"+f"(d[114]),"+f"(d[115]),"+f"(d[116]),"+f"(d[117]),"+f"(d[118]),"+f"(d[119]),
        "+f"(d[120]),"+f"(d[121]),"+f"(d[122]),"+f"(d[123]),"+f"(d[124]),"+f"(d[125]),"+f"(d[126]),"+f"(d[127])
      : "r"(a0), "r"(a1), "r"(a2), "r"(a3), "l"(db), "r"(sd));
}
__device__ __forceinline__ void wgmma_rs_n192(float (&d)[96], uint32_t a0, uint32_t a1, uint32_t a2, uint32_t a3, uint64_t db) {
  asm volatile("wgmma.mma_async.sync.aligned.m64n192k16.f32.bf16.bf16 {"
      "%0,%1,%2,%3,%4,%5,%6,%7,%8,%9,%10,%11,%12,%13,%14,%15,"
      "%16,%17,%18,%19,%20,%21,%22,%23,%24,%25,%26,%27,%28,%29,%30,%31,"
      "%32,%33,%34,%35,%36,%37,%38,%39,%40,%41,%42,%43,%44,%45,%46,%47,"
      "%48,%49,%50,%51,%52,%53,%54,%55,%56,%57,%58,%59,%60,%61,%62,%63,"
      "%64,%65,%66,%67,%68,%69,%70,%71,%72,%73,%74,%75,%76,%77,%78,%79,"
      "%80,%81,%82,%83,%84,%85,%86,%87,%88,%89,%90,%91,%92,%93,%94,%95"
      "}, {%96,%97,%98,%99}, %100, 1, 1, 1, 1;\n"
      : "+f"(d[0]),"+f"(d[1]),"+f"(d[2]),"+f"(d[3]),"+f"(d[4]),"+f"(d[5]),"+f"(d[6]),"+f"(d[7]),
        "+f"(d[8]),"+f"(d[9]),"+f"(d[10]),"+f"(d[11]),"+f"(d[12]),"+f"(d[13]),"+f"(d[14]),"+f"(d[15]),
        "+f"(d[16]),"+f"(d[17]),"+f"(d[18]),"+f"(d[19]),"+f"(d[20]),"+f"(d[21]),"+f"(d[22]),"+f"(d[23]),
        "+f"(d[24]),"+f"(d[25]),"+f"(d[26]),"+f"(d[27]),"+f"(d[28]),"+f"(d[29]),"+f"(d[30]),"+f"(d[31]),
        "+f"(d[32]),"+f"(d[33]),"+f"(d[34]),"+f"(d[35]),"+f"(d[36]),"+f"(d[37]),"+f"(d[38]),"+f"(d[39]),
        "+f"(d[40]),"+f"(d[41]),"+f"(d[42]),"+f"(d[43]),"+f"(d[44]),"+f"(d[45]),"+f"(d[46]),"+f"(d[47]),
        "+f"(d[48]),"+f"(d[49]),"+f"(d[50]),"+f"(d[51]),"+f"(d[52]),"+f"(d[53]),"+f"(d[54]),"+f"(d[55]),
        "+f"(d[56]),"+f"(d[57]),"+f"(d[58]),"+f"(d[59]),"+f"(d[60]),"+f"(d[61]),"+f"(d[62]),"+f"(d[63]),
        "+f"(d[64]),"+f"(d[65]),"+f"(d[66]),"+f"(d[67]),"+f"(d[68]),"+f"(d[69]),"+f"(d[70]),"+f"(d[71]),
        "+f"(d[72]),"+f"(d[73]),"+f"(d[74]),"+f"(d[75]),"+f"(d[76]),"+f"(d[77]),"+f"(d[78]),"+f"(d[79]),
        "+f"(d[80]),"+f"(d[81]),"+f"(d[82]),"+f"(d[83]),"+f"(d[84]),"+f"(d[85]),"+f"(d[86]),"+f"(d[87]),
        "+f"(d[88]),"+f"(d[89]),"+f"(d[90]),"+f"(d[91]),"+f"(d[92]),"+f"(d[93]),"+f"(d[94]),"+f"(d[95])
      : "r"(a0), "r"(a1), "r"(a2), "r"(a3), "l"(db));
}


constexpr int C_LN = 0, C_PX = 16, C_PY = 32;
constexpr int NB_CONS = 1, NB_LN = 2, NB_LAG = 4, NB_INIT = 6, NB_RDY = 7;
constexpr int LAGX = 3;
constexpr int LAGY = 6;
constexpr int LAG2 = 5;
constexpr int NLL = 4;
constexpr int POLL_DELAY = 1200;
constexpr int POLL_DELAY2 = 1000;
constexpr int POLL_DELAY3 = 600;
constexpr int FILT_DELAY = 800;
constexpr int WARM = 4;
constexpr int ALEAD = 6;
constexpr int XTRIG = 20;
constexpr int HTRIG = 0;
constexpr int SM_E = 0, SM_X = 16384, SM_E2 = 32768, SM_W = 49152, SM_FC = 69632, SM_T = 73728 - T1_BYTES;
constexpr unsigned long long KORDER = 0xBA9432DC876510ull;
constexpr unsigned long long BSLOT = 0x52140A98D52140ull, PSLOT = 0xB763CB763CB763ull;
constexpr unsigned long long BDEP = 0xFFEC97531ull, PDEP = 0xBA754ull;
constexpr uint32_t HI128 = desc_hi(1024, 1), HI64 = desc_hi(512, 2);

struct Bars {
  uint64_t full1[32], empty1[32], full2[16], fullA[8], empty2[8], emptyP[9], sig, done, fullP[32], hbar, tbar, hint[3], sbar;
  uint32_t epoch, pad;
};

template <int NK, bool STORE, int J0 = 0, int J1 = NK>
__device__ __forceinline__ void make_p(const float (&acc)[NK * 16], float r0, float r1, uint4 (&p)[NK], uint4* pbase, int ks0, uint32_t tag) {
#pragma unroll
  for (int j = J0; j < J1; j++) {
    uint32_t w[4];
#pragma unroll
    for (int i = 0; i < 4; i++) {
      const int a = 8 * j + 2 * i, b = a + NK * 8;
      w[i] = pack2(swiglu(acc[a], acc[b], (i & 1) ? r1 : r0), swiglu(acc[a + 1], acc[b + 1], (i & 1) ? r1 : r0));
    }
    asm volatile("" : "+r"(w[0]), "+r"(w[1]), "+r"(w[2]), "+r"(w[3]));
    p[j] = make_uint4(w[0], w[1], w[2], w[3]);
    if (STORE) st_tag(pbase + ((ks0 + j) >> 2) * 1024 + ((ks0 + j) & 3) * 32, p[j], tag);
  }
}
__device__ __forceinline__ void spin_until(uint32_t t) {
  while ((int)(clock32() - t) < 0) {}
}

__global__ void __cluster_dims__(2, 1, 1) __launch_bounds__(NTHREADS, 1)
fused_kernel(const __nv_bfloat16* __restrict__ x, const Tables* __restrict__ tab, Scratch* __restrict__ scr,
             __nv_bfloat16* __restrict__ out, const char* __restrict__ wg_raw, const char* __restrict__ wu_raw,
             const char* __restrict__ wd_raw,
             const __grid_constant__ CUtensorMap tmWR, const __grid_constant__ CUtensorMap tmWI,
             const __grid_constant__ CUtensorMap tmGX, const __grid_constant__ CUtensorMap tmUX,
             const __grid_constant__ CUtensorMap tmGY, const __grid_constant__ CUtensorMap tmUY,
             const __grid_constant__ CUtensorMap tmD) {
  extern __shared__ __align__(1024) char smem_raw[];
  const uint32_t sbase = s2u(smem_raw);
  const uint32_t sbar = sbase + 14 * SLOT, sstat = sbar + 1408;
  const int tid = threadIdx.x, lane = tid & 31;
  const int c = blockIdx.x, rk = c & 1, f = (c >> 1) & 7, rb = 2 * (c >> 4) + rk;
  const int rb2 = 2 * (c >> 4) + (f >> 2), kh = (f >> 1) & 1, nq = 2 * (f & 1) + rk;
#define BAR(field, i) (sbar + (uint32_t)offsetof(Bars, field) + 8u * (i))
#define TOFF(field) (sbase + SM_T + (uint32_t)offsetof(Tables, field) + lane * 16)

  if (tid >= 256) {
    asm volatile("setmaxnreg.dec.sync.aligned.u32 40;");
    const int warp = __shfl_sync(0xffffffffu, tid >> 5, 0);
    if (lane == 0) {
      auto init = [&](uint32_t b, int n, int count, int bytes) {
#pragma unroll
        for (int i = 0; i < n; i++) mbar_init(b + 8 * i, count);
#pragma unroll
        for (int i = 0; i < (bytes ? n : 0); i++) mbar_expect(b + 8 * i, bytes);
      };
      if (warp == 8) {
        if (sbase & 1023) die();
        init(BAR(tbar, 0), 1, 1, T2_BYTES + 2 * 10240);
        init(BAR(hbar, 0), 1, 1, 16384);
        init(BAR(hint, 0), 3, 1, 0);
        init(BAR(sbar, 0), 1, 32, 0);
        init(BAR(empty2, 0), 19, 8, 0);
      } else if (warp == 9) {
        init(BAR(full1, 0), 16, 1, 16384);
        init(BAR(full1, 16), 16, 1, 12288);
      } else if (warp == 10) {
        init(BAR(fullP, 0), 30, 1, 8192);
      } else {
        init(BAR(full2, 0), 24, 1, 16384);
        init(BAR(empty1, 0), 32, 16, 0);
      }
      asm volatile("fence.mbarrier_init.release.cluster;" ::: "memory");
    }
    if (tid == 256) {
      const int w0 = ((c >> 3) * 257 + 32 * (c & 7) + 1) & ~7;
      asm volatile("prefetch.tensormap [%0];" ::"l"(&tmWR) : "memory");
      asm volatile("prefetch.tensormap [%0];" ::"l"(&tmWI) : "memory");
      spin_until(clock32() + FILT_DELAY);
      tma3(sbase + SM_W, &tmWR, BAR(tbar, 0), w0, 0, 0);
      tma3(sbase + SM_W + 10240, &tmWI, BAR(tbar, 0), w0, 0, 0);
      bulk_load(sbase + SM_T + T1_BYTES, reinterpret_cast<const char*>(tab) + T1_BYTES, T2_BYTES, BAR(tbar, 0));
    }
    if (tid == 288) {
      asm volatile("prefetch.tensormap [%0];" ::"l"(rk ? &tmUX : &tmGX) : "memory");
      asm volatile("prefetch.tensormap [%0];" ::"l"(rk ? &tmUY : &tmGY) : "memory");
      asm volatile("prefetch.tensormap [%0];" ::"l"(&tmD) : "memory");
    }
    if (tid == 320) {
      const unsigned e = ld_relaxed(&scr->cnt[(C_LN + rb) * 32]) >> 3;
      asm volatile("st.shared.u32 [%0], %1;" ::"r"(BAR(epoch, 0)), "r"(e) : "memory");
    }
    __syncwarp();
    asm volatile("barrier.cluster.arrive.relaxed.aligned;" ::: "memory");
    bar_arrive(NB_RDY, 384);
    asm volatile("barrier.cluster.wait.aligned;" ::: "memory");
    bar_sync(NB_INIT, 384);
    unsigned epoch;
    asm volatile("ld.shared.u32 %0, [%1];" : "=r"(epoch) : "r"(BAR(epoch, 0)) : "memory");
    if (warp == 8) {
      if (lane == 0) {
        const int ax = (7 * f + 3 * (f & 1)) >> 1;
        const int ay = 7 * f + ((f & 1) ? 0 : 4);
        const CUtensorMap* tx = rk ? &tmUX : &tmGX;
        const CUtensorMap* ty = rk ? &tmUY : &tmGY;
        mbar_wait_bounded(BAR(sig, 0));
        uint32_t s = 2;
#pragma unroll 1
        for (int n = 0; n < 16; n++) {
          if (n >= 6) mbar_wait_bounded(BAR(empty1, n - 6));
          tma3_mc(sbase + (8 + s) * SLOT + rk * 8192, tx, BAR(full1, n), n * 32, ax);
          if (++s == 6) s = 0;
          if (n >= 10 && n < 15) {
            const int k = n - 10;
            tma3_mc(sbase + k * 12288 + rk * 6144, ty, BAR(full1, 16 + k), (k + 8) * 32, ay);
          }
        }
#pragma unroll 1
        for (int k = 5; k < 16; k++) {
          mbar_wait_bounded(BAR(empty1, k < 13 ? 10 + ((12 * (k - 5) + 11) >> 4) : 8 + k));
          tma3_mc(sbase + 8 * SLOT + ((k - 5) & 7) * 12288 + rk * 6144, ty, BAR(full1, 16 + k), ((k + 8) & 15) * 32, ay);
        }
        mbar_wait_bounded(BAR(done, 0));
      }
    } else if (warp == 9) {
      if (lane == 0) {
        mbar_wait(BAR(fullA, 4));
        wait_counter(&scr->cnt[(C_LN + rb2) * 32], (epoch + 1) * 8);
        asm volatile("fence.proxy.async.global;" ::: "memory");
#pragma unroll 1
        for (int i = 0; i < 14; i++) {
          const int kblk = 14 * kh + (int)((KORDER >> (4 * i)) & 15);
          mbar_wait(i < 9 ? BAR(empty1, 16 + (uint32_t)((BDEP >> (4 * i)) & 15)) : BAR(empty2, i - 9));
          tma3(sbase + (uint32_t)((BSLOT >> (4 * i)) & 15) * SLOT, &tmD, BAR(full2, i), 0, 64 * kblk, 2 * nq);
        }
        mbar_wait(BAR(empty2, 5));
        bulk_load(sbase + 13 * SLOT, &scr->LN[(rb2 * 8 + 2 * nq) * 1024 + kh * 512], 8192, BAR(hbar, 0));
        bulk_load(sbase + 13 * SLOT + 8192, &scr->LN[(rb2 * 8 + 2 * nq + 1) * 1024 + kh * 512], 8192, BAR(hbar, 0));
      }
    } else if (warp == 10) {
      bar_sync(NB_LN, 288);
      if (lane == 0) {
        red_release(&scr->cnt[(C_LN + rb) * 32]);
        wait_counter(&scr->cnt[(C_LN + rb) * 32], (epoch + 1) * 8);
        asm volatile("fence.proxy.async.global;" ::: "memory");
#pragma unroll 1
        for (int kb = NLL; kb < 8; kb++) {
          if (2 * kb >= ALEAD) mbar_wait(BAR(empty1, 2 * kb - ALEAD));
          bulk_load(sbase + kb * SLOT, &scr->LN[(rb * 8 + kb) * 1024], 16384, BAR(fullA, kb));
        }
#pragma unroll 1
        for (int s = 0; s < 14; s++) {
          const int kblk = 14 * kh + (int)((KORDER >> (4 * s)) & 15);
          if (s == 0 || s == 8 || s == 11) {
            mbar_wait(BAR(hint, s == 0 ? 0 : s == 8 ? 1 : 2));
          }
          mbar_wait(s < 5 ? BAR(empty1, 16 + (uint32_t)((PDEP >> (4 * s)) & 15)) : BAR(emptyP, s - 5));
          bulk_load_mc(sbase + (uint32_t)((PSLOT >> (4 * s)) & 15) * SLOT + rk * 8192, &scr->P[(rb2 * 28 + kblk) * 1024 + rk * 512], 8192, BAR(fullP, 16 * rk + s));
        }
      }
    } else {
      if (lane == 0) {
        mbar_wait(BAR(tbar, 0));
        l2_prefetch(wg_raw + (size_t)c * 5376, 5376);
        l2_prefetch(wu_raw + (size_t)c * 5376, 5376);
        mbar_wait(BAR(sig, 0));
        l2_prefetch(wg_raw + 688128 + (size_t)c * 8960, 8960);
        l2_prefetch(wu_raw + 688128 + (size_t)c * 8960, 8960);
      }
      mbar_wait(BAR(fullA, 4));
      if (lane == 0) l2_prefetch(wd_raw + (size_t)c * 14336, 14336);
      {
        const uint32_t tag = (epoch + 1) & 1;
        uint4 v0, v1, v2;
        while (true) {
          v0 = ld_b128(&scr->ST[rb * 64 + lane]);
          v1 = ld_b128(&scr->ST[rb * 64 + 32 + lane]);
          v2 = ld_b128(&scr->ST[rb2 * 64 + 32 * kh + lane]);
          if (!__any_sync(0xffffffffu, ((v0.x ^ tag) | (v1.x ^ tag) | (v2.x ^ tag)) & 1u)) break;
        }
        sts4(sstat + lane * 16, v0.x & ~1u, v0.y, v0.z, v0.w);
        sts4(sstat + 512 + lane * 16, v1.x & ~1u, v1.y, v1.z, v1.w);
        sts4(sstat + 1024 + lane * 16, v2.x & ~1u, v2.y, v2.z, v2.w);
        mbar_arrive(BAR(sbar, 0));
      }
      if (lane == 0) {
        mbar_wait(BAR(empty1, XTRIG));
        while ((int)(ld_relaxed(&scr->cnt[(C_PX + rb2) * 32 + kh]) - (epoch + 1) * 32) < 0) {
        }
        mbar_arrive(BAR(hint, 0));
        mbar_wait(BAR(emptyP, HTRIG));
        uint32_t done = 0;
        while (done != 3) {
          uint2 v;
          asm volatile("ld.relaxed.gpu.global.v2.u32 {%0,%1}, [%2];" : "=r"(v.x), "=r"(v.y) : "l"(&scr->cnt[(C_PY + rb2) * 32 + 4 * (rk ^ kh ^ 1) + 2 * kh]) : "memory");
          if (!(done & 1) && (int)(v.x - (epoch + 1) * 8) >= 0) { done |= 1; mbar_arrive(BAR(hint, 1)); }
          if (!(done & 2) && (int)(v.y - (epoch + 1) * 8) >= 0) { done |= 2; mbar_arrive(BAR(hint, 2)); }
        }
      }
    }
  } else {
    const int warp = __shfl_sync(0xffffffffu, tid >> 5, 0);
    const int g = lane >> 2, t = lane & 3;
    uint4 fa[4], fb[4], tw[6];
#pragma unroll
    for (int i = 0; i < 4; i++) fa[i] = ldg_ca4(&tab->fa[i][lane][0]);
#pragma unroll
    for (int i = 0; i < 6; i++) tw[i] = ldg_ca4(&tab->tw1[i][lane][0]);
#pragma unroll
    for (int i = 0; i < 4; i++) fb[i] = ldg_ca4(&tab->fb[i][lane][0]);
#pragma unroll
    for (int i = 0; i < 4; i++) {
      const int r = i >> 1, ch = (i & 1) * 32 + lane;
      cp_async16(sbase + SM_X + (2 * warp + r) * 1024 + ((ch ^ ((ch >> 3) & 1)) * 16),
                 x + (size_t)(c + 128 * (2 * warp + r)) * 512 + ch * 8);
    }
    asm volatile("cp.async.commit_group;" ::: "memory");
    asm volatile("barrier.cluster.arrive.relaxed.aligned;" ::: "memory");
    uint32_t rbar;
    asm volatile("mapa.shared::cluster.u32 %0, %1, %2;" : "=r"(rbar) : "r"(sbar), "r"(rk ^ 1));
#define RBAR(field, i) (rbar + (uint32_t)offsetof(Bars, field) + 8u * (i))
    {
      const int ln = (tid >> 1) & 31, lg = ln >> 2, lt = ln & 3, i = 4 * (tid >> 6) + 2 * (tid & 1);
      const int kidx = lt + 8 * (i >> 3), nidx = 4 * ((i >> 1) & 3) + (lg >> 1);
      const uint32_t a0 = cfrag<2048>((c + 128 * kidx) * nidx, lg & 1), a1 = cfrag<2048>((c + 128 * (kidx + 4)) * nidx, lg & 1);
      const uint32_t b0 = cfrag<2048>(-(c + 128 * nidx) * kidx, lg & 1), b1 = cfrag<2048>(-(c + 128 * nidx) * (kidx + 4), lg & 1);
      asm volatile("st.shared.v2.u32 [%0], {%1,%2};" ::"r"(sbase + SM_FC + tid * 8), "r"(a0), "r"(a1) : "memory");
      asm volatile("st.shared.v2.u32 [%0], {%1,%2};" ::"r"(sbase + SM_FC + 2048 + tid * 8), "r"(b0), "r"(b1) : "memory");
    }
    bar_sync(NB_CONS, 256);
    uint4 fc[4];
#pragma unroll
    for (int i = 0; i < 4; i++) fc[i] = lds4(sbase + SM_FC + i * 512 + lane * 16);
    asm volatile("cp.async.wait_group 0;" ::: "memory");
    __syncwarp();
    bar_arrive(NB_INIT, 384);
    uint32_t tag, ones;
    uint4 q[4], o[4];
    {
      uint32_t v[2][8];
#pragma unroll
      for (int r = 0; r < 2; r++)
#pragma unroll
        for (int ks = 0; ks < 2; ks++) {
          const int ch = 32 * ks + 2 * (lane & 15) + (lane >> 4);
          asm volatile("ldmatrix.sync.aligned.m8n8.x4.trans.shared.b16 {%0,%1,%2,%3}, [%4];"
                       : "=r"(v[r][4 * ks]), "=r"(v[r][4 * ks + 1]), "=r"(v[r][4 * ks + 2]), "=r"(v[r][4 * ks + 3])
                       : "r"(sbase + SM_X + (2 * warp + r) * 1024 + ((ch ^ ((ch >> 3) & 1)) * 16)) : "memory");
        }
      float sq[2];
#pragma unroll
      for (int r = 0; r < 2; r++) {
        float s0 = 0.f, s1 = 0.f;
#pragma unroll
        for (int i = 0; i < 8; i++) {
          const float lo = bf_lo(v[r][i]), hi = u2f(v[r][i] & 0xffff0000u);
          s0 = fmaf(lo, lo, s0);
          s1 = fmaf(hi, hi, s1);
        }
        sq[r] = s0 + s1;
      }
      {
        float w = ((lane & 1) ? sq[1] : sq[0]) + __shfl_xor_sync(0xffffffffu, (lane & 1) ? sq[0] : sq[1], 1);
        w += __shfl_xor_sync(0xffffffffu, w, 2);
        w = sum_groups(w);
        const float o2 = __shfl_xor_sync(0xffffffffu, w, 1);
        sq[0] = (lane & 1) ? o2 : w;
        sq[1] = (lane & 1) ? w : o2;
      }
#pragma unroll
      for (int r = 0; r < 2; r++) {
        float dd[2][4], ee[2][4];
#pragma unroll
        for (int nt = 0; nt < 2; nt++) {
          mma_az(dd[nt], fa[0], v[r][2 * nt], v[r][2 * nt + 1]);
          mma_a(dd[nt], fa[1], v[r][4 + 2 * nt], v[r][5 + 2 * nt]);
          mma_az(ee[nt], fa[2], v[r][2 * nt], v[r][2 * nt + 1]);
          mma_a(ee[nt], fa[3], v[r][4 + 2 * nt], v[r][5 + 2 * nt]);
        }
        float mean = (dd[0][0] + dd[0][1]) + (dd[1][0] + dd[1][1]);
        mean += __shfl_xor_sync(0xffffffffu, mean, 1);
        mean += __shfl_xor_sync(0xffffffffu, mean, 2);
        mean = __shfl_sync(0xffffffffu, mean, 0) * (1.f / 512.f);
        const float rs = rsqrtf(fmaxf(fmaf(-mean, mean, sq[r] * (1.f / 512.f)), 0.f) + 1e-5f);
        float acc[4][4];
#pragma unroll
        for (int nt = 0; nt < 2; nt++) {
          const float (&d)[4] = dd[nt];
          const float (&e)[4] = ee[nt];
          const uint4 &ka = tw[2 * nt], &kb = tw[2 * nt + 1], &kc = tw[4 + nt];
          const uint32_t a0 = pack2(d[0] * u2f(ka.x) + d[2] * u2f(ka.y), d[1] * u2f(kb.x) + d[3] * u2f(kb.y));
          const uint32_t a2 = pack2(d[0] * u2f(ka.z) + d[2] * u2f(ka.w), d[1] * u2f(kb.z) + d[3] * u2f(kb.w));
          const uint32_t a1 = pack2(e[0] * u2f(kc.x) + e[2] * u2f(kc.y), e[1] * u2f(kc.z) + e[3] * u2f(kc.w));
          const uint32_t a3 = pack2(e[2] * u2f(kc.x) - e[0] * u2f(kc.y), e[3] * u2f(kc.z) - e[1] * u2f(kc.w));
          const uint32_t dc = pack2(fmaf(mean, -32.f, d[0]), fmaf(mean, -32.f, d[1]));
          const uint32_t h0 = g == 0 ? dc : a0, h2 = g == 0 ? 0u : a2;
          if (nt == 0) {
            mma16816_z(acc[0], a0, a1, a2, a3, fb[2 * nt].x, fb[2 * nt].y);
            mma16816_z(acc[1], a0, a1, a2, a3, fb[2 * nt].z, fb[2 * nt].w);
            mma16816_z(acc[2], h0, a1, h2, a3, fb[2 * nt + 1].x, fb[2 * nt + 1].y);
            mma16816_z(acc[3], h0, a1, h2, a3, fb[2 * nt + 1].z, fb[2 * nt + 1].w);
          } else {
            mma16816(acc[0], a0, a1, a2, a3, fb[2 * nt].x, fb[2 * nt].y);
            mma16816(acc[1], a0, a1, a2, a3, fb[2 * nt].z, fb[2 * nt].w);
            mma16816(acc[2], h0, a1, h2, a3, fb[2 * nt + 1].x, fb[2 * nt + 1].y);
            mma16816(acc[3], h0, a1, h2, a3, fb[2 * nt + 1].z, fb[2 * nt + 1].w);
          }
        }
#pragma unroll
        for (int h = 0; h < 2; h++) {
          const int j = 2 * warp + r, m = 2 * t + h;
          sts4(sbase + SM_E + ((j * 8 + m) * 8 + (g ^ (2 * t) ^ (2 * (j & 3)))) * 16,
               pack2(acc[h][0] * rs, acc[h][1] * rs), pack2(acc[h][2] * rs, acc[h][3] * rs),
               pack2(acc[2 + h][0] * rs, acc[2 + h][1] * rs), pack2(acc[2 + h][2] * rs, acc[2 + h][3] * rs));
        }
      }
      bar_sync(NB_RDY, 384);
      const uint32_t ea = sbase + SM_E + ((t * 8 + warp) * 8 + (g ^ (warp & 6) ^ (2 * t))) * 16;
      lds_frag(q[0], q[1], ea, ea + 4096);
      lds_frag(q[2], q[3], ea + 8192, ea + 12288);
      asm volatile("ld.shared.u32 %0, [%1];" : "=r"(tag) : "r"(BAR(epoch, 0)) : "memory");
      ones = ~(tag >> 31);
      tag = (tag + 1) & 1;
      cdft16(q, fc, o);
#pragma unroll
      for (int vv = 0; vv < 4; vv++) {
        o[vv].y &= ~1u;
        o[vv].z = (o[vv].z & ~1u) | (tag ^ 1);
        st_tag(&scr->Z1[(((4 * vv + t) * 8 + warp) * 128 + c) * 8 + g], o[vv], tag);
      }
    }
    asm volatile("setmaxnreg.inc.sync.aligned.u32 232;");
    {
      uint4* const zp = &scr->Z1[(c * 128 + 8 * t + warp) * 8 + g];
      const uint32_t tst = clock32();
      mbar_wait(BAR(tbar, 0));
      uint4 f2[4], g2[4];
#pragma unroll
      for (int i = 0; i < 4; i++) {
        f2[i] = lds4(TOFF(f2) + warp * 2048 + i * 512);
        g2[i] = lds4(TOFF(g2) + warp * 2048 + i * 512);
      }
      const uint4 f8 = lds4(TOFF(f8)), g8 = lds4(TOFF(g8));
      asm volatile("barrier.cluster.wait.aligned;" ::: "memory");
      spin_until(tst + POLL_DELAY);
      ld_tag4_issue<256>(q, zp);
      float wfr[16], wfi[16];
      {
        const float nyq = ((c & 7) == 7 && g == 0) ? 0.5f : 1.f;
        uint32_t wa = sbase + SM_W + (16 * warp + t) * 80 + ((2 * (c >> 3) + 2) & 15) - 2;
        asm volatile("" : "+r"(wa));
        const uint32_t wb[3] = {wa + 2 * (g == 0 ? 16 : g), wa + 2 * g, wa - 2 * g};
#pragma unroll
        for (int i = 0; i < 16; i++) {
          const int ci = i >> 3, dd = (i >> 2) & 1, e = i & 3;
          const uint32_t a = wb[e < 2 ? e : 2] + (ci * 8 + 4 * dd) * 80 + (e == 0 ? 0 : e == 1 ? 16 : e == 2 ? 64 : 48);
          wfr[i] = bf_lo(lds_u16(a)) * (e == 2 ? nyq : 1.f);
          wfi[i] = bf_lo(lds_u16(a + 10240)) * (e == 2 ? nyq : 1.f);
        }
      }
      ld_tag4_finish<256>(q, zp, tag);
#pragma unroll
      for (int i = 0; i < 4; i++) q[i].z &= ~1u;
      reg_frag(q, ones);
      cdft16(q, f2, o);
      const uint32_t e2 = sbase + SM_E2;
#pragma unroll
      for (int vv = 0; vv < 4; vv++)
        sts4(e2 + ((warp * 16 + 4 * vv + t) * 8 + (g ^ (2 * t) ^ (2 * (warp & 3)))) * 16, o[vv].x, o[vv].y, o[vv].z, o[vv].w);
      bar_sync(NB_CONS, 256);
      uint32_t ad[2], res[2][2][4];
#pragma unroll
      for (int ci = 0; ci < 2; ci++) {
        const int cc = 2 * warp + ci;
        ad[ci] = e2 + ((t * 16 + cc) * 8 + (g ^ (2 * (cc & 3)) ^ (2 * t))) * 16;
        lds_frag(q[2 * ci], q[2 * ci + 1], ad[ci], ad[ci] + 8192);
      }
#pragma unroll
      for (int ci = 0; ci < 2; ci++)
#pragma unroll
        for (int p = 0; p < 2; p++) {
          uint32_t y[2][2];
#pragma unroll
          for (int vv = 0; vv < 2; vv++) {
            float d[4];
            mma_az(d, q[2 * ci + p], word(f8, 2 * vv), word(f8, 2 * vv + 1));
#pragma unroll
            for (int rr = 0; rr < 2; rr++) {
              const float fr = wfr[ci * 8 + vv * 4 + 2 * p + rr], fi = wfi[ci * 8 + vv * 4 + 2 * p + rr];
              y[vv][rr] = pack2(d[2 * rr] * fr - d[2 * rr + 1] * fi, d[2 * rr] * fi + d[2 * rr + 1] * fr);
            }
          }
#pragma unroll
          for (int vv = 0; vv < 2; vv++) {
            float d[4];
            mma16816_z(d, y[0][0], y[0][1], y[1][0], y[1][1], word(g8, 2 * vv), word(g8, 2 * vv + 1));
            res[ci][vv][2 * p] = pack2(d[0], d[1]);
            res[ci][vv][2 * p + 1] = pack2(d[2], d[3]);
          }
        }
#pragma unroll
      for (int i = 0; i < 4; i++)
        sts4(ad[i >> 1] + (i & 1) * 8192, res[i >> 1][i & 1][0], res[i >> 1][i & 1][1], res[i >> 1][i & 1][2], res[i >> 1][i & 1][3]);
      bar_sync(NB_CONS, 256);
      const uint32_t eb = e2 + ((warp * 16 + t) * 8 + (g ^ (2 * t) ^ (2 * (warp & 3)))) * 16;
      lds_frag(q[0], q[1], eb, eb + 512);
      lds_frag(q[2], q[3], eb + 1024, eb + 1536);
      cdft16(q, g2, o);
#pragma unroll
      for (int vv = 0; vv < 4; vv++) {
        o[vv].y &= ~1u;
        o[vv].z = (o[vv].z & ~1u) | tag;
        st_tag(zp + vv * 256, o[vv], tag);
      }
    }
    {
      const uint4* const zp = &scr->Z1[((t * 8 + warp) * 128 + c) * 8 + g];
      const uint32_t tst = clock32();
      uint4 gb[4], ga[4], gc[4], tw[4];
      uint2 xr[2][4];
      uint2* lnp[2];
#pragma unroll
      for (int r = 0; r < 2; r++) {
        const int row = 16 * f + 2 * warp + r;
        lnp[r] = reinterpret_cast<uint2*>(&scr->LN[(rb * 8 + (g >> 2)) * 1024 + row * 8 + ((2 * (g & 3) + (t >> 1)) ^ (row & 7))]) + (t & 1);
        asm volatile("" : "+l"(lnp[r]));
      }
#pragma unroll
      for (int i = 0; i < 4; i++) {
        gc[i] = lds4(sbase + SM_FC + 2048 + i * 512 + lane * 16);
        gb[i] = lds4(TOFF(gb) + i * 512);
        ga[i] = lds4(TOFF(ga) + i * 512);
        tw[i] = lds4(TOFF(tw3) + i * 512);
        const int ch = 2 * (g + 8 * i) + (t >> 1);
#pragma unroll
        for (int r = 0; r < 2; r++) xr[r][i] = lds2(sbase + SM_X + (2 * warp + r) * 1024 + ((ch ^ ((ch >> 3) & 1)) * 16) + (t & 1) * 8);
      }
      spin_until(tst + POLL_DELAY2);
      ld_tag4_issue<32768>(q, zp);
      ld_tag4_finish<32768, true>(q, zp, tag);
      if (lane == 0) mbar_arrive(BAR(sig, 0));
      reg_frag(q, ones);
      cdft16(q, gc, o);
#pragma unroll
      for (int vv = 0; vv < 4; vv++)
        sts4(sbase + SM_E + (((4 * vv + t) * 8 + warp) * 8 + (g ^ (warp & 6) ^ (2 * t))) * 16, o[vv].x, o[vv].y, o[vv].z, o[vv].w);
      bar_sync(NB_CONS, 256);
      uint32_t hv[2][8];
      const float mk = t == 0 ? 0.f : 1.f;
#pragma unroll
      for (int r = 0; r < 2; r++) {
        const int j = 2 * warp + r;
        uint4 u[2];
#pragma unroll
        for (int h = 0; h < 2; h++) u[h] = lds4(sbase + SM_E + ((j * 8 + 2 * t + h) * 8 + (g ^ (2 * t) ^ (2 * (j & 3)))) * 16);
        const uint32_t bp[4][2] = {{u[0].x, u[1].x & ones}, {u[0].y & ones, u[1].y}, {u[0].z, u[1].z & ones}, {u[0].w & ones, u[1].w}};
        float y[2][2][4];
#pragma unroll
        for (int i = 0; i < 2; i++) {
          float lo[4], hi[4], e[4];
          mma_az(lo, gb[2 * i], bp[0][0], bp[0][1]);
          mma_az(hi, gb[2 * i + 1], bp[2][0], bp[2][1]);
          mma_az(e, gb[2 * i], bp[1][0], bp[1][1]);
          mma_a(e, gb[2 * i + 1], bp[3][0], bp[3][1]);
          const uint4 &ka = tw[2 * i], &kb = tw[2 * i + 1];
          const float tr0 = fmaf(hi[0], mk, lo[0]), ti0 = fmaf(hi[2], mk, lo[2]);
          const float tr1 = lo[1] + hi[1], ti1 = lo[3] + hi[3];
          const float vr0 = tr0 * u2f(ka.x) - ti0 * u2f(ka.y), vi0 = tr0 * u2f(ka.y) + ti0 * u2f(ka.x);
          const float vr1 = tr1 * u2f(ka.z) - ti1 * u2f(ka.w), vi1 = tr1 * u2f(ka.w) + ti1 * u2f(ka.z);
          const uint32_t b0 = pack2(t == 0 ? hi[0] : vr0, vr1), b1 = pack2(t == 0 ? vr0 : vi0, vi1);
          const uint32_t b2 = pack2(e[0] * u2f(kb.x) - e[2] * u2f(kb.y), e[1] * u2f(kb.z) - e[3] * u2f(kb.w));
          const uint32_t b3 = pack2(e[0] * u2f(kb.y) + e[2] * u2f(kb.x), e[1] * u2f(kb.w) + e[3] * u2f(kb.z));
#pragma unroll
          for (int mt = 0; mt < 2; mt++) {
            mma_az(y[mt][i], ga[2 * mt], b0, b1);
            mma_a(y[mt][i], ga[2 * mt + 1], b2, b3);
          }
        }
#pragma unroll
        for (int i = 0; i < 4; i++) {
          hv[r][2 * i] = hadd2_bf16(xr[r][i].x, pack2(y[i >> 1][0][2 * (i & 1)], y[i >> 1][0][2 * (i & 1) + 1]));
          hv[r][2 * i + 1] = hadd2_bf16(xr[r][i].y, pack2(y[i >> 1][1][2 * (i & 1)], y[i >> 1][1][2 * (i & 1) + 1]));
        }
      }
      float mean[2];
      uint32_t mb[2];
#pragma unroll
      for (int r = 0; r < 2; r++) {
        mean[r] = sum_groups(quad_sum(hv[r])) * (1.f / 512.f);
        mb[r] = pack2(mean[r], mean[r]);
      }
#pragma unroll
      for (int i = 0; i < 4; i++)
#pragma unroll
        for (int r = 0; r < 2; r++) {
          hv[r][2 * i] = hsub2_bf16(hv[r][2 * i], mb[r]);
          hv[r][2 * i + 1] = hsub2_bf16(hv[r][2 * i + 1], mb[r]);
          st_tag8(lnp[r] + i * 4096, hv[r][2 * i], hv[r][2 * i + 1], i < 2 ? tag : (hv[r][2 * i] & 1u));
        }
      bar_arrive(NB_LN, 288);
      const uint32_t ones2 = ~(lds2(BAR(epoch, 0)).x >> 31);
      float rstd[2];
#pragma unroll
      for (int r = 0; r < 2; r++) {
        hv[r][0] &= ones2;
        rstd[r] = row_rstd(hv[r], mean[r] - bf_lo(mb[r]));
      }
      if (lane == 0)
        st_tag(&scr->ST[rb * 64 + 8 * f + warp], make_uint4(mb[0] << 16, __float_as_uint(rstd[0]), mb[1] << 16, __float_as_uint(rstd[1])), tag);
    }
    const int wgi = warp >> 2, wq = warp & 3;
    const int wr = wgi ^ (f >> 2) ^ 1, rt = 4 * wr + wq;
    uint4* const pbase = &scr->P[rb * 28 * 1024 + rt * 128 + lane];
    const uint32_t a_lo0 = desc_lo(sbase + wr * 8192, 16);
    const uint32_t ebar = lane == 0 ? BAR(empty1, 0) : RBAR(empty1, 0);
    float r0, r1;
    uint4 px[8], py[6];
    const int rh = wgi ^ kh ^ 1;
    const uint32_t fpb = BAR(fullP, 16 * rh);
    const uint4* const psrc = &scr->P[(rb2 * 28 + 14 * kh) * 1024 + (4 * rh + wq) * 128 + lane];
    const uint32_t pa0 = sbase + (4 * rh + wq) * 2048;
    uint4 pf[3][4], ha[4][4];
    uint32_t rdy = 0, got0;
    {
      float acc[128];
#pragma unroll
      for (int i = 0; i < 128; i++) acc[i] = 0.f;
      const uint32_t b_lo0 = desc_lo(sbase + 8 * SLOT, 4096);
      const uint32_t t3 = clock32();
      if (WARM) {
        wg_fence();
#pragma unroll
        for (int i = 0; i < WARM; i++) wgmma_n256(acc, desc64(a_lo0 + 6 * 1024, HI128), desc64(b_lo0, HI128));
        wg_commit();
      }
      const uint4* const ap = &scr->LN[rb * 8 * 1024 + rt * 128 + lane];
      const uint32_t sa = sbase + rt * 2048, amask = (lane & 1) ? ~0u : ~1u;
      auto fetch_a = [&](int kb) {
#pragma unroll
        for (int i = 0; i < 4; i++) cp_async16(sa + kb * SLOT + (lane + 32 * i) * 16, ap + kb * 1024 + 32 * i);
        asm volatile("cp.async.commit_group;" ::: "memory");
      };
      auto load_a = [&](int kb) {
#pragma unroll
        for (int ks = 0; ks < 4; ks++)
          asm volatile("ldmatrix.sync.aligned.m8n8.x4.shared.b16 {%0,%1,%2,%3}, [%4];"
                       : "=r"(ha[kb][ks].x), "=r"(ha[kb][ks].y), "=r"(ha[kb][ks].z), "=r"(ha[kb][ks].w)
                       : "r"(sa + kb * SLOT + (lane & 15) * 128 + (((2 * ks + (lane >> 4)) ^ (lane & 7)) * 16)) : "memory");
      };
      auto check_a = [&](int kb) {
        int it = 0;
#pragma unroll 1
        while (true) {
          uint32_t m = 0;
#pragma unroll
          for (int ks = 0; ks < 4; ks++) m |= tag_miss(ha[kb][ks].x, ha[kb][ks].y, ha[kb][ks].z, ha[kb][ks].w, tag);
          if (!__any_sync(0xffffffffu, m & ~amask)) break;
          fetch_a(kb);
          asm volatile("cp.async.wait_group 0;" ::: "memory");
          __syncwarp();
          load_a(kb);
          if (++it > SPIN_LIMIT) { die(); break; }
        }
#pragma unroll
        for (int ks = 0; ks < 4; ks++)
          asm volatile("and.b32 %0, %0, %4; and.b32 %1, %1, %4; and.b32 %2, %2, %4; and.b32 %3, %3, %4;"
                       : "+r"(ha[kb][ks].x), "+r"(ha[kb][ks].y), "+r"(ha[kb][ks].z), "+r"(ha[kb][ks].w) : "r"(amask));
      };
      bar_sync(NB_CONS, 256);
      spin_until(t3 + POLL_DELAY3);
#pragma unroll
      for (int kb = 0; kb < 4; kb++) fetch_a(kb);
      asm volatile("cp.async.wait_group 3;" ::: "memory");
      __syncwarp();
      load_a(0);
#pragma unroll
      for (int n = 0; n < 8; n++) {
        const int kb = n >> 1, hh = n & 1;
        if (hh == 0) check_a(kb);
        if (hh == 1 && kb < 3) {
          if (kb == 0) asm volatile("cp.async.wait_group 2;" ::: "memory");
          if (kb == 1) asm volatile("cp.async.wait_group 1;" ::: "memory");
          if (kb == 2) asm volatile("cp.async.wait_group 0;" ::: "memory");
          __syncwarp();
        }
        if (!rdy) mbar_wait(BAR(full1, n));
        const uint32_t bl = b_lo0 + ((n + 2) % 6) * 1024;
        wg_fence();
        if (hh == 1 && kb < 3) load_a(kb + 1);
        rdy = mbar_test(BAR(full1, n + 1));
        const uint4 &a0 = ha[kb][2 * hh], &a1 = ha[kb][2 * hh + 1];
        wgmma_rs_n256(acc, a0.x, a0.y, a0.z, a0.w, desc64(bl, HI128), n != 0 ? 1 : ~ones);
        wgmma_rs_n256(acc, a1.x, a1.y, a1.z, a1.w, desc64(bl + 128, HI128));
        wg_commit();
        wg_wait<1>();
        if (n != 0 && lane < 2) mbar_arrive_remote(ebar + 8 * (n - 1));
      }
      uint32_t slot = 4;
#pragma unroll 1
      for (int kb = 4; kb < 8; kb++) {
        mbar_wait(BAR(fullA, kb));
#pragma unroll
        for (int hh = 0; hh < 2; hh++) {
          if (hh == ((16 - LAGX) & 1) && kb == ((16 - LAGX) >> 1) && wgi == 1) bar_sync(NB_LAG, 256);
          mbar_wait(BAR(full1, 2 * kb + hh));
          const uint32_t al = a_lo0 + kb * 1024 + hh * 4, bl = b_lo0 + slot * 1024;
          wg_fence();
          wgmma_n256(acc, desc64(al, HI128), desc64(bl, HI128));
          wgmma_n256(acc, desc64(al + 2, HI128), desc64(bl + 128, HI128));
          wg_commit();
          if (hh == 1 && kb == 7 && wgi == 0) bar_arrive(NB_LAG, 256);
          wg_wait<1>();
          if (lane < 2) mbar_arrive_remote(ebar + 8 * (2 * kb + hh - 1));
          if (++slot == 6) slot = 0;
        }
      }
      mbar_wait(BAR(sbar, 0));
      r0 = __uint_as_float(lds2(sstat + (16 * rt + g) * 8).y);
      r1 = __uint_as_float(lds2(sstat + (16 * rt + g + 8) * 8).y);
      wg_wait<0>();
      if (lane < 2) mbar_arrive_remote(ebar + 8 * 15);
      make_p<8, false>(acc, r0, r1, px, pbase, 0, tag);
    }
    {
      float acc[96];
#pragma unroll
      for (int i = 0; i < 96; i++) acc[i] = 0.f;
      const uint32_t b_lo0 = desc_lo(sbase, 2048);
      uint4* const pdst = pbase + ((7 * f + 3 * (f & 1)) >> 1) * 1024;
      auto stage_y = [&](int k) {
        if (k < 4) mbar_wait_bounded(BAR(full1, 16 + k));
        else mbar_wait(BAR(full1, 16 + k));
        const uint32_t al = a_lo0 + (4 + (k >> 1)) * 1024 + (k & 1) * 4, bl = b_lo0 + (k < 5 ? k * 768 : 8192 + (k - 5) * 768);
        wg_fence();
        wgmma_n192(acc, desc64(al, HI128), desc64(bl, HI64));
        wgmma_n192(acc, desc64(al + 2, HI128), desc64(bl + 64, HI64));
        wg_commit();
      };
#pragma unroll
      for (int k = 0; k < 4; k++) {
        stage_y(k);
        st_tag(pdst + (k >> 1) * 1024 + (k & 1) * 64, px[2 * k], tag);
        st_tag(pdst + (k >> 1) * 1024 + (k & 1) * 64 + 32, px[2 * k + 1], tag);
        if (k == 3 && lane == 0) red_relaxed(&scr->cnt[(C_PX + rb) * 32 + (f >> 2)]);
        wg_wait<1>();
        if (k != 0 && lane < 2) mbar_arrive_remote(ebar + 8 * (15 + k));
      }
#pragma unroll 1
      for (int k = 4; k < 8; k++) {
        stage_y(k);
        wg_wait<1>();
        if (k != 0 && lane < 2) mbar_arrive_remote(ebar + 8 * (15 + k));
      }
      rdy = 0;
#pragma unroll
      for (int k = 8; k < 16; k++) {
        if (k == 16 - LAGY && wgi == 1) bar_sync(NB_LAG, 256);
        if (!rdy) mbar_wait(BAR(full1, 16 + k));
        const uint32_t bl = b_lo0 + 8192 + ((k - 5) & 7) * 768;
        const uint4 &a0 = ha[(k - 8) >> 1][2 * (k & 1)], &a1 = ha[(k - 8) >> 1][2 * (k & 1) + 1];
        wg_fence();
        if (k < 15) rdy = mbar_test(BAR(full1, 17 + k));
        wgmma_rs_n192(acc, a0.x, a0.y, a0.z, a0.w, desc64(bl, HI64));
        wgmma_rs_n192(acc, a1.x, a1.y, a1.z, a1.w, desc64(bl + 64, HI64));
        wg_commit();
        if (k == 15 && wgi == 0) bar_arrive(NB_LAG, 256);
        wg_wait<1>();
        if (lane < 2) mbar_arrive_remote(ebar + 8 * (15 + k));
      }
      got0 = __all_sync(0xffffffffu, mbar_test(fpb));
      if (got0) {
#pragma unroll
        for (int kk = 0; kk < 4; kk++) pf[0][kk] = lds4(pa0 + 3 * SLOT + kk * 512 + lane * 16);
      }
      wg_wait<0>();
      if (lane < 2) mbar_arrive_remote(ebar + 8 * 31);
      const int ks0 = 14 * f + ((f & 1) ? 0 : 8);
      auto reread = [&]() {
        asm volatile("ld.volatile.shared.f32 %0, [%2+4]; ld.volatile.shared.f32 %1, [%2+68];" : "=f"(r0), "=f"(r1) : "r"(sstat + (16 * rt + g) * 8) : "memory");
      };
      make_p<6, true, 0, 2>(acc, r0, r1, py, pbase, ks0, tag);
      reread();
      make_p<6, true, 2, 4>(acc, r0, r1, py, pbase, ks0, tag);
      if (lane == 0) red_relaxed(&scr->cnt[(C_PY + rb) * 32 + 4 * wgi + (f >> 1)]);
      reread();
      rdy = mbar_test(BAR(full2, 0)) & mbar_test(fpb + 8);
      make_p<6, true, 4, 6>(acc, r0, r1, py, pbase, ks0, tag);
    }
    {
      float acc[64];
      const uint32_t b2_lo0 = desc_lo(sbase, 8192);
      const uint32_t pbar = rh == rk ? BAR(emptyP, 0) : RBAR(emptyP, 0);
      if (!got0) {
        mbar_wait(fpb);
#pragma unroll
        for (int kk = 0; kk < 4; kk++) pf[0][kk] = lds4(pa0 + 3 * SLOT + kk * 512 + lane * 16);
      }
#pragma unroll
      for (int s = 0; s < 14; s++) {
        uint4 (&a)[4] = pf[s % 3];
        ld_tag4_finish<32>(a, psrc + (int)((KORDER >> (4 * s)) & 15) * 1024, tag);
        if (s < 9 && lane == 0) mbar_arrive_remote(pbar + 8 * s);
        if (s >= 2) {
          wg_wait<1>();
          if (s <= 7 && lane == 0) mbar_arrive(BAR(empty2, s - 2));
        }
        if (!rdy) {
          if (s < 13) mbar_wait(fpb + 8 * (s + 1));
          mbar_wait(BAR(full2, s));
        }
        if (s == 14 - LAG2 && wgi == 1) bar_sync(NB_LAG, 256);
        const uint32_t bl = b2_lo0 + (uint32_t)((BSLOT >> (4 * s)) & 15) * 1024;
        wg_fence();
        if (s < 13) {
#pragma unroll
          for (int kk = 0; kk < 4; kk++)
            pf[(s + 1) % 3][kk] = lds4(pa0 + (uint32_t)((PSLOT >> (4 * (s + 1))) & 15) * SLOT + kk * 512 + lane * 16);
          rdy = mbar_test(BAR(full2, s + 1));
          if (s < 12) rdy &= mbar_test(fpb + 8 * (s + 2));
        }
        if (s == 0) wgmma_rs_n128(acc, a[0].x, a[0].y, a[0].z, a[0].w, desc64(bl, HI128), 0);
        else wgmma_rs_n128(acc, a[0].x, a[0].y, a[0].z, a[0].w, desc64(bl, HI128));
#pragma unroll
        for (int kk = 1; kk < 4; kk++) wgmma_rs_n128(acc, a[kk].x, a[kk].y, a[kk].z, a[kk].w, desc64(bl + kk * 128, HI128));
        wg_commit();
      }
      if (wgi == 0) {
        bar_arrive(NB_LAG, 256);
        uint4* const dst = &scr->Z1[(tid >> 3) * 1024 + (c ^ 4) * 8 + (tid & 7)];
        wg_wait<0>();
#pragma unroll
        for (int i = 0; i < 8; i++)
          st_tag(dst + i * 16384, make_uint4(pack2(acc[8 * i], acc[8 * i + 1]), pack2(acc[8 * i + 2], acc[8 * i + 3]) | 1u,
                                           pack2(acc[8 * i + 4], acc[8 * i + 5]), pack2(acc[8 * i + 6], acc[8 * i + 7])), tag);
      } else {
        uint4 pv[2][4];
        const uint4* const xsrc = &scr->Z1[((tid & 127) >> 3) * 1024 + c * 8 + (tid & 7)];
        ld_tag4_issue<16384>(pv[0], xsrc);
        ld_tag4_issue<16384>(pv[1], xsrc + 65536);
        uint32_t w[32];
        {
          const uint32_t m0 = __byte_perm(lds2(sstat + 1024 + (16 * wq + g) * 8).x, 0, 0x3232);
          const uint32_t m1 = __byte_perm(lds2(sstat + 1024 + (16 * wq + g + 8) * 8).x, 0, 0x3232);
          const uint32_t hb = sbase + 13 * SLOT + (16 * wq + (lane & 15)) * 128;
          const uint32_t mk = ((t & 1) == 0 && nq < 2) ? ~1u : ~0u;
          mbar_wait(BAR(hbar, 0));
#pragma unroll
          for (int i = 0; i < 8; i++) {
            asm volatile("ldmatrix.sync.aligned.m8n8.x4.shared.b16 {%0,%1,%2,%3}, [%4];"
                         : "=r"(w[4 * i]), "=r"(w[4 * i + 1]), "=r"(w[4 * i + 2]), "=r"(w[4 * i + 3])
                         : "r"(hb + (i >> 2) * 8192 + (((2 * (i & 3) + (lane >> 4)) ^ (lane & 7)) * 16)) : "memory");
#pragma unroll
            for (int e = 0; e < 4; e++) w[4 * i + e] = hadd2_bf16(w[4 * i + e] & mk, (e & 1) ? m1 : m0);
          }
        }
        wg_wait<0>();
#pragma unroll
        for (int i = 0; i < 32; i++) w[i] = hadd2_bf16(w[i], pack2(acc[2 * i], acc[2 * i + 1]));
#pragma unroll 1
        while (!__all_sync(0xffffffffu, pv[0][0].y & pv[0][1].y & pv[0][2].y & pv[0][3].y & pv[1][0].y & pv[1][1].y & pv[1][2].y & pv[1][3].y & 1u)) {
          ld_tag4_issue<16384>(pv[0], xsrc);
          ld_tag4_issue<16384>(pv[1], xsrc + 65536);
        }
#pragma unroll
        for (int i = 0; i < 8; i++) {
          const uint4& p = pv[i >> 2][i & 3];
          asm volatile("stmatrix.sync.aligned.m8n8.x4.shared.b16 [%0], {%1,%2,%3,%4};"
                       ::"r"(pa0 + (11 + ((lane >> 3) & 1)) * SLOT + (lane & 7) * 256 + (((2 * i + (lane >> 4)) ^ (lane & 7)) * 16)),
                         "r"(hadd2_bf16(w[4 * i], p.x & ~1u)), "r"(hadd2_bf16(w[4 * i + 1], p.y & ~1u)), "r"(hadd2_bf16(w[4 * i + 2], p.z)),
                         "r"(hadd2_bf16(w[4 * i + 3], p.w)) : "memory");
        }
        __syncwarp();
        uint4* const dst = reinterpret_cast<uint4*>(out) + (16 * (c >> 4) + 2 * (4 * rh + wq) + (rb2 & 1) + 128 * (lane >> 4)) * 64 + nq * 16 + (lane & 15);
#pragma unroll
        for (int i = 0; i < 8; i++) {
          const int r = 2 * (i & 3) + (lane >> 4);
          dst[i * 256 * 64] = lds4(pa0 + (11 + (i >> 2)) * SLOT + r * 256 + (((lane & 15) ^ r) * 16));
        }
      }
      if (lane == 0) mbar_arrive(BAR(done, 0));
    }
  }
#undef BAR
#undef TOFF
#undef RBAR
}

typedef CUresult (*EncodeFn)(CUtensorMap*, CUtensorMapDataType, cuuint32_t, void*, const cuuint64_t*, const cuuint64_t*,
                             const cuuint32_t*, const cuuint32_t*, CUtensorMapInterleave, CUtensorMapSwizzle,
                             CUtensorMapL2promotion, CUtensorMapFloatOOBfill);

}

extern "C" void kernel_launch(void* const* d_in, const int* in_sizes, int n_in, void* d_out, int out_size) {
  (void)in_sizes; (void)n_in; (void)out_size;
  static EncodeFn encode = nullptr;
  static void *tab = nullptr, *scr = nullptr;
  if (!encode) {
    void* fn = nullptr;
    cudaDriverEntryPointQueryResult qr;
    cudaGetDriverEntryPoint("cuTensorMapEncodeTiled", &fn, cudaEnableDefault, &qr);
    encode = (EncodeFn)fn;
    cudaGetSymbolAddress(&tab, g_tab);
    cudaGetSymbolAddress(&scr, g_scr);
    cudaFuncSetAttribute(fused_kernel, cudaFuncAttributeMaxDynamicSharedMemorySize, SMEM_BYTES);
  }
  CUtensorMap tmGX, tmUX, tmGY, tmUY, tmD, tmWR, tmWI;
  const cuuint32_t es[5] = {1, 1, 1, 1, 1};
  auto enc = [&](CUtensorMap* m, void* p, int rank, const cuuint64_t* gd, const cuuint64_t* gs, const cuuint32_t* bd,
                 CUtensorMapSwizzle sw, CUtensorMapL2promotion pr) {
    encode(m, CU_TENSOR_MAP_DATA_TYPE_BFLOAT16, rank, p, gd, gs, bd, es, CU_TENSOR_MAP_INTERLEAVE_NONE, sw, pr,
           CU_TENSOR_MAP_FLOAT_OOB_FILL_NONE);
  };
  {
    const cuuint64_t gd[3] = {64, 512, 28}, gs[2] = {3584, 128};
    const cuuint32_t bd[3] = {64, 32, 2};
    enc(&tmGX, d_in[4], 3, gd, gs, bd, CU_TENSOR_MAP_SWIZZLE_128B, CU_TENSOR_MAP_L2_PROMOTION_L2_256B);
    enc(&tmUX, d_in[5], 3, gd, gs, bd, CU_TENSOR_MAP_SWIZZLE_128B, CU_TENSOR_MAP_L2_PROMOTION_L2_256B);
  }
  {
    const cuuint64_t gd[3] = {32, 512, 56}, gs[2] = {3584, 64};
    const cuuint32_t bd[3] = {32, 32, 3};
    enc(&tmGY, d_in[4], 3, gd, gs, bd, CU_TENSOR_MAP_SWIZZLE_64B, CU_TENSOR_MAP_L2_PROMOTION_L2_128B);
    enc(&tmUY, d_in[5], 3, gd, gs, bd, CU_TENSOR_MAP_SWIZZLE_64B, CU_TENSOR_MAP_L2_PROMOTION_L2_128B);
  }
  {
    const cuuint64_t gd[3] = {64, 1792, 8}, gs[2] = {1024, 128};
    const cuuint32_t bd[3] = {64, 64, 2};
    enc(&tmD, d_in[6], 3, gd, gs, bd, CU_TENSOR_MAP_SWIZZLE_128B, CU_TENSOR_MAP_L2_PROMOTION_L2_256B);
  }
  {
    const cuuint64_t gd[3] = {4112, 8, 16}, gs[2] = {16 * 8224, 8224};
    const cuuint32_t bd[3] = {40, 8, 16};
    enc(&tmWR, d_in[1], 3, gd, gs, bd, CU_TENSOR_MAP_SWIZZLE_NONE, CU_TENSOR_MAP_L2_PROMOTION_NONE);
    enc(&tmWI, d_in[2], 3, gd, gs, bd, CU_TENSOR_MAP_SWIZZLE_NONE, CU_TENSOR_MAP_L2_PROMOTION_NONE);
  }
  fused_kernel<<<NCTA, NTHREADS, SMEM_BYTES>>>((const __nv_bfloat16*)d_in[0], (const Tables*)tab, (Scratch*)scr,
                                               (__nv_bfloat16*)d_out, (const char*)d_in[4], (const char*)d_in[5],
                                               (const char*)d_in[6], tmWR, tmWI, tmGX, tmUX, tmGY, tmUY, tmD);
}
```

```cpp
#include <cuda_runtime.h>
#include <cuda_bf16.h>
#include <cuda.h>
#include <stdint.h>

namespace {

constexpr int NCTA = 128;
constexpr int NTHREADS = 384;
constexpr int SLOT = 16384;
constexpr int SMEM_BYTES = 14 * SLOT + 3072;
constexpr int SPIN_LIMIT = 1 << 22;

struct Scratch {
  uint4 Z1[128 * 1024];
  uint4 LN[16 * 8 * 1024];
  uint4 P[16 * 28 * 1024];
  uint4 ST[1024];
  unsigned cnt[64 * 32];
};
__device__ __align__(1024) Scratch g_scr;

constexpr double ccos(int i, int n) {
  i &= n - 1;
  if (i > n / 2) i = n - i;
  if (4 * i == n) return 0.0;
  const bool neg = 4 * i > n;
  if (neg) i = n / 2 - i;
  const double a = 6.283185307179586476925 * i / n, a2 = a * a;
  double term = 1.0, sum = 1.0;
  for (int k = 1; k < 14; k++) { term *= -a2 / ((2 * k - 1) * (2 * k)); sum += term; }
  return neg ? -sum : sum;
}
constexpr double csin(int i, int n) { return ccos(i - n / 4, n); }
constexpr unsigned fbits(double v, int mant) {
  if (v == 0.0) return 0;
  const unsigned sg = v < 0 ? 1u : 0u;
  if (v < 0) v = -v;
  int e = 127;
  while (v < 1.0) { v *= 2.0; e--; }
  const unsigned m = (unsigned)((v - 1.0) * (double)(1u << mant) + 0.5);
  return (sg << (8 + mant)) + ((unsigned)e << mant) + m;
}
constexpr unsigned pkb(double lo, double hi) { return fbits(lo, 7) | (fbits(hi, 7) << 16); }
constexpr double fa_elem(int mt, int r, int n1) {
  const int k1 = 8 * mt + (r & 7);
  return r < 8 ? ccos(k1 * n1, 32) : k1 == 0 ? ccos(16 * n1, 32) : -csin(k1 * n1, 32);
}
constexpr unsigned cfrag_c(int idx, int n, int ri, double s = 1.0) {
  return ri ? pkb(-s * csin(idx, n), s * ccos(idx, n)) : pkb(s * ccos(idx, n), s * csin(idx, n));
}
struct Tables {
  unsigned fa[4][32][4];
  unsigned fb[4][32][4];
  unsigned tw1[6][32][4];
  unsigned f2[8][4][32][4];
  unsigned g2[8][4][32][4];
  unsigned gb[4][32][4];
  unsigned ga[4][32][4];
  unsigned tw3[4][32][4];
  unsigned f8[32][4], g8[32][4];
};
constexpr int T1_BYTES = 7168, T2_BYTES = 39936;
static_assert(sizeof(Tables) == T1_BYTES + T2_BYTES, "table size");
constexpr Tables make_tables() {
  Tables T = {};
  for (int l = 0; l < 32; l++) {
    const int g = l >> 2, t = l & 3;
    for (int a = 0; a < 2; a++)
      for (int b = 0; b < 2; b++) {
        for (int r = 0; r < 4; r++) {
          const int row = g + 8 * (r & 1), col = 2 * t + 8 * (r >> 1);
          T.fa[2 * a + b][l][r] = pkb(fa_elem(a, row, 16 * b + col), fa_elem(a, row, 16 * b + col + 1));
          T.ga[2 * a + b][l][r] = pkb(fa_elem(b, col, 16 * a + row), fa_elem(b, col + 1, 16 * a + row));
        }
        const double sg = b ? -1.0 : 1.0;
        for (int h = 0; h < 2; h++) {
          const int ri = g & 1, m = 2 * (g >> 1) + h, k2 = b ? 15 - m : m;
          const int pa = (8 * a + 2 * t) * k2, pb = (8 * a + 2 * t + 1) * k2;
          T.fb[2 * a + b][l][2 * h] = ri == 0 ? pkb(ccos(pa, 16), ccos(pb, 16)) : pkb(-sg * csin(pa, 16), -sg * csin(pb, 16));
          T.fb[2 * a + b][l][2 * h + 1] = ri == 0 ? pkb(csin(pa, 16), csin(pb, 16)) : pkb(sg * ccos(pa, 16), sg * ccos(pb, 16));
        }
        const int n2 = 4 * (g >> 1) + 2 * a + (g & 1);
        for (int h = 0; h < 2; h++) {
          const int p = n2 * (b ? 15 - 2 * t - h : 2 * t + h);
          T.gb[2 * a + b][l][2 * h] = pkb(ccos(p, 16), -sg * csin(p, 16));
          T.gb[2 * a + b][l][2 * h + 1] = pkb(csin(p, 16), sg * ccos(p, 16));
          const int k1 = 8 * b + 2 * t + h, q = n2 * (k1 == 0 ? 16 : k1);
          T.tw3[2 * a + b][l][2 * h] = fbits(ccos(q, 512), 23);
          T.tw3[2 * a + b][l][2 * h + 1] = fbits(csin(q, 512), 23);
        }
        const int p = (8 * a + 2 * t + b) * (g == 0 ? 16 : g);
        T.tw1[2 * a + b][l][0] = fbits(g == 0 ? 0.0 : ccos(p, 512), 23);
        T.tw1[2 * a + b][l][1] = fbits(g == 0 ? ccos(p, 512) : csin(p, 512), 23);
        T.tw1[2 * a + b][l][2] = fbits(g == 0 ? 0.0 : -csin(p, 512), 23);
        T.tw1[2 * a + b][l][3] = fbits(g == 0 ? -csin(p, 512) : ccos(p, 512), 23);
        T.tw1[4 + a][l][2 * b] = fbits(ccos((8 * a + 2 * t + b) * (g + 8), 512), 23);
        T.tw1[4 + a][l][2 * b + 1] = fbits(csin((8 * a + 2 * t + b) * (g + 8), 512), 23);
      }
    for (int i = 0; i < 4; i++) {
      const int p8 = (t + 4 * (i & 1)) * (4 * (i >> 1) + (g >> 1));
      T.f8[l][i] = cfrag_c(p8, 8, g & 1);
      T.g8[l][i] = cfrag_c(-p8, 8, g & 1, 1.0 / (1 << 19));
    }
    for (int w = 0; w < 8; w++)
      for (int i = 0; i < 16; i++) {
        const int kidx = t + 4 * (i & 1) + 8 * (i >> 3), nidx = 4 * ((i >> 1) & 3) + (g >> 1);
        T.f2[w][i >> 2][l][i & 3] = cfrag_c((8 * kidx + w) * nidx, 128, g & 1);
        T.g2[w][i >> 2][l][i & 3] = cfrag_c(-(8 * nidx + w) * kidx, 128, g & 1);
      }
  }
  return T;
}
__device__ const __align__(128) Tables g_tab = make_tables();

__device__ __forceinline__ void die() { asm volatile("st.global.u32 [%0], %1;" ::"l"(0ull), "r"(0) : "memory"); }
__device__ __forceinline__ uint32_t s2u(const void* p) { return (uint32_t)__cvta_generic_to_shared(p); }
__device__ __forceinline__ void mbar_init(uint32_t b, int c) { asm volatile("mbarrier.init.shared::cta.b64 [%0], %1;" ::"r"(b), "r"(c)); }
__device__ __forceinline__ void mbar_expect(uint32_t b, int bytes) {
  asm volatile("mbarrier.arrive.expect_tx.shared::cta.b64 _, [%0], %1;" ::"r"(b), "r"(bytes) : "memory");
}
__device__ __forceinline__ void mbar_arrive(uint32_t b) { asm volatile("mbarrier.arrive.shared::cta.b64 _, [%0];" ::"r"(b) : "memory"); }
__device__ __forceinline__ uint32_t mbar_try(uint32_t b, uint32_t parity) {
  uint32_t ok;
  asm volatile("{.reg .pred p; mbarrier.try_wait.parity.shared::cta.b64 p, [%1], %2; selp.u32 %0,1,0,p;}"
               : "=r"(ok) : "r"(b), "r"(parity) : "memory");
  return ok;
}
__device__ __forceinline__ uint32_t mbar_test(uint32_t b) {
  uint32_t ok;
  asm volatile("{.reg .pred p; mbarrier.test_wait.parity.shared::cta.b64 p, [%1], 0; selp.u32 %0,1,0,p;}" : "=r"(ok) : "r"(b) : "memory");
  return ok;
}
__device__ __forceinline__ void mbar_wait_bounded(uint32_t b) {
  int it = 0;
#pragma unroll 1
  while (!mbar_try(b, 0))
    if (++it > SPIN_LIMIT) { die(); break; }
}
__device__ __forceinline__ void mbar_wait(uint32_t b) {
  asm volatile("{.reg .pred p;\nW_%=: mbarrier.try_wait.parity.shared::cta.b64 p, [%0], 0;\n@!p bra W_%=;}" ::"r"(b) : "memory");
}
__device__ __forceinline__ void bar_sync(int id, int n) { asm volatile("bar.sync %0, %1;" ::"r"(id), "r"(n) : "memory"); }
__device__ __forceinline__ void bar_arrive(int id, int n) { asm volatile("bar.arrive %0, %1;" ::"r"(id), "r"(n) : "memory"); }
__device__ __forceinline__ void red_release(unsigned* p) { asm volatile("red.release.gpu.global.add.u32 [%0], 1;" ::"l"(p) : "memory"); }
__device__ __forceinline__ void red_relaxed(unsigned* p) { asm volatile("red.relaxed.gpu.global.add.u32 [%0], 1;" ::"l"(p) : "memory"); }
__device__ __forceinline__ unsigned ld_acquire(const unsigned* p) {
  unsigned v;
  asm volatile("ld.acquire.gpu.global.u32 %0, [%1];" : "=r"(v) : "l"(p) : "memory");
  return v;
}
__device__ __forceinline__ unsigned ld_relaxed(const unsigned* p) {
  unsigned v;
  asm volatile("ld.relaxed.gpu.global.u32 %0, [%1];" : "=r"(v) : "l"(p) : "memory");
  return v;
}
__device__ __forceinline__ void wait_counter(const unsigned* p, unsigned target) {
#pragma unroll 1
  while ((int)(ld_acquire(p) - target) < 0) {}
}
__device__ __forceinline__ void sts4(uint32_t a, uint32_t x, uint32_t y, uint32_t z, uint32_t w) {
  asm volatile("st.shared.v4.u32 [%0], {%1,%2,%3,%4};" ::"r"(a), "r"(x), "r"(y), "r"(z), "r"(w) : "memory");
}
__device__ __forceinline__ uint4 lds4(uint32_t a) {
  uint4 v;
  asm volatile("ld.shared.v4.u32 {%0,%1,%2,%3}, [%4];" : "=r"(v.x), "=r"(v.y), "=r"(v.z), "=r"(v.w) : "r"(a) : "memory");
  return v;
}
__device__ __forceinline__ uint32_t pack2(float lo, float hi) {
  uint32_t r;
  asm("cvt.rn.bf16x2.f32 %0, %1, %2;" : "=r"(r) : "f"(hi), "f"(lo));
  return r;
}
__device__ __forceinline__ float bf_lo(uint32_t v) { return __uint_as_float(v << 16); }
__device__ __forceinline__ uint32_t hadd2_bf16(uint32_t a, uint32_t b) {
  uint32_t r;
  asm("add.rn.bf16x2 %0, %1, %2;" : "=r"(r) : "r"(a), "r"(b));
  return r;
}
__device__ __forceinline__ void mma16816(float (&d)[4], uint32_t a0, uint32_t a1, uint32_t a2, uint32_t a3, uint32_t b0, uint32_t b1) {
  asm("mma.sync.aligned.m16n8k16.row.col.f32.bf16.bf16.f32 {%0,%1,%2,%3}, {%4,%5,%6,%7}, {%8,%9}, {%0,%1,%2,%3};"
      : "+f"(d[0]), "+f"(d[1]), "+f"(d[2]), "+f"(d[3])
      : "r"(a0), "r"(a1), "r"(a2), "r"(a3), "r"(b0), "r"(b1));
}
__device__ __forceinline__ void mma16816_z(float (&d)[4], uint32_t a0, uint32_t a1, uint32_t a2, uint32_t a3, uint32_t b0, uint32_t b1) {
  asm("{.reg .f32 z; mov.f32 z, 0f00000000;\n"
      "mma.sync.aligned.m16n8k16.row.col.f32.bf16.bf16.f32 {%0,%1,%2,%3}, {%4,%5,%6,%7}, {%8,%9}, {z,z,z,z};}"
      : "=f"(d[0]), "=f"(d[1]), "=f"(d[2]), "=f"(d[3])
      : "r"(a0), "r"(a1), "r"(a2), "r"(a3), "r"(b0), "r"(b1));
}
template <int N>
__device__ __forceinline__ void cs_frac(int idx, float& c, float& s) {
  int i = ((idx + N / 2) & (N - 1)) - N / 2;
  float a = (float)i * (6.283185307179586f / N);
  c = __cosf(a);
  s = __sinf(a);
}
template <int N>
__device__ __forceinline__ uint32_t cfrag(int idx, int ri) {
  float c, s;
  cs_frac<N>(idx, c, s);
  return ri ? pack2(-s, c) : pack2(c, s);
}
__device__ __forceinline__ uint32_t word(const uint4& v, int e) { return e == 0 ? v.x : e == 1 ? v.y : e == 2 ? v.z : v.w; }
__device__ __forceinline__ void cdft16(const uint4 (&A)[4], const uint4 (&F)[4], uint4 (&o)[4]) {
  float acc[2][4][4];
#pragma unroll
  for (int ks = 0; ks < 2; ks++)
#pragma unroll
    for (int p = 0; p < 2; p++)
#pragma unroll
      for (int v = 0; v < 4; v++) {
        const uint4& a = A[2 * ks + p];
        const uint32_t b0 = word(F[ks * 2 + (v >> 1)], (v & 1) * 2), b1 = word(F[ks * 2 + (v >> 1)], (v & 1) * 2 + 1);
        if (ks == 0) mma16816_z(acc[p][v], a.x, a.y, a.z, a.w, b0, b1);
        else mma16816(acc[p][v], a.x, a.y, a.z, a.w, b0, b1);
      }
#pragma unroll
  for (int v = 0; v < 4; v++)
    o[v] = make_uint4(pack2(acc[0][v][0], acc[0][v][1]), pack2(acc[0][v][2], acc[0][v][3]),
                      pack2(acc[1][v][0], acc[1][v][1]), pack2(acc[1][v][2], acc[1][v][3]));
}
__device__ __forceinline__ void lds_frag(uint4& f0, uint4& f1, uint32_t a0, uint32_t a1) {
  asm volatile("ld.volatile.shared.v2.u32 {%0,%1}, [%8]; ld.volatile.shared.v2.u32 {%2,%3}, [%9];\n"
               "ld.volatile.shared.v2.u32 {%4,%5}, [%8+8]; ld.volatile.shared.v2.u32 {%6,%7}, [%9+8];"
               : "=r"(f0.x), "=r"(f0.y), "=r"(f0.z), "=r"(f0.w), "=r"(f1.x), "=r"(f1.y), "=r"(f1.z), "=r"(f1.w) : "r"(a0), "r"(a1) : "memory");
}
__device__ __forceinline__ void reg_frag(uint4 (&q)[4], uint32_t ones) {
#pragma unroll
  for (int ks = 0; ks < 2; ks++) {
    const uint4 a = q[2 * ks], b = q[2 * ks + 1];
    q[2 * ks] = make_uint4(a.x, a.y, b.x & ones, b.y & ones);
    q[2 * ks + 1] = make_uint4(a.z & ones, a.w & ones, b.z, b.w);
  }
}
__device__ __forceinline__ void st_tag(uint4* p, const uint4& v, uint32_t tag) {
  asm volatile("st.relaxed.gpu.global.v4.b32 [%0], {%1,%2,%3,%4};"
               ::"l"(p), "r"((v.x & ~1u) | tag), "r"(v.y), "r"(v.z), "r"(v.w) : "memory");
}
__device__ __forceinline__ void st_tag8(void* p, uint32_t x, uint32_t y, uint32_t tag) {
  asm volatile("st.relaxed.gpu.global.v2.b32 [%0], {%1,%2};" ::"l"(p), "r"((x & ~1u) | tag), "r"(y) : "memory");
}
__device__ __forceinline__ uint4 ld_b128(const uint4* p) {
  uint4 v;
  asm volatile("ld.relaxed.gpu.global.v4.b32 {%0,%1,%2,%3}, [%4];"
               : "=r"(v.x), "=r"(v.y), "=r"(v.z), "=r"(v.w) : "l"(p) : "memory");
  return v;
}
template <int STRIDE>
__device__ __forceinline__ void ld_tag4_issue(uint4 (&q)[4], const uint4* p) {
#pragma unroll
  for (int i = 0; i < 4; i++) q[i] = ld_b128(p + i * STRIDE);
}
__device__ __forceinline__ uint32_t tag_miss(uint32_t a, uint32_t b, uint32_t c, uint32_t d, uint32_t tag) {
  uint32_t r;
  asm("{.reg .b32 u, v; lop3.b32 u, %1, %2, %5, 0x7e; lop3.b32 v, %3, %4, %5, 0x7e; lop3.b32 %0, u, v, 1, 0xa8;}"
      : "=r"(r) : "r"(a), "r"(b), "r"(c), "r"(d), "r"(tag));
  return r;
}
template <int STRIDE, bool HALVES = false>
__device__ __forceinline__ void ld_tag4_finish(uint4 (&q)[4], const uint4* p, uint32_t tag) {
  int it = 0;
#pragma unroll 1
  while (__any_sync(0xffffffffu, tag_miss(q[0].x, q[1].x, q[2].x, q[3].x, tag) | (HALVES ? tag_miss(q[0].z, q[1].z, q[2].z, q[3].z, tag) : 0u))) {
    ld_tag4_issue<STRIDE>(q, p);
    if (++it > SPIN_LIMIT) { die(); break; }
  }
#pragma unroll
  for (int i = 0; i < 4; i++) {
    asm volatile("and.b32 %0, %0, 0xfffffffe;" : "+r"(q[i].x));
    if (HALVES) q[i].z &= ~1u;
  }
}
__device__ __forceinline__ float quad_sum(const uint32_t (&a)[8]) {
  float d[4];
  mma16816_z(d, a[0], a[1], a[2], a[3], 0x3f803f80u, 0x3f803f80u);
  mma16816(d, a[4], a[5], a[6], a[7], 0x3f803f80u, 0x3f803f80u);
  return d[0] + d[2];
}
__device__ __forceinline__ float sum_groups(float v) {
  v += __shfl_xor_sync(0xffffffffu, v, 4);
  v += __shfl_xor_sync(0xffffffffu, v, 8);
  v += __shfl_xor_sync(0xffffffffu, v, 16);
  return v;
}
__device__ __forceinline__ uint32_t hsub2_bf16(uint32_t a, uint32_t b) {
  uint32_t r;
  asm("sub.rn.bf16x2 %0, %1, %2;" : "=r"(r) : "r"(a), "r"(b));
  return r;
}
__device__ __forceinline__ float row_rstd(const uint32_t (&c)[8], float delta) {
  uint32_t s[8];
#pragma unroll
  for (int i = 0; i < 8; i++) asm("mul.rn.bf16x2 %0, %1, %1;" : "=r"(s[i]) : "r"(c[i]));
  return rsqrtf(fmaxf(fmaf(-delta, delta, sum_groups(quad_sum(s)) * (1.f / 512.f)), 0.f) + 1e-5f);
}
__device__ __forceinline__ uint64_t desc64(uint32_t lo, uint32_t hi) {
  uint64_t d;
  asm("mov.b64 %0, {%1, %2};" : "=l"(d) : "r"(lo), "r"(hi));
  return d;
}
constexpr uint32_t desc_hi(uint32_t sbo, uint32_t swz) { return (sbo >> 4) | (swz << 30); }
__device__ __forceinline__ uint32_t desc_lo(uint32_t addr, uint32_t lbo) { return ((addr & 0x3FFFF) >> 4) | ((lbo >> 4) << 16); }
__device__ __forceinline__ void cp_async16(uint32_t dst, const void* src) {
  asm volatile("cp.async.cg.shared.global [%0], [%1], 16;" ::"r"(dst), "l"(src) : "memory");
}
__device__ __forceinline__ uint2 lds2(uint32_t a) {
  uint2 v;
  asm volatile("ld.shared.v2.u32 {%0,%1}, [%2];" : "=r"(v.x), "=r"(v.y) : "r"(a) : "memory");
  return v;
}
__device__ __forceinline__ uint32_t lds_u16(uint32_t a) {
  uint16_t v;
  asm volatile("ld.shared.u16 %0, [%1];" : "=h"(v) : "r"(a) : "memory");
  return v;
}
__device__ __forceinline__ void wg_fence() { asm volatile("wgmma.fence.sync.aligned;" ::: "memory"); }
__device__ __forceinline__ void wg_commit() { asm volatile("wgmma.commit_group.sync.aligned;" ::: "memory"); }
template <int N>
__device__ __forceinline__ void wg_wait() { asm volatile("wgmma.wait_group.sync.aligned %0;" ::"n"(N) : "memory"); }
__device__ __forceinline__ void bulk_load(uint32_t dst, const void* src, int bytes, uint32_t bar) {
  asm volatile("cp.async.bulk.shared::cluster.global.mbarrier::complete_tx::bytes [%0], [%1], %2, [%3];"
               ::"r"(dst), "l"(src), "r"(bytes), "r"(bar) : "memory");
}
__device__ __forceinline__ void bulk_load_mc(uint32_t dst, const void* src, int bytes, uint32_t bar) {
  asm volatile("cp.async.bulk.shared::cluster.global.mbarrier::complete_tx::bytes.multicast::cluster [%0], [%1], %2, [%3], %4;"
               ::"r"(dst), "l"(src), "r"(bytes), "r"(bar), "h"((uint16_t)3) : "memory");
}
__device__ __forceinline__ void tma3(uint32_t dst, const CUtensorMap* tm, uint32_t bar, int c0, int c1, int c2) {
  asm volatile("cp.async.bulk.tensor.3d.shared::cluster.global.mbarrier::complete_tx::bytes [%0], [%1, {%3,%4,%5}], [%2];"
               ::"r"(dst), "l"(tm), "r"(bar), "r"(c0), "r"(c1), "r"(c2) : "memory");
}
__device__ __forceinline__ void tma3_mc(uint32_t dst, const CUtensorMap* tm, uint32_t bar, int c1, int c2) {
  asm volatile("cp.async.bulk.tensor.3d.shared::cluster.global.mbarrier::complete_tx::bytes.multicast::cluster [%0], [%1, {%3,%4,%5}], [%2], %6;"
               ::"r"(dst), "l"(tm), "r"(bar), "r"(0), "r"(c1), "r"(c2), "h"((uint16_t)3) : "memory");
}
__device__ __forceinline__ void mbar_arrive_remote(uint32_t rb) {
  asm volatile("mbarrier.arrive.shared::cluster.b64 _, [%0];" ::"r"(rb) : "memory");
}
__device__ __forceinline__ uint4 ldg_ca4(const void* p) {
  uint4 v;
  asm volatile("ld.global.ca.v4.u32 {%0,%1,%2,%3}, [%4];" : "=r"(v.x), "=r"(v.y), "=r"(v.z), "=r"(v.w) : "l"(p) : "memory");
  return v;
}
__device__ __forceinline__ float u2f(uint32_t v) { return __uint_as_float(v); }
__device__ __forceinline__ void mma_az(float (&d)[4], const uint4& a, uint32_t b0, uint32_t b1) { mma16816_z(d, a.x, a.y, a.z, a.w, b0, b1); }
__device__ __forceinline__ void mma_a(float (&d)[4], const uint4& a, uint32_t b0, uint32_t b1) { mma16816(d, a.x, a.y, a.z, a.w, b0, b1); }
__device__ __forceinline__ uint32_t clock32() {
  uint32_t v;
  asm volatile("mov.u32 %0, %%clock;" : "=r"(v) :: "memory");
  return v;
}
__device__ __forceinline__ float swiglu(float g, float u, float r) {
  float hg = (0.5f * r) * g, th;
  asm("tanh.approx.f32 %0, %1;" : "=f"(th) : "f"(hg));
  return fmaf(hg, th, hg) * (r * u);
}
__device__ __forceinline__ void l2_prefetch(const void* p, int bytes) {
  asm volatile("cp.async.bulk.prefetch.L2.global [%0], %1;" ::"l"(p), "r"(bytes) : "memory");
}

__device__ __forceinline__ void wgmma_n256(float (&d)[128], uint64_t da, uint64_t db, int sd = 1) {
  asm volatile("{.reg .pred p; setp.ne.b32 p, %130, 0;\n"
      "wgmma.mma_async.sync.aligned.m64n256k16.f32.bf16.bf16 {"
      "%0,%1,%2,%3,%4,%5,%6,%7,%8,%9,%10,%11,%12,%13,%14,%15,"
      "%16,%17,%18,%19,%20,%21,%22,%23,%24,%25,%26,%27,%28,%29,%30,%31,"
      "%32,%33,%34,%35,%36,%37,%38,%39,%40,%41,%42,%43,%44,%45,%46,%47,"
      "%48,%49,%50,%51,%52,%53,%54,%55,%56,%57,%58,%59,%60,%61,%62,%63,"
      "%64,%65,%66,%67,%68,%69,%70,%71,%72,%73,%74,%75,%76,%77,%78,%79,"
      "%80,%81,%82,%83,%84,%85,%86,%87,%88,%89,%90,%91,%92,%93,%94,%95,"
      "%96,%97,%98,%99,%100,%101,%102,%103,%104,%105,%106,%107,%108,%109,%110,%111,"
      "%112,%113,%114,%115,%116,%117,%118,%119,%120,%121,%122,%123,%124,%125,%126,%127"
      "}, %128, %129, p, 1, 1, 0, 1;}\n"
      : "+f"(d[0]),"+f"(d[1]),"+f"(d[2]),"+f"(d[3]),"+f"(d[4]),"+f"(d[5]),"+f"(d[6]),"+f"(d[7]),
        "+f"(d[8]),"+f"(d[9]),"+f"(d[10]),"+f"(d[11]),"+f"(d[12]),"+f"(d[13]),"+f"(d[14]),"+f"(d[15]),
        "+f"(d[16]),"+f"(d[17]),"+f"(d[18]),"+f"(d[19]),"+f"(d[20]),"+f"(d[21]),"+f"(d[22]),"+f"(d[23]),
        "+f"(d[24]),"+f"(d[25]),"+f"(d[26]),"+f"(d[27]),"+f"(d[28]),"+f"(d[29]),"+f"(d[30]),"+f"(d[31]),
        "+f"(d[32]),"+f"(d[33]),"+f"(d[34]),"+f"(d[35]),"+f"(d[36]),"+f"(d[37]),"+f"(d[38]),"+f"(d[39]),
        "+f"(d[40]),"+f"(d[41]),"+f"(d[42]),"+f"(d[43]),"+f"(d[44]),"+f"(d[45]),"+f"(d[46]),"+f"(d[47]),
        "+f"(d[48]),"+f"(d[49]),"+f"(d[50]),"+f"(d[51]),"+f"(d[52]),"+f"(d[53]),"+f"(d[54]),"+f"(d[55]),
        "+f"(d[56]),"+f"(d[57]),"+f"(d[58]),"+f"(d[59]),"+f"(d[60]),"+f"(d[61]),"+f"(d[62]),"+f"(d[63]),
        "+f"(d[64]),"+f"(d[65]),"+f"(d[66]),"+f"(d[67]),"+f"(d[68]),"+f"(d[69]),"+f"(d[70]),"+f"(d[71]),
        "+f"(d[72]),"+f"(d[73]),"+f"(d[74]),"+f"(d[75]),"+f"(d[76]),"+f"(d[77]),"+f"(d[78]),"+f"(d[79]),
        "+f"(d[80]),"+f"(d[81]),"+f"(d[82]),"+f"(d[83]),"+f"(d[84]),"+f"(d[85]),"+f"(d[86]),"+f"(d[87]),
        "+f"(d[88]),"+f"(d[89]),"+f"(d[90]),"+f"(d[91]),"+f"(d[92]),"+f"(d[93]),"+f"(d[94]),"+f"(d[95]),
        "+f"(d[96]),"+f"(d[97]),"+f"(d[98]),"+f"(d[99]),"+f"(d[100]),"+f"(d[101]),"+f"(d[102]),"+f"(d[103]),
        "+f"(d[104]),"+f"(d[105]),"+f"(d[106]),"+f"(d[107]),"+f"(d[108]),"+f"(d[109]),"+f"(d[110]),"+f"(d[111]),
        "+f"(d[112]),"+f"(d[113]),"+f"(d[114]),"+f"(d[115]),"+f"(d[116]),"+f"(d[117]),"+f"(d[118]),"+f"(d[119]),
        "+f"(d[120]),"+f"(d[121]),"+f"(d[122]),"+f"(d[123]),"+f"(d[124]),"+f"(d[125]),"+f"(d[126]),"+f"(d[127])
      : "l"(da), "l"(db), "r"(sd));
}
__device__ __forceinline__ void wgmma_n192(float (&d)[96], uint64_t da, uint64_t db) {
  asm volatile("wgmma.mma_async.sync.aligned.m64n192k16.f32.bf16.bf16 {"
      "%0,%1,%2,%3,%4,%5,%6,%7,%8,%9,%10,%11,%12,%13,%14,%15,"
      "%16,%17,%18,%19,%20,%21,%22,%23,%24,%25,%26,%27,%28,%29,%30,%31,"
      "%32,%33,%34,%35,%36,%37,%38,%39,%40,%41,%42,%43,%44,%45,%46,%47,"
      "%48,%49,%50,%51,%52,%53,%54,%55,%56,%57,%58,%59,%60,%61,%62,%63,"
      "%64,%65,%66,%67,%68,%69,%70,%71,%72,%73,%74,%75,%76,%77,%78,%79,"
      "%80,%81,%82,%83,%84,%85,%86,%87,%88,%89,%90,%91,%92,%93,%94,%95"
      "}, %96, %97, 1, 1, 1, 0, 1;\n"
      : "+f"(d[0]),"+f"(d[1]),"+f"(d[2]),"+f"(d[3]),"+f"(d[4]),"+f"(d[5]),"+f"(d[6]),"+f"(d[7]),
        "+f"(d[8]),"+f"(d[9]),"+f"(d[10]),"+f"(d[11]),"+f"(d[12]),"+f"(d[13]),"+f"(d[14]),"+f"(d[15]),
        "+f"(d[16]),"+f"(d[17]),"+f"(d[18]),"+f"(d[19]),"+f"(d[20]),"+f"(d[21]),"+f"(d[22]),"+f"(d[23]),
        "+f"(d[24]),"+f"(d[25]),"+f"(d[26]),"+f"(d[27]),"+f"(d[28]),"+f"(d[29]),"+f"(d[30]),"+f"(d[31]),
        "+f"(d[32]),"+f"(d[33]),"+f"(d[34]),"+f"(d[35]),"+f"(d[36]),"+f"(d[37]),"+f"(d[38]),"+f"(d[39]),
        "+f"(d[40]),"+f"(d[41]),"+f"(d[42]),"+f"(d[43]),"+f"(d[44]),"+f"(d[45]),"+f"(d[46]),"+f"(d[47]),
        "+f"(d[48]),"+f"(d[49]),"+f"(d[50]),"+f"(d[51]),"+f"(d[52]),"+f"(d[53]),"+f"(d[54]),"+f"(d[55]),
        "+f"(d[56]),"+f"(d[57]),"+f"(d[58]),"+f"(d[59]),"+f"(d[60]),"+f"(d[61]),"+f"(d[62]),"+f"(d[63]),
        "+f"(d[64]),"+f"(d[65]),"+f"(d[66]),"+f"(d[67]),"+f"(d[68]),"+f"(d[69]),"+f"(d[70]),"+f"(d[71]),
        "+f"(d[72]),"+f"(d[73]),"+f"(d[74]),"+f"(d[75]),"+f"(d[76]),"+f"(d[77]),"+f"(d[78]),"+f"(d[79]),
        "+f"(d[80]),"+f"(d[81]),"+f"(d[82]),"+f"(d[83]),"+f"(d[84]),"+f"(d[85]),"+f"(d[86]),"+f"(d[87]),
        "+f"(d[88]),"+f"(d[89]),"+f"(d[90]),"+f"(d[91]),"+f"(d[92]),"+f"(d[93]),"+f"(d[94]),"+f"(d[95])
      : "l"(da), "l"(db));
}
__device__ __forceinline__ void wgmma_rs_n128(float (&d)[64], uint32_t a0, uint32_t a1, uint32_t a2, uint32_t a3, uint64_t db, int sd = 1) {
  asm volatile("{.reg .pred p; setp.ne.b32 p, %69, 0;\n"
      "wgmma.mma_async.sync.aligned.m64n128k16.f32.bf16.bf16 {"
      "%0,%1,%2,%3,%4,%5,%6,%7,%8,%9,%10,%11,%12,%13,%14,%15,"
      "%16,%17,%18,%19,%20,%21,%22,%23,%24,%25,%26,%27,%28,%29,%30,%31,"
      "%32,%33,%34,%35,%36,%37,%38,%39,%40,%41,%42,%43,%44,%45,%46,%47,"
      "%48,%49,%50,%51,%52,%53,%54,%55,%56,%57,%58,%59,%60,%61,%62,%63"
      "}, {%64,%65,%66,%67}, %68, p, 1, 1, 1;}\n"
      : "+f"(d[0]),"+f"(d[1]),"+f"(d[2]),"+f"(d[3]),"+f"(d[4]),"+f"(d[5]),"+f"(d[6]),"+f"(d[7]),
        "+f"(d[8]),"+f"(d[9]),"+f"(d[10]),"+f"(d[11]),"+f"(d[12]),"+f"(d[13]),"+f"(d[14]),"+f"(d[15]),
        "+f"(d[16]),"+f"(d[17]),"+f"(d[18]),"+f"(d[19]),"+f"(d[20]),"+f"(d[21]),"+f"(d[22]),"+f"(d[23]),
        "+f"(d[24]),"+f"(d[25]),"+f"(d[26]),"+f"(d[27]),"+f"(d[28]),"+f"(d[29]),"+f"(d[30]),"+f"(d[31]),
        "+f"(d[32]),"+f"(d[33]),"+f"(d[34]),"+f"(d[35]),"+f"(d[36]),"+f"(d[37]),"+f"(d[38]),"+f"(d[39]),
        "+f"(d[40]),"+f"(d[41]),"+f"(d[42]),"+f"(d[43]),"+f"(d[44]),"+f"(d[45]),"+f"(d[46]),"+f"(d[47]),
        "+f"(d[48]),"+f"(d[49]),"+f"(d[50]),"+f"(d[51]),"+f"(d[52]),"+f"(d[53]),"+f"(d[54]),"+f"(d[55]),
        "+f"(d[56]),"+f"(d[57]),"+f"(d[58]),"+f"(d[59]),"+f"(d[60]),"+f"(d[61]),"+f"(d[62]),"+f"(d[63])
      : "r"(a0), "r"(a1), "r"(a2), "r"(a3), "l"(db), "r"(sd));
}
__device__ __forceinline__ void wgmma_rs_n256(float (&d)[128], uint32_t a0, uint32_t a1, uint32_t a2, uint32_t a3, uint64_t db, int sd = 1) {
  asm volatile("{.reg .pred p; setp.ne.b32 p, %133, 0;\n"
      "wgmma.mma_async.sync.aligned.m64n256k16.f32.bf16.bf16 {"
      "%0,%1,%2,%3,%4,%5,%6,%7,%8,%9,%10,%11,%12,%13,%14,%15,"
      "%16,%17,%18,%19,%20,%21,%22,%23,%24,%25,%26,%27,%28,%29,%30,%31,"
      "%32,%33,%34,%35,%36,%37,%38,%39,%40,%41,%42,%43,%44,%45,%46,%47,"
      "%48,%49,%50,%51,%52,%53,%54,%55,%56,%57,%58,%59,%60,%61,%62,%63,"
      "%64,%65,%66,%67,%68,%69,%70,%71,%72,%73,%74,%75,%76,%77,%78,%79,"
      "%80,%81,%82,%83,%84,%85,%86,%87,%88,%89,%90,%91,%92,%93,%94,%95,"
      "%96,%97,%98,%99,%100,%101,%102,%103,%104,%105,%106,%107,%108,%109,%110,%111,"
      "%112,%113,%114,%115,%116,%117,%118,%119,%120,%121,%122,%123,%124,%125,%126,%127"
      "}, {%128,%129,%130,%131}, %132, p, 1, 1, 1;}\n"
      : "+f"(d[0]),"+f"(d[1]),"+f"(d[2]),"+f"(d[3]),"+f"(d[4]),"+f"(d[5]),"+f"(d[6]),"+f"(d[7]),
        "+f"(d[8]),"+f"(d[9]),"+f"(d[10]),"+f"(d[11]),"+f"(d[12]),"+f"(d[13]),"+f"(d[14]),"+f"(d[15]),
        "+f"(d[16]),"+f"(d[17]),"+f"(d[18]),"+f"(d[19]),"+f"(d[20]),"+f"(d[21]),"+f"(d[22]),"+f"(d[23]),
        "+f"(d[24]),"+f"(d[25]),"+f"(d[26]),"+f"(d[27]),"+f"(d[28]),"+f"(d[29]),"+f"(d[30]),"+f"(d[31]),
        "+f"(d[32]),"+f"(d[33]),"+f"(d[34]),"+f"(d[35]),"+f"(d[36]),"+f"(d[37]),"+f"(d[38]),"+f"(d[39]),
        "+f"(d[40]),"+f"(d[41]),"+f"(d[42]),"+f"(d[43]),"+f"(d[44]),"+f"(d[45]),"+f"(d[46]),"+f"(d[47]),
        "+f"(d[48]),"+f"(d[49]),"+f"(d[50]),"+f"(d[51]),"+f"(d[52]),"+f"(d[53]),"+f"(d[54]),"+f"(d[55]),
        "+f"(d[56]),"+f"(d[57]),"+f"(d[58]),"+f"(d[59]),"+f"(d[60]),"+f"(d[61]),"+f"(d[62]),"+f"(d[63]),
        "+f"(d[64]),"+f"(d[65]),"+f"(d[66]),"+f"(d[67]),"+f"(d[68]),"+f"(d[69]),"+f"(d[70]),"+f"(d[71]),
        "+f"(d[72]),"+f"(d[73]),"+f"(d[74]),"+f"(d[75]),"+f"(d[76]),"+f"(d[77]),"+f"(d[78]),"+f"(d[79]),
        "+f"(d[80]),"+f"(d[81]),"+f"(d[82]),"+f"(d[83]),"+f"(d[84]),"+f"(d[85]),"+f"(d[86]),"+f"(d[87]),
        "+f"(d[88]),"+f"(d[89]),"+f"(d[90]),"+f"(d[91]),"+f"(d[92]),"+f"(d[93]),"+f"(d[94]),"+f"(d[95]),
        "+f"(d[96]),"+f"(d[97]),"+f"(d[98]),"+f"(d[99]),"+f"(d[100]),"+f"(d[101]),"+f"(d[102]),"+f"(d[103]),
        "+f"(d[104]),"+f"(d[105]),"+f"(d[106]),"+f"(d[107]),"+f"(d[108]),"+f"(d[109]),"+f"(d[110]),"+f"(d[111]),
        "+f"(d[112]),"+f"(d[113]),"+f"(d[114]),"+f"(d[115]),"+f"(d[116]),"+f"(d[117]),"+f"(d[118]),"+f"(d[119]),
        "+f"(d[120]),"+f"(d[121]),"+f"(d[122]),"+f"(d[123]),"+f"(d[124]),"+f"(d[125]),"+f"(d[126]),"+f"(d[127])
      : "r"(a0), "r"(a1), "r"(a2), "r"(a3), "l"(db), "r"(sd));
}
__device__ __forceinline__ void wgmma_rs_n192(float (&d)[96], uint32_t a0, uint32_t a1, uint32_t a2, uint32_t a3, uint64_t db) {
  asm volatile("wgmma.mma_async.sync.aligned.m64n192k16.f32.bf16.bf16 {"
      "%0,%1,%2,%3,%4,%5,%6,%7,%8,%9,%10,%11,%12,%13,%14,%15,"
      "%16,%17,%18,%19,%20,%21,%22,%23,%24,%25,%26,%27,%28,%29,%30,%31,"
      "%32,%33,%34,%35,%36,%37,%38,%39,%40,%41,%42,%43,%44,%45,%46,%47,"
      "%48,%49,%50,%51,%52,%53,%54,%55,%56,%57,%58,%59,%60,%61,%62,%63,"
      "%64,%65,%66,%67,%68,%69,%70,%71,%72,%73,%74,%75,%76,%77,%78,%79,"
      "%80,%81,%82,%83,%84,%85,%86,%87,%88,%89,%90,%91,%92,%93,%94,%95"
      "}, {%96,%97,%98,%99}, %100, 1, 1, 1, 1;\n"
      : "+f"(d[0]),"+f"(d[1]),"+f"(d[2]),"+f"(d[3]),"+f"(d[4]),"+f"(d[5]),"+f"(d[6]),"+f"(d[7]),
        "+f"(d[8]),"+f"(d[9]),"+f"(d[10]),"+f"(d[11]),"+f"(d[12]),"+f"(d[13]),"+f"(d[14]),"+f"(d[15]),
        "+f"(d[16]),"+f"(d[17]),"+f"(d[18]),"+f"(d[19]),"+f"(d[20]),"+f"(d[21]),"+f"(d[22]),"+f"(d[23]),
        "+f"(d[24]),"+f"(d[25]),"+f"(d[26]),"+f"(d[27]),"+f"(d[28]),"+f"(d[29]),"+f"(d[30]),"+f"(d[31]),
        "+f"(d[32]),"+f"(d[33]),"+f"(d[34]),"+f"(d[35]),"+f"(d[36]),"+f"(d[37]),"+f"(d[38]),"+f"(d[39]),
        "+f"(d[40]),"+f"(d[41]),"+f"(d[42]),"+f"(d[43]),"+f"(d[44]),"+f"(d[45]),"+f"(d[46]),"+f"(d[47]),
        "+f"(d[48]),"+f"(d[49]),"+f"(d[50]),"+f"(d[51]),"+f"(d[52]),"+f"(d[53]),"+f"(d[54]),"+f"(d[55]),
        "+f"(d[56]),"+f"(d[57]),"+f"(d[58]),"+f"(d[59]),"+f"(d[60]),"+f"(d[61]),"+f"(d[62]),"+f"(d[63]),
        "+f"(d[64]),"+f"(d[65]),"+f"(d[66]),"+f"(d[67]),"+f"(d[68]),"+f"(d[69]),"+f"(d[70]),"+f"(d[71]),
        "+f"(d[72]),"+f"(d[73]),"+f"(d[74]),"+f"(d[75]),"+f"(d[76]),"+f"(d[77]),"+f"(d[78]),"+f"(d[79]),
        "+f"(d[80]),"+f"(d[81]),"+f"(d[82]),"+f"(d[83]),"+f"(d[84]),"+f"(d[85]),"+f"(d[86]),"+f"(d[87]),
        "+f"(d[88]),"+f"(d[89]),"+f"(d[90]),"+f"(d[91]),"+f"(d[92]),"+f"(d[93]),"+f"(d[94]),"+f"(d[95])
      : "r"(a0), "r"(a1), "r"(a2), "r"(a3), "l"(db));
}


constexpr int C_LN = 0, C_PX = 16, C_PY = 32;
constexpr int NB_CONS = 1, NB_LN = 2, NB_LAG = 4, NB_INIT = 6, NB_RDY = 7;
constexpr int LAGX = 3;
constexpr int LAGY = 6;
constexpr int LAG2 = 5;
constexpr int NLL = 4;
constexpr int POLL_DELAY = 1150;
constexpr int POLL_DELAY2 = 1000;
constexpr int POLL_DELAY3 = 600;
constexpr int FILT_DELAY = 600;
constexpr int WARM = 4;
constexpr int ALEAD = 8;
constexpr int XTRIG = 20;
constexpr int HTRIG = 0;
constexpr int SM_E = 0, SM_X = 16384, SM_E2 = 32768, SM_W = 49152, SM_FC = 69632, SM_T = 73728 - T1_BYTES;
constexpr unsigned long long KORDER = 0xBA9432DC876510ull;
constexpr unsigned long long BSLOT = 0x52140A98D52140ull, PSLOT = 0xB763CB763CB763ull;
constexpr unsigned long long BDEP = 0xFFEC97531ull, PDEP = 0xBA754ull;
constexpr uint32_t HI128 = desc_hi(1024, 1), HI64 = desc_hi(512, 2);

struct Bars {
  uint64_t full1[32], empty1[32], full2[16], fullA[8], empty2[8], emptyP[9], sig[2], done, fullP[32], hbar, tbar, hint[3], sbar;
  uint32_t epoch, pad;
};

template <int NK, bool STORE, int J0 = 0, int J1 = NK>
__device__ __forceinline__ void make_p(const float (&acc)[NK * 16], float r0, float r1, uint4 (&p)[NK], uint4* pbase, int ks0, uint32_t tag) {
#pragma unroll
  for (int j = J0; j < J1; j++) {
    uint32_t w[4];
#pragma unroll
    for (int i = 0; i < 4; i++) {
      const int a = 8 * j + 2 * i, b = a + NK * 8;
      w[i] = pack2(swiglu(acc[a], acc[b], (i & 1) ? r1 : r0), swiglu(acc[a + 1], acc[b + 1], (i & 1) ? r1 : r0));
    }
    asm volatile("" : "+r"(w[0]), "+r"(w[1]), "+r"(w[2]), "+r"(w[3]));
    p[j] = make_uint4(w[0], w[1], w[2], w[3]);
    if (STORE) st_tag(pbase + ((ks0 + j) >> 2) * 1024 + ((ks0 + j) & 3) * 32, p[j], tag);
  }
}
__device__ __forceinline__ void spin_until(uint32_t t) {
  while ((int)(clock32() - t) < 0) {}
}

__global__ void __cluster_dims__(2, 1, 1) __launch_bounds__(NTHREADS, 1)
fused_kernel(const __nv_bfloat16* __restrict__ x, const Tables* __restrict__ tab, Scratch* __restrict__ scr,
             __nv_bfloat16* __restrict__ out, const char* __restrict__ wg_raw, const char* __restrict__ wu_raw,
             const char* __restrict__ wd_raw,
             const __grid_constant__ CUtensorMap tmWR, const __grid_constant__ CUtensorMap tmWI,
             const __grid_constant__ CUtensorMap tmGX, const __grid_constant__ CUtensorMap tmUX,
             const __grid_constant__ CUtensorMap tmGY, const __grid_constant__ CUtensorMap tmUY,
             const __grid_constant__ CUtensorMap tmD) {
  extern __shared__ __align__(1024) char smem_raw[];
  const uint32_t sbase = s2u(smem_raw);
  const uint32_t sbar = sbase + 14 * SLOT, sstat = sbar + 1408;
  const int tid = threadIdx.x, lane = tid & 31;
  const int c = blockIdx.x, rk = c & 1, f = (c >> 1) & 7, rb = 2 * (c >> 4) + rk;
  const int rb2 = 2 * (c >> 4) + (f >> 2), kh = (f >> 1) & 1, nq = 2 * (f & 1) + rk;
#define BAR(field, i) (sbar + (uint32_t)offsetof(Bars, field) + 8u * (i))
#define TOFF(field) (sbase + SM_T + (uint32_t)offsetof(Tables, field) + lane * 16)

  if (tid >= 256) {
    asm volatile("setmaxnreg.dec.sync.aligned.u32 40;");
    const int warp = __shfl_sync(0xffffffffu, tid >> 5, 0);
    if (lane == 0) {
      auto init = [&](uint32_t b, int n, int count, int bytes) {
#pragma unroll
        for (int i = 0; i < n; i++) mbar_init(b + 8 * i, count);
#pragma unroll
        for (int i = 0; i < (bytes ? n : 0); i++) mbar_expect(b + 8 * i, bytes);
      };
      if (warp == 8) {
        if (sbase & 1023) die();
        init(BAR(tbar, 0), 1, 1, T2_BYTES + 2 * 10240);
        init(BAR(hbar, 0), 1, 1, 16384);
        init(BAR(hint, 0), 3, 1, 0);
        init(BAR(sbar, 0), 1, 32, 0);
        init(BAR(empty2, 0), 20, 8, 0);
      } else if (warp == 9) {
        init(BAR(full1, 0), 16, 1, 16384);
        init(BAR(full1, 16), 16, 1, 12288);
      } else if (warp == 10) {
        init(BAR(fullP, 0), 30, 1, 8192);
      } else {
        init(BAR(full2, 0), 24, 1, 16384);
        init(BAR(empty1, 0), 32, 16, 0);
      }
      asm volatile("fence.mbarrier_init.release.cluster;" ::: "memory");
    }
    if (tid == 256) {
      const int w0 = ((c >> 3) * 257 + 32 * (c & 7) + 1) & ~7;
      asm volatile("prefetch.tensormap [%0];" ::"l"(&tmWR) : "memory");
      asm volatile("prefetch.tensormap [%0];" ::"l"(&tmWI) : "memory");
      spin_until(clock32() + FILT_DELAY);
      tma3(sbase + SM_W, &tmWR, BAR(tbar, 0), w0, 0, 0);
      tma3(sbase + SM_W + 10240, &tmWI, BAR(tbar, 0), w0, 0, 0);
      bulk_load(sbase + SM_T + T1_BYTES, reinterpret_cast<const char*>(tab) + T1_BYTES, T2_BYTES, BAR(tbar, 0));
    }
    if (tid == 288) {
      asm volatile("prefetch.tensormap [%0];" ::"l"(rk ? &tmUX : &tmGX) : "memory");
      asm volatile("prefetch.tensormap [%0];" ::"l"(rk ? &tmUY : &tmGY) : "memory");
      asm volatile("prefetch.tensormap [%0];" ::"l"(&tmD) : "memory");
    }
    if (tid == 320) {
      const unsigned e = ld_relaxed(&scr->cnt[(C_LN + rb) * 32]) >> 3;
      asm volatile("st.shared.u32 [%0], %1;" ::"r"(BAR(epoch, 0)), "r"(e) : "memory");
    }
    __syncwarp();
    asm volatile("barrier.cluster.arrive.relaxed.aligned;" ::: "memory");
    bar_arrive(NB_RDY, 384);
    asm volatile("barrier.cluster.wait.aligned;" ::: "memory");
    bar_sync(NB_INIT, 384);
    unsigned epoch;
    asm volatile("ld.shared.u32 %0, [%1];" : "=r"(epoch) : "r"(BAR(epoch, 0)) : "memory");
    if (warp == 8) {
      if (lane == 0) {
        const int ax = (7 * f + 3 * (f & 1)) >> 1;
        const int ay = 7 * f + ((f & 1) ? 0 : 4);
        const CUtensorMap* tx = rk ? &tmUX : &tmGX;
        const CUtensorMap* ty = rk ? &tmUY : &tmGY;
        mbar_wait_bounded(BAR(sig, 0));
        uint32_t s = 2;
#pragma unroll 1
        for (int n = 0; n < 16; n++) {
          if (n >= 6) mbar_wait_bounded(BAR(empty1, n - 6));
          tma3_mc(sbase + (8 + s) * SLOT + rk * 8192, tx, BAR(full1, n), n * 32, ax);
          if (++s == 6) s = 0;
          if (n >= 10 && n < 15) {
            const int k = n - 10;
            tma3_mc(sbase + k * 12288 + rk * 6144, ty, BAR(full1, 16 + k), (k + 8) * 32, ay);
          }
        }
#pragma unroll 1
        for (int k = 5; k < 16; k++) {
          mbar_wait_bounded(BAR(empty1, k < 13 ? 10 + ((12 * (k - 5) + 11) >> 4) : 8 + k));
          tma3_mc(sbase + 8 * SLOT + ((k - 5) & 7) * 12288 + rk * 6144, ty, BAR(full1, 16 + k), ((k + 8) & 15) * 32, ay);
        }
        mbar_wait_bounded(BAR(done, 0));
      }
    } else if (warp == 9) {
      if (lane == 0) {
        mbar_wait(BAR(fullA, 4));
        wait_counter(&scr->cnt[(C_LN + rb2) * 32], (epoch + 1) * 8);
        asm volatile("fence.proxy.async.global;" ::: "memory");
#pragma unroll 1
        for (int i = 0; i < 14; i++) {
          const int kblk = 14 * kh + (int)((KORDER >> (4 * i)) & 15);
          mbar_wait(i < 9 ? BAR(empty1, 16 + (uint32_t)((BDEP >> (4 * i)) & 15)) : BAR(empty2, i - 9));
          tma3(sbase + (uint32_t)((BSLOT >> (4 * i)) & 15) * SLOT, &tmD, BAR(full2, i), 0, 64 * kblk, 2 * nq);
        }
        mbar_wait(BAR(empty2, 5));
        bulk_load(sbase + 13 * SLOT, &scr->LN[(rb2 * 8 + 2 * nq) * 1024 + kh * 512], 8192, BAR(hbar, 0));
        bulk_load(sbase + 13 * SLOT + 8192, &scr->LN[(rb2 * 8 + 2 * nq + 1) * 1024 + kh * 512], 8192, BAR(hbar, 0));
      }
    } else if (warp == 10) {
      bar_sync(NB_LN, 288);
      if (lane == 0) {
        red_release(&scr->cnt[(C_LN + rb) * 32]);
        wait_counter(&scr->cnt[(C_LN + rb) * 32], (epoch + 1) * 8);
        asm volatile("fence.proxy.async.global;" ::: "memory");
#pragma unroll 1
        for (int kb = NLL; kb < 8; kb++) {
          if (2 * kb >= ALEAD) mbar_wait(BAR(empty1, 2 * kb - ALEAD));
          bulk_load(sbase + kb * SLOT, &scr->LN[(rb * 8 + kb) * 1024], 16384, BAR(fullA, kb));
        }
#pragma unroll 1
        for (int s = 0; s < 14; s++) {
          const int kblk = 14 * kh + (int)((KORDER >> (4 * s)) & 15);
          if (s == 0 || s == 8 || s == 11) {
            mbar_wait(BAR(hint, s == 0 ? 0 : s == 8 ? 1 : 2));
          }
          mbar_wait(s < 5 ? BAR(empty1, 16 + (uint32_t)((PDEP >> (4 * s)) & 15)) : BAR(emptyP, s - 5));
          bulk_load_mc(sbase + (uint32_t)((PSLOT >> (4 * s)) & 15) * SLOT + rk * 8192, &scr->P[(rb2 * 28 + kblk) * 1024 + rk * 512], 8192, BAR(fullP, 16 * rk + s));
        }
      }
    } else {
      if (lane == 0) {
        mbar_wait(BAR(sig, 1));
        l2_prefetch(wg_raw + (size_t)c * 5376, 5376);
        l2_prefetch(wu_raw + (size_t)c * 5376, 5376);
        mbar_wait(BAR(sig, 0));
        l2_prefetch(wg_raw + 688128 + (size_t)c * 8960, 8960);
        l2_prefetch(wu_raw + 688128 + (size_t)c * 8960, 8960);
      }
      mbar_wait(BAR(fullA, 4));
      if (lane == 0) l2_prefetch(wd_raw + (size_t)c * 14336, 14336);
      {
        const uint32_t tag = (epoch + 1) & 1;
        uint4 v0, v1, v2;
        while (true) {
          v0 = ld_b128(&scr->ST[rb * 64 + lane]);
          v1 = ld_b128(&scr->ST[rb * 64 + 32 + lane]);
          v2 = ld_b128(&scr->ST[rb2 * 64 + 32 * kh + lane]);
          if (!__any_sync(0xffffffffu, ((v0.x ^ tag) | (v1.x ^ tag) | (v2.x ^ tag)) & 1u)) break;
        }
        sts4(sstat + lane * 16, v0.x & ~1u, v0.y, v0.z, v0.w);
        sts4(sstat + 512 + lane * 16, v1.x & ~1u, v1.y, v1.z, v1.w);
        sts4(sstat + 1024 + lane * 16, v2.x & ~1u, v2.y, v2.z, v2.w);
        mbar_arrive(BAR(sbar, 0));
      }
      if (lane == 0) {
        mbar_wait(BAR(empty1, XTRIG));
        while ((int)(ld_relaxed(&scr->cnt[(C_PX + rb2) * 32 + kh]) - (epoch + 1) * 32) < 0) {
        }
        mbar_arrive(BAR(hint, 0));
        mbar_wait(BAR(emptyP, HTRIG));
        uint32_t done = 0;
        while (done != 3) {
          uint2 v;
          asm volatile("ld.relaxed.gpu.global.v2.u32 {%0,%1}, [%2];" : "=r"(v.x), "=r"(v.y) : "l"(&scr->cnt[(C_PY + rb2) * 32 + 4 * (rk ^ kh ^ 1) + 2 * kh]) : "memory");
          if (!(done & 1) && (int)(v.x - (epoch + 1) * 8) >= 0) { done |= 1; mbar_arrive(BAR(hint, 1)); }
          if (!(done & 2) && (int)(v.y - (epoch + 1) * 8) >= 0) { done |= 2; mbar_arrive(BAR(hint, 2)); }
        }
      }
    }
  } else {
    const int warp = __shfl_sync(0xffffffffu, tid >> 5, 0);
    const int g = lane >> 2, t = lane & 3;
    uint4 fa[4], fb[4], tw[6];
#pragma unroll
    for (int i = 0; i < 4; i++) fa[i] = ldg_ca4(&tab->fa[i][lane][0]);
#pragma unroll
    for (int i = 0; i < 6; i++) tw[i] = ldg_ca4(&tab->tw1[i][lane][0]);
#pragma unroll
    for (int i = 0; i < 4; i++) fb[i] = ldg_ca4(&tab->fb[i][lane][0]);
#pragma unroll
    for (int i = 0; i < 4; i++) {
      const int r = i >> 1, ch = (i & 1) * 32 + lane;
      cp_async16(sbase + SM_X + (2 * warp + r) * 1024 + ((ch ^ ((ch >> 3) & 1)) * 16),
                 x + (size_t)(c + 128 * (2 * warp + r)) * 512 + ch * 8);
    }
    asm volatile("cp.async.commit_group;" ::: "memory");
    asm volatile("barrier.cluster.arrive.relaxed.aligned;" ::: "memory");
    uint32_t rbar;
    asm volatile("mapa.shared::cluster.u32 %0, %1, %2;" : "=r"(rbar) : "r"(sbar), "r"(rk ^ 1));
#define RBAR(field, i) (rbar + (uint32_t)offsetof(Bars, field) + 8u * (i))
    {
      const int ln = (tid >> 1) & 31, lg = ln >> 2, lt = ln & 3, i = 4 * (tid >> 6) + 2 * (tid & 1);
      const int kidx = lt + 8 * (i >> 3), nidx = 4 * ((i >> 1) & 3) + (lg >> 1);
      const uint32_t a0 = cfrag<2048>((c + 128 * kidx) * nidx, lg & 1), a1 = cfrag<2048>((c + 128 * (kidx + 4)) * nidx, lg & 1);
      const uint32_t b0 = cfrag<2048>(-(c + 128 * nidx) * kidx, lg & 1), b1 = cfrag<2048>(-(c + 128 * nidx) * (kidx + 4), lg & 1);
      asm volatile("st.shared.v2.u32 [%0], {%1,%2};" ::"r"(sbase + SM_FC + tid * 8), "r"(a0), "r"(a1) : "memory");
      asm volatile("st.shared.v2.u32 [%0], {%1,%2};" ::"r"(sbase + SM_FC + 2048 + tid * 8), "r"(b0), "r"(b1) : "memory");
    }
    bar_sync(NB_CONS, 256);
    uint4 fc[4];
#pragma unroll
    for (int i = 0; i < 4; i++) fc[i] = lds4(sbase + SM_FC + i * 512 + lane * 16);
    asm volatile("cp.async.wait_group 0;" ::: "memory");
    __syncwarp();
    bar_arrive(NB_INIT, 384);
    uint32_t tag, ones;
    uint4 q[4], o[4];
    {
      uint32_t v[2][8];
#pragma unroll
      for (int r = 0; r < 2; r++)
#pragma unroll
        for (int ks = 0; ks < 2; ks++) {
          const int ch = 32 * ks + 2 * (lane & 15) + (lane >> 4);
          asm volatile("ldmatrix.sync.aligned.m8n8.x4.trans.shared.b16 {%0,%1,%2,%3}, [%4];"
                       : "=r"(v[r][4 * ks]), "=r"(v[r][4 * ks + 1]), "=r"(v[r][4 * ks + 2]), "=r"(v[r][4 * ks + 3])
                       : "r"(sbase + SM_X + (2 * warp + r) * 1024 + ((ch ^ ((ch >> 3) & 1)) * 16)) : "memory");
        }
      float sq[2];
#pragma unroll
      for (int r = 0; r < 2; r++) {
        float s0 = 0.f, s1 = 0.f;
#pragma unroll
        for (int i = 0; i < 8; i++) {
          const float lo = bf_lo(v[r][i]), hi = u2f(v[r][i] & 0xffff0000u);
          s0 = fmaf(lo, lo, s0);
          s1 = fmaf(hi, hi, s1);
        }
        sq[r] = s0 + s1;
      }
      {
        float w = ((lane & 1) ? sq[1] : sq[0]) + __shfl_xor_sync(0xffffffffu, (lane & 1) ? sq[0] : sq[1], 1);
        w += __shfl_xor_sync(0xffffffffu, w, 2);
        w = sum_groups(w);
        const float o2 = __shfl_xor_sync(0xffffffffu, w, 1);
        sq[0] = (lane & 1) ? o2 : w;
        sq[1] = (lane & 1) ? w : o2;
      }
#pragma unroll
      for (int r = 0; r < 2; r++) {
        float dd[2][4], ee[2][4];
#pragma unroll
        for (int nt = 0; nt < 2; nt++) {
          mma_az(dd[nt], fa[0], v[r][2 * nt], v[r][2 * nt + 1]);
          mma_a(dd[nt], fa[1], v[r][4 + 2 * nt], v[r][5 + 2 * nt]);
          mma_az(ee[nt], fa[2], v[r][2 * nt], v[r][2 * nt + 1]);
          mma_a(ee[nt], fa[3], v[r][4 + 2 * nt], v[r][5 + 2 * nt]);
        }
        float mean = (dd[0][0] + dd[0][1]) + (dd[1][0] + dd[1][1]);
        mean += __shfl_xor_sync(0xffffffffu, mean, 1);
        mean += __shfl_xor_sync(0xffffffffu, mean, 2);
        mean = __shfl_sync(0xffffffffu, mean, 0) * (1.f / 512.f);
        const float rs = rsqrtf(fmaxf(fmaf(-mean, mean, sq[r] * (1.f / 512.f)), 0.f) + 1e-5f);
        float acc[4][4];
#pragma unroll
        for (int nt = 0; nt < 2; nt++) {
          const float (&d)[4] = dd[nt];
          const float (&e)[4] = ee[nt];
          const uint4 &ka = tw[2 * nt], &kb = tw[2 * nt + 1], &kc = tw[4 + nt];
          const uint32_t a0 = pack2(d[0] * u2f(ka.x) + d[2] * u2f(ka.y), d[1] * u2f(kb.x) + d[3] * u2f(kb.y));
          const uint32_t a2 = pack2(d[0] * u2f(ka.z) + d[2] * u2f(ka.w), d[1] * u2f(kb.z) + d[3] * u2f(kb.w));
          const uint32_t a1 = pack2(e[0] * u2f(kc.x) + e[2] * u2f(kc.y), e[1] * u2f(kc.z) + e[3] * u2f(kc.w));
          const uint32_t a3 = pack2(e[2] * u2f(kc.x) - e[0] * u2f(kc.y), e[3] * u2f(kc.z) - e[1] * u2f(kc.w));
          const uint32_t dc = pack2(fmaf(mean, -32.f, d[0]), fmaf(mean, -32.f, d[1]));
          const uint32_t h0 = g == 0 ? dc : a0, h2 = g == 0 ? 0u : a2;
          if (nt == 0) {
            mma16816_z(acc[0], a0, a1, a2, a3, fb[2 * nt].x, fb[2 * nt].y);
            mma16816_z(acc[1], a0, a1, a2, a3, fb[2 * nt].z, fb[2 * nt].w);
            mma16816_z(acc[2], h0, a1, h2, a3, fb[2 * nt + 1].x, fb[2 * nt + 1].y);
            mma16816_z(acc[3], h0, a1, h2, a3, fb[2 * nt + 1].z, fb[2 * nt + 1].w);
          } else {
            mma16816(acc[0], a0, a1, a2, a3, fb[2 * nt].x, fb[2 * nt].y);
            mma16816(acc[1], a0, a1, a2, a3, fb[2 * nt].z, fb[2 * nt].w);
            mma16816(acc[2], h0, a1, h2, a3, fb[2 * nt + 1].x, fb[2 * nt + 1].y);
            mma16816(acc[3], h0, a1, h2, a3, fb[2 * nt + 1].z, fb[2 * nt + 1].w);
          }
        }
#pragma unroll
        for (int h = 0; h < 2; h++) {
          const int j = 2 * warp + r, m = 2 * t + h;
          sts4(sbase + SM_E + ((j * 8 + m) * 8 + (g ^ (2 * t) ^ (2 * (j & 3)))) * 16,
               pack2(acc[h][0] * rs, acc[h][1] * rs), pack2(acc[h][2] * rs, acc[h][3] * rs),
               pack2(acc[2 + h][0] * rs, acc[2 + h][1] * rs), pack2(acc[2 + h][2] * rs, acc[2 + h][3] * rs));
        }
      }
      bar_sync(NB_RDY, 384);
      const uint32_t ea = sbase + SM_E + ((t * 8 + warp) * 8 + (g ^ (warp & 6) ^ (2 * t))) * 16;
      lds_frag(q[0], q[1], ea, ea + 4096);
      lds_frag(q[2], q[3], ea + 8192, ea + 12288);
      asm volatile("ld.shared.u32 %0, [%1];" : "=r"(tag) : "r"(BAR(epoch, 0)) : "memory");
      ones = ~(tag >> 31);
      tag = (tag + 1) & 1;
      cdft16(q, fc, o);
#pragma unroll
      for (int vv = 0; vv < 4; vv++) {
        o[vv].y &= ~1u;
        o[vv].z = (o[vv].z & ~1u) | (tag ^ 1);
        st_tag(&scr->Z1[(((4 * vv + t) * 8 + warp) * 128 + c) * 8 + g], o[vv], tag);
      }
    }
    asm volatile("setmaxnreg.inc.sync.aligned.u32 232;");
    {
      uint4* const zp = &scr->Z1[(c * 128 + 8 * t + warp) * 8 + g];
      const uint32_t tst = clock32();
      mbar_wait(BAR(tbar, 0));
      uint4 f2[4], g2[4];
#pragma unroll
      for (int i = 0; i < 4; i++) {
        f2[i] = lds4(TOFF(f2) + warp * 2048 + i * 512);
        g2[i] = lds4(TOFF(g2) + warp * 2048 + i * 512);
      }
      const uint4 f8 = lds4(TOFF(f8)), g8 = lds4(TOFF(g8));
      asm volatile("barrier.cluster.wait.aligned;" ::: "memory");
      spin_until(tst + POLL_DELAY);
      ld_tag4_issue<256>(q, zp);
      float wfr[16], wfi[16];
      {
        const float nyq = ((c & 7) == 7 && g == 0) ? 0.5f : 1.f;
        uint32_t wa = sbase + SM_W + (16 * warp + t) * 80 + ((2 * (c >> 3) + 2) & 15) - 2;
        asm volatile("" : "+r"(wa));
        const uint32_t wb[3] = {wa + 2 * (g == 0 ? 16 : g), wa + 2 * g, wa - 2 * g};
#pragma unroll
        for (int i = 0; i < 16; i++) {
          const int ci = i >> 3, dd = (i >> 2) & 1, e = i & 3;
          const uint32_t a = wb[e < 2 ? e : 2] + (ci * 8 + 4 * dd) * 80 + (e == 0 ? 0 : e == 1 ? 16 : e == 2 ? 64 : 48);
          wfr[i] = bf_lo(lds_u16(a)) * (e == 2 ? nyq : 1.f);
          wfi[i] = bf_lo(lds_u16(a + 10240)) * (e == 2 ? nyq : 1.f);
        }
      }
      ld_tag4_finish<256>(q, zp, tag);
      if (lane == 0) mbar_arrive(BAR(sig, 1));
#pragma unroll
      for (int i = 0; i < 4; i++) q[i].z &= ~1u;
      reg_frag(q, ones);
      cdft16(q, f2, o);
      const uint32_t e2 = sbase + SM_E2;
#pragma unroll
      for (int vv = 0; vv < 4; vv++)
        sts4(e2 + ((warp * 16 + 4 * vv + t) * 8 + (g ^ (2 * t) ^ (2 * (warp & 3)))) * 16, o[vv].x, o[vv].y, o[vv].z, o[vv].w);
      bar_sync(NB_CONS, 256);
      uint32_t ad[2], res[2][2][4];
#pragma unroll
      for (int ci = 0; ci < 2; ci++) {
        const int cc = 2 * warp + ci;
        ad[ci] = e2 + ((t * 16 + cc) * 8 + (g ^ (2 * (cc & 3)) ^ (2 * t))) * 16;
        lds_frag(q[2 * ci], q[2 * ci + 1], ad[ci], ad[ci] + 8192);
      }
#pragma unroll
      for (int ci = 0; ci < 2; ci++)
#pragma unroll
        for (int p = 0; p < 2; p++) {
          uint32_t y[2][2];
#pragma unroll
          for (int vv = 0; vv < 2; vv++) {
            float d[4];
            mma_az(d, q[2 * ci + p], word(f8, 2 * vv), word(f8, 2 * vv + 1));
#pragma unroll
            for (int rr = 0; rr < 2; rr++) {
              const float fr = wfr[ci * 8 + vv * 4 + 2 * p + rr], fi = wfi[ci * 8 + vv * 4 + 2 * p + rr];
              y[vv][rr] = pack2(d[2 * rr] * fr - d[2 * rr + 1] * fi, d[2 * rr] * fi + d[2 * rr + 1] * fr);
            }
          }
#pragma unroll
          for (int vv = 0; vv < 2; vv++) {
            float d[4];
            mma16816_z(d, y[0][0], y[0][1], y[1][0], y[1][1], word(g8, 2 * vv), word(g8, 2 * vv + 1));
            res[ci][vv][2 * p] = pack2(d[0], d[1]);
            res[ci][vv][2 * p + 1] = pack2(d[2], d[3]);
          }
        }
#pragma unroll
      for (int i = 0; i < 4; i++)
        sts4(ad[i >> 1] + (i & 1) * 8192, res[i >> 1][i & 1][0], res[i >> 1][i & 1][1], res[i >> 1][i & 1][2], res[i >> 1][i & 1][3]);
      bar_sync(NB_CONS, 256);
      const uint32_t eb = e2 + ((warp * 16 + t) * 8 + (g ^ (2 * t) ^ (2 * (warp & 3)))) * 16;
      lds_frag(q[0], q[1], eb, eb + 512);
      lds_frag(q[2], q[3], eb + 1024, eb + 1536);
      cdft16(q, g2, o);
#pragma unroll
      for (int vv = 0; vv < 4; vv++) {
        o[vv].y &= ~1u;
        o[vv].z = (o[vv].z & ~1u) | tag;
        st_tag(zp + vv * 256, o[vv], tag);
      }
    }
    {
      const uint4* const zp = &scr->Z1[((t * 8 + warp) * 128 + c) * 8 + g];
      const uint32_t tst = clock32();
      uint4 gb[4], ga[4], gc[4], tw[4];
      uint2 xr[2][4];
      uint2* lnp[2];
#pragma unroll
      for (int r = 0; r < 2; r++) {
        const int row = 16 * f + 2 * warp + r;
        lnp[r] = reinterpret_cast<uint2*>(&scr->LN[(rb * 8 + (g >> 2)) * 1024 + row * 8 + ((2 * (g & 3) + (t >> 1)) ^ (row & 7))]) + (t & 1);
        asm volatile("" : "+l"(lnp[r]));
      }
#pragma unroll
      for (int i = 0; i < 4; i++) {
        gc[i] = lds4(sbase + SM_FC + 2048 + i * 512 + lane * 16);
        gb[i] = lds4(TOFF(gb) + i * 512);
        ga[i] = lds4(TOFF(ga) + i * 512);
        tw[i] = lds4(TOFF(tw3) + i * 512);
        const int ch = 2 * (g + 8 * i) + (t >> 1);
#pragma unroll
        for (int r = 0; r < 2; r++) xr[r][i] = lds2(sbase + SM_X + (2 * warp + r) * 1024 + ((ch ^ ((ch >> 3) & 1)) * 16) + (t & 1) * 8);
      }
      spin_until(tst + POLL_DELAY2);
      ld_tag4_issue<32768>(q, zp);
      ld_tag4_finish<32768, true>(q, zp, tag);
      if (lane == 0) mbar_arrive(BAR(sig, 0));
      reg_frag(q, ones);
      cdft16(q, gc, o);
#pragma unroll
      for (int vv = 0; vv < 4; vv++)
        sts4(sbase + SM_E + (((4 * vv + t) * 8 + warp) * 8 + (g ^ (warp & 6) ^ (2 * t))) * 16, o[vv].x, o[vv].y, o[vv].z, o[vv].w);
      bar_sync(NB_CONS, 256);
      uint32_t hv[2][8];
      const float mk = t == 0 ? 0.f : 1.f;
#pragma unroll
      for (int r = 0; r < 2; r++) {
        const int j = 2 * warp + r;
        uint4 u[2];
#pragma unroll
        for (int h = 0; h < 2; h++) u[h] = lds4(sbase + SM_E + ((j * 8 + 2 * t + h) * 8 + (g ^ (2 * t) ^ (2 * (j & 3)))) * 16);
        const uint32_t bp[4][2] = {{u[0].x, u[1].x & ones}, {u[0].y & ones, u[1].y}, {u[0].z, u[1].z & ones}, {u[0].w & ones, u[1].w}};
        float y[2][2][4];
#pragma unroll
        for (int i = 0; i < 2; i++) {
          float lo[4], hi[4], e[4];
          mma_az(lo, gb[2 * i], bp[0][0], bp[0][1]);
          mma_az(hi, gb[2 * i + 1], bp[2][0], bp[2][1]);
          mma_az(e, gb[2 * i], bp[1][0], bp[1][1]);
          mma_a(e, gb[2 * i + 1], bp[3][0], bp[3][1]);
          const uint4 &ka = tw[2 * i], &kb = tw[2 * i + 1];
          const float tr0 = fmaf(hi[0], mk, lo[0]), ti0 = fmaf(hi[2], mk, lo[2]);
          const float tr1 = lo[1] + hi[1], ti1 = lo[3] + hi[3];
          const float vr0 = tr0 * u2f(ka.x) - ti0 * u2f(ka.y), vi0 = tr0 * u2f(ka.y) + ti0 * u2f(ka.x);
          const float vr1 = tr1 * u2f(ka.z) - ti1 * u2f(ka.w), vi1 = tr1 * u2f(ka.w) + ti1 * u2f(ka.z);
          const uint32_t b0 = pack2(t == 0 ? hi[0] : vr0, vr1), b1 = pack2(t == 0 ? vr0 : vi0, vi1);
          const uint32_t b2 = pack2(e[0] * u2f(kb.x) - e[2] * u2f(kb.y), e[1] * u2f(kb.z) - e[3] * u2f(kb.w));
          const uint32_t b3 = pack2(e[0] * u2f(kb.y) + e[2] * u2f(kb.x), e[1] * u2f(kb.w) + e[3] * u2f(kb.z));
#pragma unroll
          for (int mt = 0; mt < 2; mt++) {
            mma_az(y[mt][i], ga[2 * mt], b0, b1);
            mma_a(y[mt][i], ga[2 * mt + 1], b2, b3);
          }
        }
#pragma unroll
        for (int i = 0; i < 4; i++) {
          hv[r][2 * i] = hadd2_bf16(xr[r][i].x, pack2(y[i >> 1][0][2 * (i & 1)], y[i >> 1][0][2 * (i & 1) + 1]));
          hv[r][2 * i + 1] = hadd2_bf16(xr[r][i].y, pack2(y[i >> 1][1][2 * (i & 1)], y[i >> 1][1][2 * (i & 1) + 1]));
        }
      }
      float mean[2];
      uint32_t mb[2];
#pragma unroll
      for (int r = 0; r < 2; r++) {
        mean[r] = sum_groups(quad_sum(hv[r])) * (1.f / 512.f);
        mb[r] = pack2(mean[r], mean[r]);
      }
#pragma unroll
      for (int i = 0; i < 4; i++)
#pragma unroll
        for (int r = 0; r < 2; r++) {
          hv[r][2 * i] = hsub2_bf16(hv[r][2 * i], mb[r]);
          hv[r][2 * i + 1] = hsub2_bf16(hv[r][2 * i + 1], mb[r]);
          st_tag8(lnp[r] + i * 4096, hv[r][2 * i], hv[r][2 * i + 1], i < 2 ? tag : (hv[r][2 * i] & 1u));
        }
      bar_arrive(NB_LN, 288);
      const uint32_t ones2 = ~(lds2(BAR(epoch, 0)).x >> 31);
      float rstd[2];
#pragma unroll
      for (int r = 0; r < 2; r++) {
        hv[r][0] &= ones2;
        rstd[r] = row_rstd(hv[r], mean[r] - bf_lo(mb[r]));
      }
      if (lane == 0)
        st_tag(&scr->ST[rb * 64 + 8 * f + warp], make_uint4(mb[0] << 16, __float_as_uint(rstd[0]), mb[1] << 16, __float_as_uint(rstd[1])), tag);
    }
    const int wgi = warp >> 2, wq = warp & 3;
    const int wr = wgi ^ (f >> 2) ^ 1, rt = 4 * wr + wq;
    uint4* const pbase = &scr->P[rb * 28 * 1024 + rt * 128 + lane];
    const uint32_t a_lo0 = desc_lo(sbase + wr * 8192, 16);
    const uint32_t ebar = lane == 0 ? BAR(empty1, 0) : RBAR(empty1, 0);
    float r0, r1;
    uint4 px[8], py[6];
    const int rh = wgi ^ kh ^ 1;
    const uint32_t fpb = BAR(fullP, 16 * rh);
    const uint4* const psrc = &scr->P[(rb2 * 28 + 14 * kh) * 1024 + (4 * rh + wq) * 128 + lane];
    const uint32_t pa0 = sbase + (4 * rh + wq) * 2048;
    uint4 pf[3][4], ha[4][4];
    uint32_t rdy = 0, got0;
    {
      float acc[128];
#pragma unroll
      for (int i = 0; i < 128; i++) acc[i] = 0.f;
      const uint32_t b_lo0 = desc_lo(sbase + 8 * SLOT, 4096);
      const uint32_t t3 = clock32();
      if (WARM) {
        wg_fence();
#pragma unroll
        for (int i = 0; i < WARM; i++) wgmma_n256(acc, desc64(a_lo0 + 6 * 1024, HI128), desc64(b_lo0, HI128));
        wg_commit();
      }
      const uint4* const ap = &scr->LN[rb * 8 * 1024 + rt * 128 + lane];
      const uint32_t sa = sbase + rt * 2048, amask = (lane & 1) ? ~0u : ~1u;
      auto fetch_a = [&](int kb) {
#pragma unroll
        for (int i = 0; i < 4; i++) cp_async16(sa + kb * SLOT + (lane + 32 * i) * 16, ap + kb * 1024 + 32 * i);
        asm volatile("cp.async.commit_group;" ::: "memory");
      };
      auto load_a = [&](int kb) {
#pragma unroll
        for (int ks = 0; ks < 4; ks++)
          asm volatile("ldmatrix.sync.aligned.m8n8.x4.shared.b16 {%0,%1,%2,%3}, [%4];"
                       : "=r"(ha[kb][ks].x), "=r"(ha[kb][ks].y), "=r"(ha[kb][ks].z), "=r"(ha[kb][ks].w)
                       : "r"(sa + kb * SLOT + (lane & 15) * 128 + (((2 * ks + (lane >> 4)) ^ (lane & 7)) * 16)) : "memory");
      };
      auto check_a = [&](int kb) {
        int it = 0;
#pragma unroll 1
        while (true) {
          uint32_t m = 0;
#pragma unroll
          for (int ks = 0; ks < 4; ks++) m |= tag_miss(ha[kb][ks].x, ha[kb][ks].y, ha[kb][ks].z, ha[kb][ks].w, tag);
          if (!__any_sync(0xffffffffu, m & ~amask)) break;
          fetch_a(kb);
          asm volatile("cp.async.wait_group 0;" ::: "memory");
          __syncwarp();
          load_a(kb);
          if (++it > SPIN_LIMIT) { die(); break; }
        }
#pragma unroll
        for (int ks = 0; ks < 4; ks++)
          asm volatile("and.b32 %0, %0, %4; and.b32 %1, %1, %4; and.b32 %2, %2, %4; and.b32 %3, %3, %4;"
                       : "+r"(ha[kb][ks].x), "+r"(ha[kb][ks].y), "+r"(ha[kb][ks].z), "+r"(ha[kb][ks].w) : "r"(amask));
      };
      bar_sync(NB_CONS, 256);
      spin_until(t3 + POLL_DELAY3);
      fetch_a(0);
      fetch_a(1);
      asm volatile("cp.async.wait_group 1;" ::: "memory");
      __syncwarp();
      load_a(0);
#pragma unroll
      for (int n = 0; n < 8; n++) {
        const int kb = n >> 1, hh = n & 1;
        if (hh == 0) {
          check_a(kb);
          if (kb < 2) fetch_a(kb + 2);
        }
        if (hh == 1 && kb < 3) {
          if (kb < 2) asm volatile("cp.async.wait_group 1;" ::: "memory");
          else asm volatile("cp.async.wait_group 0;" ::: "memory");
          __syncwarp();
        }
        if (!rdy) mbar_wait(BAR(full1, n));
        const uint32_t bl = b_lo0 + ((n + 2) % 6) * 1024;
        wg_fence();
        if (hh == 1 && kb < 3) load_a(kb + 1);
        rdy = mbar_test(BAR(full1, n + 1));
        const uint4 &a0 = ha[kb][2 * hh], &a1 = ha[kb][2 * hh + 1];
        wgmma_rs_n256(acc, a0.x, a0.y, a0.z, a0.w, desc64(bl, HI128), n != 0 ? 1 : ~ones);
        wgmma_rs_n256(acc, a1.x, a1.y, a1.z, a1.w, desc64(bl + 128, HI128));
        wg_commit();
        wg_wait<1>();
        if (n != 0 && lane < 2) mbar_arrive_remote(ebar + 8 * (n - 1));
      }
      uint32_t slot = 4;
#pragma unroll 1
      for (int kb = 4; kb < 8; kb++) {
        mbar_wait(BAR(fullA, kb));
#pragma unroll
        for (int hh = 0; hh < 2; hh++) {
          if (hh == ((16 - LAGX) & 1) && kb == ((16 - LAGX) >> 1) && wgi == 1) bar_sync(NB_LAG, 256);
          mbar_wait(BAR(full1, 2 * kb + hh));
          const uint32_t al = a_lo0 + kb * 1024 + hh * 4, bl = b_lo0 + slot * 1024;
          wg_fence();
          wgmma_n256(acc, desc64(al, HI128), desc64(bl, HI128));
          wgmma_n256(acc, desc64(al + 2, HI128), desc64(bl + 128, HI128));
          wg_commit();
          if (hh == 1 && kb == 7 && wgi == 0) bar_arrive(NB_LAG, 256);
          wg_wait<1>();
          if (lane < 2) mbar_arrive_remote(ebar + 8 * (2 * kb + hh - 1));
          if (++slot == 6) slot = 0;
        }
      }
      mbar_wait(BAR(sbar, 0));
      r0 = __uint_as_float(lds2(sstat + (16 * rt + g) * 8).y);
      r1 = __uint_as_float(lds2(sstat + (16 * rt + g + 8) * 8).y);
      wg_wait<0>();
      if (lane < 2) mbar_arrive_remote(ebar + 8 * 15);
      make_p<8, false>(acc, r0, r1, px, pbase, 0, tag);
    }
    {
      float acc[96];
#pragma unroll
      for (int i = 0; i < 96; i++) acc[i] = 0.f;
      const uint32_t b_lo0 = desc_lo(sbase, 2048);
      uint4* const pdst = pbase + ((7 * f + 3 * (f & 1)) >> 1) * 1024;
      auto stage_y = [&](int k) {
        if (k < 4) mbar_wait_bounded(BAR(full1, 16 + k));
        else mbar_wait(BAR(full1, 16 + k));
        const uint32_t al = a_lo0 + (4 + (k >> 1)) * 1024 + (k & 1) * 4, bl = b_lo0 + (k < 5 ? k * 768 : 8192 + (k - 5) * 768);
        wg_fence();
        wgmma_n192(acc, desc64(al, HI128), desc64(bl, HI64));
        wgmma_n192(acc, desc64(al + 2, HI128), desc64(bl + 64, HI64));
        wg_commit();
      };
#pragma unroll
      for (int k = 0; k < 4; k++) {
        stage_y(k);
        st_tag(pdst + (k >> 1) * 1024 + (k & 1) * 64, px[2 * k], tag);
        st_tag(pdst + (k >> 1) * 1024 + (k & 1) * 64 + 32, px[2 * k + 1], tag);
        if (k == 3 && lane == 0) red_relaxed(&scr->cnt[(C_PX + rb) * 32 + (f >> 2)]);
        wg_wait<1>();
        if (k != 0 && lane < 2) mbar_arrive_remote(ebar + 8 * (15 + k));
      }
#pragma unroll 1
      for (int k = 4; k < 8; k++) {
        stage_y(k);
        wg_wait<1>();
        if (k != 0 && lane < 2) mbar_arrive_remote(ebar + 8 * (15 + k));
      }
      rdy = 0;
#pragma unroll
      for (int k = 8; k < 16; k++) {
        if (k == 16 - LAGY && wgi == 1) bar_sync(NB_LAG, 256);
        if (!rdy) mbar_wait(BAR(full1, 16 + k));
        const uint32_t bl = b_lo0 + 8192 + ((k - 5) & 7) * 768;
        const uint4 &a0 = ha[(k - 8) >> 1][2 * (k & 1)], &a1 = ha[(k - 8) >> 1][2 * (k & 1) + 1];
        wg_fence();
        if (k < 15) rdy = mbar_test(BAR(full1, 17 + k));
        wgmma_rs_n192(acc, a0.x, a0.y, a0.z, a0.w, desc64(bl, HI64));
        wgmma_rs_n192(acc, a1.x, a1.y, a1.z, a1.w, desc64(bl + 64, HI64));
        wg_commit();
        if (k == 15 && wgi == 0) bar_arrive(NB_LAG, 256);
        wg_wait<1>();
        if (lane < 2) mbar_arrive_remote(ebar + 8 * (15 + k));
      }
      got0 = __all_sync(0xffffffffu, mbar_test(fpb));
      if (got0) {
#pragma unroll
        for (int kk = 0; kk < 4; kk++) pf[0][kk] = lds4(pa0 + 3 * SLOT + kk * 512 + lane * 16);
      }
      wg_wait<0>();
      if (lane < 2) mbar_arrive_remote(ebar + 8 * 31);
      const int ks0 = 14 * f + ((f & 1) ? 0 : 8);
      auto reread = [&]() {
        asm volatile("ld.volatile.shared.f32 %0, [%2+4]; ld.volatile.shared.f32 %1, [%2+68];" : "=f"(r0), "=f"(r1) : "r"(sstat + (16 * rt + g) * 8) : "memory");
      };
      make_p<6, true, 0, 2>(acc, r0, r1, py, pbase, ks0, tag);
      reread();
      make_p<6, true, 2, 4>(acc, r0, r1, py, pbase, ks0, tag);
      if (lane == 0) red_relaxed(&scr->cnt[(C_PY + rb) * 32 + 4 * wgi + (f >> 1)]);
      reread();
      rdy = mbar_test(BAR(full2, 0)) & mbar_test(fpb + 8);
      make_p<6, true, 4, 6>(acc, r0, r1, py, pbase, ks0, tag);
    }
    {
      float acc[64];
      const uint32_t b2_lo0 = desc_lo(sbase, 8192);
      const uint32_t pbar = rh == rk ? BAR(emptyP, 0) : RBAR(emptyP, 0);
      if (!got0) {
        mbar_wait(fpb);
#pragma unroll
        for (int kk = 0; kk < 4; kk++) pf[0][kk] = lds4(pa0 + 3 * SLOT + kk * 512 + lane * 16);
      }
#pragma unroll
      for (int s = 0; s < 14; s++) {
        uint4 (&a)[4] = pf[s % 3];
        ld_tag4_finish<32>(a, psrc + (int)((KORDER >> (4 * s)) & 15) * 1024, tag);
        if (s < 9 && lane == 0) mbar_arrive_remote(pbar + 8 * s);
        if (s >= 2) {
          wg_wait<1>();
          if (s <= 7 && lane == 0) mbar_arrive(BAR(empty2, s - 2));
        }
        if (!rdy) {
          if (s < 13) mbar_wait(fpb + 8 * (s + 1));
          mbar_wait(BAR(full2, s));
        }
        if (s == 14 - LAG2 && wgi == 1) bar_sync(NB_LAG, 256);
        const uint32_t bl = b2_lo0 + (uint32_t)((BSLOT >> (4 * s)) & 15) * 1024;
        wg_fence();
        if (s < 13) {
#pragma unroll
          for (int kk = 0; kk < 4; kk++)
            pf[(s + 1) % 3][kk] = lds4(pa0 + (uint32_t)((PSLOT >> (4 * (s + 1))) & 15) * SLOT + kk * 512 + lane * 16);
          rdy = mbar_test(BAR(full2, s + 1));
          if (s < 12) rdy &= mbar_test(fpb + 8 * (s + 2));
        }
        if (s == 0) wgmma_rs_n128(acc, a[0].x, a[0].y, a[0].z, a[0].w, desc64(bl, HI128), 0);
        else wgmma_rs_n128(acc, a[0].x, a[0].y, a[0].z, a[0].w, desc64(bl, HI128));
#pragma unroll
        for (int kk = 1; kk < 4; kk++) wgmma_rs_n128(acc, a[kk].x, a[kk].y, a[kk].z, a[kk].w, desc64(bl + kk * 128, HI128));
        wg_commit();
      }
      if (wgi == 0) {
        bar_arrive(NB_LAG, 256);
        uint4* const dst = &scr->Z1[(tid >> 3) * 1024 + (c ^ 4) * 8 + (tid & 7)];
        wg_wait<0>();
#pragma unroll
        for (int i = 0; i < 8; i++)
          st_tag(dst + i * 16384, make_uint4(pack2(acc[8 * i], acc[8 * i + 1]), pack2(acc[8 * i + 2], acc[8 * i + 3]) | 1u,
                                           pack2(acc[8 * i + 4], acc[8 * i + 5]), pack2(acc[8 * i + 6], acc[8 * i + 7])), tag);
      } else {
        uint4 pv[2][4];
        const uint4* const xsrc = &scr->Z1[((tid & 127) >> 3) * 1024 + c * 8 + (tid & 7)];
        ld_tag4_issue<16384>(pv[0], xsrc);
        ld_tag4_issue<16384>(pv[1], xsrc + 65536);
        uint32_t w[32];
        {
          const uint32_t m0 = __byte_perm(lds2(sstat + 1024 + (16 * wq + g) * 8).x, 0, 0x3232);
          const uint32_t m1 = __byte_perm(lds2(sstat + 1024 + (16 * wq + g + 8) * 8).x, 0, 0x3232);
          const uint32_t hb = sbase + 13 * SLOT + (16 * wq + (lane & 15)) * 128;
          const uint32_t mk = ((t & 1) == 0 && nq < 2) ? ~1u : ~0u;
          mbar_wait(BAR(hbar, 0));
#pragma unroll
          for (int i = 0; i < 8; i++) {
            asm volatile("ldmatrix.sync.aligned.m8n8.x4.shared.b16 {%0,%1,%2,%3}, [%4];"
                         : "=r"(w[4 * i]), "=r"(w[4 * i + 1]), "=r"(w[4 * i + 2]), "=r"(w[4 * i + 3])
                         : "r"(hb + (i >> 2) * 8192 + (((2 * (i & 3) + (lane >> 4)) ^ (lane & 7)) * 16)) : "memory");
#pragma unroll
            for (int e = 0; e < 4; e++) w[4 * i + e] = hadd2_bf16(w[4 * i + e] & mk, (e & 1) ? m1 : m0);
          }
        }
        wg_wait<0>();
#pragma unroll
        for (int i = 0; i < 32; i++) w[i] = hadd2_bf16(w[i], pack2(acc[2 * i], acc[2 * i + 1]));
#pragma unroll 1
        while (!__all_sync(0xffffffffu, pv[0][0].y & pv[0][1].y & pv[0][2].y & pv[0][3].y & pv[1][0].y & pv[1][1].y & pv[1][2].y & pv[1][3].y & 1u)) {
          ld_tag4_issue<16384>(pv[0], xsrc);
          ld_tag4_issue<16384>(pv[1], xsrc + 65536);
        }
#pragma unroll
        for (int i = 0; i < 8; i++) {
          const uint4& p = pv[i >> 2][i & 3];
          asm volatile("stmatrix.sync.aligned.m8n8.x4.shared.b16 [%0], {%1,%2,%3,%4};"
                       ::"r"(pa0 + (11 + ((lane >> 3) & 1)) * SLOT + (lane & 7) * 256 + (((2 * i + (lane >> 4)) ^ (lane & 7)) * 16)),
                         "r"(hadd2_bf16(w[4 * i], p.x & ~1u)), "r"(hadd2_bf16(w[4 * i + 1], p.y & ~1u)), "r"(hadd2_bf16(w[4 * i + 2], p.z)),
                         "r"(hadd2_bf16(w[4 * i + 3], p.w)) : "memory");
        }
        __syncwarp();
        uint4* const dst = reinterpret_cast<uint4*>(out) + (16 * (c >> 4) + 2 * (4 * rh + wq) + (rb2 & 1) + 128 * (lane >> 4)) * 64 + nq * 16 + (lane & 15);
#pragma unroll
        for (int i = 0; i < 8; i++) {
          const int r = 2 * (i & 3) + (lane >> 4);
          dst[i * 256 * 64] = lds4(pa0 + (11 + (i >> 2)) * SLOT + r * 256 + (((lane & 15) ^ r) * 16));
        }
      }
      if (lane == 0) mbar_arrive(BAR(done, 0));
    }
  }
#undef BAR
#undef TOFF
#undef RBAR
}

typedef CUresult (*EncodeFn)(CUtensorMap*, CUtensorMapDataType, cuuint32_t, void*, const cuuint64_t*, const cuuint64_t*,
                             const cuuint32_t*, const cuuint32_t*, CUtensorMapInterleave, CUtensorMapSwizzle,
                             CUtensorMapL2promotion, CUtensorMapFloatOOBfill);

}

extern "C" void kernel_launch(void* const* d_in, const int* in_sizes, int n_in, void* d_out, int out_size) {
  (void)in_sizes; (void)n_in; (void)out_size;
  static EncodeFn encode = nullptr;
  static void *tab = nullptr, *scr = nullptr;
  if (!encode) {
    void* fn = nullptr;
    cudaDriverEntryPointQueryResult qr;
    cudaGetDriverEntryPoint("cuTensorMapEncodeTiled", &fn, cudaEnableDefault, &qr);
    encode = (EncodeFn)fn;
    cudaGetSymbolAddress(&tab, g_tab);
    cudaGetSymbolAddress(&scr, g_scr);
    cudaFuncSetAttribute(fused_kernel, cudaFuncAttributeMaxDynamicSharedMemorySize, SMEM_BYTES);
  }
  CUtensorMap tmGX, tmUX, tmGY, tmUY, tmD, tmWR, tmWI;
  const cuuint32_t es[5] = {1, 1, 1, 1, 1};
  auto enc = [&](CUtensorMap* m, void* p, int rank, const cuuint64_t* gd, const cuuint64_t* gs, const cuuint32_t* bd,
                 CUtensorMapSwizzle sw, CUtensorMapL2promotion pr) {
    encode(m, CU_TENSOR_MAP_DATA_TYPE_BFLOAT16, rank, p, gd, gs, bd, es, CU_TENSOR_MAP_INTERLEAVE_NONE, sw, pr,
           CU_TENSOR_MAP_FLOAT_OOB_FILL_NONE);
  };
  {
    const cuuint64_t gd[3] = {64, 512, 28}, gs[2] = {3584, 128};
    const cuuint32_t bd[3] = {64, 32, 2};
    enc(&tmGX, d_in[4], 3, gd, gs, bd, CU_TENSOR_MAP_SWIZZLE_128B, CU_TENSOR_MAP_L2_PROMOTION_L2_256B);
    enc(&tmUX, d_in[5], 3, gd, gs, bd, CU_TENSOR_MAP_SWIZZLE_128B, CU_TENSOR_MAP_L2_PROMOTION_L2_256B);
  }
  {
    const cuuint64_t gd[3] = {32, 512, 56}, gs[2] = {3584, 64};
    const cuuint32_t bd[3] = {32, 32, 3};
    enc(&tmGY, d_in[4], 3, gd, gs, bd, CU_TENSOR_MAP_SWIZZLE_64B, CU_TENSOR_MAP_L2_PROMOTION_L2_128B);
    enc(&tmUY, d_in[5], 3, gd, gs, bd, CU_TENSOR_MAP_SWIZZLE_64B, CU_TENSOR_MAP_L2_PROMOTION_L2_128B);
  }
  {
    const cuuint64_t gd[3] = {64, 1792, 8}, gs[2] = {1024, 128};
    const cuuint32_t bd[3] = {64, 64, 2};
    enc(&tmD, d_in[6], 3, gd, gs, bd, CU_TENSOR_MAP_SWIZZLE_128B, CU_TENSOR_MAP_L2_PROMOTION_L2_256B);
  }
  {
    const cuuint64_t gd[3] = {4112, 8, 16}, gs[2] = {16 * 8224, 8224};
    const cuuint32_t bd[3] = {40, 8, 16};
    enc(&tmWR, d_in[1], 3, gd, gs, bd, CU_TENSOR_MAP_SWIZZLE_NONE, CU_TENSOR_MAP_L2_PROMOTION_NONE);
    enc(&tmWI, d_in[2], 3, gd, gs, bd, CU_TENSOR_MAP_SWIZZLE_NONE, CU_TENSOR_MAP_L2_PROMOTION_NONE);
  }
  fused_kernel<<<NCTA, NTHREADS, SMEM_BYTES>>>((const __nv_bfloat16*)d_in[0], (const Tables*)tab, (Scratch*)scr,
                                               (__nv_bfloat16*)d_out, (const char*)d_in[4], (const char*)d_in[5],
                                               (const char*)d_in[6], tmWR, tmWI, tmGX, tmUX, tmGY, tmUY, tmD);
}
```

```cpp
#include <cuda_runtime.h>
#include <cuda_bf16.h>
#include <cuda.h>
#include <stdint.h>

namespace {

constexpr int NCTA = 128;
constexpr int NTHREADS = 384;
constexpr int SLOT = 16384;
constexpr int SMEM_BYTES = 14 * SLOT + 3072;
constexpr int SPIN_LIMIT = 1 << 22;

struct Scratch {
  uint4 Z1[128 * 1024];
  uint4 LN[16 * 8 * 1024];
  uint4 P[16 * 28 * 1024];
  uint4 ST[1024];
  unsigned cnt[64 * 32];
};
__device__ __align__(1024) Scratch g_scr;

constexpr double ccos(int i, int n) {
  i &= n - 1;
  if (i > n / 2) i = n - i;
  if (4 * i == n) return 0.0;
  const bool neg = 4 * i > n;
  if (neg) i = n / 2 - i;
  const double a = 6.283185307179586476925 * i / n, a2 = a * a;
  double term = 1.0, sum = 1.0;
  for (int k = 1; k < 14; k++) { term *= -a2 / ((2 * k - 1) * (2 * k)); sum += term; }
  return neg ? -sum : sum;
}
constexpr double csin(int i, int n) { return ccos(i - n / 4, n); }
constexpr unsigned fbits(double v, int mant) {
  if (v == 0.0) return 0;
  const unsigned sg = v < 0 ? 1u : 0u;
  if (v < 0) v = -v;
  int e = 127;
  while (v < 1.0) { v *= 2.0; e--; }
  const unsigned m = (unsigned)((v - 1.0) * (double)(1u << mant) + 0.5);
  return (sg << (8 + mant)) + ((unsigned)e << mant) + m;
}
constexpr unsigned pkb(double lo, double hi) { return fbits(lo, 7) | (fbits(hi, 7) << 16); }
constexpr double fa_elem(int mt, int r, int n1) {
  const int k1 = 8 * mt + (r & 7);
  return r < 8 ? ccos(k1 * n1, 32) : k1 == 0 ? ccos(16 * n1, 32) : -csin(k1 * n1, 32);
}
constexpr unsigned cfrag_c(int idx, int n, int ri, double s = 1.0) {
  return ri ? pkb(-s * csin(idx, n), s * ccos(idx, n)) : pkb(s * ccos(idx, n), s * csin(idx, n));
}
struct Tables {
  unsigned fa[4][32][4];
  unsigned fb[4][32][4];
  unsigned tw1[6][32][4];
  unsigned f2[8][4][32][4];
  unsigned g2[8][4][32][4];
  unsigned gb[4][32][4];
  unsigned ga[4][32][4];
  unsigned tw3[4][32][4];
  unsigned f8[32][4], g8[32][4];
};
constexpr int T1_BYTES = 7168, T2_BYTES = 39936;
static_assert(sizeof(Tables) == T1_BYTES + T2_BYTES, "table size");
constexpr Tables make_tables() {
  Tables T = {};
  for (int l = 0; l < 32; l++) {
    const int g = l >> 2, t = l & 3;
    for (int a = 0; a < 2; a++)
      for (int b = 0; b < 2; b++) {
        for (int r = 0; r < 4; r++) {
          const int row = g + 8 * (r & 1), col = 2 * t + 8 * (r >> 1);
          T.fa[2 * a + b][l][r] = pkb(fa_elem(a, row, 16 * b + col), fa_elem(a, row, 16 * b + col + 1));
          T.ga[2 * a + b][l][r] = pkb(fa_elem(b, col, 16 * a + row), fa_elem(b, col + 1, 16 * a + row));
        }
        const double sg = b ? -1.0 : 1.0;
        for (int h = 0; h < 2; h++) {
          const int ri = g & 1, m = 2 * (g >> 1) + h, k2 = b ? 15 - m : m;
          const int pa = (8 * a + 2 * t) * k2, pb = (8 * a + 2 * t + 1) * k2;
          T.fb[2 * a + b][l][2 * h] = ri == 0 ? pkb(ccos(pa, 16), ccos(pb, 16)) : pkb(-sg * csin(pa, 16), -sg * csin(pb, 16));
          T.fb[2 * a + b][l][2 * h + 1] = ri == 0 ? pkb(csin(pa, 16), csin(pb, 16)) : pkb(sg * ccos(pa, 16), sg * ccos(pb, 16));
        }
        const int n2 = 4 * (g >> 1) + 2 * a + (g & 1);
        for (int h = 0; h < 2; h++) {
          const int p = n2 * (b ? 15 - 2 * t - h : 2 * t + h);
          T.gb[2 * a + b][l][2 * h] = pkb(ccos(p, 16), -sg * csin(p, 16));
          T.gb[2 * a + b][l][2 * h + 1] = pkb(csin(p, 16), sg * ccos(p, 16));
          const int k1 = 8 * b + 2 * t + h, q = n2 * (k1 == 0 ? 16 : k1);
          T.tw3[2 * a + b][l][2 * h] = fbits(ccos(q, 512), 23);
          T.tw3[2 * a + b][l][2 * h + 1] = fbits(csin(q, 512), 23);
        }
        const int p = (8 * a + 2 * t + b) * (g == 0 ? 16 : g);
        T.tw1[2 * a + b][l][0] = fbits(g == 0 ? 0.0 : ccos(p, 512), 23);
        T.tw1[2 * a + b][l][1] = fbits(g == 0 ? ccos(p, 512) : csin(p, 512), 23);
        T.tw1[2 * a + b][l][2] = fbits(g == 0 ? 0.0 : -csin(p, 512), 23);
        T.tw1[2 * a + b][l][3] = fbits(g == 0 ? -csin(p, 512) : ccos(p, 512), 23);
        T.tw1[4 + a][l][2 * b] = fbits(ccos((8 * a + 2 * t + b) * (g + 8), 512), 23);
        T.tw1[4 + a][l][2 * b + 1] = fbits(csin((8 * a + 2 * t + b) * (g + 8), 512), 23);
      }
    for (int i = 0; i < 4; i++) {
      const int p8 = (t + 4 * (i & 1)) * (4 * (i >> 1) + (g >> 1));
      T.f8[l][i] = cfrag_c(p8, 8, g & 1);
      T.g8[l][i] = cfrag_c(-p8, 8, g & 1, 1.0 / (1 << 19));
    }
    for (int w = 0; w < 8; w++)
      for (int i = 0; i < 16; i++) {
        const int kidx = t + 4 * (i & 1) + 8 * (i >> 3), nidx = 4 * ((i >> 1) & 3) + (g >> 1);
        T.f2[w][i >> 2][l][i & 3] = cfrag_c((8 * kidx + w) * nidx, 128, g & 1);
        T.g2[w][i >> 2][l][i & 3] = cfrag_c(-(8 * nidx + w) * kidx, 128, g & 1);
      }
  }
  return T;
}
__device__ const __align__(128) Tables g_tab = make_tables();

__device__ __forceinline__ void die() { asm volatile("st.global.u32 [%0], %1;" ::"l"(0ull), "r"(0) : "memory"); }
__device__ __forceinline__ uint32_t s2u(const void* p) { return (uint32_t)__cvta_generic_to_shared(p); }
__device__ __forceinline__ void mbar_init(uint32_t b, int c) { asm volatile("mbarrier.init.shared::cta.b64 [%0], %1;" ::"r"(b), "r"(c)); }
__device__ __forceinline__ void mbar_expect(uint32_t b, int bytes) {
  asm volatile("mbarrier.arrive.expect_tx.shared::cta.b64 _, [%0], %1;" ::"r"(b), "r"(bytes) : "memory");
}
__device__ __forceinline__ void mbar_arrive(uint32_t b) { asm volatile("mbarrier.arrive.shared::cta.b64 _, [%0];" ::"r"(b) : "memory"); }
__device__ __forceinline__ uint32_t mbar_try(uint32_t b, uint32_t parity) {
  uint32_t ok;
  asm volatile("{.reg .pred p; mbarrier.try_wait.parity.shared::cta.b64 p, [%1], %2; selp.u32 %0,1,0,p;}"
               : "=r"(ok) : "r"(b), "r"(parity) : "memory");
  return ok;
}
__device__ __forceinline__ uint32_t mbar_test(uint32_t b) {
  uint32_t ok;
  asm volatile("{.reg .pred p; mbarrier.test_wait.parity.shared::cta.b64 p, [%1], 0; selp.u32 %0,1,0,p;}" : "=r"(ok) : "r"(b) : "memory");
  return ok;
}
__device__ __forceinline__ void mbar_wait_bounded(uint32_t b) {
  int it = 0;
#pragma unroll 1
  while (!mbar_try(b, 0))
    if (++it > SPIN_LIMIT) { die(); break; }
}
__device__ __forceinline__ void mbar_wait(uint32_t b) {
  asm volatile("{.reg .pred p;\nW_%=: mbarrier.try_wait.parity.shared::cta.b64 p, [%0], 0;\n@!p bra W_%=;}" ::"r"(b) : "memory");
}
__device__ __forceinline__ void bar_sync(int id, int n) { asm volatile("bar.sync %0, %1;" ::"r"(id), "r"(n) : "memory"); }
__device__ __forceinline__ void bar_arrive(int id, int n) { asm volatile("bar.arrive %0, %1;" ::"r"(id), "r"(n) : "memory"); }
__device__ __forceinline__ void red_release(unsigned* p) { asm volatile("red.release.gpu.global.add.u32 [%0], 1;" ::"l"(p) : "memory"); }
__device__ __forceinline__ void red_relaxed(unsigned* p) { asm volatile("red.relaxed.gpu.global.add.u32 [%0], 1;" ::"l"(p) : "memory"); }
__device__ __forceinline__ unsigned ld_acquire(const unsigned* p) {
  unsigned v;
  asm volatile("ld.acquire.gpu.global.u32 %0, [%1];" : "=r"(v) : "l"(p) : "memory");
  return v;
}
__device__ __forceinline__ unsigned ld_relaxed(const unsigned* p) {
  unsigned v;
  asm volatile("ld.relaxed.gpu.global.u32 %0, [%1];" : "=r"(v) : "l"(p) : "memory");
  return v;
}
__device__ __forceinline__ void wait_counter(const unsigned* p, unsigned target) {
#pragma unroll 1
  while ((int)(ld_acquire(p) - target) < 0) {}
}
__device__ __forceinline__ void sts4(uint32_t a, uint32_t x, uint32_t y, uint32_t z, uint32_t w) {
  asm volatile("st.shared.v4.u32 [%0], {%1,%2,%3,%4};" ::"r"(a), "r"(x), "r"(y), "r"(z), "r"(w) : "memory");
}
__device__ __forceinline__ uint4 lds4(uint32_t a) {
  uint4 v;
  asm volatile("ld.shared.v4.u32 {%0,%1,%2,%3}, [%4];" : "=r"(v.x), "=r"(v.y), "=r"(v.z), "=r"(v.w) : "r"(a) : "memory");
  return v;
}
__device__ __forceinline__ uint32_t pack2(float lo, float hi) {
  uint32_t r;
  asm("cvt.rn.bf16x2.f32 %0, %1, %2;" : "=r"(r) : "f"(hi), "f"(lo));
  return r;
}
__device__ __forceinline__ float bf_lo(uint32_t v) { return __uint_as_float(v << 16); }
__device__ __forceinline__ uint32_t hadd2_bf16(uint32_t a, uint32_t b) {
  uint32_t r;
  asm("add.rn.bf16x2 %0, %1, %2;" : "=r"(r) : "r"(a), "r"(b));
  return r;
}
__device__ __forceinline__ void mma16816(float (&d)[4], uint32_t a0, uint32_t a1, uint32_t a2, uint32_t a3, uint32_t b0, uint32_t b1) {
  asm("mma.sync.aligned.m16n8k16.row.col.f32.bf16.bf16.f32 {%0,%1,%2,%3}, {%4,%5,%6,%7}, {%8,%9}, {%0,%1,%2,%3};"
      : "+f"(d[0]), "+f"(d[1]), "+f"(d[2]), "+f"(d[3])
      : "r"(a0), "r"(a1), "r"(a2), "r"(a3), "r"(b0), "r"(b1));
}
__device__ __forceinline__ void mma16816_z(float (&d)[4], uint32_t a0, uint32_t a1, uint32_t a2, uint32_t a3, uint32_t b0, uint32_t b1) {
  asm("{.reg .f32 z; mov.f32 z, 0f00000000;\n"
      "mma.sync.aligned.m16n8k16.row.col.f32.bf16.bf16.f32 {%0,%1,%2,%3}, {%4,%5,%6,%7}, {%8,%9}, {z,z,z,z};}"
      : "=f"(d[0]), "=f"(d[1]), "=f"(d[2]), "=f"(d[3])
      : "r"(a0), "r"(a1), "r"(a2), "r"(a3), "r"(b0), "r"(b1));
}
template <int N>
__device__ __forceinline__ void cs_frac(int idx, float& c, float& s) {
  int i = ((idx + N / 2) & (N - 1)) - N / 2;
  float a = (float)i * (6.283185307179586f / N);
  c = __cosf(a);
  s = __sinf(a);
}
template <int N>
__device__ __forceinline__ uint32_t cfrag(int idx, int ri) {
  float c, s;
  cs_frac<N>(idx, c, s);
  return ri ? pack2(-s, c) : pack2(c, s);
}
__device__ __forceinline__ uint32_t word(const uint4& v, int e) { return e == 0 ? v.x : e == 1 ? v.y : e == 2 ? v.z : v.w; }
__device__ __forceinline__ void cdft16(const uint4 (&A)[4], const uint4 (&F)[4], uint4 (&o)[4]) {
  float acc[2][4][4];
#pragma unroll
  for (int ks = 0; ks < 2; ks++)
#pragma unroll
    for (int p = 0; p < 2; p++)
#pragma unroll
      for (int v = 0; v < 4; v++) {
        const uint4& a = A[2 * ks + p];
        const uint32_t b0 = word(F[ks * 2 + (v >> 1)], (v & 1) * 2), b1 = word(F[ks * 2 + (v >> 1)], (v & 1) * 2 + 1);
        if (ks == 0) mma16816_z(acc[p][v], a.x, a.y, a.z, a.w, b0, b1);
        else mma16816(acc[p][v], a.x, a.y, a.z, a.w, b0, b1);
      }
#pragma unroll
  for (int v = 0; v < 4; v++)
    o[v] = make_uint4(pack2(acc[0][v][0], acc[0][v][1]), pack2(acc[0][v][2], acc[0][v][3]),
                      pack2(acc[1][v][0], acc[1][v][1]), pack2(acc[1][v][2], acc[1][v][3]));
}
__device__ __forceinline__ void lds_frag(uint4& f0, uint4& f1, uint32_t a0, uint32_t a1) {
  asm volatile("ld.volatile.shared.v2.u32 {%0,%1}, [%8]; ld.volatile.shared.v2.u32 {%2,%3}, [%9];\n"
               "ld.volatile.shared.v2.u32 {%4,%5}, [%8+8]; ld.volatile.shared.v2.u32 {%6,%7}, [%9+8];"
               : "=r"(f0.x), "=r"(f0.y), "=r"(f0.z), "=r"(f0.w), "=r"(f1.x), "=r"(f1.y), "=r"(f1.z), "=r"(f1.w) : "r"(a0), "r"(a1) : "memory");
}
__device__ __forceinline__ void reg_frag(uint4 (&q)[4], uint32_t ones) {
#pragma unroll
  for (int ks = 0; ks < 2; ks++) {
    const uint4 a = q[2 * ks], b = q[2 * ks + 1];
    q[2 * ks] = make_uint4(a.x, a.y, b.x & ones, b.y & ones);
    q[2 * ks + 1] = make_uint4(a.z & ones, a.w & ones, b.z, b.w);
  }
}
__device__ __forceinline__ void st_tag(uint4* p, const uint4& v, uint32_t tag) {
  asm volatile("st.relaxed.gpu.global.v4.b32 [%0], {%1,%2,%3,%4};"
               ::"l"(p), "r"((v.x & ~1u) | tag), "r"(v.y), "r"(v.z), "r"(v.w) : "memory");
}
__device__ __forceinline__ void st_tag8(void* p, uint32_t x, uint32_t y, uint32_t tag) {
  asm volatile("st.relaxed.gpu.global.v2.b32 [%0], {%1,%2};" ::"l"(p), "r"((x & ~1u) | tag), "r"(y) : "memory");
}
__device__ __forceinline__ uint4 ld_b128(const uint4* p) {
  uint4 v;
  asm volatile("ld.relaxed.gpu.global.v4.b32 {%0,%1,%2,%3}, [%4];"
               : "=r"(v.x), "=r"(v.y), "=r"(v.z), "=r"(v.w) : "l"(p) : "memory");
  return v;
}
template <int STRIDE>
__device__ __forceinline__ void ld_tag4_issue(uint4 (&q)[4], const uint4* p) {
#pragma unroll
  for (int i = 0; i < 4; i++) q[i] = ld_b128(p + i * STRIDE);
}
__device__ __forceinline__ uint32_t tag_miss(uint32_t a, uint32_t b, uint32_t c, uint32_t d, uint32_t tag) {
  uint32_t r;
  asm("{.reg .b32 u, v; lop3.b32 u, %1, %2, %5, 0x7e; lop3.b32 v, %3, %4, %5, 0x7e; lop3.b32 %0, u, v, 1, 0xa8;}"
      : "=r"(r) : "r"(a), "r"(b), "r"(c), "r"(d), "r"(tag));
  return r;
}
template <int STRIDE, bool HALVES = false>
__device__ __forceinline__ void ld_tag4_finish(uint4 (&q)[4], const uint4* p, uint32_t tag) {
  int it = 0;
#pragma unroll 1
  while (__any_sync(0xffffffffu, tag_miss(q[0].x, q[1].x, q[2].x, q[3].x, tag) | (HALVES ? tag_miss(q[0].z, q[1].z, q[2].z, q[3].z, tag) : 0u))) {
    ld_tag4_issue<STRIDE>(q, p);
    if (++it > SPIN_LIMIT) { die(); break; }
  }
#pragma unroll
  for (int i = 0; i < 4; i++) {
    asm volatile("and.b32 %0, %0, 0xfffffffe;" : "+r"(q[i].x));
    if (HALVES) q[i].z &= ~1u;
  }
}
__device__ __forceinline__ float quad_sum(const uint32_t (&a)[8]) {
  float d[4];
  mma16816_z(d, a[0], a[1], a[2], a[3], 0x3f803f80u, 0x3f803f80u);
  mma16816(d, a[4], a[5], a[6], a[7], 0x3f803f80u, 0x3f803f80u);
  return d[0] + d[2];
}
__device__ __forceinline__ float sum_groups(float v) {
  v += __shfl_xor_sync(0xffffffffu, v, 4);
  v += __shfl_xor_sync(0xffffffffu, v, 8);
  v += __shfl_xor_sync(0xffffffffu, v, 16);
  return v;
}
__device__ __forceinline__ uint32_t hsub2_bf16(uint32_t a, uint32_t b) {
  uint32_t r;
  asm("sub.rn.bf16x2 %0, %1, %2;" : "=r"(r) : "r"(a), "r"(b));
  return r;
}
__device__ __forceinline__ float row_rstd(const uint32_t (&c)[8]) {
  uint32_t s[8];
#pragma unroll
  for (int i = 0; i < 8; i++) asm("mul.rn.bf16x2 %0, %1, %1;" : "=r"(s[i]) : "r"(c[i]));
  return rsqrtf(fmaf(sum_groups(quad_sum(s)), 1.f / 512.f, 1e-5f));
}
__device__ __forceinline__ uint64_t desc64(uint32_t lo, uint32_t hi) {
  uint64_t d;
  asm("mov.b64 %0, {%1, %2};" : "=l"(d) : "r"(lo), "r"(hi));
  return d;
}
constexpr uint32_t desc_hi(uint32_t sbo, uint32_t swz) { return (sbo >> 4) | (swz << 30); }
__device__ __forceinline__ uint32_t desc_lo(uint32_t addr, uint32_t lbo) { return ((addr & 0x3FFFF) >> 4) | ((lbo >> 4) << 16); }
__device__ __forceinline__ void cp_async16(uint32_t dst, const void* src) {
  asm volatile("cp.async.cg.shared.global [%0], [%1], 16;" ::"r"(dst), "l"(src) : "memory");
}
__device__ __forceinline__ uint2 lds2(uint32_t a) {
  uint2 v;
  asm volatile("ld.shared.v2.u32 {%0,%1}, [%2];" : "=r"(v.x), "=r"(v.y) : "r"(a) : "memory");
  return v;
}
__device__ __forceinline__ uint32_t lds_u16(uint32_t a) {
  uint16_t v;
  asm volatile("ld.shared.u16 %0, [%1];" : "=h"(v) : "r"(a) : "memory");
  return v;
}
__device__ __forceinline__ void wg_fence() { asm volatile("wgmma.fence.sync.aligned;" ::: "memory"); }
__device__ __forceinline__ void wg_commit() { asm volatile("wgmma.commit_group.sync.aligned;" ::: "memory"); }
template <int N>
__device__ __forceinline__ void wg_wait() { asm volatile("wgmma.wait_group.sync.aligned %0;" ::"n"(N) : "memory"); }
__device__ __forceinline__ void bulk_load(uint32_t dst, const void* src, int bytes, uint32_t bar) {
  asm volatile("cp.async.bulk.shared::cluster.global.mbarrier::complete_tx::bytes [%0], [%1], %2, [%3];"
               ::"r"(dst), "l"(src), "r"(bytes), "r"(bar) : "memory");
}
__device__ __forceinline__ void bulk_load_mc(uint32_t dst, const void* src, int bytes, uint32_t bar) {
  asm volatile("cp.async.bulk.shared::cluster.global.mbarrier::complete_tx::bytes.multicast::cluster [%0], [%1], %2, [%3], %4;"
               ::"r"(dst), "l"(src), "r"(bytes), "r"(bar), "h"((uint16_t)3) : "memory");
}
__device__ __forceinline__ void tma3(uint32_t dst, const CUtensorMap* tm, uint32_t bar, int c0, int c1, int c2) {
  asm volatile("cp.async.bulk.tensor.3d.shared::cluster.global.mbarrier::complete_tx::bytes [%0], [%1, {%3,%4,%5}], [%2];"
               ::"r"(dst), "l"(tm), "r"(bar), "r"(c0), "r"(c1), "r"(c2) : "memory");
}
__device__ __forceinline__ void tma3_mc(uint32_t dst, const CUtensorMap* tm, uint32_t bar, int c1, int c2) {
  asm volatile("cp.async.bulk.tensor.3d.shared::cluster.global.mbarrier::complete_tx::bytes.multicast::cluster [%0], [%1, {%3,%4,%5}], [%2], %6;"
               ::"r"(dst), "l"(tm), "r"(bar), "r"(0), "r"(c1), "r"(c2), "h"((uint16_t)3) : "memory");
}
__device__ __forceinline__ void mbar_arrive_remote(uint32_t rb) {
  asm volatile("mbarrier.arrive.shared::cluster.b64 _, [%0];" ::"r"(rb) : "memory");
}
__device__ __forceinline__ uint4 ldg_ca4(const void* p) {
  uint4 v;
  asm volatile("ld.global.ca.v4.u32 {%0,%1,%2,%3}, [%4];" : "=r"(v.x), "=r"(v.y), "=r"(v.z), "=r"(v.w) : "l"(p) : "memory");
  return v;
}
__device__ __forceinline__ float u2f(uint32_t v) { return __uint_as_float(v); }
__device__ __forceinline__ void mma_az(float (&d)[4], const uint4& a, uint32_t b0, uint32_t b1) { mma16816_z(d, a.x, a.y, a.z, a.w, b0, b1); }
__device__ __forceinline__ void mma_a(float (&d)[4], const uint4& a, uint32_t b0, uint32_t b1) { mma16816(d, a.x, a.y, a.z, a.w, b0, b1); }
__device__ __forceinline__ uint32_t clock32() {
  uint32_t v;
  asm volatile("mov.u32 %0, %%clock;" : "=r"(v) :: "memory");
  return v;
}
__device__ __forceinline__ float swiglu(float g, float u, float r) {
  float hg = (0.5f * r) * g, th;
  asm("tanh.approx.f32 %0, %1;" : "=f"(th) : "f"(hg));
  return fmaf(hg, th, hg) * (r * u);
}
__device__ __forceinline__ void l2_prefetch(const void* p, int bytes) {
  asm volatile("cp.async.bulk.prefetch.L2.global [%0], %1;" ::"l"(p), "r"(bytes) : "memory");
}

__device__ __forceinline__ void wgmma_n256(float (&d)[128], uint64_t da, uint64_t db, int sd = 1) {
  asm volatile("{.reg .pred p; setp.ne.b32 p, %130, 0;\n"
      "wgmma.mma_async.sync.aligned.m64n256k16.f32.bf16.bf16 {"
      "%0,%1,%2,%3,%4,%5,%6,%7,%8,%9,%10,%11,%12,%13,%14,%15,"
      "%16,%17,%18,%19,%20,%21,%22,%23,%24,%25,%26,%27,%28,%29,%30,%31,"
      "%32,%33,%34,%35,%36,%37,%38,%39,%40,%41,%42,%43,%44,%45,%46,%47,"
      "%48,%49,%50,%51,%52,%53,%54,%55,%56,%57,%58,%59,%60,%61,%62,%63,"
      "%64,%65,%66,%67,%68,%69,%70,%71,%72,%73,%74,%75,%76,%77,%78,%79,"
      "%80,%81,%82,%83,%84,%85,%86,%87,%88,%89,%90,%91,%92,%93,%94,%95,"
      "%96,%97,%98,%99,%100,%101,%102,%103,%104,%105,%106,%107,%108,%109,%110,%111,"
      "%112,%113,%114,%115,%116,%117,%118,%119,%120,%121,%122,%123,%124,%125,%126,%127"
      "}, %128, %129, p, 1, 1, 0, 1;}\n"
      : "+f"(d[0]),"+f"(d[1]),"+f"(d[2]),"+f"(d[3]),"+f"(d[4]),"+f"(d[5]),"+f"(d[6]),"+f"(d[7]),
        "+f"(d[8]),"+f"(d[9]),"+f"(d[10]),"+f"(d[11]),"+f"(d[12]),"+f"(d[13]),"+f"(d[14]),"+f"(d[15]),
        "+f"(d[16]),"+f"(d[17]),"+f"(d[18]),"+f"(d[19]),"+f"(d[20]),"+f"(d[21]),"+f"(d[22]),"+f"(d[23]),
        "+f"(d[24]),"+f"(d[25]),"+f"(d[26]),"+f"(d[27]),"+f"(d[28]),"+f"(d[29]),"+f"(d[30]),"+f"(d[31]),
        "+f"(d[32]),"+f"(d[33]),"+f"(d[34]),"+f"(d[35]),"+f"(d[36]),"+f"(d[37]),"+f"(d[38]),"+f"(d[39]),
        "+f"(d[40]),"+f"(d[41]),"+f"(d[42]),"+f"(d[43]),"+f"(d[44]),"+f"(d[45]),"+f"(d[46]),"+f"(d[47]),
        "+f"(d[48]),"+f"(d[49]),"+f"(d[50]),"+f"(d[51]),"+f"(d[52]),"+f"(d[53]),"+f"(d[54]),"+f"(d[55]),
        "+f"(d[56]),"+f"(d[57]),"+f"(d[58]),"+f"(d[59]),"+f"(d[60]),"+f"(d[61]),"+f"(d[62]),"+f"(d[63]),
        "+f"(d[64]),"+f"(d[65]),"+f"(d[66]),"+f"(d[67]),"+f"(d[68]),"+f"(d[69]),"+f"(d[70]),"+f"(d[71]),
        "+f"(d[72]),"+f"(d[73]),"+f"(d[74]),"+f"(d[75]),"+f"(d[76]),"+f"(d[77]),"+f"(d[78]),"+f"(d[79]),
        "+f"(d[80]),"+f"(d[81]),"+f"(d[82]),"+f"(d[83]),"+f"(d[84]),"+f"(d[85]),"+f"(d[86]),"+f"(d[87]),
        "+f"(d[88]),"+f"(d[89]),"+f"(d[90]),"+f"(d[91]),"+f"(d[92]),"+f"(d[93]),"+f"(d[94]),"+f"(d[95]),
        "+f"(d[96]),"+f"(d[97]),"+f"(d[98]),"+f"(d[99]),"+f"(d[100]),"+f"(d[101]),"+f"(d[102]),"+f"(d[103]),
        "+f"(d[104]),"+f"(d[105]),"+f"(d[106]),"+f"(d[107]),"+f"(d[108]),"+f"(d[109]),"+f"(d[110]),"+f"(d[111]),
        "+f"(d[112]),"+f"(d[113]),"+f"(d[114]),"+f"(d[115]),"+f"(d[116]),"+f"(d[117]),"+f"(d[118]),"+f"(d[119]),
        "+f"(d[120]),"+f"(d[121]),"+f"(d[122]),"+f"(d[123]),"+f"(d[124]),"+f"(d[125]),"+f"(d[126]),"+f"(d[127])
      : "l"(da), "l"(db), "r"(sd));
}
__device__ __forceinline__ void wgmma_n192(float (&d)[96], uint64_t da, uint64_t db) {
  asm volatile("wgmma.mma_async.sync.aligned.m64n192k16.f32.bf16.bf16 {"
      "%0,%1,%2,%3,%4,%5,%6,%7,%8,%9,%10,%11,%12,%13,%14,%15,"
      "%16,%17,%18,%19,%20,%21,%22,%23,%24,%25,%26,%27,%28,%29,%30,%31,"
      "%32,%33,%34,%35,%36,%37,%38,%39,%40,%41,%42,%43,%44,%45,%46,%47,"
      "%48,%49,%50,%51,%52,%53,%54,%55,%56,%57,%58,%59,%60,%61,%62,%63,"
      "%64,%65,%66,%67,%68,%69,%70,%71,%72,%73,%74,%75,%76,%77,%78,%79,"
      "%80,%81,%82,%83,%84,%85,%86,%87,%88,%89,%90,%91,%92,%93,%94,%95"
      "}, %96, %97, 1, 1, 1, 0, 1;\n"
      : "+f"(d[0]),"+f"(d[1]),"+f"(d[2]),"+f"(d[3]),"+f"(d[4]),"+f"(d[5]),"+f"(d[6]),"+f"(d[7]),
        "+f"(d[8]),"+f"(d[9]),"+f"(d[10]),"+f"(d[11]),"+f"(d[12]),"+f"(d[13]),"+f"(d[14]),"+f"(d[15]),
        "+f"(d[16]),"+f"(d[17]),"+f"(d[18]),"+f"(d[19]),"+f"(d[20]),"+f"(d[21]),"+f"(d[22]),"+f"(d[23]),
        "+f"(d[24]),"+f"(d[25]),"+f"(d[26]),"+f"(d[27]),"+f"(d[28]),"+f"(d[29]),"+f"(d[30]),"+f"(d[31]),
        "+f"(d[32]),"+f"(d[33]),"+f"(d[34]),"+f"(d[35]),"+f"(d[36]),"+f"(d[37]),"+f"(d[38]),"+f"(d[39]),
        "+f"(d[40]),"+f"(d[41]),"+f"(d[42]),"+f"(d[43]),"+f"(d[44]),"+f"(d[45]),"+f"(d[46]),"+f"(d[47]),
        "+f"(d[48]),"+f"(d[49]),"+f"(d[50]),"+f"(d[51]),"+f"(d[52]),"+f"(d[53]),"+f"(d[54]),"+f"(d[55]),
        "+f"(d[56]),"+f"(d[57]),"+f"(d[58]),"+f"(d[59]),"+f"(d[60]),"+f"(d[61]),"+f"(d[62]),"+f"(d[63]),
        "+f"(d[64]),"+f"(d[65]),"+f"(d[66]),"+f"(d[67]),"+f"(d[68]),"+f"(d[69]),"+f"(d[70]),"+f"(d[71]),
        "+f"(d[72]),"+f"(d[73]),"+f"(d[74]),"+f"(d[75]),"+f"(d[76]),"+f"(d[77]),"+f"(d[78]),"+f"(d[79]),
        "+f"(d[80]),"+f"(d[81]),"+f"(d[82]),"+f"(d[83]),"+f"(d[84]),"+f"(d[85]),"+f"(d[86]),"+f"(d[87]),
        "+f"(d[88]),"+f"(d[89]),"+f"(d[90]),"+f"(d[91]),"+f"(d[92]),"+f"(d[93]),"+f"(d[94]),"+f"(d[95])
      : "l"(da), "l"(db));
}
__device__ __forceinline__ void wgmma_rs_n128(float (&d)[64], uint32_t a0, uint32_t a1, uint32_t a2, uint32_t a3, uint64_t db, int sd = 1) {
  asm volatile("{.reg .pred p; setp.ne.b32 p, %69, 0;\n"
      "wgmma.mma_async.sync.aligned.m64n128k16.f32.bf16.bf16 {"
      "%0,%1,%2,%3,%4,%5,%6,%7,%8,%9,%10,%11,%12,%13,%14,%15,"
      "%16,%17,%18,%19,%20,%21,%22,%23,%24,%25,%26,%27,%28,%29,%30,%31,"
      "%32,%33,%34,%35,%36,%37,%38,%39,%40,%41,%42,%43,%44,%45,%46,%47,"
      "%48,%49,%50,%51,%52,%53,%54,%55,%56,%57,%58,%59,%60,%61,%62,%63"
      "}, {%64,%65,%66,%67}, %68, p, 1, 1, 1;}\n"
      : "+f"(d[0]),"+f"(d[1]),"+f"(d[2]),"+f"(d[3]),"+f"(d[4]),"+f"(d[5]),"+f"(d[6]),"+f"(d[7]),
        "+f"(d[8]),"+f"(d[9]),"+f"(d[10]),"+f"(d[11]),"+f"(d[12]),"+f"(d[13]),"+f"(d[14]),"+f"(d[15]),
        "+f"(d[16]),"+f"(d[17]),"+f"(d[18]),"+f"(d[19]),"+f"(d[20]),"+f"(d[21]),"+f"(d[22]),"+f"(d[23]),
        "+f"(d[24]),"+f"(d[25]),"+f"(d[26]),"+f"(d[27]),"+f"(d[28]),"+f"(d[29]),"+f"(d[30]),"+f"(d[31]),
        "+f"(d[32]),"+f"(d[33]),"+f"(d[34]),"+f"(d[35]),"+f"(d[36]),"+f"(d[37]),"+f"(d[38]),"+f"(d[39]),
        "+f"(d[40]),"+f"(d[41]),"+f"(d[42]),"+f"(d[43]),"+f"(d[44]),"+f"(d[45]),"+f"(d[46]),"+f"(d[47]),
        "+f"(d[48]),"+f"(d[49]),"+f"(d[50]),"+f"(d[51]),"+f"(d[52]),"+f"(d[53]),"+f"(d[54]),"+f"(d[55]),
        "+f"(d[56]),"+f"(d[57]),"+f"(d[58]),"+f"(d[59]),"+f"(d[60]),"+f"(d[61]),"+f"(d[62]),"+f"(d[63])
      : "r"(a0), "r"(a1), "r"(a2), "r"(a3), "l"(db), "r"(sd));
}
__device__ __forceinline__ void wgmma_rs_n256(float (&d)[128], uint32_t a0, uint32_t a1, uint32_t a2, uint32_t a3, uint64_t db, int sd = 1) {
  asm volatile("{.reg .pred p; setp.ne.b32 p, %133, 0;\n"
      "wgmma.mma_async.sync.aligned.m64n256k16.f32.bf16.bf16 {"
      "%0,%1,%2,%3,%4,%5,%6,%7,%8,%9,%10,%11,%12,%13,%14,%15,"
      "%16,%17,%18,%19,%20,%21,%22,%23,%24,%25,%26,%27,%28,%29,%30,%31,"
      "%32,%33,%34,%35,%36,%37,%38,%39,%40,%41,%42,%43,%44,%45,%46,%47,"
      "%48,%49,%50,%51,%52,%53,%54,%55,%56,%57,%58,%59,%60,%61,%62,%63,"
      "%64,%65,%66,%67,%68,%69,%70,%71,%72,%73,%74,%75,%76,%77,%78,%79,"
      "%80,%81,%82,%83,%84,%85,%86,%87,%88,%89,%90,%91,%92,%93,%94,%95,"
      "%96,%97,%98,%99,%100,%101,%102,%103,%104,%105,%106,%107,%108,%109,%110,%111,"
      "%112,%113,%114,%115,%116,%117,%118,%119,%120,%121,%122,%123,%124,%125,%126,%127"
      "}, {%128,%129,%130,%131}, %132, p, 1, 1, 1;}\n"
      : "+f"(d[0]),"+f"(d[1]),"+f"(d[2]),"+f"(d[3]),"+f"(d[4]),"+f"(d[5]),"+f"(d[6]),"+f"(d[7]),
        "+f"(d[8]),"+f"(d[9]),"+f"(d[10]),"+f"(d[11]),"+f"(d[12]),"+f"(d[13]),"+f"(d[14]),"+f"(d[15]),
        "+f"(d[16]),"+f"(d[17]),"+f"(d[18]),"+f"(d[19]),"+f"(d[20]),"+f"(d[21]),"+f"(d[22]),"+f"(d[23]),
        "+f"(d[24]),"+f"(d[25]),"+f"(d[26]),"+f"(d[27]),"+f"(d[28]),"+f"(d[29]),"+f"(d[30]),"+f"(d[31]),
        "+f"(d[32]),"+f"(d[33]),"+f"(d[34]),"+f"(d[35]),"+f"(d[36]),"+f"(d[37]),"+f"(d[38]),"+f"(d[39]),
        "+f"(d[40]),"+f"(d[41]),"+f"(d[42]),"+f"(d[43]),"+f"(d[44]),"+f"(d[45]),"+f"(d[46]),"+f"(d[47]),
        "+f"(d[48]),"+f"(d[49]),"+f"(d[50]),"+f"(d[51]),"+f"(d[52]),"+f"(d[53]),"+f"(d[54]),"+f"(d[55]),
        "+f"(d[56]),"+f"(d[57]),"+f"(d[58]),"+f"(d[59]),"+f"(d[60]),"+f"(d[61]),"+f"(d[62]),"+f"(d[63]),
        "+f"(d[64]),"+f"(d[65]),"+f"(d[66]),"+f"(d[67]),"+f"(d[68]),"+f"(d[69]),"+f"(d[70]),"+f"(d[71]),
        "+f"(d[72]),"+f"(d[73]),"+f"(d[74]),"+f"(d[75]),"+f"(d[76]),"+f"(d[77]),"+f"(d[78]),"+f"(d[79]),
        "+f"(d[80]),"+f"(d[81]),"+f"(d[82]),"+f"(d[83]),"+f"(d[84]),"+f"(d[85]),"+f"(d[86]),"+f"(d[87]),
        "+f"(d[88]),"+f"(d[89]),"+f"(d[90]),"+f"(d[91]),"+f"(d[92]),"+f"(d[93]),"+f"(d[94]),"+f"(d[95]),
        "+f"(d[96]),"+f"(d[97]),"+f"(d[98]),"+f"(d[99]),"+f"(d[100]),"+f"(d[101]),"+f"(d[102]),"+f"(d[103]),
        "+f"(d[104]),"+f"(d[105]),"+f"(d[106]),"+f"(d[107]),"+f"(d[108]),"+f"(d[109]),"+f"(d[110]),"+f"(d[111]),
        "+f"(d[112]),"+f"(d[113]),"+f"(d[114]),"+f"(d[115]),"+f"(d[116]),"+f"(d[117]),"+f"(d[118]),"+f"(d[119]),
        "+f"(d[120]),"+f"(d[121]),"+f"(d[122]),"+f"(d[123]),"+f"(d[124]),"+f"(d[125]),"+f"(d[126]),"+f"(d[127])
      : "r"(a0), "r"(a1), "r"(a2), "r"(a3), "l"(db), "r"(sd));
}
__device__ __forceinline__ void wgmma_rs_n192(float (&d)[96], uint32_t a0, uint32_t a1, uint32_t a2, uint32_t a3, uint64_t db) {
  asm volatile("wgmma.mma_async.sync.aligned.m64n192k16.f32.bf16.bf16 {"
      "%0,%1,%2,%3,%4,%5,%6,%7,%8,%9,%10,%11,%12,%13,%14,%15,"
      "%16,%17,%18,%19,%20,%21,%22,%23,%24,%25,%26,%27,%28,%29,%30,%31,"
      "%32,%33,%34,%35,%36,%37,%38,%39,%40,%41,%42,%43,%44,%45,%46,%47,"
      "%48,%49,%50,%51,%52,%53,%54,%55,%56,%57,%58,%59,%60,%61,%62,%63,"
      "%64,%65,%66,%67,%68,%69,%70,%71,%72,%73,%74,%75,%76,%77,%78,%79,"
      "%80,%81,%82,%83,%84,%85,%86,%87,%88,%89,%90,%91,%92,%93,%94,%95"
      "}, {%96,%97,%98,%99}, %100, 1, 1, 1, 1;\n"
      : "+f"(d[0]),"+f"(d[1]),"+f"(d[2]),"+f"(d[3]),"+f"(d[4]),"+f"(d[5]),"+f"(d[6]),"+f"(d[7]),
        "+f"(d[8]),"+f"(d[9]),"+f"(d[10]),"+f"(d[11]),"+f"(d[12]),"+f"(d[13]),"+f"(d[14]),"+f"(d[15]),
        "+f"(d[16]),"+f"(d[17]),"+f"(d[18]),"+f"(d[19]),"+f"(d[20]),"+f"(d[21]),"+f"(d[22]),"+f"(d[23]),
        "+f"(d[24]),"+f"(d[25]),"+f"(d[26]),"+f"(d[27]),"+f"(d[28]),"+f"(d[29]),"+f"(d[30]),"+f"(d[31]),
        "+f"(d[32]),"+f"(d[33]),"+f"(d[34]),"+f"(d[35]),"+f"(d[36]),"+f"(d[37]),"+f"(d[38]),"+f"(d[39]),
        "+f"(d[40]),"+f"(d[41]),"+f"(d[42]),"+f"(d[43]),"+f"(d[44]),"+f"(d[45]),"+f"(d[46]),"+f"(d[47]),
        "+f"(d[48]),"+f"(d[49]),"+f"(d[50]),"+f"(d[51]),"+f"(d[52]),"+f"(d[53]),"+f"(d[54]),"+f"(d[55]),
        "+f"(d[56]),"+f"(d[57]),"+f"(d[58]),"+f"(d[59]),"+f"(d[60]),"+f"(d[61]),"+f"(d[62]),"+f"(d[63]),
        "+f"(d[64]),"+f"(d[65]),"+f"(d[66]),"+f"(d[67]),"+f"(d[68]),"+f"(d[69]),"+f"(d[70]),"+f"(d[71]),
        "+f"(d[72]),"+f"(d[73]),"+f"(d[74]),"+f"(d[75]),"+f"(d[76]),"+f"(d[77]),"+f"(d[78]),"+f"(d[79]),
        "+f"(d[80]),"+f"(d[81]),"+f"(d[82]),"+f"(d[83]),"+f"(d[84]),"+f"(d[85]),"+f"(d[86]),"+f"(d[87]),
        "+f"(d[88]),"+f"(d[89]),"+f"(d[90]),"+f"(d[91]),"+f"(d[92]),"+f"(d[93]),"+f"(d[94]),"+f"(d[95])
      : "r"(a0), "r"(a1), "r"(a2), "r"(a3), "l"(db));
}


constexpr int C_LN = 0, C_PX = 16, C_PY = 32;
constexpr int NB_CONS = 1, NB_LN = 2, NB_LAG = 4, NB_INIT = 6, NB_RDY = 7;
constexpr int LAGX = 3;
constexpr int LAGY = 6;
constexpr int LAG2 = 5;
constexpr int NLL = 4;
constexpr int POLL_DELAY = 1150;
constexpr int POLL_DELAY2 = 1000;
constexpr int POLL_DELAY3 = 600;
constexpr int FILT_DELAY = 600;
constexpr int WARM = 4;
constexpr int ALEAD = 8;
constexpr int XTRIG = 20;
constexpr int HTRIG = 0;
constexpr int SM_E = 0, SM_X = 16384, SM_E2 = 32768, SM_W = 49152, SM_FC = 69632, SM_T = 73728 - T1_BYTES;
constexpr unsigned long long KORDER = 0xBA9432DC876510ull;
constexpr unsigned long long BSLOT = 0xA9854210DA9854ull, PSLOT = 0xB763CB763CB763ull;
constexpr unsigned long long BDEP = 0xFFEC97631ull, PDEP = 0xBA754ull;
constexpr uint32_t HI128 = desc_hi(1024, 1), HI64 = desc_hi(512, 2);

struct Bars {
  uint64_t full1[32], empty1[32], full2[16], fullA[8], empty2[8], emptyP[9], sig[2], done, fullP[32], hbar, tbar, hint[3], sbar;
  uint32_t epoch, pad;
};

template <int NK, bool STORE, int J0 = 0, int J1 = NK>
__device__ __forceinline__ void make_p(const float (&acc)[NK * 16], float r0, float r1, uint4 (&p)[NK], uint4* pbase, int ks0, uint32_t tag) {
#pragma unroll
  for (int j = J0; j < J1; j++) {
    uint32_t w[4];
#pragma unroll
    for (int i = 0; i < 4; i++) {
      const int a = 8 * j + 2 * i, b = a + NK * 8;
      w[i] = pack2(swiglu(acc[a], acc[b], (i & 1) ? r1 : r0), swiglu(acc[a + 1], acc[b + 1], (i & 1) ? r1 : r0));
    }
    asm volatile("" : "+r"(w[0]), "+r"(w[1]), "+r"(w[2]), "+r"(w[3]));
    p[j] = make_uint4(w[0], w[1], w[2], w[3]);
    if (STORE) st_tag(pbase + ((ks0 + j) >> 2) * 1024 + ((ks0 + j) & 3) * 32, p[j], tag);
  }
}
__device__ __forceinline__ void spin_until(uint32_t t) {
  while ((int)(clock32() - t) < 0) {}
}

__global__ void __cluster_dims__(2, 1, 1) __launch_bounds__(NTHREADS, 1)
fused_kernel(const __nv_bfloat16* __restrict__ x, const Tables* __restrict__ tab, Scratch* __restrict__ scr,
             __nv_bfloat16* __restrict__ out, const char* __restrict__ wg_raw, const char* __restrict__ wu_raw,
             const char* __restrict__ wd_raw,
             const __grid_constant__ CUtensorMap tmWR, const __grid_constant__ CUtensorMap tmWI,
             const __grid_constant__ CUtensorMap tmGX, const __grid_constant__ CUtensorMap tmUX,
             const __grid_constant__ CUtensorMap tmGY, const __grid_constant__ CUtensorMap tmUY,
             const __grid_constant__ CUtensorMap tmD) {
  extern __shared__ __align__(1024) char smem_raw[];
  const uint32_t sbase = s2u(smem_raw);
  const uint32_t sbar = sbase + 14 * SLOT, sstat = sbar + 1408;
  const int tid = threadIdx.x, lane = tid & 31;
  const int c = blockIdx.x, rk = c & 1, f = (c >> 1) & 7, rb = 2 * (c >> 4) + rk;
  const int rb2 = 2 * (c >> 4) + (f >> 2), kh = (f >> 1) & 1, nq = 2 * (f & 1) + rk;
#define BAR(field, i) (sbar + (uint32_t)offsetof(Bars, field) + 8u * (i))
#define TOFF(field) (sbase + SM_T + (uint32_t)offsetof(Tables, field) + lane * 16)

  if (tid >= 256) {
    asm volatile("setmaxnreg.dec.sync.aligned.u32 40;");
    const int warp = __shfl_sync(0xffffffffu, tid >> 5, 0);
    if (lane == 0) {
      auto init = [&](uint32_t b, int n, int count, int bytes) {
#pragma unroll
        for (int i = 0; i < n; i++) mbar_init(b + 8 * i, count);
#pragma unroll
        for (int i = 0; i < (bytes ? n : 0); i++) mbar_expect(b + 8 * i, bytes);
      };
      if (warp == 8) {
        if (sbase & 1023) die();
        init(BAR(tbar, 0), 1, 1, T2_BYTES + 2 * 10240);
        init(BAR(hbar, 0), 1, 1, 16384);
        init(BAR(hint, 0), 3, 1, 0);
        init(BAR(sbar, 0), 1, 32, 0);
        init(BAR(empty2, 0), 20, 8, 0);
      } else if (warp == 9) {
        init(BAR(full1, 0), 16, 1, 16384);
        init(BAR(full1, 16), 16, 1, 12288);
      } else if (warp == 10) {
        init(BAR(fullP, 0), 30, 1, 8192);
      } else {
        init(BAR(full2, 0), 24, 1, 16384);
        init(BAR(empty1, 0), 32, 16, 0);
      }
      asm volatile("fence.mbarrier_init.release.cluster;" ::: "memory");
    }
    if (tid == 256) {
      const int w0 = ((c >> 3) * 257 + 32 * (c & 7) + 1) & ~7;
      asm volatile("prefetch.tensormap [%0];" ::"l"(&tmWR) : "memory");
      asm volatile("prefetch.tensormap [%0];" ::"l"(&tmWI) : "memory");
      spin_until(clock32() + FILT_DELAY);
      tma3(sbase + SM_W, &tmWR, BAR(tbar, 0), w0, 0, 0);
      tma3(sbase + SM_W + 10240, &tmWI, BAR(tbar, 0), w0, 0, 0);
      bulk_load(sbase + SM_T + T1_BYTES, reinterpret_cast<const char*>(tab) + T1_BYTES, T2_BYTES, BAR(tbar, 0));
    }
    if (tid == 288) {
      asm volatile("prefetch.tensormap [%0];" ::"l"(rk ? &tmUX : &tmGX) : "memory");
      asm volatile("prefetch.tensormap [%0];" ::"l"(rk ? &tmUY : &tmGY) : "memory");
      asm volatile("prefetch.tensormap [%0];" ::"l"(&tmD) : "memory");
    }
    if (tid == 320) {
      const unsigned e = ld_relaxed(&scr->cnt[(C_LN + rb) * 32]) >> 3;
      asm volatile("st.shared.u32 [%0], %1;" ::"r"(BAR(epoch, 0)), "r"(e) : "memory");
    }
    __syncwarp();
    asm volatile("barrier.cluster.arrive.relaxed.aligned;" ::: "memory");
    bar_arrive(NB_RDY, 384);
    asm volatile("barrier.cluster.wait.aligned;" ::: "memory");
    bar_sync(NB_INIT, 384);
    unsigned epoch;
    asm volatile("ld.shared.u32 %0, [%1];" : "=r"(epoch) : "r"(BAR(epoch, 0)) : "memory");
    if (warp == 8) {
      if (lane == 0) {
        const int ax = (7 * f + 3 * (f & 1)) >> 1;
        const int ay = 7 * f + ((f & 1) ? 0 : 4);
        const CUtensorMap* tx = rk ? &tmUX : &tmGX;
        const CUtensorMap* ty = rk ? &tmUY : &tmGY;
        mbar_wait_bounded(BAR(sig, 0));
        uint32_t s = 2;
#pragma unroll 1
        for (int n = 0; n < 16; n++) {
          if (n >= 6) mbar_wait_bounded(BAR(empty1, n - 6));
          tma3_mc(sbase + (8 + s) * SLOT + rk * 8192, tx, BAR(full1, n), n * 32, ax);
          if (++s == 6) s = 0;
          if (n >= 10 && n < 15) {
            const int k = n - 10;
            tma3_mc(sbase + k * 12288 + rk * 6144, ty, BAR(full1, 16 + k), (k + 8) * 32, ay);
          }
        }
#pragma unroll 1
        for (int k = 5; k < 16; k++) {
          mbar_wait_bounded(BAR(empty1, k < 13 ? 10 + ((12 * (k - 5) + 11) >> 4) : 3 + k));
          tma3_mc(sbase + (k < 13 ? 8 * SLOT + (k - 5) * 12288 : (k - 13) * 12288) + rk * 6144, ty, BAR(full1, 16 + k), ((k + 8) & 15) * 32, ay);
        }
        mbar_wait_bounded(BAR(done, 0));
      }
    } else if (warp == 9) {
      if (lane == 0) {
        mbar_wait(BAR(fullA, 4));
        wait_counter(&scr->cnt[(C_LN + rb2) * 32], (epoch + 1) * 8);
        asm volatile("fence.proxy.async.global;" ::: "memory");
#pragma unroll 1
        for (int i = 0; i < 14; i++) {
          const int kblk = 14 * kh + (int)((KORDER >> (4 * i)) & 15);
          mbar_wait(i < 9 ? BAR(empty1, 16 + (uint32_t)((BDEP >> (4 * i)) & 15)) : BAR(empty2, i - 9));
          tma3(sbase + (uint32_t)((BSLOT >> (4 * i)) & 15) * SLOT, &tmD, BAR(full2, i), 0, 64 * kblk, 2 * nq);
        }
        mbar_wait(BAR(empty2, 5));
        bulk_load(sbase + 13 * SLOT, &scr->LN[(rb2 * 8 + 2 * nq) * 1024 + kh * 512], 8192, BAR(hbar, 0));
        bulk_load(sbase + 13 * SLOT + 8192, &scr->LN[(rb2 * 8 + 2 * nq + 1) * 1024 + kh * 512], 8192, BAR(hbar, 0));
      }
    } else if (warp == 10) {
      bar_sync(NB_LN, 288);
      if (lane == 0) {
        red_release(&scr->cnt[(C_LN + rb) * 32]);
        wait_counter(&scr->cnt[(C_LN + rb) * 32], (epoch + 1) * 8);
        asm volatile("fence.proxy.async.global;" ::: "memory");
#pragma unroll 1
        for (int kb = NLL; kb < 8; kb++) {
          if (2 * kb >= ALEAD) mbar_wait(BAR(empty1, 2 * kb - ALEAD));
          bulk_load(sbase + kb * SLOT, &scr->LN[(rb * 8 + kb) * 1024], 16384, BAR(fullA, kb));
        }
#pragma unroll 1
        for (int s = 0; s < 14; s++) {
          const int kblk = 14 * kh + (int)((KORDER >> (4 * s)) & 15);
          if (s == 0 || s == 8 || s == 11) {
            mbar_wait(BAR(hint, s == 0 ? 0 : s == 8 ? 1 : 2));
          }
          mbar_wait(s < 5 ? BAR(empty1, 16 + (uint32_t)((PDEP >> (4 * s)) & 15)) : BAR(emptyP, s - 5));
          bulk_load_mc(sbase + (uint32_t)((PSLOT >> (4 * s)) & 15) * SLOT + rk * 8192, &scr->P[(rb2 * 28 + kblk) * 1024 + rk * 512], 8192, BAR(fullP, 16 * rk + s));
        }
      }
    } else {
      if (lane == 0) {
        mbar_wait(BAR(sig, 1));
        l2_prefetch(wg_raw + (size_t)c * 5376, 5376);
        l2_prefetch(wu_raw + (size_t)c * 5376, 5376);
        mbar_wait(BAR(sig, 0));
        l2_prefetch(wg_raw + 688128 + (size_t)c * 8960, 8960);
        l2_prefetch(wu_raw + 688128 + (size_t)c * 8960, 8960);
      }
      mbar_wait(BAR(fullA, 4));
      if (lane == 0) l2_prefetch(wd_raw + (size_t)c * 14336, 14336);
      {
        const uint32_t tag = (epoch + 1) & 1;
        uint4 v0, v1, v2;
        while (true) {
          v0 = ld_b128(&scr->ST[rb * 64 + lane]);
          v1 = ld_b128(&scr->ST[rb * 64 + 32 + lane]);
          v2 = ld_b128(&scr->ST[rb2 * 64 + 32 * kh + lane]);
          if (!__any_sync(0xffffffffu, ((v0.x ^ tag) | (v1.x ^ tag) | (v2.x ^ tag)) & 1u)) break;
        }
        sts4(sstat + lane * 16, v0.x & ~1u, v0.y, v0.z, v0.w);
        sts4(sstat + 512 + lane * 16, v1.x & ~1u, v1.y, v1.z, v1.w);
        sts4(sstat + 1024 + lane * 16, v2.x & ~1u, v2.y, v2.z, v2.w);
        mbar_arrive(BAR(sbar, 0));
      }
      if (lane == 0) {
        mbar_wait(BAR(empty1, XTRIG));
        while ((int)(ld_relaxed(&scr->cnt[(C_PX + rb2) * 32 + kh]) - (epoch + 1) * 32) < 0) {
        }
        mbar_arrive(BAR(hint, 0));
        mbar_wait(BAR(emptyP, HTRIG));
        uint32_t done = 0;
        while (done != 3) {
          uint2 v;
          asm volatile("ld.relaxed.gpu.global.v2.u32 {%0,%1}, [%2];" : "=r"(v.x), "=r"(v.y) : "l"(&scr->cnt[(C_PY + rb2) * 32 + 4 * (rk ^ kh ^ 1) + 2 * kh]) : "memory");
          if (!(done & 1) && (int)(v.x - (epoch + 1) * 8) >= 0) { done |= 1; mbar_arrive(BAR(hint, 1)); }
          if (!(done & 2) && (int)(v.y - (epoch + 1) * 8) >= 0) { done |= 2; mbar_arrive(BAR(hint, 2)); }
        }
      }
    }
  } else {
    const int warp = __shfl_sync(0xffffffffu, tid >> 5, 0);
    const int g = lane >> 2, t = lane & 3;
    uint4 fa[4], fb[4], tw[6];
#pragma unroll
    for (int i = 0; i < 4; i++) fa[i] = ldg_ca4(&tab->fa[i][lane][0]);
#pragma unroll
    for (int i = 0; i < 6; i++) tw[i] = ldg_ca4(&tab->tw1[i][lane][0]);
#pragma unroll
    for (int i = 0; i < 4; i++) fb[i] = ldg_ca4(&tab->fb[i][lane][0]);
#pragma unroll
    for (int i = 0; i < 4; i++) {
      const int r = i >> 1, ch = (i & 1) * 32 + lane;
      cp_async16(sbase + SM_X + (2 * warp + r) * 1024 + ((ch ^ ((ch >> 3) & 1)) * 16),
                 x + (size_t)(c + 128 * (2 * warp + r)) * 512 + ch * 8);
    }
    asm volatile("cp.async.commit_group;" ::: "memory");
    asm volatile("barrier.cluster.arrive.relaxed.aligned;" ::: "memory");
    uint32_t rbar;
    asm volatile("mapa.shared::cluster.u32 %0, %1, %2;" : "=r"(rbar) : "r"(sbar), "r"(rk ^ 1));
#define RBAR(field, i) (rbar + (uint32_t)offsetof(Bars, field) + 8u * (i))
    {
      const int ln = (tid >> 1) & 31, lg = ln >> 2, lt = ln & 3, i = 4 * (tid >> 6) + 2 * (tid & 1);
      const int kidx = lt + 8 * (i >> 3), nidx = 4 * ((i >> 1) & 3) + (lg >> 1);
      const uint32_t a0 = cfrag<2048>((c + 128 * kidx) * nidx, lg & 1), a1 = cfrag<2048>((c + 128 * (kidx + 4)) * nidx, lg & 1);
      const uint32_t b0 = cfrag<2048>(-(c + 128 * nidx) * kidx, lg & 1), b1 = cfrag<2048>(-(c + 128 * nidx) * (kidx + 4), lg & 1);
      asm volatile("st.shared.v2.u32 [%0], {%1,%2};" ::"r"(sbase + SM_FC + tid * 8), "r"(a0), "r"(a1) : "memory");
      asm volatile("st.shared.v2.u32 [%0], {%1,%2};" ::"r"(sbase + SM_FC + 2048 + tid * 8), "r"(b0), "r"(b1) : "memory");
    }
    bar_sync(NB_CONS, 256);
    uint4 fc[4];
#pragma unroll
    for (int i = 0; i < 4; i++) fc[i] = lds4(sbase + SM_FC + i * 512 + lane * 16);
    asm volatile("cp.async.wait_group 0;" ::: "memory");
    __syncwarp();
    bar_arrive(NB_INIT, 384);
    uint32_t tag, ones;
    uint4 q[4], o[4];
    {
      uint32_t v[2][8];
#pragma unroll
      for (int r = 0; r < 2; r++)
#pragma unroll
        for (int ks = 0; ks < 2; ks++) {
          const int ch = 32 * ks + 2 * (lane & 15) + (lane >> 4);
          asm volatile("ldmatrix.sync.aligned.m8n8.x4.trans.shared.b16 {%0,%1,%2,%3}, [%4];"
                       : "=r"(v[r][4 * ks]), "=r"(v[r][4 * ks + 1]), "=r"(v[r][4 * ks + 2]), "=r"(v[r][4 * ks + 3])
                       : "r"(sbase + SM_X + (2 * warp + r) * 1024 + ((ch ^ ((ch >> 3) & 1)) * 16)) : "memory");
        }
      float sq[2];
#pragma unroll
      for (int r = 0; r < 2; r++) {
        float s0 = 0.f, s1 = 0.f;
#pragma unroll
        for (int i = 0; i < 8; i++) {
          const float lo = bf_lo(v[r][i]), hi = u2f(v[r][i] & 0xffff0000u);
          s0 = fmaf(lo, lo, s0);
          s1 = fmaf(hi, hi, s1);
        }
        sq[r] = s0 + s1;
      }
      {
        float w = ((lane & 1) ? sq[1] : sq[0]) + __shfl_xor_sync(0xffffffffu, (lane & 1) ? sq[0] : sq[1], 1);
        w += __shfl_xor_sync(0xffffffffu, w, 2);
        w = sum_groups(w);
        const float o2 = __shfl_xor_sync(0xffffffffu, w, 1);
        sq[0] = (lane & 1) ? o2 : w;
        sq[1] = (lane & 1) ? w : o2;
      }
#pragma unroll
      for (int r = 0; r < 2; r++) {
        float dd[2][4], ee[2][4];
#pragma unroll
        for (int nt = 0; nt < 2; nt++) {
          mma_az(dd[nt], fa[0], v[r][2 * nt], v[r][2 * nt + 1]);
          mma_a(dd[nt], fa[1], v[r][4 + 2 * nt], v[r][5 + 2 * nt]);
          mma_az(ee[nt], fa[2], v[r][2 * nt], v[r][2 * nt + 1]);
          mma_a(ee[nt], fa[3], v[r][4 + 2 * nt], v[r][5 + 2 * nt]);
        }
        float mean = (dd[0][0] + dd[0][1]) + (dd[1][0] + dd[1][1]);
        mean += __shfl_xor_sync(0xffffffffu, mean, 1);
        mean += __shfl_xor_sync(0xffffffffu, mean, 2);
        mean = __shfl_sync(0xffffffffu, mean, 0) * (1.f / 512.f);
        const float rs = rsqrtf(fmaxf(fmaf(-mean, mean, sq[r] * (1.f / 512.f)), 0.f) + 1e-5f);
        float acc[4][4];
#pragma unroll
        for (int nt = 0; nt < 2; nt++) {
          const float (&d)[4] = dd[nt];
          const float (&e)[4] = ee[nt];
          const uint4 &ka = tw[2 * nt], &kb = tw[2 * nt + 1], &kc = tw[4 + nt];
          const uint32_t a0 = pack2(d[0] * u2f(ka.x) + d[2] * u2f(ka.y), d[1] * u2f(kb.x) + d[3] * u2f(kb.y));
          const uint32_t a2 = pack2(d[0] * u2f(ka.z) + d[2] * u2f(ka.w), d[1] * u2f(kb.z) + d[3] * u2f(kb.w));
          const uint32_t a1 = pack2(e[0] * u2f(kc.x) + e[2] * u2f(kc.y), e[1] * u2f(kc.z) + e[3] * u2f(kc.w));
          const uint32_t a3 = pack2(e[2] * u2f(kc.x) - e[0] * u2f(kc.y), e[3] * u2f(kc.z) - e[1] * u2f(kc.w));
          const uint32_t dc = pack2(fmaf(mean, -32.f, d[0]), fmaf(mean, -32.f, d[1]));
          const uint32_t h0 = g == 0 ? dc : a0, h2 = g == 0 ? 0u : a2;
          if (nt == 0) {
            mma16816_z(acc[0], a0, a1, a2, a3, fb[2 * nt].x, fb[2 * nt].y);
            mma16816_z(acc[1], a0, a1, a2, a3, fb[2 * nt].z, fb[2 * nt].w);
            mma16816_z(acc[2], h0, a1, h2, a3, fb[2 * nt + 1].x, fb[2 * nt + 1].y);
            mma16816_z(acc[3], h0, a1, h2, a3, fb[2 * nt + 1].z, fb[2 * nt + 1].w);
          } else {
            mma16816(acc[0], a0, a1, a2, a3, fb[2 * nt].x, fb[2 * nt].y);
            mma16816(acc[1], a0, a1, a2, a3, fb[2 * nt].z, fb[2 * nt].w);
            mma16816(acc[2], h0, a1, h2, a3, fb[2 * nt + 1].x, fb[2 * nt + 1].y);
            mma16816(acc[3], h0, a1, h2, a3, fb[2 * nt + 1].z, fb[2 * nt + 1].w);
          }
        }
#pragma unroll
        for (int h = 0; h < 2; h++) {
          const int j = 2 * warp + r, m = 2 * t + h;
          sts4(sbase + SM_E + ((j * 8 + m) * 8 + (g ^ (2 * t) ^ (2 * (j & 3)))) * 16,
               pack2(acc[h][0] * rs, acc[h][1] * rs), pack2(acc[h][2] * rs, acc[h][3] * rs),
               pack2(acc[2 + h][0] * rs, acc[2 + h][1] * rs), pack2(acc[2 + h][2] * rs, acc[2 + h][3] * rs));
        }
      }
      bar_sync(NB_RDY, 384);
      const uint32_t ea = sbase + SM_E + ((t * 8 + warp) * 8 + (g ^ (warp & 6) ^ (2 * t))) * 16;
      lds_frag(q[0], q[1], ea, ea + 4096);
      lds_frag(q[2], q[3], ea + 8192, ea + 12288);
      asm volatile("ld.shared.u32 %0, [%1];" : "=r"(tag) : "r"(BAR(epoch, 0)) : "memory");
      ones = ~(tag >> 31);
      tag = (tag + 1) & 1;
      cdft16(q, fc, o);
#pragma unroll
      for (int vv = 0; vv < 4; vv++) {
        o[vv].y &= ~1u;
        o[vv].z = (o[vv].z & ~1u) | (tag ^ 1);
        st_tag(&scr->Z1[(((4 * vv + t) * 8 + warp) * 128 + c) * 8 + g], o[vv], tag);
      }
    }
    asm volatile("setmaxnreg.inc.sync.aligned.u32 232;");
    {
      uint4* const zp = &scr->Z1[(c * 128 + 8 * t + warp) * 8 + g];
      const uint32_t tst = clock32();
      mbar_wait(BAR(tbar, 0));
      uint4 f2[4], g2[4];
#pragma unroll
      for (int i = 0; i < 4; i++) {
        f2[i] = lds4(TOFF(f2) + warp * 2048 + i * 512);
        g2[i] = lds4(TOFF(g2) + warp * 2048 + i * 512);
      }
      const uint4 f8 = lds4(TOFF(f8)), g8 = lds4(TOFF(g8));
      asm volatile("barrier.cluster.wait.aligned;" ::: "memory");
      spin_until(tst + POLL_DELAY);
      ld_tag4_issue<256>(q, zp);
      float wfr[16], wfi[16];
      {
        const float nyq = ((c & 7) == 7 && g == 0) ? 0.5f : 1.f;
        uint32_t wa = sbase + SM_W + (16 * warp + t) * 80 + ((2 * (c >> 3) + 2) & 15) - 2;
        asm volatile("" : "+r"(wa));
        const uint32_t wb[3] = {wa + 2 * (g == 0 ? 16 : g), wa + 2 * g, wa - 2 * g};
#pragma unroll
        for (int i = 0; i < 16; i++) {
          const int ci = i >> 3, dd = (i >> 2) & 1, e = i & 3;
          const uint32_t a = wb[e < 2 ? e : 2] + (ci * 8 + 4 * dd) * 80 + (e == 0 ? 0 : e == 1 ? 16 : e == 2 ? 64 : 48);
          wfr[i] = bf_lo(lds_u16(a)) * (e == 2 ? nyq : 1.f);
          wfi[i] = bf_lo(lds_u16(a + 10240)) * (e == 2 ? nyq : 1.f);
        }
      }
      ld_tag4_finish<256>(q, zp, tag);
      if (lane == 0) mbar_arrive(BAR(sig, 1));
#pragma unroll
      for (int i = 0; i < 4; i++) q[i].z &= ~1u;
      reg_frag(q, ones);
      cdft16(q, f2, o);
      const uint32_t e2 = sbase + SM_E2;
#pragma unroll
      for (int vv = 0; vv < 4; vv++)
        sts4(e2 + ((warp * 16 + 4 * vv + t) * 8 + (g ^ (2 * t) ^ (2 * (warp & 3)))) * 16, o[vv].x, o[vv].y, o[vv].z, o[vv].w);
      bar_sync(NB_CONS, 256);
      uint32_t ad[2], res[2][2][4];
#pragma unroll
      for (int ci = 0; ci < 2; ci++) {
        const int cc = 2 * warp + ci;
        ad[ci] = e2 + ((t * 16 + cc) * 8 + (g ^ (2 * (cc & 3)) ^ (2 * t))) * 16;
        lds_frag(q[2 * ci], q[2 * ci + 1], ad[ci], ad[ci] + 8192);
      }
#pragma unroll
      for (int ci = 0; ci < 2; ci++)
#pragma unroll
        for (int p = 0; p < 2; p++) {
          uint32_t y[2][2];
#pragma unroll
          for (int vv = 0; vv < 2; vv++) {
            float d[4];
            mma_az(d, q[2 * ci + p], word(f8, 2 * vv), word(f8, 2 * vv + 1));
#pragma unroll
            for (int rr = 0; rr < 2; rr++) {
              const float fr = wfr[ci * 8 + vv * 4 + 2 * p + rr], fi = wfi[ci * 8 + vv * 4 + 2 * p + rr];
              y[vv][rr] = pack2(d[2 * rr] * fr - d[2 * rr + 1] * fi, d[2 * rr] * fi + d[2 * rr + 1] * fr);
            }
          }
#pragma unroll
          for (int vv = 0; vv < 2; vv++) {
            float d[4];
            mma16816_z(d, y[0][0], y[0][1], y[1][0], y[1][1], word(g8, 2 * vv), word(g8, 2 * vv + 1));
            res[ci][vv][2 * p] = pack2(d[0], d[1]);
            res[ci][vv][2 * p + 1] = pack2(d[2], d[3]);
          }
        }
#pragma unroll
      for (int i = 0; i < 4; i++)
        sts4(ad[i >> 1] + (i & 1) * 8192, res[i >> 1][i & 1][0], res[i >> 1][i & 1][1], res[i >> 1][i & 1][2], res[i >> 1][i & 1][3]);
      bar_sync(NB_CONS, 256);
      const uint32_t eb = e2 + ((warp * 16 + t) * 8 + (g ^ (2 * t) ^ (2 * (warp & 3)))) * 16;
      lds_frag(q[0], q[1], eb, eb + 512);
      lds_frag(q[2], q[3], eb + 1024, eb + 1536);
      cdft16(q, g2, o);
#pragma unroll
      for (int vv = 0; vv < 4; vv++) {
        o[vv].y &= ~1u;
        o[vv].z = (o[vv].z & ~1u) | tag;
        st_tag(zp + vv * 256, o[vv], tag);
      }
    }
    {
      const uint4* const zp = &scr->Z1[((t * 8 + warp) * 128 + c) * 8 + g];
      const uint32_t tst = clock32();
      uint4 gb[4], ga[4], gc[4], tw[4];
      uint2 xr[2][4];
      uint2* lnp[2];
#pragma unroll
      for (int r = 0; r < 2; r++) {
        const int row = 16 * f + 2 * warp + r;
        lnp[r] = reinterpret_cast<uint2*>(&scr->LN[(rb * 8 + (g >> 2)) * 1024 + row * 8 + ((2 * (g & 3) + (t >> 1)) ^ (row & 7))]) + (t & 1);
        asm volatile("" : "+l"(lnp[r]));
      }
#pragma unroll
      for (int i = 0; i < 4; i++) {
        gc[i] = lds4(sbase + SM_FC + 2048 + i * 512 + lane * 16);
        gb[i] = lds4(TOFF(gb) + i * 512);
        ga[i] = lds4(TOFF(ga) + i * 512);
        tw[i] = lds4(TOFF(tw3) + i * 512);
        const int ch = 2 * (g + 8 * i) + (t >> 1);
#pragma unroll
        for (int r = 0; r < 2; r++) xr[r][i] = lds2(sbase + SM_X + (2 * warp + r) * 1024 + ((ch ^ ((ch >> 3) & 1)) * 16) + (t & 1) * 8);
      }
      spin_until(tst + POLL_DELAY2);
      ld_tag4_issue<32768>(q, zp);
      ld_tag4_finish<32768, true>(q, zp, tag);
      if (lane == 0) mbar_arrive(BAR(sig, 0));
      reg_frag(q, ones);
      cdft16(q, gc, o);
#pragma unroll
      for (int vv = 0; vv < 4; vv++)
        sts4(sbase + SM_E + (((4 * vv + t) * 8 + warp) * 8 + (g ^ (warp & 6) ^ (2 * t))) * 16, o[vv].x, o[vv].y, o[vv].z, o[vv].w);
      bar_sync(NB_CONS, 256);
      uint32_t hv[2][8];
      const float mk = t == 0 ? 0.f : 1.f;
#pragma unroll
      for (int r = 0; r < 2; r++) {
        const int j = 2 * warp + r;
        uint4 u[2];
#pragma unroll
        for (int h = 0; h < 2; h++) u[h] = lds4(sbase + SM_E + ((j * 8 + 2 * t + h) * 8 + (g ^ (2 * t) ^ (2 * (j & 3)))) * 16);
        const uint32_t bp[4][2] = {{u[0].x, u[1].x & ones}, {u[0].y & ones, u[1].y}, {u[0].z, u[1].z & ones}, {u[0].w & ones, u[1].w}};
        float y[2][2][4];
#pragma unroll
        for (int i = 0; i < 2; i++) {
          float lo[4], hi[4], e[4];
          mma_az(lo, gb[2 * i], bp[0][0], bp[0][1]);
          mma_az(hi, gb[2 * i + 1], bp[2][0], bp[2][1]);
          mma_az(e, gb[2 * i], bp[1][0], bp[1][1]);
          mma_a(e, gb[2 * i + 1], bp[3][0], bp[3][1]);
          const uint4 &ka = tw[2 * i], &kb = tw[2 * i + 1];
          const float tr0 = fmaf(hi[0], mk, lo[0]), ti0 = fmaf(hi[2], mk, lo[2]);
          const float tr1 = lo[1] + hi[1], ti1 = lo[3] + hi[3];
          const float vr0 = tr0 * u2f(ka.x) - ti0 * u2f(ka.y), vi0 = tr0 * u2f(ka.y) + ti0 * u2f(ka.x);
          const float vr1 = tr1 * u2f(ka.z) - ti1 * u2f(ka.w), vi1 = tr1 * u2f(ka.w) + ti1 * u2f(ka.z);
          const uint32_t b0 = pack2(t == 0 ? hi[0] : vr0, vr1), b1 = pack2(t == 0 ? vr0 : vi0, vi1);
          const uint32_t b2 = pack2(e[0] * u2f(kb.x) - e[2] * u2f(kb.y), e[1] * u2f(kb.z) - e[3] * u2f(kb.w));
          const uint32_t b3 = pack2(e[0] * u2f(kb.y) + e[2] * u2f(kb.x), e[1] * u2f(kb.w) + e[3] * u2f(kb.z));
#pragma unroll
          for (int mt = 0; mt < 2; mt++) {
            mma_az(y[mt][i], ga[2 * mt], b0, b1);
            mma_a(y[mt][i], ga[2 * mt + 1], b2, b3);
          }
        }
#pragma unroll
        for (int i = 0; i < 4; i++) {
          hv[r][2 * i] = hadd2_bf16(xr[r][i].x, pack2(y[i >> 1][0][2 * (i & 1)], y[i >> 1][0][2 * (i & 1) + 1]));
          hv[r][2 * i + 1] = hadd2_bf16(xr[r][i].y, pack2(y[i >> 1][1][2 * (i & 1)], y[i >> 1][1][2 * (i & 1) + 1]));
        }
      }
      uint32_t mb[2], ml[2];
#pragma unroll
      for (int r = 0; r < 2; r++) {
        const float mean = sum_groups(quad_sum(hv[r])) * (1.f / 512.f);
        mb[r] = pack2(mean, mean);
        ml[r] = pack2(mean - bf_lo(mb[r]), mean - bf_lo(mb[r])) & 0xfffefffeu;
      }
#pragma unroll
      for (int i = 0; i < 4; i++)
#pragma unroll
        for (int r = 0; r < 2; r++) {
          hv[r][2 * i] = hsub2_bf16(hsub2_bf16(hv[r][2 * i], mb[r]), ml[r]);
          hv[r][2 * i + 1] = hsub2_bf16(hsub2_bf16(hv[r][2 * i + 1], mb[r]), ml[r]);
          st_tag8(lnp[r] + i * 4096, hv[r][2 * i], hv[r][2 * i + 1], i < 2 ? tag : (hv[r][2 * i] & 1u));
        }
      bar_arrive(NB_LN, 288);
      const uint32_t ones2 = ~(lds2(BAR(epoch, 0)).x >> 31);
      float rstd[2];
#pragma unroll
      for (int r = 0; r < 2; r++) {
        hv[r][0] &= ones2;
        rstd[r] = row_rstd(hv[r]);
      }
      if (lane == 0)
        st_tag(&scr->ST[rb * 64 + 8 * f + warp], make_uint4(__byte_perm(ml[0], mb[0], 0x5410), __float_as_uint(rstd[0]), __byte_perm(ml[1], mb[1], 0x5410), __float_as_uint(rstd[1])), tag);
    }
    const int wgi = warp >> 2, wq = warp & 3;
    const int wr = wgi ^ (f >> 2) ^ 1, rt = 4 * wr + wq;
    uint4* const pbase = &scr->P[rb * 28 * 1024 + rt * 128 + lane];
    const uint32_t a_lo0 = desc_lo(sbase + wr * 8192, 16);
    const uint32_t ebar = lane == 0 ? BAR(empty1, 0) : RBAR(empty1, 0);
    float r0, r1;
    uint4 px[8], py[6];
    const int rh = wgi ^ kh ^ 1;
    const uint32_t fpb = BAR(fullP, 16 * rh);
    const uint4* const psrc = &scr->P[(rb2 * 28 + 14 * kh) * 1024 + (4 * rh + wq) * 128 + lane];
    const uint32_t pa0 = sbase + (4 * rh + wq) * 2048;
    uint4 pf[3][4], ha[4][4];
    uint32_t rdy = 0, got0;
    {
      float acc[128];
#pragma unroll
      for (int i = 0; i < 128; i++) acc[i] = 0.f;
      const uint32_t b_lo0 = desc_lo(sbase + 8 * SLOT, 4096);
      const uint32_t t3 = clock32();
      if (WARM) {
        wg_fence();
#pragma unroll
        for (int i = 0; i < WARM; i++) wgmma_n256(acc, desc64(a_lo0 + 6 * 1024, HI128), desc64(b_lo0, HI128));
        wg_commit();
      }
      const uint4* const ap = &scr->LN[rb * 8 * 1024 + rt * 128 + lane];
      const uint32_t sa = sbase + rt * 2048, amask = (lane & 1) ? ~0u : ~1u;
      auto fetch_a = [&](int kb) {
#pragma unroll
        for (int i = 0; i < 4; i++) cp_async16(sa + kb * SLOT + (lane + 32 * i) * 16, ap + kb * 1024 + 32 * i);
        asm volatile("cp.async.commit_group;" ::: "memory");
      };
      auto load_a = [&](int kb) {
#pragma unroll
        for (int ks = 0; ks < 4; ks++)
          asm volatile("ldmatrix.sync.aligned.m8n8.x4.shared.b16 {%0,%1,%2,%3}, [%4];"
                       : "=r"(ha[kb][ks].x), "=r"(ha[kb][ks].y), "=r"(ha[kb][ks].z), "=r"(ha[kb][ks].w)
                       : "r"(sa + kb * SLOT + (lane & 15) * 128 + (((2 * ks + (lane >> 4)) ^ (lane & 7)) * 16)) : "memory");
      };
      auto check_a = [&](int kb) {
        int it = 0;
#pragma unroll 1
        while (true) {
          uint32_t m = 0;
#pragma unroll
          for (int ks = 0; ks < 4; ks++) m |= tag_miss(ha[kb][ks].x, ha[kb][ks].y, ha[kb][ks].z, ha[kb][ks].w, tag);
          if (!__any_sync(0xffffffffu, m & ~amask)) break;
          fetch_a(kb);
          asm volatile("cp.async.wait_group 0;" ::: "memory");
          __syncwarp();
          load_a(kb);
          if (++it > SPIN_LIMIT) { die(); break; }
        }
#pragma unroll
        for (int ks = 0; ks < 4; ks++)
          asm volatile("and.b32 %0, %0, %4; and.b32 %1, %1, %4; and.b32 %2, %2, %4; and.b32 %3, %3, %4;"
                       : "+r"(ha[kb][ks].x), "+r"(ha[kb][ks].y), "+r"(ha[kb][ks].z), "+r"(ha[kb][ks].w) : "r"(amask));
      };
      bar_sync(NB_CONS, 256);
      spin_until(t3 + POLL_DELAY3);
      fetch_a(0);
      fetch_a(1);
      asm volatile("cp.async.wait_group 1;" ::: "memory");
      __syncwarp();
      load_a(0);
#pragma unroll
      for (int n = 0; n < 8; n++) {
        const int kb = n >> 1, hh = n & 1;
        if (hh == 0) {
          check_a(kb);
          if (kb < 2) fetch_a(kb + 2);
        }
        if (hh == 1 && kb < 3) {
          if (kb < 2) asm volatile("cp.async.wait_group 1;" ::: "memory");
          else asm volatile("cp.async.wait_group 0;" ::: "memory");
          __syncwarp();
        }
        if (!rdy) mbar_wait(BAR(full1, n));
        const uint32_t bl = b_lo0 + ((n + 2) % 6) * 1024;
        wg_fence();
        if (hh == 1 && kb < 3) load_a(kb + 1);
        rdy = mbar_test(BAR(full1, n + 1));
        const uint4 &a0 = ha[kb][2 * hh], &a1 = ha[kb][2 * hh + 1];
        wgmma_rs_n256(acc, a0.x, a0.y, a0.z, a0.w, desc64(bl, HI128), n != 0 ? 1 : ~ones);
        wgmma_rs_n256(acc, a1.x, a1.y, a1.z, a1.w, desc64(bl + 128, HI128));
        wg_commit();
        wg_wait<1>();
        if (n != 0 && lane < 2) mbar_arrive_remote(ebar + 8 * (n - 1));
      }
      uint32_t slot = 4;
#pragma unroll 1
      for (int kb = 4; kb < 8; kb++) {
        mbar_wait(BAR(fullA, kb));
#pragma unroll
        for (int hh = 0; hh < 2; hh++) {
          if (hh == ((16 - LAGX) & 1) && kb == ((16 - LAGX) >> 1) && wgi == 1) bar_sync(NB_LAG, 256);
          mbar_wait(BAR(full1, 2 * kb + hh));
          const uint32_t al = a_lo0 + kb * 1024 + hh * 4, bl = b_lo0 + slot * 1024;
          wg_fence();
          wgmma_n256(acc, desc64(al, HI128), desc64(bl, HI128));
          wgmma_n256(acc, desc64(al + 2, HI128), desc64(bl + 128, HI128));
          wg_commit();
          if (hh == 1 && kb == 7 && wgi == 0) bar_arrive(NB_LAG, 256);
          wg_wait<1>();
          if (lane < 2) mbar_arrive_remote(ebar + 8 * (2 * kb + hh - 1));
          if (++slot == 6) slot = 0;
        }
      }
      mbar_wait(BAR(sbar, 0));
      r0 = __uint_as_float(lds2(sstat + (16 * rt + g) * 8).y);
      r1 = __uint_as_float(lds2(sstat + (16 * rt + g + 8) * 8).y);
      wg_wait<0>();
      if (lane < 2) mbar_arrive_remote(ebar + 8 * 15);
      make_p<8, false>(acc, r0, r1, px, pbase, 0, tag);
    }
    {
      float acc[96];
#pragma unroll
      for (int i = 0; i < 96; i++) acc[i] = 0.f;
      const uint32_t b_lo0 = desc_lo(sbase, 2048);
      uint4* const pdst = pbase + ((7 * f + 3 * (f & 1)) >> 1) * 1024;
      auto stage_y = [&](int k) {
        if (k < 4) mbar_wait_bounded(BAR(full1, 16 + k));
        else mbar_wait(BAR(full1, 16 + k));
        const uint32_t al = a_lo0 + (4 + (k >> 1)) * 1024 + (k & 1) * 4, bl = b_lo0 + (k < 5 ? k * 768 : 8192 + (k - 5) * 768);
        wg_fence();
        wgmma_n192(acc, desc64(al, HI128), desc64(bl, HI64));
        wgmma_n192(acc, desc64(al + 2, HI128), desc64(bl + 64, HI64));
        wg_commit();
      };
#pragma unroll
      for (int k = 0; k < 4; k++) {
        stage_y(k);
        st_tag(pdst + (k >> 1) * 1024 + (k & 1) * 64, px[2 * k], tag);
        st_tag(pdst + (k >> 1) * 1024 + (k & 1) * 64 + 32, px[2 * k + 1], tag);
        if (k == 3 && lane == 0) red_relaxed(&scr->cnt[(C_PX + rb) * 32 + (f >> 2)]);
        wg_wait<1>();
        if (k != 0 && lane < 2) mbar_arrive_remote(ebar + 8 * (15 + k));
      }
#pragma unroll 1
      for (int k = 4; k < 8; k++) {
        stage_y(k);
        wg_wait<1>();
        if (k != 0 && lane < 2) mbar_arrive_remote(ebar + 8 * (15 + k));
      }
      rdy = 0;
#pragma unroll
      for (int k = 8; k < 16; k++) {
        if (k == 16 - LAGY && wgi == 1) bar_sync(NB_LAG, 256);
        if (!rdy) mbar_wait(BAR(full1, 16 + k));
        const uint32_t bl = b_lo0 + (k < 13 ? 8192 + (k - 5) * 768 : (k - 13) * 768);
        const uint4 &a0 = ha[(k - 8) >> 1][2 * (k & 1)], &a1 = ha[(k - 8) >> 1][2 * (k & 1) + 1];
        wg_fence();
        if (k < 15) rdy = mbar_test(BAR(full1, 17 + k));
        wgmma_rs_n192(acc, a0.x, a0.y, a0.z, a0.w, desc64(bl, HI64));
        wgmma_rs_n192(acc, a1.x, a1.y, a1.z, a1.w, desc64(bl + 64, HI64));
        wg_commit();
        if (k == 15 && wgi == 0) bar_arrive(NB_LAG, 256);
        wg_wait<1>();
        if (lane < 2) mbar_arrive_remote(ebar + 8 * (15 + k));
      }
      got0 = __all_sync(0xffffffffu, mbar_test(fpb));
      if (got0) {
#pragma unroll
        for (int kk = 0; kk < 4; kk++) pf[0][kk] = lds4(pa0 + 3 * SLOT + kk * 512 + lane * 16);
      }
      wg_wait<0>();
      if (lane < 2) mbar_arrive_remote(ebar + 8 * 31);
      const int ks0 = 14 * f + ((f & 1) ? 0 : 8);
      auto reread = [&]() {
        asm volatile("ld.volatile.shared.f32 %0, [%2+4]; ld.volatile.shared.f32 %1, [%2+68];" : "=f"(r0), "=f"(r1) : "r"(sstat + (16 * rt + g) * 8) : "memory");
      };
      make_p<6, true, 0, 2>(acc, r0, r1, py, pbase, ks0, tag);
      reread();
      make_p<6, true, 2, 4>(acc, r0, r1, py, pbase, ks0, tag);
      if (lane == 0) red_relaxed(&scr->cnt[(C_PY + rb) * 32 + 4 * wgi + (f >> 1)]);
      reread();
      rdy = mbar_test(BAR(full2, 0)) & mbar_test(fpb + 8);
      make_p<6, true, 4, 6>(acc, r0, r1, py, pbase, ks0, tag);
    }
    {
      float acc[64];
      const uint32_t b2_lo0 = desc_lo(sbase, 8192);
      const uint32_t pbar = rh == rk ? BAR(emptyP, 0) : RBAR(emptyP, 0);
      if (!got0) {
        mbar_wait(fpb);
#pragma unroll
        for (int kk = 0; kk < 4; kk++) pf[0][kk] = lds4(pa0 + 3 * SLOT + kk * 512 + lane * 16);
      }
#pragma unroll
      for (int s = 0; s < 14; s++) {
        uint4 (&a)[4] = pf[s % 3];
        ld_tag4_finish<32>(a, psrc + (int)((KORDER >> (4 * s)) & 15) * 1024, tag);
        if (s < 9 && lane == 0) mbar_arrive_remote(pbar + 8 * s);
        if (s >= 2) {
          wg_wait<1>();
          if (s <= 7 && lane == 0) mbar_arrive(BAR(empty2, s - 2));
        }
        if (!rdy) {
          if (s < 13) mbar_wait(fpb + 8 * (s + 1));
          mbar_wait(BAR(full2, s));
        }
        if (s == 14 - LAG2 && wgi == 1) bar_sync(NB_LAG, 256);
        const uint32_t bl = b2_lo0 + (uint32_t)((BSLOT >> (4 * s)) & 15) * 1024;
        wg_fence();
        if (s < 13) {
#pragma unroll
          for (int kk = 0; kk < 4; kk++)
            pf[(s + 1) % 3][kk] = lds4(pa0 + (uint32_t)((PSLOT >> (4 * (s + 1))) & 15) * SLOT + kk * 512 + lane * 16);
          rdy = mbar_test(BAR(full2, s + 1));
          if (s < 12) rdy &= mbar_test(fpb + 8 * (s + 2));
        }
        if (s == 0) wgmma_rs_n128(acc, a[0].x, a[0].y, a[0].z, a[0].w, desc64(bl, HI128), 0);
        else wgmma_rs_n128(acc, a[0].x, a[0].y, a[0].z, a[0].w, desc64(bl, HI128));
#pragma unroll
        for (int kk = 1; kk < 4; kk++) wgmma_rs_n128(acc, a[kk].x, a[kk].y, a[kk].z, a[kk].w, desc64(bl + kk * 128, HI128));
        wg_commit();
      }
      if (wgi == 0) {
        bar_arrive(NB_LAG, 256);
        uint4* const dst = &scr->Z1[(tid >> 3) * 1024 + (c ^ 4) * 8 + (tid & 7)];
        wg_wait<0>();
#pragma unroll
        for (int i = 0; i < 8; i++)
          st_tag(dst + i * 16384, make_uint4(pack2(acc[8 * i], acc[8 * i + 1]), pack2(acc[8 * i + 2], acc[8 * i + 3]) | 1u,
                                           pack2(acc[8 * i + 4], acc[8 * i + 5]), pack2(acc[8 * i + 6], acc[8 * i + 7])), tag);
      } else {
        uint4 pv[2][4];
        const uint4* const xsrc = &scr->Z1[((tid & 127) >> 3) * 1024 + c * 8 + (tid & 7)];
        ld_tag4_issue<16384>(pv[0], xsrc);
        ld_tag4_issue<16384>(pv[1], xsrc + 65536);
        uint32_t w[32];
        {
          const uint32_t s0 = lds2(sstat + 1024 + (16 * wq + g) * 8).x, s1 = lds2(sstat + 1024 + (16 * wq + g + 8) * 8).x;
          const uint32_t m0 = __byte_perm(s0, 0, 0x3232), m1 = __byte_perm(s1, 0, 0x3232);
          const uint32_t l0 = __byte_perm(s0, 0, 0x1010), l1 = __byte_perm(s1, 0, 0x1010);
          const uint32_t hb = sbase + 13 * SLOT + (16 * wq + (lane & 15)) * 128;
          const uint32_t mk = ((t & 1) == 0 && nq < 2) ? ~1u : ~0u;
          mbar_wait(BAR(hbar, 0));
#pragma unroll
          for (int i = 0; i < 8; i++) {
            asm volatile("ldmatrix.sync.aligned.m8n8.x4.shared.b16 {%0,%1,%2,%3}, [%4];"
                         : "=r"(w[4 * i]), "=r"(w[4 * i + 1]), "=r"(w[4 * i + 2]), "=r"(w[4 * i + 3])
                         : "r"(hb + (i >> 2) * 8192 + (((2 * (i & 3) + (lane >> 4)) ^ (lane & 7)) * 16)) : "memory");
#pragma unroll
            for (int e = 0; e < 4; e++) w[4 * i + e] = hadd2_bf16(hadd2_bf16(w[4 * i + e] & mk, (e & 1) ? l1 : l0), (e & 1) ? m1 : m0);
          }
        }
        wg_wait<0>();
#pragma unroll
        for (int i = 0; i < 32; i++) w[i] = hadd2_bf16(w[i], pack2(acc[2 * i], acc[2 * i + 1]));
#pragma unroll 1
        while (!__all_sync(0xffffffffu, pv[0][0].y & pv[0][1].y & pv[0][2].y & pv[0][3].y & pv[1][0].y & pv[1][1].y & pv[1][2].y & pv[1][3].y & 1u)) {
          ld_tag4_issue<16384>(pv[0], xsrc);
          ld_tag4_issue<16384>(pv[1], xsrc + 65536);
        }
#pragma unroll
        for (int i = 0; i < 8; i++) {
          const uint4& p = pv[i >> 2][i & 3];
          asm volatile("stmatrix.sync.aligned.m8n8.x4.shared.b16 [%0], {%1,%2,%3,%4};"
                       ::"r"(pa0 + (11 + ((lane >> 3) & 1)) * SLOT + (lane & 7) * 256 + (((2 * i + (lane >> 4)) ^ (lane & 7)) * 16)),
                         "r"(hadd2_bf16(w[4 * i], p.x & ~1u)), "r"(hadd2_bf16(w[4 * i + 1], p.y & ~1u)), "r"(hadd2_bf16(w[4 * i + 2], p.z)),
                         "r"(hadd2_bf16(w[4 * i + 3], p.w)) : "memory");
        }
        __syncwarp();
        uint4* const dst = reinterpret_cast<uint4*>(out) + (16 * (c >> 4) + 2 * (4 * rh + wq) + (rb2 & 1) + 128 * (lane >> 4)) * 64 + nq * 16 + (lane & 15);
#pragma unroll
        for (int i = 0; i < 8; i++) {
          const int r = 2 * (i & 3) + (lane >> 4);
          dst[i * 256 * 64] = lds4(pa0 + (11 + (i >> 2)) * SLOT + r * 256 + (((lane & 15) ^ r) * 16));
        }
      }
      if (lane == 0) mbar_arrive(BAR(done, 0));
    }
  }
#undef BAR
#undef TOFF
#undef RBAR
}

typedef CUresult (*EncodeFn)(CUtensorMap*, CUtensorMapDataType, cuuint32_t, void*, const cuuint64_t*, const cuuint64_t*,
                             const cuuint32_t*, const cuuint32_t*, CUtensorMapInterleave, CUtensorMapSwizzle,
                             CUtensorMapL2promotion, CUtensorMapFloatOOBfill);

}

extern "C" void kernel_launch(void* const* d_in, const int* in_sizes, int n_in, void* d_out, int out_size) {
  (void)in_sizes; (void)n_in; (void)out_size;
  static EncodeFn encode = nullptr;
  static void *tab = nullptr, *scr = nullptr;
  if (!encode) {
    void* fn = nullptr;
    cudaDriverEntryPointQueryResult qr;
    cudaGetDriverEntryPoint("cuTensorMapEncodeTiled", &fn, cudaEnableDefault, &qr);
    encode = (EncodeFn)fn;
    cudaGetSymbolAddress(&tab, g_tab);
    cudaGetSymbolAddress(&scr, g_scr);
    cudaFuncSetAttribute(fused_kernel, cudaFuncAttributeMaxDynamicSharedMemorySize, SMEM_BYTES);
  }
  CUtensorMap tmGX, tmUX, tmGY, tmUY, tmD, tmWR, tmWI;
  const cuuint32_t es[5] = {1, 1, 1, 1, 1};
  auto enc = [&](CUtensorMap* m, void* p, int rank, const cuuint64_t* gd, const cuuint64_t* gs, const cuuint32_t* bd,
                 CUtensorMapSwizzle sw, CUtensorMapL2promotion pr) {
    encode(m, CU_TENSOR_MAP_DATA_TYPE_BFLOAT16, rank, p, gd, gs, bd, es, CU_TENSOR_MAP_INTERLEAVE_NONE, sw, pr,
           CU_TENSOR_MAP_FLOAT_OOB_FILL_NONE);
  };
  {
    const cuuint64_t gd[3] = {64, 512, 28}, gs[2] = {3584, 128};
    const cuuint32_t bd[3] = {64, 32, 2};
    enc(&tmGX, d_in[4], 3, gd, gs, bd, CU_TENSOR_MAP_SWIZZLE_128B, CU_TENSOR_MAP_L2_PROMOTION_L2_256B);
    enc(&tmUX, d_in[5], 3, gd, gs, bd, CU_TENSOR_MAP_SWIZZLE_128B, CU_TENSOR_MAP_L2_PROMOTION_L2_256B);
  }
  {
    const cuuint64_t gd[3] = {32, 512, 56}, gs[2] = {3584, 64};
    const cuuint32_t bd[3] = {32, 32, 3};
    enc(&tmGY, d_in[4], 3, gd, gs, bd, CU_TENSOR_MAP_SWIZZLE_64B, CU_TENSOR_MAP_L2_PROMOTION_L2_128B);
    enc(&tmUY, d_in[5], 3, gd, gs, bd, CU_TENSOR_MAP_SWIZZLE_64B, CU_TENSOR_MAP_L2_PROMOTION_L2_128B);
  }
  {
    const cuuint64_t gd[3] = {64, 1792, 8}, gs[2] = {1024, 128};
    const cuuint32_t bd[3] = {64, 64, 2};
    enc(&tmD, d_in[6], 3, gd, gs, bd, CU_TENSOR_MAP_SWIZZLE_128B, CU_TENSOR_MAP_L2_PROMOTION_L2_256B);
  }
  {
    const cuuint64_t gd[3] = {4112, 8, 16}, gs[2] = {16 * 8224, 8224};
    const cuuint32_t bd[3] = {40, 8, 16};
    enc(&tmWR, d_in[1], 3, gd, gs, bd, CU_TENSOR_MAP_SWIZZLE_NONE, CU_TENSOR_MAP_L2_PROMOTION_NONE);
    enc(&tmWI, d_in[2], 3, gd, gs, bd, CU_TENSOR_MAP_SWIZZLE_NONE, CU_TENSOR_MAP_L2_PROMOTION_NONE);
  }
  fused_kernel<<<NCTA, NTHREADS, SMEM_BYTES>>>((const __nv_bfloat16*)d_in[0], (const Tables*)tab, (Scratch*)scr,
                                               (__nv_bfloat16*)d_out, (const char*)d_in[4], (const char*)d_in[5],
                                               (const char*)d_in[6], tmWR, tmWI, tmGX, tmUX, tmGY, tmUY, tmD);
}
```

```cpp
#include <cuda_runtime.h>
#include <cuda_bf16.h>
#include <cuda.h>
#include <stdint.h>

namespace {

constexpr int NCTA = 128;
constexpr int NTHREADS = 384;
constexpr int SLOT = 16384;
constexpr int SMEM_BYTES = 14 * SLOT + 3072;
constexpr int SPIN_LIMIT = 1 << 22;

struct Scratch {
  uint4 Z1[128 * 1024];
  uint4 LN[16 * 8 * 1024];
  uint4 P[16 * 28 * 1024];
  uint4 ST[1024];
  unsigned cnt[64 * 32];
};
__device__ __align__(1024) Scratch g_scr;

constexpr double ccos(int i, int n) {
  i &= n - 1;
  if (i > n / 2) i = n - i;
  if (4 * i == n) return 0.0;
  const bool neg = 4 * i > n;
  if (neg) i = n / 2 - i;
  const double a = 6.283185307179586476925 * i / n, a2 = a * a;
  double term = 1.0, sum = 1.0;
  for (int k = 1; k < 14; k++) { term *= -a2 / ((2 * k - 1) * (2 * k)); sum += term; }
  return neg ? -sum : sum;
}
constexpr double csin(int i, int n) { return ccos(i - n / 4, n); }
constexpr unsigned fbits(double v, int mant) {
  if (v == 0.0) return 0;
  const unsigned sg = v < 0 ? 1u : 0u;
  if (v < 0) v = -v;
  int e = 127;
  while (v < 1.0) { v *= 2.0; e--; }
  const unsigned m = (unsigned)((v - 1.0) * (double)(1u << mant) + 0.5);
  return (sg << (8 + mant)) + ((unsigned)e << mant) + m;
}
constexpr unsigned pkb(double lo, double hi) { return fbits(lo, 7) | (fbits(hi, 7) << 16); }
constexpr double fa_elem(int mt, int r, int n1) {
  const int k1 = 8 * mt + (r & 7);
  return r < 8 ? ccos(k1 * n1, 32) : k1 == 0 ? ccos(16 * n1, 32) : -csin(k1 * n1, 32);
}
constexpr unsigned cfrag_c(int idx, int n, int ri, double s = 1.0) {
  return ri ? pkb(-s * csin(idx, n), s * ccos(idx, n)) : pkb(s * ccos(idx, n), s * csin(idx, n));
}
struct Tables {
  unsigned fa[4][32][4];
  unsigned fb[4][32][4];
  unsigned tw1[6][32][4];
  unsigned f2[8][4][32][4];
  unsigned g2[8][4][32][4];
  unsigned gb[4][32][4];
  unsigned ga[4][32][4];
  unsigned tw3[4][32][4];
  unsigned f8[32][4], g8[32][4];
};
constexpr int T1_BYTES = 7168, T2_BYTES = 39936;
static_assert(sizeof(Tables) == T1_BYTES + T2_BYTES, "table size");
constexpr Tables make_tables() {
  Tables T = {};
  for (int l = 0; l < 32; l++) {
    const int g = l >> 2, t = l & 3;
    for (int a = 0; a < 2; a++)
      for (int b = 0; b < 2; b++) {
        for (int r = 0; r < 4; r++) {
          const int row = g + 8 * (r & 1), col = 2 * t + 8 * (r >> 1);
          T.fa[2 * a + b][l][r] = pkb(fa_elem(a, row, 16 * b + col), fa_elem(a, row, 16 * b + col + 1));
          T.ga[2 * a + b][l][r] = pkb(fa_elem(b, col, 16 * a + row), fa_elem(b, col + 1, 16 * a + row));
        }
        const double sg = b ? -1.0 : 1.0;
        for (int h = 0; h < 2; h++) {
          const int ri = g & 1, m = 2 * (g >> 1) + h, k2 = b ? 15 - m : m;
          const int pa = (8 * a + 2 * t) * k2, pb = (8 * a + 2 * t + 1) * k2;
          T.fb[2 * a + b][l][2 * h] = ri == 0 ? pkb(ccos(pa, 16), ccos(pb, 16)) : pkb(-sg * csin(pa, 16), -sg * csin(pb, 16));
          T.fb[2 * a + b][l][2 * h + 1] = ri == 0 ? pkb(csin(pa, 16), csin(pb, 16)) : pkb(sg * ccos(pa, 16), sg * ccos(pb, 16));
        }
        const int n2 = 4 * (g >> 1) + 2 * a + (g & 1);
        for (int h = 0; h < 2; h++) {
          const int p = n2 * (b ? 15 - 2 * t - h : 2 * t + h);
          T.gb[2 * a + b][l][2 * h] = pkb(ccos(p, 16), -sg * csin(p, 16));
          T.gb[2 * a + b][l][2 * h + 1] = pkb(csin(p, 16), sg * ccos(p, 16));
          const int k1 = 8 * b + 2 * t + h, q = n2 * (k1 == 0 ? 16 : k1);
          T.tw3[2 * a + b][l][2 * h] = fbits(ccos(q, 512), 23);
          T.tw3[2 * a + b][l][2 * h + 1] = fbits(csin(q, 512), 23);
        }
        const int p = (8 * a + 2 * t + b) * (g == 0 ? 16 : g);
        T.tw1[2 * a + b][l][0] = fbits(g == 0 ? 0.0 : ccos(p, 512), 23);
        T.tw1[2 * a + b][l][1] = fbits(g == 0 ? ccos(p, 512) : csin(p, 512), 23);
        T.tw1[2 * a + b][l][2] = fbits(g == 0 ? 0.0 : -csin(p, 512), 23);
        T.tw1[2 * a + b][l][3] = fbits(g == 0 ? -csin(p, 512) : ccos(p, 512), 23);
        T.tw1[4 + a][l][2 * b] = fbits(ccos((8 * a + 2 * t + b) * (g + 8), 512), 23);
        T.tw1[4 + a][l][2 * b + 1] = fbits(csin((8 * a + 2 * t + b) * (g + 8), 512), 23);
      }
    for (int i = 0; i < 4; i++) {
      const int p8 = (t + 4 * (i & 1)) * (4 * (i >> 1) + (g >> 1));
      T.f8[l][i] = cfrag_c(p8, 8, g & 1);
      T.g8[l][i] = cfrag_c(-p8, 8, g & 1, 1.0 / (1 << 19));
    }
    for (int w = 0; w < 8; w++)
      for (int i = 0; i < 16; i++) {
        const int kidx = t + 4 * (i & 1) + 8 * (i >> 3), nidx = 4 * ((i >> 1) & 3) + (g >> 1);
        T.f2[w][i >> 2][l][i & 3] = cfrag_c((8 * kidx + w) * nidx, 128, g & 1);
        T.g2[w][i >> 2][l][i & 3] = cfrag_c(-(8 * nidx + w) * kidx, 128, g & 1);
      }
  }
  return T;
}
__device__ const __align__(128) Tables g_tab = make_tables();

__device__ __forceinline__ void die() { asm volatile("st.global.u32 [%0], %1;" ::"l"(0ull), "r"(0) : "memory"); }
__device__ __forceinline__ uint32_t s2u(const void* p) { return (uint32_t)__cvta_generic_to_shared(p); }
__device__ __forceinline__ void mbar_init(uint32_t b, int c) { asm volatile("mbarrier.init.shared::cta.b64 [%0], %1;" ::"r"(b), "r"(c)); }
__device__ __forceinline__ void mbar_expect(uint32_t b, int bytes) {
  asm volatile("mbarrier.arrive.expect_tx.shared::cta.b64 _, [%0], %1;" ::"r"(b), "r"(bytes) : "memory");
}
__device__ __forceinline__ void mbar_arrive(uint32_t b) { asm volatile("mbarrier.arrive.shared::cta.b64 _, [%0];" ::"r"(b) : "memory"); }
__device__ __forceinline__ uint32_t mbar_try(uint32_t b, uint32_t parity) {
  uint32_t ok;
  asm volatile("{.reg .pred p; mbarrier.try_wait.parity.shared::cta.b64 p, [%1], %2; selp.u32 %0,1,0,p;}"
               : "=r"(ok) : "r"(b), "r"(parity) : "memory");
  return ok;
}
__device__ __forceinline__ uint32_t mbar_test(uint32_t b) {
  uint32_t ok;
  asm volatile("{.reg .pred p; mbarrier.test_wait.parity.shared::cta.b64 p, [%1], 0; selp.u32 %0,1,0,p;}" : "=r"(ok) : "r"(b) : "memory");
  return ok;
}
__device__ __forceinline__ void mbar_wait_bounded(uint32_t b) {
  int it = 0;
#pragma unroll 1
  while (!mbar_try(b, 0))
    if (++it > SPIN_LIMIT) { die(); break; }
}
__device__ __forceinline__ void mbar_wait(uint32_t b) {
  asm volatile("{.reg .pred p;\nW_%=: mbarrier.try_wait.parity.shared::cta.b64 p, [%0], 0;\n@!p bra W_%=;}" ::"r"(b) : "memory");
}
__device__ __forceinline__ void bar_sync(int id, int n) { asm volatile("bar.sync %0, %1;" ::"r"(id), "r"(n) : "memory"); }
__device__ __forceinline__ void bar_arrive(int id, int n) { asm volatile("bar.arrive %0, %1;" ::"r"(id), "r"(n) : "memory"); }
__device__ __forceinline__ void red_release(unsigned* p) { asm volatile("red.release.gpu.global.add.u32 [%0], 1;" ::"l"(p) : "memory"); }
__device__ __forceinline__ void red_relaxed(unsigned* p) { asm volatile("red.relaxed.gpu.global.add.u32 [%0], 1;" ::"l"(p) : "memory"); }
__device__ __forceinline__ unsigned ld_acquire(const unsigned* p) {
  unsigned v;
  asm volatile("ld.acquire.gpu.global.u32 %0, [%1];" : "=r"(v) : "l"(p) : "memory");
  return v;
}
__device__ __forceinline__ unsigned ld_relaxed(const unsigned* p) {
  unsigned v;
  asm volatile("ld.relaxed.gpu.global.u32 %0, [%1];" : "=r"(v) : "l"(p) : "memory");
  return v;
}
__device__ __forceinline__ void wait_counter(const unsigned* p, unsigned target) {
#pragma unroll 1
  while ((int)(ld_acquire(p) - target) < 0) {}
}
__device__ __forceinline__ void sts4(uint32_t a, uint32_t x, uint32_t y, uint32_t z, uint32_t w) {
  asm volatile("st.shared.v4.u32 [%0], {%1,%2,%3,%4};" ::"r"(a), "r"(x), "r"(y), "r"(z), "r"(w) : "memory");
}
__device__ __forceinline__ uint4 lds4(uint32_t a) {
  uint4 v;
  asm volatile("ld.shared.v4.u32 {%0,%1,%2,%3}, [%4];" : "=r"(v.x), "=r"(v.y), "=r"(v.z), "=r"(v.w) : "r"(a) : "memory");
  return v;
}
__device__ __forceinline__ uint32_t pack2(float lo, float hi) {
  uint32_t r;
  asm("cvt.rn.bf16x2.f32 %0, %1, %2;" : "=r"(r) : "f"(hi), "f"(lo));
  return r;
}
__device__ __forceinline__ float bf_lo(uint32_t v) { return __uint_as_float(v << 16); }
__device__ __forceinline__ uint32_t hadd2_bf16(uint32_t a, uint32_t b) {
  uint32_t r;
  asm("add.rn.bf16x2 %0, %1, %2;" : "=r"(r) : "r"(a), "r"(b));
  return r;
}
__device__ __forceinline__ void mma16816(float (&d)[4], uint32_t a0, uint32_t a1, uint32_t a2, uint32_t a3, uint32_t b0, uint32_t b1) {
  asm("mma.sync.aligned.m16n8k16.row.col.f32.bf16.bf16.f32 {%0,%1,%2,%3}, {%4,%5,%6,%7}, {%8,%9}, {%0,%1,%2,%3};"
      : "+f"(d[0]), "+f"(d[1]), "+f"(d[2]), "+f"(d[3])
      : "r"(a0), "r"(a1), "r"(a2), "r"(a3), "r"(b0), "r"(b1));
}
__device__ __forceinline__ void mma16816_z(float (&d)[4], uint32_t a0, uint32_t a1, uint32_t a2, uint32_t a3, uint32_t b0, uint32_t b1) {
  asm("{.reg .f32 z; mov.f32 z, 0f00000000;\n"
      "mma.sync.aligned.m16n8k16.row.col.f32.bf16.bf16.f32 {%0,%1,%2,%3}, {%4,%5,%6,%7}, {%8,%9}, {z,z,z,z};}"
      : "=f"(d[0]), "=f"(d[1]), "=f"(d[2]), "=f"(d[3])
      : "r"(a0), "r"(a1), "r"(a2), "r"(a3), "r"(b0), "r"(b1));
}
template <int N>
__device__ __forceinline__ void cs_frac(int idx, float& c, float& s) {
  int i = ((idx + N / 2) & (N - 1)) - N / 2;
  float a = (float)i * (6.283185307179586f / N);
  c = __cosf(a);
  s = __sinf(a);
}
template <int N>
__device__ __forceinline__ uint32_t cfrag(int idx, int ri) {
  float c, s;
  cs_frac<N>(idx, c, s);
  return ri ? pack2(-s, c) : pack2(c, s);
}
__device__ __forceinline__ uint32_t word(const uint4& v, int e) { return e == 0 ? v.x : e == 1 ? v.y : e == 2 ? v.z : v.w; }
__device__ __forceinline__ void cdft16(const uint4 (&A)[4], const uint4 (&F)[4], uint4 (&o)[4]) {
  float acc[2][4][4];
#pragma unroll
  for (int ks = 0; ks < 2; ks++)
#pragma unroll
    for (int p = 0; p < 2; p++)
#pragma unroll
      for (int v = 0; v < 4; v++) {
        const uint4& a = A[2 * ks + p];
        const uint32_t b0 = word(F[ks * 2 + (v >> 1)], (v & 1) * 2), b1 = word(F[ks * 2 + (v >> 1)], (v & 1) * 2 + 1);
        if (ks == 0) mma16816_z(acc[p][v], a.x, a.y, a.z, a.w, b0, b1);
        else mma16816(acc[p][v], a.x, a.y, a.z, a.w, b0, b1);
      }
#pragma unroll
  for (int v = 0; v < 4; v++)
    o[v] = make_uint4(pack2(acc[0][v][0], acc[0][v][1]), pack2(acc[0][v][2], acc[0][v][3]),
                      pack2(acc[1][v][0], acc[1][v][1]), pack2(acc[1][v][2], acc[1][v][3]));
}
__device__ __forceinline__ void lds_frag(uint4& f0, uint4& f1, uint32_t a0, uint32_t a1) {
  asm volatile("ld.volatile.shared.v2.u32 {%0,%1}, [%8]; ld.volatile.shared.v2.u32 {%2,%3}, [%9];\n"
               "ld.volatile.shared.v2.u32 {%4,%5}, [%8+8]; ld.volatile.shared.v2.u32 {%6,%7}, [%9+8];"
               : "=r"(f0.x), "=r"(f0.y), "=r"(f0.z), "=r"(f0.w), "=r"(f1.x), "=r"(f1.y), "=r"(f1.z), "=r"(f1.w) : "r"(a0), "r"(a1) : "memory");
}
__device__ __forceinline__ void reg_frag(uint4 (&q)[4], uint32_t ones) {
#pragma unroll
  for (int ks = 0; ks < 2; ks++) {
    const uint4 a = q[2 * ks], b = q[2 * ks + 1];
    q[2 * ks] = make_uint4(a.x, a.y, b.x & ones, b.y & ones);
    q[2 * ks + 1] = make_uint4(a.z & ones, a.w & ones, b.z, b.w);
  }
}
__device__ __forceinline__ void st_tag(uint4* p, const uint4& v, uint32_t tag) {
  asm volatile("st.relaxed.gpu.global.v4.b32 [%0], {%1,%2,%3,%4};"
               ::"l"(p), "r"((v.x & ~1u) | tag), "r"(v.y), "r"(v.z), "r"(v.w) : "memory");
}
__device__ __forceinline__ void st_tag8(void* p, uint32_t x, uint32_t y, uint32_t tag) {
  asm volatile("st.relaxed.gpu.global.v2.b32 [%0], {%1,%2};" ::"l"(p), "r"((x & ~1u) | tag), "r"(y) : "memory");
}
__device__ __forceinline__ uint4 ld_b128(const uint4* p) {
  uint4 v;
  asm volatile("ld.relaxed.gpu.global.v4.b32 {%0,%1,%2,%3}, [%4];"
               : "=r"(v.x), "=r"(v.y), "=r"(v.z), "=r"(v.w) : "l"(p) : "memory");
  return v;
}
template <int STRIDE>
__device__ __forceinline__ void ld_tag4_issue(uint4 (&q)[4], const uint4* p) {
#pragma unroll
  for (int i = 0; i < 4; i++) q[i] = ld_b128(p + i * STRIDE);
}
__device__ __forceinline__ uint32_t tag_miss(uint32_t a, uint32_t b, uint32_t c, uint32_t d, uint32_t tag) {
  uint32_t r;
  asm("{.reg .b32 u, v; lop3.b32 u, %1, %2, %5, 0x7e; lop3.b32 v, %3, %4, %5, 0x7e; lop3.b32 %0, u, v, 1, 0xa8;}"
      : "=r"(r) : "r"(a), "r"(b), "r"(c), "r"(d), "r"(tag));
  return r;
}
template <int STRIDE, bool HALVES = false>
__device__ __forceinline__ void ld_tag4_finish(uint4 (&q)[4], const uint4* p, uint32_t tag) {
  int it = 0;
#pragma unroll 1
  while (__any_sync(0xffffffffu, tag_miss(q[0].x, q[1].x, q[2].x, q[3].x, tag) | (HALVES ? tag_miss(q[0].z, q[1].z, q[2].z, q[3].z, tag) : 0u))) {
    ld_tag4_issue<STRIDE>(q, p);
    if (++it > SPIN_LIMIT) { die(); break; }
  }
#pragma unroll
  for (int i = 0; i < 4; i++) {
    asm volatile("and.b32 %0, %0, 0xfffffffe;" : "+r"(q[i].x));
    if (HALVES) q[i].z &= ~1u;
  }
}
__device__ __forceinline__ float quad_sum(const uint32_t (&a)[8]) {
  float d[4];
  mma16816_z(d, a[0], a[1], a[2], a[3], 0x3f803f80u, 0x3f803f80u);
  mma16816(d, a[4], a[5], a[6], a[7], 0x3f803f80u, 0x3f803f80u);
  return d[0] + d[2];
}
__device__ __forceinline__ float sum_groups(float v) {
  v += __shfl_xor_sync(0xffffffffu, v, 4);
  v += __shfl_xor_sync(0xffffffffu, v, 8);
  v += __shfl_xor_sync(0xffffffffu, v, 16);
  return v;
}
__device__ __forceinline__ uint32_t hsub2_bf16(uint32_t a, uint32_t b) {
  uint32_t r;
  asm("sub.rn.bf16x2 %0, %1, %2;" : "=r"(r) : "r"(a), "r"(b));
  return r;
}
__device__ __forceinline__ float row_rstd(const uint32_t (&c)[8]) {
  uint32_t s[8];
#pragma unroll
  for (int i = 0; i < 8; i++) asm("mul.rn.bf16x2 %0, %1, %1;" : "=r"(s[i]) : "r"(c[i]));
  return rsqrtf(fmaf(sum_groups(quad_sum(s)), 1.f / 512.f, 1e-5f));
}
__device__ __forceinline__ uint64_t desc64(uint32_t lo, uint32_t hi) {
  uint64_t d;
  asm("mov.b64 %0, {%1, %2};" : "=l"(d) : "r"(lo), "r"(hi));
  return d;
}
constexpr uint32_t desc_hi(uint32_t sbo, uint32_t swz) { return (sbo >> 4) | (swz << 30); }
__device__ __forceinline__ uint32_t desc_lo(uint32_t addr, uint32_t lbo) { return ((addr & 0x3FFFF) >> 4) | ((lbo >> 4) << 16); }
__device__ __forceinline__ void cp_async16(uint32_t dst, const void* src) {
  asm volatile("cp.async.cg.shared.global [%0], [%1], 16;" ::"r"(dst), "l"(src) : "memory");
}
__device__ __forceinline__ uint2 lds2(uint32_t a) {
  uint2 v;
  asm volatile("ld.shared.v2.u32 {%0,%1}, [%2];" : "=r"(v.x), "=r"(v.y) : "r"(a) : "memory");
  return v;
}
__device__ __forceinline__ uint32_t lds_u16(uint32_t a) {
  uint16_t v;
  asm volatile("ld.shared.u16 %0, [%1];" : "=h"(v) : "r"(a) : "memory");
  return v;
}
__device__ __forceinline__ void wg_fence() { asm volatile("wgmma.fence.sync.aligned;" ::: "memory"); }
__device__ __forceinline__ void wg_commit() { asm volatile("wgmma.commit_group.sync.aligned;" ::: "memory"); }
template <int N>
__device__ __forceinline__ void wg_wait() { asm volatile("wgmma.wait_group.sync.aligned %0;" ::"n"(N) : "memory"); }
__device__ __forceinline__ void bulk_load(uint32_t dst, const void* src, int bytes, uint32_t bar) {
  asm volatile("cp.async.bulk.shared::cluster.global.mbarrier::complete_tx::bytes [%0], [%1], %2, [%3];"
               ::"r"(dst), "l"(src), "r"(bytes), "r"(bar) : "memory");
}
__device__ __forceinline__ void bulk_load_mc(uint32_t dst, const void* src, int bytes, uint32_t bar) {
  asm volatile("cp.async.bulk.shared::cluster.global.mbarrier::complete_tx::bytes.multicast::cluster [%0], [%1], %2, [%3], %4;"
               ::"r"(dst), "l"(src), "r"(bytes), "r"(bar), "h"((uint16_t)3) : "memory");
}
__device__ __forceinline__ void tma3(uint32_t dst, const CUtensorMap* tm, uint32_t bar, int c0, int c1, int c2) {
  asm volatile("cp.async.bulk.tensor.3d.shared::cluster.global.mbarrier::complete_tx::bytes [%0], [%1, {%3,%4,%5}], [%2];"
               ::"r"(dst), "l"(tm), "r"(bar), "r"(c0), "r"(c1), "r"(c2) : "memory");
}
__device__ __forceinline__ void tma3_mc(uint32_t dst, const CUtensorMap* tm, uint32_t bar, int c1, int c2) {
  asm volatile("cp.async.bulk.tensor.3d.shared::cluster.global.mbarrier::complete_tx::bytes.multicast::cluster [%0], [%1, {%3,%4,%5}], [%2], %6;"
               ::"r"(dst), "l"(tm), "r"(bar), "r"(0), "r"(c1), "r"(c2), "h"((uint16_t)3) : "memory");
}
__device__ __forceinline__ void mbar_arrive_remote(uint32_t rb) {
  asm volatile("mbarrier.arrive.shared::cluster.b64 _, [%0];" ::"r"(rb) : "memory");
}
__device__ __forceinline__ uint4 ldg_ca4(const void* p) {
  uint4 v;
  asm volatile("ld.global.ca.v4.u32 {%0,%1,%2,%3}, [%4];" : "=r"(v.x), "=r"(v.y), "=r"(v.z), "=r"(v.w) : "l"(p) : "memory");
  return v;
}
__device__ __forceinline__ float u2f(uint32_t v) { return __uint_as_float(v); }
__device__ __forceinline__ void mma_az(float (&d)[4], const uint4& a, uint32_t b0, uint32_t b1) { mma16816_z(d, a.x, a.y, a.z, a.w, b0, b1); }
__device__ __forceinline__ void mma_a(float (&d)[4], const uint4& a, uint32_t b0, uint32_t b1) { mma16816(d, a.x, a.y, a.z, a.w, b0, b1); }
__device__ __forceinline__ uint32_t clock32() {
  uint32_t v;
  asm volatile("mov.u32 %0, %%clock;" : "=r"(v) :: "memory");
  return v;
}
__device__ __forceinline__ float swiglu(float g, float u, float r) {
  float hg = (0.5f * r) * g, th;
  asm("tanh.approx.f32 %0, %1;" : "=f"(th) : "f"(hg));
  return fmaf(hg, th, hg) * (r * u);
}
__device__ __forceinline__ void l2_prefetch(const void* p, int bytes) {
  asm volatile("cp.async.bulk.prefetch.L2.global [%0], %1;" ::"l"(p), "r"(bytes) : "memory");
}

__device__ __forceinline__ void wgmma_n256(float (&d)[128], uint64_t da, uint64_t db, int sd = 1) {
  asm volatile("{.reg .pred p; setp.ne.b32 p, %130, 0;\n"
      "wgmma.mma_async.sync.aligned.m64n256k16.f32.bf16.bf16 {"
      "%0,%1,%2,%3,%4,%5,%6,%7,%8,%9,%10,%11,%12,%13,%14,%15,"
      "%16,%17,%18,%19,%20,%21,%22,%23,%24,%25,%26,%27,%28,%29,%30,%31,"
      "%32,%33,%34,%35,%36,%37,%38,%39,%40,%41,%42,%43,%44,%45,%46,%47,"
      "%48,%49,%50,%51,%52,%53,%54,%55,%56,%57,%58,%59,%60,%61,%62,%63,"
      "%64,%65,%66,%67,%68,%69,%70,%71,%72,%73,%74,%75,%76,%77,%78,%79,"
      "%80,%81,%82,%83,%84,%85,%86,%87,%88,%89,%90,%91,%92,%93,%94,%95,"
      "%96,%97,%98,%99,%100,%101,%102,%103,%104,%105,%106,%107,%108,%109,%110,%111,"
      "%112,%113,%114,%115,%116,%117,%118,%119,%120,%121,%122,%123,%124,%125,%126,%127"
      "}, %128, %129, p, 1, 1, 0, 1;}\n"
      : "+f"(d[0]),"+f"(d[1]),"+f"(d[2]),"+f"(d[3]),"+f"(d[4]),"+f"(d[5]),"+f"(d[6]),"+f"(d[7]),
        "+f"(d[8]),"+f"(d[9]),"+f"(d[10]),"+f"(d[11]),"+f"(d[12]),"+f"(d[13]),"+f"(d[14]),"+f"(d[15]),
        "+f"(d[16]),"+f"(d[17]),"+f"(d[18]),"+f"(d[19]),"+f"(d[20]),"+f"(d[21]),"+f"(d[22]),"+f"(d[23]),
        "+f"(d[24]),"+f"(d[25]),"+f"(d[26]),"+f"(d[27]),"+f"(d[28]),"+f"(d[29]),"+f"(d[30]),"+f"(d[31]),
        "+f"(d[32]),"+f"(d[33]),"+f"(d[34]),"+f"(d[35]),"+f"(d[36]),"+f"(d[37]),"+f"(d[38]),"+f"(d[39]),
        "+f"(d[40]),"+f"(d[41]),"+f"(d[42]),"+f"(d[43]),"+f"(d[44]),"+f"(d[45]),"+f"(d[46]),"+f"(d[47]),
        "+f"(d[48]),"+f"(d[49]),"+f"(d[50]),"+f"(d[51]),"+f"(d[52]),"+f"(d[53]),"+f"(d[54]),"+f"(d[55]),
        "+f"(d[56]),"+f"(d[57]),"+f"(d[58]),"+f"(d[59]),"+f"(d[60]),"+f"(d[61]),"+f"(d[62]),"+f"(d[63]),
        "+f"(d[64]),"+f"(d[65]),"+f"(d[66]),"+f"(d[67]),"+f"(d[68]),"+f"(d[69]),"+f"(d[70]),"+f"(d[71]),
        "+f"(d[72]),"+f"(d[73]),"+f"(d[74]),"+f"(d[75]),"+f"(d[76]),"+f"(d[77]),"+f"(d[78]),"+f"(d[79]),
        "+f"(d[80]),"+f"(d[81]),"+f"(d[82]),"+f"(d[83]),"+f"(d[84]),"+f"(d[85]),"+f"(d[86]),"+f"(d[87]),
        "+f"(d[88]),"+f"(d[89]),"+f"(d[90]),"+f"(d[91]),"+f"(d[92]),"+f"(d[93]),"+f"(d[94]),"+f"(d[95]),
        "+f"(d[96]),"+f"(d[97]),"+f"(d[98]),"+f"(d[99]),"+f"(d[100]),"+f"(d[101]),"+f"(d[102]),"+f"(d[103]),
        "+f"(d[104]),"+f"(d[105]),"+f"(d[106]),"+f"(d[107]),"+f"(d[108]),"+f"(d[109]),"+f"(d[110]),"+f"(d[111]),
        "+f"(d[112]),"+f"(d[113]),"+f"(d[114]),"+f"(d[115]),"+f"(d[116]),"+f"(d[117]),"+f"(d[118]),"+f"(d[119]),
        "+f"(d[120]),"+f"(d[121]),"+f"(d[122]),"+f"(d[123]),"+f"(d[124]),"+f"(d[125]),"+f"(d[126]),"+f"(d[127])
      : "l"(da), "l"(db), "r"(sd));
}
__device__ __forceinline__ void wgmma_n192(float (&d)[96], uint64_t da, uint64_t db) {
  asm volatile("wgmma.mma_async.sync.aligned.m64n192k16.f32.bf16.bf16 {"
      "%0,%1,%2,%3,%4,%5,%6,%7,%8,%9,%10,%11,%12,%13,%14,%15,"
      "%16,%17,%18,%19,%20,%21,%22,%23,%24,%25,%26,%27,%28,%29,%30,%31,"
      "%32,%33,%34,%35,%36,%37,%38,%39,%40,%41,%42,%43,%44,%45,%46,%47,"
      "%48,%49,%50,%51,%52,%53,%54,%55,%56,%57,%58,%59,%60,%61,%62,%63,"
      "%64,%65,%66,%67,%68,%69,%70,%71,%72,%73,%74,%75,%76,%77,%78,%79,"
      "%80,%81,%82,%83,%84,%85,%86,%87,%88,%89,%90,%91,%92,%93,%94,%95"
      "}, %96, %97, 1, 1, 1, 0, 1;\n"
      : "+f"(d[0]),"+f"(d[1]),"+f"(d[2]),"+f"(d[3]),"+f"(d[4]),"+f"(d[5]),"+f"(d[6]),"+f"(d[7]),
        "+f"(d[8]),"+f"(d[9]),"+f"(d[10]),"+f"(d[11]),"+f"(d[12]),"+f"(d[13]),"+f"(d[14]),"+f"(d[15]),
        "+f"(d[16]),"+f"(d[17]),"+f"(d[18]),"+f"(d[19]),"+f"(d[20]),"+f"(d[21]),"+f"(d[22]),"+f"(d[23]),
        "+f"(d[24]),"+f"(d[25]),"+f"(d[26]),"+f"(d[27]),"+f"(d[28]),"+f"(d[29]),"+f"(d[30]),"+f"(d[31]),
        "+f"(d[32]),"+f"(d[33]),"+f"(d[34]),"+f"(d[35]),"+f"(d[36]),"+f"(d[37]),"+f"(d[38]),"+f"(d[39]),
        "+f"(d[40]),"+f"(d[41]),"+f"(d[42]),"+f"(d[43]),"+f"(d[44]),"+f"(d[45]),"+f"(d[46]),"+f"(d[47]),
        "+f"(d[48]),"+f"(d[49]),"+f"(d[50]),"+f"(d[51]),"+f"(d[52]),"+f"(d[53]),"+f"(d[54]),"+f"(d[55]),
        "+f"(d[56]),"+f"(d[57]),"+f"(d[58]),"+f"(d[59]),"+f"(d[60]),"+f"(d[61]),"+f"(d[62]),"+f"(d[63]),
        "+f"(d[64]),"+f"(d[65]),"+f"(d[66]),"+f"(d[67]),"+f"(d[68]),"+f"(d[69]),"+f"(d[70]),"+f"(d[71]),
        "+f"(d[72]),"+f"(d[73]),"+f"(d[74]),"+f"(d[75]),"+f"(d[76]),"+f"(d[77]),"+f"(d[78]),"+f"(d[79]),
        "+f"(d[80]),"+f"(d[81]),"+f"(d[82]),"+f"(d[83]),"+f"(d[84]),"+f"(d[85]),"+f"(d[86]),"+f"(d[87]),
        "+f"(d[88]),"+f"(d[89]),"+f"(d[90]),"+f"(d[91]),"+f"(d[92]),"+f"(d[93]),"+f"(d[94]),"+f"(d[95])
      : "l"(da), "l"(db));
}
__device__ __forceinline__ void wgmma_rs_n128(float (&d)[64], uint32_t a0, uint32_t a1, uint32_t a2, uint32_t a3, uint64_t db, int sd = 1) {
  asm volatile("{.reg .pred p; setp.ne.b32 p, %69, 0;\n"
      "wgmma.mma_async.sync.aligned.m64n128k16.f32.bf16.bf16 {"
      "%0,%1,%2,%3,%4,%5,%6,%7,%8,%9,%10,%11,%12,%13,%14,%15,"
      "%16,%17,%18,%19,%20,%21,%22,%23,%24,%25,%26,%27,%28,%29,%30,%31,"
      "%32,%33,%34,%35,%36,%37,%38,%39,%40,%41,%42,%43,%44,%45,%46,%47,"
      "%48,%49,%50,%51,%52,%53,%54,%55,%56,%57,%58,%59,%60,%61,%62,%63"
      "}, {%64,%65,%66,%67}, %68, p, 1, 1, 1;}\n"
      : "+f"(d[0]),"+f"(d[1]),"+f"(d[2]),"+f"(d[3]),"+f"(d[4]),"+f"(d[5]),"+f"(d[6]),"+f"(d[7]),
        "+f"(d[8]),"+f"(d[9]),"+f"(d[10]),"+f"(d[11]),"+f"(d[12]),"+f"(d[13]),"+f"(d[14]),"+f"(d[15]),
        "+f"(d[16]),"+f"(d[17]),"+f"(d[18]),"+f"(d[19]),"+f"(d[20]),"+f"(d[21]),"+f"(d[22]),"+f"(d[23]),
        "+f"(d[24]),"+f"(d[25]),"+f"(d[26]),"+f"(d[27]),"+f"(d[28]),"+f"(d[29]),"+f"(d[30]),"+f"(d[31]),
        "+f"(d[32]),"+f"(d[33]),"+f"(d[34]),"+f"(d[35]),"+f"(d[36]),"+f"(d[37]),"+f"(d[38]),"+f"(d[39]),
        "+f"(d[40]),"+f"(d[41]),"+f"(d[42]),"+f"(d[43]),"+f"(d[44]),"+f"(d[45]),"+f"(d[46]),"+f"(d[47]),
        "+f"(d[48]),"+f"(d[49]),"+f"(d[50]),"+f"(d[51]),"+f"(d[52]),"+f"(d[53]),"+f"(d[54]),"+f"(d[55]),
        "+f"(d[56]),"+f"(d[57]),"+f"(d[58]),"+f"(d[59]),"+f"(d[60]),"+f"(d[61]),"+f"(d[62]),"+f"(d[63])
      : "r"(a0), "r"(a1), "r"(a2), "r"(a3), "l"(db), "r"(sd));
}
__device__ __forceinline__ void wgmma_rs_n256(float (&d)[128], uint32_t a0, uint32_t a1, uint32_t a2, uint32_t a3, uint64_t db, int sd = 1) {
  asm volatile("{.reg .pred p; setp.ne.b32 p, %133, 0;\n"
      "wgmma.mma_async.sync.aligned.m64n256k16.f32.bf16.bf16 {"
      "%0,%1,%2,%3,%4,%5,%6,%7,%8,%9,%10,%11,%12,%13,%14,%15,"
      "%16,%17,%18,%19,%20,%21,%22,%23,%24,%25,%26,%27,%28,%29,%30,%31,"
      "%32,%33,%34,%35,%36,%37,%38,%39,%40,%41,%42,%43,%44,%45,%46,%47,"
      "%48,%49,%50,%51,%52,%53,%54,%55,%56,%57,%58,%59,%60,%61,%62,%63,"
      "%64,%65,%66,%67,%68,%69,%70,%71,%72,%73,%74,%75,%76,%77,%78,%79,"
      "%80,%81,%82,%83,%84,%85,%86,%87,%88,%89,%90,%91,%92,%93,%94,%95,"
      "%96,%97,%98,%99,%100,%101,%102,%103,%104,%105,%106,%107,%108,%109,%110,%111,"
      "%112,%113,%114,%115,%116,%117,%118,%119,%120,%121,%122,%123,%124,%125,%126,%127"
      "}, {%128,%129,%130,%131}, %132, p, 1, 1, 1;}\n"
      : "+f"(d[0]),"+f"(d[1]),"+f"(d[2]),"+f"(d[3]),"+f"(d[4]),"+f"(d[5]),"+f"(d[6]),"+f"(d[7]),
        "+f"(d[8]),"+f"(d[9]),"+f"(d[10]),"+f"(d[11]),"+f"(d[12]),"+f"(d[13]),"+f"(d[14]),"+f"(d[15]),
        "+f"(d[16]),"+f"(d[17]),"+f"(d[18]),"+f"(d[19]),"+f"(d[20]),"+f"(d[21]),"+f"(d[22]),"+f"(d[23]),
        "+f"(d[24]),"+f"(d[25]),"+f"(d[26]),"+f"(d[27]),"+f"(d[28]),"+f"(d[29]),"+f"(d[30]),"+f"(d[31]),
        "+f"(d[32]),"+f"(d[33]),"+f"(d[34]),"+f"(d[35]),"+f"(d[36]),"+f"(d[37]),"+f"(d[38]),"+f"(d[39]),
        "+f"(d[40]),"+f"(d[41]),"+f"(d[42]),"+f"(d[43]),"+f"(d[44]),"+f"(d[45]),"+f"(d[46]),"+f"(d[47]),
        "+f"(d[48]),"+f"(d[49]),"+f"(d[50]),"+f"(d[51]),"+f"(d[52]),"+f"(d[53]),"+f"(d[54]),"+f"(d[55]),
        "+f"(d[56]),"+f"(d[57]),"+f"(d[58]),"+f"(d[59]),"+f"(d[60]),"+f"(d[61]),"+f"(d[62]),"+f"(d[63]),
        "+f"(d[64]),"+f"(d[65]),"+f"(d[66]),"+f"(d[67]),"+f"(d[68]),"+f"(d[69]),"+f"(d[70]),"+f"(d[71]),
        "+f"(d[72]),"+f"(d[73]),"+f"(d[74]),"+f"(d[75]),"+f"(d[76]),"+f"(d[77]),"+f"(d[78]),"+f"(d[79]),
        "+f"(d[80]),"+f"(d[81]),"+f"(d[82]),"+f"(d[83]),"+f"(d[84]),"+f"(d[85]),"+f"(d[86]),"+f"(d[87]),
        "+f"(d[88]),"+f"(d[89]),"+f"(d[90]),"+f"(d[91]),"+f"(d[92]),"+f"(d[93]),"+f"(d[94]),"+f"(d[95]),
        "+f"(d[96]),"+f"(d[97]),"+f"(d[98]),"+f"(d[99]),"+f"(d[100]),"+f"(d[101]),"+f"(d[102]),"+f"(d[103]),
        "+f"(d[104]),"+f"(d[105]),"+f"(d[106]),"+f"(d[107]),"+f"(d[108]),"+f"(d[109]),"+f"(d[110]),"+f"(d[111]),
        "+f"(d[112]),"+f"(d[113]),"+f"(d[114]),"+f"(d[115]),"+f"(d[116]),"+f"(d[117]),"+f"(d[118]),"+f"(d[119]),
        "+f"(d[120]),"+f"(d[121]),"+f"(d[122]),"+f"(d[123]),"+f"(d[124]),"+f"(d[125]),"+f"(d[126]),"+f"(d[127])
      : "r"(a0), "r"(a1), "r"(a2), "r"(a3), "l"(db), "r"(sd));
}
__device__ __forceinline__ void wgmma_rs_n192(float (&d)[96], uint32_t a0, uint32_t a1, uint32_t a2, uint32_t a3, uint64_t db) {
  asm volatile("wgmma.mma_async.sync.aligned.m64n192k16.f32.bf16.bf16 {"
      "%0,%1,%2,%3,%4,%5,%6,%7,%8,%9,%10,%11,%12,%13,%14,%15,"
      "%16,%17,%18,%19,%20,%21,%22,%23,%24,%25,%26,%27,%28,%29,%30,%31,"
      "%32,%33,%34,%35,%36,%37,%38,%39,%40,%41,%42,%43,%44,%45,%46,%47,"
      "%48,%49,%50,%51,%52,%53,%54,%55,%56,%57,%58,%59,%60,%61,%62,%63,"
      "%64,%65,%66,%67,%68,%69,%70,%71,%72,%73,%74,%75,%76,%77,%78,%79,"
      "%80,%81,%82,%83,%84,%85,%86,%87,%88,%89,%90,%91,%92,%93,%94,%95"
      "}, {%96,%97,%98,%99}, %100, 1, 1, 1, 1;\n"
      : "+f"(d[0]),"+f"(d[1]),"+f"(d[2]),"+f"(d[3]),"+f"(d[4]),"+f"(d[5]),"+f"(d[6]),"+f"(d[7]),
        "+f"(d[8]),"+f"(d[9]),"+f"(d[10]),"+f"(d[11]),"+f"(d[12]),"+f"(d[13]),"+f"(d[14]),"+f"(d[15]),
        "+f"(d[16]),"+f"(d[17]),"+f"(d[18]),"+f"(d[19]),"+f"(d[20]),"+f"(d[21]),"+f"(d[22]),"+f"(d[23]),
        "+f"(d[24]),"+f"(d[25]),"+f"(d[26]),"+f"(d[27]),"+f"(d[28]),"+f"(d[29]),"+f"(d[30]),"+f"(d[31]),
        "+f"(d[32]),"+f"(d[33]),"+f"(d[34]),"+f"(d[35]),"+f"(d[36]),"+f"(d[37]),"+f"(d[38]),"+f"(d[39]),
        "+f"(d[40]),"+f"(d[41]),"+f"(d[42]),"+f"(d[43]),"+f"(d[44]),"+f"(d[45]),"+f"(d[46]),"+f"(d[47]),
        "+f"(d[48]),"+f"(d[49]),"+f"(d[50]),"+f"(d[51]),"+f"(d[52]),"+f"(d[53]),"+f"(d[54]),"+f"(d[55]),
        "+f"(d[56]),"+f"(d[57]),"+f"(d[58]),"+f"(d[59]),"+f"(d[60]),"+f"(d[61]),"+f"(d[62]),"+f"(d[63]),
        "+f"(d[64]),"+f"(d[65]),"+f"(d[66]),"+f"(d[67]),"+f"(d[68]),"+f"(d[69]),"+f"(d[70]),"+f"(d[71]),
        "+f"(d[72]),"+f"(d[73]),"+f"(d[74]),"+f"(d[75]),"+f"(d[76]),"+f"(d[77]),"+f"(d[78]),"+f"(d[79]),
        "+f"(d[80]),"+f"(d[81]),"+f"(d[82]),"+f"(d[83]),"+f"(d[84]),"+f"(d[85]),"+f"(d[86]),"+f"(d[87]),
        "+f"(d[88]),"+f"(d[89]),"+f"(d[90]),"+f"(d[91]),"+f"(d[92]),"+f"(d[93]),"+f"(d[94]),"+f"(d[95])
      : "r"(a0), "r"(a1), "r"(a2), "r"(a3), "l"(db));
}


constexpr int C_LN = 0, C_PX = 16, C_PY = 32;
constexpr int NB_CONS = 1, NB_LN = 2, NB_LAG = 4, NB_INIT = 6, NB_RDY = 7;
constexpr int LAGX = 4;
constexpr int LAGY = 6;
constexpr int LAG2 = 5;
constexpr int NLL = 4;
constexpr int POLL_DELAY = 1150;
constexpr int POLL_DELAY2 = 1000;
constexpr int POLL_DELAY3 = 600;
constexpr int YD = 2;
constexpr int FILT_DELAY = 600;
constexpr int WARM = 4;
constexpr int ALEAD = 8;
constexpr int XTRIG = 20;
constexpr int HTRIG = 0;
constexpr int SM_E = 0, SM_X = 16384, SM_E2 = 32768, SM_W = 49152, SM_FC = 69632, SM_T = 73728 - T1_BYTES;
constexpr unsigned long long KORDER = 0xBA9432DC876510ull;
constexpr unsigned long long BSLOT = 0xA9854210DA9854ull, PSLOT = 0xB763CB763CB763ull;
constexpr unsigned long long BDEP = 0xFFEC97631ull, PDEP = 0xBA754ull;
constexpr uint32_t HI128 = desc_hi(1024, 1), HI64 = desc_hi(512, 2);

struct Bars {
  uint64_t full1[32], empty1[32], full2[16], fullA[8], empty2[8], emptyP[9], sig[2], done, fullP[32], hbar, tbar, hint[3], sbar;
  uint32_t epoch, pad;
};

template <int NK, bool STORE, int J0 = 0, int J1 = NK>
__device__ __forceinline__ void make_p(const float (&acc)[NK * 16], float r0, float r1, uint4 (&p)[NK], uint4* pbase, int ks0, uint32_t tag) {
#pragma unroll
  for (int j = J0; j < J1; j++) {
    uint32_t w[4];
#pragma unroll
    for (int i = 0; i < 4; i++) {
      const int a = 8 * j + 2 * i, b = a + NK * 8;
      w[i] = pack2(swiglu(acc[a], acc[b], (i & 1) ? r1 : r0), swiglu(acc[a + 1], acc[b + 1], (i & 1) ? r1 : r0));
    }
    asm volatile("" : "+r"(w[0]), "+r"(w[1]), "+r"(w[2]), "+r"(w[3]));
    p[j] = make_uint4(w[0], w[1], w[2], w[3]);
    if (STORE) st_tag(pbase + ((ks0 + j) >> 2) * 1024 + ((ks0 + j) & 3) * 32, p[j], tag);
  }
}
__device__ __forceinline__ void spin_until(uint32_t t) {
  while ((int)(clock32() - t) < 0) {}
}

__global__ void __cluster_dims__(2, 1, 1) __launch_bounds__(NTHREADS, 1)
fused_kernel(const __nv_bfloat16* __restrict__ x, const Tables* __restrict__ tab, Scratch* __restrict__ scr,
             __nv_bfloat16* __restrict__ out, const char* __restrict__ wg_raw, const char* __restrict__ wu_raw,
             const char* __restrict__ wd_raw,
             const __grid_constant__ CUtensorMap tmWR, const __grid_constant__ CUtensorMap tmWI,
             const __grid_constant__ CUtensorMap tmGX, const __grid_constant__ CUtensorMap tmUX,
             const __grid_constant__ CUtensorMap tmGY, const __grid_constant__ CUtensorMap tmUY,
             const __grid_constant__ CUtensorMap tmD) {
  extern __shared__ __align__(1024) char smem_raw[];
  const uint32_t sbase = s2u(smem_raw);
  const uint32_t sbar = sbase + 14 * SLOT, sstat = sbar + 1408;
  const int tid = threadIdx.x, lane = tid & 31;
  const int c = blockIdx.x, rk = c & 1, f = (c >> 1) & 7, rb = 2 * (c >> 4) + rk;
  const int rb2 = 2 * (c >> 4) + (f >> 2), kh = (f >> 1) & 1, nq = 2 * (f & 1) + rk;
#define BAR(field, i) (sbar + (uint32_t)offsetof(Bars, field) + 8u * (i))
#define TOFF(field) (sbase + SM_T + (uint32_t)offsetof(Tables, field) + lane * 16)

  if (tid >= 256) {
    asm volatile("setmaxnreg.dec.sync.aligned.u32 40;");
    const int warp = __shfl_sync(0xffffffffu, tid >> 5, 0);
    if (lane == 0) {
      auto init = [&](uint32_t b, int n, int count, int bytes) {
#pragma unroll
        for (int i = 0; i < n; i++) mbar_init(b + 8 * i, count);
#pragma unroll
        for (int i = 0; i < (bytes ? n : 0); i++) mbar_expect(b + 8 * i, bytes);
      };
      if (warp == 8) {
        if (sbase & 1023) die();
        init(BAR(tbar, 0), 1, 1, T2_BYTES + 2 * 10240);
        init(BAR(hbar, 0), 1, 1, 16384);
        init(BAR(hint, 0), 3, 1, 0);
        init(BAR(sbar, 0), 1, 32, 0);
        init(BAR(empty2, 0), 20, 8, 0);
      } else if (warp == 9) {
        init(BAR(full1, 0), 16, 1, 16384);
        init(BAR(full1, 16), 16, 1, 12288);
      } else if (warp == 10) {
        init(BAR(fullP, 0), 30, 1, 8192);
      } else {
        init(BAR(full2, 0), 24, 1, 16384);
        init(BAR(empty1, 0), 32, 16, 0);
      }
      asm volatile("fence.mbarrier_init.release.cluster;" ::: "memory");
    }
    if (tid == 256) {
      const int w0 = ((c >> 3) * 257 + 32 * (c & 7) + 1) & ~7;
      asm volatile("prefetch.tensormap [%0];" ::"l"(&tmWR) : "memory");
      asm volatile("prefetch.tensormap [%0];" ::"l"(&tmWI) : "memory");
      spin_until(clock32() + FILT_DELAY);
      tma3(sbase + SM_W, &tmWR, BAR(tbar, 0), w0, 0, 0);
      tma3(sbase + SM_W + 10240, &tmWI, BAR(tbar, 0), w0, 0, 0);
      bulk_load(sbase + SM_T + T1_BYTES, reinterpret_cast<const char*>(tab) + T1_BYTES, T2_BYTES, BAR(tbar, 0));
    }
    if (tid == 288) {
      asm volatile("prefetch.tensormap [%0];" ::"l"(rk ? &tmUX : &tmGX) : "memory");
      asm volatile("prefetch.tensormap [%0];" ::"l"(rk ? &tmUY : &tmGY) : "memory");
      asm volatile("prefetch.tensormap [%0];" ::"l"(&tmD) : "memory");
    }
    if (tid == 320) {
      const unsigned e = ld_relaxed(&scr->cnt[(C_LN + rb) * 32]) >> 3;
      asm volatile("st.shared.u32 [%0], %1;" ::"r"(BAR(epoch, 0)), "r"(e) : "memory");
    }
    __syncwarp();
    asm volatile("barrier.cluster.arrive.relaxed.aligned;" ::: "memory");
    bar_arrive(NB_RDY, 384);
    asm volatile("barrier.cluster.wait.aligned;" ::: "memory");
    bar_sync(NB_INIT, 384);
    unsigned epoch;
    asm volatile("ld.shared.u32 %0, [%1];" : "=r"(epoch) : "r"(BAR(epoch, 0)) : "memory");
    if (warp == 8) {
      if (lane == 0) {
        const int ax = (7 * f + 3 * (f & 1)) >> 1;
        const int ay = 7 * f + ((f & 1) ? 0 : 4);
        const CUtensorMap* tx = rk ? &tmUX : &tmGX;
        const CUtensorMap* ty = rk ? &tmUY : &tmGY;
        mbar_wait_bounded(BAR(sig, 0));
        uint32_t s = 2;
#pragma unroll 1
        for (int n = 0; n < 16; n++) {
          if (n >= 6) mbar_wait_bounded(BAR(empty1, n - 6));
          tma3_mc(sbase + (8 + s) * SLOT + rk * 8192, tx, BAR(full1, n), n * 32, ax);
          if (++s == 6) s = 0;
          if (n >= 10 && n < 15) {
            const int k = n - 10;
            tma3_mc(sbase + k * 12288 + rk * 6144, ty, BAR(full1, 16 + k), (k + 8) * 32, ay);
          }
        }
#pragma unroll 1
        for (int k = 5; k < 16; k++) {
          mbar_wait_bounded(BAR(empty1, k < 13 ? 10 + ((12 * (k - 5) + 11) >> 4) : 3 + k));
          tma3_mc(sbase + (k < 13 ? 8 * SLOT + (k - 5) * 12288 : (k - 13) * 12288) + rk * 6144, ty, BAR(full1, 16 + k), ((k + 8) & 15) * 32, ay);
        }
        mbar_wait_bounded(BAR(done, 0));
      }
    } else if (warp == 9) {
      if (lane == 0) {
        mbar_wait(BAR(fullA, 4));
        wait_counter(&scr->cnt[(C_LN + rb2) * 32], (epoch + 1) * 8);
        asm volatile("fence.proxy.async.global;" ::: "memory");
#pragma unroll 1
        for (int i = 0; i < 14; i++) {
          const int kblk = 14 * kh + (int)((KORDER >> (4 * i)) & 15);
          mbar_wait(i < 9 ? BAR(empty1, 16 + (uint32_t)((BDEP >> (4 * i)) & 15)) : BAR(empty2, i - 9));
          tma3(sbase + (uint32_t)((BSLOT >> (4 * i)) & 15) * SLOT, &tmD, BAR(full2, i), 0, 64 * kblk, 2 * nq);
        }
        mbar_wait(BAR(empty2, 5));
        bulk_load(sbase + 13 * SLOT, &scr->LN[(rb2 * 8 + 2 * nq) * 1024 + kh * 512], 8192, BAR(hbar, 0));
        bulk_load(sbase + 13 * SLOT + 8192, &scr->LN[(rb2 * 8 + 2 * nq + 1) * 1024 + kh * 512], 8192, BAR(hbar, 0));
      }
    } else if (warp == 10) {
      bar_sync(NB_LN, 288);
      if (lane == 0) {
        red_release(&scr->cnt[(C_LN + rb) * 32]);
        wait_counter(&scr->cnt[(C_LN + rb) * 32], (epoch + 1) * 8);
        asm volatile("fence.proxy.async.global;" ::: "memory");
#pragma unroll 1
        for (int kb = NLL; kb < 8; kb++) {
          if (2 * kb >= ALEAD) mbar_wait(BAR(empty1, 2 * kb - ALEAD));
          bulk_load(sbase + kb * SLOT, &scr->LN[(rb * 8 + kb) * 1024], 16384, BAR(fullA, kb));
        }
#pragma unroll 1
        for (int s = 0; s < 14; s++) {
          const int kblk = 14 * kh + (int)((KORDER >> (4 * s)) & 15);
          if (s == 0 || s == 8 || s == 11) {
            mbar_wait(BAR(hint, s == 0 ? 0 : s == 8 ? 1 : 2));
          }
          mbar_wait(s < 5 ? BAR(empty1, 16 + (uint32_t)((PDEP >> (4 * s)) & 15)) : BAR(emptyP, s - 5));
          bulk_load_mc(sbase + (uint32_t)((PSLOT >> (4 * s)) & 15) * SLOT + rk * 8192, &scr->P[(rb2 * 28 + kblk) * 1024 + rk * 512], 8192, BAR(fullP, 16 * rk + s));
        }
      }
    } else {
      if (lane == 0) {
        mbar_wait(BAR(sig, 1));
        l2_prefetch(wg_raw + (size_t)c * 5376, 5376);
        l2_prefetch(wu_raw + (size_t)c * 5376, 5376);
        mbar_wait(BAR(sig, 0));
        l2_prefetch(wg_raw + 688128 + (size_t)c * 8960, 8960);
        l2_prefetch(wu_raw + 688128 + (size_t)c * 8960, 8960);
      }
      mbar_wait(BAR(fullA, 4));
      if (lane == 0) l2_prefetch(wd_raw + (size_t)c * 14336, 14336);
      {
        const uint32_t tag = (epoch + 1) & 1;
        uint4 v0, v1, v2;
        while (true) {
          v0 = ld_b128(&scr->ST[rb * 64 + lane]);
          v1 = ld_b128(&scr->ST[rb * 64 + 32 + lane]);
          v2 = ld_b128(&scr->ST[rb2 * 64 + 32 * kh + lane]);
          if (!__any_sync(0xffffffffu, ((v0.x ^ tag) | (v1.x ^ tag) | (v2.x ^ tag)) & 1u)) break;
        }
        sts4(sstat + lane * 16, v0.x & ~1u, v0.y, v0.z, v0.w);
        sts4(sstat + 512 + lane * 16, v1.x & ~1u, v1.y, v1.z, v1.w);
        sts4(sstat + 1024 + lane * 16, v2.x & ~1u, v2.y, v2.z, v2.w);
        mbar_arrive(BAR(sbar, 0));
      }
      if (lane == 0) {
        mbar_wait(BAR(empty1, XTRIG));
        while ((int)(ld_relaxed(&scr->cnt[(C_PX + rb2) * 32 + kh]) - (epoch + 1) * 32) < 0) {
        }
        mbar_arrive(BAR(hint, 0));
        mbar_wait(BAR(emptyP, HTRIG));
        uint32_t done = 0;
        while (done != 3) {
          uint2 v;
          asm volatile("ld.relaxed.gpu.global.v2.u32 {%0,%1}, [%2];" : "=r"(v.x), "=r"(v.y) : "l"(&scr->cnt[(C_PY + rb2) * 32 + 4 * (rk ^ kh ^ 1) + 2 * kh]) : "memory");
          if (!(done & 1) && (int)(v.x - (epoch + 1) * 8) >= 0) { done |= 1; mbar_arrive(BAR(hint, 1)); }
          if (!(done & 2) && (int)(v.y - (epoch + 1) * 8) >= 0) { done |= 2; mbar_arrive(BAR(hint, 2)); }
        }
      }
    }
  } else {
    const int warp = __shfl_sync(0xffffffffu, tid >> 5, 0);
    const int g = lane >> 2, t = lane & 3;
    uint4 fa[4], fb[4], tw[6];
#pragma unroll
    for (int i = 0; i < 4; i++) fa[i] = ldg_ca4(&tab->fa[i][lane][0]);
#pragma unroll
    for (int i = 0; i < 6; i++) tw[i] = ldg_ca4(&tab->tw1[i][lane][0]);
#pragma unroll
    for (int i = 0; i < 4; i++) fb[i] = ldg_ca4(&tab->fb[i][lane][0]);
#pragma unroll
    for (int i = 0; i < 4; i++) {
      const int r = i >> 1, ch = (i & 1) * 32 + lane;
      cp_async16(sbase + SM_X + (2 * warp + r) * 1024 + ((ch ^ ((ch >> 3) & 1)) * 16),
                 x + (size_t)(c + 128 * (2 * warp + r)) * 512 + ch * 8);
    }
    asm volatile("cp.async.commit_group;" ::: "memory");
    asm volatile("barrier.cluster.arrive.relaxed.aligned;" ::: "memory");
    uint32_t rbar;
    asm volatile("mapa.shared::cluster.u32 %0, %1, %2;" : "=r"(rbar) : "r"(sbar), "r"(rk ^ 1));
#define RBAR(field, i) (rbar + (uint32_t)offsetof(Bars, field) + 8u * (i))
    {
      const int ln = (tid >> 1) & 31, lg = ln >> 2, lt = ln & 3, i = 4 * (tid >> 6) + 2 * (tid & 1);
      const int kidx = lt + 8 * (i >> 3), nidx = 4 * ((i >> 1) & 3) + (lg >> 1);
      const uint32_t a0 = cfrag<2048>((c + 128 * kidx) * nidx, lg & 1), a1 = cfrag<2048>((c + 128 * (kidx + 4)) * nidx, lg & 1);
      const uint32_t b0 = cfrag<2048>(-(c + 128 * nidx) * kidx, lg & 1), b1 = cfrag<2048>(-(c + 128 * nidx) * (kidx + 4), lg & 1);
      asm volatile("st.shared.v2.u32 [%0], {%1,%2};" ::"r"(sbase + SM_FC + tid * 8), "r"(a0), "r"(a1) : "memory");
      asm volatile("st.shared.v2.u32 [%0], {%1,%2};" ::"r"(sbase + SM_FC + 2048 + tid * 8), "r"(b0), "r"(b1) : "memory");
    }
    bar_sync(NB_CONS, 256);
    uint4 fc[4];
#pragma unroll
    for (int i = 0; i < 4; i++) fc[i] = lds4(sbase + SM_FC + i * 512 + lane * 16);
    asm volatile("cp.async.wait_group 0;" ::: "memory");
    __syncwarp();
    bar_arrive(NB_INIT, 384);
    uint32_t tag, ones;
    uint4 q[4], o[4];
    {
      uint32_t v[2][8];
#pragma unroll
      for (int r = 0; r < 2; r++)
#pragma unroll
        for (int ks = 0; ks < 2; ks++) {
          const int ch = 32 * ks + 2 * (lane & 15) + (lane >> 4);
          asm volatile("ldmatrix.sync.aligned.m8n8.x4.trans.shared.b16 {%0,%1,%2,%3}, [%4];"
                       : "=r"(v[r][4 * ks]), "=r"(v[r][4 * ks + 1]), "=r"(v[r][4 * ks + 2]), "=r"(v[r][4 * ks + 3])
                       : "r"(sbase + SM_X + (2 * warp + r) * 1024 + ((ch ^ ((ch >> 3) & 1)) * 16)) : "memory");
        }
      float sq[2];
#pragma unroll
      for (int r = 0; r < 2; r++) {
        float s0 = 0.f, s1 = 0.f;
#pragma unroll
        for (int i = 0; i < 8; i++) {
          const float lo = bf_lo(v[r][i]), hi = u2f(v[r][i] & 0xffff0000u);
          s0 = fmaf(lo, lo, s0);
          s1 = fmaf(hi, hi, s1);
        }
        sq[r] = s0 + s1;
      }
      {
        float w = ((lane & 1) ? sq[1] : sq[0]) + __shfl_xor_sync(0xffffffffu, (lane & 1) ? sq[0] : sq[1], 1);
        w += __shfl_xor_sync(0xffffffffu, w, 2);
        w = sum_groups(w);
        const float o2 = __shfl_xor_sync(0xffffffffu, w, 1);
        sq[0] = (lane & 1) ? o2 : w;
        sq[1] = (lane & 1) ? w : o2;
      }
#pragma unroll
      for (int r = 0; r < 2; r++) {
        float dd[2][4], ee[2][4];
#pragma unroll
        for (int nt = 0; nt < 2; nt++) {
          mma_az(dd[nt], fa[0], v[r][2 * nt], v[r][2 * nt + 1]);
          mma_a(dd[nt], fa[1], v[r][4 + 2 * nt], v[r][5 + 2 * nt]);
          mma_az(ee[nt], fa[2], v[r][2 * nt], v[r][2 * nt + 1]);
          mma_a(ee[nt], fa[3], v[r][4 + 2 * nt], v[r][5 + 2 * nt]);
        }
        float mean = (dd[0][0] + dd[0][1]) + (dd[1][0] + dd[1][1]);
        mean += __shfl_xor_sync(0xffffffffu, mean, 1);
        mean += __shfl_xor_sync(0xffffffffu, mean, 2);
        mean = __shfl_sync(0xffffffffu, mean, 0) * (1.f / 512.f);
        const float rs = rsqrtf(fmaxf(fmaf(-mean, mean, sq[r] * (1.f / 512.f)), 0.f) + 1e-5f);
        float acc[4][4];
#pragma unroll
        for (int nt = 0; nt < 2; nt++) {
          const float (&d)[4] = dd[nt];
          const float (&e)[4] = ee[nt];
          const uint4 &ka = tw[2 * nt], &kb = tw[2 * nt + 1], &kc = tw[4 + nt];
          const uint32_t a0 = pack2(d[0] * u2f(ka.x) + d[2] * u2f(ka.y), d[1] * u2f(kb.x) + d[3] * u2f(kb.y));
          const uint32_t a2 = pack2(d[0] * u2f(ka.z) + d[2] * u2f(ka.w), d[1] * u2f(kb.z) + d[3] * u2f(kb.w));
          const uint32_t a1 = pack2(e[0] * u2f(kc.x) + e[2] * u2f(kc.y), e[1] * u2f(kc.z) + e[3] * u2f(kc.w));
          const uint32_t a3 = pack2(e[2] * u2f(kc.x) - e[0] * u2f(kc.y), e[3] * u2f(kc.z) - e[1] * u2f(kc.w));
          const uint32_t dc = pack2(fmaf(mean, -32.f, d[0]), fmaf(mean, -32.f, d[1]));
          const uint32_t h0 = g == 0 ? dc : a0, h2 = g == 0 ? 0u : a2;
          if (nt == 0) {
            mma16816_z(acc[0], a0, a1, a2, a3, fb[2 * nt].x, fb[2 * nt].y);
            mma16816_z(acc[1], a0, a1, a2, a3, fb[2 * nt].z, fb[2 * nt].w);
            mma16816_z(acc[2], h0, a1, h2, a3, fb[2 * nt + 1].x, fb[2 * nt + 1].y);
            mma16816_z(acc[3], h0, a1, h2, a3, fb[2 * nt + 1].z, fb[2 * nt + 1].w);
          } else {
            mma16816(acc[0], a0, a1, a2, a3, fb[2 * nt].x, fb[2 * nt].y);
            mma16816(acc[1], a0, a1, a2, a3, fb[2 * nt].z, fb[2 * nt].w);
            mma16816(acc[2], h0, a1, h2, a3, fb[2 * nt + 1].x, fb[2 * nt + 1].y);
            mma16816(acc[3], h0, a1, h2, a3, fb[2 * nt + 1].z, fb[2 * nt + 1].w);
          }
        }
#pragma unroll
        for (int h = 0; h < 2; h++) {
          const int j = 2 * warp + r, m = 2 * t + h;
          sts4(sbase + SM_E + ((j * 8 + m) * 8 + (g ^ (2 * t) ^ (2 * (j & 3)))) * 16,
               pack2(acc[h][0] * rs, acc[h][1] * rs), pack2(acc[h][2] * rs, acc[h][3] * rs),
               pack2(acc[2 + h][0] * rs, acc[2 + h][1] * rs), pack2(acc[2 + h][2] * rs, acc[2 + h][3] * rs));
        }
      }
      bar_sync(NB_RDY, 384);
      const uint32_t ea = sbase + SM_E + ((t * 8 + warp) * 8 + (g ^ (warp & 6) ^ (2 * t))) * 16;
      lds_frag(q[0], q[1], ea, ea + 4096);
      lds_frag(q[2], q[3], ea + 8192, ea + 12288);
      asm volatile("ld.shared.u32 %0, [%1];" : "=r"(tag) : "r"(BAR(epoch, 0)) : "memory");
      ones = ~(tag >> 31);
      tag = (tag + 1) & 1;
      cdft16(q, fc, o);
#pragma unroll
      for (int vv = 0; vv < 4; vv++) {
        o[vv].y &= ~1u;
        o[vv].z = (o[vv].z & ~1u) | (tag ^ 1);
        st_tag(&scr->Z1[(((4 * vv + t) * 8 + warp) * 128 + c) * 8 + g], o[vv], tag);
      }
    }
    asm volatile("setmaxnreg.inc.sync.aligned.u32 232;");
    {
      uint4* const zp = &scr->Z1[(c * 128 + 8 * t + warp) * 8 + g];
      const uint32_t tst = clock32();
      mbar_wait(BAR(tbar, 0));
      uint4 f2[4], g2[4];
#pragma unroll
      for (int i = 0; i < 4; i++) {
        f2[i] = lds4(TOFF(f2) + warp * 2048 + i * 512);
        g2[i] = lds4(TOFF(g2) + warp * 2048 + i * 512);
      }
      const uint4 f8 = lds4(TOFF(f8)), g8 = lds4(TOFF(g8));
      asm volatile("barrier.cluster.wait.aligned;" ::: "memory");
      spin_until(tst + POLL_DELAY);
      ld_tag4_issue<256>(q, zp);
      float wfr[16], wfi[16];
      {
        const float nyq = ((c & 7) == 7 && g == 0) ? 0.5f : 1.f;
        uint32_t wa = sbase + SM_W + (16 * warp + t) * 80 + ((2 * (c >> 3) + 2) & 15) - 2;
        asm volatile("" : "+r"(wa));
        const uint32_t wb[3] = {wa + 2 * (g == 0 ? 16 : g), wa + 2 * g, wa - 2 * g};
#pragma unroll
        for (int i = 0; i < 16; i++) {
          const int ci = i >> 3, dd = (i >> 2) & 1, e = i & 3;
          const uint32_t a = wb[e < 2 ? e : 2] + (ci * 8 + 4 * dd) * 80 + (e == 0 ? 0 : e == 1 ? 16 : e == 2 ? 64 : 48);
          wfr[i] = bf_lo(lds_u16(a)) * (e == 2 ? nyq : 1.f);
          wfi[i] = bf_lo(lds_u16(a + 10240)) * (e == 2 ? nyq : 1.f);
        }
      }
      ld_tag4_finish<256>(q, zp, tag);
      if (lane == 0) mbar_arrive(BAR(sig, 1));
#pragma unroll
      for (int i = 0; i < 4; i++) q[i].z &= ~1u;
      reg_frag(q, ones);
      cdft16(q, f2, o);
      const uint32_t e2 = sbase + SM_E2;
#pragma unroll
      for (int vv = 0; vv < 4; vv++)
        sts4(e2 + ((warp * 16 + 4 * vv + t) * 8 + (g ^ (2 * t) ^ (2 * (warp & 3)))) * 16, o[vv].x, o[vv].y, o[vv].z, o[vv].w);
      bar_sync(NB_CONS, 256);
      uint32_t ad[2], res[2][2][4];
#pragma unroll
      for (int ci = 0; ci < 2; ci++) {
        const int cc = 2 * warp + ci;
        ad[ci] = e2 + ((t * 16 + cc) * 8 + (g ^ (2 * (cc & 3)) ^ (2 * t))) * 16;
        lds_frag(q[2 * ci], q[2 * ci + 1], ad[ci], ad[ci] + 8192);
      }
#pragma unroll
      for (int ci = 0; ci < 2; ci++)
#pragma unroll
        for (int p = 0; p < 2; p++) {
          uint32_t y[2][2];
#pragma unroll
          for (int vv = 0; vv < 2; vv++) {
            float d[4];
            mma_az(d, q[2 * ci + p], word(f8, 2 * vv), word(f8, 2 * vv + 1));
#pragma unroll
            for (int rr = 0; rr < 2; rr++) {
              const float fr = wfr[ci * 8 + vv * 4 + 2 * p + rr], fi = wfi[ci * 8 + vv * 4 + 2 * p + rr];
              y[vv][rr] = pack2(d[2 * rr] * fr - d[2 * rr + 1] * fi, d[2 * rr] * fi + d[2 * rr + 1] * fr);
            }
          }
#pragma unroll
          for (int vv = 0; vv < 2; vv++) {
            float d[4];
            mma16816_z(d, y[0][0], y[0][1], y[1][0], y[1][1], word(g8, 2 * vv), word(g8, 2 * vv + 1));
            res[ci][vv][2 * p] = pack2(d[0], d[1]);
            res[ci][vv][2 * p + 1] = pack2(d[2], d[3]);
          }
        }
#pragma unroll
      for (int i = 0; i < 4; i++)
        sts4(ad[i >> 1] + (i & 1) * 8192, res[i >> 1][i & 1][0], res[i >> 1][i & 1][1], res[i >> 1][i & 1][2], res[i >> 1][i & 1][3]);
      bar_sync(NB_CONS, 256);
      const uint32_t eb = e2 + ((warp * 16 + t) * 8 + (g ^ (2 * t) ^ (2 * (warp & 3)))) * 16;
      lds_frag(q[0], q[1], eb, eb + 512);
      lds_frag(q[2], q[3], eb + 1024, eb + 1536);
      cdft16(q, g2, o);
#pragma unroll
      for (int vv = 0; vv < 4; vv++) {
        o[vv].y &= ~1u;
        o[vv].z = (o[vv].z & ~1u) | tag;
        st_tag(zp + vv * 256, o[vv], tag);
      }
    }
    {
      const uint4* const zp = &scr->Z1[((t * 8 + warp) * 128 + c) * 8 + g];
      const uint32_t tst = clock32();
      uint4 gb[4], ga[4], gc[4], tw[4];
      uint2 xr[2][4];
      uint2* lnp[2];
#pragma unroll
      for (int r = 0; r < 2; r++) {
        const int row = 16 * f + 2 * warp + r;
        lnp[r] = reinterpret_cast<uint2*>(&scr->LN[(rb * 8 + (g >> 2)) * 1024 + row * 8 + ((2 * (g & 3) + (t >> 1)) ^ (row & 7))]) + (t & 1);
        asm volatile("" : "+l"(lnp[r]));
      }
#pragma unroll
      for (int i = 0; i < 4; i++) {
        gc[i] = lds4(sbase + SM_FC + 2048 + i * 512 + lane * 16);
        gb[i] = lds4(TOFF(gb) + i * 512);
        ga[i] = lds4(TOFF(ga) + i * 512);
        tw[i] = lds4(TOFF(tw3) + i * 512);
        const int ch = 2 * (g + 8 * i) + (t >> 1);
#pragma unroll
        for (int r = 0; r < 2; r++) xr[r][i] = lds2(sbase + SM_X + (2 * warp + r) * 1024 + ((ch ^ ((ch >> 3) & 1)) * 16) + (t & 1) * 8);
      }
      spin_until(tst + POLL_DELAY2);
      ld_tag4_issue<32768>(q, zp);
      ld_tag4_finish<32768, true>(q, zp, tag);
      if (lane == 0) mbar_arrive(BAR(sig, 0));
      reg_frag(q, ones);
      cdft16(q, gc, o);
#pragma unroll
      for (int vv = 0; vv < 4; vv++)
        sts4(sbase + SM_E + (((4 * vv + t) * 8 + warp) * 8 + (g ^ (warp & 6) ^ (2 * t))) * 16, o[vv].x, o[vv].y, o[vv].z, o[vv].w);
      bar_sync(NB_CONS, 256);
      uint32_t hv[2][8];
      const float mk = t == 0 ? 0.f : 1.f;
#pragma unroll
      for (int r = 0; r < 2; r++) {
        const int j = 2 * warp + r;
        uint4 u[2];
#pragma unroll
        for (int h = 0; h < 2; h++) u[h] = lds4(sbase + SM_E + ((j * 8 + 2 * t + h) * 8 + (g ^ (2 * t) ^ (2 * (j & 3)))) * 16);
        const uint32_t bp[4][2] = {{u[0].x, u[1].x & ones}, {u[0].y & ones, u[1].y}, {u[0].z, u[1].z & ones}, {u[0].w & ones, u[1].w}};
        float y[2][2][4];
#pragma unroll
        for (int i = 0; i < 2; i++) {
          float lo[4], hi[4], e[4];
          mma_az(lo, gb[2 * i], bp[0][0], bp[0][1]);
          mma_az(hi, gb[2 * i + 1], bp[2][0], bp[2][1]);
          mma_az(e, gb[2 * i], bp[1][0], bp[1][1]);
          mma_a(e, gb[2 * i + 1], bp[3][0], bp[3][1]);
          const uint4 &ka = tw[2 * i], &kb = tw[2 * i + 1];
          const float tr0 = fmaf(hi[0], mk, lo[0]), ti0 = fmaf(hi[2], mk, lo[2]);
          const float tr1 = lo[1] + hi[1], ti1 = lo[3] + hi[3];
          const float vr0 = tr0 * u2f(ka.x) - ti0 * u2f(ka.y), vi0 = tr0 * u2f(ka.y) + ti0 * u2f(ka.x);
          const float vr1 = tr1 * u2f(ka.z) - ti1 * u2f(ka.w), vi1 = tr1 * u2f(ka.w) + ti1 * u2f(ka.z);
          const uint32_t b0 = pack2(t == 0 ? hi[0] : vr0, vr1), b1 = pack2(t == 0 ? vr0 : vi0, vi1);
          const uint32_t b2 = pack2(e[0] * u2f(kb.x) - e[2] * u2f(kb.y), e[1] * u2f(kb.z) - e[3] * u2f(kb.w));
          const uint32_t b3 = pack2(e[0] * u2f(kb.y) + e[2] * u2f(kb.x), e[1] * u2f(kb.w) + e[3] * u2f(kb.z));
#pragma unroll
          for (int mt = 0; mt < 2; mt++) {
            mma_az(y[mt][i], ga[2 * mt], b0, b1);
            mma_a(y[mt][i], ga[2 * mt + 1], b2, b3);
          }
        }
#pragma unroll
        for (int i = 0; i < 4; i++) {
          hv[r][2 * i] = hadd2_bf16(xr[r][i].x, pack2(y[i >> 1][0][2 * (i & 1)], y[i >> 1][0][2 * (i & 1) + 1]));
          hv[r][2 * i + 1] = hadd2_bf16(xr[r][i].y, pack2(y[i >> 1][1][2 * (i & 1)], y[i >> 1][1][2 * (i & 1) + 1]));
        }
      }
      uint32_t mb[2], ml[2];
#pragma unroll
      for (int r = 0; r < 2; r++) {
        const float mean = sum_groups(quad_sum(hv[r])) * (1.f / 512.f);
        mb[r] = pack2(mean, mean);
        ml[r] = pack2(mean - bf_lo(mb[r]), mean - bf_lo(mb[r])) & 0xfffefffeu;
      }
#pragma unroll
      for (int i = 0; i < 4; i++)
#pragma unroll
        for (int r = 0; r < 2; r++) {
          hv[r][2 * i] = hsub2_bf16(hsub2_bf16(hv[r][2 * i], mb[r]), ml[r]);
          hv[r][2 * i + 1] = hsub2_bf16(hsub2_bf16(hv[r][2 * i + 1], mb[r]), ml[r]);
          st_tag8(lnp[r] + i * 4096, hv[r][2 * i], hv[r][2 * i + 1], i < 2 ? tag : (hv[r][2 * i] & 1u));
        }
      bar_arrive(NB_LN, 288);
      const uint32_t ones2 = ~(lds2(BAR(epoch, 0)).x >> 31);
      float rstd[2];
#pragma unroll
      for (int r = 0; r < 2; r++) {
        hv[r][0] &= ones2;
        rstd[r] = row_rstd(hv[r]);
      }
      if (lane == 0)
        st_tag(&scr->ST[rb * 64 + 8 * f + warp], make_uint4(__byte_perm(ml[0], mb[0], 0x5410), __float_as_uint(rstd[0]), __byte_perm(ml[1], mb[1], 0x5410), __float_as_uint(rstd[1])), tag);
    }
    const int wgi = warp >> 2, wq = warp & 3;
    const int wr = wgi ^ (f >> 2) ^ 1, rt = 4 * wr + wq;
    uint4* const pbase = &scr->P[rb * 28 * 1024 + rt * 128 + lane];
    const uint32_t a_lo0 = desc_lo(sbase + wr * 8192, 16);
    const uint32_t ebar = lane == 0 ? BAR(empty1, 0) : RBAR(empty1, 0);
    float r0, r1;
    uint4 px[8], py[6];
    const int rh = wgi ^ kh ^ 1;
    const uint32_t fpb = BAR(fullP, 16 * rh);
    const uint4* const psrc = &scr->P[(rb2 * 28 + 14 * kh) * 1024 + (4 * rh + wq) * 128 + lane];
    const uint32_t pa0 = sbase + (4 * rh + wq) * 2048;
    uint4 pf[3][4], ha[4][4];
    uint32_t rdy = 0, got0;
    {
      float acc[128];
#pragma unroll
      for (int i = 0; i < 128; i++) acc[i] = 0.f;
      const uint32_t b_lo0 = desc_lo(sbase + 8 * SLOT, 4096);
      const uint32_t t3 = clock32();
      if (WARM) {
        wg_fence();
#pragma unroll
        for (int i = 0; i < WARM; i++) wgmma_n256(acc, desc64(a_lo0 + 6 * 1024, HI128), desc64(b_lo0, HI128));
        wg_commit();
      }
      const uint4* const ap = &scr->LN[rb * 8 * 1024 + rt * 128 + lane];
      const uint32_t sa = sbase + rt * 2048, amask = (lane & 1) ? ~0u : ~1u;
      auto fetch_a = [&](int kb) {
#pragma unroll
        for (int i = 0; i < 4; i++) cp_async16(sa + kb * SLOT + (lane + 32 * i) * 16, ap + kb * 1024 + 32 * i);
        asm volatile("cp.async.commit_group;" ::: "memory");
      };
      auto load_a = [&](int kb) {
#pragma unroll
        for (int ks = 0; ks < 4; ks++)
          asm volatile("ldmatrix.sync.aligned.m8n8.x4.shared.b16 {%0,%1,%2,%3}, [%4];"
                       : "=r"(ha[kb][ks].x), "=r"(ha[kb][ks].y), "=r"(ha[kb][ks].z), "=r"(ha[kb][ks].w)
                       : "r"(sa + kb * SLOT + (lane & 15) * 128 + (((2 * ks + (lane >> 4)) ^ (lane & 7)) * 16)) : "memory");
      };
      auto check_a = [&](int kb) {
        int it = 0;
#pragma unroll 1
        while (true) {
          uint32_t m = 0;
#pragma unroll
          for (int ks = 0; ks < 4; ks++) m |= tag_miss(ha[kb][ks].x, ha[kb][ks].y, ha[kb][ks].z, ha[kb][ks].w, tag);
          if (!__any_sync(0xffffffffu, m & ~amask)) break;
          fetch_a(kb);
          asm volatile("cp.async.wait_group 0;" ::: "memory");
          __syncwarp();
          load_a(kb);
          if (++it > SPIN_LIMIT) { die(); break; }
        }
#pragma unroll
        for (int ks = 0; ks < 4; ks++)
          asm volatile("and.b32 %0, %0, %4; and.b32 %1, %1, %4; and.b32 %2, %2, %4; and.b32 %3, %3, %4;"
                       : "+r"(ha[kb][ks].x), "+r"(ha[kb][ks].y), "+r"(ha[kb][ks].z), "+r"(ha[kb][ks].w) : "r"(amask));
      };
      bar_sync(NB_CONS, 256);
      spin_until(t3 + POLL_DELAY3);
      fetch_a(0);
      fetch_a(1);
      asm volatile("cp.async.wait_group 1;" ::: "memory");
      __syncwarp();
      load_a(0);
#pragma unroll
      for (int n = 0; n < 8; n++) {
        const int kb = n >> 1, hh = n & 1;
        if (hh == 0) {
          check_a(kb);
          if (kb < 2) fetch_a(kb + 2);
        }
        if (hh == 1 && kb < 3) {
          if (kb < 2) asm volatile("cp.async.wait_group 1;" ::: "memory");
          else asm volatile("cp.async.wait_group 0;" ::: "memory");
          __syncwarp();
        }
        if (!rdy) mbar_wait(BAR(full1, n));
        const uint32_t bl = b_lo0 + ((n + 2) % 6) * 1024;
        wg_fence();
        if (hh == 1 && kb < 3) load_a(kb + 1);
        rdy = mbar_test(BAR(full1, n + 1));
        const uint4 &a0 = ha[kb][2 * hh], &a1 = ha[kb][2 * hh + 1];
        wgmma_rs_n256(acc, a0.x, a0.y, a0.z, a0.w, desc64(bl, HI128), n != 0 ? 1 : ~ones);
        wgmma_rs_n256(acc, a1.x, a1.y, a1.z, a1.w, desc64(bl + 128, HI128));
        wg_commit();
        wg_wait<1>();
        if (n != 0 && lane < 2) mbar_arrive_remote(ebar + 8 * (n - 1));
      }
      uint32_t slot = 4;
#pragma unroll 1
      for (int kb = 4; kb < 8; kb++) {
        mbar_wait(BAR(fullA, kb));
#pragma unroll
        for (int hh = 0; hh < 2; hh++) {
          if (hh == ((16 - LAGX) & 1) && kb == ((16 - LAGX) >> 1) && wgi == 1) bar_sync(NB_LAG, 256);
          mbar_wait(BAR(full1, 2 * kb + hh));
          const uint32_t al = a_lo0 + kb * 1024 + hh * 4, bl = b_lo0 + slot * 1024;
          wg_fence();
          wgmma_n256(acc, desc64(al, HI128), desc64(bl, HI128));
          wgmma_n256(acc, desc64(al + 2, HI128), desc64(bl + 128, HI128));
          wg_commit();
          if (hh == 1 && kb == 7 && wgi == 0) bar_arrive(NB_LAG, 256);
          wg_wait<1>();
          if (lane < 2) mbar_arrive_remote(ebar + 8 * (2 * kb + hh - 1));
          if (++slot == 6) slot = 0;
        }
      }
      mbar_wait(BAR(sbar, 0));
      r0 = __uint_as_float(lds2(sstat + (16 * rt + g) * 8).y);
      r1 = __uint_as_float(lds2(sstat + (16 * rt + g + 8) * 8).y);
      wg_wait<0>();
      if (lane < 2) mbar_arrive_remote(ebar + 8 * 15);
      make_p<8, false>(acc, r0, r1, px, pbase, 0, tag);
    }
    {
      float acc[96];
#pragma unroll
      for (int i = 0; i < 96; i++) acc[i] = 0.f;
      const uint32_t b_lo0 = desc_lo(sbase, 2048);
      uint4* const pdst = pbase + ((7 * f + 3 * (f & 1)) >> 1) * 1024;
      auto stage_y = [&](int k) {
        if (k < 4) mbar_wait_bounded(BAR(full1, 16 + k));
        else mbar_wait(BAR(full1, 16 + k));
        const uint32_t al = a_lo0 + (4 + (k >> 1)) * 1024 + (k & 1) * 4, bl = b_lo0 + (k < 5 ? k * 768 : 8192 + (k - 5) * 768);
        wg_fence();
        wgmma_n192(acc, desc64(al, HI128), desc64(bl, HI64));
        wgmma_n192(acc, desc64(al + 2, HI128), desc64(bl + 64, HI64));
        wg_commit();
      };
#pragma unroll
      for (int k = 0; k < 4; k++) {
        stage_y(k);
        st_tag(pdst + (k >> 1) * 1024 + (k & 1) * 64, px[2 * k], tag);
        st_tag(pdst + (k >> 1) * 1024 + (k & 1) * 64 + 32, px[2 * k + 1], tag);
        if (k == 3 && lane == 0) red_relaxed(&scr->cnt[(C_PX + rb) * 32 + (f >> 2)]);
        wg_wait<1>();
        if (k != 0 && lane < 2) mbar_arrive_remote(ebar + 8 * (15 + k));
      }
#pragma unroll 1
      for (int k = 4; k < 8; k++) {
        stage_y(k);
        wg_wait<1>();
        if (k != 0 && lane < 2) mbar_arrive_remote(ebar + 8 * (15 + k));
      }
      rdy = 0;
#pragma unroll
      for (int k = 8; k < 16; k++) {
        if (k == 16 - LAGY && wgi == 1) bar_sync(NB_LAG, 256);
        if (!rdy) mbar_wait(BAR(full1, 16 + k));
        const uint32_t bl = b_lo0 + (k < 13 ? 8192 + (k - 5) * 768 : (k - 13) * 768);
        const uint4 &a0 = ha[(k - 8) >> 1][2 * (k & 1)], &a1 = ha[(k - 8) >> 1][2 * (k & 1) + 1];
        wg_fence();
        if (k < 15) rdy = mbar_test(BAR(full1, 17 + k));
        wgmma_rs_n192(acc, a0.x, a0.y, a0.z, a0.w, desc64(bl, HI64));
        wgmma_rs_n192(acc, a1.x, a1.y, a1.z, a1.w, desc64(bl + 64, HI64));
        wg_commit();
        if (YD == 1 && k == 15 && wgi == 0) bar_arrive(NB_LAG, 256);
        wg_wait<YD>();
        if (k - YD >= 7 && lane < 2) mbar_arrive_remote(ebar + 8 * (16 + k - YD));
      }
      if (YD > 2) {
        wg_wait<2>();
        if (lane < 2) mbar_arrive_remote(ebar + 8 * 29);
      }
      if (YD > 1) {
        if (wgi == 0) bar_arrive(NB_LAG, 256);
        wg_wait<1>();
        if (lane < 2) mbar_arrive_remote(ebar + 8 * 30);
      }
      got0 = __all_sync(0xffffffffu, mbar_test(fpb));
      if (got0) {
#pragma unroll
        for (int kk = 0; kk < 4; kk++) pf[0][kk] = lds4(pa0 + 3 * SLOT + kk * 512 + lane * 16);
      }
      wg_wait<0>();
      if (lane < 2) mbar_arrive_remote(ebar + 8 * 31);
      const int ks0 = 14 * f + ((f & 1) ? 0 : 8);
      auto reread = [&]() {
        asm volatile("ld.volatile.shared.f32 %0, [%2+4]; ld.volatile.shared.f32 %1, [%2+68];" : "=f"(r0), "=f"(r1) : "r"(sstat + (16 * rt + g) * 8) : "memory");
      };
      make_p<6, true, 0, 2>(acc, r0, r1, py, pbase, ks0, tag);
      reread();
      make_p<6, true, 2, 4>(acc, r0, r1, py, pbase, ks0, tag);
      if (lane == 0) red_relaxed(&scr->cnt[(C_PY + rb) * 32 + 4 * wgi + (f >> 1)]);
      reread();
      rdy = mbar_test(BAR(full2, 0)) & mbar_test(fpb + 8);
      make_p<6, true, 4, 6>(acc, r0, r1, py, pbase, ks0, tag);
    }
    {
      float acc[64];
      const uint32_t b2_lo0 = desc_lo(sbase, 8192);
      const uint32_t pbar = rh == rk ? BAR(emptyP, 0) : RBAR(emptyP, 0);
      if (!got0) {
        mbar_wait(fpb);
#pragma unroll
        for (int kk = 0; kk < 4; kk++) pf[0][kk] = lds4(pa0 + 3 * SLOT + kk * 512 + lane * 16);
      }
#pragma unroll
      for (int s = 0; s < 14; s++) {
        uint4 (&a)[4] = pf[s % 3];
        ld_tag4_finish<32>(a, psrc + (int)((KORDER >> (4 * s)) & 15) * 1024, tag);
        if (s < 9 && lane == 0) mbar_arrive_remote(pbar + 8 * s);
        if (s >= 2) {
          wg_wait<1>();
          if (s <= 7 && lane == 0) mbar_arrive(BAR(empty2, s - 2));
        }
        if (!rdy) {
          if (s < 13) mbar_wait(fpb + 8 * (s + 1));
          mbar_wait(BAR(full2, s));
        }
        if (s == 14 - LAG2 && wgi == 1) bar_sync(NB_LAG, 256);
        const uint32_t bl = b2_lo0 + (uint32_t)((BSLOT >> (4 * s)) & 15) * 1024;
        wg_fence();
        if (s < 13) {
#pragma unroll
          for (int kk = 0; kk < 4; kk++)
            pf[(s + 1) % 3][kk] = lds4(pa0 + (uint32_t)((PSLOT >> (4 * (s + 1))) & 15) * SLOT + kk * 512 + lane * 16);
          rdy = mbar_test(BAR(full2, s + 1));
          if (s < 12) rdy &= mbar_test(fpb + 8 * (s + 2));
        }
        if (s == 0) wgmma_rs_n128(acc, a[0].x, a[0].y, a[0].z, a[0].w, desc64(bl, HI128), 0);
        else wgmma_rs_n128(acc, a[0].x, a[0].y, a[0].z, a[0].w, desc64(bl, HI128));
#pragma unroll
        for (int kk = 1; kk < 4; kk++) wgmma_rs_n128(acc, a[kk].x, a[kk].y, a[kk].z, a[kk].w, desc64(bl + kk * 128, HI128));
        wg_commit();
      }
      if (wgi == 0) {
        bar_arrive(NB_LAG, 256);
        uint4* const dst = &scr->Z1[(tid >> 3) * 1024 + (c ^ 4) * 8 + (tid & 7)];
        wg_wait<0>();
#pragma unroll
        for (int i = 0; i < 8; i++)
          st_tag(dst + i * 16384, make_uint4(pack2(acc[8 * i], acc[8 * i + 1]), pack2(acc[8 * i + 2], acc[8 * i + 3]) | 1u,
                                           pack2(acc[8 * i + 4], acc[8 * i + 5]), pack2(acc[8 * i + 6], acc[8 * i + 7])), tag);
      } else {
        uint4 pv[2][4];
        const uint4* const xsrc = &scr->Z1[((tid & 127) >> 3) * 1024 + c * 8 + (tid & 7)];
        ld_tag4_issue<16384>(pv[0], xsrc);
        ld_tag4_issue<16384>(pv[1], xsrc + 65536);
        uint32_t w[32];
        {
          const uint32_t s0 = lds2(sstat + 1024 + (16 * wq + g) * 8).x, s1 = lds2(sstat + 1024 + (16 * wq + g + 8) * 8).x;
          const uint32_t m0 = __byte_perm(s0, 0, 0x3232), m1 = __byte_perm(s1, 0, 0x3232);
          const uint32_t l0 = __byte_perm(s0, 0, 0x1010), l1 = __byte_perm(s1, 0, 0x1010);
          const uint32_t hb = sbase + 13 * SLOT + (16 * wq + (lane & 15)) * 128;
          const uint32_t mk = ((t & 1) == 0 && nq < 2) ? ~1u : ~0u;
          mbar_wait(BAR(hbar, 0));
#pragma unroll
          for (int i = 0; i < 8; i++) {
            asm volatile("ldmatrix.sync.aligned.m8n8.x4.shared.b16 {%0,%1,%2,%3}, [%4];"
                         : "=r"(w[4 * i]), "=r"(w[4 * i + 1]), "=r"(w[4 * i + 2]), "=r"(w[4 * i + 3])
                         : "r"(hb + (i >> 2) * 8192 + (((2 * (i & 3) + (lane >> 4)) ^ (lane & 7)) * 16)) : "memory");
#pragma unroll
            for (int e = 0; e < 4; e++) w[4 * i + e] = hadd2_bf16(hadd2_bf16(w[4 * i + e] & mk, (e & 1) ? l1 : l0), (e & 1) ? m1 : m0);
          }
        }
        wg_wait<0>();
#pragma unroll
        for (int i = 0; i < 32; i++) w[i] = hadd2_bf16(w[i], pack2(acc[2 * i], acc[2 * i + 1]));
#pragma unroll 1
        while (!__all_sync(0xffffffffu, pv[0][0].y & pv[0][1].y & pv[0][2].y & pv[0][3].y & pv[1][0].y & pv[1][1].y & pv[1][2].y & pv[1][3].y & 1u)) {
          ld_tag4_issue<16384>(pv[0], xsrc);
          ld_tag4_issue<16384>(pv[1], xsrc + 65536);
        }
#pragma unroll
        for (int i = 0; i < 8; i++) {
          const uint4& p = pv[i >> 2][i & 3];
          asm volatile("stmatrix.sync.aligned.m8n8.x4.shared.b16 [%0], {%1,%2,%3,%4};"
                       ::"r"(pa0 + (11 + ((lane >> 3) & 1)) * SLOT + (lane & 7) * 256 + (((2 * i + (lane >> 4)) ^ (lane & 7)) * 16)),
                         "r"(hadd2_bf16(w[4 * i], p.x & ~1u)), "r"(hadd2_bf16(w[4 * i + 1], p.y & ~1u)), "r"(hadd2_bf16(w[4 * i + 2], p.z)),
                         "r"(hadd2_bf16(w[4 * i + 3], p.w)) : "memory");
        }
        __syncwarp();
        uint4* const dst = reinterpret_cast<uint4*>(out) + (16 * (c >> 4) + 2 * (4 * rh + wq) + (rb2 & 1) + 128 * (lane >> 4)) * 64 + nq * 16 + (lane & 15);
#pragma unroll
        for (int i = 0; i < 8; i++) {
          const int r = 2 * (i & 3) + (lane >> 4);
          dst[i * 256 * 64] = lds4(pa0 + (11 + (i >> 2)) * SLOT + r * 256 + (((lane & 15) ^ r) * 16));
        }
      }
      if (lane == 0) mbar_arrive(BAR(done, 0));
    }
  }
#undef BAR
#undef TOFF
#undef RBAR
}

typedef CUresult (*EncodeFn)(CUtensorMap*, CUtensorMapDataType, cuuint32_t, void*, const cuuint64_t*, const cuuint64_t*,
                             const cuuint32_t*, const cuuint32_t*, CUtensorMapInterleave, CUtensorMapSwizzle,
                             CUtensorMapL2promotion, CUtensorMapFloatOOBfill);

}

extern "C" void kernel_launch(void* const* d_in, const int* in_sizes, int n_in, void* d_out, int out_size) {
  (void)in_sizes; (void)n_in; (void)out_size;
  static EncodeFn encode = nullptr;
  static void *tab = nullptr, *scr = nullptr;
  if (!encode) {
    void* fn = nullptr;
    cudaDriverEntryPointQueryResult qr;
    cudaGetDriverEntryPoint("cuTensorMapEncodeTiled", &fn, cudaEnableDefault, &qr);
    encode = (EncodeFn)fn;
    cudaGetSymbolAddress(&tab, g_tab);
    cudaGetSymbolAddress(&scr, g_scr);
    cudaFuncSetAttribute(fused_kernel, cudaFuncAttributeMaxDynamicSharedMemorySize, SMEM_BYTES);
  }
  CUtensorMap tmGX, tmUX, tmGY, tmUY, tmD, tmWR, tmWI;
  const cuuint32_t es[5] = {1, 1, 1, 1, 1};
  auto enc = [&](CUtensorMap* m, void* p, int rank, const cuuint64_t* gd, const cuuint64_t* gs, const cuuint32_t* bd,
                 CUtensorMapSwizzle sw, CUtensorMapL2promotion pr) {
    encode(m, CU_TENSOR_MAP_DATA_TYPE_BFLOAT16, rank, p, gd, gs, bd, es, CU_TENSOR_MAP_INTERLEAVE_NONE, sw, pr,
           CU_TENSOR_MAP_FLOAT_OOB_FILL_NONE);
  };
  {
    const cuuint64_t gd[3] = {64, 512, 28}, gs[2] = {3584, 128};
    const cuuint32_t bd[3] = {64, 32, 2};
    enc(&tmGX, d_in[4], 3, gd, gs, bd, CU_TENSOR_MAP_SWIZZLE_128B, CU_TENSOR_MAP_L2_PROMOTION_L2_256B);
    enc(&tmUX, d_in[5], 3, gd, gs, bd, CU_TENSOR_MAP_SWIZZLE_128B, CU_TENSOR_MAP_L2_PROMOTION_L2_256B);
  }
  {
    const cuuint64_t gd[3] = {32, 512, 56}, gs[2] = {3584, 64};
    const cuuint32_t bd[3] = {32, 32, 3};
    enc(&tmGY, d_in[4], 3, gd, gs, bd, CU_TENSOR_MAP_SWIZZLE_64B, CU_TENSOR_MAP_L2_PROMOTION_L2_128B);
    enc(&tmUY, d_in[5], 3, gd, gs, bd, CU_TENSOR_MAP_SWIZZLE_64B, CU_TENSOR_MAP_L2_PROMOTION_L2_128B);
  }
  {
    const cuuint64_t gd[3] = {64, 1792, 8}, gs[2] = {1024, 128};
    const cuuint32_t bd[3] = {64, 64, 2};
    enc(&tmD, d_in[6], 3, gd, gs, bd, CU_TENSOR_MAP_SWIZZLE_128B, CU_TENSOR_MAP_L2_PROMOTION_L2_256B);
  }
  {
    const cuuint64_t gd[3] = {4112, 8, 16}, gs[2] = {16 * 8224, 8224};
    const cuuint32_t bd[3] = {40, 8, 16};
    enc(&tmWR, d_in[1], 3, gd, gs, bd, CU_TENSOR_MAP_SWIZZLE_NONE, CU_TENSOR_MAP_L2_PROMOTION_NONE);
    enc(&tmWI, d_in[2], 3, gd, gs, bd, CU_TENSOR_MAP_SWIZZLE_NONE, CU_TENSOR_MAP_L2_PROMOTION_NONE);
  }
  fused_kernel<<<NCTA, NTHREADS, SMEM_BYTES>>>((const __nv_bfloat16*)d_in[0], (const Tables*)tab, (Scratch*)scr,
                                               (__nv_bfloat16*)d_out, (const char*)d_in[4], (const char*)d_in[5],
                                               (const char*)d_in[6], tmWR, tmWI, tmGX, tmUX, tmGY, tmUY, tmD);
}
```

```cpp
#include <cuda_runtime.h>
#include <cuda_bf16.h>
#include <cuda.h>
#include <stdint.h>

namespace {

constexpr int NCTA = 128;
constexpr int NTHREADS = 384;
constexpr int SLOT = 16384;
constexpr int SMEM_BYTES = 14 * SLOT + 3072;
constexpr int SPIN_LIMIT = 1 << 22;

struct Scratch {
  uint4 Z1[128 * 1024];
  uint4 LN[16 * 8 * 1024];
  uint4 P[16 * 28 * 1024];
  uint4 ST[1024];
  unsigned cnt[64 * 32];
};
__device__ __align__(1024) Scratch g_scr;

constexpr double ccos(int i, int n) {
  i &= n - 1;
  if (i > n / 2) i = n - i;
  if (4 * i == n) return 0.0;
  const bool neg = 4 * i > n;
  if (neg) i = n / 2 - i;
  const double a = 6.283185307179586476925 * i / n, a2 = a * a;
  double term = 1.0, sum = 1.0;
  for (int k = 1; k < 14; k++) { term *= -a2 / ((2 * k - 1) * (2 * k)); sum += term; }
  return neg ? -sum : sum;
}
constexpr double csin(int i, int n) { return ccos(i - n / 4, n); }
constexpr unsigned fbits(double v, int mant) {
  if (v == 0.0) return 0;
  const unsigned sg = v < 0 ? 1u : 0u;
  if (v < 0) v = -v;
  int e = 127;
  while (v < 1.0) { v *= 2.0; e--; }
  const unsigned m = (unsigned)((v - 1.0) * (double)(1u << mant) + 0.5);
  return (sg << (8 + mant)) + ((unsigned)e << mant) + m;
}
constexpr unsigned pkb(double lo, double hi) { return fbits(lo, 7) | (fbits(hi, 7) << 16); }
constexpr double fa_elem(int mt, int r, int n1) {
  const int k1 = 8 * mt + (r & 7);
  return r < 8 ? ccos(k1 * n1, 32) : k1 == 0 ? ccos(16 * n1, 32) : -csin(k1 * n1, 32);
}
constexpr unsigned cfrag_c(int idx, int n, int ri, double s = 1.0) {
  return ri ? pkb(-s * csin(idx, n), s * ccos(idx, n)) : pkb(s * ccos(idx, n), s * csin(idx, n));
}
struct Tables {
  unsigned fa[4][32][4];
  unsigned fb[4][32][4];
  unsigned tw1[6][32][4];
  unsigned f2[8][4][32][4];
  unsigned g2[8][4][32][4];
  unsigned gb[4][32][4];
  unsigned ga[4][32][4];
  unsigned tw3[4][32][4];
  unsigned f8[32][4], g8[32][4];
};
constexpr int T1_BYTES = 7168, T2_BYTES = 39936;
static_assert(sizeof(Tables) == T1_BYTES + T2_BYTES, "table size");
constexpr Tables make_tables() {
  Tables T = {};
  for (int l = 0; l < 32; l++) {
    const int g = l >> 2, t = l & 3;
    for (int a = 0; a < 2; a++)
      for (int b = 0; b < 2; b++) {
        for (int r = 0; r < 4; r++) {
          const int row = g + 8 * (r & 1), col = 2 * t + 8 * (r >> 1);
          T.fa[2 * a + b][l][r] = pkb(fa_elem(a, row, 16 * b + col), fa_elem(a, row, 16 * b + col + 1));
          T.ga[2 * a + b][l][r] = pkb(fa_elem(b, col, 16 * a + row), fa_elem(b, col + 1, 16 * a + row));
        }
        const double sg = b ? -1.0 : 1.0;
        for (int h = 0; h < 2; h++) {
          const int ri = g & 1, m = 2 * (g >> 1) + h, k2 = b ? 15 - m : m;
          const int pa = (8 * a + 2 * t) * k2, pb = (8 * a + 2 * t + 1) * k2;
          T.fb[2 * a + b][l][2 * h] = ri == 0 ? pkb(ccos(pa, 16), ccos(pb, 16)) : pkb(-sg * csin(pa, 16), -sg * csin(pb, 16));
          T.fb[2 * a + b][l][2 * h + 1] = ri == 0 ? pkb(csin(pa, 16), csin(pb, 16)) : pkb(sg * ccos(pa, 16), sg * ccos(pb, 16));
        }
        const int n2 = 4 * (g >> 1) + 2 * a + (g & 1);
        for (int h = 0; h < 2; h++) {
          const int p = n2 * (b ? 15 - 2 * t - h : 2 * t + h);
          T.gb[2 * a + b][l][2 * h] = pkb(ccos(p, 16), -sg * csin(p, 16));
          T.gb[2 * a + b][l][2 * h + 1] = pkb(csin(p, 16), sg * ccos(p, 16));
          const int k1 = 8 * b + 2 * t + h, q = n2 * (k1 == 0 ? 16 : k1);
          T.tw3[2 * a + b][l][2 * h] = fbits(ccos(q, 512), 23);
          T.tw3[2 * a + b][l][2 * h + 1] = fbits(csin(q, 512), 23);
        }
        const int p = (8 * a + 2 * t + b) * (g == 0 ? 16 : g);
        T.tw1[2 * a + b][l][0] = fbits(g == 0 ? 0.0 : ccos(p, 512), 23);
        T.tw1[2 * a + b][l][1] = fbits(g == 0 ? ccos(p, 512) : csin(p, 512), 23);
        T.tw1[2 * a + b][l][2] = fbits(g == 0 ? 0.0 : -csin(p, 512), 23);
        T.tw1[2 * a + b][l][3] = fbits(g == 0 ? -csin(p, 512) : ccos(p, 512), 23);
        T.tw1[4 + a][l][2 * b] = fbits(ccos((8 * a + 2 * t + b) * (g + 8), 512), 23);
        T.tw1[4 + a][l][2 * b + 1] = fbits(csin((8 * a + 2 * t + b) * (g + 8), 512), 23);
      }
    for (int i = 0; i < 4; i++) {
      const int p8 = (t + 4 * (i & 1)) * (4 * (i >> 1) + (g >> 1));
      T.f8[l][i] = cfrag_c(p8, 8, g & 1);
      T.g8[l][i] = cfrag_c(-p8, 8, g & 1, 1.0 / (1 << 19));
    }
    for (int w = 0; w < 8; w++)
      for (int i = 0; i < 16; i++) {
        const int kidx = t + 4 * (i & 1) + 8 * (i >> 3), nidx = 4 * ((i >> 1) & 3) + (g >> 1);
        T.f2[w][i >> 2][l][i & 3] = cfrag_c((8 * kidx + w) * nidx, 128, g & 1);
        T.g2[w][i >> 2][l][i & 3] = cfrag_c(-(8 * nidx + w) * kidx, 128, g & 1);
      }
  }
  return T;
}
__device__ const __align__(128) Tables g_tab = make_tables();

__device__ __forceinline__ void die() { asm volatile("st.global.u32 [%0], %1;" ::"l"(0ull), "r"(0) : "memory"); }
__device__ __forceinline__ uint32_t s2u(const void* p) { return (uint32_t)__cvta_generic_to_shared(p); }
__device__ __forceinline__ void mbar_init(uint32_t b, int c) { asm volatile("mbarrier.init.shared::cta.b64 [%0], %1;" ::"r"(b), "r"(c)); }
__device__ __forceinline__ void mbar_expect(uint32_t b, int bytes) {
  asm volatile("mbarrier.arrive.expect_tx.shared::cta.b64 _, [%0], %1;" ::"r"(b), "r"(bytes) : "memory");
}
__device__ __forceinline__ void mbar_arrive(uint32_t b) { asm volatile("mbarrier.arrive.shared::cta.b64 _, [%0];" ::"r"(b) : "memory"); }
__device__ __forceinline__ uint32_t mbar_try(uint32_t b, uint32_t parity) {
  uint32_t ok;
  asm volatile("{.reg .pred p; mbarrier.try_wait.parity.shared::cta.b64 p, [%1], %2; selp.u32 %0,1,0,p;}"
               : "=r"(ok) : "r"(b), "r"(parity) : "memory");
  return ok;
}
__device__ __forceinline__ uint32_t mbar_test(uint32_t b) {
  uint32_t ok;
  asm volatile("{.reg .pred p; mbarrier.test_wait.parity.shared::cta.b64 p, [%1], 0; selp.u32 %0,1,0,p;}" : "=r"(ok) : "r"(b) : "memory");
  return ok;
}
__device__ __forceinline__ void mbar_wait_bounded(uint32_t b) {
  int it = 0;
#pragma unroll 1
  while (!mbar_try(b, 0))
    if (++it > SPIN_LIMIT) { die(); break; }
}
__device__ __forceinline__ void mbar_wait(uint32_t b) {
  asm volatile("{.reg .pred p;\nW_%=: mbarrier.try_wait.parity.shared::cta.b64 p, [%0], 0;\n@!p bra W_%=;}" ::"r"(b) : "memory");
}
__device__ __forceinline__ void bar_sync(int id, int n) { asm volatile("bar.sync %0, %1;" ::"r"(id), "r"(n) : "memory"); }
__device__ __forceinline__ void bar_arrive(int id, int n) { asm volatile("bar.arrive %0, %1;" ::"r"(id), "r"(n) : "memory"); }
__device__ __forceinline__ void red_release(unsigned* p) { asm volatile("red.release.gpu.global.add.u32 [%0], 1;" ::"l"(p) : "memory"); }
__device__ __forceinline__ void red_relaxed(unsigned* p) { asm volatile("red.relaxed.gpu.global.add.u32 [%0], 1;" ::"l"(p) : "memory"); }
__device__ __forceinline__ unsigned ld_acquire(const unsigned* p) {
  unsigned v;
  asm volatile("ld.acquire.gpu.global.u32 %0, [%1];" : "=r"(v) : "l"(p) : "memory");
  return v;
}
__device__ __forceinline__ unsigned ld_relaxed(const unsigned* p) {
  unsigned v;
  asm volatile("ld.relaxed.gpu.global.u32 %0, [%1];" : "=r"(v) : "l"(p) : "memory");
  return v;
}
__device__ __forceinline__ void wait_counter(const unsigned* p, unsigned target) {
#pragma unroll 1
  while ((int)(ld_acquire(p) - target) < 0) {}
}
__device__ __forceinline__ void sts4(uint32_t a, uint32_t x, uint32_t y, uint32_t z, uint32_t w) {
  asm volatile("st.shared.v4.u32 [%0], {%1,%2,%3,%4};" ::"r"(a), "r"(x), "r"(y), "r"(z), "r"(w) : "memory");
}
__device__ __forceinline__ uint4 lds4(uint32_t a) {
  uint4 v;
  asm volatile("ld.shared.v4.u32 {%0,%1,%2,%3}, [%4];" : "=r"(v.x), "=r"(v.y), "=r"(v.z), "=r"(v.w) : "r"(a) : "memory");
  return v;
}
__device__ __forceinline__ uint32_t pack2(float lo, float hi) {
  uint32_t r;
  asm("cvt.rn.bf16x2.f32 %0, %1, %2;" : "=r"(r) : "f"(hi), "f"(lo));
  return r;
}
__device__ __forceinline__ float bf_lo(uint32_t v) { return __uint_as_float(v << 16); }
__device__ __forceinline__ uint32_t hadd2_bf16(uint32_t a, uint32_t b) {
  uint32_t r;
  asm("add.rn.bf16x2 %0, %1, %2;" : "=r"(r) : "r"(a), "r"(b));
  return r;
}
__device__ __forceinline__ void mma16816(float (&d)[4], uint32_t a0, uint32_t a1, uint32_t a2, uint32_t a3, uint32_t b0, uint32_t b1) {
  asm("mma.sync.aligned.m16n8k16.row.col.f32.bf16.bf16.f32 {%0,%1,%2,%3}, {%4,%5,%6,%7}, {%8,%9}, {%0,%1,%2,%3};"
      : "+f"(d[0]), "+f"(d[1]), "+f"(d[2]), "+f"(d[3])
      : "r"(a0), "r"(a1), "r"(a2), "r"(a3), "r"(b0), "r"(b1));
}
__device__ __forceinline__ void mma16816_z(float (&d)[4], uint32_t a0, uint32_t a1, uint32_t a2, uint32_t a3, uint32_t b0, uint32_t b1) {
  asm("{.reg .f32 z; mov.f32 z, 0f00000000;\n"
      "mma.sync.aligned.m16n8k16.row.col.f32.bf16.bf16.f32 {%0,%1,%2,%3}, {%4,%5,%6,%7}, {%8,%9}, {z,z,z,z};}"
      : "=f"(d[0]), "=f"(d[1]), "=f"(d[2]), "=f"(d[3])
      : "r"(a0), "r"(a1), "r"(a2), "r"(a3), "r"(b0), "r"(b1));
}
template <int N>
__device__ __forceinline__ void cs_frac(int idx, float& c, float& s) {
  int i = ((idx + N / 2) & (N - 1)) - N / 2;
  float a = (float)i * (6.283185307179586f / N);
  c = __cosf(a);
  s = __sinf(a);
}
template <int N>
__device__ __forceinline__ uint32_t cfrag(int idx, int ri) {
  float c, s;
  cs_frac<N>(idx, c, s);
  return ri ? pack2(-s, c) : pack2(c, s);
}
__device__ __forceinline__ uint32_t word(const uint4& v, int e) { return e == 0 ? v.x : e == 1 ? v.y : e == 2 ? v.z : v.w; }
__device__ __forceinline__ void cdft16(const uint4 (&A)[4], const uint4 (&F)[4], uint4 (&o)[4]) {
  float acc[2][4][4];
#pragma unroll
  for (int ks = 0; ks < 2; ks++)
#pragma unroll
    for (int p = 0; p < 2; p++)
#pragma unroll
      for (int v = 0; v < 4; v++) {
        const uint4& a = A[2 * ks + p];
        const uint32_t b0 = word(F[ks * 2 + (v >> 1)], (v & 1) * 2), b1 = word(F[ks * 2 + (v >> 1)], (v & 1) * 2 + 1);
        if (ks == 0) mma16816_z(acc[p][v], a.x, a.y, a.z, a.w, b0, b1);
        else mma16816(acc[p][v], a.x, a.y, a.z, a.w, b0, b1);
      }
#pragma unroll
  for (int v = 0; v < 4; v++)
    o[v] = make_uint4(pack2(acc[0][v][0], acc[0][v][1]), pack2(acc[0][v][2], acc[0][v][3]),
                      pack2(acc[1][v][0], acc[1][v][1]), pack2(acc[1][v][2], acc[1][v][3]));
}
__device__ __forceinline__ void lds_frag(uint4& f0, uint4& f1, uint32_t a0, uint32_t a1) {
  asm volatile("ld.volatile.shared.v2.u32 {%0,%1}, [%8]; ld.volatile.shared.v2.u32 {%2,%3}, [%9];\n"
               "ld.volatile.shared.v2.u32 {%4,%5}, [%8+8]; ld.volatile.shared.v2.u32 {%6,%7}, [%9+8];"
               : "=r"(f0.x), "=r"(f0.y), "=r"(f0.z), "=r"(f0.w), "=r"(f1.x), "=r"(f1.y), "=r"(f1.z), "=r"(f1.w) : "r"(a0), "r"(a1) : "memory");
}
__device__ __forceinline__ void reg_frag(uint4 (&q)[4], uint32_t ones) {
#pragma unroll
  for (int ks = 0; ks < 2; ks++) {
    const uint4 a = q[2 * ks], b = q[2 * ks + 1];
    q[2 * ks] = make_uint4(a.x, a.y, b.x & ones, b.y & ones);
    q[2 * ks + 1] = make_uint4(a.z & ones, a.w & ones, b.z, b.w);
  }
}
__device__ __forceinline__ void st_tag(uint4* p, const uint4& v, uint32_t tag) {
  asm volatile("st.relaxed.gpu.global.v4.b32 [%0], {%1,%2,%3,%4};"
               ::"l"(p), "r"((v.x & ~1u) | tag), "r"(v.y), "r"(v.z), "r"(v.w) : "memory");
}
__device__ __forceinline__ void st_tag8(void* p, uint32_t x, uint32_t y, uint32_t tag) {
  asm volatile("st.relaxed.gpu.global.v2.b32 [%0], {%1,%2};" ::"l"(p), "r"((x & ~1u) | tag), "r"(y) : "memory");
}
__device__ __forceinline__ uint4 ld_b128(const uint4* p) {
  uint4 v;
  asm volatile("ld.relaxed.gpu.global.v4.b32 {%0,%1,%2,%3}, [%4];"
               : "=r"(v.x), "=r"(v.y), "=r"(v.z), "=r"(v.w) : "l"(p) : "memory");
  return v;
}
template <int STRIDE>
__device__ __forceinline__ void ld_tag4_issue(uint4 (&q)[4], const uint4* p) {
#pragma unroll
  for (int i = 0; i < 4; i++) q[i] = ld_b128(p + i * STRIDE);
}
__device__ __forceinline__ uint32_t tag_miss(uint32_t a, uint32_t b, uint32_t c, uint32_t d, uint32_t tag) {
  uint32_t r;
  asm("{.reg .b32 u, v; lop3.b32 u, %1, %2, %5, 0x7e; lop3.b32 v, %3, %4, %5, 0x7e; lop3.b32 %0, u, v, 1, 0xa8;}"
      : "=r"(r) : "r"(a), "r"(b), "r"(c), "r"(d), "r"(tag));
  return r;
}
template <int STRIDE, bool HALVES = false>
__device__ __forceinline__ void ld_tag4_finish(uint4 (&q)[4], const uint4* p, uint32_t tag) {
  int it = 0;
#pragma unroll 1
  while (__any_sync(0xffffffffu, tag_miss(q[0].x, q[1].x, q[2].x, q[3].x, tag) | (HALVES ? tag_miss(q[0].z, q[1].z, q[2].z, q[3].z, tag) : 0u))) {
    ld_tag4_issue<STRIDE>(q, p);
    if (++it > SPIN_LIMIT) { die(); break; }
  }
#pragma unroll
  for (int i = 0; i < 4; i++) {
    asm volatile("and.b32 %0, %0, 0xfffffffe;" : "+r"(q[i].x));
    if (HALVES) q[i].z &= ~1u;
  }
}
__device__ __forceinline__ float quad_sum(const uint32_t (&a)[8]) {
  float d[4];
  mma16816_z(d, a[0], a[1], a[2], a[3], 0x3f803f80u, 0x3f803f80u);
  mma16816(d, a[4], a[5], a[6], a[7], 0x3f803f80u, 0x3f803f80u);
  return d[0] + d[2];
}
__device__ __forceinline__ float sum_groups(float v) {
  v += __shfl_xor_sync(0xffffffffu, v, 4);
  v += __shfl_xor_sync(0xffffffffu, v, 8);
  v += __shfl_xor_sync(0xffffffffu, v, 16);
  return v;
}
__device__ __forceinline__ uint32_t hsub2_bf16(uint32_t a, uint32_t b) {
  uint32_t r;
  asm("sub.rn.bf16x2 %0, %1, %2;" : "=r"(r) : "r"(a), "r"(b));
  return r;
}
__device__ __forceinline__ float row_rstd(const uint32_t (&c)[8]) {
  uint32_t s[8];
#pragma unroll
  for (int i = 0; i < 8; i++) asm("mul.rn.bf16x2 %0, %1, %1;" : "=r"(s[i]) : "r"(c[i]));
  return rsqrtf(fmaf(sum_groups(quad_sum(s)), 1.f / 512.f, 1e-5f));
}
__device__ __forceinline__ uint64_t desc64(uint32_t lo, uint32_t hi) {
  uint64_t d;
  asm("mov.b64 %0, {%1, %2};" : "=l"(d) : "r"(lo), "r"(hi));
  return d;
}
constexpr uint32_t desc_hi(uint32_t sbo, uint32_t swz) { return (sbo >> 4) | (swz << 30); }
__device__ __forceinline__ uint32_t desc_lo(uint32_t addr, uint32_t lbo) { return ((addr & 0x3FFFF) >> 4) | ((lbo >> 4) << 16); }
__device__ __forceinline__ void cp_async16(uint32_t dst, const void* src) {
  asm volatile("cp.async.cg.shared.global [%0], [%1], 16;" ::"r"(dst), "l"(src) : "memory");
}
__device__ __forceinline__ uint2 lds2(uint32_t a) {
  uint2 v;
  asm volatile("ld.shared.v2.u32 {%0,%1}, [%2];" : "=r"(v.x), "=r"(v.y) : "r"(a) : "memory");
  return v;
}
__device__ __forceinline__ uint32_t lds_u16(uint32_t a) {
  uint16_t v;
  asm volatile("ld.shared.u16 %0, [%1];" : "=h"(v) : "r"(a) : "memory");
  return v;
}
__device__ __forceinline__ void wg_fence() { asm volatile("wgmma.fence.sync.aligned;" ::: "memory"); }
__device__ __forceinline__ void wg_commit() { asm volatile("wgmma.commit_group.sync.aligned;" ::: "memory"); }
template <int N>
__device__ __forceinline__ void wg_wait() { asm volatile("wgmma.wait_group.sync.aligned %0;" ::"n"(N) : "memory"); }
__device__ __forceinline__ void bulk_load(uint32_t dst, const void* src, int bytes, uint32_t bar) {
  asm volatile("cp.async.bulk.shared::cluster.global.mbarrier::complete_tx::bytes [%0], [%1], %2, [%3];"
               ::"r"(dst), "l"(src), "r"(bytes), "r"(bar) : "memory");
}
__device__ __forceinline__ void bulk_load_mc(uint32_t dst, const void* src, int bytes, uint32_t bar) {
  asm volatile("cp.async.bulk.shared::cluster.global.mbarrier::complete_tx::bytes.multicast::cluster [%0], [%1], %2, [%3], %4;"
               ::"r"(dst), "l"(src), "r"(bytes), "r"(bar), "h"((uint16_t)3) : "memory");
}
__device__ __forceinline__ void tma3(uint32_t dst, const CUtensorMap* tm, uint32_t bar, int c0, int c1, int c2) {
  asm volatile("cp.async.bulk.tensor.3d.shared::cluster.global.mbarrier::complete_tx::bytes [%0], [%1, {%3,%4,%5}], [%2];"
               ::"r"(dst), "l"(tm), "r"(bar), "r"(c0), "r"(c1), "r"(c2) : "memory");
}
__device__ __forceinline__ void tma3_mc(uint32_t dst, const CUtensorMap* tm, uint32_t bar, int c1, int c2) {
  asm volatile("cp.async.bulk.tensor.3d.shared::cluster.global.mbarrier::complete_tx::bytes.multicast::cluster [%0], [%1, {%3,%4,%5}], [%2], %6;"
               ::"r"(dst), "l"(tm), "r"(bar), "r"(0), "r"(c1), "r"(c2), "h"((uint16_t)3) : "memory");
}
__device__ __forceinline__ void mbar_arrive_remote(uint32_t rb) {
  asm volatile("mbarrier.arrive.shared::cluster.b64 _, [%0];" ::"r"(rb) : "memory");
}
__device__ __forceinline__ uint4 ldg_ca4(const void* p) {
  uint4 v;
  asm volatile("ld.global.ca.v4.u32 {%0,%1,%2,%3}, [%4];" : "=r"(v.x), "=r"(v.y), "=r"(v.z), "=r"(v.w) : "l"(p) : "memory");
  return v;
}
__device__ __forceinline__ float u2f(uint32_t v) { return __uint_as_float(v); }
__device__ __forceinline__ void mma_az(float (&d)[4], const uint4& a, uint32_t b0, uint32_t b1) { mma16816_z(d, a.x, a.y, a.z, a.w, b0, b1); }
__device__ __forceinline__ void mma_a(float (&d)[4], const uint4& a, uint32_t b0, uint32_t b1) { mma16816(d, a.x, a.y, a.z, a.w, b0, b1); }
__device__ __forceinline__ uint32_t clock32() {
  uint32_t v;
  asm volatile("mov.u32 %0, %%clock;" : "=r"(v) :: "memory");
  return v;
}
__device__ __forceinline__ float swiglu(float g, float u, float r) {
  float hg = (0.5f * r) * g, th;
  asm("tanh.approx.f32 %0, %1;" : "=f"(th) : "f"(hg));
  return fmaf(hg, th, hg) * (r * u);
}
__device__ __forceinline__ void l2_prefetch(const void* p, int bytes) {
  asm volatile("cp.async.bulk.prefetch.L2.global [%0], %1;" ::"l"(p), "r"(bytes) : "memory");
}

__device__ __forceinline__ void wgmma_n256(float (&d)[128], uint64_t da, uint64_t db, int sd = 1) {
  asm volatile("{.reg .pred p; setp.ne.b32 p, %130, 0;\n"
      "wgmma.mma_async.sync.aligned.m64n256k16.f32.bf16.bf16 {"
      "%0,%1,%2,%3,%4,%5,%6,%7,%8,%9,%10,%11,%12,%13,%14,%15,"
      "%16,%17,%18,%19,%20,%21,%22,%23,%24,%25,%26,%27,%28,%29,%30,%31,"
      "%32,%33,%34,%35,%36,%37,%38,%39,%40,%41,%42,%43,%44,%45,%46,%47,"
      "%48,%49,%50,%51,%52,%53,%54,%55,%56,%57,%58,%59,%60,%61,%62,%63,"
      "%64,%65,%66,%67,%68,%69,%70,%71,%72,%73,%74,%75,%76,%77,%78,%79,"
      "%80,%81,%82,%83,%84,%85,%86,%87,%88,%89,%90,%91,%92,%93,%94,%95,"
      "%96,%97,%98,%99,%100,%101,%102,%103,%104,%105,%106,%107,%108,%109,%110,%111,"
      "%112,%113,%114,%115,%116,%117,%118,%119,%120,%121,%122,%123,%124,%125,%126,%127"
      "}, %128, %129, p, 1, 1, 0, 1;}\n"
      : "+f"(d[0]),"+f"(d[1]),"+f"(d[2]),"+f"(d[3]),"+f"(d[4]),"+f"(d[5]),"+f"(d[6]),"+f"(d[7]),
        "+f"(d[8]),"+f"(d[9]),"+f"(d[10]),"+f"(d[11]),"+f"(d[12]),"+f"(d[13]),"+f"(d[14]),"+f"(d[15]),
        "+f"(d[16]),"+f"(d[17]),"+f"(d[18]),"+f"(d[19]),"+f"(d[20]),"+f"(d[21]),"+f"(d[22]),"+f"(d[23]),
        "+f"(d[24]),"+f"(d[25]),"+f"(d[26]),"+f"(d[27]),"+f"(d[28]),"+f"(d[29]),"+f"(d[30]),"+f"(d[31]),
        "+f"(d[32]),"+f"(d[33]),"+f"(d[34]),"+f"(d[35]),"+f"(d[36]),"+f"(d[37]),"+f"(d[38]),"+f"(d[39]),
        "+f"(d[40]),"+f"(d[41]),"+f"(d[42]),"+f"(d[43]),"+f"(d[44]),"+f"(d[45]),"+f"(d[46]),"+f"(d[47]),
        "+f"(d[48]),"+f"(d[49]),"+f"(d[50]),"+f"(d[51]),"+f"(d[52]),"+f"(d[53]),"+f"(d[54]),"+f"(d[55]),
        "+f"(d[56]),"+f"(d[57]),"+f"(d[58]),"+f"(d[59]),"+f"(d[60]),"+f"(d[61]),"+f"(d[62]),"+f"(d[63]),
        "+f"(d[64]),"+f"(d[65]),"+f"(d[66]),"+f"(d[67]),"+f"(d[68]),"+f"(d[69]),"+f"(d[70]),"+f"(d[71]),
        "+f"(d[72]),"+f"(d[73]),"+f"(d[74]),"+f"(d[75]),"+f"(d[76]),"+f"(d[77]),"+f"(d[78]),"+f"(d[79]),
        "+f"(d[80]),"+f"(d[81]),"+f"(d[82]),"+f"(d[83]),"+f"(d[84]),"+f"(d[85]),"+f"(d[86]),"+f"(d[87]),
        "+f"(d[88]),"+f"(d[89]),"+f"(d[90]),"+f"(d[91]),"+f"(d[92]),"+f"(d[93]),"+f"(d[94]),"+f"(d[95]),
        "+f"(d[96]),"+f"(d[97]),"+f"(d[98]),"+f"(d[99]),"+f"(d[100]),"+f"(d[101]),"+f"(d[102]),"+f"(d[103]),
        "+f"(d[104]),"+f"(d[105]),"+f"(d[106]),"+f"(d[107]),"+f"(d[108]),"+f"(d[109]),"+f"(d[110]),"+f"(d[111]),
        "+f"(d[112]),"+f"(d[113]),"+f"(d[114]),"+f"(d[115]),"+f"(d[116]),"+f"(d[117]),"+f"(d[118]),"+f"(d[119]),
        "+f"(d[120]),"+f"(d[121]),"+f"(d[122]),"+f"(d[123]),"+f"(d[124]),"+f"(d[125]),"+f"(d[126]),"+f"(d[127])
      : "l"(da), "l"(db), "r"(sd));
}
__device__ __forceinline__ void wgmma_n192(float (&d)[96], uint64_t da, uint64_t db) {
  asm volatile("wgmma.mma_async.sync.aligned.m64n192k16.f32.bf16.bf16 {"
      "%0,%1,%2,%3,%4,%5,%6,%7,%8,%9,%10,%11,%12,%13,%14,%15,"
      "%16,%17,%18,%19,%20,%21,%22,%23,%24,%25,%26,%27,%28,%29,%30,%31,"
      "%32,%33,%34,%35,%36,%37,%38,%39,%40,%41,%42,%43,%44,%45,%46,%47,"
      "%48,%49,%50,%51,%52,%53,%54,%55,%56,%57,%58,%59,%60,%61,%62,%63,"
      "%64,%65,%66,%67,%68,%69,%70,%71,%72,%73,%74,%75,%76,%77,%78,%79,"
      "%80,%81,%82,%83,%84,%85,%86,%87,%88,%89,%90,%91,%92,%93,%94,%95"
      "}, %96, %97, 1, 1, 1, 0, 1;\n"
      : "+f"(d[0]),"+f"(d[1]),"+f"(d[2]),"+f"(d[3]),"+f"(d[4]),"+f"(d[5]),"+f"(d[6]),"+f"(d[7]),
        "+f"(d[8]),"+f"(d[9]),"+f"(d[10]),"+f"(d[11]),"+f"(d[12]),"+f"(d[13]),"+f"(d[14]),"+f"(d[15]),
        "+f"(d[16]),"+f"(d[17]),"+f"(d[18]),"+f"(d[19]),"+f"(d[20]),"+f"(d[21]),"+f"(d[22]),"+f"(d[23]),
        "+f"(d[24]),"+f"(d[25]),"+f"(d[26]),"+f"(d[27]),"+f"(d[28]),"+f"(d[29]),"+f"(d[30]),"+f"(d[31]),
        "+f"(d[32]),"+f"(d[33]),"+f"(d[34]),"+f"(d[35]),"+f"(d[36]),"+f"(d[37]),"+f"(d[38]),"+f"(d[39]),
        "+f"(d[40]),"+f"(d[41]),"+f"(d[42]),"+f"(d[43]),"+f"(d[44]),"+f"(d[45]),"+f"(d[46]),"+f"(d[47]),
        "+f"(d[48]),"+f"(d[49]),"+f"(d[50]),"+f"(d[51]),"+f"(d[52]),"+f"(d[53]),"+f"(d[54]),"+f"(d[55]),
        "+f"(d[56]),"+f"(d[57]),"+f"(d[58]),"+f"(d[59]),"+f"(d[60]),"+f"(d[61]),"+f"(d[62]),"+f"(d[63]),
        "+f"(d[64]),"+f"(d[65]),"+f"(d[66]),"+f"(d[67]),"+f"(d[68]),"+f"(d[69]),"+f"(d[70]),"+f"(d[71]),
        "+f"(d[72]),"+f"(d[73]),"+f"(d[74]),"+f"(d[75]),"+f"(d[76]),"+f"(d[77]),"+f"(d[78]),"+f"(d[79]),
        "+f"(d[80]),"+f"(d[81]),"+f"(d[82]),"+f"(d[83]),"+f"(d[84]),"+f"(d[85]),"+f"(d[86]),"+f"(d[87]),
        "+f"(d[88]),"+f"(d[89]),"+f"(d[90]),"+f"(d[91]),"+f"(d[92]),"+f"(d[93]),"+f"(d[94]),"+f"(d[95])
      : "l"(da), "l"(db));
}
__device__ __forceinline__ void wgmma_rs_n128(float (&d)[64], uint32_t a0, uint32_t a1, uint32_t a2, uint32_t a3, uint64_t db, int sd = 1) {
  asm volatile("{.reg .pred p; setp.ne.b32 p, %69, 0;\n"
      "wgmma.mma_async.sync.aligned.m64n128k16.f32.bf16.bf16 {"
      "%0,%1,%2,%3,%4,%5,%6,%7,%8,%9,%10,%11,%12,%13,%14,%15,"
      "%16,%17,%18,%19,%20,%21,%22,%23,%24,%25,%26,%27,%28,%29,%30,%31,"
      "%32,%33,%34,%35,%36,%37,%38,%39,%40,%41,%42,%43,%44,%45,%46,%47,"
      "%48,%49,%50,%51,%52,%53,%54,%55,%56,%57,%58,%59,%60,%61,%62,%63"
      "}, {%64,%65,%66,%67}, %68, p, 1, 1, 1;}\n"
      : "+f"(d[0]),"+f"(d[1]),"+f"(d[2]),"+f"(d[3]),"+f"(d[4]),"+f"(d[5]),"+f"(d[6]),"+f"(d[7]),
        "+f"(d[8]),"+f"(d[9]),"+f"(d[10]),"+f"(d[11]),"+f"(d[12]),"+f"(d[13]),"+f"(d[14]),"+f"(d[15]),
        "+f"(d[16]),"+f"(d[17]),"+f"(d[18]),"+f"(d[19]),"+f"(d[20]),"+f"(d[21]),"+f"(d[22]),"+f"(d[23]),
        "+f"(d[24]),"+f"(d[25]),"+f"(d[26]),"+f"(d[27]),"+f"(d[28]),"+f"(d[29]),"+f"(d[30]),"+f"(d[31]),
        "+f"(d[32]),"+f"(d[33]),"+f"(d[34]),"+f"(d[35]),"+f"(d[36]),"+f"(d[37]),"+f"(d[38]),"+f"(d[39]),
        "+f"(d[40]),"+f"(d[41]),"+f"(d[42]),"+f"(d[43]),"+f"(d[44]),"+f"(d[45]),"+f"(d[46]),"+f"(d[47]),
        "+f"(d[48]),"+f"(d[49]),"+f"(d[50]),"+f"(d[51]),"+f"(d[52]),"+f"(d[53]),"+f"(d[54]),"+f"(d[55]),
        "+f"(d[56]),"+f"(d[57]),"+f"(d[58]),"+f"(d[59]),"+f"(d[60]),"+f"(d[61]),"+f"(d[62]),"+f"(d[63])
      : "r"(a0), "r"(a1), "r"(a2), "r"(a3), "l"(db), "r"(sd));
}
__device__ __forceinline__ void wgmma_rs_n256(float (&d)[128], uint32_t a0, uint32_t a1, uint32_t a2, uint32_t a3, uint64_t db, int sd = 1) {
  asm volatile("{.reg .pred p; setp.ne.b32 p, %133, 0;\n"
      "wgmma.mma_async.sync.aligned.m64n256k16.f32.bf16.bf16 {"
      "%0,%1,%2,%3,%4,%5,%6,%7,%8,%9,%10,%11,%12,%13,%14,%15,"
      "%16,%17,%18,%19,%20,%21,%22,%23,%24,%25,%26,%27,%28,%29,%30,%31,"
      "%32,%33,%34,%35,%36,%37,%38,%39,%40,%41,%42,%43,%44,%45,%46,%47,"
      "%48,%49,%50,%51,%52,%53,%54,%55,%56,%57,%58,%59,%60,%61,%62,%63,"
      "%64,%65,%66,%67,%68,%69,%70,%71,%72,%73,%74,%75,%76,%77,%78,%79,"
      "%80,%81,%82,%83,%84,%85,%86,%87,%88,%89,%90,%91,%92,%93,%94,%95,"
      "%96,%97,%98,%99,%100,%101,%102,%103,%104,%105,%106,%107,%108,%109,%110,%111,"
      "%112,%113,%114,%115,%116,%117,%118,%119,%120,%121,%122,%123,%124,%125,%126,%127"
      "}, {%128,%129,%130,%131}, %132, p, 1, 1, 1;}\n"
      : "+f"(d[0]),"+f"(d[1]),"+f"(d[2]),"+f"(d[3]),"+f"(d[4]),"+f"(d[5]),"+f"(d[6]),"+f"(d[7]),
        "+f"(d[8]),"+f"(d[9]),"+f"(d[10]),"+f"(d[11]),"+f"(d[12]),"+f"(d[13]),"+f"(d[14]),"+f"(d[15]),
        "+f"(d[16]),"+f"(d[17]),"+f"(d[18]),"+f"(d[19]),"+f"(d[20]),"+f"(d[21]),"+f"(d[22]),"+f"(d[23]),
        "+f"(d[24]),"+f"(d[25]),"+f"(d[26]),"+f"(d[27]),"+f"(d[28]),"+f"(d[29]),"+f"(d[30]),"+f"(d[31]),
        "+f"(d[32]),"+f"(d[33]),"+f"(d[34]),"+f"(d[35]),"+f"(d[36]),"+f"(d[37]),"+f"(d[38]),"+f"(d[39]),
        "+f"(d[40]),"+f"(d[41]),"+f"(d[42]),"+f"(d[43]),"+f"(d[44]),"+f"(d[45]),"+f"(d[46]),"+f"(d[47]),
        "+f"(d[48]),"+f"(d[49]),"+f"(d[50]),"+f"(d[51]),"+f"(d[52]),"+f"(d[53]),"+f"(d[54]),"+f"(d[55]),
        "+f"(d[56]),"+f"(d[57]),"+f"(d[58]),"+f"(d[59]),"+f"(d[60]),"+f"(d[61]),"+f"(d[62]),"+f"(d[63]),
        "+f"(d[64]),"+f"(d[65]),"+f"(d[66]),"+f"(d[67]),"+f"(d[68]),"+f"(d[69]),"+f"(d[70]),"+f"(d[71]),
        "+f"(d[72]),"+f"(d[73]),"+f"(d[74]),"+f"(d[75]),"+f"(d[76]),"+f"(d[77]),"+f"(d[78]),"+f"(d[79]),
        "+f"(d[80]),"+f"(d[81]),"+f"(d[82]),"+f"(d[83]),"+f"(d[84]),"+f"(d[85]),"+f"(d[86]),"+f"(d[87]),
        "+f"(d[88]),"+f"(d[89]),"+f"(d[90]),"+f"(d[91]),"+f"(d[92]),"+f"(d[93]),"+f"(d[94]),"+f"(d[95]),
        "+f"(d[96]),"+f"(d[97]),"+f"(d[98]),"+f"(d[99]),"+f"(d[100]),"+f"(d[101]),"+f"(d[102]),"+f"(d[103]),
        "+f"(d[104]),"+f"(d[105]),"+f"(d[106]),"+f"(d[107]),"+f"(d[108]),"+f"(d[109]),"+f"(d[110]),"+f"(d[111]),
        "+f"(d[112]),"+f"(d[113]),"+f"(d[114]),"+f"(d[115]),"+f"(d[116]),"+f"(d[117]),"+f"(d[118]),"+f"(d[119]),
        "+f"(d[120]),"+f"(d[121]),"+f"(d[122]),"+f"(d[123]),"+f"(d[124]),"+f"(d[125]),"+f"(d[126]),"+f"(d[127])
      : "r"(a0), "r"(a1), "r"(a2), "r"(a3), "l"(db), "r"(sd));
}
__device__ __forceinline__ void wgmma_rs_n192(float (&d)[96], uint32_t a0, uint32_t a1, uint32_t a2, uint32_t a3, uint64_t db) {
  asm volatile("wgmma.mma_async.sync.aligned.m64n192k16.f32.bf16.bf16 {"
      "%0,%1,%2,%3,%4,%5,%6,%7,%8,%9,%10,%11,%12,%13,%14,%15,"
      "%16,%17,%18,%19,%20,%21,%22,%23,%24,%25,%26,%27,%28,%29,%30,%31,"
      "%32,%33,%34,%35,%36,%37,%38,%39,%40,%41,%42,%43,%44,%45,%46,%47,"
      "%48,%49,%50,%51,%52,%53,%54,%55,%56,%57,%58,%59,%60,%61,%62,%63,"
      "%64,%65,%66,%67,%68,%69,%70,%71,%72,%73,%74,%75,%76,%77,%78,%79,"
      "%80,%81,%82,%83,%84,%85,%86,%87,%88,%89,%90,%91,%92,%93,%94,%95"
      "}, {%96,%97,%98,%99}, %100, 1, 1, 1, 1;\n"
      : "+f"(d[0]),"+f"(d[1]),"+f"(d[2]),"+f"(d[3]),"+f"(d[4]),"+f"(d[5]),"+f"(d[6]),"+f"(d[7]),
        "+f"(d[8]),"+f"(d[9]),"+f"(d[10]),"+f"(d[11]),"+f"(d[12]),"+f"(d[13]),"+f"(d[14]),"+f"(d[15]),
        "+f"(d[16]),"+f"(d[17]),"+f"(d[18]),"+f"(d[19]),"+f"(d[20]),"+f"(d[21]),"+f"(d[22]),"+f"(d[23]),
        "+f"(d[24]),"+f"(d[25]),"+f"(d[26]),"+f"(d[27]),"+f"(d[28]),"+f"(d[29]),"+f"(d[30]),"+f"(d[31]),
        "+f"(d[32]),"+f"(d[33]),"+f"(d[34]),"+f"(d[35]),"+f"(d[36]),"+f"(d[37]),"+f"(d[38]),"+f"(d[39]),
        "+f"(d[40]),"+f"(d[41]),"+f"(d[42]),"+f"(d[43]),"+f"(d[44]),"+f"(d[45]),"+f"(d[46]),"+f"(d[47]),
        "+f"(d[48]),"+f"(d[49]),"+f"(d[50]),"+f"(d[51]),"+f"(d[52]),"+f"(d[53]),"+f"(d[54]),"+f"(d[55]),
        "+f"(d[56]),"+f"(d[57]),"+f"(d[58]),"+f"(d[59]),"+f"(d[60]),"+f"(d[61]),"+f"(d[62]),"+f"(d[63]),
        "+f"(d[64]),"+f"(d[65]),"+f"(d[66]),"+f"(d[67]),"+f"(d[68]),"+f"(d[69]),"+f"(d[70]),"+f"(d[71]),
        "+f"(d[72]),"+f"(d[73]),"+f"(d[74]),"+f"(d[75]),"+f"(d[76]),"+f"(d[77]),"+f"(d[78]),"+f"(d[79]),
        "+f"(d[80]),"+f"(d[81]),"+f"(d[82]),"+f"(d[83]),"+f"(d[84]),"+f"(d[85]),"+f"(d[86]),"+f"(d[87]),
        "+f"(d[88]),"+f"(d[89]),"+f"(d[90]),"+f"(d[91]),"+f"(d[92]),"+f"(d[93]),"+f"(d[94]),"+f"(d[95])
      : "r"(a0), "r"(a1), "r"(a2), "r"(a3), "l"(db));
}


constexpr int C_LN = 0, C_PX = 16, C_PY = 32;
constexpr int NB_CONS = 1, NB_LN = 2, NB_LAG = 4, NB_INIT = 6, NB_RDY = 7;
constexpr int LAGX = 4;
constexpr int LAGY = 6;
constexpr int LAG2 = 5;
constexpr int NLL = 4;
constexpr int POLL_DELAY = 1150;
constexpr int POLL_DELAY2 = 1000;
constexpr int POLL_DELAY3 = 600;
constexpr int FILT_DELAY = 600;
constexpr int WARM = 4;
constexpr int ALEAD = 8;
constexpr int XTRIG = 20;
constexpr int HTRIG = 0;
constexpr int SM_E = 0, SM_X = 16384, SM_E2 = 32768, SM_W = 49152, SM_FC = 69632, SM_T = 73728 - T1_BYTES;
constexpr unsigned long long KORDER = 0xBA9432DC876510ull;
constexpr unsigned long long BSLOT = 0xA9854210DA9854ull, PSLOT = 0xB763CB763CB763ull;
constexpr unsigned long long BDEP = 0xFFEC97631ull, PDEP = 0xBA754ull;
constexpr uint32_t HI128 = desc_hi(1024, 1), HI64 = desc_hi(512, 2);

struct Bars {
  uint64_t full1[32], empty1[32], full2[16], fullA[8], empty2[8], emptyP[9], sig[2], done, fullP[32], hbar, tbar, hint[3], sbar;
  uint32_t epoch, pad;
};

template <int NK, bool STORE, int J0 = 0, int J1 = NK>
__device__ __forceinline__ void make_p(const float (&acc)[NK * 16], float r0, float r1, uint4 (&p)[NK], uint4* pbase, int ks0, uint32_t tag) {
#pragma unroll
  for (int j = J0; j < J1; j++) {
    uint32_t w[4];
#pragma unroll
    for (int i = 0; i < 4; i++) {
      const int a = 8 * j + 2 * i, b = a + NK * 8;
      w[i] = pack2(swiglu(acc[a], acc[b], (i & 1) ? r1 : r0), swiglu(acc[a + 1], acc[b + 1], (i & 1) ? r1 : r0));
    }
    asm volatile("" : "+r"(w[0]), "+r"(w[1]), "+r"(w[2]), "+r"(w[3]));
    p[j] = make_uint4(w[0], w[1], w[2], w[3]);
    if (STORE) st_tag(pbase + ((ks0 + j) >> 2) * 1024 + ((ks0 + j) & 3) * 32, p[j], tag);
  }
}
__device__ __forceinline__ void spin_until(uint32_t t) {
  while ((int)(clock32() - t) < 0) {}
}

__global__ void __cluster_dims__(2, 1, 1) __launch_bounds__(NTHREADS, 1)
fused_kernel(const __nv_bfloat16* __restrict__ x, const Tables* __restrict__ tab, Scratch* __restrict__ scr,
             __nv_bfloat16* __restrict__ out, const char* __restrict__ wg_raw, const char* __restrict__ wu_raw,
             const char* __restrict__ wd_raw,
             const __grid_constant__ CUtensorMap tmWR, const __grid_constant__ CUtensorMap tmWI,
             const __grid_constant__ CUtensorMap tmGX, const __grid_constant__ CUtensorMap tmUX,
             const __grid_constant__ CUtensorMap tmGY, const __grid_constant__ CUtensorMap tmUY,
             const __grid_constant__ CUtensorMap tmD) {
  extern __shared__ __align__(1024) char smem_raw[];
  const uint32_t sbase = s2u(smem_raw);
  const uint32_t sbar = sbase + 14 * SLOT, sstat = sbar + 1408;
  const int tid = threadIdx.x, lane = tid & 31;
  const int c = blockIdx.x, rk = c & 1, f = (c >> 1) & 7, rb = 2 * (c >> 4) + rk;
  const int rb2 = 2 * (c >> 4) + (f >> 2), kh = (f >> 1) & 1, nq = 2 * (f & 1) + rk;
#define BAR(field, i) (sbar + (uint32_t)offsetof(Bars, field) + 8u * (i))
#define TOFF(field) (sbase + SM_T + (uint32_t)offsetof(Tables, field) + lane * 16)

  if (tid >= 256) {
    asm volatile("setmaxnreg.dec.sync.aligned.u32 40;");
    const int warp = __shfl_sync(0xffffffffu, tid >> 5, 0);
    if (lane == 0) {
      auto init = [&](uint32_t b, int n, int count, int bytes) {
#pragma unroll
        for (int i = 0; i < n; i++) mbar_init(b + 8 * i, count);
#pragma unroll
        for (int i = 0; i < (bytes ? n : 0); i++) mbar_expect(b + 8 * i, bytes);
      };
      if (warp == 8) {
        if (sbase & 1023) die();
        init(BAR(tbar, 0), 1, 1, T2_BYTES + 2 * 10240);
        init(BAR(hbar, 0), 1, 1, 16384);
        init(BAR(hint, 0), 3, 1, 0);
        init(BAR(sbar, 0), 1, 32, 0);
        init(BAR(empty2, 0), 20, 8, 0);
      } else if (warp == 9) {
        init(BAR(full1, 0), 16, 1, 16384);
        init(BAR(full1, 16), 16, 1, 12288);
      } else if (warp == 10) {
        init(BAR(fullP, 0), 30, 1, 8192);
      } else {
        init(BAR(full2, 0), 24, 1, 16384);
        init(BAR(empty1, 0), 32, 16, 0);
      }
      asm volatile("fence.mbarrier_init.release.cluster;" ::: "memory");
    }
    if (tid == 256) {
      const int w0 = ((c >> 3) * 257 + 32 * (c & 7) + 1) & ~7;
      asm volatile("prefetch.tensormap [%0];" ::"l"(&tmWR) : "memory");
      asm volatile("prefetch.tensormap [%0];" ::"l"(&tmWI) : "memory");
      spin_until(clock32() + FILT_DELAY);
      tma3(sbase + SM_W, &tmWR, BAR(tbar, 0), w0, 0, 0);
      tma3(sbase + SM_W + 10240, &tmWI, BAR(tbar, 0), w0, 0, 0);
      bulk_load(sbase + SM_T + T1_BYTES, reinterpret_cast<const char*>(tab) + T1_BYTES, T2_BYTES, BAR(tbar, 0));
    }
    if (tid == 288) {
      asm volatile("prefetch.tensormap [%0];" ::"l"(rk ? &tmUX : &tmGX) : "memory");
      asm volatile("prefetch.tensormap [%0];" ::"l"(rk ? &tmUY : &tmGY) : "memory");
      asm volatile("prefetch.tensormap [%0];" ::"l"(&tmD) : "memory");
    }
    if (tid == 320) {
      const unsigned e = ld_relaxed(&scr->cnt[(C_LN + rb) * 32]) >> 3;
      asm volatile("st.shared.u32 [%0], %1;" ::"r"(BAR(epoch, 0)), "r"(e) : "memory");
    }
    __syncwarp();
    asm volatile("barrier.cluster.arrive.relaxed.aligned;" ::: "memory");
    bar_arrive(NB_RDY, 384);
    asm volatile("barrier.cluster.wait.aligned;" ::: "memory");
    bar_sync(NB_INIT, 384);
    unsigned epoch;
    asm volatile("ld.shared.u32 %0, [%1];" : "=r"(epoch) : "r"(BAR(epoch, 0)) : "memory");
    if (warp == 8) {
      if (lane == 0) {
        const int ax = (7 * f + 3 * (f & 1)) >> 1;
        const int ay = 7 * f + ((f & 1) ? 0 : 4);
        const CUtensorMap* tx = rk ? &tmUX : &tmGX;
        const CUtensorMap* ty = rk ? &tmUY : &tmGY;
        mbar_wait_bounded(BAR(sig, 0));
        uint32_t s = 2;
#pragma unroll 1
        for (int n = 0; n < 16; n++) {
          if (n >= 6) mbar_wait_bounded(BAR(empty1, n - 6));
          tma3_mc(sbase + (8 + s) * SLOT + rk * 8192, tx, BAR(full1, n), n * 32, ax);
          if (++s == 6) s = 0;
          if (n >= 10 && n < 15) {
            const int k = n - 10;
            tma3_mc(sbase + k * 12288 + rk * 6144, ty, BAR(full1, 16 + k), (k + 8) * 32, ay);
          }
        }
#pragma unroll 1
        for (int k = 5; k < 16; k++) {
          mbar_wait_bounded(BAR(empty1, k < 13 ? 10 + ((12 * (k - 5) + 11) >> 4) : 3 + k));
          tma3_mc(sbase + (k < 13 ? 8 * SLOT + (k - 5) * 12288 : (k - 13) * 12288) + rk * 6144, ty, BAR(full1, 16 + k), ((k + 8) & 15) * 32, ay);
        }
        mbar_wait_bounded(BAR(done, 0));
      }
    } else if (warp == 9) {
      if (lane == 0) {
        mbar_wait(BAR(fullA, 4));
        wait_counter(&scr->cnt[(C_LN + rb2) * 32], (epoch + 1) * 8);
        asm volatile("fence.proxy.async.global;" ::: "memory");
#pragma unroll 1
        for (int i = 0; i < 14; i++) {
          const int kblk = 14 * kh + (int)((KORDER >> (4 * i)) & 15);
          mbar_wait(i < 9 ? BAR(empty1, 16 + (uint32_t)((BDEP >> (4 * i)) & 15)) : BAR(empty2, i - 9));
          tma3(sbase + (uint32_t)((BSLOT >> (4 * i)) & 15) * SLOT, &tmD, BAR(full2, i), 0, 64 * kblk, 2 * nq);
        }
        mbar_wait(BAR(empty2, 5));
        bulk_load(sbase + 13 * SLOT, &scr->LN[(rb2 * 8 + 2 * nq) * 1024 + kh * 512], 8192, BAR(hbar, 0));
        bulk_load(sbase + 13 * SLOT + 8192, &scr->LN[(rb2 * 8 + 2 * nq + 1) * 1024 + kh * 512], 8192, BAR(hbar, 0));
      }
    } else if (warp == 10) {
      bar_sync(NB_LN, 288);
      if (lane == 0) {
        red_release(&scr->cnt[(C_LN + rb) * 32]);
        wait_counter(&scr->cnt[(C_LN + rb) * 32], (epoch + 1) * 8);
        asm volatile("fence.proxy.async.global;" ::: "memory");
#pragma unroll 1
        for (int kb = NLL; kb < 8; kb++) {
          if (2 * kb >= ALEAD) mbar_wait(BAR(empty1, 2 * kb - ALEAD));
          bulk_load(sbase + kb * SLOT, &scr->LN[(rb * 8 + kb) * 1024], 16384, BAR(fullA, kb));
        }
#pragma unroll 1
        for (int s = 0; s < 14; s++) {
          const int kblk = 14 * kh + (int)((KORDER >> (4 * s)) & 15);
          if (s == 0 || s == 8 || s == 11) {
            mbar_wait(BAR(hint, s == 0 ? 0 : s == 8 ? 1 : 2));
          }
          mbar_wait(s < 5 ? BAR(empty1, 16 + (uint32_t)((PDEP >> (4 * s)) & 15)) : BAR(emptyP, s - 5));
          bulk_load_mc(sbase + (uint32_t)((PSLOT >> (4 * s)) & 15) * SLOT + rk * 8192, &scr->P[(rb2 * 28 + kblk) * 1024 + rk * 512], 8192, BAR(fullP, 16 * rk + s));
        }
      }
    } else {
      if (lane == 0) {
        mbar_wait(BAR(sig, 1));
        l2_prefetch(wg_raw + (size_t)c * 5376, 5376);
        l2_prefetch(wu_raw + (size_t)c * 5376, 5376);
        mbar_wait(BAR(sig, 0));
        l2_prefetch(wg_raw + 688128 + (size_t)c * 8960, 8960);
        l2_prefetch(wu_raw + 688128 + (size_t)c * 8960, 8960);
      }
      mbar_wait(BAR(fullA, 4));
      if (lane == 0) l2_prefetch(wd_raw + (size_t)c * 14336, 14336);
      {
        const uint32_t tag = (epoch + 1) & 1;
        uint4 v0, v1, v2;
        while (true) {
          v0 = ld_b128(&scr->ST[rb * 64 + lane]);
          v1 = ld_b128(&scr->ST[rb * 64 + 32 + lane]);
          v2 = ld_b128(&scr->ST[rb2 * 64 + 32 * kh + lane]);
          if (!__any_sync(0xffffffffu, ((v0.x ^ tag) | (v1.x ^ tag) | (v2.x ^ tag)) & 1u)) break;
        }
        sts4(sstat + lane * 16, v0.x & ~1u, v0.y, v0.z, v0.w);
        sts4(sstat + 512 + lane * 16, v1.x & ~1u, v1.y, v1.z, v1.w);
        sts4(sstat + 1024 + lane * 16, v2.x & ~1u, v2.y, v2.z, v2.w);
        mbar_arrive(BAR(sbar, 0));
      }
      if (lane == 0) {
        mbar_wait(BAR(empty1, XTRIG));
        while ((int)(ld_relaxed(&scr->cnt[(C_PX + rb2) * 32 + kh]) - (epoch + 1) * 32) < 0) {
        }
        mbar_arrive(BAR(hint, 0));
        mbar_wait(BAR(emptyP, HTRIG));
        uint32_t done = 0;
        while (done != 3) {
          uint2 v;
          asm volatile("ld.relaxed.gpu.global.v2.u32 {%0,%1}, [%2];" : "=r"(v.x), "=r"(v.y) : "l"(&scr->cnt[(C_PY + rb2) * 32 + 4 * (rk ^ kh ^ 1) + 2 * kh]) : "memory");
          if (!(done & 1) && (int)(v.x - (epoch + 1) * 8) >= 0) { done |= 1; mbar_arrive(BAR(hint, 1)); }
          if (!(done & 2) && (int)(v.y - (epoch + 1) * 8) >= 0) { done |= 2; mbar_arrive(BAR(hint, 2)); }
        }
      }
    }
  } else {
    const int warp = __shfl_sync(0xffffffffu, tid >> 5, 0);
    const int g = lane >> 2, t = lane & 3;
    uint4 fa[4], fb[4], tw[6];
#pragma unroll
    for (int i = 0; i < 4; i++) fa[i] = ldg_ca4(&tab->fa[i][lane][0]);
#pragma unroll
    for (int i = 0; i < 6; i++) tw[i] = ldg_ca4(&tab->tw1[i][lane][0]);
#pragma unroll
    for (int i = 0; i < 4; i++) fb[i] = ldg_ca4(&tab->fb[i][lane][0]);
#pragma unroll
    for (int i = 0; i < 4; i++) {
      const int r = i >> 1, ch = (i & 1) * 32 + lane;
      cp_async16(sbase + SM_X + (2 * warp + r) * 1024 + ((ch ^ ((ch >> 3) & 1)) * 16),
                 x + (size_t)(c + 128 * (2 * warp + r)) * 512 + ch * 8);
    }
    asm volatile("cp.async.commit_group;" ::: "memory");
    asm volatile("barrier.cluster.arrive.relaxed.aligned;" ::: "memory");
    uint32_t rbar;
    asm volatile("mapa.shared::cluster.u32 %0, %1, %2;" : "=r"(rbar) : "r"(sbar), "r"(rk ^ 1));
#define RBAR(field, i) (rbar + (uint32_t)offsetof(Bars, field) + 8u * (i))
    {
      const int ln = (tid >> 1) & 31, lg = ln >> 2, lt = ln & 3, i = 4 * (tid >> 6) + 2 * (tid & 1);
      const int kidx = lt + 8 * (i >> 3), nidx = 4 * ((i >> 1) & 3) + (lg >> 1);
      const uint32_t a0 = cfrag<2048>((c + 128 * kidx) * nidx, lg & 1), a1 = cfrag<2048>((c + 128 * (kidx + 4)) * nidx, lg & 1);
      const uint32_t b0 = cfrag<2048>(-(c + 128 * nidx) * kidx, lg & 1), b1 = cfrag<2048>(-(c + 128 * nidx) * (kidx + 4), lg & 1);
      asm volatile("st.shared.v2.u32 [%0], {%1,%2};" ::"r"(sbase + SM_FC + tid * 8), "r"(a0), "r"(a1) : "memory");
      asm volatile("st.shared.v2.u32 [%0], {%1,%2};" ::"r"(sbase + SM_FC + 2048 + tid * 8), "r"(b0), "r"(b1) : "memory");
    }
    bar_sync(NB_CONS, 256);
    uint4 fc[4];
#pragma unroll
    for (int i = 0; i < 4; i++) fc[i] = lds4(sbase + SM_FC + i * 512 + lane * 16);
    asm volatile("cp.async.wait_group 0;" ::: "memory");
    __syncwarp();
    bar_arrive(NB_INIT, 384);
    uint32_t tag, ones;
    uint4 q[4], o[4];
    {
      uint32_t v[2][8];
#pragma unroll
      for (int r = 0; r < 2; r++)
#pragma unroll
        for (int ks = 0; ks < 2; ks++) {
          const int ch = 32 * ks + 2 * (lane & 15) + (lane >> 4);
          asm volatile("ldmatrix.sync.aligned.m8n8.x4.trans.shared.b16 {%0,%1,%2,%3}, [%4];"
                       : "=r"(v[r][4 * ks]), "=r"(v[r][4 * ks + 1]), "=r"(v[r][4 * ks + 2]), "=r"(v[r][4 * ks + 3])
                       : "r"(sbase + SM_X + (2 * warp + r) * 1024 + ((ch ^ ((ch >> 3) & 1)) * 16)) : "memory");
        }
      float sq[2];
#pragma unroll
      for (int r = 0; r < 2; r++) {
        float s0 = 0.f, s1 = 0.f;
#pragma unroll
        for (int i = 0; i < 8; i++) {
          const float lo = bf_lo(v[r][i]), hi = u2f(v[r][i] & 0xffff0000u);
          s0 = fmaf(lo, lo, s0);
          s1 = fmaf(hi, hi, s1);
        }
        sq[r] = s0 + s1;
      }
      {
        float w = ((lane & 1) ? sq[1] : sq[0]) + __shfl_xor_sync(0xffffffffu, (lane & 1) ? sq[0] : sq[1], 1);
        w += __shfl_xor_sync(0xffffffffu, w, 2);
        w = sum_groups(w);
        const float o2 = __shfl_xor_sync(0xffffffffu, w, 1);
        sq[0] = (lane & 1) ? o2 : w;
        sq[1] = (lane & 1) ? w : o2;
      }
#pragma unroll
      for (int r = 0; r < 2; r++) {
        float dd[2][4], ee[2][4];
#pragma unroll
        for (int nt = 0; nt < 2; nt++) {
          mma_az(dd[nt], fa[0], v[r][2 * nt], v[r][2 * nt + 1]);
          mma_a(dd[nt], fa[1], v[r][4 + 2 * nt], v[r][5 + 2 * nt]);
          mma_az(ee[nt], fa[2], v[r][2 * nt], v[r][2 * nt + 1]);
          mma_a(ee[nt], fa[3], v[r][4 + 2 * nt], v[r][5 + 2 * nt]);
        }
        float mean = (dd[0][0] + dd[0][1]) + (dd[1][0] + dd[1][1]);
        mean += __shfl_xor_sync(0xffffffffu, mean, 1);
        mean += __shfl_xor_sync(0xffffffffu, mean, 2);
        mean = __shfl_sync(0xffffffffu, mean, 0) * (1.f / 512.f);
        const float rs = rsqrtf(fmaxf(fmaf(-mean, mean, sq[r] * (1.f / 512.f)), 0.f) + 1e-5f);
        float acc[4][4];
#pragma unroll
        for (int nt = 0; nt < 2; nt++) {
          const float (&d)[4] = dd[nt];
          const float (&e)[4] = ee[nt];
          const uint4 &ka = tw[2 * nt], &kb = tw[2 * nt + 1], &kc = tw[4 + nt];
          const uint32_t a0 = pack2(d[0] * u2f(ka.x) + d[2] * u2f(ka.y), d[1] * u2f(kb.x) + d[3] * u2f(kb.y));
          const uint32_t a2 = pack2(d[0] * u2f(ka.z) + d[2] * u2f(ka.w), d[1] * u2f(kb.z) + d[3] * u2f(kb.w));
          const uint32_t a1 = pack2(e[0] * u2f(kc.x) + e[2] * u2f(kc.y), e[1] * u2f(kc.z) + e[3] * u2f(kc.w));
          const uint32_t a3 = pack2(e[2] * u2f(kc.x) - e[0] * u2f(kc.y), e[3] * u2f(kc.z) - e[1] * u2f(kc.w));
          const uint32_t dc = pack2(fmaf(mean, -32.f, d[0]), fmaf(mean, -32.f, d[1]));
          const uint32_t h0 = g == 0 ? dc : a0, h2 = g == 0 ? 0u : a2;
          if (nt == 0) {
            mma16816_z(acc[0], a0, a1, a2, a3, fb[2 * nt].x, fb[2 * nt].y);
            mma16816_z(acc[1], a0, a1, a2, a3, fb[2 * nt].z, fb[2 * nt].w);
            mma16816_z(acc[2], h0, a1, h2, a3, fb[2 * nt + 1].x, fb[2 * nt + 1].y);
            mma16816_z(acc[3], h0, a1, h2, a3, fb[2 * nt + 1].z, fb[2 * nt + 1].w);
          } else {
            mma16816(acc[0], a0, a1, a2, a3, fb[2 * nt].x, fb[2 * nt].y);
            mma16816(acc[1], a0, a1, a2, a3, fb[2 * nt].z, fb[2 * nt].w);
            mma16816(acc[2], h0, a1, h2, a3, fb[2 * nt + 1].x, fb[2 * nt + 1].y);
            mma16816(acc[3], h0, a1, h2, a3, fb[2 * nt + 1].z, fb[2 * nt + 1].w);
          }
        }
#pragma unroll
        for (int h = 0; h < 2; h++) {
          const int j = 2 * warp + r, m = 2 * t + h;
          sts4(sbase + SM_E + ((j * 8 + m) * 8 + (g ^ (2 * t) ^ (2 * (j & 3)))) * 16,
               pack2(acc[h][0] * rs, acc[h][1] * rs), pack2(acc[h][2] * rs, acc[h][3] * rs),
               pack2(acc[2 + h][0] * rs, acc[2 + h][1] * rs), pack2(acc[2 + h][2] * rs, acc[2 + h][3] * rs));
        }
      }
      bar_sync(NB_RDY, 384);
      const uint32_t ea = sbase + SM_E + ((t * 8 + warp) * 8 + (g ^ (warp & 6) ^ (2 * t))) * 16;
      lds_frag(q[0], q[1], ea, ea + 4096);
      lds_frag(q[2], q[3], ea + 8192, ea + 12288);
      asm volatile("ld.shared.u32 %0, [%1];" : "=r"(tag) : "r"(BAR(epoch, 0)) : "memory");
      ones = ~(tag >> 31);
      tag = (tag + 1) & 1;
      cdft16(q, fc, o);
#pragma unroll
      for (int vv = 0; vv < 4; vv++) {
        o[vv].z = (o[vv].z & ~1u) | (tag ^ 1);
        st_tag(&scr->Z1[(((4 * vv + t) * 8 + warp) * 128 + c) * 8 + g], o[vv], tag);
      }
    }
    asm volatile("setmaxnreg.inc.sync.aligned.u32 232;");
    {
      uint4* const zp = &scr->Z1[(c * 128 + 8 * t + warp) * 8 + g];
      const uint32_t tst = clock32();
      mbar_wait(BAR(tbar, 0));
      uint4 f2[4], g2[4];
#pragma unroll
      for (int i = 0; i < 4; i++) {
        f2[i] = lds4(TOFF(f2) + warp * 2048 + i * 512);
        g2[i] = lds4(TOFF(g2) + warp * 2048 + i * 512);
      }
      const uint4 f8 = lds4(TOFF(f8)), g8 = lds4(TOFF(g8));
      asm volatile("barrier.cluster.wait.aligned;" ::: "memory");
      spin_until(tst + POLL_DELAY);
      ld_tag4_issue<256>(q, zp);
      float wfr[16], wfi[16];
      {
        const float nyq = ((c & 7) == 7 && g == 0) ? 0.5f : 1.f;
        uint32_t wa = sbase + SM_W + (16 * warp + t) * 80 + ((2 * (c >> 3) + 2) & 15) - 2;
        asm volatile("" : "+r"(wa));
        const uint32_t wb[3] = {wa + 2 * (g == 0 ? 16 : g), wa + 2 * g, wa - 2 * g};
#pragma unroll
        for (int i = 0; i < 16; i++) {
          const int ci = i >> 3, dd = (i >> 2) & 1, e = i & 3;
          const uint32_t a = wb[e < 2 ? e : 2] + (ci * 8 + 4 * dd) * 80 + (e == 0 ? 0 : e == 1 ? 16 : e == 2 ? 64 : 48);
          wfr[i] = bf_lo(lds_u16(a)) * (e == 2 ? nyq : 1.f);
          wfi[i] = bf_lo(lds_u16(a + 10240)) * (e == 2 ? nyq : 1.f);
        }
      }
      ld_tag4_finish<256>(q, zp, tag);
      if (lane == 0) mbar_arrive(BAR(sig, 1));
#pragma unroll
      for (int i = 0; i < 4; i++) q[i].z &= ~1u;
      reg_frag(q, ones);
      cdft16(q, f2, o);
      const uint32_t e2 = sbase + SM_E2;
#pragma unroll
      for (int vv = 0; vv < 4; vv++)
        sts4(e2 + ((warp * 16 + 4 * vv + t) * 8 + (g ^ (2 * t) ^ (2 * (warp & 3)))) * 16, o[vv].x, o[vv].y, o[vv].z, o[vv].w);
      bar_sync(NB_CONS, 256);
      uint32_t ad[2], res[2][2][4];
#pragma unroll
      for (int ci = 0; ci < 2; ci++) {
        const int cc = 2 * warp + ci;
        ad[ci] = e2 + ((t * 16 + cc) * 8 + (g ^ (2 * (cc & 3)) ^ (2 * t))) * 16;
        lds_frag(q[2 * ci], q[2 * ci + 1], ad[ci], ad[ci] + 8192);
      }
#pragma unroll
      for (int ci = 0; ci < 2; ci++)
#pragma unroll
        for (int p = 0; p < 2; p++) {
          uint32_t y[2][2];
#pragma unroll
          for (int vv = 0; vv < 2; vv++) {
            float d[4];
            mma_az(d, q[2 * ci + p], word(f8, 2 * vv), word(f8, 2 * vv + 1));
#pragma unroll
            for (int rr = 0; rr < 2; rr++) {
              const float fr = wfr[ci * 8 + vv * 4 + 2 * p + rr], fi = wfi[ci * 8 + vv * 4 + 2 * p + rr];
              y[vv][rr] = pack2(d[2 * rr] * fr - d[2 * rr + 1] * fi, d[2 * rr] * fi + d[2 * rr + 1] * fr);
            }
          }
#pragma unroll
          for (int vv = 0; vv < 2; vv++) {
            float d[4];
            mma16816_z(d, y[0][0], y[0][1], y[1][0], y[1][1], word(g8, 2 * vv), word(g8, 2 * vv + 1));
            res[ci][vv][2 * p] = pack2(d[0], d[1]);
            res[ci][vv][2 * p + 1] = pack2(d[2], d[3]);
          }
        }
#pragma unroll
      for (int i = 0; i < 4; i++)
        sts4(ad[i >> 1] + (i & 1) * 8192, res[i >> 1][i & 1][0], res[i >> 1][i & 1][1], res[i >> 1][i & 1][2], res[i >> 1][i & 1][3]);
      bar_sync(NB_CONS, 256);
      const uint32_t eb = e2 + ((warp * 16 + t) * 8 + (g ^ (2 * t) ^ (2 * (warp & 3)))) * 16;
      lds_frag(q[0], q[1], eb, eb + 512);
      lds_frag(q[2], q[3], eb + 1024, eb + 1536);
      cdft16(q, g2, o);
#pragma unroll
      for (int vv = 0; vv < 4; vv++) {
        o[vv].y &= ~1u;
        o[vv].z = (o[vv].z & ~1u) | tag;
        st_tag(zp + vv * 256, o[vv], tag);
      }
    }
    {
      const uint4* const zp = &scr->Z1[((t * 8 + warp) * 128 + c) * 8 + g];
      const uint32_t tst = clock32();
      uint4 gb[4], ga[4], gc[4], tw[4];
      uint2 xr[2][4];
      uint2* lnp[2];
#pragma unroll
      for (int r = 0; r < 2; r++) {
        const int row = 16 * f + 2 * warp + r;
        lnp[r] = reinterpret_cast<uint2*>(&scr->LN[(rb * 8 + (g >> 2)) * 1024 + row * 8 + ((2 * (g & 3) + (t >> 1)) ^ (row & 7))]) + (t & 1);
        asm volatile("" : "+l"(lnp[r]));
      }
#pragma unroll
      for (int i = 0; i < 4; i++) {
        gc[i] = lds4(sbase + SM_FC + 2048 + i * 512 + lane * 16);
        gb[i] = lds4(TOFF(gb) + i * 512);
        ga[i] = lds4(TOFF(ga) + i * 512);
        tw[i] = lds4(TOFF(tw3) + i * 512);
        const int ch = 2 * (g + 8 * i) + (t >> 1);
#pragma unroll
        for (int r = 0; r < 2; r++) xr[r][i] = lds2(sbase + SM_X + (2 * warp + r) * 1024 + ((ch ^ ((ch >> 3) & 1)) * 16) + (t & 1) * 8);
      }
      spin_until(tst + POLL_DELAY2);
      ld_tag4_issue<32768>(q, zp);
      ld_tag4_finish<32768, true>(q, zp, tag);
      if (lane == 0) mbar_arrive(BAR(sig, 0));
      reg_frag(q, ones);
      cdft16(q, gc, o);
#pragma unroll
      for (int vv = 0; vv < 4; vv++)
        sts4(sbase + SM_E + (((4 * vv + t) * 8 + warp) * 8 + (g ^ (warp & 6) ^ (2 * t))) * 16, o[vv].x, o[vv].y, o[vv].z, o[vv].w);
      bar_sync(NB_CONS, 256);
      uint32_t hv[2][8];
      const float mk = t == 0 ? 0.f : 1.f;
#pragma unroll
      for (int r = 0; r < 2; r++) {
        const int j = 2 * warp + r;
        uint4 u[2];
#pragma unroll
        for (int h = 0; h < 2; h++) u[h] = lds4(sbase + SM_E + ((j * 8 + 2 * t + h) * 8 + (g ^ (2 * t) ^ (2 * (j & 3)))) * 16);
        const uint32_t bp[4][2] = {{u[0].x, u[1].x & ones}, {u[0].y & ones, u[1].y}, {u[0].z, u[1].z & ones}, {u[0].w & ones, u[1].w}};
        float y[2][2][4];
#pragma unroll
        for (int i = 0; i < 2; i++) {
          float lo[4], hi[4], e[4];
          mma_az(lo, gb[2 * i], bp[0][0], bp[0][1]);
          mma_az(hi, gb[2 * i + 1], bp[2][0], bp[2][1]);
          mma_az(e, gb[2 * i], bp[1][0], bp[1][1]);
          mma_a(e, gb[2 * i + 1], bp[3][0], bp[3][1]);
          const uint4 &ka = tw[2 * i], &kb = tw[2 * i + 1];
          const float tr0 = fmaf(hi[0], mk, lo[0]), ti0 = fmaf(hi[2], mk, lo[2]);
          const float tr1 = lo[1] + hi[1], ti1 = lo[3] + hi[3];
          const float vr0 = tr0 * u2f(ka.x) - ti0 * u2f(ka.y), vi0 = tr0 * u2f(ka.y) + ti0 * u2f(ka.x);
          const float vr1 = tr1 * u2f(ka.z) - ti1 * u2f(ka.w), vi1 = tr1 * u2f(ka.w) + ti1 * u2f(ka.z);
          const uint32_t b0 = pack2(t == 0 ? hi[0] : vr0, vr1), b1 = pack2(t == 0 ? vr0 : vi0, vi1);
          const uint32_t b2 = pack2(e[0] * u2f(kb.x) - e[2] * u2f(kb.y), e[1] * u2f(kb.z) - e[3] * u2f(kb.w));
          const uint32_t b3 = pack2(e[0] * u2f(kb.y) + e[2] * u2f(kb.x), e[1] * u2f(kb.w) + e[3] * u2f(kb.z));
#pragma unroll
          for (int mt = 0; mt < 2; mt++) {
            mma_az(y[mt][i], ga[2 * mt], b0, b1);
            mma_a(y[mt][i], ga[2 * mt + 1], b2, b3);
          }
        }
#pragma unroll
        for (int i = 0; i < 4; i++) {
          hv[r][2 * i] = hadd2_bf16(xr[r][i].x, pack2(y[i >> 1][0][2 * (i & 1)], y[i >> 1][0][2 * (i & 1) + 1]));
          hv[r][2 * i + 1] = hadd2_bf16(xr[r][i].y, pack2(y[i >> 1][1][2 * (i & 1)], y[i >> 1][1][2 * (i & 1) + 1]));
        }
      }
      uint32_t mb[2], ml[2];
#pragma unroll
      for (int r = 0; r < 2; r++) {
        const float mean = sum_groups(quad_sum(hv[r])) * (1.f / 512.f);
        mb[r] = pack2(mean, mean);
        ml[r] = pack2(mean - bf_lo(mb[r]), mean - bf_lo(mb[r])) & 0xfffefffeu;
      }
#pragma unroll
      for (int i = 0; i < 4; i++)
#pragma unroll
        for (int r = 0; r < 2; r++) {
          hv[r][2 * i] = hsub2_bf16(hsub2_bf16(hv[r][2 * i], mb[r]), ml[r]);
          hv[r][2 * i + 1] = hsub2_bf16(hsub2_bf16(hv[r][2 * i + 1], mb[r]), ml[r]);
          st_tag8(lnp[r] + i * 4096, hv[r][2 * i], hv[r][2 * i + 1], i < 2 ? tag : (hv[r][2 * i] & 1u));
        }
      bar_arrive(NB_LN, 288);
      const uint32_t ones2 = ~(lds2(BAR(epoch, 0)).x >> 31);
      float rstd[2];
#pragma unroll
      for (int r = 0; r < 2; r++) {
        hv[r][0] &= ones2;
        rstd[r] = row_rstd(hv[r]);
      }
      if (lane == 0)
        st_tag(&scr->ST[rb * 64 + 8 * f + warp], make_uint4(__byte_perm(ml[0], mb[0], 0x5410), __float_as_uint(rstd[0]), __byte_perm(ml[1], mb[1], 0x5410), __float_as_uint(rstd[1])), tag);
    }
    const int wgi = warp >> 2, wq = warp & 3;
    const int wr = wgi ^ (f >> 2) ^ 1, rt = 4 * wr + wq;
    uint4* const pbase = &scr->P[rb * 28 * 1024 + rt * 128 + lane];
    const uint32_t a_lo0 = desc_lo(sbase + wr * 8192, 16);
    const uint32_t ebar = lane == 0 ? BAR(empty1, 0) : RBAR(empty1, 0);
    float r0, r1;
    uint4 px[8], py[6];
    const int rh = wgi ^ kh ^ 1;
    const uint32_t fpb = BAR(fullP, 16 * rh);
    const uint4* const psrc = &scr->P[(rb2 * 28 + 14 * kh) * 1024 + (4 * rh + wq) * 128 + lane];
    const uint32_t pa0 = sbase + (4 * rh + wq) * 2048;
    uint4 pf[3][4], ha[4][4];
    uint32_t rdy = 0, got0;
    {
      float acc[128];
#pragma unroll
      for (int i = 0; i < 128; i++) acc[i] = 0.f;
      const uint32_t b_lo0 = desc_lo(sbase + 8 * SLOT, 4096);
      const uint32_t t3 = clock32();
      if (WARM) {
        wg_fence();
#pragma unroll
        for (int i = 0; i < WARM; i++) wgmma_n256(acc, desc64(a_lo0 + 6 * 1024, HI128), desc64(b_lo0, HI128));
        wg_commit();
      }
      const uint4* const ap = &scr->LN[rb * 8 * 1024 + rt * 128 + lane];
      const uint32_t sa = sbase + rt * 2048, amask = (lane & 1) ? ~0u : ~1u;
      auto fetch_a = [&](int kb) {
#pragma unroll
        for (int i = 0; i < 4; i++) cp_async16(sa + kb * SLOT + (lane + 32 * i) * 16, ap + kb * 1024 + 32 * i);
        asm volatile("cp.async.commit_group;" ::: "memory");
      };
      auto load_a = [&](int kb) {
#pragma unroll
        for (int ks = 0; ks < 4; ks++)
          asm volatile("ldmatrix.sync.aligned.m8n8.x4.shared.b16 {%0,%1,%2,%3}, [%4];"
                       : "=r"(ha[kb][ks].x), "=r"(ha[kb][ks].y), "=r"(ha[kb][ks].z), "=r"(ha[kb][ks].w)
                       : "r"(sa + kb * SLOT + (lane & 15) * 128 + (((2 * ks + (lane >> 4)) ^ (lane & 7)) * 16)) : "memory");
      };
      auto check_a = [&](int kb) {
        int it = 0;
#pragma unroll 1
        while (true) {
          uint32_t m = 0;
#pragma unroll
          for (int ks = 0; ks < 4; ks++) m |= tag_miss(ha[kb][ks].x, ha[kb][ks].y, ha[kb][ks].z, ha[kb][ks].w, tag);
          if (!__any_sync(0xffffffffu, m & ~amask)) break;
          fetch_a(kb);
          asm volatile("cp.async.wait_group 0;" ::: "memory");
          __syncwarp();
          load_a(kb);
          if (++it > SPIN_LIMIT) { die(); break; }
        }
#pragma unroll
        for (int ks = 0; ks < 4; ks++)
          asm volatile("and.b32 %0, %0, %4; and.b32 %1, %1, %4; and.b32 %2, %2, %4; and.b32 %3, %3, %4;"
                       : "+r"(ha[kb][ks].x), "+r"(ha[kb][ks].y), "+r"(ha[kb][ks].z), "+r"(ha[kb][ks].w) : "r"(amask));
      };
      bar_sync(NB_CONS, 256);
      spin_until(t3 + POLL_DELAY3);
      fetch_a(0);
      fetch_a(1);
      asm volatile("cp.async.wait_group 1;" ::: "memory");
      __syncwarp();
      load_a(0);
#pragma unroll
      for (int n = 0; n < 8; n++) {
        const int kb = n >> 1, hh = n & 1;
        if (hh == 0) {
          check_a(kb);
          if (kb < 2) fetch_a(kb + 2);
        }
        if (hh == 1 && kb < 3) {
          if (kb < 2) asm volatile("cp.async.wait_group 1;" ::: "memory");
          else asm volatile("cp.async.wait_group 0;" ::: "memory");
          __syncwarp();
        }
        if (!rdy) mbar_wait(BAR(full1, n));
        const uint32_t bl = b_lo0 + ((n + 2) % 6) * 1024;
        wg_fence();
        if (hh == 1 && kb < 3) load_a(kb + 1);
        rdy = mbar_test(BAR(full1, n + 1));
        const uint4 &a0 = ha[kb][2 * hh], &a1 = ha[kb][2 * hh + 1];
        wgmma_rs_n256(acc, a0.x, a0.y, a0.z, a0.w, desc64(bl, HI128), n != 0 ? 1 : ~ones);
        wgmma_rs_n256(acc, a1.x, a1.y, a1.z, a1.w, desc64(bl + 128, HI128));
        wg_commit();
        wg_wait<1>();
        if (n != 0 && lane < 2) mbar_arrive_remote(ebar + 8 * (n - 1));
      }
      uint32_t slot = 4;
#pragma unroll 1
      for (int kb = 4; kb < 8; kb++) {
        mbar_wait(BAR(fullA, kb));
#pragma unroll
        for (int hh = 0; hh < 2; hh++) {
          if (hh == ((16 - LAGX) & 1) && kb == ((16 - LAGX) >> 1) && wgi == 1) bar_sync(NB_LAG, 256);
          mbar_wait(BAR(full1, 2 * kb + hh));
          const uint32_t al = a_lo0 + kb * 1024 + hh * 4, bl = b_lo0 + slot * 1024;
          wg_fence();
          wgmma_n256(acc, desc64(al, HI128), desc64(bl, HI128));
          wgmma_n256(acc, desc64(al + 2, HI128), desc64(bl + 128, HI128));
          wg_commit();
          if (hh == 1 && kb == 7 && wgi == 0) bar_arrive(NB_LAG, 256);
          wg_wait<1>();
          if (lane < 2) mbar_arrive_remote(ebar + 8 * (2 * kb + hh - 1));
          if (++slot == 6) slot = 0;
        }
      }
      mbar_wait(BAR(sbar, 0));
      r0 = __uint_as_float(lds2(sstat + (16 * rt + g) * 8).y);
      r1 = __uint_as_float(lds2(sstat + (16 * rt + g + 8) * 8).y);
      wg_wait<0>();
      if (lane < 2) mbar_arrive_remote(ebar + 8 * 15);
      make_p<8, false>(acc, r0, r1, px, pbase, 0, tag);
    }
    {
      float acc[96];
#pragma unroll
      for (int i = 0; i < 96; i++) acc[i] = 0.f;
      const uint32_t b_lo0 = desc_lo(sbase, 2048);
      uint4* const pdst = pbase + ((7 * f + 3 * (f & 1)) >> 1) * 1024;
      auto stage_y = [&](int k) {
        if (k < 4) mbar_wait_bounded(BAR(full1, 16 + k));
        else mbar_wait(BAR(full1, 16 + k));
        const uint32_t al = a_lo0 + (4 + (k >> 1)) * 1024 + (k & 1) * 4, bl = b_lo0 + (k < 5 ? k * 768 : 8192 + (k - 5) * 768);
        wg_fence();
        wgmma_n192(acc, desc64(al, HI128), desc64(bl, HI64));
        wgmma_n192(acc, desc64(al + 2, HI128), desc64(bl + 64, HI64));
        wg_commit();
      };
#pragma unroll
      for (int k = 0; k < 4; k++) {
        stage_y(k);
        st_tag(pdst + (k >> 1) * 1024 + (k & 1) * 64, px[2 * k], tag);
        st_tag(pdst + (k >> 1) * 1024 + (k & 1) * 64 + 32, px[2 * k + 1], tag);
        if (k == 3 && lane == 0) red_relaxed(&scr->cnt[(C_PX + rb) * 32 + (f >> 2)]);
        wg_wait<1>();
        if (k != 0 && lane < 2) mbar_arrive_remote(ebar + 8 * (15 + k));
      }
#pragma unroll 1
      for (int k = 4; k < 8; k++) {
        stage_y(k);
        wg_wait<1>();
        if (k != 0 && lane < 2) mbar_arrive_remote(ebar + 8 * (15 + k));
      }
      rdy = 0;
#pragma unroll
      for (int k = 8; k < 16; k++) {
        if (k == 16 - LAGY && wgi == 1) bar_sync(NB_LAG, 256);
        if (!rdy) mbar_wait(BAR(full1, 16 + k));
        const uint32_t bl = b_lo0 + (k < 13 ? 8192 + (k - 5) * 768 : (k - 13) * 768);
        const uint4 &a0 = ha[(k - 8) >> 1][2 * (k & 1)], &a1 = ha[(k - 8) >> 1][2 * (k & 1) + 1];
        wg_fence();
        if (k < 15) rdy = mbar_test(BAR(full1, 17 + k));
        wgmma_rs_n192(acc, a0.x, a0.y, a0.z, a0.w, desc64(bl, HI64));
        wgmma_rs_n192(acc, a1.x, a1.y, a1.z, a1.w, desc64(bl + 64, HI64));
        wg_commit();
        if (k == 15 && wgi == 0) bar_arrive(NB_LAG, 256);
        wg_wait<1>();
        if (lane < 2) mbar_arrive_remote(ebar + 8 * (15 + k));
      }
      got0 = __all_sync(0xffffffffu, mbar_test(fpb));
      if (got0) {
#pragma unroll
        for (int kk = 0; kk < 4; kk++) pf[0][kk] = lds4(pa0 + 3 * SLOT + kk * 512 + lane * 16);
      }
      wg_wait<0>();
      if (lane < 2) mbar_arrive_remote(ebar + 8 * 31);
      const int ks0 = 14 * f + ((f & 1) ? 0 : 8);
      auto reread = [&]() {
        asm volatile("ld.volatile.shared.f32 %0, [%2+4]; ld.volatile.shared.f32 %1, [%2+68];" : "=f"(r0), "=f"(r1) : "r"(sstat + (16 * rt + g) * 8) : "memory");
      };
      make_p<6, true, 0, 2>(acc, r0, r1, py, pbase, ks0, tag);
      reread();
      make_p<6, true, 2, 4>(acc, r0, r1, py, pbase, ks0, tag);
      if (lane == 0) red_relaxed(&scr->cnt[(C_PY + rb) * 32 + 4 * wgi + (f >> 1)]);
      reread();
      rdy = mbar_test(BAR(full2, 0)) & mbar_test(fpb + 8);
      make_p<6, true, 4, 6>(acc, r0, r1, py, pbase, ks0, tag);
    }
    {
      float acc[64];
      const uint32_t b2_lo0 = desc_lo(sbase, 8192);
      const uint32_t pbar = rh == rk ? BAR(emptyP, 0) : RBAR(emptyP, 0);
      if (!got0) {
        mbar_wait(fpb);
#pragma unroll
        for (int kk = 0; kk < 4; kk++) pf[0][kk] = lds4(pa0 + 3 * SLOT + kk * 512 + lane * 16);
      }
#pragma unroll
      for (int s = 0; s < 14; s++) {
        uint4 (&a)[4] = pf[s % 3];
        ld_tag4_finish<32>(a, psrc + (int)((KORDER >> (4 * s)) & 15) * 1024, tag);
        if (s < 9 && lane == 0) mbar_arrive_remote(pbar + 8 * s);
        if (s >= 2) {
          wg_wait<1>();
          if (s <= 7 && lane == 0) mbar_arrive(BAR(empty2, s - 2));
        }
        if (!rdy) {
          if (s < 13) mbar_wait(fpb + 8 * (s + 1));
          mbar_wait(BAR(full2, s));
        }
        if (s == 14 - LAG2 && wgi == 1) bar_sync(NB_LAG, 256);
        const uint32_t bl = b2_lo0 + (uint32_t)((BSLOT >> (4 * s)) & 15) * 1024;
        wg_fence();
        if (s < 13) {
#pragma unroll
          for (int kk = 0; kk < 4; kk++)
            pf[(s + 1) % 3][kk] = lds4(pa0 + (uint32_t)((PSLOT >> (4 * (s + 1))) & 15) * SLOT + kk * 512 + lane * 16);
          rdy = mbar_test(BAR(full2, s + 1));
          if (s < 12) rdy &= mbar_test(fpb + 8 * (s + 2));
        }
        if (s == 0) wgmma_rs_n128(acc, a[0].x, a[0].y, a[0].z, a[0].w, desc64(bl, HI128), 0);
        else wgmma_rs_n128(acc, a[0].x, a[0].y, a[0].z, a[0].w, desc64(bl, HI128));
#pragma unroll
        for (int kk = 1; kk < 4; kk++) wgmma_rs_n128(acc, a[kk].x, a[kk].y, a[kk].z, a[kk].w, desc64(bl + kk * 128, HI128));
        wg_commit();
      }
      if (wgi == 0) {
        bar_arrive(NB_LAG, 256);
        uint4* const dst = &scr->Z1[(tid >> 3) * 1024 + (c ^ 4) * 8 + (tid & 7)];
        wg_wait<0>();
#pragma unroll
        for (int i = 0; i < 8; i++)
          st_tag(dst + i * 16384, make_uint4(pack2(acc[8 * i], acc[8 * i + 1]), pack2(acc[8 * i + 2], acc[8 * i + 3]) | 1u,
                                           pack2(acc[8 * i + 4], acc[8 * i + 5]), pack2(acc[8 * i + 6], acc[8 * i + 7])), tag);
      } else {
        uint4 pv[2][4];
        const uint4* const xsrc = &scr->Z1[((tid & 127) >> 3) * 1024 + c * 8 + (tid & 7)];
        ld_tag4_issue<16384>(pv[0], xsrc);
        ld_tag4_issue<16384>(pv[1], xsrc + 65536);
        uint32_t w[32];
        {
          const uint32_t s0 = lds2(sstat + 1024 + (16 * wq + g) * 8).x, s1 = lds2(sstat + 1024 + (16 * wq + g + 8) * 8).x;
          const uint32_t m0 = __byte_perm(s0, 0, 0x3232), m1 = __byte_perm(s1, 0, 0x3232);
          const uint32_t l0 = __byte_perm(s0, 0, 0x1010), l1 = __byte_perm(s1, 0, 0x1010);
          const uint32_t hb = sbase + 13 * SLOT + (16 * wq + (lane & 15)) * 128;
          const uint32_t mk = ((t & 1) == 0 && nq < 2) ? ~1u : ~0u;
          mbar_wait(BAR(hbar, 0));
#pragma unroll
          for (int i = 0; i < 8; i++) {
            asm volatile("ldmatrix.sync.aligned.m8n8.x4.shared.b16 {%0,%1,%2,%3}, [%4];"
                         : "=r"(w[4 * i]), "=r"(w[4 * i + 1]), "=r"(w[4 * i + 2]), "=r"(w[4 * i + 3])
                         : "r"(hb + (i >> 2) * 8192 + (((2 * (i & 3) + (lane >> 4)) ^ (lane & 7)) * 16)) : "memory");
#pragma unroll
            for (int e = 0; e < 4; e++) w[4 * i + e] = hadd2_bf16(hadd2_bf16(w[4 * i + e] & mk, (e & 1) ? l1 : l0), (e & 1) ? m1 : m0);
          }
        }
        wg_wait<0>();
#pragma unroll
        for (int i = 0; i < 32; i++) w[i] = hadd2_bf16(w[i], pack2(acc[2 * i], acc[2 * i + 1]));
#pragma unroll 1
        while (!__all_sync(0xffffffffu, pv[0][0].y & pv[0][1].y & pv[0][2].y & pv[0][3].y & pv[1][0].y & pv[1][1].y & pv[1][2].y & pv[1][3].y & 1u)) {
          ld_tag4_issue<16384>(pv[0], xsrc);
          ld_tag4_issue<16384>(pv[1], xsrc + 65536);
        }
#pragma unroll
        for (int i = 0; i < 8; i++) {
          const uint4& p = pv[i >> 2][i & 3];
          asm volatile("stmatrix.sync.aligned.m8n8.x4.shared.b16 [%0], {%1,%2,%3,%4};"
                       ::"r"(pa0 + (11 + ((lane >> 3) & 1)) * SLOT + (lane & 7) * 256 + (((2 * i + (lane >> 4)) ^ (lane & 7)) * 16)),
                         "r"(hadd2_bf16(w[4 * i], p.x & ~1u)), "r"(hadd2_bf16(w[4 * i + 1], p.y & ~1u)), "r"(hadd2_bf16(w[4 * i + 2], p.z)),
                         "r"(hadd2_bf16(w[4 * i + 3], p.w)) : "memory");
        }
        __syncwarp();
        uint4* const dst = reinterpret_cast<uint4*>(out) + (16 * (c >> 4) + 2 * (4 * rh + wq) + (rb2 & 1) + 128 * (lane >> 4)) * 64 + nq * 16 + (lane & 15);
#pragma unroll
        for (int i = 0; i < 8; i++) {
          const int r = 2 * (i & 3) + (lane >> 4);
          dst[i * 256 * 64] = lds4(pa0 + (11 + (i >> 2)) * SLOT + r * 256 + (((lane & 15) ^ r) * 16));
        }
      }
      if (lane == 0) mbar_arrive(BAR(done, 0));
    }
  }
#undef BAR
#undef TOFF
#undef RBAR
}

typedef CUresult (*EncodeFn)(CUtensorMap*, CUtensorMapDataType, cuuint32_t, void*, const cuuint64_t*, const cuuint64_t*,
                             const cuuint32_t*, const cuuint32_t*, CUtensorMapInterleave, CUtensorMapSwizzle,
                             CUtensorMapL2promotion, CUtensorMapFloatOOBfill);

}

extern "C" void kernel_launch(void* const* d_in, const int* in_sizes, int n_in, void* d_out, int out_size) {
  (void)in_sizes; (void)n_in; (void)out_size;
  static EncodeFn encode = nullptr;
  static void *tab = nullptr, *scr = nullptr;
  if (!encode) {
    void* fn = nullptr;
    cudaDriverEntryPointQueryResult qr;
    cudaGetDriverEntryPoint("cuTensorMapEncodeTiled", &fn, cudaEnableDefault, &qr);
    encode = (EncodeFn)fn;
    cudaGetSymbolAddress(&tab, g_tab);
    cudaGetSymbolAddress(&scr, g_scr);
    cudaFuncSetAttribute(fused_kernel, cudaFuncAttributeMaxDynamicSharedMemorySize, SMEM_BYTES);
  }
  CUtensorMap tmGX, tmUX, tmGY, tmUY, tmD, tmWR, tmWI;
  const cuuint32_t es[5] = {1, 1, 1, 1, 1};
  auto enc = [&](CUtensorMap* m, void* p, int rank, const cuuint64_t* gd, const cuuint64_t* gs, const cuuint32_t* bd,
                 CUtensorMapSwizzle sw, CUtensorMapL2promotion pr) {
    encode(m, CU_TENSOR_MAP_DATA_TYPE_BFLOAT16, rank, p, gd, gs, bd, es, CU_TENSOR_MAP_INTERLEAVE_NONE, sw, pr,
           CU_TENSOR_MAP_FLOAT_OOB_FILL_NONE);
  };
  {
    const cuuint64_t gd[3] = {64, 512, 28}, gs[2] = {3584, 128};
    const cuuint32_t bd[3] = {64, 32, 2};
    enc(&tmGX, d_in[4], 3, gd, gs, bd, CU_TENSOR_MAP_SWIZZLE_128B, CU_TENSOR_MAP_L2_PROMOTION_L2_256B);
    enc(&tmUX, d_in[5], 3, gd, gs, bd, CU_TENSOR_MAP_SWIZZLE_128B, CU_TENSOR_MAP_L2_PROMOTION_L2_256B);
  }
  {
    const cuuint64_t gd[3] = {32, 512, 56}, gs[2] = {3584, 64};
    const cuuint32_t bd[3] = {32, 32, 3};
    enc(&tmGY, d_in[4], 3, gd, gs, bd, CU_TENSOR_MAP_SWIZZLE_64B, CU_TENSOR_MAP_L2_PROMOTION_L2_128B);
    enc(&tmUY, d_in[5], 3, gd, gs, bd, CU_TENSOR_MAP_SWIZZLE_64B, CU_TENSOR_MAP_L2_PROMOTION_L2_128B);
  }
  {
    const cuuint64_t gd[3] = {64, 1792, 8}, gs[2] = {1024, 128};
    const cuuint32_t bd[3] = {64, 64, 2};
    enc(&tmD, d_in[6], 3, gd, gs, bd, CU_TENSOR_MAP_SWIZZLE_128B, CU_TENSOR_MAP_L2_PROMOTION_L2_256B);
  }
  {
    const cuuint64_t gd[3] = {4112, 8, 16}, gs[2] = {16 * 8224, 8224};
    const cuuint32_t bd[3] = {40, 8, 16};
    enc(&tmWR, d_in[1], 3, gd, gs, bd, CU_TENSOR_MAP_SWIZZLE_NONE, CU_TENSOR_MAP_L2_PROMOTION_NONE);
    enc(&tmWI, d_in[2], 3, gd, gs, bd, CU_TENSOR_MAP_SWIZZLE_NONE, CU_TENSOR_MAP_L2_PROMOTION_NONE);
  }
  fused_kernel<<<NCTA, NTHREADS, SMEM_BYTES>>>((const __nv_bfloat16*)d_in[0], (const Tables*)tab, (Scratch*)scr,
                                               (__nv_bfloat16*)d_out, (const char*)d_in[4], (const char*)d_in[5],
                                               (const char*)d_in[6], tmWR, tmWI, tmGX, tmUX, tmGY, tmUY, tmD);
}
```
